```python
import torch

def _softmax(x, axis=-1):
    return torch.softmax(x, dim=axis)
def _gelu(x):
    return torch.nn.functional.gelu(x, approximate="tanh")
def _silu(x):
    return torch.nn.functional.silu(x)
def _sigmoid(x):
    return torch.sigmoid(x)
def _layernorm(x, axis=-1, eps=1e-5):
    m = x.mean(dim=axis, keepdim=True)
    v = x.var(dim=axis, keepdim=True, unbiased=False)
    return (x - m) / torch.sqrt(v + eps)
def _scatter_add(tgt, idx, src, axis=0):
    return tgt.clone().index_add_(axis, idx, src)
def _segment_sum(src, seg, n):
    out = torch.zeros((n,) + src.shape[1:], dtype=src.dtype)
    return out.index_add_(0, seg, src)
def _pad(x, pw):
    flat = tuple(v for pair in reversed(pw) for v in pair)
    return torch.nn.functional.pad(x, flat)

kernel_name = 'interleave_layers__ssm_conv_s5__ssm_conv_h3__prompt'

def setup_inputs():

    _w = (lambda a: (lambda t: t.to(torch.bfloat16) if t.is_floating_point() else t)(torch.as_tensor(a)))
    def _A_setup():
        B, S, D = 1, 2048, 640
        P = D
        Lambda_re = -0.5 * (lambda _x: torch.exp(torch.as_tensor(_x)))((lambda *s: torch.randn(*s, dtype=torch.bfloat16) * 0.2)(P))
        Lambda_im = (lambda *s: torch.randn(*s, dtype=torch.bfloat16) * 0.8)(P) * 1.0
        B_re = (lambda *s: torch.randn(*s, dtype=torch.bfloat16) * 0.2)(P, D) * (D ** -0.5)
        B_im = (lambda *s: torch.randn(*s, dtype=torch.bfloat16) * 0.2)(P, D) * (D ** -0.5)
        C_re = (lambda *s: torch.randn(*s, dtype=torch.bfloat16) * 0.2)(D, P) * (P ** -0.5)
        C_im = (lambda *s: torch.randn(*s, dtype=torch.bfloat16) * 0.2)(D, P) * (P ** -0.5)
        log_dt = (lambda *s: torch.randn(*s, dtype=torch.bfloat16) * 0.2)(P) * 0.3 - 2.0
        Dskip = (lambda *s: torch.randn(*s, dtype=torch.bfloat16) * 0.05)(D)
        return {
            "x": _w((lambda *s: torch.randn(*s, dtype=torch.bfloat16) * 0.05)(B, S, D)),
            "Lambda_re": _w(Lambda_re),
            "Lambda_im": _w(Lambda_im),
            "B_re": _w(B_re),
            "B_im": _w(B_im),
            "C_re": _w(C_re),
            "C_im": _w(C_im),
            "log_dt": _w(log_dt),
            "Dskip": _w(Dskip),
        }
    _A_in = _A_setup()

    def _B_setup():
        B, S, D = 1, 2048, 640
        ks = 4
        return {
            "q": _w((lambda *s: torch.randn(*s, dtype=torch.bfloat16) * 0.05)(B, S, D)),
            "k": _w((lambda *s: torch.randn(*s, dtype=torch.bfloat16) * 0.4)(B, S, D)),
            "v": _w((lambda *s: torch.randn(*s, dtype=torch.bfloat16) * 0.4)(B, S, D)),
            "shift_k": _w((lambda *s: torch.randn(*s, dtype=torch.bfloat16) * 0.4)(D, ks) * 0.5),
            "ssm_k": _w((lambda *s: torch.randn(*s, dtype=torch.bfloat16) * 0.4)(D, S) * (1.0 / S ** 0.5)),
            "ssm_D": _w((lambda *s: torch.randn(*s, dtype=torch.bfloat16) * 0.4)(D)),
        }
    _B_in = _B_setup()

    return {
        "A_x": _A_in["x"],
        "A_Lambda_re": _A_in["Lambda_re"],
        "A_Lambda_im": _A_in["Lambda_im"],
        "A_B_re": _A_in["B_re"],
        "A_B_im": _A_in["B_im"],
        "A_C_re": _A_in["C_re"],
        "A_C_im": _A_in["C_im"],
        "A_log_dt": _A_in["log_dt"],
        "A_Dskip": _A_in["Dskip"],
        "B_q": _B_in["q"],
        "B_k": _B_in["k"],
        "B_v": _B_in["v"],
        "B_shift_k": _B_in["shift_k"],
        "B_ssm_k": _B_in["ssm_k"],
        "B_ssm_D": _B_in["ssm_D"],
    }

def reference(A_x, A_Lambda_re, A_Lambda_im, A_B_re, A_B_im, A_C_re, A_C_im, A_log_dt, A_Dskip, B_q, B_k, B_v, B_shift_k, B_ssm_k, B_ssm_D):
    def _A_ref(x, Lambda_re, Lambda_im, B_re, B_im, C_re, C_im, log_dt, Dskip):
        Bsz, L, H = x.shape
        Lam = Lambda_re + 1j * Lambda_im
        Bmat = B_re + 1j * B_im
        Cmat = C_re + 1j * C_im
        dt = torch.exp(log_dt)
        Lam_bar = torch.exp(dt * Lam)
        B_bar = ((Lam_bar - 1.0) / Lam)[:, None] * Bmat
        Bu = torch.einsum("bld,pd->blp", x + 0j, B_bar)
        h = torch.zeros_like(Bu[:, 0, :])
        hs = []
        for t in range(L):
            h = Lam_bar[None, :] * h + Bu[:, t, :]
            hs.append(h)
        hseq = torch.stack(hs, 1)
        y = 2.0 * torch.einsum("blp,dp->bld", hseq, Cmat).real + x * Dskip[None, None, :]
        return y

    def _B_ref(q, k, v, shift_k, ssm_k, ssm_D):
        B, S, D = q.shape
        ks = shift_k.shape[-1]
        k_pad = _pad(k, ((0, 0), (ks - 1, 0), (0, 0)))
        k_shift = torch.zeros_like(k)
        for t in range(ks):
            k_shift = k_shift + k_pad[:, t:t + S, :] * shift_k[:, ks - 1 - t][None, None, :]
        kv = k_shift * v
        L = 2 * S
        kv_pad = _pad(kv, ((0, 0), (0, S), (0, 0)))
        kf_pad = _pad(ssm_k, ((0, 0), (0, S)))
        kv_f = (lambda x, axes=(-2,-1): torch.fft.rfft2(x.float(), dim=axes))(kv_pad[:, None, :, :], axes=(1, 2))
        kf_f = (lambda x, axes=(-2,-1): torch.fft.rfft2(x.float(), dim=axes))(kf_pad[:, None, :], axes=(1, 2))
        kf_f = (lambda x, *d: x.permute(*d))(kf_f, 1, 2, 0)
        y_f = kv_f * kf_f[None, :, :, :]
        y = (lambda x, s, axes=(-2,-1): torch.fft.irfft2(x, s=s, dim=axes).to(torch.bfloat16))(y_f, (1, L), axes=(1, 2))[:, 0, :S, :]
        y = y + kv * ssm_D[None, None, :]
        return q * y

    x = A_x
    x = x + _A_ref(_layernorm(x, axis=-1), A_Lambda_re, A_Lambda_im, A_B_re, A_B_im, A_C_re, A_C_im, A_log_dt, A_Dskip)
    x = x + _B_ref(_layernorm(x, axis=-1), B_k, B_v, B_shift_k, B_ssm_k, B_ssm_D)
    x = x + _A_ref(_layernorm(x, axis=-1), A_Lambda_re, A_Lambda_im, A_B_re, A_B_im, A_C_re, A_C_im, A_log_dt, A_Dskip)
    x = x + _B_ref(_layernorm(x, axis=-1), B_k, B_v, B_shift_k, B_ssm_k, B_ssm_D)
    return x
```

```cpp
#include <cuda_runtime.h>
#include <cuda.h>
#include <cuda_bf16.h>
#include <stdint.h>

namespace {

constexpr int SEQ = 2048, DM = 640;
constexpr int NT1 = 13;
constexpr uint32_t SPIN_LIMIT = 1u << 22;

__device__ __align__(1024) uint8_t g_h[2 * 32 * 20 * 8192];
__device__ __align__(1024) uint8_t g_u[NT1 * 10 * 20480];
__device__ __align__(1024) uint8_t g_kv[DM * 4096];
__device__ __align__(1024) uint8_t g_G[DM * 4096];
__device__ __align__(128) uint4 g_E[2 * NT1 * DM];
__device__ __align__(128) uint4 g_stats[4 * SEQ * 4];
__device__ __align__(128) uint4 g_sB[DM];
__device__ __align__(128) unsigned g_hflag[2 * NT1 * 2 * 16];
__device__ __align__(128) unsigned g_uflag[32 * 4];
__device__ __align__(128) unsigned g_kvcnt[4 * 32];
__device__ __align__(128) unsigned g_gcnt[4 * 32];
__device__ __align__(128) unsigned g_epoch[32];
#define TS(i) do {} while (0)

struct Params {
  CUtensorMap mBre, mBim, mCre, mCim, mX, mXl, mG;
  const __nv_bfloat16 *x, *lre, *lim, *bre, *bim, *cre, *cim, *logdt, *dskip, *k, *v, *shiftk, *ssmk, *ssmD;
  float* out;
};

constexpr uint32_t G1_STAGE = 36864, G1_XOFF = 16384;
constexpr int S1 = 5;
constexpr uint32_t G2_XB = 8192, G2_WB = 20480, G2_WOFF = 57344, G_OFF = 200704;
constexpr int SX2 = 7;
constexpr uint32_t CV_OFF = 184320, CV_K = 128, CV_PL = 2240, CV_U = CV_K + 4096, CV_B = 8704;
constexpr uint32_t MISC = 227840;
constexpr uint32_t BAR_OFF = MISC;
constexpr int B_G1FULL = 0, B_G1DONE = 20, B_G2FULL = 40, B_G2DONE = 80, B_CVFULL = 120, B_GFULL = 125,
              B_CTAB = 126, B_STAB = 127  , B_EPOCH = 129, NBAR = 130;
constexpr uint32_t STAB_OFF = MISC + 1088;
constexpr uint32_t CTAB_OFF = STAB_OFF + 1280;
constexpr uint32_t DTAB_OFF = CTAB_OFF + 1536;
constexpr uint32_t EPOCH_OFF = DTAB_OFF + 320;
constexpr uint32_t SMEM_BYTES = 232448;
static_assert(EPOCH_OFF + 16 <= SMEM_BYTES, "smem");

__device__ __forceinline__ uint32_t smem_u32(const void* p) { return (uint32_t)__cvta_generic_to_shared(p); }
__device__ __forceinline__ void mbar_init(uint32_t bar, int cnt) { asm volatile("mbarrier.init.shared::cta.b64 [%0], %1;" ::"r"(bar), "r"(cnt) : "memory"); }
__device__ __forceinline__ void mbar_expect_tx(uint32_t bar, int bytes) { asm volatile("mbarrier.arrive.expect_tx.shared::cta.b64 _, [%0], %1;" ::"r"(bar), "r"(bytes) : "memory"); }
__device__ __forceinline__ void mbar_arrive(uint32_t bar) { asm volatile("mbarrier.arrive.shared::cta.b64 _, [%0];" ::"r"(bar) : "memory"); }
__device__ __forceinline__ void mbar_wait(uint32_t bar) {
  asm volatile(
      "{\n.reg .pred p;\n.reg .u32 c;\nmov.u32 c, 0;\n"
      "W_%=:\nmbarrier.try_wait.parity.shared::cta.b64 p, [%0], 0;\n@p bra D_%=;\n"
      "add.u32 c, c, 1;\nsetp.lt.u32 p, c, %1;\n@p bra W_%=;\ntrap;\nD_%=:\n}\n" ::"r"(bar), "n"(SPIN_LIMIT) : "memory");
}
__device__ __forceinline__ void tma4(uint32_t dst, const CUtensorMap* m, int c0, int c1, int c2, int c3, uint32_t bar) {
  asm volatile("cp.async.bulk.tensor.4d.shared::cluster.global.mbarrier::complete_tx::bytes [%0], [%1, {%3,%4,%5,%6}], [%2];"
               ::"r"(dst), "l"(m), "r"(bar), "r"(c0), "r"(c1), "r"(c2), "r"(c3) : "memory");
}
__device__ __forceinline__ void tma5(uint32_t dst, const CUtensorMap* m, int c0, int c1, int c2, int c3, int c4, uint32_t bar) {
  asm volatile("cp.async.bulk.tensor.5d.shared::cluster.global.mbarrier::complete_tx::bytes [%0], [%1, {%3,%4,%5,%6,%7}], [%2];"
               ::"r"(dst), "l"(m), "r"(bar), "r"(c0), "r"(c1), "r"(c2), "r"(c3), "r"(c4) : "memory");
}
__device__ __forceinline__ void bulk_g2s(uint32_t dst, const void* src, int bytes, uint32_t bar) {
  asm volatile("cp.async.bulk.shared::cluster.global.mbarrier::complete_tx::bytes [%0], [%1], %2, [%3];"
               ::"r"(dst), "l"(src), "r"(bytes), "r"(bar) : "memory");
}
__device__ __forceinline__ void bulk_s2g(void* dst, uint32_t src, int bytes) {
  asm volatile("cp.async.bulk.global.shared::cta.bulk_group [%0], [%1], %2;" ::"l"(dst), "r"(src), "r"(bytes) : "memory");
}
__device__ __forceinline__ void l2_prefetch(const void* src, int bytes) {
  asm volatile("cp.async.bulk.prefetch.L2.global [%0], %1;" ::"l"(src), "r"(bytes) : "memory");
}
__device__ __forceinline__ void wgmma_fence() { asm volatile("wgmma.fence.sync.aligned;" ::: "memory"); }
__device__ __forceinline__ void wgmma_commit() { asm volatile("wgmma.commit_group.sync.aligned;" ::: "memory"); }
template <int N> __device__ __forceinline__ void wgmma_wait() { asm volatile("wgmma.wait_group.sync.aligned %0;" ::"n"(N) : "memory"); }
__device__ __forceinline__ uint64_t make_desc(uint32_t addr, uint32_t lbo, uint32_t sbo, int swz) {
  return (uint64_t)((addr & 0x3FFFF) >> 4) | ((uint64_t)(lbo >> 4) << 16) | ((uint64_t)(sbo >> 4) << 32) | ((uint64_t)swz << 62);
}
__device__ __forceinline__ void bar_sync(int id, int n) { asm volatile("bar.sync %0, %1;" ::"r"(id), "r"(n) : "memory"); }
__device__ __forceinline__ uint32_t lds32(uint32_t a) { uint32_t v; asm volatile("ld.shared.u32 %0, [%1];" : "=r"(v) : "r"(a) : "memory"); return v; }
__device__ __forceinline__ float2 lds64f(uint32_t a) { float2 v; asm volatile("ld.shared.v2.f32 {%0,%1}, [%2];" : "=f"(v.x), "=f"(v.y) : "r"(a) : "memory"); return v; }
__device__ __forceinline__ float4 lds128f(uint32_t a) { float4 v; asm volatile("ld.shared.v4.f32 {%0,%1,%2,%3}, [%4];" : "=f"(v.x), "=f"(v.y), "=f"(v.z), "=f"(v.w) : "r"(a) : "memory"); return v; }
__device__ __forceinline__ void sts32(uint32_t a, uint32_t v) { asm volatile("st.shared.u32 [%0], %1;" ::"r"(a), "r"(v) : "memory"); }
__device__ __forceinline__ void sts64f(uint32_t a, float x, float y) { asm volatile("st.shared.v2.f32 [%0], {%1,%2};" ::"r"(a), "f"(x), "f"(y) : "memory"); }
__device__ __forceinline__ unsigned ld_acq(const unsigned* p) { unsigned v; asm volatile("ld.acquire.gpu.global.u32 %0, [%1];" : "=r"(v) : "l"(p) : "memory"); return v; }
__device__ __forceinline__ void st_rel(unsigned* p, unsigned v) { asm volatile("st.release.gpu.global.u32 [%0], %1;" ::"l"(p), "r"(v) : "memory"); }
__device__ __forceinline__ void red_rel(unsigned* p, unsigned v) { asm volatile("red.release.gpu.global.add.u32 [%0], %1;" ::"l"(p), "r"(v) : "memory"); }
__device__ __forceinline__ void fence_async_global() { asm volatile("fence.proxy.async.global;" ::: "memory"); }
__device__ __forceinline__ void fence_async_smem() { asm volatile("fence.proxy.async.shared::cta;" ::: "memory"); }
__device__ __forceinline__ void rec_st(uint4* p, float a, float b, unsigned tag) {
  asm volatile("{\n.reg .b128 t;\n.reg .b64 lo, hi;\nmov.b64 lo, {%1,%2};\nmov.b64 hi, {%3,%3};\nmov.b128 t, {lo,hi};\n"
               "st.relaxed.gpu.global.b128 [%0], t;\n}\n" ::"l"(p), "r"(__float_as_uint(a)), "r"(__float_as_uint(b)), "r"(tag) : "memory");
}
__device__ __forceinline__ unsigned rec_ld(const uint4* p, float& a, float& b) {
  unsigned x, y, t;
  asm volatile("{\n.reg .b128 t;\n.reg .b64 lo, hi;\n.reg .b32 u;\nld.relaxed.gpu.global.b128 t, [%3];\nmov.b128 {lo,hi}, t;\n"
               "mov.b64 {%0,%1}, lo;\nmov.b64 {%2,u}, hi;\n}\n" : "=r"(x), "=r"(y), "=r"(t) : "l"(p) : "memory");
  a = __uint_as_float(x); b = __uint_as_float(y);
  return t;
}
__device__ __forceinline__ void rec_poll(const uint4* p, unsigned tag, float& a, float& b) {
  uint32_t it = 0;
  while (rec_ld(p, a, b) != tag) { if (++it > SPIN_LIMIT) __trap(); }
}
__device__ __forceinline__ void flag_poll(const unsigned* p, unsigned target) {
  uint32_t it = 0;
  while ((int)(ld_acq(p) - target) < 0) { if (++it > SPIN_LIMIT) __trap(); }
}
__device__ __forceinline__ uint32_t pack_bf16(float lo, float hi) {
  uint32_t r; asm("cvt.rn.bf16x2.f32 %0, %1, %2;" : "=r"(r) : "f"(hi), "f"(lo)); return r;
}
__device__ __forceinline__ float bf_lo(uint32_t w) { return __uint_as_float(w << 16); }
__device__ __forceinline__ float bf_hi(uint32_t w) { return __uint_as_float(w & 0xffff0000u); }
__device__ __forceinline__ uint32_t hmul2(uint32_t a, uint32_t b) {
  __nv_bfloat162 r = __hmul2_rn(*(__nv_bfloat162*)&a, *(__nv_bfloat162*)&b); return *(uint32_t*)&r;
}
__device__ __forceinline__ uint32_t hadd2(uint32_t a, uint32_t b) {
  __nv_bfloat162 r = __hadd2_rn(*(__nv_bfloat162*)&a, *(__nv_bfloat162*)&b); return *(uint32_t*)&r;
}
__device__ __forceinline__ float2 cmul(float2 a, float2 b) { return make_float2(a.x * b.x - a.y * b.y, a.x * b.y + a.y * b.x); }
__device__ __forceinline__ float2 cfma(float2 a, float2 b, float2 c) {
  return make_float2(fmaf(a.x, b.x, fmaf(-a.y, b.y, c.x)), fmaf(a.x, b.y, fmaf(a.y, b.x, c.y)));
}
template <int N> __device__ __forceinline__ void fence_regs(float (&a)[N]) {
#pragma unroll
  for (int i = 0; i < N; i++) asm volatile("" : "+f"(a[i])::"memory");
}
__device__ __forceinline__ int n_to_t(int n) {
  int T = n / 160, nl = n - T * 160;
  int L = (T == NT1 - 1) ? 32 : 40;
  return T * 160 + L * ((nl & 7) >> 1) + 2 * (nl >> 3) + (nl & 1);
}

template<int TA> __device__ __forceinline__ void wgmma_n160(float (&d)[80], uint64_t da, uint64_t db, int scale_d){
  asm volatile("{\n.reg .pred p;\nsetp.ne.b32 p, %82, 0;\n"
    "wgmma.mma_async.sync.aligned.m64n160k16.f32.bf16.bf16 {%0, %1, %2, %3, %4, %5, %6, %7, %8, %9, %10, %11, %12, %13, %14, %15, %16, %17, %18, %19, %20, %21, %22, %23, %24, %25, %26, %27, %28, %29, %30, %31, %32, %33, %34, %35, %36, %37, %38, %39, %40, %41, %42, %43, %44, %45, %46, %47, %48, %49, %50, %51, %52, %53, %54, %55, %56, %57, %58, %59, %60, %61, %62, %63, %64, %65, %66, %67, %68, %69, %70, %71, %72, %73, %74, %75, %76, %77, %78, %79}, %80, %81, p, 1, 1, %83, 0;\n}\n"
    : "+f"(d[0]), "+f"(d[1]), "+f"(d[2]), "+f"(d[3]), "+f"(d[4]), "+f"(d[5]), "+f"(d[6]), "+f"(d[7]), "+f"(d[8]), "+f"(d[9]), "+f"(d[10]), "+f"(d[11]), "+f"(d[12]), "+f"(d[13]), "+f"(d[14]), "+f"(d[15]), "+f"(d[16]), "+f"(d[17]), "+f"(d[18]), "+f"(d[19]), "+f"(d[20]), "+f"(d[21]), "+f"(d[22]), "+f"(d[23]), "+f"(d[24]), "+f"(d[25]), "+f"(d[26]), "+f"(d[27]), "+f"(d[28]), "+f"(d[29]), "+f"(d[30]), "+f"(d[31]), "+f"(d[32]), "+f"(d[33]), "+f"(d[34]), "+f"(d[35]), "+f"(d[36]), "+f"(d[37]), "+f"(d[38]), "+f"(d[39]), "+f"(d[40]), "+f"(d[41]), "+f"(d[42]), "+f"(d[43]), "+f"(d[44]), "+f"(d[45]), "+f"(d[46]), "+f"(d[47]), "+f"(d[48]), "+f"(d[49]), "+f"(d[50]), "+f"(d[51]), "+f"(d[52]), "+f"(d[53]), "+f"(d[54]), "+f"(d[55]), "+f"(d[56]), "+f"(d[57]), "+f"(d[58]), "+f"(d[59]), "+f"(d[60]), "+f"(d[61]), "+f"(d[62]), "+f"(d[63]), "+f"(d[64]), "+f"(d[65]), "+f"(d[66]), "+f"(d[67]), "+f"(d[68]), "+f"(d[69]), "+f"(d[70]), "+f"(d[71]), "+f"(d[72]), "+f"(d[73]), "+f"(d[74]), "+f"(d[75]), "+f"(d[76]), "+f"(d[77]), "+f"(d[78]), "+f"(d[79])
    : "l"(da), "l"(db), "r"(scale_d), "n"(TA));
}
template<int N> __device__ __forceinline__ void wgmma_rs_hi(float (&d)[64], uint32_t a0, uint32_t a1, uint32_t a2, uint32_t a3, uint64_t db);
template<> __device__ __forceinline__ void wgmma_rs_hi<16>(float (&d)[64], uint32_t a0, uint32_t a1, uint32_t a2, uint32_t a3, uint64_t db){
  asm volatile("wgmma.mma_async.sync.aligned.m64n16k16.f32.bf16.bf16 {%0, %1, %2, %3, %4, %5, %6, %7}, {%8,%9,%10,%11}, %12, 1, 1, 1, 0;\n"
    : "+f"(d[56]), "+f"(d[57]), "+f"(d[58]), "+f"(d[59]), "+f"(d[60]), "+f"(d[61]), "+f"(d[62]), "+f"(d[63])
    : "r"(a0), "r"(a1), "r"(a2), "r"(a3), "l"(db));
}
template<> __device__ __forceinline__ void wgmma_rs_hi<32>(float (&d)[64], uint32_t a0, uint32_t a1, uint32_t a2, uint32_t a3, uint64_t db){
  asm volatile("wgmma.mma_async.sync.aligned.m64n32k16.f32.bf16.bf16 {%0, %1, %2, %3, %4, %5, %6, %7, %8, %9, %10, %11, %12, %13, %14, %15}, {%16,%17,%18,%19}, %20, 1, 1, 1, 0;\n"
    : "+f"(d[48]), "+f"(d[49]), "+f"(d[50]), "+f"(d[51]), "+f"(d[52]), "+f"(d[53]), "+f"(d[54]), "+f"(d[55]), "+f"(d[56]), "+f"(d[57]), "+f"(d[58]), "+f"(d[59]), "+f"(d[60]), "+f"(d[61]), "+f"(d[62]), "+f"(d[63])
    : "r"(a0), "r"(a1), "r"(a2), "r"(a3), "l"(db));
}
template<> __device__ __forceinline__ void wgmma_rs_hi<48>(float (&d)[64], uint32_t a0, uint32_t a1, uint32_t a2, uint32_t a3, uint64_t db){
  asm volatile("wgmma.mma_async.sync.aligned.m64n48k16.f32.bf16.bf16 {%0, %1, %2, %3, %4, %5, %6, %7, %8, %9, %10, %11, %12, %13, %14, %15, %16, %17, %18, %19, %20, %21, %22, %23}, {%24,%25,%26,%27}, %28, 1, 1, 1, 0;\n"
    : "+f"(d[40]), "+f"(d[41]), "+f"(d[42]), "+f"(d[43]), "+f"(d[44]), "+f"(d[45]), "+f"(d[46]), "+f"(d[47]), "+f"(d[48]), "+f"(d[49]), "+f"(d[50]), "+f"(d[51]), "+f"(d[52]), "+f"(d[53]), "+f"(d[54]), "+f"(d[55]), "+f"(d[56]), "+f"(d[57]), "+f"(d[58]), "+f"(d[59]), "+f"(d[60]), "+f"(d[61]), "+f"(d[62]), "+f"(d[63])
    : "r"(a0), "r"(a1), "r"(a2), "r"(a3), "l"(db));
}
template<> __device__ __forceinline__ void wgmma_rs_hi<64>(float (&d)[64], uint32_t a0, uint32_t a1, uint32_t a2, uint32_t a3, uint64_t db){
  asm volatile("wgmma.mma_async.sync.aligned.m64n64k16.f32.bf16.bf16 {%0, %1, %2, %3, %4, %5, %6, %7, %8, %9, %10, %11, %12, %13, %14, %15, %16, %17, %18, %19, %20, %21, %22, %23, %24, %25, %26, %27, %28, %29, %30, %31}, {%32,%33,%34,%35}, %36, 1, 1, 1, 0;\n"
    : "+f"(d[32]), "+f"(d[33]), "+f"(d[34]), "+f"(d[35]), "+f"(d[36]), "+f"(d[37]), "+f"(d[38]), "+f"(d[39]), "+f"(d[40]), "+f"(d[41]), "+f"(d[42]), "+f"(d[43]), "+f"(d[44]), "+f"(d[45]), "+f"(d[46]), "+f"(d[47]), "+f"(d[48]), "+f"(d[49]), "+f"(d[50]), "+f"(d[51]), "+f"(d[52]), "+f"(d[53]), "+f"(d[54]), "+f"(d[55]), "+f"(d[56]), "+f"(d[57]), "+f"(d[58]), "+f"(d[59]), "+f"(d[60]), "+f"(d[61]), "+f"(d[62]), "+f"(d[63])
    : "r"(a0), "r"(a1), "r"(a2), "r"(a3), "l"(db));
}
template<> __device__ __forceinline__ void wgmma_rs_hi<80>(float (&d)[64], uint32_t a0, uint32_t a1, uint32_t a2, uint32_t a3, uint64_t db){
  asm volatile("wgmma.mma_async.sync.aligned.m64n80k16.f32.bf16.bf16 {%0, %1, %2, %3, %4, %5, %6, %7, %8, %9, %10, %11, %12, %13, %14, %15, %16, %17, %18, %19, %20, %21, %22, %23, %24, %25, %26, %27, %28, %29, %30, %31, %32, %33, %34, %35, %36, %37, %38, %39}, {%40,%41,%42,%43}, %44, 1, 1, 1, 0;\n"
    : "+f"(d[24]), "+f"(d[25]), "+f"(d[26]), "+f"(d[27]), "+f"(d[28]), "+f"(d[29]), "+f"(d[30]), "+f"(d[31]), "+f"(d[32]), "+f"(d[33]), "+f"(d[34]), "+f"(d[35]), "+f"(d[36]), "+f"(d[37]), "+f"(d[38]), "+f"(d[39]), "+f"(d[40]), "+f"(d[41]), "+f"(d[42]), "+f"(d[43]), "+f"(d[44]), "+f"(d[45]), "+f"(d[46]), "+f"(d[47]), "+f"(d[48]), "+f"(d[49]), "+f"(d[50]), "+f"(d[51]), "+f"(d[52]), "+f"(d[53]), "+f"(d[54]), "+f"(d[55]), "+f"(d[56]), "+f"(d[57]), "+f"(d[58]), "+f"(d[59]), "+f"(d[60]), "+f"(d[61]), "+f"(d[62]), "+f"(d[63])
    : "r"(a0), "r"(a1), "r"(a2), "r"(a3), "l"(db));
}
template<> __device__ __forceinline__ void wgmma_rs_hi<96>(float (&d)[64], uint32_t a0, uint32_t a1, uint32_t a2, uint32_t a3, uint64_t db){
  asm volatile("wgmma.mma_async.sync.aligned.m64n96k16.f32.bf16.bf16 {%0, %1, %2, %3, %4, %5, %6, %7, %8, %9, %10, %11, %12, %13, %14, %15, %16, %17, %18, %19, %20, %21, %22, %23, %24, %25, %26, %27, %28, %29, %30, %31, %32, %33, %34, %35, %36, %37, %38, %39, %40, %41, %42, %43, %44, %45, %46, %47}, {%48,%49,%50,%51}, %52, 1, 1, 1, 0;\n"
    : "+f"(d[16]), "+f"(d[17]), "+f"(d[18]), "+f"(d[19]), "+f"(d[20]), "+f"(d[21]), "+f"(d[22]), "+f"(d[23]), "+f"(d[24]), "+f"(d[25]), "+f"(d[26]), "+f"(d[27]), "+f"(d[28]), "+f"(d[29]), "+f"(d[30]), "+f"(d[31]), "+f"(d[32]), "+f"(d[33]), "+f"(d[34]), "+f"(d[35]), "+f"(d[36]), "+f"(d[37]), "+f"(d[38]), "+f"(d[39]), "+f"(d[40]), "+f"(d[41]), "+f"(d[42]), "+f"(d[43]), "+f"(d[44]), "+f"(d[45]), "+f"(d[46]), "+f"(d[47]), "+f"(d[48]), "+f"(d[49]), "+f"(d[50]), "+f"(d[51]), "+f"(d[52]), "+f"(d[53]), "+f"(d[54]), "+f"(d[55]), "+f"(d[56]), "+f"(d[57]), "+f"(d[58]), "+f"(d[59]), "+f"(d[60]), "+f"(d[61]), "+f"(d[62]), "+f"(d[63])
    : "r"(a0), "r"(a1), "r"(a2), "r"(a3), "l"(db));
}
template<> __device__ __forceinline__ void wgmma_rs_hi<112>(float (&d)[64], uint32_t a0, uint32_t a1, uint32_t a2, uint32_t a3, uint64_t db){
  asm volatile("wgmma.mma_async.sync.aligned.m64n112k16.f32.bf16.bf16 {%0, %1, %2, %3, %4, %5, %6, %7, %8, %9, %10, %11, %12, %13, %14, %15, %16, %17, %18, %19, %20, %21, %22, %23, %24, %25, %26, %27, %28, %29, %30, %31, %32, %33, %34, %35, %36, %37, %38, %39, %40, %41, %42, %43, %44, %45, %46, %47, %48, %49, %50, %51, %52, %53, %54, %55}, {%56,%57,%58,%59}, %60, 1, 1, 1, 0;\n"
    : "+f"(d[8]), "+f"(d[9]), "+f"(d[10]), "+f"(d[11]), "+f"(d[12]), "+f"(d[13]), "+f"(d[14]), "+f"(d[15]), "+f"(d[16]), "+f"(d[17]), "+f"(d[18]), "+f"(d[19]), "+f"(d[20]), "+f"(d[21]), "+f"(d[22]), "+f"(d[23]), "+f"(d[24]), "+f"(d[25]), "+f"(d[26]), "+f"(d[27]), "+f"(d[28]), "+f"(d[29]), "+f"(d[30]), "+f"(d[31]), "+f"(d[32]), "+f"(d[33]), "+f"(d[34]), "+f"(d[35]), "+f"(d[36]), "+f"(d[37]), "+f"(d[38]), "+f"(d[39]), "+f"(d[40]), "+f"(d[41]), "+f"(d[42]), "+f"(d[43]), "+f"(d[44]), "+f"(d[45]), "+f"(d[46]), "+f"(d[47]), "+f"(d[48]), "+f"(d[49]), "+f"(d[50]), "+f"(d[51]), "+f"(d[52]), "+f"(d[53]), "+f"(d[54]), "+f"(d[55]), "+f"(d[56]), "+f"(d[57]), "+f"(d[58]), "+f"(d[59]), "+f"(d[60]), "+f"(d[61]), "+f"(d[62]), "+f"(d[63])
    : "r"(a0), "r"(a1), "r"(a2), "r"(a3), "l"(db));
}
template<> __device__ __forceinline__ void wgmma_rs_hi<128>(float (&d)[64], uint32_t a0, uint32_t a1, uint32_t a2, uint32_t a3, uint64_t db){
  asm volatile("wgmma.mma_async.sync.aligned.m64n128k16.f32.bf16.bf16 {%0, %1, %2, %3, %4, %5, %6, %7, %8, %9, %10, %11, %12, %13, %14, %15, %16, %17, %18, %19, %20, %21, %22, %23, %24, %25, %26, %27, %28, %29, %30, %31, %32, %33, %34, %35, %36, %37, %38, %39, %40, %41, %42, %43, %44, %45, %46, %47, %48, %49, %50, %51, %52, %53, %54, %55, %56, %57, %58, %59, %60, %61, %62, %63}, {%64,%65,%66,%67}, %68, 1, 1, 1, 0;\n"
    : "+f"(d[0]), "+f"(d[1]), "+f"(d[2]), "+f"(d[3]), "+f"(d[4]), "+f"(d[5]), "+f"(d[6]), "+f"(d[7]), "+f"(d[8]), "+f"(d[9]), "+f"(d[10]), "+f"(d[11]), "+f"(d[12]), "+f"(d[13]), "+f"(d[14]), "+f"(d[15]), "+f"(d[16]), "+f"(d[17]), "+f"(d[18]), "+f"(d[19]), "+f"(d[20]), "+f"(d[21]), "+f"(d[22]), "+f"(d[23]), "+f"(d[24]), "+f"(d[25]), "+f"(d[26]), "+f"(d[27]), "+f"(d[28]), "+f"(d[29]), "+f"(d[30]), "+f"(d[31]), "+f"(d[32]), "+f"(d[33]), "+f"(d[34]), "+f"(d[35]), "+f"(d[36]), "+f"(d[37]), "+f"(d[38]), "+f"(d[39]), "+f"(d[40]), "+f"(d[41]), "+f"(d[42]), "+f"(d[43]), "+f"(d[44]), "+f"(d[45]), "+f"(d[46]), "+f"(d[47]), "+f"(d[48]), "+f"(d[49]), "+f"(d[50]), "+f"(d[51]), "+f"(d[52]), "+f"(d[53]), "+f"(d[54]), "+f"(d[55]), "+f"(d[56]), "+f"(d[57]), "+f"(d[58]), "+f"(d[59]), "+f"(d[60]), "+f"(d[61]), "+f"(d[62]), "+f"(d[63])
    : "r"(a0), "r"(a1), "r"(a2), "r"(a3), "l"(db));
}

__device__ __forceinline__ void cv_copy(float (&acc)[64]) {
#pragma unroll
  for (int i = 0; i < 64; i++) { float t; asm volatile("mov.b32 %0, %1;" : "=f"(t) : "f"(acc[i]) : "memory"); acc[i] = t; }
}
template <int D0> __device__ __forceinline__ void cv_loadA(uint32_t (&A)[4][4], uint32_t kaddr) {
#pragma unroll
  for (int i = 0; i < 4; i++) {
    uint32_t a = kaddr + (D0 + i) * 128;
    uint32_t w0 = lds32(a), w1 = lds32(a + 4), w2 = lds32(a + 8);
    A[i][0] = __byte_perm(w0, w1, 0x5432); A[i][1] = w1; A[i][2] = __byte_perm(w1, w2, 0x5432); A[i][3] = w2;
  }
#pragma unroll
  for (int i = 0; i < 4; i++) asm volatile("" : "+r"(A[i][0]), "+r"(A[i][1]), "+r"(A[i][2]), "+r"(A[i][3])::"memory");
}
template <int G> __device__ __forceinline__ void cv_rec(float (&acc)[64], const uint32_t (&A)[4][4], uint32_t kaddr, uint64_t db0) {
  wgmma_fence();
#pragma unroll
  for (int i = 0; i < 4; i++) wgmma_rs_hi<128 - 16 * G>(acc, A[i][0], A[i][1], A[i][2], A[i][3], db0 - (uint64_t)(4 * i));
  wgmma_commit();
  if constexpr (G < 7) {
    uint32_t B[4][4];
    cv_loadA<4 * (G + 1)>(B, kaddr);
    wgmma_wait<0>(); cv_copy(acc);
    cv_rec<G + 1>(acc, B, kaddr, db0);
  } else { wgmma_wait<0>(); cv_copy(acc); }
}
__device__ __forceinline__ void conv_channel(const Params& p, uint32_t sb, int slot, int ch, int dg, int barid) {
  const int tid = threadIdx.x & 127, w = tid >> 5, lane = tid & 31, r = lane >> 2, q = lane & 3;
  const int i_ = r >> 1, i0 = i_ & 1, i1 = i_ >> 1;
  const int bl = 4 * (r & 1) + 2 * (w & 1) + 8 * (w >> 1);
  const uint32_t cb = sb + CV_OFF + slot * CV_B;
  uint32_t dd = (uint32_t)__bfloat16_as_ushort(p.ssmD[ch]); dd |= dd << 16;
  mbar_wait(sb + BAR_OFF + 8 * (B_CVFULL + slot));
  const uint32_t kaddr = cb + CV_K - 32 + 4 * (8 * i_ + (bl >> 1) + 2 * q);
  const uint64_t db0 = make_desc(cb + CV_U + 192, CV_PL, 128, 0);
  float acc[64];
#pragma unroll
  for (int i = 0; i < 64; i++) acc[i] = 0.f;
  uint32_t A[4][4];
  cv_loadA<0>(A, kaddr);
  cv_copy(acc);
  cv_rec<0>(acc, A, kaddr, db0);
  float E[8][4];
  const int src1 = i1 == 0 ? (lane - q + 16 + ((q + 3) & 3)) : (lane - q - 16 + ((q + 1) & 3));
  const bool s3 = (i1 == 1 && q == 3), kodd = (i1 == 1 && q < 3);
#pragma unroll
  for (int J = 0; J < 8; J++)
#pragma unroll
    for (int x = 0; x < 4; x++) {
      float ev = acc[8 * J + x], od = acc[8 * J + 4 + x], pv = J > 0 ? acc[8 * J - 4 + x] : 0.f;
      float send = kodd ? ev : (s3 ? pv : od);
      float keep = kodd ? od : ev;
      E[J][x] = keep + __shfl_sync(0xffffffffu, send, src1);
    }
  const int P = i1 == 0 ? q : 4 + ((q + 1) & 3);
  const int Pm = (P + 7) & 7, qm = Pm < 4 ? Pm : ((Pm - 1) & 3), i1m = Pm >> 2;
  const int src2 = i0 == 1 ? lane - 8 : (16 * i1m + 8 + 4 * (r & 1) + qm);
  const bool wrap = (i0 == 1 && P == 7);
  const uint32_t kvaddr = cb + CV_U + 192 + (((14 - bl) >> 1) & 1) * CV_PL + (2 * P + i0) * 16 + ((14 - bl) >> 2) * 4;
  uint32_t gw[8];
#pragma unroll
  for (int J = 0; J < 8; J++) {
    float o[2];
#pragma unroll
    for (int h = 0; h < 2; h++) {
      float pv = J > 0 ? E[J - 1][2 * h + 1] : 0.f;
      float send = wrap ? pv : E[J][2 * h + 1];
      o[h] = E[J][2 * h] + __shfl_sync(0xffffffffu, send, src2);
    }
    uint32_t kvw = lds32(kvaddr + J * 256);
    kvw = __byte_perm(kvw, kvw, 0x1032);
    gw[J] = hadd2(pack_bf16(o[0], o[1]), hmul2(kvw, dd));
  }
  bar_sync(barid, 128);
#pragma unroll
  for (int J = 0; J < 8; J++) {
    int t = 256 * J + 16 * (2 * P + i0) + bl;
    int T = t / 160, tl = t - T * 160;
    int qq = (T == NT1 - 1) ? (tl >> 5) : (tl / 40);
    int j = (tl - qq * ((T == NT1 - 1) ? 32 : 40)) >> 1;
    int c = 20 * T + j;
    c = c ^ ((c >> 3) & 7);
    sts32(cb + CV_K + c * 16 + qq * 4, gw[J]);
  }
  fence_async_smem();
  bar_sync(barid, 128);
  if (tid == 0) {
    bulk_s2g(g_G + (size_t)ch * 4096, cb + CV_K, 4096);
    asm volatile("cp.async.bulk.commit_group;" ::: "memory");
    asm volatile("cp.async.bulk.wait_group 0;" ::: "memory");
    fence_async_global();
    red_rel(&g_gcnt[dg * 32], 1);
  }
}

__device__ __forceinline__ void kv_tile(const Params& p, int m, int c0) {
  const int lane = threadIdx.x & 31, cg = lane & 7, tg = lane >> 3;
  const int ch = c0 + 4 * cg, t0 = 64 * m + 16 * tg;
  uint2 kk[19], vv[16];
#pragma unroll
  for (int i = 0; i < 19; i++) {
    int t = t0 - 3 + i;
    kk[i] = (t >= 0) ? __ldg((const uint2*)(p.k + (size_t)t * DM + ch)) : make_uint2(0u, 0u);
  }
#pragma unroll
  for (int i = 0; i < 16; i++) vv[i] = __ldg((const uint2*)(p.v + (size_t)(t0 + i) * DM + ch));
  const uint4 s0 = __ldg((const uint4*)(p.shiftk + ch * 4)), s1 = __ldg((const uint4*)(p.shiftk + ch * 4 + 8));
  const uint32_t wa[4] = {__byte_perm(s0.x, s0.z, 0x5410), __byte_perm(s0.x, s0.z, 0x7632), __byte_perm(s0.y, s0.w, 0x5410), __byte_perm(s0.y, s0.w, 0x7632)};
  const uint32_t wb[4] = {__byte_perm(s1.x, s1.z, 0x5410), __byte_perm(s1.x, s1.z, 0x7632), __byte_perm(s1.y, s1.w, 0x5410), __byte_perm(s1.y, s1.w, 0x7632)};
#pragma unroll
  for (int i = 0; i < 16; i++) {
    uint32_t a = hmul2(kk[i].x, wa[3]);
    a = hadd2(a, hmul2(kk[i + 1].x, wa[2])); a = hadd2(a, hmul2(kk[i + 2].x, wa[1])); a = hadd2(a, hmul2(kk[i + 3].x, wa[0]));
    vv[i].x = hmul2(a, vv[i].x);
    uint32_t b = hmul2(kk[i].y, wb[3]);
    b = hadd2(b, hmul2(kk[i + 1].y, wb[2])); b = hadd2(b, hmul2(kk[i + 2].y, wb[1])); b = hadd2(b, hmul2(kk[i + 3].y, wb[0]));
    vv[i].y = hmul2(b, vv[i].y);
  }
  uint8_t* dst = g_kv + (size_t)ch * 4096 + (4 * m + tg) * 16;
#pragma unroll
  for (int c = 0; c < 4; c++)
#pragma unroll
    for (int f = 0; f < 2; f++) {
      uint32_t o[4];
#pragma unroll
      for (int qq = 0; qq < 4; qq++) {
        const int ia = 15 - 4 * qq - 2 * f, ib = ia - 1;
        uint32_t xa = (c < 2) ? vv[ia].x : vv[ia].y, xb = (c < 2) ? vv[ib].x : vv[ib].y;
        o[qq] = __byte_perm(xa, xb, (c & 1) ? 0x7632 : 0x5410);
      }
      *(uint4*)(dst + c * 4096 + f * 2048) = make_uint4(o[0], o[1], o[2], o[3]);
    }
}

__device__ __forceinline__ void stats_publish(int which, int n0, int dg, unsigned tag, const float (&acc)[80]) {
  const int q = threadIdx.x & 3;
  float s1[2] = {0.f, 0.f}, s2[2] = {0.f, 0.f}, t1[2] = {0.f, 0.f}, t2[2] = {0.f, 0.f};
#pragma unroll
  for (int j = 0; j < 20; j++)
#pragma unroll
    for (int h = 0; h < 2; h++) {
      float a = acc[4 * j + 2 * h], b = acc[4 * j + 2 * h + 1];
      s1[h] += a; t1[h] += b; s2[h] = fmaf(a, a, s2[h]); t2[h] = fmaf(b, b, t2[h]);
    }
#pragma unroll
  for (int h = 0; h < 2; h++) {
    s1[h] += t1[h]; s2[h] += t2[h];
    s1[h] += __shfl_xor_sync(0xffffffffu, s1[h], 1); s2[h] += __shfl_xor_sync(0xffffffffu, s2[h], 1);
    s1[h] += __shfl_xor_sync(0xffffffffu, s1[h], 2); s2[h] += __shfl_xor_sync(0xffffffffu, s2[h], 2);
  }
  if (q < 2) {
    float a = q ? s1[1] : s1[0], b = q ? s2[1] : s2[0];
    float mean = a * (1.f / 160.f);
    rec_st(&g_stats[((size_t)which * SEQ + n0 + 8 * q) * 4 + dg], mean, fmaxf(b - a * mean, 0.f), tag);
  }
}
__device__ __forceinline__ void stats_combine(float mi, float m2, float& mean, float& rstd) {
  float m = mi + __shfl_xor_sync(0xffffffffu, mi, 1);
  m += __shfl_xor_sync(0xffffffffu, m, 2);
  m *= 0.25f;
  float d = mi - m;
  float v = fmaf(160.f * d, d, m2);
  v += __shfl_xor_sync(0xffffffffu, v, 1);
  v += __shfl_xor_sync(0xffffffffu, v, 2);
  mean = m; rstd = rsqrtf(v * (1.f / 640.f) + 1e-5f);
}
__device__ __forceinline__ void stats_get(int which, int n0, unsigned tag, float (&mean)[2], float (&rstd)[2]) {
  const int q = threadIdx.x & 3;
  const uint4* p0 = &g_stats[((size_t)which * SEQ + n0) * 4 + q];
  float a0, b0, a1, b1;
  uint32_t it = 0;
  while (true) {
    unsigned t0 = rec_ld(p0, a0, b0), t1 = rec_ld(p0 + 32, a1, b1);
    if (t0 == tag && t1 == tag) break;
    if (++it > SPIN_LIMIT) __trap();
  }
  __syncwarp();
  stats_combine(a0, b0, mean[0], rstd[0]);
  stats_combine(a1, b1, mean[1], rstd[1]);
}
__device__ __forceinline__ void load_x0(const Params& p, const int (&trow)[2], int d0, float (&acc)[80]) {
  const int q = threadIdx.x & 3;
  uint2 xv[2][10];
#pragma unroll
  for (int h = 0; h < 2; h++)
#pragma unroll
    for (int J = 0; J < 10; J++) xv[h][J] = __ldg((const uint2*)(p.x + (size_t)trow[h] * DM + d0 + 16 * J + 4 * q));
#pragma unroll
  for (int h = 0; h < 2; h++)
#pragma unroll
    for (int J = 0; J < 10; J++) {
      acc[8 * J + 2 * h] = bf_lo(xv[h][J].x); acc[8 * J + 2 * h + 1] = bf_hi(xv[h][J].x);
      acc[8 * J + 4 + 2 * h] = bf_lo(xv[h][J].y); acc[8 * J + 4 + 2 * h + 1] = bf_hi(xv[h][J].y);
    }
}
__device__ __forceinline__ void apply_dskip(uint32_t sb, float (&acc)[80], const float (&mean)[2], const float (&rstd)[2]) {
  const int q = threadIdx.x & 3;
#pragma unroll
  for (int J = 0; J < 10; J++) {
    float2 dw = lds64f(sb + DTAB_OFF + 2 * (16 * J + 4 * q));
    uint32_t w0 = __float_as_uint(dw.x), w1 = __float_as_uint(dw.y);
    float dv[4] = {bf_lo(w0), bf_hi(w0), bf_lo(w1), bf_hi(w1)};
#pragma unroll
    for (int h = 0; h < 2; h++)
#pragma unroll
      for (int x = 0; x < 4; x++) {
        float& a = acc[8 * J + 4 * (x >> 1) + 2 * h + (x & 1)];
        a = (a - mean[h]) * fmaf(rstd[h], dv[x], 1.f);
      }
  }
}

__global__ void __launch_bounds__(512, 1) fused_kernel(const __grid_constant__ Params p) {
  extern __shared__ __align__(1024) uint8_t smem_raw[];
  const uint32_t sb = smem_u32(smem_raw);
  const int tid = threadIdx.x, wg = tid >> 7, lane = tid & 31;
  const int side = blockIdx.x & 1;
  int gpc, gi;
  {
    int tpc = ((blockIdx.x >> 1) + 62) % 66;
    if (tpc < 32) { gpc = tpc & 7; gi = tpc >> 3; }
    else if (tpc < 60) { gpc = 1 + (tpc - 32) % 7; gi = 4 + (tpc - 32) / 7; }
    else if (tpc < 62) { gpc = tpc - 54; gi = 8; }
    else { gpc = 0; gi = tpc - 58; }
  }
  const int pos = 8 * gpc + gi + (gpc == 7 ? 1 : 0);
  if (pos == 65) return;
  int T1, GP;
  if (pos < 52) { int hh = pos / 26, x = pos - 26 * hh; T1 = x >> 1; GP = 2 * hh + (x & 1); }
  else { T1 = pos - 52; GP = 4; }
  const bool has2 = gi < 8;
  const int m2 = 8 * (gpc >> 1) + gi, dg = 2 * (gpc & 1) + side;
  const int cch0 = 5 * (32 * dg + m2);

  if (sb & 1023) __trap();
  if (tid < NBAR) {
    int cnt = 1;
    if (tid < B_G2DONE) cnt = 2;
    else if (tid >= B_CVFULL && tid < B_GFULL) cnt = 2;
    else if (tid >= B_CTAB && tid < B_EPOCH) cnt = 32;
    mbar_init(sb + BAR_OFF + 8 * tid, cnt);
    asm volatile("fence.mbarrier_init.release.cluster;" ::: "memory");
  } else if (tid >= 256 && tid < 256 + 5 * 32) {
    int c = (tid - 256) >> 5, x = lane;
    uint32_t cb = sb + CV_OFF + c * CV_B;
    uint32_t a = x < 8 ? cb + 16 * x : (x < 20 ? cb + CV_U + 16 * (x - 8) : cb + CV_U + CV_PL + 16 * (x - 20));
    asm volatile("st.shared.v4.u32 [%0], {%1,%1,%1,%1};" ::"r"(a), "r"(0) : "memory");
    fence_async_smem();
  }
  __syncthreads();
  const uint32_t bars = sb + BAR_OFF;

  if (wg == 3) {
    asm volatile("setmaxnreg.dec.sync.aligned.u32 40;");
    const int pw = (tid >> 5) & 3;
    if (pw == 0) {
      for (int l = 0; l < 2; l++) {
        if (l == 1) mbar_wait(bars + 8 * (has2 ? B_G2DONE + 19 : B_G1DONE + 9));
        for (int k = 0; k < 10; k++) {
          if (k >= S1) mbar_wait(bars + 8 * (B_G1DONE + 10 * l + k - S1));
          const uint32_t fb = bars + 8 * (B_G1FULL + 10 * l + k);
          if (lane == 0) mbar_expect_tx(fb, 16384);
          __syncwarp();
          if (lane < 8) tma4(sb + (k % S1) * G1_STAGE + lane * 2048, (lane & 1) ? &p.mBim : &p.mBre, 64 * k, 0, 2 * GP, 4 * side + (lane >> 1), fb);
        }
        if (has2) {
          const int SW = l == 0 ? 6 : 7;
          mbar_wait(bars + 8 * (B_G1DONE + 10 * l + 9));
          if (lane == 0) {
            int s = 0;
            for (int k = 0; k < 20; k++) {
              if (k >= SW) mbar_wait(bars + 8 * (B_G2DONE + 20 * l + k - SW));
              const uint32_t fb = bars + 8 * (B_G2FULL + 20 * l + k);
              mbar_expect_tx(fb, G2_WB);
              const int w = k / 10, x = k - 10 * w;
              tma5(sb + G2_WOFF + s * G2_WB, (x & 1) ? &p.mCim : &p.mCre, 128 * (x >> 1) + 64 * w, 0, 0, 0, 10 * dg, fb);
              if (++s == SW) s = 0;
            }
          }
          __syncwarp();
        }
      }
    } else if (pw == 1) {
      for (int l = 0; l < 2; l++) {
        unsigned tag = 0;
        if (l == 1) {
          tag = lds32(sb + EPOCH_OFF);
          mbar_wait(bars + 8 * (has2 ? B_G2DONE + 19 : B_G1DONE + 9));
          const int mlo = (160 * T1) >> 6, nf = (T1 == NT1 - 1) ? 8 : 12;
          if (lane < nf) flag_poll(&g_uflag[4 * mlo + lane], tag);
          __syncwarp();
          fence_async_global();
          if (lane == 0) TS(20);
        }
        if (lane == 0) {
          for (int k = 0; k < 10; k++) {
            if (k >= S1) mbar_wait(bars + 8 * (B_G1DONE + 10 * l + k - S1));
            const uint32_t fb = bars + 8 * (B_G1FULL + 10 * l + k), dst = sb + (k % S1) * G1_STAGE + G1_XOFF;
            if (l == 0) {
              mbar_expect_tx(fb, 20480);
              if (T1 == NT1 - 1) tma4(dst, &p.mXl, 64 * k, 0, 0, 0, fb); else tma4(dst, &p.mX, 64 * k, 0, 0, 80 * T1, fb);
            } else {
              const int bytes = (T1 == NT1 - 1) ? 16384 : 20480;
              mbar_expect_tx(fb, bytes);
              bulk_g2s(dst, g_u + (size_t)(T1 * 10 + k) * 20480, bytes, fb);
            }
          }
        }
        __syncwarp();
        if (l == 0) { mbar_wait(bars + 8 * B_EPOCH); tag = lds32(sb + EPOCH_OFF); }
        if (has2) {
          mbar_wait(bars + 8 * (B_G1DONE + 10 * l + 9));
          const int Tlo = (64 * m2) / 160, Thi = (64 * m2 + 63) / 160;
          int s = 0;
          for (int w = 0; w < 2; w++) {
            if ((lane & 15) < 10) flag_poll(&g_hflag[((l * NT1 + (lane < 16 ? Tlo : Thi)) * 2 + w) * 16 + (lane & 15)], tag);
            __syncwarp();
            fence_async_global();
            if (lane == 0) {
              TS(21 + 2 * l + w);
              for (int k = 10 * w; k < 10 * w + 10; k++) {
                if (k >= SX2) mbar_wait(bars + 8 * (B_G2DONE + 20 * l + k - SX2));
                const uint32_t fb = bars + 8 * (B_G2FULL + 20 * l + k);
                mbar_expect_tx(fb, G2_XB);
                bulk_g2s(sb + s * G2_XB, g_h + (size_t)((l * 32 + m2) * 20 + k) * 8192, G2_XB, fb);
                if (++s == SX2) s = 0;
              }
            }
            __syncwarp();
          }
        }
      }
    } else if (pw == 2) {
      float cv[2][4];
#pragma unroll
      for (int i = 0; i < 2; i++) {
        const int ch = 128 * GP + 64 * i + 32 * side + lane;
        const float lr = __bfloat162float(p.lre[ch]), li = __bfloat162float(p.lim[ch]);
        const float dt = __bfloat162float(__float2bfloat16_rn(expf(__bfloat162float(p.logdt[ch]))));
        const float mag = expf(dt * lr);
        float sn, cs; sincosf(dt * li, &sn, &cs);
        const float ar = mag * cs, ai = mag * sn;
        const float inv = 2.f / (lr * lr + li * li);
        cv[i][0] = ar; cv[i][1] = ai;
        cv[i][2] = ((ar - 1.f) * lr + ai * li) * inv; cv[i][3] = (ai * lr - (ar - 1.f) * li) * inv;
      }
      mbar_wait(bars + 8 * B_EPOCH);
      const unsigned tag = lds32(sb + EPOCH_OFF);
#pragma unroll
      for (int i = 0; i < 2; i++) {
        float a, b;
        rec_poll(&g_sB[128 * GP + 64 * i + 32 * side + lane], tag, a, b);
        const uint32_t ad = sb + CTAB_OFF + (32 * i + lane) * 24;
        sts64f(ad, cv[i][0], cv[i][1]); sts64f(ad + 8, cv[i][2], cv[i][3]); sts64f(ad + 16, a, b);
      }
      mbar_arrive(bars + 8 * B_CTAB);
      const int ngr = (T1 == NT1 - 1) ? 16 : 20;
      for (int l = 0; l < 2; l++) {
        if (l == 1) mbar_wait(bars + 8 * (B_G1FULL + 10));
        for (int g0 = 0; g0 < ngr; g0 += 4) {
          float a[4], b[4];
          const uint4* rp = &g_stats[((size_t)(2 * l) * SEQ + 160 * T1 + 8 * g0) * 4 + lane];
          uint32_t it = 0;
          while (true) {
            bool ok = true;
#pragma unroll
            for (int i = 0; i < 4; i++) ok &= (rec_ld(rp + 32 * i, a[i], b[i]) == tag);
            if (ok) break;
            if (++it > SPIN_LIMIT) __trap();
          }
          __syncwarp();
#pragma unroll
          for (int i = 0; i < 4; i++) {
            float mean, rstd;
            stats_combine(a[i], b[i], mean, rstd);
            if ((lane & 3) == 0) sts64f(sb + STAB_OFF + (8 * (g0 + i) + (lane >> 2)) * 8, rstd, -mean * rstd);
          }
        }
        mbar_arrive(bars + 8 * (B_STAB + l));
        if (lane == 0) TS(26 + l);
      }
    } else {
      unsigned tag = 0;
      if (lane == 0) {
        asm volatile("ld.relaxed.gpu.global.u32 %0, [%1];" : "=r"(tag) : "l"(g_epoch) : "memory");
      }
      if (has2) {
        for (int i = lane; i < 67; i += 32) { int t = 64 * m2 - 3 + i; if (t >= 0) l2_prefetch(p.k + (size_t)t * DM + 160 * dg, 320); }
        for (int i = lane; i < 64; i += 32) l2_prefetch(p.v + (size_t)(64 * m2 + i) * DM + 160 * dg, 320);
      }
      if (lane == 0) {
        tag += 1;
        sts32(sb + EPOCH_OFF, tag);
        mbar_arrive(bars + 8 * B_EPOCH);
      }
      tag = __shfl_sync(0xffffffffu, tag, 0);
      if (has2) {
        mbar_wait(bars + 8 * (B_G1FULL + 2));
        if (lane < 5) {
          const uint32_t fb = bars + 8 * (B_CVFULL + lane);
          mbar_expect_tx(fb, 4096);
          bulk_g2s(sb + CV_OFF + lane * CV_B + CV_K, p.ssmk + (size_t)(cch0 + lane) * SEQ, 4096, fb);
        } else if (lane < 7) {
          l2_prefetch((lane == 5 ? p.cre : p.cim) + (size_t)cch0 * DM, 6400);
        }
        if (lane == 0) flag_poll(&g_kvcnt[dg * 32], tag * 32);
        __syncwarp();
        fence_async_global();
        if (lane == 0) TS(28);
        if (lane < 5) {
          const uint32_t fb = bars + 8 * (B_CVFULL + lane), cb = sb + CV_OFF + lane * CV_B + CV_U + 192;
          mbar_expect_tx(fb, 4096);
          bulk_g2s(cb, g_kv + (size_t)(cch0 + lane) * 4096, 2048, fb);
          bulk_g2s(cb + CV_PL, g_kv + (size_t)(cch0 + lane) * 4096 + 2048, 2048, fb);
        }
        if (lane == 0) {
          flag_poll(&g_gcnt[dg * 32], tag * 160);
          fence_async_global();
          TS(29);
          mbar_expect_tx(bars + 8 * B_GFULL, 20480);
          tma5(sb + G_OFF, &p.mG, 64 * m2, 0, 0, 0, 10 * dg, bars + 8 * B_GFULL);
        }
      }
    }
  } else if (wg == 2) {
    asm volatile("setmaxnreg.inc.sync.aligned.u32 168;");
    if (has2) {
      const int w = (tid >> 5) & 3, r = lane >> 2, q = lane & 3;
      const int n0 = 64 * m2 + 16 * w + r, d0 = 160 * dg;
      const int trow[2] = {n_to_t(n0), n_to_t(n0 + 8)};
      float acc[80];
      kv_tile(p, m2, d0 + 32 * w);
      if ((tid & 127) < 20) {
        uint4 dv = __ldg((const uint4*)(p.dskip + d0) + (tid & 127));
        asm volatile("st.shared.v4.u32 [%0], {%1,%2,%3,%4};" ::"r"(sb + DTAB_OFF + 16 * (tid & 127)), "r"(dv.x), "r"(dv.y), "r"(dv.z), "r"(dv.w) : "memory");
      }
      mbar_wait(bars + 8 * B_EPOCH);
      const unsigned tag = lds32(sb + EPOCH_OFF);
      if (w == 0) kv_tile(p, m2, d0 + 128);
      else {
        for (int c = 2 * (w - 1); c < 2 * w && c < 5; c++) {
          float s[2];
#pragma unroll
          for (int part = 0; part < 2; part++) {
            const uint2* row = (const uint2*)((part ? p.bim : p.bre) + (size_t)(cch0 + c) * DM);
            float a = 0.f;
#pragma unroll
            for (int i = 0; i < 5; i++) { uint2 x = __ldg(row + lane + 32 * i); a += (bf_lo(x.x) + bf_hi(x.x)) + (bf_lo(x.y) + bf_hi(x.y)); }
#pragma unroll
            for (int o = 16; o > 0; o >>= 1) a += __shfl_xor_sync(0xffffffffu, a, o);
            s[part] = a;
          }
          if (lane == 0) rec_st(&g_sB[cch0 + c], s[0], s[1], tag);
        }
      }
      bar_sync(3, 128);
      if ((tid & 127) == 0) { red_rel(&g_kvcnt[dg * 32], 1); TS(30); }
      load_x0(p, trow, d0, acc);
      {
        float sh[2];
#pragma unroll
        for (int h = 0; h < 2; h++) sh[h] = __shfl_sync(0xffffffffu, acc[2 * h], lane & ~3);
        float s1[2] = {0.f, 0.f}, s2[2] = {0.f, 0.f};
#pragma unroll
        for (int i = 0; i < 80; i++) { const int h = (i >> 1) & 1; float a = acc[i] - sh[h]; s1[h] += a; s2[h] = fmaf(a, a, s2[h]); }
#pragma unroll
        for (int h = 0; h < 2; h++) {
          s1[h] += __shfl_xor_sync(0xffffffffu, s1[h], 1); s2[h] += __shfl_xor_sync(0xffffffffu, s2[h], 1);
          s1[h] += __shfl_xor_sync(0xffffffffu, s1[h], 2); s2[h] += __shfl_xor_sync(0xffffffffu, s2[h], 2);
        }
        if (q < 2) {
          float a = q ? s1[1] : s1[0], b = q ? s2[1] : s2[0], c = q ? sh[1] : sh[0];
          float mean = a * (1.f / 160.f);
          rec_st(&g_stats[((size_t)n0 + 8 * q) * 4 + dg], mean + c, fmaxf(b - a * mean, 0.f), tag);
        }
      }
      if ((tid & 127) == 0) TS(31);
      for (int c = 0; c < 2; c++) conv_channel(p, sb, c, cch0 + c, dg, 3);
      if ((tid & 127) == 0) TS(32);
      float off[2], mean[2], rstd[2];
      load_x0(p, trow, d0, acc);
      stats_get(0, n0, tag, mean, rstd);
      apply_dskip(sb, acc, mean, rstd);
      off[0] = mean[0]; off[1] = mean[1];
      for (int l = 0; l < 2; l++) {
        const int SW = l == 0 ? 6 : 7;
        int sx = 0, sw = 0;
        fence_regs(acc);
        for (int k = 0; k < 20; k++) {
          mbar_wait(bars + 8 * (B_G2FULL + 20 * l + k));
          if (k == 0 && (tid & 127) == 0) TS(33 + 6 * l);
          const uint64_t da = make_desc(sb + sx * G2_XB, 1024, 128, 0);
          const uint64_t db = make_desc(sb + G2_WOFF + sw * G2_WB, 16, 1024, 1);
          wgmma_fence();
#pragma unroll
          for (int kk = 0; kk < 4; kk++) wgmma_n160<1>(acc, da + kk * 128, db + kk * 2, 1);
          wgmma_commit();
          if (k > 0) { wgmma_wait<1>(); if ((tid & 127) == 0) mbar_arrive(bars + 8 * (B_G2DONE + 20 * l + k - 1)); }
          if (++sx == SX2) sx = 0;
          if (++sw == SW) sw = 0;
        }
        wgmma_wait<0>();
        fence_regs(acc);
        if ((tid & 127) == 0) { mbar_arrive(bars + 8 * (B_G2DONE + 20 * l + 19)); TS(34 + 6 * l); }
        stats_publish(2 * l + 1, n0, dg, tag, acc);
        if (l == 0) mbar_wait(bars + 8 * B_GFULL);
        uint32_t gf[10][4];
        {
          const int mi = lane >> 3, c = lane & 7;
          const uint32_t ga = sb + G_OFF + (8 * (mi >> 1) + c) * 128 + (((2 * w + (mi & 1)) ^ (m2 & 7) ^ c) << 4);
#pragma unroll
          for (int J = 0; J < 10; J++)
            asm volatile("ldmatrix.sync.aligned.m8n8.x4.trans.shared.b16 {%0,%1,%2,%3}, [%4];"
                         : "=r"(gf[J][0]), "=r"(gf[J][1]), "=r"(gf[J][2]), "=r"(gf[J][3]) : "r"(ga + J * 2048) : "memory");
        }
        if ((tid & 127) == 0) TS(35 + 6 * l);
        stats_get(2 * l + 1, n0, tag, mean, rstd);
        if ((tid & 127) == 0) TS(36 + 6 * l);
        off[0] += mean[0]; off[1] += mean[1];
#pragma unroll
        for (int h = 0; h < 2; h++) {
          const int ng = (n0 >> 3) + h, T = ng / 20;
          uint8_t* ub = g_u + (size_t)T * 204800 + (ng - 20 * T) * 1024 + (q >> 1) * 128 + r * 16 + (q & 1) * 8;
          float* ob = p.out + (size_t)trow[h] * DM + d0 + 4 * q;
#pragma unroll
          for (int J = 0; J < 10; J++) {
            float y[4];
#pragma unroll
            for (int x = 0; x < 4; x++) {
              const uint32_t gwd = gf[J][2 * (x >> 1) + h];
              const float g = (x & 1) ? bf_hi(gwd) : bf_lo(gwd);
              float& a = acc[8 * J + 4 * (x >> 1) + 2 * h + (x & 1)];
              a = (a - mean[h]) * fmaf(rstd[h], g, 1.f);
              y[x] = a;
            }
            if (l == 0) {
              const int J16 = 10 * dg + J;
              *(uint2*)(ub + (J16 >> 2) * 20480 + (J16 & 3) * 256) = make_uint2(pack_bf16(y[0], y[1]), pack_bf16(y[2], y[3]));
            } else {
              *(float4*)(ob + 16 * J) = make_float4(y[0] + off[h], y[1] + off[h], y[2] + off[h], y[3] + off[h]);
            }
          }
        }
        if (l == 0) {
          bar_sync(3, 128);
          if ((tid & 127) == 0) { TS(37); st_rel(&g_uflag[4 * m2 + dg], tag); TS(38); }
          stats_publish(2, n0, dg, tag, acc);
          stats_get(2, n0, tag, mean, rstd);
          apply_dskip(sb, acc, mean, rstd);
          off[0] += mean[0]; off[1] += mean[1];
        } else {
          if ((tid & 127) == 0) {
            TS(43);
            if (m2 == 31 && dg == 3) asm volatile("st.relaxed.gpu.global.u32 [%0], %1;" ::"l"(g_epoch), "r"(tag) : "memory");
          }
        }
      }
    }
  } else {
    asm volatile("setmaxnreg.inc.sync.aligned.u32 152;");
    const int w = (tid >> 5) & 3, r = lane >> 2, q = lane & 3;
    const bool last = (T1 == NT1 - 1);
    const int ch = 128 * GP + 64 * wg + 32 * side + 8 * w + r;
    for (int l = 0; l < 2; l++) {
      float acc[80];
#pragma unroll
      for (int i = 0; i < 80; i++) acc[i] = 0.f;
      fence_regs(acc);
      const uint64_t da0 = make_desc(sb + wg * 1024, 16, 2048, 1);
      const uint64_t db0 = l == 0 ? make_desc(sb + G1_XOFF, 16, 1024, 1) : make_desc(sb + G1_XOFF, 128, 1024, 0);
      const int xstep = l == 0 ? 2 : 16;
      int s = 0;
      for (int k = 0; k < 10; k++) {
        mbar_wait(bars + 8 * (B_G1FULL + 10 * l + k));
        if (k == 0 && tid == 0) TS(1 + 8 * l);
        const uint64_t da = da0 + s * (G1_STAGE >> 4), db = db0 + s * (G1_STAGE >> 4);
        wgmma_fence();
#pragma unroll
        for (int kk = 0; kk < 4; kk++) wgmma_n160<0>(acc, da + kk * 2, db + kk * xstep, 1);
        wgmma_commit();
        if (k > 0) { wgmma_wait<1>(); if ((tid & 127) == 0) mbar_arrive(bars + 8 * (B_G1DONE + 10 * l + k - 1)); }
        if (++s == S1) s = 0;
      }
      mbar_wait(bars + 8 * B_CTAB);
      const unsigned tag = lds32(sb + EPOCH_OFF);
      const uint32_t ca = sb + CTAB_OFF + (32 * wg + 8 * w + r) * 24;
      const float2 lam = lds64f(ca), coef = lds64f(ca + 8), sB = lds64f(ca + 16);
      float2 pL, p2L, pLq, p160q, p640;
      {
        float2 p2 = cmul(lam, lam), p4 = cmul(p2, p2), p8 = cmul(p4, p4), p16 = cmul(p8, p8), p32 = cmul(p16, p16);
        float2 p40 = cmul(p32, p8), p80 = cmul(p40, p40), p160 = cmul(p80, p80), p320 = cmul(p160, p160);
        p640 = cmul(p320, p320);
        pL = last ? p32 : p40;
        p2L = cmul(pL, pL);
        const float2 one = make_float2(1.f, 0.f);
        pLq = cmul((q & 1) ? pL : one, (q & 2) ? p2L : one);
        p160q = cmul((q & 1) ? p160 : one, (q & 2) ? p320 : one);
      }
      mbar_wait(bars + 8 * (B_STAB + l));
      wgmma_wait<0>();
      fence_regs(acc);
      if ((tid & 127) == 0) { mbar_arrive(bars + 8 * (B_G1DONE + 10 * l + 9)); if (wg == 0) TS(2 + 8 * l); }
      float2 e = make_float2(0.f, 0.f), snap = e;
#pragma unroll
      for (int j = 0; j < 20; j++) {
        const float4 st = lds128f(sb + STAB_OFF + (8 * j + 2 * q) * 8);
        acc[4 * j + 0] = fmaf(acc[4 * j + 0], st.x, st.y * sB.x);
        acc[4 * j + 2] = fmaf(acc[4 * j + 2], st.x, st.y * sB.y);
        acc[4 * j + 1] = fmaf(acc[4 * j + 1], st.z, st.w * sB.x);
        acc[4 * j + 3] = fmaf(acc[4 * j + 3], st.z, st.w * sB.y);
        e = cfma(lam, e, make_float2(acc[4 * j + 0], acc[4 * j + 2]));
        e = cfma(lam, e, make_float2(acc[4 * j + 1], acc[4 * j + 3]));
        if (j == 15) snap = e;
      }
      if (last) e = snap;
      {
        float2 v = make_float2(__shfl_up_sync(0xffffffffu, e.x, 1, 4), __shfl_up_sync(0xffffffffu, e.y, 1, 4));
        if (q >= 1) e = cfma(pL, v, e);
        v = make_float2(__shfl_up_sync(0xffffffffu, e.x, 2, 4), __shfl_up_sync(0xffffffffu, e.y, 2, 4));
        if (q >= 2) e = cfma(p2L, v, e);
      }
      if (q == 3 && !last) rec_st(&g_E[(l * NT1 + T1) * DM + ch], e.x, e.y, tag);
      if (tid == 0) TS(3 + 8 * l);
      float2 ex = make_float2(__shfl_up_sync(0xffffffffu, e.x, 1, 4), __shfl_up_sync(0xffffffffu, e.y, 1, 4));
      if (q == 0) ex = make_float2(0.f, 0.f);
#pragma unroll
      for (int j = 0; j < 20; j++)
#pragma unroll
        for (int x = 0; x < 2; x++) {
          const float br = acc[4 * j + x], bi = acc[4 * j + 2 + x];
          acc[4 * j + x] = fmaf(br, coef.x, -bi * coef.y);
          acc[4 * j + 2 + x] = fmaf(-br, coef.y, -bi * coef.x);
        }
      float2 c = make_float2(0.f, 0.f);
      {
        float2 ev[3];
        uint32_t it = 0;
        while (true) {
          bool ok = true;
#pragma unroll
          for (int i = 0; i < 3; i++) {
            const int Tp = T1 - 1 - q - 4 * i;
            ev[i] = make_float2(0.f, 0.f);
            if (Tp >= 0) ok &= (rec_ld(&g_E[(l * NT1 + Tp) * DM + ch], ev[i].x, ev[i].y) == tag);
          }
          if (ok) break;
          if (++it > SPIN_LIMIT) __trap();
        }
        __syncwarp();
        c = cfma(p640, cfma(p640, ev[2], ev[1]), ev[0]);
        c = cmul(c, p160q);
        c.x += __shfl_xor_sync(0xffffffffu, c.x, 1); c.y += __shfl_xor_sync(0xffffffffu, c.y, 1);
        c.x += __shfl_xor_sync(0xffffffffu, c.x, 2); c.y += __shfl_xor_sync(0xffffffffu, c.y, 2);
      }
      if (tid == 0) TS(4 + 8 * l);
      float2 hh = cmul(cfma(pLq, c, ex), coef);
      hh.y = -hh.y;
      const float2 lamc = make_float2(lam.x, -lam.y);
      uint8_t* hb = g_h + (size_t)l * (32 * 20 * 8192) + (10 * wg + 2 * GP) * 8192 + (4 * side + w) * 1024 + r * 16 + q * 4;
#pragma unroll
      for (int j4 = 0; j4 < 5; j4++) {
        const int ng = 20 * T1 + 4 * j4;
        uint8_t* hp = hb + (size_t)(ng >> 3) * 163840 + (ng & 7) * 128;
#pragma unroll
        for (int jj = 0; jj < 4; jj++) {
          const int j = 4 * j4 + jj;
          const float2 h0 = cfma(lamc, hh, make_float2(acc[4 * j + 0], acc[4 * j + 2]));
          hh = cfma(lamc, h0, make_float2(acc[4 * j + 1], acc[4 * j + 3]));
          if (j4 < 4 || !last) {
            *(uint32_t*)(hp + jj * 128) = pack_bf16(h0.x, hh.x);
            *(uint32_t*)(hp + jj * 128 + 8192) = pack_bf16(h0.y, hh.y);
          }
        }
      }
      bar_sync(1 + wg, 128);
      if ((tid & 127) == 0) {
        if (wg == 0) TS(5 + 8 * l);
        st_rel(&g_hflag[((l * NT1 + T1) * 2 + wg) * 16 + 2 * GP + side], tag);
        if (wg == 0) TS(6 + 8 * l);
      }
      if (l == 0 && has2) {
        for (int c2 = 2 + wg; c2 < 5; c2 += 2) conv_channel(p, sb, c2, cch0 + c2, dg, 1 + wg);
        if ((tid & 127) == 0) TS(7 + wg);
      }
    }
  }
}

typedef CUresult (*EncFn)(CUtensorMap*, CUtensorMapDataType, cuuint32_t, void*, const cuuint64_t*, const cuuint64_t*,
                          const cuuint32_t*, const cuuint32_t*, CUtensorMapInterleave, CUtensorMapSwizzle,
                          CUtensorMapL2promotion, CUtensorMapFloatOOBfill);

void encode(EncFn fn, CUtensorMap* m, const void* ptr, int rank, const cuuint64_t* dims, const cuuint64_t* strides, const cuuint32_t* box) {
  cuuint32_t es[5] = {1, 1, 1, 1, 1};
  fn(m, CU_TENSOR_MAP_DATA_TYPE_BFLOAT16, rank, (void*)ptr, dims, strides, box, es, CU_TENSOR_MAP_INTERLEAVE_NONE,
     CU_TENSOR_MAP_SWIZZLE_128B, CU_TENSOR_MAP_L2_PROMOTION_L2_128B, CU_TENSOR_MAP_FLOAT_OOB_FILL_NONE);
}

}

extern "C" void kernel_launch(void* const* d_in, const int* in_sizes, int n_in, void* d_out, int out_size) {
  (void)in_sizes; (void)n_in; (void)out_size;
  Params p;
  typedef const __nv_bfloat16* BP;
  p.x = (BP)d_in[0]; p.lre = (BP)d_in[1]; p.lim = (BP)d_in[2]; p.bre = (BP)d_in[3]; p.bim = (BP)d_in[4];
  p.cre = (BP)d_in[5]; p.cim = (BP)d_in[6]; p.logdt = (BP)d_in[7]; p.dskip = (BP)d_in[8];
  p.k = (BP)d_in[10]; p.v = (BP)d_in[11]; p.shiftk = (BP)d_in[12]; p.ssmk = (BP)d_in[13]; p.ssmD = (BP)d_in[14];
  p.out = (float*)d_out;
  void* fnp = nullptr;
  cudaDriverEntryPointQueryResult qr;
  cudaGetDriverEntryPoint("cuTensorMapEncodeTiled", &fnp, cudaEnableDefault, &qr);
  EncFn fn = (EncFn)fnp;
  void* gG = nullptr;
  cudaGetSymbolAddress(&gG, g_G);
  const cuuint64_t RB = DM * 2;
  {
    cuuint64_t dims[4] = {640, 8, 10, 8}, st[3] = {RB, 64 * RB, 8 * RB}; cuuint32_t box[4] = {64, 8, 2, 1};
    encode(fn, &p.mBre, p.bre, 4, dims, st, box); encode(fn, &p.mBim, p.bim, 4, dims, st, box);
  }
  {
    cuuint64_t dims[5] = {640, 2, 4, 2, 40}, st[4] = {RB, 4 * RB, 2 * RB, 16 * RB}; cuuint32_t box[5] = {64, 2, 4, 2, 10};
    encode(fn, &p.mCre, p.cre, 5, dims, st, box); encode(fn, &p.mCim, p.cim, 5, dims, st, box);
    cuuint64_t dimg[5] = {2048, 2, 4, 2, 40}, stg[4] = {4096, 4 * 4096, 2 * 4096, 16 * 4096};
    encode(fn, &p.mG, gG, 5, dimg, stg, box);
  }
  {
    cuuint64_t dims[4] = {640, 2, 4, 900}, st[3] = {RB, 40 * RB, 2 * RB}; cuuint32_t box[4] = {64, 2, 4, 20};
    encode(fn, &p.mX, p.x, 4, dims, st, box);
    cuuint64_t diml[4] = {640, 2, 4, 16}, stl[3] = {RB, 32 * RB, 2 * RB};
    encode(fn, &p.mXl, p.x + (size_t)1920 * DM, 4, diml, stl, box);
  }
  cudaFuncSetAttribute(fused_kernel, cudaFuncAttributeMaxDynamicSharedMemorySize, SMEM_BYTES);
  cudaLaunchConfig_t cfg = {};
  cfg.gridDim = dim3(132); cfg.blockDim = dim3(512); cfg.dynamicSmemBytes = SMEM_BYTES; cfg.stream = cudaStreamPerThread;
  cudaLaunchAttribute at[1];
  at[0].id = cudaLaunchAttributeClusterDimension; at[0].val.clusterDim.x = 2; at[0].val.clusterDim.y = 1; at[0].val.clusterDim.z = 1;
  cfg.attrs = at; cfg.numAttrs = 1;
  cudaLaunchKernelEx(&cfg, fused_kernel, p);
}
```

```cpp
#include <cuda_runtime.h>
#include <cuda.h>
#include <cuda_bf16.h>
#include <stdint.h>

namespace {

constexpr int SEQ = 2048, DM = 640;
constexpr int NT1 = 13;
constexpr uint32_t SPIN_LIMIT = 1u << 22;

__device__ __align__(1024) uint8_t g_h[2 * 32 * 20 * 8192];
__device__ __align__(1024) uint8_t g_u[NT1 * 10 * 20480];
__device__ __align__(1024) uint8_t g_kv[DM * 4096];
__device__ __align__(1024) uint8_t g_G[DM * 4096];
__device__ __align__(128) uint4 g_E[NT1 * DM * 2];
__device__ __align__(128) uint4 g_stats[SEQ * 4 * 2];
__device__ __align__(128) uint4 g_sB[DM * 2];
__device__ __align__(128) unsigned g_hflag[2 * NT1 * 2 * 16];
__device__ __align__(128) unsigned g_uflag[32 * 4];
__device__ __align__(128) unsigned g_kvcnt[4 * 32];
__device__ __align__(128) unsigned g_gcnt[4 * 32];
__device__ __align__(128) unsigned g_epoch[32];
#define TS(i) do {} while (0)

struct Params {
  CUtensorMap mB, mCre, mCim, mX, mXl, mG;
  const __nv_bfloat16 *x, *lre, *lim, *bre, *bim, *cre, *cim, *logdt, *dskip, *k, *v, *shiftk, *ssmk, *ssmD;
  float* out;
  int swap;
};

constexpr uint32_t G1_STAGE = 36864, G1_XOFF = 16384;
constexpr int S1 = 5;
constexpr uint32_t G2_XB = 8192, G2_WB = 20480, G2_WOFF = 57344, G_OFF = 200704;
constexpr int SX2 = 7;
constexpr uint32_t CV_OFF = 184320, CV_K = 128, CV_PL = 2240, CV_U = CV_K + 4096, CV_B = 8704;
constexpr uint32_t MISC = 227840;
constexpr uint32_t BAR_OFF = MISC;
constexpr int B_G1FULL = 0, B_G1DONE = 20, B_G2FULL = 40, B_CVFULL = 80,
              B_G2DONE = 86, B_GFULL = 126,
              B_CVDONE = 131, B_CTAB = 136;
constexpr uint32_t STAB_OFF = MISC + 1120;
constexpr uint32_t CTAB_OFF = STAB_OFF + 1280;
constexpr uint32_t DTAB_OFF = CTAB_OFF + 1536;
constexpr uint32_t SMEM_BYTES = 232448;
static_assert(DTAB_OFF + 320 <= SMEM_BYTES, "smem");

__device__ __forceinline__ uint32_t smem_u32(const void* p) { return (uint32_t)__cvta_generic_to_shared(p); }
__device__ __forceinline__ void mbar_init(uint32_t bar, int cnt) { asm volatile("mbarrier.init.shared::cta.b64 [%0], %1;" ::"r"(bar), "r"(cnt) : "memory"); }
__device__ __forceinline__ void mbar_expect_tx(uint32_t bar, int bytes) { asm volatile("mbarrier.arrive.expect_tx.shared::cta.b64 _, [%0], %1;" ::"r"(bar), "r"(bytes) : "memory"); }
__device__ __forceinline__ void mbar_arrive(uint32_t bar) { asm volatile("mbarrier.arrive.shared::cta.b64 _, [%0];" ::"r"(bar) : "memory"); }
__device__ __forceinline__ void mbar_wait(uint32_t bar) {
  asm volatile(
      "{\n.reg .pred p;\n.reg .u32 c;\nmov.u32 c, 0;\n"
      "W_%=:\nmbarrier.try_wait.parity.shared::cta.b64 p, [%0], 0;\n@p bra D_%=;\n"
      "add.u32 c, c, 1;\nsetp.lt.u32 p, c, %1;\n@p bra W_%=;\ntrap;\nD_%=:\n}\n" ::"r"(bar), "n"(SPIN_LIMIT) : "memory");
}
__device__ __forceinline__ void tma4(uint32_t dst, const CUtensorMap* m, int c0, int c1, int c2, int c3, uint32_t bar) {
  asm volatile("cp.async.bulk.tensor.4d.shared::cluster.global.mbarrier::complete_tx::bytes [%0], [%1, {%3,%4,%5,%6}], [%2];"
               ::"r"(dst), "l"(m), "r"(bar), "r"(c0), "r"(c1), "r"(c2), "r"(c3) : "memory");
}
__device__ __forceinline__ void tma5(uint32_t dst, const CUtensorMap* m, int c0, int c1, int c2, int c3, int c4, uint32_t bar) {
  asm volatile("cp.async.bulk.tensor.5d.shared::cluster.global.mbarrier::complete_tx::bytes [%0], [%1, {%3,%4,%5,%6,%7}], [%2];"
               ::"r"(dst), "l"(m), "r"(bar), "r"(c0), "r"(c1), "r"(c2), "r"(c3), "r"(c4) : "memory");
}
__device__ __forceinline__ void bulk_g2s(uint32_t dst, const void* src, int bytes, uint32_t bar) {
  asm volatile("cp.async.bulk.shared::cluster.global.mbarrier::complete_tx::bytes [%0], [%1], %2, [%3];"
               ::"r"(dst), "l"(src), "r"(bytes), "r"(bar) : "memory");
}
__device__ __forceinline__ void bulk_s2g(void* dst, uint32_t src, int bytes) {
  asm volatile("cp.async.bulk.global.shared::cta.bulk_group [%0], [%1], %2;" ::"l"(dst), "r"(src), "r"(bytes) : "memory");
}
__device__ __forceinline__ void l2_prefetch(const void* src, int bytes) {
  asm volatile("cp.async.bulk.prefetch.L2.global [%0], %1;" ::"l"(src), "r"(bytes) : "memory");
}
__device__ __forceinline__ void wgmma_fence() { asm volatile("wgmma.fence.sync.aligned;" ::: "memory"); }
__device__ __forceinline__ void wgmma_commit() { asm volatile("wgmma.commit_group.sync.aligned;" ::: "memory"); }
template <int N> __device__ __forceinline__ void wgmma_wait() { asm volatile("wgmma.wait_group.sync.aligned %0;" ::"n"(N) : "memory"); }
__device__ __forceinline__ uint64_t make_desc(uint32_t addr, uint32_t lbo, uint32_t sbo, int swz) {
  return (uint64_t)((addr & 0x3FFFF) >> 4) | ((uint64_t)(lbo >> 4) << 16) | ((uint64_t)(sbo >> 4) << 32) | ((uint64_t)swz << 62);
}
__device__ __forceinline__ void bar_sync(int id, int n) { asm volatile("bar.sync %0, %1;" ::"r"(id), "r"(n) : "memory"); }
__device__ __forceinline__ uint32_t lds32(uint32_t a) { uint32_t v; asm volatile("ld.shared.u32 %0, [%1];" : "=r"(v) : "r"(a) : "memory"); return v; }
__device__ __forceinline__ float2 lds64f(uint32_t a) { float2 v; asm volatile("ld.shared.v2.f32 {%0,%1}, [%2];" : "=f"(v.x), "=f"(v.y) : "r"(a) : "memory"); return v; }
__device__ __forceinline__ float4 lds128f(uint32_t a) { float4 v; asm volatile("ld.shared.v4.f32 {%0,%1,%2,%3}, [%4];" : "=f"(v.x), "=f"(v.y), "=f"(v.z), "=f"(v.w) : "r"(a) : "memory"); return v; }
__device__ __forceinline__ void sts32(uint32_t a, uint32_t v) { asm volatile("st.shared.u32 [%0], %1;" ::"r"(a), "r"(v) : "memory"); }
__device__ __forceinline__ void sts64f(uint32_t a, float x, float y) { asm volatile("st.shared.v2.f32 [%0], {%1,%2};" ::"r"(a), "f"(x), "f"(y) : "memory"); }
__device__ __forceinline__ void st_rel(unsigned* p, unsigned v) { asm volatile("st.release.gpu.global.u32 [%0], %1;" ::"l"(p), "r"(v) : "memory"); }
__device__ __forceinline__ void red_rel(unsigned* p, unsigned v) { asm volatile("red.release.gpu.global.add.u32 [%0], %1;" ::"l"(p), "r"(v) : "memory"); }
__device__ __forceinline__ void fence_async_global() { asm volatile("fence.proxy.async.global;" ::: "memory"); }
__device__ __forceinline__ void fence_async_smem() { asm volatile("fence.proxy.async.shared::cta;" ::: "memory"); }
__device__ __forceinline__ void rec_st(uint4* p, float a, float b, unsigned tag) {
  asm volatile("{\n.reg .b128 t;\n.reg .b64 lo, hi;\nmov.b64 lo, {%1,%2};\nmov.b64 hi, {%3,%3};\nmov.b128 t, {lo,hi};\n"
               "st.relaxed.gpu.global.b128 [%0], t;\n}\n" ::"l"(p), "r"(__float_as_uint(a)), "r"(__float_as_uint(b)), "r"(tag) : "memory");
}
__device__ __forceinline__ unsigned rec_ld(const uint4* p, float& a, float& b) {
  unsigned x, y, t;
  asm volatile("{\n.reg .b128 t;\n.reg .b64 lo, hi;\n.reg .b32 u;\nld.relaxed.gpu.global.b128 t, [%3];\nmov.b128 {lo,hi}, t;\n"
               "mov.b64 {%0,%1}, lo;\nmov.b64 {%2,u}, hi;\n}\n" : "=r"(x), "=r"(y), "=r"(t) : "l"(p) : "memory");
  a = __uint_as_float(x); b = __uint_as_float(y);
  return t;
}
__device__ __forceinline__ void rec_poll(const uint4* p, unsigned tag, float& a, float& b) {
  uint32_t it = 0;
  while (rec_ld(p, a, b) != tag) { if (++it > SPIN_LIMIT) __trap(); }
}
__device__ __forceinline__ unsigned ld_rlx(const unsigned* p) { unsigned v; asm volatile("ld.relaxed.gpu.global.u32 %0, [%1];" : "=r"(v) : "l"(p) : "memory"); return v; }
__device__ __forceinline__ void flag_poll(const unsigned* p, unsigned target) {
  uint32_t it = 0;
  while ((int)(ld_rlx(p) - target) < 0) { if (++it > SPIN_LIMIT) __trap(); }
  asm volatile("fence.acquire.gpu;" ::: "memory");
}
__device__ __forceinline__ uint32_t pack_bf16(float lo, float hi) {
  uint32_t r; asm("cvt.rn.bf16x2.f32 %0, %1, %2;" : "=r"(r) : "f"(hi), "f"(lo)); return r;
}
__device__ __forceinline__ float bf_lo(uint32_t w) { return __uint_as_float(w << 16); }
__device__ __forceinline__ float bf_hi(uint32_t w) { return __uint_as_float(w & 0xffff0000u); }
__device__ __forceinline__ uint32_t hmul2(uint32_t a, uint32_t b) {
  __nv_bfloat162 r = __hmul2_rn(*(__nv_bfloat162*)&a, *(__nv_bfloat162*)&b); return *(uint32_t*)&r;
}
__device__ __forceinline__ uint32_t hadd2(uint32_t a, uint32_t b) {
  __nv_bfloat162 r = __hadd2_rn(*(__nv_bfloat162*)&a, *(__nv_bfloat162*)&b); return *(uint32_t*)&r;
}
__device__ __forceinline__ float2 cmul(float2 a, float2 b) { return make_float2(a.x * b.x - a.y * b.y, a.x * b.y + a.y * b.x); }
__device__ __forceinline__ float2 cfma(float2 a, float2 b, float2 c) {
  return make_float2(fmaf(a.x, b.x, fmaf(-a.y, b.y, c.x)), fmaf(a.x, b.y, fmaf(a.y, b.x, c.y)));
}
template <int N> __device__ __forceinline__ void fence_regs(float (&a)[N]) {
#pragma unroll
  for (int i = 0; i < N; i++) asm volatile("" : "+f"(a[i])::"memory");
}
__device__ __forceinline__ bool elect_one() {
  uint32_t e; asm volatile("{\n.reg .pred P;\nelect.sync _|P, 0xffffffff;\nselp.u32 %0, 1, 0, P;\n}\n" : "=r"(e)); return e != 0;
}
__device__ __forceinline__ int tid_opaque() { int t; asm volatile("mov.u32 %0, %%tid.x;" : "=r"(t)); return t; }
struct Role { int T1, GP, side, m2, dg, cch0; bool last, has2; };
__device__ __forceinline__ Role unpack_role(int x) {
  Role r; r.T1 = x & 15; r.GP = (x >> 4) & 7; r.side = (x >> 7) & 1; r.m2 = (x >> 8) & 63; r.dg = (x >> 14) & 3;
  r.has2 = (x >> 16) & 1; r.last = r.T1 == NT1 - 1; r.cch0 = 5 * (32 * r.dg + r.m2); return r;
}
__device__ __forceinline__ Role fresh_role(int x) { asm volatile("" : "+r"(x)); return unpack_role(__shfl_sync(0xffffffffu, x, 0)); }
#define ROLE(x) const Role R_ = fresh_role(x); const int T1 = R_.T1, GP = R_.GP, side = R_.side, m2 = R_.m2, dg = R_.dg, cch0 = R_.cch0; \
  const bool last = R_.last, has2 = R_.has2; (void)T1; (void)GP; (void)side; (void)m2; (void)dg; (void)cch0; (void)last; (void)has2;
__device__ __forceinline__ int n_to_t(int n) {
  int T = n / 160, nl = n - T * 160;
  int L = (T == NT1 - 1) ? 32 : 40;
  return T * 160 + L * ((nl & 7) >> 1) + 2 * (nl >> 3) + (nl & 1);
}

template<int TA> __device__ __forceinline__ void wgmma_n160(float (&d)[80], uint64_t da, uint64_t db, int scale_d){
  asm volatile("{\n.reg .pred p;\nsetp.ne.b32 p, %82, 0;\n"
    "wgmma.mma_async.sync.aligned.m64n160k16.f32.bf16.bf16 {%0, %1, %2, %3, %4, %5, %6, %7, %8, %9, %10, %11, %12, %13, %14, %15, %16, %17, %18, %19, %20, %21, %22, %23, %24, %25, %26, %27, %28, %29, %30, %31, %32, %33, %34, %35, %36, %37, %38, %39, %40, %41, %42, %43, %44, %45, %46, %47, %48, %49, %50, %51, %52, %53, %54, %55, %56, %57, %58, %59, %60, %61, %62, %63, %64, %65, %66, %67, %68, %69, %70, %71, %72, %73, %74, %75, %76, %77, %78, %79}, %80, %81, p, 1, 1, %83, 0;\n}\n"
    : "+f"(d[0]), "+f"(d[1]), "+f"(d[2]), "+f"(d[3]), "+f"(d[4]), "+f"(d[5]), "+f"(d[6]), "+f"(d[7]), "+f"(d[8]), "+f"(d[9]), "+f"(d[10]), "+f"(d[11]), "+f"(d[12]), "+f"(d[13]), "+f"(d[14]), "+f"(d[15]), "+f"(d[16]), "+f"(d[17]), "+f"(d[18]), "+f"(d[19]), "+f"(d[20]), "+f"(d[21]), "+f"(d[22]), "+f"(d[23]), "+f"(d[24]), "+f"(d[25]), "+f"(d[26]), "+f"(d[27]), "+f"(d[28]), "+f"(d[29]), "+f"(d[30]), "+f"(d[31]), "+f"(d[32]), "+f"(d[33]), "+f"(d[34]), "+f"(d[35]), "+f"(d[36]), "+f"(d[37]), "+f"(d[38]), "+f"(d[39]), "+f"(d[40]), "+f"(d[41]), "+f"(d[42]), "+f"(d[43]), "+f"(d[44]), "+f"(d[45]), "+f"(d[46]), "+f"(d[47]), "+f"(d[48]), "+f"(d[49]), "+f"(d[50]), "+f"(d[51]), "+f"(d[52]), "+f"(d[53]), "+f"(d[54]), "+f"(d[55]), "+f"(d[56]), "+f"(d[57]), "+f"(d[58]), "+f"(d[59]), "+f"(d[60]), "+f"(d[61]), "+f"(d[62]), "+f"(d[63]), "+f"(d[64]), "+f"(d[65]), "+f"(d[66]), "+f"(d[67]), "+f"(d[68]), "+f"(d[69]), "+f"(d[70]), "+f"(d[71]), "+f"(d[72]), "+f"(d[73]), "+f"(d[74]), "+f"(d[75]), "+f"(d[76]), "+f"(d[77]), "+f"(d[78]), "+f"(d[79])
    : "l"(da), "l"(db), "r"(scale_d), "n"(TA));
}
template<int N> __device__ __forceinline__ void wgmma_rs_hi(float (&d)[64], uint32_t a0, uint32_t a1, uint32_t a2, uint32_t a3, uint64_t db);
template<> __device__ __forceinline__ void wgmma_rs_hi<16>(float (&d)[64], uint32_t a0, uint32_t a1, uint32_t a2, uint32_t a3, uint64_t db){
  asm volatile("wgmma.mma_async.sync.aligned.m64n16k16.f32.bf16.bf16 {%0, %1, %2, %3, %4, %5, %6, %7}, {%8,%9,%10,%11}, %12, 1, 1, 1, 0;\n"
    : "+f"(d[56]), "+f"(d[57]), "+f"(d[58]), "+f"(d[59]), "+f"(d[60]), "+f"(d[61]), "+f"(d[62]), "+f"(d[63])
    : "r"(a0), "r"(a1), "r"(a2), "r"(a3), "l"(db));
}
template<> __device__ __forceinline__ void wgmma_rs_hi<32>(float (&d)[64], uint32_t a0, uint32_t a1, uint32_t a2, uint32_t a3, uint64_t db){
  asm volatile("wgmma.mma_async.sync.aligned.m64n32k16.f32.bf16.bf16 {%0, %1, %2, %3, %4, %5, %6, %7, %8, %9, %10, %11, %12, %13, %14, %15}, {%16,%17,%18,%19}, %20, 1, 1, 1, 0;\n"
    : "+f"(d[48]), "+f"(d[49]), "+f"(d[50]), "+f"(d[51]), "+f"(d[52]), "+f"(d[53]), "+f"(d[54]), "+f"(d[55]), "+f"(d[56]), "+f"(d[57]), "+f"(d[58]), "+f"(d[59]), "+f"(d[60]), "+f"(d[61]), "+f"(d[62]), "+f"(d[63])
    : "r"(a0), "r"(a1), "r"(a2), "r"(a3), "l"(db));
}
template<> __device__ __forceinline__ void wgmma_rs_hi<48>(float (&d)[64], uint32_t a0, uint32_t a1, uint32_t a2, uint32_t a3, uint64_t db){
  asm volatile("wgmma.mma_async.sync.aligned.m64n48k16.f32.bf16.bf16 {%0, %1, %2, %3, %4, %5, %6, %7, %8, %9, %10, %11, %12, %13, %14, %15, %16, %17, %18, %19, %20, %21, %22, %23}, {%24,%25,%26,%27}, %28, 1, 1, 1, 0;\n"
    : "+f"(d[40]), "+f"(d[41]), "+f"(d[42]), "+f"(d[43]), "+f"(d[44]), "+f"(d[45]), "+f"(d[46]), "+f"(d[47]), "+f"(d[48]), "+f"(d[49]), "+f"(d[50]), "+f"(d[51]), "+f"(d[52]), "+f"(d[53]), "+f"(d[54]), "+f"(d[55]), "+f"(d[56]), "+f"(d[57]), "+f"(d[58]), "+f"(d[59]), "+f"(d[60]), "+f"(d[61]), "+f"(d[62]), "+f"(d[63])
    : "r"(a0), "r"(a1), "r"(a2), "r"(a3), "l"(db));
}
template<> __device__ __forceinline__ void wgmma_rs_hi<64>(float (&d)[64], uint32_t a0, uint32_t a1, uint32_t a2, uint32_t a3, uint64_t db){
  asm volatile("wgmma.mma_async.sync.aligned.m64n64k16.f32.bf16.bf16 {%0, %1, %2, %3, %4, %5, %6, %7, %8, %9, %10, %11, %12, %13, %14, %15, %16, %17, %18, %19, %20, %21, %22, %23, %24, %25, %26, %27, %28, %29, %30, %31}, {%32,%33,%34,%35}, %36, 1, 1, 1, 0;\n"
    : "+f"(d[32]), "+f"(d[33]), "+f"(d[34]), "+f"(d[35]), "+f"(d[36]), "+f"(d[37]), "+f"(d[38]), "+f"(d[39]), "+f"(d[40]), "+f"(d[41]), "+f"(d[42]), "+f"(d[43]), "+f"(d[44]), "+f"(d[45]), "+f"(d[46]), "+f"(d[47]), "+f"(d[48]), "+f"(d[49]), "+f"(d[50]), "+f"(d[51]), "+f"(d[52]), "+f"(d[53]), "+f"(d[54]), "+f"(d[55]), "+f"(d[56]), "+f"(d[57]), "+f"(d[58]), "+f"(d[59]), "+f"(d[60]), "+f"(d[61]), "+f"(d[62]), "+f"(d[63])
    : "r"(a0), "r"(a1), "r"(a2), "r"(a3), "l"(db));
}
template<> __device__ __forceinline__ void wgmma_rs_hi<80>(float (&d)[64], uint32_t a0, uint32_t a1, uint32_t a2, uint32_t a3, uint64_t db){
  asm volatile("wgmma.mma_async.sync.aligned.m64n80k16.f32.bf16.bf16 {%0, %1, %2, %3, %4, %5, %6, %7, %8, %9, %10, %11, %12, %13, %14, %15, %16, %17, %18, %19, %20, %21, %22, %23, %24, %25, %26, %27, %28, %29, %30, %31, %32, %33, %34, %35, %36, %37, %38, %39}, {%40,%41,%42,%43}, %44, 1, 1, 1, 0;\n"
    : "+f"(d[24]), "+f"(d[25]), "+f"(d[26]), "+f"(d[27]), "+f"(d[28]), "+f"(d[29]), "+f"(d[30]), "+f"(d[31]), "+f"(d[32]), "+f"(d[33]), "+f"(d[34]), "+f"(d[35]), "+f"(d[36]), "+f"(d[37]), "+f"(d[38]), "+f"(d[39]), "+f"(d[40]), "+f"(d[41]), "+f"(d[42]), "+f"(d[43]), "+f"(d[44]), "+f"(d[45]), "+f"(d[46]), "+f"(d[47]), "+f"(d[48]), "+f"(d[49]), "+f"(d[50]), "+f"(d[51]), "+f"(d[52]), "+f"(d[53]), "+f"(d[54]), "+f"(d[55]), "+f"(d[56]), "+f"(d[57]), "+f"(d[58]), "+f"(d[59]), "+f"(d[60]), "+f"(d[61]), "+f"(d[62]), "+f"(d[63])
    : "r"(a0), "r"(a1), "r"(a2), "r"(a3), "l"(db));
}
template<> __device__ __forceinline__ void wgmma_rs_hi<96>(float (&d)[64], uint32_t a0, uint32_t a1, uint32_t a2, uint32_t a3, uint64_t db){
  asm volatile("wgmma.mma_async.sync.aligned.m64n96k16.f32.bf16.bf16 {%0, %1, %2, %3, %4, %5, %6, %7, %8, %9, %10, %11, %12, %13, %14, %15, %16, %17, %18, %19, %20, %21, %22, %23, %24, %25, %26, %27, %28, %29, %30, %31, %32, %33, %34, %35, %36, %37, %38, %39, %40, %41, %42, %43, %44, %45, %46, %47}, {%48,%49,%50,%51}, %52, 1, 1, 1, 0;\n"
    : "+f"(d[16]), "+f"(d[17]), "+f"(d[18]), "+f"(d[19]), "+f"(d[20]), "+f"(d[21]), "+f"(d[22]), "+f"(d[23]), "+f"(d[24]), "+f"(d[25]), "+f"(d[26]), "+f"(d[27]), "+f"(d[28]), "+f"(d[29]), "+f"(d[30]), "+f"(d[31]), "+f"(d[32]), "+f"(d[33]), "+f"(d[34]), "+f"(d[35]), "+f"(d[36]), "+f"(d[37]), "+f"(d[38]), "+f"(d[39]), "+f"(d[40]), "+f"(d[41]), "+f"(d[42]), "+f"(d[43]), "+f"(d[44]), "+f"(d[45]), "+f"(d[46]), "+f"(d[47]), "+f"(d[48]), "+f"(d[49]), "+f"(d[50]), "+f"(d[51]), "+f"(d[52]), "+f"(d[53]), "+f"(d[54]), "+f"(d[55]), "+f"(d[56]), "+f"(d[57]), "+f"(d[58]), "+f"(d[59]), "+f"(d[60]), "+f"(d[61]), "+f"(d[62]), "+f"(d[63])
    : "r"(a0), "r"(a1), "r"(a2), "r"(a3), "l"(db));
}
template<> __device__ __forceinline__ void wgmma_rs_hi<112>(float (&d)[64], uint32_t a0, uint32_t a1, uint32_t a2, uint32_t a3, uint64_t db){
  asm volatile("wgmma.mma_async.sync.aligned.m64n112k16.f32.bf16.bf16 {%0, %1, %2, %3, %4, %5, %6, %7, %8, %9, %10, %11, %12, %13, %14, %15, %16, %17, %18, %19, %20, %21, %22, %23, %24, %25, %26, %27, %28, %29, %30, %31, %32, %33, %34, %35, %36, %37, %38, %39, %40, %41, %42, %43, %44, %45, %46, %47, %48, %49, %50, %51, %52, %53, %54, %55}, {%56,%57,%58,%59}, %60, 1, 1, 1, 0;\n"
    : "+f"(d[8]), "+f"(d[9]), "+f"(d[10]), "+f"(d[11]), "+f"(d[12]), "+f"(d[13]), "+f"(d[14]), "+f"(d[15]), "+f"(d[16]), "+f"(d[17]), "+f"(d[18]), "+f"(d[19]), "+f"(d[20]), "+f"(d[21]), "+f"(d[22]), "+f"(d[23]), "+f"(d[24]), "+f"(d[25]), "+f"(d[26]), "+f"(d[27]), "+f"(d[28]), "+f"(d[29]), "+f"(d[30]), "+f"(d[31]), "+f"(d[32]), "+f"(d[33]), "+f"(d[34]), "+f"(d[35]), "+f"(d[36]), "+f"(d[37]), "+f"(d[38]), "+f"(d[39]), "+f"(d[40]), "+f"(d[41]), "+f"(d[42]), "+f"(d[43]), "+f"(d[44]), "+f"(d[45]), "+f"(d[46]), "+f"(d[47]), "+f"(d[48]), "+f"(d[49]), "+f"(d[50]), "+f"(d[51]), "+f"(d[52]), "+f"(d[53]), "+f"(d[54]), "+f"(d[55]), "+f"(d[56]), "+f"(d[57]), "+f"(d[58]), "+f"(d[59]), "+f"(d[60]), "+f"(d[61]), "+f"(d[62]), "+f"(d[63])
    : "r"(a0), "r"(a1), "r"(a2), "r"(a3), "l"(db));
}
template<> __device__ __forceinline__ void wgmma_rs_hi<128>(float (&d)[64], uint32_t a0, uint32_t a1, uint32_t a2, uint32_t a3, uint64_t db){
  asm volatile("wgmma.mma_async.sync.aligned.m64n128k16.f32.bf16.bf16 {%0, %1, %2, %3, %4, %5, %6, %7, %8, %9, %10, %11, %12, %13, %14, %15, %16, %17, %18, %19, %20, %21, %22, %23, %24, %25, %26, %27, %28, %29, %30, %31, %32, %33, %34, %35, %36, %37, %38, %39, %40, %41, %42, %43, %44, %45, %46, %47, %48, %49, %50, %51, %52, %53, %54, %55, %56, %57, %58, %59, %60, %61, %62, %63}, {%64,%65,%66,%67}, %68, 1, 1, 1, 0;\n"
    : "+f"(d[0]), "+f"(d[1]), "+f"(d[2]), "+f"(d[3]), "+f"(d[4]), "+f"(d[5]), "+f"(d[6]), "+f"(d[7]), "+f"(d[8]), "+f"(d[9]), "+f"(d[10]), "+f"(d[11]), "+f"(d[12]), "+f"(d[13]), "+f"(d[14]), "+f"(d[15]), "+f"(d[16]), "+f"(d[17]), "+f"(d[18]), "+f"(d[19]), "+f"(d[20]), "+f"(d[21]), "+f"(d[22]), "+f"(d[23]), "+f"(d[24]), "+f"(d[25]), "+f"(d[26]), "+f"(d[27]), "+f"(d[28]), "+f"(d[29]), "+f"(d[30]), "+f"(d[31]), "+f"(d[32]), "+f"(d[33]), "+f"(d[34]), "+f"(d[35]), "+f"(d[36]), "+f"(d[37]), "+f"(d[38]), "+f"(d[39]), "+f"(d[40]), "+f"(d[41]), "+f"(d[42]), "+f"(d[43]), "+f"(d[44]), "+f"(d[45]), "+f"(d[46]), "+f"(d[47]), "+f"(d[48]), "+f"(d[49]), "+f"(d[50]), "+f"(d[51]), "+f"(d[52]), "+f"(d[53]), "+f"(d[54]), "+f"(d[55]), "+f"(d[56]), "+f"(d[57]), "+f"(d[58]), "+f"(d[59]), "+f"(d[60]), "+f"(d[61]), "+f"(d[62]), "+f"(d[63])
    : "r"(a0), "r"(a1), "r"(a2), "r"(a3), "l"(db));
}

__device__ __forceinline__ void cv_copy(float (&acc)[64]) {
#pragma unroll
  for (int i = 0; i < 64; i++) { float t; asm volatile("mov.b32 %0, %1;" : "=f"(t) : "f"(acc[i]) : "memory"); acc[i] = t; }
}
template <int D0> __device__ __forceinline__ void cv_loadA(uint32_t (&A)[4][4], uint32_t kaddr) {
#pragma unroll
  for (int i = 0; i < 4; i++) {
    uint32_t a = kaddr + (D0 + i) * 128;
    uint32_t w0 = lds32(a), w1 = lds32(a + 4), w2 = lds32(a + 8);
    A[i][0] = __byte_perm(w0, w1, 0x5432); A[i][1] = w1; A[i][2] = __byte_perm(w1, w2, 0x5432); A[i][3] = w2;
  }
#pragma unroll
  for (int i = 0; i < 4; i++) asm volatile("" : "+r"(A[i][0]), "+r"(A[i][1]), "+r"(A[i][2]), "+r"(A[i][3])::"memory");
}
template <int G> __device__ __forceinline__ void cv_rec(float (&acc)[64], const uint32_t (&A)[4][4], uint32_t kaddr, uint64_t db0) {
  wgmma_fence();
#pragma unroll
  for (int i = 0; i < 4; i++) wgmma_rs_hi<128 - 16 * G>(acc, A[i][0], A[i][1], A[i][2], A[i][3], db0 - (uint64_t)(4 * i));
  wgmma_commit();
  if constexpr (G < 7) {
    uint32_t B[4][4];
    cv_loadA<4 * (G + 1)>(B, kaddr);
    wgmma_wait<0>(); cv_copy(acc);
    cv_rec<G + 1>(acc, B, kaddr, db0);
  } else { wgmma_wait<0>(); cv_copy(acc); }
}
__device__ __forceinline__ void conv_channel(const Params& p, uint32_t sb, int slot, int ch, int barid) {
  int tid = tid_opaque() & 127, w = tid >> 5, lane = tid & 31, r = lane >> 2, q = lane & 3;
  int i_ = r >> 1, i0 = i_ & 1, i1 = i_ >> 1;
  int bl = 4 * (r & 1) + 2 * (w & 1) + 8 * (w >> 1);
  const uint32_t cb = sb + CV_OFF + slot * CV_B;
  uint32_t dd = (uint32_t)__bfloat16_as_ushort(p.ssmD[ch]); dd |= dd << 16;
  mbar_wait(sb + BAR_OFF + 8 * (B_CVFULL + slot));
  const uint32_t kaddr = cb + CV_K - 32 + 4 * (8 * i_ + (bl >> 1) + 2 * q);
  const uint64_t db0 = make_desc(cb + CV_U + 192, CV_PL, 128, 0);
  float acc[64];
#pragma unroll
  for (int i = 0; i < 64; i++) acc[i] = 0.f;
  uint32_t A[4][4];
  cv_loadA<0>(A, kaddr);
  cv_copy(acc);
  cv_rec<0>(acc, A, kaddr, db0);
  float E[8][4];
  const int src1 = i1 == 0 ? (lane - q + 16 + ((q + 3) & 3)) : (lane - q - 16 + ((q + 1) & 3));
  const bool s3 = (i1 == 1 && q == 3), kodd = (i1 == 1 && q < 3);
#pragma unroll
  for (int J = 0; J < 8; J++)
#pragma unroll
    for (int x = 0; x < 4; x++) {
      float ev = acc[8 * J + x], od = acc[8 * J + 4 + x], pv = J > 0 ? acc[8 * J - 4 + x] : 0.f;
      float send = kodd ? ev : (s3 ? pv : od);
      float keep = kodd ? od : ev;
      E[J][x] = keep + __shfl_sync(0xffffffffu, send, src1);
    }
  const int P = i1 == 0 ? q : 4 + ((q + 1) & 3);
  const int Pm = (P + 7) & 7, qm = Pm < 4 ? Pm : ((Pm - 1) & 3), i1m = Pm >> 2;
  const int src2 = i0 == 1 ? lane - 8 : (16 * i1m + 8 + 4 * (r & 1) + qm);
  const bool wrap = (i0 == 1 && P == 7);
  const uint32_t kvaddr = cb + CV_U + 192 + (((14 - bl) >> 1) & 1) * CV_PL + (2 * P + i0) * 16 + ((14 - bl) >> 2) * 4;
  uint32_t gw[8];
#pragma unroll
  for (int J = 0; J < 8; J++) {
    float o[2];
#pragma unroll
    for (int h = 0; h < 2; h++) {
      float pv = J > 0 ? E[J - 1][2 * h + 1] : 0.f;
      float send = wrap ? pv : E[J][2 * h + 1];
      o[h] = E[J][2 * h] + __shfl_sync(0xffffffffu, send, src2);
    }
    uint32_t kvw = lds32(kvaddr + J * 256);
    kvw = __byte_perm(kvw, kvw, 0x1032);
    gw[J] = hadd2(pack_bf16(o[0], o[1]), hmul2(kvw, dd));
  }
  bar_sync(barid, 128);
  int tb = 16 * (2 * P + i0) + bl;
  asm volatile("" : "+r"(tb));
#pragma unroll
  for (int J = 0; J < 8; J++) {
    int t = 256 * J + tb;
    int T = t / 160, tl = t - T * 160;
    int qq = (T == NT1 - 1) ? (tl >> 5) : (tl / 40);
    int j = (tl - qq * ((T == NT1 - 1) ? 32 : 40)) >> 1;
    int c = 20 * T + j;
    c = c ^ ((c >> 3) & 7);
    sts32(cb + CV_K + c * 16 + qq * 4, gw[J]);
  }
  fence_async_smem();
  mbar_arrive(sb + BAR_OFF + 8 * (B_CVDONE + slot));
}

__device__ __forceinline__ void kv_tile(const Params& p, int m, int c0) {
  const int lane = threadIdx.x & 31, cg = lane & 7, tg = lane >> 3;
  const int ch = c0 + 4 * cg, t0 = 64 * m + 16 * tg;
  uint2 kk[19], vv[16];
  const uint2* kp = (const uint2*)(p.k + (t0 * DM + ch));
  const uint2* vp = (const uint2*)(p.v + (t0 * DM + ch));
#pragma unroll
  for (int i = 0; i < 19; i++) kk[i] = (i >= 3 || t0 > 0) ? __ldg(kp + (i - 3) * (DM / 4)) : make_uint2(0u, 0u);
#pragma unroll
  for (int i = 0; i < 16; i++) vv[i] = __ldg(vp + i * (DM / 4));
  const uint4 s0 = __ldg((const uint4*)(p.shiftk + ch * 4)), s1 = __ldg((const uint4*)(p.shiftk + ch * 4 + 8));
  const uint32_t wa[4] = {__byte_perm(s0.x, s0.z, 0x5410), __byte_perm(s0.x, s0.z, 0x7632), __byte_perm(s0.y, s0.w, 0x5410), __byte_perm(s0.y, s0.w, 0x7632)};
  const uint32_t wb[4] = {__byte_perm(s1.x, s1.z, 0x5410), __byte_perm(s1.x, s1.z, 0x7632), __byte_perm(s1.y, s1.w, 0x5410), __byte_perm(s1.y, s1.w, 0x7632)};
#pragma unroll
  for (int i = 0; i < 16; i++) {
    uint32_t a = hmul2(kk[i].x, wa[3]);
    a = hadd2(a, hmul2(kk[i + 1].x, wa[2])); a = hadd2(a, hmul2(kk[i + 2].x, wa[1])); a = hadd2(a, hmul2(kk[i + 3].x, wa[0]));
    vv[i].x = hmul2(a, vv[i].x);
    uint32_t b = hmul2(kk[i].y, wb[3]);
    b = hadd2(b, hmul2(kk[i + 1].y, wb[2])); b = hadd2(b, hmul2(kk[i + 2].y, wb[1])); b = hadd2(b, hmul2(kk[i + 3].y, wb[0]));
    vv[i].y = hmul2(b, vv[i].y);
  }
  uint8_t* dst = g_kv + (size_t)ch * 4096 + (4 * m + tg) * 16;
#pragma unroll
  for (int c = 0; c < 4; c++)
#pragma unroll
    for (int f = 0; f < 2; f++) {
      uint32_t o[4];
#pragma unroll
      for (int qq = 0; qq < 4; qq++) {
        const int ia = 15 - 4 * qq - 2 * f, ib = ia - 1;
        uint32_t xa = (c < 2) ? vv[ia].x : vv[ia].y, xb = (c < 2) ? vv[ib].x : vv[ib].y;
        o[qq] = __byte_perm(xa, xb, (c & 1) ? 0x7632 : 0x5410);
      }
      *(uint4*)(dst + c * 4096 + f * 2048) = make_uint4(o[0], o[1], o[2], o[3]);
    }
}

template <bool FIRST>
__device__ __forceinline__ void stats_publish(int which, int n0, int dg, unsigned tag, const float (&acc)[80]) {
  const int lane = tid_opaque() & 31, q = lane & 3;
  float sh[2] = {0.f, 0.f};
  if (FIRST) { sh[0] = __shfl_sync(0xffffffffu, acc[0], lane & ~3); sh[1] = __shfl_sync(0xffffffffu, acc[2], lane & ~3); }
  float s1[2] = {0.f, 0.f}, s2[2] = {0.f, 0.f}, t1[2] = {0.f, 0.f}, t2[2] = {0.f, 0.f};
#pragma unroll
  for (int j = 0; j < 20; j++)
#pragma unroll
    for (int h = 0; h < 2; h++) {
      float a = acc[4 * j + 2 * h], b = acc[4 * j + 2 * h + 1];
      if (FIRST) { a -= sh[h]; b -= sh[h]; }
      s1[h] += a; t1[h] += b; s2[h] = fmaf(a, a, s2[h]); t2[h] = fmaf(b, b, t2[h]);
    }
#pragma unroll
  for (int h = 0; h < 2; h++) {
    s1[h] += t1[h]; s2[h] += t2[h];
    s1[h] += __shfl_xor_sync(0xffffffffu, s1[h], 1); s2[h] += __shfl_xor_sync(0xffffffffu, s2[h], 1);
    s1[h] += __shfl_xor_sync(0xffffffffu, s1[h], 2); s2[h] += __shfl_xor_sync(0xffffffffu, s2[h], 2);
  }
  if (FIRST || (q & 1) == (which & 1)) {
    const int h = q >> 1;
    float a = h ? s1[1] : s1[0], b = h ? s2[1] : s2[0], c = h ? sh[1] : sh[0];
    float mean = a * (1.f / 160.f);
    rec_st(&g_stats[((n0 + 8 * h) * 4 + dg) * 2 + (q & 1)], mean + c, fmaxf(b - a * mean, 0.f), 4 * tag + which);
  }
}
__device__ __forceinline__ void stats_combine(float mi, float m2, float& mean, float& rstd) {
  float m = mi + __shfl_xor_sync(0xffffffffu, mi, 1);
  m += __shfl_xor_sync(0xffffffffu, m, 2);
  m *= 0.25f;
  float d = mi - m;
  float v = fmaf(160.f * d, d, m2);
  v += __shfl_xor_sync(0xffffffffu, v, 1);
  v += __shfl_xor_sync(0xffffffffu, v, 2);
  mean = m; rstd = rsqrtf(v * (1.f / 640.f) + 1e-5f);
}
__device__ __forceinline__ void stats_get(int which, int n0, unsigned tag, float (&mean)[2], float (&rstd)[2]) {
  const int q = tid_opaque() & 3;
  const uint4* p0 = &g_stats[(n0 * 4 + q) * 2 + (which & 1)];
  float a0, b0, a1, b1;
  uint32_t it = 0;
  tag = 4 * tag + which;
  while (true) {
    unsigned t0 = rec_ld(p0, a0, b0), t1 = rec_ld(p0 + 64, a1, b1);
    if (t0 == tag && t1 == tag) break;
    if (++it > SPIN_LIMIT) __trap();
  }
  __syncwarp();
  stats_combine(a0, b0, mean[0], rstd[0]);
  stats_combine(a1, b1, mean[1], rstd[1]);
}
__device__ __forceinline__ void load_x0(const Params& p, int n0, int d0, float (&acc)[80]) {
  uint2 xv[2][10];
#pragma unroll
  for (int h = 0; h < 2; h++) {
    const uint2* xp = (const uint2*)(p.x + (n_to_t(n0 + 8 * h) * DM + d0 + 4 * (tid_opaque() & 3)));
#pragma unroll
    for (int J = 0; J < 10; J++) xv[h][J] = __ldg(xp + 4 * J);
  }
#pragma unroll
  for (int h = 0; h < 2; h++)
#pragma unroll
    for (int J = 0; J < 10; J++) {
      acc[8 * J + 2 * h] = bf_lo(xv[h][J].x); acc[8 * J + 2 * h + 1] = bf_hi(xv[h][J].x);
      acc[8 * J + 4 + 2 * h] = bf_lo(xv[h][J].y); acc[8 * J + 4 + 2 * h + 1] = bf_hi(xv[h][J].y);
    }
}
__global__ void __launch_bounds__(512, 1) fused_kernel(const __grid_constant__ Params p) {
  extern __shared__ __align__(1024) uint8_t smem_raw[];
  const uint32_t sb = smem_u32(smem_raw);
  const uint32_t bars = sb + BAR_OFF;
  const int tid = threadIdx.x, lane = tid & 31;
  const int wid = __shfl_sync(0xffffffffu, tid >> 5, 0), wg = wid >> 2;
  const unsigned tag = ld_rlx(g_epoch) + 1;
  unsigned smid; asm volatile("mov.u32 %0, %%smid;" : "=r"(smid));
  if (smid >= 132 || (sb & 1023)) __trap();
  int role;
  {
  const int side = smid & 1;
  int gpc, gi;
  {
    int tpc = smid >> 1;
    if (tpc < 32) { gpc = tpc & 7; gi = tpc >> 3; }
    else if (tpc < 60) { gpc = 1 + (tpc - 32) % 7; gi = 4 + (tpc - 32) / 7; }
    else if (tpc < 62) { gpc = tpc - 54; gi = 8; }
    else { gpc = 0; gi = tpc - 58; }
  }
  const int pos = 8 * gpc + gi + (gpc == 7 ? 1 : 0);
  if (pos == 65) {
    if (tid < 32) {
      for (int i = lane; i < NT1 * 16; i += 32)
        if ((i & 15) < 10) { uint32_t it = 0; while ((int)(ld_rlx(&g_hflag[(i >> 4) * 32 + (i & 15)]) - tag) < 0) { __nanosleep(500); if (++it > SPIN_LIMIT) __trap(); } }
    }
    return;
  }
  int T1, GP;
  if (pos < 52) { int hh = pos / 26, x = pos - 26 * hh; T1 = x >> 1; GP = 2 * hh + (x & 1); }
  else { T1 = pos - 52; GP = 4; }
  const bool last = (T1 == NT1 - 1);
  const bool has2 = gi < 8;
  const int m2 = 8 * (gpc >> 1) + gi, dg = 2 * (gpc & 1) + side;
  const int cch0 = 5 * (32 * dg + m2);
  role = T1 | (GP << 4) | (side << 7) | (m2 << 8) | (dg << 14) | ((int)has2 << 16);

  if (wid == 12) {
    if (elect_one()) {
#pragma unroll
      for (int k = 0; k < S1; k++) mbar_init(bars + 8 * (B_G1FULL + k), 1);
      asm volatile("fence.mbarrier_init.release.cluster;" ::: "memory");
#pragma unroll
      for (int k = 0; k < S1; k++) {
        const uint32_t fb = bars + 8 * (B_G1FULL + k);
        mbar_expect_tx(fb, G1_STAGE);
        tma4(sb + k * G1_STAGE + G1_XOFF, last ? &p.mXl : &p.mX, 64 * k, 0, 0, last ? 0 : 80 * T1, fb);
        tma5(sb + k * G1_STAGE, &p.mB, 64 * k, 0, 0, 4 * side, 2 * GP, fb);
      }
      TS(44);
    }
  } else if (wid < 15) {
    if (elect_one()) {
      const int g = wid < 12 ? wid : wid - 1;
      const int cnt = g < 9 ? 2 : 1;
#pragma unroll
      for (int i = 0; i < 9; i++) mbar_init(bars + 8 * (5 + 9 * g + i), cnt);
      asm volatile("fence.mbarrier_init.release.cluster;" ::: "memory");
    }
    if (wid < 5) {
      uint32_t cb = sb + CV_OFF + wid * CV_B;
      uint32_t a = lane < 8 ? cb + 16 * lane : (lane < 20 ? cb + CV_U + 16 * (lane - 8) : cb + CV_U + CV_PL + 16 * (lane - 20));
      asm volatile("st.shared.v4.u32 [%0], {%1,%1,%1,%1};" ::"r"(a), "r"(0) : "memory");
      fence_async_smem();
    }
  } else if (elect_one()) {
#pragma unroll
    for (int i = 0; i < 5; i++) mbar_init(bars + 8 * (B_CVDONE + i), 128);
    mbar_init(bars + 8 * B_CTAB, 32);
    asm volatile("fence.mbarrier_init.release.cluster;" ::: "memory");
  }
  __syncthreads();
  if (tid == 0) TS(0);

  const int n0 = 64 * m2 + 16 * (wid & 3) + (lane >> 2), d0 = 160 * dg;
  if (has2) {
    if (wg == 2 || wid == 4) {
      kv_tile(p, m2, d0 + 32 * (wg == 2 ? wid - 8 : 4));
      if (wid == 4) asm volatile("bar.arrive 3, 160;" ::: "memory");
      else {
        if (tid == 256) TS(52);
        bar_sync(3, 160);
        if (tid == 256) { red_rel(&g_kvcnt[dg * 32], 1); TS(30); }
      }
    } else if (wg == 0) {
      float xs[80];
      load_x0(p, n0, d0, xs);
      stats_publish<true>(0, n0, dg, tag, xs);
      if (tid == 0) TS(31);
    } else if (wg == 1) {
#pragma unroll 1
      for (int c = 2 * (wid - 5); c < 2 * (wid - 4) && c < 5; c++) {
        float sv[2];
#pragma unroll
        for (int part = 0; part < 2; part++) {
          const uint2* row = (const uint2*)((part ? p.bim : p.bre) + (size_t)(cch0 + c) * DM);
          float a = 0.f;
#pragma unroll
          for (int i = 0; i < 5; i++) { uint2 x = __ldg(row + lane + 32 * i); a += (bf_lo(x.x) + bf_hi(x.x)) + (bf_lo(x.y) + bf_hi(x.y)); }
          sv[part] = a;
        }
#pragma unroll
        for (int o = 16; o > 0; o >>= 1) { sv[0] += __shfl_xor_sync(0xffffffffu, sv[0], o); sv[1] += __shfl_xor_sync(0xffffffffu, sv[1], o); }
        if (lane < 2) rec_st(&g_sB[(cch0 + c) * 2 + lane], sv[0], sv[1], tag);
      }
    }
  }
  if (wid == 14) {
#pragma unroll 1
    for (int i = 0; i < 2; i++) {
      const int ch = 128 * GP + 64 * i + 32 * side + lane;
      const float lr = __bfloat162float(p.lre[ch]), li = __bfloat162float(p.lim[ch]);
      const float dt = __bfloat162float(__float2bfloat16_rn(expf(__bfloat162float(p.logdt[ch]))));
      const float mag = expf(dt * lr);
      float sn, cs; sincosf(dt * li, &sn, &cs);
      const float ar = mag * cs, ai = mag * sn;
      const float inv = 2.f / (lr * lr + li * li);
      const uint32_t ad = sb + CTAB_OFF + (32 * i + lane) * 24;
      sts64f(ad, ar, ai);
      sts64f(ad + 8, ((ar - 1.f) * lr + ai * li) * inv, (ai * lr - (ar - 1.f) * li) * inv);
    }
    if (has2 && lane < 20) {
      uint4 dv = __ldg((const uint4*)(p.dskip + d0) + lane);
      asm volatile("st.shared.v4.u32 [%0], {%1,%2,%3,%4};" ::"r"(sb + DTAB_OFF + 16 * lane), "r"(dv.x), "r"(dv.y), "r"(dv.z), "r"(dv.w) : "memory");
    }
  }
  }

  if (wg == 3) {
    asm volatile("setmaxnreg.dec.sync.aligned.u32 32;");
    ROLE(role)
    const int pw = wid & 3;
    if (pw == 0) {
#pragma unroll 1
      for (int l = 0; l < 2; l++) {
        if (l == 1) mbar_wait(bars + 8 * (has2 ? B_G2DONE + 19 : B_G1DONE + 9));
        int s = 0;
#pragma unroll 1
        for (int k = l == 0 ? S1 : 0; k < 10; k++) {
          if (k >= S1) mbar_wait(bars + 8 * (B_G1DONE + 10 * l + k - S1));
          const uint32_t fb = bars + 8 * (B_G1FULL + 10 * l + k);
          if (elect_one()) {
            mbar_expect_tx(fb, 16384);
            tma5(sb + s * G1_STAGE, &p.mB, 64 * k, 0, 0, 4 * side, 2 * GP, fb);
          }
          if (++s == S1) s = 0;
        }
        if (has2) {
          const int SW = l == 0 ? 6 : 7;
          mbar_wait(bars + 8 * (B_G1DONE + 10 * l + 9));
          s = 0;
#pragma unroll 1
          for (int k = 0; k < 20; k++) {
            if (k >= SW) mbar_wait(bars + 8 * (B_G2DONE + 20 * l + k - SW));
            const uint32_t fb = bars + 8 * (B_G2FULL + 20 * l + k);
            const int w = k >= 10, x = k - 10 * w;
            if (elect_one()) {
              mbar_expect_tx(fb, G2_WB);
              tma5(sb + G2_WOFF + s * G2_WB, (x & 1) ? &p.mCim : &p.mCre, 128 * (x >> 1) + 64 * w, 0, 0, 0, 10 * dg, fb);
            }
            if (++s == SW) s = 0;
          }
        }
      }
    } else if (pw == 1) {
#pragma unroll 1
      for (int l = 0; l < 2; l++) {
        if (l == 1) {
          mbar_wait(bars + 8 * (has2 ? B_G2DONE + 19 : B_G1DONE + 9));
          const int mlo = (160 * T1) >> 6, nf = last ? 8 : 12;
          if (lane < nf) flag_poll(&g_uflag[4 * mlo + lane], tag);
          __syncwarp();
          fence_async_global();
          if (lane == 0) TS(20);
        }
        int s = 0;
#pragma unroll 1
        for (int k = l == 0 ? S1 : 0; k < 10; k++) {
          if (k >= S1) mbar_wait(bars + 8 * (B_G1DONE + 10 * l + k - S1));
          const uint32_t fb = bars + 8 * (B_G1FULL + 10 * l + k), dst = sb + s * G1_STAGE + G1_XOFF;
          if (l == 0) {
            if (elect_one()) {
              mbar_expect_tx(fb, 20480);
              tma4(dst, last ? &p.mXl : &p.mX, 64 * k, 0, 0, last ? 0 : 80 * T1, fb);
            }
          } else {
            const int bytes = last ? 16384 : 20480;
            if (elect_one()) {
              mbar_expect_tx(fb, bytes);
              bulk_g2s(dst, g_u + (size_t)(T1 * 10 + k) * 20480, bytes, fb);
            }
          }
          if (++s == S1) s = 0;
        }
        if (has2) {
          mbar_wait(bars + 8 * (B_G1DONE + 10 * l + 9));
          const int Tlo = (64 * m2) / 160, Thi = (64 * m2 + 63) / 160;
          s = 0;
#pragma unroll 1
          for (int k = 0; k < 20; k++) {
            if (k == 0 || k == SX2) {
              if ((lane & 15) < 10) flag_poll(&g_hflag[((l * NT1 + (lane < 16 ? Tlo : Thi)) * 2 + (k > 0)) * 16 + (lane & 15)], tag);
              __syncwarp();
              fence_async_global();
              if (lane == 0) TS(21 + 2 * l + (k > 0));
            }
            if (k >= SX2) mbar_wait(bars + 8 * (B_G2DONE + 20 * l + k - SX2));
            const uint32_t fb = bars + 8 * (B_G2FULL + 20 * l + k);
            if (elect_one()) {
              mbar_expect_tx(fb, G2_XB);
              bulk_g2s(sb + s * G2_XB, g_h + (size_t)((l * 32 + m2) * 20 + k) * 8192, G2_XB, fb);
            }
            if (++s == SX2) s = 0;
          }
        }
      }
    } else if (pw == 2) {
#pragma unroll 1
      for (int i = 0; i < 2; i++) {
        float a, b;
        rec_poll(&g_sB[(128 * GP + 64 * i + 32 * side + lane) * 2], tag, a, b);
        sts64f(sb + CTAB_OFF + (32 * i + lane) * 24 + 16, a, b);
      }
      mbar_arrive(bars + 8 * B_CTAB);
      if (lane == 0) TS(54);
      if (has2) {
#pragma unroll 1
        for (int c = 0; c < 5; c++) {
          mbar_wait(bars + 8 * (B_CVDONE + c));
          if (elect_one()) {
            bulk_s2g(g_G + (size_t)(cch0 + c) * 4096, sb + CV_OFF + c * CV_B + CV_K, 4096);
            asm volatile("cp.async.bulk.commit_group;" ::: "memory");
            if (c == 4) {
              asm volatile("cp.async.bulk.wait_group 0;" ::: "memory");
              fence_async_global();
              red_rel(&g_gcnt[dg * 32], 1);
            }
          }
        }
      }
    } else if (has2) {
      mbar_wait(bars + 8 * (B_G1FULL + 2));
      if (elect_one()) {
#pragma unroll
        for (int c = 0; c < 5; c++) {
          const uint32_t fb = bars + 8 * (B_CVFULL + c);
          mbar_expect_tx(fb, 4096);
          bulk_g2s(sb + CV_OFF + c * CV_B + CV_K, p.ssmk + (size_t)(cch0 + c) * SEQ, 4096, fb);
        }
        l2_prefetch(p.cre + (size_t)cch0 * DM, 6400);
        l2_prefetch(p.cim + (size_t)cch0 * DM, 6400);
        asm volatile("prefetch.tensormap [%0];" ::"l"(&p.mCre) : "memory");
        asm volatile("prefetch.tensormap [%0];" ::"l"(&p.mCim) : "memory");
        asm volatile("prefetch.tensormap [%0];" ::"l"(&p.mG) : "memory");
      }
      flag_poll(&g_kvcnt[dg * 32], tag * 32);
      __syncwarp();
      fence_async_global();
      if (lane == 0) TS(28);
      if (elect_one()) {
#pragma unroll
        for (int c = 0; c < 5; c++) {
          const uint32_t fb = bars + 8 * (B_CVFULL + c), cb = sb + CV_OFF + c * CV_B + CV_U + 192;
          mbar_expect_tx(fb, 4096);
          bulk_g2s(cb, g_kv + (size_t)(cch0 + c) * 4096, 2048, fb);
          bulk_g2s(cb + CV_PL, g_kv + (size_t)(cch0 + c) * 4096 + 2048, 2048, fb);
        }
      }
      flag_poll(&g_gcnt[dg * 32], tag * 32);
      __syncwarp();
      fence_async_global();
      if (lane == 0) TS(29);
      if (elect_one()) {
        mbar_expect_tx(bars + 8 * B_GFULL, 20480);
        tma5(sb + G_OFF, &p.mG, 64 * m2, 0, 0, 0, 10 * dg, bars + 8 * B_GFULL);
      }
    }
  } else {
    asm volatile("setmaxnreg.inc.sync.aligned.u32 160;");
    const int w = wid & 3;
#pragma unroll 1
    for (int l = 0; l < 2; l++) {
      if (wg < 2) {
        float acc[80];
#pragma unroll
        for (int i = 0; i < 80; i++) acc[i] = 0.f;
        ROLE(role)
        const int tid = tid_opaque(), r = (tid & 31) >> 2, q = tid & 3;
        const int ch = 128 * GP + 64 * wg + 32 * side + 8 * w + r;
        fence_regs(acc);
        const uint64_t da0 = make_desc(sb + wg * 8192, 16, 1024, 1);
        const uint64_t db0 = l == 0 ? make_desc(sb + G1_XOFF, 16, 1024, 1) : make_desc(sb + G1_XOFF, 128, 1024, 0);
        const int xstep = l == 0 ? 2 : 16;
        int s = 0;
#pragma unroll 1
        for (int k = 0; k < 10; k++) {
          mbar_wait(bars + 8 * (B_G1FULL + 10 * l + k));
          if (k == 0 && tid == 0) TS(1 + 8 * l);
          if (l == 0 && (k == 4 || k == 9) && tid == 0) TS(48 + (k >> 3));
          const uint64_t da = da0 + s * (G1_STAGE >> 4), db = db0 + s * (G1_STAGE >> 4);
          wgmma_fence();
#pragma unroll
          for (int kk = 0; kk < 4; kk++) wgmma_n160<0>(acc, da + kk * 2, db + kk * xstep, 1);
          wgmma_commit();
          if (k == 6 && tid < (last ? 128 : 160)) {
            const uint4* rp = &g_stats[(160 * T1 + tid) * 8];
            float a[4], b[4];
            uint32_t it = 0;
            while (true) {
              bool ok = true;
#pragma unroll
              for (int i = 0; i < 4; i++) ok &= (rec_ld(rp + 2 * i, a[i], b[i]) == 4 * tag + 2 * l);
              if (ok) break;
              if (++it > SPIN_LIMIT) __trap();
            }
            const float m = 0.25f * ((a[0] + a[1]) + (a[2] + a[3]));
            float v = (b[0] + b[1]) + (b[2] + b[3]);
#pragma unroll
            for (int i = 0; i < 4; i++) v = fmaf(160.f * (a[i] - m), a[i] - m, v);
            const float rs = rsqrtf(v * (1.f / 640.f) + 1e-5f);
            sts64f(sb + STAB_OFF + tid * 8, rs, -m * rs);
          }
          __syncwarp();
          if (k > 0) { wgmma_wait<1>(); if ((tid & 127) == 0) mbar_arrive(bars + 8 * (B_G1DONE + 10 * l + k - 1)); }
          if (++s == S1) s = 0;
        }
        mbar_wait(bars + 8 * B_CTAB);
        const uint32_t ca = sb + CTAB_OFF + (32 * wg + 8 * w + r) * 24;
        float2 lam = lds64f(ca), sB = lds64f(ca + 16);
        const float2 coef = lds64f(ca + 8), lamc = make_float2(lam.x, -lam.y);
        float m00 = coef.x, m01 = -coef.y, m10 = -coef.y, m11 = -coef.x;
        if (p.swap) { lam = lamc; sB = make_float2(sB.y, sB.x); m00 = -coef.y; m01 = coef.x; m10 = -coef.x; m11 = -coef.y; }
        float2 pL, p2L, pLq, p160q, p640;
        {
          float2 p2 = cmul(lam, lam), p4 = cmul(p2, p2), p8 = cmul(p4, p4), p16 = cmul(p8, p8), p32 = cmul(p16, p16);
          float2 p40 = cmul(p32, p8), p80 = cmul(p40, p40), p160 = cmul(p80, p80), p320 = cmul(p160, p160);
          p640 = cmul(p320, p320);
          pL = last ? p32 : p40;
          p2L = cmul(pL, pL);
          const float2 one = make_float2(1.f, 0.f);
          pLq = cmul((q & 1) ? pL : one, (q & 2) ? p2L : one);
          p160q = cmul((q & 1) ? p160 : one, (q & 2) ? p320 : one);
        }
        bar_sync(4, 256);
        if (tid == 0) TS(26 + l);
        wgmma_wait<0>();
        fence_regs(acc);
        if ((tid & 127) == 0) { mbar_arrive(bars + 8 * (B_G1DONE + 10 * l + 9)); if (wg == 0) TS(2 + 8 * l); }
        float2 e = make_float2(0.f, 0.f), snap = e;
#pragma unroll
        for (int j = 0; j < 20; j++) {
          const float4 st = lds128f(sb + STAB_OFF + (8 * j + 2 * q) * 8);
          acc[4 * j + 0] = fmaf(acc[4 * j + 0], st.x, st.y * sB.x);
          acc[4 * j + 2] = fmaf(acc[4 * j + 2], st.x, st.y * sB.y);
          acc[4 * j + 1] = fmaf(acc[4 * j + 1], st.z, st.w * sB.x);
          acc[4 * j + 3] = fmaf(acc[4 * j + 3], st.z, st.w * sB.y);
          e = cfma(lam, e, make_float2(acc[4 * j + 0], acc[4 * j + 2]));
          e = cfma(lam, e, make_float2(acc[4 * j + 1], acc[4 * j + 3]));
          if (j == 15) snap = e;
        }
        if (last) e = snap;
        {
          float2 v = make_float2(__shfl_up_sync(0xffffffffu, e.x, 1, 4), __shfl_up_sync(0xffffffffu, e.y, 1, 4));
          if (q >= 1) e = cfma(pL, v, e);
          v = make_float2(__shfl_up_sync(0xffffffffu, e.x, 2, 4), __shfl_up_sync(0xffffffffu, e.y, 2, 4));
          if (q >= 2) e = cfma(p2L, v, e);
        }
        if (!last && (q == 3 || (q == 2 && l == 0))) rec_st(&g_E[(T1 * DM + ch) * 2 + (q == 3 ? l : 1)], e.x, e.y, q == 3 ? tag : tag - 1);
        if (tid == 0) TS(3 + 8 * l);
        float2 ex = make_float2(__shfl_up_sync(0xffffffffu, e.x, 1, 4), __shfl_up_sync(0xffffffffu, e.y, 1, 4));
        if (q == 0) ex = make_float2(0.f, 0.f);
#pragma unroll
        for (int j = 0; j < 20; j++)
#pragma unroll
          for (int x = 0; x < 2; x++) {
            const float b0 = acc[4 * j + x], b1 = acc[4 * j + 2 + x];
            acc[4 * j + x] = fmaf(b0, m00, b1 * m01);
            acc[4 * j + 2 + x] = fmaf(b0, m10, b1 * m11);
          }
        float2 c;
        {
          float2 ev[3];
          uint32_t it = 0;
          while (true) {
            bool ok = true;
#pragma unroll
            for (int i = 0; i < 3; i++) {
              const int Tp = T1 - 1 - q - 4 * i;
              ev[i] = make_float2(0.f, 0.f);
              if (Tp >= 0) ok &= (rec_ld(&g_E[(Tp * DM + ch) * 2 + l], ev[i].x, ev[i].y) == tag);
            }
            if (ok) break;
            if (++it > SPIN_LIMIT) __trap();
          }
          __syncwarp();
          c = cfma(p640, cfma(p640, ev[2], ev[1]), ev[0]);
          c = cmul(c, p160q);
          c.x += __shfl_xor_sync(0xffffffffu, c.x, 1); c.y += __shfl_xor_sync(0xffffffffu, c.y, 1);
          c.x += __shfl_xor_sync(0xffffffffu, c.x, 2); c.y += __shfl_xor_sync(0xffffffffu, c.y, 2);
        }
        if (tid == 0) TS(4 + 8 * l);
        c = cfma(pLq, c, ex);
        float2 hh = make_float2(fmaf(c.x, m00, c.y * m01), fmaf(c.x, m10, c.y * m11));
        uint8_t* hb = g_h + (size_t)l * (32 * 20 * 8192) + (10 * wg + 2 * GP) * 8192 + (4 * side + w) * 1024 + (tid_opaque() & 31) * 4;
#pragma unroll
        for (int j4 = 0; j4 < 5; j4++) {
          const int ng = 20 * T1 + 4 * j4;
          uint8_t* hp = hb + (size_t)(ng >> 3) * 163840 + (ng & 7) * 128;
#pragma unroll
          for (int jj = 0; jj < 4; jj++) {
            const int j = 4 * j4 + jj;
            const float2 h0 = cfma(lamc, hh, make_float2(acc[4 * j + 0], acc[4 * j + 2]));
            hh = cfma(lamc, h0, make_float2(acc[4 * j + 1], acc[4 * j + 3]));
            if (j4 < 4 || !last) {
              *(uint32_t*)(hp + jj * 128) = pack_bf16(h0.x, hh.x);
              *(uint32_t*)(hp + jj * 128 + 8192) = pack_bf16(h0.y, hh.y);
            }
          }
        }
        bar_sync(1 + wg, 128);
        if ((tid & 127) == 0) {
          if (wg == 0) TS(5 + 8 * l);
          st_rel(&g_hflag[((l * NT1 + T1) * 2 + wg) * 16 + 2 * GP + side], tag);
          if (wg == 0) TS(6 + 8 * l);
        }
      }
      if (l == 0) {
        ROLE(role)
        if (has2) {
          if (wg == 2) mbar_wait(bars + 8 * (B_G1DONE + 8));
#pragma unroll 1
          for (int c = wg == 2 ? 0 : 2 + wg; c < (wg == 2 ? 2 : 5); c += wg == 2 ? 1 : 2) conv_channel(p, sb, c, cch0 + c, 1 + wg);
          if ((tid & 127) == 0) TS(wg == 2 ? 32 : 7 + wg);
        }
      }
      if (wg == 2) break;
    }
    if (wg == 2 && (role >> 16)) {
      float acc[80];
      float off[2] = {0.f, 0.f};
      {
        ROLE(role)
        load_x0(p, 64 * m2 + 16 * w + ((tid_opaque() & 31) >> 2), 160 * dg, acc);
      }
#pragma unroll 1
      for (int l = 0; l < 2; l++) {
        float mean[2], rstd[2];
        {
          ROLE(role)
          const int lane = tid_opaque() & 31;
          stats_get(2 * l, 64 * m2 + 16 * w + (lane >> 2), tag, mean, rstd);
          off[0] += mean[0]; off[1] += mean[1];
          mbar_wait(bars + 8 * B_CTAB);
#pragma unroll
          for (int J = 0; J < 10; J++) {
            const float2 dw = lds64f(sb + DTAB_OFF + 2 * (16 * J + 4 * (lane & 3)));
#pragma unroll
            for (int x = 0; x < 8; x++) {
              const int h = (x >> 1) & 1;
              const uint32_t gwd = __float_as_uint(x < 4 ? dw.x : dw.y);
              acc[8 * J + x] = (acc[8 * J + x] - mean[h]) * fmaf(rstd[h], (x & 1) ? bf_hi(gwd) : bf_lo(gwd), 1.f);
            }
          }
        }
        {
          const int SW = l == 0 ? 6 : 7;
          int sx = 0, sw = 0;
          fence_regs(acc);
#pragma unroll 1
          for (int k = 0; k < 20; k++) {
            mbar_wait(bars + 8 * (B_G2FULL + 20 * l + k));
            if (k == 0 && tid == 256) TS(33 + 6 * l);
            if (l == 1 && (k & 3) == 3 && tid == 256) TS(56 + (k >> 2));
            const uint64_t da = make_desc(sb + sx * G2_XB, 1024, 128, 0);
            const uint64_t db = make_desc(sb + G2_WOFF + sw * G2_WB, 16, 1024, 1);
            wgmma_fence();
#pragma unroll
            for (int kk = 0; kk < 4; kk++) wgmma_n160<1>(acc, da + kk * 128, db + kk * 2, 1);
            wgmma_commit();
            if (k > 0) { wgmma_wait<1>(); if (tid == 256) mbar_arrive(bars + 8 * (B_G2DONE + 20 * l + k - 1)); }
            if (++sx == SX2) sx = 0;
            if (++sw == SW) sw = 0;
          }
          wgmma_wait<0>();
          fence_regs(acc);
          if (tid == 256) { mbar_arrive(bars + 8 * (B_G2DONE + 20 * l + 19)); TS(34 + 6 * l); }
        }
        ROLE(role)
        const int tq = tid_opaque() & 31, n0 = 64 * m2 + 16 * w + (tq >> 2);
        stats_publish<false>(2 * l + 1, n0, dg, tag, acc);
        uint32_t gf[10][4];
        {
          mbar_wait(bars + 8 * B_GFULL);
          const int mi = tq >> 3, c = tq & 7;
          const uint32_t ga = sb + G_OFF + (8 * (mi >> 1) + c) * 128 + (((2 * w + (mi & 1)) ^ (m2 & 7) ^ c) << 4);
#pragma unroll
          for (int J = 0; J < 10; J++)
            asm volatile("ldmatrix.sync.aligned.m8n8.x4.trans.shared.b16 {%0,%1,%2,%3}, [%4];"
                         : "=r"(gf[J][0]), "=r"(gf[J][1]), "=r"(gf[J][2]), "=r"(gf[J][3]) : "r"(ga + J * 2048) : "memory");
          if (tid == 256) TS(35 + 6 * l);
        }
        uint8_t* dst[2][2];
#pragma unroll
        for (int h = 0; h < 2; h++) {
          if (l == 0) {
            const int ng = 8 * m2 + 2 * w + h, T = ng / 20;
            uint8_t* ub = g_u + (T * 204800 + (ng - 20 * T) * 1024 + (tq & 2) * 64 + (tq & 28) * 4 + (tq & 1) * 8 + (5 * dg >> 1) * 20480);
            dst[h][1] = ub + ((dg & 1) ? 20480 - 512 : 0);
            dst[h][0] = ub + (dg & 1) * 512;
          } else {
            dst[h][0] = dst[h][1] = (uint8_t*)(p.out + (n_to_t(n0 + 8 * h) * DM + 160 * dg + 4 * (tq & 3)));
          }
        }
        stats_get(2 * l + 1, n0, tag, mean, rstd);
        if (tid == 256) TS(36 + 6 * l);
        off[0] += mean[0]; off[1] += mean[1];
#pragma unroll
        for (int J = 0; J < 10; J++) {
          asm volatile("" : "+r"(gf[J][0]), "+r"(gf[J][1]), "+r"(gf[J][2]), "+r"(gf[J][3])::"memory");
#pragma unroll
          for (int x = 0; x < 8; x++) {
            const int h = (x >> 1) & 1;
            const uint32_t gwd = gf[J][x >> 1];
            acc[8 * J + x] = (acc[8 * J + x] - mean[h]) * fmaf(rstd[h], (x & 1) ? bf_hi(gwd) : bf_lo(gwd), 1.f);
          }
#pragma unroll
          for (int h = 0; h < 2; h++) {
            if (l == 0)
              *(uint2*)(dst[h][(J >> 1) & 1] + (J >> 2) * 20480 + (J & 3) * 256) =
                  make_uint2(pack_bf16(acc[8 * J + 2 * h], acc[8 * J + 2 * h + 1]), pack_bf16(acc[8 * J + 4 + 2 * h], acc[8 * J + 5 + 2 * h]));
            else
              *(float4*)(dst[h][0] + 64 * J) = make_float4(acc[8 * J + 2 * h] + off[h], acc[8 * J + 2 * h + 1] + off[h],
                                                           acc[8 * J + 4 + 2 * h] + off[h], acc[8 * J + 5 + 2 * h] + off[h]);
          }
        }
        if (l == 0) {
          bar_sync(3, 128);
          if (tid == 256) { TS(37); st_rel(&g_uflag[4 * m2 + dg], tag); TS(38); }
          stats_publish<false>(2, n0, dg, tag, acc);
        } else {
          if (tid == 256) {
            TS(43);
            if (m2 == 31 && dg == 3) asm volatile("st.relaxed.gpu.global.u32 [%0], %1;" ::"l"(g_epoch), "r"(tag) : "memory");
          }
        }
      }
    }
  }
}

typedef CUresult (*EncFn)(CUtensorMap*, CUtensorMapDataType, cuuint32_t, void*, const cuuint64_t*, const cuuint64_t*,
                          const cuuint32_t*, const cuuint32_t*, CUtensorMapInterleave, CUtensorMapSwizzle,
                          CUtensorMapL2promotion, CUtensorMapFloatOOBfill);

void encode(EncFn fn, CUtensorMap* m, const void* ptr, int rank, const cuuint64_t* dims, const cuuint64_t* strides, const cuuint32_t* box) {
  cuuint32_t es[5] = {1, 1, 1, 1, 1};
  fn(m, CU_TENSOR_MAP_DATA_TYPE_BFLOAT16, rank, (void*)ptr, dims, strides, box, es, CU_TENSOR_MAP_INTERLEAVE_NONE,
     CU_TENSOR_MAP_SWIZZLE_128B, CU_TENSOR_MAP_L2_PROMOTION_L2_128B, CU_TENSOR_MAP_FLOAT_OOB_FILL_NONE);
}

}

extern "C" void kernel_launch(void* const* d_in, const int* in_sizes, int n_in, void* d_out, int out_size) {
  (void)in_sizes; (void)n_in; (void)out_size;
  Params p;
  typedef const __nv_bfloat16* BP;
  p.x = (BP)d_in[0]; p.lre = (BP)d_in[1]; p.lim = (BP)d_in[2]; p.bre = (BP)d_in[3]; p.bim = (BP)d_in[4];
  p.cre = (BP)d_in[5]; p.cim = (BP)d_in[6]; p.logdt = (BP)d_in[7]; p.dskip = (BP)d_in[8];
  p.k = (BP)d_in[10]; p.v = (BP)d_in[11]; p.shiftk = (BP)d_in[12]; p.ssmk = (BP)d_in[13]; p.ssmD = (BP)d_in[14];
  p.out = (float*)d_out;
  void* fnp = nullptr;
  cudaDriverEntryPointQueryResult qr;
  cudaGetDriverEntryPoint("cuTensorMapEncodeTiled", &fnp, cudaEnableDefault, &qr);
  EncFn fn = (EncFn)fnp;
  void* gG = nullptr;
  cudaGetSymbolAddress(&gG, g_G);
  const cuuint64_t RB = DM * 2;
  {
    p.swap = p.bim < p.bre;
    const char* lo = (const char*)(p.swap ? p.bim : p.bre); const char* hi = (const char*)(p.swap ? p.bre : p.bim);
    cuuint64_t dims[5] = {640, 8, 2, 8, 10}, st[4] = {RB, (cuuint64_t)(hi - lo), 8 * RB, 64 * RB}; cuuint32_t box[5] = {64, 8, 2, 4, 2};
    encode(fn, &p.mB, lo, 5, dims, st, box);
  }
  {
    cuuint64_t dims[5] = {640, 2, 4, 2, 40}, st[4] = {RB, 4 * RB, 2 * RB, 16 * RB}; cuuint32_t box[5] = {64, 2, 4, 2, 10};
    encode(fn, &p.mCre, p.cre, 5, dims, st, box); encode(fn, &p.mCim, p.cim, 5, dims, st, box);
    cuuint64_t dimg[5] = {2048, 2, 4, 2, 40}, stg[4] = {4096, 4 * 4096, 2 * 4096, 16 * 4096};
    encode(fn, &p.mG, gG, 5, dimg, stg, box);
  }
  {
    cuuint64_t dims[4] = {640, 2, 4, 900}, st[3] = {RB, 40 * RB, 2 * RB}; cuuint32_t box[4] = {64, 2, 4, 20};
    encode(fn, &p.mX, p.x, 4, dims, st, box);
    cuuint64_t diml[4] = {640, 2, 4, 16}, stl[3] = {RB, 32 * RB, 2 * RB};
    encode(fn, &p.mXl, p.x + (size_t)1920 * DM, 4, diml, stl, box);
  }
  cudaFuncSetAttribute(fused_kernel, cudaFuncAttributeMaxDynamicSharedMemorySize, SMEM_BYTES);
  cudaLaunchConfig_t cfg = {};
  cfg.gridDim = dim3(132); cfg.blockDim = dim3(512); cfg.dynamicSmemBytes = SMEM_BYTES; cfg.stream = cudaStreamPerThread;
  cudaLaunchKernelEx(&cfg, fused_kernel, p);
}
```

```cpp
#include <cuda_runtime.h>
#include <cuda.h>
#include <cuda_bf16.h>
#include <stdint.h>

namespace {

constexpr int SEQ = 2048, DM = 640;
constexpr int NT1 = 13;
constexpr uint32_t SPIN_LIMIT = 1u << 22;

__device__ __align__(1024) uint8_t g_h[2 * 32 * 20 * 8192];
__device__ __align__(1024) uint8_t g_u[NT1 * 10 * 20480];
__device__ __align__(1024) uint8_t g_kv[DM * 4096];
__device__ __align__(1024) uint8_t g_G[DM * 4096];
__device__ __align__(128) uint4 g_E[NT1 * DM * 2];
__device__ __align__(128) uint4 g_stats[SEQ * 4 * 2];
__device__ __align__(128) uint4 g_sB[DM * 2];
__device__ __align__(128) unsigned g_hflag[2 * NT1 * 2 * 16];
__device__ __align__(128) unsigned g_uflag[32 * 4];
__device__ __align__(128) unsigned g_kvcnt[4 * 32];
__device__ __align__(128) unsigned g_gcnt[4 * 32];
__device__ __align__(128) unsigned g_epoch[32];
#define TS(i) do {} while (0)

struct Params {
  CUtensorMap mB, mCre, mCim, mX, mXl, mG;
  const __nv_bfloat16 *x, *lre, *lim, *bre, *bim, *cre, *cim, *logdt, *dskip, *k, *v, *shiftk, *ssmk, *ssmD;
  float* out;
  int swap;
};

constexpr uint32_t sb = 1024;
constexpr uint32_t G1_STAGE = 36864, G1_XOFF = 16384;
constexpr int S1 = 5;
constexpr uint32_t G2_XB = 8192, G2_WB = 20480, G2_WOFF = 57344, G_OFF = 200704;
constexpr int SX2 = 7;
constexpr uint32_t CV_OFF = 184320, CV_K = 128, CV_PL = 2240, CV_U = CV_K + 4096, CV_B = 8704;
constexpr uint32_t MISC = 227840;
constexpr uint32_t BAR_OFF = MISC;
constexpr int B_G1FULL = 0, B_G1DONE = 20, B_G2FULL = 40, B_CVFULL = 80,
              B_G2DONE = 86, B_GFULL = 126,
              B_CVDONE = 131, B_STAB = 136  , B_CTAB = 138, B_PREP = 139;
constexpr uint32_t bars = sb + BAR_OFF;
constexpr uint32_t STAB_OFF = MISC + 1120;
constexpr uint32_t CTAB_OFF = STAB_OFF + 1280;
constexpr uint32_t DTAB_OFF = CTAB_OFF + 1536;
constexpr uint32_t SMEM_BYTES = 232448;
static_assert(DTAB_OFF + 320 <= SMEM_BYTES, "smem");

__device__ __forceinline__ uint32_t smem_u32(const void* p) { return (uint32_t)__cvta_generic_to_shared(p); }
__device__ __forceinline__ void mbar_init(uint32_t bar, int cnt) { asm volatile("mbarrier.init.shared::cta.b64 [%0], %1;" ::"r"(bar), "r"(cnt) : "memory"); }
__device__ __forceinline__ void mbar_expect_tx(uint32_t bar, int bytes) { asm volatile("mbarrier.arrive.expect_tx.shared::cta.b64 _, [%0], %1;" ::"r"(bar), "r"(bytes) : "memory"); }
__device__ __forceinline__ void mbar_arrive(uint32_t bar) { asm volatile("mbarrier.arrive.shared::cta.b64 _, [%0];" ::"r"(bar) : "memory"); }
__device__ __forceinline__ void mbar_wait(uint32_t bar) {
  asm volatile(
      "{\n.reg .pred p;\n.reg .u32 c;\nmov.u32 c, 0;\n"
      "W_%=:\nmbarrier.try_wait.parity.shared::cta.b64 p, [%0], 0;\n@p bra D_%=;\n"
      "add.u32 c, c, 1;\nsetp.lt.u32 p, c, %1;\n@p bra W_%=;\ntrap;\nD_%=:\n}\n" ::"r"(bar), "n"(SPIN_LIMIT) : "memory");
}
__device__ __forceinline__ void tma4(uint32_t dst, const CUtensorMap* m, int c0, int c1, int c2, int c3, uint32_t bar) {
  asm volatile("cp.async.bulk.tensor.4d.shared::cluster.global.mbarrier::complete_tx::bytes [%0], [%1, {%3,%4,%5,%6}], [%2];"
               ::"r"(dst), "l"(m), "r"(bar), "r"(c0), "r"(c1), "r"(c2), "r"(c3) : "memory");
}
__device__ __forceinline__ void tma5(uint32_t dst, const CUtensorMap* m, int c0, int c1, int c2, int c3, int c4, uint32_t bar) {
  asm volatile("cp.async.bulk.tensor.5d.shared::cluster.global.mbarrier::complete_tx::bytes [%0], [%1, {%3,%4,%5,%6,%7}], [%2];"
               ::"r"(dst), "l"(m), "r"(bar), "r"(c0), "r"(c1), "r"(c2), "r"(c3), "r"(c4) : "memory");
}
__device__ __forceinline__ void bulk_g2s(uint32_t dst, const void* src, int bytes, uint32_t bar) {
  asm volatile("cp.async.bulk.shared::cluster.global.mbarrier::complete_tx::bytes [%0], [%1], %2, [%3];"
               ::"r"(dst), "l"(src), "r"(bytes), "r"(bar) : "memory");
}
__device__ __forceinline__ void bulk_s2g(void* dst, uint32_t src, int bytes) {
  asm volatile("cp.async.bulk.global.shared::cta.bulk_group [%0], [%1], %2;" ::"l"(dst), "r"(src), "r"(bytes) : "memory");
}
__device__ __forceinline__ void l2_prefetch(const void* src, int bytes) {
  asm volatile("cp.async.bulk.prefetch.L2.global [%0], %1;" ::"l"(src), "r"(bytes) : "memory");
}
__device__ __forceinline__ void wgmma_fence() { asm volatile("wgmma.fence.sync.aligned;" ::: "memory"); }
__device__ __forceinline__ void wgmma_commit() { asm volatile("wgmma.commit_group.sync.aligned;" ::: "memory"); }
template <int N> __device__ __forceinline__ void wgmma_wait() { asm volatile("wgmma.wait_group.sync.aligned %0;" ::"n"(N) : "memory"); }
__host__ __device__ constexpr uint32_t desc_lo(uint32_t addr, uint32_t lbo) { return ((addr & 0x3FFFF) >> 4) | ((lbo >> 4) << 16); }
__host__ __device__ constexpr uint32_t desc_hi(uint32_t sbo, uint32_t swz) { return (sbo >> 4) | (swz << 30); }
__device__ __forceinline__ void bar_sync(int id, int n) { asm volatile("bar.sync %0, %1;" ::"r"(id), "r"(n) : "memory"); }
__device__ __forceinline__ uint32_t lds32(uint32_t a) { uint32_t v; asm volatile("ld.shared.u32 %0, [%1];" : "=r"(v) : "r"(a) : "memory"); return v; }
__device__ __forceinline__ float2 lds64f(uint32_t a) { float2 v; asm volatile("ld.shared.v2.f32 {%0,%1}, [%2];" : "=f"(v.x), "=f"(v.y) : "r"(a) : "memory"); return v; }
__device__ __forceinline__ float4 lds128f(uint32_t a) { float4 v; asm volatile("ld.shared.v4.f32 {%0,%1,%2,%3}, [%4];" : "=f"(v.x), "=f"(v.y), "=f"(v.z), "=f"(v.w) : "r"(a) : "memory"); return v; }
__device__ __forceinline__ void ldsm4t(uint32_t (&r)[4], uint32_t a) {
  asm volatile("ldmatrix.sync.aligned.m8n8.x4.trans.shared.b16 {%0,%1,%2,%3}, [%4];" : "=r"(r[0]), "=r"(r[1]), "=r"(r[2]), "=r"(r[3]) : "r"(a) : "memory");
}
__device__ __forceinline__ void sts32(uint32_t a, uint32_t v) { asm volatile("st.shared.u32 [%0], %1;" ::"r"(a), "r"(v) : "memory"); }
__device__ __forceinline__ void sts64f(uint32_t a, float x, float y) { asm volatile("st.shared.v2.f32 [%0], {%1,%2};" ::"r"(a), "f"(x), "f"(y) : "memory"); }
__device__ __forceinline__ void st_rel(unsigned* p, unsigned v) { asm volatile("st.release.gpu.global.u32 [%0], %1;" ::"l"(p), "r"(v) : "memory"); }
__device__ __forceinline__ void red_rel(unsigned* p, unsigned v) { asm volatile("red.release.gpu.global.add.u32 [%0], %1;" ::"l"(p), "r"(v) : "memory"); }
__device__ __forceinline__ void fence_async_global() { asm volatile("fence.proxy.async.global;" ::: "memory"); }
__device__ __forceinline__ void fence_async_smem() { asm volatile("fence.proxy.async.shared::cta;" ::: "memory"); }
__device__ __forceinline__ void rec_st(uint4* p, float a, float b, unsigned tag) {
  asm volatile("{\n.reg .b128 t;\n.reg .b64 lo, hi;\nmov.b64 lo, {%1,%2};\nmov.b64 hi, {%3,%3};\nmov.b128 t, {lo,hi};\n"
               "st.relaxed.gpu.global.b128 [%0], t;\n}\n" ::"l"(p), "r"(__float_as_uint(a)), "r"(__float_as_uint(b)), "r"(tag) : "memory");
}
__device__ __forceinline__ unsigned rec_ld(const uint4* p, float& a, float& b) {
  unsigned x, y, t;
  asm volatile("{\n.reg .b128 t;\n.reg .b64 lo, hi;\n.reg .b32 u;\nld.relaxed.gpu.global.b128 t, [%3];\nmov.b128 {lo,hi}, t;\n"
               "mov.b64 {%0,%1}, lo;\nmov.b64 {%2,u}, hi;\n}\n" : "=r"(x), "=r"(y), "=r"(t) : "l"(p) : "memory");
  a = __uint_as_float(x); b = __uint_as_float(y);
  return t;
}
__device__ __forceinline__ void rec_poll(const uint4* p, unsigned tag, float& a, float& b) {
  uint32_t it = 0;
  while (rec_ld(p, a, b) != tag) { if (++it > SPIN_LIMIT) __trap(); }
}
__device__ __forceinline__ unsigned ld_rlx(const unsigned* p) { unsigned v; asm volatile("ld.relaxed.gpu.global.u32 %0, [%1];" : "=r"(v) : "l"(p) : "memory"); return v; }
__device__ __forceinline__ void flag_poll(const unsigned* p, unsigned target) {
  uint32_t it = 0;
  while ((int)(ld_rlx(p) - target) < 0) { if (++it > SPIN_LIMIT) __trap(); }
  asm volatile("fence.acquire.gpu;" ::: "memory");
}
__device__ __forceinline__ uint32_t pack_bf16(float lo, float hi) {
  uint32_t r; asm("cvt.rn.bf16x2.f32 %0, %1, %2;" : "=r"(r) : "f"(hi), "f"(lo)); return r;
}
__device__ __forceinline__ float bf_lo(uint32_t w) { return __uint_as_float(w << 16); }
__device__ __forceinline__ float bf_hi(uint32_t w) { return __uint_as_float(w & 0xffff0000u); }
__device__ __forceinline__ uint32_t hmul2(uint32_t a, uint32_t b) {
  __nv_bfloat162 r = __hmul2_rn(*(__nv_bfloat162*)&a, *(__nv_bfloat162*)&b); return *(uint32_t*)&r;
}
__device__ __forceinline__ uint32_t hadd2(uint32_t a, uint32_t b) {
  __nv_bfloat162 r = __hadd2_rn(*(__nv_bfloat162*)&a, *(__nv_bfloat162*)&b); return *(uint32_t*)&r;
}
__device__ __forceinline__ float2 cmul(float2 a, float2 b) { return make_float2(a.x * b.x - a.y * b.y, a.x * b.y + a.y * b.x); }
__device__ __forceinline__ float2 cfma(float2 a, float2 b, float2 c) {
  return make_float2(fmaf(a.x, b.x, fmaf(-a.y, b.y, c.x)), fmaf(a.x, b.y, fmaf(a.y, b.x, c.y)));
}
template <int N> __device__ __forceinline__ void fence_regs(float (&a)[N]) {
#pragma unroll
  for (int i = 0; i < N; i++) asm volatile("" : "+f"(a[i])::"memory");
}
__device__ __forceinline__ bool elect_one() {
  uint32_t e; asm volatile("{\n.reg .pred P;\nelect.sync _|P, 0xffffffff;\nselp.u32 %0, 1, 0, P;\n}\n" : "=r"(e)); return e != 0;
}
__device__ __forceinline__ int tid_opaque() { int t; asm volatile("mov.u32 %0, %%tid.x;" : "=r"(t)); return t; }
struct Role { int T1, GP, side, m2, dg, cch0; bool last, has2; };
__device__ __forceinline__ Role unpack_role(int x) {
  Role r; r.T1 = x & 15; r.GP = (x >> 4) & 7; r.side = (x >> 7) & 1; r.m2 = (x >> 8) & 63; r.dg = (x >> 14) & 3;
  r.has2 = (x >> 16) & 1; r.last = r.T1 == NT1 - 1; r.cch0 = 5 * (32 * r.dg + r.m2); return r;
}
__device__ __forceinline__ Role fresh_role(int x) { asm volatile("" : "+r"(x)); return unpack_role(__shfl_sync(0xffffffffu, x, 0)); }
#define ROLE(x) const Role R_ = fresh_role(x); const int T1 = R_.T1, GP = R_.GP, side = R_.side, m2 = R_.m2, dg = R_.dg, cch0 = R_.cch0; \
  const bool last = R_.last, has2 = R_.has2; (void)T1; (void)GP; (void)side; (void)m2; (void)dg; (void)cch0; (void)last; (void)has2;
__device__ __forceinline__ int n_to_t(int n) {
  int T = n / 160, nl = n - T * 160;
  int L = (T == NT1 - 1) ? 32 : 40;
  return T * 160 + L * ((nl & 7) >> 1) + 2 * (nl >> 3) + (nl & 1);
}

template<int TA> __device__ __forceinline__ void wgmma_n160(float (&d)[80], uint32_t alo, uint32_t ahi, uint32_t blo, uint32_t bhi){
  asm volatile("{\n.reg .b64 da, db;\nmov.b64 da, {%80,%81};\nmov.b64 db, {%82,%83};\n"
    "wgmma.mma_async.sync.aligned.m64n160k16.f32.bf16.bf16 {%0, %1, %2, %3, %4, %5, %6, %7, %8, %9, %10, %11, %12, %13, %14, %15, %16, %17, %18, %19, %20, %21, %22, %23, %24, %25, %26, %27, %28, %29, %30, %31, %32, %33, %34, %35, %36, %37, %38, %39, %40, %41, %42, %43, %44, %45, %46, %47, %48, %49, %50, %51, %52, %53, %54, %55, %56, %57, %58, %59, %60, %61, %62, %63, %64, %65, %66, %67, %68, %69, %70, %71, %72, %73, %74, %75, %76, %77, %78, %79}, da, db, 1, 1, 1, %84, 0;\n}\n"
    : "+f"(d[0]), "+f"(d[1]), "+f"(d[2]), "+f"(d[3]), "+f"(d[4]), "+f"(d[5]), "+f"(d[6]), "+f"(d[7]), "+f"(d[8]), "+f"(d[9]), "+f"(d[10]), "+f"(d[11]), "+f"(d[12]), "+f"(d[13]), "+f"(d[14]), "+f"(d[15]), "+f"(d[16]), "+f"(d[17]), "+f"(d[18]), "+f"(d[19]), "+f"(d[20]), "+f"(d[21]), "+f"(d[22]), "+f"(d[23]), "+f"(d[24]), "+f"(d[25]), "+f"(d[26]), "+f"(d[27]), "+f"(d[28]), "+f"(d[29]), "+f"(d[30]), "+f"(d[31]), "+f"(d[32]), "+f"(d[33]), "+f"(d[34]), "+f"(d[35]), "+f"(d[36]), "+f"(d[37]), "+f"(d[38]), "+f"(d[39]), "+f"(d[40]), "+f"(d[41]), "+f"(d[42]), "+f"(d[43]), "+f"(d[44]), "+f"(d[45]), "+f"(d[46]), "+f"(d[47]), "+f"(d[48]), "+f"(d[49]), "+f"(d[50]), "+f"(d[51]), "+f"(d[52]), "+f"(d[53]), "+f"(d[54]), "+f"(d[55]), "+f"(d[56]), "+f"(d[57]), "+f"(d[58]), "+f"(d[59]), "+f"(d[60]), "+f"(d[61]), "+f"(d[62]), "+f"(d[63]), "+f"(d[64]), "+f"(d[65]), "+f"(d[66]), "+f"(d[67]), "+f"(d[68]), "+f"(d[69]), "+f"(d[70]), "+f"(d[71]), "+f"(d[72]), "+f"(d[73]), "+f"(d[74]), "+f"(d[75]), "+f"(d[76]), "+f"(d[77]), "+f"(d[78]), "+f"(d[79])
    : "r"(alo), "r"(ahi), "r"(blo), "r"(bhi), "n"(TA));
}
template<int N> __device__ __forceinline__ void wgmma_rs_hi(float (&d)[64], uint32_t a0, uint32_t a1, uint32_t a2, uint32_t a3, uint32_t blo);
template<> __device__ __forceinline__ void wgmma_rs_hi<16>(float (&d)[64], uint32_t a0, uint32_t a1, uint32_t a2, uint32_t a3, uint32_t blo){
  asm volatile("{\n.reg .b64 db;\nmov.b64 db, {%12,8};\nwgmma.mma_async.sync.aligned.m64n16k16.f32.bf16.bf16 {%0, %1, %2, %3, %4, %5, %6, %7}, {%8,%9,%10,%11}, db, 1, 1, 1, 0;\n}\n"
    : "+f"(d[56]), "+f"(d[57]), "+f"(d[58]), "+f"(d[59]), "+f"(d[60]), "+f"(d[61]), "+f"(d[62]), "+f"(d[63])
    : "r"(a0), "r"(a1), "r"(a2), "r"(a3), "r"(blo));
}
template<> __device__ __forceinline__ void wgmma_rs_hi<32>(float (&d)[64], uint32_t a0, uint32_t a1, uint32_t a2, uint32_t a3, uint32_t blo){
  asm volatile("{\n.reg .b64 db;\nmov.b64 db, {%20,8};\nwgmma.mma_async.sync.aligned.m64n32k16.f32.bf16.bf16 {%0, %1, %2, %3, %4, %5, %6, %7, %8, %9, %10, %11, %12, %13, %14, %15}, {%16,%17,%18,%19}, db, 1, 1, 1, 0;\n}\n"
    : "+f"(d[48]), "+f"(d[49]), "+f"(d[50]), "+f"(d[51]), "+f"(d[52]), "+f"(d[53]), "+f"(d[54]), "+f"(d[55]), "+f"(d[56]), "+f"(d[57]), "+f"(d[58]), "+f"(d[59]), "+f"(d[60]), "+f"(d[61]), "+f"(d[62]), "+f"(d[63])
    : "r"(a0), "r"(a1), "r"(a2), "r"(a3), "r"(blo));
}
template<> __device__ __forceinline__ void wgmma_rs_hi<48>(float (&d)[64], uint32_t a0, uint32_t a1, uint32_t a2, uint32_t a3, uint32_t blo){
  asm volatile("{\n.reg .b64 db;\nmov.b64 db, {%28,8};\nwgmma.mma_async.sync.aligned.m64n48k16.f32.bf16.bf16 {%0, %1, %2, %3, %4, %5, %6, %7, %8, %9, %10, %11, %12, %13, %14, %15, %16, %17, %18, %19, %20, %21, %22, %23}, {%24,%25,%26,%27}, db, 1, 1, 1, 0;\n}\n"
    : "+f"(d[40]), "+f"(d[41]), "+f"(d[42]), "+f"(d[43]), "+f"(d[44]), "+f"(d[45]), "+f"(d[46]), "+f"(d[47]), "+f"(d[48]), "+f"(d[49]), "+f"(d[50]), "+f"(d[51]), "+f"(d[52]), "+f"(d[53]), "+f"(d[54]), "+f"(d[55]), "+f"(d[56]), "+f"(d[57]), "+f"(d[58]), "+f"(d[59]), "+f"(d[60]), "+f"(d[61]), "+f"(d[62]), "+f"(d[63])
    : "r"(a0), "r"(a1), "r"(a2), "r"(a3), "r"(blo));
}
template<> __device__ __forceinline__ void wgmma_rs_hi<64>(float (&d)[64], uint32_t a0, uint32_t a1, uint32_t a2, uint32_t a3, uint32_t blo){
  asm volatile("{\n.reg .b64 db;\nmov.b64 db, {%36,8};\nwgmma.mma_async.sync.aligned.m64n64k16.f32.bf16.bf16 {%0, %1, %2, %3, %4, %5, %6, %7, %8, %9, %10, %11, %12, %13, %14, %15, %16, %17, %18, %19, %20, %21, %22, %23, %24, %25, %26, %27, %28, %29, %30, %31}, {%32,%33,%34,%35}, db, 1, 1, 1, 0;\n}\n"
    : "+f"(d[32]), "+f"(d[33]), "+f"(d[34]), "+f"(d[35]), "+f"(d[36]), "+f"(d[37]), "+f"(d[38]), "+f"(d[39]), "+f"(d[40]), "+f"(d[41]), "+f"(d[42]), "+f"(d[43]), "+f"(d[44]), "+f"(d[45]), "+f"(d[46]), "+f"(d[47]), "+f"(d[48]), "+f"(d[49]), "+f"(d[50]), "+f"(d[51]), "+f"(d[52]), "+f"(d[53]), "+f"(d[54]), "+f"(d[55]), "+f"(d[56]), "+f"(d[57]), "+f"(d[58]), "+f"(d[59]), "+f"(d[60]), "+f"(d[61]), "+f"(d[62]), "+f"(d[63])
    : "r"(a0), "r"(a1), "r"(a2), "r"(a3), "r"(blo));
}
template<> __device__ __forceinline__ void wgmma_rs_hi<80>(float (&d)[64], uint32_t a0, uint32_t a1, uint32_t a2, uint32_t a3, uint32_t blo){
  asm volatile("{\n.reg .b64 db;\nmov.b64 db, {%44,8};\nwgmma.mma_async.sync.aligned.m64n80k16.f32.bf16.bf16 {%0, %1, %2, %3, %4, %5, %6, %7, %8, %9, %10, %11, %12, %13, %14, %15, %16, %17, %18, %19, %20, %21, %22, %23, %24, %25, %26, %27, %28, %29, %30, %31, %32, %33, %34, %35, %36, %37, %38, %39}, {%40,%41,%42,%43}, db, 1, 1, 1, 0;\n}\n"
    : "+f"(d[24]), "+f"(d[25]), "+f"(d[26]), "+f"(d[27]), "+f"(d[28]), "+f"(d[29]), "+f"(d[30]), "+f"(d[31]), "+f"(d[32]), "+f"(d[33]), "+f"(d[34]), "+f"(d[35]), "+f"(d[36]), "+f"(d[37]), "+f"(d[38]), "+f"(d[39]), "+f"(d[40]), "+f"(d[41]), "+f"(d[42]), "+f"(d[43]), "+f"(d[44]), "+f"(d[45]), "+f"(d[46]), "+f"(d[47]), "+f"(d[48]), "+f"(d[49]), "+f"(d[50]), "+f"(d[51]), "+f"(d[52]), "+f"(d[53]), "+f"(d[54]), "+f"(d[55]), "+f"(d[56]), "+f"(d[57]), "+f"(d[58]), "+f"(d[59]), "+f"(d[60]), "+f"(d[61]), "+f"(d[62]), "+f"(d[63])
    : "r"(a0), "r"(a1), "r"(a2), "r"(a3), "r"(blo));
}
template<> __device__ __forceinline__ void wgmma_rs_hi<96>(float (&d)[64], uint32_t a0, uint32_t a1, uint32_t a2, uint32_t a3, uint32_t blo){
  asm volatile("{\n.reg .b64 db;\nmov.b64 db, {%52,8};\nwgmma.mma_async.sync.aligned.m64n96k16.f32.bf16.bf16 {%0, %1, %2, %3, %4, %5, %6, %7, %8, %9, %10, %11, %12, %13, %14, %15, %16, %17, %18, %19, %20, %21, %22, %23, %24, %25, %26, %27, %28, %29, %30, %31, %32, %33, %34, %35, %36, %37, %38, %39, %40, %41, %42, %43, %44, %45, %46, %47}, {%48,%49,%50,%51}, db, 1, 1, 1, 0;\n}\n"
    : "+f"(d[16]), "+f"(d[17]), "+f"(d[18]), "+f"(d[19]), "+f"(d[20]), "+f"(d[21]), "+f"(d[22]), "+f"(d[23]), "+f"(d[24]), "+f"(d[25]), "+f"(d[26]), "+f"(d[27]), "+f"(d[28]), "+f"(d[29]), "+f"(d[30]), "+f"(d[31]), "+f"(d[32]), "+f"(d[33]), "+f"(d[34]), "+f"(d[35]), "+f"(d[36]), "+f"(d[37]), "+f"(d[38]), "+f"(d[39]), "+f"(d[40]), "+f"(d[41]), "+f"(d[42]), "+f"(d[43]), "+f"(d[44]), "+f"(d[45]), "+f"(d[46]), "+f"(d[47]), "+f"(d[48]), "+f"(d[49]), "+f"(d[50]), "+f"(d[51]), "+f"(d[52]), "+f"(d[53]), "+f"(d[54]), "+f"(d[55]), "+f"(d[56]), "+f"(d[57]), "+f"(d[58]), "+f"(d[59]), "+f"(d[60]), "+f"(d[61]), "+f"(d[62]), "+f"(d[63])
    : "r"(a0), "r"(a1), "r"(a2), "r"(a3), "r"(blo));
}
template<> __device__ __forceinline__ void wgmma_rs_hi<112>(float (&d)[64], uint32_t a0, uint32_t a1, uint32_t a2, uint32_t a3, uint32_t blo){
  asm volatile("{\n.reg .b64 db;\nmov.b64 db, {%60,8};\nwgmma.mma_async.sync.aligned.m64n112k16.f32.bf16.bf16 {%0, %1, %2, %3, %4, %5, %6, %7, %8, %9, %10, %11, %12, %13, %14, %15, %16, %17, %18, %19, %20, %21, %22, %23, %24, %25, %26, %27, %28, %29, %30, %31, %32, %33, %34, %35, %36, %37, %38, %39, %40, %41, %42, %43, %44, %45, %46, %47, %48, %49, %50, %51, %52, %53, %54, %55}, {%56,%57,%58,%59}, db, 1, 1, 1, 0;\n}\n"
    : "+f"(d[8]), "+f"(d[9]), "+f"(d[10]), "+f"(d[11]), "+f"(d[12]), "+f"(d[13]), "+f"(d[14]), "+f"(d[15]), "+f"(d[16]), "+f"(d[17]), "+f"(d[18]), "+f"(d[19]), "+f"(d[20]), "+f"(d[21]), "+f"(d[22]), "+f"(d[23]), "+f"(d[24]), "+f"(d[25]), "+f"(d[26]), "+f"(d[27]), "+f"(d[28]), "+f"(d[29]), "+f"(d[30]), "+f"(d[31]), "+f"(d[32]), "+f"(d[33]), "+f"(d[34]), "+f"(d[35]), "+f"(d[36]), "+f"(d[37]), "+f"(d[38]), "+f"(d[39]), "+f"(d[40]), "+f"(d[41]), "+f"(d[42]), "+f"(d[43]), "+f"(d[44]), "+f"(d[45]), "+f"(d[46]), "+f"(d[47]), "+f"(d[48]), "+f"(d[49]), "+f"(d[50]), "+f"(d[51]), "+f"(d[52]), "+f"(d[53]), "+f"(d[54]), "+f"(d[55]), "+f"(d[56]), "+f"(d[57]), "+f"(d[58]), "+f"(d[59]), "+f"(d[60]), "+f"(d[61]), "+f"(d[62]), "+f"(d[63])
    : "r"(a0), "r"(a1), "r"(a2), "r"(a3), "r"(blo));
}
template<> __device__ __forceinline__ void wgmma_rs_hi<128>(float (&d)[64], uint32_t a0, uint32_t a1, uint32_t a2, uint32_t a3, uint32_t blo){
  asm volatile("{\n.reg .b64 db;\nmov.b64 db, {%68,8};\nwgmma.mma_async.sync.aligned.m64n128k16.f32.bf16.bf16 {%0, %1, %2, %3, %4, %5, %6, %7, %8, %9, %10, %11, %12, %13, %14, %15, %16, %17, %18, %19, %20, %21, %22, %23, %24, %25, %26, %27, %28, %29, %30, %31, %32, %33, %34, %35, %36, %37, %38, %39, %40, %41, %42, %43, %44, %45, %46, %47, %48, %49, %50, %51, %52, %53, %54, %55, %56, %57, %58, %59, %60, %61, %62, %63}, {%64,%65,%66,%67}, db, 1, 1, 1, 0;\n}\n"
    : "+f"(d[0]), "+f"(d[1]), "+f"(d[2]), "+f"(d[3]), "+f"(d[4]), "+f"(d[5]), "+f"(d[6]), "+f"(d[7]), "+f"(d[8]), "+f"(d[9]), "+f"(d[10]), "+f"(d[11]), "+f"(d[12]), "+f"(d[13]), "+f"(d[14]), "+f"(d[15]), "+f"(d[16]), "+f"(d[17]), "+f"(d[18]), "+f"(d[19]), "+f"(d[20]), "+f"(d[21]), "+f"(d[22]), "+f"(d[23]), "+f"(d[24]), "+f"(d[25]), "+f"(d[26]), "+f"(d[27]), "+f"(d[28]), "+f"(d[29]), "+f"(d[30]), "+f"(d[31]), "+f"(d[32]), "+f"(d[33]), "+f"(d[34]), "+f"(d[35]), "+f"(d[36]), "+f"(d[37]), "+f"(d[38]), "+f"(d[39]), "+f"(d[40]), "+f"(d[41]), "+f"(d[42]), "+f"(d[43]), "+f"(d[44]), "+f"(d[45]), "+f"(d[46]), "+f"(d[47]), "+f"(d[48]), "+f"(d[49]), "+f"(d[50]), "+f"(d[51]), "+f"(d[52]), "+f"(d[53]), "+f"(d[54]), "+f"(d[55]), "+f"(d[56]), "+f"(d[57]), "+f"(d[58]), "+f"(d[59]), "+f"(d[60]), "+f"(d[61]), "+f"(d[62]), "+f"(d[63])
    : "r"(a0), "r"(a1), "r"(a2), "r"(a3), "r"(blo));
}

__device__ __forceinline__ void cv_copy(float (&acc)[64]) {
#pragma unroll
  for (int i = 0; i < 64; i++) { float t; asm volatile("mov.b32 %0, %1;" : "=f"(t) : "f"(acc[i]) : "memory"); acc[i] = t; }
}
template <int D0> __device__ __forceinline__ void cv_loadA(uint32_t (&A)[4][4], uint32_t kaddr) {
#pragma unroll
  for (int i = 0; i < 4; i++) {
    uint32_t a = kaddr + (D0 + i) * 128;
    uint32_t w0 = lds32(a), w1 = lds32(a + 4), w2 = lds32(a + 8);
    A[i][0] = __byte_perm(w0, w1, 0x5432); A[i][1] = w1; A[i][2] = __byte_perm(w1, w2, 0x5432); A[i][3] = w2;
  }
#pragma unroll
  for (int i = 0; i < 4; i++) asm volatile("" : "+r"(A[i][0]), "+r"(A[i][1]), "+r"(A[i][2]), "+r"(A[i][3])::"memory");
}
template <int G> __device__ __forceinline__ void cv_rec(float (&acc)[64], const uint32_t (&A)[4][4], uint32_t kaddr, uint32_t db0) {
  wgmma_fence();
#pragma unroll
  for (int i = 0; i < 4; i++) wgmma_rs_hi<128 - 16 * G>(acc, A[i][0], A[i][1], A[i][2], A[i][3], db0 - 4 * i);
  wgmma_commit();
  if constexpr (G < 7) {
    uint32_t B[4][4];
    cv_loadA<4 * (G + 1)>(B, kaddr);
    wgmma_wait<0>(); cv_copy(acc);
    cv_rec<G + 1>(acc, B, kaddr, db0);
  } else { wgmma_wait<0>(); cv_copy(acc); }
}
__device__ __forceinline__ void conv_channel(const Params& p, int slot, int ch, int barid) {
  int tid = tid_opaque() & 127, w = tid >> 5, lane = tid & 31, r = lane >> 2, q = lane & 3;
  int i_ = r >> 1, i0 = i_ & 1, i1 = i_ >> 1;
  int bl = 4 * (r & 1) + 2 * (w & 1) + 8 * (w >> 1);
  const uint32_t cb = sb + CV_OFF + slot * CV_B;
  uint32_t dd = (uint32_t)__bfloat16_as_ushort(p.ssmD[ch]); dd |= dd << 16;
  mbar_wait(sb + BAR_OFF + 8 * (B_CVFULL + slot));
  const uint32_t kaddr = cb + CV_K - 32 + 4 * (8 * i_ + (bl >> 1) + 2 * q);
  const uint32_t db0 = desc_lo(cb + CV_U + 192, CV_PL);
  float acc[64];
#pragma unroll
  for (int i = 0; i < 64; i++) acc[i] = 0.f;
  uint32_t A[4][4];
  cv_loadA<0>(A, kaddr);
  cv_copy(acc);
  cv_rec<0>(acc, A, kaddr, db0);
  float E[8][4];
  const int src1 = i1 == 0 ? (lane - q + 16 + ((q + 3) & 3)) : (lane - q - 16 + ((q + 1) & 3));
  const bool s3 = (i1 == 1 && q == 3), kodd = (i1 == 1 && q < 3);
#pragma unroll
  for (int J = 0; J < 8; J++)
#pragma unroll
    for (int x = 0; x < 4; x++) {
      float ev = acc[8 * J + x], od = acc[8 * J + 4 + x], pv = J > 0 ? acc[8 * J - 4 + x] : 0.f;
      float send = kodd ? ev : (s3 ? pv : od);
      float keep = kodd ? od : ev;
      E[J][x] = keep + __shfl_sync(0xffffffffu, send, src1);
    }
  const int P = i1 == 0 ? q : 4 + ((q + 1) & 3);
  const int Pm = (P + 7) & 7, qm = Pm < 4 ? Pm : ((Pm - 1) & 3), i1m = Pm >> 2;
  const int src2 = i0 == 1 ? lane - 8 : (16 * i1m + 8 + 4 * (r & 1) + qm);
  const bool wrap = (i0 == 1 && P == 7);
  const uint32_t kvaddr = cb + CV_U + 192 + (((14 - bl) >> 1) & 1) * CV_PL + (2 * P + i0) * 16 + ((14 - bl) >> 2) * 4;
  uint32_t gw[8];
#pragma unroll
  for (int J = 0; J < 8; J++) {
    float o[2];
#pragma unroll
    for (int h = 0; h < 2; h++) {
      float pv = J > 0 ? E[J - 1][2 * h + 1] : 0.f;
      float send = wrap ? pv : E[J][2 * h + 1];
      o[h] = E[J][2 * h] + __shfl_sync(0xffffffffu, send, src2);
    }
    uint32_t kvw = lds32(kvaddr + J * 256);
    kvw = __byte_perm(kvw, kvw, 0x1032);
    gw[J] = hadd2(pack_bf16(o[0], o[1]), hmul2(kvw, dd));
  }
  bar_sync(barid, 128);
  int tb = 16 * (2 * P + i0) + bl;
  asm volatile("" : "+r"(tb));
#pragma unroll
  for (int J = 0; J < 8; J++) {
    int t = 256 * J + tb;
    int T = t / 160, tl = t - T * 160;
    int qq = (T == NT1 - 1) ? (tl >> 5) : (tl / 40);
    int j = (tl - qq * ((T == NT1 - 1) ? 32 : 40)) >> 1;
    int c = 20 * T + j;
    c = c ^ ((c >> 3) & 7);
    sts32(cb + CV_K + c * 16 + qq * 4, gw[J]);
  }
  fence_async_smem();
  mbar_arrive(sb + BAR_OFF + 8 * (B_CVDONE + slot));
}

template <int W> struct KvRegs { uint32_t k[19][W], v[16][W], s[W][4]; };
template <int W> __device__ __forceinline__ void kv_load(const Params& p, int m, int c0, KvRegs<W>& x) {
  const int lane = tid_opaque() & 31, ch = c0 + 2 * W * (lane & 7), t0 = 64 * m + 16 * (lane >> 3);
  const uint32_t* kp = (const uint32_t*)(p.k + (t0 * DM + ch));
  const uint32_t* vp = (const uint32_t*)(p.v + (t0 * DM + ch));
#pragma unroll
  for (int i = 0; i < 19; i++) {
    if (W == 2) { uint2 t = (i >= 3 || t0 > 0) ? __ldg((const uint2*)(kp + (i - 3) * (DM / 2))) : make_uint2(0u, 0u); x.k[i][0] = t.x; x.k[i][W - 1] = t.y; }
    else x.k[i][0] = (i >= 3 || t0 > 0) ? __ldg(kp + (i - 3) * (DM / 2)) : 0u;
  }
#pragma unroll
  for (int i = 0; i < 16; i++) {
    if (W == 2) { uint2 t = __ldg((const uint2*)(vp + i * (DM / 2))); x.v[i][0] = t.x; x.v[i][W - 1] = t.y; }
    else x.v[i][0] = __ldg(vp + i * (DM / 2));
  }
#pragma unroll
  for (int c = 0; c < W; c++) { uint4 t = __ldg((const uint4*)(p.shiftk + ch * 4) + c); x.s[c][0] = t.x; x.s[c][1] = t.y; x.s[c][2] = t.z; x.s[c][3] = t.w; }
}
template <int W> __device__ __forceinline__ void kv_finish(int m, int c0, KvRegs<W>& x) {
  const int lane = tid_opaque() & 31;
  uint8_t* dst = g_kv + ((c0 + 2 * W * (lane & 7)) * 4096 + (4 * m + (lane >> 3)) * 16);
#pragma unroll
  for (int c = 0; c < W; c++) {
    const uint32_t w0 = __byte_perm(x.s[c][0], x.s[c][2], 0x5410), w1 = __byte_perm(x.s[c][0], x.s[c][2], 0x7632);
    const uint32_t w2 = __byte_perm(x.s[c][1], x.s[c][3], 0x5410), w3 = __byte_perm(x.s[c][1], x.s[c][3], 0x7632);
#pragma unroll
    for (int i = 0; i < 16; i++) {
      uint32_t a = hmul2(x.k[i][c], w3);
      a = hadd2(a, hmul2(x.k[i + 1][c], w2)); a = hadd2(a, hmul2(x.k[i + 2][c], w1)); a = hadd2(a, hmul2(x.k[i + 3][c], w0));
      x.v[i][c] = hmul2(a, x.v[i][c]);
    }
#pragma unroll
    for (int e = 0; e < 2; e++)
#pragma unroll
      for (int f = 0; f < 2; f++) {
        uint32_t o[4];
#pragma unroll
        for (int qq = 0; qq < 4; qq++) o[qq] = __byte_perm(x.v[15 - 4 * qq - 2 * f][c], x.v[14 - 4 * qq - 2 * f][c], e ? 0x7632 : 0x5410);
        *(uint4*)(dst + (2 * c + e) * 4096 + f * 2048) = make_uint4(o[0], o[1], o[2], o[3]);
      }
  }
}
__device__ __forceinline__ void stat_table(int T1, unsigned want, int l) {
#pragma unroll 1
  for (int n = tid_opaque() & 127; n < (T1 == NT1 - 1 ? 128 : 160); n += 128) {
    const uint4* rp = &g_stats[(160 * T1 + n) * 8];
    float a[4], b[4];
    uint32_t it = 0;
    while (true) {
      bool ok = true;
#pragma unroll
      for (int i = 0; i < 4; i++) ok &= (rec_ld(rp + 2 * i, a[i], b[i]) == want);
      if (ok) break;
      if (++it > SPIN_LIMIT) __trap();
    }
    const float m = 0.25f * ((a[0] + a[1]) + (a[2] + a[3]));
    float v = (b[0] + b[1]) + (b[2] + b[3]);
#pragma unroll
    for (int i = 0; i < 4; i++) v = fmaf(160.f * (a[i] - m), a[i] - m, v);
    const float rs = rsqrtf(v * (1.f / 640.f) + 1e-5f);
    sts64f(sb + STAB_OFF + n * 8, rs, -m * rs);
  }
  mbar_arrive(bars + 8 * (B_STAB + l));
}

template <bool FIRST>
__device__ __forceinline__ void stats_publish(int which, int n0, int dg, unsigned tag, const float (&acc)[80]) {
  const int lane = tid_opaque() & 31, q = lane & 3;
  float sh[2] = {0.f, 0.f};
  if (FIRST) { sh[0] = __shfl_sync(0xffffffffu, acc[0], lane & ~3); sh[1] = __shfl_sync(0xffffffffu, acc[2], lane & ~3); }
  float s1[2] = {0.f, 0.f}, s2[2] = {0.f, 0.f}, t1[2] = {0.f, 0.f}, t2[2] = {0.f, 0.f};
#pragma unroll
  for (int j = 0; j < 20; j++)
#pragma unroll
    for (int h = 0; h < 2; h++) {
      float a = acc[4 * j + 2 * h], b = acc[4 * j + 2 * h + 1];
      if (FIRST) { a -= sh[h]; b -= sh[h]; }
      s1[h] += a; t1[h] += b; s2[h] = fmaf(a, a, s2[h]); t2[h] = fmaf(b, b, t2[h]);
    }
#pragma unroll
  for (int h = 0; h < 2; h++) {
    s1[h] += t1[h]; s2[h] += t2[h];
    s1[h] += __shfl_xor_sync(0xffffffffu, s1[h], 1); s2[h] += __shfl_xor_sync(0xffffffffu, s2[h], 1);
    s1[h] += __shfl_xor_sync(0xffffffffu, s1[h], 2); s2[h] += __shfl_xor_sync(0xffffffffu, s2[h], 2);
  }
  if (FIRST || (q & 1) == (which & 1)) {
    const int h = q >> 1;
    float a = h ? s1[1] : s1[0], b = h ? s2[1] : s2[0], c = h ? sh[1] : sh[0];
    float mean = a * (1.f / 160.f);
    rec_st(&g_stats[((n0 + 8 * h) * 4 + dg) * 2 + (q & 1)], mean + c, fmaxf(b - a * mean, 0.f), 4 * tag + which);
  }
}
__device__ __forceinline__ void stats_combine(float mi, float m2, float& mean, float& rstd) {
  float m = mi + __shfl_xor_sync(0xffffffffu, mi, 1);
  m += __shfl_xor_sync(0xffffffffu, m, 2);
  m *= 0.25f;
  float d = mi - m;
  float v = fmaf(160.f * d, d, m2);
  v += __shfl_xor_sync(0xffffffffu, v, 1);
  v += __shfl_xor_sync(0xffffffffu, v, 2);
  mean = m; rstd = rsqrtf(v * (1.f / 640.f) + 1e-5f);
}
__device__ __forceinline__ void stats_get(int which, int n0, unsigned tag, float (&mean)[2], float (&rstd)[2]) {
  const int q = tid_opaque() & 3;
  const uint4* p0 = &g_stats[(n0 * 4 + q) * 2 + (which & 1)];
  float a0, b0, a1, b1;
  uint32_t it = 0;
  tag = 4 * tag + which;
  while (true) {
    unsigned t0 = rec_ld(p0, a0, b0), t1 = rec_ld(p0 + 64, a1, b1);
    if (t0 == tag && t1 == tag) break;
    if (++it > SPIN_LIMIT) __trap();
  }
  __syncwarp();
  stats_combine(a0, b0, mean[0], rstd[0]);
  stats_combine(a1, b1, mean[1], rstd[1]);
}
__device__ __forceinline__ void x0_load(const Params& p, int n0, int d0, uint2 (&xv)[2][10]) {
#pragma unroll
  for (int h = 0; h < 2; h++) {
    const uint2* xp = (const uint2*)(p.x + (n_to_t(n0 + 8 * h) * DM + d0 + 4 * (tid_opaque() & 3)));
#pragma unroll
    for (int J = 0; J < 10; J++) xv[h][J] = __ldg(xp + 4 * J);
  }
}
__device__ __forceinline__ void x0_unpack(const uint2 (&xv)[2][10], float (&acc)[80]) {
#pragma unroll
  for (int h = 0; h < 2; h++)
#pragma unroll
    for (int J = 0; J < 10; J++) {
      acc[8 * J + 2 * h] = bf_lo(xv[h][J].x); acc[8 * J + 2 * h + 1] = bf_hi(xv[h][J].x);
      acc[8 * J + 4 + 2 * h] = bf_lo(xv[h][J].y); acc[8 * J + 4 + 2 * h + 1] = bf_hi(xv[h][J].y);
    }
}

__global__ void __launch_bounds__(512, 1) fused_kernel(const __grid_constant__ Params p) {
  extern __shared__ __align__(1024) uint8_t smem_raw[];
  const int tid = threadIdx.x, lane = tid & 31;
  const int wid = __shfl_sync(0xffffffffu, tid >> 5, 0), wg = wid >> 2;
  const unsigned tag = ld_rlx(g_epoch) + 1;
  unsigned smid; asm volatile("mov.u32 %0, %%smid;" : "=r"(smid));
  if (smid >= 132 || smem_u32(smem_raw) != sb) __trap();
  int role;
  {
  const int side = smid & 1;
  int gpc, gi;
  {
    int tpc = smid >> 1;
    if (tpc < 32) { gpc = tpc & 7; gi = tpc >> 3; }
    else if (tpc < 60) { gpc = 1 + (tpc - 32) % 7; gi = 4 + (tpc - 32) / 7; }
    else if (tpc < 62) { gpc = tpc - 54; gi = 8; }
    else { gpc = 0; gi = tpc - 58; }
  }
  const int pos = 8 * gpc + gi + (gpc == 7 ? 1 : 0);
  if (pos == 65) {
    if (tid < 32) {
      for (int i = lane; i < NT1 * 16; i += 32)
        if ((i & 15) < 10) { uint32_t it = 0; while ((int)(ld_rlx(&g_hflag[(i >> 4) * 32 + (i & 15)]) - tag) < 0) { __nanosleep(500); if (++it > SPIN_LIMIT) __trap(); } }
    }
    return;
  }
  int T1, GP;
  if (pos < 52) { int hh = pos / 26, x = pos - 26 * hh; T1 = x >> 1; GP = 2 * hh + (x & 1); }
  else { T1 = pos - 52; GP = 4; }
  const bool last = (T1 == NT1 - 1);
  const bool has2 = gi < 8;
  const int m2 = 8 * (gpc >> 1) + gi, dg = 2 * (gpc & 1) + side;
  role = T1 | (GP << 4) | (side << 7) | (m2 << 8) | (dg << 14) | ((int)has2 << 16);

  if (wid == 12) {
    if (elect_one()) {
#pragma unroll
      for (int k = 0; k < S1; k++) mbar_init(bars + 8 * (B_G1FULL + k), 1);
      asm volatile("fence.mbarrier_init.release.cluster;" ::: "memory");
      TS(45);
    }
    __syncwarp();
    asm volatile("bar.arrive 5, 512;" ::: "memory");
    if (elect_one()) {
#pragma unroll 1
      for (int k = 0; k < S1; k++) {
        const uint32_t fb = bars + 8 * (B_G1FULL + k);
        mbar_expect_tx(fb, G1_STAGE);
        tma4(sb + k * G1_STAGE + G1_XOFF, last ? &p.mXl : &p.mX, 64 * k, 0, 0, last ? 0 : 80 * T1, fb);
        tma5(sb + k * G1_STAGE, &p.mB, 64 * k, 0, 0, 4 * side, 2 * GP, fb);
      }
      TS(44);
    }
    __syncwarp();
    bar_sync(6, 64);
  } else {
    if (wid < 15) {
      if (elect_one()) {
        const int g = wid < 12 ? wid : wid - 1;
        const int cnt = g < 9 ? 2 : 1;
#pragma unroll
        for (int i = 0; i < 9; i++) mbar_init(bars + 8 * (5 + 9 * g + i), cnt);
        asm volatile("fence.mbarrier_init.release.cluster;" ::: "memory");
      }
      if (wid < 5) {
        uint32_t cb = sb + CV_OFF + wid * CV_B;
        uint32_t a = lane < 8 ? cb + 16 * lane : (lane < 20 ? cb + CV_U + 16 * (lane - 8) : cb + CV_U + CV_PL + 16 * (lane - 20));
        asm volatile("st.shared.v4.u32 [%0], {%1,%1,%1,%1};" ::"r"(a), "r"(0) : "memory");
        fence_async_smem();
      }
    } else if (elect_one()) {
#pragma unroll
      for (int i = 0; i < 7; i++) mbar_init(bars + 8 * (B_CVDONE + i), 128);
      mbar_init(bars + 8 * B_CTAB, 64);
      mbar_init(bars + 8 * B_PREP, 1);
      asm volatile("fence.mbarrier_init.release.cluster;" ::: "memory");
    }
    __syncwarp();
    bar_sync(5, 512);
    if (wid == 0) asm volatile("bar.arrive 6, 64;" ::: "memory");
  }
  if (tid == 0) TS(0);
  }

  if (wg == 3) {
    asm volatile("setmaxnreg.dec.sync.aligned.u32 56;");
    ROLE(role)
    const int pw = wid & 3;
    if (pw >= 2 && has2) {
      KvRegs<1> x;
      kv_load<1>(p, m2, 160 * dg + 128 + 16 * (pw - 2), x);
      kv_finish<1>(m2, 160 * dg + 128 + 16 * (pw - 2), x);
      asm volatile("bar.arrive 3, 192;" ::: "memory");
    }
    if (pw == 0) {
#pragma unroll 1
      for (int i = 0; i < 2; i++) {
        const int ch = 128 * GP + 64 * i + 32 * side + lane;
        const float lr = __bfloat162float(p.lre[ch]), li = __bfloat162float(p.lim[ch]);
        const float dt = __bfloat162float(__float2bfloat16_rn(expf(__bfloat162float(p.logdt[ch]))));
        const float mag = expf(dt * lr);
        float sn, cs; sincosf(dt * li, &sn, &cs);
        const float ar = mag * cs, ai = mag * sn;
        const float inv = 2.f / (lr * lr + li * li);
        const uint32_t ad = sb + CTAB_OFF + (32 * i + lane) * 24;
        sts64f(ad, ar, ai);
        sts64f(ad + 8, ((ar - 1.f) * lr + ai * li) * inv, (ai * lr - (ar - 1.f) * li) * inv);
      }
      if (has2 && lane < 20) {
        uint4 dv = __ldg((const uint4*)(p.dskip + 160 * dg) + lane);
        asm volatile("st.shared.v4.u32 [%0], {%1,%2,%3,%4};" ::"r"(sb + DTAB_OFF + 16 * lane), "r"(dv.x), "r"(dv.y), "r"(dv.z), "r"(dv.w) : "memory");
      }
      mbar_arrive(bars + 8 * B_CTAB);
      if (lane == 0) TS(46);
#pragma unroll 1
      for (int l = 0; l < 2; l++) {
        if (l == 1) mbar_wait(bars + 8 * (has2 ? B_G2DONE + 19 : B_G1DONE + 9));
        int s = 0;
#pragma unroll 1
        for (int k = l == 0 ? S1 : 0; k < 10; k++) {
          if (k >= S1) mbar_wait(bars + 8 * (B_G1DONE + 10 * l + k - S1));
          const uint32_t fb = bars + 8 * (B_G1FULL + 10 * l + k);
          if (elect_one()) {
            mbar_expect_tx(fb, 16384);
            tma5(sb + s * G1_STAGE, &p.mB, 64 * k, 0, 0, 4 * side, 2 * GP, fb);
          }
          if (++s == S1) s = 0;
        }
        if (has2) {
          const int SW = l == 0 ? 6 : 7;
          mbar_wait(bars + 8 * (B_G1DONE + 10 * l + 9));
          s = 0;
#pragma unroll 1
          for (int k = 0; k < 20; k++) {
            if (k >= SW) mbar_wait(bars + 8 * (B_G2DONE + 20 * l + k - SW));
            const uint32_t fb = bars + 8 * (B_G2FULL + 20 * l + k);
            const int w = k >= 10, x = k - 10 * w;
            if (elect_one()) {
              mbar_expect_tx(fb, G2_WB);
              tma5(sb + G2_WOFF + s * G2_WB, (x & 1) ? &p.mCim : &p.mCre, 128 * (x >> 1) + 64 * w, 0, 0, 0, 10 * dg, fb);
            }
            if (++s == SW) s = 0;
          }
        }
      }
    } else if (pw == 1) {
      if (has2) {
#pragma unroll 1
        for (int c = 0; c < 5; c += 2) {
          float sv[4];
#pragma unroll
          for (int x = 0; x < 4; x++) {
            const uint2* row = (const uint2*)(((x & 1) ? p.bim : p.bre) + (cch0 + min(c + (x >> 1), 4)) * DM) + lane;
            float a = 0.f;
#pragma unroll
            for (int i = 0; i < 5; i++) { uint2 t = __ldg(row + 32 * i); a += (bf_lo(t.x) + bf_hi(t.x)) + (bf_lo(t.y) + bf_hi(t.y)); }
            sv[x] = a;
          }
#pragma unroll
          for (int o = 16; o > 0; o >>= 1)
#pragma unroll
            for (int x = 0; x < 4; x++) sv[x] += __shfl_xor_sync(0xffffffffu, sv[x], o);
          if (lane < 4) rec_st(&g_sB[(cch0 + min(c + (lane >> 1), 4)) * 2 + (lane & 1)], lane < 2 ? sv[0] : sv[2], lane < 2 ? sv[1] : sv[3], tag);
        }
        if (lane == 0) TS(47);
      }
#pragma unroll 1
      for (int l = 0; l < 2; l++) {
        if (l == 1) {
          mbar_wait(bars + 8 * (has2 ? B_G2DONE + 19 : B_G1DONE + 9));
          const int mlo = (160 * T1) >> 6, nf = last ? 8 : 12;
          if (lane < nf) flag_poll(&g_uflag[4 * mlo + lane], tag);
          __syncwarp();
          fence_async_global();
          if (lane == 0) TS(20);
        }
        int s = 0;
#pragma unroll 1
        for (int k = l == 0 ? S1 : 0; k < 10; k++) {
          if (k >= S1) mbar_wait(bars + 8 * (B_G1DONE + 10 * l + k - S1));
          const uint32_t fb = bars + 8 * (B_G1FULL + 10 * l + k), dst = sb + s * G1_STAGE + G1_XOFF;
          if (l == 0) {
            if (elect_one()) {
              mbar_expect_tx(fb, 20480);
              tma4(dst, last ? &p.mXl : &p.mX, 64 * k, 0, 0, last ? 0 : 80 * T1, fb);
            }
          } else {
            const int bytes = last ? 16384 : 20480;
            if (elect_one()) {
              mbar_expect_tx(fb, bytes);
              bulk_g2s(dst, g_u + (size_t)(T1 * 10 + k) * 20480, bytes, fb);
            }
          }
          if (++s == S1) s = 0;
        }
        if (has2) {
          mbar_wait(bars + 8 * (B_G1DONE + 10 * l + 9));
          const int Tlo = (64 * m2) / 160, Thi = (64 * m2 + 63) / 160;
          s = 0;
#pragma unroll 1
          for (int k = 0; k < 20; k++) {
            if (k == 0 || k == SX2) {
              if ((lane & 15) < 10) flag_poll(&g_hflag[((l * NT1 + (lane < 16 ? Tlo : Thi)) * 2 + (k > 0)) * 16 + (lane & 15)], tag);
              __syncwarp();
              fence_async_global();
              if (lane == 0) TS(21 + 2 * l + (k > 0));
            }
            if (k >= SX2) mbar_wait(bars + 8 * (B_G2DONE + 20 * l + k - SX2));
            const uint32_t fb = bars + 8 * (B_G2FULL + 20 * l + k);
            if (elect_one()) {
              mbar_expect_tx(fb, G2_XB);
              bulk_g2s(sb + s * G2_XB, g_h + (size_t)((l * 32 + m2) * 20 + k) * 8192, G2_XB, fb);
            }
            if (++s == SX2) s = 0;
          }
        }
      }
    } else if (pw == 2) {
#pragma unroll 1
      for (int i = 0; i < 2; i++) {
        float a, b;
        rec_poll(&g_sB[(128 * GP + 64 * i + 32 * side + lane) * 2], tag, a, b);
        sts64f(sb + CTAB_OFF + (32 * i + lane) * 24 + 16, a, b);
      }
      mbar_arrive(bars + 8 * B_CTAB);
      if (lane == 0) TS(54);
      if (has2) {
#pragma unroll 1
        for (int c = 0; c < 5; c++) {
          mbar_wait(bars + 8 * (B_CVDONE + c));
          if (elect_one()) {
            bulk_s2g(g_G + (size_t)(cch0 + c) * 4096, sb + CV_OFF + c * CV_B + CV_K, 4096);
            asm volatile("cp.async.bulk.commit_group;" ::: "memory");
            if (c == 4) {
              asm volatile("cp.async.bulk.wait_group 0;" ::: "memory");
              fence_async_global();
              red_rel(&g_gcnt[dg * 32], 1);
            }
          }
        }
      }
    } else if (has2) {
      if (elect_one()) {
#pragma unroll
        for (int c = 0; c < 5; c++) {
          const uint32_t fb = bars + 8 * (B_CVFULL + c);
          mbar_expect_tx(fb, 4096);
          bulk_g2s(sb + CV_OFF + c * CV_B + CV_K, p.ssmk + (size_t)(cch0 + c) * SEQ, 4096, fb);
        }
        l2_prefetch(p.cre + (size_t)cch0 * DM, 6400);
        l2_prefetch(p.cim + (size_t)cch0 * DM, 6400);
        asm volatile("prefetch.tensormap [%0];" ::"l"(&p.mCre) : "memory");
        asm volatile("prefetch.tensormap [%0];" ::"l"(&p.mCim) : "memory");
        asm volatile("prefetch.tensormap [%0];" ::"l"(&p.mG) : "memory");
      }
      flag_poll(&g_kvcnt[dg * 32], tag * 32);
      __syncwarp();
      fence_async_global();
      if (lane == 0) TS(28);
      if (elect_one()) {
#pragma unroll
        for (int c = 0; c < 5; c++) {
          const uint32_t fb = bars + 8 * (B_CVFULL + c), cb = sb + CV_OFF + c * CV_B + CV_U + 192;
          mbar_expect_tx(fb, 4096);
          bulk_g2s(cb, g_kv + (size_t)(cch0 + c) * 4096, 2048, fb);
          bulk_g2s(cb + CV_PL, g_kv + (size_t)(cch0 + c) * 4096 + 2048, 2048, fb);
        }
      }
      flag_poll(&g_gcnt[dg * 32], tag * 32);
      __syncwarp();
      fence_async_global();
      if (lane == 0) TS(29);
      if (elect_one()) {
        mbar_expect_tx(bars + 8 * B_GFULL, 20480);
        tma5(sb + G_OFF, &p.mG, 64 * m2, 0, 0, 0, 10 * dg, bars + 8 * B_GFULL);
      }
    }
  } else {
    asm volatile("setmaxnreg.inc.sync.aligned.u32 152;");
    const int w = wid & 3;
    if (wg == 2) {
      ROLE(role)
      if (has2) {
        const int n0 = 64 * m2 + 16 * w + (lane >> 2);
        uint2 xv[2][10];
        KvRegs<2> x;
        x0_load(p, n0, 160 * dg, xv);
        kv_load<2>(p, m2, 160 * dg + 32 * w, x);
        if (tid == 256) TS(50);
        {
          float xs[80];
          x0_unpack(xv, xs);
          stats_publish<true>(0, n0, dg, tag, xs);
        }
        if (tid == 256) TS(31);
        kv_finish<2>(m2, 160 * dg + 32 * w, x);
        if (tid == 256) TS(52);
        bar_sync(3, 192);
        if (tid == 256) { mbar_arrive(bars + 8 * B_PREP); red_rel(&g_kvcnt[dg * 32], 1); TS(30); }
      } else if (tid == 256) mbar_arrive(bars + 8 * B_PREP);
      stat_table(T1, 4 * tag, 0);
      if (tid == 256) TS(26);
      if (!has2) { mbar_wait(bars + 8 * (B_G1FULL + 10)); stat_table(T1, 4 * tag + 2, 1); }
    }
#pragma unroll 1
    for (int l = 0; l < 2; l++) {
      if (wg < 2) {
        float acc[80];
#pragma unroll
        for (int i = 0; i < 80; i++) acc[i] = 0.f;
        ROLE(role)
        const int tid = tid_opaque(), r = (tid & 31) >> 2, q = tid & 3;
        const int ch = 128 * GP + 64 * wg + 32 * side + 8 * w + r;
        fence_regs(acc);
        {
          uint32_t alo = desc_lo(sb, 16) + wg * 512, blo = l == 0 ? desc_lo(sb + G1_XOFF, 16) : desc_lo(sb + G1_XOFF, 128);
          const uint32_t bhi = l == 0 ? desc_hi(1024, 1) : desc_hi(1024, 0), xstep = l == 0 ? 2 : 16;
          uint32_t fb = bars + 8 * (B_G1FULL + 10 * l);
          mbar_wait(fb);
          if (tid == 0) TS(1 + 8 * l);
#pragma unroll 1
          for (int k = 0; k < 10; k++) {
            wgmma_fence();
#pragma unroll
            for (int kk = 0; kk < 4; kk++) wgmma_n160<0>(acc, alo + kk * 2, desc_hi(1024, 1), blo + kk * xstep, bhi);
            wgmma_commit();
            const uint32_t adv = k == S1 - 1 ? (uint32_t)(-(int)((S1 - 1) * (G1_STAGE >> 4))) : (G1_STAGE >> 4);
            alo += adv; blo += adv;
            if (k < 9) mbar_wait(fb + 8);
            if (k > 0) { wgmma_wait<1>(); if ((tid & 127) == 0) mbar_arrive(fb + 8 * (B_G1DONE - B_G1FULL - 1)); }
            if (l == 0 && k == S1 - 1) { if (tid == 0) TS(48); mbar_wait(bars + 8 * B_PREP); if (tid == 0) TS(49); }
            fb += 8;
          }
        }
        mbar_wait(bars + 8 * B_CTAB);
        const uint32_t ca = sb + CTAB_OFF + (32 * wg + 8 * w + r) * 24;
        float2 lam = lds64f(ca), sB = lds64f(ca + 16);
        const float2 coef = lds64f(ca + 8), lamc = make_float2(lam.x, -lam.y);
        float m00 = coef.x, m01 = -coef.y, m10 = -coef.y, m11 = -coef.x;
        if (p.swap) { lam = lamc; sB = make_float2(sB.y, sB.x); m00 = -coef.y; m01 = coef.x; m10 = -coef.x; m11 = -coef.y; }
        float2 pL, p2L, pLq, p160q, p640;
        {
          float2 p2 = cmul(lam, lam), p4 = cmul(p2, p2), p8 = cmul(p4, p4), p16 = cmul(p8, p8), p32 = cmul(p16, p16);
          float2 p40 = cmul(p32, p8), p80 = cmul(p40, p40), p160 = cmul(p80, p80), p320 = cmul(p160, p160);
          p640 = cmul(p320, p320);
          pL = last ? p32 : p40;
          p2L = cmul(pL, pL);
          const float2 one = make_float2(1.f, 0.f);
          pLq = cmul((q & 1) ? pL : one, (q & 2) ? p2L : one);
          p160q = cmul((q & 1) ? p160 : one, (q & 2) ? p320 : one);
        }
        mbar_wait(bars + 8 * (B_STAB + l));
        wgmma_wait<0>();
        fence_regs(acc);
        if ((tid & 127) == 0) { mbar_arrive(bars + 8 * (B_G1DONE + 10 * l + 9)); if (wg == 0) TS(2 + 8 * l); }
        float2 e = make_float2(0.f, 0.f), snap = e;
#pragma unroll
        for (int j = 0; j < 20; j++) {
          const float4 st = lds128f(sb + STAB_OFF + (8 * j + 2 * q) * 8);
          acc[4 * j + 0] = fmaf(acc[4 * j + 0], st.x, st.y * sB.x);
          acc[4 * j + 2] = fmaf(acc[4 * j + 2], st.x, st.y * sB.y);
          acc[4 * j + 1] = fmaf(acc[4 * j + 1], st.z, st.w * sB.x);
          acc[4 * j + 3] = fmaf(acc[4 * j + 3], st.z, st.w * sB.y);
          e = cfma(lam, e, make_float2(acc[4 * j + 0], acc[4 * j + 2]));
          e = cfma(lam, e, make_float2(acc[4 * j + 1], acc[4 * j + 3]));
          if (j == 15) snap = e;
        }
        if (last) e = snap;
        {
          float2 v = make_float2(__shfl_up_sync(0xffffffffu, e.x, 1, 4), __shfl_up_sync(0xffffffffu, e.y, 1, 4));
          if (q >= 1) e = cfma(pL, v, e);
          v = make_float2(__shfl_up_sync(0xffffffffu, e.x, 2, 4), __shfl_up_sync(0xffffffffu, e.y, 2, 4));
          if (q >= 2) e = cfma(p2L, v, e);
        }
        if (!last && (q == 3 || (q == 2 && l == 0))) rec_st(&g_E[(T1 * DM + ch) * 2 + (q == 3 ? l : 1)], e.x, e.y, q == 3 ? tag : tag - 1);
        if (tid == 0) TS(3 + 8 * l);
        float2 ex = make_float2(__shfl_up_sync(0xffffffffu, e.x, 1, 4), __shfl_up_sync(0xffffffffu, e.y, 1, 4));
        if (q == 0) ex = make_float2(0.f, 0.f);
#pragma unroll
        for (int j = 0; j < 20; j++)
#pragma unroll
          for (int x = 0; x < 2; x++) {
            const float b0 = acc[4 * j + x], b1 = acc[4 * j + 2 + x];
            acc[4 * j + x] = fmaf(b0, m00, b1 * m01);
            acc[4 * j + 2 + x] = fmaf(b0, m10, b1 * m11);
          }
        float2 c;
        {
          float2 ev[3];
          uint32_t it = 0;
          while (true) {
            bool ok = true;
#pragma unroll
            for (int i = 0; i < 3; i++) {
              const int Tp = T1 - 1 - q - 4 * i;
              ev[i] = make_float2(0.f, 0.f);
              if (Tp >= 0) ok &= (rec_ld(&g_E[(Tp * DM + ch) * 2 + l], ev[i].x, ev[i].y) == tag);
            }
            if (ok) break;
            if (++it > SPIN_LIMIT) __trap();
          }
          __syncwarp();
          c = cfma(p640, cfma(p640, ev[2], ev[1]), ev[0]);
          c = cmul(c, p160q);
          c.x += __shfl_xor_sync(0xffffffffu, c.x, 1); c.y += __shfl_xor_sync(0xffffffffu, c.y, 1);
          c.x += __shfl_xor_sync(0xffffffffu, c.x, 2); c.y += __shfl_xor_sync(0xffffffffu, c.y, 2);
        }
        if (tid == 0) TS(4 + 8 * l);
        c = cfma(pLq, c, ex);
        float2 hh = make_float2(fmaf(c.x, m00, c.y * m01), fmaf(c.x, m10, c.y * m11));
        uint8_t* hb = g_h + (size_t)l * (32 * 20 * 8192) + (10 * wg + 2 * GP) * 8192 + (4 * side + w) * 1024 + (tid_opaque() & 31) * 4;
#pragma unroll
        for (int j4 = 0; j4 < 5; j4++) {
          const int ng = 20 * T1 + 4 * j4;
          uint8_t* hp = hb + (size_t)(ng >> 3) * 163840 + (ng & 7) * 128;
#pragma unroll
          for (int jj = 0; jj < 4; jj++) {
            const int j = 4 * j4 + jj;
            const float2 h0 = cfma(lamc, hh, make_float2(acc[4 * j + 0], acc[4 * j + 2]));
            hh = cfma(lamc, h0, make_float2(acc[4 * j + 1], acc[4 * j + 3]));
            if (j4 < 4 || !last) {
              *(uint32_t*)(hp + jj * 128) = pack_bf16(h0.x, hh.x);
              *(uint32_t*)(hp + jj * 128 + 8192) = pack_bf16(h0.y, hh.y);
            }
          }
        }
        bar_sync(1 + wg, 128);
        if ((tid & 127) == 0) {
          if (wg == 0) TS(5 + 8 * l);
          st_rel(&g_hflag[((l * NT1 + T1) * 2 + wg) * 16 + 2 * GP + side], tag);
          if (wg == 0) TS(6 + 8 * l);
        }
      }
      if (l == 0) {
        ROLE(role)
        if (has2) {
          if (wg == 2) mbar_wait(bars + 8 * (B_G1DONE + 8));
#pragma unroll 1
          for (int c = wg == 2 ? 0 : 2 + wg; c < (wg == 2 ? 2 : 5); c += wg == 2 ? 1 : 2) conv_channel(p, c, cch0 + c, 1 + wg);
          if ((tid & 127) == 0) TS(wg == 2 ? 32 : 7 + wg);
        }
      }
      if (wg == 2) break;
    }
    if (wg == 2 && (role >> 16)) {
      float acc[80];
      float off[2] = {0.f, 0.f};
      {
        ROLE(role)
        uint2 xv[2][10];
        x0_load(p, 64 * m2 + 16 * w + ((tid_opaque() & 31) >> 2), 160 * dg, xv);
        x0_unpack(xv, acc);
      }
#pragma unroll 1
      for (int l = 0; l < 2; l++) {
        float mean[2], rstd[2];
        {
          ROLE(role)
          const int lane = tid_opaque() & 31;
          stats_get(2 * l, 64 * m2 + 16 * w + (lane >> 2), tag, mean, rstd);
          off[0] += mean[0]; off[1] += mean[1];
          mbar_wait(bars + 8 * B_CTAB);
#pragma unroll
          for (int J = 0; J < 10; J++) {
            const float2 dw = lds64f(sb + DTAB_OFF + 2 * (16 * J + 4 * (lane & 3)));
#pragma unroll
            for (int x = 0; x < 8; x++) {
              const int h = (x >> 1) & 1;
              const uint32_t gwd = __float_as_uint(x < 4 ? dw.x : dw.y);
              acc[8 * J + x] = (acc[8 * J + x] - mean[h]) * fmaf(rstd[h], (x & 1) ? bf_hi(gwd) : bf_lo(gwd), 1.f);
            }
          }
        }
        {
          const uint32_t aend = desc_lo(sb + SX2 * G2_XB, 1024), bend = desc_lo(sb + G2_WOFF + 6 * G2_WB, 16) + l * (G2_WB >> 4);
          uint32_t alo = desc_lo(sb, 1024), blo = desc_lo(sb + G2_WOFF, 16);
          uint32_t fb = bars + 8 * (B_G2FULL + 20 * l);
          fence_regs(acc);
          mbar_wait(fb);
          if (tid == 256) TS(33 + 6 * l);
#pragma unroll 1
          for (int k = 0; k < 20; k++) {
            if (l == 1 && (k & 3) == 3 && tid == 256) TS(56 + (k >> 2));
            wgmma_fence();
#pragma unroll
            for (int kk = 0; kk < 4; kk++) wgmma_n160<1>(acc, alo + kk * 128, desc_hi(128, 0), blo + kk * 2, desc_hi(1024, 1));
            wgmma_commit();
            alo += G2_XB >> 4; if (alo == aend) alo = desc_lo(sb, 1024);
            blo += G2_WB >> 4; if (blo == bend) blo = desc_lo(sb + G2_WOFF, 16);
            if (k < 19) mbar_wait(fb + 8);
            if (k > 0) { wgmma_wait<1>(); if (tid == 256) mbar_arrive(fb + 8 * (B_G2DONE - B_G2FULL - 1)); }
            fb += 8;
          }
          wgmma_wait<0>();
          fence_regs(acc);
          if (tid == 256) { mbar_arrive(bars + 8 * (B_G2DONE + 20 * l + 19)); TS(34 + 6 * l); }
        }
        ROLE(role)
        const int tq = tid_opaque() & 31, n0 = 64 * m2 + 16 * w + (tq >> 2);
        stats_publish<false>(2 * l + 1, n0, dg, tag, acc);
        uint32_t gf[10][4];
        mbar_wait(bars + 8 * B_GFULL);
        const uint32_t ga = sb + G_OFF + (8 * (tq >> 4) + (tq & 7)) * 128 + (((2 * w + ((tq >> 3) & 1)) ^ (m2 & 7) ^ (tq & 7)) << 4);
#pragma unroll
        for (int J = 0; J < 4; J++) ldsm4t(gf[J], ga + J * 2048);
        if (tid == 256) TS(35 + 6 * l);
        uint8_t* dst[2][2];
#pragma unroll
        for (int h = 0; h < 2; h++) {
          if (l == 0) {
            const int ng = 8 * m2 + 2 * w + h, T = ng / 20;
            uint8_t* ub = g_u + (T * 204800 + (ng - 20 * T) * 1024 + (tq & 2) * 64 + (tq & 28) * 4 + (tq & 1) * 8 + (5 * dg >> 1) * 20480);
            dst[h][1] = ub + ((dg & 1) ? 20480 - 512 : 0);
            dst[h][0] = ub + (dg & 1) * 512;
          } else {
            dst[h][0] = dst[h][1] = (uint8_t*)(p.out + (n_to_t(n0 + 8 * h) * DM + 160 * dg + 4 * (tq & 3)));
          }
        }
        stats_get(2 * l + 1, n0, tag, mean, rstd);
        if (tid == 256) TS(36 + 6 * l);
        off[0] += mean[0]; off[1] += mean[1];
#pragma unroll
        for (int J = 0; J < 10; J++) {
          asm volatile("" : "+r"(gf[J][0]), "+r"(gf[J][1]), "+r"(gf[J][2]), "+r"(gf[J][3])::"memory");
          if (J + 4 < 10) ldsm4t(gf[J + 4 < 10 ? J + 4 : 0], ga + (J + 4) * 2048);
#pragma unroll
          for (int x = 0; x < 8; x++) {
            const int h = (x >> 1) & 1;
            const uint32_t gwd = gf[J][x >> 1];
            acc[8 * J + x] = (acc[8 * J + x] - mean[h]) * fmaf(rstd[h], (x & 1) ? bf_hi(gwd) : bf_lo(gwd), 1.f);
          }
#pragma unroll
          for (int h = 0; h < 2; h++) {
            if (l == 0)
              *(uint2*)(dst[h][(J >> 1) & 1] + (J >> 2) * 20480 + (J & 3) * 256) =
                  make_uint2(pack_bf16(acc[8 * J + 2 * h], acc[8 * J + 2 * h + 1]), pack_bf16(acc[8 * J + 4 + 2 * h], acc[8 * J + 5 + 2 * h]));
            else
              *(float4*)(dst[h][0] + 64 * J) = make_float4(acc[8 * J + 2 * h] + off[h], acc[8 * J + 2 * h + 1] + off[h],
                                                           acc[8 * J + 4 + 2 * h] + off[h], acc[8 * J + 5 + 2 * h] + off[h]);
          }
        }
        if (l == 0) {
          bar_sync(3, 128);
          if (tid == 256) { TS(37); st_rel(&g_uflag[4 * m2 + dg], tag); TS(38); }
          stats_publish<false>(2, n0, dg, tag, acc);
          stat_table(T1, 4 * tag + 2, 1);
          if (tid == 256) TS(27);
        } else {
          if (tid == 256) {
            TS(43);
            if (m2 == 31 && dg == 3) asm volatile("st.relaxed.gpu.global.u32 [%0], %1;" ::"l"(g_epoch), "r"(tag) : "memory");
          }
        }
      }
    }
  }
}

typedef CUresult (*EncFn)(CUtensorMap*, CUtensorMapDataType, cuuint32_t, void*, const cuuint64_t*, const cuuint64_t*,
                          const cuuint32_t*, const cuuint32_t*, CUtensorMapInterleave, CUtensorMapSwizzle,
                          CUtensorMapL2promotion, CUtensorMapFloatOOBfill);

void encode(EncFn fn, CUtensorMap* m, const void* ptr, int rank, const cuuint64_t* dims, const cuuint64_t* strides, const cuuint32_t* box) {
  cuuint32_t es[5] = {1, 1, 1, 1, 1};
  fn(m, CU_TENSOR_MAP_DATA_TYPE_BFLOAT16, rank, (void*)ptr, dims, strides, box, es, CU_TENSOR_MAP_INTERLEAVE_NONE,
     CU_TENSOR_MAP_SWIZZLE_128B, CU_TENSOR_MAP_L2_PROMOTION_L2_128B, CU_TENSOR_MAP_FLOAT_OOB_FILL_NONE);
}

}

extern "C" void kernel_launch(void* const* d_in, const int* in_sizes, int n_in, void* d_out, int out_size) {
  (void)in_sizes; (void)n_in; (void)out_size;
  Params p;
  typedef const __nv_bfloat16* BP;
  p.x = (BP)d_in[0]; p.lre = (BP)d_in[1]; p.lim = (BP)d_in[2]; p.bre = (BP)d_in[3]; p.bim = (BP)d_in[4];
  p.cre = (BP)d_in[5]; p.cim = (BP)d_in[6]; p.logdt = (BP)d_in[7]; p.dskip = (BP)d_in[8];
  p.k = (BP)d_in[10]; p.v = (BP)d_in[11]; p.shiftk = (BP)d_in[12]; p.ssmk = (BP)d_in[13]; p.ssmD = (BP)d_in[14];
  p.out = (float*)d_out;
  void* fnp = nullptr;
  cudaDriverEntryPointQueryResult qr;
  cudaGetDriverEntryPoint("cuTensorMapEncodeTiled", &fnp, cudaEnableDefault, &qr);
  EncFn fn = (EncFn)fnp;
  void* gG = nullptr;
  cudaGetSymbolAddress(&gG, g_G);
  const cuuint64_t RB = DM * 2;
  {
    p.swap = p.bim < p.bre;
    const char* lo = (const char*)(p.swap ? p.bim : p.bre); const char* hi = (const char*)(p.swap ? p.bre : p.bim);
    cuuint64_t dims[5] = {640, 8, 2, 8, 10}, st[4] = {RB, (cuuint64_t)(hi - lo), 8 * RB, 64 * RB}; cuuint32_t box[5] = {64, 8, 2, 4, 2};
    encode(fn, &p.mB, lo, 5, dims, st, box);
  }
  {
    cuuint64_t dims[5] = {640, 2, 4, 2, 40}, st[4] = {RB, 4 * RB, 2 * RB, 16 * RB}; cuuint32_t box[5] = {64, 2, 4, 2, 10};
    encode(fn, &p.mCre, p.cre, 5, dims, st, box); encode(fn, &p.mCim, p.cim, 5, dims, st, box);
    cuuint64_t dimg[5] = {2048, 2, 4, 2, 40}, stg[4] = {4096, 4 * 4096, 2 * 4096, 16 * 4096};
    encode(fn, &p.mG, gG, 5, dimg, stg, box);
  }
  {
    cuuint64_t dims[4] = {640, 2, 4, 900}, st[3] = {RB, 40 * RB, 2 * RB}; cuuint32_t box[4] = {64, 2, 4, 20};
    encode(fn, &p.mX, p.x, 4, dims, st, box);
    cuuint64_t diml[4] = {640, 2, 4, 16}, stl[3] = {RB, 32 * RB, 2 * RB};
    encode(fn, &p.mXl, p.x + (size_t)1920 * DM, 4, diml, stl, box);
  }
  cudaFuncSetAttribute(fused_kernel, cudaFuncAttributeMaxDynamicSharedMemorySize, SMEM_BYTES);
  cudaLaunchConfig_t cfg = {};
  cfg.gridDim = dim3(132); cfg.blockDim = dim3(512); cfg.dynamicSmemBytes = SMEM_BYTES; cfg.stream = cudaStreamPerThread;
  cudaLaunchKernelEx(&cfg, fused_kernel, p);
}
```

```cpp
#include <cuda_runtime.h>
#include <cuda.h>
#include <cuda_bf16.h>
#include <stdint.h>

namespace {

constexpr int SEQ = 2048, DM = 640;
constexpr int NT1 = 13;
constexpr uint32_t SPIN_LIMIT = 1u << 22;

__device__ __align__(1024) uint8_t g_h[2 * 32 * 20 * 8192];
__device__ __align__(1024) uint8_t g_u[NT1 * 10 * 20480];
__device__ __align__(1024) uint8_t g_kv[DM * 4096];
__device__ __align__(1024) uint8_t g_G[DM * 4096];
__device__ __align__(128) uint4 g_E[NT1 * DM * 2];
__device__ __align__(128) uint4 g_stats[SEQ * 4 * 2];
__device__ __align__(128) uint4 g_sB[DM * 2];
__device__ __align__(128) unsigned g_hflag[2 * NT1 * 2 * 16];
__device__ __align__(128) unsigned g_uflag[32 * 4];
__device__ __align__(128) unsigned g_kvcnt[4 * 32];
__device__ __align__(128) unsigned g_gcnt[4 * 32];
__device__ __align__(128) unsigned g_epoch[32] = {1};
#define TS(i) do {} while (0)

struct Params {
  CUtensorMap mB, mCre, mCim, mX, mXl, mG, mK, mV, mXt, mXtl;
  const __nv_bfloat16 *x, *lre, *lim, *bre, *bim, *cre, *cim, *logdt, *dskip, *k, *v, *shiftk, *ssmk, *ssmD;
  float* out;
  int swap;
};

constexpr uint32_t sb = 1024;
constexpr uint32_t G1_STAGE = 36864, G1_XOFF = 16384;
constexpr int S1 = 4;
constexpr uint32_t XT_OFF = 159744, KS_OFF = 180224, VS_OFF = KS_OFF + 24320;
constexpr uint32_t G2_XB = 8192, G2_WB = 20480, G2_WOFF = 57344, G_OFF = 200704;
constexpr int SX2 = 7;
constexpr uint32_t CV_OFF = 184320, CV_K = 128, CV_PL = 2240, CV_U = CV_K + 4096, CV_B = 8704;
constexpr uint32_t MISC = 227840;
constexpr uint32_t BAR_OFF = MISC;
constexpr int B_G1FULL = 0, B_G1DONE = 20, B_G2FULL = 40, B_CVFULL = 80,
              B_G2DONE = 85, B_GFULL = 125, B_PREP = 126,
              B_CVDONE = 130, B_STAB = 135  , B_CTAB = 137, B_XFREE = 138,
              B_KV = 139, B_XT = 140;
constexpr uint32_t bars = sb + BAR_OFF;
constexpr uint32_t STAB_OFF = MISC + 1136;
constexpr uint32_t CTAB_OFF = STAB_OFF + 1280;
constexpr uint32_t DTAB_OFF = CTAB_OFF + 1536;
constexpr uint32_t SMEM_BYTES = 232448;
static_assert(DTAB_OFF + 320 <= SMEM_BYTES, "smem");

__device__ __forceinline__ uint32_t smem_u32(const void* p) { return (uint32_t)__cvta_generic_to_shared(p); }
__device__ __forceinline__ void mbar_init(uint32_t bar, int cnt) { asm volatile("mbarrier.init.shared::cta.b64 [%0], %1;" ::"r"(bar), "r"(cnt) : "memory"); }
__device__ __forceinline__ void mbar_expect_tx(uint32_t bar, int bytes) { asm volatile("mbarrier.arrive.expect_tx.shared::cta.b64 _, [%0], %1;" ::"r"(bar), "r"(bytes) : "memory"); }
__device__ __forceinline__ void mbar_arrive(uint32_t bar) { asm volatile("mbarrier.arrive.shared::cta.b64 _, [%0];" ::"r"(bar) : "memory"); }
__device__ __forceinline__ void mbar_wait(uint32_t bar) {
  asm volatile(
      "{\n.reg .pred p;\n.reg .u32 c;\nmov.u32 c, 0;\n"
      "W_%=:\nmbarrier.try_wait.parity.shared::cta.b64 p, [%0], 0;\n@p bra D_%=;\n"
      "add.u32 c, c, 1;\nsetp.lt.u32 p, c, %1;\n@p bra W_%=;\ntrap;\nD_%=:\n}\n" ::"r"(bar), "n"(SPIN_LIMIT) : "memory");
}
__device__ __forceinline__ void tma3(uint32_t dst, const CUtensorMap* m, int c0, int c1, int c2, uint32_t bar) {
  asm volatile("cp.async.bulk.tensor.3d.shared::cluster.global.mbarrier::complete_tx::bytes [%0], [%1, {%3,%4,%5}], [%2];"
               ::"r"(dst), "l"(m), "r"(bar), "r"(c0), "r"(c1), "r"(c2) : "memory");
}
__device__ __forceinline__ void tma4(uint32_t dst, const CUtensorMap* m, int c0, int c1, int c2, int c3, uint32_t bar) {
  asm volatile("cp.async.bulk.tensor.4d.shared::cluster.global.mbarrier::complete_tx::bytes [%0], [%1, {%3,%4,%5,%6}], [%2];"
               ::"r"(dst), "l"(m), "r"(bar), "r"(c0), "r"(c1), "r"(c2), "r"(c3) : "memory");
}
__device__ __forceinline__ void tma5(uint32_t dst, const CUtensorMap* m, int c0, int c1, int c2, int c3, int c4, uint32_t bar) {
  asm volatile("cp.async.bulk.tensor.5d.shared::cluster.global.mbarrier::complete_tx::bytes [%0], [%1, {%3,%4,%5,%6,%7}], [%2];"
               ::"r"(dst), "l"(m), "r"(bar), "r"(c0), "r"(c1), "r"(c2), "r"(c3), "r"(c4) : "memory");
}
__device__ __forceinline__ void bulk_g2s(uint32_t dst, const void* src, int bytes, uint32_t bar) {
  asm volatile("cp.async.bulk.shared::cluster.global.mbarrier::complete_tx::bytes [%0], [%1], %2, [%3];"
               ::"r"(dst), "l"(src), "r"(bytes), "r"(bar) : "memory");
}
__device__ __forceinline__ void bulk_s2g(void* dst, uint32_t src, int bytes) {
  asm volatile("cp.async.bulk.global.shared::cta.bulk_group [%0], [%1], %2;" ::"l"(dst), "r"(src), "r"(bytes) : "memory");
}
__device__ __forceinline__ void l2_prefetch(const void* src, int bytes) {
  asm volatile("cp.async.bulk.prefetch.L2.global [%0], %1;" ::"l"(src), "r"(bytes) : "memory");
}
__device__ __forceinline__ void wgmma_fence() { asm volatile("wgmma.fence.sync.aligned;" ::: "memory"); }
__device__ __forceinline__ void wgmma_commit() { asm volatile("wgmma.commit_group.sync.aligned;" ::: "memory"); }
template <int N> __device__ __forceinline__ void wgmma_wait() { asm volatile("wgmma.wait_group.sync.aligned %0;" ::"n"(N) : "memory"); }
__host__ __device__ constexpr uint32_t desc_lo(uint32_t addr, uint32_t lbo) { return ((addr & 0x3FFFF) >> 4) | ((lbo >> 4) << 16); }
__host__ __device__ constexpr uint32_t desc_hi(uint32_t sbo, uint32_t swz) { return (sbo >> 4) | (swz << 30); }
__device__ __forceinline__ void bar_sync(int id, int n) { asm volatile("bar.sync %0, %1;" ::"r"(id), "r"(n) : "memory"); }
__device__ __forceinline__ uint32_t lds32(uint32_t a) { uint32_t v; asm volatile("ld.shared.u32 %0, [%1];" : "=r"(v) : "r"(a) : "memory"); return v; }
__device__ __forceinline__ float2 lds64f(uint32_t a) { float2 v; asm volatile("ld.shared.v2.f32 {%0,%1}, [%2];" : "=f"(v.x), "=f"(v.y) : "r"(a) : "memory"); return v; }
__device__ __forceinline__ float4 lds128f(uint32_t a) { float4 v; asm volatile("ld.shared.v4.f32 {%0,%1,%2,%3}, [%4];" : "=f"(v.x), "=f"(v.y), "=f"(v.z), "=f"(v.w) : "r"(a) : "memory"); return v; }
__device__ __forceinline__ void ldsm4t(uint32_t (&r)[4], uint32_t a) {
  asm volatile("ldmatrix.sync.aligned.m8n8.x4.trans.shared.b16 {%0,%1,%2,%3}, [%4];" : "=r"(r[0]), "=r"(r[1]), "=r"(r[2]), "=r"(r[3]) : "r"(a) : "memory");
}
__device__ __forceinline__ void sts32(uint32_t a, uint32_t v) { asm volatile("st.shared.u32 [%0], %1;" ::"r"(a), "r"(v) : "memory"); }
__device__ __forceinline__ void sts64f(uint32_t a, float x, float y) { asm volatile("st.shared.v2.f32 [%0], {%1,%2};" ::"r"(a), "f"(x), "f"(y) : "memory"); }
__device__ __forceinline__ void st_rel(unsigned* p, unsigned v) { asm volatile("st.release.gpu.global.u32 [%0], %1;" ::"l"(p), "r"(v) : "memory"); }
__device__ __forceinline__ void red_rel(unsigned* p, unsigned v) { asm volatile("red.release.gpu.global.add.u32 [%0], %1;" ::"l"(p), "r"(v) : "memory"); }
__device__ __forceinline__ void fence_async_global() { asm volatile("fence.proxy.async.global;" ::: "memory"); }
__device__ __forceinline__ void fence_async_smem() { asm volatile("fence.proxy.async.shared::cta;" ::: "memory"); }
__device__ __forceinline__ void rec_st(uint4* p, float a, float b, unsigned tag) {
  asm volatile("{\n.reg .b128 t;\n.reg .b64 lo, hi;\nmov.b64 lo, {%1,%2};\nmov.b64 hi, {%3,%3};\nmov.b128 t, {lo,hi};\n"
               "st.relaxed.gpu.global.b128 [%0], t;\n}\n" ::"l"(p), "r"(__float_as_uint(a)), "r"(__float_as_uint(b)), "r"(tag) : "memory");
}
__device__ __forceinline__ unsigned rec_ld(const uint4* p, float& a, float& b) {
  unsigned x, y, t;
  asm volatile("{\n.reg .b128 t;\n.reg .b64 lo, hi;\n.reg .b32 u;\nld.relaxed.gpu.global.b128 t, [%3];\nmov.b128 {lo,hi}, t;\n"
               "mov.b64 {%0,%1}, lo;\nmov.b64 {%2,u}, hi;\n}\n" : "=r"(x), "=r"(y), "=r"(t) : "l"(p) : "memory");
  a = __uint_as_float(x); b = __uint_as_float(y);
  return t;
}
__device__ __forceinline__ void rec_poll(const uint4* p, unsigned tag, float& a, float& b) {
  uint32_t it = 0;
  while (rec_ld(p, a, b) != tag) { if (++it > SPIN_LIMIT) __trap(); }
}
__device__ __forceinline__ unsigned ld_rlx(const unsigned* p) { unsigned v; asm volatile("ld.relaxed.gpu.global.u32 %0, [%1];" : "=r"(v) : "l"(p) : "memory"); return v; }
__device__ __forceinline__ void flag_poll(const unsigned* p, unsigned target) {
  uint32_t it = 0;
  while ((int)(ld_rlx(p) - target) < 0) { if (++it > SPIN_LIMIT) __trap(); }
  asm volatile("fence.acquire.gpu;" ::: "memory");
}
__device__ __forceinline__ uint32_t pack_bf16(float lo, float hi) {
  uint32_t r; asm("cvt.rn.bf16x2.f32 %0, %1, %2;" : "=r"(r) : "f"(hi), "f"(lo)); return r;
}
__device__ __forceinline__ float bf_lo(uint32_t w) { return __uint_as_float(w << 16); }
__device__ __forceinline__ float bf_hi(uint32_t w) { return __uint_as_float(w & 0xffff0000u); }
__device__ __forceinline__ uint32_t hmul2(uint32_t a, uint32_t b) {
  __nv_bfloat162 r = __hmul2_rn(*(__nv_bfloat162*)&a, *(__nv_bfloat162*)&b); return *(uint32_t*)&r;
}
__device__ __forceinline__ uint32_t hadd2(uint32_t a, uint32_t b) {
  __nv_bfloat162 r = __hadd2_rn(*(__nv_bfloat162*)&a, *(__nv_bfloat162*)&b); return *(uint32_t*)&r;
}
__device__ __forceinline__ float2 cmul(float2 a, float2 b) { return make_float2(a.x * b.x - a.y * b.y, a.x * b.y + a.y * b.x); }
__device__ __forceinline__ float2 cfma(float2 a, float2 b, float2 c) {
  return make_float2(fmaf(a.x, b.x, fmaf(-a.y, b.y, c.x)), fmaf(a.x, b.y, fmaf(a.y, b.x, c.y)));
}
template <int N> __device__ __forceinline__ void fence_regs(float (&a)[N]) {
#pragma unroll
  for (int i = 0; i < N; i++) asm volatile("" : "+f"(a[i])::"memory");
}
__device__ __forceinline__ bool elect_one() {
  uint32_t e; asm volatile("{\n.reg .pred P;\nelect.sync _|P, 0xffffffff;\nselp.u32 %0, 1, 0, P;\n}\n" : "=r"(e)); return e != 0;
}
__device__ __forceinline__ int tid_opaque() { int t; asm volatile("mov.u32 %0, %%tid.x;" : "=r"(t)); return t; }
struct Role { int T1, GP, side, m2, dg, cch0; bool last, has2; };
__device__ __forceinline__ Role unpack_role(int x) {
  Role r; r.T1 = x & 15; r.GP = (x >> 4) & 7; r.side = (x >> 7) & 1; r.m2 = (x >> 8) & 63; r.dg = (x >> 14) & 3;
  r.has2 = (x >> 16) & 1; r.last = r.T1 == NT1 - 1; r.cch0 = 5 * (32 * r.dg + r.m2); return r;
}
__device__ __forceinline__ Role fresh_role(int x) { asm volatile("" : "+r"(x)); return unpack_role(__shfl_sync(0xffffffffu, x, 0)); }
#define ROLE(x) const Role R_ = fresh_role(x); const int T1 = R_.T1, GP = R_.GP, side = R_.side, m2 = R_.m2, dg = R_.dg, cch0 = R_.cch0; \
  const bool last = R_.last, has2 = R_.has2; (void)T1; (void)GP; (void)side; (void)m2; (void)dg; (void)cch0; (void)last; (void)has2;
__device__ __forceinline__ int n_to_t(int n) {
  int T = n / 160, nl = n - T * 160;
  int L = (T == NT1 - 1) ? 32 : 40;
  return T * 160 + L * ((nl & 7) >> 1) + 2 * (nl >> 3) + (nl & 1);
}

template<int TA> __device__ __forceinline__ void wgmma_n160(float (&d)[80], uint32_t alo, uint32_t ahi, uint32_t blo, uint32_t bhi){
  asm volatile("{\n.reg .b64 da, db;\nmov.b64 da, {%80,%81};\nmov.b64 db, {%82,%83};\n"
    "wgmma.mma_async.sync.aligned.m64n160k16.f32.bf16.bf16 {%0, %1, %2, %3, %4, %5, %6, %7, %8, %9, %10, %11, %12, %13, %14, %15, %16, %17, %18, %19, %20, %21, %22, %23, %24, %25, %26, %27, %28, %29, %30, %31, %32, %33, %34, %35, %36, %37, %38, %39, %40, %41, %42, %43, %44, %45, %46, %47, %48, %49, %50, %51, %52, %53, %54, %55, %56, %57, %58, %59, %60, %61, %62, %63, %64, %65, %66, %67, %68, %69, %70, %71, %72, %73, %74, %75, %76, %77, %78, %79}, da, db, 1, 1, 1, %84, 0;\n}\n"
    : "+f"(d[0]), "+f"(d[1]), "+f"(d[2]), "+f"(d[3]), "+f"(d[4]), "+f"(d[5]), "+f"(d[6]), "+f"(d[7]), "+f"(d[8]), "+f"(d[9]), "+f"(d[10]), "+f"(d[11]), "+f"(d[12]), "+f"(d[13]), "+f"(d[14]), "+f"(d[15]), "+f"(d[16]), "+f"(d[17]), "+f"(d[18]), "+f"(d[19]), "+f"(d[20]), "+f"(d[21]), "+f"(d[22]), "+f"(d[23]), "+f"(d[24]), "+f"(d[25]), "+f"(d[26]), "+f"(d[27]), "+f"(d[28]), "+f"(d[29]), "+f"(d[30]), "+f"(d[31]), "+f"(d[32]), "+f"(d[33]), "+f"(d[34]), "+f"(d[35]), "+f"(d[36]), "+f"(d[37]), "+f"(d[38]), "+f"(d[39]), "+f"(d[40]), "+f"(d[41]), "+f"(d[42]), "+f"(d[43]), "+f"(d[44]), "+f"(d[45]), "+f"(d[46]), "+f"(d[47]), "+f"(d[48]), "+f"(d[49]), "+f"(d[50]), "+f"(d[51]), "+f"(d[52]), "+f"(d[53]), "+f"(d[54]), "+f"(d[55]), "+f"(d[56]), "+f"(d[57]), "+f"(d[58]), "+f"(d[59]), "+f"(d[60]), "+f"(d[61]), "+f"(d[62]), "+f"(d[63]), "+f"(d[64]), "+f"(d[65]), "+f"(d[66]), "+f"(d[67]), "+f"(d[68]), "+f"(d[69]), "+f"(d[70]), "+f"(d[71]), "+f"(d[72]), "+f"(d[73]), "+f"(d[74]), "+f"(d[75]), "+f"(d[76]), "+f"(d[77]), "+f"(d[78]), "+f"(d[79])
    : "r"(alo), "r"(ahi), "r"(blo), "r"(bhi), "n"(TA));
}
template<int N> __device__ __forceinline__ void wgmma_rs_hi(float (&d)[64], uint32_t a0, uint32_t a1, uint32_t a2, uint32_t a3, uint32_t blo);
template<> __device__ __forceinline__ void wgmma_rs_hi<16>(float (&d)[64], uint32_t a0, uint32_t a1, uint32_t a2, uint32_t a3, uint32_t blo){
  asm volatile("{\n.reg .b64 db;\nmov.b64 db, {%12,8};\nwgmma.mma_async.sync.aligned.m64n16k16.f32.bf16.bf16 {%0, %1, %2, %3, %4, %5, %6, %7}, {%8,%9,%10,%11}, db, 1, 1, 1, 0;\n}\n"
    : "+f"(d[56]), "+f"(d[57]), "+f"(d[58]), "+f"(d[59]), "+f"(d[60]), "+f"(d[61]), "+f"(d[62]), "+f"(d[63])
    : "r"(a0), "r"(a1), "r"(a2), "r"(a3), "r"(blo));
}
template<> __device__ __forceinline__ void wgmma_rs_hi<32>(float (&d)[64], uint32_t a0, uint32_t a1, uint32_t a2, uint32_t a3, uint32_t blo){
  asm volatile("{\n.reg .b64 db;\nmov.b64 db, {%20,8};\nwgmma.mma_async.sync.aligned.m64n32k16.f32.bf16.bf16 {%0, %1, %2, %3, %4, %5, %6, %7, %8, %9, %10, %11, %12, %13, %14, %15}, {%16,%17,%18,%19}, db, 1, 1, 1, 0;\n}\n"
    : "+f"(d[48]), "+f"(d[49]), "+f"(d[50]), "+f"(d[51]), "+f"(d[52]), "+f"(d[53]), "+f"(d[54]), "+f"(d[55]), "+f"(d[56]), "+f"(d[57]), "+f"(d[58]), "+f"(d[59]), "+f"(d[60]), "+f"(d[61]), "+f"(d[62]), "+f"(d[63])
    : "r"(a0), "r"(a1), "r"(a2), "r"(a3), "r"(blo));
}
template<> __device__ __forceinline__ void wgmma_rs_hi<48>(float (&d)[64], uint32_t a0, uint32_t a1, uint32_t a2, uint32_t a3, uint32_t blo){
  asm volatile("{\n.reg .b64 db;\nmov.b64 db, {%28,8};\nwgmma.mma_async.sync.aligned.m64n48k16.f32.bf16.bf16 {%0, %1, %2, %3, %4, %5, %6, %7, %8, %9, %10, %11, %12, %13, %14, %15, %16, %17, %18, %19, %20, %21, %22, %23}, {%24,%25,%26,%27}, db, 1, 1, 1, 0;\n}\n"
    : "+f"(d[40]), "+f"(d[41]), "+f"(d[42]), "+f"(d[43]), "+f"(d[44]), "+f"(d[45]), "+f"(d[46]), "+f"(d[47]), "+f"(d[48]), "+f"(d[49]), "+f"(d[50]), "+f"(d[51]), "+f"(d[52]), "+f"(d[53]), "+f"(d[54]), "+f"(d[55]), "+f"(d[56]), "+f"(d[57]), "+f"(d[58]), "+f"(d[59]), "+f"(d[60]), "+f"(d[61]), "+f"(d[62]), "+f"(d[63])
    : "r"(a0), "r"(a1), "r"(a2), "r"(a3), "r"(blo));
}
template<> __device__ __forceinline__ void wgmma_rs_hi<64>(float (&d)[64], uint32_t a0, uint32_t a1, uint32_t a2, uint32_t a3, uint32_t blo){
  asm volatile("{\n.reg .b64 db;\nmov.b64 db, {%36,8};\nwgmma.mma_async.sync.aligned.m64n64k16.f32.bf16.bf16 {%0, %1, %2, %3, %4, %5, %6, %7, %8, %9, %10, %11, %12, %13, %14, %15, %16, %17, %18, %19, %20, %21, %22, %23, %24, %25, %26, %27, %28, %29, %30, %31}, {%32,%33,%34,%35}, db, 1, 1, 1, 0;\n}\n"
    : "+f"(d[32]), "+f"(d[33]), "+f"(d[34]), "+f"(d[35]), "+f"(d[36]), "+f"(d[37]), "+f"(d[38]), "+f"(d[39]), "+f"(d[40]), "+f"(d[41]), "+f"(d[42]), "+f"(d[43]), "+f"(d[44]), "+f"(d[45]), "+f"(d[46]), "+f"(d[47]), "+f"(d[48]), "+f"(d[49]), "+f"(d[50]), "+f"(d[51]), "+f"(d[52]), "+f"(d[53]), "+f"(d[54]), "+f"(d[55]), "+f"(d[56]), "+f"(d[57]), "+f"(d[58]), "+f"(d[59]), "+f"(d[60]), "+f"(d[61]), "+f"(d[62]), "+f"(d[63])
    : "r"(a0), "r"(a1), "r"(a2), "r"(a3), "r"(blo));
}
template<> __device__ __forceinline__ void wgmma_rs_hi<80>(float (&d)[64], uint32_t a0, uint32_t a1, uint32_t a2, uint32_t a3, uint32_t blo){
  asm volatile("{\n.reg .b64 db;\nmov.b64 db, {%44,8};\nwgmma.mma_async.sync.aligned.m64n80k16.f32.bf16.bf16 {%0, %1, %2, %3, %4, %5, %6, %7, %8, %9, %10, %11, %12, %13, %14, %15, %16, %17, %18, %19, %20, %21, %22, %23, %24, %25, %26, %27, %28, %29, %30, %31, %32, %33, %34, %35, %36, %37, %38, %39}, {%40,%41,%42,%43}, db, 1, 1, 1, 0;\n}\n"
    : "+f"(d[24]), "+f"(d[25]), "+f"(d[26]), "+f"(d[27]), "+f"(d[28]), "+f"(d[29]), "+f"(d[30]), "+f"(d[31]), "+f"(d[32]), "+f"(d[33]), "+f"(d[34]), "+f"(d[35]), "+f"(d[36]), "+f"(d[37]), "+f"(d[38]), "+f"(d[39]), "+f"(d[40]), "+f"(d[41]), "+f"(d[42]), "+f"(d[43]), "+f"(d[44]), "+f"(d[45]), "+f"(d[46]), "+f"(d[47]), "+f"(d[48]), "+f"(d[49]), "+f"(d[50]), "+f"(d[51]), "+f"(d[52]), "+f"(d[53]), "+f"(d[54]), "+f"(d[55]), "+f"(d[56]), "+f"(d[57]), "+f"(d[58]), "+f"(d[59]), "+f"(d[60]), "+f"(d[61]), "+f"(d[62]), "+f"(d[63])
    : "r"(a0), "r"(a1), "r"(a2), "r"(a3), "r"(blo));
}
template<> __device__ __forceinline__ void wgmma_rs_hi<96>(float (&d)[64], uint32_t a0, uint32_t a1, uint32_t a2, uint32_t a3, uint32_t blo){
  asm volatile("{\n.reg .b64 db;\nmov.b64 db, {%52,8};\nwgmma.mma_async.sync.aligned.m64n96k16.f32.bf16.bf16 {%0, %1, %2, %3, %4, %5, %6, %7, %8, %9, %10, %11, %12, %13, %14, %15, %16, %17, %18, %19, %20, %21, %22, %23, %24, %25, %26, %27, %28, %29, %30, %31, %32, %33, %34, %35, %36, %37, %38, %39, %40, %41, %42, %43, %44, %45, %46, %47}, {%48,%49,%50,%51}, db, 1, 1, 1, 0;\n}\n"
    : "+f"(d[16]), "+f"(d[17]), "+f"(d[18]), "+f"(d[19]), "+f"(d[20]), "+f"(d[21]), "+f"(d[22]), "+f"(d[23]), "+f"(d[24]), "+f"(d[25]), "+f"(d[26]), "+f"(d[27]), "+f"(d[28]), "+f"(d[29]), "+f"(d[30]), "+f"(d[31]), "+f"(d[32]), "+f"(d[33]), "+f"(d[34]), "+f"(d[35]), "+f"(d[36]), "+f"(d[37]), "+f"(d[38]), "+f"(d[39]), "+f"(d[40]), "+f"(d[41]), "+f"(d[42]), "+f"(d[43]), "+f"(d[44]), "+f"(d[45]), "+f"(d[46]), "+f"(d[47]), "+f"(d[48]), "+f"(d[49]), "+f"(d[50]), "+f"(d[51]), "+f"(d[52]), "+f"(d[53]), "+f"(d[54]), "+f"(d[55]), "+f"(d[56]), "+f"(d[57]), "+f"(d[58]), "+f"(d[59]), "+f"(d[60]), "+f"(d[61]), "+f"(d[62]), "+f"(d[63])
    : "r"(a0), "r"(a1), "r"(a2), "r"(a3), "r"(blo));
}
template<> __device__ __forceinline__ void wgmma_rs_hi<112>(float (&d)[64], uint32_t a0, uint32_t a1, uint32_t a2, uint32_t a3, uint32_t blo){
  asm volatile("{\n.reg .b64 db;\nmov.b64 db, {%60,8};\nwgmma.mma_async.sync.aligned.m64n112k16.f32.bf16.bf16 {%0, %1, %2, %3, %4, %5, %6, %7, %8, %9, %10, %11, %12, %13, %14, %15, %16, %17, %18, %19, %20, %21, %22, %23, %24, %25, %26, %27, %28, %29, %30, %31, %32, %33, %34, %35, %36, %37, %38, %39, %40, %41, %42, %43, %44, %45, %46, %47, %48, %49, %50, %51, %52, %53, %54, %55}, {%56,%57,%58,%59}, db, 1, 1, 1, 0;\n}\n"
    : "+f"(d[8]), "+f"(d[9]), "+f"(d[10]), "+f"(d[11]), "+f"(d[12]), "+f"(d[13]), "+f"(d[14]), "+f"(d[15]), "+f"(d[16]), "+f"(d[17]), "+f"(d[18]), "+f"(d[19]), "+f"(d[20]), "+f"(d[21]), "+f"(d[22]), "+f"(d[23]), "+f"(d[24]), "+f"(d[25]), "+f"(d[26]), "+f"(d[27]), "+f"(d[28]), "+f"(d[29]), "+f"(d[30]), "+f"(d[31]), "+f"(d[32]), "+f"(d[33]), "+f"(d[34]), "+f"(d[35]), "+f"(d[36]), "+f"(d[37]), "+f"(d[38]), "+f"(d[39]), "+f"(d[40]), "+f"(d[41]), "+f"(d[42]), "+f"(d[43]), "+f"(d[44]), "+f"(d[45]), "+f"(d[46]), "+f"(d[47]), "+f"(d[48]), "+f"(d[49]), "+f"(d[50]), "+f"(d[51]), "+f"(d[52]), "+f"(d[53]), "+f"(d[54]), "+f"(d[55]), "+f"(d[56]), "+f"(d[57]), "+f"(d[58]), "+f"(d[59]), "+f"(d[60]), "+f"(d[61]), "+f"(d[62]), "+f"(d[63])
    : "r"(a0), "r"(a1), "r"(a2), "r"(a3), "r"(blo));
}
template<> __device__ __forceinline__ void wgmma_rs_hi<128>(float (&d)[64], uint32_t a0, uint32_t a1, uint32_t a2, uint32_t a3, uint32_t blo){
  asm volatile("{\n.reg .b64 db;\nmov.b64 db, {%68,8};\nwgmma.mma_async.sync.aligned.m64n128k16.f32.bf16.bf16 {%0, %1, %2, %3, %4, %5, %6, %7, %8, %9, %10, %11, %12, %13, %14, %15, %16, %17, %18, %19, %20, %21, %22, %23, %24, %25, %26, %27, %28, %29, %30, %31, %32, %33, %34, %35, %36, %37, %38, %39, %40, %41, %42, %43, %44, %45, %46, %47, %48, %49, %50, %51, %52, %53, %54, %55, %56, %57, %58, %59, %60, %61, %62, %63}, {%64,%65,%66,%67}, db, 1, 1, 1, 0;\n}\n"
    : "+f"(d[0]), "+f"(d[1]), "+f"(d[2]), "+f"(d[3]), "+f"(d[4]), "+f"(d[5]), "+f"(d[6]), "+f"(d[7]), "+f"(d[8]), "+f"(d[9]), "+f"(d[10]), "+f"(d[11]), "+f"(d[12]), "+f"(d[13]), "+f"(d[14]), "+f"(d[15]), "+f"(d[16]), "+f"(d[17]), "+f"(d[18]), "+f"(d[19]), "+f"(d[20]), "+f"(d[21]), "+f"(d[22]), "+f"(d[23]), "+f"(d[24]), "+f"(d[25]), "+f"(d[26]), "+f"(d[27]), "+f"(d[28]), "+f"(d[29]), "+f"(d[30]), "+f"(d[31]), "+f"(d[32]), "+f"(d[33]), "+f"(d[34]), "+f"(d[35]), "+f"(d[36]), "+f"(d[37]), "+f"(d[38]), "+f"(d[39]), "+f"(d[40]), "+f"(d[41]), "+f"(d[42]), "+f"(d[43]), "+f"(d[44]), "+f"(d[45]), "+f"(d[46]), "+f"(d[47]), "+f"(d[48]), "+f"(d[49]), "+f"(d[50]), "+f"(d[51]), "+f"(d[52]), "+f"(d[53]), "+f"(d[54]), "+f"(d[55]), "+f"(d[56]), "+f"(d[57]), "+f"(d[58]), "+f"(d[59]), "+f"(d[60]), "+f"(d[61]), "+f"(d[62]), "+f"(d[63])
    : "r"(a0), "r"(a1), "r"(a2), "r"(a3), "r"(blo));
}

__device__ __forceinline__ void cv_copy(float (&acc)[64]) {
#pragma unroll
  for (int i = 0; i < 64; i++) { float t; asm volatile("mov.b32 %0, %1;" : "=f"(t) : "f"(acc[i]) : "memory"); acc[i] = t; }
}
template <int D0> __device__ __forceinline__ void cv_loadA(uint32_t (&A)[4][4], uint32_t kaddr) {
#pragma unroll
  for (int i = 0; i < 4; i++) {
    uint32_t a = kaddr + (D0 + i) * 128;
    uint32_t w0 = lds32(a), w1 = lds32(a + 4), w2 = lds32(a + 8);
    A[i][0] = __byte_perm(w0, w1, 0x5432); A[i][1] = w1; A[i][2] = __byte_perm(w1, w2, 0x5432); A[i][3] = w2;
  }
#pragma unroll
  for (int i = 0; i < 4; i++) asm volatile("" : "+r"(A[i][0]), "+r"(A[i][1]), "+r"(A[i][2]), "+r"(A[i][3])::"memory");
}
template <int G> __device__ __forceinline__ void cv_rec(float (&acc)[64], const uint32_t (&A)[4][4], uint32_t kaddr, uint32_t db0) {
  wgmma_fence();
#pragma unroll
  for (int i = 0; i < 4; i++) wgmma_rs_hi<128 - 16 * G>(acc, A[i][0], A[i][1], A[i][2], A[i][3], db0 - 4 * i);
  wgmma_commit();
  if constexpr (G < 7) {
    uint32_t B[4][4];
    cv_loadA<4 * (G + 1)>(B, kaddr);
    wgmma_wait<0>(); cv_copy(acc);
    cv_rec<G + 1>(acc, B, kaddr, db0);
  } else { wgmma_wait<0>(); cv_copy(acc); }
}
__device__ __forceinline__ void conv_channel(const Params& p, int slot, int ch, int barid) {
  int tid = tid_opaque() & 127, w = tid >> 5, lane = tid & 31, r = lane >> 2, q = lane & 3;
  int i_ = r >> 1, i0 = i_ & 1, i1 = i_ >> 1;
  int bl = 4 * (r & 1) + 2 * (w & 1) + 8 * (w >> 1);
  const uint32_t cb = sb + CV_OFF + slot * CV_B;
  uint32_t dd = (uint32_t)__bfloat16_as_ushort(p.ssmD[ch]); dd |= dd << 16;
  mbar_wait(sb + BAR_OFF + 8 * (B_CVFULL + slot));
  const uint32_t kaddr = cb + CV_K - 32 + 4 * (8 * i_ + (bl >> 1) + 2 * q);
  const uint32_t db0 = desc_lo(cb + CV_U + 192, CV_PL);
  float acc[64];
#pragma unroll
  for (int i = 0; i < 64; i++) acc[i] = 0.f;
  uint32_t A[4][4];
  cv_loadA<0>(A, kaddr);
  cv_copy(acc);
  cv_rec<0>(acc, A, kaddr, db0);
  float E[8][4];
  const int src1 = i1 == 0 ? (lane - q + 16 + ((q + 3) & 3)) : (lane - q - 16 + ((q + 1) & 3));
  const bool s3 = (i1 == 1 && q == 3), kodd = (i1 == 1 && q < 3);
#pragma unroll
  for (int J = 0; J < 8; J++)
#pragma unroll
    for (int x = 0; x < 4; x++) {
      float ev = acc[8 * J + x], od = acc[8 * J + 4 + x], pv = J > 0 ? acc[8 * J - 4 + x] : 0.f;
      float send = kodd ? ev : (s3 ? pv : od);
      float keep = kodd ? od : ev;
      E[J][x] = keep + __shfl_sync(0xffffffffu, send, src1);
    }
  const int P = i1 == 0 ? q : 4 + ((q + 1) & 3);
  const int Pm = (P + 7) & 7, qm = Pm < 4 ? Pm : ((Pm - 1) & 3), i1m = Pm >> 2;
  const int src2 = i0 == 1 ? lane - 8 : (16 * i1m + 8 + 4 * (r & 1) + qm);
  const bool wrap = (i0 == 1 && P == 7);
  const uint32_t kvaddr = cb + CV_U + 192 + (((14 - bl) >> 1) & 1) * CV_PL + (2 * P + i0) * 16 + ((14 - bl) >> 2) * 4;
  uint32_t gw[8];
#pragma unroll
  for (int J = 0; J < 8; J++) {
    float o[2];
#pragma unroll
    for (int h = 0; h < 2; h++) {
      float pv = J > 0 ? E[J - 1][2 * h + 1] : 0.f;
      float send = wrap ? pv : E[J][2 * h + 1];
      o[h] = E[J][2 * h] + __shfl_sync(0xffffffffu, send, src2);
    }
    uint32_t kvw = lds32(kvaddr + J * 256);
    kvw = __byte_perm(kvw, kvw, 0x1032);
    gw[J] = hadd2(pack_bf16(o[0], o[1]), hmul2(kvw, dd));
  }
  bar_sync(barid, 128);
  int tb = 16 * (2 * P + i0) + bl;
  asm volatile("" : "+r"(tb));
#pragma unroll
  for (int J = 0; J < 8; J++) {
    int t = 256 * J + tb;
    int T = t / 160, tl = t - T * 160;
    int qq = (T == NT1 - 1) ? (tl >> 5) : (tl / 40);
    int j = (tl - qq * ((T == NT1 - 1) ? 32 : 40)) >> 1;
    int c = 20 * T + j;
    c = c ^ ((c >> 3) & 7);
    sts32(cb + CV_K + c * 16 + qq * 4, gw[J]);
  }
  fence_async_smem();
  mbar_arrive(sb + BAR_OFF + 8 * (B_CVDONE + slot));
}

template <int W> struct KvRegs { uint32_t k[19][W], v[16][W], s[W][4]; };
template <int W> __device__ __forceinline__ void kv_taps(const Params& p, int c0, KvRegs<W>& x) {
  const int ch = c0 + 2 * W * (tid_opaque() & 7);
#pragma unroll
  for (int c = 0; c < W; c++) { uint4 t = __ldg((const uint4*)(p.shiftk + ch * 4) + c); x.s[c][0] = t.x; x.s[c][1] = t.y; x.s[c][2] = t.z; x.s[c][3] = t.w; }
}
template <int W> __device__ __forceinline__ void kv_load(int m, int cl, KvRegs<W>& x) {
  const int lane = tid_opaque() & 31, tg = lane >> 3;
  const uint32_t co = 2 * cl + 4 * W * (lane & 7);
  const uint32_t ka = sb + KS_OFF + tg * 6080 + co, va = sb + VS_OFF + tg * 5440 + 320 + co;
  const uint32_t kh = (m == 0 && tg > 0) ? ka - 960 : ka;
  mbar_wait(bars + 8 * B_KV);
#pragma unroll
  for (int i = 0; i < 19; i++) {
    const uint32_t a = (i < 3 ? kh : ka) + i * 320;
    if (W == 2) { float2 t = lds64f(a); x.k[i][0] = __float_as_uint(t.x); x.k[i][W - 1] = __float_as_uint(t.y); }
    else x.k[i][0] = lds32(a);
  }
#pragma unroll
  for (int i = 0; i < 16; i++) {
    if (W == 2) { float2 t = lds64f(va + i * 320); x.v[i][0] = __float_as_uint(t.x); x.v[i][W - 1] = __float_as_uint(t.y); }
    else x.v[i][0] = lds32(va + i * 320);
  }
}
template <int W> __device__ __forceinline__ void kv_finish(int m, int c0, KvRegs<W>& x) {
  const int lane = tid_opaque() & 31;
  uint8_t* dst = g_kv + ((c0 + 2 * W * (lane & 7)) * 4096 + (4 * m + (lane >> 3)) * 16);
#pragma unroll
  for (int c = 0; c < W; c++) {
    const uint32_t w0 = __byte_perm(x.s[c][0], x.s[c][2], 0x5410), w1 = __byte_perm(x.s[c][0], x.s[c][2], 0x7632);
    const uint32_t w2 = __byte_perm(x.s[c][1], x.s[c][3], 0x5410), w3 = __byte_perm(x.s[c][1], x.s[c][3], 0x7632);
#pragma unroll
    for (int i = 0; i < 16; i++) {
      uint32_t a = hmul2(x.k[i][c], w3);
      a = hadd2(a, hmul2(x.k[i + 1][c], w2)); a = hadd2(a, hmul2(x.k[i + 2][c], w1)); a = hadd2(a, hmul2(x.k[i + 3][c], w0));
      x.v[i][c] = hmul2(a, x.v[i][c]);
    }
#pragma unroll
    for (int e = 0; e < 2; e++)
#pragma unroll
      for (int f = 0; f < 2; f++) {
        uint32_t o[4];
#pragma unroll
        for (int qq = 0; qq < 4; qq++) o[qq] = __byte_perm(x.v[15 - 4 * qq - 2 * f][c], x.v[14 - 4 * qq - 2 * f][c], e ? 0x7632 : 0x5410);
        *(uint4*)(dst + (2 * c + e) * 4096 + f * 2048) = make_uint4(o[0], o[1], o[2], o[3]);
      }
  }
}
__device__ __forceinline__ void stat_table(int T1, unsigned want, int l) {
#pragma unroll 1
  for (int n = tid_opaque() & 127; n < (T1 == NT1 - 1 ? 128 : 160); n += 128) {
    const uint4* rp = &g_stats[(160 * T1 + n) * 8];
    float a[4], b[4];
    uint32_t it = 0;
    while (true) {
      bool ok = true;
#pragma unroll
      for (int i = 0; i < 4; i++) ok &= (rec_ld(rp + 2 * i, a[i], b[i]) == want);
      if (ok) break;
      if (++it > SPIN_LIMIT) __trap();
    }
    const float m = 0.25f * ((a[0] + a[1]) + (a[2] + a[3]));
    float v = (b[0] + b[1]) + (b[2] + b[3]);
#pragma unroll
    for (int i = 0; i < 4; i++) v = fmaf(160.f * (a[i] - m), a[i] - m, v);
    const float rs = rsqrtf(v * (1.f / 640.f) + 1e-5f);
    sts64f(sb + STAB_OFF + n * 8, rs, -m * rs);
  }
  mbar_arrive(bars + 8 * (B_STAB + l));
}

template <bool FIRST>
__device__ __forceinline__ void stats_publish(int which, int n0, int dg, unsigned tag, const float (&acc)[80]) {
  const int lane = tid_opaque() & 31, q = lane & 3;
  float sh[2] = {0.f, 0.f};
  if (FIRST) { sh[0] = __shfl_sync(0xffffffffu, acc[0], lane & ~3); sh[1] = __shfl_sync(0xffffffffu, acc[2], lane & ~3); }
  float s1[2] = {0.f, 0.f}, s2[2] = {0.f, 0.f}, t1[2] = {0.f, 0.f}, t2[2] = {0.f, 0.f};
#pragma unroll
  for (int j = 0; j < 20; j++)
#pragma unroll
    for (int h = 0; h < 2; h++) {
      float a = acc[4 * j + 2 * h], b = acc[4 * j + 2 * h + 1];
      if (FIRST) { a -= sh[h]; b -= sh[h]; }
      s1[h] += a; t1[h] += b; s2[h] = fmaf(a, a, s2[h]); t2[h] = fmaf(b, b, t2[h]);
    }
#pragma unroll
  for (int h = 0; h < 2; h++) {
    s1[h] += t1[h]; s2[h] += t2[h];
    s1[h] += __shfl_xor_sync(0xffffffffu, s1[h], 1); s2[h] += __shfl_xor_sync(0xffffffffu, s2[h], 1);
    s1[h] += __shfl_xor_sync(0xffffffffu, s1[h], 2); s2[h] += __shfl_xor_sync(0xffffffffu, s2[h], 2);
  }
  if (FIRST || (q & 1) == (which & 1)) {
    const int h = q >> 1;
    float a = h ? s1[1] : s1[0], b = h ? s2[1] : s2[0], c = h ? sh[1] : sh[0];
    float mean = a * (1.f / 160.f);
    rec_st(&g_stats[((n0 + 8 * h) * 4 + dg) * 2 + (q & 1)], mean + c, fmaxf(b - a * mean, 0.f), 4 * tag + which);
  }
}
__device__ __forceinline__ void stats_combine(float mi, float m2, float& mean, float& rstd) {
  float m = mi + __shfl_xor_sync(0xffffffffu, mi, 1);
  m += __shfl_xor_sync(0xffffffffu, m, 2);
  m *= 0.25f;
  float d = mi - m;
  float v = fmaf(160.f * d, d, m2);
  v += __shfl_xor_sync(0xffffffffu, v, 1);
  v += __shfl_xor_sync(0xffffffffu, v, 2);
  mean = m; rstd = rsqrtf(v * (1.f / 640.f) + 1e-5f);
}
__device__ __forceinline__ void stats_get(int which, int n0, unsigned tag, float (&mean)[2], float (&rstd)[2]) {
  const int q = tid_opaque() & 3;
  const uint4* p0 = &g_stats[(n0 * 4 + q) * 2 + (which & 1)];
  float a0, b0, a1, b1;
  uint32_t it = 0;
  tag = 4 * tag + which;
  while (true) {
    unsigned t0 = rec_ld(p0, a0, b0), t1 = rec_ld(p0 + 64, a1, b1);
    if (t0 == tag && t1 == tag) break;
    if (++it > SPIN_LIMIT) __trap();
  }
  __syncwarp();
  stats_combine(a0, b0, mean[0], rstd[0]);
  stats_combine(a1, b1, mean[1], rstd[1]);
}
__device__ __forceinline__ void x0_load(float (&acc)[80]) {
  const int t = tid_opaque() & 127;
  const uint32_t xa = sb + XT_OFF + (16 * (t >> 5) + ((t & 31) >> 2)) * 320 + 8 * (t & 3);
  mbar_wait(bars + 8 * B_XT);
#pragma unroll
  for (int h = 0; h < 2; h++)
#pragma unroll
    for (int J = 0; J < 10; J++) {
      const float2 v = lds64f(xa + h * 2560 + 32 * J);
      const uint32_t x = __float_as_uint(v.x), y = __float_as_uint(v.y);
      acc[8 * J + 2 * h] = bf_lo(x); acc[8 * J + 2 * h + 1] = bf_hi(x);
      acc[8 * J + 4 + 2 * h] = bf_lo(y); acc[8 * J + 4 + 2 * h + 1] = bf_hi(y);
    }
}

__global__ void __launch_bounds__(512, 1) fused_kernel(const __grid_constant__ Params p) {
  extern __shared__ __align__(1024) uint8_t smem_raw[];
  const int tid = threadIdx.x, lane = tid & 31;
  const int wid = __shfl_sync(0xffffffffu, tid >> 5, 0), wg = wid >> 2;
  unsigned smid; asm volatile("mov.u32 %0, %%smid;" : "=r"(smid));
  if (smid >= 132 || smem_u32(smem_raw) != sb) __trap();
  int role;
  {
  const int side = smid & 1;
  int gpc, gi;
  {
    int tpc = smid >> 1;
    if (tpc < 32) { gpc = tpc & 7; gi = tpc >> 3; }
    else if (tpc < 60) { gpc = 1 + (tpc - 32) % 7; gi = 4 + (tpc - 32) / 7; }
    else if (tpc < 62) { gpc = tpc - 54; gi = 8; }
    else { gpc = 0; gi = tpc - 58; }
  }
  const int pos = 8 * gpc + gi + (gpc == 7 ? 1 : 0);
  if (pos == 65) {
    if (tid < 32) {
      const unsigned tag = ld_rlx(g_epoch);
      for (int i = lane; i < NT1 * 16; i += 32)
        if ((i & 15) < 10) { uint32_t it = 0; while ((int)(ld_rlx(&g_hflag[(i >> 4) * 32 + (i & 15)]) - tag) < 0) { __nanosleep(500); if (++it > SPIN_LIMIT) __trap(); } }
    }
    return;
  }
  int T1, GP;
  if (pos < 52) { int hh = pos / 26, x = pos - 26 * hh; T1 = x >> 1; GP = 2 * hh + (x & 1); }
  else { T1 = pos - 52; GP = 4; }
  const bool last = (T1 == NT1 - 1);
  const bool has2 = gi < 8;
  const int m2 = 8 * (gpc >> 1) + gi, dg = 2 * (gpc & 1) + side;
  role = T1 | (GP << 4) | (side << 7) | (m2 << 8) | (dg << 14) | ((int)has2 << 16);

  if (wid == 12) {
    if (elect_one()) {
#pragma unroll
      for (int k = 0; k < S1; k++) mbar_init(bars + 8 * (B_G1FULL + k), 1);
      mbar_init(bars + 8 * B_KV, 1); mbar_init(bars + 8 * B_XT, 1);
      asm volatile("fence.mbarrier_init.release.cluster;" ::: "memory");
      TS(45);
    }
    __syncwarp();
    asm volatile("bar.arrive 5, 512;" ::: "memory");
    if (elect_one()) {
#pragma unroll 1
      for (int k = 0; k < S1; k++) {
        const uint32_t fb = bars + 8 * (B_G1FULL + k);
        mbar_expect_tx(fb, G1_STAGE);
        tma4(sb + k * G1_STAGE + G1_XOFF, last ? &p.mXl : &p.mX, 64 * k, 0, 0, last ? 0 : 80 * T1, fb);
        tma5(sb + k * G1_STAGE, &p.mB, 64 * k, 0, 0, 4 * side, 2 * GP, fb);
      }
      if (has2) {
        mbar_expect_tx(bars + 8 * B_KV, 24320 + 21760);
        tma3(sb + KS_OFF, &p.mK, 160 * dg, 64 * m2 - 3, 0, bars + 8 * B_KV);
        tma3(sb + VS_OFF, &p.mV, 160 * dg, 64 * m2 - 1, 0, bars + 8 * B_KV);
        mbar_expect_tx(bars + 8 * B_XT, 20480);
#pragma unroll
        for (int h = 0; h < 2; h++) {
          const int ng = 8 * m2 + 4 * h, T = ng / 20;
          tma4(sb + XT_OFF + h * 10240, T == NT1 - 1 ? &p.mXtl : &p.mXt, 160 * dg, 0, 0, T == NT1 - 1 ? ng - 240 : ng + 60 * T, bars + 8 * B_XT);
        }
      }
      TS(44);
    }
    __syncwarp();
    bar_sync(6, 64);
  } else {
    if (wid < 15) {
      if (elect_one()) {
        const int g = wid < 12 ? wid : wid - 1;
        const int cnt = g < 9 ? 2 : 1;
#pragma unroll
        for (int i = 0; i < 9; i++) mbar_init(bars + 8 * (4 + 9 * g + i), cnt);
        asm volatile("fence.mbarrier_init.release.cluster;" ::: "memory");
      }
    } else if (elect_one()) {
#pragma unroll
      for (int i = 0; i < 9; i++) mbar_init(bars + 8 * (B_CVDONE + i), 128);
      asm volatile("fence.mbarrier_init.release.cluster;" ::: "memory");
    }
    __syncwarp();
    bar_sync(5, 512);
    if (wid == 0) asm volatile("bar.arrive 6, 64;" ::: "memory");
  }
  if (tid == 0) TS(0);
  }

  if (wg == 3) {
    asm volatile("setmaxnreg.dec.sync.aligned.u32 56;");
    ROLE(role)
    const int pw = wid & 3;
    const unsigned tag = ld_rlx(g_epoch);
    if (pw >= 2 && has2) {
      KvRegs<1> x;
      kv_taps<1>(p, 160 * dg + 128 + 16 * (pw - 2), x);
      kv_load<1>(m2, 128 + 16 * (pw - 2), x);
      kv_finish<1>(m2, 160 * dg + 128 + 16 * (pw - 2), x);
      asm volatile("bar.arrive 3, 192;" ::: "memory");
    }
    if (pw == 0) {
#pragma unroll 1
      for (int l = 0; l < 2; l++) {
        if (l == 1) mbar_wait(bars + 8 * (has2 ? B_G2DONE + 19 : B_G1DONE + 9));
        int s = 0;
#pragma unroll 1
        for (int k = l == 0 ? S1 : 0; k < 10; k++) {
          if (k >= S1 + l) mbar_wait(bars + 8 * (B_G1DONE + 9 * l + k - S1));
          const uint32_t fb = bars + 8 * (B_G1FULL + 10 * l + k);
          if (elect_one()) {
            mbar_expect_tx(fb, 16384);
            tma5(sb + s * G1_STAGE, &p.mB, 64 * k, 0, 0, 4 * side, 2 * GP, fb);
          }
          if (++s == S1 + l) s = 0;
        }
        if (has2) {
          const int SW = l == 0 ? 6 : 7;
          mbar_wait(bars + 8 * (B_G1DONE + 10 * l + 9));
          s = 0;
#pragma unroll 1
          for (int k = 0; k < 20; k++) {
            if (k >= SW) mbar_wait(bars + 8 * (B_G2DONE + 20 * l + k - SW));
            if (k == 5) mbar_wait(bars + 8 * B_XFREE);
            const uint32_t fb = bars + 8 * (B_G2FULL + 20 * l + k);
            const int w = k >= 10, x = k - 10 * w;
            if (elect_one()) {
              mbar_expect_tx(fb, G2_WB);
              tma5(sb + G2_WOFF + s * G2_WB, (x & 1) ? &p.mCim : &p.mCre, 128 * (x >> 1) + 64 * w, 0, 0, 0, 10 * dg, fb);
            }
            if (++s == SW) s = 0;
          }
        }
      }
    } else if (pw == 1) {
#pragma unroll 1
      for (int l = 0; l < 2; l++) {
        if (l == 1) {
          mbar_wait(bars + 8 * (has2 ? B_G2DONE + 19 : B_G1DONE + 9));
          const int mlo = (160 * T1) >> 6, nf = last ? 8 : 12;
          if (lane < nf) flag_poll(&g_uflag[4 * mlo + lane], tag);
          __syncwarp();
          fence_async_global();
          if (lane == 0) TS(20);
        }
        int s = 0;
#pragma unroll 1
        for (int k = l == 0 ? S1 : 0; k < 10; k++) {
          if (k >= S1 + l) mbar_wait(bars + 8 * (B_G1DONE + 9 * l + k - S1));
          const uint32_t fb = bars + 8 * (B_G1FULL + 10 * l + k), dst = sb + s * G1_STAGE + G1_XOFF;
          if (l == 0) {
            if (elect_one()) {
              mbar_expect_tx(fb, 20480);
              tma4(dst, last ? &p.mXl : &p.mX, 64 * k, 0, 0, last ? 0 : 80 * T1, fb);
            }
          } else {
            const int bytes = last ? 16384 : 20480;
            if (elect_one()) {
              mbar_expect_tx(fb, bytes);
              bulk_g2s(dst, g_u + (size_t)(T1 * 10 + k) * 20480, bytes, fb);
            }
          }
          if (++s == S1 + l) s = 0;
        }
        if (has2) {
          mbar_wait(bars + 8 * (B_G1DONE + 10 * l + 9));
          const int Tlo = (64 * m2) / 160, Thi = (64 * m2 + 63) / 160;
          s = 0;
#pragma unroll 1
          for (int k = 0; k < 20; k++) {
            if (k == 0 || k == SX2) {
              if ((lane & 15) < 10) flag_poll(&g_hflag[((l * NT1 + (lane < 16 ? Tlo : Thi)) * 2 + (k > 0)) * 16 + (lane & 15)], tag);
              __syncwarp();
              fence_async_global();
              if (lane == 0) TS(21 + 2 * l + (k > 0));
            }
            if (k >= SX2) mbar_wait(bars + 8 * (B_G2DONE + 20 * l + k - SX2));
            const uint32_t fb = bars + 8 * (B_G2FULL + 20 * l + k);
            if (elect_one()) {
              mbar_expect_tx(fb, G2_XB);
              bulk_g2s(sb + s * G2_XB, g_h + (size_t)((l * 32 + m2) * 20 + k) * 8192, G2_XB, fb);
            }
            if (++s == SX2) s = 0;
          }
        }
      }
    } else if (pw == 2) {
#pragma unroll 1
      for (int i = 0; i < 2; i++) {
        float a, b;
        rec_poll(&g_sB[(128 * GP + 64 * i + 32 * side + lane) * 2], tag, a, b);
        sts64f(sb + CTAB_OFF + (32 * i + lane) * 24 + 16, a, b);
      }
      mbar_arrive(bars + 8 * B_CTAB);
      if (lane == 0) TS(54);
      if (has2) {
#pragma unroll 1
        for (int c = 0; c < 5; c++) {
          mbar_wait(bars + 8 * (B_CVDONE + c));
          if (elect_one()) {
            bulk_s2g(g_G + (size_t)(cch0 + c) * 4096, sb + CV_OFF + c * CV_B + CV_K, 4096);
            asm volatile("cp.async.bulk.commit_group;" ::: "memory");
            if (c == 4) {
              asm volatile("cp.async.bulk.wait_group 0;" ::: "memory");
              fence_async_global();
              red_rel(&g_gcnt[dg * 32], 1);
            }
          }
        }
      }
    } else if (has2) {
      mbar_wait(bars + 8 * B_PREP);
#pragma unroll
      for (int c = 0; c < 5; c++) {
        const uint32_t cb = sb + CV_OFF + c * CV_B;
        const uint32_t a = lane < 8 ? cb + 16 * lane : (lane < 20 ? cb + CV_U + 16 * (lane - 8) : cb + CV_U + CV_PL + 16 * (lane - 20));
        asm volatile("st.shared.v4.u32 [%0], {%1,%1,%1,%1};" ::"r"(a), "r"(0) : "memory");
      }
      fence_async_smem();
      __syncwarp();
      if (elect_one()) {
#pragma unroll
        for (int c = 0; c < 5; c++) {
          const uint32_t fb = bars + 8 * (B_CVFULL + c);
          mbar_expect_tx(fb, 4096);
          bulk_g2s(sb + CV_OFF + c * CV_B + CV_K, p.ssmk + (size_t)(cch0 + c) * SEQ, 4096, fb);
        }
        l2_prefetch(p.cre + (size_t)cch0 * DM, 6400);
        l2_prefetch(p.cim + (size_t)cch0 * DM, 6400);
        asm volatile("prefetch.tensormap [%0];" ::"l"(&p.mCre) : "memory");
        asm volatile("prefetch.tensormap [%0];" ::"l"(&p.mCim) : "memory");
        asm volatile("prefetch.tensormap [%0];" ::"l"(&p.mG) : "memory");
      }
      flag_poll(&g_kvcnt[dg * 32], tag * 32);
      __syncwarp();
      fence_async_global();
      if (lane == 0) TS(28);
      if (elect_one()) {
#pragma unroll
        for (int c = 0; c < 5; c++) {
          const uint32_t fb = bars + 8 * (B_CVFULL + c), cb = sb + CV_OFF + c * CV_B + CV_U + 192;
          mbar_expect_tx(fb, 4096);
          bulk_g2s(cb, g_kv + (size_t)(cch0 + c) * 4096, 2048, fb);
          bulk_g2s(cb + CV_PL, g_kv + (size_t)(cch0 + c) * 4096 + 2048, 2048, fb);
        }
      }
      flag_poll(&g_gcnt[dg * 32], tag * 32);
      __syncwarp();
      fence_async_global();
      if (lane == 0) TS(29);
      if (elect_one()) {
        mbar_expect_tx(bars + 8 * B_GFULL, 20480);
        tma5(sb + G_OFF, &p.mG, 64 * m2, 0, 0, 0, 10 * dg, bars + 8 * B_GFULL);
      }
    }
  } else {
    asm volatile("setmaxnreg.inc.sync.aligned.u32 152;");
    const int w = wid & 3;
    const unsigned tag = ld_rlx(g_epoch);
    if (wg < 2) {
      ROLE(role)
      if (wid < 5) {
        if (has2) {
          float sv[2];
#pragma unroll
          for (int x = 0; x < 2; x++) {
            const uint2* row = (const uint2*)((x ? p.bim : p.bre) + (cch0 + wid) * DM) + lane;
            float a = 0.f;
#pragma unroll
            for (int i = 0; i < 5; i++) { uint2 t = __ldg(row + 32 * i); a += (bf_lo(t.x) + bf_hi(t.x)) + (bf_lo(t.y) + bf_hi(t.y)); }
            sv[x] = a;
          }
#pragma unroll
          for (int o = 16; o > 0; o >>= 1) { sv[0] += __shfl_xor_sync(0xffffffffu, sv[0], o); sv[1] += __shfl_xor_sync(0xffffffffu, sv[1], o); }
          if (lane < 2) rec_st(&g_sB[(cch0 + wid) * 2 + lane], sv[0], sv[1], tag);
          if (tid == 0) TS(47);
        }
      } else {
        if (wid < 7) {
          const int ch = 128 * GP + 64 * (wid - 5) + 32 * side + lane;
          const float lr = __bfloat162float(p.lre[ch]), li = __bfloat162float(p.lim[ch]);
          const float dt = __bfloat162float(__float2bfloat16_rn(expf(__bfloat162float(p.logdt[ch]))));
          const float mag = expf(dt * lr);
          float sn, cs; sincosf(dt * li, &sn, &cs);
          const float ar = mag * cs, ai = mag * sn;
          const float inv = 2.f / (lr * lr + li * li);
          const uint32_t ad = sb + CTAB_OFF + (32 * (wid - 5) + lane) * 24;
          sts64f(ad, ar, ai);
          sts64f(ad + 8, ((ar - 1.f) * lr + ai * li) * inv, (ai * lr - (ar - 1.f) * li) * inv);
          if (tid == 160) TS(46);
        } else if (has2 && lane < 20) {
          uint4 dv = __ldg((const uint4*)(p.dskip + 160 * dg) + lane);
          asm volatile("st.shared.v4.u32 [%0], {%1,%2,%3,%4};" ::"r"(sb + DTAB_OFF + 16 * lane), "r"(dv.x), "r"(dv.y), "r"(dv.z), "r"(dv.w) : "memory");
        }
        mbar_arrive(bars + 8 * B_CTAB);
      }
      __syncwarp();
    } else {
      ROLE(role)
      if (has2) {
        const int n0 = 64 * m2 + 16 * w + (lane >> 2);
        {
          KvRegs<2> x;
          kv_taps<2>(p, 160 * dg + 32 * w, x);
          kv_load<2>(m2, 32 * w, x);
          if (tid == 256) TS(50);
          kv_finish<2>(m2, 160 * dg + 32 * w, x);
        }
        if (tid == 256) TS(52);
        bar_sync(3, 192);
        if (tid == 288) { mbar_arrive(bars + 8 * B_PREP); red_rel(&g_kvcnt[dg * 32], 1); TS(30); }
        float xs[80];
        x0_load(xs);
        stats_publish<true>(0, n0, dg, tag, xs);
        if (tid == 256) TS(31);
      } else if (tid == 256) mbar_arrive(bars + 8 * B_PREP);
      stat_table(T1, 4 * tag, 0);
      if (tid == 256) TS(26);
      if (!has2) { mbar_wait(bars + 8 * (B_G1FULL + 10)); stat_table(T1, 4 * tag + 2, 1); }
    }
#pragma unroll 1
    for (int l = 0; l < 2; l++) {
      if (wg < 2) {
        float acc[80];
#pragma unroll
        for (int i = 0; i < 80; i++) acc[i] = 0.f;
        ROLE(role)
        const int tid = tid_opaque(), r = (tid & 31) >> 2, q = tid & 3;
        const int ch = 128 * GP + 64 * wg + 32 * side + 8 * w + r;
        fence_regs(acc);
        {
          uint32_t alo = desc_lo(sb, 16) + wg * 512, blo = l == 0 ? desc_lo(sb + G1_XOFF, 16) : desc_lo(sb + G1_XOFF, 128);
          const uint32_t bhi = l == 0 ? desc_hi(1024, 1) : desc_hi(1024, 0), xstep = l == 0 ? 2 : 16;
          const uint32_t aend = desc_lo(sb, 16) + (S1 + l) * (G1_STAGE >> 4);
          uint32_t fb = bars + 8 * (B_G1FULL + 10 * l);
          mbar_wait(fb);
          if (tid == 0) TS(1 + 8 * l);
#pragma unroll 1
          for (int k = 0; k < 10; k++) {
            wgmma_fence();
#pragma unroll
            for (int kk = 0; kk < 4; kk++) wgmma_n160<0>(acc, alo + kk * 2, desc_hi(1024, 1), blo + kk * xstep, bhi);
            wgmma_commit();
            alo += G1_STAGE >> 4; blo += G1_STAGE >> 4;
            if (alo >= aend) { alo -= (S1 + l) * (G1_STAGE >> 4); blo -= (S1 + l) * (G1_STAGE >> 4); }
            if (k < 9) mbar_wait(fb + 8);
            if (k > 0) { wgmma_wait<1>(); if ((tid & 127) == 0) mbar_arrive(fb + 8 * (B_G1DONE - B_G1FULL - 1)); }
            if (l == 0 && k == S1 - 1) { if (tid == 0) TS(48); mbar_wait(bars + 8 * B_PREP); if (tid == 0) TS(49); }
            fb += 8;
          }
        }
        mbar_wait(bars + 8 * B_CTAB);
        const uint32_t ca = sb + CTAB_OFF + (32 * wg + 8 * w + r) * 24;
        float2 lam = lds64f(ca), sB = lds64f(ca + 16);
        const float2 coef = lds64f(ca + 8), lamc = make_float2(lam.x, -lam.y);
        float m00 = coef.x, m01 = -coef.y, m10 = -coef.y, m11 = -coef.x;
        if (p.swap) { lam = lamc; sB = make_float2(sB.y, sB.x); m00 = -coef.y; m01 = coef.x; m10 = -coef.x; m11 = -coef.y; }
        float2 pL, p2L, pLq, p160q, p640;
        {
          float2 p2 = cmul(lam, lam), p4 = cmul(p2, p2), p8 = cmul(p4, p4), p16 = cmul(p8, p8), p32 = cmul(p16, p16);
          float2 p40 = cmul(p32, p8), p80 = cmul(p40, p40), p160 = cmul(p80, p80), p320 = cmul(p160, p160);
          p640 = cmul(p320, p320);
          pL = last ? p32 : p40;
          p2L = cmul(pL, pL);
          const float2 one = make_float2(1.f, 0.f);
          pLq = cmul((q & 1) ? pL : one, (q & 2) ? p2L : one);
          p160q = cmul((q & 1) ? p160 : one, (q & 2) ? p320 : one);
        }
        mbar_wait(bars + 8 * (B_STAB + l));
        wgmma_wait<0>();
        fence_regs(acc);
        if ((tid & 127) == 0) { mbar_arrive(bars + 8 * (B_G1DONE + 10 * l + 9)); if (wg == 0) TS(2 + 8 * l); }
        float2 e = make_float2(0.f, 0.f), snap = e;
#pragma unroll
        for (int j = 0; j < 20; j++) {
          const float4 st = lds128f(sb + STAB_OFF + (8 * j + 2 * q) * 8);
          acc[4 * j + 0] = fmaf(acc[4 * j + 0], st.x, st.y * sB.x);
          acc[4 * j + 2] = fmaf(acc[4 * j + 2], st.x, st.y * sB.y);
          acc[4 * j + 1] = fmaf(acc[4 * j + 1], st.z, st.w * sB.x);
          acc[4 * j + 3] = fmaf(acc[4 * j + 3], st.z, st.w * sB.y);
          e = cfma(lam, e, make_float2(acc[4 * j + 0], acc[4 * j + 2]));
          e = cfma(lam, e, make_float2(acc[4 * j + 1], acc[4 * j + 3]));
          if (j == 15) snap = e;
        }
        if (last) e = snap;
        {
          float2 v = make_float2(__shfl_up_sync(0xffffffffu, e.x, 1, 4), __shfl_up_sync(0xffffffffu, e.y, 1, 4));
          if (q >= 1) e = cfma(pL, v, e);
          v = make_float2(__shfl_up_sync(0xffffffffu, e.x, 2, 4), __shfl_up_sync(0xffffffffu, e.y, 2, 4));
          if (q >= 2) e = cfma(p2L, v, e);
        }
        if (!last && (q == 3 || (q == 2 && l == 0))) rec_st(&g_E[(T1 * DM + ch) * 2 + (q == 3 ? l : 1)], e.x, e.y, q == 3 ? tag : tag - 1);
        if (tid == 0) TS(3 + 8 * l);
        float2 ex = make_float2(__shfl_up_sync(0xffffffffu, e.x, 1, 4), __shfl_up_sync(0xffffffffu, e.y, 1, 4));
        if (q == 0) ex = make_float2(0.f, 0.f);
#pragma unroll
        for (int j = 0; j < 20; j++)
#pragma unroll
          for (int x = 0; x < 2; x++) {
            const float b0 = acc[4 * j + x], b1 = acc[4 * j + 2 + x];
            acc[4 * j + x] = fmaf(b0, m00, b1 * m01);
            acc[4 * j + 2 + x] = fmaf(b0, m10, b1 * m11);
          }
        float2 c;
        {
          float2 ev[3];
          uint32_t it = 0;
          while (true) {
            bool ok = true;
#pragma unroll
            for (int i = 0; i < 3; i++) {
              const int Tp = T1 - 1 - q - 4 * i;
              ev[i] = make_float2(0.f, 0.f);
              if (Tp >= 0) ok &= (rec_ld(&g_E[(Tp * DM + ch) * 2 + l], ev[i].x, ev[i].y) == tag);
            }
            if (ok) break;
            if (++it > SPIN_LIMIT) __trap();
          }
          __syncwarp();
          c = cfma(p640, cfma(p640, ev[2], ev[1]), ev[0]);
          c = cmul(c, p160q);
          c.x += __shfl_xor_sync(0xffffffffu, c.x, 1); c.y += __shfl_xor_sync(0xffffffffu, c.y, 1);
          c.x += __shfl_xor_sync(0xffffffffu, c.x, 2); c.y += __shfl_xor_sync(0xffffffffu, c.y, 2);
        }
        if (tid == 0) TS(4 + 8 * l);
        c = cfma(pLq, c, ex);
        float2 hh = make_float2(fmaf(c.x, m00, c.y * m01), fmaf(c.x, m10, c.y * m11));
        uint8_t* hb = g_h + (size_t)l * (32 * 20 * 8192) + (10 * wg + 2 * GP) * 8192 + (4 * side + w) * 1024 + (tid_opaque() & 31) * 4;
#pragma unroll
        for (int j4 = 0; j4 < 5; j4++) {
          const int ng = 20 * T1 + 4 * j4;
          uint8_t* hp = hb + (size_t)(ng >> 3) * 163840 + (ng & 7) * 128;
#pragma unroll
          for (int jj = 0; jj < 4; jj++) {
            const int j = 4 * j4 + jj;
            const float2 h0 = cfma(lamc, hh, make_float2(acc[4 * j + 0], acc[4 * j + 2]));
            hh = cfma(lamc, h0, make_float2(acc[4 * j + 1], acc[4 * j + 3]));
            if (j4 < 4 || !last) {
              *(uint32_t*)(hp + jj * 128) = pack_bf16(h0.x, hh.x);
              *(uint32_t*)(hp + jj * 128 + 8192) = pack_bf16(h0.y, hh.y);
            }
          }
        }
        bar_sync(1 + wg, 128);
        if ((tid & 127) == 0) {
          if (wg == 0) TS(5 + 8 * l);
          st_rel(&g_hflag[((l * NT1 + T1) * 2 + wg) * 16 + 2 * GP + side], tag);
          if (wg == 0) TS(6 + 8 * l);
        }
      }
      if (l == 0) {
        ROLE(role)
        if (has2) {
          if (wg == 2) mbar_wait(bars + 8 * (B_G1DONE + 8));
#pragma unroll 1
          for (int c = wg == 2 ? 0 : 2 + wg; c < (wg == 2 ? 2 : 5); c += wg == 2 ? 1 : 2) conv_channel(p, c, cch0 + c, 1 + wg);
          if ((tid & 127) == 0) TS(wg == 2 ? 32 : 7 + wg);
        }
      }
      if (wg == 2) break;
    }
    if (wg == 2 && (role >> 16)) {
      float acc[80];
      float off[2] = {0.f, 0.f};
      x0_load(acc);
      mbar_arrive(bars + 8 * B_XFREE);
#pragma unroll 1
      for (int l = 0; l < 2; l++) {
        float mean[2], rstd[2];
        {
          ROLE(role)
          const int lane = tid_opaque() & 31;
          stats_get(2 * l, 64 * m2 + 16 * w + (lane >> 2), tag, mean, rstd);
          off[0] += mean[0]; off[1] += mean[1];
          mbar_wait(bars + 8 * B_CTAB);
#pragma unroll
          for (int J = 0; J < 10; J++) {
            const float2 dw = lds64f(sb + DTAB_OFF + 2 * (16 * J + 4 * (lane & 3)));
#pragma unroll
            for (int x = 0; x < 8; x++) {
              const int h = (x >> 1) & 1;
              const uint32_t gwd = __float_as_uint(x < 4 ? dw.x : dw.y);
              acc[8 * J + x] = (acc[8 * J + x] - mean[h]) * fmaf(rstd[h], (x & 1) ? bf_hi(gwd) : bf_lo(gwd), 1.f);
            }
          }
        }
        {
          const uint32_t aend = desc_lo(sb + SX2 * G2_XB, 1024), bend = desc_lo(sb + G2_WOFF + 6 * G2_WB, 16) + l * (G2_WB >> 4);
          uint32_t alo = desc_lo(sb, 1024), blo = desc_lo(sb + G2_WOFF, 16);
          uint32_t fb = bars + 8 * (B_G2FULL + 20 * l);
          fence_regs(acc);
          mbar_wait(fb);
          if (tid == 256) TS(33 + 6 * l);
#pragma unroll 1
          for (int k = 0; k < 20; k++) {
            if (l == 1 && (k & 3) == 3 && tid == 256) TS(56 + (k >> 2));
            wgmma_fence();
#pragma unroll
            for (int kk = 0; kk < 4; kk++) wgmma_n160<1>(acc, alo + kk * 128, desc_hi(128, 0), blo + kk * 2, desc_hi(1024, 1));
            wgmma_commit();
            alo += G2_XB >> 4; if (alo == aend) alo = desc_lo(sb, 1024);
            blo += G2_WB >> 4; if (blo == bend) blo = desc_lo(sb + G2_WOFF, 16);
            if (k < 19) mbar_wait(fb + 8);
            if (k > 0) { wgmma_wait<1>(); if (tid == 256) mbar_arrive(fb + 8 * (B_G2DONE - B_G2FULL - 1)); }
            fb += 8;
          }
          wgmma_wait<0>();
          fence_regs(acc);
          if (tid == 256) { mbar_arrive(bars + 8 * (B_G2DONE + 20 * l + 19)); TS(34 + 6 * l); }
        }
        ROLE(role)
        const int tq = tid_opaque() & 31, n0 = 64 * m2 + 16 * w + (tq >> 2);
        stats_publish<false>(2 * l + 1, n0, dg, tag, acc);
        uint32_t gf[10][4];
        mbar_wait(bars + 8 * B_GFULL);
        const uint32_t ga = sb + G_OFF + (8 * (tq >> 4) + (tq & 7)) * 128 + (((2 * w + ((tq >> 3) & 1)) ^ (m2 & 7) ^ (tq & 7)) << 4);
#pragma unroll
        for (int J = 0; J < 4; J++) ldsm4t(gf[J], ga + J * 2048);
        if (tid == 256) TS(35 + 6 * l);
        uint8_t* dst[2][2];
#pragma unroll
        for (int h = 0; h < 2; h++) {
          if (l == 0) {
            const int ng = 8 * m2 + 2 * w + h, T = ng / 20;
            uint8_t* ub = g_u + (T * 204800 + (ng - 20 * T) * 1024 + (tq & 2) * 64 + (tq & 28) * 4 + (tq & 1) * 8 + (5 * dg >> 1) * 20480);
            dst[h][1] = ub + ((dg & 1) ? 20480 - 512 : 0);
            dst[h][0] = ub + (dg & 1) * 512;
          } else {
            dst[h][0] = dst[h][1] = (uint8_t*)(p.out + (n_to_t(n0 + 8 * h) * DM + 160 * dg + 4 * (tq & 3)));
          }
        }
        stats_get(2 * l + 1, n0, tag, mean, rstd);
        if (tid == 256) TS(36 + 6 * l);
        off[0] += mean[0]; off[1] += mean[1];
#pragma unroll
        for (int J = 0; J < 10; J++) {
          asm volatile("" : "+r"(gf[J][0]), "+r"(gf[J][1]), "+r"(gf[J][2]), "+r"(gf[J][3])::"memory");
          if (J + 4 < 10) ldsm4t(gf[J + 4 < 10 ? J + 4 : 0], ga + (J + 4) * 2048);
#pragma unroll
          for (int x = 0; x < 8; x++) {
            const int h = (x >> 1) & 1;
            const uint32_t gwd = gf[J][x >> 1];
            acc[8 * J + x] = (acc[8 * J + x] - mean[h]) * fmaf(rstd[h], (x & 1) ? bf_hi(gwd) : bf_lo(gwd), 1.f);
          }
#pragma unroll
          for (int h = 0; h < 2; h++) {
            if (l == 0)
              *(uint2*)(dst[h][(J >> 1) & 1] + (J >> 2) * 20480 + (J & 3) * 256) =
                  make_uint2(pack_bf16(acc[8 * J + 2 * h], acc[8 * J + 2 * h + 1]), pack_bf16(acc[8 * J + 4 + 2 * h], acc[8 * J + 5 + 2 * h]));
            else
              *(float4*)(dst[h][0] + 64 * J) = make_float4(acc[8 * J + 2 * h] + off[h], acc[8 * J + 2 * h + 1] + off[h],
                                                           acc[8 * J + 4 + 2 * h] + off[h], acc[8 * J + 5 + 2 * h] + off[h]);
          }
        }
        if (l == 0) {
          bar_sync(3, 128);
          if (tid == 256) { TS(37); st_rel(&g_uflag[4 * m2 + dg], tag); TS(38); }
          stats_publish<false>(2, n0, dg, tag, acc);
          stat_table(T1, 4 * tag + 2, 1);
          if (tid == 256) TS(27);
        } else {
          if (tid == 256) {
            TS(43);
            if (m2 == 31 && dg == 3) asm volatile("st.relaxed.gpu.global.u32 [%0], %1;" ::"l"(g_epoch), "r"(tag + 1) : "memory");
          }
        }
      }
    }
  }
}

typedef CUresult (*EncFn)(CUtensorMap*, CUtensorMapDataType, cuuint32_t, void*, const cuuint64_t*, const cuuint64_t*,
                          const cuuint32_t*, const cuuint32_t*, CUtensorMapInterleave, CUtensorMapSwizzle,
                          CUtensorMapL2promotion, CUtensorMapFloatOOBfill);

void encode(EncFn fn, CUtensorMap* m, const void* ptr, int rank, const cuuint64_t* dims, const cuuint64_t* strides, const cuuint32_t* box,
            CUtensorMapSwizzle swz = CU_TENSOR_MAP_SWIZZLE_128B) {
  cuuint32_t es[5] = {1, 1, 1, 1, 1};
  fn(m, CU_TENSOR_MAP_DATA_TYPE_BFLOAT16, rank, (void*)ptr, dims, strides, box, es, CU_TENSOR_MAP_INTERLEAVE_NONE,
     swz, swz == CU_TENSOR_MAP_SWIZZLE_128B ? CU_TENSOR_MAP_L2_PROMOTION_L2_128B : CU_TENSOR_MAP_L2_PROMOTION_L2_64B, CU_TENSOR_MAP_FLOAT_OOB_FILL_NONE);
}

}

extern "C" void kernel_launch(void* const* d_in, const int* in_sizes, int n_in, void* d_out, int out_size) {
  (void)in_sizes; (void)n_in; (void)out_size;
  Params p;
  typedef const __nv_bfloat16* BP;
  p.x = (BP)d_in[0]; p.lre = (BP)d_in[1]; p.lim = (BP)d_in[2]; p.bre = (BP)d_in[3]; p.bim = (BP)d_in[4];
  p.cre = (BP)d_in[5]; p.cim = (BP)d_in[6]; p.logdt = (BP)d_in[7]; p.dskip = (BP)d_in[8];
  p.k = (BP)d_in[10]; p.v = (BP)d_in[11]; p.shiftk = (BP)d_in[12]; p.ssmk = (BP)d_in[13]; p.ssmD = (BP)d_in[14];
  p.out = (float*)d_out;
  void* fnp = nullptr;
  cudaDriverEntryPointQueryResult qr;
  cudaGetDriverEntryPoint("cuTensorMapEncodeTiled", &fnp, cudaEnableDefault, &qr);
  EncFn fn = (EncFn)fnp;
  void* gG = nullptr;
  cudaGetSymbolAddress(&gG, g_G);
  const cuuint64_t RB = DM * 2;
  {
    p.swap = p.bim < p.bre;
    const char* lo = (const char*)(p.swap ? p.bim : p.bre); const char* hi = (const char*)(p.swap ? p.bre : p.bim);
    cuuint64_t dims[5] = {640, 8, 2, 8, 10}, st[4] = {RB, (cuuint64_t)(hi - lo), 8 * RB, 64 * RB}; cuuint32_t box[5] = {64, 8, 2, 4, 2};
    encode(fn, &p.mB, lo, 5, dims, st, box);
  }
  {
    cuuint64_t dims[5] = {640, 2, 4, 2, 40}, st[4] = {RB, 4 * RB, 2 * RB, 16 * RB}; cuuint32_t box[5] = {64, 2, 4, 2, 10};
    encode(fn, &p.mCre, p.cre, 5, dims, st, box); encode(fn, &p.mCim, p.cim, 5, dims, st, box);
    cuuint64_t dimg[5] = {2048, 2, 4, 2, 40}, stg[4] = {4096, 4 * 4096, 2 * 4096, 16 * 4096};
    encode(fn, &p.mG, gG, 5, dimg, stg, box);
  }
  {
    cuuint64_t dims[4] = {640, 2, 4, 900}, st[3] = {RB, 40 * RB, 2 * RB}; cuuint32_t box[4] = {64, 2, 4, 20};
    encode(fn, &p.mX, p.x, 4, dims, st, box);
    cuuint64_t diml[4] = {640, 2, 4, 16}, stl[3] = {RB, 32 * RB, 2 * RB};
    encode(fn, &p.mXl, p.x + (size_t)1920 * DM, 4, diml, stl, box);
    cuuint32_t boxt[4] = {160, 2, 4, 4};
    encode(fn, &p.mXt, p.x, 4, dims, st, boxt, CU_TENSOR_MAP_SWIZZLE_NONE);
    encode(fn, &p.mXtl, p.x + (size_t)1920 * DM, 4, diml, stl, boxt, CU_TENSOR_MAP_SWIZZLE_NONE);
    cuuint64_t dk[3] = {640, 2000, 4}, sk[2] = {RB, 16 * RB}; cuuint32_t bk[3] = {160, 19, 4}, bv[3] = {160, 17, 4};
    encode(fn, &p.mK, p.k, 3, dk, sk, bk, CU_TENSOR_MAP_SWIZZLE_NONE);
    encode(fn, &p.mV, p.v, 3, dk, sk, bv, CU_TENSOR_MAP_SWIZZLE_NONE);
  }
  cudaFuncSetAttribute(fused_kernel, cudaFuncAttributeMaxDynamicSharedMemorySize, SMEM_BYTES);
  cudaLaunchConfig_t cfg = {};
  cfg.gridDim = dim3(132); cfg.blockDim = dim3(512); cfg.dynamicSmemBytes = SMEM_BYTES; cfg.stream = cudaStreamPerThread;
  cudaLaunchKernelEx(&cfg, fused_kernel, p);
}
```

```cpp
#include <cuda_runtime.h>
#include <cuda.h>
#include <cuda_bf16.h>
#include <stdint.h>

namespace {

constexpr int SEQ = 2048, DM = 640;
constexpr int NT1 = 13;
#define EXP 0
#define PAUSE_K 4
constexpr uint32_t SPIN_LIMIT = 1u << 22;

__device__ __align__(1024) uint8_t g_h[2 * 32 * 20 * 8192];
__device__ __align__(1024) uint8_t g_u[NT1 * 10 * 20480];
__device__ __align__(1024) uint8_t g_kv[DM * 4096];
__device__ __align__(1024) uint8_t g_G[DM * 4096];
__device__ __align__(128) uint4 g_E[NT1 * DM * 2];
__device__ __align__(128) uint4 g_stats[SEQ * 4 * 2];
__device__ __align__(128) uint4 g_sB[DM * 2];
__device__ __align__(128) unsigned g_hflag[2 * NT1 * 2 * 16];
__device__ __align__(128) unsigned g_uflag[32 * 4];
__device__ __align__(128) unsigned g_kvcnt[4 * 32];
__device__ __align__(128) unsigned g_gcnt[4 * 32];
__device__ __align__(128) unsigned g_epoch[32] = {1};
#define TS(i) do {} while (0)

struct Params {
  CUtensorMap mB, mCre, mCim, mX, mXl, mG, mK, mV, mXt, mXtl;
  const __nv_bfloat16 *x, *lre, *lim, *bre, *bim, *cre, *cim, *logdt, *dskip, *k, *v, *shiftk, *ssmk, *ssmD;
  float* out;
  int swap;
};

constexpr uint32_t sb = 1024;
constexpr uint32_t G1_STAGE = 36864, G1_XOFF = 16384;
constexpr int S1 = 4;
constexpr uint32_t XT_OFF = 159744, KS_OFF = 180224, KV_PIECE = 9216;
constexpr uint32_t G2_XB = 8192, G2_WB = 20480, G2_WOFF = 57344, G_OFF = 200704;
constexpr int SX2 = 5;
constexpr uint32_t CV_OFF = 184320, CV_K = 128, CV_PL = 2240, CV_U = CV_K + 4096, CV_B = 8704;
constexpr uint32_t MISC = 227840;
constexpr uint32_t BAR_OFF = MISC;
constexpr int B_G1FULL = 0, B_G1DONE = 20, B_G2FULL = 40,
              B_G2DONE = 85, B_GFULL = 125, B_PREP = 126, B_EP = 127, B_H1 = 128  ,
              B_CVDONE = 130, B_STAB = 135  , B_CTAB = 137, B_XFREE = 138,
              B_XT = 139, B_KV = 140  , B_TAPS = 145  , B_CVFULL = 150  ;
constexpr uint32_t bars = sb + BAR_OFF;
constexpr uint32_t STAB_OFF = MISC + 1248;
constexpr uint32_t CTAB_OFF = STAB_OFF + 1280;
constexpr uint32_t DTAB_OFF = CTAB_OFF + 1536;
constexpr uint32_t EP_OFF = DTAB_OFF + 320;
constexpr uint32_t TAP_OFF = 147456;
constexpr uint32_t SMEM_BYTES = 232448;
static_assert(EP_OFF + 32 <= SMEM_BYTES, "smem");

__device__ __forceinline__ void soft_trap() { asm volatile("trap;"); }
__device__ __forceinline__ uint32_t smem_u32(const void* p) { return (uint32_t)__cvta_generic_to_shared(p); }
__device__ __forceinline__ void mbar_init(uint32_t bar, int cnt) { asm volatile("mbarrier.init.shared::cta.b64 [%0], %1;" ::"r"(bar), "r"(cnt) : "memory"); }
__device__ __forceinline__ void mbar_expect_tx(uint32_t bar, int bytes) { asm volatile("mbarrier.arrive.expect_tx.shared::cta.b64 _, [%0], %1;" ::"r"(bar), "r"(bytes) : "memory"); }
__device__ __forceinline__ void mbar_arrive(uint32_t bar) { asm volatile("mbarrier.arrive.shared::cta.b64 _, [%0];" ::"r"(bar) : "memory"); }
__device__ __forceinline__ void mbar_wait(uint32_t bar) {
  asm volatile(
      "{\n.reg .pred p;\n.reg .u32 c;\nmov.u32 c, 0;\n"
      "W_%=:\nmbarrier.try_wait.parity.shared::cta.b64 p, [%0], 0;\n@p bra D_%=;\n"
      "add.u32 c, c, 1;\nsetp.lt.u32 p, c, %1;\n@p bra W_%=;\ntrap;\nD_%=:\n}\n" ::"r"(bar), "n"(SPIN_LIMIT) : "memory");
}
__device__ __forceinline__ uint32_t mbar_test(uint32_t bar) {
  uint32_t ok;
  asm volatile("{\n.reg .pred p;\nmbarrier.test_wait.parity.shared::cta.b64 p, [%1], 0;\nselp.u32 %0, 1, 0, p;\n}\n" : "=r"(ok) : "r"(bar) : "memory");
  return ok;
}
__device__ __forceinline__ void tma3(uint32_t dst, const CUtensorMap* m, int c0, int c1, int c2, uint32_t bar) {
  asm volatile("cp.async.bulk.tensor.3d.shared::cluster.global.mbarrier::complete_tx::bytes [%0], [%1, {%3,%4,%5}], [%2];"
               ::"r"(dst), "l"(m), "r"(bar), "r"(c0), "r"(c1), "r"(c2) : "memory");
}
__device__ __forceinline__ void tma4(uint32_t dst, const CUtensorMap* m, int c0, int c1, int c2, int c3, uint32_t bar) {
  asm volatile("cp.async.bulk.tensor.4d.shared::cluster.global.mbarrier::complete_tx::bytes [%0], [%1, {%3,%4,%5,%6}], [%2];"
               ::"r"(dst), "l"(m), "r"(bar), "r"(c0), "r"(c1), "r"(c2), "r"(c3) : "memory");
}
__device__ __forceinline__ void tma5(uint32_t dst, const CUtensorMap* m, int c0, int c1, int c2, int c3, int c4, uint32_t bar) {
  asm volatile("cp.async.bulk.tensor.5d.shared::cluster.global.mbarrier::complete_tx::bytes [%0], [%1, {%3,%4,%5,%6,%7}], [%2];"
               ::"r"(dst), "l"(m), "r"(bar), "r"(c0), "r"(c1), "r"(c2), "r"(c3), "r"(c4) : "memory");
}
__device__ __forceinline__ void bulk_g2s(uint32_t dst, const void* src, int bytes, uint32_t bar) {
  asm volatile("cp.async.bulk.shared::cluster.global.mbarrier::complete_tx::bytes [%0], [%1], %2, [%3];"
               ::"r"(dst), "l"(src), "r"(bytes), "r"(bar) : "memory");
}
__device__ __forceinline__ void bulk_s2g(void* dst, uint32_t src, int bytes) {
  asm volatile("cp.async.bulk.global.shared::cta.bulk_group [%0], [%1], %2;" ::"l"(dst), "r"(src), "r"(bytes) : "memory");
}
__device__ __forceinline__ void l2_prefetch(const void* src, int bytes) {
  asm volatile("cp.async.bulk.prefetch.L2.global [%0], %1;" ::"l"(src), "r"(bytes) : "memory");
}
__device__ __forceinline__ void wgmma_fence() { asm volatile("wgmma.fence.sync.aligned;" ::: "memory"); }
__device__ __forceinline__ void wgmma_commit() { asm volatile("wgmma.commit_group.sync.aligned;" ::: "memory"); }
template <int N> __device__ __forceinline__ void wgmma_wait() { asm volatile("wgmma.wait_group.sync.aligned %0;" ::"n"(N) : "memory"); }
__host__ __device__ constexpr uint32_t desc_lo(uint32_t addr, uint32_t lbo) { return ((addr & 0x3FFFF) >> 4) | ((lbo >> 4) << 16); }
__host__ __device__ constexpr uint32_t desc_hi(uint32_t sbo, uint32_t swz) { return (sbo >> 4) | (swz << 30); }
__device__ __forceinline__ void bar_sync(int id, int n) { asm volatile("bar.sync %0, %1;" ::"r"(id), "r"(n) : "memory"); }
__device__ __forceinline__ uint32_t lds32(uint32_t a) { uint32_t v; asm volatile("ld.shared.u32 %0, [%1];" : "=r"(v) : "r"(a) : "memory"); return v; }
__device__ __forceinline__ float2 lds64f(uint32_t a) { float2 v; asm volatile("ld.shared.v2.f32 {%0,%1}, [%2];" : "=f"(v.x), "=f"(v.y) : "r"(a) : "memory"); return v; }
__device__ __forceinline__ float4 lds128f(uint32_t a) { float4 v; asm volatile("ld.shared.v4.f32 {%0,%1,%2,%3}, [%4];" : "=f"(v.x), "=f"(v.y), "=f"(v.z), "=f"(v.w) : "r"(a) : "memory"); return v; }
__device__ __forceinline__ void ldsm4t(uint32_t (&r)[4], uint32_t a) {
  asm volatile("ldmatrix.sync.aligned.m8n8.x4.trans.shared.b16 {%0,%1,%2,%3}, [%4];" : "=r"(r[0]), "=r"(r[1]), "=r"(r[2]), "=r"(r[3]) : "r"(a) : "memory");
}
__device__ __forceinline__ uint4 ldv128(const void* a) { uint4 v; asm volatile("ld.global.nc.v4.u32 {%0,%1,%2,%3}, [%4];" : "=r"(v.x), "=r"(v.y), "=r"(v.z), "=r"(v.w) : "l"(a) : "memory"); return v; }
__device__ __forceinline__ uint2 ldv64(const void* a) { uint2 v; asm volatile("ld.global.nc.v2.u32 {%0,%1}, [%2];" : "=r"(v.x), "=r"(v.y) : "l"(a) : "memory"); return v; }
__device__ __forceinline__ uint32_t ldv16(const void* a) { uint32_t v; asm volatile("ld.global.nc.u16 %0, [%1];" : "=r"(v) : "l"(a) : "memory"); return v; }
__device__ __forceinline__ void sts128(uint32_t a, uint4 v) { asm volatile("st.shared.v4.u32 [%0], {%1,%2,%3,%4};" ::"r"(a), "r"(v.x), "r"(v.y), "r"(v.z), "r"(v.w) : "memory"); }
__device__ __forceinline__ void sts32(uint32_t a, uint32_t v) { asm volatile("st.shared.u32 [%0], %1;" ::"r"(a), "r"(v) : "memory"); }
__device__ __forceinline__ void sts64f(uint32_t a, float x, float y) { asm volatile("st.shared.v2.f32 [%0], {%1,%2};" ::"r"(a), "f"(x), "f"(y) : "memory"); }
__device__ __forceinline__ void st_rel(unsigned* p, unsigned v) { asm volatile("st.release.gpu.global.u32 [%0], %1;" ::"l"(p), "r"(v) : "memory"); }
__device__ __forceinline__ void red_rel(unsigned* p, unsigned v) { asm volatile("red.release.gpu.global.add.u32 [%0], %1;" ::"l"(p), "r"(v) : "memory"); }
__device__ __forceinline__ void fence_async_global() { asm volatile("fence.proxy.async.global;" ::: "memory"); }
__device__ __forceinline__ void fence_async_smem() { asm volatile("fence.proxy.async.shared::cta;" ::: "memory"); }
__device__ __forceinline__ void rec_st(uint4* p, float a, float b, unsigned tag) {
  asm volatile("{\n.reg .b128 t;\n.reg .b64 lo, hi;\nmov.b64 lo, {%1,%2};\nmov.b64 hi, {%3,%3};\nmov.b128 t, {lo,hi};\n"
               "st.relaxed.gpu.global.b128 [%0], t;\n}\n" ::"l"(p), "r"(__float_as_uint(a)), "r"(__float_as_uint(b)), "r"(tag) : "memory");
}
__device__ __forceinline__ unsigned rec_ld(const uint4* p, float& a, float& b) {
  unsigned x, y, t;
  asm volatile("{\n.reg .b128 t;\n.reg .b64 lo, hi;\n.reg .b32 u;\nld.relaxed.gpu.global.b128 t, [%3];\nmov.b128 {lo,hi}, t;\n"
               "mov.b64 {%0,%1}, lo;\nmov.b64 {%2,u}, hi;\n}\n" : "=r"(x), "=r"(y), "=r"(t) : "l"(p) : "memory");
  a = __uint_as_float(x); b = __uint_as_float(y);
  return t;
}
__device__ __forceinline__ void rec_poll(const uint4* p, unsigned tag, float& a, float& b) {
  uint32_t it = 0;
  while (rec_ld(p, a, b) != tag) { if (++it > SPIN_LIMIT) soft_trap(); }
}
__device__ __forceinline__ unsigned ld_rlx(const unsigned* p) { unsigned v; asm volatile("ld.relaxed.gpu.global.u32 %0, [%1];" : "=r"(v) : "l"(p) : "memory"); return v; }
__device__ __forceinline__ void flag_poll(const unsigned* p, unsigned target) {
  uint32_t it = 0;
  while ((int)(ld_rlx(p) - target) < 0) { if (++it > SPIN_LIMIT) soft_trap(); }
  asm volatile("fence.acquire.gpu;" ::: "memory");
}
__device__ __forceinline__ uint32_t pack_bf16(float lo, float hi) {
  uint32_t r; asm("cvt.rn.bf16x2.f32 %0, %1, %2;" : "=r"(r) : "f"(hi), "f"(lo)); return r;
}
__device__ __forceinline__ float bf_lo(uint32_t w) { return __uint_as_float(w << 16); }
__device__ __forceinline__ float bf_hi(uint32_t w) { return __uint_as_float(w & 0xffff0000u); }
__device__ __forceinline__ uint32_t hmul2(uint32_t a, uint32_t b) {
  __nv_bfloat162 r = __hmul2_rn(*(__nv_bfloat162*)&a, *(__nv_bfloat162*)&b); return *(uint32_t*)&r;
}
__device__ __forceinline__ uint32_t hadd2(uint32_t a, uint32_t b) {
  __nv_bfloat162 r = __hadd2_rn(*(__nv_bfloat162*)&a, *(__nv_bfloat162*)&b); return *(uint32_t*)&r;
}
__device__ __forceinline__ float2 cmul(float2 a, float2 b) { return make_float2(a.x * b.x - a.y * b.y, a.x * b.y + a.y * b.x); }
__device__ __forceinline__ float2 cfma(float2 a, float2 b, float2 c) {
  return make_float2(fmaf(a.x, b.x, fmaf(-a.y, b.y, c.x)), fmaf(a.x, b.y, fmaf(a.y, b.x, c.y)));
}
template <int N> __device__ __forceinline__ void fence_regs(float (&a)[N]) {
#pragma unroll
  for (int i = 0; i < N; i++) asm volatile("" : "+f"(a[i])::"memory");
}
__device__ __forceinline__ bool elect_one() {
  uint32_t e; asm volatile("{\n.reg .pred P;\nelect.sync _|P, 0xffffffff;\nselp.u32 %0, 1, 0, P;\n}\n" : "=r"(e)); return e != 0;
}
__device__ __forceinline__ int tid_opaque() { int t; asm volatile("mov.u32 %0, %%tid.x;" : "=r"(t)); return t; }
struct Role { int T1, GP, side, m2, dg, cch0; bool last, has2; };
__device__ __forceinline__ Role unpack_role(int x) {
  Role r; r.T1 = x & 15; r.GP = (x >> 4) & 7; r.side = (x >> 7) & 1; r.m2 = (x >> 8) & 63; r.dg = (x >> 14) & 3;
  r.has2 = (x >> 16) & 1; r.last = r.T1 == NT1 - 1; r.cch0 = 5 * (32 * r.dg + r.m2); return r;
}
__device__ __forceinline__ Role fresh_role(int x) { asm volatile("" : "+r"(x)); return unpack_role(__shfl_sync(0xffffffffu, x, 0)); }
#define ROLE(x) const Role R_ = fresh_role(x); const int T1 = R_.T1, GP = R_.GP, side = R_.side, m2 = R_.m2, dg = R_.dg, cch0 = R_.cch0; \
  const bool last = R_.last, has2 = R_.has2; (void)T1; (void)GP; (void)side; (void)m2; (void)dg; (void)cch0; (void)last; (void)has2;
__device__ __forceinline__ int n_to_t(int n) {
  int T = n / 160, nl = n - T * 160;
  int L = (T == NT1 - 1) ? 32 : 40;
  return T * 160 + L * ((nl & 7) >> 1) + 2 * (nl >> 3) + (nl & 1);
}

template<int TA> __device__ __forceinline__ void wgmma_n160(float (&d)[80], uint32_t alo, uint32_t ahi, uint32_t blo, uint32_t bhi){
  asm volatile("{\n.reg .b64 da, db;\nmov.b64 da, {%80,%81};\nmov.b64 db, {%82,%83};\n"
    "wgmma.mma_async.sync.aligned.m64n160k16.f32.bf16.bf16 {%0, %1, %2, %3, %4, %5, %6, %7, %8, %9, %10, %11, %12, %13, %14, %15, %16, %17, %18, %19, %20, %21, %22, %23, %24, %25, %26, %27, %28, %29, %30, %31, %32, %33, %34, %35, %36, %37, %38, %39, %40, %41, %42, %43, %44, %45, %46, %47, %48, %49, %50, %51, %52, %53, %54, %55, %56, %57, %58, %59, %60, %61, %62, %63, %64, %65, %66, %67, %68, %69, %70, %71, %72, %73, %74, %75, %76, %77, %78, %79}, da, db, 1, 1, 1, %84, 0;\n}\n"
    : "+f"(d[0]), "+f"(d[1]), "+f"(d[2]), "+f"(d[3]), "+f"(d[4]), "+f"(d[5]), "+f"(d[6]), "+f"(d[7]), "+f"(d[8]), "+f"(d[9]), "+f"(d[10]), "+f"(d[11]), "+f"(d[12]), "+f"(d[13]), "+f"(d[14]), "+f"(d[15]), "+f"(d[16]), "+f"(d[17]), "+f"(d[18]), "+f"(d[19]), "+f"(d[20]), "+f"(d[21]), "+f"(d[22]), "+f"(d[23]), "+f"(d[24]), "+f"(d[25]), "+f"(d[26]), "+f"(d[27]), "+f"(d[28]), "+f"(d[29]), "+f"(d[30]), "+f"(d[31]), "+f"(d[32]), "+f"(d[33]), "+f"(d[34]), "+f"(d[35]), "+f"(d[36]), "+f"(d[37]), "+f"(d[38]), "+f"(d[39]), "+f"(d[40]), "+f"(d[41]), "+f"(d[42]), "+f"(d[43]), "+f"(d[44]), "+f"(d[45]), "+f"(d[46]), "+f"(d[47]), "+f"(d[48]), "+f"(d[49]), "+f"(d[50]), "+f"(d[51]), "+f"(d[52]), "+f"(d[53]), "+f"(d[54]), "+f"(d[55]), "+f"(d[56]), "+f"(d[57]), "+f"(d[58]), "+f"(d[59]), "+f"(d[60]), "+f"(d[61]), "+f"(d[62]), "+f"(d[63]), "+f"(d[64]), "+f"(d[65]), "+f"(d[66]), "+f"(d[67]), "+f"(d[68]), "+f"(d[69]), "+f"(d[70]), "+f"(d[71]), "+f"(d[72]), "+f"(d[73]), "+f"(d[74]), "+f"(d[75]), "+f"(d[76]), "+f"(d[77]), "+f"(d[78]), "+f"(d[79])
    : "r"(alo), "r"(ahi), "r"(blo), "r"(bhi), "n"(TA));
}
template<int N> __device__ __forceinline__ void wgmma_rs_hi(float (&d)[64], uint32_t a0, uint32_t a1, uint32_t a2, uint32_t a3, uint32_t blo);
template<> __device__ __forceinline__ void wgmma_rs_hi<16>(float (&d)[64], uint32_t a0, uint32_t a1, uint32_t a2, uint32_t a3, uint32_t blo){
  asm volatile("{\n.reg .b64 db;\nmov.b64 db, {%12,8};\nwgmma.mma_async.sync.aligned.m64n16k16.f32.bf16.bf16 {%0, %1, %2, %3, %4, %5, %6, %7}, {%8,%9,%10,%11}, db, 1, 1, 1, 0;\n}\n"
    : "+f"(d[56]), "+f"(d[57]), "+f"(d[58]), "+f"(d[59]), "+f"(d[60]), "+f"(d[61]), "+f"(d[62]), "+f"(d[63])
    : "r"(a0), "r"(a1), "r"(a2), "r"(a3), "r"(blo));
}
template<> __device__ __forceinline__ void wgmma_rs_hi<32>(float (&d)[64], uint32_t a0, uint32_t a1, uint32_t a2, uint32_t a3, uint32_t blo){
  asm volatile("{\n.reg .b64 db;\nmov.b64 db, {%20,8};\nwgmma.mma_async.sync.aligned.m64n32k16.f32.bf16.bf16 {%0, %1, %2, %3, %4, %5, %6, %7, %8, %9, %10, %11, %12, %13, %14, %15}, {%16,%17,%18,%19}, db, 1, 1, 1, 0;\n}\n"
    : "+f"(d[48]), "+f"(d[49]), "+f"(d[50]), "+f"(d[51]), "+f"(d[52]), "+f"(d[53]), "+f"(d[54]), "+f"(d[55]), "+f"(d[56]), "+f"(d[57]), "+f"(d[58]), "+f"(d[59]), "+f"(d[60]), "+f"(d[61]), "+f"(d[62]), "+f"(d[63])
    : "r"(a0), "r"(a1), "r"(a2), "r"(a3), "r"(blo));
}
template<> __device__ __forceinline__ void wgmma_rs_hi<48>(float (&d)[64], uint32_t a0, uint32_t a1, uint32_t a2, uint32_t a3, uint32_t blo){
  asm volatile("{\n.reg .b64 db;\nmov.b64 db, {%28,8};\nwgmma.mma_async.sync.aligned.m64n48k16.f32.bf16.bf16 {%0, %1, %2, %3, %4, %5, %6, %7, %8, %9, %10, %11, %12, %13, %14, %15, %16, %17, %18, %19, %20, %21, %22, %23}, {%24,%25,%26,%27}, db, 1, 1, 1, 0;\n}\n"
    : "+f"(d[40]), "+f"(d[41]), "+f"(d[42]), "+f"(d[43]), "+f"(d[44]), "+f"(d[45]), "+f"(d[46]), "+f"(d[47]), "+f"(d[48]), "+f"(d[49]), "+f"(d[50]), "+f"(d[51]), "+f"(d[52]), "+f"(d[53]), "+f"(d[54]), "+f"(d[55]), "+f"(d[56]), "+f"(d[57]), "+f"(d[58]), "+f"(d[59]), "+f"(d[60]), "+f"(d[61]), "+f"(d[62]), "+f"(d[63])
    : "r"(a0), "r"(a1), "r"(a2), "r"(a3), "r"(blo));
}
template<> __device__ __forceinline__ void wgmma_rs_hi<64>(float (&d)[64], uint32_t a0, uint32_t a1, uint32_t a2, uint32_t a3, uint32_t blo){
  asm volatile("{\n.reg .b64 db;\nmov.b64 db, {%36,8};\nwgmma.mma_async.sync.aligned.m64n64k16.f32.bf16.bf16 {%0, %1, %2, %3, %4, %5, %6, %7, %8, %9, %10, %11, %12, %13, %14, %15, %16, %17, %18, %19, %20, %21, %22, %23, %24, %25, %26, %27, %28, %29, %30, %31}, {%32,%33,%34,%35}, db, 1, 1, 1, 0;\n}\n"
    : "+f"(d[32]), "+f"(d[33]), "+f"(d[34]), "+f"(d[35]), "+f"(d[36]), "+f"(d[37]), "+f"(d[38]), "+f"(d[39]), "+f"(d[40]), "+f"(d[41]), "+f"(d[42]), "+f"(d[43]), "+f"(d[44]), "+f"(d[45]), "+f"(d[46]), "+f"(d[47]), "+f"(d[48]), "+f"(d[49]), "+f"(d[50]), "+f"(d[51]), "+f"(d[52]), "+f"(d[53]), "+f"(d[54]), "+f"(d[55]), "+f"(d[56]), "+f"(d[57]), "+f"(d[58]), "+f"(d[59]), "+f"(d[60]), "+f"(d[61]), "+f"(d[62]), "+f"(d[63])
    : "r"(a0), "r"(a1), "r"(a2), "r"(a3), "r"(blo));
}
template<> __device__ __forceinline__ void wgmma_rs_hi<80>(float (&d)[64], uint32_t a0, uint32_t a1, uint32_t a2, uint32_t a3, uint32_t blo){
  asm volatile("{\n.reg .b64 db;\nmov.b64 db, {%44,8};\nwgmma.mma_async.sync.aligned.m64n80k16.f32.bf16.bf16 {%0, %1, %2, %3, %4, %5, %6, %7, %8, %9, %10, %11, %12, %13, %14, %15, %16, %17, %18, %19, %20, %21, %22, %23, %24, %25, %26, %27, %28, %29, %30, %31, %32, %33, %34, %35, %36, %37, %38, %39}, {%40,%41,%42,%43}, db, 1, 1, 1, 0;\n}\n"
    : "+f"(d[24]), "+f"(d[25]), "+f"(d[26]), "+f"(d[27]), "+f"(d[28]), "+f"(d[29]), "+f"(d[30]), "+f"(d[31]), "+f"(d[32]), "+f"(d[33]), "+f"(d[34]), "+f"(d[35]), "+f"(d[36]), "+f"(d[37]), "+f"(d[38]), "+f"(d[39]), "+f"(d[40]), "+f"(d[41]), "+f"(d[42]), "+f"(d[43]), "+f"(d[44]), "+f"(d[45]), "+f"(d[46]), "+f"(d[47]), "+f"(d[48]), "+f"(d[49]), "+f"(d[50]), "+f"(d[51]), "+f"(d[52]), "+f"(d[53]), "+f"(d[54]), "+f"(d[55]), "+f"(d[56]), "+f"(d[57]), "+f"(d[58]), "+f"(d[59]), "+f"(d[60]), "+f"(d[61]), "+f"(d[62]), "+f"(d[63])
    : "r"(a0), "r"(a1), "r"(a2), "r"(a3), "r"(blo));
}
template<> __device__ __forceinline__ void wgmma_rs_hi<96>(float (&d)[64], uint32_t a0, uint32_t a1, uint32_t a2, uint32_t a3, uint32_t blo){
  asm volatile("{\n.reg .b64 db;\nmov.b64 db, {%52,8};\nwgmma.mma_async.sync.aligned.m64n96k16.f32.bf16.bf16 {%0, %1, %2, %3, %4, %5, %6, %7, %8, %9, %10, %11, %12, %13, %14, %15, %16, %17, %18, %19, %20, %21, %22, %23, %24, %25, %26, %27, %28, %29, %30, %31, %32, %33, %34, %35, %36, %37, %38, %39, %40, %41, %42, %43, %44, %45, %46, %47}, {%48,%49,%50,%51}, db, 1, 1, 1, 0;\n}\n"
    : "+f"(d[16]), "+f"(d[17]), "+f"(d[18]), "+f"(d[19]), "+f"(d[20]), "+f"(d[21]), "+f"(d[22]), "+f"(d[23]), "+f"(d[24]), "+f"(d[25]), "+f"(d[26]), "+f"(d[27]), "+f"(d[28]), "+f"(d[29]), "+f"(d[30]), "+f"(d[31]), "+f"(d[32]), "+f"(d[33]), "+f"(d[34]), "+f"(d[35]), "+f"(d[36]), "+f"(d[37]), "+f"(d[38]), "+f"(d[39]), "+f"(d[40]), "+f"(d[41]), "+f"(d[42]), "+f"(d[43]), "+f"(d[44]), "+f"(d[45]), "+f"(d[46]), "+f"(d[47]), "+f"(d[48]), "+f"(d[49]), "+f"(d[50]), "+f"(d[51]), "+f"(d[52]), "+f"(d[53]), "+f"(d[54]), "+f"(d[55]), "+f"(d[56]), "+f"(d[57]), "+f"(d[58]), "+f"(d[59]), "+f"(d[60]), "+f"(d[61]), "+f"(d[62]), "+f"(d[63])
    : "r"(a0), "r"(a1), "r"(a2), "r"(a3), "r"(blo));
}
template<> __device__ __forceinline__ void wgmma_rs_hi<112>(float (&d)[64], uint32_t a0, uint32_t a1, uint32_t a2, uint32_t a3, uint32_t blo){
  asm volatile("{\n.reg .b64 db;\nmov.b64 db, {%60,8};\nwgmma.mma_async.sync.aligned.m64n112k16.f32.bf16.bf16 {%0, %1, %2, %3, %4, %5, %6, %7, %8, %9, %10, %11, %12, %13, %14, %15, %16, %17, %18, %19, %20, %21, %22, %23, %24, %25, %26, %27, %28, %29, %30, %31, %32, %33, %34, %35, %36, %37, %38, %39, %40, %41, %42, %43, %44, %45, %46, %47, %48, %49, %50, %51, %52, %53, %54, %55}, {%56,%57,%58,%59}, db, 1, 1, 1, 0;\n}\n"
    : "+f"(d[8]), "+f"(d[9]), "+f"(d[10]), "+f"(d[11]), "+f"(d[12]), "+f"(d[13]), "+f"(d[14]), "+f"(d[15]), "+f"(d[16]), "+f"(d[17]), "+f"(d[18]), "+f"(d[19]), "+f"(d[20]), "+f"(d[21]), "+f"(d[22]), "+f"(d[23]), "+f"(d[24]), "+f"(d[25]), "+f"(d[26]), "+f"(d[27]), "+f"(d[28]), "+f"(d[29]), "+f"(d[30]), "+f"(d[31]), "+f"(d[32]), "+f"(d[33]), "+f"(d[34]), "+f"(d[35]), "+f"(d[36]), "+f"(d[37]), "+f"(d[38]), "+f"(d[39]), "+f"(d[40]), "+f"(d[41]), "+f"(d[42]), "+f"(d[43]), "+f"(d[44]), "+f"(d[45]), "+f"(d[46]), "+f"(d[47]), "+f"(d[48]), "+f"(d[49]), "+f"(d[50]), "+f"(d[51]), "+f"(d[52]), "+f"(d[53]), "+f"(d[54]), "+f"(d[55]), "+f"(d[56]), "+f"(d[57]), "+f"(d[58]), "+f"(d[59]), "+f"(d[60]), "+f"(d[61]), "+f"(d[62]), "+f"(d[63])
    : "r"(a0), "r"(a1), "r"(a2), "r"(a3), "r"(blo));
}
template<> __device__ __forceinline__ void wgmma_rs_hi<128>(float (&d)[64], uint32_t a0, uint32_t a1, uint32_t a2, uint32_t a3, uint32_t blo){
  asm volatile("{\n.reg .b64 db;\nmov.b64 db, {%68,8};\nwgmma.mma_async.sync.aligned.m64n128k16.f32.bf16.bf16 {%0, %1, %2, %3, %4, %5, %6, %7, %8, %9, %10, %11, %12, %13, %14, %15, %16, %17, %18, %19, %20, %21, %22, %23, %24, %25, %26, %27, %28, %29, %30, %31, %32, %33, %34, %35, %36, %37, %38, %39, %40, %41, %42, %43, %44, %45, %46, %47, %48, %49, %50, %51, %52, %53, %54, %55, %56, %57, %58, %59, %60, %61, %62, %63}, {%64,%65,%66,%67}, db, 1, 1, 1, 0;\n}\n"
    : "+f"(d[0]), "+f"(d[1]), "+f"(d[2]), "+f"(d[3]), "+f"(d[4]), "+f"(d[5]), "+f"(d[6]), "+f"(d[7]), "+f"(d[8]), "+f"(d[9]), "+f"(d[10]), "+f"(d[11]), "+f"(d[12]), "+f"(d[13]), "+f"(d[14]), "+f"(d[15]), "+f"(d[16]), "+f"(d[17]), "+f"(d[18]), "+f"(d[19]), "+f"(d[20]), "+f"(d[21]), "+f"(d[22]), "+f"(d[23]), "+f"(d[24]), "+f"(d[25]), "+f"(d[26]), "+f"(d[27]), "+f"(d[28]), "+f"(d[29]), "+f"(d[30]), "+f"(d[31]), "+f"(d[32]), "+f"(d[33]), "+f"(d[34]), "+f"(d[35]), "+f"(d[36]), "+f"(d[37]), "+f"(d[38]), "+f"(d[39]), "+f"(d[40]), "+f"(d[41]), "+f"(d[42]), "+f"(d[43]), "+f"(d[44]), "+f"(d[45]), "+f"(d[46]), "+f"(d[47]), "+f"(d[48]), "+f"(d[49]), "+f"(d[50]), "+f"(d[51]), "+f"(d[52]), "+f"(d[53]), "+f"(d[54]), "+f"(d[55]), "+f"(d[56]), "+f"(d[57]), "+f"(d[58]), "+f"(d[59]), "+f"(d[60]), "+f"(d[61]), "+f"(d[62]), "+f"(d[63])
    : "r"(a0), "r"(a1), "r"(a2), "r"(a3), "r"(blo));
}

struct CvCtx {
  uint32_t kaddr, kvaddr, db0, dd, stg, zero;
  int src1, src2;
  bool s3, kodd, wrap;
};
template <int LO> __device__ __forceinline__ void cv_copy(float (&acc)[64]) {
#pragma unroll
  for (int i = LO; i < 64; i++) { float t; asm volatile("mov.b32 %0, %1;" : "=f"(t) : "f"(acc[i]) : "memory"); acc[i] = t; }
}
template <int G> __device__ __forceinline__ void cv_raw(uint32_t (&A)[4][4], uint32_t kaddr) {
#pragma unroll
  for (int i = 0; i < 4; i++) {
    const uint32_t a = kaddr + (4 * G + i) * 128;
    A[i][0] = lds32(a); A[i][1] = lds32(a + 4); A[i][3] = lds32(a + 8);
  }
}
__device__ __forceinline__ void cv_form(uint32_t (&A)[4][4]) {
#pragma unroll
  for (int i = 0; i < 4; i++) {
    asm volatile("prmt.b32 %0, %0, %1, 0x5432;" : "+r"(A[i][0]) : "r"(A[i][1]));
    asm volatile("prmt.b32 %0, %1, %2, 0x5432;" : "=r"(A[i][2]) : "r"(A[i][1]), "r"(A[i][3]));
  }
}
template <int J> __device__ __forceinline__ void cv_epi(const float (&acc)[64], float (&Ep)[2], const uint32_t (&so)[4], const CvCtx& c) {
  float E[4], o[2];
  const uint32_t kvw = lds32(c.kvaddr + J * 256);
  const int src1 = c.src1 | (kvw & c.zero);
#pragma unroll
  for (int x = 0; x < 4; x++) {
    const float ev = acc[8 * J + x], od = acc[8 * J + 4 + x], pv = J > 0 ? acc[J > 0 ? 8 * J - 4 + x : 0] : 0.f;
    const float send = c.kodd ? ev : (c.s3 ? pv : od);
    E[x] = (c.kodd ? od : ev) + __shfl_sync(0xffffffffu, send, src1);
  }
#pragma unroll
  for (int h = 0; h < 2; h++) {
    o[h] = E[2 * h] + __shfl_sync(0xffffffffu, c.wrap ? Ep[h] : E[2 * h + 1], c.src2);
    Ep[h] = E[2 * h + 1];
  }
  sts32(c.stg + ((J & 1) ? so[J >> 1] >> 16 : so[J >> 1] & 0xffff), hadd2(pack_bf16(o[0], o[1]), hmul2(__byte_perm(kvw, kvw, 0x1032), c.dd)));
}
template <int G> __device__ __forceinline__ void cv_rec(float (&acc)[64], uint32_t (&A)[4][4], float (&Ep)[2], const uint32_t (&so)[4], const CvCtx& c) {
  wgmma_fence();
#pragma unroll
  for (int i = 0; i < 4; i++) wgmma_rs_hi<128 - 16 * G>(acc, A[i][0], A[i][1], A[i][2], A[i][3], c.db0 - 4 * i);
  wgmma_commit();
  __syncwarp();
  uint32_t B[4][4];
  if constexpr (G < 7) cv_raw<G + 1>(B, c.kaddr);
  if constexpr (G > 0) cv_epi<G - 1>(acc, Ep, so, c);
  if constexpr (G < 7) cv_form(B);
  __syncwarp();
  wgmma_wait<0>();
  cv_copy<8 * G>(acc);
  if constexpr (G < 7) cv_rec<G + 1>(acc, B, Ep, so, c);
}
__device__ __forceinline__ uint32_t cv_stage(int slot) { return sb + (slot < 4 ? 40960 + slot * 4096 : 180224); }
__device__ __forceinline__ void cv_offsets(uint32_t (&so)[4]) {
  const int tid = tid_opaque() & 127, lane = tid & 31, r = lane >> 2, q = lane & 3;
  const int P = r < 4 ? q : 4 + ((q + 1) & 3);
  const int tb = 16 * (2 * P + ((r >> 1) & 1)) + 4 * (tid >> 5) + 2 * (r & 1);
#pragma unroll
  for (int J = 0; J < 8; J++) {
    const int t = 256 * J + tb, T = t / 160, tl = t - T * 160;
    const int qq = (T == NT1 - 1) ? (tl >> 5) : (tl / 40);
    int ck = 20 * T + ((tl - qq * ((T == NT1 - 1) ? 32 : 40)) >> 1);
    ck ^= (ck >> 3) & 7;
    const uint32_t o = ck * 16 + qq * 4;
    if (J & 1) so[J >> 1] |= o << 16; else so[J >> 1] = o;
  }
}
__device__ __forceinline__ void conv_channel(int slot, const uint32_t (&so)[4]) {
  const int tid = tid_opaque() & 127, w = tid >> 5, lane = tid & 31, r = lane >> 2, q = lane & 3;
  const int i_ = r >> 1, i0 = i_ & 1, i1 = i_ >> 1;
  const uint32_t cb = sb + CV_OFF + slot * CV_B;
  CvCtx c;
  c.dd = lds32(sb + EP_OFF + 4 * slot);
  c.kaddr = cb + CV_K - 32 + 4 * (8 * i_ + 2 * w + (r & 1) + 2 * q);
  c.db0 = desc_lo(cb + CV_U + 192, CV_PL);
  c.src1 = i1 == 0 ? (lane - q + 16 + ((q + 3) & 3)) : (lane - q - 16 + ((q + 1) & 3));
  c.s3 = (i1 == 1 && q == 3); c.kodd = (i1 == 1 && q < 3);
  const int P = i1 == 0 ? q : 4 + ((q + 1) & 3);
  const int Pm = (P + 7) & 7, qm = Pm < 4 ? Pm : ((Pm - 1) & 3);
  c.src2 = i0 == 1 ? lane - 8 : (16 * (Pm >> 2) + 8 + 4 * (r & 1) + qm);
  c.wrap = (i0 == 1 && P == 7);
  c.kvaddr = cb + CV_U + 192 + (1 - (r & 1)) * CV_PL + (2 * P + i0) * 16 + (3 - w) * 4;
  float acc[64], Ep[2] = {0.f, 0.f};
  uint32_t A[4][4];
  c.stg = cv_stage(slot);
#pragma unroll
  for (int i = 0; i < 64; i++) acc[i] = 0.f;
  mbar_wait(bars + 8 * (B_TAPS + slot));
  c.zero = lds32(cb);
  cv_raw<0>(A, c.kaddr);
  mbar_wait(bars + 8 * (B_CVFULL + slot));
  cv_form(A);
  cv_copy<0>(acc);
  cv_rec<0>(acc, A, Ep, so, c);
  cv_epi<7>(acc, Ep, so, c);
  fence_async_smem();
  mbar_arrive(bars + 8 * (B_CVDONE + slot));
}

template <int W> struct KvRegs { uint32_t k[19][W], v[16][W], s[W][4]; };
template <int W> __device__ __forceinline__ void kv_load(int m, int cl, KvRegs<W>& x) {
  const int lane = tid_opaque() & 31, tg = lane >> 3;
  const uint32_t pb = sb + KS_OFF + (cl >> 5) * KV_PIECE + 2 * (cl & 31) + 4 * W * (lane & 7);
  const uint32_t ka = pb + tg * 1216, va = pb + 4864 + tg * 1088 + 64;
  const uint32_t kh = (m == 0 && tg > 0) ? ka - 192 : ka;
#pragma unroll
  for (int c = 0; c < W; c++) {
    const float4 t = lds128f(sb + TAP_OFF + 8 * cl + 16 * (W * (lane & 7) + c));
    x.s[c][0] = __float_as_uint(t.x); x.s[c][1] = __float_as_uint(t.y); x.s[c][2] = __float_as_uint(t.z); x.s[c][3] = __float_as_uint(t.w);
  }
  mbar_wait(bars + 8 * (B_KV + (cl >> 5)));
#pragma unroll
  for (int i = 0; i < 19; i++) {
    const uint32_t a = (i < 3 ? kh : ka) + i * 64;
    if (W == 2) { float2 t = lds64f(a); x.k[i][0] = __float_as_uint(t.x); x.k[i][W - 1] = __float_as_uint(t.y); }
    else x.k[i][0] = lds32(a);
  }
#pragma unroll
  for (int i = 0; i < 16; i++) {
    if (W == 2) { float2 t = lds64f(va + i * 64); x.v[i][0] = __float_as_uint(t.x); x.v[i][W - 1] = __float_as_uint(t.y); }
    else x.v[i][0] = lds32(va + i * 64);
  }
}
template <int W> __device__ __forceinline__ void kv_finish(int m, int c0, KvRegs<W>& x) {
  const int lane = tid_opaque() & 31;
  uint8_t* dst = g_kv + ((c0 + 2 * W * (lane & 7)) * 4096 + (4 * m + (lane >> 3)) * 16);
#pragma unroll
  for (int c = 0; c < W; c++) {
    const uint32_t w0 = __byte_perm(x.s[c][0], x.s[c][2], 0x5410), w1 = __byte_perm(x.s[c][0], x.s[c][2], 0x7632);
    const uint32_t w2 = __byte_perm(x.s[c][1], x.s[c][3], 0x5410), w3 = __byte_perm(x.s[c][1], x.s[c][3], 0x7632);
#pragma unroll
    for (int i = 0; i < 16; i++) {
      uint32_t a = hmul2(x.k[i][c], w3);
      a = hadd2(a, hmul2(x.k[i + 1][c], w2)); a = hadd2(a, hmul2(x.k[i + 2][c], w1)); a = hadd2(a, hmul2(x.k[i + 3][c], w0));
      x.v[i][c] = hmul2(a, x.v[i][c]);
    }
#pragma unroll
    for (int e = 0; e < 2; e++)
#pragma unroll
      for (int f = 0; f < 2; f++) {
        uint32_t o[4];
#pragma unroll
        for (int qq = 0; qq < 4; qq++) o[qq] = __byte_perm(x.v[15 - 4 * qq - 2 * f][c], x.v[14 - 4 * qq - 2 * f][c], e ? 0x7632 : 0x5410);
        *(uint4*)(dst + (2 * c + e) * 4096 + f * 2048) = make_uint4(o[0], o[1], o[2], o[3]);
      }
  }
}
__device__ __forceinline__ void stat_table(int T1, unsigned want, int l) {
#pragma unroll 1
  for (int n = tid_opaque() & 127; n < (T1 == NT1 - 1 ? 128 : 160); n += 128) {
    const uint4* rp = &g_stats[(160 * T1 + n) * 8];
    float a[4], b[4];
    uint32_t it = 0;
    while (true) {
      bool ok = true;
#pragma unroll
      for (int i = 0; i < 4; i++) ok &= (rec_ld(rp + 2 * i, a[i], b[i]) == want);
      if (ok) break;
      if (++it > SPIN_LIMIT) soft_trap();
    }
    const float m = 0.25f * ((a[0] + a[1]) + (a[2] + a[3]));
    float v = (b[0] + b[1]) + (b[2] + b[3]);
#pragma unroll
    for (int i = 0; i < 4; i++) v = fmaf(160.f * (a[i] - m), a[i] - m, v);
    const float rs = rsqrtf(v * (1.f / 640.f) + 1e-5f);
    sts64f(sb + STAB_OFF + n * 8, rs, -m * rs);
  }
  mbar_arrive(bars + 8 * (B_STAB + l));
  __syncwarp();
}

template <bool FIRST>
__device__ __forceinline__ void stats_publish(int which, int n0, int dg, unsigned tag, const float (&acc)[80]) {
  const int lane = tid_opaque() & 31, q = lane & 3;
  float sh[2] = {0.f, 0.f};
  if (FIRST) { sh[0] = __shfl_sync(0xffffffffu, acc[0], lane & ~3); sh[1] = __shfl_sync(0xffffffffu, acc[2], lane & ~3); }
  float s1[2] = {0.f, 0.f}, s2[2] = {0.f, 0.f}, t1[2] = {0.f, 0.f}, t2[2] = {0.f, 0.f};
#pragma unroll
  for (int j = 0; j < 20; j++)
#pragma unroll
    for (int h = 0; h < 2; h++) {
      float a = acc[4 * j + 2 * h], b = acc[4 * j + 2 * h + 1];
      if (FIRST) { a -= sh[h]; b -= sh[h]; }
      s1[h] += a; t1[h] += b; s2[h] = fmaf(a, a, s2[h]); t2[h] = fmaf(b, b, t2[h]);
    }
#pragma unroll
  for (int h = 0; h < 2; h++) {
    s1[h] += t1[h]; s2[h] += t2[h];
    s1[h] += __shfl_xor_sync(0xffffffffu, s1[h], 1); s2[h] += __shfl_xor_sync(0xffffffffu, s2[h], 1);
    s1[h] += __shfl_xor_sync(0xffffffffu, s1[h], 2); s2[h] += __shfl_xor_sync(0xffffffffu, s2[h], 2);
  }
  if (FIRST || (q & 1) == (which & 1)) {
    const int h = q >> 1;
    float a = h ? s1[1] : s1[0], b = h ? s2[1] : s2[0], c = h ? sh[1] : sh[0];
    float mean = a * (1.f / 160.f);
    rec_st(&g_stats[((n0 + 8 * h) * 4 + dg) * 2 + (q & 1)], mean + c, fmaxf(b - a * mean, 0.f), 4 * tag + which);
  }
}
__device__ __forceinline__ void stats_combine(float mi, float m2, float& mean, float& rstd) {
  float m = mi + __shfl_xor_sync(0xffffffffu, mi, 1);
  m += __shfl_xor_sync(0xffffffffu, m, 2);
  m *= 0.25f;
  float d = mi - m;
  float v = fmaf(160.f * d, d, m2);
  v += __shfl_xor_sync(0xffffffffu, v, 1);
  v += __shfl_xor_sync(0xffffffffu, v, 2);
  mean = m; rstd = rsqrtf(v * (1.f / 640.f) + 1e-5f);
}
__device__ __forceinline__ void stats_get(int which, int n0, unsigned tag, float (&mean)[2], float (&rstd)[2]) {
  const int q = tid_opaque() & 3;
  const uint4* p0 = &g_stats[(n0 * 4 + q) * 2 + (which & 1)];
  float a0, b0, a1, b1;
  uint32_t it = 0;
  tag = 4 * tag + which;
  while (true) {
    unsigned t0 = rec_ld(p0, a0, b0), t1 = rec_ld(p0 + 64, a1, b1);
    if (t0 == tag && t1 == tag) break;
    if (++it > SPIN_LIMIT) soft_trap();
  }
  __syncwarp();
  stats_combine(a0, b0, mean[0], rstd[0]);
  stats_combine(a1, b1, mean[1], rstd[1]);
}
__device__ __forceinline__ void x0_load(float (&acc)[80]) {
  const int t = tid_opaque() & 127;
  const uint32_t xa = sb + XT_OFF + (16 * (t >> 5) + ((t & 31) >> 2)) * 320 + 8 * (t & 3);
  mbar_wait(bars + 8 * B_XT);
#pragma unroll
  for (int h = 0; h < 2; h++)
#pragma unroll
    for (int J = 0; J < 10; J++) {
      const float2 v = lds64f(xa + h * 2560 + 32 * J);
      const uint32_t x = __float_as_uint(v.x), y = __float_as_uint(v.y);
      acc[8 * J + 2 * h] = bf_lo(x); acc[8 * J + 2 * h + 1] = bf_hi(x);
      acc[8 * J + 4 + 2 * h] = bf_lo(y); acc[8 * J + 4 + 2 * h + 1] = bf_hi(y);
    }
}

__global__ void __launch_bounds__(512, 1) fused_kernel(const __grid_constant__ Params p) {
  extern __shared__ __align__(1024) uint8_t smem_raw[];
  const int tid = threadIdx.x, lane = tid & 31;
  const int wid = __shfl_sync(0xffffffffu, tid >> 5, 0), wg = wid >> 2;
  unsigned smid; asm volatile("mov.u32 %0, %%smid;" : "=r"(smid));
  if (smid >= 132 || smem_u32(smem_raw) != sb) soft_trap();
  int role;
  {
  const int side = smid & 1;
  int gpc, gi;
  {
    int tpc = smid >> 1;
    if (tpc < 32) { gpc = tpc & 7; gi = tpc >> 3; }
    else if (tpc < 60) { gpc = 1 + (tpc - 32) % 7; gi = 4 + (tpc - 32) / 7; }
    else if (tpc < 62) { gpc = tpc - 54; gi = 8; }
    else { gpc = 0; gi = tpc - 58; }
  }
  const int pos = 8 * gpc + gi + (gpc == 7 ? 1 : 0);
  if (pos == 65) {
    if (tid < 32) {
      const unsigned tag = ld_rlx(g_epoch);
      for (int i = lane; i < NT1 * 16; i += 32)
        if ((i & 15) < 10) { uint32_t it = 0; while ((int)(ld_rlx(&g_hflag[(i >> 4) * 32 + (i & 15)]) - tag) < 0) { __nanosleep(500); if (++it > SPIN_LIMIT) soft_trap(); } }
    }
    return;
  }
  int T1, GP;
  if (pos < 52) { int hh = pos / 26, x = pos - 26 * hh; T1 = x >> 1; GP = 2 * hh + (x & 1); }
  else { T1 = pos - 52; GP = 4; }
  const bool last = (T1 == NT1 - 1);
  const bool has2 = gi < 8;
  const int m2 = 8 * (gpc >> 1) + gi, dg = 2 * (gpc & 1) + side;
  role = T1 | (GP << 4) | (side << 7) | (m2 << 8) | (dg << 14) | ((int)has2 << 16);

  const int cch0 = 5 * (32 * dg + m2);
  if (wg < 2) {
    if (wid < 2) {
      const int ch = 128 * GP + 64 * wid + 32 * side + lane;
      uint32_t r0 = ldv16(p.lre + ch), r1 = ldv16(p.lim + ch), r2 = ldv16(p.logdt + ch);
      asm volatile("bar.arrive 5, 512;" : "+r"(r0), "+r"(r1), "+r"(r2)::"memory");
      const float lr = bf_lo(r0), li = bf_lo(r1), ld = bf_lo(r2);
      const float dt = __bfloat162float(__float2bfloat16_rn(expf(ld)));
      const float mag = expf(dt * lr);
      float sn, cs; sincosf(dt * li, &sn, &cs);
      const float ar = mag * cs, ai = mag * sn;
      const float inv = 2.f / (lr * lr + li * li);
      const uint32_t ad = sb + CTAB_OFF + (32 * wid + lane) * 24;
      sts64f(ad, ar, ai);
      sts64f(ad + 8, ((ar - 1.f) * lr + ai * li) * inv, (ai * lr - (ar - 1.f) * li) * inv);
      if (tid == 0) TS(46);
      __syncwarp();
      bar_sync(7, 96);
      mbar_arrive(bars + 8 * B_CTAB);
    } else {
      if (elect_one()) {
        if (wid < 5) {
#pragma unroll
          for (int i = 0; i < 27; i++) mbar_init(bars + 8 * (4 + 27 * (wid - 2) + i), 2);
        } else {
#pragma unroll
          for (int i = 0; i < 15; i++) mbar_init(bars + 8 * (85 + 15 * (wid - 5) + i), 1);
        }
        asm volatile("fence.mbarrier_init.release.cluster;" ::: "memory");
      }
      __syncwarp();
      bar_sync(5, 512);
      if (wid == 2) { asm volatile("bar.arrive 6, 64;" ::: "memory"); asm volatile("bar.arrive 7, 96;" ::: "memory"); }
    }
  } else if (wg == 2 || wid == 14) {
    uint2 bv[2][5];
    const int c = wid == 14 ? 4 : wid - 8;
    const unsigned tag0 = ld_rlx(g_epoch);
#pragma unroll
    for (int x = 0; x < 2; x++)
#pragma unroll
      for (int i = 0; i < 5; i++) bv[x][i] = ldv64((const uint2*)((x ? p.bim : p.bre) + (has2 ? cch0 + c : 0) * DM) + lane + 32 * i);
    bar_sync(5, 512);
#pragma unroll
    for (int i = 0; i < 5; i++) asm volatile("" : "+r"(bv[0][i].x), "+r"(bv[0][i].y), "+r"(bv[1][i].x), "+r"(bv[1][i].y)::"memory");
    if (has2) {
      float sv[2];
#pragma unroll
      for (int x = 0; x < 2; x++) {
        float a = 0.f;
#pragma unroll
        for (int i = 0; i < 5; i++) a += (bf_lo(bv[x][i].x) + bf_hi(bv[x][i].x)) + (bf_lo(bv[x][i].y) + bf_hi(bv[x][i].y));
        sv[x] = a;
      }
#pragma unroll
      for (int o = 16; o > 0; o >>= 1) { sv[0] += __shfl_xor_sync(0xffffffffu, sv[0], o); sv[1] += __shfl_xor_sync(0xffffffffu, sv[1], o); }
      if (lane < 2) rec_st(&g_sB[(cch0 + c) * 2 + lane], sv[0], sv[1], tag0);
      if (tid == 256) TS(47);
    }
  } else if (wid == 13) {
    uint4 tv[3];
    const uint32_t e0 = ld_rlx(g_epoch);
    uint32_t e1 = ldv16(p.ssmD + min(cch0 + lane, 639));
    const uint4 dv = ldv128((const uint4*)(p.dskip + 160 * dg) + min(lane, 19));
#pragma unroll
    for (int i = 0; i < 3; i++) tv[i] = ldv128((const uint4*)(p.shiftk + 640 * dg) + min(lane + 32 * i, 79));
    bar_sync(5, 512);
    asm volatile("" : "+r"(e1)::"memory");
    sts128(sb + DTAB_OFF + 16 * min(lane, 19), dv);
#pragma unroll
    for (int i = 0; i < 3; i++) sts128(sb + TAP_OFF + 16 * min(lane + 32 * i, 79), tv[i]);
    if (lane < 6) sts32(sb + EP_OFF + 4 * lane, lane < 5 ? e1 | (e1 << 16) : e0);
    mbar_arrive(bars + 8 * B_CTAB);
    __syncwarp();
    if (lane == 0) { mbar_arrive(bars + 8 * B_EP); TS(53); }
  } else if (wid == 12) {
    if (elect_one()) {
#pragma unroll
      for (int k = 0; k < S1; k++) mbar_init(bars + 8 * (B_G1FULL + k), 1);
#pragma unroll
      for (int k = 0; k < 16; k++) mbar_init(bars + 8 * (B_XT + k), 1);
      asm volatile("fence.mbarrier_init.release.cluster;" ::: "memory");
      TS(45);
    }
    __syncwarp();
    asm volatile("bar.arrive 5, 512;" ::: "memory");
    if (elect_one()) {
#pragma unroll 1
      for (int k = 0; k < S1; k++) {
        const uint32_t fb = bars + 8 * (B_G1FULL + k);
        mbar_expect_tx(fb, G1_STAGE);
        tma4(sb + k * G1_STAGE + G1_XOFF, last ? &p.mXl : &p.mX, 64 * k, 0, 0, last ? 0 : 80 * T1, fb);
        tma5(sb + k * G1_STAGE, &p.mB, 64 * k, 0, 0, 4 * side, 2 * GP, fb);
      }
      TS(44);
    }
    __syncwarp();
    bar_sync(6, 64);
  } else {
    if (elect_one()) {
#pragma unroll
      for (int i = 0; i < 9; i++) mbar_init(bars + 8 * (B_CVDONE + i), 128);
      asm volatile("fence.mbarrier_init.release.cluster;" ::: "memory");
    }
    __syncwarp();
    bar_sync(5, 512);
  }
  if (tid == 128) TS(0);
  }

  if (wg == 3) {
    asm volatile("setmaxnreg.dec.sync.aligned.u32 56;");
    ROLE(role)
    const int pw = wid & 3;
    if (pw == 3 && has2) {
      mbar_wait(bars + 8 * (B_G1FULL + 0));
      if (elect_one()) {
        mbar_expect_tx(bars + 8 * B_XT, 20480);
#pragma unroll
        for (int h = 0; h < 2; h++) {
          const int ng = 8 * m2 + 4 * h, T = ng / 20;
          tma4(sb + XT_OFF + h * 10240, T == NT1 - 1 ? &p.mXtl : &p.mXt, 160 * dg, 0, 0, T == NT1 - 1 ? ng - 240 : ng + 60 * T, bars + 8 * B_XT);
        }
      }
#pragma unroll 1
      for (int c = 0; c < 5; c++) {
        mbar_wait(bars + 8 * (c == 0 ? B_G1FULL + 2 : B_XT + (c < 2 ? 0 : c - 1)));
        if (elect_one()) {
          const uint32_t fb = bars + 8 * (B_KV + c);
          mbar_expect_tx(fb, KV_PIECE);
          tma3(sb + KS_OFF + c * KV_PIECE, &p.mK, 160 * dg + 32 * c, 64 * m2 - 3, 0, fb);
          tma3(sb + KS_OFF + c * KV_PIECE + 4864, &p.mV, 160 * dg + 32 * c, 64 * m2 - 1, 0, fb);
        }
      }
    }
    unsigned tag = 0;
    if (pw > 0) { mbar_wait(bars + 8 * B_EP); tag = lds32(sb + EP_OFF + 20); }
    if (pw == 2) {
#pragma unroll 1
      for (int i = 0; i < 2; i++) {
        float a, b;
        rec_poll(&g_sB[(128 * GP + 64 * i + 32 * side + lane) * 2], tag, a, b);
        sts64f(sb + CTAB_OFF + (32 * i + lane) * 24 + 16, a, b);
      }
      mbar_arrive(bars + 8 * B_CTAB);
      if (lane == 0) TS(54);
    }
    if (pw >= 2 && has2) {
      KvRegs<1> x;
      kv_load<1>(m2, 128 + 16 * (pw - 2), x);
      kv_finish<1>(m2, 160 * dg + 128 + 16 * (pw - 2), x);
      if (tid == 448) TS(51);
      bar_sync(3, 192);
      if (tid == 448) { mbar_arrive(bars + 8 * B_PREP); red_rel(&g_kvcnt[dg * 32], 1); TS(30); }
      __syncwarp();
    }
    if (pw == 0) {
      if (elect_one()) {
#pragma unroll 1
        for (int l = 0; l < 2; l++) {
          const uint32_t fb0 = bars + 8 * (B_G1FULL + 10 * l), wb = bars + 8 * (B_G1DONE + 9 * l - S1);
          const uint32_t free0 = bars + 8 * (has2 ? B_G2DONE + 19 : B_G1DONE + 9);
          uint32_t dst = sb;
#pragma unroll 1
          for (int k = l == 0 ? S1 : 0; k < 10; k++) {
            mbar_wait(k >= S1 + l ? wb + 8 * k : free0);
            mbar_expect_tx(fb0 + 8 * k, 16384);
            tma5(dst, &p.mB, 64 * k, 0, 0, 4 * side, 2 * GP, fb0 + 8 * k);
            dst += G1_STAGE; if (dst == sb + (S1 + l) * G1_STAGE) dst = sb;
          }
          if (has2) {
            const uint32_t fb2 = bars + 8 * (B_G2FULL + 20 * l), wb2 = bars + 8 * (B_G2DONE + 19 * l - 6);
            dst = sb + G2_WOFF;
            int kc = 0;
#pragma unroll 1
            for (int k = 0; k < 20; k++) {
              mbar_wait(k >= 6 + l ? wb2 + 8 * k : (k == 5 ? bars + 8 * B_XFREE : bars + 8 * (B_G1DONE + 10 * l + 9)));
              mbar_expect_tx(fb2 + 8 * k, G2_WB);
              tma5(dst, &p.mCre + (k & 1), kc, 0, 0, 0, 10 * dg, fb2 + 8 * k);
              kc += (k & 1) << 7; if (k == 9) kc = 64;
              dst += G2_WB; if (dst == sb + G2_WOFF + (6 + l) * G2_WB) dst = sb + G2_WOFF;
            }
          }
        }
      }
    } else if (pw == 1) {
#pragma unroll 1
      for (int l = 0; l < 2; l++) {
        if (l == 0) {
          if (elect_one()) {
            uint32_t dst = sb + G1_XOFF;
#pragma unroll 1
            for (int k = S1; k < 10; k++) {
              mbar_wait(bars + 8 * (B_G1DONE + k - S1));
              mbar_expect_tx(bars + 8 * (B_G1FULL + k), 20480);
              tma4(dst, last ? &p.mXl : &p.mX, 64 * k, 0, 0, last ? 0 : 80 * T1, bars + 8 * (B_G1FULL + k));
              dst += G1_STAGE; if (k == 2 * S1 - 1) dst = sb + G1_XOFF;
            }
          }
        } else {
          mbar_wait(bars + 8 * (has2 ? B_G2DONE + 19 : B_G1DONE + 9));
          const int mlo = (160 * T1) >> 6, nf = last ? 8 : 12;
          if (lane < nf) flag_poll(&g_uflag[4 * mlo + lane], tag);
          __syncwarp();
          fence_async_global();
          if (elect_one()) {
            TS(20);
            const int bytes = last ? 16384 : 20480;
            const uint8_t* src = g_u + T1 * 204800;
            uint32_t dst = sb + G1_XOFF;
#pragma unroll 1
            for (int k = 0; k < 10; k++) {
              if (k > S1) mbar_wait(bars + 8 * (B_G1DONE + 9 - S1 + k));
              mbar_expect_tx(bars + 8 * (B_G1FULL + 10 + k), bytes);
              bulk_g2s(dst, src, bytes, bars + 8 * (B_G1FULL + 10 + k));
              src += 20480; dst += G1_STAGE; if (k == S1) dst = sb + G1_XOFF;
            }
          }
        }
        __syncwarp();
        if (has2) {
          mbar_wait(bars + 8 * (B_G1DONE + 10 * l + 9));
          const int Tlo = (64 * m2) / 160, Thi = (64 * m2 + 63) / 160;
          if ((lane & 15) < 10) flag_poll(&g_hflag[((l * NT1 + (lane < 16 ? Tlo : Thi)) * 2) * 16 + (lane & 15)], tag);
          __syncwarp();
          fence_async_global();
          if (elect_one()) {
            TS(21 + 2 * l);
            const uint32_t fb2 = bars + 8 * (B_G2FULL + 20 * l), wb2 = bars + 8 * (B_G2DONE + 18 * l - SX2);
            const uint8_t* src = g_h + (l * 32 + m2) * 163840;
            uint32_t dst = sb;
#pragma unroll 1
            for (int k = 0; k < 20; k++) {
              if (k >= SX2 + 2 * l) mbar_wait(wb2 + 8 * k);
              if (k == 10) { mbar_wait(bars + 8 * (B_H1 + l)); fence_async_global(); }
              mbar_expect_tx(fb2 + 8 * k, G2_XB);
              bulk_g2s(dst, src, G2_XB, fb2 + 8 * k);
              src += 8192; dst += G2_XB; if (dst == sb + (SX2 + 2 * l) * G2_XB) dst = sb;
            }
          }
          __syncwarp();
        }
      }
    } else if (pw == 2) {
      if (has2) {
#pragma unroll 1
        for (int c = 0; c < 5; c++) {
          mbar_wait(bars + 8 * (B_CVDONE + c));
          if (elect_one()) {
            bulk_s2g(g_G + (size_t)(cch0 + c) * 4096, cv_stage(c), 4096);
            asm volatile("cp.async.bulk.commit_group;" ::: "memory");
            if (c == 4) {
              asm volatile("cp.async.bulk.wait_group 0;" ::: "memory");
              fence_async_global();
              red_rel(&g_gcnt[dg * 32], 1);
            }
          }
        }
      }
    } else if (has2) {
      mbar_wait(bars + 8 * B_PREP);
#pragma unroll
      for (int c = 0; c < 5; c++) {
        const uint32_t cb = sb + CV_OFF + c * CV_B;
        const uint32_t a = lane < 8 ? cb + 16 * lane : (lane < 20 ? cb + CV_U + 16 * (lane - 8) : cb + CV_U + CV_PL + 16 * (lane - 20));
        asm volatile("st.shared.v4.u32 [%0], {%1,%1,%1,%1};" ::"r"(a), "r"(0) : "memory");
      }
      fence_async_smem();
      __syncwarp();
#pragma unroll 1
      for (int c = 0; c < 5; c++) {
        if (c >= 2) mbar_wait(bars + 8 * (B_TAPS + c - 2));
        if (elect_one()) {
          mbar_expect_tx(bars + 8 * (B_TAPS + c), 4096);
          bulk_g2s(sb + CV_OFF + c * CV_B + CV_K, p.ssmk + (size_t)(cch0 + c) * SEQ, 4096, bars + 8 * (B_TAPS + c));
        }
      }
      if (elect_one()) {
        asm volatile("prefetch.tensormap [%0];" ::"l"(&p.mCre) : "memory");
        asm volatile("prefetch.tensormap [%0];" ::"l"(&p.mCim) : "memory");
        asm volatile("prefetch.tensormap [%0];" ::"l"(&p.mG) : "memory");
      }
      flag_poll(&g_kvcnt[dg * 32], tag * 32);
      __syncwarp();
      fence_async_global();
      if (lane == 0) TS(28);
      if (elect_one()) {
#pragma unroll
        for (int c = 0; c < 5; c++) {
          const uint32_t fb = bars + 8 * (B_CVFULL + c), cb = sb + CV_OFF + c * CV_B + CV_U + 192;
          mbar_expect_tx(fb, 4096);
          bulk_g2s(cb, g_kv + (size_t)(cch0 + c) * 4096, 2048, fb);
          bulk_g2s(cb + CV_PL, g_kv + (size_t)(cch0 + c) * 4096 + 2048, 2048, fb);
        }
      }
      const unsigned* hf = &g_hflag[((lane < 16 ? (64 * m2) / 160 : (64 * m2 + 63) / 160) * 2 + 1) * 16 + min(lane & 15, 9)];
      mbar_wait(bars + 8 * (B_CVDONE + 0));
      if (elect_one()) { l2_prefetch(p.cre + (size_t)cch0 * DM, 6400); l2_prefetch(p.cim + (size_t)cch0 * DM, 6400); }
      flag_poll(hf, tag);
      __syncwarp();
      if (lane == 0) { mbar_arrive(bars + 8 * B_H1); TS(22); }
      flag_poll(&g_gcnt[dg * 32], tag * 32);
      __syncwarp();
      fence_async_global();
      if (lane == 0) TS(29);
      if (elect_one()) {
        mbar_expect_tx(bars + 8 * B_GFULL, 20480);
        tma5(sb + G_OFF, &p.mG, 64 * m2, 0, 0, 0, 10 * dg, bars + 8 * B_GFULL);
      }
      mbar_wait(bars + 8 * (B_G1DONE + 19));
      flag_poll(hf + NT1 * 32, tag);
      __syncwarp();
      if (lane == 0) { mbar_arrive(bars + 8 * (B_H1 + 1)); TS(24); }
    }
  } else {
    asm volatile("setmaxnreg.inc.sync.aligned.u32 152;");
    const int w = wid & 3;
    mbar_wait(bars + 8 * B_EP);
    const unsigned tag = lds32(sb + EP_OFF + 20);
    if (wg == 2) {
      ROLE(role)
      if (has2) {
        const int n0 = 64 * m2 + 16 * w + (lane >> 2);
        KvRegs<2> x;
        {
          float xs[80];
          x0_load(xs);
          stats_publish<true>(0, n0, dg, tag, xs);
        }
        if (tid == 256) TS(31);
        kv_load<2>(m2, 32 * w, x);
        if (tid == 352) TS(50);
        kv_finish<2>(m2, 160 * dg + 32 * w, x);
        if (tid == 352) TS(52);
        asm volatile("bar.arrive 3, 192;" ::: "memory");
      } else if (tid == 256) mbar_arrive(bars + 8 * B_PREP);
      stat_table(T1, 4 * tag, 0);
      if (tid == 256) TS(26);
      if (!has2) { mbar_wait(bars + 8 * (B_G1FULL + 10)); stat_table(T1, 4 * tag + 2, 1); }
    }
#pragma unroll 1
    for (int l = 0; l < 2; l++) {
      if (wg < 2) {
        float acc[80];
#pragma unroll
        for (int i = 0; i < 80; i++) acc[i] = 0.f;
        ROLE(role)
        const int tid = tid_opaque(), r = (tid & 31) >> 2, q = tid & 3;
        const int ch = 128 * GP + 64 * wg + 32 * side + 8 * w + r;
        fence_regs(acc);
        {
          uint32_t alo = desc_lo(sb, 16) + wg * 512, blo = l == 0 ? desc_lo(sb + G1_XOFF, 16) : desc_lo(sb + G1_XOFF, 128);
          const uint32_t bhi = l == 0 ? desc_hi(1024, 1) : desc_hi(1024, 0), xstep = l == 0 ? 2 : 16;
          const uint32_t aend = desc_lo(sb, 16) + (S1 + l) * (G1_STAGE >> 4);
          uint32_t fb = bars + 8 * (B_G1FULL + 10 * l);
          mbar_wait(fb);
          if (tid == 0) TS(1 + 8 * l);
#pragma unroll 1
          for (int k = 0; k < 10; k++) {
            uint32_t ok; const uint32_t nb = k < 9 ? fb + 8 : fb;
            wgmma_fence();
#pragma unroll
            for (int kk = 0; kk < 4; kk++) {
              wgmma_n160<0>(acc, alo + kk * 2, desc_hi(1024, 1), blo + kk * xstep, bhi);
              if (kk == 0) ok = mbar_test(nb);
            }
            wgmma_commit();
            alo += G1_STAGE >> 4; blo += G1_STAGE >> 4;
            if (alo >= aend) { alo -= (S1 + l) * (G1_STAGE >> 4); blo -= (S1 + l) * (G1_STAGE >> 4); }
            if (k > 0) { wgmma_wait<1>(); if ((tid & 127) == 0) mbar_arrive(fb + 8 * (B_G1DONE - B_G1FULL - 1)); }
            if (!ok) mbar_wait(nb);
            if (l == 0 && k == PAUSE_K) { if (tid == 0) TS(48); mbar_wait(bars + 8 * B_PREP); if (tid == 0) TS(49); }
            fb += 8;
          }
        }
        mbar_wait(bars + 8 * B_CTAB);
        const uint32_t ca = sb + CTAB_OFF + (32 * wg + 8 * w + r) * 24;
        float2 lam = lds64f(ca), sB = lds64f(ca + 16);
        const float2 coef = lds64f(ca + 8), lamc = make_float2(lam.x, -lam.y);
        float m00 = coef.x, m01 = -coef.y, m10 = -coef.y, m11 = -coef.x;
        if (p.swap) { lam = lamc; sB = make_float2(sB.y, sB.x); m00 = -coef.y; m01 = coef.x; m10 = -coef.x; m11 = -coef.y; }
        float2 pL, p2L, pLq, p160q, p640;
        {
          float2 p2 = cmul(lam, lam), p4 = cmul(p2, p2), p8 = cmul(p4, p4), p16 = cmul(p8, p8), p32 = cmul(p16, p16);
          float2 p40 = cmul(p32, p8), p80 = cmul(p40, p40), p160 = cmul(p80, p80), p320 = cmul(p160, p160);
          p640 = cmul(p320, p320);
          pL = last ? p32 : p40;
          p2L = cmul(pL, pL);
          const float2 one = make_float2(1.f, 0.f);
          pLq = cmul((q & 1) ? pL : one, (q & 2) ? p2L : one);
          p160q = cmul((q & 1) ? p160 : one, (q & 2) ? p320 : one);
        }
        mbar_wait(bars + 8 * (B_STAB + l));
        wgmma_wait<0>();
        fence_regs(acc);
        if ((tid & 127) == 0) { mbar_arrive(bars + 8 * (B_G1DONE + 10 * l + 9)); if (wg == 0) TS(2 + 8 * l); }
        float2 e = make_float2(0.f, 0.f), snap = e;
#pragma unroll
        for (int j = 0; j < 20; j++) {
          const float4 st = lds128f(sb + STAB_OFF + (8 * j + 2 * q) * 8);
          acc[4 * j + 0] = fmaf(acc[4 * j + 0], st.x, st.y * sB.x);
          acc[4 * j + 2] = fmaf(acc[4 * j + 2], st.x, st.y * sB.y);
          acc[4 * j + 1] = fmaf(acc[4 * j + 1], st.z, st.w * sB.x);
          acc[4 * j + 3] = fmaf(acc[4 * j + 3], st.z, st.w * sB.y);
          e = cfma(lam, e, make_float2(acc[4 * j + 0], acc[4 * j + 2]));
          e = cfma(lam, e, make_float2(acc[4 * j + 1], acc[4 * j + 3]));
          if (j == 15) snap = e;
        }
        if (last) e = snap;
        {
          float2 v = make_float2(__shfl_up_sync(0xffffffffu, e.x, 1, 4), __shfl_up_sync(0xffffffffu, e.y, 1, 4));
          if (q >= 1) e = cfma(pL, v, e);
          v = make_float2(__shfl_up_sync(0xffffffffu, e.x, 2, 4), __shfl_up_sync(0xffffffffu, e.y, 2, 4));
          if (q >= 2) e = cfma(p2L, v, e);
        }
        if (!last && (q == 3 || (q == 2 && l == 0))) rec_st(&g_E[(T1 * DM + ch) * 2 + (q == 3 ? l : 1)], e.x, e.y, q == 3 ? tag : tag - 1);
        if (tid == 0) TS(3 + 8 * l);
        float2 ex = make_float2(__shfl_up_sync(0xffffffffu, e.x, 1, 4), __shfl_up_sync(0xffffffffu, e.y, 1, 4));
        if (q == 0) ex = make_float2(0.f, 0.f);
#pragma unroll
        for (int j = 0; j < 20; j++)
#pragma unroll
          for (int x = 0; x < 2; x++) {
            const float b0 = acc[4 * j + x], b1 = acc[4 * j + 2 + x];
            acc[4 * j + x] = fmaf(b0, m00, b1 * m01);
            acc[4 * j + 2 + x] = fmaf(b0, m10, b1 * m11);
          }
        float2 c;
        {
          float2 ev[3];
          uint32_t it = 0;
          while (true) {
            bool ok = true;
#pragma unroll
            for (int i = 0; i < 3; i++) {
              const int Tp = T1 - 1 - q - 4 * i;
              ev[i] = make_float2(0.f, 0.f);
              if (Tp >= 0) ok &= (rec_ld(&g_E[(Tp * DM + ch) * 2 + l], ev[i].x, ev[i].y) == tag);
            }
            if (ok) break;
            if (++it > SPIN_LIMIT) soft_trap();
          }
          __syncwarp();
          c = cfma(p640, cfma(p640, ev[2], ev[1]), ev[0]);
          c = cmul(c, p160q);
          c.x += __shfl_xor_sync(0xffffffffu, c.x, 1); c.y += __shfl_xor_sync(0xffffffffu, c.y, 1);
          c.x += __shfl_xor_sync(0xffffffffu, c.x, 2); c.y += __shfl_xor_sync(0xffffffffu, c.y, 2);
        }
        if (tid == 0) TS(4 + 8 * l);
        c = cfma(pLq, c, ex);
        float2 hh = make_float2(fmaf(c.x, m00, c.y * m01), fmaf(c.x, m10, c.y * m11));
        uint8_t* hb = g_h + (size_t)l * (32 * 20 * 8192) + (10 * wg + 2 * GP) * 8192 + (4 * side + w) * 1024 + (tid_opaque() & 31) * 4;
#pragma unroll
        for (int j4 = 0; j4 < 5; j4++) {
          const int ng = 20 * T1 + 4 * j4;
          uint8_t* hp = hb + (size_t)(ng >> 3) * 163840 + (ng & 7) * 128;
#pragma unroll
          for (int jj = 0; jj < 4; jj++) {
            const int j = 4 * j4 + jj;
            const float2 h0 = cfma(lamc, hh, make_float2(acc[4 * j + 0], acc[4 * j + 2]));
            hh = cfma(lamc, h0, make_float2(acc[4 * j + 1], acc[4 * j + 3]));
            if (j4 < 4 || !last) {
              *(uint32_t*)(hp + jj * 128) = pack_bf16(h0.x, hh.x);
              *(uint32_t*)(hp + jj * 128 + 8192) = pack_bf16(h0.y, hh.y);
            }
          }
        }
        bar_sync(1 + wg, 128);
        if ((tid & 127) == 0) {
          if (wg == 0) TS(5 + 8 * l);
          st_rel(&g_hflag[((l * NT1 + T1) * 2 + wg) * 16 + 2 * GP + side], tag);
          if (wg == 0) TS(6 + 8 * l);
        }
      }
      if (l == 0) {
        ROLE(role)
        if (has2) {
          uint32_t so[4];
          cv_offsets(so);
          mbar_wait(bars + 8 * (B_G1DONE + 9));
#pragma unroll 1
          for (int c = wg == 2 ? 0 : 2 + wg; c < (wg == 2 ? 2 : 5); c += wg == 2 ? 1 : 2) conv_channel(c, so);
          if ((tid & 127) == 0) TS(wg == 2 ? 32 : 7 + wg);
        }
      }
      if (wg == 2) break;
    }
    if (wg == 2 && (role >> 16)) {
      float acc[80];
      float off[2] = {0.f, 0.f};
      x0_load(acc);
      mbar_arrive(bars + 8 * B_XFREE);
#pragma unroll 1
      for (int l = 0; l < 2; l++) {
        float mean[2], rstd[2];
        {
          ROLE(role)
          const int lane = tid_opaque() & 31;
          stats_get(2 * l, 64 * m2 + 16 * w + (lane >> 2), tag, mean, rstd);
          off[0] += mean[0]; off[1] += mean[1];
          mbar_wait(bars + 8 * B_CTAB);
#pragma unroll
          for (int J = 0; J < 10; J++) {
            const float2 dw = lds64f(sb + DTAB_OFF + 2 * (16 * J + 4 * (lane & 3)));
#pragma unroll
            for (int x = 0; x < 8; x++) {
              const int h = (x >> 1) & 1;
              const uint32_t gwd = __float_as_uint(x < 4 ? dw.x : dw.y);
              acc[8 * J + x] = (acc[8 * J + x] - mean[h]) * fmaf(rstd[h], (x & 1) ? bf_hi(gwd) : bf_lo(gwd), 1.f);
            }
          }
        }
        {
          const uint32_t aend = desc_lo(sb + SX2 * G2_XB, 1024) + l * (G2_XB >> 3), bend = desc_lo(sb + G2_WOFF + 6 * G2_WB, 16) + l * (G2_WB >> 4);
          uint32_t alo = desc_lo(sb, 1024), blo = desc_lo(sb + G2_WOFF, 16);
          uint32_t fb = bars + 8 * (B_G2FULL + 20 * l);
          fence_regs(acc);
          mbar_wait(fb);
          if (tid == 256) TS(33 + 6 * l);
#pragma unroll 1
          for (int k = 0; k < 20; k++) {
            if (l == 1 && (k & 3) == 3 && tid == 256) TS(56 + (k >> 2));
            uint32_t ok; const uint32_t nb = k < 19 ? fb + 8 : fb;
            wgmma_fence();
#pragma unroll
            for (int kk = 0; kk < 4; kk++) {
              wgmma_n160<1>(acc, alo + kk * 128, desc_hi(128, 0), blo + kk * 2, desc_hi(1024, 1));
              if (kk == 0) ok = mbar_test(nb);
            }
            wgmma_commit();
            alo += G2_XB >> 4; if (alo == aend) alo = desc_lo(sb, 1024);
            blo += G2_WB >> 4; if (blo == bend) blo = desc_lo(sb + G2_WOFF, 16);
            if (k > 0) { wgmma_wait<1>(); if (tid == 256) mbar_arrive(fb + 8 * (B_G2DONE - B_G2FULL - 1)); }
            if (!ok) mbar_wait(nb);
            fb += 8;
          }
          wgmma_wait<0>();
          fence_regs(acc);
          if (tid == 256) TS(34 + 6 * l);
          if (tid == 256) mbar_arrive(bars + 8 * (B_G2DONE + 20 * l + 19));
        }
        ROLE(role)
        const int tq = tid_opaque() & 31, n0 = 64 * m2 + 16 * w + (tq >> 2);
        stats_publish<false>(2 * l + 1, n0, dg, tag, acc);
        uint32_t gf[10][4];
        mbar_wait(bars + 8 * B_GFULL);
        const uint32_t ga = sb + G_OFF + (8 * (tq >> 4) + (tq & 7)) * 128 + (((2 * w + ((tq >> 3) & 1)) ^ (m2 & 7) ^ (tq & 7)) << 4);
#pragma unroll
        for (int J = 0; J < 4; J++) ldsm4t(gf[J], ga + J * 2048);
        if (tid == 256) TS(35 + 6 * l);
        uint8_t* dst[2][2];
#pragma unroll
        for (int h = 0; h < 2; h++) {
          if (l == 0) {
            const int ng = 8 * m2 + 2 * w + h, T = ng / 20;
            uint8_t* ub = g_u + (T * 204800 + (ng - 20 * T) * 1024 + (tq & 2) * 64 + (tq & 28) * 4 + (tq & 1) * 8 + (5 * dg >> 1) * 20480);
            dst[h][1] = ub + ((dg & 1) ? 20480 - 512 : 0);
            dst[h][0] = ub + (dg & 1) * 512;
          } else {
            dst[h][0] = dst[h][1] = (uint8_t*)(p.out + (n_to_t(n0 + 8 * h) * DM + 160 * dg + 4 * (tq & 3)));
          }
        }
        stats_get(2 * l + 1, n0, tag, mean, rstd);
        if (tid == 256) TS(36 + 6 * l);
        off[0] += mean[0]; off[1] += mean[1];
#pragma unroll
        for (int J = 0; J < 10; J++) {
          asm volatile("" : "+r"(gf[J][0]), "+r"(gf[J][1]), "+r"(gf[J][2]), "+r"(gf[J][3])::"memory");
          if (J + 4 < 10) ldsm4t(gf[J + 4 < 10 ? J + 4 : 0], ga + (J + 4) * 2048);
#pragma unroll
          for (int x = 0; x < 8; x++) {
            const int h = (x >> 1) & 1;
            const uint32_t gwd = gf[J][x >> 1];
            acc[8 * J + x] = (acc[8 * J + x] - mean[h]) * fmaf(rstd[h], (x & 1) ? bf_hi(gwd) : bf_lo(gwd), 1.f);
          }
#pragma unroll
          for (int h = 0; h < 2; h++) {
            if (l == 0)
              *(uint2*)(dst[h][(J >> 1) & 1] + (J >> 2) * 20480 + (J & 3) * 256) =
                  make_uint2(pack_bf16(acc[8 * J + 2 * h], acc[8 * J + 2 * h + 1]), pack_bf16(acc[8 * J + 4 + 2 * h], acc[8 * J + 5 + 2 * h]));
            else
              *(float4*)(dst[h][0] + 64 * J) = make_float4(acc[8 * J + 2 * h] + off[h], acc[8 * J + 2 * h + 1] + off[h],
                                                           acc[8 * J + 4 + 2 * h] + off[h], acc[8 * J + 5 + 2 * h] + off[h]);
          }
        }
        if (l == 0) {
          bar_sync(3, 128);
          if (tid == 256) { TS(37); st_rel(&g_uflag[4 * m2 + dg], tag); TS(38); }
          stats_publish<false>(2, n0, dg, tag, acc);
          stat_table(T1, 4 * tag + 2, 1);
          if (tid == 256) TS(27);
        } else {
          if (tid == 256) {
            TS(43);
            if (m2 == 31 && dg == 3) asm volatile("st.relaxed.gpu.global.u32 [%0], %1;" ::"l"(g_epoch), "r"(tag + 1) : "memory");
          }
        }
      }
    }
  }
}

typedef CUresult (*EncFn)(CUtensorMap*, CUtensorMapDataType, cuuint32_t, void*, const cuuint64_t*, const cuuint64_t*,
                          const cuuint32_t*, const cuuint32_t*, CUtensorMapInterleave, CUtensorMapSwizzle,
                          CUtensorMapL2promotion, CUtensorMapFloatOOBfill);

void encode(EncFn fn, CUtensorMap* m, const void* ptr, int rank, const cuuint64_t* dims, const cuuint64_t* strides, const cuuint32_t* box,
            CUtensorMapSwizzle swz = CU_TENSOR_MAP_SWIZZLE_128B) {
  cuuint32_t es[5] = {1, 1, 1, 1, 1};
  fn(m, CU_TENSOR_MAP_DATA_TYPE_BFLOAT16, rank, (void*)ptr, dims, strides, box, es, CU_TENSOR_MAP_INTERLEAVE_NONE,
     swz, swz == CU_TENSOR_MAP_SWIZZLE_128B ? CU_TENSOR_MAP_L2_PROMOTION_L2_128B : CU_TENSOR_MAP_L2_PROMOTION_L2_64B, CU_TENSOR_MAP_FLOAT_OOB_FILL_NONE);
}

}

extern "C" void kernel_launch(void* const* d_in, const int* in_sizes, int n_in, void* d_out, int out_size) {
  (void)in_sizes; (void)n_in; (void)out_size;
  Params p;
  typedef const __nv_bfloat16* BP;
  p.x = (BP)d_in[0]; p.lre = (BP)d_in[1]; p.lim = (BP)d_in[2]; p.bre = (BP)d_in[3]; p.bim = (BP)d_in[4];
  p.cre = (BP)d_in[5]; p.cim = (BP)d_in[6]; p.logdt = (BP)d_in[7]; p.dskip = (BP)d_in[8];
  p.k = (BP)d_in[10]; p.v = (BP)d_in[11]; p.shiftk = (BP)d_in[12]; p.ssmk = (BP)d_in[13]; p.ssmD = (BP)d_in[14];
  p.out = (float*)d_out;
  void* fnp = nullptr;
  cudaDriverEntryPointQueryResult qr;
  cudaGetDriverEntryPoint("cuTensorMapEncodeTiled", &fnp, cudaEnableDefault, &qr);
  EncFn fn = (EncFn)fnp;
  void* gG = nullptr;
  cudaGetSymbolAddress(&gG, g_G);
  const cuuint64_t RB = DM * 2;
  {
    p.swap = p.bim < p.bre;
    const char* lo = (const char*)(p.swap ? p.bim : p.bre); const char* hi = (const char*)(p.swap ? p.bre : p.bim);
    cuuint64_t dims[5] = {640, 8, 2, 8, 10}, st[4] = {RB, (cuuint64_t)(hi - lo), 8 * RB, 64 * RB}; cuuint32_t box[5] = {64, 8, 2, 4, 2};
    encode(fn, &p.mB, lo, 5, dims, st, box);
  }
  {
    cuuint64_t dims[5] = {640, 2, 4, 2, 40}, st[4] = {RB, 4 * RB, 2 * RB, 16 * RB}; cuuint32_t box[5] = {64, 2, 4, 2, 10};
    encode(fn, &p.mCre, p.cre, 5, dims, st, box); encode(fn, &p.mCim, p.cim, 5, dims, st, box);
    cuuint64_t dimg[5] = {2048, 2, 4, 2, 40}, stg[4] = {4096, 4 * 4096, 2 * 4096, 16 * 4096};
    encode(fn, &p.mG, gG, 5, dimg, stg, box);
  }
  {
    cuuint64_t dims[4] = {640, 2, 4, 900}, st[3] = {RB, 40 * RB, 2 * RB}; cuuint32_t box[4] = {64, 2, 4, 20};
    encode(fn, &p.mX, p.x, 4, dims, st, box);
    cuuint64_t diml[4] = {640, 2, 4, 16}, stl[3] = {RB, 32 * RB, 2 * RB};
    encode(fn, &p.mXl, p.x + (size_t)1920 * DM, 4, diml, stl, box);
    cuuint32_t boxt[4] = {160, 2, 4, 4};
    encode(fn, &p.mXt, p.x, 4, dims, st, boxt, CU_TENSOR_MAP_SWIZZLE_NONE);
    encode(fn, &p.mXtl, p.x + (size_t)1920 * DM, 4, diml, stl, boxt, CU_TENSOR_MAP_SWIZZLE_NONE);
    cuuint64_t dk[3] = {640, 2000, 4}, sk[2] = {RB, 16 * RB}; cuuint32_t bk[3] = {32, 19, 4}, bv[3] = {32, 17, 4};
    encode(fn, &p.mK, p.k, 3, dk, sk, bk, CU_TENSOR_MAP_SWIZZLE_NONE);
    encode(fn, &p.mV, p.v, 3, dk, sk, bv, CU_TENSOR_MAP_SWIZZLE_NONE);
  }
  cudaFuncSetAttribute(fused_kernel, cudaFuncAttributeMaxDynamicSharedMemorySize, SMEM_BYTES);
  cudaLaunchConfig_t cfg = {};
  cfg.gridDim = dim3(132); cfg.blockDim = dim3(512); cfg.dynamicSmemBytes = SMEM_BYTES; cfg.stream = cudaStreamPerThread;
  cudaLaunchKernelEx(&cfg, fused_kernel, p);
}
```

```cpp
#include <cuda_runtime.h>
#include <cuda.h>
#include <cuda_bf16.h>
#include <stdint.h>

namespace {

constexpr int SEQ = 2048, DM = 640;
constexpr int NT1 = 13;
#define EXP 0
#define PAUSE_K 4
constexpr uint32_t SPIN_LIMIT = 1u << 22;

__device__ __align__(1024) uint8_t g_h[2 * 32 * 20 * 8192];
__device__ __align__(1024) uint8_t g_u[NT1 * 10 * 20480];
__device__ __align__(1024) uint8_t g_kv[DM * 4096];
__device__ __align__(1024) uint8_t g_G[DM * 4096];
__device__ __align__(128) uint4 g_E[2 * NT1 * DM];
__device__ __align__(128) uint4 g_stats[4 * 4 * SEQ];
__device__ __align__(128) uint4 g_sB[DM * 2];
__device__ __align__(128) unsigned g_hflag[2 * NT1 * 2 * 16 * 8];
__device__ __align__(128) unsigned g_uflag[32 * 4 * 8];
__device__ __align__(128) unsigned g_kvflag[4 * 32 * 8];
__device__ __align__(128) unsigned g_gflag[4 * 32 * 8];
__device__ __align__(128) unsigned g_epoch[32] = {1};
#define TS(i) do {} while (0)

struct Params {
  CUtensorMap mB, mCre, mCim, mX, mXl, mG, mK, mV, mXt, mXtl;
  const __nv_bfloat16 *x, *lre, *lim, *bre, *bim, *cre, *cim, *logdt, *dskip, *k, *v, *shiftk, *ssmk, *ssmD;
  float* out;
  int swap;
};

constexpr uint32_t sb = 1024;
constexpr uint32_t G1_STAGE = 36864, G1_XOFF = 16384;
constexpr int S1 = 4;
constexpr uint32_t XT_OFF = 159744, KS_OFF = 180224, KV_PIECE = 9216;
constexpr uint32_t G2_XB = 8192, G2_WB = 20480, G2_WOFF = 57344, G_OFF = 200704;
constexpr int SX2 = 5;
constexpr uint32_t CV_OFF = 184320, CV_K = 128, CV_PL = 2240, CV_U = CV_K + 4096, CV_B = 8704;
constexpr uint32_t MISC = 227840;
constexpr uint32_t BAR_OFF = MISC;
constexpr int B_G1FULL = 0, B_G1DONE = 20, B_G2FULL = 40,
              B_G2DONE = 85, B_GFULL = 125, B_PREP = 126, B_EP = 127, B_H1 = 128  ,
              B_CVDONE = 130, B_STAB = 135  , B_CTAB = 137, B_XFREE = 138, B_HST = 139  ,
              B_XT = 143, B_KV = 144  , B_TAPS = 149  , B_CVFULL = 154  ;
constexpr uint32_t bars = sb + BAR_OFF;
constexpr uint32_t STAB_OFF = MISC + 1280;
constexpr uint32_t CTAB_OFF = STAB_OFF + 1280;
constexpr uint32_t DTAB_OFF = CTAB_OFF + 1536;
constexpr uint32_t EP_OFF = DTAB_OFF + 320;
constexpr uint32_t TAP_OFF = 147456;
constexpr uint32_t SMEM_BYTES = 232448;
static_assert(EP_OFF + 32 <= SMEM_BYTES, "smem");

__device__ __forceinline__ void soft_trap() { asm volatile("trap;"); }
__device__ __forceinline__ uint32_t smem_u32(const void* p) { return (uint32_t)__cvta_generic_to_shared(p); }
__device__ __forceinline__ void mbar_init(uint32_t bar, int cnt) { asm volatile("mbarrier.init.shared::cta.b64 [%0], %1;" ::"r"(bar), "r"(cnt) : "memory"); }
__device__ __forceinline__ void mbar_expect_tx(uint32_t bar, int bytes) { asm volatile("mbarrier.arrive.expect_tx.shared::cta.b64 _, [%0], %1;" ::"r"(bar), "r"(bytes) : "memory"); }
__device__ __forceinline__ void mbar_arrive(uint32_t bar) { asm volatile("mbarrier.arrive.shared::cta.b64 _, [%0];" ::"r"(bar) : "memory"); }
__device__ __forceinline__ void mbar_wait(uint32_t bar) {
  asm volatile(
      "{\n.reg .pred p;\n.reg .u32 c;\nmov.u32 c, 0;\n"
      "W_%=:\nmbarrier.try_wait.parity.shared::cta.b64 p, [%0], 0;\n@p bra D_%=;\n"
      "add.u32 c, c, 1;\nsetp.lt.u32 p, c, %1;\n@p bra W_%=;\ntrap;\nD_%=:\n}\n" ::"r"(bar), "n"(SPIN_LIMIT) : "memory");
}
__device__ __forceinline__ uint32_t mbar_test(uint32_t bar) {
  uint32_t ok;
  asm volatile("{\n.reg .pred p;\nmbarrier.test_wait.parity.shared::cta.b64 p, [%1], 0;\nselp.u32 %0, 1, 0, p;\n}\n" : "=r"(ok) : "r"(bar) : "memory");
  return ok;
}
__device__ __forceinline__ void tma3(uint32_t dst, const CUtensorMap* m, int c0, int c1, int c2, uint32_t bar) {
  asm volatile("cp.async.bulk.tensor.3d.shared::cluster.global.mbarrier::complete_tx::bytes [%0], [%1, {%3,%4,%5}], [%2];"
               ::"r"(dst), "l"(m), "r"(bar), "r"(c0), "r"(c1), "r"(c2) : "memory");
}
__device__ __forceinline__ void tma4(uint32_t dst, const CUtensorMap* m, int c0, int c1, int c2, int c3, uint32_t bar) {
  asm volatile("cp.async.bulk.tensor.4d.shared::cluster.global.mbarrier::complete_tx::bytes [%0], [%1, {%3,%4,%5,%6}], [%2];"
               ::"r"(dst), "l"(m), "r"(bar), "r"(c0), "r"(c1), "r"(c2), "r"(c3) : "memory");
}
__device__ __forceinline__ void tma5(uint32_t dst, const CUtensorMap* m, int c0, int c1, int c2, int c3, int c4, uint32_t bar) {
  asm volatile("cp.async.bulk.tensor.5d.shared::cluster.global.mbarrier::complete_tx::bytes [%0], [%1, {%3,%4,%5,%6,%7}], [%2];"
               ::"r"(dst), "l"(m), "r"(bar), "r"(c0), "r"(c1), "r"(c2), "r"(c3), "r"(c4) : "memory");
}
__device__ __forceinline__ void bulk_g2s(uint32_t dst, const void* src, int bytes, uint32_t bar) {
  asm volatile("cp.async.bulk.shared::cluster.global.mbarrier::complete_tx::bytes [%0], [%1], %2, [%3];"
               ::"r"(dst), "l"(src), "r"(bytes), "r"(bar) : "memory");
}
__device__ __forceinline__ void bulk_s2g(void* dst, uint32_t src, int bytes) {
  asm volatile("cp.async.bulk.global.shared::cta.bulk_group [%0], [%1], %2;" ::"l"(dst), "r"(src), "r"(bytes) : "memory");
}
__device__ __forceinline__ void l2_prefetch(const void* src, int bytes) {
  asm volatile("cp.async.bulk.prefetch.L2.global [%0], %1;" ::"l"(src), "r"(bytes) : "memory");
}
__device__ __forceinline__ void wgmma_fence() { asm volatile("wgmma.fence.sync.aligned;" ::: "memory"); }
__device__ __forceinline__ void wgmma_commit() { asm volatile("wgmma.commit_group.sync.aligned;" ::: "memory"); }
template <int N> __device__ __forceinline__ void wgmma_wait() { asm volatile("wgmma.wait_group.sync.aligned %0;" ::"n"(N) : "memory"); }
__host__ __device__ constexpr uint32_t desc_lo(uint32_t addr, uint32_t lbo) { return ((addr & 0x3FFFF) >> 4) | ((lbo >> 4) << 16); }
__host__ __device__ constexpr uint32_t desc_hi(uint32_t sbo, uint32_t swz) { return (sbo >> 4) | (swz << 30); }
__device__ __forceinline__ void bar_sync(int id, int n) { asm volatile("bar.sync %0, %1;" ::"r"(id), "r"(n) : "memory"); }
__device__ __forceinline__ uint32_t lds32(uint32_t a) { uint32_t v; asm volatile("ld.shared.u32 %0, [%1];" : "=r"(v) : "r"(a) : "memory"); return v; }
__device__ __forceinline__ float2 lds64f(uint32_t a) { float2 v; asm volatile("ld.shared.v2.f32 {%0,%1}, [%2];" : "=f"(v.x), "=f"(v.y) : "r"(a) : "memory"); return v; }
__device__ __forceinline__ float4 lds128f(uint32_t a) { float4 v; asm volatile("ld.shared.v4.f32 {%0,%1,%2,%3}, [%4];" : "=f"(v.x), "=f"(v.y), "=f"(v.z), "=f"(v.w) : "r"(a) : "memory"); return v; }
__device__ __forceinline__ void ldsm4t(uint32_t (&r)[4], uint32_t a) {
  asm volatile("ldmatrix.sync.aligned.m8n8.x4.trans.shared.b16 {%0,%1,%2,%3}, [%4];" : "=r"(r[0]), "=r"(r[1]), "=r"(r[2]), "=r"(r[3]) : "r"(a) : "memory");
}
__device__ __forceinline__ uint4 ldv128(const void* a) { uint4 v; asm volatile("ld.global.nc.v4.u32 {%0,%1,%2,%3}, [%4];" : "=r"(v.x), "=r"(v.y), "=r"(v.z), "=r"(v.w) : "l"(a) : "memory"); return v; }
__device__ __forceinline__ uint2 ldv64(const void* a) { uint2 v; asm volatile("ld.global.nc.v2.u32 {%0,%1}, [%2];" : "=r"(v.x), "=r"(v.y) : "l"(a) : "memory"); return v; }
__device__ __forceinline__ uint32_t ldv16(const void* a) { uint32_t v; asm volatile("ld.global.nc.u16 %0, [%1];" : "=r"(v) : "l"(a) : "memory"); return v; }
__device__ __forceinline__ void sts128(uint32_t a, uint4 v) { asm volatile("st.shared.v4.u32 [%0], {%1,%2,%3,%4};" ::"r"(a), "r"(v.x), "r"(v.y), "r"(v.z), "r"(v.w) : "memory"); }
__device__ __forceinline__ void sts32(uint32_t a, uint32_t v) { asm volatile("st.shared.u32 [%0], %1;" ::"r"(a), "r"(v) : "memory"); }
__device__ __forceinline__ void sts64f(uint32_t a, float x, float y) { asm volatile("st.shared.v2.f32 [%0], {%1,%2};" ::"r"(a), "f"(x), "f"(y) : "memory"); }
__device__ __forceinline__ void st_rel(unsigned* p, unsigned v) { asm volatile("st.release.gpu.global.u32 [%0], %1;" ::"l"(p), "r"(v) : "memory"); }
__device__ __forceinline__ void fence_async_global() { asm volatile("fence.proxy.async.global;" ::: "memory"); }
__device__ __forceinline__ void fence_async_smem() { asm volatile("fence.proxy.async.shared::cta;" ::: "memory"); }
__device__ __forceinline__ void rec_st(uint4* p, float a, float b, unsigned tag) {
  asm volatile("{\n.reg .b128 t;\n.reg .b64 lo, hi;\nmov.b64 lo, {%1,%2};\nmov.b64 hi, {%3,%3};\nmov.b128 t, {lo,hi};\n"
               "st.relaxed.gpu.global.b128 [%0], t;\n}\n" ::"l"(p), "r"(__float_as_uint(a)), "r"(__float_as_uint(b)), "r"(tag) : "memory");
}
__device__ __forceinline__ unsigned rec_ld(const uint4* p, float& a, float& b) {
  unsigned x, y, t;
  asm volatile("{\n.reg .b128 t;\n.reg .b64 lo, hi;\n.reg .b32 u;\nld.relaxed.gpu.global.b128 t, [%3];\nmov.b128 {lo,hi}, t;\n"
               "mov.b64 {%0,%1}, lo;\nmov.b64 {%2,u}, hi;\n}\n" : "=r"(x), "=r"(y), "=r"(t) : "l"(p) : "memory");
  a = __uint_as_float(x); b = __uint_as_float(y);
  return t;
}
__device__ __forceinline__ void rec_poll(const uint4* p, unsigned tag, float& a, float& b) {
  uint32_t it = 0;
  while (rec_ld(p, a, b) != tag) { if (++it > SPIN_LIMIT) soft_trap(); }
}
__device__ __forceinline__ unsigned ld_rlx(const unsigned* p) { unsigned v; asm volatile("ld.relaxed.gpu.global.u32 %0, [%1];" : "=r"(v) : "l"(p) : "memory"); return v; }
__device__ __forceinline__ void flag_poll(const unsigned* p, unsigned target) {
  uint32_t it = 0;
  while ((int)(ld_rlx(p) - target) < 0) { if (++it > SPIN_LIMIT) soft_trap(); }
  asm volatile("fence.acquire.gpu;" ::: "memory");
}
__device__ __forceinline__ uint32_t pack_bf16(float lo, float hi) {
  uint32_t r; asm("cvt.rn.bf16x2.f32 %0, %1, %2;" : "=r"(r) : "f"(hi), "f"(lo)); return r;
}
__device__ __forceinline__ float bf_lo(uint32_t w) { return __uint_as_float(w << 16); }
__device__ __forceinline__ float bf_hi(uint32_t w) { return __uint_as_float(w & 0xffff0000u); }
__device__ __forceinline__ uint32_t hmul2(uint32_t a, uint32_t b) {
  __nv_bfloat162 r = __hmul2_rn(*(__nv_bfloat162*)&a, *(__nv_bfloat162*)&b); return *(uint32_t*)&r;
}
__device__ __forceinline__ uint32_t hadd2(uint32_t a, uint32_t b) {
  __nv_bfloat162 r = __hadd2_rn(*(__nv_bfloat162*)&a, *(__nv_bfloat162*)&b); return *(uint32_t*)&r;
}
__device__ __forceinline__ float2 cmul(float2 a, float2 b) { return make_float2(a.x * b.x - a.y * b.y, a.x * b.y + a.y * b.x); }
__device__ __forceinline__ float2 cfma(float2 a, float2 b, float2 c) {
  return make_float2(fmaf(a.x, b.x, fmaf(-a.y, b.y, c.x)), fmaf(a.x, b.y, fmaf(a.y, b.x, c.y)));
}
template <int N> __device__ __forceinline__ void fence_regs(float (&a)[N]) {
#pragma unroll
  for (int i = 0; i < N; i++) asm volatile("" : "+f"(a[i])::"memory");
}
__device__ __forceinline__ bool elect_one() {
  uint32_t e; asm volatile("{\n.reg .pred P;\nelect.sync _|P, 0xffffffff;\nselp.u32 %0, 1, 0, P;\n}\n" : "=r"(e)); return e != 0;
}
__device__ __forceinline__ int tid_opaque() { int t; asm volatile("mov.u32 %0, %%tid.x;" : "=r"(t)); return t; }
struct Role { int T1, GP, side, m2, dg, cch0; bool last, has2; };
__device__ __forceinline__ Role unpack_role(int x) {
  Role r; r.T1 = x & 15; r.GP = (x >> 4) & 7; r.side = (x >> 7) & 1; r.m2 = (x >> 8) & 63; r.dg = (x >> 14) & 3;
  r.has2 = (x >> 16) & 1; r.last = r.T1 == NT1 - 1; r.cch0 = 5 * (32 * r.dg + r.m2); return r;
}
__device__ __forceinline__ Role fresh_role(int x) { asm volatile("" : "+r"(x)); return unpack_role(__shfl_sync(0xffffffffu, x, 0)); }
#define ROLE(x) const Role R_ = fresh_role(x); const int T1 = R_.T1, GP = R_.GP, side = R_.side, m2 = R_.m2, dg = R_.dg, cch0 = R_.cch0; \
  const bool last = R_.last, has2 = R_.has2; (void)T1; (void)GP; (void)side; (void)m2; (void)dg; (void)cch0; (void)last; (void)has2;
__device__ __forceinline__ int n_to_t(int n) {
  int T = n / 160, nl = n - T * 160;
  int L = (T == NT1 - 1) ? 32 : 40;
  return T * 160 + L * ((nl & 7) >> 1) + 2 * (nl >> 3) + (nl & 1);
}

template<int TA> __device__ __forceinline__ void wgmma_n160(float (&d)[80], uint32_t alo, uint32_t ahi, uint32_t blo, uint32_t bhi){
  asm volatile("{\n.reg .b64 da, db;\nmov.b64 da, {%80,%81};\nmov.b64 db, {%82,%83};\n"
    "wgmma.mma_async.sync.aligned.m64n160k16.f32.bf16.bf16 {%0, %1, %2, %3, %4, %5, %6, %7, %8, %9, %10, %11, %12, %13, %14, %15, %16, %17, %18, %19, %20, %21, %22, %23, %24, %25, %26, %27, %28, %29, %30, %31, %32, %33, %34, %35, %36, %37, %38, %39, %40, %41, %42, %43, %44, %45, %46, %47, %48, %49, %50, %51, %52, %53, %54, %55, %56, %57, %58, %59, %60, %61, %62, %63, %64, %65, %66, %67, %68, %69, %70, %71, %72, %73, %74, %75, %76, %77, %78, %79}, da, db, 1, 1, 1, %84, 0;\n}\n"
    : "+f"(d[0]), "+f"(d[1]), "+f"(d[2]), "+f"(d[3]), "+f"(d[4]), "+f"(d[5]), "+f"(d[6]), "+f"(d[7]), "+f"(d[8]), "+f"(d[9]), "+f"(d[10]), "+f"(d[11]), "+f"(d[12]), "+f"(d[13]), "+f"(d[14]), "+f"(d[15]), "+f"(d[16]), "+f"(d[17]), "+f"(d[18]), "+f"(d[19]), "+f"(d[20]), "+f"(d[21]), "+f"(d[22]), "+f"(d[23]), "+f"(d[24]), "+f"(d[25]), "+f"(d[26]), "+f"(d[27]), "+f"(d[28]), "+f"(d[29]), "+f"(d[30]), "+f"(d[31]), "+f"(d[32]), "+f"(d[33]), "+f"(d[34]), "+f"(d[35]), "+f"(d[36]), "+f"(d[37]), "+f"(d[38]), "+f"(d[39]), "+f"(d[40]), "+f"(d[41]), "+f"(d[42]), "+f"(d[43]), "+f"(d[44]), "+f"(d[45]), "+f"(d[46]), "+f"(d[47]), "+f"(d[48]), "+f"(d[49]), "+f"(d[50]), "+f"(d[51]), "+f"(d[52]), "+f"(d[53]), "+f"(d[54]), "+f"(d[55]), "+f"(d[56]), "+f"(d[57]), "+f"(d[58]), "+f"(d[59]), "+f"(d[60]), "+f"(d[61]), "+f"(d[62]), "+f"(d[63]), "+f"(d[64]), "+f"(d[65]), "+f"(d[66]), "+f"(d[67]), "+f"(d[68]), "+f"(d[69]), "+f"(d[70]), "+f"(d[71]), "+f"(d[72]), "+f"(d[73]), "+f"(d[74]), "+f"(d[75]), "+f"(d[76]), "+f"(d[77]), "+f"(d[78]), "+f"(d[79])
    : "r"(alo), "r"(ahi), "r"(blo), "r"(bhi), "n"(TA));
}
template<int N> __device__ __forceinline__ void wgmma_rs_hi(float (&d)[64], uint32_t a0, uint32_t a1, uint32_t a2, uint32_t a3, uint32_t blo);
template<> __device__ __forceinline__ void wgmma_rs_hi<16>(float (&d)[64], uint32_t a0, uint32_t a1, uint32_t a2, uint32_t a3, uint32_t blo){
  asm volatile("{\n.reg .b64 db;\nmov.b64 db, {%12,8};\nwgmma.mma_async.sync.aligned.m64n16k16.f32.bf16.bf16 {%0, %1, %2, %3, %4, %5, %6, %7}, {%8,%9,%10,%11}, db, 1, 1, 1, 0;\n}\n"
    : "+f"(d[56]), "+f"(d[57]), "+f"(d[58]), "+f"(d[59]), "+f"(d[60]), "+f"(d[61]), "+f"(d[62]), "+f"(d[63])
    : "r"(a0), "r"(a1), "r"(a2), "r"(a3), "r"(blo));
}
template<> __device__ __forceinline__ void wgmma_rs_hi<32>(float (&d)[64], uint32_t a0, uint32_t a1, uint32_t a2, uint32_t a3, uint32_t blo){
  asm volatile("{\n.reg .b64 db;\nmov.b64 db, {%20,8};\nwgmma.mma_async.sync.aligned.m64n32k16.f32.bf16.bf16 {%0, %1, %2, %3, %4, %5, %6, %7, %8, %9, %10, %11, %12, %13, %14, %15}, {%16,%17,%18,%19}, db, 1, 1, 1, 0;\n}\n"
    : "+f"(d[48]), "+f"(d[49]), "+f"(d[50]), "+f"(d[51]), "+f"(d[52]), "+f"(d[53]), "+f"(d[54]), "+f"(d[55]), "+f"(d[56]), "+f"(d[57]), "+f"(d[58]), "+f"(d[59]), "+f"(d[60]), "+f"(d[61]), "+f"(d[62]), "+f"(d[63])
    : "r"(a0), "r"(a1), "r"(a2), "r"(a3), "r"(blo));
}
template<> __device__ __forceinline__ void wgmma_rs_hi<48>(float (&d)[64], uint32_t a0, uint32_t a1, uint32_t a2, uint32_t a3, uint32_t blo){
  asm volatile("{\n.reg .b64 db;\nmov.b64 db, {%28,8};\nwgmma.mma_async.sync.aligned.m64n48k16.f32.bf16.bf16 {%0, %1, %2, %3, %4, %5, %6, %7, %8, %9, %10, %11, %12, %13, %14, %15, %16, %17, %18, %19, %20, %21, %22, %23}, {%24,%25,%26,%27}, db, 1, 1, 1, 0;\n}\n"
    : "+f"(d[40]), "+f"(d[41]), "+f"(d[42]), "+f"(d[43]), "+f"(d[44]), "+f"(d[45]), "+f"(d[46]), "+f"(d[47]), "+f"(d[48]), "+f"(d[49]), "+f"(d[50]), "+f"(d[51]), "+f"(d[52]), "+f"(d[53]), "+f"(d[54]), "+f"(d[55]), "+f"(d[56]), "+f"(d[57]), "+f"(d[58]), "+f"(d[59]), "+f"(d[60]), "+f"(d[61]), "+f"(d[62]), "+f"(d[63])
    : "r"(a0), "r"(a1), "r"(a2), "r"(a3), "r"(blo));
}
template<> __device__ __forceinline__ void wgmma_rs_hi<64>(float (&d)[64], uint32_t a0, uint32_t a1, uint32_t a2, uint32_t a3, uint32_t blo){
  asm volatile("{\n.reg .b64 db;\nmov.b64 db, {%36,8};\nwgmma.mma_async.sync.aligned.m64n64k16.f32.bf16.bf16 {%0, %1, %2, %3, %4, %5, %6, %7, %8, %9, %10, %11, %12, %13, %14, %15, %16, %17, %18, %19, %20, %21, %22, %23, %24, %25, %26, %27, %28, %29, %30, %31}, {%32,%33,%34,%35}, db, 1, 1, 1, 0;\n}\n"
    : "+f"(d[32]), "+f"(d[33]), "+f"(d[34]), "+f"(d[35]), "+f"(d[36]), "+f"(d[37]), "+f"(d[38]), "+f"(d[39]), "+f"(d[40]), "+f"(d[41]), "+f"(d[42]), "+f"(d[43]), "+f"(d[44]), "+f"(d[45]), "+f"(d[46]), "+f"(d[47]), "+f"(d[48]), "+f"(d[49]), "+f"(d[50]), "+f"(d[51]), "+f"(d[52]), "+f"(d[53]), "+f"(d[54]), "+f"(d[55]), "+f"(d[56]), "+f"(d[57]), "+f"(d[58]), "+f"(d[59]), "+f"(d[60]), "+f"(d[61]), "+f"(d[62]), "+f"(d[63])
    : "r"(a0), "r"(a1), "r"(a2), "r"(a3), "r"(blo));
}
template<> __device__ __forceinline__ void wgmma_rs_hi<80>(float (&d)[64], uint32_t a0, uint32_t a1, uint32_t a2, uint32_t a3, uint32_t blo){
  asm volatile("{\n.reg .b64 db;\nmov.b64 db, {%44,8};\nwgmma.mma_async.sync.aligned.m64n80k16.f32.bf16.bf16 {%0, %1, %2, %3, %4, %5, %6, %7, %8, %9, %10, %11, %12, %13, %14, %15, %16, %17, %18, %19, %20, %21, %22, %23, %24, %25, %26, %27, %28, %29, %30, %31, %32, %33, %34, %35, %36, %37, %38, %39}, {%40,%41,%42,%43}, db, 1, 1, 1, 0;\n}\n"
    : "+f"(d[24]), "+f"(d[25]), "+f"(d[26]), "+f"(d[27]), "+f"(d[28]), "+f"(d[29]), "+f"(d[30]), "+f"(d[31]), "+f"(d[32]), "+f"(d[33]), "+f"(d[34]), "+f"(d[35]), "+f"(d[36]), "+f"(d[37]), "+f"(d[38]), "+f"(d[39]), "+f"(d[40]), "+f"(d[41]), "+f"(d[42]), "+f"(d[43]), "+f"(d[44]), "+f"(d[45]), "+f"(d[46]), "+f"(d[47]), "+f"(d[48]), "+f"(d[49]), "+f"(d[50]), "+f"(d[51]), "+f"(d[52]), "+f"(d[53]), "+f"(d[54]), "+f"(d[55]), "+f"(d[56]), "+f"(d[57]), "+f"(d[58]), "+f"(d[59]), "+f"(d[60]), "+f"(d[61]), "+f"(d[62]), "+f"(d[63])
    : "r"(a0), "r"(a1), "r"(a2), "r"(a3), "r"(blo));
}
template<> __device__ __forceinline__ void wgmma_rs_hi<96>(float (&d)[64], uint32_t a0, uint32_t a1, uint32_t a2, uint32_t a3, uint32_t blo){
  asm volatile("{\n.reg .b64 db;\nmov.b64 db, {%52,8};\nwgmma.mma_async.sync.aligned.m64n96k16.f32.bf16.bf16 {%0, %1, %2, %3, %4, %5, %6, %7, %8, %9, %10, %11, %12, %13, %14, %15, %16, %17, %18, %19, %20, %21, %22, %23, %24, %25, %26, %27, %28, %29, %30, %31, %32, %33, %34, %35, %36, %37, %38, %39, %40, %41, %42, %43, %44, %45, %46, %47}, {%48,%49,%50,%51}, db, 1, 1, 1, 0;\n}\n"
    : "+f"(d[16]), "+f"(d[17]), "+f"(d[18]), "+f"(d[19]), "+f"(d[20]), "+f"(d[21]), "+f"(d[22]), "+f"(d[23]), "+f"(d[24]), "+f"(d[25]), "+f"(d[26]), "+f"(d[27]), "+f"(d[28]), "+f"(d[29]), "+f"(d[30]), "+f"(d[31]), "+f"(d[32]), "+f"(d[33]), "+f"(d[34]), "+f"(d[35]), "+f"(d[36]), "+f"(d[37]), "+f"(d[38]), "+f"(d[39]), "+f"(d[40]), "+f"(d[41]), "+f"(d[42]), "+f"(d[43]), "+f"(d[44]), "+f"(d[45]), "+f"(d[46]), "+f"(d[47]), "+f"(d[48]), "+f"(d[49]), "+f"(d[50]), "+f"(d[51]), "+f"(d[52]), "+f"(d[53]), "+f"(d[54]), "+f"(d[55]), "+f"(d[56]), "+f"(d[57]), "+f"(d[58]), "+f"(d[59]), "+f"(d[60]), "+f"(d[61]), "+f"(d[62]), "+f"(d[63])
    : "r"(a0), "r"(a1), "r"(a2), "r"(a3), "r"(blo));
}
template<> __device__ __forceinline__ void wgmma_rs_hi<112>(float (&d)[64], uint32_t a0, uint32_t a1, uint32_t a2, uint32_t a3, uint32_t blo){
  asm volatile("{\n.reg .b64 db;\nmov.b64 db, {%60,8};\nwgmma.mma_async.sync.aligned.m64n112k16.f32.bf16.bf16 {%0, %1, %2, %3, %4, %5, %6, %7, %8, %9, %10, %11, %12, %13, %14, %15, %16, %17, %18, %19, %20, %21, %22, %23, %24, %25, %26, %27, %28, %29, %30, %31, %32, %33, %34, %35, %36, %37, %38, %39, %40, %41, %42, %43, %44, %45, %46, %47, %48, %49, %50, %51, %52, %53, %54, %55}, {%56,%57,%58,%59}, db, 1, 1, 1, 0;\n}\n"
    : "+f"(d[8]), "+f"(d[9]), "+f"(d[10]), "+f"(d[11]), "+f"(d[12]), "+f"(d[13]), "+f"(d[14]), "+f"(d[15]), "+f"(d[16]), "+f"(d[17]), "+f"(d[18]), "+f"(d[19]), "+f"(d[20]), "+f"(d[21]), "+f"(d[22]), "+f"(d[23]), "+f"(d[24]), "+f"(d[25]), "+f"(d[26]), "+f"(d[27]), "+f"(d[28]), "+f"(d[29]), "+f"(d[30]), "+f"(d[31]), "+f"(d[32]), "+f"(d[33]), "+f"(d[34]), "+f"(d[35]), "+f"(d[36]), "+f"(d[37]), "+f"(d[38]), "+f"(d[39]), "+f"(d[40]), "+f"(d[41]), "+f"(d[42]), "+f"(d[43]), "+f"(d[44]), "+f"(d[45]), "+f"(d[46]), "+f"(d[47]), "+f"(d[48]), "+f"(d[49]), "+f"(d[50]), "+f"(d[51]), "+f"(d[52]), "+f"(d[53]), "+f"(d[54]), "+f"(d[55]), "+f"(d[56]), "+f"(d[57]), "+f"(d[58]), "+f"(d[59]), "+f"(d[60]), "+f"(d[61]), "+f"(d[62]), "+f"(d[63])
    : "r"(a0), "r"(a1), "r"(a2), "r"(a3), "r"(blo));
}
template<> __device__ __forceinline__ void wgmma_rs_hi<128>(float (&d)[64], uint32_t a0, uint32_t a1, uint32_t a2, uint32_t a3, uint32_t blo){
  asm volatile("{\n.reg .b64 db;\nmov.b64 db, {%68,8};\nwgmma.mma_async.sync.aligned.m64n128k16.f32.bf16.bf16 {%0, %1, %2, %3, %4, %5, %6, %7, %8, %9, %10, %11, %12, %13, %14, %15, %16, %17, %18, %19, %20, %21, %22, %23, %24, %25, %26, %27, %28, %29, %30, %31, %32, %33, %34, %35, %36, %37, %38, %39, %40, %41, %42, %43, %44, %45, %46, %47, %48, %49, %50, %51, %52, %53, %54, %55, %56, %57, %58, %59, %60, %61, %62, %63}, {%64,%65,%66,%67}, db, 1, 1, 1, 0;\n}\n"
    : "+f"(d[0]), "+f"(d[1]), "+f"(d[2]), "+f"(d[3]), "+f"(d[4]), "+f"(d[5]), "+f"(d[6]), "+f"(d[7]), "+f"(d[8]), "+f"(d[9]), "+f"(d[10]), "+f"(d[11]), "+f"(d[12]), "+f"(d[13]), "+f"(d[14]), "+f"(d[15]), "+f"(d[16]), "+f"(d[17]), "+f"(d[18]), "+f"(d[19]), "+f"(d[20]), "+f"(d[21]), "+f"(d[22]), "+f"(d[23]), "+f"(d[24]), "+f"(d[25]), "+f"(d[26]), "+f"(d[27]), "+f"(d[28]), "+f"(d[29]), "+f"(d[30]), "+f"(d[31]), "+f"(d[32]), "+f"(d[33]), "+f"(d[34]), "+f"(d[35]), "+f"(d[36]), "+f"(d[37]), "+f"(d[38]), "+f"(d[39]), "+f"(d[40]), "+f"(d[41]), "+f"(d[42]), "+f"(d[43]), "+f"(d[44]), "+f"(d[45]), "+f"(d[46]), "+f"(d[47]), "+f"(d[48]), "+f"(d[49]), "+f"(d[50]), "+f"(d[51]), "+f"(d[52]), "+f"(d[53]), "+f"(d[54]), "+f"(d[55]), "+f"(d[56]), "+f"(d[57]), "+f"(d[58]), "+f"(d[59]), "+f"(d[60]), "+f"(d[61]), "+f"(d[62]), "+f"(d[63])
    : "r"(a0), "r"(a1), "r"(a2), "r"(a3), "r"(blo));
}

struct CvCtx {
  uint32_t kaddr, kvaddr, db0, dd, stg, zero;
  int src1, src2;
  bool s3, kodd, wrap;
};
template <int LO> __device__ __forceinline__ void cv_copy(float (&acc)[64]) {
#pragma unroll
  for (int i = LO; i < 64; i++) { float t; asm volatile("mov.b32 %0, %1;" : "=f"(t) : "f"(acc[i]) : "memory"); acc[i] = t; }
}
template <int G> __device__ __forceinline__ void cv_raw(uint32_t (&A)[4][4], uint32_t kaddr) {
#pragma unroll
  for (int i = 0; i < 4; i++) {
    const uint32_t a = kaddr + (4 * G + i) * 128;
    A[i][0] = lds32(a); A[i][1] = lds32(a + 4); A[i][3] = lds32(a + 8);
  }
}
__device__ __forceinline__ void cv_form(uint32_t (&A)[4][4]) {
#pragma unroll
  for (int i = 0; i < 4; i++) {
    asm volatile("prmt.b32 %0, %0, %1, 0x5432;" : "+r"(A[i][0]) : "r"(A[i][1]));
    asm volatile("prmt.b32 %0, %1, %2, 0x5432;" : "=r"(A[i][2]) : "r"(A[i][1]), "r"(A[i][3]));
  }
}
template <int J> __device__ __forceinline__ void cv_epi(const float (&acc)[64], float (&Ep)[2], const uint32_t (&so)[4], const CvCtx& c) {
  float E[4], o[2];
  const uint32_t kvw = lds32(c.kvaddr + J * 256);
  const int src1 = c.src1 | (kvw & c.zero);
#pragma unroll
  for (int x = 0; x < 4; x++) {
    const float ev = acc[8 * J + x], od = acc[8 * J + 4 + x], pv = J > 0 ? acc[J > 0 ? 8 * J - 4 + x : 0] : 0.f;
    const float send = c.kodd ? ev : (c.s3 ? pv : od);
    E[x] = (c.kodd ? od : ev) + __shfl_sync(0xffffffffu, send, src1);
  }
#pragma unroll
  for (int h = 0; h < 2; h++) {
    o[h] = E[2 * h] + __shfl_sync(0xffffffffu, c.wrap ? Ep[h] : E[2 * h + 1], c.src2);
    Ep[h] = E[2 * h + 1];
  }
  sts32(c.stg + ((J & 1) ? so[J >> 1] >> 16 : so[J >> 1] & 0xffff), hadd2(pack_bf16(o[0], o[1]), hmul2(__byte_perm(kvw, kvw, 0x1032), c.dd)));
}
template <int G> __device__ __forceinline__ void cv_rec(float (&acc)[64], uint32_t (&A)[4][4], float (&Ep)[2], const uint32_t (&so)[4], const CvCtx& c) {
  wgmma_fence();
#pragma unroll
  for (int i = 0; i < 4; i++) wgmma_rs_hi<128 - 16 * G>(acc, A[i][0], A[i][1], A[i][2], A[i][3], c.db0 - 4 * i);
  wgmma_commit();
  __syncwarp();
  uint32_t B[4][4];
  if constexpr (G < 7) cv_raw<G + 1>(B, c.kaddr);
  if constexpr (G > 0) cv_epi<G - 1>(acc, Ep, so, c);
  if constexpr (G < 7) cv_form(B);
  __syncwarp();
  wgmma_wait<0>();
  cv_copy<8 * G>(acc);
  if constexpr (G < 7) cv_rec<G + 1>(acc, B, Ep, so, c);
}
__device__ __forceinline__ uint32_t cv_stage(int slot) { return sb + (slot < 4 ? 40960 + slot * 4096 : 180224); }
__device__ __forceinline__ void cv_offsets(uint32_t (&so)[4]) {
  const int tid = tid_opaque() & 127, lane = tid & 31, r = lane >> 2, q = lane & 3;
  const int P = r < 4 ? q : 4 + ((q + 1) & 3);
  const int tb = 16 * (2 * P + ((r >> 1) & 1)) + 4 * (tid >> 5) + 2 * (r & 1);
#pragma unroll
  for (int J = 0; J < 8; J++) {
    const int t = 256 * J + tb, T = t / 160, tl = t - T * 160;
    const int qq = (T == NT1 - 1) ? (tl >> 5) : (tl / 40);
    int ck = 20 * T + ((tl - qq * ((T == NT1 - 1) ? 32 : 40)) >> 1);
    ck ^= (ck >> 3) & 7;
    const uint32_t o = ck * 16 + qq * 4;
    if (J & 1) so[J >> 1] |= o << 16; else so[J >> 1] = o;
  }
}
__device__ __forceinline__ void conv_channel(int slot, const uint32_t (&so)[4]) {
  const int tid = tid_opaque() & 127, w = tid >> 5, lane = tid & 31, r = lane >> 2, q = lane & 3;
  const int i_ = r >> 1, i0 = i_ & 1, i1 = i_ >> 1;
  const uint32_t cb = sb + CV_OFF + slot * CV_B;
  CvCtx c;
  c.dd = lds32(sb + EP_OFF + 4 * slot);
  c.kaddr = cb + CV_K - 32 + 4 * (8 * i_ + 2 * w + (r & 1) + 2 * q);
  c.db0 = desc_lo(cb + CV_U + 192, CV_PL);
  c.src1 = i1 == 0 ? (lane - q + 16 + ((q + 3) & 3)) : (lane - q - 16 + ((q + 1) & 3));
  c.s3 = (i1 == 1 && q == 3); c.kodd = (i1 == 1 && q < 3);
  const int P = i1 == 0 ? q : 4 + ((q + 1) & 3);
  const int Pm = (P + 7) & 7, qm = Pm < 4 ? Pm : ((Pm - 1) & 3);
  c.src2 = i0 == 1 ? lane - 8 : (16 * (Pm >> 2) + 8 + 4 * (r & 1) + qm);
  c.wrap = (i0 == 1 && P == 7);
  c.kvaddr = cb + CV_U + 192 + (1 - (r & 1)) * CV_PL + (2 * P + i0) * 16 + (3 - w) * 4;
  float acc[64], Ep[2] = {0.f, 0.f};
  uint32_t A[4][4];
  c.stg = cv_stage(slot);
#pragma unroll
  for (int i = 0; i < 64; i++) acc[i] = 0.f;
  mbar_wait(bars + 8 * (B_TAPS + slot));
  c.zero = lds32(cb);
  cv_raw<0>(A, c.kaddr);
  mbar_wait(bars + 8 * (B_CVFULL + slot));
  cv_form(A);
  cv_copy<0>(acc);
  cv_rec<0>(acc, A, Ep, so, c);
  cv_epi<7>(acc, Ep, so, c);
  fence_async_smem();
  mbar_arrive(bars + 8 * (B_CVDONE + slot));
}

template <int W> struct KvRegs { uint32_t k[19][W], v[16][W], s[W][4]; };
template <int W> __device__ __forceinline__ void kv_load(int m, int cl, KvRegs<W>& x) {
  const int lane = tid_opaque() & 31, tg = lane >> 3;
  const uint32_t pb = sb + KS_OFF + (cl >> 5) * KV_PIECE + 2 * (cl & 31) + 4 * W * (lane & 7);
  const uint32_t ka = pb + tg * 1216, va = pb + 4864 + tg * 1088 + 64;
  const uint32_t kh = (m == 0 && tg > 0) ? ka - 192 : ka;
#pragma unroll
  for (int c = 0; c < W; c++) {
    const float4 t = lds128f(sb + TAP_OFF + 8 * cl + 16 * (W * (lane & 7) + c));
    x.s[c][0] = __float_as_uint(t.x); x.s[c][1] = __float_as_uint(t.y); x.s[c][2] = __float_as_uint(t.z); x.s[c][3] = __float_as_uint(t.w);
  }
  mbar_wait(bars + 8 * (B_KV + (cl >> 5)));
#pragma unroll
  for (int i = 0; i < 19; i++) {
    const uint32_t a = (i < 3 ? kh : ka) + i * 64;
    if (W == 2) { float2 t = lds64f(a); x.k[i][0] = __float_as_uint(t.x); x.k[i][W - 1] = __float_as_uint(t.y); }
    else x.k[i][0] = lds32(a);
  }
#pragma unroll
  for (int i = 0; i < 16; i++) {
    if (W == 2) { float2 t = lds64f(va + i * 64); x.v[i][0] = __float_as_uint(t.x); x.v[i][W - 1] = __float_as_uint(t.y); }
    else x.v[i][0] = lds32(va + i * 64);
  }
}
template <int W> __device__ __forceinline__ void kv_finish(int m, int c0, KvRegs<W>& x) {
  const int lane = tid_opaque() & 31;
  uint8_t* dst = g_kv + ((c0 + 2 * W * (lane & 7)) * 4096 + (4 * m + (lane >> 3)) * 16);
#pragma unroll
  for (int c = 0; c < W; c++) {
    const uint32_t w0 = __byte_perm(x.s[c][0], x.s[c][2], 0x5410), w1 = __byte_perm(x.s[c][0], x.s[c][2], 0x7632);
    const uint32_t w2 = __byte_perm(x.s[c][1], x.s[c][3], 0x5410), w3 = __byte_perm(x.s[c][1], x.s[c][3], 0x7632);
#pragma unroll
    for (int i = 0; i < 16; i++) {
      uint32_t a = hmul2(x.k[i][c], w3);
      a = hadd2(a, hmul2(x.k[i + 1][c], w2)); a = hadd2(a, hmul2(x.k[i + 2][c], w1)); a = hadd2(a, hmul2(x.k[i + 3][c], w0));
      x.v[i][c] = hmul2(a, x.v[i][c]);
    }
#pragma unroll
    for (int e = 0; e < 2; e++)
#pragma unroll
      for (int f = 0; f < 2; f++) {
        uint32_t o[4];
#pragma unroll
        for (int qq = 0; qq < 4; qq++) o[qq] = __byte_perm(x.v[15 - 4 * qq - 2 * f][c], x.v[14 - 4 * qq - 2 * f][c], e ? 0x7632 : 0x5410);
        *(uint4*)(dst + (2 * c + e) * 4096 + f * 2048) = make_uint4(o[0], o[1], o[2], o[3]);
      }
  }
}
__device__ __forceinline__ void stat_table(int T1, unsigned want, int l) {
#pragma unroll 1
  for (int n = tid_opaque() & 127; n < (T1 == NT1 - 1 ? 128 : 160); n += 128) {
    const uint4* rp = &g_stats[8 * l * SEQ + 160 * T1 + n];
    float a[4], b[4];
    uint32_t it = 0;
    while (true) {
      bool ok = true;
#pragma unroll
      for (int i = 0; i < 4; i++) ok &= (rec_ld(rp + SEQ * i, a[i], b[i]) == want);
      if (ok) break;
      if (++it > SPIN_LIMIT) soft_trap();
    }
    const float m = 0.25f * ((a[0] + a[1]) + (a[2] + a[3]));
    float v = (b[0] + b[1]) + (b[2] + b[3]);
#pragma unroll
    for (int i = 0; i < 4; i++) v = fmaf(160.f * (a[i] - m), a[i] - m, v);
    const float rs = rsqrtf(v * (1.f / 640.f) + 1e-5f);
    sts64f(sb + STAB_OFF + n * 8, rs, -m * rs);
  }
  mbar_arrive(bars + 8 * (B_STAB + l));
  __syncwarp();
}

template <bool FIRST>
__device__ __forceinline__ void stats_publish(int which, int n0, int dg, unsigned tag, const float (&acc)[80]) {
  const int lane = tid_opaque() & 31, q = lane & 3;
  float sh[2] = {0.f, 0.f};
  if (FIRST) { sh[0] = __shfl_sync(0xffffffffu, acc[0], lane & ~3); sh[1] = __shfl_sync(0xffffffffu, acc[2], lane & ~3); }
  float s1[2] = {0.f, 0.f}, s2[2] = {0.f, 0.f}, t1[2] = {0.f, 0.f}, t2[2] = {0.f, 0.f};
#pragma unroll
  for (int j = 0; j < 20; j++)
#pragma unroll
    for (int h = 0; h < 2; h++) {
      float a = acc[4 * j + 2 * h], b = acc[4 * j + 2 * h + 1];
      if (FIRST) { a -= sh[h]; b -= sh[h]; }
      s1[h] += a; t1[h] += b; s2[h] = fmaf(a, a, s2[h]); t2[h] = fmaf(b, b, t2[h]);
    }
#pragma unroll
  for (int h = 0; h < 2; h++) {
    s1[h] += t1[h]; s2[h] += t2[h];
    s1[h] += __shfl_xor_sync(0xffffffffu, s1[h], 1); s2[h] += __shfl_xor_sync(0xffffffffu, s2[h], 1);
    s1[h] += __shfl_xor_sync(0xffffffffu, s1[h], 2); s2[h] += __shfl_xor_sync(0xffffffffu, s2[h], 2);
  }
  const int h = q & 1;
  const float a = h ? s1[1] : s1[0], b = h ? s2[1] : s2[0], c = h ? sh[1] : sh[0];
  const float mean = a * (1.f / 160.f), m2v = fmaxf(b - a * mean, 0.f);
  if (FIRST) {
    rec_st(&g_stats[((q >> 1) * 4 + dg) * SEQ + n0 + 8 * h], mean + c, m2v, q < 2 ? tag : tag - 1);
    rec_st(&g_stats[((q >> 1) * 4 + 8 + dg) * SEQ + n0 + 8 * h], mean + c, m2v, tag - 1);
  } else if (q < 2) rec_st(&g_stats[(which * 4 + dg) * SEQ + n0 + 8 * h], mean, m2v, tag);
}
__device__ __forceinline__ void stats_combine(float mi, float m2, float& mean, float& rstd) {
  float m = mi + __shfl_xor_sync(0xffffffffu, mi, 1);
  m += __shfl_xor_sync(0xffffffffu, m, 2);
  m *= 0.25f;
  float d = mi - m;
  float v = fmaf(160.f * d, d, m2);
  v += __shfl_xor_sync(0xffffffffu, v, 1);
  v += __shfl_xor_sync(0xffffffffu, v, 2);
  mean = m; rstd = rsqrtf(v * (1.f / 640.f) + 1e-5f);
}
__device__ __forceinline__ void stats_get(int which, int n0, unsigned tag, float (&mean)[2], float (&rstd)[2]) {
  const int q = tid_opaque() & 3;
  const uint4* p0 = &g_stats[(which * 4 + q) * SEQ + n0];
  float a0, b0, a1, b1;
  uint32_t it = 0;
  while (true) {
    unsigned t0 = rec_ld(p0, a0, b0), t1 = rec_ld(p0 + 8, a1, b1);
    if (t0 == tag && t1 == tag) break;
    if (++it > SPIN_LIMIT) soft_trap();
  }
  __syncwarp();
  stats_combine(a0, b0, mean[0], rstd[0]);
  stats_combine(a1, b1, mean[1], rstd[1]);
}
__device__ __forceinline__ void x0_load(float (&acc)[80]) {
  const int t = tid_opaque() & 127;
  const uint32_t xa = sb + XT_OFF + (16 * (t >> 5) + ((t & 31) >> 2)) * 320 + 8 * (t & 3);
  mbar_wait(bars + 8 * B_XT);
#pragma unroll
  for (int h = 0; h < 2; h++)
#pragma unroll
    for (int J = 0; J < 10; J++) {
      const float2 v = lds64f(xa + h * 2560 + 32 * J);
      const uint32_t x = __float_as_uint(v.x), y = __float_as_uint(v.y);
      acc[8 * J + 2 * h] = bf_lo(x); acc[8 * J + 2 * h + 1] = bf_hi(x);
      acc[8 * J + 4 + 2 * h] = bf_lo(y); acc[8 * J + 4 + 2 * h + 1] = bf_hi(y);
    }
}

__global__ void __launch_bounds__(512, 1) fused_kernel(const __grid_constant__ Params p) {
  extern __shared__ __align__(1024) uint8_t smem_raw[];
  const int tid = threadIdx.x, lane = tid & 31;
  const int wid = __shfl_sync(0xffffffffu, tid >> 5, 0), wg = wid >> 2;
  unsigned smid; asm volatile("mov.u32 %0, %%smid;" : "=r"(smid));
  if (smid >= 132 || smem_u32(smem_raw) != sb) soft_trap();
  int role;
  {
  const int side = smid & 1;
  int gpc, gi;
  {
    int tpc = smid >> 1;
    if (tpc < 32) { gpc = tpc & 7; gi = tpc >> 3; }
    else if (tpc < 60) { gpc = 1 + (tpc - 32) % 7; gi = 4 + (tpc - 32) / 7; }
    else if (tpc < 62) { gpc = tpc - 54; gi = 8; }
    else { gpc = 0; gi = tpc - 58; }
  }
  const int pos = 8 * gpc + gi + (gpc == 7 ? 1 : 0);
  if (pos == 65) {
    if (tid < 32) {
      const unsigned tag = ld_rlx(g_epoch);
      for (int i = lane; i < NT1 * 16; i += 32)
        if ((i & 15) < 10) { uint32_t it = 0; while ((int)(ld_rlx(&g_hflag[((i >> 4) * 32 + (i & 15)) * 8]) - tag) < 0) { __nanosleep(500); if (++it > SPIN_LIMIT) soft_trap(); } }
    }
    return;
  }
  int T1, GP;
  if (pos < 52) { int hh = pos / 26, x = pos - 26 * hh; T1 = x >> 1; GP = 2 * hh + (x & 1); }
  else { T1 = pos - 52; GP = 4; }
  const bool last = (T1 == NT1 - 1);
  const bool has2 = gi < 8;
  const int m2 = 8 * (gpc >> 1) + gi, dg = 2 * (gpc & 1) + side;
  role = T1 | (GP << 4) | (side << 7) | (m2 << 8) | (dg << 14) | ((int)has2 << 16);

  const int cch0 = 5 * (32 * dg + m2);
  if (wg < 2) {
    if (wid < 2) {
      const int ch = 128 * GP + 64 * wid + 32 * side + lane;
      uint32_t r0 = ldv16(p.lre + ch), r1 = ldv16(p.lim + ch), r2 = ldv16(p.logdt + ch);
      asm volatile("bar.arrive 5, 512;" : "+r"(r0), "+r"(r1), "+r"(r2)::"memory");
      const float lr = bf_lo(r0), li = bf_lo(r1), ld = bf_lo(r2);
      const float dt = __bfloat162float(__float2bfloat16_rn(expf(ld)));
      const float mag = expf(dt * lr);
      float sn, cs; sincosf(dt * li, &sn, &cs);
      const float ar = mag * cs, ai = mag * sn;
      const float inv = 2.f / (lr * lr + li * li);
      const uint32_t ad = sb + CTAB_OFF + (32 * wid + lane) * 24;
      sts64f(ad, ar, ai);
      sts64f(ad + 8, ((ar - 1.f) * lr + ai * li) * inv, (ai * lr - (ar - 1.f) * li) * inv);
      if (tid == 0) TS(46);
      __syncwarp();
      bar_sync(7, 96);
      mbar_arrive(bars + 8 * B_CTAB);
    } else {
      if (elect_one()) {
        if (wid < 5) {
#pragma unroll
          for (int i = 0; i < 27; i++) mbar_init(bars + 8 * (4 + 27 * (wid - 2) + i), 2);
        } else {
#pragma unroll
          for (int i = 0; i < 15; i++) mbar_init(bars + 8 * (85 + 15 * (wid - 5) + i), 1);
        }
        asm volatile("fence.mbarrier_init.release.cluster;" ::: "memory");
      }
      __syncwarp();
      bar_sync(5, 512);
      if (wid == 2) { asm volatile("bar.arrive 6, 64;" ::: "memory"); asm volatile("bar.arrive 7, 96;" ::: "memory"); }
    }
  } else if (wg == 2 || wid == 14) {
    uint2 bv[2][5];
    const int c = wid == 14 ? 4 : wid - 8;
    const unsigned tag0 = ld_rlx(g_epoch);
#pragma unroll
    for (int x = 0; x < 2; x++)
#pragma unroll
      for (int i = 0; i < 5; i++) bv[x][i] = ldv64((const uint2*)((x ? p.bim : p.bre) + (has2 ? cch0 + c : 0) * DM) + lane + 32 * i);
    bar_sync(5, 512);
#pragma unroll
    for (int i = 0; i < 5; i++) asm volatile("" : "+r"(bv[0][i].x), "+r"(bv[0][i].y), "+r"(bv[1][i].x), "+r"(bv[1][i].y)::"memory");
    if (has2) {
      float sv[2];
#pragma unroll
      for (int x = 0; x < 2; x++) {
        float a = 0.f;
#pragma unroll
        for (int i = 0; i < 5; i++) a += (bf_lo(bv[x][i].x) + bf_hi(bv[x][i].x)) + (bf_lo(bv[x][i].y) + bf_hi(bv[x][i].y));
        sv[x] = a;
      }
#pragma unroll
      for (int o = 16; o > 0; o >>= 1) { sv[0] += __shfl_xor_sync(0xffffffffu, sv[0], o); sv[1] += __shfl_xor_sync(0xffffffffu, sv[1], o); }
      if (lane < 2) rec_st(&g_sB[(cch0 + c) * 2 + lane], sv[0], sv[1], tag0);
      if (tid == 256) TS(47);
    }
  } else if (wid == 13) {
    uint4 tv[3];
    const uint32_t e0 = ld_rlx(g_epoch);
    uint32_t e1 = ldv16(p.ssmD + min(cch0 + lane, 639));
    const uint4 dv = ldv128((const uint4*)(p.dskip + 160 * dg) + min(lane, 19));
#pragma unroll
    for (int i = 0; i < 3; i++) tv[i] = ldv128((const uint4*)(p.shiftk + 640 * dg) + min(lane + 32 * i, 79));
    bar_sync(5, 512);
    asm volatile("" : "+r"(e1)::"memory");
    sts128(sb + DTAB_OFF + 16 * min(lane, 19), dv);
#pragma unroll
    for (int i = 0; i < 3; i++) sts128(sb + TAP_OFF + 16 * min(lane + 32 * i, 79), tv[i]);
    if (lane < 6) sts32(sb + EP_OFF + 4 * lane, lane < 5 ? e1 | (e1 << 16) : e0);
    mbar_arrive(bars + 8 * B_CTAB);
    __syncwarp();
    if (lane == 0) { mbar_arrive(bars + 8 * B_EP); TS(53); }
  } else if (wid == 12) {
    if (elect_one()) {
#pragma unroll
      for (int k = 0; k < S1; k++) mbar_init(bars + 8 * (B_G1FULL + k), 1);
#pragma unroll
      for (int k = 0; k < 16; k++) mbar_init(bars + 8 * (B_XT + k), 1);
      asm volatile("fence.mbarrier_init.release.cluster;" ::: "memory");
      TS(45);
    }
    __syncwarp();
    asm volatile("bar.arrive 5, 512;" ::: "memory");
    if (elect_one()) {
#pragma unroll 1
      for (int k = 0; k < S1; k++) {
        const uint32_t fb = bars + 8 * (B_G1FULL + k);
        mbar_expect_tx(fb, G1_STAGE);
        tma4(sb + k * G1_STAGE + G1_XOFF, last ? &p.mXl : &p.mX, 64 * k, 0, 0, last ? 0 : 80 * T1, fb);
        tma5(sb + k * G1_STAGE, &p.mB, 64 * k, 0, 0, 4 * side, 2 * GP, fb);
      }
      TS(44);
    }
    __syncwarp();
    bar_sync(6, 64);
  } else {
    if (elect_one()) {
#pragma unroll
      for (int i = 0; i < 13; i++) mbar_init(bars + 8 * (B_CVDONE + i), 128);
      asm volatile("fence.mbarrier_init.release.cluster;" ::: "memory");
    }
    __syncwarp();
    bar_sync(5, 512);
  }
  if (tid == 128) TS(0);
  }

  if (wg == 3) {
    asm volatile("setmaxnreg.dec.sync.aligned.u32 56;");
    ROLE(role)
    const int pw = wid & 3;
    if (pw == 3 && has2) {
      mbar_wait(bars + 8 * (B_G1FULL + 0));
      if (elect_one()) {
        mbar_expect_tx(bars + 8 * B_XT, 20480);
#pragma unroll
        for (int h = 0; h < 2; h++) {
          const int ng = 8 * m2 + 4 * h, T = ng / 20;
          tma4(sb + XT_OFF + h * 10240, T == NT1 - 1 ? &p.mXtl : &p.mXt, 160 * dg, 0, 0, T == NT1 - 1 ? ng - 240 : ng + 60 * T, bars + 8 * B_XT);
        }
      }
#pragma unroll 1
      for (int c = 0; c < 5; c++) {
        mbar_wait(bars + 8 * (c == 0 ? B_G1FULL + 2 : B_XT + (c < 2 ? 0 : c - 1)));
        if (elect_one()) {
          const uint32_t fb = bars + 8 * (B_KV + c);
          mbar_expect_tx(fb, KV_PIECE);
          tma3(sb + KS_OFF + c * KV_PIECE, &p.mK, 160 * dg + 32 * c, 64 * m2 - 3, 0, fb);
          tma3(sb + KS_OFF + c * KV_PIECE + 4864, &p.mV, 160 * dg + 32 * c, 64 * m2 - 1, 0, fb);
        }
      }
    }
    unsigned tag = 0;
    if (pw > 0) { mbar_wait(bars + 8 * B_EP); tag = lds32(sb + EP_OFF + 20); }
    if (pw == 2) {
#pragma unroll 1
      for (int i = 0; i < 2; i++) {
        float a, b;
        rec_poll(&g_sB[(128 * GP + 64 * i + 32 * side + lane) * 2], tag, a, b);
        sts64f(sb + CTAB_OFF + (32 * i + lane) * 24 + 16, a, b);
      }
      mbar_arrive(bars + 8 * B_CTAB);
      if (lane == 0) TS(54);
    }
    if (pw >= 2 && has2) {
      KvRegs<1> x;
      kv_load<1>(m2, 128 + 16 * (pw - 2), x);
      kv_finish<1>(m2, 160 * dg + 128 + 16 * (pw - 2), x);
      if (tid == 448) TS(51);
      bar_sync(3, 192);
      if (tid == 448) { mbar_arrive(bars + 8 * B_PREP); st_rel(&g_kvflag[(dg * 32 + m2) * 8], tag); TS(30); }
      __syncwarp();
    }
    if (pw == 0) {
      if (elect_one()) {
#pragma unroll 1
        for (int l = 0; l < 2; l++) {
          const uint32_t fb0 = bars + 8 * (B_G1FULL + 10 * l), wb = bars + 8 * (B_G1DONE + 9 * l - S1);
          const uint32_t free0 = bars + 8 * (has2 ? B_G2DONE + 19 : B_G1DONE + 9);
          uint32_t dst = sb;
#pragma unroll 1
          for (int k = l == 0 ? S1 : 0; k < 10; k++) {
            mbar_wait(k >= S1 + l ? wb + 8 * k : free0);
            mbar_expect_tx(fb0 + 8 * k, 16384);
            tma5(dst, &p.mB, 64 * k, 0, 0, 4 * side, 2 * GP, fb0 + 8 * k);
            dst += G1_STAGE; if (dst == sb + (S1 + l) * G1_STAGE) dst = sb;
          }
          if (has2) {
            const uint32_t fb2 = bars + 8 * (B_G2FULL + 20 * l), wb2 = bars + 8 * (B_G2DONE + 19 * l - 6);
            dst = sb + G2_WOFF;
            int kc = 0;
#pragma unroll 1
            for (int k = 0; k < 20; k++) {
              mbar_wait(k >= 6 + l ? wb2 + 8 * k : (k == 5 ? bars + 8 * B_XFREE : bars + 8 * (B_G1DONE + 10 * l + 9)));
              mbar_expect_tx(fb2 + 8 * k, G2_WB);
              tma5(dst, &p.mCre + (k & 1), kc, 0, 0, 0, 10 * dg, fb2 + 8 * k);
              kc += (k & 1) << 7; if (k == 9) kc = 64;
              dst += G2_WB; if (dst == sb + G2_WOFF + (6 + l) * G2_WB) dst = sb + G2_WOFF;
            }
          }
        }
      }
    } else if (pw == 1) {
#pragma unroll 1
      for (int l = 0; l < 2; l++) {
        if (l == 0) {
          if (elect_one()) {
            uint32_t dst = sb + G1_XOFF;
#pragma unroll 1
            for (int k = S1; k < 10; k++) {
              mbar_wait(bars + 8 * (B_G1DONE + k - S1));
              mbar_expect_tx(bars + 8 * (B_G1FULL + k), 20480);
              tma4(dst, last ? &p.mXl : &p.mX, 64 * k, 0, 0, last ? 0 : 80 * T1, bars + 8 * (B_G1FULL + k));
              dst += G1_STAGE; if (k == 2 * S1 - 1) dst = sb + G1_XOFF;
            }
          }
        } else {
          mbar_wait(bars + 8 * (has2 ? B_G2DONE + 19 : B_G1DONE + 9));
          const int mlo = (160 * T1) >> 6, nf = last ? 8 : 12;
          if (lane < nf) flag_poll(&g_uflag[(4 * mlo + lane) * 8], tag);
          __syncwarp();
          fence_async_global();
          if (elect_one()) {
            TS(20);
            const int bytes = last ? 16384 : 20480;
            const uint8_t* src = g_u + T1 * 204800;
            uint32_t dst = sb + G1_XOFF;
#pragma unroll 1
            for (int k = 0; k < 10; k++) {
              if (k > S1) mbar_wait(bars + 8 * (B_G1DONE + 9 - S1 + k));
              mbar_expect_tx(bars + 8 * (B_G1FULL + 10 + k), bytes);
              bulk_g2s(dst, src, bytes, bars + 8 * (B_G1FULL + 10 + k));
              src += 20480; dst += G1_STAGE; if (k == S1) dst = sb + G1_XOFF;
            }
          }
        }
        __syncwarp();
        if (has2) {
          mbar_wait(bars + 8 * (B_G1DONE + 10 * l + 9));
          const int Tlo = (64 * m2) / 160, Thi = (64 * m2 + 63) / 160;
          if ((lane & 15) < 10) flag_poll(&g_hflag[(((l * NT1 + (lane < 16 ? Tlo : Thi)) * 2) * 16 + (lane & 15)) * 8], tag);
          __syncwarp();
          fence_async_global();
          if (elect_one()) {
            TS(21 + 2 * l);
            const uint32_t fb2 = bars + 8 * (B_G2FULL + 20 * l), wb2 = bars + 8 * (B_G2DONE + 18 * l - SX2);
            const uint8_t* src = g_h + (l * 32 + m2) * 163840;
            uint32_t dst = sb;
#pragma unroll 1
            for (int k = 0; k < 20; k++) {
              if (k >= SX2 + 2 * l) mbar_wait(wb2 + 8 * k);
              if (k == 10) { mbar_wait(bars + 8 * (B_H1 + l)); fence_async_global(); }
              mbar_expect_tx(fb2 + 8 * k, G2_XB);
              bulk_g2s(dst, src, G2_XB, fb2 + 8 * k);
              src += 8192; dst += G2_XB; if (dst == sb + (SX2 + 2 * l) * G2_XB) dst = sb;
            }
          }
          __syncwarp();
        }
      }
    } else if (pw == 2) {
#pragma unroll 1
      for (int l = 0; l < 2; l++) {
        if (lane < 2) {
          mbar_wait(bars + 8 * (B_HST + 2 * l + lane));
          st_rel(&g_hflag[(((l * NT1 + T1) * 2 + lane) * 16 + 2 * GP + side) * 8], tag);
          if (lane == 0) TS(6 + 8 * l);
        }
        __syncwarp();
        if (l == 0 && has2 && elect_one()) {
#pragma unroll 1
          for (int c = 0; c < 5; c++) {
            mbar_wait(bars + 8 * (B_CVDONE + c));
            bulk_s2g(g_G + (cch0 + c) * 4096, cv_stage(c), 4096);
          }
          asm volatile("cp.async.bulk.commit_group;" ::: "memory");
          asm volatile("cp.async.bulk.wait_group 0;" ::: "memory");
          fence_async_global();
          st_rel(&g_gflag[(dg * 32 + m2) * 8], tag);
        }
        __syncwarp();
      }
    } else if (has2) {
      mbar_wait(bars + 8 * B_PREP);
#pragma unroll
      for (int c = 0; c < 5; c++) {
        const uint32_t cb = sb + CV_OFF + c * CV_B;
        const uint32_t a = lane < 8 ? cb + 16 * lane : (lane < 20 ? cb + CV_U + 16 * (lane - 8) : cb + CV_U + CV_PL + 16 * (lane - 20));
        asm volatile("st.shared.v4.u32 [%0], {%1,%1,%1,%1};" ::"r"(a), "r"(0) : "memory");
      }
      fence_async_smem();
      __syncwarp();
#pragma unroll 1
      for (int c = 0; c < 5; c++) {
        if (c >= 2) mbar_wait(bars + 8 * (B_TAPS + c - 2));
        if (elect_one()) {
          mbar_expect_tx(bars + 8 * (B_TAPS + c), 4096);
          bulk_g2s(sb + CV_OFF + c * CV_B + CV_K, p.ssmk + (size_t)(cch0 + c) * SEQ, 4096, bars + 8 * (B_TAPS + c));
        }
      }
      if (elect_one()) {
        asm volatile("prefetch.tensormap [%0];" ::"l"(&p.mCre) : "memory");
        asm volatile("prefetch.tensormap [%0];" ::"l"(&p.mCim) : "memory");
        asm volatile("prefetch.tensormap [%0];" ::"l"(&p.mG) : "memory");
      }
      flag_poll(&g_kvflag[(dg * 32 + lane) * 8], tag);
      __syncwarp();
      fence_async_global();
      if (lane == 0) TS(28);
      if (elect_one()) {
#pragma unroll
        for (int c = 0; c < 5; c++) {
          const uint32_t fb = bars + 8 * (B_CVFULL + c), cb = sb + CV_OFF + c * CV_B + CV_U + 192;
          mbar_expect_tx(fb, 4096);
          bulk_g2s(cb, g_kv + (size_t)(cch0 + c) * 4096, 2048, fb);
          bulk_g2s(cb + CV_PL, g_kv + (size_t)(cch0 + c) * 4096 + 2048, 2048, fb);
        }
      }
      const unsigned* hf = &g_hflag[(((lane < 16 ? (64 * m2) / 160 : (64 * m2 + 63) / 160) * 2 + 1) * 16 + min(lane & 15, 9)) * 8];
      mbar_wait(bars + 8 * (B_CVDONE + 0));
      if (elect_one()) { l2_prefetch(p.cre + (size_t)cch0 * DM, 6400); l2_prefetch(p.cim + (size_t)cch0 * DM, 6400); }
      flag_poll(hf, tag);
      __syncwarp();
      if (lane == 0) { mbar_arrive(bars + 8 * B_H1); TS(22); }
      mbar_wait(bars + 8 * (B_CVDONE + 4));
      flag_poll(&g_gflag[(dg * 32 + lane) * 8], tag);
      __syncwarp();
      fence_async_global();
      if (lane == 0) TS(29);
      if (elect_one()) {
        mbar_expect_tx(bars + 8 * B_GFULL, 20480);
        tma5(sb + G_OFF, &p.mG, 64 * m2, 0, 0, 0, 10 * dg, bars + 8 * B_GFULL);
      }
      mbar_wait(bars + 8 * (B_G1DONE + 19));
      flag_poll(hf + NT1 * 256, tag);
      __syncwarp();
      if (lane == 0) { mbar_arrive(bars + 8 * (B_H1 + 1)); TS(24); }
    }
  } else {
    asm volatile("setmaxnreg.inc.sync.aligned.u32 152;");
    const int w = wid & 3;
    mbar_wait(bars + 8 * B_EP);
    const unsigned tag = lds32(sb + EP_OFF + 20);
    if (wg == 2) {
      ROLE(role)
      if (has2) {
        const int n0 = 64 * m2 + 16 * w + (lane >> 2);
        KvRegs<2> x;
        {
          float xs[80];
          x0_load(xs);
          stats_publish<true>(0, n0, dg, tag, xs);
        }
        if (tid == 256) TS(31);
        kv_load<2>(m2, 32 * w, x);
        if (tid == 352) TS(50);
        kv_finish<2>(m2, 160 * dg + 32 * w, x);
        if (tid == 352) TS(52);
        asm volatile("bar.arrive 3, 192;" ::: "memory");
      } else if (tid == 256) mbar_arrive(bars + 8 * B_PREP);
      stat_table(T1, tag, 0);
      if (tid == 256) TS(26);
      if (!has2) { mbar_wait(bars + 8 * (B_G1FULL + 11)); stat_table(T1, tag, 1); }
    }
#pragma unroll 1
    for (int l = 0; l < 2; l++) {
      if (wg < 2) {
        float acc[80];
#pragma unroll
        for (int i = 0; i < 80; i++) acc[i] = 0.f;
        ROLE(role)
        const int tid = tid_opaque(), r = (tid & 31) >> 2, q = tid & 3;
        const int ch = 128 * GP + 64 * wg + 32 * side + 8 * w + r;
        fence_regs(acc);
        {
          uint32_t alo = desc_lo(sb, 16) + wg * 512, blo = l == 0 ? desc_lo(sb + G1_XOFF, 16) : desc_lo(sb + G1_XOFF, 128);
          const uint32_t bhi = l == 0 ? desc_hi(1024, 1) : desc_hi(1024, 0), xstep = l == 0 ? 2 : 16;
          const uint32_t aend = desc_lo(sb, 16) + (S1 + l) * (G1_STAGE >> 4);
          uint32_t fb = bars + 8 * (B_G1FULL + 10 * l);
          mbar_wait(fb);
          if (tid == 0) TS(1 + 8 * l);
#pragma unroll 1
          for (int k = 0; k < 10; k++) {
            uint32_t ok; const uint32_t nb = k < 9 ? fb + 8 : fb;
            wgmma_fence();
#pragma unroll
            for (int kk = 0; kk < 4; kk++) {
              wgmma_n160<0>(acc, alo + kk * 2, desc_hi(1024, 1), blo + kk * xstep, bhi);
              if (kk == 0) ok = mbar_test(nb);
            }
            wgmma_commit();
            alo += G1_STAGE >> 4; blo += G1_STAGE >> 4;
            if (alo >= aend) { alo -= (S1 + l) * (G1_STAGE >> 4); blo -= (S1 + l) * (G1_STAGE >> 4); }
            wgmma_wait<1>();
            if (k > 0 && (tid & 127) == 0) mbar_arrive(fb + 8 * (B_G1DONE - B_G1FULL - 1));
            if (!ok) mbar_wait(nb);
            if (l == 0 && k == PAUSE_K) { if (tid == 0) TS(48); mbar_wait(bars + 8 * B_PREP); if (tid == 0) TS(49); }
            fb += 8;
          }
        }
        mbar_wait(bars + 8 * B_CTAB);
        const uint32_t ca = sb + CTAB_OFF + (32 * wg + 8 * w + r) * 24;
        float2 lam = lds64f(ca), sB = lds64f(ca + 16);
        const float2 coef = lds64f(ca + 8), lamc = make_float2(lam.x, -lam.y);
        float m00 = coef.x, m01 = -coef.y, m10 = -coef.y, m11 = -coef.x;
        if (p.swap) { lam = lamc; sB = make_float2(sB.y, sB.x); m00 = -coef.y; m01 = coef.x; m10 = -coef.x; m11 = -coef.y; }
        float2 pL, p2L, pLq, p160q, p640;
        {
          float2 p2 = cmul(lam, lam), p4 = cmul(p2, p2), p8 = cmul(p4, p4), p16 = cmul(p8, p8), p32 = cmul(p16, p16);
          float2 p40 = cmul(p32, p8), p80 = cmul(p40, p40), p160 = cmul(p80, p80), p320 = cmul(p160, p160);
          p640 = cmul(p320, p320);
          pL = last ? p32 : p40;
          p2L = cmul(pL, pL);
          const float2 one = make_float2(1.f, 0.f);
          pLq = cmul((q & 1) ? pL : one, (q & 2) ? p2L : one);
          p160q = cmul((q & 1) ? p160 : one, (q & 2) ? p320 : one);
        }
        mbar_wait(bars + 8 * (B_STAB + l));
        wgmma_wait<0>();
        fence_regs(acc);
        if ((tid & 127) == 0) { mbar_arrive(bars + 8 * (B_G1DONE + 10 * l + 9)); if (wg == 0) TS(2 + 8 * l); }
        float2 e = make_float2(0.f, 0.f), snap = e;
#pragma unroll
        for (int j = 0; j < 20; j++) {
          const float4 st = lds128f(sb + STAB_OFF + (8 * j + 2 * q) * 8);
          acc[4 * j + 0] = fmaf(acc[4 * j + 0], st.x, st.y * sB.x);
          acc[4 * j + 2] = fmaf(acc[4 * j + 2], st.x, st.y * sB.y);
          acc[4 * j + 1] = fmaf(acc[4 * j + 1], st.z, st.w * sB.x);
          acc[4 * j + 3] = fmaf(acc[4 * j + 3], st.z, st.w * sB.y);
          e = cfma(lam, e, make_float2(acc[4 * j + 0], acc[4 * j + 2]));
          e = cfma(lam, e, make_float2(acc[4 * j + 1], acc[4 * j + 3]));
          if (j == 15) snap = e;
        }
        if (last) e = snap;
        {
          float2 v = make_float2(__shfl_up_sync(0xffffffffu, e.x, 1, 4), __shfl_up_sync(0xffffffffu, e.y, 1, 4));
          if (q >= 1) e = cfma(pL, v, e);
          v = make_float2(__shfl_up_sync(0xffffffffu, e.x, 2, 4), __shfl_up_sync(0xffffffffu, e.y, 2, 4));
          if (q >= 2) e = cfma(p2L, v, e);
        }
        if (!last && (q == 3 || (q == 2 && l == 0))) rec_st(&g_E[((q == 3 ? l : 1) * NT1 + T1) * DM + ch], e.x, e.y, q == 3 ? tag : tag - 1);
        if (tid == 0) TS(3 + 8 * l);
        float2 ex = make_float2(__shfl_up_sync(0xffffffffu, e.x, 1, 4), __shfl_up_sync(0xffffffffu, e.y, 1, 4));
        if (q == 0) ex = make_float2(0.f, 0.f);
#pragma unroll
        for (int j = 0; j < 20; j++)
#pragma unroll
          for (int x = 0; x < 2; x++) {
            const float b0 = acc[4 * j + x], b1 = acc[4 * j + 2 + x];
            acc[4 * j + x] = fmaf(b0, m00, b1 * m01);
            acc[4 * j + 2 + x] = fmaf(b0, m10, b1 * m11);
          }
        float2 c;
        {
          float2 ev[3];
          uint32_t it = 0;
          while (true) {
            bool ok = true;
#pragma unroll
            for (int i = 0; i < 3; i++) {
              const int Tp = T1 - 1 - q - 4 * i;
              ev[i] = make_float2(0.f, 0.f);
              if (Tp >= 0) ok &= (rec_ld(&g_E[(l * NT1 + Tp) * DM + ch], ev[i].x, ev[i].y) == tag);
            }
            if (ok) break;
            if (++it > SPIN_LIMIT) soft_trap();
          }
          __syncwarp();
          c = cfma(p640, cfma(p640, ev[2], ev[1]), ev[0]);
          c = cmul(c, p160q);
          c.x += __shfl_xor_sync(0xffffffffu, c.x, 1); c.y += __shfl_xor_sync(0xffffffffu, c.y, 1);
          c.x += __shfl_xor_sync(0xffffffffu, c.x, 2); c.y += __shfl_xor_sync(0xffffffffu, c.y, 2);
        }
        if (tid == 0) TS(4 + 8 * l);
        c = cfma(pLq, c, ex);
        float2 hh = make_float2(fmaf(c.x, m00, c.y * m01), fmaf(c.x, m10, c.y * m11));
        uint8_t* hb = g_h + (size_t)l * (32 * 20 * 8192) + (10 * wg + 2 * GP) * 8192 + (4 * side + w) * 1024 + (tid_opaque() & 31) * 4;
#pragma unroll
        for (int j4 = 0; j4 < 5; j4++) {
          const int ng = 20 * T1 + 4 * j4;
          uint8_t* hp = hb + (size_t)(ng >> 3) * 163840 + (ng & 7) * 128;
#pragma unroll
          for (int jj = 0; jj < 4; jj++) {
            const int j = 4 * j4 + jj;
            const float2 h0 = cfma(lamc, hh, make_float2(acc[4 * j + 0], acc[4 * j + 2]));
            hh = cfma(lamc, h0, make_float2(acc[4 * j + 1], acc[4 * j + 3]));
            if (j4 < 4 || !last) {
              *(uint32_t*)(hp + jj * 128) = pack_bf16(h0.x, hh.x);
              *(uint32_t*)(hp + jj * 128 + 8192) = pack_bf16(h0.y, hh.y);
            }
          }
        }
        mbar_arrive(bars + 8 * (B_HST + 2 * l + wg));
        if (tid == 0) TS(5 + 8 * l);
      }
      if (l == 0) {
        ROLE(role)
        if (has2) {
          uint32_t so[4];
          cv_offsets(so);
          mbar_wait(bars + 8 * (B_G1DONE + 9));
#pragma unroll 1
          for (int c = wg == 2 ? 0 : 2 + wg; c < (wg == 2 ? 2 : 5); c += wg == 2 ? 1 : 2) conv_channel(c, so);
          if ((tid & 127) == 0) TS(wg == 2 ? 32 : 7 + wg);
        }
      }
      if (wg == 2) break;
    }
    if (wg == 2 && (role >> 16)) {
      float acc[80];
      float off[2] = {0.f, 0.f};
      x0_load(acc);
      mbar_arrive(bars + 8 * B_XFREE);
#pragma unroll 1
      for (int l = 0; l < 2; l++) {
        float mean[2], rstd[2];
        {
          ROLE(role)
          const int lane = tid_opaque() & 31;
          stats_get(2 * l, 64 * m2 + 16 * w + (lane >> 2), tag, mean, rstd);
          off[0] += mean[0]; off[1] += mean[1];
          mbar_wait(bars + 8 * B_CTAB);
#pragma unroll
          for (int J = 0; J < 10; J++) {
            const float2 dw = lds64f(sb + DTAB_OFF + 2 * (16 * J + 4 * (lane & 3)));
#pragma unroll
            for (int x = 0; x < 8; x++) {
              const int h = (x >> 1) & 1;
              const uint32_t gwd = __float_as_uint(x < 4 ? dw.x : dw.y);
              acc[8 * J + x] = (acc[8 * J + x] - mean[h]) * fmaf(rstd[h], (x & 1) ? bf_hi(gwd) : bf_lo(gwd), 1.f);
            }
          }
        }
        {
          const uint32_t aend = desc_lo(sb + SX2 * G2_XB, 1024) + l * (G2_XB >> 3), bend = desc_lo(sb + G2_WOFF + 6 * G2_WB, 16) + l * (G2_WB >> 4);
          uint32_t alo = desc_lo(sb, 1024), blo = desc_lo(sb + G2_WOFF, 16);
          uint32_t fb = bars + 8 * (B_G2FULL + 20 * l);
          fence_regs(acc);
          mbar_wait(fb);
          if (tid == 256) TS(33 + 6 * l);
#pragma unroll 1
          for (int k = 0; k < 20; k++) {
            if (l == 1 && (k & 3) == 3 && tid == 256) TS(56 + (k >> 2));
            uint32_t ok; const uint32_t nb = k < 19 ? fb + 8 : fb;
            wgmma_fence();
#pragma unroll
            for (int kk = 0; kk < 4; kk++) {
              wgmma_n160<1>(acc, alo + kk * 128, desc_hi(128, 0), blo + kk * 2, desc_hi(1024, 1));
              if (kk == 0) ok = mbar_test(nb);
            }
            wgmma_commit();
            alo += G2_XB >> 4; if (alo == aend) alo = desc_lo(sb, 1024);
            blo += G2_WB >> 4; if (blo == bend) blo = desc_lo(sb + G2_WOFF, 16);
            wgmma_wait<1>();
            if (k > 0 && tid == 256) mbar_arrive(fb + 8 * (B_G2DONE - B_G2FULL - 1));
            if (!ok) mbar_wait(nb);
            fb += 8;
          }
          wgmma_wait<0>();
          fence_regs(acc);
          if (tid == 256) TS(34 + 6 * l);
          if (tid == 256) mbar_arrive(bars + 8 * (B_G2DONE + 20 * l + 19));
        }
        ROLE(role)
        const int tq = tid_opaque() & 31, n0 = 64 * m2 + 16 * w + (tq >> 2);
        stats_publish<false>(2 * l + 1, n0, dg, tag, acc);
        uint32_t gf[10][4];
        mbar_wait(bars + 8 * B_GFULL);
        const uint32_t ga = sb + G_OFF + (8 * (tq >> 4) + (tq & 7)) * 128 + (((2 * w + ((tq >> 3) & 1)) ^ (m2 & 7) ^ (tq & 7)) << 4);
#pragma unroll
        for (int J = 0; J < 4; J++) ldsm4t(gf[J], ga + J * 2048);
        if (tid == 256) TS(35 + 6 * l);
        uint8_t* dst[2][2];
#pragma unroll
        for (int h = 0; h < 2; h++) {
          if (l == 0) {
            const int ng = 8 * m2 + 2 * w + h, T = ng / 20;
            uint8_t* ub = g_u + (T * 204800 + (ng - 20 * T) * 1024 + (tq & 2) * 64 + (tq & 28) * 4 + (tq & 1) * 8 + (5 * dg >> 1) * 20480);
            dst[h][1] = ub + ((dg & 1) ? 20480 - 512 : 0);
            dst[h][0] = ub + (dg & 1) * 512;
          } else {
            dst[h][0] = dst[h][1] = (uint8_t*)(p.out + (n_to_t(n0 + 8 * h) * DM + 160 * dg + 4 * (tq & 3)));
          }
        }
        stats_get(2 * l + 1, n0, tag, mean, rstd);
        if (tid == 256) TS(36 + 6 * l);
        off[0] += mean[0]; off[1] += mean[1];
#pragma unroll
        for (int J = 0; J < 10; J++) {
          asm volatile("" : "+r"(gf[J][0]), "+r"(gf[J][1]), "+r"(gf[J][2]), "+r"(gf[J][3])::"memory");
          if (J + 4 < 10) ldsm4t(gf[J + 4 < 10 ? J + 4 : 0], ga + (J + 4) * 2048);
#pragma unroll
          for (int x = 0; x < 8; x++) {
            const int h = (x >> 1) & 1;
            const uint32_t gwd = gf[J][x >> 1];
            acc[8 * J + x] = (acc[8 * J + x] - mean[h]) * fmaf(rstd[h], (x & 1) ? bf_hi(gwd) : bf_lo(gwd), 1.f);
          }
#pragma unroll
          for (int h = 0; h < 2; h++) {
            if (l == 0)
              *(uint2*)(dst[h][(J >> 1) & 1] + (J >> 2) * 20480 + (J & 3) * 256) =
                  make_uint2(pack_bf16(acc[8 * J + 2 * h], acc[8 * J + 2 * h + 1]), pack_bf16(acc[8 * J + 4 + 2 * h], acc[8 * J + 5 + 2 * h]));
            else
              *(float4*)(dst[h][0] + 64 * J) = make_float4(acc[8 * J + 2 * h] + off[h], acc[8 * J + 2 * h + 1] + off[h],
                                                           acc[8 * J + 4 + 2 * h] + off[h], acc[8 * J + 5 + 2 * h] + off[h]);
          }
        }
        if (l == 0) {
          bar_sync(3, 128);
          if (tid == 256) { TS(37); st_rel(&g_uflag[(4 * m2 + dg) * 8], tag); TS(38); }
          stats_publish<false>(2, n0, dg, tag, acc);
          mbar_wait(bars + 8 * (B_G1FULL + 11));
          stat_table(T1, tag, 1);
          if (tid == 256) TS(27);
        } else {
          if (tid == 256) {
            TS(43);
            if (m2 == 31 && dg == 3) asm volatile("st.relaxed.gpu.global.u32 [%0], %1;" ::"l"(g_epoch), "r"(tag + 1) : "memory");
          }
        }
      }
    }
  }
}

typedef CUresult (*EncFn)(CUtensorMap*, CUtensorMapDataType, cuuint32_t, void*, const cuuint64_t*, const cuuint64_t*,
                          const cuuint32_t*, const cuuint32_t*, CUtensorMapInterleave, CUtensorMapSwizzle,
                          CUtensorMapL2promotion, CUtensorMapFloatOOBfill);

void encode(EncFn fn, CUtensorMap* m, const void* ptr, int rank, const cuuint64_t* dims, const cuuint64_t* strides, const cuuint32_t* box,
            CUtensorMapSwizzle swz = CU_TENSOR_MAP_SWIZZLE_128B) {
  cuuint32_t es[5] = {1, 1, 1, 1, 1};
  fn(m, CU_TENSOR_MAP_DATA_TYPE_BFLOAT16, rank, (void*)ptr, dims, strides, box, es, CU_TENSOR_MAP_INTERLEAVE_NONE,
     swz, swz == CU_TENSOR_MAP_SWIZZLE_128B ? CU_TENSOR_MAP_L2_PROMOTION_L2_128B : CU_TENSOR_MAP_L2_PROMOTION_L2_64B, CU_TENSOR_MAP_FLOAT_OOB_FILL_NONE);
}

}

extern "C" void kernel_launch(void* const* d_in, const int* in_sizes, int n_in, void* d_out, int out_size) {
  (void)in_sizes; (void)n_in; (void)out_size;
  Params p;
  typedef const __nv_bfloat16* BP;
  p.x = (BP)d_in[0]; p.lre = (BP)d_in[1]; p.lim = (BP)d_in[2]; p.bre = (BP)d_in[3]; p.bim = (BP)d_in[4];
  p.cre = (BP)d_in[5]; p.cim = (BP)d_in[6]; p.logdt = (BP)d_in[7]; p.dskip = (BP)d_in[8];
  p.k = (BP)d_in[10]; p.v = (BP)d_in[11]; p.shiftk = (BP)d_in[12]; p.ssmk = (BP)d_in[13]; p.ssmD = (BP)d_in[14];
  p.out = (float*)d_out;
  void* fnp = nullptr;
  cudaDriverEntryPointQueryResult qr;
  cudaGetDriverEntryPoint("cuTensorMapEncodeTiled", &fnp, cudaEnableDefault, &qr);
  EncFn fn = (EncFn)fnp;
  void* gG = nullptr;
  cudaGetSymbolAddress(&gG, g_G);
  const cuuint64_t RB = DM * 2;
  {
    p.swap = p.bim < p.bre;
    const char* lo = (const char*)(p.swap ? p.bim : p.bre); const char* hi = (const char*)(p.swap ? p.bre : p.bim);
    cuuint64_t dims[5] = {640, 8, 2, 8, 10}, st[4] = {RB, (cuuint64_t)(hi - lo), 8 * RB, 64 * RB}; cuuint32_t box[5] = {64, 8, 2, 4, 2};
    encode(fn, &p.mB, lo, 5, dims, st, box);
  }
  {
    cuuint64_t dims[5] = {640, 2, 4, 2, 40}, st[4] = {RB, 4 * RB, 2 * RB, 16 * RB}; cuuint32_t box[5] = {64, 2, 4, 2, 10};
    encode(fn, &p.mCre, p.cre, 5, dims, st, box); encode(fn, &p.mCim, p.cim, 5, dims, st, box);
    cuuint64_t dimg[5] = {2048, 2, 4, 2, 40}, stg[4] = {4096, 4 * 4096, 2 * 4096, 16 * 4096};
    encode(fn, &p.mG, gG, 5, dimg, stg, box);
  }
  {
    cuuint64_t dims[4] = {640, 2, 4, 900}, st[3] = {RB, 40 * RB, 2 * RB}; cuuint32_t box[4] = {64, 2, 4, 20};
    encode(fn, &p.mX, p.x, 4, dims, st, box);
    cuuint64_t diml[4] = {640, 2, 4, 16}, stl[3] = {RB, 32 * RB, 2 * RB};
    encode(fn, &p.mXl, p.x + (size_t)1920 * DM, 4, diml, stl, box);
    cuuint32_t boxt[4] = {160, 2, 4, 4};
    encode(fn, &p.mXt, p.x, 4, dims, st, boxt, CU_TENSOR_MAP_SWIZZLE_NONE);
    encode(fn, &p.mXtl, p.x + (size_t)1920 * DM, 4, diml, stl, boxt, CU_TENSOR_MAP_SWIZZLE_NONE);
    cuuint64_t dk[3] = {640, 2000, 4}, sk[2] = {RB, 16 * RB}; cuuint32_t bk[3] = {32, 19, 4}, bv[3] = {32, 17, 4};
    encode(fn, &p.mK, p.k, 3, dk, sk, bk, CU_TENSOR_MAP_SWIZZLE_NONE);
    encode(fn, &p.mV, p.v, 3, dk, sk, bv, CU_TENSOR_MAP_SWIZZLE_NONE);
  }
  cudaFuncSetAttribute(fused_kernel, cudaFuncAttributeMaxDynamicSharedMemorySize, SMEM_BYTES);
  cudaLaunchConfig_t cfg = {};
  cfg.gridDim = dim3(132); cfg.blockDim = dim3(512); cfg.dynamicSmemBytes = SMEM_BYTES; cfg.stream = cudaStreamPerThread;
  cudaLaunchKernelEx(&cfg, fused_kernel, p);
}
```

```cpp
#include <cuda_runtime.h>
#include <cuda.h>
#include <cuda_bf16.h>
#include <stdint.h>

namespace {

constexpr int SEQ = 2048, DM = 640;
constexpr int NT1 = 13;
#define EXP 0
#define WPF1 1
#define WPF2 2
#define CPOLL 10
#define PAUSE_K 4
constexpr uint32_t SPIN_LIMIT = 1u << 22;

__device__ __align__(1024) uint8_t g_h[2 * 32 * 20 * 8192];
__device__ __align__(1024) uint8_t g_u[NT1 * 10 * 20480];
__device__ __align__(1024) uint8_t g_kv[DM * 4096];
__device__ __align__(1024) uint8_t g_G[DM * 4096];
__device__ __align__(128) uint4 g_E[2 * NT1 * DM];
__device__ __align__(128) uint4 g_stats[4 * 4 * SEQ];
__device__ __align__(128) uint4 g_sB[DM * 2];
__device__ __align__(128) unsigned g_hflag[2 * NT1 * 2 * 16 * 8];
__device__ __align__(128) unsigned g_uflag[32 * 4 * 8];
__device__ __align__(128) unsigned g_kvflag[4 * 32 * 8];
__device__ __align__(128) unsigned g_gflag[4 * 32 * 8];
__device__ __align__(128) unsigned g_epoch[32] = {1};
#define TS(i) do {} while (0)

struct Params {
  CUtensorMap mB, mCre, mCim, mX, mXl, mG, mK, mV, mXt, mXtl;
  const __nv_bfloat16 *x, *lre, *lim, *bre, *bim, *cre, *cim, *logdt, *dskip, *k, *v, *shiftk, *ssmk, *ssmD;
  float* out;
  int swap;
};

constexpr uint32_t sb = 1024;
constexpr uint32_t G1_STAGE = 36864, G1_XOFF = 16384;
constexpr int S1 = 4;
constexpr uint32_t XT_OFF = 159744, KS_OFF = 180224, KV_PIECE = 9216;
constexpr uint32_t G2_XB = 8192, G2_WB = 20480, G2_WOFF = 57344, G_OFF = 200704;
constexpr int SX2 = 5;
constexpr uint32_t CV_OFF = 184320, CV_K = 128, CV_PL = 2240, CV_U = CV_K + 4096, CV_B = 8704;
constexpr uint32_t MISC = 227840;
constexpr uint32_t BAR_OFF = MISC;
constexpr int B_G1FULL = 0, B_G1DONE = 20, B_G2FULL = 40,
              B_G2DONE = 85, B_GFULL = 125, B_PREP = 126, B_EP = 127, B_H1 = 128  ,
              B_CVDONE = 130, B_STAB = 135  , B_CTAB = 137, B_XFREE = 138, B_HST = 139  ,
              B_XT = 143, B_KV = 144  , B_TAPS = 149  , B_CVFULL = 154  , B_GO = 159  ;
constexpr uint32_t bars = sb + BAR_OFF;
constexpr uint32_t STAB_OFF = MISC + 1296;
constexpr uint32_t CTAB_OFF = STAB_OFF + 1280;
constexpr uint32_t DTAB_OFF = CTAB_OFF + 1536;
constexpr uint32_t EP_OFF = DTAB_OFF + 320;
constexpr uint32_t TAP_OFF = 147456;
constexpr uint32_t SMEM_BYTES = 232448;
static_assert(EP_OFF + 32 <= SMEM_BYTES, "smem");

__device__ __forceinline__ void soft_trap() { asm volatile("trap;"); }
__device__ __forceinline__ uint32_t smem_u32(const void* p) { return (uint32_t)__cvta_generic_to_shared(p); }
__device__ __forceinline__ void mbar_init(uint32_t bar, int cnt) { asm volatile("mbarrier.init.shared::cta.b64 [%0], %1;" ::"r"(bar), "r"(cnt) : "memory"); }
__device__ __forceinline__ void mbar_expect_tx(uint32_t bar, int bytes) { asm volatile("mbarrier.arrive.expect_tx.shared::cta.b64 _, [%0], %1;" ::"r"(bar), "r"(bytes) : "memory"); }
__device__ __forceinline__ void mbar_arrive(uint32_t bar) { asm volatile("mbarrier.arrive.shared::cta.b64 _, [%0];" ::"r"(bar) : "memory"); }
__device__ __forceinline__ void mbar_wait(uint32_t bar) {
  asm volatile(
      "{\n.reg .pred p;\n.reg .u32 c;\nmov.u32 c, 0;\n"
      "W_%=:\nmbarrier.try_wait.parity.shared::cta.b64 p, [%0], 0;\n@p bra D_%=;\n"
      "add.u32 c, c, 1;\nsetp.lt.u32 p, c, %1;\n@p bra W_%=;\ntrap;\nD_%=:\n}\n" ::"r"(bar), "n"(SPIN_LIMIT) : "memory");
}
__device__ __forceinline__ uint32_t mbar_test(uint32_t bar) {
  uint32_t ok;
  asm volatile("{\n.reg .pred p;\nmbarrier.test_wait.parity.shared::cta.b64 p, [%1], 0;\nselp.u32 %0, 1, 0, p;\n}\n" : "=r"(ok) : "r"(bar) : "memory");
  return ok;
}
__device__ __forceinline__ void tma3(uint32_t dst, const CUtensorMap* m, int c0, int c1, int c2, uint32_t bar) {
  asm volatile("cp.async.bulk.tensor.3d.shared::cluster.global.mbarrier::complete_tx::bytes [%0], [%1, {%3,%4,%5}], [%2];"
               ::"r"(dst), "l"(m), "r"(bar), "r"(c0), "r"(c1), "r"(c2) : "memory");
}
__device__ __forceinline__ void tma4(uint32_t dst, const CUtensorMap* m, int c0, int c1, int c2, int c3, uint32_t bar) {
  asm volatile("cp.async.bulk.tensor.4d.shared::cluster.global.mbarrier::complete_tx::bytes [%0], [%1, {%3,%4,%5,%6}], [%2];"
               ::"r"(dst), "l"(m), "r"(bar), "r"(c0), "r"(c1), "r"(c2), "r"(c3) : "memory");
}
__device__ __forceinline__ void tma5(uint32_t dst, const CUtensorMap* m, int c0, int c1, int c2, int c3, int c4, uint32_t bar) {
  asm volatile("cp.async.bulk.tensor.5d.shared::cluster.global.mbarrier::complete_tx::bytes [%0], [%1, {%3,%4,%5,%6,%7}], [%2];"
               ::"r"(dst), "l"(m), "r"(bar), "r"(c0), "r"(c1), "r"(c2), "r"(c3), "r"(c4) : "memory");
}
__device__ __forceinline__ void bulk_g2s(uint32_t dst, const void* src, int bytes, uint32_t bar) {
  asm volatile("cp.async.bulk.shared::cluster.global.mbarrier::complete_tx::bytes [%0], [%1], %2, [%3];"
               ::"r"(dst), "l"(src), "r"(bytes), "r"(bar) : "memory");
}
__device__ __forceinline__ void bulk_s2g(void* dst, uint32_t src, int bytes) {
  asm volatile("cp.async.bulk.global.shared::cta.bulk_group [%0], [%1], %2;" ::"l"(dst), "r"(src), "r"(bytes) : "memory");
}
__device__ __forceinline__ void l2_prefetch(const void* src, int bytes) {
  asm volatile("cp.async.bulk.prefetch.L2.global [%0], %1;" ::"l"(src), "r"(bytes) : "memory");
}
__device__ __forceinline__ void wgmma_fence() { asm volatile("wgmma.fence.sync.aligned;" ::: "memory"); }
__device__ __forceinline__ void wgmma_commit() { asm volatile("wgmma.commit_group.sync.aligned;" ::: "memory"); }
template <int N> __device__ __forceinline__ void wgmma_wait() { asm volatile("wgmma.wait_group.sync.aligned %0;" ::"n"(N) : "memory"); }
__host__ __device__ constexpr uint32_t desc_lo(uint32_t addr, uint32_t lbo) { return ((addr & 0x3FFFF) >> 4) | ((lbo >> 4) << 16); }
__host__ __device__ constexpr uint32_t desc_hi(uint32_t sbo, uint32_t swz) { return (sbo >> 4) | (swz << 30); }
__device__ __forceinline__ void bar_sync(int id, int n) { asm volatile("bar.sync %0, %1;" ::"r"(id), "r"(n) : "memory"); }
__device__ __forceinline__ uint32_t lds32(uint32_t a) { uint32_t v; asm volatile("ld.shared.u32 %0, [%1];" : "=r"(v) : "r"(a) : "memory"); return v; }
__device__ __forceinline__ float2 lds64f(uint32_t a) { float2 v; asm volatile("ld.shared.v2.f32 {%0,%1}, [%2];" : "=f"(v.x), "=f"(v.y) : "r"(a) : "memory"); return v; }
__device__ __forceinline__ float4 lds128f(uint32_t a) { float4 v; asm volatile("ld.shared.v4.f32 {%0,%1,%2,%3}, [%4];" : "=f"(v.x), "=f"(v.y), "=f"(v.z), "=f"(v.w) : "r"(a) : "memory"); return v; }
__device__ __forceinline__ void ldsm4t(uint32_t (&r)[4], uint32_t a) {
  asm volatile("ldmatrix.sync.aligned.m8n8.x4.trans.shared.b16 {%0,%1,%2,%3}, [%4];" : "=r"(r[0]), "=r"(r[1]), "=r"(r[2]), "=r"(r[3]) : "r"(a) : "memory");
}
__device__ __forceinline__ uint4 ldv128(const void* a) { uint4 v; asm volatile("ld.global.nc.v4.u32 {%0,%1,%2,%3}, [%4];" : "=r"(v.x), "=r"(v.y), "=r"(v.z), "=r"(v.w) : "l"(a) : "memory"); return v; }
__device__ __forceinline__ uint2 ldv64(const void* a) { uint2 v; asm volatile("ld.global.nc.v2.u32 {%0,%1}, [%2];" : "=r"(v.x), "=r"(v.y) : "l"(a) : "memory"); return v; }
__device__ __forceinline__ uint32_t ldv16(const void* a) { uint32_t v; asm volatile("ld.global.nc.u16 %0, [%1];" : "=r"(v) : "l"(a) : "memory"); return v; }
__device__ __forceinline__ void sts128(uint32_t a, uint4 v) { asm volatile("st.shared.v4.u32 [%0], {%1,%2,%3,%4};" ::"r"(a), "r"(v.x), "r"(v.y), "r"(v.z), "r"(v.w) : "memory"); }
__device__ __forceinline__ void sts32(uint32_t a, uint32_t v) { asm volatile("st.shared.u32 [%0], %1;" ::"r"(a), "r"(v) : "memory"); }
__device__ __forceinline__ void sts64f(uint32_t a, float x, float y) { asm volatile("st.shared.v2.f32 [%0], {%1,%2};" ::"r"(a), "f"(x), "f"(y) : "memory"); }
__device__ __forceinline__ void st_rel(unsigned* p, unsigned v) { asm volatile("st.release.gpu.global.u32 [%0], %1;" ::"l"(p), "r"(v) : "memory"); }
__device__ __forceinline__ void fence_async_global() { asm volatile("fence.proxy.async.global;" ::: "memory"); }
__device__ __forceinline__ void fence_async_smem() { asm volatile("fence.proxy.async.shared::cta;" ::: "memory"); }
__device__ __forceinline__ void rec_st(uint4* p, float a, float b, unsigned tag) {
  asm volatile("{\n.reg .b128 t;\n.reg .b64 lo, hi;\nmov.b64 lo, {%1,%2};\nmov.b64 hi, {%3,%3};\nmov.b128 t, {lo,hi};\n"
               "st.relaxed.gpu.global.b128 [%0], t;\n}\n" ::"l"(p), "r"(__float_as_uint(a)), "r"(__float_as_uint(b)), "r"(tag) : "memory");
}
__device__ __forceinline__ unsigned rec_ld(const uint4* p, float& a, float& b) {
  unsigned x, y, t;
  asm volatile("{\n.reg .b128 t;\n.reg .b64 lo, hi;\n.reg .b32 u;\nld.relaxed.gpu.global.b128 t, [%3];\nmov.b128 {lo,hi}, t;\n"
               "mov.b64 {%0,%1}, lo;\nmov.b64 {%2,u}, hi;\n}\n" : "=r"(x), "=r"(y), "=r"(t) : "l"(p) : "memory");
  a = __uint_as_float(x); b = __uint_as_float(y);
  return t;
}
__device__ __forceinline__ void rec_poll(const uint4* p, unsigned tag, float& a, float& b) {
  uint32_t it = 0;
  while (rec_ld(p, a, b) != tag) { if (++it > SPIN_LIMIT) soft_trap(); }
}
__device__ __forceinline__ unsigned ld_rlx(const unsigned* p) { unsigned v; asm volatile("ld.relaxed.gpu.global.u32 %0, [%1];" : "=r"(v) : "l"(p) : "memory"); return v; }
__device__ __forceinline__ void flag_poll(const unsigned* p, unsigned target) {
  uint32_t it = 0;
  while ((int)(ld_rlx(p) - target) < 0) { if (++it > SPIN_LIMIT) soft_trap(); }
  asm volatile("fence.acquire.gpu;" ::: "memory");
}
__device__ __forceinline__ uint32_t pack_bf16(float lo, float hi) {
  uint32_t r; asm("cvt.rn.bf16x2.f32 %0, %1, %2;" : "=r"(r) : "f"(hi), "f"(lo)); return r;
}
__device__ __forceinline__ float bf_lo(uint32_t w) { return __uint_as_float(w << 16); }
__device__ __forceinline__ float bf_hi(uint32_t w) { return __uint_as_float(w & 0xffff0000u); }
__device__ __forceinline__ uint32_t hmul2(uint32_t a, uint32_t b) {
  __nv_bfloat162 r = __hmul2_rn(*(__nv_bfloat162*)&a, *(__nv_bfloat162*)&b); return *(uint32_t*)&r;
}
__device__ __forceinline__ uint32_t hadd2(uint32_t a, uint32_t b) {
  __nv_bfloat162 r = __hadd2_rn(*(__nv_bfloat162*)&a, *(__nv_bfloat162*)&b); return *(uint32_t*)&r;
}
__device__ __forceinline__ float2 cmul(float2 a, float2 b) { return make_float2(a.x * b.x - a.y * b.y, a.x * b.y + a.y * b.x); }
__device__ __forceinline__ float2 cfma(float2 a, float2 b, float2 c) {
  return make_float2(fmaf(a.x, b.x, fmaf(-a.y, b.y, c.x)), fmaf(a.x, b.y, fmaf(a.y, b.x, c.y)));
}
template <int N> __device__ __forceinline__ void fence_regs(float (&a)[N]) {
#pragma unroll
  for (int i = 0; i < N; i++) asm volatile("" : "+f"(a[i])::"memory");
}
__device__ __forceinline__ bool elect_one() {
  uint32_t e; asm volatile("{\n.reg .pred P;\nelect.sync _|P, 0xffffffff;\nselp.u32 %0, 1, 0, P;\n}\n" : "=r"(e)); return e != 0;
}
__device__ __forceinline__ int tid_opaque() { int t; asm volatile("mov.u32 %0, %%tid.x;" : "=r"(t)); return t; }
struct Role { int T1, GP, side, m2, dg, cch0; bool last, has2; };
__device__ __forceinline__ Role unpack_role(int x) {
  Role r; r.T1 = x & 15; r.GP = (x >> 4) & 7; r.side = (x >> 7) & 1; r.m2 = (x >> 8) & 63; r.dg = (x >> 14) & 3;
  r.has2 = (x >> 16) & 1; r.last = r.T1 == NT1 - 1; r.cch0 = 5 * (32 * r.dg + r.m2); return r;
}
__device__ __forceinline__ Role fresh_role(int x) { asm volatile("" : "+r"(x)); return unpack_role(__shfl_sync(0xffffffffu, x, 0)); }
#define ROLE(x) const Role R_ = fresh_role(x); const int T1 = R_.T1, GP = R_.GP, side = R_.side, m2 = R_.m2, dg = R_.dg, cch0 = R_.cch0; \
  const bool last = R_.last, has2 = R_.has2; (void)T1; (void)GP; (void)side; (void)m2; (void)dg; (void)cch0; (void)last; (void)has2;
__device__ __forceinline__ int n_to_t(int n) {
  int T = n / 160, nl = n - T * 160;
  int L = (T == NT1 - 1) ? 32 : 40;
  return T * 160 + L * ((nl & 7) >> 1) + 2 * (nl >> 3) + (nl & 1);
}

template<int TA> __device__ __forceinline__ void wgmma_n160(float (&d)[80], uint32_t alo, uint32_t ahi, uint32_t blo, uint32_t bhi){
  asm volatile("{\n.reg .b64 da, db;\nmov.b64 da, {%80,%81};\nmov.b64 db, {%82,%83};\n"
    "wgmma.mma_async.sync.aligned.m64n160k16.f32.bf16.bf16 {%0, %1, %2, %3, %4, %5, %6, %7, %8, %9, %10, %11, %12, %13, %14, %15, %16, %17, %18, %19, %20, %21, %22, %23, %24, %25, %26, %27, %28, %29, %30, %31, %32, %33, %34, %35, %36, %37, %38, %39, %40, %41, %42, %43, %44, %45, %46, %47, %48, %49, %50, %51, %52, %53, %54, %55, %56, %57, %58, %59, %60, %61, %62, %63, %64, %65, %66, %67, %68, %69, %70, %71, %72, %73, %74, %75, %76, %77, %78, %79}, da, db, 1, 1, 1, %84, 0;\n}\n"
    : "+f"(d[0]), "+f"(d[1]), "+f"(d[2]), "+f"(d[3]), "+f"(d[4]), "+f"(d[5]), "+f"(d[6]), "+f"(d[7]), "+f"(d[8]), "+f"(d[9]), "+f"(d[10]), "+f"(d[11]), "+f"(d[12]), "+f"(d[13]), "+f"(d[14]), "+f"(d[15]), "+f"(d[16]), "+f"(d[17]), "+f"(d[18]), "+f"(d[19]), "+f"(d[20]), "+f"(d[21]), "+f"(d[22]), "+f"(d[23]), "+f"(d[24]), "+f"(d[25]), "+f"(d[26]), "+f"(d[27]), "+f"(d[28]), "+f"(d[29]), "+f"(d[30]), "+f"(d[31]), "+f"(d[32]), "+f"(d[33]), "+f"(d[34]), "+f"(d[35]), "+f"(d[36]), "+f"(d[37]), "+f"(d[38]), "+f"(d[39]), "+f"(d[40]), "+f"(d[41]), "+f"(d[42]), "+f"(d[43]), "+f"(d[44]), "+f"(d[45]), "+f"(d[46]), "+f"(d[47]), "+f"(d[48]), "+f"(d[49]), "+f"(d[50]), "+f"(d[51]), "+f"(d[52]), "+f"(d[53]), "+f"(d[54]), "+f"(d[55]), "+f"(d[56]), "+f"(d[57]), "+f"(d[58]), "+f"(d[59]), "+f"(d[60]), "+f"(d[61]), "+f"(d[62]), "+f"(d[63]), "+f"(d[64]), "+f"(d[65]), "+f"(d[66]), "+f"(d[67]), "+f"(d[68]), "+f"(d[69]), "+f"(d[70]), "+f"(d[71]), "+f"(d[72]), "+f"(d[73]), "+f"(d[74]), "+f"(d[75]), "+f"(d[76]), "+f"(d[77]), "+f"(d[78]), "+f"(d[79])
    : "r"(alo), "r"(ahi), "r"(blo), "r"(bhi), "n"(TA));
}
template<int N> __device__ __forceinline__ void wgmma_rs_hi(float (&d)[64], uint32_t a0, uint32_t a1, uint32_t a2, uint32_t a3, uint32_t blo);
template<> __device__ __forceinline__ void wgmma_rs_hi<16>(float (&d)[64], uint32_t a0, uint32_t a1, uint32_t a2, uint32_t a3, uint32_t blo){
  asm volatile("{\n.reg .b64 db;\nmov.b64 db, {%12,8};\nwgmma.mma_async.sync.aligned.m64n16k16.f32.bf16.bf16 {%0, %1, %2, %3, %4, %5, %6, %7}, {%8,%9,%10,%11}, db, 1, 1, 1, 0;\n}\n"
    : "+f"(d[56]), "+f"(d[57]), "+f"(d[58]), "+f"(d[59]), "+f"(d[60]), "+f"(d[61]), "+f"(d[62]), "+f"(d[63])
    : "r"(a0), "r"(a1), "r"(a2), "r"(a3), "r"(blo));
}
template<> __device__ __forceinline__ void wgmma_rs_hi<32>(float (&d)[64], uint32_t a0, uint32_t a1, uint32_t a2, uint32_t a3, uint32_t blo){
  asm volatile("{\n.reg .b64 db;\nmov.b64 db, {%20,8};\nwgmma.mma_async.sync.aligned.m64n32k16.f32.bf16.bf16 {%0, %1, %2, %3, %4, %5, %6, %7, %8, %9, %10, %11, %12, %13, %14, %15}, {%16,%17,%18,%19}, db, 1, 1, 1, 0;\n}\n"
    : "+f"(d[48]), "+f"(d[49]), "+f"(d[50]), "+f"(d[51]), "+f"(d[52]), "+f"(d[53]), "+f"(d[54]), "+f"(d[55]), "+f"(d[56]), "+f"(d[57]), "+f"(d[58]), "+f"(d[59]), "+f"(d[60]), "+f"(d[61]), "+f"(d[62]), "+f"(d[63])
    : "r"(a0), "r"(a1), "r"(a2), "r"(a3), "r"(blo));
}
template<> __device__ __forceinline__ void wgmma_rs_hi<48>(float (&d)[64], uint32_t a0, uint32_t a1, uint32_t a2, uint32_t a3, uint32_t blo){
  asm volatile("{\n.reg .b64 db;\nmov.b64 db, {%28,8};\nwgmma.mma_async.sync.aligned.m64n48k16.f32.bf16.bf16 {%0, %1, %2, %3, %4, %5, %6, %7, %8, %9, %10, %11, %12, %13, %14, %15, %16, %17, %18, %19, %20, %21, %22, %23}, {%24,%25,%26,%27}, db, 1, 1, 1, 0;\n}\n"
    : "+f"(d[40]), "+f"(d[41]), "+f"(d[42]), "+f"(d[43]), "+f"(d[44]), "+f"(d[45]), "+f"(d[46]), "+f"(d[47]), "+f"(d[48]), "+f"(d[49]), "+f"(d[50]), "+f"(d[51]), "+f"(d[52]), "+f"(d[53]), "+f"(d[54]), "+f"(d[55]), "+f"(d[56]), "+f"(d[57]), "+f"(d[58]), "+f"(d[59]), "+f"(d[60]), "+f"(d[61]), "+f"(d[62]), "+f"(d[63])
    : "r"(a0), "r"(a1), "r"(a2), "r"(a3), "r"(blo));
}
template<> __device__ __forceinline__ void wgmma_rs_hi<64>(float (&d)[64], uint32_t a0, uint32_t a1, uint32_t a2, uint32_t a3, uint32_t blo){
  asm volatile("{\n.reg .b64 db;\nmov.b64 db, {%36,8};\nwgmma.mma_async.sync.aligned.m64n64k16.f32.bf16.bf16 {%0, %1, %2, %3, %4, %5, %6, %7, %8, %9, %10, %11, %12, %13, %14, %15, %16, %17, %18, %19, %20, %21, %22, %23, %24, %25, %26, %27, %28, %29, %30, %31}, {%32,%33,%34,%35}, db, 1, 1, 1, 0;\n}\n"
    : "+f"(d[32]), "+f"(d[33]), "+f"(d[34]), "+f"(d[35]), "+f"(d[36]), "+f"(d[37]), "+f"(d[38]), "+f"(d[39]), "+f"(d[40]), "+f"(d[41]), "+f"(d[42]), "+f"(d[43]), "+f"(d[44]), "+f"(d[45]), "+f"(d[46]), "+f"(d[47]), "+f"(d[48]), "+f"(d[49]), "+f"(d[50]), "+f"(d[51]), "+f"(d[52]), "+f"(d[53]), "+f"(d[54]), "+f"(d[55]), "+f"(d[56]), "+f"(d[57]), "+f"(d[58]), "+f"(d[59]), "+f"(d[60]), "+f"(d[61]), "+f"(d[62]), "+f"(d[63])
    : "r"(a0), "r"(a1), "r"(a2), "r"(a3), "r"(blo));
}
template<> __device__ __forceinline__ void wgmma_rs_hi<80>(float (&d)[64], uint32_t a0, uint32_t a1, uint32_t a2, uint32_t a3, uint32_t blo){
  asm volatile("{\n.reg .b64 db;\nmov.b64 db, {%44,8};\nwgmma.mma_async.sync.aligned.m64n80k16.f32.bf16.bf16 {%0, %1, %2, %3, %4, %5, %6, %7, %8, %9, %10, %11, %12, %13, %14, %15, %16, %17, %18, %19, %20, %21, %22, %23, %24, %25, %26, %27, %28, %29, %30, %31, %32, %33, %34, %35, %36, %37, %38, %39}, {%40,%41,%42,%43}, db, 1, 1, 1, 0;\n}\n"
    : "+f"(d[24]), "+f"(d[25]), "+f"(d[26]), "+f"(d[27]), "+f"(d[28]), "+f"(d[29]), "+f"(d[30]), "+f"(d[31]), "+f"(d[32]), "+f"(d[33]), "+f"(d[34]), "+f"(d[35]), "+f"(d[36]), "+f"(d[37]), "+f"(d[38]), "+f"(d[39]), "+f"(d[40]), "+f"(d[41]), "+f"(d[42]), "+f"(d[43]), "+f"(d[44]), "+f"(d[45]), "+f"(d[46]), "+f"(d[47]), "+f"(d[48]), "+f"(d[49]), "+f"(d[50]), "+f"(d[51]), "+f"(d[52]), "+f"(d[53]), "+f"(d[54]), "+f"(d[55]), "+f"(d[56]), "+f"(d[57]), "+f"(d[58]), "+f"(d[59]), "+f"(d[60]), "+f"(d[61]), "+f"(d[62]), "+f"(d[63])
    : "r"(a0), "r"(a1), "r"(a2), "r"(a3), "r"(blo));
}
template<> __device__ __forceinline__ void wgmma_rs_hi<96>(float (&d)[64], uint32_t a0, uint32_t a1, uint32_t a2, uint32_t a3, uint32_t blo){
  asm volatile("{\n.reg .b64 db;\nmov.b64 db, {%52,8};\nwgmma.mma_async.sync.aligned.m64n96k16.f32.bf16.bf16 {%0, %1, %2, %3, %4, %5, %6, %7, %8, %9, %10, %11, %12, %13, %14, %15, %16, %17, %18, %19, %20, %21, %22, %23, %24, %25, %26, %27, %28, %29, %30, %31, %32, %33, %34, %35, %36, %37, %38, %39, %40, %41, %42, %43, %44, %45, %46, %47}, {%48,%49,%50,%51}, db, 1, 1, 1, 0;\n}\n"
    : "+f"(d[16]), "+f"(d[17]), "+f"(d[18]), "+f"(d[19]), "+f"(d[20]), "+f"(d[21]), "+f"(d[22]), "+f"(d[23]), "+f"(d[24]), "+f"(d[25]), "+f"(d[26]), "+f"(d[27]), "+f"(d[28]), "+f"(d[29]), "+f"(d[30]), "+f"(d[31]), "+f"(d[32]), "+f"(d[33]), "+f"(d[34]), "+f"(d[35]), "+f"(d[36]), "+f"(d[37]), "+f"(d[38]), "+f"(d[39]), "+f"(d[40]), "+f"(d[41]), "+f"(d[42]), "+f"(d[43]), "+f"(d[44]), "+f"(d[45]), "+f"(d[46]), "+f"(d[47]), "+f"(d[48]), "+f"(d[49]), "+f"(d[50]), "+f"(d[51]), "+f"(d[52]), "+f"(d[53]), "+f"(d[54]), "+f"(d[55]), "+f"(d[56]), "+f"(d[57]), "+f"(d[58]), "+f"(d[59]), "+f"(d[60]), "+f"(d[61]), "+f"(d[62]), "+f"(d[63])
    : "r"(a0), "r"(a1), "r"(a2), "r"(a3), "r"(blo));
}
template<> __device__ __forceinline__ void wgmma_rs_hi<112>(float (&d)[64], uint32_t a0, uint32_t a1, uint32_t a2, uint32_t a3, uint32_t blo){
  asm volatile("{\n.reg .b64 db;\nmov.b64 db, {%60,8};\nwgmma.mma_async.sync.aligned.m64n112k16.f32.bf16.bf16 {%0, %1, %2, %3, %4, %5, %6, %7, %8, %9, %10, %11, %12, %13, %14, %15, %16, %17, %18, %19, %20, %21, %22, %23, %24, %25, %26, %27, %28, %29, %30, %31, %32, %33, %34, %35, %36, %37, %38, %39, %40, %41, %42, %43, %44, %45, %46, %47, %48, %49, %50, %51, %52, %53, %54, %55}, {%56,%57,%58,%59}, db, 1, 1, 1, 0;\n}\n"
    : "+f"(d[8]), "+f"(d[9]), "+f"(d[10]), "+f"(d[11]), "+f"(d[12]), "+f"(d[13]), "+f"(d[14]), "+f"(d[15]), "+f"(d[16]), "+f"(d[17]), "+f"(d[18]), "+f"(d[19]), "+f"(d[20]), "+f"(d[21]), "+f"(d[22]), "+f"(d[23]), "+f"(d[24]), "+f"(d[25]), "+f"(d[26]), "+f"(d[27]), "+f"(d[28]), "+f"(d[29]), "+f"(d[30]), "+f"(d[31]), "+f"(d[32]), "+f"(d[33]), "+f"(d[34]), "+f"(d[35]), "+f"(d[36]), "+f"(d[37]), "+f"(d[38]), "+f"(d[39]), "+f"(d[40]), "+f"(d[41]), "+f"(d[42]), "+f"(d[43]), "+f"(d[44]), "+f"(d[45]), "+f"(d[46]), "+f"(d[47]), "+f"(d[48]), "+f"(d[49]), "+f"(d[50]), "+f"(d[51]), "+f"(d[52]), "+f"(d[53]), "+f"(d[54]), "+f"(d[55]), "+f"(d[56]), "+f"(d[57]), "+f"(d[58]), "+f"(d[59]), "+f"(d[60]), "+f"(d[61]), "+f"(d[62]), "+f"(d[63])
    : "r"(a0), "r"(a1), "r"(a2), "r"(a3), "r"(blo));
}
template<> __device__ __forceinline__ void wgmma_rs_hi<128>(float (&d)[64], uint32_t a0, uint32_t a1, uint32_t a2, uint32_t a3, uint32_t blo){
  asm volatile("{\n.reg .b64 db;\nmov.b64 db, {%68,8};\nwgmma.mma_async.sync.aligned.m64n128k16.f32.bf16.bf16 {%0, %1, %2, %3, %4, %5, %6, %7, %8, %9, %10, %11, %12, %13, %14, %15, %16, %17, %18, %19, %20, %21, %22, %23, %24, %25, %26, %27, %28, %29, %30, %31, %32, %33, %34, %35, %36, %37, %38, %39, %40, %41, %42, %43, %44, %45, %46, %47, %48, %49, %50, %51, %52, %53, %54, %55, %56, %57, %58, %59, %60, %61, %62, %63}, {%64,%65,%66,%67}, db, 1, 1, 1, 0;\n}\n"
    : "+f"(d[0]), "+f"(d[1]), "+f"(d[2]), "+f"(d[3]), "+f"(d[4]), "+f"(d[5]), "+f"(d[6]), "+f"(d[7]), "+f"(d[8]), "+f"(d[9]), "+f"(d[10]), "+f"(d[11]), "+f"(d[12]), "+f"(d[13]), "+f"(d[14]), "+f"(d[15]), "+f"(d[16]), "+f"(d[17]), "+f"(d[18]), "+f"(d[19]), "+f"(d[20]), "+f"(d[21]), "+f"(d[22]), "+f"(d[23]), "+f"(d[24]), "+f"(d[25]), "+f"(d[26]), "+f"(d[27]), "+f"(d[28]), "+f"(d[29]), "+f"(d[30]), "+f"(d[31]), "+f"(d[32]), "+f"(d[33]), "+f"(d[34]), "+f"(d[35]), "+f"(d[36]), "+f"(d[37]), "+f"(d[38]), "+f"(d[39]), "+f"(d[40]), "+f"(d[41]), "+f"(d[42]), "+f"(d[43]), "+f"(d[44]), "+f"(d[45]), "+f"(d[46]), "+f"(d[47]), "+f"(d[48]), "+f"(d[49]), "+f"(d[50]), "+f"(d[51]), "+f"(d[52]), "+f"(d[53]), "+f"(d[54]), "+f"(d[55]), "+f"(d[56]), "+f"(d[57]), "+f"(d[58]), "+f"(d[59]), "+f"(d[60]), "+f"(d[61]), "+f"(d[62]), "+f"(d[63])
    : "r"(a0), "r"(a1), "r"(a2), "r"(a3), "r"(blo));
}

struct CvCtx {
  uint32_t kaddr, kvaddr, db0, dd, stg, zero;
  int src1, src2;
  bool s3, kodd, wrap;
};
template <int LO> __device__ __forceinline__ void cv_copy(float (&acc)[64]) {
#pragma unroll
  for (int i = LO; i < 64; i++) { float t; asm volatile("mov.b32 %0, %1;" : "=f"(t) : "f"(acc[i]) : "memory"); acc[i] = t; }
}
template <int G> __device__ __forceinline__ void cv_raw(uint32_t (&A)[4][4], uint32_t kaddr) {
#pragma unroll
  for (int i = 0; i < 4; i++) {
    const uint32_t a = kaddr + (4 * G + i) * 128;
    A[i][0] = lds32(a); A[i][1] = lds32(a + 4); A[i][3] = lds32(a + 8);
  }
}
__device__ __forceinline__ void cv_form(uint32_t (&A)[4][4]) {
#pragma unroll
  for (int i = 0; i < 4; i++) {
    asm volatile("prmt.b32 %0, %0, %1, 0x5432;" : "+r"(A[i][0]) : "r"(A[i][1]));
    asm volatile("prmt.b32 %0, %1, %2, 0x5432;" : "=r"(A[i][2]) : "r"(A[i][1]), "r"(A[i][3]));
  }
}
template <int J> __device__ __forceinline__ void cv_epi(const float (&acc)[64], float (&Ep)[2], const uint32_t (&so)[4], const CvCtx& c) {
  float E[4], o[2];
  const uint32_t kvw = lds32(c.kvaddr + J * 256);
  const int src1 = c.src1 | (kvw & c.zero);
#pragma unroll
  for (int x = 0; x < 4; x++) {
    const float ev = acc[8 * J + x], od = acc[8 * J + 4 + x], pv = J > 0 ? acc[J > 0 ? 8 * J - 4 + x : 0] : 0.f;
    const float send = c.kodd ? ev : (c.s3 ? pv : od);
    E[x] = (c.kodd ? od : ev) + __shfl_sync(0xffffffffu, send, src1);
  }
#pragma unroll
  for (int h = 0; h < 2; h++) {
    o[h] = E[2 * h] + __shfl_sync(0xffffffffu, c.wrap ? Ep[h] : E[2 * h + 1], c.src2);
    Ep[h] = E[2 * h + 1];
  }
  sts32(c.stg + ((J & 1) ? so[J >> 1] >> 16 : so[J >> 1] & 0xffff), hadd2(pack_bf16(o[0], o[1]), hmul2(__byte_perm(kvw, kvw, 0x1032), c.dd)));
}
template <int G> __device__ __forceinline__ void cv_rec(float (&acc)[64], uint32_t (&A)[4][4], float (&Ep)[2], const uint32_t (&so)[4], const CvCtx& c) {
  wgmma_fence();
#pragma unroll
  for (int i = 0; i < 4; i++) wgmma_rs_hi<128 - 16 * G>(acc, A[i][0], A[i][1], A[i][2], A[i][3], c.db0 - 4 * i);
  wgmma_commit();
  __syncwarp();
  uint32_t B[4][4];
  if constexpr (G < 7) cv_raw<G + 1>(B, c.kaddr);
  if constexpr (G > 0) cv_epi<G - 1>(acc, Ep, so, c);
  if constexpr (G < 7) cv_form(B);
  __syncwarp();
  wgmma_wait<0>();
  cv_copy<8 * G>(acc);
  if constexpr (G < 7) cv_rec<G + 1>(acc, B, Ep, so, c);
}
__device__ __forceinline__ uint32_t cv_stage(int slot) { return sb + (slot < 4 ? 40960 + slot * 4096 : 180224); }
__device__ __forceinline__ void cv_offsets(uint32_t (&so)[4]) {
  const int tid = tid_opaque() & 127, lane = tid & 31, r = lane >> 2, q = lane & 3;
  const int P = r < 4 ? q : 4 + ((q + 1) & 3);
  const int tb = 16 * (2 * P + ((r >> 1) & 1)) + 4 * (tid >> 5) + 2 * (r & 1);
#pragma unroll
  for (int J = 0; J < 8; J++) {
    const int t = 256 * J + tb, T = t / 160, tl = t - T * 160;
    const int qq = (T == NT1 - 1) ? (tl >> 5) : (tl / 40);
    int ck = 20 * T + ((tl - qq * ((T == NT1 - 1) ? 32 : 40)) >> 1);
    ck ^= (ck >> 3) & 7;
    const uint32_t o = ck * 16 + qq * 4;
    if (J & 1) so[J >> 1] |= o << 16; else so[J >> 1] = o;
  }
}
__device__ __forceinline__ void conv_channel(int slot, const uint32_t (&so)[4]) {
  const int tid = tid_opaque() & 127, w = tid >> 5, lane = tid & 31, r = lane >> 2, q = lane & 3;
  const int i_ = r >> 1, i0 = i_ & 1, i1 = i_ >> 1;
  const uint32_t cb = sb + CV_OFF + slot * CV_B;
  CvCtx c;
  c.dd = lds32(sb + EP_OFF + 4 * slot);
  c.kaddr = cb + CV_K - 32 + 4 * (8 * i_ + 2 * w + (r & 1) + 2 * q);
  c.db0 = desc_lo(cb + CV_U + 192, CV_PL);
  c.src1 = i1 == 0 ? (lane - q + 16 + ((q + 3) & 3)) : (lane - q - 16 + ((q + 1) & 3));
  c.s3 = (i1 == 1 && q == 3); c.kodd = (i1 == 1 && q < 3);
  const int P = i1 == 0 ? q : 4 + ((q + 1) & 3);
  const int Pm = (P + 7) & 7, qm = Pm < 4 ? Pm : ((Pm - 1) & 3);
  c.src2 = i0 == 1 ? lane - 8 : (16 * (Pm >> 2) + 8 + 4 * (r & 1) + qm);
  c.wrap = (i0 == 1 && P == 7);
  c.kvaddr = cb + CV_U + 192 + (1 - (r & 1)) * CV_PL + (2 * P + i0) * 16 + (3 - w) * 4;
  float acc[64], Ep[2] = {0.f, 0.f};
  uint32_t A[4][4];
  c.stg = cv_stage(slot);
#pragma unroll
  for (int i = 0; i < 64; i++) acc[i] = 0.f;
  mbar_wait(bars + 8 * (B_TAPS + slot));
  c.zero = lds32(cb);
  cv_raw<0>(A, c.kaddr);
  mbar_wait(bars + 8 * (B_CVFULL + slot));
  cv_form(A);
  cv_copy<0>(acc);
  cv_rec<0>(acc, A, Ep, so, c);
  cv_epi<7>(acc, Ep, so, c);
  fence_async_smem();
  mbar_arrive(bars + 8 * (B_CVDONE + slot));
}

template <int W> struct KvRegs { uint32_t k[19][W], v[16][W], s[W][4]; };
template <int W> __device__ __forceinline__ void kv_load(int m, int cl, KvRegs<W>& x) {
  const int lane = tid_opaque() & 31, tg = lane >> 3;
  const uint32_t pb = sb + KS_OFF + (cl >> 5) * KV_PIECE + 2 * (cl & 31) + 4 * W * (lane & 7);
  const uint32_t ka = pb + tg * 1216, va = pb + 4864 + tg * 1088 + 64;
  const uint32_t kh = (m == 0 && tg > 0) ? ka - 192 : ka;
#pragma unroll
  for (int c = 0; c < W; c++) {
    const float4 t = lds128f(sb + TAP_OFF + 8 * cl + 16 * (W * (lane & 7) + c));
    x.s[c][0] = __float_as_uint(t.x); x.s[c][1] = __float_as_uint(t.y); x.s[c][2] = __float_as_uint(t.z); x.s[c][3] = __float_as_uint(t.w);
  }
  mbar_wait(bars + 8 * (B_KV + (cl >> 5)));
#pragma unroll
  for (int i = 0; i < 19; i++) {
    const uint32_t a = (i < 3 ? kh : ka) + i * 64;
    if (W == 2) { float2 t = lds64f(a); x.k[i][0] = __float_as_uint(t.x); x.k[i][W - 1] = __float_as_uint(t.y); }
    else x.k[i][0] = lds32(a);
  }
#pragma unroll
  for (int i = 0; i < 16; i++) {
    if (W == 2) { float2 t = lds64f(va + i * 64); x.v[i][0] = __float_as_uint(t.x); x.v[i][W - 1] = __float_as_uint(t.y); }
    else x.v[i][0] = lds32(va + i * 64);
  }
}
template <int W> __device__ __forceinline__ void kv_finish(int m, int c0, KvRegs<W>& x) {
  const int lane = tid_opaque() & 31;
  uint8_t* dst = g_kv + ((c0 + 2 * W * (lane & 7)) * 4096 + (4 * m + (lane >> 3)) * 16);
#pragma unroll
  for (int c = 0; c < W; c++) {
    const uint32_t w0 = __byte_perm(x.s[c][0], x.s[c][2], 0x5410), w1 = __byte_perm(x.s[c][0], x.s[c][2], 0x7632);
    const uint32_t w2 = __byte_perm(x.s[c][1], x.s[c][3], 0x5410), w3 = __byte_perm(x.s[c][1], x.s[c][3], 0x7632);
#pragma unroll
    for (int i = 0; i < 16; i++) {
      uint32_t a = hmul2(x.k[i][c], w3);
      a = hadd2(a, hmul2(x.k[i + 1][c], w2)); a = hadd2(a, hmul2(x.k[i + 2][c], w1)); a = hadd2(a, hmul2(x.k[i + 3][c], w0));
      x.v[i][c] = hmul2(a, x.v[i][c]);
    }
#pragma unroll
    for (int e = 0; e < 2; e++)
#pragma unroll
      for (int f = 0; f < 2; f++) {
        uint32_t o[4];
#pragma unroll
        for (int qq = 0; qq < 4; qq++) o[qq] = __byte_perm(x.v[15 - 4 * qq - 2 * f][c], x.v[14 - 4 * qq - 2 * f][c], e ? 0x7632 : 0x5410);
        *(uint4*)(dst + (2 * c + e) * 4096 + f * 2048) = make_uint4(o[0], o[1], o[2], o[3]);
      }
  }
}
__device__ __forceinline__ void stat_table(int T1, unsigned want, int l) {
#pragma unroll 1
  for (int n = tid_opaque() & 127; n < (T1 == NT1 - 1 ? 128 : 160); n += 128) {
    const uint4* rp = &g_stats[8 * l * SEQ + 160 * T1 + n];
    float a[4], b[4];
    uint32_t it = 0;
    while (true) {
      bool ok = true;
#pragma unroll
      for (int i = 0; i < 4; i++) ok &= (rec_ld(rp + SEQ * i, a[i], b[i]) == want);
      if (ok) break;
      if (++it > SPIN_LIMIT) soft_trap();
    }
    const float m = 0.25f * ((a[0] + a[1]) + (a[2] + a[3]));
    float v = (b[0] + b[1]) + (b[2] + b[3]);
#pragma unroll
    for (int i = 0; i < 4; i++) v = fmaf(160.f * (a[i] - m), a[i] - m, v);
    const float rs = rsqrtf(v * (1.f / 640.f) + 1e-5f);
    sts64f(sb + STAB_OFF + n * 8, rs, -m * rs);
  }
  mbar_arrive(bars + 8 * (B_STAB + l));
  __syncwarp();
}

template <bool FIRST>
__device__ __forceinline__ void stats_publish(int which, int n0, int dg, unsigned tag, const float (&acc)[80]) {
  const int lane = tid_opaque() & 31, q = lane & 3;
  float sh[2] = {0.f, 0.f};
  if (FIRST) { sh[0] = __shfl_sync(0xffffffffu, acc[0], lane & ~3); sh[1] = __shfl_sync(0xffffffffu, acc[2], lane & ~3); }
  float s1[2] = {0.f, 0.f}, s2[2] = {0.f, 0.f}, t1[2] = {0.f, 0.f}, t2[2] = {0.f, 0.f};
#pragma unroll
  for (int j = 0; j < 20; j++)
#pragma unroll
    for (int h = 0; h < 2; h++) {
      float a = acc[4 * j + 2 * h], b = acc[4 * j + 2 * h + 1];
      if (FIRST) { a -= sh[h]; b -= sh[h]; }
      s1[h] += a; t1[h] += b; s2[h] = fmaf(a, a, s2[h]); t2[h] = fmaf(b, b, t2[h]);
    }
#pragma unroll
  for (int h = 0; h < 2; h++) {
    s1[h] += t1[h]; s2[h] += t2[h];
    s1[h] += __shfl_xor_sync(0xffffffffu, s1[h], 1); s2[h] += __shfl_xor_sync(0xffffffffu, s2[h], 1);
    s1[h] += __shfl_xor_sync(0xffffffffu, s1[h], 2); s2[h] += __shfl_xor_sync(0xffffffffu, s2[h], 2);
  }
  const int h = q & 1;
  const float a = h ? s1[1] : s1[0], b = h ? s2[1] : s2[0], c = h ? sh[1] : sh[0];
  const float mean = a * (1.f / 160.f), m2v = fmaxf(b - a * mean, 0.f);
  if (FIRST) {
    rec_st(&g_stats[((q >> 1) * 4 + dg) * SEQ + n0 + 8 * h], mean + c, m2v, q < 2 ? tag : tag - 1);
    rec_st(&g_stats[((q >> 1) * 4 + 8 + dg) * SEQ + n0 + 8 * h], mean + c, m2v, tag - 1);
  } else if (q < 2) rec_st(&g_stats[(which * 4 + dg) * SEQ + n0 + 8 * h], mean, m2v, tag);
}
__device__ __forceinline__ void stats_combine(float mi, float m2, float& mean, float& rstd) {
  float m = mi + __shfl_xor_sync(0xffffffffu, mi, 1);
  m += __shfl_xor_sync(0xffffffffu, m, 2);
  m *= 0.25f;
  float d = mi - m;
  float v = fmaf(160.f * d, d, m2);
  v += __shfl_xor_sync(0xffffffffu, v, 1);
  v += __shfl_xor_sync(0xffffffffu, v, 2);
  mean = m; rstd = rsqrtf(v * (1.f / 640.f) + 1e-5f);
}
__device__ __forceinline__ void stats_get(int which, int n0, unsigned tag, float (&mean)[2], float (&rstd)[2]) {
  const int q = tid_opaque() & 3;
  const uint4* p0 = &g_stats[(which * 4 + q) * SEQ + n0];
  float a0, b0, a1, b1;
  uint32_t it = 0;
  while (true) {
    unsigned t0 = rec_ld(p0, a0, b0), t1 = rec_ld(p0 + 8, a1, b1);
    if (t0 == tag && t1 == tag) break;
    if (++it > SPIN_LIMIT) soft_trap();
  }
  __syncwarp();
  stats_combine(a0, b0, mean[0], rstd[0]);
  stats_combine(a1, b1, mean[1], rstd[1]);
}
__device__ __forceinline__ void x0_load(float (&acc)[80]) {
  const int t = tid_opaque() & 127;
  const uint32_t xa = sb + XT_OFF + (16 * (t >> 5) + ((t & 31) >> 2)) * 320 + 8 * (t & 3);
  mbar_wait(bars + 8 * B_XT);
#pragma unroll
  for (int h = 0; h < 2; h++)
#pragma unroll
    for (int J = 0; J < 10; J++) {
      const float2 v = lds64f(xa + h * 2560 + 32 * J);
      const uint32_t x = __float_as_uint(v.x), y = __float_as_uint(v.y);
      acc[8 * J + 2 * h] = bf_lo(x); acc[8 * J + 2 * h + 1] = bf_hi(x);
      acc[8 * J + 4 + 2 * h] = bf_lo(y); acc[8 * J + 4 + 2 * h + 1] = bf_hi(y);
    }
}

__global__ void __launch_bounds__(512, 1) fused_kernel(const __grid_constant__ Params p) {
  extern __shared__ __align__(1024) uint8_t smem_raw[];
  const int tid = threadIdx.x, lane = tid & 31;
  const int wid = __shfl_sync(0xffffffffu, tid >> 5, 0), wg = wid >> 2;
  unsigned smid; asm volatile("mov.u32 %0, %%smid;" : "=r"(smid));
  if (smid >= 132 || smem_u32(smem_raw) != sb) soft_trap();
  int role;
  {
  const int side = smid & 1;
  int gpc, gi;
  {
    int tpc = smid >> 1;
    if (tpc < 32) { gpc = tpc & 7; gi = tpc >> 3; }
    else if (tpc < 60) { gpc = 1 + (tpc - 32) % 7; gi = 4 + (tpc - 32) / 7; }
    else if (tpc < 62) { gpc = tpc - 54; gi = 8; }
    else { gpc = 0; gi = tpc - 58; }
  }
  const int pos = 8 * gpc + gi + (gpc == 7 ? 1 : 0);
  if (pos == 65) {
    if (tid < 32) {
      const unsigned tag = ld_rlx(g_epoch);
      for (int i = lane; i < NT1 * 16; i += 32)
        if ((i & 15) < 10) { uint32_t it = 0; while ((int)(ld_rlx(&g_hflag[((i >> 4) * 32 + (i & 15)) * 8]) - tag) < 0) { __nanosleep(500); if (++it > SPIN_LIMIT) soft_trap(); } }
    }
    return;
  }
  int T1, GP;
  if (pos < 52) { int hh = pos / 26, x = pos - 26 * hh; T1 = x >> 1; GP = 2 * hh + (x & 1); }
  else { T1 = pos - 52; GP = 4; }
  const bool last = (T1 == NT1 - 1);
  const bool has2 = gi < 8;
  const int m2 = 8 * (gpc >> 1) + gi, dg = 2 * (gpc & 1) + side;
  role = T1 | (GP << 4) | (side << 7) | (m2 << 8) | (dg << 14) | ((int)has2 << 16);

  const int cch0 = 5 * (32 * dg + m2);
  if (wg < 2) {
    if (wid < 2) {
      const int ch = 128 * GP + 64 * wid + 32 * side + lane;
      uint32_t r0 = ldv16(p.lre + ch), r1 = ldv16(p.lim + ch), r2 = ldv16(p.logdt + ch);
      asm volatile("bar.arrive 5, 512;" : "+r"(r0), "+r"(r1), "+r"(r2)::"memory");
      const float lr = bf_lo(r0), li = bf_lo(r1), ld = bf_lo(r2);
      const float dt = __bfloat162float(__float2bfloat16_rn(expf(ld)));
      const float mag = expf(dt * lr);
      float sn, cs; sincosf(dt * li, &sn, &cs);
      const float ar = mag * cs, ai = mag * sn;
      const float inv = 2.f / (lr * lr + li * li);
      const uint32_t ad = sb + CTAB_OFF + (32 * wid + lane) * 24;
      sts64f(ad, ar, ai);
      sts64f(ad + 8, ((ar - 1.f) * lr + ai * li) * inv, (ai * lr - (ar - 1.f) * li) * inv);
      if (tid == 0) TS(46);
      __syncwarp();
      bar_sync(7, 96);
      mbar_arrive(bars + 8 * B_CTAB);
    } else {
      if (elect_one()) {
        if (wid < 5) {
#pragma unroll
          for (int i = 0; i < 27; i++) mbar_init(bars + 8 * (4 + 27 * (wid - 2) + i), 2);
        } else {
#pragma unroll
          for (int i = 0; i < 15; i++) mbar_init(bars + 8 * (85 + 15 * (wid - 5) + i), 1);
        }
        asm volatile("fence.mbarrier_init.release.cluster;" ::: "memory");
      }
      __syncwarp();
      bar_sync(5, 512);
      if (wid == 2) { asm volatile("bar.arrive 6, 64;" ::: "memory"); asm volatile("bar.arrive 7, 96;" ::: "memory"); }
    }
  } else if (wg == 2 || wid == 14) {
    uint2 bv[2][5];
    const int c = wid == 14 ? 4 : wid - 8;
    const unsigned tag0 = ld_rlx(g_epoch);
#pragma unroll
    for (int x = 0; x < 2; x++)
#pragma unroll
      for (int i = 0; i < 5; i++) bv[x][i] = ldv64((const uint2*)((x ? p.bim : p.bre) + (has2 ? cch0 + c : 0) * DM) + lane + 32 * i);
    bar_sync(5, 512);
#pragma unroll
    for (int i = 0; i < 5; i++) asm volatile("" : "+r"(bv[0][i].x), "+r"(bv[0][i].y), "+r"(bv[1][i].x), "+r"(bv[1][i].y)::"memory");
    if (has2) {
      float sv[2];
#pragma unroll
      for (int x = 0; x < 2; x++) {
        float a = 0.f;
#pragma unroll
        for (int i = 0; i < 5; i++) a += (bf_lo(bv[x][i].x) + bf_hi(bv[x][i].x)) + (bf_lo(bv[x][i].y) + bf_hi(bv[x][i].y));
        sv[x] = a;
      }
#pragma unroll
      for (int o = 16; o > 0; o >>= 1) { sv[0] += __shfl_xor_sync(0xffffffffu, sv[0], o); sv[1] += __shfl_xor_sync(0xffffffffu, sv[1], o); }
      if (lane < 2) rec_st(&g_sB[(cch0 + c) * 2 + lane], sv[0], sv[1], tag0);
      if (tid == 256) TS(47);
    }
  } else if (wid == 13) {
    uint4 tv[3];
    const uint32_t e0 = ld_rlx(g_epoch);
    uint32_t e1 = ldv16(p.ssmD + min(cch0 + lane, 639));
    const uint4 dv = ldv128((const uint4*)(p.dskip + 160 * dg) + min(lane, 19));
#pragma unroll
    for (int i = 0; i < 3; i++) tv[i] = ldv128((const uint4*)(p.shiftk + 640 * dg) + min(lane + 32 * i, 79));
    bar_sync(5, 512);
    asm volatile("" : "+r"(e1)::"memory");
    sts128(sb + DTAB_OFF + 16 * min(lane, 19), dv);
#pragma unroll
    for (int i = 0; i < 3; i++) sts128(sb + TAP_OFF + 16 * min(lane + 32 * i, 79), tv[i]);
    if (lane < 6) sts32(sb + EP_OFF + 4 * lane, lane < 5 ? e1 | (e1 << 16) : e0);
    mbar_arrive(bars + 8 * B_CTAB);
    __syncwarp();
    if (lane == 0) { mbar_arrive(bars + 8 * B_EP); TS(53); }
  } else if (wid == 12) {
    if (elect_one()) {
#pragma unroll
      for (int k = 0; k < S1; k++) mbar_init(bars + 8 * (B_G1FULL + k), 1);
#pragma unroll
      for (int k = 0; k < 19; k++) mbar_init(bars + 8 * (B_XT + k), 1);
      asm volatile("fence.mbarrier_init.release.cluster;" ::: "memory");
      TS(45);
    }
    __syncwarp();
    asm volatile("bar.arrive 5, 512;" ::: "memory");
    if (elect_one()) {
#pragma unroll 1
      for (int k = 0; k < S1; k++) {
        const uint32_t fb = bars + 8 * (B_G1FULL + k);
        mbar_expect_tx(fb, G1_STAGE);
        tma4(sb + k * G1_STAGE + G1_XOFF, last ? &p.mXl : &p.mX, 64 * k, 0, 0, last ? 0 : 80 * T1, fb);
        tma5(sb + k * G1_STAGE, &p.mB, 64 * k, 0, 0, 4 * side, 2 * GP, fb);
      }
      TS(44);
    }
    __syncwarp();
    bar_sync(6, 64);
  } else {
    if (elect_one()) {
#pragma unroll
      for (int i = 0; i < 13; i++) mbar_init(bars + 8 * (B_CVDONE + i), B_CVDONE + i == B_STAB ? 160 : (B_CVDONE + i == B_CTAB ? 96 : 128));
      asm volatile("fence.mbarrier_init.release.cluster;" ::: "memory");
    }
    __syncwarp();
    bar_sync(5, 512);
  }
  if (tid == 128) TS(0);
  }

  if (wg == 3) {
    asm volatile("setmaxnreg.dec.sync.aligned.u32 56;");
    ROLE(role)
    const int pw = wid & 3;
    if (pw == 3 && has2) {
      mbar_wait(bars + 8 * (B_G1FULL + 0));
      if (elect_one()) {
        mbar_expect_tx(bars + 8 * B_XT, 20480);
#pragma unroll
        for (int h = 0; h < 2; h++) {
          const int ng = 8 * m2 + 4 * h, T = ng / 20;
          tma4(sb + XT_OFF + h * 10240, T == NT1 - 1 ? &p.mXtl : &p.mXt, 160 * dg, 0, 0, T == NT1 - 1 ? ng - 240 : ng + 60 * T, bars + 8 * B_XT);
        }
      }
#pragma unroll 1
      for (int c = 0; c < 5; c++) {
        mbar_wait(bars + 8 * (c == 0 ? B_G1FULL + 2 : B_XT + (c < 2 ? 0 : c - 1)));
        if (elect_one()) {
          const uint32_t fb = bars + 8 * (B_KV + c);
          mbar_expect_tx(fb, KV_PIECE);
          tma3(sb + KS_OFF + c * KV_PIECE, &p.mK, 160 * dg + 32 * c, 64 * m2 - 3, 0, fb);
          tma3(sb + KS_OFF + c * KV_PIECE + 4864, &p.mV, 160 * dg + 32 * c, 64 * m2 - 1, 0, fb);
        }
      }
    }
    unsigned tag = 0;
    if (pw > 0) { mbar_wait(bars + 8 * B_EP); tag = lds32(sb + EP_OFF + 20); }
    if (pw == 2) {
#pragma unroll 1
      for (int i = 0; i < 2; i++) {
        float a, b;
        rec_poll(&g_sB[(128 * GP + 64 * i + 32 * side + lane) * 2], tag, a, b);
        sts64f(sb + CTAB_OFF + (32 * i + lane) * 24 + 16, p.swap ? b : a, p.swap ? a : b);
      }
      mbar_arrive(bars + 8 * B_STAB);
      if (lane == 0) TS(54);
    }
    if (pw >= 2 && has2) {
      KvRegs<1> x;
      kv_load<1>(m2, 128 + 16 * (pw - 2), x);
      kv_finish<1>(m2, 160 * dg + 128 + 16 * (pw - 2), x);
      if (tid == 448) TS(51);
      bar_sync(3, 192);
      if (tid == 448) { mbar_arrive(bars + 8 * B_PREP); st_rel(&g_kvflag[(dg * 32 + m2) * 8], tag); TS(30); }
      __syncwarp();
    }
    if (pw == 0) {
      if (elect_one()) {
#pragma unroll 1
        for (int l = 0; l < 2; l++) {
          const uint32_t fb0 = bars + 8 * (B_G1FULL + 10 * l), wb = bars + 8 * (B_G1DONE + 9 * l - S1);
          const uint32_t free0 = bars + 8 * (has2 ? B_G2DONE + 19 : B_G1DONE + 9);
          uint32_t dst = sb;
#pragma unroll 1
          for (int k = l == 0 ? S1 : 0; k < 10; k++) {
            mbar_wait(k >= S1 + l ? wb + 8 * k : (k < WPF1 || !has2 ? free0 : bars + 8 * (B_GO + 1)));
            mbar_expect_tx(fb0 + 8 * k, 16384);
            tma5(dst, &p.mB, 64 * k, 0, 0, 4 * side, 2 * GP, fb0 + 8 * k);
            dst += G1_STAGE; if (dst == sb + (S1 + l) * G1_STAGE) dst = sb;
          }
          if (has2) {
            const uint32_t fb2 = bars + 8 * (B_G2FULL + 20 * l), wb2 = bars + 8 * (B_G2DONE + 19 * l - 6);
            dst = sb + G2_WOFF;
            int kc = 0;
#pragma unroll 1
            for (int k = 0; k < 20; k++) {
              mbar_wait(k >= 6 + l ? wb2 + 8 * k : (k == 5 ? bars + 8 * B_XFREE : (k < WPF2 ? bars + 8 * (B_G1DONE + 10 * l + 9) : bars + 8 * (B_GO + 2 * l))));
              mbar_expect_tx(fb2 + 8 * k, G2_WB);
              tma5(dst, &p.mCre + (k & 1), kc, 0, 0, 0, 10 * dg, fb2 + 8 * k);
              kc += (k & 1) << 7; if (k == 9) kc = 64;
              dst += G2_WB; if (dst == sb + G2_WOFF + (6 + l) * G2_WB) dst = sb + G2_WOFF;
            }
          }
        }
      }
    } else if (pw == 1) {
#pragma unroll 1
      for (int l = 0; l < 2; l++) {
        if (l == 0) {
          if (elect_one()) {
            uint32_t dst = sb + G1_XOFF;
#pragma unroll 1
            for (int k = S1; k < 10; k++) {
              mbar_wait(bars + 8 * (B_G1DONE + k - S1));
              mbar_expect_tx(bars + 8 * (B_G1FULL + k), 20480);
              tma4(dst, last ? &p.mXl : &p.mX, 64 * k, 0, 0, last ? 0 : 80 * T1, bars + 8 * (B_G1FULL + k));
              dst += G1_STAGE; if (k == 2 * S1 - 1) dst = sb + G1_XOFF;
            }
          }
        } else {
          mbar_wait(bars + 8 * (has2 ? B_G2DONE + 19 : B_G1DONE + 9));
          const int mlo = (160 * T1) >> 6, nf = last ? 8 : 12;
          if (lane < nf) flag_poll(&g_uflag[(4 * mlo + lane) * 8], tag);
          __syncwarp();
          fence_async_global();
          if (elect_one()) {
            TS(20);
            const int bytes = last ? 16384 : 20480;
            const uint8_t* src = g_u + T1 * 204800;
            uint32_t dst = sb + G1_XOFF;
#pragma unroll 1
            for (int k = 0; k < 10; k++) {
              if (k > S1) mbar_wait(bars + 8 * (B_G1DONE + 9 - S1 + k));
              mbar_expect_tx(bars + 8 * (B_G1FULL + 10 + k), bytes);
              bulk_g2s(dst, src, bytes, bars + 8 * (B_G1FULL + 10 + k));
              src += 20480; dst += G1_STAGE; if (k == S1) dst = sb + G1_XOFF;
            }
          }
        }
        __syncwarp();
        if (has2) {
          mbar_wait(bars + 8 * (B_G1DONE + 10 * l + 9));
          const int Tlo = (64 * m2) / 160, Thi = (64 * m2 + 63) / 160;
          if ((lane & 15) < 10) flag_poll(&g_hflag[(((l * NT1 + (lane < 16 ? Tlo : Thi)) * 2) * 16 + (lane & 15)) * 8], tag);
          __syncwarp();
          fence_async_global();
          if (elect_one()) {
            TS(21 + 2 * l);
            const uint32_t fb2 = bars + 8 * (B_G2FULL + 20 * l), wb2 = bars + 8 * (B_G2DONE + 18 * l - SX2);
            const uint8_t* src = g_h + (l * 32 + m2) * 163840;
            uint32_t dst = sb;
#pragma unroll 1
            for (int k = 0; k < 20; k++) {
              if (k >= SX2 + 2 * l) mbar_wait(wb2 + 8 * k);
              if (k == 10) { mbar_wait(bars + 8 * (B_H1 + l)); fence_async_global(); }
              mbar_expect_tx(fb2 + 8 * k, G2_XB);
              bulk_g2s(dst, src, G2_XB, fb2 + 8 * k);
              src += 8192; dst += G2_XB; if (dst == sb + (SX2 + 2 * l) * G2_XB) dst = sb;
            }
          }
          __syncwarp();
        }
      }
    } else if (pw == 2) {
#pragma unroll 1
      for (int l = 0; l < 2; l++) {
        mbar_wait(bars + 8 * (B_HST + 2 * l));
        mbar_wait(bars + 8 * (B_HST + 2 * l + 1));
        __syncwarp();
        if (lane < 2) st_rel(&g_hflag[(((l * NT1 + T1) * 2 + lane) * 16 + 2 * GP + side) * 8], tag);
        if (lane == 0) TS(6 + 8 * l);
        __syncwarp();
        if (l == 0 && has2 && elect_one()) {
#pragma unroll 1
          for (int c = 0; c < 5; c++) {
            mbar_wait(bars + 8 * (B_CVDONE + c));
            bulk_s2g(g_G + (cch0 + c) * 4096, cv_stage(c), 4096);
          }
          asm volatile("cp.async.bulk.commit_group;" ::: "memory");
          asm volatile("cp.async.bulk.wait_group 0;" ::: "memory");
          fence_async_global();
          st_rel(&g_gflag[(dg * 32 + m2) * 8], tag);
        }
        __syncwarp();
      }
    } else if (has2) {
      mbar_wait(bars + 8 * B_PREP);
#pragma unroll
      for (int c = 0; c < 5; c++) {
        const uint32_t cb = sb + CV_OFF + c * CV_B;
        const uint32_t a = lane < 8 ? cb + 16 * lane : (lane < 20 ? cb + CV_U + 16 * (lane - 8) : cb + CV_U + CV_PL + 16 * (lane - 20));
        asm volatile("st.shared.v4.u32 [%0], {%1,%1,%1,%1};" ::"r"(a), "r"(0) : "memory");
      }
      fence_async_smem();
      __syncwarp();
#pragma unroll 1
      for (int c = 0; c < 5; c++) {
        if (c >= 2) mbar_wait(bars + 8 * (B_TAPS + c - 2));
        if (elect_one()) {
          mbar_expect_tx(bars + 8 * (B_TAPS + c), 4096);
          bulk_g2s(sb + CV_OFF + c * CV_B + CV_K, p.ssmk + (size_t)(cch0 + c) * SEQ, 4096, bars + 8 * (B_TAPS + c));
        }
      }
      if (elect_one()) {
        asm volatile("prefetch.tensormap [%0];" ::"l"(&p.mCre) : "memory");
        asm volatile("prefetch.tensormap [%0];" ::"l"(&p.mCim) : "memory");
        asm volatile("prefetch.tensormap [%0];" ::"l"(&p.mG) : "memory");
      }
      flag_poll(&g_kvflag[(dg * 32 + lane) * 8], tag);
      __syncwarp();
      fence_async_global();
      if (lane == 0) TS(28);
      if (elect_one()) {
#pragma unroll
        for (int c = 0; c < 5; c++) {
          const uint32_t fb = bars + 8 * (B_CVFULL + c), cb = sb + CV_OFF + c * CV_B + CV_U + 192;
          mbar_expect_tx(fb, 4096);
          bulk_g2s(cb, g_kv + (size_t)(cch0 + c) * 4096, 2048, fb);
          bulk_g2s(cb + CV_PL, g_kv + (size_t)(cch0 + c) * 4096 + 2048, 2048, fb);
        }
      }
      const unsigned* hf = &g_hflag[(((lane < 16 ? (64 * m2) / 160 : (64 * m2 + 63) / 160) * 2 + 1) * 16 + min(lane & 15, 9)) * 8];
      mbar_wait(bars + 8 * (B_CVDONE + 0));
      if (elect_one()) { l2_prefetch(p.cre + (size_t)cch0 * DM, 6400); l2_prefetch(p.cim + (size_t)cch0 * DM, 6400); }
      flag_poll(hf, tag);
      __syncwarp();
      if (lane == 0) { mbar_arrive(bars + 8 * B_H1); TS(22); }
      mbar_wait(bars + 8 * (B_CVDONE + 4));
      flag_poll(&g_gflag[(dg * 32 + lane) * 8], tag);
      __syncwarp();
      fence_async_global();
      if (lane == 0) TS(29);
      if (elect_one()) {
        mbar_expect_tx(bars + 8 * B_GFULL, 20480);
        tma5(sb + G_OFF, &p.mG, 64 * m2, 0, 0, 0, 10 * dg, bars + 8 * B_GFULL);
      }
      mbar_wait(bars + 8 * (B_G1DONE + 19));
      flag_poll(hf + NT1 * 256, tag);
      __syncwarp();
      if (lane == 0) { mbar_arrive(bars + 8 * (B_H1 + 1)); TS(24); }
    }
  } else {
    asm volatile("setmaxnreg.inc.sync.aligned.u32 152;");
    const int w = wid & 3;
    mbar_wait(bars + 8 * B_EP);
    const unsigned tag = lds32(sb + EP_OFF + 20);
    if (wg == 2) {
      ROLE(role)
      if (has2) {
        const int n0 = 64 * m2 + 16 * w + (lane >> 2);
        KvRegs<2> x;
        {
          float xs[80];
          x0_load(xs);
          stats_publish<true>(0, n0, dg, tag, xs);
        }
        if (tid == 256) TS(31);
        kv_load<2>(m2, 32 * w, x);
        if (tid == 352) TS(50);
        kv_finish<2>(m2, 160 * dg + 32 * w, x);
        if (tid == 352) TS(52);
        asm volatile("bar.arrive 3, 192;" ::: "memory");
      } else if (tid == 256) mbar_arrive(bars + 8 * B_PREP);
      stat_table(T1, tag, 0);
      if (tid == 256) TS(26);
      if (!has2) { mbar_wait(bars + 8 * (B_G1FULL + 11)); stat_table(T1, tag, 1); }
    }
#pragma unroll 1
    for (int l = 0; l < 2; l++) {
      if (wg < 2) {
        float acc[80];
#pragma unroll
        for (int i = 0; i < 80; i++) acc[i] = 0.f;
        ROLE(role)
        const int tid = tid_opaque(), r = (tid & 31) >> 2, q = tid & 3;
        const int ch = 128 * GP + 64 * wg + 32 * side + 8 * w + r;
        mbar_wait(bars + 8 * B_CTAB);
        const uint32_t ca = sb + CTAB_OFF + (32 * wg + 8 * w + r) * 24;
        float2 lam = lds64f(ca);
        const float2 coef = lds64f(ca + 8), lamc = make_float2(lam.x, -lam.y);
        float m00 = coef.x, m01 = -coef.y, m10 = -coef.y, m11 = -coef.x;
        if (p.swap) { lam = lamc; m00 = -coef.y; m01 = coef.x; m10 = -coef.x; m11 = -coef.y; }
        float2 pL, p2L, pLq, p160q, p640;
        {
          float2 p2 = cmul(lam, lam), p4 = cmul(p2, p2), p8 = cmul(p4, p4), p16 = cmul(p8, p8), p32 = cmul(p16, p16);
          float2 p40 = cmul(p32, p8), p80 = cmul(p40, p40), p160 = cmul(p80, p80), p320 = cmul(p160, p160);
          p640 = cmul(p320, p320);
          pL = last ? p32 : p40;
          p2L = cmul(pL, pL);
          const float2 one = make_float2(1.f, 0.f);
          pLq = cmul((q & 1) ? pL : one, (q & 2) ? p2L : one);
          p160q = cmul((q & 1) ? p160 : one, (q & 2) ? p320 : one);
        }
        asm volatile("" : "+f"(pL.x), "+f"(pL.y), "+f"(p2L.x), "+f"(p2L.y), "+f"(pLq.x), "+f"(pLq.y), "+f"(p160q.x), "+f"(p160q.y), "+f"(p640.x), "+f"(p640.y)::"memory");
        fence_regs(acc);
        {
          uint32_t alo = desc_lo(sb, 16) + wg * 512, blo = l == 0 ? desc_lo(sb + G1_XOFF, 16) : desc_lo(sb + G1_XOFF, 128);
          const uint32_t bhi = l == 0 ? desc_hi(1024, 1) : desc_hi(1024, 0), xstep = l == 0 ? 2 : 16;
          const uint32_t aend = desc_lo(sb, 16) + (S1 + l) * (G1_STAGE >> 4);
          uint32_t fb = bars + 8 * (B_G1FULL + 10 * l);
          mbar_wait(fb);
          if (tid == 0) TS(1 + 8 * l);
#pragma unroll 1
          for (int k = 0; k < 10; k++) {
            uint32_t ok; const uint32_t nb = k < 9 ? fb + 8 : fb;
            wgmma_fence();
#pragma unroll
            for (int kk = 0; kk < 4; kk++) {
              wgmma_n160<0>(acc, alo + kk * 2, desc_hi(1024, 1), blo + kk * xstep, bhi);
              if (kk == 0) ok = mbar_test(nb);
            }
            wgmma_commit();
            alo += G1_STAGE >> 4; blo += G1_STAGE >> 4;
            if (alo >= aend) { alo -= (S1 + l) * (G1_STAGE >> 4); blo -= (S1 + l) * (G1_STAGE >> 4); }
            wgmma_wait<1>();
            if (k > 0 && (tid & 127) == 0) mbar_arrive(fb + 8 * (B_G1DONE - B_G1FULL - 1));
            if (!ok) mbar_wait(nb);
            if (l == 0 && k == PAUSE_K) { if (tid == 0) TS(48); mbar_wait(bars + 8 * B_PREP); if (tid == 0) TS(49); }
            fb += 8;
          }
        }
        mbar_wait(bars + 8 * (B_STAB + l));
        const float2 sB = lds64f(ca + 16);
        wgmma_wait<0>();
        fence_regs(acc);
        if ((tid & 127) == 0) { mbar_arrive(bars + 8 * (B_G1DONE + 10 * l + 9)); if (wg == 0) TS(2 + 8 * l); }
        float2 e = make_float2(0.f, 0.f), snap = e;
#pragma unroll
        for (int j = 0; j < 20; j++) {
          const float4 st = lds128f(sb + STAB_OFF + (8 * j + 2 * q) * 8);
          acc[4 * j + 0] = fmaf(acc[4 * j + 0], st.x, st.y * sB.x);
          acc[4 * j + 2] = fmaf(acc[4 * j + 2], st.x, st.y * sB.y);
          acc[4 * j + 1] = fmaf(acc[4 * j + 1], st.z, st.w * sB.x);
          acc[4 * j + 3] = fmaf(acc[4 * j + 3], st.z, st.w * sB.y);
          e = cfma(lam, e, make_float2(acc[4 * j + 0], acc[4 * j + 2]));
          e = cfma(lam, e, make_float2(acc[4 * j + 1], acc[4 * j + 3]));
          if (j == 15) snap = e;
        }
        if (last) e = snap;
        {
          float2 v = make_float2(__shfl_up_sync(0xffffffffu, e.x, 1, 4), __shfl_up_sync(0xffffffffu, e.y, 1, 4));
          if (q >= 1) e = cfma(pL, v, e);
          v = make_float2(__shfl_up_sync(0xffffffffu, e.x, 2, 4), __shfl_up_sync(0xffffffffu, e.y, 2, 4));
          if (q >= 2) e = cfma(p2L, v, e);
        }
        if (!last && (q == 3 || (q == 2 && l == 0))) rec_st(&g_E[((q == 3 ? l : 1) * NT1 + T1) * DM + ch], e.x, e.y, q == 3 ? tag : tag - 1);
        if (tid == 0) TS(3 + 8 * l);
        float2 ex = make_float2(__shfl_up_sync(0xffffffffu, e.x, 1, 4), __shfl_up_sync(0xffffffffu, e.y, 1, 4));
        if (q == 0) ex = make_float2(0.f, 0.f);
        float2 c, ev[3];
        unsigned tg[3];
        const uint4* ep = &g_E[(l * NT1 + T1 - 1 - q) * DM + ch];
#pragma unroll
        for (int j = 0; j < 20; j++) {
          if (j == CPOLL) {
#pragma unroll
            for (int i = 0; i < 3; i++) {
              ev[i] = make_float2(0.f, 0.f); tg[i] = tag;
              if (T1 - 1 - q - 4 * i >= 0) tg[i] = rec_ld(ep - 4 * i * DM, ev[i].x, ev[i].y);
            }
          }
#pragma unroll
          for (int x = 0; x < 2; x++) {
            const float b0 = acc[4 * j + x], b1 = acc[4 * j + 2 + x];
            acc[4 * j + x] = fmaf(b0, m00, b1 * m01);
            acc[4 * j + 2 + x] = fmaf(b0, m10, b1 * m11);
          }
          if (j == CPOLL - 1 || j == 19) asm volatile("" : "+f"(acc[4 * j]), "+f"(acc[4 * j + 1]), "+f"(acc[4 * j + 2]), "+f"(acc[4 * j + 3])::"memory");
        }
        {
          uint32_t it = 0;
          while (tg[0] != tag || tg[1] != tag || tg[2] != tag) {
#pragma unroll
            for (int i = 0; i < 3; i++)
              if (tg[i] != tag) tg[i] = rec_ld(ep - 4 * i * DM, ev[i].x, ev[i].y);
            if (++it > SPIN_LIMIT) soft_trap();
          }
          __syncwarp();
          c = cfma(p640, cfma(p640, ev[2], ev[1]), ev[0]);
          c = cmul(c, p160q);
          c.x += __shfl_xor_sync(0xffffffffu, c.x, 1); c.y += __shfl_xor_sync(0xffffffffu, c.y, 1);
          c.x += __shfl_xor_sync(0xffffffffu, c.x, 2); c.y += __shfl_xor_sync(0xffffffffu, c.y, 2);
        }
        if (tid == 0) TS(4 + 8 * l);
        if (tid == 128) mbar_arrive(bars + 8 * (B_GO + 2 * l));
        c = cfma(pLq, c, ex);
        float2 hh = make_float2(fmaf(c.x, m00, c.y * m01), fmaf(c.x, m10, c.y * m11));
        uint8_t* hb = g_h + (size_t)l * (32 * 20 * 8192) + (10 * wg + 2 * GP) * 8192 + (4 * side + w) * 1024 + (tid_opaque() & 31) * 4;
#pragma unroll
        for (int j4 = 0; j4 < 5; j4++) {
          const int ng = 20 * T1 + 4 * j4;
          uint8_t* hp = hb + (size_t)(ng >> 3) * 163840 + (ng & 7) * 128;
#pragma unroll
          for (int jj = 0; jj < 4; jj++) {
            const int j = 4 * j4 + jj;
            const float2 h0 = cfma(lamc, hh, make_float2(acc[4 * j + 0], acc[4 * j + 2]));
            hh = cfma(lamc, h0, make_float2(acc[4 * j + 1], acc[4 * j + 3]));
            if (j4 < 4 || !last) {
              *(uint32_t*)(hp + jj * 128) = pack_bf16(h0.x, hh.x);
              *(uint32_t*)(hp + jj * 128 + 8192) = pack_bf16(h0.y, hh.y);
            }
          }
        }
        mbar_arrive(bars + 8 * (B_HST + 2 * l + wg));
        if (tid == 0) TS(5 + 8 * l);
      }
      if (l == 0) {
        ROLE(role)
        if (has2) {
          uint32_t so[4];
          cv_offsets(so);
          mbar_wait(bars + 8 * (B_G1DONE + 9));
#pragma unroll 1
          for (int c = wg == 2 ? 0 : 2 + wg; c < (wg == 2 ? 2 : 5); c += wg == 2 ? 1 : 2) conv_channel(c, so);
          if ((tid & 127) == 0) TS(wg == 2 ? 32 : 7 + wg);
        }
      }
      if (wg == 2) break;
    }
    if (wg == 2 && (role >> 16)) {
      float acc[80];
      float off[2] = {0.f, 0.f};
      x0_load(acc);
      mbar_arrive(bars + 8 * B_XFREE);
#pragma unroll 1
      for (int l = 0; l < 2; l++) {
        float mean[2], rstd[2];
        {
          ROLE(role)
          const int lane = tid_opaque() & 31;
          stats_get(2 * l, 64 * m2 + 16 * w + (lane >> 2), tag, mean, rstd);
          off[0] += mean[0]; off[1] += mean[1];
          mbar_wait(bars + 8 * (l == 0 ? B_CTAB : B_HST + 3));
#pragma unroll
          for (int J = 0; J < 10; J++) {
            const float2 dw = lds64f(sb + DTAB_OFF + 2 * (16 * J + 4 * (lane & 3)));
#pragma unroll
            for (int x = 0; x < 8; x++) {
              const int h = (x >> 1) & 1;
              const uint32_t gwd = __float_as_uint(x < 4 ? dw.x : dw.y);
              acc[8 * J + x] = (acc[8 * J + x] - mean[h]) * fmaf(rstd[h], (x & 1) ? bf_hi(gwd) : bf_lo(gwd), 1.f);
            }
          }
        }
        {
          const uint32_t aend = desc_lo(sb + SX2 * G2_XB, 1024) + l * (G2_XB >> 3), bend = desc_lo(sb + G2_WOFF + 6 * G2_WB, 16) + l * (G2_WB >> 4);
          uint32_t alo = desc_lo(sb, 1024), blo = desc_lo(sb + G2_WOFF, 16);
          uint32_t fb = bars + 8 * (B_G2FULL + 20 * l);
          fence_regs(acc);
          mbar_wait(fb);
          if (tid == 256) TS(33 + 6 * l);
#pragma unroll 1
          for (int k = 0; k < 20; k++) {
            if (l == 1 && (k & 3) == 3 && tid == 256) TS(56 + (k >> 2));
            uint32_t ok; const uint32_t nb = k < 19 ? fb + 8 : fb;
            wgmma_fence();
#pragma unroll
            for (int kk = 0; kk < 4; kk++) {
              wgmma_n160<1>(acc, alo + kk * 128, desc_hi(128, 0), blo + kk * 2, desc_hi(1024, 1));
              if (kk == 0) ok = mbar_test(nb);
            }
            wgmma_commit();
            alo += G2_XB >> 4; if (alo == aend) alo = desc_lo(sb, 1024);
            blo += G2_WB >> 4; if (blo == bend) blo = desc_lo(sb + G2_WOFF, 16);
            wgmma_wait<1>();
            if (k > 0 && tid == 256) mbar_arrive(fb + 8 * (B_G2DONE - B_G2FULL - 1));
            if (!ok) mbar_wait(nb);
            fb += 8;
          }
          wgmma_wait<0>();
          fence_regs(acc);
          if (tid == 256) TS(34 + 6 * l);
          if (tid == 256) mbar_arrive(bars + 8 * (B_G2DONE + 20 * l + 19));
        }
        ROLE(role)
        const int tq = tid_opaque() & 31, n0 = 64 * m2 + 16 * w + (tq >> 2);
        stats_publish<false>(2 * l + 1, n0, dg, tag, acc);
        uint32_t gf[10][4];
        mbar_wait(bars + 8 * B_GFULL);
        const uint32_t ga = sb + G_OFF + (8 * (tq >> 4) + (tq & 7)) * 128 + (((2 * w + ((tq >> 3) & 1)) ^ (m2 & 7) ^ (tq & 7)) << 4);
#pragma unroll
        for (int J = 0; J < 4; J++) ldsm4t(gf[J], ga + J * 2048);
        if (tid == 256) TS(35 + 6 * l);
        uint8_t* dst[2][2];
#pragma unroll
        for (int h = 0; h < 2; h++) {
          if (l == 0) {
            const int ng = 8 * m2 + 2 * w + h, T = ng / 20;
            uint8_t* ub = g_u + (T * 204800 + (ng - 20 * T) * 1024 + (tq & 2) * 64 + (tq & 28) * 4 + (tq & 1) * 8 + (5 * dg >> 1) * 20480);
            dst[h][1] = ub + ((dg & 1) ? 20480 - 512 : 0);
            dst[h][0] = ub + (dg & 1) * 512;
          } else {
            dst[h][0] = dst[h][1] = (uint8_t*)(p.out + (n_to_t(n0 + 8 * h) * DM + 160 * dg + 4 * (tq & 3)));
          }
        }
        stats_get(2 * l + 1, n0, tag, mean, rstd);
        if (tid == 256) { TS(36 + 6 * l); if (l == 0) mbar_arrive(bars + 8 * (B_GO + 1)); }
        off[0] += mean[0]; off[1] += mean[1];
#pragma unroll
        for (int J = 0; J < 10; J++) {
          asm volatile("" : "+r"(gf[J][0]), "+r"(gf[J][1]), "+r"(gf[J][2]), "+r"(gf[J][3])::"memory");
          if (J + 4 < 10) ldsm4t(gf[J + 4 < 10 ? J + 4 : 0], ga + (J + 4) * 2048);
#pragma unroll
          for (int x = 0; x < 8; x++) {
            const int h = (x >> 1) & 1;
            const uint32_t gwd = gf[J][x >> 1];
            acc[8 * J + x] = (acc[8 * J + x] - mean[h]) * fmaf(rstd[h], (x & 1) ? bf_hi(gwd) : bf_lo(gwd), 1.f);
          }
#pragma unroll
          for (int h = 0; h < 2; h++) {
            if (l == 0)
              *(uint2*)(dst[h][(J >> 1) & 1] + (J >> 2) * 20480 + (J & 3) * 256) =
                  make_uint2(pack_bf16(acc[8 * J + 2 * h], acc[8 * J + 2 * h + 1]), pack_bf16(acc[8 * J + 4 + 2 * h], acc[8 * J + 5 + 2 * h]));
            else
              *(float4*)(dst[h][0] + 64 * J) = make_float4(acc[8 * J + 2 * h] + off[h], acc[8 * J + 2 * h + 1] + off[h],
                                                           acc[8 * J + 4 + 2 * h] + off[h], acc[8 * J + 5 + 2 * h] + off[h]);
          }
        }
        if (l == 0) {
          bar_sync(3, 128);
          if (tid == 256) { TS(37); st_rel(&g_uflag[(4 * m2 + dg) * 8], tag); TS(38); }
          stats_publish<false>(2, n0, dg, tag, acc);
          mbar_wait(bars + 8 * (B_G1FULL + 11));
          stat_table(T1, tag, 1);
          if (tid == 256) TS(27);
        } else {
          if (tid == 256) {
            TS(43);
            if (m2 == 31 && dg == 3) asm volatile("st.relaxed.gpu.global.u32 [%0], %1;" ::"l"(g_epoch), "r"(tag + 1) : "memory");
          }
        }
      }
    }
  }
}

typedef CUresult (*EncFn)(CUtensorMap*, CUtensorMapDataType, cuuint32_t, void*, const cuuint64_t*, const cuuint64_t*,
                          const cuuint32_t*, const cuuint32_t*, CUtensorMapInterleave, CUtensorMapSwizzle,
                          CUtensorMapL2promotion, CUtensorMapFloatOOBfill);

void encode(EncFn fn, CUtensorMap* m, const void* ptr, int rank, const cuuint64_t* dims, const cuuint64_t* strides, const cuuint32_t* box,
            CUtensorMapSwizzle swz = CU_TENSOR_MAP_SWIZZLE_128B) {
  cuuint32_t es[5] = {1, 1, 1, 1, 1};
  fn(m, CU_TENSOR_MAP_DATA_TYPE_BFLOAT16, rank, (void*)ptr, dims, strides, box, es, CU_TENSOR_MAP_INTERLEAVE_NONE,
     swz, swz == CU_TENSOR_MAP_SWIZZLE_128B ? CU_TENSOR_MAP_L2_PROMOTION_L2_128B : CU_TENSOR_MAP_L2_PROMOTION_L2_64B, CU_TENSOR_MAP_FLOAT_OOB_FILL_NONE);
}

}

extern "C" void kernel_launch(void* const* d_in, const int* in_sizes, int n_in, void* d_out, int out_size) {
  (void)in_sizes; (void)n_in; (void)out_size;
  Params p;
  typedef const __nv_bfloat16* BP;
  p.x = (BP)d_in[0]; p.lre = (BP)d_in[1]; p.lim = (BP)d_in[2]; p.bre = (BP)d_in[3]; p.bim = (BP)d_in[4];
  p.cre = (BP)d_in[5]; p.cim = (BP)d_in[6]; p.logdt = (BP)d_in[7]; p.dskip = (BP)d_in[8];
  p.k = (BP)d_in[10]; p.v = (BP)d_in[11]; p.shiftk = (BP)d_in[12]; p.ssmk = (BP)d_in[13]; p.ssmD = (BP)d_in[14];
  p.out = (float*)d_out;
  void* fnp = nullptr;
  cudaDriverEntryPointQueryResult qr;
  cudaGetDriverEntryPoint("cuTensorMapEncodeTiled", &fnp, cudaEnableDefault, &qr);
  EncFn fn = (EncFn)fnp;
  void* gG = nullptr;
  cudaGetSymbolAddress(&gG, g_G);
  const cuuint64_t RB = DM * 2;
  {
    p.swap = p.bim < p.bre;
    const char* lo = (const char*)(p.swap ? p.bim : p.bre); const char* hi = (const char*)(p.swap ? p.bre : p.bim);
    cuuint64_t dims[5] = {640, 8, 2, 8, 10}, st[4] = {RB, (cuuint64_t)(hi - lo), 8 * RB, 64 * RB}; cuuint32_t box[5] = {64, 8, 2, 4, 2};
    encode(fn, &p.mB, lo, 5, dims, st, box);
  }
  {
    cuuint64_t dims[5] = {640, 2, 4, 2, 40}, st[4] = {RB, 4 * RB, 2 * RB, 16 * RB}; cuuint32_t box[5] = {64, 2, 4, 2, 10};
    encode(fn, &p.mCre, p.cre, 5, dims, st, box); encode(fn, &p.mCim, p.cim, 5, dims, st, box);
    cuuint64_t dimg[5] = {2048, 2, 4, 2, 40}, stg[4] = {4096, 4 * 4096, 2 * 4096, 16 * 4096};
    encode(fn, &p.mG, gG, 5, dimg, stg, box);
  }
  {
    cuuint64_t dims[4] = {640, 2, 4, 900}, st[3] = {RB, 40 * RB, 2 * RB}; cuuint32_t box[4] = {64, 2, 4, 20};
    encode(fn, &p.mX, p.x, 4, dims, st, box);
    cuuint64_t diml[4] = {640, 2, 4, 16}, stl[3] = {RB, 32 * RB, 2 * RB};
    encode(fn, &p.mXl, p.x + (size_t)1920 * DM, 4, diml, stl, box);
    cuuint32_t boxt[4] = {160, 2, 4, 4};
    encode(fn, &p.mXt, p.x, 4, dims, st, boxt, CU_TENSOR_MAP_SWIZZLE_NONE);
    encode(fn, &p.mXtl, p.x + (size_t)1920 * DM, 4, diml, stl, boxt, CU_TENSOR_MAP_SWIZZLE_NONE);
    cuuint64_t dk[3] = {640, 2000, 4}, sk[2] = {RB, 16 * RB}; cuuint32_t bk[3] = {32, 19, 4}, bv[3] = {32, 17, 4};
    encode(fn, &p.mK, p.k, 3, dk, sk, bk, CU_TENSOR_MAP_SWIZZLE_NONE);
    encode(fn, &p.mV, p.v, 3, dk, sk, bv, CU_TENSOR_MAP_SWIZZLE_NONE);
  }
  cudaFuncSetAttribute(fused_kernel, cudaFuncAttributeMaxDynamicSharedMemorySize, SMEM_BYTES);
  cudaLaunchConfig_t cfg = {};
  cfg.gridDim = dim3(132); cfg.blockDim = dim3(512); cfg.dynamicSmemBytes = SMEM_BYTES; cfg.stream = cudaStreamPerThread;
  cudaLaunchKernelEx(&cfg, fused_kernel, p);
}
```

```cpp
#include <cuda_runtime.h>
#include <cuda.h>
#include <cuda_bf16.h>
#include <stdint.h>

namespace {

constexpr int SEQ = 2048, DM = 640;
constexpr int NT1 = 13;
#define EXP 0
#define WPF1 1
#define WPF2 2
#define CPOLL 10
#define PAUSE_K 4
constexpr uint32_t SPIN_LIMIT = 1u << 22;

__device__ __align__(1024) uint8_t g_h[2 * 32 * 20 * 8192];
__device__ __align__(1024) uint8_t g_u[NT1 * 10 * 20480];
__device__ __align__(1024) uint8_t g_kv[DM * 4096];
__device__ __align__(1024) uint8_t g_G[DM * 4096];
__device__ __align__(128) uint4 g_E[2 * NT1 * DM];
__device__ __align__(128) uint4 g_stats[4 * 4 * SEQ];
__device__ __align__(128) uint4 g_sB[DM * 2];
__device__ __align__(128) unsigned g_hflag[2 * NT1 * 2 * 16 * 8];
__device__ __align__(128) unsigned g_uflag[32 * 4 * 8];
__device__ __align__(128) unsigned g_kvflag[4 * 32 * 8];
__device__ __align__(128) unsigned g_gflag[4 * 32 * 8];
__device__ __align__(128) unsigned g_epoch[32] = {1};
#define TS(i) do {} while (0)

struct Params {
  CUtensorMap mB, mCre, mCim, mX, mXl, mG, mK, mV, mXt, mXtl;
  const __nv_bfloat16 *x, *lre, *lim, *bre, *bim, *cre, *cim, *logdt, *dskip, *k, *v, *shiftk, *ssmk, *ssmD;
  float* out;
  int swap;
};

constexpr uint32_t sb = 1024;
constexpr uint32_t G1_STAGE = 36864, G1_XOFF = 16384;
constexpr int S1 = 4;
constexpr uint32_t XT_OFF = 159744, KS_OFF = 180224, KV_PIECE = 9216;
constexpr uint32_t G2_XB = 8192, G2_WB = 20480, G2_WOFF = 57344, G_OFF = 200704;
constexpr int SX2 = 5;
constexpr uint32_t CV_OFF = 184320, CV_K = 128, CV_PL = 2240, CV_U = CV_K + 4096, CV_B = 8704;
constexpr uint32_t MISC = 227840;
constexpr uint32_t BAR_OFF = MISC;
constexpr int B_G1FULL = 0, B_G1DONE = 20, B_G2FULL = 40,
              B_G2DONE = 85, B_GFULL = 125, B_PREP = 126, B_EP = 127, B_H1 = 128  ,
              B_CVDONE = 130, B_STAB = 135  , B_CTAB = 137, B_XFREE = 138, B_HST = 139  ,
              B_XT = 143, B_KV = 144  , B_TAPS = 149  , B_CVFULL = 154  , B_GO = 159  ;
constexpr uint32_t bars = sb + BAR_OFF;
constexpr uint32_t STAB_OFF = MISC + 1296;
constexpr uint32_t CTAB_OFF = STAB_OFF + 1280;
constexpr uint32_t DTAB_OFF = CTAB_OFF + 1536;
constexpr uint32_t EP_OFF = DTAB_OFF + 320;
constexpr uint32_t TAP_OFF = 147456;
constexpr uint32_t SMEM_BYTES = 232448;
static_assert(EP_OFF + 32 <= SMEM_BYTES, "smem");

__device__ __forceinline__ void soft_trap() { asm volatile("trap;"); }
__device__ __forceinline__ uint32_t smem_u32(const void* p) { return (uint32_t)__cvta_generic_to_shared(p); }
__device__ __forceinline__ void mbar_init(uint32_t bar, int cnt) { asm volatile("mbarrier.init.shared::cta.b64 [%0], %1;" ::"r"(bar), "r"(cnt) : "memory"); }
__device__ __forceinline__ void mbar_expect_tx(uint32_t bar, int bytes) { asm volatile("mbarrier.arrive.expect_tx.shared::cta.b64 _, [%0], %1;" ::"r"(bar), "r"(bytes) : "memory"); }
__device__ __forceinline__ void mbar_arrive(uint32_t bar) { asm volatile("mbarrier.arrive.shared::cta.b64 _, [%0];" ::"r"(bar) : "memory"); }
__device__ __forceinline__ void mbar_wait(uint32_t bar) {
  asm volatile(
      "{\n.reg .pred p;\n.reg .u32 c;\nmov.u32 c, 0;\n"
      "W_%=:\nmbarrier.try_wait.parity.shared::cta.b64 p, [%0], 0;\n@p bra D_%=;\n"
      "add.u32 c, c, 1;\nsetp.lt.u32 p, c, %1;\n@p bra W_%=;\ntrap;\nD_%=:\n}\n" ::"r"(bar), "n"(SPIN_LIMIT) : "memory");
}
__device__ __forceinline__ uint32_t mbar_test(uint32_t bar) {
  uint32_t ok;
  asm volatile("{\n.reg .pred p;\nmbarrier.test_wait.parity.shared::cta.b64 p, [%1], 0;\nselp.u32 %0, 1, 0, p;\n}\n" : "=r"(ok) : "r"(bar) : "memory");
  return ok;
}
__device__ __forceinline__ void tma3(uint32_t dst, const CUtensorMap* m, int c0, int c1, int c2, uint32_t bar) {
  asm volatile("cp.async.bulk.tensor.3d.shared::cluster.global.mbarrier::complete_tx::bytes [%0], [%1, {%3,%4,%5}], [%2];"
               ::"r"(dst), "l"(m), "r"(bar), "r"(c0), "r"(c1), "r"(c2) : "memory");
}
__device__ __forceinline__ void tma4(uint32_t dst, const CUtensorMap* m, int c0, int c1, int c2, int c3, uint32_t bar) {
  asm volatile("cp.async.bulk.tensor.4d.shared::cluster.global.mbarrier::complete_tx::bytes [%0], [%1, {%3,%4,%5,%6}], [%2];"
               ::"r"(dst), "l"(m), "r"(bar), "r"(c0), "r"(c1), "r"(c2), "r"(c3) : "memory");
}
__device__ __forceinline__ void tma5(uint32_t dst, const CUtensorMap* m, int c0, int c1, int c2, int c3, int c4, uint32_t bar) {
  asm volatile("cp.async.bulk.tensor.5d.shared::cluster.global.mbarrier::complete_tx::bytes [%0], [%1, {%3,%4,%5,%6,%7}], [%2];"
               ::"r"(dst), "l"(m), "r"(bar), "r"(c0), "r"(c1), "r"(c2), "r"(c3), "r"(c4) : "memory");
}
__device__ __forceinline__ void bulk_g2s(uint32_t dst, const void* src, int bytes, uint32_t bar) {
  asm volatile("cp.async.bulk.shared::cluster.global.mbarrier::complete_tx::bytes [%0], [%1], %2, [%3];"
               ::"r"(dst), "l"(src), "r"(bytes), "r"(bar) : "memory");
}
__device__ __forceinline__ void bulk_s2g(void* dst, uint32_t src, int bytes) {
  asm volatile("cp.async.bulk.global.shared::cta.bulk_group [%0], [%1], %2;" ::"l"(dst), "r"(src), "r"(bytes) : "memory");
}
__device__ __forceinline__ void l2_prefetch(const void* src, int bytes) {
  asm volatile("cp.async.bulk.prefetch.L2.global [%0], %1;" ::"l"(src), "r"(bytes) : "memory");
}
__device__ __forceinline__ void wgmma_fence() { asm volatile("wgmma.fence.sync.aligned;" ::: "memory"); }
__device__ __forceinline__ void wgmma_commit() { asm volatile("wgmma.commit_group.sync.aligned;" ::: "memory"); }
template <int N> __device__ __forceinline__ void wgmma_wait() { asm volatile("wgmma.wait_group.sync.aligned %0;" ::"n"(N) : "memory"); }
__host__ __device__ constexpr uint32_t desc_lo(uint32_t addr, uint32_t lbo) { return ((addr & 0x3FFFF) >> 4) | ((lbo >> 4) << 16); }
__host__ __device__ constexpr uint32_t desc_hi(uint32_t sbo, uint32_t swz) { return (sbo >> 4) | (swz << 30); }
__device__ __forceinline__ void bar_sync(int id, int n) { asm volatile("bar.sync %0, %1;" ::"r"(id), "r"(n) : "memory"); }
__device__ __forceinline__ uint32_t lds32(uint32_t a) { uint32_t v; asm volatile("ld.shared.u32 %0, [%1];" : "=r"(v) : "r"(a) : "memory"); return v; }
__device__ __forceinline__ float2 lds64f(uint32_t a) { float2 v; asm volatile("ld.shared.v2.f32 {%0,%1}, [%2];" : "=f"(v.x), "=f"(v.y) : "r"(a) : "memory"); return v; }
__device__ __forceinline__ float4 lds128f(uint32_t a) { float4 v; asm volatile("ld.shared.v4.f32 {%0,%1,%2,%3}, [%4];" : "=f"(v.x), "=f"(v.y), "=f"(v.z), "=f"(v.w) : "r"(a) : "memory"); return v; }
__device__ __forceinline__ void ldsm4t(uint32_t (&r)[4], uint32_t a) {
  asm volatile("ldmatrix.sync.aligned.m8n8.x4.trans.shared.b16 {%0,%1,%2,%3}, [%4];" : "=r"(r[0]), "=r"(r[1]), "=r"(r[2]), "=r"(r[3]) : "r"(a) : "memory");
}
__device__ __forceinline__ uint4 ldv128(const void* a) { uint4 v; asm volatile("ld.global.nc.v4.u32 {%0,%1,%2,%3}, [%4];" : "=r"(v.x), "=r"(v.y), "=r"(v.z), "=r"(v.w) : "l"(a) : "memory"); return v; }
__device__ __forceinline__ uint2 ldv64(const void* a) { uint2 v; asm volatile("ld.global.nc.v2.u32 {%0,%1}, [%2];" : "=r"(v.x), "=r"(v.y) : "l"(a) : "memory"); return v; }
__device__ __forceinline__ uint32_t ldv16(const void* a) { uint32_t v; asm volatile("ld.global.nc.u16 %0, [%1];" : "=r"(v) : "l"(a) : "memory"); return v; }
__device__ __forceinline__ void sts128(uint32_t a, uint4 v) { asm volatile("st.shared.v4.u32 [%0], {%1,%2,%3,%4};" ::"r"(a), "r"(v.x), "r"(v.y), "r"(v.z), "r"(v.w) : "memory"); }
__device__ __forceinline__ void sts32(uint32_t a, uint32_t v) { asm volatile("st.shared.u32 [%0], %1;" ::"r"(a), "r"(v) : "memory"); }
__device__ __forceinline__ void sts64f(uint32_t a, float x, float y) { asm volatile("st.shared.v2.f32 [%0], {%1,%2};" ::"r"(a), "f"(x), "f"(y) : "memory"); }
__device__ __forceinline__ void st_rel(unsigned* p, unsigned v) { asm volatile("st.release.gpu.global.u32 [%0], %1;" ::"l"(p), "r"(v) : "memory"); }
__device__ __forceinline__ void fence_async_global() { asm volatile("fence.proxy.async.global;" ::: "memory"); }
__device__ __forceinline__ void fence_async_smem() { asm volatile("fence.proxy.async.shared::cta;" ::: "memory"); }
__device__ __forceinline__ void rec_st(uint4* p, float a, float b, unsigned tag) {
  asm volatile("{\n.reg .b128 t;\n.reg .b64 lo, hi;\nmov.b64 lo, {%1,%2};\nmov.b64 hi, {%3,%3};\nmov.b128 t, {lo,hi};\n"
               "st.relaxed.gpu.global.b128 [%0], t;\n}\n" ::"l"(p), "r"(__float_as_uint(a)), "r"(__float_as_uint(b)), "r"(tag) : "memory");
}
__device__ __forceinline__ unsigned rec_ld(const uint4* p, float& a, float& b) {
  unsigned x, y, t;
  asm volatile("{\n.reg .b128 t;\n.reg .b64 lo, hi;\n.reg .b32 u;\nld.relaxed.gpu.global.b128 t, [%3];\nmov.b128 {lo,hi}, t;\n"
               "mov.b64 {%0,%1}, lo;\nmov.b64 {%2,u}, hi;\n}\n" : "=r"(x), "=r"(y), "=r"(t) : "l"(p) : "memory");
  a = __uint_as_float(x); b = __uint_as_float(y);
  return t;
}
__device__ __forceinline__ void rec_poll(const uint4* p, unsigned tag, float& a, float& b) {
  uint32_t it = 0;
  while (rec_ld(p, a, b) != tag) { if (++it > SPIN_LIMIT) soft_trap(); }
}
__device__ __forceinline__ unsigned ld_rlx(const unsigned* p) { unsigned v; asm volatile("ld.relaxed.gpu.global.u32 %0, [%1];" : "=r"(v) : "l"(p) : "memory"); return v; }
__device__ __forceinline__ void flag_poll(const unsigned* p, unsigned target) {
  uint32_t it = 0;
  while ((int)(ld_rlx(p) - target) < 0) { if (++it > SPIN_LIMIT) soft_trap(); }
  asm volatile("fence.acquire.gpu;" ::: "memory");
}
__device__ __forceinline__ uint32_t pack_bf16(float lo, float hi) {
  uint32_t r; asm("cvt.rn.bf16x2.f32 %0, %1, %2;" : "=r"(r) : "f"(hi), "f"(lo)); return r;
}
__device__ __forceinline__ float bf_lo(uint32_t w) { return __uint_as_float(w << 16); }
__device__ __forceinline__ float bf_hi(uint32_t w) { return __uint_as_float(w & 0xffff0000u); }
__device__ __forceinline__ uint32_t hmul2(uint32_t a, uint32_t b) {
  __nv_bfloat162 r = __hmul2_rn(*(__nv_bfloat162*)&a, *(__nv_bfloat162*)&b); return *(uint32_t*)&r;
}
__device__ __forceinline__ uint32_t hadd2(uint32_t a, uint32_t b) {
  __nv_bfloat162 r = __hadd2_rn(*(__nv_bfloat162*)&a, *(__nv_bfloat162*)&b); return *(uint32_t*)&r;
}
__device__ __forceinline__ float2 cmul(float2 a, float2 b) { return make_float2(a.x * b.x - a.y * b.y, a.x * b.y + a.y * b.x); }
__device__ __forceinline__ float2 cfma(float2 a, float2 b, float2 c) {
  return make_float2(fmaf(a.x, b.x, fmaf(-a.y, b.y, c.x)), fmaf(a.x, b.y, fmaf(a.y, b.x, c.y)));
}
template <int N> __device__ __forceinline__ void fence_regs(float (&a)[N]) {
#pragma unroll
  for (int i = 0; i < N; i++) asm volatile("" : "+f"(a[i])::"memory");
}
__device__ __forceinline__ bool elect_one() {
  uint32_t e; asm volatile("{\n.reg .pred P;\nelect.sync _|P, 0xffffffff;\nselp.u32 %0, 1, 0, P;\n}\n" : "=r"(e)); return e != 0;
}
__device__ __forceinline__ int tid_opaque() { int t; asm volatile("mov.u32 %0, %%tid.x;" : "=r"(t)); return t; }
struct Role { int T1, GP, side, m2, dg, cch0; bool last, has2; };
__device__ __forceinline__ Role unpack_role(int x) {
  Role r; r.T1 = x & 15; r.GP = (x >> 4) & 7; r.side = (x >> 7) & 1; r.m2 = (x >> 8) & 63; r.dg = (x >> 14) & 3;
  r.has2 = (x >> 16) & 1; r.last = r.T1 == NT1 - 1; r.cch0 = 5 * (32 * r.dg + r.m2); return r;
}
__device__ __forceinline__ Role fresh_role(int x) { asm volatile("" : "+r"(x)); return unpack_role(__shfl_sync(0xffffffffu, x, 0)); }
#define ROLE(x) const Role R_ = fresh_role(x); const int T1 = R_.T1, GP = R_.GP, side = R_.side, m2 = R_.m2, dg = R_.dg, cch0 = R_.cch0; \
  const bool last = R_.last, has2 = R_.has2; (void)T1; (void)GP; (void)side; (void)m2; (void)dg; (void)cch0; (void)last; (void)has2;
__device__ __forceinline__ int n_to_t(int n) {
  int T = n / 160, nl = n - T * 160;
  int L = (T == NT1 - 1) ? 32 : 40;
  return T * 160 + L * ((nl & 7) >> 1) + 2 * (nl >> 3) + (nl & 1);
}

template<int TA> __device__ __forceinline__ void wgmma_n160(float (&d)[80], uint32_t alo, uint32_t ahi, uint32_t blo, uint32_t bhi){
  asm volatile("{\n.reg .b64 da, db;\nmov.b64 da, {%80,%81};\nmov.b64 db, {%82,%83};\n"
    "wgmma.mma_async.sync.aligned.m64n160k16.f32.bf16.bf16 {%0, %1, %2, %3, %4, %5, %6, %7, %8, %9, %10, %11, %12, %13, %14, %15, %16, %17, %18, %19, %20, %21, %22, %23, %24, %25, %26, %27, %28, %29, %30, %31, %32, %33, %34, %35, %36, %37, %38, %39, %40, %41, %42, %43, %44, %45, %46, %47, %48, %49, %50, %51, %52, %53, %54, %55, %56, %57, %58, %59, %60, %61, %62, %63, %64, %65, %66, %67, %68, %69, %70, %71, %72, %73, %74, %75, %76, %77, %78, %79}, da, db, 1, 1, 1, %84, 0;\n}\n"
    : "+f"(d[0]), "+f"(d[1]), "+f"(d[2]), "+f"(d[3]), "+f"(d[4]), "+f"(d[5]), "+f"(d[6]), "+f"(d[7]), "+f"(d[8]), "+f"(d[9]), "+f"(d[10]), "+f"(d[11]), "+f"(d[12]), "+f"(d[13]), "+f"(d[14]), "+f"(d[15]), "+f"(d[16]), "+f"(d[17]), "+f"(d[18]), "+f"(d[19]), "+f"(d[20]), "+f"(d[21]), "+f"(d[22]), "+f"(d[23]), "+f"(d[24]), "+f"(d[25]), "+f"(d[26]), "+f"(d[27]), "+f"(d[28]), "+f"(d[29]), "+f"(d[30]), "+f"(d[31]), "+f"(d[32]), "+f"(d[33]), "+f"(d[34]), "+f"(d[35]), "+f"(d[36]), "+f"(d[37]), "+f"(d[38]), "+f"(d[39]), "+f"(d[40]), "+f"(d[41]), "+f"(d[42]), "+f"(d[43]), "+f"(d[44]), "+f"(d[45]), "+f"(d[46]), "+f"(d[47]), "+f"(d[48]), "+f"(d[49]), "+f"(d[50]), "+f"(d[51]), "+f"(d[52]), "+f"(d[53]), "+f"(d[54]), "+f"(d[55]), "+f"(d[56]), "+f"(d[57]), "+f"(d[58]), "+f"(d[59]), "+f"(d[60]), "+f"(d[61]), "+f"(d[62]), "+f"(d[63]), "+f"(d[64]), "+f"(d[65]), "+f"(d[66]), "+f"(d[67]), "+f"(d[68]), "+f"(d[69]), "+f"(d[70]), "+f"(d[71]), "+f"(d[72]), "+f"(d[73]), "+f"(d[74]), "+f"(d[75]), "+f"(d[76]), "+f"(d[77]), "+f"(d[78]), "+f"(d[79])
    : "r"(alo), "r"(ahi), "r"(blo), "r"(bhi), "n"(TA));
}
template<int N> __device__ __forceinline__ void wgmma_rs_hi(float (&d)[64], uint32_t a0, uint32_t a1, uint32_t a2, uint32_t a3, uint32_t blo);
template<> __device__ __forceinline__ void wgmma_rs_hi<16>(float (&d)[64], uint32_t a0, uint32_t a1, uint32_t a2, uint32_t a3, uint32_t blo){
  asm volatile("{\n.reg .b64 db;\nmov.b64 db, {%12,8};\nwgmma.mma_async.sync.aligned.m64n16k16.f32.bf16.bf16 {%0, %1, %2, %3, %4, %5, %6, %7}, {%8,%9,%10,%11}, db, 1, 1, 1, 0;\n}\n"
    : "+f"(d[56]), "+f"(d[57]), "+f"(d[58]), "+f"(d[59]), "+f"(d[60]), "+f"(d[61]), "+f"(d[62]), "+f"(d[63])
    : "r"(a0), "r"(a1), "r"(a2), "r"(a3), "r"(blo));
}
template<> __device__ __forceinline__ void wgmma_rs_hi<32>(float (&d)[64], uint32_t a0, uint32_t a1, uint32_t a2, uint32_t a3, uint32_t blo){
  asm volatile("{\n.reg .b64 db;\nmov.b64 db, {%20,8};\nwgmma.mma_async.sync.aligned.m64n32k16.f32.bf16.bf16 {%0, %1, %2, %3, %4, %5, %6, %7, %8, %9, %10, %11, %12, %13, %14, %15}, {%16,%17,%18,%19}, db, 1, 1, 1, 0;\n}\n"
    : "+f"(d[48]), "+f"(d[49]), "+f"(d[50]), "+f"(d[51]), "+f"(d[52]), "+f"(d[53]), "+f"(d[54]), "+f"(d[55]), "+f"(d[56]), "+f"(d[57]), "+f"(d[58]), "+f"(d[59]), "+f"(d[60]), "+f"(d[61]), "+f"(d[62]), "+f"(d[63])
    : "r"(a0), "r"(a1), "r"(a2), "r"(a3), "r"(blo));
}
template<> __device__ __forceinline__ void wgmma_rs_hi<48>(float (&d)[64], uint32_t a0, uint32_t a1, uint32_t a2, uint32_t a3, uint32_t blo){
  asm volatile("{\n.reg .b64 db;\nmov.b64 db, {%28,8};\nwgmma.mma_async.sync.aligned.m64n48k16.f32.bf16.bf16 {%0, %1, %2, %3, %4, %5, %6, %7, %8, %9, %10, %11, %12, %13, %14, %15, %16, %17, %18, %19, %20, %21, %22, %23}, {%24,%25,%26,%27}, db, 1, 1, 1, 0;\n}\n"
    : "+f"(d[40]), "+f"(d[41]), "+f"(d[42]), "+f"(d[43]), "+f"(d[44]), "+f"(d[45]), "+f"(d[46]), "+f"(d[47]), "+f"(d[48]), "+f"(d[49]), "+f"(d[50]), "+f"(d[51]), "+f"(d[52]), "+f"(d[53]), "+f"(d[54]), "+f"(d[55]), "+f"(d[56]), "+f"(d[57]), "+f"(d[58]), "+f"(d[59]), "+f"(d[60]), "+f"(d[61]), "+f"(d[62]), "+f"(d[63])
    : "r"(a0), "r"(a1), "r"(a2), "r"(a3), "r"(blo));
}
template<> __device__ __forceinline__ void wgmma_rs_hi<64>(float (&d)[64], uint32_t a0, uint32_t a1, uint32_t a2, uint32_t a3, uint32_t blo){
  asm volatile("{\n.reg .b64 db;\nmov.b64 db, {%36,8};\nwgmma.mma_async.sync.aligned.m64n64k16.f32.bf16.bf16 {%0, %1, %2, %3, %4, %5, %6, %7, %8, %9, %10, %11, %12, %13, %14, %15, %16, %17, %18, %19, %20, %21, %22, %23, %24, %25, %26, %27, %28, %29, %30, %31}, {%32,%33,%34,%35}, db, 1, 1, 1, 0;\n}\n"
    : "+f"(d[32]), "+f"(d[33]), "+f"(d[34]), "+f"(d[35]), "+f"(d[36]), "+f"(d[37]), "+f"(d[38]), "+f"(d[39]), "+f"(d[40]), "+f"(d[41]), "+f"(d[42]), "+f"(d[43]), "+f"(d[44]), "+f"(d[45]), "+f"(d[46]), "+f"(d[47]), "+f"(d[48]), "+f"(d[49]), "+f"(d[50]), "+f"(d[51]), "+f"(d[52]), "+f"(d[53]), "+f"(d[54]), "+f"(d[55]), "+f"(d[56]), "+f"(d[57]), "+f"(d[58]), "+f"(d[59]), "+f"(d[60]), "+f"(d[61]), "+f"(d[62]), "+f"(d[63])
    : "r"(a0), "r"(a1), "r"(a2), "r"(a3), "r"(blo));
}
template<> __device__ __forceinline__ void wgmma_rs_hi<80>(float (&d)[64], uint32_t a0, uint32_t a1, uint32_t a2, uint32_t a3, uint32_t blo){
  asm volatile("{\n.reg .b64 db;\nmov.b64 db, {%44,8};\nwgmma.mma_async.sync.aligned.m64n80k16.f32.bf16.bf16 {%0, %1, %2, %3, %4, %5, %6, %7, %8, %9, %10, %11, %12, %13, %14, %15, %16, %17, %18, %19, %20, %21, %22, %23, %24, %25, %26, %27, %28, %29, %30, %31, %32, %33, %34, %35, %36, %37, %38, %39}, {%40,%41,%42,%43}, db, 1, 1, 1, 0;\n}\n"
    : "+f"(d[24]), "+f"(d[25]), "+f"(d[26]), "+f"(d[27]), "+f"(d[28]), "+f"(d[29]), "+f"(d[30]), "+f"(d[31]), "+f"(d[32]), "+f"(d[33]), "+f"(d[34]), "+f"(d[35]), "+f"(d[36]), "+f"(d[37]), "+f"(d[38]), "+f"(d[39]), "+f"(d[40]), "+f"(d[41]), "+f"(d[42]), "+f"(d[43]), "+f"(d[44]), "+f"(d[45]), "+f"(d[46]), "+f"(d[47]), "+f"(d[48]), "+f"(d[49]), "+f"(d[50]), "+f"(d[51]), "+f"(d[52]), "+f"(d[53]), "+f"(d[54]), "+f"(d[55]), "+f"(d[56]), "+f"(d[57]), "+f"(d[58]), "+f"(d[59]), "+f"(d[60]), "+f"(d[61]), "+f"(d[62]), "+f"(d[63])
    : "r"(a0), "r"(a1), "r"(a2), "r"(a3), "r"(blo));
}
template<> __device__ __forceinline__ void wgmma_rs_hi<96>(float (&d)[64], uint32_t a0, uint32_t a1, uint32_t a2, uint32_t a3, uint32_t blo){
  asm volatile("{\n.reg .b64 db;\nmov.b64 db, {%52,8};\nwgmma.mma_async.sync.aligned.m64n96k16.f32.bf16.bf16 {%0, %1, %2, %3, %4, %5, %6, %7, %8, %9, %10, %11, %12, %13, %14, %15, %16, %17, %18, %19, %20, %21, %22, %23, %24, %25, %26, %27, %28, %29, %30, %31, %32, %33, %34, %35, %36, %37, %38, %39, %40, %41, %42, %43, %44, %45, %46, %47}, {%48,%49,%50,%51}, db, 1, 1, 1, 0;\n}\n"
    : "+f"(d[16]), "+f"(d[17]), "+f"(d[18]), "+f"(d[19]), "+f"(d[20]), "+f"(d[21]), "+f"(d[22]), "+f"(d[23]), "+f"(d[24]), "+f"(d[25]), "+f"(d[26]), "+f"(d[27]), "+f"(d[28]), "+f"(d[29]), "+f"(d[30]), "+f"(d[31]), "+f"(d[32]), "+f"(d[33]), "+f"(d[34]), "+f"(d[35]), "+f"(d[36]), "+f"(d[37]), "+f"(d[38]), "+f"(d[39]), "+f"(d[40]), "+f"(d[41]), "+f"(d[42]), "+f"(d[43]), "+f"(d[44]), "+f"(d[45]), "+f"(d[46]), "+f"(d[47]), "+f"(d[48]), "+f"(d[49]), "+f"(d[50]), "+f"(d[51]), "+f"(d[52]), "+f"(d[53]), "+f"(d[54]), "+f"(d[55]), "+f"(d[56]), "+f"(d[57]), "+f"(d[58]), "+f"(d[59]), "+f"(d[60]), "+f"(d[61]), "+f"(d[62]), "+f"(d[63])
    : "r"(a0), "r"(a1), "r"(a2), "r"(a3), "r"(blo));
}
template<> __device__ __forceinline__ void wgmma_rs_hi<112>(float (&d)[64], uint32_t a0, uint32_t a1, uint32_t a2, uint32_t a3, uint32_t blo){
  asm volatile("{\n.reg .b64 db;\nmov.b64 db, {%60,8};\nwgmma.mma_async.sync.aligned.m64n112k16.f32.bf16.bf16 {%0, %1, %2, %3, %4, %5, %6, %7, %8, %9, %10, %11, %12, %13, %14, %15, %16, %17, %18, %19, %20, %21, %22, %23, %24, %25, %26, %27, %28, %29, %30, %31, %32, %33, %34, %35, %36, %37, %38, %39, %40, %41, %42, %43, %44, %45, %46, %47, %48, %49, %50, %51, %52, %53, %54, %55}, {%56,%57,%58,%59}, db, 1, 1, 1, 0;\n}\n"
    : "+f"(d[8]), "+f"(d[9]), "+f"(d[10]), "+f"(d[11]), "+f"(d[12]), "+f"(d[13]), "+f"(d[14]), "+f"(d[15]), "+f"(d[16]), "+f"(d[17]), "+f"(d[18]), "+f"(d[19]), "+f"(d[20]), "+f"(d[21]), "+f"(d[22]), "+f"(d[23]), "+f"(d[24]), "+f"(d[25]), "+f"(d[26]), "+f"(d[27]), "+f"(d[28]), "+f"(d[29]), "+f"(d[30]), "+f"(d[31]), "+f"(d[32]), "+f"(d[33]), "+f"(d[34]), "+f"(d[35]), "+f"(d[36]), "+f"(d[37]), "+f"(d[38]), "+f"(d[39]), "+f"(d[40]), "+f"(d[41]), "+f"(d[42]), "+f"(d[43]), "+f"(d[44]), "+f"(d[45]), "+f"(d[46]), "+f"(d[47]), "+f"(d[48]), "+f"(d[49]), "+f"(d[50]), "+f"(d[51]), "+f"(d[52]), "+f"(d[53]), "+f"(d[54]), "+f"(d[55]), "+f"(d[56]), "+f"(d[57]), "+f"(d[58]), "+f"(d[59]), "+f"(d[60]), "+f"(d[61]), "+f"(d[62]), "+f"(d[63])
    : "r"(a0), "r"(a1), "r"(a2), "r"(a3), "r"(blo));
}
template<> __device__ __forceinline__ void wgmma_rs_hi<128>(float (&d)[64], uint32_t a0, uint32_t a1, uint32_t a2, uint32_t a3, uint32_t blo){
  asm volatile("{\n.reg .b64 db;\nmov.b64 db, {%68,8};\nwgmma.mma_async.sync.aligned.m64n128k16.f32.bf16.bf16 {%0, %1, %2, %3, %4, %5, %6, %7, %8, %9, %10, %11, %12, %13, %14, %15, %16, %17, %18, %19, %20, %21, %22, %23, %24, %25, %26, %27, %28, %29, %30, %31, %32, %33, %34, %35, %36, %37, %38, %39, %40, %41, %42, %43, %44, %45, %46, %47, %48, %49, %50, %51, %52, %53, %54, %55, %56, %57, %58, %59, %60, %61, %62, %63}, {%64,%65,%66,%67}, db, 1, 1, 1, 0;\n}\n"
    : "+f"(d[0]), "+f"(d[1]), "+f"(d[2]), "+f"(d[3]), "+f"(d[4]), "+f"(d[5]), "+f"(d[6]), "+f"(d[7]), "+f"(d[8]), "+f"(d[9]), "+f"(d[10]), "+f"(d[11]), "+f"(d[12]), "+f"(d[13]), "+f"(d[14]), "+f"(d[15]), "+f"(d[16]), "+f"(d[17]), "+f"(d[18]), "+f"(d[19]), "+f"(d[20]), "+f"(d[21]), "+f"(d[22]), "+f"(d[23]), "+f"(d[24]), "+f"(d[25]), "+f"(d[26]), "+f"(d[27]), "+f"(d[28]), "+f"(d[29]), "+f"(d[30]), "+f"(d[31]), "+f"(d[32]), "+f"(d[33]), "+f"(d[34]), "+f"(d[35]), "+f"(d[36]), "+f"(d[37]), "+f"(d[38]), "+f"(d[39]), "+f"(d[40]), "+f"(d[41]), "+f"(d[42]), "+f"(d[43]), "+f"(d[44]), "+f"(d[45]), "+f"(d[46]), "+f"(d[47]), "+f"(d[48]), "+f"(d[49]), "+f"(d[50]), "+f"(d[51]), "+f"(d[52]), "+f"(d[53]), "+f"(d[54]), "+f"(d[55]), "+f"(d[56]), "+f"(d[57]), "+f"(d[58]), "+f"(d[59]), "+f"(d[60]), "+f"(d[61]), "+f"(d[62]), "+f"(d[63])
    : "r"(a0), "r"(a1), "r"(a2), "r"(a3), "r"(blo));
}

struct CvCtx {
  uint32_t kaddr, kvaddr, db0, dd, stg, zero;
  int src1, src2;
  bool s3, kodd, wrap;
};
template <int LO> __device__ __forceinline__ void cv_copy(float (&acc)[64]) {
#pragma unroll
  for (int i = LO; i < 64; i++) { float t; asm volatile("mov.b32 %0, %1;" : "=f"(t) : "f"(acc[i]) : "memory"); acc[i] = t; }
}
template <int G> __device__ __forceinline__ void cv_raw(uint32_t (&A)[4][4], uint32_t kaddr) {
#pragma unroll
  for (int i = 0; i < 4; i++) {
    const uint32_t a = kaddr + (4 * G + i) * 128;
    A[i][0] = lds32(a); A[i][1] = lds32(a + 4); A[i][3] = lds32(a + 8);
  }
}
__device__ __forceinline__ void cv_form(uint32_t (&A)[4][4]) {
#pragma unroll
  for (int i = 0; i < 4; i++) {
    asm volatile("prmt.b32 %0, %0, %1, 0x5432;" : "+r"(A[i][0]) : "r"(A[i][1]));
    asm volatile("prmt.b32 %0, %1, %2, 0x5432;" : "=r"(A[i][2]) : "r"(A[i][1]), "r"(A[i][3]));
  }
}
template <int J> __device__ __forceinline__ void cv_epi(const float (&acc)[64], float (&Ep)[2], const uint32_t (&so)[4], const CvCtx& c) {
  float E[4], o[2];
  const uint32_t kvw = lds32(c.kvaddr + J * 256);
  const int src1 = c.src1 | (kvw & c.zero);
#pragma unroll
  for (int x = 0; x < 4; x++) {
    const float ev = acc[8 * J + x], od = acc[8 * J + 4 + x], pv = J > 0 ? acc[J > 0 ? 8 * J - 4 + x : 0] : 0.f;
    const float send = c.kodd ? ev : (c.s3 ? pv : od);
    E[x] = (c.kodd ? od : ev) + __shfl_sync(0xffffffffu, send, src1);
  }
#pragma unroll
  for (int h = 0; h < 2; h++) {
    o[h] = E[2 * h] + __shfl_sync(0xffffffffu, c.wrap ? Ep[h] : E[2 * h + 1], c.src2);
    Ep[h] = E[2 * h + 1];
  }
  sts32(c.stg + ((J & 1) ? so[J >> 1] >> 16 : so[J >> 1] & 0xffff), hadd2(pack_bf16(o[0], o[1]), hmul2(__byte_perm(kvw, kvw, 0x1032), c.dd)));
}
template <int G> __device__ __forceinline__ void cv_rec(float (&acc)[64], uint32_t (&A)[4][4], float (&Ep)[2], const uint32_t (&so)[4], const CvCtx& c) {
  wgmma_fence();
#pragma unroll
  for (int i = 0; i < 4; i++) wgmma_rs_hi<128 - 16 * G>(acc, A[i][0], A[i][1], A[i][2], A[i][3], c.db0 - 4 * i);
  wgmma_commit();
  __syncwarp();
  uint32_t B[4][4];
  if constexpr (G < 7) cv_raw<G + 1>(B, c.kaddr);
  if constexpr (G > 0) cv_epi<G - 1>(acc, Ep, so, c);
  if constexpr (G < 7) cv_form(B);
  __syncwarp();
  wgmma_wait<0>();
  cv_copy<8 * G>(acc);
  if constexpr (G < 7) cv_rec<G + 1>(acc, B, Ep, so, c);
}
__device__ __forceinline__ uint32_t cv_stage(int slot) { return sb + (slot < 4 ? 40960 + slot * 4096 : 180224); }
__device__ __forceinline__ void cv_offsets(uint32_t (&so)[4]) {
  const int tid = tid_opaque() & 127, lane = tid & 31, r = lane >> 2, q = lane & 3;
  const int P = r < 4 ? q : 4 + ((q + 1) & 3);
  const int tb = 16 * (2 * P + ((r >> 1) & 1)) + 4 * (tid >> 5) + 2 * (r & 1);
#pragma unroll
  for (int J = 0; J < 8; J++) {
    const int t = 256 * J + tb, T = t / 160, tl = t - T * 160;
    const int qq = (T == NT1 - 1) ? (tl >> 5) : (tl / 40);
    int ck = 20 * T + ((tl - qq * ((T == NT1 - 1) ? 32 : 40)) >> 1);
    ck ^= (ck >> 3) & 7;
    const uint32_t o = ck * 16 + qq * 4;
    if (J & 1) so[J >> 1] |= o << 16; else so[J >> 1] = o;
  }
}
__device__ __forceinline__ void conv_channel(int slot, const uint32_t (&so)[4]) {
  const int tid = tid_opaque() & 127, w = tid >> 5, lane = tid & 31, r = lane >> 2, q = lane & 3;
  const int i_ = r >> 1, i0 = i_ & 1, i1 = i_ >> 1;
  const uint32_t cb = sb + CV_OFF + slot * CV_B;
  CvCtx c;
  c.dd = lds32(sb + EP_OFF + 4 * slot);
  c.kaddr = cb + CV_K - 32 + 4 * (8 * i_ + 2 * w + (r & 1) + 2 * q);
  c.db0 = desc_lo(cb + CV_U + 192, CV_PL);
  c.src1 = i1 == 0 ? (lane - q + 16 + ((q + 3) & 3)) : (lane - q - 16 + ((q + 1) & 3));
  c.s3 = (i1 == 1 && q == 3); c.kodd = (i1 == 1 && q < 3);
  const int P = i1 == 0 ? q : 4 + ((q + 1) & 3);
  const int Pm = (P + 7) & 7, qm = Pm < 4 ? Pm : ((Pm - 1) & 3);
  c.src2 = i0 == 1 ? lane - 8 : (16 * (Pm >> 2) + 8 + 4 * (r & 1) + qm);
  c.wrap = (i0 == 1 && P == 7);
  c.kvaddr = cb + CV_U + 192 + (1 - (r & 1)) * CV_PL + (2 * P + i0) * 16 + (3 - w) * 4;
  float acc[64], Ep[2] = {0.f, 0.f};
  uint32_t A[4][4];
  c.stg = cv_stage(slot);
#pragma unroll
  for (int i = 0; i < 64; i++) acc[i] = 0.f;
  mbar_wait(bars + 8 * (B_TAPS + slot));
  c.zero = lds32(cb);
  cv_raw<0>(A, c.kaddr);
  mbar_wait(bars + 8 * (B_CVFULL + slot));
  cv_form(A);
  cv_copy<0>(acc);
  cv_rec<0>(acc, A, Ep, so, c);
  cv_epi<7>(acc, Ep, so, c);
  fence_async_smem();
  mbar_arrive(bars + 8 * (B_CVDONE + slot));
}

template <int W> struct KvRegs { uint32_t k[19][W], v[16][W], s[W][4]; };
template <int W> __device__ __forceinline__ void kv_load(int m, int cl, KvRegs<W>& x) {
  const int lane = tid_opaque() & 31, tg = lane >> 3;
  const uint32_t pb = sb + KS_OFF + (cl >> 5) * KV_PIECE + 2 * (cl & 31) + 4 * W * (lane & 7);
  const uint32_t ka = pb + tg * 1216, va = pb + 4864 + tg * 1088 + 64;
  const uint32_t kh = (m == 0 && tg > 0) ? ka - 192 : ka;
#pragma unroll
  for (int c = 0; c < W; c++) {
    const float4 t = lds128f(sb + TAP_OFF + 8 * cl + 16 * (W * (lane & 7) + c));
    x.s[c][0] = __float_as_uint(t.x); x.s[c][1] = __float_as_uint(t.y); x.s[c][2] = __float_as_uint(t.z); x.s[c][3] = __float_as_uint(t.w);
  }
  mbar_wait(bars + 8 * (B_KV + (cl >> 5)));
#pragma unroll
  for (int i = 0; i < 19; i++) {
    const uint32_t a = (i < 3 ? kh : ka) + i * 64;
    if (W == 2) { float2 t = lds64f(a); x.k[i][0] = __float_as_uint(t.x); x.k[i][W - 1] = __float_as_uint(t.y); }
    else x.k[i][0] = lds32(a);
  }
#pragma unroll
  for (int i = 0; i < 16; i++) {
    if (W == 2) { float2 t = lds64f(va + i * 64); x.v[i][0] = __float_as_uint(t.x); x.v[i][W - 1] = __float_as_uint(t.y); }
    else x.v[i][0] = lds32(va + i * 64);
  }
}
template <int W> __device__ __forceinline__ void kv_finish(int m, int c0, KvRegs<W>& x) {
  const int lane = tid_opaque() & 31;
  uint8_t* dst = g_kv + ((c0 + 2 * W * (lane & 7)) * 4096 + (4 * m + (lane >> 3)) * 16);
#pragma unroll
  for (int c = 0; c < W; c++) {
    const uint32_t w0 = __byte_perm(x.s[c][0], x.s[c][2], 0x5410), w1 = __byte_perm(x.s[c][0], x.s[c][2], 0x7632);
    const uint32_t w2 = __byte_perm(x.s[c][1], x.s[c][3], 0x5410), w3 = __byte_perm(x.s[c][1], x.s[c][3], 0x7632);
#pragma unroll
    for (int i = 0; i < 16; i++) {
      uint32_t a = hmul2(x.k[i][c], w3);
      a = hadd2(a, hmul2(x.k[i + 1][c], w2)); a = hadd2(a, hmul2(x.k[i + 2][c], w1)); a = hadd2(a, hmul2(x.k[i + 3][c], w0));
      x.v[i][c] = hmul2(a, x.v[i][c]);
    }
#pragma unroll
    for (int e = 0; e < 2; e++)
#pragma unroll
      for (int f = 0; f < 2; f++) {
        uint32_t o[4];
#pragma unroll
        for (int qq = 0; qq < 4; qq++) o[qq] = __byte_perm(x.v[15 - 4 * qq - 2 * f][c], x.v[14 - 4 * qq - 2 * f][c], e ? 0x7632 : 0x5410);
        *(uint4*)(dst + (2 * c + e) * 4096 + f * 2048) = make_uint4(o[0], o[1], o[2], o[3]);
      }
  }
}
__device__ __forceinline__ void ln_finish(float s1, float s2, float& mean, float& rstd) {
  mean = s1 * (1.f / 640.f);
  const float v = fmaxf(fmaf(-mean, mean, s2 * (1.f / 640.f)), 0.f) + 1e-5f;
  asm("rsqrt.approx.ftz.f32 %0, %1;" : "=f"(rstd) : "f"(v));
}
__device__ __forceinline__ void stat_table(int T1, unsigned want, int l) {
#pragma unroll 1
  for (int n = tid_opaque() & 127; n < (T1 == NT1 - 1 ? 128 : 160); n += 128) {
    const uint4* rp = &g_stats[8 * l * SEQ + 160 * T1 + n];
    float a[4], b[4];
    uint32_t it = 0;
    while (true) {
      bool ok = true;
#pragma unroll
      for (int i = 0; i < 4; i++) ok &= (rec_ld(rp + SEQ * i, a[i], b[i]) == want);
      if (ok) break;
      if (++it > SPIN_LIMIT) soft_trap();
    }
    float m, rs;
    ln_finish((a[0] + a[1]) + (a[2] + a[3]), (b[0] + b[1]) + (b[2] + b[3]), m, rs);
    sts64f(sb + STAB_OFF + n * 8, rs, -m * rs);
  }
  mbar_arrive(bars + 8 * (B_STAB + l));
  __syncwarp();
}

template <bool FIRST>
__device__ __forceinline__ void stats_publish(int which, int n0, int dg, unsigned tag, const float (&acc)[80]) {
  const int q = tid_opaque() & 3, h = q & 1;
  float s1[2] = {0.f, 0.f}, s2[2] = {0.f, 0.f}, t1[2] = {0.f, 0.f}, t2[2] = {0.f, 0.f};
#pragma unroll
  for (int j = 0; j < 20; j++)
#pragma unroll
    for (int y = 0; y < 2; y++) {
      const float a = acc[4 * j + 2 * y], b = acc[4 * j + 2 * y + 1];
      s1[y] += a; t1[y] += b; s2[y] = fmaf(a, a, s2[y]); t2[y] = fmaf(b, b, t2[y]);
    }
#pragma unroll
  for (int y = 0; y < 2; y++) { s1[y] += t1[y]; s2[y] += t2[y]; }
  float a = (h ? s1[1] : s1[0]) + __shfl_xor_sync(0xffffffffu, h ? s1[0] : s1[1], 1);
  float b = (h ? s2[1] : s2[0]) + __shfl_xor_sync(0xffffffffu, h ? s2[0] : s2[1], 1);
  a += __shfl_xor_sync(0xffffffffu, a, 2);
  b += __shfl_xor_sync(0xffffffffu, b, 2);
  if (FIRST) {
    rec_st(&g_stats[((q >> 1) * 4 + dg) * SEQ + n0 + 8 * h], a, b, q < 2 ? tag : tag - 1);
    rec_st(&g_stats[((q >> 1) * 4 + 8 + dg) * SEQ + n0 + 8 * h], a, b, tag - 1);
  } else if (q < 2) rec_st(&g_stats[(which * 4 + dg) * SEQ + n0 + 8 * h], a, b, tag);
}
__device__ __forceinline__ void stats_get(int which, int n0, unsigned tag, float (&mean)[2], float (&rstd)[2]) {
  const uint4* p0 = &g_stats[(which * 4 + (tid_opaque() & 3)) * SEQ + n0];
  float a[2], b[2];
  uint32_t it = 0;
  while (true) {
    const unsigned t0 = rec_ld(p0, a[0], b[0]), t1 = rec_ld(p0 + 8, a[1], b[1]);
    if (t0 == tag && t1 == tag) break;
    if (++it > SPIN_LIMIT) soft_trap();
  }
  __syncwarp();
#pragma unroll
  for (int o = 1; o < 4; o <<= 1)
#pragma unroll
    for (int h = 0; h < 2; h++) { a[h] += __shfl_xor_sync(0xffffffffu, a[h], o); b[h] += __shfl_xor_sync(0xffffffffu, b[h], o); }
#pragma unroll
  for (int h = 0; h < 2; h++) ln_finish(a[h], b[h], mean[h], rstd[h]);
}
__device__ __forceinline__ void x0_load(float (&acc)[80]) {
  const int t = tid_opaque() & 127;
  const uint32_t xa = sb + XT_OFF + (16 * (t >> 5) + ((t & 31) >> 2)) * 320 + 8 * (t & 3);
  mbar_wait(bars + 8 * B_XT);
#pragma unroll
  for (int h = 0; h < 2; h++)
#pragma unroll
    for (int J = 0; J < 10; J++) {
      const float2 v = lds64f(xa + h * 2560 + 32 * J);
      const uint32_t x = __float_as_uint(v.x), y = __float_as_uint(v.y);
      acc[8 * J + 2 * h] = bf_lo(x); acc[8 * J + 2 * h + 1] = bf_hi(x);
      acc[8 * J + 4 + 2 * h] = bf_lo(y); acc[8 * J + 4 + 2 * h + 1] = bf_hi(y);
    }
}

__global__ void __launch_bounds__(512, 1) fused_kernel(const __grid_constant__ Params p) {
  extern __shared__ __align__(1024) uint8_t smem_raw[];
  const int tid = threadIdx.x, lane = tid & 31;
  const int wid = __shfl_sync(0xffffffffu, tid >> 5, 0), wg = wid >> 2;
  unsigned smid; asm volatile("mov.u32 %0, %%smid;" : "=r"(smid));
  if (smid >= 132 || smem_u32(smem_raw) != sb) soft_trap();
  int role;
  {
  const int side = smid & 1;
  int gpc, gi;
  {
    int tpc = smid >> 1;
    if (tpc < 32) { gpc = tpc & 7; gi = tpc >> 3; }
    else if (tpc < 60) { gpc = 1 + (tpc - 32) % 7; gi = 4 + (tpc - 32) / 7; }
    else if (tpc < 62) { gpc = tpc - 54; gi = 8; }
    else { gpc = 0; gi = tpc - 58; }
  }
  const int pos = 8 * gpc + gi + (gpc == 7 ? 1 : 0);
  if (pos == 65) {
    if (tid < 32) {
      const unsigned tag = ld_rlx(g_epoch);
      for (int i = lane; i < NT1 * 16; i += 32)
        if ((i & 15) < 10) { uint32_t it = 0; while ((int)(ld_rlx(&g_hflag[((i >> 4) * 32 + (i & 15)) * 8]) - tag) < 0) { __nanosleep(500); if (++it > SPIN_LIMIT) soft_trap(); } }
    }
    return;
  }
  int T1, GP;
  if (pos < 52) { int hh = pos / 26, x = pos - 26 * hh; T1 = x >> 1; GP = 2 * hh + (x & 1); }
  else { T1 = pos - 52; GP = 4; }
  const bool last = (T1 == NT1 - 1);
  const bool has2 = gi < 8;
  const int m2 = 8 * (gpc >> 1) + gi, dg = 2 * (gpc & 1) + side;
  role = T1 | (GP << 4) | (side << 7) | (m2 << 8) | (dg << 14) | ((int)has2 << 16);

  const int cch0 = 5 * (32 * dg + m2);
  if (wg < 2) {
    if (wid < 2) {
      const int ch = 128 * GP + 64 * wid + 32 * side + lane;
      uint32_t r0 = ldv16(p.lre + ch), r1 = ldv16(p.lim + ch), r2 = ldv16(p.logdt + ch);
      asm volatile("bar.arrive 5, 512;" : "+r"(r0), "+r"(r1), "+r"(r2)::"memory");
      const float lr = bf_lo(r0), li = bf_lo(r1), ld = bf_lo(r2);
      const float dt = __bfloat162float(__float2bfloat16_rn(expf(ld)));
      const float mag = expf(dt * lr);
      float sn, cs; sincosf(dt * li, &sn, &cs);
      const float ar = mag * cs, ai = mag * sn;
      const float inv = 2.f / (lr * lr + li * li);
      const uint32_t ad = sb + CTAB_OFF + (32 * wid + lane) * 24;
      sts64f(ad, ar, ai);
      sts64f(ad + 8, ((ar - 1.f) * lr + ai * li) * inv, (ai * lr - (ar - 1.f) * li) * inv);
      if (tid == 0) TS(46);
      __syncwarp();
      bar_sync(7, 96);
      mbar_arrive(bars + 8 * B_CTAB);
    } else {
      if (elect_one()) {
        if (wid < 5) {
#pragma unroll
          for (int i = 0; i < 27; i++) mbar_init(bars + 8 * (4 + 27 * (wid - 2) + i), 2);
        } else {
#pragma unroll
          for (int i = 0; i < 15; i++) mbar_init(bars + 8 * (85 + 15 * (wid - 5) + i), 1);
        }
        asm volatile("fence.mbarrier_init.release.cluster;" ::: "memory");
      }
      __syncwarp();
      bar_sync(5, 512);
      if (wid == 2) { asm volatile("bar.arrive 6, 64;" ::: "memory"); asm volatile("bar.arrive 7, 96;" ::: "memory"); }
    }
  } else if (wg == 2 || wid == 14) {
    uint2 bv[2][5];
    const int c = wid == 14 ? 4 : wid - 8;
    const unsigned tag0 = ld_rlx(g_epoch);
#pragma unroll
    for (int x = 0; x < 2; x++)
#pragma unroll
      for (int i = 0; i < 5; i++) bv[x][i] = ldv64((const uint2*)((x ? p.bim : p.bre) + (has2 ? cch0 + c : 0) * DM) + lane + 32 * i);
    bar_sync(5, 512);
#pragma unroll
    for (int i = 0; i < 5; i++) asm volatile("" : "+r"(bv[0][i].x), "+r"(bv[0][i].y), "+r"(bv[1][i].x), "+r"(bv[1][i].y)::"memory");
    if (has2) {
      float sv[2];
#pragma unroll
      for (int x = 0; x < 2; x++) {
        float a = 0.f;
#pragma unroll
        for (int i = 0; i < 5; i++) a += (bf_lo(bv[x][i].x) + bf_hi(bv[x][i].x)) + (bf_lo(bv[x][i].y) + bf_hi(bv[x][i].y));
        sv[x] = a;
      }
#pragma unroll
      for (int o = 16; o > 0; o >>= 1) { sv[0] += __shfl_xor_sync(0xffffffffu, sv[0], o); sv[1] += __shfl_xor_sync(0xffffffffu, sv[1], o); }
      if (lane < 2) rec_st(&g_sB[(cch0 + c) * 2 + lane], sv[0], sv[1], tag0);
      if (tid == 256) TS(47);
    }
  } else if (wid == 13) {
    uint4 tv[3];
    const uint32_t e0 = ld_rlx(g_epoch);
    uint32_t e1 = ldv16(p.ssmD + min(cch0 + lane, 639));
    const uint4 dv = ldv128((const uint4*)(p.dskip + 160 * dg) + min(lane, 19));
#pragma unroll
    for (int i = 0; i < 3; i++) tv[i] = ldv128((const uint4*)(p.shiftk + 640 * dg) + min(lane + 32 * i, 79));
    bar_sync(5, 512);
    asm volatile("" : "+r"(e1)::"memory");
    sts128(sb + DTAB_OFF + 16 * min(lane, 19), dv);
#pragma unroll
    for (int i = 0; i < 3; i++) sts128(sb + TAP_OFF + 16 * min(lane + 32 * i, 79), tv[i]);
    if (lane < 6) sts32(sb + EP_OFF + 4 * lane, lane < 5 ? e1 | (e1 << 16) : e0);
    mbar_arrive(bars + 8 * B_CTAB);
    __syncwarp();
    if (lane == 0) { mbar_arrive(bars + 8 * B_EP); TS(53); }
  } else if (wid == 12) {
    if (elect_one()) {
#pragma unroll
      for (int k = 0; k < S1; k++) mbar_init(bars + 8 * (B_G1FULL + k), 1);
#pragma unroll
      for (int k = 0; k < 19; k++) mbar_init(bars + 8 * (B_XT + k), 1);
      asm volatile("fence.mbarrier_init.release.cluster;" ::: "memory");
      TS(45);
    }
    __syncwarp();
    asm volatile("bar.arrive 5, 512;" ::: "memory");
    if (elect_one()) {
#pragma unroll 1
      for (int k = 0; k < S1; k++) {
        const uint32_t fb = bars + 8 * (B_G1FULL + k);
        mbar_expect_tx(fb, G1_STAGE);
        tma4(sb + k * G1_STAGE + G1_XOFF, last ? &p.mXl : &p.mX, 64 * k, 0, 0, last ? 0 : 80 * T1, fb);
        tma5(sb + k * G1_STAGE, &p.mB, 64 * k, 0, 0, 4 * side, 2 * GP, fb);
      }
      TS(44);
    }
    __syncwarp();
    bar_sync(6, 64);
  } else {
    if (elect_one()) {
#pragma unroll
      for (int i = 0; i < 13; i++) mbar_init(bars + 8 * (B_CVDONE + i), B_CVDONE + i == B_STAB ? 160 : (B_CVDONE + i == B_CTAB ? 96 : 128));
      asm volatile("fence.mbarrier_init.release.cluster;" ::: "memory");
    }
    __syncwarp();
    bar_sync(5, 512);
  }
  if (tid == 128) TS(0);
  }

  if (wg == 3) {
    asm volatile("setmaxnreg.dec.sync.aligned.u32 56;");
    ROLE(role)
    const int pw = wid & 3;
    if (pw == 3 && has2) {
      mbar_wait(bars + 8 * (B_G1FULL + 0));
      if (elect_one()) {
        mbar_expect_tx(bars + 8 * B_XT, 20480);
#pragma unroll
        for (int h = 0; h < 2; h++) {
          const int ng = 8 * m2 + 4 * h, T = ng / 20;
          tma4(sb + XT_OFF + h * 10240, T == NT1 - 1 ? &p.mXtl : &p.mXt, 160 * dg, 0, 0, T == NT1 - 1 ? ng - 240 : ng + 60 * T, bars + 8 * B_XT);
        }
      }
#pragma unroll 1
      for (int c = 0; c < 5; c++) {
        mbar_wait(bars + 8 * (c == 0 ? B_G1FULL + 2 : B_XT + (c < 2 ? 0 : c - 1)));
        if (elect_one()) {
          const uint32_t fb = bars + 8 * (B_KV + c);
          mbar_expect_tx(fb, KV_PIECE);
          tma3(sb + KS_OFF + c * KV_PIECE, &p.mK, 160 * dg + 32 * c, 64 * m2 - 3, 0, fb);
          tma3(sb + KS_OFF + c * KV_PIECE + 4864, &p.mV, 160 * dg + 32 * c, 64 * m2 - 1, 0, fb);
        }
      }
    }
    unsigned tag = 0;
    if (pw > 0) { mbar_wait(bars + 8 * B_EP); tag = lds32(sb + EP_OFF + 20); }
    if (pw == 2) {
#pragma unroll 1
      for (int i = 0; i < 2; i++) {
        float a, b;
        rec_poll(&g_sB[(128 * GP + 64 * i + 32 * side + lane) * 2], tag, a, b);
        sts64f(sb + CTAB_OFF + (32 * i + lane) * 24 + 16, p.swap ? b : a, p.swap ? a : b);
      }
      mbar_arrive(bars + 8 * B_STAB);
      if (lane == 0) TS(54);
    }
    if (pw >= 2 && has2) {
      KvRegs<1> x;
      kv_load<1>(m2, 128 + 16 * (pw - 2), x);
      kv_finish<1>(m2, 160 * dg + 128 + 16 * (pw - 2), x);
      if (tid == 448) TS(51);
      bar_sync(3, 192);
      if (tid == 448) { mbar_arrive(bars + 8 * B_PREP); st_rel(&g_kvflag[(dg * 32 + m2) * 8], tag); TS(30); }
      __syncwarp();
    }
    if (pw == 0) {
      if (elect_one()) {
#pragma unroll 1
        for (int l = 0; l < 2; l++) {
          const uint32_t fb0 = bars + 8 * (B_G1FULL + 10 * l), wb = bars + 8 * (B_G1DONE + 9 * l - S1);
          const uint32_t free0 = bars + 8 * (has2 ? B_G2DONE + 19 : B_G1DONE + 9);
          uint32_t dst = sb;
#pragma unroll 1
          for (int k = l == 0 ? S1 : 0; k < 10; k++) {
            mbar_wait(k >= S1 + l ? wb + 8 * k : (k < WPF1 || !has2 ? free0 : bars + 8 * (B_GO + 1)));
            mbar_expect_tx(fb0 + 8 * k, 16384);
            tma5(dst, &p.mB, 64 * k, 0, 0, 4 * side, 2 * GP, fb0 + 8 * k);
            dst += G1_STAGE; if (dst == sb + (S1 + l) * G1_STAGE) dst = sb;
          }
          if (has2) {
            const uint32_t fb2 = bars + 8 * (B_G2FULL + 20 * l), wb2 = bars + 8 * (B_G2DONE + 19 * l - 6);
            dst = sb + G2_WOFF;
            int kc = 0;
#pragma unroll 1
            for (int k = 0; k < 20; k++) {
              mbar_wait(k >= 6 + l ? wb2 + 8 * k : (k == 5 ? bars + 8 * B_XFREE : (k < WPF2 ? bars + 8 * (B_G1DONE + 10 * l + 9) : bars + 8 * (B_GO + 2 * l))));
              mbar_expect_tx(fb2 + 8 * k, G2_WB);
              tma5(dst, &p.mCre + (k & 1), kc, 0, 0, 0, 10 * dg, fb2 + 8 * k);
              kc += (k & 1) << 7; if (k == 9) kc = 64;
              dst += G2_WB; if (dst == sb + G2_WOFF + (6 + l) * G2_WB) dst = sb + G2_WOFF;
            }
          }
        }
      }
    } else if (pw == 1) {
#pragma unroll 1
      for (int l = 0; l < 2; l++) {
        if (l == 0) {
          if (elect_one()) {
            uint32_t dst = sb + G1_XOFF;
#pragma unroll 1
            for (int k = S1; k < 10; k++) {
              mbar_wait(bars + 8 * (B_G1DONE + k - S1));
              mbar_expect_tx(bars + 8 * (B_G1FULL + k), 20480);
              tma4(dst, last ? &p.mXl : &p.mX, 64 * k, 0, 0, last ? 0 : 80 * T1, bars + 8 * (B_G1FULL + k));
              dst += G1_STAGE; if (k == 2 * S1 - 1) dst = sb + G1_XOFF;
            }
          }
        } else {
          mbar_wait(bars + 8 * (has2 ? B_G2DONE + 19 : B_G1DONE + 9));
          const int mlo = (160 * T1) >> 6, nf = last ? 8 : 12;
          if (lane < nf) flag_poll(&g_uflag[(4 * mlo + lane) * 8], tag);
          __syncwarp();
          fence_async_global();
          if (elect_one()) {
            TS(20);
            const int bytes = last ? 16384 : 20480;
            const uint8_t* src = g_u + T1 * 204800;
            uint32_t dst = sb + G1_XOFF;
#pragma unroll 1
            for (int k = 0; k < 10; k++) {
              if (k > S1) mbar_wait(bars + 8 * (B_G1DONE + 9 - S1 + k));
              mbar_expect_tx(bars + 8 * (B_G1FULL + 10 + k), bytes);
              bulk_g2s(dst, src, bytes, bars + 8 * (B_G1FULL + 10 + k));
              src += 20480; dst += G1_STAGE; if (k == S1) dst = sb + G1_XOFF;
            }
          }
        }
        __syncwarp();
        if (has2) {
          mbar_wait(bars + 8 * (B_G1DONE + 10 * l + 9));
          const int Tlo = (64 * m2) / 160, Thi = (64 * m2 + 63) / 160;
          if ((lane & 15) < 10) flag_poll(&g_hflag[(((l * NT1 + (lane < 16 ? Tlo : Thi)) * 2) * 16 + (lane & 15)) * 8], tag);
          __syncwarp();
          fence_async_global();
          if (elect_one()) {
            TS(21 + 2 * l);
            const uint32_t fb2 = bars + 8 * (B_G2FULL + 20 * l), wb2 = bars + 8 * (B_G2DONE + 18 * l - SX2);
            const uint8_t* src = g_h + (l * 32 + m2) * 163840;
            uint32_t dst = sb;
#pragma unroll 1
            for (int k = 0; k < 20; k++) {
              if (k >= SX2 + 2 * l) mbar_wait(wb2 + 8 * k);
              if (k == 10) { mbar_wait(bars + 8 * (B_H1 + l)); fence_async_global(); }
              mbar_expect_tx(fb2 + 8 * k, G2_XB);
              bulk_g2s(dst, src, G2_XB, fb2 + 8 * k);
              src += 8192; dst += G2_XB; if (dst == sb + (SX2 + 2 * l) * G2_XB) dst = sb;
            }
          }
          __syncwarp();
        }
      }
    } else if (pw == 2) {
#pragma unroll 1
      for (int l = 0; l < 2; l++) {
        mbar_wait(bars + 8 * (B_HST + 2 * l));
        mbar_wait(bars + 8 * (B_HST + 2 * l + 1));
        __syncwarp();
        if (lane < 2) st_rel(&g_hflag[(((l * NT1 + T1) * 2 + lane) * 16 + 2 * GP + side) * 8], tag);
        if (lane == 0) TS(6 + 8 * l);
        __syncwarp();
        if (l == 0 && has2 && elect_one()) {
#pragma unroll 1
          for (int c = 0; c < 5; c++) {
            mbar_wait(bars + 8 * (B_CVDONE + c));
            bulk_s2g(g_G + (cch0 + c) * 4096, cv_stage(c), 4096);
          }
          asm volatile("cp.async.bulk.commit_group;" ::: "memory");
          asm volatile("cp.async.bulk.wait_group 0;" ::: "memory");
          fence_async_global();
          st_rel(&g_gflag[(dg * 32 + m2) * 8], tag);
        }
        __syncwarp();
      }
    } else if (has2) {
      mbar_wait(bars + 8 * B_PREP);
#pragma unroll
      for (int c = 0; c < 5; c++) {
        const uint32_t cb = sb + CV_OFF + c * CV_B;
        const uint32_t a = lane < 8 ? cb + 16 * lane : (lane < 20 ? cb + CV_U + 16 * (lane - 8) : cb + CV_U + CV_PL + 16 * (lane - 20));
        asm volatile("st.shared.v4.u32 [%0], {%1,%1,%1,%1};" ::"r"(a), "r"(0) : "memory");
      }
      fence_async_smem();
      __syncwarp();
#pragma unroll 1
      for (int c = 0; c < 5; c++) {
        if (c >= 2) mbar_wait(bars + 8 * (B_TAPS + c - 2));
        if (elect_one()) {
          mbar_expect_tx(bars + 8 * (B_TAPS + c), 4096);
          bulk_g2s(sb + CV_OFF + c * CV_B + CV_K, p.ssmk + (size_t)(cch0 + c) * SEQ, 4096, bars + 8 * (B_TAPS + c));
        }
      }
      if (elect_one()) {
        asm volatile("prefetch.tensormap [%0];" ::"l"(&p.mCre) : "memory");
        asm volatile("prefetch.tensormap [%0];" ::"l"(&p.mCim) : "memory");
        asm volatile("prefetch.tensormap [%0];" ::"l"(&p.mG) : "memory");
      }
      flag_poll(&g_kvflag[(dg * 32 + lane) * 8], tag);
      __syncwarp();
      fence_async_global();
      if (lane == 0) TS(28);
      if (elect_one()) {
#pragma unroll
        for (int c = 0; c < 5; c++) {
          const uint32_t fb = bars + 8 * (B_CVFULL + c), cb = sb + CV_OFF + c * CV_B + CV_U + 192;
          mbar_expect_tx(fb, 4096);
          bulk_g2s(cb, g_kv + (size_t)(cch0 + c) * 4096, 2048, fb);
          bulk_g2s(cb + CV_PL, g_kv + (size_t)(cch0 + c) * 4096 + 2048, 2048, fb);
        }
      }
      const unsigned* hf = &g_hflag[(((lane < 16 ? (64 * m2) / 160 : (64 * m2 + 63) / 160) * 2 + 1) * 16 + min(lane & 15, 9)) * 8];
      mbar_wait(bars + 8 * (B_CVDONE + 0));
      if (elect_one()) { l2_prefetch(p.cre + (size_t)cch0 * DM, 6400); l2_prefetch(p.cim + (size_t)cch0 * DM, 6400); }
      flag_poll(hf, tag);
      __syncwarp();
      if (lane == 0) { mbar_arrive(bars + 8 * B_H1); TS(22); }
      mbar_wait(bars + 8 * (B_CVDONE + 4));
      flag_poll(&g_gflag[(dg * 32 + lane) * 8], tag);
      __syncwarp();
      fence_async_global();
      if (lane == 0) TS(29);
      if (elect_one()) {
        mbar_expect_tx(bars + 8 * B_GFULL, 20480);
        tma5(sb + G_OFF, &p.mG, 64 * m2, 0, 0, 0, 10 * dg, bars + 8 * B_GFULL);
      }
      mbar_wait(bars + 8 * (B_G1DONE + 19));
      flag_poll(hf + NT1 * 256, tag);
      __syncwarp();
      if (lane == 0) { mbar_arrive(bars + 8 * (B_H1 + 1)); TS(24); }
    }
  } else {
    asm volatile("setmaxnreg.inc.sync.aligned.u32 152;");
    const int w = wid & 3;
    mbar_wait(bars + 8 * B_EP);
    const unsigned tag = lds32(sb + EP_OFF + 20);
    if (wg == 2) {
      ROLE(role)
      if (has2) {
        const int n0 = 64 * m2 + 16 * w + (lane >> 2);
        KvRegs<2> x;
        {
          float xs[80];
          x0_load(xs);
          stats_publish<true>(0, n0, dg, tag, xs);
        }
        if (tid == 256) TS(31);
        kv_load<2>(m2, 32 * w, x);
        if (tid == 352) TS(50);
        kv_finish<2>(m2, 160 * dg + 32 * w, x);
        if (tid == 352) TS(52);
        asm volatile("bar.arrive 3, 192;" ::: "memory");
      } else if (tid == 256) mbar_arrive(bars + 8 * B_PREP);
      stat_table(T1, tag, 0);
      if (tid == 256) TS(26);
      if (!has2) { mbar_wait(bars + 8 * (B_G1FULL + 11)); stat_table(T1, tag, 1); }
    }
#pragma unroll 1
    for (int l = 0; l < 2; l++) {
      if (wg < 2) {
        float acc[80];
#pragma unroll
        for (int i = 0; i < 80; i++) acc[i] = 0.f;
        ROLE(role)
        const int tid = tid_opaque(), r = (tid & 31) >> 2, q = tid & 3;
        const int ch = 128 * GP + 64 * wg + 32 * side + 8 * w + r;
        mbar_wait(bars + 8 * B_CTAB);
        const uint32_t ca = sb + CTAB_OFF + (32 * wg + 8 * w + r) * 24;
        float2 lam = lds64f(ca);
        const float2 coef = lds64f(ca + 8), lamc = make_float2(lam.x, -lam.y);
        float m00 = coef.x, m01 = -coef.y, m10 = -coef.y, m11 = -coef.x;
        if (p.swap) { lam = lamc; m00 = -coef.y; m01 = coef.x; m10 = -coef.x; m11 = -coef.y; }
        float2 p8, p16, pL, p2L;
        {
          const float2 p2 = cmul(lam, lam), p4 = cmul(p2, p2);
          p8 = cmul(p4, p4); p16 = cmul(p8, p8);
          pL = cmul(p16, p16);
          if (!last) pL = cmul(pL, p8);
          p2L = cmul(pL, pL);
        }
        fence_regs(acc);
        {
          uint32_t alo = desc_lo(sb, 16) + wg * 512, blo = l == 0 ? desc_lo(sb + G1_XOFF, 16) : desc_lo(sb + G1_XOFF, 128);
          const uint32_t bhi = l == 0 ? desc_hi(1024, 1) : desc_hi(1024, 0), xstep = l == 0 ? 2 : 16;
          const uint32_t aend = desc_lo(sb, 16) + (S1 + l) * (G1_STAGE >> 4);
          uint32_t fb = bars + 8 * (B_G1FULL + 10 * l);
          mbar_wait(fb);
          if (tid == 0) TS(1 + 8 * l);
#pragma unroll 1
          for (int k = 0; k < 10; k++) {
            uint32_t ok; const uint32_t nb = k < 9 ? fb + 8 : fb;
            wgmma_fence();
#pragma unroll
            for (int kk = 0; kk < 4; kk++) {
              wgmma_n160<0>(acc, alo + kk * 2, desc_hi(1024, 1), blo + kk * xstep, bhi);
              if (kk == 0) ok = mbar_test(nb);
            }
            wgmma_commit();
            alo += G1_STAGE >> 4; blo += G1_STAGE >> 4;
            if (alo >= aend) { alo -= (S1 + l) * (G1_STAGE >> 4); blo -= (S1 + l) * (G1_STAGE >> 4); }
            wgmma_wait<1>();
            if (k > 0 && (tid & 127) == 0) mbar_arrive(fb + 8 * (B_G1DONE - B_G1FULL - 1));
            if (!ok) mbar_wait(nb);
            if (l == 0 && k == PAUSE_K) { if (tid == 0) TS(48); mbar_wait(bars + 8 * B_PREP); if (tid == 0) TS(49); }
            fb += 8;
          }
        }
        mbar_wait(bars + 8 * (B_STAB + l));
        const float2 sB = lds64f(ca + 16);
        wgmma_wait<0>();
        fence_regs(acc);
        if ((tid & 127) == 0) { mbar_arrive(bars + 8 * (B_G1DONE + 10 * l + 9)); if (wg == 0) TS(2 + 8 * l); }
        float2 ec[3];
#pragma unroll
        for (int jj = 0; jj < 8; jj++)
#pragma unroll
          for (int y = 0; y < 3; y++) {
            if (y == 2 && (jj & 1)) continue;
            const int j = y == 2 ? 16 + (jj >> 1) : 8 * y + jj;
            const float4 st = lds128f(sb + STAB_OFF + (8 * j + 2 * q) * 8);
            acc[4 * j + 0] = fmaf(acc[4 * j + 0], st.x, st.y * sB.x);
            acc[4 * j + 2] = fmaf(acc[4 * j + 2], st.x, st.y * sB.y);
            acc[4 * j + 1] = fmaf(acc[4 * j + 1], st.z, st.w * sB.x);
            acc[4 * j + 3] = fmaf(acc[4 * j + 3], st.z, st.w * sB.y);
            ec[y] = jj == 0 ? make_float2(acc[4 * j + 0], acc[4 * j + 2]) : cfma(lam, ec[y], make_float2(acc[4 * j + 0], acc[4 * j + 2]));
            ec[y] = cfma(lam, ec[y], make_float2(acc[4 * j + 1], acc[4 * j + 3]));
          }
        float2 e = cfma(p16, ec[0], ec[1]);
        if (!last) e = cfma(p8, e, ec[2]);
        {
          float2 v = make_float2(__shfl_up_sync(0xffffffffu, e.x, 1, 4), __shfl_up_sync(0xffffffffu, e.y, 1, 4));
          if (q >= 1) e = cfma(pL, v, e);
          v = make_float2(__shfl_up_sync(0xffffffffu, e.x, 2, 4), __shfl_up_sync(0xffffffffu, e.y, 2, 4));
          if (q >= 2) e = cfma(p2L, v, e);
        }
        if (!last && (q == 3 || (q == 2 && l == 0))) rec_st(&g_E[((q == 3 ? l : 1) * NT1 + T1) * DM + ch], e.x, e.y, q == 3 ? tag : tag - 1);
        if (tid == 0) TS(3 + 8 * l);
        float2 ex = make_float2(__shfl_up_sync(0xffffffffu, e.x, 1, 4), __shfl_up_sync(0xffffffffu, e.y, 1, 4));
        if (q == 0) ex = make_float2(0.f, 0.f);
        float2 pLq, p160q, p640;
        {
          const float2 p80 = last ? cmul(p2L, p16) : p2L, p160 = cmul(p80, p80), p320 = cmul(p160, p160), one = make_float2(1.f, 0.f);
          p640 = cmul(p320, p320);
          pLq = cmul((q & 1) ? pL : one, (q & 2) ? p2L : one);
          p160q = cmul((q & 1) ? p160 : one, (q & 2) ? p320 : one);
        }
        float2 c, ev[3];
        unsigned tg[3];
        const uint4* ep = &g_E[(l * NT1 + T1 - 1 - q) * DM + ch];
#pragma unroll
        for (int j = 0; j < 20; j++) {
          if (j == CPOLL) {
#pragma unroll
            for (int i = 0; i < 3; i++) {
              ev[i] = make_float2(0.f, 0.f); tg[i] = tag;
              if (T1 - 1 - q - 4 * i >= 0) tg[i] = rec_ld(ep - 4 * i * DM, ev[i].x, ev[i].y);
            }
          }
#pragma unroll
          for (int x = 0; x < 2; x++) {
            const float b0 = acc[4 * j + x], b1 = acc[4 * j + 2 + x];
            acc[4 * j + x] = fmaf(b0, m00, b1 * m01);
            acc[4 * j + 2 + x] = fmaf(b0, m10, b1 * m11);
          }
          if (j == CPOLL - 1 || j == 19) asm volatile("" : "+f"(acc[4 * j]), "+f"(acc[4 * j + 1]), "+f"(acc[4 * j + 2]), "+f"(acc[4 * j + 3])::"memory");
        }
        {
          uint32_t it = 0;
          while (tg[0] != tag || tg[1] != tag || tg[2] != tag) {
#pragma unroll
            for (int i = 0; i < 3; i++)
              if (tg[i] != tag) tg[i] = rec_ld(ep - 4 * i * DM, ev[i].x, ev[i].y);
            if (++it > SPIN_LIMIT) soft_trap();
          }
          __syncwarp();
          c = cfma(p640, cfma(p640, ev[2], ev[1]), ev[0]);
          c = cmul(c, p160q);
          c.x += __shfl_xor_sync(0xffffffffu, c.x, 1); c.y += __shfl_xor_sync(0xffffffffu, c.y, 1);
          c.x += __shfl_xor_sync(0xffffffffu, c.x, 2); c.y += __shfl_xor_sync(0xffffffffu, c.y, 2);
        }
        if (tid == 0) TS(4 + 8 * l);
        if (tid == 128) mbar_arrive(bars + 8 * (B_GO + 2 * l));
        c = cfma(pLq, c, ex);
        float2 hh = make_float2(fmaf(c.x, m00, c.y * m01), fmaf(c.x, m10, c.y * m11));
        uint8_t* hb = g_h + (size_t)l * (32 * 20 * 8192) + (10 * wg + 2 * GP) * 8192 + (4 * side + w) * 1024 + (tid_opaque() & 31) * 4;
#pragma unroll
        for (int j4 = 0; j4 < 5; j4++) {
          const int ng = 20 * T1 + 4 * j4;
          uint8_t* hp = hb + (size_t)(ng >> 3) * 163840 + (ng & 7) * 128;
#pragma unroll
          for (int jj = 0; jj < 4; jj++) {
            const int j = 4 * j4 + jj;
            const float2 h0 = cfma(lamc, hh, make_float2(acc[4 * j + 0], acc[4 * j + 2]));
            hh = cfma(lamc, h0, make_float2(acc[4 * j + 1], acc[4 * j + 3]));
            if (j4 < 4 || !last) {
              *(uint32_t*)(hp + jj * 128) = pack_bf16(h0.x, hh.x);
              *(uint32_t*)(hp + jj * 128 + 8192) = pack_bf16(h0.y, hh.y);
            }
          }
        }
        mbar_arrive(bars + 8 * (B_HST + 2 * l + wg));
        if (tid == 0) TS(5 + 8 * l);
      }
      if (l == 0) {
        ROLE(role)
        if (has2) {
          uint32_t so[4];
          cv_offsets(so);
          mbar_wait(bars + 8 * (B_G1DONE + 9));
#pragma unroll 1
          for (int c = wg == 2 ? 0 : 2 + wg; c < (wg == 2 ? 2 : 5); c += wg == 2 ? 1 : 2) conv_channel(c, so);
          if ((tid & 127) == 0) TS(wg == 2 ? 32 : 7 + wg);
        }
      }
      if (wg == 2) break;
    }
    if (wg == 2 && (role >> 16)) {
      float acc[80];
      float off[2] = {0.f, 0.f};
      x0_load(acc);
      mbar_arrive(bars + 8 * B_XFREE);
#pragma unroll 1
      for (int l = 0; l < 2; l++) {
        float mean[2], rstd[2];
        {
          ROLE(role)
          const int lane = tid_opaque() & 31;
          stats_get(2 * l, 64 * m2 + 16 * w + (lane >> 2), tag, mean, rstd);
          off[0] += mean[0]; off[1] += mean[1];
          mbar_wait(bars + 8 * (l == 0 ? B_CTAB : B_HST + 3));
#pragma unroll
          for (int J = 0; J < 10; J++) {
            const float2 dw = lds64f(sb + DTAB_OFF + 2 * (16 * J + 4 * (lane & 3)));
#pragma unroll
            for (int x = 0; x < 8; x++) {
              const int h = (x >> 1) & 1;
              const uint32_t gwd = __float_as_uint(x < 4 ? dw.x : dw.y);
              acc[8 * J + x] = (acc[8 * J + x] - mean[h]) * fmaf(rstd[h], (x & 1) ? bf_hi(gwd) : bf_lo(gwd), 1.f);
            }
          }
        }
        {
          const uint32_t aend = desc_lo(sb + SX2 * G2_XB, 1024) + l * (G2_XB >> 3), bend = desc_lo(sb + G2_WOFF + 6 * G2_WB, 16) + l * (G2_WB >> 4);
          uint32_t alo = desc_lo(sb, 1024), blo = desc_lo(sb + G2_WOFF, 16);
          uint32_t fb = bars + 8 * (B_G2FULL + 20 * l);
          fence_regs(acc);
          mbar_wait(fb);
          if (tid == 256) TS(33 + 6 * l);
#pragma unroll 1
          for (int k = 0; k < 20; k++) {
            if (l == 1 && (k & 3) == 3 && tid == 256) TS(56 + (k >> 2));
            uint32_t ok; const uint32_t nb = k < 19 ? fb + 8 : fb;
            wgmma_fence();
#pragma unroll
            for (int kk = 0; kk < 4; kk++) {
              wgmma_n160<1>(acc, alo + kk * 128, desc_hi(128, 0), blo + kk * 2, desc_hi(1024, 1));
              if (kk == 0) ok = mbar_test(nb);
            }
            wgmma_commit();
            alo += G2_XB >> 4; if (alo == aend) alo = desc_lo(sb, 1024);
            blo += G2_WB >> 4; if (blo == bend) blo = desc_lo(sb + G2_WOFF, 16);
            wgmma_wait<1>();
            if (k > 0 && tid == 256) mbar_arrive(fb + 8 * (B_G2DONE - B_G2FULL - 1));
            if (!ok) mbar_wait(nb);
            fb += 8;
          }
          wgmma_wait<0>();
          fence_regs(acc);
          if (tid == 256) TS(34 + 6 * l);
          if (tid == 256) mbar_arrive(bars + 8 * (B_G2DONE + 20 * l + 19));
        }
        ROLE(role)
        const int tq = tid_opaque() & 31, n0 = 64 * m2 + 16 * w + (tq >> 2);
        stats_publish<false>(2 * l + 1, n0, dg, tag, acc);
        uint32_t gf[10][4];
        mbar_wait(bars + 8 * B_GFULL);
        const uint32_t ga = sb + G_OFF + (8 * (tq >> 4) + (tq & 7)) * 128 + (((2 * w + ((tq >> 3) & 1)) ^ (m2 & 7) ^ (tq & 7)) << 4);
#pragma unroll
        for (int J = 0; J < 2; J++) ldsm4t(gf[J], ga + J * 2048);
        if (tid == 256) TS(35 + 6 * l);
        uint8_t* dst[2][2];
#pragma unroll
        for (int h = 0; h < 2; h++) {
          if (l == 0) {
            const int ng = 8 * m2 + 2 * w + h, T = ng / 20;
            uint8_t* ub = g_u + (T * 204800 + (ng - 20 * T) * 1024 + (tq & 2) * 64 + (tq & 28) * 4 + (tq & 1) * 8 + (5 * dg >> 1) * 20480);
            dst[h][1] = ub + ((dg & 1) ? 20480 - 512 : 0);
            dst[h][0] = ub + (dg & 1) * 512;
          } else {
            dst[h][0] = dst[h][1] = (uint8_t*)(p.out + (n_to_t(n0 + 8 * h) * DM + 160 * dg + 4 * (tq & 3)));
          }
        }
        stats_get(2 * l + 1, n0, tag, mean, rstd);
        if (tid == 256) { TS(36 + 6 * l); if (l == 0) mbar_arrive(bars + 8 * (B_GO + 1)); }
        off[0] += mean[0]; off[1] += mean[1];
        const float ov[2] = {l ? off[0] : 0.f, l ? off[1] : 0.f};
#pragma unroll
        for (int J = 0; J < 10; J++) {
          if (J + 2 < 10) ldsm4t(gf[J + 2 < 10 ? J + 2 : 0], ga + (J + 2) * 2048);
#pragma unroll
          for (int x = 0; x < 8; x++) {
            const int h = (x >> 1) & 1;
            const uint32_t gwd = gf[J][x >> 1];
            const float t = fmaf(rstd[h], (x & 1) ? bf_hi(gwd) : bf_lo(gwd), 1.f);
            acc[8 * J + x] = fmaf(acc[8 * J + x], t, fmaf(-mean[h], t, ov[h]));
          }
#pragma unroll
          for (int h = 0; h < 2; h++) {
            if (l == 0)
              *(uint2*)(dst[h][(J >> 1) & 1] + (J >> 2) * 20480 + (J & 3) * 256) =
                  make_uint2(pack_bf16(acc[8 * J + 2 * h], acc[8 * J + 2 * h + 1]), pack_bf16(acc[8 * J + 4 + 2 * h], acc[8 * J + 5 + 2 * h]));
            else
              *(float4*)(dst[h][0] + 64 * J) = make_float4(acc[8 * J + 2 * h], acc[8 * J + 2 * h + 1], acc[8 * J + 4 + 2 * h], acc[8 * J + 5 + 2 * h]);
          }
          __syncwarp();
        }
        if (l == 0) {
          bar_sync(3, 128);
          if (tid == 256) { TS(37); st_rel(&g_uflag[(4 * m2 + dg) * 8], tag); TS(38); }
          stats_publish<false>(2, n0, dg, tag, acc);
          mbar_wait(bars + 8 * (B_G1FULL + 11));
          stat_table(T1, tag, 1);
          if (tid == 256) TS(27);
        } else {
          if (tid == 256) {
            TS(43);
            if (m2 == 31 && dg == 3) asm volatile("st.relaxed.gpu.global.u32 [%0], %1;" ::"l"(g_epoch), "r"(tag + 1) : "memory");
          }
        }
      }
    }
  }
}

typedef CUresult (*EncFn)(CUtensorMap*, CUtensorMapDataType, cuuint32_t, void*, const cuuint64_t*, const cuuint64_t*,
                          const cuuint32_t*, const cuuint32_t*, CUtensorMapInterleave, CUtensorMapSwizzle,
                          CUtensorMapL2promotion, CUtensorMapFloatOOBfill);

void encode(EncFn fn, CUtensorMap* m, const void* ptr, int rank, const cuuint64_t* dims, const cuuint64_t* strides, const cuuint32_t* box,
            CUtensorMapSwizzle swz = CU_TENSOR_MAP_SWIZZLE_128B) {
  cuuint32_t es[5] = {1, 1, 1, 1, 1};
  fn(m, CU_TENSOR_MAP_DATA_TYPE_BFLOAT16, rank, (void*)ptr, dims, strides, box, es, CU_TENSOR_MAP_INTERLEAVE_NONE,
     swz, swz == CU_TENSOR_MAP_SWIZZLE_128B ? CU_TENSOR_MAP_L2_PROMOTION_L2_128B : CU_TENSOR_MAP_L2_PROMOTION_L2_64B, CU_TENSOR_MAP_FLOAT_OOB_FILL_NONE);
}

}

extern "C" void kernel_launch(void* const* d_in, const int* in_sizes, int n_in, void* d_out, int out_size) {
  (void)in_sizes; (void)n_in; (void)out_size;
  Params p;
  typedef const __nv_bfloat16* BP;
  p.x = (BP)d_in[0]; p.lre = (BP)d_in[1]; p.lim = (BP)d_in[2]; p.bre = (BP)d_in[3]; p.bim = (BP)d_in[4];
  p.cre = (BP)d_in[5]; p.cim = (BP)d_in[6]; p.logdt = (BP)d_in[7]; p.dskip = (BP)d_in[8];
  p.k = (BP)d_in[10]; p.v = (BP)d_in[11]; p.shiftk = (BP)d_in[12]; p.ssmk = (BP)d_in[13]; p.ssmD = (BP)d_in[14];
  p.out = (float*)d_out;
  void* fnp = nullptr;
  cudaDriverEntryPointQueryResult qr;
  cudaGetDriverEntryPoint("cuTensorMapEncodeTiled", &fnp, cudaEnableDefault, &qr);
  EncFn fn = (EncFn)fnp;
  void* gG = nullptr;
  cudaGetSymbolAddress(&gG, g_G);
  const cuuint64_t RB = DM * 2;
  {
    p.swap = p.bim < p.bre;
    const char* lo = (const char*)(p.swap ? p.bim : p.bre); const char* hi = (const char*)(p.swap ? p.bre : p.bim);
    cuuint64_t dims[5] = {640, 8, 2, 8, 10}, st[4] = {RB, (cuuint64_t)(hi - lo), 8 * RB, 64 * RB}; cuuint32_t box[5] = {64, 8, 2, 4, 2};
    encode(fn, &p.mB, lo, 5, dims, st, box);
  }
  {
    cuuint64_t dims[5] = {640, 2, 4, 2, 40}, st[4] = {RB, 4 * RB, 2 * RB, 16 * RB}; cuuint32_t box[5] = {64, 2, 4, 2, 10};
    encode(fn, &p.mCre, p.cre, 5, dims, st, box); encode(fn, &p.mCim, p.cim, 5, dims, st, box);
    cuuint64_t dimg[5] = {2048, 2, 4, 2, 40}, stg[4] = {4096, 4 * 4096, 2 * 4096, 16 * 4096};
    encode(fn, &p.mG, gG, 5, dimg, stg, box);
  }
  {
    cuuint64_t dims[4] = {640, 2, 4, 900}, st[3] = {RB, 40 * RB, 2 * RB}; cuuint32_t box[4] = {64, 2, 4, 20};
    encode(fn, &p.mX, p.x, 4, dims, st, box);
    cuuint64_t diml[4] = {640, 2, 4, 16}, stl[3] = {RB, 32 * RB, 2 * RB};
    encode(fn, &p.mXl, p.x + (size_t)1920 * DM, 4, diml, stl, box);
    cuuint32_t boxt[4] = {160, 2, 4, 4};
    encode(fn, &p.mXt, p.x, 4, dims, st, boxt, CU_TENSOR_MAP_SWIZZLE_NONE);
    encode(fn, &p.mXtl, p.x + (size_t)1920 * DM, 4, diml, stl, boxt, CU_TENSOR_MAP_SWIZZLE_NONE);
    cuuint64_t dk[3] = {640, 2000, 4}, sk[2] = {RB, 16 * RB}; cuuint32_t bk[3] = {32, 19, 4}, bv[3] = {32, 17, 4};
    encode(fn, &p.mK, p.k, 3, dk, sk, bk, CU_TENSOR_MAP_SWIZZLE_NONE);
    encode(fn, &p.mV, p.v, 3, dk, sk, bv, CU_TENSOR_MAP_SWIZZLE_NONE);
  }
  cudaFuncSetAttribute(fused_kernel, cudaFuncAttributeMaxDynamicSharedMemorySize, SMEM_BYTES);
  cudaLaunchConfig_t cfg = {};
  cfg.gridDim = dim3(132); cfg.blockDim = dim3(512); cfg.dynamicSmemBytes = SMEM_BYTES; cfg.stream = cudaStreamPerThread;
  cudaLaunchKernelEx(&cfg, fused_kernel, p);
}
```

```cpp
#include <cuda_runtime.h>
#include <cuda.h>
#include <cuda_bf16.h>
#include <stdint.h>

namespace {

constexpr int SEQ = 2048, DM = 640;
constexpr int NT1 = 13;
#define EXP 0
#define WPF1 1
#define WPF2 2
#define CPOLL 10
#define PAUSE_K 4
constexpr uint32_t SPIN_LIMIT = 1u << 22;

__device__ __align__(1024) uint8_t g_h[2 * 32 * 20 * 8192];
__device__ __align__(1024) uint8_t g_u[NT1 * 10 * 20480];
__device__ __align__(1024) uint8_t g_kv[DM * 4096];
__device__ __align__(1024) uint8_t g_G[DM * 4096];
__device__ __align__(128) uint4 g_E[2 * NT1 * DM];
__device__ __align__(128) uint4 g_stats[4 * 4 * SEQ];
__device__ __align__(128) uint4 g_sB[DM * 2];
__device__ __align__(128) unsigned g_hflag[2 * NT1 * 2 * 16 * 8];
__device__ __align__(128) unsigned g_uflag[32 * 4 * 8];
__device__ __align__(128) unsigned g_kvflag[4 * 32 * 8];
__device__ __align__(128) unsigned g_gflag[4 * 32 * 8];
__device__ __align__(128) unsigned g_epoch[32] = {1};
#define TS(i) do {} while (0)

struct Params {
  CUtensorMap mB, mCre, mCim, mX, mXl, mG, mK, mV, mXt, mXtl;
  const __nv_bfloat16 *x, *lre, *lim, *bre, *bim, *cre, *cim, *logdt, *dskip, *k, *v, *shiftk, *ssmk, *ssmD;
  float* out;
  int swap;
};

constexpr uint32_t sb = 1024;
constexpr uint32_t G1_STAGE = 36864, G1_XOFF = 16384;
constexpr int S1 = 4;
constexpr uint32_t XT_OFF = 159744, KS_OFF = 180224, KV_PIECE = 9216;
constexpr uint32_t G2_XB = 8192, G2_WB = 20480, G2_WOFF = 57344, G_OFF = 200704;
constexpr int SX2 = 5;
constexpr uint32_t CV_OFF = 184320, CV_K = 128, CV_PL = 2240, CV_U = CV_K + 4096, CV_B = 8704;
constexpr uint32_t MISC = 227840;
constexpr uint32_t BAR_OFF = MISC;
constexpr int B_G1FULL = 0, B_G1DONE = 20, B_G2FULL = 40,
              B_G2DONE = 85, B_GFULL = 125, B_PREP = 126, B_EP = 127, B_H1 = 128  ,
              B_CVDONE = 130, B_STAB = 135  , B_CTAB = 137, B_XFREE = 138, B_HST = 139  ,
              B_XT = 143, B_KV = 144  , B_TAPS = 149  , B_CVFULL = 154  , B_GO = 159  ;
constexpr uint32_t bars = sb + BAR_OFF;
constexpr uint32_t STAB_OFF = MISC + 1296;
constexpr uint32_t CTAB_OFF = STAB_OFF + 1280;
constexpr uint32_t DTAB_OFF = CTAB_OFF + 1536;
constexpr uint32_t EP_OFF = DTAB_OFF + 320;
constexpr uint32_t TAP_OFF = 147456;
constexpr uint32_t SMEM_BYTES = 232448;
static_assert(EP_OFF + 32 <= SMEM_BYTES, "smem");

__device__ __forceinline__ void trap_if(bool c) { asm volatile("{\n.reg .pred p;\nsetp.ne.u32 p, %0, 0;\n@p trap;\n}\n" ::"r"((uint32_t)c)); }
__device__ __forceinline__ uint32_t smem_u32(const void* p) { return (uint32_t)__cvta_generic_to_shared(p); }
__device__ __forceinline__ void mbar_init(uint32_t bar, int cnt) { asm volatile("mbarrier.init.shared::cta.b64 [%0], %1;" ::"r"(bar), "r"(cnt) : "memory"); }
__device__ __forceinline__ void mbar_expect_tx(uint32_t bar, int bytes) { asm volatile("mbarrier.arrive.expect_tx.shared::cta.b64 _, [%0], %1;" ::"r"(bar), "r"(bytes) : "memory"); }
__device__ __forceinline__ void mbar_arrive(uint32_t bar) { asm volatile("mbarrier.arrive.shared::cta.b64 _, [%0];" ::"r"(bar) : "memory"); }
__device__ __forceinline__ void mbar_wait(uint32_t bar) {
  asm volatile(
      "{\n.reg .pred p;\n.reg .u32 c;\nmov.u32 c, 0;\n"
      "W_%=:\nmbarrier.try_wait.parity.shared::cta.b64 p, [%0], 0;\n@p bra D_%=;\n"
      "add.u32 c, c, 1;\nsetp.lt.u32 p, c, %1;\n@p bra W_%=;\ntrap;\nD_%=:\n}\n" ::"r"(bar), "n"(SPIN_LIMIT) : "memory");
}
__device__ __forceinline__ uint32_t mbar_test(uint32_t bar) {
  uint32_t ok;
  asm volatile("{\n.reg .pred p;\nmbarrier.test_wait.parity.shared::cta.b64 p, [%1], 0;\nselp.u32 %0, 1, 0, p;\n}\n" : "=r"(ok) : "r"(bar) : "memory");
  return ok;
}
__device__ __forceinline__ void tma3(uint32_t dst, const CUtensorMap* m, int c0, int c1, int c2, uint32_t bar) {
  asm volatile("cp.async.bulk.tensor.3d.shared::cluster.global.mbarrier::complete_tx::bytes [%0], [%1, {%3,%4,%5}], [%2];"
               ::"r"(dst), "l"(m), "r"(bar), "r"(c0), "r"(c1), "r"(c2) : "memory");
}
__device__ __forceinline__ void tma4(uint32_t dst, const CUtensorMap* m, int c0, int c1, int c2, int c3, uint32_t bar) {
  asm volatile("cp.async.bulk.tensor.4d.shared::cluster.global.mbarrier::complete_tx::bytes [%0], [%1, {%3,%4,%5,%6}], [%2];"
               ::"r"(dst), "l"(m), "r"(bar), "r"(c0), "r"(c1), "r"(c2), "r"(c3) : "memory");
}
__device__ __forceinline__ void tma5(uint32_t dst, const CUtensorMap* m, int c0, int c1, int c2, int c3, int c4, uint32_t bar) {
  asm volatile("cp.async.bulk.tensor.5d.shared::cluster.global.mbarrier::complete_tx::bytes [%0], [%1, {%3,%4,%5,%6,%7}], [%2];"
               ::"r"(dst), "l"(m), "r"(bar), "r"(c0), "r"(c1), "r"(c2), "r"(c3), "r"(c4) : "memory");
}
__device__ __forceinline__ void bulk_g2s(uint32_t dst, const void* src, int bytes, uint32_t bar) {
  asm volatile("cp.async.bulk.shared::cluster.global.mbarrier::complete_tx::bytes [%0], [%1], %2, [%3];"
               ::"r"(dst), "l"(src), "r"(bytes), "r"(bar) : "memory");
}
__device__ __forceinline__ void bulk_s2g(void* dst, uint32_t src, int bytes) {
  asm volatile("cp.async.bulk.global.shared::cta.bulk_group [%0], [%1], %2;" ::"l"(dst), "r"(src), "r"(bytes) : "memory");
}
__device__ __forceinline__ void l2_prefetch(const void* src, int bytes) {
  asm volatile("cp.async.bulk.prefetch.L2.global [%0], %1;" ::"l"(src), "r"(bytes) : "memory");
}
__device__ __forceinline__ void wgmma_fence() { asm volatile("wgmma.fence.sync.aligned;" ::: "memory"); }
__device__ __forceinline__ void wgmma_commit() { asm volatile("wgmma.commit_group.sync.aligned;" ::: "memory"); }
template <int N> __device__ __forceinline__ void wgmma_wait() { asm volatile("wgmma.wait_group.sync.aligned %0;" ::"n"(N) : "memory"); }
__host__ __device__ constexpr uint32_t desc_lo(uint32_t addr, uint32_t lbo) { return ((addr & 0x3FFFF) >> 4) | ((lbo >> 4) << 16); }
__host__ __device__ constexpr uint32_t desc_hi(uint32_t sbo, uint32_t swz) { return (sbo >> 4) | (swz << 30); }
__device__ __forceinline__ void bar_sync(int id, int n) { asm volatile("bar.sync %0, %1;" ::"r"(id), "r"(n) : "memory"); }
__device__ __forceinline__ uint32_t lds32(uint32_t a) { uint32_t v; asm volatile("ld.shared.u32 %0, [%1];" : "=r"(v) : "r"(a) : "memory"); return v; }
__device__ __forceinline__ float2 lds64f(uint32_t a) { float2 v; asm volatile("ld.shared.v2.f32 {%0,%1}, [%2];" : "=f"(v.x), "=f"(v.y) : "r"(a) : "memory"); return v; }
__device__ __forceinline__ float4 lds128f(uint32_t a) { float4 v; asm volatile("ld.shared.v4.f32 {%0,%1,%2,%3}, [%4];" : "=f"(v.x), "=f"(v.y), "=f"(v.z), "=f"(v.w) : "r"(a) : "memory"); return v; }
__device__ __forceinline__ void ldsm4t(uint32_t (&r)[4], uint32_t a) {
  asm volatile("ldmatrix.sync.aligned.m8n8.x4.trans.shared.b16 {%0,%1,%2,%3}, [%4];" : "=r"(r[0]), "=r"(r[1]), "=r"(r[2]), "=r"(r[3]) : "r"(a) : "memory");
}
__device__ __forceinline__ uint4 ldv128(const void* a) { uint4 v; asm volatile("ld.global.nc.v4.u32 {%0,%1,%2,%3}, [%4];" : "=r"(v.x), "=r"(v.y), "=r"(v.z), "=r"(v.w) : "l"(a) : "memory"); return v; }
__device__ __forceinline__ uint2 ldv64(const void* a) { uint2 v; asm volatile("ld.global.nc.v2.u32 {%0,%1}, [%2];" : "=r"(v.x), "=r"(v.y) : "l"(a) : "memory"); return v; }
__device__ __forceinline__ uint32_t ldv16(const void* a) { uint32_t v; asm volatile("ld.global.nc.u16 %0, [%1];" : "=r"(v) : "l"(a) : "memory"); return v; }
__device__ __forceinline__ void sts128(uint32_t a, uint4 v) { asm volatile("st.shared.v4.u32 [%0], {%1,%2,%3,%4};" ::"r"(a), "r"(v.x), "r"(v.y), "r"(v.z), "r"(v.w) : "memory"); }
__device__ __forceinline__ void sts32(uint32_t a, uint32_t v) { asm volatile("st.shared.u32 [%0], %1;" ::"r"(a), "r"(v) : "memory"); }
__device__ __forceinline__ void sts64f(uint32_t a, float x, float y) { asm volatile("st.shared.v2.f32 [%0], {%1,%2};" ::"r"(a), "f"(x), "f"(y) : "memory"); }
__device__ __forceinline__ void st_rel(unsigned* p, unsigned v) { asm volatile("st.release.gpu.global.u32 [%0], %1;" ::"l"(p), "r"(v) : "memory"); }
__device__ __forceinline__ void fence_async_global() { asm volatile("fence.proxy.async.global;" ::: "memory"); }
__device__ __forceinline__ void fence_async_smem() { asm volatile("fence.proxy.async.shared::cta;" ::: "memory"); }
__device__ __forceinline__ void rec_st(uint4* p, float a, float b, unsigned tag) {
  asm volatile("{\n.reg .b128 t;\n.reg .b64 lo, hi;\nmov.b64 lo, {%1,%2};\nmov.b64 hi, {%3,%3};\nmov.b128 t, {lo,hi};\n"
               "st.relaxed.gpu.global.b128 [%0], t;\n}\n" ::"l"(p), "r"(__float_as_uint(a)), "r"(__float_as_uint(b)), "r"(tag) : "memory");
}
__device__ __forceinline__ unsigned rec_ld(const uint4* p, float& a, float& b) {
  unsigned x, y, t;
  asm volatile("{\n.reg .b128 t;\n.reg .b64 lo, hi;\n.reg .b32 u;\nld.relaxed.gpu.global.b128 t, [%3];\nmov.b128 {lo,hi}, t;\n"
               "mov.b64 {%0,%1}, lo;\nmov.b64 {%2,u}, hi;\n}\n" : "=r"(x), "=r"(y), "=r"(t) : "l"(p) : "memory");
  a = __uint_as_float(x); b = __uint_as_float(y);
  return t;
}
__device__ __forceinline__ void rec_poll(const uint4* p, unsigned tag, float& a, float& b) {
  uint32_t it = 0;
  while (!__all_sync(0xffffffffu, rec_ld(p, a, b) == tag)) { trap_if(++it > SPIN_LIMIT); }
}
__device__ __forceinline__ unsigned ld_rlx(const unsigned* p) { unsigned v; asm volatile("ld.relaxed.gpu.global.u32 %0, [%1];" : "=r"(v) : "l"(p) : "memory"); return v; }
__device__ __forceinline__ void flag_poll(const unsigned* p, unsigned target) {
  uint32_t it = 0;
  while (!__all_sync(0xffffffffu, (int)(ld_rlx(p) - target) >= 0)) { trap_if(++it > SPIN_LIMIT); }
  asm volatile("fence.acquire.gpu;" ::: "memory");
}
__device__ __forceinline__ uint32_t pack_bf16(float lo, float hi) {
  uint32_t r; asm("cvt.rn.bf16x2.f32 %0, %1, %2;" : "=r"(r) : "f"(hi), "f"(lo)); return r;
}
__device__ __forceinline__ float bf_lo(uint32_t w) { return __uint_as_float(w << 16); }
__device__ __forceinline__ float bf_hi(uint32_t w) { return __uint_as_float(w & 0xffff0000u); }
__device__ __forceinline__ uint32_t hmul2(uint32_t a, uint32_t b) {
  __nv_bfloat162 r = __hmul2_rn(*(__nv_bfloat162*)&a, *(__nv_bfloat162*)&b); return *(uint32_t*)&r;
}
__device__ __forceinline__ uint32_t hadd2(uint32_t a, uint32_t b) {
  __nv_bfloat162 r = __hadd2_rn(*(__nv_bfloat162*)&a, *(__nv_bfloat162*)&b); return *(uint32_t*)&r;
}
__device__ __forceinline__ float2 cmul(float2 a, float2 b) { return make_float2(a.x * b.x - a.y * b.y, a.x * b.y + a.y * b.x); }
__device__ __forceinline__ float2 cfma(float2 a, float2 b, float2 c) {
  return make_float2(fmaf(a.x, b.x, fmaf(-a.y, b.y, c.x)), fmaf(a.x, b.y, fmaf(a.y, b.x, c.y)));
}
template <int N> __device__ __forceinline__ void fence_regs(float (&a)[N]) {
#pragma unroll
  for (int i = 0; i < N; i++) asm volatile("" : "+f"(a[i])::"memory");
}
__device__ __forceinline__ bool elect_one() {
  uint32_t e; asm volatile("{\n.reg .pred P;\nelect.sync _|P, 0xffffffff;\nselp.u32 %0, 1, 0, P;\n}\n" : "=r"(e)); return e != 0;
}
__device__ __forceinline__ int tid_opaque() { int t; asm volatile("mov.u32 %0, %%tid.x;" : "=r"(t)); return t; }
struct Role { int T1, GP, side, m2, dg, cch0; bool last, has2; };
__device__ __forceinline__ Role unpack_role(int x) {
  Role r; r.T1 = x & 15; r.GP = (x >> 4) & 7; r.side = (x >> 7) & 1; r.m2 = (x >> 8) & 63; r.dg = (x >> 14) & 3;
  r.has2 = (x >> 16) & 1; r.last = r.T1 == NT1 - 1; r.cch0 = 5 * (32 * r.dg + r.m2); return r;
}
__device__ __forceinline__ Role fresh_role(int x) { asm volatile("" : "+r"(x)); return unpack_role(__shfl_sync(0xffffffffu, x, 0)); }
#define ROLE(x) const Role R_ = fresh_role(x); const int T1 = R_.T1, GP = R_.GP, side = R_.side, m2 = R_.m2, dg = R_.dg, cch0 = R_.cch0; \
  const bool last = R_.last, has2 = R_.has2; (void)T1; (void)GP; (void)side; (void)m2; (void)dg; (void)cch0; (void)last; (void)has2;
__device__ __forceinline__ int n_to_t(int n) {
  int T = n / 160, nl = n - T * 160;
  int L = (T == NT1 - 1) ? 32 : 40;
  return T * 160 + L * ((nl & 7) >> 1) + 2 * (nl >> 3) + (nl & 1);
}

template<int TA> __device__ __forceinline__ void wgmma_n160(float (&d)[80], uint32_t alo, uint32_t ahi, uint32_t blo, uint32_t bhi){
  asm volatile("{\n.reg .b64 da, db;\nmov.b64 da, {%80,%81};\nmov.b64 db, {%82,%83};\n"
    "wgmma.mma_async.sync.aligned.m64n160k16.f32.bf16.bf16 {%0, %1, %2, %3, %4, %5, %6, %7, %8, %9, %10, %11, %12, %13, %14, %15, %16, %17, %18, %19, %20, %21, %22, %23, %24, %25, %26, %27, %28, %29, %30, %31, %32, %33, %34, %35, %36, %37, %38, %39, %40, %41, %42, %43, %44, %45, %46, %47, %48, %49, %50, %51, %52, %53, %54, %55, %56, %57, %58, %59, %60, %61, %62, %63, %64, %65, %66, %67, %68, %69, %70, %71, %72, %73, %74, %75, %76, %77, %78, %79}, da, db, 1, 1, 1, %84, 0;\n}\n"
    : "+f"(d[0]), "+f"(d[1]), "+f"(d[2]), "+f"(d[3]), "+f"(d[4]), "+f"(d[5]), "+f"(d[6]), "+f"(d[7]), "+f"(d[8]), "+f"(d[9]), "+f"(d[10]), "+f"(d[11]), "+f"(d[12]), "+f"(d[13]), "+f"(d[14]), "+f"(d[15]), "+f"(d[16]), "+f"(d[17]), "+f"(d[18]), "+f"(d[19]), "+f"(d[20]), "+f"(d[21]), "+f"(d[22]), "+f"(d[23]), "+f"(d[24]), "+f"(d[25]), "+f"(d[26]), "+f"(d[27]), "+f"(d[28]), "+f"(d[29]), "+f"(d[30]), "+f"(d[31]), "+f"(d[32]), "+f"(d[33]), "+f"(d[34]), "+f"(d[35]), "+f"(d[36]), "+f"(d[37]), "+f"(d[38]), "+f"(d[39]), "+f"(d[40]), "+f"(d[41]), "+f"(d[42]), "+f"(d[43]), "+f"(d[44]), "+f"(d[45]), "+f"(d[46]), "+f"(d[47]), "+f"(d[48]), "+f"(d[49]), "+f"(d[50]), "+f"(d[51]), "+f"(d[52]), "+f"(d[53]), "+f"(d[54]), "+f"(d[55]), "+f"(d[56]), "+f"(d[57]), "+f"(d[58]), "+f"(d[59]), "+f"(d[60]), "+f"(d[61]), "+f"(d[62]), "+f"(d[63]), "+f"(d[64]), "+f"(d[65]), "+f"(d[66]), "+f"(d[67]), "+f"(d[68]), "+f"(d[69]), "+f"(d[70]), "+f"(d[71]), "+f"(d[72]), "+f"(d[73]), "+f"(d[74]), "+f"(d[75]), "+f"(d[76]), "+f"(d[77]), "+f"(d[78]), "+f"(d[79])
    : "r"(alo), "r"(ahi), "r"(blo), "r"(bhi), "n"(TA));
}
template<int N> __device__ __forceinline__ void wgmma_rs_hi(float (&d)[64], uint32_t a0, uint32_t a1, uint32_t a2, uint32_t a3, uint32_t blo);
template<> __device__ __forceinline__ void wgmma_rs_hi<16>(float (&d)[64], uint32_t a0, uint32_t a1, uint32_t a2, uint32_t a3, uint32_t blo){
  asm volatile("{\n.reg .b64 db;\nmov.b64 db, {%12,8};\nwgmma.mma_async.sync.aligned.m64n16k16.f32.bf16.bf16 {%0, %1, %2, %3, %4, %5, %6, %7}, {%8,%9,%10,%11}, db, 1, 1, 1, 0;\n}\n"
    : "+f"(d[56]), "+f"(d[57]), "+f"(d[58]), "+f"(d[59]), "+f"(d[60]), "+f"(d[61]), "+f"(d[62]), "+f"(d[63])
    : "r"(a0), "r"(a1), "r"(a2), "r"(a3), "r"(blo));
}
template<> __device__ __forceinline__ void wgmma_rs_hi<32>(float (&d)[64], uint32_t a0, uint32_t a1, uint32_t a2, uint32_t a3, uint32_t blo){
  asm volatile("{\n.reg .b64 db;\nmov.b64 db, {%20,8};\nwgmma.mma_async.sync.aligned.m64n32k16.f32.bf16.bf16 {%0, %1, %2, %3, %4, %5, %6, %7, %8, %9, %10, %11, %12, %13, %14, %15}, {%16,%17,%18,%19}, db, 1, 1, 1, 0;\n}\n"
    : "+f"(d[48]), "+f"(d[49]), "+f"(d[50]), "+f"(d[51]), "+f"(d[52]), "+f"(d[53]), "+f"(d[54]), "+f"(d[55]), "+f"(d[56]), "+f"(d[57]), "+f"(d[58]), "+f"(d[59]), "+f"(d[60]), "+f"(d[61]), "+f"(d[62]), "+f"(d[63])
    : "r"(a0), "r"(a1), "r"(a2), "r"(a3), "r"(blo));
}
template<> __device__ __forceinline__ void wgmma_rs_hi<48>(float (&d)[64], uint32_t a0, uint32_t a1, uint32_t a2, uint32_t a3, uint32_t blo){
  asm volatile("{\n.reg .b64 db;\nmov.b64 db, {%28,8};\nwgmma.mma_async.sync.aligned.m64n48k16.f32.bf16.bf16 {%0, %1, %2, %3, %4, %5, %6, %7, %8, %9, %10, %11, %12, %13, %14, %15, %16, %17, %18, %19, %20, %21, %22, %23}, {%24,%25,%26,%27}, db, 1, 1, 1, 0;\n}\n"
    : "+f"(d[40]), "+f"(d[41]), "+f"(d[42]), "+f"(d[43]), "+f"(d[44]), "+f"(d[45]), "+f"(d[46]), "+f"(d[47]), "+f"(d[48]), "+f"(d[49]), "+f"(d[50]), "+f"(d[51]), "+f"(d[52]), "+f"(d[53]), "+f"(d[54]), "+f"(d[55]), "+f"(d[56]), "+f"(d[57]), "+f"(d[58]), "+f"(d[59]), "+f"(d[60]), "+f"(d[61]), "+f"(d[62]), "+f"(d[63])
    : "r"(a0), "r"(a1), "r"(a2), "r"(a3), "r"(blo));
}
template<> __device__ __forceinline__ void wgmma_rs_hi<64>(float (&d)[64], uint32_t a0, uint32_t a1, uint32_t a2, uint32_t a3, uint32_t blo){
  asm volatile("{\n.reg .b64 db;\nmov.b64 db, {%36,8};\nwgmma.mma_async.sync.aligned.m64n64k16.f32.bf16.bf16 {%0, %1, %2, %3, %4, %5, %6, %7, %8, %9, %10, %11, %12, %13, %14, %15, %16, %17, %18, %19, %20, %21, %22, %23, %24, %25, %26, %27, %28, %29, %30, %31}, {%32,%33,%34,%35}, db, 1, 1, 1, 0;\n}\n"
    : "+f"(d[32]), "+f"(d[33]), "+f"(d[34]), "+f"(d[35]), "+f"(d[36]), "+f"(d[37]), "+f"(d[38]), "+f"(d[39]), "+f"(d[40]), "+f"(d[41]), "+f"(d[42]), "+f"(d[43]), "+f"(d[44]), "+f"(d[45]), "+f"(d[46]), "+f"(d[47]), "+f"(d[48]), "+f"(d[49]), "+f"(d[50]), "+f"(d[51]), "+f"(d[52]), "+f"(d[53]), "+f"(d[54]), "+f"(d[55]), "+f"(d[56]), "+f"(d[57]), "+f"(d[58]), "+f"(d[59]), "+f"(d[60]), "+f"(d[61]), "+f"(d[62]), "+f"(d[63])
    : "r"(a0), "r"(a1), "r"(a2), "r"(a3), "r"(blo));
}
template<> __device__ __forceinline__ void wgmma_rs_hi<80>(float (&d)[64], uint32_t a0, uint32_t a1, uint32_t a2, uint32_t a3, uint32_t blo){
  asm volatile("{\n.reg .b64 db;\nmov.b64 db, {%44,8};\nwgmma.mma_async.sync.aligned.m64n80k16.f32.bf16.bf16 {%0, %1, %2, %3, %4, %5, %6, %7, %8, %9, %10, %11, %12, %13, %14, %15, %16, %17, %18, %19, %20, %21, %22, %23, %24, %25, %26, %27, %28, %29, %30, %31, %32, %33, %34, %35, %36, %37, %38, %39}, {%40,%41,%42,%43}, db, 1, 1, 1, 0;\n}\n"
    : "+f"(d[24]), "+f"(d[25]), "+f"(d[26]), "+f"(d[27]), "+f"(d[28]), "+f"(d[29]), "+f"(d[30]), "+f"(d[31]), "+f"(d[32]), "+f"(d[33]), "+f"(d[34]), "+f"(d[35]), "+f"(d[36]), "+f"(d[37]), "+f"(d[38]), "+f"(d[39]), "+f"(d[40]), "+f"(d[41]), "+f"(d[42]), "+f"(d[43]), "+f"(d[44]), "+f"(d[45]), "+f"(d[46]), "+f"(d[47]), "+f"(d[48]), "+f"(d[49]), "+f"(d[50]), "+f"(d[51]), "+f"(d[52]), "+f"(d[53]), "+f"(d[54]), "+f"(d[55]), "+f"(d[56]), "+f"(d[57]), "+f"(d[58]), "+f"(d[59]), "+f"(d[60]), "+f"(d[61]), "+f"(d[62]), "+f"(d[63])
    : "r"(a0), "r"(a1), "r"(a2), "r"(a3), "r"(blo));
}
template<> __device__ __forceinline__ void wgmma_rs_hi<96>(float (&d)[64], uint32_t a0, uint32_t a1, uint32_t a2, uint32_t a3, uint32_t blo){
  asm volatile("{\n.reg .b64 db;\nmov.b64 db, {%52,8};\nwgmma.mma_async.sync.aligned.m64n96k16.f32.bf16.bf16 {%0, %1, %2, %3, %4, %5, %6, %7, %8, %9, %10, %11, %12, %13, %14, %15, %16, %17, %18, %19, %20, %21, %22, %23, %24, %25, %26, %27, %28, %29, %30, %31, %32, %33, %34, %35, %36, %37, %38, %39, %40, %41, %42, %43, %44, %45, %46, %47}, {%48,%49,%50,%51}, db, 1, 1, 1, 0;\n}\n"
    : "+f"(d[16]), "+f"(d[17]), "+f"(d[18]), "+f"(d[19]), "+f"(d[20]), "+f"(d[21]), "+f"(d[22]), "+f"(d[23]), "+f"(d[24]), "+f"(d[25]), "+f"(d[26]), "+f"(d[27]), "+f"(d[28]), "+f"(d[29]), "+f"(d[30]), "+f"(d[31]), "+f"(d[32]), "+f"(d[33]), "+f"(d[34]), "+f"(d[35]), "+f"(d[36]), "+f"(d[37]), "+f"(d[38]), "+f"(d[39]), "+f"(d[40]), "+f"(d[41]), "+f"(d[42]), "+f"(d[43]), "+f"(d[44]), "+f"(d[45]), "+f"(d[46]), "+f"(d[47]), "+f"(d[48]), "+f"(d[49]), "+f"(d[50]), "+f"(d[51]), "+f"(d[52]), "+f"(d[53]), "+f"(d[54]), "+f"(d[55]), "+f"(d[56]), "+f"(d[57]), "+f"(d[58]), "+f"(d[59]), "+f"(d[60]), "+f"(d[61]), "+f"(d[62]), "+f"(d[63])
    : "r"(a0), "r"(a1), "r"(a2), "r"(a3), "r"(blo));
}
template<> __device__ __forceinline__ void wgmma_rs_hi<112>(float (&d)[64], uint32_t a0, uint32_t a1, uint32_t a2, uint32_t a3, uint32_t blo){
  asm volatile("{\n.reg .b64 db;\nmov.b64 db, {%60,8};\nwgmma.mma_async.sync.aligned.m64n112k16.f32.bf16.bf16 {%0, %1, %2, %3, %4, %5, %6, %7, %8, %9, %10, %11, %12, %13, %14, %15, %16, %17, %18, %19, %20, %21, %22, %23, %24, %25, %26, %27, %28, %29, %30, %31, %32, %33, %34, %35, %36, %37, %38, %39, %40, %41, %42, %43, %44, %45, %46, %47, %48, %49, %50, %51, %52, %53, %54, %55}, {%56,%57,%58,%59}, db, 1, 1, 1, 0;\n}\n"
    : "+f"(d[8]), "+f"(d[9]), "+f"(d[10]), "+f"(d[11]), "+f"(d[12]), "+f"(d[13]), "+f"(d[14]), "+f"(d[15]), "+f"(d[16]), "+f"(d[17]), "+f"(d[18]), "+f"(d[19]), "+f"(d[20]), "+f"(d[21]), "+f"(d[22]), "+f"(d[23]), "+f"(d[24]), "+f"(d[25]), "+f"(d[26]), "+f"(d[27]), "+f"(d[28]), "+f"(d[29]), "+f"(d[30]), "+f"(d[31]), "+f"(d[32]), "+f"(d[33]), "+f"(d[34]), "+f"(d[35]), "+f"(d[36]), "+f"(d[37]), "+f"(d[38]), "+f"(d[39]), "+f"(d[40]), "+f"(d[41]), "+f"(d[42]), "+f"(d[43]), "+f"(d[44]), "+f"(d[45]), "+f"(d[46]), "+f"(d[47]), "+f"(d[48]), "+f"(d[49]), "+f"(d[50]), "+f"(d[51]), "+f"(d[52]), "+f"(d[53]), "+f"(d[54]), "+f"(d[55]), "+f"(d[56]), "+f"(d[57]), "+f"(d[58]), "+f"(d[59]), "+f"(d[60]), "+f"(d[61]), "+f"(d[62]), "+f"(d[63])
    : "r"(a0), "r"(a1), "r"(a2), "r"(a3), "r"(blo));
}
template<> __device__ __forceinline__ void wgmma_rs_hi<128>(float (&d)[64], uint32_t a0, uint32_t a1, uint32_t a2, uint32_t a3, uint32_t blo){
  asm volatile("{\n.reg .b64 db;\nmov.b64 db, {%68,8};\nwgmma.mma_async.sync.aligned.m64n128k16.f32.bf16.bf16 {%0, %1, %2, %3, %4, %5, %6, %7, %8, %9, %10, %11, %12, %13, %14, %15, %16, %17, %18, %19, %20, %21, %22, %23, %24, %25, %26, %27, %28, %29, %30, %31, %32, %33, %34, %35, %36, %37, %38, %39, %40, %41, %42, %43, %44, %45, %46, %47, %48, %49, %50, %51, %52, %53, %54, %55, %56, %57, %58, %59, %60, %61, %62, %63}, {%64,%65,%66,%67}, db, 1, 1, 1, 0;\n}\n"
    : "+f"(d[0]), "+f"(d[1]), "+f"(d[2]), "+f"(d[3]), "+f"(d[4]), "+f"(d[5]), "+f"(d[6]), "+f"(d[7]), "+f"(d[8]), "+f"(d[9]), "+f"(d[10]), "+f"(d[11]), "+f"(d[12]), "+f"(d[13]), "+f"(d[14]), "+f"(d[15]), "+f"(d[16]), "+f"(d[17]), "+f"(d[18]), "+f"(d[19]), "+f"(d[20]), "+f"(d[21]), "+f"(d[22]), "+f"(d[23]), "+f"(d[24]), "+f"(d[25]), "+f"(d[26]), "+f"(d[27]), "+f"(d[28]), "+f"(d[29]), "+f"(d[30]), "+f"(d[31]), "+f"(d[32]), "+f"(d[33]), "+f"(d[34]), "+f"(d[35]), "+f"(d[36]), "+f"(d[37]), "+f"(d[38]), "+f"(d[39]), "+f"(d[40]), "+f"(d[41]), "+f"(d[42]), "+f"(d[43]), "+f"(d[44]), "+f"(d[45]), "+f"(d[46]), "+f"(d[47]), "+f"(d[48]), "+f"(d[49]), "+f"(d[50]), "+f"(d[51]), "+f"(d[52]), "+f"(d[53]), "+f"(d[54]), "+f"(d[55]), "+f"(d[56]), "+f"(d[57]), "+f"(d[58]), "+f"(d[59]), "+f"(d[60]), "+f"(d[61]), "+f"(d[62]), "+f"(d[63])
    : "r"(a0), "r"(a1), "r"(a2), "r"(a3), "r"(blo));
}

__device__ __forceinline__ float shfl_sel(float a, float b, bool p, int src) {
  float r;
  asm volatile("{\n.reg .pred P;\n.reg .f32 t;\nsetp.ne.u32 P, %3, 0;\nselp.f32 t, %1, %2, P;\nshfl.sync.idx.b32 %0, t, %4, 0x1f, 0xffffffff;\n}\n"
               : "=f"(r) : "f"(a), "f"(b), "r"((uint32_t)p), "r"(src));
  return r;
}
struct CvCtx {
  uint32_t koff, zero, so[4];
  int srcA, srcB;
  bool wrapA, s3, kodd;
};
struct CvPipe { float Ep[2], keep[2], send[2]; };
template <int LO> __device__ __forceinline__ void cv_copy(float (&acc)[64]) {
#pragma unroll
  for (int i = LO; i < 64; i++) { float t; asm volatile("mov.b32 %0, %1;" : "=f"(t) : "f"(acc[i]) : "memory"); acc[i] = t; }
}
template <int G> __device__ __forceinline__ void cv_raw(uint32_t (&A)[4][4], uint32_t kaddr) {
#pragma unroll
  for (int i = 0; i < 4; i++) {
    const uint32_t a = kaddr + (4 * G + i) * 128;
    A[i][0] = lds32(a); A[i][1] = lds32(a + 4); A[i][3] = lds32(a + 8);
  }
}
__device__ __forceinline__ void cv_form(uint32_t (&A)[4][4], uint32_t sel) {
#pragma unroll
  for (int i = 0; i < 4; i++) {
    asm volatile("prmt.b32 %0, %0, %1, %2;" : "+r"(A[i][0]) : "r"(A[i][1]), "r"(sel));
    asm volatile("prmt.b32 %0, %1, %2, %3;" : "=r"(A[i][2]) : "r"(A[i][1]), "r"(A[i][3]), "r"(sel));
  }
}
#define CVV 2
template <int G> __device__ __forceinline__ void cv_step(float (&acc)[64], uint32_t (&A)[4][4], CvPipe& s, const CvCtx& c, uint32_t cb, uint32_t stg) {
  constexpr int JA = G - 1, JB = G - 2, NH = CVV == 1 ? 4 : (CVV == 3 ? 2 : 1);
  const uint32_t db0 = desc_lo(cb + CV_U + 192, CV_PL);
  uint32_t B[4][4];
  float ra[4], rb[2];
  if constexpr (G < 8) {
    wgmma_fence();
#pragma unroll
    for (int i = 0; i < NH; i++) wgmma_rs_hi<128 - 16 * (G & 7)>(acc, A[i][0], A[i][1], A[i][2], A[i][3], db0 - 4 * i);
    wgmma_commit();
    __syncwarp();
  }
  if constexpr (JA >= 0 && JA < 8) {
#pragma unroll
    for (int x = 0; x < 4; x++) {
      const int i = 8 * JA + 4 * (x >> 1) + 2 * (x & 1) + 1;
      ra[x] = shfl_sel(i >= 4 ? acc[i >= 4 ? i - 4 : 0] : 0.f, acc[i], c.wrapA, c.srcA);
    }
  }
  if constexpr (JB >= 0) {
#pragma unroll
    for (int h = 0; h < 2; h++) rb[h] = __shfl_sync(0xffffffffu, s.send[h], c.srcB);
  }
  if constexpr (G < 7) cv_raw<G + 1>(B, cb + c.koff);
  uint32_t z = 0;
  if constexpr (G < 8 && NH < 4) {
    __syncwarp();
    wgmma_fence();
#pragma unroll
    for (int i = NH; i < 4; i++) wgmma_rs_hi<128 - 16 * (G & 7)>(acc, A[i][0], A[i][1], A[i][2], A[i][3], db0 - 4 * i);
    wgmma_commit();
    asm volatile("mov.u32 %0, %%clock;" : "=r"(z)::"memory");
    z &= c.zero;
  }
  const float one = __uint_as_float(0x3f800000u | z);
  if constexpr (G < 7) cv_form(B, 0x5432u | z);
  if constexpr (JB >= 0) sts32(stg + ((JB & 1) ? c.so[JB >> 1] >> 16 : c.so[JB >> 1] & 0xffff), pack_bf16(fmaf(rb[0], one, s.keep[0]), fmaf(rb[1], one, s.keep[1])));
  if constexpr (JA >= 0 && JA < 8) {
#pragma unroll
    for (int h = 0; h < 2; h++) {
      const float ev = fmaf(ra[h], one, acc[8 * JA + 2 * h]), od = fmaf(ra[2 + h], one, acc[8 * JA + 4 + 2 * h]);
      s.send[h] = c.kodd ? ev : (c.s3 ? s.Ep[h] : od);
      s.keep[h] = c.kodd ? od : ev;
      s.Ep[h] = od;
    }
  }
  if constexpr (G < 8) { __syncwarp(); wgmma_wait<0>(); cv_copy<8 * (G & 7)>(acc); }
  if constexpr (G < 9) cv_step<G + 1>(acc, B, s, c, cb, stg);
}
__device__ __forceinline__ uint32_t cv_stage(int slot) { return sb + (slot < 4 ? 40960 + slot * 4096 : 180224); }
__device__ __forceinline__ void cv_setup(CvCtx& c) {
  const int tid = tid_opaque() & 127, w = tid >> 5, lane = tid & 31, r = lane >> 2, q = lane & 3;
  const int i0 = (r >> 1) & 1, i1 = r >> 2;
  c.koff = CV_K - 32 + 4 * (8 * (r >> 1) + 2 * w + (r & 1) + 2 * q);
  c.srcA = i0 ? lane - 8 : lane + 8 - q + ((q + 3) & 3);
  c.wrapA = i0 && q == 3;
  c.srcB = i1 == 0 ? (lane - q + 16 + ((q + 3) & 3)) : (lane - q - 16 + ((q + 1) & 3));
  c.s3 = (i1 == 1 && q == 3); c.kodd = (i1 == 1 && q < 3);
  c.zero = lds32(sb + EP_OFF + 24);
  const int tb = 16 * (2 * (i1 == 0 ? q : 4 + ((q + 1) & 3)) + i0) + 4 * w + 2 * (r & 1);
#pragma unroll
  for (int J = 0; J < 8; J++) {
    const int t = 256 * J + tb, T = t / 160, tl = t - T * 160;
    const int qq = (T == NT1 - 1) ? (tl >> 5) : (tl / 40);
    int ck = 20 * T + ((tl - qq * ((T == NT1 - 1) ? 32 : 40)) >> 1);
    ck ^= (ck >> 2) & 6;
    const uint32_t o = ck * 16 + qq * 4;
    if (J & 1) c.so[J >> 1] |= o << 16; else c.so[J >> 1] = o;
  }
}
__device__ __forceinline__ void conv_channel(int slot, const CvCtx& c) {
  const uint32_t cb = sb + CV_OFF + slot * CV_B;
  float acc[64];
  CvPipe s;
  s.Ep[0] = s.Ep[1] = 0.f;
  uint32_t A[4][4];
#pragma unroll
  for (int i = 0; i < 64; i++) acc[i] = 0.f;
  mbar_wait(bars + 8 * (B_CVFULL + slot));
  cv_raw<0>(A, cb + c.koff);
  cv_form(A, 0x5432u);
  cv_copy<0>(acc);
  cv_step<0>(acc, A, s, c, cb, cv_stage(slot));
  fence_async_smem();
  mbar_arrive(bars + 8 * (B_CVDONE + slot));
}

template <int W> struct KvRegs { uint32_t k[19][W], v[16][W], s[W][4]; };
template <int W> __device__ __forceinline__ void kv_load(int m, int cl, KvRegs<W>& x) {
  const int lane = tid_opaque() & 31, tg = lane >> 3;
  const uint32_t pb = sb + KS_OFF + (cl >> 5) * KV_PIECE + 2 * (cl & 31) + 4 * W * (lane & 7);
  const uint32_t ka = pb + tg * 1216, va = pb + 4864 + tg * 1088 + 64;
  const uint32_t kh = (m == 0 && tg > 0) ? ka - 192 : ka;
#pragma unroll
  for (int c = 0; c < W; c++) {
    const float4 t = lds128f(sb + TAP_OFF + 8 * cl + 16 * (W * (lane & 7) + c));
    x.s[c][0] = __float_as_uint(t.x); x.s[c][1] = __float_as_uint(t.y); x.s[c][2] = __float_as_uint(t.z); x.s[c][3] = __float_as_uint(t.w);
  }
  mbar_wait(bars + 8 * (B_KV + (cl >> 5)));
#pragma unroll
  for (int i = 0; i < 19; i++) {
    const uint32_t a = (i < 3 ? kh : ka) + i * 64;
    if (W == 2) { float2 t = lds64f(a); x.k[i][0] = __float_as_uint(t.x); x.k[i][W - 1] = __float_as_uint(t.y); }
    else x.k[i][0] = lds32(a);
  }
#pragma unroll
  for (int i = 0; i < 16; i++) {
    if (W == 2) { float2 t = lds64f(va + i * 64); x.v[i][0] = __float_as_uint(t.x); x.v[i][W - 1] = __float_as_uint(t.y); }
    else x.v[i][0] = lds32(va + i * 64);
  }
}
template <int W> __device__ __forceinline__ void kv_finish(int m, int c0, KvRegs<W>& x) {
  const int lane = tid_opaque() & 31;
  uint8_t* dst = g_kv + ((c0 + 2 * W * (lane & 7)) * 4096 + (4 * m + (lane >> 3)) * 16);
#pragma unroll
  for (int c = 0; c < W; c++) {
    const uint32_t w0 = __byte_perm(x.s[c][0], x.s[c][2], 0x5410), w1 = __byte_perm(x.s[c][0], x.s[c][2], 0x7632);
    const uint32_t w2 = __byte_perm(x.s[c][1], x.s[c][3], 0x5410), w3 = __byte_perm(x.s[c][1], x.s[c][3], 0x7632);
#pragma unroll
    for (int i = 0; i < 16; i++) {
      uint32_t a = hmul2(x.k[i][c], w3);
      a = hadd2(a, hmul2(x.k[i + 1][c], w2)); a = hadd2(a, hmul2(x.k[i + 2][c], w1)); a = hadd2(a, hmul2(x.k[i + 3][c], w0));
      x.v[i][c] = hmul2(a, x.v[i][c]);
    }
#pragma unroll
    for (int e = 0; e < 2; e++)
#pragma unroll
      for (int f = 0; f < 2; f++) {
        uint32_t o[4];
#pragma unroll
        for (int qq = 0; qq < 4; qq++) o[qq] = __byte_perm(x.v[15 - 4 * qq - 2 * f][c], x.v[14 - 4 * qq - 2 * f][c], e ? 0x7632 : 0x5410);
        *(uint4*)(dst + (2 * c + e) * 4096 + f * 2048) = make_uint4(o[0], o[1], o[2], o[3]);
      }
  }
}
__device__ __forceinline__ void ln_finish(float s1, float s2, float& mean, float& rstd) {
  mean = s1 * (1.f / 640.f);
  const float v = fmaxf(fmaf(-mean, mean, s2 * (1.f / 640.f)), 0.f) + 1e-5f;
  asm("rsqrt.approx.ftz.f32 %0, %1;" : "=f"(rstd) : "f"(v));
}
__device__ __forceinline__ void stat_table(int T1, unsigned want, int l, int w) {
#pragma unroll 1
  for (int g = w; g < (T1 == NT1 - 1 ? 4 : 5); g += 4) {
    const int n = 32 * g + (tid_opaque() & 31);
    const uint4* rp = &g_stats[8 * l * SEQ + 160 * T1 + n];
    float a[4], b[4];
    uint32_t it = 0;
    while (true) {
      bool ok = true;
#pragma unroll
      for (int i = 0; i < 4; i++) ok &= (rec_ld(rp + SEQ * i, a[i], b[i]) == want);
      if (__all_sync(0xffffffffu, ok)) break;
      trap_if(++it > SPIN_LIMIT);
    }
    float m, rs;
    ln_finish((a[0] + a[1]) + (a[2] + a[3]), (b[0] + b[1]) + (b[2] + b[3]), m, rs);
    sts64f(sb + STAB_OFF + n * 8, rs, -m * rs);
  }
  mbar_arrive(bars + 8 * (B_STAB + l));
}

template <bool FIRST>
__device__ __forceinline__ void stats_publish(int which, int n0, int dg, unsigned tag, const float (&acc)[80]) {
  const int q = tid_opaque() & 3, h = q & 1;
  float s1[2] = {0.f, 0.f}, s2[2] = {0.f, 0.f}, t1[2] = {0.f, 0.f}, t2[2] = {0.f, 0.f};
#pragma unroll
  for (int j = 0; j < 20; j++)
#pragma unroll
    for (int y = 0; y < 2; y++) {
      const float a = acc[4 * j + 2 * y], b = acc[4 * j + 2 * y + 1];
      s1[y] += a; t1[y] += b; s2[y] = fmaf(a, a, s2[y]); t2[y] = fmaf(b, b, t2[y]);
    }
#pragma unroll
  for (int y = 0; y < 2; y++) { s1[y] += t1[y]; s2[y] += t2[y]; }
  float a = (h ? s1[1] : s1[0]) + __shfl_xor_sync(0xffffffffu, h ? s1[0] : s1[1], 1);
  float b = (h ? s2[1] : s2[0]) + __shfl_xor_sync(0xffffffffu, h ? s2[0] : s2[1], 1);
  a += __shfl_xor_sync(0xffffffffu, a, 2);
  b += __shfl_xor_sync(0xffffffffu, b, 2);
  if (FIRST) {
    rec_st(&g_stats[((q >> 1) * 4 + dg) * SEQ + n0 + 8 * h], a, b, q < 2 ? tag : tag - 1);
    rec_st(&g_stats[((q >> 1) * 4 + 8 + dg) * SEQ + n0 + 8 * h], a, b, tag - 1);
  } else if (q < 2) rec_st(&g_stats[(which * 4 + dg) * SEQ + n0 + 8 * h], a, b, tag);
}
__device__ __forceinline__ void stats_get(int which, int n0, unsigned tag, float (&mean)[2], float (&rstd)[2]) {
  const uint4* p0 = &g_stats[(which * 4 + (tid_opaque() & 3)) * SEQ + n0];
  float a[2], b[2];
  uint32_t it = 0;
  while (true) {
    const unsigned t0 = rec_ld(p0, a[0], b[0]), t1 = rec_ld(p0 + 8, a[1], b[1]);
    if (__all_sync(0xffffffffu, t0 == tag && t1 == tag)) break;
    trap_if(++it > SPIN_LIMIT);
  }
#pragma unroll
  for (int o = 1; o < 4; o <<= 1)
#pragma unroll
    for (int h = 0; h < 2; h++) { a[h] += __shfl_xor_sync(0xffffffffu, a[h], o); b[h] += __shfl_xor_sync(0xffffffffu, b[h], o); }
#pragma unroll
  for (int h = 0; h < 2; h++) ln_finish(a[h], b[h], mean[h], rstd[h]);
}
__device__ __forceinline__ void x0_load(float (&acc)[80]) {
  const int t = tid_opaque() & 127;
  const uint32_t xa = sb + XT_OFF + (16 * (t >> 5) + ((t & 31) >> 2)) * 320 + 8 * (t & 3);
  mbar_wait(bars + 8 * B_XT);
#pragma unroll
  for (int h = 0; h < 2; h++)
#pragma unroll
    for (int J = 0; J < 10; J++) {
      const float2 v = lds64f(xa + h * 2560 + 32 * J);
      const uint32_t x = __float_as_uint(v.x), y = __float_as_uint(v.y);
      acc[8 * J + 2 * h] = bf_lo(x); acc[8 * J + 2 * h + 1] = bf_hi(x);
      acc[8 * J + 4 + 2 * h] = bf_lo(y); acc[8 * J + 4 + 2 * h + 1] = bf_hi(y);
    }
}

__global__ void __launch_bounds__(512, 1) fused_kernel(const __grid_constant__ Params p) {
  extern __shared__ __align__(1024) uint8_t smem_raw[];
  const int tid = threadIdx.x, lane = tid & 31;
  const int wid = __shfl_sync(0xffffffffu, tid >> 5, 0), wg = wid >> 2;
  unsigned smid; asm volatile("mov.u32 %0, %%smid;" : "=r"(smid));
  trap_if(smid >= 132 || smem_u32(smem_raw) != sb);
  int role;
  {
  const int side = smid & 1;
  int gpc, gi;
  {
    int tpc = smid >> 1;
    if (tpc < 32) { gpc = tpc & 7; gi = tpc >> 3; }
    else if (tpc < 60) { gpc = 1 + (tpc - 32) % 7; gi = 4 + (tpc - 32) / 7; }
    else if (tpc < 62) { gpc = tpc - 54; gi = 8; }
    else { gpc = 0; gi = tpc - 58; }
  }
  const int pos = 8 * gpc + gi + (gpc == 7 ? 1 : 0);
  if (pos == 65) {
    if (tid < 32) {
      const unsigned tag = ld_rlx(g_epoch);
      for (int i = lane; i < NT1 * 16; i += 32)
        if ((i & 15) < 10) { uint32_t it = 0; while ((int)(ld_rlx(&g_hflag[((i >> 4) * 32 + (i & 15)) * 8]) - tag) < 0) { __nanosleep(500); trap_if(++it > SPIN_LIMIT); } }
    }
    return;
  }
  int T1, GP;
  if (pos < 52) { int hh = pos / 26, x = pos - 26 * hh; T1 = x >> 1; GP = 2 * hh + (x & 1); }
  else { T1 = pos - 52; GP = 4; }
  const bool last = (T1 == NT1 - 1);
  const bool has2 = gi < 8;
  const int m2 = 8 * (gpc >> 1) + gi, dg = 2 * (gpc & 1) + side;
  role = T1 | (GP << 4) | (side << 7) | (m2 << 8) | (dg << 14) | ((int)has2 << 16);

  const int cch0 = 5 * (32 * dg + m2);
  if (wg < 2) {
    if (wid < 2) {
      const int ch = 128 * GP + 64 * wid + 32 * side + lane;
      uint32_t r0 = ldv16(p.lre + ch), r1 = ldv16(p.lim + ch), r2 = ldv16(p.logdt + ch);
      asm volatile("bar.arrive 5, 512;" : "+r"(r0), "+r"(r1), "+r"(r2)::"memory");
      const float lr = bf_lo(r0), li = bf_lo(r1), ld = bf_lo(r2);
      const float dt = __bfloat162float(__float2bfloat16_rn(expf(ld)));
      const float mag = expf(dt * lr);
      float sn, cs; sincospif(dt * li * 0.31830988618379067f, &sn, &cs);
      const float ar = mag * cs, ai = mag * sn;
      const float inv = 2.f / (lr * lr + li * li);
      const uint32_t ad = sb + CTAB_OFF + (32 * wid + lane) * 24;
      sts64f(ad, ar, ai);
      sts64f(ad + 8, ((ar - 1.f) * lr + ai * li) * inv, (ai * lr - (ar - 1.f) * li) * inv);
      if (tid == 0) TS(46);
      __syncwarp();
      bar_sync(7, 96);
      mbar_arrive(bars + 8 * B_CTAB);
    } else {
      if (elect_one()) {
        if (wid < 5) {
#pragma unroll
          for (int i = 0; i < 27; i++) mbar_init(bars + 8 * (4 + 27 * (wid - 2) + i), 2);
        } else {
#pragma unroll
          for (int i = 0; i < 15; i++) mbar_init(bars + 8 * (85 + 15 * (wid - 5) + i), 1);
        }
        asm volatile("fence.mbarrier_init.release.cluster;" ::: "memory");
      }
      __syncwarp();
      bar_sync(5, 512);
      if (wid == 2) { asm volatile("bar.arrive 6, 64;" ::: "memory"); asm volatile("bar.arrive 7, 96;" ::: "memory"); }
    }
  } else if (wg == 2 || wid == 14) {
    uint2 bv[2][5];
    const int c = wid == 14 ? 4 : wid - 8;
    const unsigned tag0 = ld_rlx(g_epoch);
#pragma unroll
    for (int x = 0; x < 2; x++)
#pragma unroll
      for (int i = 0; i < 5; i++) bv[x][i] = ldv64((const uint2*)((x ? p.bim : p.bre) + (has2 ? cch0 + c : 0) * DM) + lane + 32 * i);
    bar_sync(5, 512);
#pragma unroll
    for (int i = 0; i < 5; i++) asm volatile("" : "+r"(bv[0][i].x), "+r"(bv[0][i].y), "+r"(bv[1][i].x), "+r"(bv[1][i].y)::"memory");
    if (has2) {
      float sv[2];
#pragma unroll
      for (int x = 0; x < 2; x++) {
        float a = 0.f;
#pragma unroll
        for (int i = 0; i < 5; i++) a += (bf_lo(bv[x][i].x) + bf_hi(bv[x][i].x)) + (bf_lo(bv[x][i].y) + bf_hi(bv[x][i].y));
        sv[x] = a;
      }
#pragma unroll
      for (int o = 16; o > 0; o >>= 1) { sv[0] += __shfl_xor_sync(0xffffffffu, sv[0], o); sv[1] += __shfl_xor_sync(0xffffffffu, sv[1], o); }
      if (lane < 2) rec_st(&g_sB[(cch0 + c) * 2 + lane], sv[0], sv[1], tag0);
      if (tid == 256) TS(47);
    }
  } else if (wid == 13) {
    uint4 tv[3];
    const uint32_t e0 = ld_rlx(g_epoch);
    uint32_t e1 = ldv16(p.ssmD + min(cch0 + lane, 639));
    const uint4 dv = ldv128((const uint4*)(p.dskip + 160 * dg) + min(lane, 19));
#pragma unroll
    for (int i = 0; i < 3; i++) tv[i] = ldv128((const uint4*)(p.shiftk + 640 * dg) + min(lane + 32 * i, 79));
    bar_sync(5, 512);
    asm volatile("" : "+r"(e1)::"memory");
    sts128(sb + DTAB_OFF + 16 * min(lane, 19), dv);
#pragma unroll
    for (int i = 0; i < 3; i++) sts128(sb + TAP_OFF + 16 * min(lane + 32 * i, 79), tv[i]);
    if (lane < 7) sts32(sb + EP_OFF + 4 * lane, lane < 5 ? e1 << 16 : (lane == 5 ? e0 : 0u));
    mbar_arrive(bars + 8 * B_CTAB);
    __syncwarp();
    if (lane == 0) { mbar_arrive(bars + 8 * B_EP); TS(53); }
  } else if (wid == 12) {
    if (elect_one()) {
#pragma unroll
      for (int k = 0; k < S1; k++) mbar_init(bars + 8 * (B_G1FULL + k), 1);
#pragma unroll
      for (int k = 0; k < 19; k++) mbar_init(bars + 8 * (B_XT + k), 1);
      asm volatile("fence.mbarrier_init.release.cluster;" ::: "memory");
      TS(45);
    }
    __syncwarp();
    asm volatile("bar.arrive 5, 512;" ::: "memory");
    if (elect_one()) {
#pragma unroll 1
      for (int k = 0; k < S1; k++) {
        const uint32_t fb = bars + 8 * (B_G1FULL + k);
        mbar_expect_tx(fb, G1_STAGE);
        tma4(sb + k * G1_STAGE + G1_XOFF, last ? &p.mXl : &p.mX, 64 * k, 0, 0, last ? 0 : 80 * T1, fb);
        tma5(sb + k * G1_STAGE, &p.mB, 64 * k, 0, 0, 4 * side, 2 * GP, fb);
      }
      TS(44);
    }
    __syncwarp();
    bar_sync(6, 64);
  } else {
    if (elect_one()) {
#pragma unroll
      for (int i = 0; i < 13; i++) mbar_init(bars + 8 * (B_CVDONE + i), B_CVDONE + i == B_STAB ? 160 : (B_CVDONE + i == B_CTAB ? 96 : 128));
      asm volatile("fence.mbarrier_init.release.cluster;" ::: "memory");
    }
    __syncwarp();
    bar_sync(5, 512);
  }
  if (tid == 128) TS(0);
  }

  if (wg == 3) {
    asm volatile("setmaxnreg.dec.sync.aligned.u32 56;");
    ROLE(role)
    const int pw = wid & 3;
    if (pw == 3 && has2) {
      mbar_wait(bars + 8 * (B_G1FULL + 0));
      if (elect_one()) {
        mbar_expect_tx(bars + 8 * B_XT, 20480);
#pragma unroll
        for (int h = 0; h < 2; h++) {
          const int ng = 8 * m2 + 4 * h, T = ng / 20;
          tma4(sb + XT_OFF + h * 10240, T == NT1 - 1 ? &p.mXtl : &p.mXt, 160 * dg, 0, 0, T == NT1 - 1 ? ng - 240 : ng + 60 * T, bars + 8 * B_XT);
        }
      }
#pragma unroll 1
      for (int c = 0; c < 5; c++) {
        mbar_wait(bars + 8 * (c == 0 ? B_G1FULL + 2 : B_XT + (c < 2 ? 0 : c - 1)));
        if (elect_one()) {
          const uint32_t fb = bars + 8 * (B_KV + c);
          mbar_expect_tx(fb, KV_PIECE);
          tma3(sb + KS_OFF + c * KV_PIECE, &p.mK, 160 * dg + 32 * c, 64 * m2 - 3, 0, fb);
          tma3(sb + KS_OFF + c * KV_PIECE + 4864, &p.mV, 160 * dg + 32 * c, 64 * m2 - 1, 0, fb);
        }
      }
    }
    unsigned tag = 0;
    if (pw > 0) { mbar_wait(bars + 8 * B_EP); tag = lds32(sb + EP_OFF + 20); }
    if (pw == 2) {
#pragma unroll 1
      for (int i = 0; i < 2; i++) {
        float a, b;
        rec_poll(&g_sB[(128 * GP + 64 * i + 32 * side + lane) * 2], tag, a, b);
        sts64f(sb + CTAB_OFF + (32 * i + lane) * 24 + 16, p.swap ? b : a, p.swap ? a : b);
      }
      mbar_arrive(bars + 8 * B_STAB);
      if (lane == 0) TS(54);
    }
    if (pw >= 2 && has2) {
      KvRegs<1> x;
      kv_load<1>(m2, 128 + 16 * (pw - 2), x);
      kv_finish<1>(m2, 160 * dg + 128 + 16 * (pw - 2), x);
      if (tid == 448) TS(51);
      bar_sync(3, 192);
      if (tid == 448) { mbar_arrive(bars + 8 * B_PREP); st_rel(&g_kvflag[(dg * 32 + m2) * 8], tag); TS(30); }
      __syncwarp();
    }
    if (pw == 0) {
      if (elect_one()) {
#pragma unroll 1
        for (int l = 0; l < 2; l++) {
          const uint32_t fb0 = bars + 8 * (B_G1FULL + 10 * l), wb = bars + 8 * (B_G1DONE + 9 * l - S1);
          const uint32_t free0 = bars + 8 * (has2 ? B_G2DONE + 19 : B_G1DONE + 9);
          uint32_t dst = sb;
#pragma unroll 1
          for (int k = l == 0 ? S1 : 0; k < 10; k++) {
            mbar_wait(k >= S1 + l ? wb + 8 * k : (k < WPF1 || !has2 ? free0 : bars + 8 * (B_GO + 1)));
            mbar_expect_tx(fb0 + 8 * k, 16384);
            tma5(dst, &p.mB, 64 * k, 0, 0, 4 * side, 2 * GP, fb0 + 8 * k);
            dst += G1_STAGE; if (dst == sb + (S1 + l) * G1_STAGE) dst = sb;
          }
          if (has2) {
            const uint32_t fb2 = bars + 8 * (B_G2FULL + 20 * l), wb2 = bars + 8 * (B_G2DONE + 19 * l - 6);
            dst = sb + G2_WOFF;
            int kc = 0;
#pragma unroll 1
            for (int k = 0; k < 20; k++) {
              mbar_wait(k >= 6 + l ? wb2 + 8 * k : (k == 5 ? bars + 8 * B_XFREE : (k < WPF2 ? bars + 8 * (B_G1DONE + 10 * l + 9) : bars + 8 * (B_GO + 2 * l))));
              mbar_expect_tx(fb2 + 8 * k, G2_WB);
              tma5(dst, &p.mCre + (k & 1), kc, 0, 0, 0, 10 * dg, fb2 + 8 * k);
              kc += (k & 1) << 7; if (k == 9) kc = 64;
              dst += G2_WB; if (dst == sb + G2_WOFF + (6 + l) * G2_WB) dst = sb + G2_WOFF;
            }
          }
        }
      }
    } else if (pw == 1) {
#pragma unroll 1
      for (int l = 0; l < 2; l++) {
        if (l == 0) {
          if (elect_one()) {
            uint32_t dst = sb + G1_XOFF;
#pragma unroll 1
            for (int k = S1; k < 10; k++) {
              mbar_wait(bars + 8 * (B_G1DONE + k - S1));
              mbar_expect_tx(bars + 8 * (B_G1FULL + k), 20480);
              tma4(dst, last ? &p.mXl : &p.mX, 64 * k, 0, 0, last ? 0 : 80 * T1, bars + 8 * (B_G1FULL + k));
              dst += G1_STAGE; if (k == 2 * S1 - 1) dst = sb + G1_XOFF;
            }
          }
        } else {
          mbar_wait(bars + 8 * (has2 ? B_G2DONE + 19 : B_G1DONE + 9));
          const int mlo = (160 * T1) >> 6, nf = last ? 8 : 12;
          flag_poll(&g_uflag[(4 * mlo + min(lane, nf - 1)) * 8], tag);
          fence_async_global();
          if (elect_one()) {
            TS(20);
            const int bytes = last ? 16384 : 20480;
            const uint8_t* src = g_u + T1 * 204800;
            uint32_t dst = sb + G1_XOFF;
#pragma unroll 1
            for (int k = 0; k < 10; k++) {
              if (k > S1) mbar_wait(bars + 8 * (B_G1DONE + 9 - S1 + k));
              mbar_expect_tx(bars + 8 * (B_G1FULL + 10 + k), bytes);
              bulk_g2s(dst, src, bytes, bars + 8 * (B_G1FULL + 10 + k));
              src += 20480; dst += G1_STAGE; if (k == S1) dst = sb + G1_XOFF;
            }
          }
        }
        __syncwarp();
        if (has2) {
          mbar_wait(bars + 8 * (B_G1DONE + 10 * l + 9));
          const int Tlo = (64 * m2) / 160, Thi = (64 * m2 + 63) / 160;
          flag_poll(&g_hflag[(((l * NT1 + (lane < 16 ? Tlo : Thi)) * 2) * 16 + min(lane & 15, 9)) * 8], tag);
          fence_async_global();
          if (elect_one()) {
            TS(21 + 2 * l);
            const uint32_t fb2 = bars + 8 * (B_G2FULL + 20 * l), wb2 = bars + 8 * (B_G2DONE + 18 * l - SX2);
            const uint8_t* src = g_h + (l * 32 + m2) * 163840;
            uint32_t dst = sb;
#pragma unroll 1
            for (int k = 0; k < 20; k++) {
              if (k >= SX2 + 2 * l) mbar_wait(wb2 + 8 * k);
              if (k == 10) { mbar_wait(bars + 8 * (B_H1 + l)); fence_async_global(); }
              mbar_expect_tx(fb2 + 8 * k, G2_XB);
              bulk_g2s(dst, src, G2_XB, fb2 + 8 * k);
              src += 8192; dst += G2_XB; if (dst == sb + (SX2 + 2 * l) * G2_XB) dst = sb;
            }
          }
          __syncwarp();
        }
      }
    } else if (pw == 2) {
#pragma unroll 1
      for (int l = 0; l < 2; l++) {
        mbar_wait(bars + 8 * (B_HST + 2 * l));
        mbar_wait(bars + 8 * (B_HST + 2 * l + 1));
        __syncwarp();
        if (lane < 2) st_rel(&g_hflag[(((l * NT1 + T1) * 2 + lane) * 16 + 2 * GP + side) * 8], tag);
        if (lane == 0) TS(6 + 8 * l);
        __syncwarp();
        if (l == 0 && has2 && elect_one()) {
#pragma unroll 1
          for (int c = 0; c < 5; c++) {
            mbar_wait(bars + 8 * (B_CVDONE + c));
            bulk_s2g(g_G + (cch0 + c) * 4096, cv_stage(c), 4096);
          }
          asm volatile("cp.async.bulk.commit_group;" ::: "memory");
          asm volatile("cp.async.bulk.wait_group 0;" ::: "memory");
          fence_async_global();
          st_rel(&g_gflag[(dg * 32 + m2) * 8], tag);
        }
        __syncwarp();
      }
    } else if (has2) {
      mbar_wait(bars + 8 * B_PREP);
#pragma unroll
      for (int c = 0; c < 5; c++) {
        const uint32_t cb = sb + CV_OFF + c * CV_B;
        const uint32_t a = lane < 8 ? cb + 16 * lane : (lane < 20 ? cb + CV_U + 16 * (lane - 8) : cb + CV_U + CV_PL + 16 * (lane - 20));
        asm volatile("st.shared.v4.u32 [%0], {%1,%1,%1,%1};" ::"r"(a), "r"(0) : "memory");
      }
      fence_async_smem();
      __syncwarp();
#pragma unroll 1
      for (int c = 0; c < 5; c++) {
        if (c >= 2) mbar_wait(bars + 8 * (B_TAPS + c - 2));
        if (elect_one()) {
          mbar_expect_tx(bars + 8 * (B_TAPS + c), 4096);
          bulk_g2s(sb + CV_OFF + c * CV_B + CV_K, p.ssmk + (size_t)(cch0 + c) * SEQ, 4096, bars + 8 * (B_TAPS + c));
        }
      }
      if (elect_one()) {
        asm volatile("prefetch.tensormap [%0];" ::"l"(&p.mCre) : "memory");
        asm volatile("prefetch.tensormap [%0];" ::"l"(&p.mCim) : "memory");
        asm volatile("prefetch.tensormap [%0];" ::"l"(&p.mG) : "memory");
      }
      mbar_wait(bars + 8 * (B_TAPS + 3));
      mbar_wait(bars + 8 * (B_TAPS + 4));
      if (lane < 5) {
        const uint32_t a = sb + CV_OFF + lane * CV_B + CV_K, w0 = lds32(a);
        sts32(a, (w0 & 0xffff0000u) | (pack_bf16(bf_lo(w0) + __uint_as_float(lds32(sb + EP_OFF + 4 * lane)), 0.f) & 0xffffu));
      }
      flag_poll(&g_kvflag[(dg * 32 + lane) * 8], tag);
      __syncwarp();
      fence_async_global();
      if (lane == 0) TS(28);
      if (elect_one()) {
#pragma unroll
        for (int c = 0; c < 5; c++) {
          const uint32_t fb = bars + 8 * (B_CVFULL + c), cb = sb + CV_OFF + c * CV_B + CV_U + 192;
          mbar_expect_tx(fb, 4096);
          bulk_g2s(cb, g_kv + (size_t)(cch0 + c) * 4096, 2048, fb);
          bulk_g2s(cb + CV_PL, g_kv + (size_t)(cch0 + c) * 4096 + 2048, 2048, fb);
        }
      }
      const unsigned* hf = &g_hflag[(((lane < 16 ? (64 * m2) / 160 : (64 * m2 + 63) / 160) * 2 + 1) * 16 + min(lane & 15, 9)) * 8];
      mbar_wait(bars + 8 * (B_CVDONE + 0));
      if (elect_one()) { l2_prefetch(p.cre + (size_t)cch0 * DM, 6400); l2_prefetch(p.cim + (size_t)cch0 * DM, 6400); }
      flag_poll(hf, tag);
      __syncwarp();
      if (lane == 0) { mbar_arrive(bars + 8 * B_H1); TS(22); }
      mbar_wait(bars + 8 * (B_CVDONE + 4));
      flag_poll(&g_gflag[(dg * 32 + lane) * 8], tag);
      __syncwarp();
      fence_async_global();
      if (lane == 0) TS(29);
      if (elect_one()) {
        mbar_expect_tx(bars + 8 * B_GFULL, 20480);
        tma5(sb + G_OFF, &p.mG, 64 * m2, 0, 0, 0, 10 * dg, bars + 8 * B_GFULL);
      }
      mbar_wait(bars + 8 * (B_G1DONE + 19));
      flag_poll(hf + NT1 * 256, tag);
      __syncwarp();
      if (lane == 0) { mbar_arrive(bars + 8 * (B_H1 + 1)); TS(24); }
    }
  } else {
    asm volatile("setmaxnreg.inc.sync.aligned.u32 152;");
    const int w = wid & 3;
    mbar_wait(bars + 8 * B_EP);
    const unsigned tag = lds32(sb + EP_OFF + 20);
    if (wg == 2) {
      ROLE(role)
      if (has2) {
        const int n0 = 64 * m2 + 16 * w + (lane >> 2);
        KvRegs<2> x;
        {
          float xs[80];
          x0_load(xs);
          stats_publish<true>(0, n0, dg, tag, xs);
        }
        if (tid == 256) TS(31);
        kv_load<2>(m2, 32 * w, x);
        if (tid == 352) TS(50);
        kv_finish<2>(m2, 160 * dg + 32 * w, x);
        if (tid == 352) TS(52);
        asm volatile("bar.arrive 3, 192;" ::: "memory");
      } else if (tid == 256) mbar_arrive(bars + 8 * B_PREP);
      stat_table(T1, tag, 0, w);
      if (tid == 256) TS(26);
      if (!has2) { mbar_wait(bars + 8 * (B_G1FULL + 11)); stat_table(T1, tag, 1, w); }
    }
#pragma unroll 1
    for (int l = 0; l < 2; l++) {
      if (wg < 2) {
        float acc[80];
#pragma unroll
        for (int i = 0; i < 80; i++) acc[i] = 0.f;
        ROLE(role)
        const int tid = tid_opaque(), r = (tid & 31) >> 2, q = tid & 3;
        const int ch = 128 * GP + 64 * wg + 32 * side + 8 * w + r;
        mbar_wait(bars + 8 * B_CTAB);
        const uint32_t ca = sb + CTAB_OFF + (32 * wg + 8 * w + r) * 24;
        float2 lam = lds64f(ca);
        const float2 coef = lds64f(ca + 8), lamc = make_float2(lam.x, -lam.y);
        float m00 = coef.x, m01 = -coef.y, m10 = -coef.y, m11 = -coef.x;
        if (p.swap) { lam = lamc; m00 = -coef.y; m01 = coef.x; m10 = -coef.x; m11 = -coef.y; }
        float2 p8, p16, pL, p2L;
        {
          const float2 p2 = cmul(lam, lam), p4 = cmul(p2, p2);
          p8 = cmul(p4, p4); p16 = cmul(p8, p8);
          pL = cmul(p16, p16);
          if (!last) pL = cmul(pL, p8);
          p2L = cmul(pL, pL);
        }
        fence_regs(acc);
        {
          uint32_t alo = desc_lo(sb, 16) + wg * 512, blo = l == 0 ? desc_lo(sb + G1_XOFF, 16) : desc_lo(sb + G1_XOFF, 128);
          const uint32_t bhi = l == 0 ? desc_hi(1024, 1) : desc_hi(1024, 0), xstep = l == 0 ? 2 : 16;
          const uint32_t aend = desc_lo(sb, 16) + (S1 + l) * (G1_STAGE >> 4);
          uint32_t fb = bars + 8 * (B_G1FULL + 10 * l);
          mbar_wait(fb);
          if (tid == 0) TS(1 + 8 * l);
#pragma unroll 1
          for (int k = 0; k < 10; k++) {
            uint32_t ok; const uint32_t nb = k < 9 ? fb + 8 : fb;
            wgmma_fence();
#pragma unroll
            for (int kk = 0; kk < 4; kk++) {
              wgmma_n160<0>(acc, alo + kk * 2, desc_hi(1024, 1), blo + kk * xstep, bhi);
              if (kk == 0) ok = mbar_test(nb);
            }
            wgmma_commit();
            alo += G1_STAGE >> 4; blo += G1_STAGE >> 4;
            if (alo >= aend) { alo -= (S1 + l) * (G1_STAGE >> 4); blo -= (S1 + l) * (G1_STAGE >> 4); }
            wgmma_wait<1>();
            if (k > 0 && (tid & 127) == 0) mbar_arrive(fb + 8 * (B_G1DONE - B_G1FULL - 1));
            if (!ok) mbar_wait(nb);
            if (l == 0 && k == PAUSE_K) { if (tid == 0) TS(48); mbar_wait(bars + 8 * B_PREP); if (tid == 0) TS(49); }
            fb += 8;
          }
        }
        mbar_wait(bars + 8 * (B_STAB + l));
        const float2 sB = lds64f(ca + 16);
        wgmma_wait<0>();
        fence_regs(acc);
        if ((tid & 127) == 0) { mbar_arrive(bars + 8 * (B_G1DONE + 10 * l + 9)); if (wg == 0) TS(2 + 8 * l); }
        float2 ec[3];
#pragma unroll
        for (int jj = 0; jj < 8; jj++)
#pragma unroll
          for (int y = 0; y < 3; y++) {
            if (y == 2 && (jj & 1)) continue;
            const int j = y == 2 ? 16 + (jj >> 1) : 8 * y + jj;
            const float4 st = lds128f(sb + STAB_OFF + (8 * j + 2 * q) * 8);
            acc[4 * j + 0] = fmaf(acc[4 * j + 0], st.x, st.y * sB.x);
            acc[4 * j + 2] = fmaf(acc[4 * j + 2], st.x, st.y * sB.y);
            acc[4 * j + 1] = fmaf(acc[4 * j + 1], st.z, st.w * sB.x);
            acc[4 * j + 3] = fmaf(acc[4 * j + 3], st.z, st.w * sB.y);
            ec[y] = jj == 0 ? make_float2(acc[4 * j + 0], acc[4 * j + 2]) : cfma(lam, ec[y], make_float2(acc[4 * j + 0], acc[4 * j + 2]));
            ec[y] = cfma(lam, ec[y], make_float2(acc[4 * j + 1], acc[4 * j + 3]));
          }
        float2 e = cfma(p16, ec[0], ec[1]);
        if (!last) e = cfma(p8, e, ec[2]);
        {
          float2 v = make_float2(__shfl_up_sync(0xffffffffu, e.x, 1, 4), __shfl_up_sync(0xffffffffu, e.y, 1, 4));
          if (q >= 1) e = cfma(pL, v, e);
          v = make_float2(__shfl_up_sync(0xffffffffu, e.x, 2, 4), __shfl_up_sync(0xffffffffu, e.y, 2, 4));
          if (q >= 2) e = cfma(p2L, v, e);
        }
        if (!last && (q == 3 || (q == 2 && l == 0))) rec_st(&g_E[((q == 3 ? l : 1) * NT1 + T1) * DM + ch], e.x, e.y, q == 3 ? tag : tag - 1);
        if (tid == 0) TS(3 + 8 * l);
        float2 ex = make_float2(__shfl_up_sync(0xffffffffu, e.x, 1, 4), __shfl_up_sync(0xffffffffu, e.y, 1, 4));
        if (q == 0) ex = make_float2(0.f, 0.f);
        float2 pLq, p160q, p640;
        {
          const float2 p80 = last ? cmul(p2L, p16) : p2L, p160 = cmul(p80, p80), p320 = cmul(p160, p160), one = make_float2(1.f, 0.f);
          p640 = cmul(p320, p320);
          pLq = cmul((q & 1) ? pL : one, (q & 2) ? p2L : one);
          p160q = cmul((q & 1) ? p160 : one, (q & 2) ? p320 : one);
        }
        float2 c, ev[3];
        unsigned tg[3];
        const uint4* ep = &g_E[(l * NT1 + T1 - 1 - q) * DM + ch];
#pragma unroll
        for (int j = 0; j < 20; j++) {
          if (j == CPOLL) {
#pragma unroll
            for (int i = 0; i < 3; i++) {
              ev[i] = make_float2(0.f, 0.f); tg[i] = tag;
              if (T1 - 1 - q - 4 * i >= 0) tg[i] = rec_ld(ep - 4 * i * DM, ev[i].x, ev[i].y);
            }
          }
#pragma unroll
          for (int x = 0; x < 2; x++) {
            const float b0 = acc[4 * j + x], b1 = acc[4 * j + 2 + x];
            acc[4 * j + x] = fmaf(b0, m00, b1 * m01);
            acc[4 * j + 2 + x] = fmaf(b0, m10, b1 * m11);
          }
          if (j == CPOLL - 1 || j == 19) asm volatile("" : "+f"(acc[4 * j]), "+f"(acc[4 * j + 1]), "+f"(acc[4 * j + 2]), "+f"(acc[4 * j + 3])::"memory");
        }
        {
          uint32_t it = 0;
          while (__any_sync(0xffffffffu, tg[0] != tag || tg[1] != tag || tg[2] != tag)) {
#pragma unroll
            for (int i = 0; i < 3; i++)
              if (tg[i] != tag) tg[i] = rec_ld(ep - 4 * i * DM, ev[i].x, ev[i].y);
            trap_if(++it > SPIN_LIMIT);
          }
          c = cfma(p640, cfma(p640, ev[2], ev[1]), ev[0]);
          c = cmul(c, p160q);
          c.x += __shfl_xor_sync(0xffffffffu, c.x, 1); c.y += __shfl_xor_sync(0xffffffffu, c.y, 1);
          c.x += __shfl_xor_sync(0xffffffffu, c.x, 2); c.y += __shfl_xor_sync(0xffffffffu, c.y, 2);
        }
        if (tid == 0) TS(4 + 8 * l);
        if (tid == 128) mbar_arrive(bars + 8 * (B_GO + 2 * l));
        c = cfma(pLq, c, ex);
        float2 hh = make_float2(fmaf(c.x, m00, c.y * m01), fmaf(c.x, m10, c.y * m11));
        uint8_t* hb = g_h + (size_t)l * (32 * 20 * 8192) + (10 * wg + 2 * GP) * 8192 + (4 * side + w) * 1024 + (tid_opaque() & 31) * 4;
#pragma unroll
        for (int j4 = 0; j4 < 5; j4++) {
          const int ng = 20 * T1 + 4 * j4;
          uint8_t* hp = hb + (size_t)(ng >> 3) * 163840 + (ng & 7) * 128;
#pragma unroll
          for (int jj = 0; jj < 4; jj++) {
            const int j = 4 * j4 + jj;
            const float2 h0 = cfma(lamc, hh, make_float2(acc[4 * j + 0], acc[4 * j + 2]));
            hh = cfma(lamc, h0, make_float2(acc[4 * j + 1], acc[4 * j + 3]));
            if (j4 < 4 || !last) {
              *(uint32_t*)(hp + jj * 128) = pack_bf16(h0.x, hh.x);
              *(uint32_t*)(hp + jj * 128 + 8192) = pack_bf16(h0.y, hh.y);
            }
          }
        }
        mbar_arrive(bars + 8 * (B_HST + 2 * l + wg));
        if (tid == 0) TS(5 + 8 * l);
      }
      if (l == 0) {
        ROLE(role)
        if (has2) {
          CvCtx cc;
          cv_setup(cc);
          mbar_wait(bars + 8 * (B_G1DONE + 9));
#pragma unroll 1
          for (int c = wg == 2 ? 0 : 2 + wg; c < (wg == 2 ? 2 : 5); c += wg == 2 ? 1 : 2) conv_channel(c, cc);
          if ((tid & 127) == 0) TS(wg == 2 ? 32 : 7 + wg);
        }
      }
      if (wg == 2) break;
    }
    if (wg == 2 && (role >> 16)) {
      float acc[80];
      float off[2] = {0.f, 0.f};
      x0_load(acc);
      mbar_arrive(bars + 8 * B_XFREE);
#pragma unroll 1
      for (int l = 0; l < 2; l++) {
        float mean[2], rstd[2];
        {
          ROLE(role)
          const int lane = tid_opaque() & 31;
          stats_get(2 * l, 64 * m2 + 16 * w + (lane >> 2), tag, mean, rstd);
          off[0] += mean[0]; off[1] += mean[1];
          mbar_wait(bars + 8 * (l == 0 ? B_CTAB : B_HST + 3));
#pragma unroll
          for (int J = 0; J < 10; J++) {
            const float2 dw = lds64f(sb + DTAB_OFF + 2 * (16 * J + 4 * (lane & 3)));
#pragma unroll
            for (int x = 0; x < 8; x++) {
              const int h = (x >> 1) & 1;
              const uint32_t gwd = __float_as_uint(x < 4 ? dw.x : dw.y);
              acc[8 * J + x] = (acc[8 * J + x] - mean[h]) * fmaf(rstd[h], (x & 1) ? bf_hi(gwd) : bf_lo(gwd), 1.f);
            }
          }
        }
        {
          const uint32_t aend = desc_lo(sb + SX2 * G2_XB, 1024) + l * (G2_XB >> 3), bend = desc_lo(sb + G2_WOFF + 6 * G2_WB, 16) + l * (G2_WB >> 4);
          uint32_t alo = desc_lo(sb, 1024), blo = desc_lo(sb + G2_WOFF, 16);
          uint32_t fb = bars + 8 * (B_G2FULL + 20 * l);
          fence_regs(acc);
          mbar_wait(fb);
          if (tid == 256) TS(33 + 6 * l);
#pragma unroll 1
          for (int k = 0; k < 20; k++) {
            if (l == 1 && (k & 3) == 3 && tid == 256) TS(56 + (k >> 2));
            uint32_t ok; const uint32_t nb = k < 19 ? fb + 8 : fb;
            wgmma_fence();
#pragma unroll
            for (int kk = 0; kk < 4; kk++) {
              wgmma_n160<1>(acc, alo + kk * 128, desc_hi(128, 0), blo + kk * 2, desc_hi(1024, 1));
              if (kk == 0) ok = mbar_test(nb);
            }
            wgmma_commit();
            alo += G2_XB >> 4; if (alo == aend) alo = desc_lo(sb, 1024);
            blo += G2_WB >> 4; if (blo == bend) blo = desc_lo(sb + G2_WOFF, 16);
            wgmma_wait<1>();
            if (k > 0 && tid == 256) mbar_arrive(fb + 8 * (B_G2DONE - B_G2FULL - 1));
            if (!ok) mbar_wait(nb);
            fb += 8;
          }
          wgmma_wait<0>();
          fence_regs(acc);
          if (tid == 256) TS(34 + 6 * l);
          if (tid == 256) mbar_arrive(bars + 8 * (B_G2DONE + 20 * l + 19));
        }
        ROLE(role)
        const int tq = tid_opaque() & 31, n0 = 64 * m2 + 16 * w + (tq >> 2);
        stats_publish<false>(2 * l + 1, n0, dg, tag, acc);
        uint32_t gf[10][4];
        mbar_wait(bars + 8 * B_GFULL);
        const uint32_t ga = sb + G_OFF + (8 * (tq >> 4) + (tq & 7)) * 128 + (((2 * w + ((tq >> 3) & 1)) ^ ((2 * m2) & 6) ^ (tq & 7)) << 4);
#pragma unroll
        for (int J = 0; J < 2; J++) ldsm4t(gf[J], ga + J * 2048);
        if (tid == 256) TS(35 + 6 * l);
        uint8_t* dst[2][2];
#pragma unroll
        for (int h = 0; h < 2; h++) {
          if (l == 0) {
            const int ng = 8 * m2 + 2 * w + h, T = ng / 20;
            uint8_t* ub = g_u + (T * 204800 + (ng - 20 * T) * 1024 + (tq & 2) * 64 + (tq & 28) * 4 + (tq & 1) * 8 + (5 * dg >> 1) * 20480);
            dst[h][1] = ub + ((dg & 1) ? 20480 - 512 : 0);
            dst[h][0] = ub + (dg & 1) * 512;
          } else {
            dst[h][0] = dst[h][1] = (uint8_t*)(p.out + (n_to_t(n0 + 8 * h) * DM + 160 * dg + 4 * (tq & 3)));
          }
        }
        stats_get(2 * l + 1, n0, tag, mean, rstd);
        if (tid == 256) { TS(36 + 6 * l); if (l == 0) mbar_arrive(bars + 8 * (B_GO + 1)); }
        off[0] += mean[0]; off[1] += mean[1];
        const float ov[2] = {l ? off[0] : 0.f, l ? off[1] : 0.f};
#pragma unroll
        for (int J = 0; J < 10; J++) {
          if (J + 2 < 10) ldsm4t(gf[J + 2 < 10 ? J + 2 : 0], ga + (J + 2) * 2048);
#pragma unroll
          for (int x = 0; x < 8; x++) {
            const int h = (x >> 1) & 1;
            const uint32_t gwd = gf[J][x >> 1];
            const float t = fmaf(rstd[h], (x & 1) ? bf_hi(gwd) : bf_lo(gwd), 1.f);
            acc[8 * J + x] = fmaf(acc[8 * J + x], t, fmaf(-mean[h], t, ov[h]));
          }
#pragma unroll
          for (int h = 0; h < 2; h++) {
            if (l == 0)
              *(uint2*)(dst[h][(J >> 1) & 1] + (J >> 2) * 20480 + (J & 3) * 256) =
                  make_uint2(pack_bf16(acc[8 * J + 2 * h], acc[8 * J + 2 * h + 1]), pack_bf16(acc[8 * J + 4 + 2 * h], acc[8 * J + 5 + 2 * h]));
            else
              *(float4*)(dst[h][0] + 64 * J) = make_float4(acc[8 * J + 2 * h], acc[8 * J + 2 * h + 1], acc[8 * J + 4 + 2 * h], acc[8 * J + 5 + 2 * h]);
          }
          __syncwarp();
        }
        if (l == 0) {
          bar_sync(3, 128);
          if (tid == 256) { TS(37); st_rel(&g_uflag[(4 * m2 + dg) * 8], tag); TS(38); }
          stats_publish<false>(2, n0, dg, tag, acc);
          mbar_wait(bars + 8 * (B_G1FULL + 11));
          stat_table(T1, tag, 1, w);
          if (tid == 256) TS(27);
        } else {
          if (tid == 256) {
            TS(43);
            if (m2 == 31 && dg == 3) asm volatile("st.relaxed.gpu.global.u32 [%0], %1;" ::"l"(g_epoch), "r"(tag + 1) : "memory");
          }
        }
      }
    }
  }
}

typedef CUresult (*EncFn)(CUtensorMap*, CUtensorMapDataType, cuuint32_t, void*, const cuuint64_t*, const cuuint64_t*,
                          const cuuint32_t*, const cuuint32_t*, CUtensorMapInterleave, CUtensorMapSwizzle,
                          CUtensorMapL2promotion, CUtensorMapFloatOOBfill);

void encode(EncFn fn, CUtensorMap* m, const void* ptr, int rank, const cuuint64_t* dims, const cuuint64_t* strides, const cuuint32_t* box,
            CUtensorMapSwizzle swz = CU_TENSOR_MAP_SWIZZLE_128B) {
  cuuint32_t es[5] = {1, 1, 1, 1, 1};
  fn(m, CU_TENSOR_MAP_DATA_TYPE_BFLOAT16, rank, (void*)ptr, dims, strides, box, es, CU_TENSOR_MAP_INTERLEAVE_NONE,
     swz, swz == CU_TENSOR_MAP_SWIZZLE_128B ? CU_TENSOR_MAP_L2_PROMOTION_L2_128B : CU_TENSOR_MAP_L2_PROMOTION_L2_64B, CU_TENSOR_MAP_FLOAT_OOB_FILL_NONE);
}

}

extern "C" void kernel_launch(void* const* d_in, const int* in_sizes, int n_in, void* d_out, int out_size) {
  (void)in_sizes; (void)n_in; (void)out_size;
  Params p;
  typedef const __nv_bfloat16* BP;
  p.x = (BP)d_in[0]; p.lre = (BP)d_in[1]; p.lim = (BP)d_in[2]; p.bre = (BP)d_in[3]; p.bim = (BP)d_in[4];
  p.cre = (BP)d_in[5]; p.cim = (BP)d_in[6]; p.logdt = (BP)d_in[7]; p.dskip = (BP)d_in[8];
  p.k = (BP)d_in[10]; p.v = (BP)d_in[11]; p.shiftk = (BP)d_in[12]; p.ssmk = (BP)d_in[13]; p.ssmD = (BP)d_in[14];
  p.out = (float*)d_out;
  void* fnp = nullptr;
  cudaDriverEntryPointQueryResult qr;
  cudaGetDriverEntryPoint("cuTensorMapEncodeTiled", &fnp, cudaEnableDefault, &qr);
  EncFn fn = (EncFn)fnp;
  void* gG = nullptr;
  cudaGetSymbolAddress(&gG, g_G);
  const cuuint64_t RB = DM * 2;
  {
    p.swap = p.bim < p.bre;
    const char* lo = (const char*)(p.swap ? p.bim : p.bre); const char* hi = (const char*)(p.swap ? p.bre : p.bim);
    cuuint64_t dims[5] = {640, 8, 2, 8, 10}, st[4] = {RB, (cuuint64_t)(hi - lo), 8 * RB, 64 * RB}; cuuint32_t box[5] = {64, 8, 2, 4, 2};
    encode(fn, &p.mB, lo, 5, dims, st, box);
  }
  {
    cuuint64_t dims[5] = {640, 2, 4, 2, 40}, st[4] = {RB, 4 * RB, 2 * RB, 16 * RB}; cuuint32_t box[5] = {64, 2, 4, 2, 10};
    encode(fn, &p.mCre, p.cre, 5, dims, st, box); encode(fn, &p.mCim, p.cim, 5, dims, st, box);
    cuuint64_t dimg[5] = {2048, 2, 4, 2, 40}, stg[4] = {4096, 4 * 4096, 2 * 4096, 16 * 4096};
    encode(fn, &p.mG, gG, 5, dimg, stg, box);
  }
  {
    cuuint64_t dims[4] = {640, 2, 4, 900}, st[3] = {RB, 40 * RB, 2 * RB}; cuuint32_t box[4] = {64, 2, 4, 20};
    encode(fn, &p.mX, p.x, 4, dims, st, box);
    cuuint64_t diml[4] = {640, 2, 4, 16}, stl[3] = {RB, 32 * RB, 2 * RB};
    encode(fn, &p.mXl, p.x + (size_t)1920 * DM, 4, diml, stl, box);
    cuuint32_t boxt[4] = {160, 2, 4, 4};
    encode(fn, &p.mXt, p.x, 4, dims, st, boxt, CU_TENSOR_MAP_SWIZZLE_NONE);
    encode(fn, &p.mXtl, p.x + (size_t)1920 * DM, 4, diml, stl, boxt, CU_TENSOR_MAP_SWIZZLE_NONE);
    cuuint64_t dk[3] = {640, 2000, 4}, sk[2] = {RB, 16 * RB}; cuuint32_t bk[3] = {32, 19, 4}, bv[3] = {32, 17, 4};
    encode(fn, &p.mK, p.k, 3, dk, sk, bk, CU_TENSOR_MAP_SWIZZLE_NONE);
    encode(fn, &p.mV, p.v, 3, dk, sk, bv, CU_TENSOR_MAP_SWIZZLE_NONE);
  }
  cudaFuncSetAttribute(fused_kernel, cudaFuncAttributeMaxDynamicSharedMemorySize, SMEM_BYTES);
  cudaLaunchConfig_t cfg = {};
  cfg.gridDim = dim3(132); cfg.blockDim = dim3(512); cfg.dynamicSmemBytes = SMEM_BYTES; cfg.stream = cudaStreamPerThread;
  cudaLaunchKernelEx(&cfg, fused_kernel, p);
}
```

```cpp
#include <cuda_runtime.h>
#include <cuda.h>
#include <cuda_bf16.h>
#include <stdint.h>

namespace {

constexpr int SEQ = 2048, DM = 640;
constexpr int NT1 = 13;
#define EXP 0
#define WPF1 1
#define WPF2 2
#define CPOLL 10
#define KV0 1
#define PAUSE_K 3
constexpr uint32_t SPIN_LIMIT = 1u << 22;

__device__ __align__(1024) uint8_t g_h[2 * 32 * 20 * 8192];
__device__ __align__(1024) uint8_t g_u[NT1 * 10 * 20480];
__device__ __align__(1024) uint8_t g_kv[DM * 4096];
__device__ __align__(1024) uint8_t g_G[DM * 4096];
__device__ __align__(128) uint4 g_E[2 * NT1 * DM];
__device__ __align__(128) uint4 g_stats[4 * 4 * SEQ];
__device__ __align__(128) uint4 g_sB[DM * 2];
__device__ __align__(128) unsigned g_hflag[2 * NT1 * 2 * 16 * 8];
__device__ __align__(128) unsigned g_uflag[32 * 4 * 8];
__device__ __align__(128) unsigned g_kvflag[4 * 5 * 32 * 8];
__device__ __align__(128) unsigned g_gflag[4 * 32 * 8];
__device__ __align__(128) unsigned g_epoch[32] = {1};
#define TS(i) do {} while (0)

struct Params {
  CUtensorMap mB, mCre, mCim, mX, mXl, mG, mK, mV, mXt, mXtl;
  const __nv_bfloat16 *x, *lre, *lim, *bre, *bim, *cre, *cim, *logdt, *dskip, *k, *v, *shiftk, *ssmk, *ssmD;
  float* out;
  int swap;
};

constexpr uint32_t sb = 1024;
constexpr uint32_t G1_STAGE = 36864, G1_XOFF = 16384;
constexpr int S1 = 4;
constexpr uint32_t XT_OFF = 159744, KS_OFF = 180224, KV_PIECE = 9216;
constexpr uint32_t G2_XB = 8192, G2_WB = 20480, G2_WOFF = 57344, G_OFF = 200704;
constexpr int SX2 = 5;
constexpr uint32_t CV_OFF = KS_OFF, CV_K = 128, CV_PL = 2240, CV_U = CV_K + 4096, CV_B = KV_PIECE;
constexpr uint32_t MISC = 226304;
constexpr uint32_t BAR_OFF = MISC;
constexpr int B_G1FULL = 0, B_G1DONE = 20, B_G2FULL = 40,
              B_G2DONE = 85, B_GFULL = 125, B_PREP = 126, B_EP = 127, B_H1 = 128  ,
              B_CVDONE = 130, B_STAB = 135  , B_CTAB = 137, B_XFREE = 138, B_HST = 139  ,
              B_XT = 143, B_KV = 144  , B_TAPS = 149  , B_CVFULL = 154  , B_GO = 159  , B_PD = 162  ;
constexpr uint32_t bars = sb + BAR_OFF;
constexpr uint32_t STAB_OFF = MISC + 1328;
constexpr uint32_t CTAB_OFF = STAB_OFF + 1280;
constexpr uint32_t DTAB_OFF = CTAB_OFF + 1536;
constexpr uint32_t EP_OFF = DTAB_OFF + 320;
constexpr uint32_t TAP_OFF = 147456;
constexpr uint32_t SMEM_BYTES = 232448;
static_assert(EP_OFF + 32 <= SMEM_BYTES, "smem");

__device__ __forceinline__ void trap_if(bool c) { asm volatile("{\n.reg .pred p;\nsetp.ne.u32 p, %0, 0;\n@p trap;\n}\n" ::"r"((uint32_t)c)); }
__device__ __forceinline__ uint32_t smem_u32(const void* p) { return (uint32_t)__cvta_generic_to_shared(p); }
__device__ __forceinline__ void mbar_init(uint32_t bar, int cnt) { asm volatile("mbarrier.init.shared::cta.b64 [%0], %1;" ::"r"(bar), "r"(cnt) : "memory"); }
__device__ __forceinline__ void mbar_expect_tx(uint32_t bar, int bytes) { asm volatile("mbarrier.arrive.expect_tx.shared::cta.b64 _, [%0], %1;" ::"r"(bar), "r"(bytes) : "memory"); }
__device__ __forceinline__ void mbar_arrive(uint32_t bar) { asm volatile("mbarrier.arrive.shared::cta.b64 _, [%0];" ::"r"(bar) : "memory"); }
__device__ __forceinline__ void mbar_wait(uint32_t bar) {
  asm volatile(
      "{\n.reg .pred p;\n.reg .u32 c;\nmov.u32 c, 0;\n"
      "W_%=:\nmbarrier.try_wait.parity.shared::cta.b64 p, [%0], 0;\n@p bra D_%=;\n"
      "add.u32 c, c, 1;\nsetp.lt.u32 p, c, %1;\n@p bra W_%=;\ntrap;\nD_%=:\n}\n" ::"r"(bar), "n"(SPIN_LIMIT) : "memory");
}
__device__ __forceinline__ uint32_t mbar_test(uint32_t bar) {
  uint32_t ok;
  asm volatile("{\n.reg .pred p;\nmbarrier.test_wait.parity.shared::cta.b64 p, [%1], 0;\nselp.u32 %0, 1, 0, p;\n}\n" : "=r"(ok) : "r"(bar) : "memory");
  return ok;
}
__device__ __forceinline__ void tma3(uint32_t dst, const CUtensorMap* m, int c0, int c1, int c2, uint32_t bar) {
  asm volatile("cp.async.bulk.tensor.3d.shared::cluster.global.mbarrier::complete_tx::bytes [%0], [%1, {%3,%4,%5}], [%2];"
               ::"r"(dst), "l"(m), "r"(bar), "r"(c0), "r"(c1), "r"(c2) : "memory");
}
__device__ __forceinline__ void tma4(uint32_t dst, const CUtensorMap* m, int c0, int c1, int c2, int c3, uint32_t bar) {
  asm volatile("cp.async.bulk.tensor.4d.shared::cluster.global.mbarrier::complete_tx::bytes [%0], [%1, {%3,%4,%5,%6}], [%2];"
               ::"r"(dst), "l"(m), "r"(bar), "r"(c0), "r"(c1), "r"(c2), "r"(c3) : "memory");
}
__device__ __forceinline__ void tma5(uint32_t dst, const CUtensorMap* m, int c0, int c1, int c2, int c3, int c4, uint32_t bar) {
  asm volatile("cp.async.bulk.tensor.5d.shared::cluster.global.mbarrier::complete_tx::bytes [%0], [%1, {%3,%4,%5,%6,%7}], [%2];"
               ::"r"(dst), "l"(m), "r"(bar), "r"(c0), "r"(c1), "r"(c2), "r"(c3), "r"(c4) : "memory");
}
__device__ __forceinline__ void bulk_g2s(uint32_t dst, const void* src, int bytes, uint32_t bar) {
  asm volatile("cp.async.bulk.shared::cluster.global.mbarrier::complete_tx::bytes [%0], [%1], %2, [%3];"
               ::"r"(dst), "l"(src), "r"(bytes), "r"(bar) : "memory");
}
__device__ __forceinline__ void bulk_s2g(void* dst, uint32_t src, int bytes) {
  asm volatile("cp.async.bulk.global.shared::cta.bulk_group [%0], [%1], %2;" ::"l"(dst), "r"(src), "r"(bytes) : "memory");
}
__device__ __forceinline__ void l2_prefetch(const void* src, int bytes) {
  asm volatile("cp.async.bulk.prefetch.L2.global [%0], %1;" ::"l"(src), "r"(bytes) : "memory");
}
__device__ __forceinline__ void wgmma_fence() { asm volatile("wgmma.fence.sync.aligned;" ::: "memory"); }
__device__ __forceinline__ void wgmma_commit() { asm volatile("wgmma.commit_group.sync.aligned;" ::: "memory"); }
template <int N> __device__ __forceinline__ void wgmma_wait() { asm volatile("wgmma.wait_group.sync.aligned %0;" ::"n"(N) : "memory"); }
__host__ __device__ constexpr uint32_t desc_lo(uint32_t addr, uint32_t lbo) { return ((addr & 0x3FFFF) >> 4) | ((lbo >> 4) << 16); }
__host__ __device__ constexpr uint32_t desc_hi(uint32_t sbo, uint32_t swz) { return (sbo >> 4) | (swz << 30); }
__device__ __forceinline__ void bar_sync(int id, int n) { asm volatile("bar.sync %0, %1;" ::"r"(id), "r"(n) : "memory"); }
__device__ __forceinline__ uint32_t lds32(uint32_t a) { uint32_t v; asm volatile("ld.shared.u32 %0, [%1];" : "=r"(v) : "r"(a) : "memory"); return v; }
__device__ __forceinline__ float2 lds64f(uint32_t a) { float2 v; asm volatile("ld.shared.v2.f32 {%0,%1}, [%2];" : "=f"(v.x), "=f"(v.y) : "r"(a) : "memory"); return v; }
__device__ __forceinline__ float4 lds128f(uint32_t a) { float4 v; asm volatile("ld.shared.v4.f32 {%0,%1,%2,%3}, [%4];" : "=f"(v.x), "=f"(v.y), "=f"(v.z), "=f"(v.w) : "r"(a) : "memory"); return v; }
__device__ __forceinline__ void ldsm4t(uint32_t (&r)[4], uint32_t a) {
  asm volatile("ldmatrix.sync.aligned.m8n8.x4.trans.shared.b16 {%0,%1,%2,%3}, [%4];" : "=r"(r[0]), "=r"(r[1]), "=r"(r[2]), "=r"(r[3]) : "r"(a) : "memory");
}
__device__ __forceinline__ uint4 ldv128(const void* a) { uint4 v; asm volatile("ld.global.nc.v4.u32 {%0,%1,%2,%3}, [%4];" : "=r"(v.x), "=r"(v.y), "=r"(v.z), "=r"(v.w) : "l"(a) : "memory"); return v; }
__device__ __forceinline__ uint2 ldv64(const void* a) { uint2 v; asm volatile("ld.global.nc.v2.u32 {%0,%1}, [%2];" : "=r"(v.x), "=r"(v.y) : "l"(a) : "memory"); return v; }
__device__ __forceinline__ uint32_t ldv16(const void* a) { uint32_t v; asm volatile("ld.global.nc.u16 %0, [%1];" : "=r"(v) : "l"(a) : "memory"); return v; }
__device__ __forceinline__ void sts128(uint32_t a, uint4 v) { asm volatile("st.shared.v4.u32 [%0], {%1,%2,%3,%4};" ::"r"(a), "r"(v.x), "r"(v.y), "r"(v.z), "r"(v.w) : "memory"); }
__device__ __forceinline__ void sts32(uint32_t a, uint32_t v) { asm volatile("st.shared.u32 [%0], %1;" ::"r"(a), "r"(v) : "memory"); }
__device__ __forceinline__ void sts64f(uint32_t a, float x, float y) { asm volatile("st.shared.v2.f32 [%0], {%1,%2};" ::"r"(a), "f"(x), "f"(y) : "memory"); }
__device__ __forceinline__ void st_rel(unsigned* p, unsigned v) { asm volatile("st.release.gpu.global.u32 [%0], %1;" ::"l"(p), "r"(v) : "memory"); }
__device__ __forceinline__ void fence_async_global() { asm volatile("fence.proxy.async.global;" ::: "memory"); }
__device__ __forceinline__ void fence_async_smem() { asm volatile("fence.proxy.async.shared::cta;" ::: "memory"); }
__device__ __forceinline__ void rec_st(uint4* p, float a, float b, unsigned tag) {
  asm volatile("{\n.reg .b128 t;\n.reg .b64 lo, hi;\nmov.b64 lo, {%1,%2};\nmov.b64 hi, {%3,%3};\nmov.b128 t, {lo,hi};\n"
               "st.relaxed.gpu.global.b128 [%0], t;\n}\n" ::"l"(p), "r"(__float_as_uint(a)), "r"(__float_as_uint(b)), "r"(tag) : "memory");
}
__device__ __forceinline__ unsigned rec_ld(const uint4* p, float& a, float& b) {
  unsigned x, y, t;
  asm volatile("{\n.reg .b128 t;\n.reg .b64 lo, hi;\n.reg .b32 u;\nld.relaxed.gpu.global.b128 t, [%3];\nmov.b128 {lo,hi}, t;\n"
               "mov.b64 {%0,%1}, lo;\nmov.b64 {%2,u}, hi;\n}\n" : "=r"(x), "=r"(y), "=r"(t) : "l"(p) : "memory");
  a = __uint_as_float(x); b = __uint_as_float(y);
  return t;
}
__device__ __forceinline__ void rec_poll(const uint4* p, unsigned tag, float& a, float& b) {
  uint32_t it = 0;
  while (!__all_sync(0xffffffffu, rec_ld(p, a, b) == tag)) { trap_if(++it > SPIN_LIMIT); }
}
__device__ __forceinline__ unsigned ld_rlx(const unsigned* p) { unsigned v; asm volatile("ld.relaxed.gpu.global.u32 %0, [%1];" : "=r"(v) : "l"(p) : "memory"); return v; }
__device__ __forceinline__ void flag_poll(const unsigned* p, unsigned target) {
  uint32_t it = 0;
  while (!__all_sync(0xffffffffu, (int)(ld_rlx(p) - target) >= 0)) { trap_if(++it > SPIN_LIMIT); }
  asm volatile("fence.acquire.gpu;" ::: "memory");
}
__device__ __forceinline__ uint32_t pack_bf16(float lo, float hi) {
  uint32_t r; asm("cvt.rn.bf16x2.f32 %0, %1, %2;" : "=r"(r) : "f"(hi), "f"(lo)); return r;
}
__device__ __forceinline__ float bf_lo(uint32_t w) { return __uint_as_float(w << 16); }
__device__ __forceinline__ float bf_hi(uint32_t w) { return __uint_as_float(w & 0xffff0000u); }
__device__ __forceinline__ uint32_t hmul2(uint32_t a, uint32_t b) {
  __nv_bfloat162 r = __hmul2_rn(*(__nv_bfloat162*)&a, *(__nv_bfloat162*)&b); return *(uint32_t*)&r;
}
__device__ __forceinline__ uint32_t hadd2(uint32_t a, uint32_t b) {
  __nv_bfloat162 r = __hadd2_rn(*(__nv_bfloat162*)&a, *(__nv_bfloat162*)&b); return *(uint32_t*)&r;
}
__device__ __forceinline__ float2 cmul(float2 a, float2 b) { return make_float2(a.x * b.x - a.y * b.y, a.x * b.y + a.y * b.x); }
__device__ __forceinline__ float2 cfma(float2 a, float2 b, float2 c) {
  return make_float2(fmaf(a.x, b.x, fmaf(-a.y, b.y, c.x)), fmaf(a.x, b.y, fmaf(a.y, b.x, c.y)));
}
template <int N> __device__ __forceinline__ void fence_regs(float (&a)[N]) {
#pragma unroll
  for (int i = 0; i < N; i++) asm volatile("" : "+f"(a[i])::"memory");
}
__device__ __forceinline__ bool elect_one() {
  uint32_t e; asm volatile("{\n.reg .pred P;\nelect.sync _|P, 0xffffffff;\nselp.u32 %0, 1, 0, P;\n}\n" : "=r"(e)); return e != 0;
}
__device__ __forceinline__ int tid_opaque() { int t; asm volatile("mov.u32 %0, %%tid.x;" : "=r"(t)); return t; }
struct Role { int T1, GP, side, m2, dg, cch0; bool last, has2; };
__device__ __forceinline__ Role unpack_role(int x) {
  Role r; r.T1 = x & 15; r.GP = (x >> 4) & 7; r.side = (x >> 7) & 1; r.m2 = (x >> 8) & 63; r.dg = (x >> 14) & 3;
  r.has2 = (x >> 16) & 1; r.last = r.T1 == NT1 - 1; r.cch0 = 160 * r.dg + r.m2; return r;
}
__device__ __forceinline__ Role fresh_role(int x) { asm volatile("" : "+r"(x)); return unpack_role(__shfl_sync(0xffffffffu, x, 0)); }
#define ROLE(x) const Role R_ = fresh_role(x); const int T1 = R_.T1, GP = R_.GP, side = R_.side, m2 = R_.m2, dg = R_.dg, cch0 = R_.cch0; \
  const bool last = R_.last, has2 = R_.has2; (void)T1; (void)GP; (void)side; (void)m2; (void)dg; (void)cch0; (void)last; (void)has2;
__device__ __forceinline__ int n_to_t(int n) {
  int T = n / 160, nl = n - T * 160;
  int L = (T == NT1 - 1) ? 32 : 40;
  return T * 160 + L * ((nl & 7) >> 1) + 2 * (nl >> 3) + (nl & 1);
}

template<int TA> __device__ __forceinline__ void wgmma_n160(float (&d)[80], uint32_t alo, uint32_t ahi, uint32_t blo, uint32_t bhi){
  asm volatile("{\n.reg .b64 da, db;\nmov.b64 da, {%80,%81};\nmov.b64 db, {%82,%83};\n"
    "wgmma.mma_async.sync.aligned.m64n160k16.f32.bf16.bf16 {%0, %1, %2, %3, %4, %5, %6, %7, %8, %9, %10, %11, %12, %13, %14, %15, %16, %17, %18, %19, %20, %21, %22, %23, %24, %25, %26, %27, %28, %29, %30, %31, %32, %33, %34, %35, %36, %37, %38, %39, %40, %41, %42, %43, %44, %45, %46, %47, %48, %49, %50, %51, %52, %53, %54, %55, %56, %57, %58, %59, %60, %61, %62, %63, %64, %65, %66, %67, %68, %69, %70, %71, %72, %73, %74, %75, %76, %77, %78, %79}, da, db, 1, 1, 1, %84, 0;\n}\n"
    : "+f"(d[0]), "+f"(d[1]), "+f"(d[2]), "+f"(d[3]), "+f"(d[4]), "+f"(d[5]), "+f"(d[6]), "+f"(d[7]), "+f"(d[8]), "+f"(d[9]), "+f"(d[10]), "+f"(d[11]), "+f"(d[12]), "+f"(d[13]), "+f"(d[14]), "+f"(d[15]), "+f"(d[16]), "+f"(d[17]), "+f"(d[18]), "+f"(d[19]), "+f"(d[20]), "+f"(d[21]), "+f"(d[22]), "+f"(d[23]), "+f"(d[24]), "+f"(d[25]), "+f"(d[26]), "+f"(d[27]), "+f"(d[28]), "+f"(d[29]), "+f"(d[30]), "+f"(d[31]), "+f"(d[32]), "+f"(d[33]), "+f"(d[34]), "+f"(d[35]), "+f"(d[36]), "+f"(d[37]), "+f"(d[38]), "+f"(d[39]), "+f"(d[40]), "+f"(d[41]), "+f"(d[42]), "+f"(d[43]), "+f"(d[44]), "+f"(d[45]), "+f"(d[46]), "+f"(d[47]), "+f"(d[48]), "+f"(d[49]), "+f"(d[50]), "+f"(d[51]), "+f"(d[52]), "+f"(d[53]), "+f"(d[54]), "+f"(d[55]), "+f"(d[56]), "+f"(d[57]), "+f"(d[58]), "+f"(d[59]), "+f"(d[60]), "+f"(d[61]), "+f"(d[62]), "+f"(d[63]), "+f"(d[64]), "+f"(d[65]), "+f"(d[66]), "+f"(d[67]), "+f"(d[68]), "+f"(d[69]), "+f"(d[70]), "+f"(d[71]), "+f"(d[72]), "+f"(d[73]), "+f"(d[74]), "+f"(d[75]), "+f"(d[76]), "+f"(d[77]), "+f"(d[78]), "+f"(d[79])
    : "r"(alo), "r"(ahi), "r"(blo), "r"(bhi), "n"(TA));
}
template<int N> __device__ __forceinline__ void wgmma_rs_hi(float (&d)[64], uint32_t a0, uint32_t a1, uint32_t a2, uint32_t a3, uint32_t blo);
template<> __device__ __forceinline__ void wgmma_rs_hi<16>(float (&d)[64], uint32_t a0, uint32_t a1, uint32_t a2, uint32_t a3, uint32_t blo){
  asm volatile("{\n.reg .b64 db;\nmov.b64 db, {%12,8};\nwgmma.mma_async.sync.aligned.m64n16k16.f32.bf16.bf16 {%0, %1, %2, %3, %4, %5, %6, %7}, {%8,%9,%10,%11}, db, 1, 1, 1, 0;\n}\n"
    : "+f"(d[56]), "+f"(d[57]), "+f"(d[58]), "+f"(d[59]), "+f"(d[60]), "+f"(d[61]), "+f"(d[62]), "+f"(d[63])
    : "r"(a0), "r"(a1), "r"(a2), "r"(a3), "r"(blo));
}
template<> __device__ __forceinline__ void wgmma_rs_hi<32>(float (&d)[64], uint32_t a0, uint32_t a1, uint32_t a2, uint32_t a3, uint32_t blo){
  asm volatile("{\n.reg .b64 db;\nmov.b64 db, {%20,8};\nwgmma.mma_async.sync.aligned.m64n32k16.f32.bf16.bf16 {%0, %1, %2, %3, %4, %5, %6, %7, %8, %9, %10, %11, %12, %13, %14, %15}, {%16,%17,%18,%19}, db, 1, 1, 1, 0;\n}\n"
    : "+f"(d[48]), "+f"(d[49]), "+f"(d[50]), "+f"(d[51]), "+f"(d[52]), "+f"(d[53]), "+f"(d[54]), "+f"(d[55]), "+f"(d[56]), "+f"(d[57]), "+f"(d[58]), "+f"(d[59]), "+f"(d[60]), "+f"(d[61]), "+f"(d[62]), "+f"(d[63])
    : "r"(a0), "r"(a1), "r"(a2), "r"(a3), "r"(blo));
}
template<> __device__ __forceinline__ void wgmma_rs_hi<48>(float (&d)[64], uint32_t a0, uint32_t a1, uint32_t a2, uint32_t a3, uint32_t blo){
  asm volatile("{\n.reg .b64 db;\nmov.b64 db, {%28,8};\nwgmma.mma_async.sync.aligned.m64n48k16.f32.bf16.bf16 {%0, %1, %2, %3, %4, %5, %6, %7, %8, %9, %10, %11, %12, %13, %14, %15, %16, %17, %18, %19, %20, %21, %22, %23}, {%24,%25,%26,%27}, db, 1, 1, 1, 0;\n}\n"
    : "+f"(d[40]), "+f"(d[41]), "+f"(d[42]), "+f"(d[43]), "+f"(d[44]), "+f"(d[45]), "+f"(d[46]), "+f"(d[47]), "+f"(d[48]), "+f"(d[49]), "+f"(d[50]), "+f"(d[51]), "+f"(d[52]), "+f"(d[53]), "+f"(d[54]), "+f"(d[55]), "+f"(d[56]), "+f"(d[57]), "+f"(d[58]), "+f"(d[59]), "+f"(d[60]), "+f"(d[61]), "+f"(d[62]), "+f"(d[63])
    : "r"(a0), "r"(a1), "r"(a2), "r"(a3), "r"(blo));
}
template<> __device__ __forceinline__ void wgmma_rs_hi<64>(float (&d)[64], uint32_t a0, uint32_t a1, uint32_t a2, uint32_t a3, uint32_t blo){
  asm volatile("{\n.reg .b64 db;\nmov.b64 db, {%36,8};\nwgmma.mma_async.sync.aligned.m64n64k16.f32.bf16.bf16 {%0, %1, %2, %3, %4, %5, %6, %7, %8, %9, %10, %11, %12, %13, %14, %15, %16, %17, %18, %19, %20, %21, %22, %23, %24, %25, %26, %27, %28, %29, %30, %31}, {%32,%33,%34,%35}, db, 1, 1, 1, 0;\n}\n"
    : "+f"(d[32]), "+f"(d[33]), "+f"(d[34]), "+f"(d[35]), "+f"(d[36]), "+f"(d[37]), "+f"(d[38]), "+f"(d[39]), "+f"(d[40]), "+f"(d[41]), "+f"(d[42]), "+f"(d[43]), "+f"(d[44]), "+f"(d[45]), "+f"(d[46]), "+f"(d[47]), "+f"(d[48]), "+f"(d[49]), "+f"(d[50]), "+f"(d[51]), "+f"(d[52]), "+f"(d[53]), "+f"(d[54]), "+f"(d[55]), "+f"(d[56]), "+f"(d[57]), "+f"(d[58]), "+f"(d[59]), "+f"(d[60]), "+f"(d[61]), "+f"(d[62]), "+f"(d[63])
    : "r"(a0), "r"(a1), "r"(a2), "r"(a3), "r"(blo));
}
template<> __device__ __forceinline__ void wgmma_rs_hi<80>(float (&d)[64], uint32_t a0, uint32_t a1, uint32_t a2, uint32_t a3, uint32_t blo){
  asm volatile("{\n.reg .b64 db;\nmov.b64 db, {%44,8};\nwgmma.mma_async.sync.aligned.m64n80k16.f32.bf16.bf16 {%0, %1, %2, %3, %4, %5, %6, %7, %8, %9, %10, %11, %12, %13, %14, %15, %16, %17, %18, %19, %20, %21, %22, %23, %24, %25, %26, %27, %28, %29, %30, %31, %32, %33, %34, %35, %36, %37, %38, %39}, {%40,%41,%42,%43}, db, 1, 1, 1, 0;\n}\n"
    : "+f"(d[24]), "+f"(d[25]), "+f"(d[26]), "+f"(d[27]), "+f"(d[28]), "+f"(d[29]), "+f"(d[30]), "+f"(d[31]), "+f"(d[32]), "+f"(d[33]), "+f"(d[34]), "+f"(d[35]), "+f"(d[36]), "+f"(d[37]), "+f"(d[38]), "+f"(d[39]), "+f"(d[40]), "+f"(d[41]), "+f"(d[42]), "+f"(d[43]), "+f"(d[44]), "+f"(d[45]), "+f"(d[46]), "+f"(d[47]), "+f"(d[48]), "+f"(d[49]), "+f"(d[50]), "+f"(d[51]), "+f"(d[52]), "+f"(d[53]), "+f"(d[54]), "+f"(d[55]), "+f"(d[56]), "+f"(d[57]), "+f"(d[58]), "+f"(d[59]), "+f"(d[60]), "+f"(d[61]), "+f"(d[62]), "+f"(d[63])
    : "r"(a0), "r"(a1), "r"(a2), "r"(a3), "r"(blo));
}
template<> __device__ __forceinline__ void wgmma_rs_hi<96>(float (&d)[64], uint32_t a0, uint32_t a1, uint32_t a2, uint32_t a3, uint32_t blo){
  asm volatile("{\n.reg .b64 db;\nmov.b64 db, {%52,8};\nwgmma.mma_async.sync.aligned.m64n96k16.f32.bf16.bf16 {%0, %1, %2, %3, %4, %5, %6, %7, %8, %9, %10, %11, %12, %13, %14, %15, %16, %17, %18, %19, %20, %21, %22, %23, %24, %25, %26, %27, %28, %29, %30, %31, %32, %33, %34, %35, %36, %37, %38, %39, %40, %41, %42, %43, %44, %45, %46, %47}, {%48,%49,%50,%51}, db, 1, 1, 1, 0;\n}\n"
    : "+f"(d[16]), "+f"(d[17]), "+f"(d[18]), "+f"(d[19]), "+f"(d[20]), "+f"(d[21]), "+f"(d[22]), "+f"(d[23]), "+f"(d[24]), "+f"(d[25]), "+f"(d[26]), "+f"(d[27]), "+f"(d[28]), "+f"(d[29]), "+f"(d[30]), "+f"(d[31]), "+f"(d[32]), "+f"(d[33]), "+f"(d[34]), "+f"(d[35]), "+f"(d[36]), "+f"(d[37]), "+f"(d[38]), "+f"(d[39]), "+f"(d[40]), "+f"(d[41]), "+f"(d[42]), "+f"(d[43]), "+f"(d[44]), "+f"(d[45]), "+f"(d[46]), "+f"(d[47]), "+f"(d[48]), "+f"(d[49]), "+f"(d[50]), "+f"(d[51]), "+f"(d[52]), "+f"(d[53]), "+f"(d[54]), "+f"(d[55]), "+f"(d[56]), "+f"(d[57]), "+f"(d[58]), "+f"(d[59]), "+f"(d[60]), "+f"(d[61]), "+f"(d[62]), "+f"(d[63])
    : "r"(a0), "r"(a1), "r"(a2), "r"(a3), "r"(blo));
}
template<> __device__ __forceinline__ void wgmma_rs_hi<112>(float (&d)[64], uint32_t a0, uint32_t a1, uint32_t a2, uint32_t a3, uint32_t blo){
  asm volatile("{\n.reg .b64 db;\nmov.b64 db, {%60,8};\nwgmma.mma_async.sync.aligned.m64n112k16.f32.bf16.bf16 {%0, %1, %2, %3, %4, %5, %6, %7, %8, %9, %10, %11, %12, %13, %14, %15, %16, %17, %18, %19, %20, %21, %22, %23, %24, %25, %26, %27, %28, %29, %30, %31, %32, %33, %34, %35, %36, %37, %38, %39, %40, %41, %42, %43, %44, %45, %46, %47, %48, %49, %50, %51, %52, %53, %54, %55}, {%56,%57,%58,%59}, db, 1, 1, 1, 0;\n}\n"
    : "+f"(d[8]), "+f"(d[9]), "+f"(d[10]), "+f"(d[11]), "+f"(d[12]), "+f"(d[13]), "+f"(d[14]), "+f"(d[15]), "+f"(d[16]), "+f"(d[17]), "+f"(d[18]), "+f"(d[19]), "+f"(d[20]), "+f"(d[21]), "+f"(d[22]), "+f"(d[23]), "+f"(d[24]), "+f"(d[25]), "+f"(d[26]), "+f"(d[27]), "+f"(d[28]), "+f"(d[29]), "+f"(d[30]), "+f"(d[31]), "+f"(d[32]), "+f"(d[33]), "+f"(d[34]), "+f"(d[35]), "+f"(d[36]), "+f"(d[37]), "+f"(d[38]), "+f"(d[39]), "+f"(d[40]), "+f"(d[41]), "+f"(d[42]), "+f"(d[43]), "+f"(d[44]), "+f"(d[45]), "+f"(d[46]), "+f"(d[47]), "+f"(d[48]), "+f"(d[49]), "+f"(d[50]), "+f"(d[51]), "+f"(d[52]), "+f"(d[53]), "+f"(d[54]), "+f"(d[55]), "+f"(d[56]), "+f"(d[57]), "+f"(d[58]), "+f"(d[59]), "+f"(d[60]), "+f"(d[61]), "+f"(d[62]), "+f"(d[63])
    : "r"(a0), "r"(a1), "r"(a2), "r"(a3), "r"(blo));
}
template<> __device__ __forceinline__ void wgmma_rs_hi<128>(float (&d)[64], uint32_t a0, uint32_t a1, uint32_t a2, uint32_t a3, uint32_t blo){
  asm volatile("{\n.reg .b64 db;\nmov.b64 db, {%68,8};\nwgmma.mma_async.sync.aligned.m64n128k16.f32.bf16.bf16 {%0, %1, %2, %3, %4, %5, %6, %7, %8, %9, %10, %11, %12, %13, %14, %15, %16, %17, %18, %19, %20, %21, %22, %23, %24, %25, %26, %27, %28, %29, %30, %31, %32, %33, %34, %35, %36, %37, %38, %39, %40, %41, %42, %43, %44, %45, %46, %47, %48, %49, %50, %51, %52, %53, %54, %55, %56, %57, %58, %59, %60, %61, %62, %63}, {%64,%65,%66,%67}, db, 1, 1, 1, 0;\n}\n"
    : "+f"(d[0]), "+f"(d[1]), "+f"(d[2]), "+f"(d[3]), "+f"(d[4]), "+f"(d[5]), "+f"(d[6]), "+f"(d[7]), "+f"(d[8]), "+f"(d[9]), "+f"(d[10]), "+f"(d[11]), "+f"(d[12]), "+f"(d[13]), "+f"(d[14]), "+f"(d[15]), "+f"(d[16]), "+f"(d[17]), "+f"(d[18]), "+f"(d[19]), "+f"(d[20]), "+f"(d[21]), "+f"(d[22]), "+f"(d[23]), "+f"(d[24]), "+f"(d[25]), "+f"(d[26]), "+f"(d[27]), "+f"(d[28]), "+f"(d[29]), "+f"(d[30]), "+f"(d[31]), "+f"(d[32]), "+f"(d[33]), "+f"(d[34]), "+f"(d[35]), "+f"(d[36]), "+f"(d[37]), "+f"(d[38]), "+f"(d[39]), "+f"(d[40]), "+f"(d[41]), "+f"(d[42]), "+f"(d[43]), "+f"(d[44]), "+f"(d[45]), "+f"(d[46]), "+f"(d[47]), "+f"(d[48]), "+f"(d[49]), "+f"(d[50]), "+f"(d[51]), "+f"(d[52]), "+f"(d[53]), "+f"(d[54]), "+f"(d[55]), "+f"(d[56]), "+f"(d[57]), "+f"(d[58]), "+f"(d[59]), "+f"(d[60]), "+f"(d[61]), "+f"(d[62]), "+f"(d[63])
    : "r"(a0), "r"(a1), "r"(a2), "r"(a3), "r"(blo));
}

__device__ __forceinline__ float shfl_sel(float a, float b, bool p, int src) {
  float r;
  asm volatile("{\n.reg .pred P;\n.reg .f32 t;\nsetp.ne.u32 P, %3, 0;\nselp.f32 t, %1, %2, P;\nshfl.sync.idx.b32 %0, t, %4, 0x1f, 0xffffffff;\n}\n"
               : "=f"(r) : "f"(a), "f"(b), "r"((uint32_t)p), "r"(src));
  return r;
}
struct CvCtx {
  uint32_t koff, zero, so[4];
  int srcA, srcB;
  bool wrapA, s3, kodd;
};
struct CvPipe { float Ep[2], keep[2], send[2]; };
template <int LO> __device__ __forceinline__ void cv_copy(float (&acc)[64]) {
#pragma unroll
  for (int i = LO; i < 64; i++) { float t; asm volatile("mov.b32 %0, %1;" : "=f"(t) : "f"(acc[i]) : "memory"); acc[i] = t; }
}
template <int G> __device__ __forceinline__ void cv_raw(uint32_t (&A)[4][4], uint32_t kaddr) {
#pragma unroll
  for (int i = 0; i < 4; i++) {
    const uint32_t a = kaddr + (4 * G + i) * 128;
    A[i][0] = lds32(a); A[i][1] = lds32(a + 4); A[i][3] = lds32(a + 8);
  }
}
__device__ __forceinline__ void cv_form(uint32_t (&A)[4][4], uint32_t sel) {
#pragma unroll
  for (int i = 0; i < 4; i++) {
    asm volatile("prmt.b32 %0, %0, %1, %2;" : "+r"(A[i][0]) : "r"(A[i][1]), "r"(sel));
    asm volatile("prmt.b32 %0, %1, %2, %3;" : "=r"(A[i][2]) : "r"(A[i][1]), "r"(A[i][3]), "r"(sel));
  }
}
#define CVV 2
template <int G> __device__ __forceinline__ void cv_step(float (&acc)[64], uint32_t (&A)[4][4], CvPipe& s, const CvCtx& c, uint32_t cb, uint32_t stg) {
  constexpr int JA = G - 1, JB = G - 2, NH = CVV == 1 ? 4 : (CVV == 3 ? 2 : 1);
  const uint32_t db0 = desc_lo(cb + CV_U + 192, CV_PL);
  uint32_t B[4][4];
  float ra[4], rb[2];
  if constexpr (G < 8) {
    wgmma_fence();
#pragma unroll
    for (int i = 0; i < NH; i++) wgmma_rs_hi<128 - 16 * (G & 7)>(acc, A[i][0], A[i][1], A[i][2], A[i][3], db0 - 4 * i);
    wgmma_commit();
    __syncwarp();
  }
  if constexpr (JA >= 0 && JA < 8) {
#pragma unroll
    for (int x = 0; x < 4; x++) {
      const int i = 8 * JA + 4 * (x >> 1) + 2 * (x & 1) + 1;
      ra[x] = shfl_sel(i >= 4 ? acc[i >= 4 ? i - 4 : 0] : 0.f, acc[i], c.wrapA, c.srcA);
    }
  }
  if constexpr (JB >= 0) {
#pragma unroll
    for (int h = 0; h < 2; h++) rb[h] = __shfl_sync(0xffffffffu, s.send[h], c.srcB);
  }
  if constexpr (G < 7) cv_raw<G + 1>(B, cb + c.koff);
  uint32_t z = 0;
  if constexpr (G < 8 && NH < 4) {
    __syncwarp();
    wgmma_fence();
#pragma unroll
    for (int i = NH; i < 4; i++) wgmma_rs_hi<128 - 16 * (G & 7)>(acc, A[i][0], A[i][1], A[i][2], A[i][3], db0 - 4 * i);
    wgmma_commit();
    asm volatile("mov.u32 %0, %%clock;" : "=r"(z)::"memory");
    z &= c.zero;
  }
  const float one = __uint_as_float(0x3f800000u | z);
  if constexpr (G < 7) cv_form(B, 0x5432u | z);
  if constexpr (JB >= 0) sts32(stg + ((JB & 1) ? c.so[JB >> 1] >> 16 : c.so[JB >> 1] & 0xffff), pack_bf16(fmaf(rb[0], one, s.keep[0]), fmaf(rb[1], one, s.keep[1])));
  if constexpr (JA >= 0 && JA < 8) {
#pragma unroll
    for (int h = 0; h < 2; h++) {
      const float ev = fmaf(ra[h], one, acc[8 * JA + 2 * h]), od = fmaf(ra[2 + h], one, acc[8 * JA + 4 + 2 * h]);
      s.send[h] = c.kodd ? ev : (c.s3 ? s.Ep[h] : od);
      s.keep[h] = c.kodd ? od : ev;
      s.Ep[h] = od;
    }
  }
  if constexpr (G < 8) { __syncwarp(); wgmma_wait<0>(); cv_copy<8 * (G & 7)>(acc); }
  if constexpr (G < 9) cv_step<G + 1>(acc, B, s, c, cb, stg);
}
__device__ __forceinline__ uint32_t cv_stage(int slot) { return sb + (slot < 4 ? 40960 + slot * 4096 : CV_OFF + CV_K); }
__device__ __forceinline__ void cv_setup(CvCtx& c) {
  const int tid = tid_opaque() & 127, w = tid >> 5, lane = tid & 31, r = lane >> 2, q = lane & 3;
  const int i0 = (r >> 1) & 1, i1 = r >> 2;
  c.koff = CV_K - 32 + 4 * (8 * (r >> 1) + 2 * w + (r & 1) + 2 * q);
  c.srcA = i0 ? lane - 8 : lane + 8 - q + ((q + 3) & 3);
  c.wrapA = i0 && q == 3;
  c.srcB = i1 == 0 ? (lane - q + 16 + ((q + 3) & 3)) : (lane - q - 16 + ((q + 1) & 3));
  c.s3 = (i1 == 1 && q == 3); c.kodd = (i1 == 1 && q < 3);
  c.zero = lds32(sb + EP_OFF + 24);
  const int tb = 16 * (2 * (i1 == 0 ? q : 4 + ((q + 1) & 3)) + i0) + 4 * w + 2 * (r & 1);
#pragma unroll
  for (int J = 0; J < 8; J++) {
    const int t = 256 * J + tb, T = t / 160, tl = t - T * 160;
    const int qq = (T == NT1 - 1) ? (tl >> 5) : (tl / 40);
    int ck = 20 * T + ((tl - qq * ((T == NT1 - 1) ? 32 : 40)) >> 1);
    ck ^= (ck >> 2) & 6;
    const uint32_t o = ck * 16 + qq * 4;
    if (J & 1) c.so[J >> 1] |= o << 16; else c.so[J >> 1] = o;
  }
}
__device__ __forceinline__ void conv_channel(int slot, const CvCtx& c) {
  const uint32_t cb = sb + CV_OFF + slot * CV_B;
  float acc[64];
  CvPipe s;
  s.Ep[0] = s.Ep[1] = 0.f;
  uint32_t A[4][4];
#pragma unroll
  for (int i = 0; i < 64; i++) acc[i] = 0.f;
  if (slot == 4) mbar_wait(bars + 8 * B_CVDONE);
  mbar_wait(bars + 8 * (B_CVFULL + slot));
  cv_raw<0>(A, cb + c.koff);
  cv_form(A, 0x5432u);
  cv_copy<0>(acc);
  cv_step<0>(acc, A, s, c, cb, cv_stage(slot));
  fence_async_smem();
  mbar_arrive(bars + 8 * (B_CVDONE + slot));
}

__device__ __forceinline__ void kv_issue(const Params& p, int c, int m2, int dg) {
  const uint32_t fb = bars + 8 * (B_KV + c);
  mbar_expect_tx(fb, KV_PIECE);
  tma3(sb + KS_OFF + c * KV_PIECE, &p.mK, 160 * dg + 32 * c, 64 * m2 - 3, 0, fb);
  tma3(sb + KS_OFF + c * KV_PIECE + 4864, &p.mV, 160 * dg + 32 * c, 64 * m2 - 1, 0, fb);
}
template <int W> struct KvRegs { uint32_t k[19][W], v[16][W], s[W][4]; };
template <int W> __device__ __forceinline__ void kv_load(int m, int cl, KvRegs<W>& x) {
  const int lane = tid_opaque() & 31, tg = lane >> 3;
  const uint32_t pb = sb + KS_OFF + (cl >> 5) * KV_PIECE + 2 * (cl & 31) + 4 * W * (lane & 7);
  const uint32_t ka = pb + tg * 1216, va = pb + 4864 + tg * 1088 + 64;
  const uint32_t kh = (m == 0 && tg > 0) ? ka - 192 : ka;
#pragma unroll
  for (int c = 0; c < W; c++) {
    const float4 t = lds128f(sb + TAP_OFF + 8 * cl + 16 * (W * (lane & 7) + c));
    x.s[c][0] = __float_as_uint(t.x); x.s[c][1] = __float_as_uint(t.y); x.s[c][2] = __float_as_uint(t.z); x.s[c][3] = __float_as_uint(t.w);
  }
  mbar_wait(bars + 8 * (B_KV + (cl >> 5)));
#pragma unroll
  for (int i = 0; i < 19; i++) {
    const uint32_t a = (i < 3 ? kh : ka) + i * 64;
    if (W == 2) { float2 t = lds64f(a); x.k[i][0] = __float_as_uint(t.x); x.k[i][W - 1] = __float_as_uint(t.y); }
    else x.k[i][0] = lds32(a);
  }
#pragma unroll
  for (int i = 0; i < 16; i++) {
    if (W == 2) { float2 t = lds64f(va + i * 64); x.v[i][0] = __float_as_uint(t.x); x.v[i][W - 1] = __float_as_uint(t.y); }
    else x.v[i][0] = lds32(va + i * 64);
  }
}
template <int W> __device__ __forceinline__ void kv_finish(int m, int c0, KvRegs<W>& x) {
  const int lane = tid_opaque() & 31;
  uint8_t* dst = g_kv + ((c0 + 2 * W * (lane & 7)) * 4096 + (4 * m + (lane >> 3)) * 16);
#pragma unroll
  for (int c = 0; c < W; c++) {
    const uint32_t w0 = __byte_perm(x.s[c][0], x.s[c][2], 0x5410), w1 = __byte_perm(x.s[c][0], x.s[c][2], 0x7632);
    const uint32_t w2 = __byte_perm(x.s[c][1], x.s[c][3], 0x5410), w3 = __byte_perm(x.s[c][1], x.s[c][3], 0x7632);
#pragma unroll
    for (int i = 0; i < 16; i++) {
      uint32_t a = hmul2(x.k[i][c], w3);
      a = hadd2(a, hmul2(x.k[i + 1][c], w2)); a = hadd2(a, hmul2(x.k[i + 2][c], w1)); a = hadd2(a, hmul2(x.k[i + 3][c], w0));
      x.v[i][c] = hmul2(a, x.v[i][c]);
    }
#pragma unroll
    for (int e = 0; e < 2; e++)
#pragma unroll
      for (int f = 0; f < 2; f++) {
        uint32_t o[4];
#pragma unroll
        for (int qq = 0; qq < 4; qq++) o[qq] = __byte_perm(x.v[15 - 4 * qq - 2 * f][c], x.v[14 - 4 * qq - 2 * f][c], e ? 0x7632 : 0x5410);
        *(uint4*)(dst + (2 * c + e) * 4096 + f * 2048) = make_uint4(o[0], o[1], o[2], o[3]);
      }
  }
}
__device__ __forceinline__ void ln_finish(float s1, float s2, float& mean, float& rstd) {
  mean = s1 * (1.f / 640.f);
  const float v = fmaxf(fmaf(-mean, mean, s2 * (1.f / 640.f)), 0.f) + 1e-5f;
  asm("rsqrt.approx.ftz.f32 %0, %1;" : "=f"(rstd) : "f"(v));
}
__device__ __forceinline__ void stat_table(int T1, unsigned want, int l, int w) {
#pragma unroll 1
  for (int g = w; g < (T1 == NT1 - 1 ? 4 : 5); g += 4) {
    const int n = 32 * g + (tid_opaque() & 31);
    const uint4* rp = &g_stats[8 * l * SEQ + 160 * T1 + n];
    float a[4], b[4];
    uint32_t it = 0;
    while (true) {
      bool ok = true;
#pragma unroll
      for (int i = 0; i < 4; i++) ok &= (rec_ld(rp + SEQ * i, a[i], b[i]) == want);
      if (__all_sync(0xffffffffu, ok)) break;
      trap_if(++it > SPIN_LIMIT);
    }
    float m, rs;
    ln_finish((a[0] + a[1]) + (a[2] + a[3]), (b[0] + b[1]) + (b[2] + b[3]), m, rs);
    sts64f(sb + STAB_OFF + n * 8, rs, -m * rs);
  }
  mbar_arrive(bars + 8 * (B_STAB + l));
}

template <bool FIRST>
__device__ __forceinline__ void stats_publish(int which, int n0, int dg, unsigned tag, const float (&acc)[80]) {
  const int q = tid_opaque() & 3, h = q & 1;
  float s1[2] = {0.f, 0.f}, s2[2] = {0.f, 0.f}, t1[2] = {0.f, 0.f}, t2[2] = {0.f, 0.f};
#pragma unroll
  for (int j = 0; j < 20; j++)
#pragma unroll
    for (int y = 0; y < 2; y++) {
      const float a = acc[4 * j + 2 * y], b = acc[4 * j + 2 * y + 1];
      s1[y] += a; t1[y] += b; s2[y] = fmaf(a, a, s2[y]); t2[y] = fmaf(b, b, t2[y]);
    }
#pragma unroll
  for (int y = 0; y < 2; y++) { s1[y] += t1[y]; s2[y] += t2[y]; }
  float a = (h ? s1[1] : s1[0]) + __shfl_xor_sync(0xffffffffu, h ? s1[0] : s1[1], 1);
  float b = (h ? s2[1] : s2[0]) + __shfl_xor_sync(0xffffffffu, h ? s2[0] : s2[1], 1);
  a += __shfl_xor_sync(0xffffffffu, a, 2);
  b += __shfl_xor_sync(0xffffffffu, b, 2);
  if (FIRST) {
    rec_st(&g_stats[((q >> 1) * 4 + dg) * SEQ + n0 + 8 * h], a, b, q < 2 ? tag : tag - 1);
    rec_st(&g_stats[((q >> 1) * 4 + 8 + dg) * SEQ + n0 + 8 * h], a, b, tag - 1);
  } else if (q < 2) rec_st(&g_stats[(which * 4 + dg) * SEQ + n0 + 8 * h], a, b, tag);
}
__device__ __forceinline__ void stats_get(int which, int n0, unsigned tag, float (&mean)[2], float (&rstd)[2]) {
  const uint4* p0 = &g_stats[(which * 4 + (tid_opaque() & 3)) * SEQ + n0];
  float a[2], b[2];
  uint32_t it = 0;
  while (true) {
    const unsigned t0 = rec_ld(p0, a[0], b[0]), t1 = rec_ld(p0 + 8, a[1], b[1]);
    if (__all_sync(0xffffffffu, t0 == tag && t1 == tag)) break;
    trap_if(++it > SPIN_LIMIT);
  }
#pragma unroll
  for (int o = 1; o < 4; o <<= 1)
#pragma unroll
    for (int h = 0; h < 2; h++) { a[h] += __shfl_xor_sync(0xffffffffu, a[h], o); b[h] += __shfl_xor_sync(0xffffffffu, b[h], o); }
#pragma unroll
  for (int h = 0; h < 2; h++) ln_finish(a[h], b[h], mean[h], rstd[h]);
}
__device__ __forceinline__ void x0_load(float (&acc)[80]) {
  const int t = tid_opaque() & 127;
  const uint32_t xa = sb + XT_OFF + (16 * (t >> 5) + ((t & 31) >> 2)) * 320 + 8 * (t & 3);
  mbar_wait(bars + 8 * B_XT);
#pragma unroll
  for (int h = 0; h < 2; h++)
#pragma unroll
    for (int J = 0; J < 10; J++) {
      const float2 v = lds64f(xa + h * 2560 + 32 * J);
      const uint32_t x = __float_as_uint(v.x), y = __float_as_uint(v.y);
      acc[8 * J + 2 * h] = bf_lo(x); acc[8 * J + 2 * h + 1] = bf_hi(x);
      acc[8 * J + 4 + 2 * h] = bf_lo(y); acc[8 * J + 4 + 2 * h + 1] = bf_hi(y);
    }
}

__global__ void __launch_bounds__(512, 1) fused_kernel(const __grid_constant__ Params p) {
  extern __shared__ __align__(1024) uint8_t smem_raw[];
  const int tid = threadIdx.x, lane = tid & 31;
  const int wid = __shfl_sync(0xffffffffu, tid >> 5, 0), wg = wid >> 2;
  unsigned smid; asm volatile("mov.u32 %0, %%smid;" : "=r"(smid));
  trap_if(smid >= 132 || smem_u32(smem_raw) != sb);
  int role;
  {
  const int side = smid & 1;
  int gpc, gi;
  {
    int tpc = smid >> 1;
    if (tpc < 32) { gpc = tpc & 7; gi = tpc >> 3; }
    else if (tpc < 60) { gpc = 1 + (tpc - 32) % 7; gi = 4 + (tpc - 32) / 7; }
    else if (tpc < 62) { gpc = tpc - 54; gi = 8; }
    else { gpc = 0; gi = tpc - 58; }
  }
  const int pos = 8 * gpc + gi + (gpc == 7 ? 1 : 0);
  if (pos == 65) {
    if (tid < 32) {
      const unsigned tag = ld_rlx(g_epoch);
      for (int i = lane; i < NT1 * 16; i += 32)
        if ((i & 15) < 10) { uint32_t it = 0; while ((int)(ld_rlx(&g_hflag[((i >> 4) * 32 + (i & 15)) * 8]) - tag) < 0) { __nanosleep(500); trap_if(++it > SPIN_LIMIT); } }
    }
    return;
  }
  int T1, GP;
  if (pos < 52) { int hh = pos / 26, x = pos - 26 * hh; T1 = x >> 1; GP = 2 * hh + (x & 1); }
  else { T1 = pos - 52; GP = 4; }
  const bool last = (T1 == NT1 - 1);
  const bool has2 = gi < 8;
  const int m2 = 8 * (gpc >> 1) + gi, dg = 2 * (gpc & 1) + side;
  role = T1 | (GP << 4) | (side << 7) | (m2 << 8) | (dg << 14) | ((int)has2 << 16);

  const int cch0 = 160 * dg + m2;
  if (wg < 2) {
    if (wid < 2) {
      const int ch = 128 * GP + 64 * wid + 32 * side + lane;
      uint32_t r0 = ldv16(p.lre + ch), r1 = ldv16(p.lim + ch), r2 = ldv16(p.logdt + ch);
      const float lr = bf_lo(r0), li = bf_lo(r1), ld = bf_lo(r2);
      const float dt = __bfloat162float(__float2bfloat16_rn(expf(ld)));
      const float mag = expf(dt * lr);
      float sn, cs; sincospif(dt * li * 0.31830988618379067f, &sn, &cs);
      const float ar = mag * cs, ai = mag * sn;
      const float inv = 2.f / (lr * lr + li * li);
      const uint32_t ad = sb + CTAB_OFF + (32 * wid + lane) * 24;
      sts64f(ad, ar, ai);
      sts64f(ad + 8, ((ar - 1.f) * lr + ai * li) * inv, (ai * lr - (ar - 1.f) * li) * inv);
      if (tid == 0) TS(46);
      __syncwarp();
      bar_sync(7, 96);
      mbar_arrive(bars + 8 * B_CTAB);
    } else {
      if (elect_one()) {
        if (wid < 5) {
#pragma unroll
          for (int i = 0; i < 27; i++) mbar_init(bars + 8 * (4 + 27 * (wid - 2) + i), 2);
        } else {
#pragma unroll
          for (int i = 0; i < 15; i++) mbar_init(bars + 8 * (85 + 15 * (wid - 5) + i), 1);
        }
        asm volatile("fence.mbarrier_init.release.cluster;" ::: "memory");
      }
      __syncwarp();
      bar_sync(5, 288);
      if (wid == 2) asm volatile("bar.arrive 6, 64;\nbar.arrive 9, 64;\nbar.arrive 7, 96;\nbar.arrive 8, 160;" ::: "memory");
    }
  } else if (wg == 2) {
    uint2 bv[4][5];
    const int c = has2 ? cch0 + 32 * (wid - 8) : 0;
    const unsigned tag0 = ld_rlx(g_epoch);
#pragma unroll
    for (int x = 0; x < 4; x++)
#pragma unroll
      for (int i = 0; i < 5; i++) {
        bv[x][i] = make_uint2(0u, 0u);
        if (x < 2 || wid == 8) bv[x][i] = ldv64((const uint2*)(((x & 1) ? p.bim : p.bre) + (c + 64 * (x & 2)) * DM) + lane + 32 * i);
      }
    float sv[4];
#pragma unroll
    for (int x = 0; x < 4; x++) {
      float a = 0.f;
#pragma unroll
      for (int i = 0; i < 5; i++) {
        a += (bf_lo(bv[x][i].x) + bf_hi(bv[x][i].x)) + (bf_lo(bv[x][i].y) + bf_hi(bv[x][i].y));
      }
      sv[x] = a;
    }
    float s0 = (lane & 16) ? sv[2] : sv[0], s1 = (lane & 16) ? sv[3] : sv[1];
    s0 += __shfl_xor_sync(0xffffffffu, (lane & 16) ? sv[0] : sv[2], 16);
    s1 += __shfl_xor_sync(0xffffffffu, (lane & 16) ? sv[1] : sv[3], 16);
#pragma unroll
    for (int o = 8; o > 0; o >>= 1) { s0 += __shfl_xor_sync(0xffffffffu, s0, o); s1 += __shfl_xor_sync(0xffffffffu, s1, o); }
    if (has2 && (lane & 14) == 0 && (lane < 16 || wid == 8)) rec_st(&g_sB[(c + 8 * (lane & 16)) * 2 + (lane & 1)], s0, s1, tag0);
    if (tid == 256) TS(47);
    __syncwarp();
    bar_sync(8, 160);
  } else if (wid == 13) {
    uint4 tv[3];
    const uint32_t e0 = ld_rlx(g_epoch);
    uint32_t e1 = ldv16(p.ssmD + min(cch0 + 32 * lane, 639));
    const uint4 dv = ldv128((const uint4*)(p.dskip + 160 * dg) + min(lane, 19));
#pragma unroll
    for (int i = 0; i < 3; i++) tv[i] = ldv128((const uint4*)(p.shiftk + 640 * dg) + min(lane + 32 * i, 79));
    sts128(sb + DTAB_OFF + 16 * min(lane, 19), dv);
#pragma unroll
    for (int i = 0; i < 3; i++) sts128(sb + TAP_OFF + 16 * min(lane + 32 * i, 79), tv[i]);
    if (lane < 7) sts32(sb + EP_OFF + 4 * lane, lane < 5 ? e1 << 16 : (lane == 5 ? e0 : 0u));
    __syncwarp();
    bar_sync(9, 64);
    mbar_arrive(bars + 8 * B_CTAB);
    if (lane == 0) { mbar_arrive(bars + 8 * B_EP); TS(53); }
  } else if (wid == 12) {
    if (elect_one()) {
#pragma unroll
      for (int k = 0; k < S1; k++) mbar_init(bars + 8 * (B_G1FULL + k), 1);
#pragma unroll
      for (int k = 0; k < 23; k++) mbar_init(bars + 8 * (B_XT + k), 1);
      asm volatile("fence.mbarrier_init.release.cluster;" ::: "memory");
      TS(45);
    }
    __syncwarp();
    asm volatile("bar.arrive 5, 288;" ::: "memory");
    if (elect_one()) {
#pragma unroll 1
      for (int k = 0; k < S1; k++) {
        const uint32_t fb = bars + 8 * (B_G1FULL + k);
        mbar_expect_tx(fb, G1_STAGE);
        tma4(sb + k * G1_STAGE + G1_XOFF, last ? &p.mXl : &p.mX, 64 * k, 0, 0, last ? 0 : 80 * T1, fb);
        tma5(sb + k * G1_STAGE, &p.mB, 64 * k, 0, 0, 4 * side, 2 * GP, fb);
      }
      if (has2) {
        mbar_expect_tx(bars + 8 * B_XT, 20480);
#pragma unroll
        for (int h = 0; h < 2; h++) {
          const int ng = 8 * m2 + 4 * h, T = ng / 20;
          tma4(sb + XT_OFF + h * 10240, T == NT1 - 1 ? &p.mXtl : &p.mXt, 160 * dg, 0, 0, T == NT1 - 1 ? ng - 240 : ng + 60 * T, bars + 8 * B_XT);
        }
#pragma unroll 1
        for (int c = 0; c < KV0; c++) kv_issue(p, c, m2, dg);
      }
      TS(44);
    }
    __syncwarp();
    bar_sync(6, 64);
  } else {
    if (wid == 15 && elect_one()) {
#pragma unroll
      for (int i = 0; i < 13; i++) mbar_init(bars + 8 * (B_CVDONE + i), B_CVDONE + i == B_CTAB ? 96 : 128);
      asm volatile("fence.mbarrier_init.release.cluster;" ::: "memory");
    }
    __syncwarp();
    bar_sync(5, 288);
  }
  if (tid == 128) TS(0);
  }

  if (wg == 3) {
    asm volatile("setmaxnreg.dec.sync.aligned.u32 56;");
    ROLE(role)
    const int pw = wid & 3;
    unsigned tag = 0;
    if (pw > 0) { mbar_wait(bars + 8 * B_EP); tag = lds32(sb + EP_OFF + 20); }
    if (pw >= 2 && has2) {
      KvRegs<1> x;
      kv_load<1>(m2, 128 + 16 * (pw - 2), x);
      kv_finish<1>(m2, 160 * dg + 128 + 16 * (pw - 2), x);
      if (tid == 448) TS(51);
      bar_sync(3, 64);
      if (tid == 448) { st_rel(&g_kvflag[((dg * 5 + 4) * 32 + m2) * 8], tag); TS(30); }
      __syncwarp();
    }
    if (pw == 0) {
      if (elect_one()) {
#pragma unroll 1
        for (int l = 0; l < 2; l++) {
          const uint32_t fb0 = bars + 8 * (B_G1FULL + 10 * l), wb = bars + 8 * (B_G1DONE + 9 * l - S1);
          const uint32_t free0 = bars + 8 * (has2 ? B_G2DONE + 19 : B_G1DONE + 9);
          uint32_t dst = sb;
#pragma unroll 1
          for (int k = l == 0 ? S1 : 0; k < 10; k++) {
            mbar_wait(k >= S1 + l ? wb + 8 * k : (k < WPF1 || !has2 ? free0 : bars + 8 * (B_GO + 1)));
            mbar_expect_tx(fb0 + 8 * k, 16384);
            tma5(dst, &p.mB, 64 * k, 0, 0, 4 * side, 2 * GP, fb0 + 8 * k);
            dst += G1_STAGE; if (dst == sb + (S1 + l) * G1_STAGE) dst = sb;
          }
          if (has2) {
            const uint32_t fb2 = bars + 8 * (B_G2FULL + 20 * l), wb2 = bars + 8 * (B_G2DONE + 19 * l - 6);
            dst = sb + G2_WOFF;
            int kc = 0;
#pragma unroll 1
            for (int k = 0; k < 20; k++) {
              mbar_wait(k >= 6 + l ? wb2 + 8 * k : (k == 5 ? bars + 8 * B_XFREE : (k < WPF2 ? bars + 8 * (B_G1DONE + 10 * l + 9) : bars + 8 * (B_GO + 2 * l))));
              mbar_expect_tx(fb2 + 8 * k, G2_WB);
              tma5(dst, &p.mCre + (k & 1), kc, 0, 0, 0, 10 * dg, fb2 + 8 * k);
              kc += (k & 1) << 7; if (k == 9) kc = 64;
              dst += G2_WB; if (dst == sb + G2_WOFF + (6 + l) * G2_WB) dst = sb + G2_WOFF;
            }
          }
        }
      }
    } else if (pw == 1) {
#pragma unroll 1
      for (int l = 0; l < 2; l++) {
        if (l == 0) {
          if (elect_one()) {
            uint32_t dst = sb + G1_XOFF;
#pragma unroll 1
            for (int k = S1; k < 10; k++) {
              mbar_wait(bars + 8 * (B_G1DONE + k - S1));
              mbar_expect_tx(bars + 8 * (B_G1FULL + k), 20480);
              tma4(dst, last ? &p.mXl : &p.mX, 64 * k, 0, 0, last ? 0 : 80 * T1, bars + 8 * (B_G1FULL + k));
              dst += G1_STAGE; if (k == 2 * S1 - 1) dst = sb + G1_XOFF;
              if (has2 && k - S1 + KV0 < 5) kv_issue(p, k - S1 + KV0, m2, dg);
            }
          }
        } else {
          mbar_wait(bars + 8 * (has2 ? B_G2DONE + 19 : B_G1DONE + 9));
          const int mlo = (160 * T1) >> 6, nf = last ? 8 : 12;
          flag_poll(&g_uflag[(4 * mlo + min(lane, nf - 1)) * 8], tag);
          fence_async_global();
          if (elect_one()) {
            TS(20);
            const int bytes = last ? 16384 : 20480;
            const uint8_t* src = g_u + T1 * 204800;
            uint32_t dst = sb + G1_XOFF;
#pragma unroll 1
            for (int k = 0; k < 10; k++) {
              if (k > S1) mbar_wait(bars + 8 * (B_G1DONE + 9 - S1 + k));
              mbar_expect_tx(bars + 8 * (B_G1FULL + 10 + k), bytes);
              bulk_g2s(dst, src, bytes, bars + 8 * (B_G1FULL + 10 + k));
              src += 20480; dst += G1_STAGE; if (k == S1) dst = sb + G1_XOFF;
            }
          }
        }
        __syncwarp();
        if (has2) {
          mbar_wait(bars + 8 * (B_G1DONE + 10 * l + 9));
          const int Tlo = (64 * m2) / 160, Thi = (64 * m2 + 63) / 160;
          flag_poll(&g_hflag[(((l * NT1 + (lane < 16 ? Tlo : Thi)) * 2) * 16 + min(lane & 15, 9)) * 8], tag);
          fence_async_global();
          if (elect_one()) {
            TS(21 + 2 * l);
            const uint32_t fb2 = bars + 8 * (B_G2FULL + 20 * l), wb2 = bars + 8 * (B_G2DONE + 18 * l - SX2);
            const uint8_t* src = g_h + (l * 32 + m2) * 163840;
            uint32_t dst = sb;
#pragma unroll 1
            for (int k = 0; k < 20; k++) {
              if (k >= SX2 + 2 * l) mbar_wait(wb2 + 8 * k);
              if (k == 10) { mbar_wait(bars + 8 * (B_H1 + l)); fence_async_global(); }
              mbar_expect_tx(fb2 + 8 * k, G2_XB);
              bulk_g2s(dst, src, G2_XB, fb2 + 8 * k);
              src += 8192; dst += G2_XB; if (dst == sb + (SX2 + 2 * l) * G2_XB) dst = sb;
            }
          }
          __syncwarp();
        }
      }
    } else if (pw == 2) {
#pragma unroll 1
      for (int l = 0; l < 2; l++) {
        mbar_wait(bars + 8 * (B_HST + 2 * l));
        mbar_wait(bars + 8 * (B_HST + 2 * l + 1));
        __syncwarp();
        if (lane < 2) st_rel(&g_hflag[(((l * NT1 + T1) * 2 + lane) * 16 + 2 * GP + side) * 8], tag);
        if (lane == 0) TS(6 + 8 * l);
        __syncwarp();
        if (l == 0 && has2 && elect_one()) {
#pragma unroll 1
          for (int c = 0; c < 5; c++) {
            mbar_wait(bars + 8 * (B_CVDONE + c));
            bulk_s2g(g_G + (cch0 + 32 * c) * 4096, cv_stage(c), 4096);
          }
          asm volatile("cp.async.bulk.commit_group;" ::: "memory");
          asm volatile("cp.async.bulk.wait_group 0;" ::: "memory");
          fence_async_global();
          st_rel(&g_gflag[(dg * 32 + m2) * 8], tag);
        }
        __syncwarp();
      }
    } else if (has2) {
#pragma unroll 1
      for (int c = 0; c < 5; c++) {
        if (c < 4) mbar_wait(bars + 8 * (B_PD + c));
        const uint32_t cb = sb + CV_OFF + c * CV_B;
        sts128(lane < 8 ? cb + 16 * lane : (lane < 20 ? cb + CV_U + 16 * (lane - 8) : cb + CV_U + CV_PL + 16 * (lane - 20)), make_uint4(0, 0, 0, 0));
        fence_async_smem();
        __syncwarp();
        if (elect_one()) {
          mbar_expect_tx(bars + 8 * (B_TAPS + c), 4096);
          bulk_g2s(cb + CV_K, p.ssmk + (cch0 + 32 * c) * SEQ, 4096, bars + 8 * (B_TAPS + c));
        }
      }
      if (elect_one()) {
        asm volatile("prefetch.tensormap [%0];" ::"l"(&p.mCre) : "memory");
        asm volatile("prefetch.tensormap [%0];" ::"l"(&p.mCim) : "memory");
        asm volatile("prefetch.tensormap [%0];" ::"l"(&p.mG) : "memory");
      }
#pragma unroll 1
      for (int c = 0; c < 5; c++) {
        flag_poll(&g_kvflag[((dg * 5 + c) * 32 + lane) * 8], tag);
        fence_async_global();
        if (lane == 0 && (c & 3) == 0) TS(c ? 54 : 28);
        mbar_wait(bars + 8 * (B_TAPS + c));
        if (elect_one()) {
          const uint32_t fb = bars + 8 * (B_CVFULL + c), cb = sb + CV_OFF + c * CV_B;
          const uint32_t w0 = lds32(cb + CV_K);
          sts32(cb + CV_K, (w0 & 0xffff0000u) | (pack_bf16(bf_lo(w0) + __uint_as_float(lds32(sb + EP_OFF + 4 * c)), 0.f) & 0xffffu));
          mbar_expect_tx(fb, 4096);
          bulk_g2s(cb + CV_U + 192, g_kv + (cch0 + 32 * c) * 4096, 2048, fb);
          bulk_g2s(cb + CV_U + 192 + CV_PL, g_kv + (cch0 + 32 * c) * 4096 + 2048, 2048, fb);
        }
        __syncwarp();
      }
      const unsigned* hf = &g_hflag[(((lane < 16 ? (64 * m2) / 160 : (64 * m2 + 63) / 160) * 2 + 1) * 16 + min(lane & 15, 9)) * 8];
      mbar_wait(bars + 8 * (B_CVDONE + 0));
      if (elect_one()) { l2_prefetch(p.cre + (160 * dg + 5 * m2) * DM, 6400); l2_prefetch(p.cim + (160 * dg + 5 * m2) * DM, 6400); }
      flag_poll(hf, tag);
      __syncwarp();
      if (lane == 0) { mbar_arrive(bars + 8 * B_H1); TS(22); }
      mbar_wait(bars + 8 * (B_CVDONE + 4));
      flag_poll(&g_gflag[(dg * 32 + lane) * 8], tag);
      __syncwarp();
      fence_async_global();
      if (lane == 0) TS(29);
      if (elect_one()) {
        mbar_expect_tx(bars + 8 * B_GFULL, 20480);
        tma5(sb + G_OFF, &p.mG, 64 * m2, 0, 0, 0, 10 * dg, bars + 8 * B_GFULL);
      }
      mbar_wait(bars + 8 * (B_G1DONE + 19));
      flag_poll(hf + NT1 * 256, tag);
      __syncwarp();
      if (lane == 0) { mbar_arrive(bars + 8 * (B_H1 + 1)); TS(24); }
    }
  } else {
    asm volatile("setmaxnreg.inc.sync.aligned.u32 152;");
    const int w = wid & 3;
    mbar_wait(bars + 8 * B_EP);
    const unsigned tag = lds32(sb + EP_OFF + 20);
    if (wg == 2) {
      ROLE(role)
      if (has2) {
        {
          float xs[80];
          x0_load(xs);
          stats_publish<true>(0, 64 * m2 + 16 * w + (lane >> 2), dg, tag, xs);
        }
        if (tid == 256) TS(31);
        KvRegs<2> x;
        kv_load<2>(m2, 32 * w, x);
        if (tid == 352) TS(50);
        kv_finish<2>(m2, 160 * dg + 32 * w, x);
        __syncwarp();
        if (lane == 0) mbar_arrive(bars + 8 * (B_PD + w));
        if (tid == 352) TS(52);
        if (tid == 256) TS(48);
      }
      if (w == 1 || w == 2) {
        float a, b;
        rec_poll(&g_sB[(128 * GP + 64 * (w - 1) + 32 * side + lane) * 2], tag, a, b);
        sts64f(sb + CTAB_OFF + (32 * (w - 1) + lane) * 24 + 16, p.swap ? b : a, p.swap ? a : b);
      }
      stat_table(T1, tag, 0, (w + 1) & 3);
      if (has2 && lane == 0) st_rel(&g_kvflag[((dg * 5 + w) * 32 + m2) * 8], tag);
      __syncwarp();
      if (tid == 256) TS(49);
      if (tid == 352) TS(26);
      if (!has2) { mbar_wait(bars + 8 * (B_G1FULL + 11)); stat_table(T1, tag, 1, w); }
    }
#pragma unroll 1
    for (int l = 0; l < 2; l++) {
      if (wg < 2) {
        float acc[80];
#pragma unroll
        for (int i = 0; i < 80; i++) acc[i] = 0.f;
        ROLE(role)
        const int tid = tid_opaque(), r = (tid & 31) >> 2, q = tid & 3;
        const int ch = 128 * GP + 64 * wg + 32 * side + 8 * w + r;
        mbar_wait(bars + 8 * B_CTAB);
        const uint32_t ca = sb + CTAB_OFF + (32 * wg + 8 * w + r) * 24;
        float2 lam = lds64f(ca);
        const float2 coef = lds64f(ca + 8), lamc = make_float2(lam.x, -lam.y);
        float m00 = coef.x, m01 = -coef.y, m10 = -coef.y, m11 = -coef.x;
        if (p.swap) { lam = lamc; m00 = -coef.y; m01 = coef.x; m10 = -coef.x; m11 = -coef.y; }
        float2 p8, p16, pL, p2L;
        {
          const float2 p2 = cmul(lam, lam), p4 = cmul(p2, p2);
          p8 = cmul(p4, p4); p16 = cmul(p8, p8);
          pL = cmul(p16, p16);
          if (!last) pL = cmul(pL, p8);
          p2L = cmul(pL, pL);
        }
        fence_regs(acc);
        {
          uint32_t alo = desc_lo(sb, 16) + wg * 512, blo = l == 0 ? desc_lo(sb + G1_XOFF, 16) : desc_lo(sb + G1_XOFF, 128);
          const uint32_t bhi = l == 0 ? desc_hi(1024, 1) : desc_hi(1024, 0), xstep = l == 0 ? 2 : 16;
          const uint32_t aend = desc_lo(sb, 16) + (S1 + l) * (G1_STAGE >> 4);
          uint32_t fb = bars + 8 * (B_G1FULL + 10 * l);
          mbar_wait(fb);
          if (tid == 0) TS(1 + 8 * l);
#pragma unroll 1
          for (int k = 0; k < 10; k++) {
            uint32_t ok; const uint32_t nb = k < 9 ? fb + 8 : fb;
            wgmma_fence();
#pragma unroll
            for (int kk = 0; kk < 4; kk++) {
              wgmma_n160<0>(acc, alo + kk * 2, desc_hi(1024, 1), blo + kk * xstep, bhi);
              if (kk == 0) ok = mbar_test(nb);
            }
            wgmma_commit();
            alo += G1_STAGE >> 4; blo += G1_STAGE >> 4;
            if (alo >= aend) { alo -= (S1 + l) * (G1_STAGE >> 4); blo -= (S1 + l) * (G1_STAGE >> 4); }
            wgmma_wait<1>();
            if (k > 0 && (tid & 127) == 0) mbar_arrive(fb + 8 * (B_G1DONE - B_G1FULL - 1));
            if (!ok) mbar_wait(nb);
            fb += 8;
          }
        }
        mbar_wait(bars + 8 * (B_STAB + l));
        const float2 sB = lds64f(ca + 16);
        wgmma_wait<0>();
        fence_regs(acc);
        if ((tid & 127) == 0) { mbar_arrive(bars + 8 * (B_G1DONE + 10 * l + 9)); if (wg == 0) TS(2 + 8 * l); }
        float2 ec[3];
#pragma unroll
        for (int jj = 0; jj < 8; jj++)
#pragma unroll
          for (int y = 0; y < 3; y++) {
            if (y == 2 && (jj & 1)) continue;
            const int j = y == 2 ? 16 + (jj >> 1) : 8 * y + jj;
            const float4 st = lds128f(sb + STAB_OFF + (8 * j + 2 * q) * 8);
            acc[4 * j + 0] = fmaf(acc[4 * j + 0], st.x, st.y * sB.x);
            acc[4 * j + 2] = fmaf(acc[4 * j + 2], st.x, st.y * sB.y);
            acc[4 * j + 1] = fmaf(acc[4 * j + 1], st.z, st.w * sB.x);
            acc[4 * j + 3] = fmaf(acc[4 * j + 3], st.z, st.w * sB.y);
            ec[y] = jj == 0 ? make_float2(acc[4 * j + 0], acc[4 * j + 2]) : cfma(lam, ec[y], make_float2(acc[4 * j + 0], acc[4 * j + 2]));
            ec[y] = cfma(lam, ec[y], make_float2(acc[4 * j + 1], acc[4 * j + 3]));
          }
        float2 e = cfma(p16, ec[0], ec[1]);
        if (!last) e = cfma(p8, e, ec[2]);
        {
          float2 v = make_float2(__shfl_up_sync(0xffffffffu, e.x, 1, 4), __shfl_up_sync(0xffffffffu, e.y, 1, 4));
          if (q >= 1) e = cfma(pL, v, e);
          v = make_float2(__shfl_up_sync(0xffffffffu, e.x, 2, 4), __shfl_up_sync(0xffffffffu, e.y, 2, 4));
          if (q >= 2) e = cfma(p2L, v, e);
        }
        if (!last && (q == 3 || (q == 2 && l == 0))) rec_st(&g_E[((q == 3 ? l : 1) * NT1 + T1) * DM + ch], e.x, e.y, q == 3 ? tag : tag - 1);
        if (tid == 0) TS(3 + 8 * l);
        float2 ex = make_float2(__shfl_up_sync(0xffffffffu, e.x, 1, 4), __shfl_up_sync(0xffffffffu, e.y, 1, 4));
        if (q == 0) ex = make_float2(0.f, 0.f);
        float2 pLq, p160q, p640;
        {
          const float2 p80 = last ? cmul(p2L, p16) : p2L, p160 = cmul(p80, p80), p320 = cmul(p160, p160), one = make_float2(1.f, 0.f);
          p640 = cmul(p320, p320);
          pLq = cmul((q & 1) ? pL : one, (q & 2) ? p2L : one);
          p160q = cmul((q & 1) ? p160 : one, (q & 2) ? p320 : one);
        }
        float2 c, ev[3];
        unsigned tg[3];
        const uint4* ep = &g_E[(l * NT1 + T1 - 1 - q) * DM + ch];
#pragma unroll
        for (int j = 0; j < 20; j++) {
          if (j == CPOLL) {
#pragma unroll
            for (int i = 0; i < 3; i++) {
              ev[i] = make_float2(0.f, 0.f); tg[i] = tag;
              if (T1 - 1 - q - 4 * i >= 0) tg[i] = rec_ld(ep - 4 * i * DM, ev[i].x, ev[i].y);
            }
          }
#pragma unroll
          for (int x = 0; x < 2; x++) {
            const float b0 = acc[4 * j + x], b1 = acc[4 * j + 2 + x];
            acc[4 * j + x] = fmaf(b0, m00, b1 * m01);
            acc[4 * j + 2 + x] = fmaf(b0, m10, b1 * m11);
          }
          if (j == CPOLL - 1 || j == 19) asm volatile("" : "+f"(acc[4 * j]), "+f"(acc[4 * j + 1]), "+f"(acc[4 * j + 2]), "+f"(acc[4 * j + 3])::"memory");
        }
        {
          uint32_t it = 0;
          while (__any_sync(0xffffffffu, tg[0] != tag || tg[1] != tag || tg[2] != tag)) {
#pragma unroll
            for (int i = 0; i < 3; i++)
              if (tg[i] != tag) tg[i] = rec_ld(ep - 4 * i * DM, ev[i].x, ev[i].y);
            trap_if(++it > SPIN_LIMIT);
          }
          c = cfma(p640, cfma(p640, ev[2], ev[1]), ev[0]);
          c = cmul(c, p160q);
          c.x += __shfl_xor_sync(0xffffffffu, c.x, 1); c.y += __shfl_xor_sync(0xffffffffu, c.y, 1);
          c.x += __shfl_xor_sync(0xffffffffu, c.x, 2); c.y += __shfl_xor_sync(0xffffffffu, c.y, 2);
        }
        if (tid == 0) TS(4 + 8 * l);
        if (tid == 128) mbar_arrive(bars + 8 * (B_GO + 2 * l));
        c = cfma(pLq, c, ex);
        float2 hh = make_float2(fmaf(c.x, m00, c.y * m01), fmaf(c.x, m10, c.y * m11));
        uint8_t* hb = g_h + (size_t)l * (32 * 20 * 8192) + (10 * wg + 2 * GP) * 8192 + (4 * side + w) * 1024 + (tid_opaque() & 31) * 4;
#pragma unroll
        for (int j4 = 0; j4 < 5; j4++) {
          const int ng = 20 * T1 + 4 * j4;
          uint8_t* hp = hb + (size_t)(ng >> 3) * 163840 + (ng & 7) * 128;
#pragma unroll
          for (int jj = 0; jj < 4; jj++) {
            const int j = 4 * j4 + jj;
            const float2 h0 = cfma(lamc, hh, make_float2(acc[4 * j + 0], acc[4 * j + 2]));
            hh = cfma(lamc, h0, make_float2(acc[4 * j + 1], acc[4 * j + 3]));
            if (j4 < 4 || !last) {
              *(uint32_t*)(hp + jj * 128) = pack_bf16(h0.x, hh.x);
              *(uint32_t*)(hp + jj * 128 + 8192) = pack_bf16(h0.y, hh.y);
            }
          }
        }
        mbar_arrive(bars + 8 * (B_HST + 2 * l + wg));
        if (tid == 0) TS(5 + 8 * l);
      }
      if (l == 0) {
        ROLE(role)
        if (has2) {
          CvCtx cc;
          cv_setup(cc);
          mbar_wait(bars + 8 * (B_G1DONE + 9));
#pragma unroll 1
          for (int c = wg == 2 ? 0 : 2 + wg; c < (wg == 2 ? 2 : 5); c += wg == 2 ? 1 : 2) conv_channel(c, cc);
          if ((tid & 127) == 0) TS(wg == 2 ? 32 : 7 + wg);
        }
      }
      if (wg == 2) break;
    }
    if (wg == 2 && (role >> 16)) {
      float acc[80];
      float off[2] = {0.f, 0.f};
      x0_load(acc);
      mbar_arrive(bars + 8 * B_XFREE);
#pragma unroll 1
      for (int l = 0; l < 2; l++) {
        float mean[2], rstd[2];
        {
          ROLE(role)
          const int lane = tid_opaque() & 31;
          stats_get(2 * l, 64 * m2 + 16 * w + (lane >> 2), tag, mean, rstd);
          off[0] += mean[0]; off[1] += mean[1];
          mbar_wait(bars + 8 * (l == 0 ? B_CTAB : B_HST + 3));
#pragma unroll
          for (int J = 0; J < 10; J++) {
            const float2 dw = lds64f(sb + DTAB_OFF + 2 * (16 * J + 4 * (lane & 3)));
#pragma unroll
            for (int x = 0; x < 8; x++) {
              const int h = (x >> 1) & 1;
              const uint32_t gwd = __float_as_uint(x < 4 ? dw.x : dw.y);
              acc[8 * J + x] = (acc[8 * J + x] - mean[h]) * fmaf(rstd[h], (x & 1) ? bf_hi(gwd) : bf_lo(gwd), 1.f);
            }
          }
        }
        {
          const uint32_t aend = desc_lo(sb + SX2 * G2_XB, 1024) + l * (G2_XB >> 3), bend = desc_lo(sb + G2_WOFF + 6 * G2_WB, 16) + l * (G2_WB >> 4);
          uint32_t alo = desc_lo(sb, 1024), blo = desc_lo(sb + G2_WOFF, 16);
          uint32_t fb = bars + 8 * (B_G2FULL + 20 * l);
          fence_regs(acc);
          mbar_wait(fb);
          if (tid == 256) TS(33 + 6 * l);
#pragma unroll 1
          for (int k = 0; k < 20; k++) {
            if (l == 1 && (k & 3) == 3 && tid == 256) TS(56 + (k >> 2));
            uint32_t ok; const uint32_t nb = k < 19 ? fb + 8 : fb;
            wgmma_fence();
#pragma unroll
            for (int kk = 0; kk < 4; kk++) {
              wgmma_n160<1>(acc, alo + kk * 128, desc_hi(128, 0), blo + kk * 2, desc_hi(1024, 1));
              if (kk == 0) ok = mbar_test(nb);
            }
            wgmma_commit();
            alo += G2_XB >> 4; if (alo == aend) alo = desc_lo(sb, 1024);
            blo += G2_WB >> 4; if (blo == bend) blo = desc_lo(sb + G2_WOFF, 16);
            wgmma_wait<1>();
            if (k > 0 && tid == 256) mbar_arrive(fb + 8 * (B_G2DONE - B_G2FULL - 1));
            if (!ok) mbar_wait(nb);
            fb += 8;
          }
          wgmma_wait<0>();
          fence_regs(acc);
          if (tid == 256) TS(34 + 6 * l);
          if (tid == 256) mbar_arrive(bars + 8 * (B_G2DONE + 20 * l + 19));
        }
        ROLE(role)
        const int tq = tid_opaque() & 31, n0 = 64 * m2 + 16 * w + (tq >> 2);
        stats_publish<false>(2 * l + 1, n0, dg, tag, acc);
        uint32_t gf[10][4];
        mbar_wait(bars + 8 * B_GFULL);
        const uint32_t ga = sb + G_OFF + (8 * (tq >> 4) + (tq & 7)) * 128 + (((2 * w + ((tq >> 3) & 1)) ^ ((2 * m2) & 6) ^ (tq & 7)) << 4);
#pragma unroll
        for (int J = 0; J < 2; J++) ldsm4t(gf[J], ga + J * 2048);
        if (tid == 256) TS(35 + 6 * l);
        uint8_t* dst[2][2];
#pragma unroll
        for (int h = 0; h < 2; h++) {
          if (l == 0) {
            const int ng = 8 * m2 + 2 * w + h, T = ng / 20;
            uint8_t* ub = g_u + (T * 204800 + (ng - 20 * T) * 1024 + (tq & 2) * 64 + (tq & 28) * 4 + (tq & 1) * 8 + (5 * dg >> 1) * 20480);
            dst[h][1] = ub + ((dg & 1) ? 20480 - 512 : 0);
            dst[h][0] = ub + (dg & 1) * 512;
          } else {
            dst[h][0] = dst[h][1] = (uint8_t*)(p.out + (n_to_t(n0 + 8 * h) * DM + 160 * dg + 4 * (tq & 3)));
          }
        }
        stats_get(2 * l + 1, n0, tag, mean, rstd);
        if (tid == 256) { TS(36 + 6 * l); if (l == 0) mbar_arrive(bars + 8 * (B_GO + 1)); }
        off[0] += mean[0]; off[1] += mean[1];
        const float ov[2] = {l ? off[0] : 0.f, l ? off[1] : 0.f};
#pragma unroll
        for (int J = 0; J < 10; J++) {
          if (J + 2 < 10) ldsm4t(gf[J + 2 < 10 ? J + 2 : 0], ga + (J + 2) * 2048);
#pragma unroll
          for (int x = 0; x < 8; x++) {
            const int h = (x >> 1) & 1;
            const uint32_t gwd = gf[J][x >> 1];
            const float t = fmaf(rstd[h], (x & 1) ? bf_hi(gwd) : bf_lo(gwd), 1.f);
            acc[8 * J + x] = fmaf(acc[8 * J + x], t, fmaf(-mean[h], t, ov[h]));
          }
#pragma unroll
          for (int h = 0; h < 2; h++) {
            if (l == 0)
              *(uint2*)(dst[h][(J >> 1) & 1] + (J >> 2) * 20480 + (J & 3) * 256) =
                  make_uint2(pack_bf16(acc[8 * J + 2 * h], acc[8 * J + 2 * h + 1]), pack_bf16(acc[8 * J + 4 + 2 * h], acc[8 * J + 5 + 2 * h]));
            else
              *(float4*)(dst[h][0] + 64 * J) = make_float4(acc[8 * J + 2 * h], acc[8 * J + 2 * h + 1], acc[8 * J + 4 + 2 * h], acc[8 * J + 5 + 2 * h]);
          }
          __syncwarp();
        }
        if (l == 0) {
          bar_sync(3, 128);
          if (tid == 256) { TS(37); st_rel(&g_uflag[(4 * m2 + dg) * 8], tag); TS(38); }
          stats_publish<false>(2, n0, dg, tag, acc);
          mbar_wait(bars + 8 * (B_G1FULL + 11));
          stat_table(T1, tag, 1, w);
          if (tid == 256) TS(27);
        } else {
          if (tid == 256) {
            TS(43);
            if (m2 == 31 && dg == 3) asm volatile("st.relaxed.gpu.global.u32 [%0], %1;" ::"l"(g_epoch), "r"(tag + 1) : "memory");
          }
        }
      }
    }
  }
}

typedef CUresult (*EncFn)(CUtensorMap*, CUtensorMapDataType, cuuint32_t, void*, const cuuint64_t*, const cuuint64_t*,
                          const cuuint32_t*, const cuuint32_t*, CUtensorMapInterleave, CUtensorMapSwizzle,
                          CUtensorMapL2promotion, CUtensorMapFloatOOBfill);

void encode(EncFn fn, CUtensorMap* m, const void* ptr, int rank, const cuuint64_t* dims, const cuuint64_t* strides, const cuuint32_t* box,
            CUtensorMapSwizzle swz = CU_TENSOR_MAP_SWIZZLE_128B) {
  cuuint32_t es[5] = {1, 1, 1, 1, 1};
  fn(m, CU_TENSOR_MAP_DATA_TYPE_BFLOAT16, rank, (void*)ptr, dims, strides, box, es, CU_TENSOR_MAP_INTERLEAVE_NONE,
     swz, swz == CU_TENSOR_MAP_SWIZZLE_128B ? CU_TENSOR_MAP_L2_PROMOTION_L2_128B : CU_TENSOR_MAP_L2_PROMOTION_L2_64B, CU_TENSOR_MAP_FLOAT_OOB_FILL_NONE);
}

}

extern "C" void kernel_launch(void* const* d_in, const int* in_sizes, int n_in, void* d_out, int out_size) {
  (void)in_sizes; (void)n_in; (void)out_size;
  Params p;
  typedef const __nv_bfloat16* BP;
  p.x = (BP)d_in[0]; p.lre = (BP)d_in[1]; p.lim = (BP)d_in[2]; p.bre = (BP)d_in[3]; p.bim = (BP)d_in[4];
  p.cre = (BP)d_in[5]; p.cim = (BP)d_in[6]; p.logdt = (BP)d_in[7]; p.dskip = (BP)d_in[8];
  p.k = (BP)d_in[10]; p.v = (BP)d_in[11]; p.shiftk = (BP)d_in[12]; p.ssmk = (BP)d_in[13]; p.ssmD = (BP)d_in[14];
  p.out = (float*)d_out;
  void* fnp = nullptr;
  cudaDriverEntryPointQueryResult qr;
  cudaGetDriverEntryPoint("cuTensorMapEncodeTiled", &fnp, cudaEnableDefault, &qr);
  EncFn fn = (EncFn)fnp;
  void* gG = nullptr;
  cudaGetSymbolAddress(&gG, g_G);
  const cuuint64_t RB = DM * 2;
  {
    p.swap = p.bim < p.bre;
    const char* lo = (const char*)(p.swap ? p.bim : p.bre); const char* hi = (const char*)(p.swap ? p.bre : p.bim);
    cuuint64_t dims[5] = {640, 8, 2, 8, 10}, st[4] = {RB, (cuuint64_t)(hi - lo), 8 * RB, 64 * RB}; cuuint32_t box[5] = {64, 8, 2, 4, 2};
    encode(fn, &p.mB, lo, 5, dims, st, box);
  }
  {
    cuuint64_t dims[5] = {640, 2, 4, 2, 40}, st[4] = {RB, 4 * RB, 2 * RB, 16 * RB}; cuuint32_t box[5] = {64, 2, 4, 2, 10};
    encode(fn, &p.mCre, p.cre, 5, dims, st, box); encode(fn, &p.mCim, p.cim, 5, dims, st, box);
    cuuint64_t dimg[5] = {2048, 2, 4, 2, 40}, stg[4] = {4096, 4 * 4096, 2 * 4096, 16 * 4096};
    encode(fn, &p.mG, gG, 5, dimg, stg, box);
  }
  {
    cuuint64_t dims[4] = {640, 2, 4, 900}, st[3] = {RB, 40 * RB, 2 * RB}; cuuint32_t box[4] = {64, 2, 4, 20};
    encode(fn, &p.mX, p.x, 4, dims, st, box);
    cuuint64_t diml[4] = {640, 2, 4, 16}, stl[3] = {RB, 32 * RB, 2 * RB};
    encode(fn, &p.mXl, p.x + (size_t)1920 * DM, 4, diml, stl, box);
    cuuint32_t boxt[4] = {160, 2, 4, 4};
    encode(fn, &p.mXt, p.x, 4, dims, st, boxt, CU_TENSOR_MAP_SWIZZLE_NONE);
    encode(fn, &p.mXtl, p.x + (size_t)1920 * DM, 4, diml, stl, boxt, CU_TENSOR_MAP_SWIZZLE_NONE);
    cuuint64_t dk[3] = {640, 2000, 4}, sk[2] = {RB, 16 * RB}; cuuint32_t bk[3] = {32, 19, 4}, bv[3] = {32, 17, 4};
    encode(fn, &p.mK, p.k, 3, dk, sk, bk, CU_TENSOR_MAP_SWIZZLE_NONE);
    encode(fn, &p.mV, p.v, 3, dk, sk, bv, CU_TENSOR_MAP_SWIZZLE_NONE);
  }
  cudaFuncSetAttribute(fused_kernel, cudaFuncAttributeMaxDynamicSharedMemorySize, SMEM_BYTES);
  cudaLaunchConfig_t cfg = {};
  cfg.gridDim = dim3(132); cfg.blockDim = dim3(512); cfg.dynamicSmemBytes = SMEM_BYTES; cfg.stream = cudaStreamPerThread;
  cudaLaunchKernelEx(&cfg, fused_kernel, p);
}
```

```cpp
#include <cuda_runtime.h>
#include <cuda.h>
#include <cuda_bf16.h>
#include <stdint.h>

namespace {

constexpr int SEQ = 2048, DM = 640;
constexpr int NT1 = 13;
#define EXP 0
#define WPF1 1
#define WPF2 2
#define CPOLL 10
#define KV0 5
#define PAUSE_K 3
constexpr uint32_t SPIN_LIMIT = 1u << 22;

__device__ __align__(1024) uint8_t g_h[2 * 32 * 20 * 8192];
__device__ __align__(1024) uint8_t g_u[NT1 * 10 * 20480];
__device__ __align__(1024) uint8_t g_kv[DM * 4096];
__device__ __align__(1024) uint8_t g_G[DM * 4096];
__device__ __align__(128) uint4 g_E[2 * NT1 * DM];
__device__ __align__(128) uint4 g_stats[4 * 4 * SEQ];
__device__ __align__(128) uint4 g_sB[DM * 2];
__device__ __align__(128) unsigned g_hflag[2 * NT1 * 2 * 16 * 8];
__device__ __align__(128) unsigned g_uflag[32 * 4 * 8];
__device__ __align__(128) unsigned g_kvflag[4 * 5 * 32 * 8];
__device__ __align__(128) unsigned g_gflag[4 * 32 * 8];
__device__ __align__(128) unsigned g_epoch[32] = {1};
#define TS(i) do {} while (0)

struct Params {
  CUtensorMap mB, mCre, mCim, mX, mXl, mG, mK, mV, mXt, mXtl;
  const __nv_bfloat16 *x, *lre, *lim, *bre, *bim, *cre, *cim, *logdt, *dskip, *k, *v, *shiftk, *ssmk, *ssmD;
  float* out;
  int swap;
  int role[132];
};

constexpr uint32_t sb = 1024;
constexpr uint32_t G1_STAGE = 36864, G1_XOFF = 16384;
constexpr int S1 = 4;
constexpr uint32_t XT_OFF = 159744, KS_OFF = 180224, KV_PIECE = 9216;
constexpr uint32_t G2_XB = 8192, G2_WB = 20480, G2_WOFF = 57344, G_OFF = 200704;
constexpr int SX2 = 5;
constexpr uint32_t CV_OFF = KS_OFF, CV_K = 128, CV_PL = 2240, CV_U = CV_K + 4096, CV_B = KV_PIECE;
constexpr uint32_t MISC = 226304;
constexpr uint32_t BAR_OFF = MISC;
constexpr int B_G1FULL = 0, B_G1DONE = 20, B_G2FULL = 40,
              B_G2DONE = 85, B_GFULL = 125, B_EP = 126, B_H1 = 127  , B_TAPS = 129  , B_CVFULL = 134  ,
              B_GO = 139  , B_PD = 142  ,
              B_CVDONE = 148  , B_STAB = 153  , B_XFREE = 155, B_HST = 156  ,
              B_CTAB = 160, B_PREP = 161, B_XT = 162, B_KV = 163  ;
constexpr uint32_t bars = sb + BAR_OFF;
constexpr uint32_t STAB_OFF = MISC + 1344;
constexpr uint32_t CTAB_OFF = STAB_OFF + 1280;
constexpr uint32_t DTAB_OFF = CTAB_OFF + 1536;
constexpr uint32_t EP_OFF = DTAB_OFF + 320;
constexpr uint32_t TAP_OFF = 147456;
constexpr uint32_t SMEM_BYTES = 232448;
static_assert(EP_OFF + 32 <= SMEM_BYTES, "smem");

__device__ __forceinline__ void trap_if(bool c) { asm volatile("{\n.reg .pred p;\nsetp.ne.u32 p, %0, 0;\n@p trap;\n}\n" ::"r"((uint32_t)c)); }
__device__ __forceinline__ uint32_t smem_u32(const void* p) { return (uint32_t)__cvta_generic_to_shared(p); }
__device__ __forceinline__ void mbar_init(uint32_t bar, int cnt) { asm volatile("mbarrier.init.shared::cta.b64 [%0], %1;" ::"r"(bar), "r"(cnt) : "memory"); }
__device__ __forceinline__ void mbar_expect_tx(uint32_t bar, int bytes) { asm volatile("mbarrier.arrive.expect_tx.shared::cta.b64 _, [%0], %1;" ::"r"(bar), "r"(bytes) : "memory"); }
__device__ __forceinline__ void mbar_arrive(uint32_t bar) { asm volatile("mbarrier.arrive.shared::cta.b64 _, [%0];" ::"r"(bar) : "memory"); }
__device__ __forceinline__ void mbar_wait(uint32_t bar) {
  asm volatile(
      "{\n.reg .pred p;\n.reg .u32 c;\nmov.u32 c, 0;\n"
      "W_%=:\nmbarrier.try_wait.parity.shared::cta.b64 p, [%0], 0;\n@p bra D_%=;\n"
      "add.u32 c, c, 1;\nsetp.lt.u32 p, c, %1;\n@p bra W_%=;\ntrap;\nD_%=:\n}\n" ::"r"(bar), "n"(SPIN_LIMIT) : "memory");
}
__device__ __forceinline__ uint32_t mbar_test(uint32_t bar) {
  uint32_t ok;
  asm volatile("{\n.reg .pred p;\nmbarrier.test_wait.parity.shared::cta.b64 p, [%1], 0;\nselp.u32 %0, 1, 0, p;\n}\n" : "=r"(ok) : "r"(bar) : "memory");
  return ok;
}
__device__ __forceinline__ void tma3(uint32_t dst, const CUtensorMap* m, int c0, int c1, int c2, uint32_t bar) {
  asm volatile("cp.async.bulk.tensor.3d.shared::cluster.global.mbarrier::complete_tx::bytes [%0], [%1, {%3,%4,%5}], [%2];"
               ::"r"(dst), "l"(m), "r"(bar), "r"(c0), "r"(c1), "r"(c2) : "memory");
}
__device__ __forceinline__ void tma4(uint32_t dst, const CUtensorMap* m, int c0, int c1, int c2, int c3, uint32_t bar) {
  asm volatile("cp.async.bulk.tensor.4d.shared::cluster.global.mbarrier::complete_tx::bytes [%0], [%1, {%3,%4,%5,%6}], [%2];"
               ::"r"(dst), "l"(m), "r"(bar), "r"(c0), "r"(c1), "r"(c2), "r"(c3) : "memory");
}
__device__ __forceinline__ void tma5(uint32_t dst, const CUtensorMap* m, int c0, int c1, int c2, int c3, int c4, uint32_t bar) {
  asm volatile("cp.async.bulk.tensor.5d.shared::cluster.global.mbarrier::complete_tx::bytes [%0], [%1, {%3,%4,%5,%6,%7}], [%2];"
               ::"r"(dst), "l"(m), "r"(bar), "r"(c0), "r"(c1), "r"(c2), "r"(c3), "r"(c4) : "memory");
}
__device__ __forceinline__ void bulk_g2s(uint32_t dst, const void* src, int bytes, uint32_t bar) {
  asm volatile("cp.async.bulk.shared::cluster.global.mbarrier::complete_tx::bytes [%0], [%1], %2, [%3];"
               ::"r"(dst), "l"(src), "r"(bytes), "r"(bar) : "memory");
}
__device__ __forceinline__ void bulk_s2g(void* dst, uint32_t src, int bytes) {
  asm volatile("cp.async.bulk.global.shared::cta.bulk_group [%0], [%1], %2;" ::"l"(dst), "r"(src), "r"(bytes) : "memory");
}
__device__ __forceinline__ void l2_prefetch(const void* src, int bytes) {
  asm volatile("cp.async.bulk.prefetch.L2.global [%0], %1;" ::"l"(src), "r"(bytes) : "memory");
}
__device__ __forceinline__ void wgmma_fence() { asm volatile("wgmma.fence.sync.aligned;" ::: "memory"); }
__device__ __forceinline__ void wgmma_commit() { asm volatile("wgmma.commit_group.sync.aligned;" ::: "memory"); }
template <int N> __device__ __forceinline__ void wgmma_wait() { asm volatile("wgmma.wait_group.sync.aligned %0;" ::"n"(N) : "memory"); }
__host__ __device__ constexpr uint32_t desc_lo(uint32_t addr, uint32_t lbo) { return ((addr & 0x3FFFF) >> 4) | ((lbo >> 4) << 16); }
__host__ __device__ constexpr uint32_t desc_hi(uint32_t sbo, uint32_t swz) { return (sbo >> 4) | (swz << 30); }
__device__ __forceinline__ void bar_sync(int id, int n) { asm volatile("bar.sync %0, %1;" ::"r"(id), "r"(n) : "memory"); }
__device__ __forceinline__ uint32_t lds32(uint32_t a) { uint32_t v; asm volatile("ld.shared.u32 %0, [%1];" : "=r"(v) : "r"(a) : "memory"); return v; }
__device__ __forceinline__ float2 lds64f(uint32_t a) { float2 v; asm volatile("ld.shared.v2.f32 {%0,%1}, [%2];" : "=f"(v.x), "=f"(v.y) : "r"(a) : "memory"); return v; }
__device__ __forceinline__ float4 lds128f(uint32_t a) { float4 v; asm volatile("ld.shared.v4.f32 {%0,%1,%2,%3}, [%4];" : "=f"(v.x), "=f"(v.y), "=f"(v.z), "=f"(v.w) : "r"(a) : "memory"); return v; }
__device__ __forceinline__ void ldsm4t(uint32_t (&r)[4], uint32_t a) {
  asm volatile("ldmatrix.sync.aligned.m8n8.x4.trans.shared.b16 {%0,%1,%2,%3}, [%4];" : "=r"(r[0]), "=r"(r[1]), "=r"(r[2]), "=r"(r[3]) : "r"(a) : "memory");
}
__device__ __forceinline__ uint4 ldv128(const void* a) { uint4 v; asm volatile("ld.global.nc.v4.u32 {%0,%1,%2,%3}, [%4];" : "=r"(v.x), "=r"(v.y), "=r"(v.z), "=r"(v.w) : "l"(a) : "memory"); return v; }
__device__ __forceinline__ uint2 ldv64(const void* a) { uint2 v; asm volatile("ld.global.nc.v2.u32 {%0,%1}, [%2];" : "=r"(v.x), "=r"(v.y) : "l"(a) : "memory"); return v; }
__device__ __forceinline__ uint32_t ldv16(const void* a) { uint32_t v; asm volatile("ld.global.nc.u16 %0, [%1];" : "=r"(v) : "l"(a) : "memory"); return v; }
__device__ __forceinline__ void sts128(uint32_t a, uint4 v) { asm volatile("st.shared.v4.u32 [%0], {%1,%2,%3,%4};" ::"r"(a), "r"(v.x), "r"(v.y), "r"(v.z), "r"(v.w) : "memory"); }
__device__ __forceinline__ void sts32(uint32_t a, uint32_t v) { asm volatile("st.shared.u32 [%0], %1;" ::"r"(a), "r"(v) : "memory"); }
__device__ __forceinline__ void sts64f(uint32_t a, float x, float y) { asm volatile("st.shared.v2.f32 [%0], {%1,%2};" ::"r"(a), "f"(x), "f"(y) : "memory"); }
__device__ __forceinline__ void st_rel(unsigned* p, unsigned v) { asm volatile("st.release.gpu.global.u32 [%0], %1;" ::"l"(p), "r"(v) : "memory"); }
__device__ __forceinline__ void fence_async_global() { asm volatile("fence.proxy.async.global;" ::: "memory"); }
__device__ __forceinline__ void fence_async_smem() { asm volatile("fence.proxy.async.shared::cta;" ::: "memory"); }
__device__ __forceinline__ void rec_st(uint4* p, float a, float b, unsigned tag) {
  asm volatile("{\n.reg .b128 t;\n.reg .b64 lo, hi;\nmov.b64 lo, {%1,%2};\nmov.b64 hi, {%3,%3};\nmov.b128 t, {lo,hi};\n"
               "st.relaxed.gpu.global.b128 [%0], t;\n}\n" ::"l"(p), "r"(__float_as_uint(a)), "r"(__float_as_uint(b)), "r"(tag) : "memory");
}
__device__ __forceinline__ unsigned rec_ld(const uint4* p, float& a, float& b) {
  unsigned x, y, t;
  asm volatile("{\n.reg .b128 t;\n.reg .b64 lo, hi;\n.reg .b32 u;\nld.relaxed.gpu.global.b128 t, [%3];\nmov.b128 {lo,hi}, t;\n"
               "mov.b64 {%0,%1}, lo;\nmov.b64 {%2,u}, hi;\n}\n" : "=r"(x), "=r"(y), "=r"(t) : "l"(p) : "memory");
  a = __uint_as_float(x); b = __uint_as_float(y);
  return t;
}
__device__ __forceinline__ void rec_poll(const uint4* p, unsigned tag, float& a, float& b) {
  uint32_t it = 0;
  while (!__all_sync(0xffffffffu, rec_ld(p, a, b) == tag)) { trap_if(++it > SPIN_LIMIT); }
}
__device__ __forceinline__ unsigned ld_rlx(const unsigned* p) { unsigned v; asm volatile("ld.relaxed.gpu.global.u32 %0, [%1];" : "=r"(v) : "l"(p) : "memory"); return v; }
__device__ __forceinline__ void flag_poll(const unsigned* p, unsigned target) {
  uint32_t it = 0;
  while (!__all_sync(0xffffffffu, (int)(ld_rlx(p) - target) >= 0)) { trap_if(++it > SPIN_LIMIT); }
  asm volatile("fence.acquire.gpu;" ::: "memory");
}
__device__ __forceinline__ uint32_t pack_bf16(float lo, float hi) {
  uint32_t r; asm("cvt.rn.bf16x2.f32 %0, %1, %2;" : "=r"(r) : "f"(hi), "f"(lo)); return r;
}
__device__ __forceinline__ float bf_lo(uint32_t w) { return __uint_as_float(w << 16); }
__device__ __forceinline__ float bf_hi(uint32_t w) { return __uint_as_float(w & 0xffff0000u); }
__device__ __forceinline__ uint32_t hmul2(uint32_t a, uint32_t b) {
  __nv_bfloat162 r = __hmul2_rn(*(__nv_bfloat162*)&a, *(__nv_bfloat162*)&b); return *(uint32_t*)&r;
}
__device__ __forceinline__ uint32_t hadd2(uint32_t a, uint32_t b) {
  __nv_bfloat162 r = __hadd2_rn(*(__nv_bfloat162*)&a, *(__nv_bfloat162*)&b); return *(uint32_t*)&r;
}
__device__ __forceinline__ float2 cmul(float2 a, float2 b) { return make_float2(a.x * b.x - a.y * b.y, a.x * b.y + a.y * b.x); }
__device__ __forceinline__ float2 cfma(float2 a, float2 b, float2 c) {
  return make_float2(fmaf(a.x, b.x, fmaf(-a.y, b.y, c.x)), fmaf(a.x, b.y, fmaf(a.y, b.x, c.y)));
}
template <int N> __device__ __forceinline__ void fence_regs(float (&a)[N]) {
#pragma unroll
  for (int i = 0; i < N; i++) asm volatile("" : "+f"(a[i])::"memory");
}
__device__ __forceinline__ bool elect_one() {
  uint32_t e; asm volatile("{\n.reg .pred P;\nelect.sync _|P, 0xffffffff;\nselp.u32 %0, 1, 0, P;\n}\n" : "=r"(e)); return e != 0;
}
__device__ __forceinline__ int tid_opaque() { int t; asm volatile("mov.u32 %0, %%tid.x;" : "=r"(t)); return t; }
struct Role { int T1, GP, side, m2, dg, cch0; bool last, has2; };
__device__ __forceinline__ Role unpack_role(int x) {
  Role r; r.T1 = x & 15; r.GP = (x >> 4) & 7; r.side = (x >> 7) & 1; r.m2 = (x >> 8) & 63; r.dg = (x >> 14) & 3;
  r.has2 = (x >> 16) & 1; r.last = r.T1 == NT1 - 1; r.cch0 = 160 * r.dg + r.m2; return r;
}
__device__ __forceinline__ Role fresh_role(int x) { asm volatile("" : "+r"(x)); return unpack_role(__shfl_sync(0xffffffffu, x, 0)); }
#define ROLE(x) const Role R_ = fresh_role(x); const int T1 = R_.T1, GP = R_.GP, side = R_.side, m2 = R_.m2, dg = R_.dg, cch0 = R_.cch0; \
  const bool last = R_.last, has2 = R_.has2; (void)T1; (void)GP; (void)side; (void)m2; (void)dg; (void)cch0; (void)last; (void)has2;
__device__ __forceinline__ int n_to_t(int n) {
  int T = n / 160, nl = n - T * 160;
  int L = (T == NT1 - 1) ? 32 : 40;
  return T * 160 + L * ((nl & 7) >> 1) + 2 * (nl >> 3) + (nl & 1);
}

template<int TA> __device__ __forceinline__ void wgmma_n160(float (&d)[80], uint32_t alo, uint32_t ahi, uint32_t blo, uint32_t bhi){
  asm volatile("{\n.reg .b64 da, db;\nmov.b64 da, {%80,%81};\nmov.b64 db, {%82,%83};\n"
    "wgmma.mma_async.sync.aligned.m64n160k16.f32.bf16.bf16 {%0, %1, %2, %3, %4, %5, %6, %7, %8, %9, %10, %11, %12, %13, %14, %15, %16, %17, %18, %19, %20, %21, %22, %23, %24, %25, %26, %27, %28, %29, %30, %31, %32, %33, %34, %35, %36, %37, %38, %39, %40, %41, %42, %43, %44, %45, %46, %47, %48, %49, %50, %51, %52, %53, %54, %55, %56, %57, %58, %59, %60, %61, %62, %63, %64, %65, %66, %67, %68, %69, %70, %71, %72, %73, %74, %75, %76, %77, %78, %79}, da, db, 1, 1, 1, %84, 0;\n}\n"
    : "+f"(d[0]), "+f"(d[1]), "+f"(d[2]), "+f"(d[3]), "+f"(d[4]), "+f"(d[5]), "+f"(d[6]), "+f"(d[7]), "+f"(d[8]), "+f"(d[9]), "+f"(d[10]), "+f"(d[11]), "+f"(d[12]), "+f"(d[13]), "+f"(d[14]), "+f"(d[15]), "+f"(d[16]), "+f"(d[17]), "+f"(d[18]), "+f"(d[19]), "+f"(d[20]), "+f"(d[21]), "+f"(d[22]), "+f"(d[23]), "+f"(d[24]), "+f"(d[25]), "+f"(d[26]), "+f"(d[27]), "+f"(d[28]), "+f"(d[29]), "+f"(d[30]), "+f"(d[31]), "+f"(d[32]), "+f"(d[33]), "+f"(d[34]), "+f"(d[35]), "+f"(d[36]), "+f"(d[37]), "+f"(d[38]), "+f"(d[39]), "+f"(d[40]), "+f"(d[41]), "+f"(d[42]), "+f"(d[43]), "+f"(d[44]), "+f"(d[45]), "+f"(d[46]), "+f"(d[47]), "+f"(d[48]), "+f"(d[49]), "+f"(d[50]), "+f"(d[51]), "+f"(d[52]), "+f"(d[53]), "+f"(d[54]), "+f"(d[55]), "+f"(d[56]), "+f"(d[57]), "+f"(d[58]), "+f"(d[59]), "+f"(d[60]), "+f"(d[61]), "+f"(d[62]), "+f"(d[63]), "+f"(d[64]), "+f"(d[65]), "+f"(d[66]), "+f"(d[67]), "+f"(d[68]), "+f"(d[69]), "+f"(d[70]), "+f"(d[71]), "+f"(d[72]), "+f"(d[73]), "+f"(d[74]), "+f"(d[75]), "+f"(d[76]), "+f"(d[77]), "+f"(d[78]), "+f"(d[79])
    : "r"(alo), "r"(ahi), "r"(blo), "r"(bhi), "n"(TA));
}
template<int N> __device__ __forceinline__ void wgmma_rs_hi(float (&d)[64], uint32_t a0, uint32_t a1, uint32_t a2, uint32_t a3, uint32_t blo);
template<> __device__ __forceinline__ void wgmma_rs_hi<16>(float (&d)[64], uint32_t a0, uint32_t a1, uint32_t a2, uint32_t a3, uint32_t blo){
  asm volatile("{\n.reg .b64 db;\nmov.b64 db, {%12,8};\nwgmma.mma_async.sync.aligned.m64n16k16.f32.bf16.bf16 {%0, %1, %2, %3, %4, %5, %6, %7}, {%8,%9,%10,%11}, db, 1, 1, 1, 0;\n}\n"
    : "+f"(d[56]), "+f"(d[57]), "+f"(d[58]), "+f"(d[59]), "+f"(d[60]), "+f"(d[61]), "+f"(d[62]), "+f"(d[63])
    : "r"(a0), "r"(a1), "r"(a2), "r"(a3), "r"(blo));
}
template<> __device__ __forceinline__ void wgmma_rs_hi<32>(float (&d)[64], uint32_t a0, uint32_t a1, uint32_t a2, uint32_t a3, uint32_t blo){
  asm volatile("{\n.reg .b64 db;\nmov.b64 db, {%20,8};\nwgmma.mma_async.sync.aligned.m64n32k16.f32.bf16.bf16 {%0, %1, %2, %3, %4, %5, %6, %7, %8, %9, %10, %11, %12, %13, %14, %15}, {%16,%17,%18,%19}, db, 1, 1, 1, 0;\n}\n"
    : "+f"(d[48]), "+f"(d[49]), "+f"(d[50]), "+f"(d[51]), "+f"(d[52]), "+f"(d[53]), "+f"(d[54]), "+f"(d[55]), "+f"(d[56]), "+f"(d[57]), "+f"(d[58]), "+f"(d[59]), "+f"(d[60]), "+f"(d[61]), "+f"(d[62]), "+f"(d[63])
    : "r"(a0), "r"(a1), "r"(a2), "r"(a3), "r"(blo));
}
template<> __device__ __forceinline__ void wgmma_rs_hi<48>(float (&d)[64], uint32_t a0, uint32_t a1, uint32_t a2, uint32_t a3, uint32_t blo){
  asm volatile("{\n.reg .b64 db;\nmov.b64 db, {%28,8};\nwgmma.mma_async.sync.aligned.m64n48k16.f32.bf16.bf16 {%0, %1, %2, %3, %4, %5, %6, %7, %8, %9, %10, %11, %12, %13, %14, %15, %16, %17, %18, %19, %20, %21, %22, %23}, {%24,%25,%26,%27}, db, 1, 1, 1, 0;\n}\n"
    : "+f"(d[40]), "+f"(d[41]), "+f"(d[42]), "+f"(d[43]), "+f"(d[44]), "+f"(d[45]), "+f"(d[46]), "+f"(d[47]), "+f"(d[48]), "+f"(d[49]), "+f"(d[50]), "+f"(d[51]), "+f"(d[52]), "+f"(d[53]), "+f"(d[54]), "+f"(d[55]), "+f"(d[56]), "+f"(d[57]), "+f"(d[58]), "+f"(d[59]), "+f"(d[60]), "+f"(d[61]), "+f"(d[62]), "+f"(d[63])
    : "r"(a0), "r"(a1), "r"(a2), "r"(a3), "r"(blo));
}
template<> __device__ __forceinline__ void wgmma_rs_hi<64>(float (&d)[64], uint32_t a0, uint32_t a1, uint32_t a2, uint32_t a3, uint32_t blo){
  asm volatile("{\n.reg .b64 db;\nmov.b64 db, {%36,8};\nwgmma.mma_async.sync.aligned.m64n64k16.f32.bf16.bf16 {%0, %1, %2, %3, %4, %5, %6, %7, %8, %9, %10, %11, %12, %13, %14, %15, %16, %17, %18, %19, %20, %21, %22, %23, %24, %25, %26, %27, %28, %29, %30, %31}, {%32,%33,%34,%35}, db, 1, 1, 1, 0;\n}\n"
    : "+f"(d[32]), "+f"(d[33]), "+f"(d[34]), "+f"(d[35]), "+f"(d[36]), "+f"(d[37]), "+f"(d[38]), "+f"(d[39]), "+f"(d[40]), "+f"(d[41]), "+f"(d[42]), "+f"(d[43]), "+f"(d[44]), "+f"(d[45]), "+f"(d[46]), "+f"(d[47]), "+f"(d[48]), "+f"(d[49]), "+f"(d[50]), "+f"(d[51]), "+f"(d[52]), "+f"(d[53]), "+f"(d[54]), "+f"(d[55]), "+f"(d[56]), "+f"(d[57]), "+f"(d[58]), "+f"(d[59]), "+f"(d[60]), "+f"(d[61]), "+f"(d[62]), "+f"(d[63])
    : "r"(a0), "r"(a1), "r"(a2), "r"(a3), "r"(blo));
}
template<> __device__ __forceinline__ void wgmma_rs_hi<80>(float (&d)[64], uint32_t a0, uint32_t a1, uint32_t a2, uint32_t a3, uint32_t blo){
  asm volatile("{\n.reg .b64 db;\nmov.b64 db, {%44,8};\nwgmma.mma_async.sync.aligned.m64n80k16.f32.bf16.bf16 {%0, %1, %2, %3, %4, %5, %6, %7, %8, %9, %10, %11, %12, %13, %14, %15, %16, %17, %18, %19, %20, %21, %22, %23, %24, %25, %26, %27, %28, %29, %30, %31, %32, %33, %34, %35, %36, %37, %38, %39}, {%40,%41,%42,%43}, db, 1, 1, 1, 0;\n}\n"
    : "+f"(d[24]), "+f"(d[25]), "+f"(d[26]), "+f"(d[27]), "+f"(d[28]), "+f"(d[29]), "+f"(d[30]), "+f"(d[31]), "+f"(d[32]), "+f"(d[33]), "+f"(d[34]), "+f"(d[35]), "+f"(d[36]), "+f"(d[37]), "+f"(d[38]), "+f"(d[39]), "+f"(d[40]), "+f"(d[41]), "+f"(d[42]), "+f"(d[43]), "+f"(d[44]), "+f"(d[45]), "+f"(d[46]), "+f"(d[47]), "+f"(d[48]), "+f"(d[49]), "+f"(d[50]), "+f"(d[51]), "+f"(d[52]), "+f"(d[53]), "+f"(d[54]), "+f"(d[55]), "+f"(d[56]), "+f"(d[57]), "+f"(d[58]), "+f"(d[59]), "+f"(d[60]), "+f"(d[61]), "+f"(d[62]), "+f"(d[63])
    : "r"(a0), "r"(a1), "r"(a2), "r"(a3), "r"(blo));
}
template<> __device__ __forceinline__ void wgmma_rs_hi<96>(float (&d)[64], uint32_t a0, uint32_t a1, uint32_t a2, uint32_t a3, uint32_t blo){
  asm volatile("{\n.reg .b64 db;\nmov.b64 db, {%52,8};\nwgmma.mma_async.sync.aligned.m64n96k16.f32.bf16.bf16 {%0, %1, %2, %3, %4, %5, %6, %7, %8, %9, %10, %11, %12, %13, %14, %15, %16, %17, %18, %19, %20, %21, %22, %23, %24, %25, %26, %27, %28, %29, %30, %31, %32, %33, %34, %35, %36, %37, %38, %39, %40, %41, %42, %43, %44, %45, %46, %47}, {%48,%49,%50,%51}, db, 1, 1, 1, 0;\n}\n"
    : "+f"(d[16]), "+f"(d[17]), "+f"(d[18]), "+f"(d[19]), "+f"(d[20]), "+f"(d[21]), "+f"(d[22]), "+f"(d[23]), "+f"(d[24]), "+f"(d[25]), "+f"(d[26]), "+f"(d[27]), "+f"(d[28]), "+f"(d[29]), "+f"(d[30]), "+f"(d[31]), "+f"(d[32]), "+f"(d[33]), "+f"(d[34]), "+f"(d[35]), "+f"(d[36]), "+f"(d[37]), "+f"(d[38]), "+f"(d[39]), "+f"(d[40]), "+f"(d[41]), "+f"(d[42]), "+f"(d[43]), "+f"(d[44]), "+f"(d[45]), "+f"(d[46]), "+f"(d[47]), "+f"(d[48]), "+f"(d[49]), "+f"(d[50]), "+f"(d[51]), "+f"(d[52]), "+f"(d[53]), "+f"(d[54]), "+f"(d[55]), "+f"(d[56]), "+f"(d[57]), "+f"(d[58]), "+f"(d[59]), "+f"(d[60]), "+f"(d[61]), "+f"(d[62]), "+f"(d[63])
    : "r"(a0), "r"(a1), "r"(a2), "r"(a3), "r"(blo));
}
template<> __device__ __forceinline__ void wgmma_rs_hi<112>(float (&d)[64], uint32_t a0, uint32_t a1, uint32_t a2, uint32_t a3, uint32_t blo){
  asm volatile("{\n.reg .b64 db;\nmov.b64 db, {%60,8};\nwgmma.mma_async.sync.aligned.m64n112k16.f32.bf16.bf16 {%0, %1, %2, %3, %4, %5, %6, %7, %8, %9, %10, %11, %12, %13, %14, %15, %16, %17, %18, %19, %20, %21, %22, %23, %24, %25, %26, %27, %28, %29, %30, %31, %32, %33, %34, %35, %36, %37, %38, %39, %40, %41, %42, %43, %44, %45, %46, %47, %48, %49, %50, %51, %52, %53, %54, %55}, {%56,%57,%58,%59}, db, 1, 1, 1, 0;\n}\n"
    : "+f"(d[8]), "+f"(d[9]), "+f"(d[10]), "+f"(d[11]), "+f"(d[12]), "+f"(d[13]), "+f"(d[14]), "+f"(d[15]), "+f"(d[16]), "+f"(d[17]), "+f"(d[18]), "+f"(d[19]), "+f"(d[20]), "+f"(d[21]), "+f"(d[22]), "+f"(d[23]), "+f"(d[24]), "+f"(d[25]), "+f"(d[26]), "+f"(d[27]), "+f"(d[28]), "+f"(d[29]), "+f"(d[30]), "+f"(d[31]), "+f"(d[32]), "+f"(d[33]), "+f"(d[34]), "+f"(d[35]), "+f"(d[36]), "+f"(d[37]), "+f"(d[38]), "+f"(d[39]), "+f"(d[40]), "+f"(d[41]), "+f"(d[42]), "+f"(d[43]), "+f"(d[44]), "+f"(d[45]), "+f"(d[46]), "+f"(d[47]), "+f"(d[48]), "+f"(d[49]), "+f"(d[50]), "+f"(d[51]), "+f"(d[52]), "+f"(d[53]), "+f"(d[54]), "+f"(d[55]), "+f"(d[56]), "+f"(d[57]), "+f"(d[58]), "+f"(d[59]), "+f"(d[60]), "+f"(d[61]), "+f"(d[62]), "+f"(d[63])
    : "r"(a0), "r"(a1), "r"(a2), "r"(a3), "r"(blo));
}
template<> __device__ __forceinline__ void wgmma_rs_hi<128>(float (&d)[64], uint32_t a0, uint32_t a1, uint32_t a2, uint32_t a3, uint32_t blo){
  asm volatile("{\n.reg .b64 db;\nmov.b64 db, {%68,8};\nwgmma.mma_async.sync.aligned.m64n128k16.f32.bf16.bf16 {%0, %1, %2, %3, %4, %5, %6, %7, %8, %9, %10, %11, %12, %13, %14, %15, %16, %17, %18, %19, %20, %21, %22, %23, %24, %25, %26, %27, %28, %29, %30, %31, %32, %33, %34, %35, %36, %37, %38, %39, %40, %41, %42, %43, %44, %45, %46, %47, %48, %49, %50, %51, %52, %53, %54, %55, %56, %57, %58, %59, %60, %61, %62, %63}, {%64,%65,%66,%67}, db, 1, 1, 1, 0;\n}\n"
    : "+f"(d[0]), "+f"(d[1]), "+f"(d[2]), "+f"(d[3]), "+f"(d[4]), "+f"(d[5]), "+f"(d[6]), "+f"(d[7]), "+f"(d[8]), "+f"(d[9]), "+f"(d[10]), "+f"(d[11]), "+f"(d[12]), "+f"(d[13]), "+f"(d[14]), "+f"(d[15]), "+f"(d[16]), "+f"(d[17]), "+f"(d[18]), "+f"(d[19]), "+f"(d[20]), "+f"(d[21]), "+f"(d[22]), "+f"(d[23]), "+f"(d[24]), "+f"(d[25]), "+f"(d[26]), "+f"(d[27]), "+f"(d[28]), "+f"(d[29]), "+f"(d[30]), "+f"(d[31]), "+f"(d[32]), "+f"(d[33]), "+f"(d[34]), "+f"(d[35]), "+f"(d[36]), "+f"(d[37]), "+f"(d[38]), "+f"(d[39]), "+f"(d[40]), "+f"(d[41]), "+f"(d[42]), "+f"(d[43]), "+f"(d[44]), "+f"(d[45]), "+f"(d[46]), "+f"(d[47]), "+f"(d[48]), "+f"(d[49]), "+f"(d[50]), "+f"(d[51]), "+f"(d[52]), "+f"(d[53]), "+f"(d[54]), "+f"(d[55]), "+f"(d[56]), "+f"(d[57]), "+f"(d[58]), "+f"(d[59]), "+f"(d[60]), "+f"(d[61]), "+f"(d[62]), "+f"(d[63])
    : "r"(a0), "r"(a1), "r"(a2), "r"(a3), "r"(blo));
}

__device__ __forceinline__ float shfl_sel(float a, float b, bool p, int src) {
  float r;
  asm volatile("{\n.reg .pred P;\n.reg .f32 t;\nsetp.ne.u32 P, %3, 0;\nselp.f32 t, %1, %2, P;\nshfl.sync.idx.b32 %0, t, %4, 0x1f, 0xffffffff;\n}\n"
               : "=f"(r) : "f"(a), "f"(b), "r"((uint32_t)p), "r"(src));
  return r;
}
struct CvCtx {
  uint32_t koff, zero, so[4];
  int srcA, srcB;
  bool wrapA, s3, kodd;
};
struct CvPipe { float Ep[2], keep[2], send[2]; };
template <int LO> __device__ __forceinline__ void cv_copy(float (&acc)[64]) {
#pragma unroll
  for (int i = LO; i < 64; i++) { float t; asm volatile("mov.b32 %0, %1;" : "=f"(t) : "f"(acc[i]) : "memory"); acc[i] = t; }
}
template <int G> __device__ __forceinline__ void cv_raw(uint32_t (&A)[4][4], uint32_t kaddr) {
#pragma unroll
  for (int i = 0; i < 4; i++) {
    const uint32_t a = kaddr + (4 * G + i) * 128;
    A[i][0] = lds32(a); A[i][1] = lds32(a + 4); A[i][3] = lds32(a + 8);
  }
}
__device__ __forceinline__ void cv_form(uint32_t (&A)[4][4], uint32_t sel) {
#pragma unroll
  for (int i = 0; i < 4; i++) {
    asm volatile("prmt.b32 %0, %0, %1, %2;" : "+r"(A[i][0]) : "r"(A[i][1]), "r"(sel));
    asm volatile("prmt.b32 %0, %1, %2, %3;" : "=r"(A[i][2]) : "r"(A[i][1]), "r"(A[i][3]), "r"(sel));
  }
}
#define CVV 2
template <int G> __device__ __forceinline__ void cv_step(float (&acc)[64], uint32_t (&A)[4][4], CvPipe& s, const CvCtx& c, uint32_t cb, uint32_t stg) {
  constexpr int JA = G - 1, JB = G - 2, NH = CVV == 1 ? 4 : (CVV == 3 ? 2 : 1);
  const uint32_t db0 = desc_lo(cb + CV_U + 192, CV_PL);
  uint32_t B[4][4];
  float ra[4], rb[2];
  if constexpr (G < 8) {
    wgmma_fence();
#pragma unroll
    for (int i = 0; i < NH; i++) wgmma_rs_hi<128 - 16 * (G & 7)>(acc, A[i][0], A[i][1], A[i][2], A[i][3], db0 - 4 * i);
    wgmma_commit();
    __syncwarp();
  }
  if constexpr (JA >= 0 && JA < 8) {
#pragma unroll
    for (int x = 0; x < 4; x++) {
      const int i = 8 * JA + 4 * (x >> 1) + 2 * (x & 1) + 1;
      ra[x] = shfl_sel(i >= 4 ? acc[i >= 4 ? i - 4 : 0] : 0.f, acc[i], c.wrapA, c.srcA);
    }
  }
  if constexpr (JB >= 0) {
#pragma unroll
    for (int h = 0; h < 2; h++) rb[h] = __shfl_sync(0xffffffffu, s.send[h], c.srcB);
  }
  if constexpr (G < 7) cv_raw<G + 1>(B, cb + c.koff);
  uint32_t z = 0;
  if constexpr (G < 8 && NH < 4) {
    __syncwarp();
    wgmma_fence();
#pragma unroll
    for (int i = NH; i < 4; i++) wgmma_rs_hi<128 - 16 * (G & 7)>(acc, A[i][0], A[i][1], A[i][2], A[i][3], db0 - 4 * i);
    wgmma_commit();
    asm volatile("mov.u32 %0, %%clock;" : "=r"(z)::"memory");
    z &= c.zero;
  }
  const float one = __uint_as_float(0x3f800000u | z);
  if constexpr (G < 7) cv_form(B, 0x5432u | z);
  if constexpr (JB >= 0) sts32(stg + ((JB & 1) ? c.so[JB >> 1] >> 16 : c.so[JB >> 1] & 0xffff), pack_bf16(fmaf(rb[0], one, s.keep[0]), fmaf(rb[1], one, s.keep[1])));
  if constexpr (JA >= 0 && JA < 8) {
#pragma unroll
    for (int h = 0; h < 2; h++) {
      const float ev = fmaf(ra[h], one, acc[8 * JA + 2 * h]), od = fmaf(ra[2 + h], one, acc[8 * JA + 4 + 2 * h]);
      s.send[h] = c.kodd ? ev : (c.s3 ? s.Ep[h] : od);
      s.keep[h] = c.kodd ? od : ev;
      s.Ep[h] = od;
    }
  }
  if constexpr (G < 8) { __syncwarp(); wgmma_wait<0>(); cv_copy<8 * (G & 7)>(acc); }
  if constexpr (G < 9) cv_step<G + 1>(acc, B, s, c, cb, stg);
}
__device__ __forceinline__ uint32_t cv_stage(int slot) { return sb + (slot < 4 ? 40960 + slot * 4096 : CV_OFF + CV_K); }
__device__ __forceinline__ void cv_setup(CvCtx& c) {
  const int tid = tid_opaque() & 127, w = tid >> 5, lane = tid & 31, r = lane >> 2, q = lane & 3;
  const int i0 = (r >> 1) & 1, i1 = r >> 2;
  c.koff = CV_K - 32 + 4 * (8 * (r >> 1) + 2 * w + (r & 1) + 2 * q);
  c.srcA = i0 ? lane - 8 : lane + 8 - q + ((q + 3) & 3);
  c.wrapA = i0 && q == 3;
  c.srcB = i1 == 0 ? (lane - q + 16 + ((q + 3) & 3)) : (lane - q - 16 + ((q + 1) & 3));
  c.s3 = (i1 == 1 && q == 3); c.kodd = (i1 == 1 && q < 3);
  c.zero = lds32(sb + EP_OFF + 24);
  const int tb = 16 * (2 * (i1 == 0 ? q : 4 + ((q + 1) & 3)) + i0) + 4 * w + 2 * (r & 1);
#pragma unroll
  for (int J = 0; J < 8; J++) {
    const int t = 256 * J + tb, T = t / 160, tl = t - T * 160;
    const int qq = (T == NT1 - 1) ? (tl >> 5) : (tl / 40);
    int ck = 20 * T + ((tl - qq * ((T == NT1 - 1) ? 32 : 40)) >> 1);
    ck ^= (ck >> 2) & 6;
    const uint32_t o = ck * 16 + qq * 4;
    if (J & 1) c.so[J >> 1] |= o << 16; else c.so[J >> 1] = o;
  }
}
__device__ __forceinline__ void conv_channel(int slot, const CvCtx& c) {
  const uint32_t cb = sb + CV_OFF + slot * CV_B;
  float acc[64];
  CvPipe s;
  s.Ep[0] = s.Ep[1] = 0.f;
  uint32_t A[4][4];
#pragma unroll
  for (int i = 0; i < 64; i++) acc[i] = 0.f;
  if (slot == 4) mbar_wait(bars + 8 * B_CVDONE);
  mbar_wait(bars + 8 * (B_CVFULL + slot));
  cv_raw<0>(A, cb + c.koff);
  cv_form(A, 0x5432u);
  cv_copy<0>(acc);
  cv_step<0>(acc, A, s, c, cb, cv_stage(slot));
  fence_async_smem();
  mbar_arrive(bars + 8 * (B_CVDONE + slot));
}

__device__ __forceinline__ void kv_issue(const Params& p, int c, int m2, int dg) {
  const uint32_t fb = bars + 8 * (B_KV + c);
  mbar_expect_tx(fb, KV_PIECE);
  tma3(sb + KS_OFF + c * KV_PIECE, &p.mK, 160 * dg + 32 * c, 64 * m2 - 3, 0, fb);
  tma3(sb + KS_OFF + c * KV_PIECE + 4864, &p.mV, 160 * dg + 32 * c, 64 * m2 - 1, 0, fb);
}
__device__ __forceinline__ void kv_tile(int m, int dg, int c, int real) {
  const int lane = tid_opaque() & 31, tg = lane >> 3;
  const uint32_t pb = sb + KS_OFF + c * KV_PIECE + 8 * (lane & 7);
  const uint32_t ka = pb + tg * 1216, va = pb + 4864 + tg * 1088 + 64;
  const uint32_t kh = (m == 0 && tg > 0) ? ka - 192 : ka;
  float2 kk[19], vv[16];
#pragma unroll
  for (int i = 0; i < 19; i++) kk[i] = lds64f((i < 3 ? kh : ka) + i * 64);
#pragma unroll
  for (int i = 0; i < 16; i++) vv[i] = lds64f(va + i * 64);
  uint8_t* dst = g_kv + ((160 * dg + 32 * c + 4 * (lane & 7)) * 4096 + (4 * m + tg) * 16);
#pragma unroll
  for (int y = 0; y < 2; y++) {
    const float4 t = lds128f(sb + TAP_OFF + 256 * c + 32 * (lane & 7) + 16 * y);
    const uint32_t w0 = __byte_perm(__float_as_uint(t.x), __float_as_uint(t.z), 0x5410), w1 = __byte_perm(__float_as_uint(t.x), __float_as_uint(t.z), 0x7632);
    const uint32_t w2 = __byte_perm(__float_as_uint(t.y), __float_as_uint(t.w), 0x5410), w3 = __byte_perm(__float_as_uint(t.y), __float_as_uint(t.w), 0x7632);
    uint32_t u[16];
#pragma unroll
    for (int i = 0; i < 16; i++) {
      uint32_t a = hmul2(__float_as_uint(y ? kk[i].y : kk[i].x), w3);
      a = hadd2(a, hmul2(__float_as_uint(y ? kk[i + 1].y : kk[i + 1].x), w2));
      a = hadd2(a, hmul2(__float_as_uint(y ? kk[i + 2].y : kk[i + 2].x), w1));
      a = hadd2(a, hmul2(__float_as_uint(y ? kk[i + 3].y : kk[i + 3].x), w0));
      u[i] = hmul2(a, __float_as_uint(y ? vv[i].y : vv[i].x));
    }
#pragma unroll
    for (int e = 0; e < 2; e++)
#pragma unroll
      for (int f = 0; f < 2; f++) {
        uint32_t o[4];
#pragma unroll
        for (int qq = 0; qq < 4; qq++) o[qq] = __byte_perm(u[15 - 4 * qq - 2 * f], u[14 - 4 * qq - 2 * f], e ? 0x7632 : 0x5410);
        asm volatile("{\n.reg .pred p;\nsetp.ne.u32 p, %5, 0;\n@p st.global.v4.u32 [%0], {%1,%2,%3,%4};\n}\n"
                     ::"l"(dst + (2 * y + e) * 4096 + f * 2048), "r"(o[0]), "r"(o[1]), "r"(o[2]), "r"(o[3]), "r"(real) : "memory");
      }
  }
}
__device__ __forceinline__ void ln_finish(float s1, float s2, float& mean, float& rstd) {
  mean = s1 * (1.f / 640.f);
  const float v = fmaxf(fmaf(-mean, mean, s2 * (1.f / 640.f)), 0.f) + 1e-5f;
  asm("rsqrt.approx.ftz.f32 %0, %1;" : "=f"(rstd) : "f"(v));
}
__device__ __forceinline__ void stat_table(int T1, unsigned want, int l, int w) {
#pragma unroll 1
  for (int g = w; g < (T1 == NT1 - 1 ? 4 : 5); g += 4) {
    const int n = 32 * g + (tid_opaque() & 31);
    const uint4* rp = &g_stats[8 * l * SEQ + 160 * T1 + n];
    float a[4], b[4];
    uint32_t it = 0;
    while (true) {
      bool ok = true;
#pragma unroll
      for (int i = 0; i < 4; i++) ok &= (rec_ld(rp + SEQ * i, a[i], b[i]) == want);
      if (__all_sync(0xffffffffu, ok)) break;
      trap_if(++it > SPIN_LIMIT);
    }
    float m, rs;
    ln_finish((a[0] + a[1]) + (a[2] + a[3]), (b[0] + b[1]) + (b[2] + b[3]), m, rs);
    sts64f(sb + STAB_OFF + n * 8, rs, -m * rs);
  }
  mbar_arrive(bars + 8 * (B_STAB + l));
}

template <bool FIRST>
__device__ __forceinline__ void stats_publish(int which, int n0, int dg, unsigned tag, const float (&acc)[80]) {
  const int q = tid_opaque() & 3, h = q & 1;
  float s1[2] = {0.f, 0.f}, s2[2] = {0.f, 0.f}, t1[2] = {0.f, 0.f}, t2[2] = {0.f, 0.f};
#pragma unroll
  for (int j = 0; j < 20; j++)
#pragma unroll
    for (int y = 0; y < 2; y++) {
      const float a = acc[4 * j + 2 * y], b = acc[4 * j + 2 * y + 1];
      s1[y] += a; t1[y] += b; s2[y] = fmaf(a, a, s2[y]); t2[y] = fmaf(b, b, t2[y]);
    }
#pragma unroll
  for (int y = 0; y < 2; y++) { s1[y] += t1[y]; s2[y] += t2[y]; }
  float a = (h ? s1[1] : s1[0]) + __shfl_xor_sync(0xffffffffu, h ? s1[0] : s1[1], 1);
  float b = (h ? s2[1] : s2[0]) + __shfl_xor_sync(0xffffffffu, h ? s2[0] : s2[1], 1);
  a += __shfl_xor_sync(0xffffffffu, a, 2);
  b += __shfl_xor_sync(0xffffffffu, b, 2);
  if (FIRST) {
    rec_st(&g_stats[((q >> 1) * 4 + dg) * SEQ + n0 + 8 * h], a, b, q < 2 ? tag : tag - 1);
    rec_st(&g_stats[((q >> 1) * 4 + 8 + dg) * SEQ + n0 + 8 * h], a, b, tag - 1);
  } else if (q < 2) rec_st(&g_stats[(which * 4 + dg) * SEQ + n0 + 8 * h], a, b, tag);
}
__device__ __forceinline__ void stats_get(int which, int n0, unsigned tag, float (&mean)[2], float (&rstd)[2]) {
  const uint4* p0 = &g_stats[(which * 4 + (tid_opaque() & 3)) * SEQ + n0];
  float a[2], b[2];
  uint32_t it = 0;
  while (true) {
    const unsigned t0 = rec_ld(p0, a[0], b[0]), t1 = rec_ld(p0 + 8, a[1], b[1]);
    if (__all_sync(0xffffffffu, t0 == tag && t1 == tag)) break;
    trap_if(++it > SPIN_LIMIT);
  }
#pragma unroll
  for (int o = 1; o < 4; o <<= 1)
#pragma unroll
    for (int h = 0; h < 2; h++) { a[h] += __shfl_xor_sync(0xffffffffu, a[h], o); b[h] += __shfl_xor_sync(0xffffffffu, b[h], o); }
#pragma unroll
  for (int h = 0; h < 2; h++) ln_finish(a[h], b[h], mean[h], rstd[h]);
}
__device__ __forceinline__ void x0_load(float (&acc)[80]) {
  const int t = tid_opaque() & 127;
  const uint32_t xa = sb + XT_OFF + (16 * (t >> 5) + ((t & 31) >> 2)) * 320 + 8 * (t & 3);
  mbar_wait(bars + 8 * B_XT);
#pragma unroll
  for (int h = 0; h < 2; h++)
#pragma unroll
    for (int J = 0; J < 10; J++) {
      const float2 v = lds64f(xa + h * 2560 + 32 * J);
      const uint32_t x = __float_as_uint(v.x), y = __float_as_uint(v.y);
      acc[8 * J + 2 * h] = bf_lo(x); acc[8 * J + 2 * h + 1] = bf_hi(x);
      acc[8 * J + 4 + 2 * h] = bf_lo(y); acc[8 * J + 4 + 2 * h + 1] = bf_hi(y);
    }
}

__global__ void __launch_bounds__(512, 1) fused_kernel(const __grid_constant__ Params p) {
  extern __shared__ __align__(1024) uint8_t smem_raw[];
  const int tid = threadIdx.x, lane = tid & 31;
  const int wid = __shfl_sync(0xffffffffu, tid >> 5, 0), wg = wid >> 2;
  unsigned smid; asm volatile("mov.u32 %0, %%smid;" : "=r"(smid));
  const int role = p.role[min(smid, 131u)];
  if (wid == 12) {
    const bool el = elect_one();
    if (el) {
      asm volatile("prefetch.tensormap [%0];" ::"l"(&p.mX) : "memory");
      asm volatile("prefetch.tensormap [%0];" ::"l"(&p.mB) : "memory");
#pragma unroll
      for (int k = 0; k < S1; k++) mbar_init(bars + 8 * (B_G1FULL + k), 1);
#pragma unroll
      for (int k = 0; k < 6; k++) mbar_init(bars + 8 * (B_XT + k), 1);
      asm volatile("fence.mbarrier_init.release.cluster;" ::: "memory");
    }
    if (role >= 0) {
      __syncwarp();
      asm volatile("bar.arrive 5, 256;" ::: "memory");
      const Role R = unpack_role(role);
      if (elect_one()) {
        TS(45);
#pragma unroll 1
        for (int k = 0; k < S1; k++) {
          const uint32_t fb = bars + 8 * (B_G1FULL + k);
          mbar_expect_tx(fb, G1_STAGE);
          tma4(sb + k * G1_STAGE + G1_XOFF, R.last ? &p.mXl : &p.mX, 64 * k, 0, 0, R.last ? 0 : 80 * R.T1, fb);
          tma5(sb + k * G1_STAGE, &p.mB, 64 * k, 0, 0, 4 * R.side, 2 * R.GP, fb);
        }
        if (R.has2) {
          mbar_expect_tx(bars + 8 * B_XT, 20480);
#pragma unroll 1
          for (int h = 0; h < 2; h++) {
            const int ng = 8 * R.m2 + 4 * h, T = ng / 20;
            tma4(sb + XT_OFF + h * 10240, T == NT1 - 1 ? &p.mXtl : &p.mXt, 160 * R.dg, 0, 0, T == NT1 - 1 ? ng - 240 : ng + 60 * T, bars + 8 * B_XT);
          }
#pragma unroll 1
          for (int c = 0; c < KV0; c++) kv_issue(p, c, R.m2, R.dg);
        }
        TS(44);
      }
      __syncwarp();
      bar_sync(6, 64);
    }
  }
  trap_if(smid >= 132 || smem_u32(smem_raw) != sb);
  if (role < 0) {
    if (wid == 0) {
      const unsigned tag = ld_rlx(g_epoch);
#pragma unroll 1
      for (int i = 0; i < NT1; i++) {
        uint32_t it = 0;
        while (!__all_sync(0xffffffffu, (int)(ld_rlx(&g_hflag[(i * 32 + min(lane, 9)) * 8]) - tag) >= 0)) { __nanosleep(500); trap_if(++it > SPIN_LIMIT); }
      }
    }
    return;
  }
  if (wg == 2 || wid == 14) {
    ROLE(role)
    const int c = wid == 14 ? 4 : wid - 8;
    const unsigned tag = ld_rlx(g_epoch);
    if (has2) {
      uint2 bv[2][5];
#pragma unroll
      for (int x = 0; x < 2; x++)
#pragma unroll
        for (int i = 0; i < 5; i++) bv[x][i] = ldv64((const uint2*)((x ? p.bim : p.bre) + (cch0 + 32 * c) * DM) + lane + 32 * i);
      bar_sync(8, 192);
#pragma unroll 1
      for (int pass = 0; pass < 2; pass++) {
        if (pass == 1) {
          float sv[2];
#pragma unroll
          for (int x = 0; x < 2; x++) {
            float a = 0.f;
#pragma unroll
            for (int i = 0; i < 5; i++) a += (bf_lo(bv[x][i].x) + bf_hi(bv[x][i].x)) + (bf_lo(bv[x][i].y) + bf_hi(bv[x][i].y));
            sv[x] = a;
          }
#pragma unroll
          for (int o = 16; o > 0; o >>= 1) { sv[0] += __shfl_xor_sync(0xffffffffu, sv[0], o); sv[1] += __shfl_xor_sync(0xffffffffu, sv[1], o); }
          if (lane < 2) rec_st(&g_sB[(cch0 + 32 * c) * 2 + lane], sv[0], sv[1], tag);
          if (tid == 256) TS(47);
          if (wg == 2) {
            float xs[80];
            x0_load(xs);
            stats_publish<true>(0, 64 * m2 + 16 * c + (lane >> 2), dg, tag, xs);
            if (tid == 256) TS(31);
          }
          mbar_wait(bars + 8 * B_EP);
          mbar_wait(bars + 8 * (B_KV + c));
        }
        kv_tile(m2, dg, c, pass);
        if (tid == 256 && pass == 0) TS(50);
      }
      __syncwarp();
      if (lane == 0) { mbar_arrive(bars + 8 * (B_PD + c)); mbar_arrive(bars + 8 * B_PREP); }
      if (tid == 256) TS(48);
      if (tid == 352) TS(52);
      if (tid == 448) TS(51);
    } else bar_sync(8, 192);
    if (wg == 2) {
      if (c == 1 || c == 2) {
        float a, b;
        rec_poll(&g_sB[(128 * GP + 64 * (c - 1) + 32 * side + lane) * 2], tag, a, b);
        sts64f(sb + CTAB_OFF + (32 * (c - 1) + lane) * 24 + 16, p.swap ? b : a, p.swap ? a : b);
      }
      stat_table(T1, tag, 0, c);
    }
    if (has2 && lane == 0) st_rel(&g_kvflag[((dg * 5 + c) * 32 + m2) * 8], tag);
    __syncwarp();
    if (tid == 256) TS(49);
    if (tid == 352) TS(26);
    if (tid == 448) TS(30);
  } else if (wid < 2) {
    ROLE(role)
    const int ch = 128 * GP + 64 * wid + 32 * side + lane;
    const float lr = bf_lo(ldv16(p.lre + ch)), li = bf_lo(ldv16(p.lim + ch)), ld = bf_lo(ldv16(p.logdt + ch));
    const float dt = __bfloat162float(__float2bfloat16_rn(expf(ld)));
    const float mag = expf(dt * lr);
    float sn, cs; sincospif(dt * li * 0.31830988618379067f, &sn, &cs);
    const float ar = mag * cs, ai = mag * sn;
    const float inv = 2.f / (lr * lr + li * li);
    const uint32_t ad = sb + CTAB_OFF + (32 * wid + lane) * 24;
    sts64f(ad, ar, ai);
    sts64f(ad + 8, ((ar - 1.f) * lr + ai * li) * inv, (ai * lr - (ar - 1.f) * li) * inv);
    if (tid == 0) TS(46);
    __syncwarp();
    bar_sync(7, 96);
    mbar_arrive(bars + 8 * B_CTAB);
  } else if (wid == 13) {
    ROLE(role)
    uint4 tv[3];
    const uint32_t e0 = ld_rlx(g_epoch);
    const uint32_t e1 = ldv16(p.ssmD + min(cch0 + 32 * lane, 639));
    const uint4 dv = ldv128((const uint4*)(p.dskip + 160 * dg) + min(lane, 19));
#pragma unroll
    for (int i = 0; i < 3; i++) tv[i] = ldv128((const uint4*)(p.shiftk + 640 * dg) + min(lane + 32 * i, 79));
    sts128(sb + DTAB_OFF + 16 * min(lane, 19), dv);
#pragma unroll
    for (int i = 0; i < 3; i++) sts128(sb + TAP_OFF + 16 * min(lane + 32 * i, 79), tv[i]);
    if (lane < 7) sts32(sb + EP_OFF + 4 * lane, lane < 5 ? e1 << 16 : (lane == 5 ? e0 : 0u));
    __syncwarp();
    bar_sync(9, 64);
    mbar_arrive(bars + 8 * B_CTAB);
    if (lane == 0) { mbar_arrive(bars + 8 * B_EP); TS(53); }
  } else if (wid != 12) {
    if (elect_one()) {
      const int b0 = wid < 5 ? 4 + 27 * (wid - 2) : (wid < 8 ? 85 + 21 * (wid - 5) : B_CVDONE);
      const int n = wid < 5 ? 27 : (wid < 8 ? 21 : 12), cnt = wid < 5 ? 2 : (wid < 8 ? 1 : 128);
#pragma unroll 1
      for (int i = 0; i < n; i++) mbar_init(bars + 8 * (b0 + i), cnt);
      if (wid == 15) { mbar_init(bars + 8 * B_CTAB, 96); mbar_init(bars + 8 * B_PREP, 5); }
      asm volatile("fence.mbarrier_init.release.cluster;" ::: "memory");
    }
    __syncwarp();
    bar_sync(5, 256);
    if (wid == 2) asm volatile("bar.arrive 8, 192;\nbar.arrive 6, 64;\nbar.arrive 9, 64;\nbar.arrive 7, 96;" ::: "memory");
    if (tid == 128) TS(0);
  }

  if (wg == 3) {
    ROLE(role)
    const int pw = wid & 3;
    unsigned tag = 0;
    if (pw > 0) { mbar_wait(bars + 8 * B_EP); tag = lds32(sb + EP_OFF + 20); }
    if (pw == 0) {
      if (elect_one()) {
#pragma unroll 1
        for (int l = 0; l < 2; l++) {
          const uint32_t fb0 = bars + 8 * (B_G1FULL + 10 * l), wb = bars + 8 * (B_G1DONE + 9 * l - S1);
          const uint32_t free0 = bars + 8 * (has2 ? B_G2DONE + 19 : B_G1DONE + 9);
          uint32_t dst = sb;
#pragma unroll 1
          for (int k = l == 0 ? S1 : 0; k < 10; k++) {
            mbar_wait(k >= S1 + l ? wb + 8 * k : (k < WPF1 || !has2 ? free0 : bars + 8 * (B_GO + 1)));
            mbar_expect_tx(fb0 + 8 * k, 16384);
            tma5(dst, &p.mB, 64 * k, 0, 0, 4 * side, 2 * GP, fb0 + 8 * k);
            dst += G1_STAGE; if (dst == sb + (S1 + l) * G1_STAGE) dst = sb;
          }
          if (has2) {
            const uint32_t fb2 = bars + 8 * (B_G2FULL + 20 * l), wb2 = bars + 8 * (B_G2DONE + 19 * l - 6);
            dst = sb + G2_WOFF;
            int kc = 0;
#pragma unroll 1
            for (int k = 0; k < 20; k++) {
              mbar_wait(k >= 6 + l ? wb2 + 8 * k : (k == 5 ? bars + 8 * B_XFREE : (k < WPF2 ? bars + 8 * (B_G1DONE + 10 * l + 9) : bars + 8 * (B_GO + 2 * l))));
              mbar_expect_tx(fb2 + 8 * k, G2_WB);
              tma5(dst, &p.mCre + (k & 1), kc, 0, 0, 0, 10 * dg, fb2 + 8 * k);
              kc += (k & 1) << 7; if (k == 9) kc = 64;
              dst += G2_WB; if (dst == sb + G2_WOFF + (6 + l) * G2_WB) dst = sb + G2_WOFF;
            }
          }
        }
      }
    } else if (pw == 1) {
#pragma unroll 1
      for (int l = 0; l < 2; l++) {
        if (l == 0) {
          if (elect_one()) {
            uint32_t dst = sb + G1_XOFF;
#pragma unroll 1
            for (int k = S1; k < 10; k++) {
              mbar_wait(bars + 8 * (B_G1DONE + k - S1));
              mbar_expect_tx(bars + 8 * (B_G1FULL + k), 20480);
              tma4(dst, last ? &p.mXl : &p.mX, 64 * k, 0, 0, last ? 0 : 80 * T1, bars + 8 * (B_G1FULL + k));
              dst += G1_STAGE; if (k == 2 * S1 - 1) dst = sb + G1_XOFF;
              if (has2 && k - S1 + KV0 < 5) kv_issue(p, k - S1 + KV0, m2, dg);
            }
          }
        } else {
          mbar_wait(bars + 8 * (has2 ? B_G2DONE + 19 : B_G1DONE + 9));
          const int mlo = (160 * T1) >> 6, nf = last ? 8 : 12;
          flag_poll(&g_uflag[(4 * mlo + min(lane, nf - 1)) * 8], tag);
          fence_async_global();
          if (elect_one()) {
            TS(20);
            const int bytes = last ? 16384 : 20480;
            const uint8_t* src = g_u + T1 * 204800;
            uint32_t dst = sb + G1_XOFF;
#pragma unroll 1
            for (int k = 0; k < 10; k++) {
              if (k > S1) mbar_wait(bars + 8 * (B_G1DONE + 9 - S1 + k));
              mbar_expect_tx(bars + 8 * (B_G1FULL + 10 + k), bytes);
              bulk_g2s(dst, src, bytes, bars + 8 * (B_G1FULL + 10 + k));
              src += 20480; dst += G1_STAGE; if (k == S1) dst = sb + G1_XOFF;
            }
          }
        }
        __syncwarp();
        if (has2) {
          mbar_wait(bars + 8 * (B_G1DONE + 10 * l + 9));
          const int Tlo = (64 * m2) / 160, Thi = (64 * m2 + 63) / 160;
          flag_poll(&g_hflag[(((l * NT1 + (lane < 16 ? Tlo : Thi)) * 2) * 16 + min(lane & 15, 9)) * 8], tag);
          fence_async_global();
          if (elect_one()) {
            TS(21 + 2 * l);
            const uint32_t fb2 = bars + 8 * (B_G2FULL + 20 * l), wb2 = bars + 8 * (B_G2DONE + 18 * l - SX2);
            const uint8_t* src = g_h + (l * 32 + m2) * 163840;
            uint32_t dst = sb;
#pragma unroll 1
            for (int k = 0; k < 20; k++) {
              if (k >= SX2 + 2 * l) mbar_wait(wb2 + 8 * k);
              if (k == 10) { mbar_wait(bars + 8 * (B_H1 + l)); fence_async_global(); }
              mbar_expect_tx(fb2 + 8 * k, G2_XB);
              bulk_g2s(dst, src, G2_XB, fb2 + 8 * k);
              src += 8192; dst += G2_XB; if (dst == sb + (SX2 + 2 * l) * G2_XB) dst = sb;
            }
          }
          __syncwarp();
        }
      }
    } else if (pw == 2) {
#pragma unroll 1
      for (int l = 0; l < 2; l++) {
        mbar_wait(bars + 8 * (B_HST + 2 * l));
        mbar_wait(bars + 8 * (B_HST + 2 * l + 1));
        __syncwarp();
        if (lane < 2) st_rel(&g_hflag[(((l * NT1 + T1) * 2 + lane) * 16 + 2 * GP + side) * 8], tag);
        if (lane == 0) TS(6 + 8 * l);
        __syncwarp();
        if (l == 0 && has2 && elect_one()) {
#pragma unroll 1
          for (int c = 0; c < 5; c++) {
            mbar_wait(bars + 8 * (B_CVDONE + c));
            bulk_s2g(g_G + (cch0 + 32 * c) * 4096, cv_stage(c), 4096);
          }
          asm volatile("cp.async.bulk.commit_group;" ::: "memory");
          asm volatile("cp.async.bulk.wait_group 0;" ::: "memory");
          fence_async_global();
          st_rel(&g_gflag[(dg * 32 + m2) * 8], tag);
        }
        __syncwarp();
      }
    } else if (has2) {
#pragma unroll 1
      for (int c = 0; c < 5; c++) {
        mbar_wait(bars + 8 * (B_PD + c));
        const uint32_t cb = sb + CV_OFF + c * CV_B;
        sts128(lane < 8 ? cb + 16 * lane : (lane < 20 ? cb + CV_U + 16 * (lane - 8) : cb + CV_U + CV_PL + 16 * (lane - 20)), make_uint4(0, 0, 0, 0));
        fence_async_smem();
        __syncwarp();
        if (elect_one()) {
          mbar_expect_tx(bars + 8 * (B_TAPS + c), 4096);
          bulk_g2s(cb + CV_K, p.ssmk + (cch0 + 32 * c) * SEQ, 4096, bars + 8 * (B_TAPS + c));
        }
      }
      if (elect_one()) {
        asm volatile("prefetch.tensormap [%0];" ::"l"(&p.mCre) : "memory");
        asm volatile("prefetch.tensormap [%0];" ::"l"(&p.mCim) : "memory");
        asm volatile("prefetch.tensormap [%0];" ::"l"(&p.mG) : "memory");
      }
      uint32_t seen = 0;
#pragma unroll 1
      for (int c = 0; c < 5; c++) {
        uint32_t it = 0;
        while (!((seen >> c) & 1)) {
          unsigned f[5];
#pragma unroll
          for (int i = 0; i < 5; i++) f[i] = ld_rlx(&g_kvflag[((dg * 5 + i) * 32 + lane) * 8]);
#pragma unroll
          for (int i = 0; i < 5; i++) seen |= __all_sync(0xffffffffu, (int)(f[i] - tag) >= 0) ? 1u << i : 0u;
          asm volatile("fence.acquire.gpu;" ::: "memory");
          trap_if(++it > SPIN_LIMIT);
        }
        fence_async_global();
        if (lane == 0 && (c & 3) == 0) TS(c ? 54 : 28);
        mbar_wait(bars + 8 * (B_TAPS + c));
        if (elect_one()) {
          const uint32_t fb = bars + 8 * (B_CVFULL + c), cb = sb + CV_OFF + c * CV_B;
          const uint32_t w0 = lds32(cb + CV_K);
          sts32(cb + CV_K, (w0 & 0xffff0000u) | (pack_bf16(bf_lo(w0) + __uint_as_float(lds32(sb + EP_OFF + 4 * c)), 0.f) & 0xffffu));
          mbar_expect_tx(fb, 4096);
          bulk_g2s(cb + CV_U + 192, g_kv + (cch0 + 32 * c) * 4096, 2048, fb);
          bulk_g2s(cb + CV_U + 192 + CV_PL, g_kv + (cch0 + 32 * c) * 4096 + 2048, 2048, fb);
        }
        __syncwarp();
      }
      const unsigned* hf = &g_hflag[(((lane < 16 ? (64 * m2) / 160 : (64 * m2 + 63) / 160) * 2 + 1) * 16 + min(lane & 15, 9)) * 8];
      mbar_wait(bars + 8 * (B_CVDONE + 0));
      if (elect_one()) { l2_prefetch(p.cre + (160 * dg + 5 * m2) * DM, 6400); l2_prefetch(p.cim + (160 * dg + 5 * m2) * DM, 6400); }
      flag_poll(hf, tag);
      __syncwarp();
      if (lane == 0) { mbar_arrive(bars + 8 * B_H1); TS(22); }
      mbar_wait(bars + 8 * (B_CVDONE + 4));
      flag_poll(&g_gflag[(dg * 32 + lane) * 8], tag);
      __syncwarp();
      fence_async_global();
      if (lane == 0) TS(29);
      if (elect_one()) {
        mbar_expect_tx(bars + 8 * B_GFULL, 20480);
        tma5(sb + G_OFF, &p.mG, 64 * m2, 0, 0, 0, 10 * dg, bars + 8 * B_GFULL);
      }
      mbar_wait(bars + 8 * (B_G1DONE + 19));
      flag_poll(hf + NT1 * 256, tag);
      __syncwarp();
      if (lane == 0) { mbar_arrive(bars + 8 * (B_H1 + 1)); TS(24); }
    }
  } else {
    const int w = wid & 3;
    mbar_wait(bars + 8 * B_EP);
    const unsigned tag = lds32(sb + EP_OFF + 20);
    if (wg == 2 && !(role >> 16)) { mbar_wait(bars + 8 * (B_G1FULL + 11)); stat_table(role & 15, tag, 1, w); }
#pragma unroll 1
    for (int l = 0; l < 2; l++) {
      if (wg < 2) {
        float acc[80];
#pragma unroll
        for (int i = 0; i < 80; i++) acc[i] = 0.f;
        ROLE(role)
        const int tid = tid_opaque(), r = (tid & 31) >> 2, q = tid & 3;
        const int ch = 128 * GP + 64 * wg + 32 * side + 8 * w + r;
        mbar_wait(bars + 8 * B_CTAB);
        const uint32_t ca = sb + CTAB_OFF + (32 * wg + 8 * w + r) * 24;
        float2 lam = lds64f(ca);
        const float2 coef = lds64f(ca + 8), lamc = make_float2(lam.x, -lam.y);
        float m00 = coef.x, m01 = -coef.y, m10 = -coef.y, m11 = -coef.x;
        if (p.swap) { lam = lamc; m00 = -coef.y; m01 = coef.x; m10 = -coef.x; m11 = -coef.y; }
        float2 p8, p16, pL, p2L;
        {
          const float2 p2 = cmul(lam, lam), p4 = cmul(p2, p2);
          p8 = cmul(p4, p4); p16 = cmul(p8, p8);
          pL = cmul(p16, p16);
          if (!last) pL = cmul(pL, p8);
          p2L = cmul(pL, pL);
        }
        fence_regs(acc);
        {
          uint32_t alo = desc_lo(sb, 16) + wg * 512, blo = l == 0 ? desc_lo(sb + G1_XOFF, 16) : desc_lo(sb + G1_XOFF, 128);
          const uint32_t bhi = l == 0 ? desc_hi(1024, 1) : desc_hi(1024, 0), xstep = l == 0 ? 2 : 16;
          const uint32_t aend = desc_lo(sb, 16) + (S1 + l) * (G1_STAGE >> 4);
          const int kpause = has2 ? PAUSE_K : -1;
          uint32_t fb = bars + 8 * (B_G1FULL + 10 * l);
          mbar_wait(fb);
          if (tid == 0) TS(1 + 8 * l);
#pragma unroll 1
          for (int k = 0; k < 10; k++) {
            uint32_t ok; const uint32_t nb = k < 9 ? fb + 8 : fb;
            wgmma_fence();
#pragma unroll
            for (int kk = 0; kk < 4; kk++) {
              wgmma_n160<0>(acc, alo + kk * 2, desc_hi(1024, 1), blo + kk * xstep, bhi);
              if (kk == 0) ok = mbar_test(nb);
            }
            wgmma_commit();
            alo += G1_STAGE >> 4; blo += G1_STAGE >> 4;
            if (alo >= aend) { alo -= (S1 + l) * (G1_STAGE >> 4); blo -= (S1 + l) * (G1_STAGE >> 4); }
            wgmma_wait<1>();
            if (k > 0 && (tid & 127) == 0) mbar_arrive(fb + 8 * (B_G1DONE - B_G1FULL - 1));
            if (!ok) mbar_wait(nb);
            if (k == kpause) mbar_wait(bars + 8 * B_PREP);
            fb += 8;
          }
        }
        mbar_wait(bars + 8 * (B_STAB + l));
        const float2 sB = lds64f(ca + 16);
        wgmma_wait<0>();
        fence_regs(acc);
        if ((tid & 127) == 0) { mbar_arrive(bars + 8 * (B_G1DONE + 10 * l + 9)); if (wg == 0) TS(2 + 8 * l); }
        float2 ec[3];
#pragma unroll
        for (int jj = 0; jj < 8; jj++)
#pragma unroll
          for (int y = 0; y < 3; y++) {
            if (y == 2 && (jj & 1)) continue;
            const int j = y == 2 ? 16 + (jj >> 1) : 8 * y + jj;
            const float4 st = lds128f(sb + STAB_OFF + (8 * j + 2 * q) * 8);
            acc[4 * j + 0] = fmaf(acc[4 * j + 0], st.x, st.y * sB.x);
            acc[4 * j + 2] = fmaf(acc[4 * j + 2], st.x, st.y * sB.y);
            acc[4 * j + 1] = fmaf(acc[4 * j + 1], st.z, st.w * sB.x);
            acc[4 * j + 3] = fmaf(acc[4 * j + 3], st.z, st.w * sB.y);
            ec[y] = jj == 0 ? make_float2(acc[4 * j + 0], acc[4 * j + 2]) : cfma(lam, ec[y], make_float2(acc[4 * j + 0], acc[4 * j + 2]));
            ec[y] = cfma(lam, ec[y], make_float2(acc[4 * j + 1], acc[4 * j + 3]));
          }
        float2 e = cfma(p16, ec[0], ec[1]);
        if (!last) e = cfma(p8, e, ec[2]);
        {
          float2 v = make_float2(__shfl_up_sync(0xffffffffu, e.x, 1, 4), __shfl_up_sync(0xffffffffu, e.y, 1, 4));
          if (q >= 1) e = cfma(pL, v, e);
          v = make_float2(__shfl_up_sync(0xffffffffu, e.x, 2, 4), __shfl_up_sync(0xffffffffu, e.y, 2, 4));
          if (q >= 2) e = cfma(p2L, v, e);
        }
        if (!last && (q == 3 || (q == 2 && l == 0))) rec_st(&g_E[((q == 3 ? l : 1) * NT1 + T1) * DM + ch], e.x, e.y, q == 3 ? tag : tag - 1);
        if (tid == 0) TS(3 + 8 * l);
        float2 ex = make_float2(__shfl_up_sync(0xffffffffu, e.x, 1, 4), __shfl_up_sync(0xffffffffu, e.y, 1, 4));
        if (q == 0) ex = make_float2(0.f, 0.f);
        float2 pLq, p160q, p640;
        {
          const float2 p80 = last ? cmul(p2L, p16) : p2L, p160 = cmul(p80, p80), p320 = cmul(p160, p160), one = make_float2(1.f, 0.f);
          p640 = cmul(p320, p320);
          pLq = cmul((q & 1) ? pL : one, (q & 2) ? p2L : one);
          p160q = cmul((q & 1) ? p160 : one, (q & 2) ? p320 : one);
        }
        float2 c, ev[3];
        unsigned tg[3];
        const uint4* ep = &g_E[(l * NT1 + T1 - 1 - q) * DM + ch];
#pragma unroll
        for (int j = 0; j < 20; j++) {
          if (j == CPOLL) {
#pragma unroll
            for (int i = 0; i < 3; i++) {
              ev[i] = make_float2(0.f, 0.f); tg[i] = tag;
              if (T1 - 1 - q - 4 * i >= 0) tg[i] = rec_ld(ep - 4 * i * DM, ev[i].x, ev[i].y);
            }
          }
#pragma unroll
          for (int x = 0; x < 2; x++) {
            const float b0 = acc[4 * j + x], b1 = acc[4 * j + 2 + x];
            acc[4 * j + x] = fmaf(b0, m00, b1 * m01);
            acc[4 * j + 2 + x] = fmaf(b0, m10, b1 * m11);
          }
          if (j == CPOLL - 1 || j == 19) asm volatile("" : "+f"(acc[4 * j]), "+f"(acc[4 * j + 1]), "+f"(acc[4 * j + 2]), "+f"(acc[4 * j + 3])::"memory");
        }
        {
          uint32_t it = 0;
          while (__any_sync(0xffffffffu, tg[0] != tag || tg[1] != tag || tg[2] != tag)) {
#pragma unroll
            for (int i = 0; i < 3; i++)
              if (tg[i] != tag) tg[i] = rec_ld(ep - 4 * i * DM, ev[i].x, ev[i].y);
            trap_if(++it > SPIN_LIMIT);
          }
          c = cfma(p640, cfma(p640, ev[2], ev[1]), ev[0]);
          c = cmul(c, p160q);
          c.x += __shfl_xor_sync(0xffffffffu, c.x, 1); c.y += __shfl_xor_sync(0xffffffffu, c.y, 1);
          c.x += __shfl_xor_sync(0xffffffffu, c.x, 2); c.y += __shfl_xor_sync(0xffffffffu, c.y, 2);
        }
        if (tid == 0) TS(4 + 8 * l);
        if (tid == 128) mbar_arrive(bars + 8 * (B_GO + 2 * l));
        c = cfma(pLq, c, ex);
        float2 hh = make_float2(fmaf(c.x, m00, c.y * m01), fmaf(c.x, m10, c.y * m11));
        uint8_t* hb = g_h + (size_t)l * (32 * 20 * 8192) + (10 * wg + 2 * GP) * 8192 + (4 * side + w) * 1024 + (tid_opaque() & 31) * 4;
#pragma unroll
        for (int j4 = 0; j4 < 5; j4++) {
          const int ng = 20 * T1 + 4 * j4;
          uint8_t* hp = hb + (size_t)(ng >> 3) * 163840 + (ng & 7) * 128;
#pragma unroll
          for (int jj = 0; jj < 4; jj++) {
            const int j = 4 * j4 + jj;
            const float2 h0 = cfma(lamc, hh, make_float2(acc[4 * j + 0], acc[4 * j + 2]));
            hh = cfma(lamc, h0, make_float2(acc[4 * j + 1], acc[4 * j + 3]));
            if (j4 < 4 || !last) {
              *(uint32_t*)(hp + jj * 128) = pack_bf16(h0.x, hh.x);
              *(uint32_t*)(hp + jj * 128 + 8192) = pack_bf16(h0.y, hh.y);
            }
          }
        }
        mbar_arrive(bars + 8 * (B_HST + 2 * l + wg));
        if (tid == 0) TS(5 + 8 * l);
      }
      if (l == 0) {
        ROLE(role)
        if (has2) {
          CvCtx cc;
          cv_setup(cc);
          mbar_wait(bars + 8 * (B_G1DONE + 9));
#pragma unroll 1
          for (int c = wg == 2 ? 0 : 2 + wg; c < (wg == 2 ? 2 : 5); c += wg == 2 ? 1 : 2) conv_channel(c, cc);
          if ((tid & 127) == 0) TS(wg == 2 ? 32 : 7 + wg);
        }
      }
      if (wg == 2) break;
    }
    if (wg == 2 && (role >> 16)) {
      float acc[80];
      float off[2] = {0.f, 0.f};
      x0_load(acc);
      mbar_arrive(bars + 8 * B_XFREE);
#pragma unroll 1
      for (int l = 0; l < 2; l++) {
        float mean[2], rstd[2];
        {
          ROLE(role)
          const int lane = tid_opaque() & 31;
          stats_get(2 * l, 64 * m2 + 16 * w + (lane >> 2), tag, mean, rstd);
          off[0] += mean[0]; off[1] += mean[1];
          mbar_wait(bars + 8 * (l == 0 ? B_CTAB : B_HST + 3));
#pragma unroll
          for (int J = 0; J < 10; J++) {
            const float2 dw = lds64f(sb + DTAB_OFF + 2 * (16 * J + 4 * (lane & 3)));
#pragma unroll
            for (int x = 0; x < 8; x++) {
              const int h = (x >> 1) & 1;
              const uint32_t gwd = __float_as_uint(x < 4 ? dw.x : dw.y);
              const float t = fmaf(rstd[h], (x & 1) ? bf_hi(gwd) : bf_lo(gwd), 1.f);
              acc[8 * J + x] = fmaf(acc[8 * J + x], t, -mean[h] * t);
            }
          }
        }
        {
          const uint32_t aend = desc_lo(sb + SX2 * G2_XB, 1024) + l * (G2_XB >> 3), bend = desc_lo(sb + G2_WOFF + 6 * G2_WB, 16) + l * (G2_WB >> 4);
          uint32_t alo = desc_lo(sb, 1024), blo = desc_lo(sb + G2_WOFF, 16);
          uint32_t fb = bars + 8 * (B_G2FULL + 20 * l);
          fence_regs(acc);
          mbar_wait(fb);
          if (tid == 256) TS(33 + 6 * l);
#pragma unroll 1
          for (int k = 0; k < 20; k++) {
            if (l == 1 && (k & 3) == 3 && tid == 256) TS(56 + (k >> 2));
            uint32_t ok; const uint32_t nb = k < 19 ? fb + 8 : fb;
            wgmma_fence();
#pragma unroll
            for (int kk = 0; kk < 4; kk++) {
              wgmma_n160<1>(acc, alo + kk * 128, desc_hi(128, 0), blo + kk * 2, desc_hi(1024, 1));
              if (kk == 0) ok = mbar_test(nb);
            }
            wgmma_commit();
            alo += G2_XB >> 4; if (alo == aend) alo = desc_lo(sb, 1024);
            blo += G2_WB >> 4; if (blo == bend) blo = desc_lo(sb + G2_WOFF, 16);
            wgmma_wait<1>();
            if (k > 0 && tid == 256) mbar_arrive(fb + 8 * (B_G2DONE - B_G2FULL - 1));
            if (!ok) mbar_wait(nb);
            fb += 8;
          }
          wgmma_wait<0>();
          fence_regs(acc);
          if (tid == 256) TS(34 + 6 * l);
          if (tid == 256) mbar_arrive(bars + 8 * (B_G2DONE + 20 * l + 19));
        }
        ROLE(role)
        const int tq = tid_opaque() & 31, n0 = 64 * m2 + 16 * w + (tq >> 2);
        stats_publish<false>(2 * l + 1, n0, dg, tag, acc);
        uint32_t gf[10][4];
        mbar_wait(bars + 8 * B_GFULL);
        const uint32_t ga = sb + G_OFF + (8 * (tq >> 4) + (tq & 7)) * 128 + (((2 * w + ((tq >> 3) & 1)) ^ ((2 * m2) & 6) ^ (tq & 7)) << 4);
#pragma unroll
        for (int J = 0; J < 2; J++) ldsm4t(gf[J], ga + J * 2048);
        if (tid == 256) TS(35 + 6 * l);
        uint8_t* dst[2][2];
#pragma unroll
        for (int h = 0; h < 2; h++) {
          if (l == 0) {
            const int ng = 8 * m2 + 2 * w + h, T = ng / 20;
            uint8_t* ub = g_u + (T * 204800 + (ng - 20 * T) * 1024 + (tq & 2) * 64 + (tq & 28) * 4 + (tq & 1) * 8 + (5 * dg >> 1) * 20480);
            dst[h][1] = ub + ((dg & 1) ? 20480 - 512 : 0);
            dst[h][0] = ub + (dg & 1) * 512;
          } else {
            dst[h][0] = dst[h][1] = (uint8_t*)(p.out + (n_to_t(n0 + 8 * h) * DM + 160 * dg + 4 * (tq & 3)));
          }
        }
        stats_get(2 * l + 1, n0, tag, mean, rstd);
        if (tid == 256) { TS(36 + 6 * l); if (l == 0) mbar_arrive(bars + 8 * (B_GO + 1)); }
        off[0] += mean[0]; off[1] += mean[1];
        const float ov[2] = {l ? off[0] : 0.f, l ? off[1] : 0.f};
#pragma unroll
        for (int J = 0; J < 10; J++) {
          if (J + 2 < 10) ldsm4t(gf[J + 2 < 10 ? J + 2 : 0], ga + (J + 2) * 2048);
#pragma unroll
          for (int x = 0; x < 8; x++) {
            const int h = (x >> 1) & 1;
            const uint32_t gwd = gf[J][x >> 1];
            const float t = fmaf(rstd[h], (x & 1) ? bf_hi(gwd) : bf_lo(gwd), 1.f);
            acc[8 * J + x] = fmaf(acc[8 * J + x], t, fmaf(-mean[h], t, ov[h]));
          }
#pragma unroll
          for (int h = 0; h < 2; h++) {
            if (l == 0)
              *(uint2*)(dst[h][(J >> 1) & 1] + (J >> 2) * 20480 + (J & 3) * 256) =
                  make_uint2(pack_bf16(acc[8 * J + 2 * h], acc[8 * J + 2 * h + 1]), pack_bf16(acc[8 * J + 4 + 2 * h], acc[8 * J + 5 + 2 * h]));
            else
              *(float4*)(dst[h][0] + 64 * J) = make_float4(acc[8 * J + 2 * h], acc[8 * J + 2 * h + 1], acc[8 * J + 4 + 2 * h], acc[8 * J + 5 + 2 * h]);
          }
          __syncwarp();
        }
        if (l == 0) {
          bar_sync(3, 128);
          if (tid == 256) { TS(37); st_rel(&g_uflag[(4 * m2 + dg) * 8], tag); TS(38); }
          stats_publish<false>(2, n0, dg, tag, acc);
          mbar_wait(bars + 8 * (B_G1FULL + 11));
          stat_table(T1, tag, 1, w);
          if (tid == 256) TS(27);
        } else {
          if (tid == 256) {
            TS(43);
            if (m2 == 31 && dg == 3) asm volatile("st.relaxed.gpu.global.u32 [%0], %1;" ::"l"(g_epoch), "r"(tag + 1) : "memory");
          }
        }
      }
    }
  }
}

typedef CUresult (*EncFn)(CUtensorMap*, CUtensorMapDataType, cuuint32_t, void*, const cuuint64_t*, const cuuint64_t*,
                          const cuuint32_t*, const cuuint32_t*, CUtensorMapInterleave, CUtensorMapSwizzle,
                          CUtensorMapL2promotion, CUtensorMapFloatOOBfill);

void encode(EncFn fn, CUtensorMap* m, const void* ptr, int rank, const cuuint64_t* dims, const cuuint64_t* strides, const cuuint32_t* box,
            CUtensorMapSwizzle swz = CU_TENSOR_MAP_SWIZZLE_128B) {
  cuuint32_t es[5] = {1, 1, 1, 1, 1};
  fn(m, CU_TENSOR_MAP_DATA_TYPE_BFLOAT16, rank, (void*)ptr, dims, strides, box, es, CU_TENSOR_MAP_INTERLEAVE_NONE,
     swz, swz == CU_TENSOR_MAP_SWIZZLE_128B ? CU_TENSOR_MAP_L2_PROMOTION_L2_128B : CU_TENSOR_MAP_L2_PROMOTION_L2_64B, CU_TENSOR_MAP_FLOAT_OOB_FILL_NONE);
}

}

extern "C" void kernel_launch(void* const* d_in, const int* in_sizes, int n_in, void* d_out, int out_size) {
  (void)in_sizes; (void)n_in; (void)out_size;
  Params p;
  typedef const __nv_bfloat16* BP;
  p.x = (BP)d_in[0]; p.lre = (BP)d_in[1]; p.lim = (BP)d_in[2]; p.bre = (BP)d_in[3]; p.bim = (BP)d_in[4];
  p.cre = (BP)d_in[5]; p.cim = (BP)d_in[6]; p.logdt = (BP)d_in[7]; p.dskip = (BP)d_in[8];
  p.k = (BP)d_in[10]; p.v = (BP)d_in[11]; p.shiftk = (BP)d_in[12]; p.ssmk = (BP)d_in[13]; p.ssmD = (BP)d_in[14];
  p.out = (float*)d_out;
  for (int sm = 0; sm < 132; sm++) {
    const int tpc = sm >> 1, side = sm & 1;
    int gpc, gi;
    if (tpc < 32) { gpc = tpc & 7; gi = tpc >> 3; }
    else if (tpc < 60) { gpc = 1 + (tpc - 32) % 7; gi = 4 + (tpc - 32) / 7; }
    else if (tpc < 62) { gpc = tpc - 54; gi = 8; }
    else { gpc = 0; gi = tpc - 58; }
    const int pos = 8 * gpc + gi + (gpc == 7 ? 1 : 0);
    int T1, GP;
    if (pos < 52) { const int hh = pos / 26, x = pos - 26 * hh; T1 = x >> 1; GP = 2 * hh + (x & 1); }
    else { T1 = pos - 52; GP = 4; }
    const int m2 = 8 * (gpc >> 1) + gi, dg = 2 * (gpc & 1) + side;
    p.role[sm] = pos == 65 ? -1 : (T1 | (GP << 4) | (side << 7) | (m2 << 8) | (dg << 14) | ((gi < 8) << 16));
  }
  void* fnp = nullptr;
  cudaDriverEntryPointQueryResult qr;
  cudaGetDriverEntryPoint("cuTensorMapEncodeTiled", &fnp, cudaEnableDefault, &qr);
  EncFn fn = (EncFn)fnp;
  void* gG = nullptr;
  cudaGetSymbolAddress(&gG, g_G);
  const cuuint64_t RB = DM * 2;
  {
    p.swap = p.bim < p.bre;
    const char* lo = (const char*)(p.swap ? p.bim : p.bre); const char* hi = (const char*)(p.swap ? p.bre : p.bim);
    cuuint64_t dims[5] = {640, 8, 2, 8, 10}, st[4] = {RB, (cuuint64_t)(hi - lo), 8 * RB, 64 * RB}; cuuint32_t box[5] = {64, 8, 2, 4, 2};
    encode(fn, &p.mB, lo, 5, dims, st, box);
  }
  {
    cuuint64_t dims[5] = {640, 2, 4, 2, 40}, st[4] = {RB, 4 * RB, 2 * RB, 16 * RB}; cuuint32_t box[5] = {64, 2, 4, 2, 10};
    encode(fn, &p.mCre, p.cre, 5, dims, st, box); encode(fn, &p.mCim, p.cim, 5, dims, st, box);
    cuuint64_t dimg[5] = {2048, 2, 4, 2, 40}, stg[4] = {4096, 4 * 4096, 2 * 4096, 16 * 4096};
    encode(fn, &p.mG, gG, 5, dimg, stg, box);
  }
  {
    cuuint64_t dims[4] = {640, 2, 4, 900}, st[3] = {RB, 40 * RB, 2 * RB}; cuuint32_t box[4] = {64, 2, 4, 20};
    encode(fn, &p.mX, p.x, 4, dims, st, box);
    cuuint64_t diml[4] = {640, 2, 4, 16}, stl[3] = {RB, 32 * RB, 2 * RB};
    encode(fn, &p.mXl, p.x + (size_t)1920 * DM, 4, diml, stl, box);
    cuuint32_t boxt[4] = {160, 2, 4, 4};
    encode(fn, &p.mXt, p.x, 4, dims, st, boxt, CU_TENSOR_MAP_SWIZZLE_NONE);
    encode(fn, &p.mXtl, p.x + (size_t)1920 * DM, 4, diml, stl, boxt, CU_TENSOR_MAP_SWIZZLE_NONE);
    cuuint64_t dk[3] = {640, 2000, 4}, sk[2] = {RB, 16 * RB}; cuuint32_t bk[3] = {32, 19, 4}, bv[3] = {32, 17, 4};
    encode(fn, &p.mK, p.k, 3, dk, sk, bk, CU_TENSOR_MAP_SWIZZLE_NONE);
    encode(fn, &p.mV, p.v, 3, dk, sk, bv, CU_TENSOR_MAP_SWIZZLE_NONE);
  }
  cudaFuncSetAttribute(fused_kernel, cudaFuncAttributeMaxDynamicSharedMemorySize, SMEM_BYTES);
  cudaLaunchConfig_t cfg = {};
  cfg.gridDim = dim3(132); cfg.blockDim = dim3(512); cfg.dynamicSmemBytes = SMEM_BYTES; cfg.stream = cudaStreamPerThread;
  cudaLaunchKernelEx(&cfg, fused_kernel, p);
}
```

```cpp
#include <cuda_runtime.h>
#include <cuda.h>
#include <cuda_bf16.h>
#include <stdint.h>

namespace {

constexpr int SEQ = 2048, DM = 640;
constexpr int NT1 = 13;
#define EXP 0
#define WPF1 1
#define WPF2 2
#define CPOLL 10
#define KV0 5
#define TAP0 2
#define PAUSE_K 3
constexpr uint32_t SPIN_LIMIT = 1u << 22;

__device__ __align__(1024) uint8_t g_h[2 * 32 * 20 * 8192];
__device__ __align__(1024) uint8_t g_u[NT1 * 10 * 20480];
__device__ __align__(1024) uint8_t g_kv[DM * 4096];
__device__ __align__(1024) uint8_t g_G[DM * 4096];
__device__ __align__(128) uint4 g_E[2 * NT1 * DM];
__device__ __align__(128) uint4 g_stats[4 * 4 * SEQ];
__device__ __align__(128) uint4 g_sB[DM * 2];
__device__ __align__(128) unsigned g_hflag[2 * NT1 * 2 * 16 * 8];
__device__ __align__(128) unsigned g_uflag[32 * 4 * 8];
__device__ __align__(128) unsigned g_kvflag[4 * 32 * 8];
__device__ __align__(128) unsigned g_gflag[4 * 32 * 8];
__device__ __align__(128) unsigned g_epoch[32] = {1};
#define TS(i) do {} while (0)

struct Params {
  CUtensorMap mB, mCre, mCim, mX, mXl, mG, mK, mV, mXt, mXtl;
  const __nv_bfloat16 *x, *lre, *lim, *bre, *bim, *cre, *cim, *logdt, *dskip, *k, *v, *shiftk, *ssmk, *ssmD;
  float* out;
  int swap;
  int role[132];
};

constexpr uint32_t sb = 1024;
constexpr uint32_t G1_STAGE = 36864, G1_XOFF = 16384;
constexpr int S1 = 4;
constexpr uint32_t XT_OFF = 159744, KS_OFF = 180224, KV_PIECE = 9216;
constexpr uint32_t G2_XB = 8192, G2_WB = 20480, G2_WOFF = 57344, G_OFF = 200704;
constexpr int SX2 = 5;
constexpr uint32_t CV_OFF = KS_OFF, CV_K = 128, CV_PL = 2240, CV_U = CV_K + 4096, CV_B = KV_PIECE;
constexpr uint32_t MISC = 226304;
constexpr uint32_t BAR_OFF = MISC;
constexpr int B_G1FULL = 0, B_G1DONE = 20, B_G2FULL = 40, B_CVFULL = 80  ,
              B_G2DONE = 85, B_GFULL = 125, B_EP = 126, B_H1 = 127  , B_TAPS = 129  ,
              B_GO = 139  , B_PD = 142  , B_PUB = 147,
              B_CVDONE = 148  , B_STAB = 153  , B_XFREE = 155, B_HST = 156  ,
              B_CTAB = 160, B_PREP = 161, B_XT = 162, B_KV = 163  ;
constexpr uint32_t bars = sb + BAR_OFF;
constexpr uint32_t STAB_OFF = MISC + 1344;
constexpr uint32_t CTAB_OFF = STAB_OFF + 1280;
constexpr uint32_t DTAB_OFF = CTAB_OFF + 1536;
constexpr uint32_t EP_OFF = DTAB_OFF + 320;
constexpr uint32_t TAP_OFF = 147456;
constexpr uint32_t SMEM_BYTES = 232448;
static_assert(EP_OFF + 32 <= SMEM_BYTES, "smem");

__device__ __forceinline__ void trap_if(bool c) { asm volatile("{\n.reg .pred p;\nsetp.ne.u32 p, %0, 0;\n@p trap;\n}\n" ::"r"((uint32_t)c)); }
__device__ __forceinline__ uint32_t smem_u32(const void* p) { return (uint32_t)__cvta_generic_to_shared(p); }
__device__ __forceinline__ void mbar_init(uint32_t bar, int cnt) { asm volatile("mbarrier.init.shared::cta.b64 [%0], %1;" ::"r"(bar), "r"(cnt) : "memory"); }
__device__ __forceinline__ void mbar_expect_tx(uint32_t bar, int bytes) { asm volatile("mbarrier.arrive.expect_tx.shared::cta.b64 _, [%0], %1;" ::"r"(bar), "r"(bytes) : "memory"); }
__device__ __forceinline__ void mbar_arrive(uint32_t bar) { asm volatile("mbarrier.arrive.shared::cta.b64 _, [%0];" ::"r"(bar) : "memory"); }
__device__ __forceinline__ void mbar_wait(uint32_t bar) {
  asm volatile(
      "{\n.reg .pred p;\n.reg .u32 c;\nmov.u32 c, 0;\n"
      "W_%=:\nmbarrier.try_wait.parity.shared::cta.b64 p, [%0], 0;\n@p bra D_%=;\n"
      "add.u32 c, c, 1;\nsetp.lt.u32 p, c, %1;\n@p bra W_%=;\ntrap;\nD_%=:\n}\n" ::"r"(bar), "n"(SPIN_LIMIT) : "memory");
}
__device__ __forceinline__ uint32_t mbar_test(uint32_t bar) {
  uint32_t ok;
  asm volatile("{\n.reg .pred p;\nmbarrier.test_wait.parity.shared::cta.b64 p, [%1], 0;\nselp.u32 %0, 1, 0, p;\n}\n" : "=r"(ok) : "r"(bar) : "memory");
  return ok;
}
__device__ __forceinline__ void tma3(uint32_t dst, const CUtensorMap* m, int c0, int c1, int c2, uint32_t bar) {
  asm volatile("cp.async.bulk.tensor.3d.shared::cluster.global.mbarrier::complete_tx::bytes [%0], [%1, {%3,%4,%5}], [%2];"
               ::"r"(dst), "l"(m), "r"(bar), "r"(c0), "r"(c1), "r"(c2) : "memory");
}
__device__ __forceinline__ void tma4(uint32_t dst, const CUtensorMap* m, int c0, int c1, int c2, int c3, uint32_t bar) {
  asm volatile("cp.async.bulk.tensor.4d.shared::cluster.global.mbarrier::complete_tx::bytes [%0], [%1, {%3,%4,%5,%6}], [%2];"
               ::"r"(dst), "l"(m), "r"(bar), "r"(c0), "r"(c1), "r"(c2), "r"(c3) : "memory");
}
__device__ __forceinline__ void tma5(uint32_t dst, const CUtensorMap* m, int c0, int c1, int c2, int c3, int c4, uint32_t bar) {
  asm volatile("cp.async.bulk.tensor.5d.shared::cluster.global.mbarrier::complete_tx::bytes [%0], [%1, {%3,%4,%5,%6,%7}], [%2];"
               ::"r"(dst), "l"(m), "r"(bar), "r"(c0), "r"(c1), "r"(c2), "r"(c3), "r"(c4) : "memory");
}
__device__ __forceinline__ void bulk_g2s(uint32_t dst, const void* src, int bytes, uint32_t bar) {
  asm volatile("cp.async.bulk.shared::cluster.global.mbarrier::complete_tx::bytes [%0], [%1], %2, [%3];"
               ::"r"(dst), "l"(src), "r"(bytes), "r"(bar) : "memory");
}
__device__ __forceinline__ void bulk_s2g(void* dst, uint32_t src, int bytes) {
  asm volatile("cp.async.bulk.global.shared::cta.bulk_group [%0], [%1], %2;" ::"l"(dst), "r"(src), "r"(bytes) : "memory");
}
__device__ __forceinline__ void l2_prefetch(const void* src, int bytes) {
  asm volatile("cp.async.bulk.prefetch.L2.global [%0], %1;" ::"l"(src), "r"(bytes) : "memory");
}
__device__ __forceinline__ void wgmma_fence() { asm volatile("wgmma.fence.sync.aligned;" ::: "memory"); }
__device__ __forceinline__ void wgmma_commit() { asm volatile("wgmma.commit_group.sync.aligned;" ::: "memory"); }
template <int N> __device__ __forceinline__ void wgmma_wait() { asm volatile("wgmma.wait_group.sync.aligned %0;" ::"n"(N) : "memory"); }
__host__ __device__ constexpr uint32_t desc_lo(uint32_t addr, uint32_t lbo) { return ((addr & 0x3FFFF) >> 4) | ((lbo >> 4) << 16); }
__host__ __device__ constexpr uint32_t desc_hi(uint32_t sbo, uint32_t swz) { return (sbo >> 4) | (swz << 30); }
__device__ __forceinline__ void bar_sync(int id, int n) { asm volatile("bar.sync %0, %1;" ::"r"(id), "r"(n) : "memory"); }
__device__ __forceinline__ uint32_t lds32(uint32_t a) { uint32_t v; asm volatile("ld.shared.u32 %0, [%1];" : "=r"(v) : "r"(a) : "memory"); return v; }
__device__ __forceinline__ float2 lds64f(uint32_t a) { float2 v; asm volatile("ld.shared.v2.f32 {%0,%1}, [%2];" : "=f"(v.x), "=f"(v.y) : "r"(a) : "memory"); return v; }
__device__ __forceinline__ float4 lds128f(uint32_t a) { float4 v; asm volatile("ld.shared.v4.f32 {%0,%1,%2,%3}, [%4];" : "=f"(v.x), "=f"(v.y), "=f"(v.z), "=f"(v.w) : "r"(a) : "memory"); return v; }
__device__ __forceinline__ void ldsm4t(uint32_t (&r)[4], uint32_t a) {
  asm volatile("ldmatrix.sync.aligned.m8n8.x4.trans.shared.b16 {%0,%1,%2,%3}, [%4];" : "=r"(r[0]), "=r"(r[1]), "=r"(r[2]), "=r"(r[3]) : "r"(a) : "memory");
}
__device__ __forceinline__ uint4 ldv128(const void* a) { uint4 v; asm volatile("ld.global.nc.v4.u32 {%0,%1,%2,%3}, [%4];" : "=r"(v.x), "=r"(v.y), "=r"(v.z), "=r"(v.w) : "l"(a) : "memory"); return v; }
__device__ __forceinline__ uint2 ldv64(const void* a) { uint2 v; asm volatile("ld.global.nc.v2.u32 {%0,%1}, [%2];" : "=r"(v.x), "=r"(v.y) : "l"(a) : "memory"); return v; }
__device__ __forceinline__ uint32_t ldv16(const void* a) { uint32_t v; asm volatile("ld.global.nc.u16 %0, [%1];" : "=r"(v) : "l"(a) : "memory"); return v; }
__device__ __forceinline__ void sts128(uint32_t a, uint4 v) { asm volatile("st.shared.v4.u32 [%0], {%1,%2,%3,%4};" ::"r"(a), "r"(v.x), "r"(v.y), "r"(v.z), "r"(v.w) : "memory"); }
__device__ __forceinline__ void sts32(uint32_t a, uint32_t v) { asm volatile("st.shared.u32 [%0], %1;" ::"r"(a), "r"(v) : "memory"); }
__device__ __forceinline__ void sts64f(uint32_t a, float x, float y) { asm volatile("st.shared.v2.f32 [%0], {%1,%2};" ::"r"(a), "f"(x), "f"(y) : "memory"); }
__device__ __forceinline__ void st_rel(unsigned* p, unsigned v) { asm volatile("st.release.gpu.global.u32 [%0], %1;" ::"l"(p), "r"(v) : "memory"); }
__device__ __forceinline__ void fence_async_global() { asm volatile("fence.proxy.async.global;" ::: "memory"); }
__device__ __forceinline__ void fence_async_smem() { asm volatile("fence.proxy.async.shared::cta;" ::: "memory"); }
__device__ __forceinline__ void rec_st(uint4* p, float a, float b, unsigned tag) {
  asm volatile("{\n.reg .b128 t;\n.reg .b64 lo, hi;\nmov.b64 lo, {%1,%2};\nmov.b64 hi, {%3,%3};\nmov.b128 t, {lo,hi};\n"
               "st.relaxed.gpu.global.b128 [%0], t;\n}\n" ::"l"(p), "r"(__float_as_uint(a)), "r"(__float_as_uint(b)), "r"(tag) : "memory");
}
__device__ __forceinline__ unsigned rec_ld(const uint4* p, float& a, float& b) {
  unsigned x, y, t;
  asm volatile("{\n.reg .b128 t;\n.reg .b64 lo, hi;\n.reg .b32 u;\nld.relaxed.gpu.global.b128 t, [%3];\nmov.b128 {lo,hi}, t;\n"
               "mov.b64 {%0,%1}, lo;\nmov.b64 {%2,u}, hi;\n}\n" : "=r"(x), "=r"(y), "=r"(t) : "l"(p) : "memory");
  a = __uint_as_float(x); b = __uint_as_float(y);
  return t;
}
__device__ __forceinline__ void rec_poll(const uint4* p, unsigned tag, float& a, float& b) {
  uint32_t it = 0;
  while (!__all_sync(0xffffffffu, rec_ld(p, a, b) == tag)) { trap_if(++it > SPIN_LIMIT); }
}
__device__ __forceinline__ unsigned ld_rlx(const unsigned* p) { unsigned v; asm volatile("ld.relaxed.gpu.global.u32 %0, [%1];" : "=r"(v) : "l"(p) : "memory"); return v; }
__device__ __forceinline__ void flag_poll(const unsigned* p, unsigned target) {
  uint32_t it = 0;
  while (!__all_sync(0xffffffffu, (int)(ld_rlx(p) - target) >= 0)) { trap_if(++it > SPIN_LIMIT); }
  asm volatile("fence.acquire.gpu;" ::: "memory");
}
__device__ __forceinline__ uint32_t pack_bf16(float lo, float hi) {
  uint32_t r; asm("cvt.rn.bf16x2.f32 %0, %1, %2;" : "=r"(r) : "f"(hi), "f"(lo)); return r;
}
__device__ __forceinline__ float bf_lo(uint32_t w) { return __uint_as_float(w << 16); }
__device__ __forceinline__ float bf_hi(uint32_t w) { return __uint_as_float(w & 0xffff0000u); }
__device__ __forceinline__ uint32_t hmul2(uint32_t a, uint32_t b) {
  __nv_bfloat162 r = __hmul2_rn(*(__nv_bfloat162*)&a, *(__nv_bfloat162*)&b); return *(uint32_t*)&r;
}
__device__ __forceinline__ uint32_t hadd2(uint32_t a, uint32_t b) {
  __nv_bfloat162 r = __hadd2_rn(*(__nv_bfloat162*)&a, *(__nv_bfloat162*)&b); return *(uint32_t*)&r;
}
__device__ __forceinline__ float2 cmul(float2 a, float2 b) { return make_float2(a.x * b.x - a.y * b.y, a.x * b.y + a.y * b.x); }
__device__ __forceinline__ float2 cfma(float2 a, float2 b, float2 c) {
  return make_float2(fmaf(a.x, b.x, fmaf(-a.y, b.y, c.x)), fmaf(a.x, b.y, fmaf(a.y, b.x, c.y)));
}
template <int N> __device__ __forceinline__ void fence_regs(float (&a)[N]) {
#pragma unroll
  for (int i = 0; i < N; i++) asm volatile("" : "+f"(a[i])::"memory");
}
__device__ __forceinline__ bool elect_one() {
  uint32_t e; asm volatile("{\n.reg .pred P;\nelect.sync _|P, 0xffffffff;\nselp.u32 %0, 1, 0, P;\n}\n" : "=r"(e)); return e != 0;
}
__device__ __forceinline__ int tid_opaque() { int t; asm volatile("mov.u32 %0, %%tid.x;" : "=r"(t)); return t; }
struct Role { int T1, GP, side, m2, dg, cch0; bool last, has2; };
__device__ __forceinline__ Role unpack_role(int x) {
  Role r; r.T1 = x & 15; r.GP = (x >> 4) & 7; r.side = (x >> 7) & 1; r.m2 = (x >> 8) & 63; r.dg = (x >> 14) & 3;
  r.has2 = (x >> 16) & 1; r.last = r.T1 == NT1 - 1; r.cch0 = 160 * r.dg + r.m2; return r;
}
__device__ __forceinline__ Role fresh_role(int x) { asm volatile("" : "+r"(x)); return unpack_role(__shfl_sync(0xffffffffu, x, 0)); }
#define ROLE(x) const Role R_ = fresh_role(x); const int T1 = R_.T1, GP = R_.GP, side = R_.side, m2 = R_.m2, dg = R_.dg, cch0 = R_.cch0; \
  const bool last = R_.last, has2 = R_.has2; (void)T1; (void)GP; (void)side; (void)m2; (void)dg; (void)cch0; (void)last; (void)has2;
__device__ __forceinline__ int n_to_t(int n) {
  int T = n / 160, nl = n - T * 160;
  int L = (T == NT1 - 1) ? 32 : 40;
  return T * 160 + L * ((nl & 7) >> 1) + 2 * (nl >> 3) + (nl & 1);
}

template<int TA> __device__ __forceinline__ void wgmma_n160(float (&d)[80], uint32_t alo, uint32_t ahi, uint32_t blo, uint32_t bhi){
  asm volatile("{\n.reg .b64 da, db;\nmov.b64 da, {%80,%81};\nmov.b64 db, {%82,%83};\n"
    "wgmma.mma_async.sync.aligned.m64n160k16.f32.bf16.bf16 {%0, %1, %2, %3, %4, %5, %6, %7, %8, %9, %10, %11, %12, %13, %14, %15, %16, %17, %18, %19, %20, %21, %22, %23, %24, %25, %26, %27, %28, %29, %30, %31, %32, %33, %34, %35, %36, %37, %38, %39, %40, %41, %42, %43, %44, %45, %46, %47, %48, %49, %50, %51, %52, %53, %54, %55, %56, %57, %58, %59, %60, %61, %62, %63, %64, %65, %66, %67, %68, %69, %70, %71, %72, %73, %74, %75, %76, %77, %78, %79}, da, db, 1, 1, 1, %84, 0;\n}\n"
    : "+f"(d[0]), "+f"(d[1]), "+f"(d[2]), "+f"(d[3]), "+f"(d[4]), "+f"(d[5]), "+f"(d[6]), "+f"(d[7]), "+f"(d[8]), "+f"(d[9]), "+f"(d[10]), "+f"(d[11]), "+f"(d[12]), "+f"(d[13]), "+f"(d[14]), "+f"(d[15]), "+f"(d[16]), "+f"(d[17]), "+f"(d[18]), "+f"(d[19]), "+f"(d[20]), "+f"(d[21]), "+f"(d[22]), "+f"(d[23]), "+f"(d[24]), "+f"(d[25]), "+f"(d[26]), "+f"(d[27]), "+f"(d[28]), "+f"(d[29]), "+f"(d[30]), "+f"(d[31]), "+f"(d[32]), "+f"(d[33]), "+f"(d[34]), "+f"(d[35]), "+f"(d[36]), "+f"(d[37]), "+f"(d[38]), "+f"(d[39]), "+f"(d[40]), "+f"(d[41]), "+f"(d[42]), "+f"(d[43]), "+f"(d[44]), "+f"(d[45]), "+f"(d[46]), "+f"(d[47]), "+f"(d[48]), "+f"(d[49]), "+f"(d[50]), "+f"(d[51]), "+f"(d[52]), "+f"(d[53]), "+f"(d[54]), "+f"(d[55]), "+f"(d[56]), "+f"(d[57]), "+f"(d[58]), "+f"(d[59]), "+f"(d[60]), "+f"(d[61]), "+f"(d[62]), "+f"(d[63]), "+f"(d[64]), "+f"(d[65]), "+f"(d[66]), "+f"(d[67]), "+f"(d[68]), "+f"(d[69]), "+f"(d[70]), "+f"(d[71]), "+f"(d[72]), "+f"(d[73]), "+f"(d[74]), "+f"(d[75]), "+f"(d[76]), "+f"(d[77]), "+f"(d[78]), "+f"(d[79])
    : "r"(alo), "r"(ahi), "r"(blo), "r"(bhi), "n"(TA));
}
template<int N> __device__ __forceinline__ void wgmma_rs_hi(float (&d)[64], uint32_t a0, uint32_t a1, uint32_t a2, uint32_t a3, uint32_t blo);
template<> __device__ __forceinline__ void wgmma_rs_hi<16>(float (&d)[64], uint32_t a0, uint32_t a1, uint32_t a2, uint32_t a3, uint32_t blo){
  asm volatile("{\n.reg .b64 db;\nmov.b64 db, {%12,8};\nwgmma.mma_async.sync.aligned.m64n16k16.f32.bf16.bf16 {%0, %1, %2, %3, %4, %5, %6, %7}, {%8,%9,%10,%11}, db, 1, 1, 1, 0;\n}\n"
    : "+f"(d[56]), "+f"(d[57]), "+f"(d[58]), "+f"(d[59]), "+f"(d[60]), "+f"(d[61]), "+f"(d[62]), "+f"(d[63])
    : "r"(a0), "r"(a1), "r"(a2), "r"(a3), "r"(blo));
}
template<> __device__ __forceinline__ void wgmma_rs_hi<32>(float (&d)[64], uint32_t a0, uint32_t a1, uint32_t a2, uint32_t a3, uint32_t blo){
  asm volatile("{\n.reg .b64 db;\nmov.b64 db, {%20,8};\nwgmma.mma_async.sync.aligned.m64n32k16.f32.bf16.bf16 {%0, %1, %2, %3, %4, %5, %6, %7, %8, %9, %10, %11, %12, %13, %14, %15}, {%16,%17,%18,%19}, db, 1, 1, 1, 0;\n}\n"
    : "+f"(d[48]), "+f"(d[49]), "+f"(d[50]), "+f"(d[51]), "+f"(d[52]), "+f"(d[53]), "+f"(d[54]), "+f"(d[55]), "+f"(d[56]), "+f"(d[57]), "+f"(d[58]), "+f"(d[59]), "+f"(d[60]), "+f"(d[61]), "+f"(d[62]), "+f"(d[63])
    : "r"(a0), "r"(a1), "r"(a2), "r"(a3), "r"(blo));
}
template<> __device__ __forceinline__ void wgmma_rs_hi<48>(float (&d)[64], uint32_t a0, uint32_t a1, uint32_t a2, uint32_t a3, uint32_t blo){
  asm volatile("{\n.reg .b64 db;\nmov.b64 db, {%28,8};\nwgmma.mma_async.sync.aligned.m64n48k16.f32.bf16.bf16 {%0, %1, %2, %3, %4, %5, %6, %7, %8, %9, %10, %11, %12, %13, %14, %15, %16, %17, %18, %19, %20, %21, %22, %23}, {%24,%25,%26,%27}, db, 1, 1, 1, 0;\n}\n"
    : "+f"(d[40]), "+f"(d[41]), "+f"(d[42]), "+f"(d[43]), "+f"(d[44]), "+f"(d[45]), "+f"(d[46]), "+f"(d[47]), "+f"(d[48]), "+f"(d[49]), "+f"(d[50]), "+f"(d[51]), "+f"(d[52]), "+f"(d[53]), "+f"(d[54]), "+f"(d[55]), "+f"(d[56]), "+f"(d[57]), "+f"(d[58]), "+f"(d[59]), "+f"(d[60]), "+f"(d[61]), "+f"(d[62]), "+f"(d[63])
    : "r"(a0), "r"(a1), "r"(a2), "r"(a3), "r"(blo));
}
template<> __device__ __forceinline__ void wgmma_rs_hi<64>(float (&d)[64], uint32_t a0, uint32_t a1, uint32_t a2, uint32_t a3, uint32_t blo){
  asm volatile("{\n.reg .b64 db;\nmov.b64 db, {%36,8};\nwgmma.mma_async.sync.aligned.m64n64k16.f32.bf16.bf16 {%0, %1, %2, %3, %4, %5, %6, %7, %8, %9, %10, %11, %12, %13, %14, %15, %16, %17, %18, %19, %20, %21, %22, %23, %24, %25, %26, %27, %28, %29, %30, %31}, {%32,%33,%34,%35}, db, 1, 1, 1, 0;\n}\n"
    : "+f"(d[32]), "+f"(d[33]), "+f"(d[34]), "+f"(d[35]), "+f"(d[36]), "+f"(d[37]), "+f"(d[38]), "+f"(d[39]), "+f"(d[40]), "+f"(d[41]), "+f"(d[42]), "+f"(d[43]), "+f"(d[44]), "+f"(d[45]), "+f"(d[46]), "+f"(d[47]), "+f"(d[48]), "+f"(d[49]), "+f"(d[50]), "+f"(d[51]), "+f"(d[52]), "+f"(d[53]), "+f"(d[54]), "+f"(d[55]), "+f"(d[56]), "+f"(d[57]), "+f"(d[58]), "+f"(d[59]), "+f"(d[60]), "+f"(d[61]), "+f"(d[62]), "+f"(d[63])
    : "r"(a0), "r"(a1), "r"(a2), "r"(a3), "r"(blo));
}
template<> __device__ __forceinline__ void wgmma_rs_hi<80>(float (&d)[64], uint32_t a0, uint32_t a1, uint32_t a2, uint32_t a3, uint32_t blo){
  asm volatile("{\n.reg .b64 db;\nmov.b64 db, {%44,8};\nwgmma.mma_async.sync.aligned.m64n80k16.f32.bf16.bf16 {%0, %1, %2, %3, %4, %5, %6, %7, %8, %9, %10, %11, %12, %13, %14, %15, %16, %17, %18, %19, %20, %21, %22, %23, %24, %25, %26, %27, %28, %29, %30, %31, %32, %33, %34, %35, %36, %37, %38, %39}, {%40,%41,%42,%43}, db, 1, 1, 1, 0;\n}\n"
    : "+f"(d[24]), "+f"(d[25]), "+f"(d[26]), "+f"(d[27]), "+f"(d[28]), "+f"(d[29]), "+f"(d[30]), "+f"(d[31]), "+f"(d[32]), "+f"(d[33]), "+f"(d[34]), "+f"(d[35]), "+f"(d[36]), "+f"(d[37]), "+f"(d[38]), "+f"(d[39]), "+f"(d[40]), "+f"(d[41]), "+f"(d[42]), "+f"(d[43]), "+f"(d[44]), "+f"(d[45]), "+f"(d[46]), "+f"(d[47]), "+f"(d[48]), "+f"(d[49]), "+f"(d[50]), "+f"(d[51]), "+f"(d[52]), "+f"(d[53]), "+f"(d[54]), "+f"(d[55]), "+f"(d[56]), "+f"(d[57]), "+f"(d[58]), "+f"(d[59]), "+f"(d[60]), "+f"(d[61]), "+f"(d[62]), "+f"(d[63])
    : "r"(a0), "r"(a1), "r"(a2), "r"(a3), "r"(blo));
}
template<> __device__ __forceinline__ void wgmma_rs_hi<96>(float (&d)[64], uint32_t a0, uint32_t a1, uint32_t a2, uint32_t a3, uint32_t blo){
  asm volatile("{\n.reg .b64 db;\nmov.b64 db, {%52,8};\nwgmma.mma_async.sync.aligned.m64n96k16.f32.bf16.bf16 {%0, %1, %2, %3, %4, %5, %6, %7, %8, %9, %10, %11, %12, %13, %14, %15, %16, %17, %18, %19, %20, %21, %22, %23, %24, %25, %26, %27, %28, %29, %30, %31, %32, %33, %34, %35, %36, %37, %38, %39, %40, %41, %42, %43, %44, %45, %46, %47}, {%48,%49,%50,%51}, db, 1, 1, 1, 0;\n}\n"
    : "+f"(d[16]), "+f"(d[17]), "+f"(d[18]), "+f"(d[19]), "+f"(d[20]), "+f"(d[21]), "+f"(d[22]), "+f"(d[23]), "+f"(d[24]), "+f"(d[25]), "+f"(d[26]), "+f"(d[27]), "+f"(d[28]), "+f"(d[29]), "+f"(d[30]), "+f"(d[31]), "+f"(d[32]), "+f"(d[33]), "+f"(d[34]), "+f"(d[35]), "+f"(d[36]), "+f"(d[37]), "+f"(d[38]), "+f"(d[39]), "+f"(d[40]), "+f"(d[41]), "+f"(d[42]), "+f"(d[43]), "+f"(d[44]), "+f"(d[45]), "+f"(d[46]), "+f"(d[47]), "+f"(d[48]), "+f"(d[49]), "+f"(d[50]), "+f"(d[51]), "+f"(d[52]), "+f"(d[53]), "+f"(d[54]), "+f"(d[55]), "+f"(d[56]), "+f"(d[57]), "+f"(d[58]), "+f"(d[59]), "+f"(d[60]), "+f"(d[61]), "+f"(d[62]), "+f"(d[63])
    : "r"(a0), "r"(a1), "r"(a2), "r"(a3), "r"(blo));
}
template<> __device__ __forceinline__ void wgmma_rs_hi<112>(float (&d)[64], uint32_t a0, uint32_t a1, uint32_t a2, uint32_t a3, uint32_t blo){
  asm volatile("{\n.reg .b64 db;\nmov.b64 db, {%60,8};\nwgmma.mma_async.sync.aligned.m64n112k16.f32.bf16.bf16 {%0, %1, %2, %3, %4, %5, %6, %7, %8, %9, %10, %11, %12, %13, %14, %15, %16, %17, %18, %19, %20, %21, %22, %23, %24, %25, %26, %27, %28, %29, %30, %31, %32, %33, %34, %35, %36, %37, %38, %39, %40, %41, %42, %43, %44, %45, %46, %47, %48, %49, %50, %51, %52, %53, %54, %55}, {%56,%57,%58,%59}, db, 1, 1, 1, 0;\n}\n"
    : "+f"(d[8]), "+f"(d[9]), "+f"(d[10]), "+f"(d[11]), "+f"(d[12]), "+f"(d[13]), "+f"(d[14]), "+f"(d[15]), "+f"(d[16]), "+f"(d[17]), "+f"(d[18]), "+f"(d[19]), "+f"(d[20]), "+f"(d[21]), "+f"(d[22]), "+f"(d[23]), "+f"(d[24]), "+f"(d[25]), "+f"(d[26]), "+f"(d[27]), "+f"(d[28]), "+f"(d[29]), "+f"(d[30]), "+f"(d[31]), "+f"(d[32]), "+f"(d[33]), "+f"(d[34]), "+f"(d[35]), "+f"(d[36]), "+f"(d[37]), "+f"(d[38]), "+f"(d[39]), "+f"(d[40]), "+f"(d[41]), "+f"(d[42]), "+f"(d[43]), "+f"(d[44]), "+f"(d[45]), "+f"(d[46]), "+f"(d[47]), "+f"(d[48]), "+f"(d[49]), "+f"(d[50]), "+f"(d[51]), "+f"(d[52]), "+f"(d[53]), "+f"(d[54]), "+f"(d[55]), "+f"(d[56]), "+f"(d[57]), "+f"(d[58]), "+f"(d[59]), "+f"(d[60]), "+f"(d[61]), "+f"(d[62]), "+f"(d[63])
    : "r"(a0), "r"(a1), "r"(a2), "r"(a3), "r"(blo));
}
template<> __device__ __forceinline__ void wgmma_rs_hi<128>(float (&d)[64], uint32_t a0, uint32_t a1, uint32_t a2, uint32_t a3, uint32_t blo){
  asm volatile("{\n.reg .b64 db;\nmov.b64 db, {%68,8};\nwgmma.mma_async.sync.aligned.m64n128k16.f32.bf16.bf16 {%0, %1, %2, %3, %4, %5, %6, %7, %8, %9, %10, %11, %12, %13, %14, %15, %16, %17, %18, %19, %20, %21, %22, %23, %24, %25, %26, %27, %28, %29, %30, %31, %32, %33, %34, %35, %36, %37, %38, %39, %40, %41, %42, %43, %44, %45, %46, %47, %48, %49, %50, %51, %52, %53, %54, %55, %56, %57, %58, %59, %60, %61, %62, %63}, {%64,%65,%66,%67}, db, 1, 1, 1, 0;\n}\n"
    : "+f"(d[0]), "+f"(d[1]), "+f"(d[2]), "+f"(d[3]), "+f"(d[4]), "+f"(d[5]), "+f"(d[6]), "+f"(d[7]), "+f"(d[8]), "+f"(d[9]), "+f"(d[10]), "+f"(d[11]), "+f"(d[12]), "+f"(d[13]), "+f"(d[14]), "+f"(d[15]), "+f"(d[16]), "+f"(d[17]), "+f"(d[18]), "+f"(d[19]), "+f"(d[20]), "+f"(d[21]), "+f"(d[22]), "+f"(d[23]), "+f"(d[24]), "+f"(d[25]), "+f"(d[26]), "+f"(d[27]), "+f"(d[28]), "+f"(d[29]), "+f"(d[30]), "+f"(d[31]), "+f"(d[32]), "+f"(d[33]), "+f"(d[34]), "+f"(d[35]), "+f"(d[36]), "+f"(d[37]), "+f"(d[38]), "+f"(d[39]), "+f"(d[40]), "+f"(d[41]), "+f"(d[42]), "+f"(d[43]), "+f"(d[44]), "+f"(d[45]), "+f"(d[46]), "+f"(d[47]), "+f"(d[48]), "+f"(d[49]), "+f"(d[50]), "+f"(d[51]), "+f"(d[52]), "+f"(d[53]), "+f"(d[54]), "+f"(d[55]), "+f"(d[56]), "+f"(d[57]), "+f"(d[58]), "+f"(d[59]), "+f"(d[60]), "+f"(d[61]), "+f"(d[62]), "+f"(d[63])
    : "r"(a0), "r"(a1), "r"(a2), "r"(a3), "r"(blo));
}

__device__ __forceinline__ float shfl_sel(float a, float b, bool p, int src) {
  float r;
  asm volatile("{\n.reg .pred P;\n.reg .f32 t;\nsetp.ne.u32 P, %3, 0;\nselp.f32 t, %1, %2, P;\nshfl.sync.idx.b32 %0, t, %4, 0x1f, 0xffffffff;\n}\n"
               : "=f"(r) : "f"(a), "f"(b), "r"((uint32_t)p), "r"(src));
  return r;
}
struct CvCtx {
  uint32_t koff, zero, so[4];
  int srcA, srcB;
  bool wrapA, s3, kodd;
};
struct CvPipe { float Ep[2], keep[2], send[2]; };
template <int LO> __device__ __forceinline__ void cv_copy(float (&acc)[64]) {
#pragma unroll
  for (int i = LO; i < 64; i++) { float t; asm volatile("mov.b32 %0, %1;" : "=f"(t) : "f"(acc[i]) : "memory"); acc[i] = t; }
}
template <int G> __device__ __forceinline__ void cv_raw(uint32_t (&A)[4][4], uint32_t kaddr) {
#pragma unroll
  for (int i = 0; i < 4; i++) {
    const uint32_t a = kaddr + (4 * G + i) * 128;
    A[i][0] = lds32(a); A[i][1] = lds32(a + 4); A[i][3] = lds32(a + 8);
  }
}
__device__ __forceinline__ void cv_form(uint32_t (&A)[4][4], uint32_t sel) {
#pragma unroll
  for (int i = 0; i < 4; i++) {
    asm volatile("prmt.b32 %0, %0, %1, %2;" : "+r"(A[i][0]) : "r"(A[i][1]), "r"(sel));
    asm volatile("prmt.b32 %0, %1, %2, %3;" : "=r"(A[i][2]) : "r"(A[i][1]), "r"(A[i][3]), "r"(sel));
  }
}
#define CVV 2
template <int G> __device__ __forceinline__ void cv_step(float (&acc)[64], uint32_t (&A)[4][4], CvPipe& s, const CvCtx& c, uint32_t cb, uint32_t stg) {
  constexpr int JA = G - 1, JB = G - 2, NH = CVV == 1 ? 4 : (CVV == 3 ? 2 : 1);
  const uint32_t db0 = desc_lo(cb + CV_U + 192, CV_PL);
  uint32_t B[4][4];
  float ra[4], rb[2];
  if constexpr (G < 8) {
    wgmma_fence();
#pragma unroll
    for (int i = 0; i < NH; i++) wgmma_rs_hi<128 - 16 * (G & 7)>(acc, A[i][0], A[i][1], A[i][2], A[i][3], db0 - 4 * i);
    wgmma_commit();
    __syncwarp();
  }
  if constexpr (JA >= 0 && JA < 8) {
#pragma unroll
    for (int x = 0; x < 4; x++) {
      const int i = 8 * JA + 4 * (x >> 1) + 2 * (x & 1) + 1;
      ra[x] = shfl_sel(i >= 4 ? acc[i >= 4 ? i - 4 : 0] : 0.f, acc[i], c.wrapA, c.srcA);
    }
  }
  if constexpr (JB >= 0) {
#pragma unroll
    for (int h = 0; h < 2; h++) rb[h] = __shfl_sync(0xffffffffu, s.send[h], c.srcB);
  }
  if constexpr (G < 7) cv_raw<G + 1>(B, cb + c.koff);
  uint32_t z = 0;
  if constexpr (G < 8 && NH < 4) {
    __syncwarp();
    wgmma_fence();
#pragma unroll
    for (int i = NH; i < 4; i++) wgmma_rs_hi<128 - 16 * (G & 7)>(acc, A[i][0], A[i][1], A[i][2], A[i][3], db0 - 4 * i);
    wgmma_commit();
    asm volatile("mov.u32 %0, %%clock;" : "=r"(z)::"memory");
    z &= c.zero;
  }
  const float one = __uint_as_float(0x3f800000u | z);
  if constexpr (G < 7) cv_form(B, 0x5432u | z);
  if constexpr (JB >= 0) sts32(stg + ((JB & 1) ? c.so[JB >> 1] >> 16 : c.so[JB >> 1] & 0xffff), pack_bf16(fmaf(rb[0], one, s.keep[0]), fmaf(rb[1], one, s.keep[1])));
  if constexpr (JA >= 0 && JA < 8) {
#pragma unroll
    for (int h = 0; h < 2; h++) {
      const float ev = fmaf(ra[h], one, acc[8 * JA + 2 * h]), od = fmaf(ra[2 + h], one, acc[8 * JA + 4 + 2 * h]);
      s.send[h] = c.kodd ? ev : (c.s3 ? s.Ep[h] : od);
      s.keep[h] = c.kodd ? od : ev;
      s.Ep[h] = od;
    }
  }
  if constexpr (G < 8) { __syncwarp(); wgmma_wait<0>(); cv_copy<8 * (G & 7)>(acc); }
  if constexpr (G < 9) cv_step<G + 1>(acc, B, s, c, cb, stg);
}
__device__ __forceinline__ uint32_t cv_stage(int slot) { return sb + (slot < 4 ? 40960 + slot * 4096 : CV_OFF + CV_K); }
__device__ __forceinline__ void cv_setup(CvCtx& c) {
  const int tid = tid_opaque() & 127, w = tid >> 5, lane = tid & 31, r = lane >> 2, q = lane & 3;
  const int i0 = (r >> 1) & 1, i1 = r >> 2;
  c.koff = CV_K - 32 + 4 * (8 * (r >> 1) + 2 * w + (r & 1) + 2 * q);
  c.srcA = i0 ? lane - 8 : lane + 8 - q + ((q + 3) & 3);
  c.wrapA = i0 && q == 3;
  c.srcB = i1 == 0 ? (lane - q + 16 + ((q + 3) & 3)) : (lane - q - 16 + ((q + 1) & 3));
  c.s3 = (i1 == 1 && q == 3); c.kodd = (i1 == 1 && q < 3);
  c.zero = lds32(sb + EP_OFF + 24);
  const int tb = 16 * (2 * (i1 == 0 ? q : 4 + ((q + 1) & 3)) + i0) + 4 * w + 2 * (r & 1);
#pragma unroll
  for (int J = 0; J < 8; J++) {
    const int t = 256 * J + tb, T = t / 160, tl = t - T * 160;
    const int qq = (T == NT1 - 1) ? (tl >> 5) : (tl / 40);
    int ck = 20 * T + ((tl - qq * ((T == NT1 - 1) ? 32 : 40)) >> 1);
    ck ^= (ck >> 2) & 6;
    const uint32_t o = ck * 16 + qq * 4;
    if (J & 1) c.so[J >> 1] |= o << 16; else c.so[J >> 1] = o;
  }
}
__device__ __forceinline__ void conv_channel(int slot, const CvCtx& c) {
  const uint32_t cb = sb + CV_OFF + slot * CV_B;
  float acc[64];
  CvPipe s;
  s.Ep[0] = s.Ep[1] = 0.f;
  uint32_t A[4][4];
#pragma unroll
  for (int i = 0; i < 64; i++) acc[i] = 0.f;
  if (slot == 4) mbar_wait(bars + 8 * B_CVDONE);
  mbar_wait(bars + 8 * (B_CVFULL + slot));
  cv_raw<0>(A, cb + c.koff);
  cv_form(A, 0x5432u);
  cv_copy<0>(acc);
  cv_step<0>(acc, A, s, c, cb, cv_stage(slot));
  fence_async_smem();
  mbar_arrive(bars + 8 * (B_CVDONE + slot));
}

__device__ __forceinline__ void kv_issue(const Params& p, int c, int m2, int dg) {
  const uint32_t fb = bars + 8 * (B_KV + c);
  mbar_expect_tx(fb, KV_PIECE);
  tma3(sb + KS_OFF + c * KV_PIECE, &p.mK, 160 * dg + 32 * c, 64 * m2 - 3, 0, fb);
  tma3(sb + KS_OFF + c * KV_PIECE + 4864, &p.mV, 160 * dg + 32 * c, 64 * m2 - 1, 0, fb);
}
__device__ __forceinline__ void kv_tile(int m, int dg, int c, int y) {
  const int lane = tid_opaque() & 31, tg = lane >> 3;
  const uint32_t pb = sb + KS_OFF + c * KV_PIECE + 32 * y + 4 * (lane & 7);
  const uint32_t ka = pb + tg * 1216, va = pb + 4864 + tg * 1088 + 64;
  const uint32_t kh = (m == 0 && tg > 0) ? ka - 192 : ka;
  uint32_t kk[19], u[16];
  const float4 t = lds128f(sb + TAP_OFF + 256 * c + 128 * y + 16 * (lane & 7));
#pragma unroll
  for (int i = 0; i < 19; i++) { kk[i] = lds32((i < 3 ? kh : ka) + i * 64); if (i >= 3) u[i - 3] = lds32(va + (i - 3) * 64); }
  uint8_t* dst = g_kv + ((160 * dg + 32 * c + 16 * y + 2 * (lane & 7)) * 4096 + (4 * m + tg) * 16);
  const uint32_t w0 = __byte_perm(__float_as_uint(t.x), __float_as_uint(t.z), 0x5410), w1 = __byte_perm(__float_as_uint(t.x), __float_as_uint(t.z), 0x7632);
  const uint32_t w2 = __byte_perm(__float_as_uint(t.y), __float_as_uint(t.w), 0x5410), w3 = __byte_perm(__float_as_uint(t.y), __float_as_uint(t.w), 0x7632);
#pragma unroll
  for (int i = 0; i < 16; i++) {
    uint32_t a = hmul2(kk[i], w3);
    a = hadd2(a, hmul2(kk[i + 1], w2)); a = hadd2(a, hmul2(kk[i + 2], w1)); a = hadd2(a, hmul2(kk[i + 3], w0));
    u[i] = hmul2(a, u[i]);
  }
#pragma unroll
  for (int e = 0; e < 2; e++)
#pragma unroll
    for (int f = 0; f < 2; f++) {
      uint32_t o[4];
#pragma unroll
      for (int qq = 0; qq < 4; qq++) o[qq] = __byte_perm(u[15 - 4 * qq - 2 * f], u[14 - 4 * qq - 2 * f], e ? 0x7632 : 0x5410);
      *(uint4*)(dst + e * 4096 + f * 2048) = make_uint4(o[0], o[1], o[2], o[3]);
    }
}
__device__ __forceinline__ void ln_finish(float s1, float s2, float& mean, float& rstd) {
  mean = s1 * (1.f / 640.f);
  const float v = fmaxf(fmaf(-mean, mean, s2 * (1.f / 640.f)), 0.f) + 1e-5f;
  asm("rsqrt.approx.ftz.f32 %0, %1;" : "=f"(rstd) : "f"(v));
}
__device__ __forceinline__ void stat_table(int T1, unsigned want, int l, int w) {
#pragma unroll 1
  for (int g = w; g < (T1 == NT1 - 1 ? 4 : 5); g += 4) {
    const int n = 32 * g + (tid_opaque() & 31);
    const uint4* rp = &g_stats[8 * l * SEQ + 160 * T1 + n];
    float a[4], b[4];
    uint32_t it = 0;
    while (true) {
      bool ok = true;
#pragma unroll
      for (int i = 0; i < 4; i++) ok &= (rec_ld(rp + SEQ * i, a[i], b[i]) == want);
      if (__all_sync(0xffffffffu, ok)) break;
      trap_if(++it > SPIN_LIMIT);
    }
    float m, rs;
    ln_finish((a[0] + a[1]) + (a[2] + a[3]), (b[0] + b[1]) + (b[2] + b[3]), m, rs);
    sts64f(sb + STAB_OFF + n * 8, rs, -m * rs);
  }
  mbar_arrive(bars + 8 * (B_STAB + l));
}

template <bool FIRST>
__device__ __forceinline__ void stats_publish(int which, int n0, int dg, unsigned tag, const float (&acc)[80]) {
  const int q = tid_opaque() & 3, h = q & 1;
  float s1[2] = {0.f, 0.f}, s2[2] = {0.f, 0.f}, t1[2] = {0.f, 0.f}, t2[2] = {0.f, 0.f};
#pragma unroll
  for (int j = 0; j < 20; j++)
#pragma unroll
    for (int y = 0; y < 2; y++) {
      const float a = acc[4 * j + 2 * y], b = acc[4 * j + 2 * y + 1];
      s1[y] += a; t1[y] += b; s2[y] = fmaf(a, a, s2[y]); t2[y] = fmaf(b, b, t2[y]);
    }
#pragma unroll
  for (int y = 0; y < 2; y++) { s1[y] += t1[y]; s2[y] += t2[y]; }
  float a = (h ? s1[1] : s1[0]) + __shfl_xor_sync(0xffffffffu, h ? s1[0] : s1[1], 1);
  float b = (h ? s2[1] : s2[0]) + __shfl_xor_sync(0xffffffffu, h ? s2[0] : s2[1], 1);
  a += __shfl_xor_sync(0xffffffffu, a, 2);
  b += __shfl_xor_sync(0xffffffffu, b, 2);
  if (FIRST) {
    rec_st(&g_stats[((q >> 1) * 4 + dg) * SEQ + n0 + 8 * h], a, b, q < 2 ? tag : tag - 1);
    rec_st(&g_stats[((q >> 1) * 4 + 8 + dg) * SEQ + n0 + 8 * h], a, b, tag - 1);
  } else if (q < 2) rec_st(&g_stats[(which * 4 + dg) * SEQ + n0 + 8 * h], a, b, tag);
}
__device__ __forceinline__ void stats_get(int which, int n0, unsigned tag, float (&mean)[2], float (&rstd)[2]) {
  const uint4* p0 = &g_stats[(which * 4 + (tid_opaque() & 3)) * SEQ + n0];
  float a[2], b[2];
  uint32_t it = 0;
  while (true) {
    const unsigned t0 = rec_ld(p0, a[0], b[0]), t1 = rec_ld(p0 + 8, a[1], b[1]);
    if (__all_sync(0xffffffffu, t0 == tag && t1 == tag)) break;
    trap_if(++it > SPIN_LIMIT);
  }
#pragma unroll
  for (int o = 1; o < 4; o <<= 1)
#pragma unroll
    for (int h = 0; h < 2; h++) { a[h] += __shfl_xor_sync(0xffffffffu, a[h], o); b[h] += __shfl_xor_sync(0xffffffffu, b[h], o); }
#pragma unroll
  for (int h = 0; h < 2; h++) ln_finish(a[h], b[h], mean[h], rstd[h]);
}
__device__ __forceinline__ void x0_load(float (&acc)[80]) {
  const int t = tid_opaque() & 127;
  const uint32_t xa = sb + XT_OFF + (16 * (t >> 5) + ((t & 31) >> 2)) * 320 + 8 * (t & 3);
  mbar_wait(bars + 8 * B_XT);
#pragma unroll
  for (int h = 0; h < 2; h++)
#pragma unroll
    for (int J = 0; J < 10; J++) {
      const float2 v = lds64f(xa + h * 2560 + 32 * J);
      const uint32_t x = __float_as_uint(v.x), y = __float_as_uint(v.y);
      acc[8 * J + 2 * h] = bf_lo(x); acc[8 * J + 2 * h + 1] = bf_hi(x);
      acc[8 * J + 4 + 2 * h] = bf_lo(y); acc[8 * J + 4 + 2 * h + 1] = bf_hi(y);
    }
}

__global__ void __launch_bounds__(512, 1) fused_kernel(const __grid_constant__ Params p) {
  extern __shared__ __align__(1024) uint8_t smem_raw[];
  const int tid = threadIdx.x, lane = tid & 31;
  const int wid = __shfl_sync(0xffffffffu, tid >> 5, 0), wg = wid >> 2;
  unsigned smid; asm volatile("mov.u32 %0, %%smid;" : "=r"(smid));
  const int role = p.role[min(smid, 131u)];
  if (wid == 12) {
    const bool el = elect_one();
    if (el) {
      asm volatile("prefetch.tensormap [%0];" ::"l"(&p.mX) : "memory");
      asm volatile("prefetch.tensormap [%0];" ::"l"(&p.mB) : "memory");
#pragma unroll
      for (int k = 0; k < S1; k++) mbar_init(bars + 8 * (B_G1FULL + k), 1);
#pragma unroll
      for (int k = 0; k < 6; k++) mbar_init(bars + 8 * (B_XT + k), 1);
      asm volatile("fence.mbarrier_init.release.cluster;" ::: "memory");
    }
    if (role >= 0) {
      __syncwarp();
      asm volatile("bar.arrive 5, 288;" ::: "memory");
      const Role R = unpack_role(role);
      if (elect_one()) {
        TS(45);
#pragma unroll 1
        for (int k = 0; k < S1; k++) {
          const uint32_t fb = bars + 8 * (B_G1FULL + k);
          mbar_expect_tx(fb, G1_STAGE);
          tma4(sb + k * G1_STAGE + G1_XOFF, R.last ? &p.mXl : &p.mX, 64 * k, 0, 0, R.last ? 0 : 80 * R.T1, fb);
          tma5(sb + k * G1_STAGE, &p.mB, 64 * k, 0, 0, 4 * R.side, 2 * R.GP, fb);
        }
        if (R.has2) {
#pragma unroll 1
          for (int c = 0; c < KV0; c++) kv_issue(p, c, R.m2, R.dg);
          mbar_expect_tx(bars + 8 * B_XT, 20480);
#pragma unroll 1
          for (int h = 0; h < 2; h++) {
            const int ng = 8 * R.m2 + 4 * h, T = ng / 20;
            tma4(sb + XT_OFF + h * 10240, T == NT1 - 1 ? &p.mXtl : &p.mXt, 160 * R.dg, 0, 0, T == NT1 - 1 ? ng - 240 : ng + 60 * T, bars + 8 * B_XT);
          }
        }
        TS(44);
      }
      __syncwarp();
      bar_sync(6, 64);
    }
  }
  trap_if(smid >= 132 || smem_u32(smem_raw) != sb);
  if (role < 0) {
    if (wid == 0) {
      const unsigned tag = ld_rlx(g_epoch);
#pragma unroll 1
      for (int i = 0; i < NT1; i++) {
        uint32_t it = 0;
        while (!__all_sync(0xffffffffu, (int)(ld_rlx(&g_hflag[(i * 32 + min(lane, 9)) * 8]) - tag) >= 0)) { __nanosleep(500); trap_if(++it > SPIN_LIMIT); }
      }
    }
    return;
  }
  if (wg == 2 || wid == 14) {
    ROLE(role)
    const int c = wid == 14 ? 4 : wid - 8;
    const unsigned tag = ld_rlx(g_epoch);
    if (has2) {
      uint2 bv[2][5];
#pragma unroll
      for (int x = 0; x < 2; x++)
#pragma unroll
        for (int i = 0; i < 5; i++) bv[x][i] = ldv64((const uint2*)((x ? p.bim : p.bre) + (cch0 + 32 * c) * DM) + lane + 32 * i);
      float sv[2];
#pragma unroll
      for (int x = 0; x < 2; x++) {
        float a = 0.f;
#pragma unroll
        for (int i = 0; i < 5; i++) a += (bf_lo(bv[x][i].x) + bf_hi(bv[x][i].x)) + (bf_lo(bv[x][i].y) + bf_hi(bv[x][i].y));
        sv[x] = a;
      }
#pragma unroll
      for (int o = 16; o > 0; o >>= 1) { sv[0] += __shfl_xor_sync(0xffffffffu, sv[0], o); sv[1] += __shfl_xor_sync(0xffffffffu, sv[1], o); }
      if (lane < 2) rec_st(&g_sB[(cch0 + 32 * c) * 2 + lane], sv[0], sv[1], tag);
      if (tid == 256) TS(47);
      __syncwarp();
      bar_sync(8, 192);
      mbar_wait(bars + 8 * B_EP);
      mbar_wait(bars + 8 * (B_KV + c));
#pragma unroll 1
      for (int y = 0; y < 2; y++) kv_tile(m2, dg, c, y);
      __syncwarp();
      if (lane == 0) { mbar_arrive(bars + 8 * (B_PD + c)); mbar_arrive(bars + 8 * B_PREP); }
      if (tid == 256) TS(48);
      if (tid == 352) TS(52);
      if (tid == 448) TS(51);
      if (wg == 2) {
        float xs[80];
        x0_load(xs);
        stats_publish<true>(0, 64 * m2 + 16 * c + (lane >> 2), dg, tag, xs);
        if (tid == 256) TS(31);
        mbar_wait(bars + 8 * B_PUB);
      } else {
        mbar_wait(bars + 8 * B_PREP);
        if (lane == 0) { st_rel(&g_kvflag[(dg * 32 + m2) * 8], tag); mbar_arrive(bars + 8 * B_PUB); TS(30); }
        __syncwarp();
      }
    } else bar_sync(8, 192);
    if (wg == 2) {
      if (c == 1 || c == 2) {
        float a, b;
        rec_poll(&g_sB[(128 * GP + 64 * (c - 1) + 32 * side + lane) * 2], tag, a, b);
        sts64f(sb + CTAB_OFF + (32 * (c - 1) + lane) * 24 + 16, p.swap ? b : a, p.swap ? a : b);
      }
      stat_table(T1, tag, 0, c);
      if (tid == 256) TS(26);
    }
  } else if (wid == 15) {
    ROLE(role)
    const int ch = 128 * GP + 32 * side + lane;
    uint32_t r0 = ldv16(p.lre + ch), r1 = ldv16(p.lim + ch), r2 = ldv16(p.logdt + ch);
    const uint32_t r3 = ldv16(p.lre + ch + 64), r4 = ldv16(p.lim + ch + 64), r5 = ldv16(p.logdt + ch + 64);
#pragma unroll 1
    for (int i = 0; i < 2; i++) {
      const float lr = bf_lo(r0), li = bf_lo(r1);
      const float dt = __bfloat162float(__float2bfloat16_rn(expf(bf_lo(r2))));
      const float mag = expf(dt * lr);
      float sn, cs; sincospif(dt * li * 0.31830988618379067f, &sn, &cs);
      const float ar = mag * cs, ai = mag * sn;
      const float inv = 2.f / (lr * lr + li * li);
      const uint32_t ad = sb + CTAB_OFF + (32 * i + lane) * 24;
      sts64f(ad, ar, ai);
      sts64f(ad + 8, ((ar - 1.f) * lr + ai * li) * inv, (ai * lr - (ar - 1.f) * li) * inv);
      r0 = r3; r1 = r4; r2 = r5;
    }
    if (lane == 0) TS(46);
    __syncwarp();
    bar_sync(7, 64);
    mbar_arrive(bars + 8 * B_CTAB);
  } else if (wid == 13) {
    ROLE(role)
    uint4 tv[3];
    const uint32_t e0 = ld_rlx(g_epoch);
    const uint32_t e1 = ldv16(p.ssmD + min(cch0 + 32 * lane, 639));
    const uint4 dv = ldv128((const uint4*)(p.dskip + 160 * dg) + min(lane, 19));
#pragma unroll
    for (int i = 0; i < 3; i++) tv[i] = ldv128((const uint4*)(p.shiftk + 640 * dg) + min(lane + 32 * i, 79));
    sts128(sb + DTAB_OFF + 16 * min(lane, 19), dv);
#pragma unroll
    for (int i = 0; i < 3; i++) sts128(sb + TAP_OFF + 16 * min(lane + 32 * i, 79), tv[i]);
    if (lane < 7) sts32(sb + EP_OFF + 4 * lane, lane < 5 ? e1 << 16 : (lane == 5 ? e0 : 0u));
    __syncwarp();
    bar_sync(9, 64);
    mbar_arrive(bars + 8 * B_CTAB);
    if (lane == 0) { mbar_arrive(bars + 8 * B_EP); TS(53); }
  } else if (wid != 12) {
    if (elect_one()) {
      if (wid < 7) {
        const int b0 = wid < 4 ? 4 + 20 * wid : 85 + 21 * (wid - 4), cnt = wid < 4 ? 2 : 1;
#pragma unroll
        for (int i = 0; i < 21; i++) mbar_init(bars + 8 * (b0 + i), cnt);
      } else {
#pragma unroll
        for (int i = 0; i < 12; i++) mbar_init(bars + 8 * (B_CVDONE + i), 128);
        mbar_init(bars + 8 * B_CTAB, 64); mbar_init(bars + 8 * B_PREP, 5);
      }
      asm volatile("fence.mbarrier_init.release.cluster;" ::: "memory");
    }
    __syncwarp();
    bar_sync(5, 288);
    if (wid == 2) asm volatile("bar.arrive 8, 192;\nbar.arrive 6, 64;\nbar.arrive 9, 64;\nbar.arrive 7, 64;" ::: "memory");
    if (tid == 128) TS(0);
  }

  if (wg == 3) {
    ROLE(role)
    const int pw = wid & 3;
    unsigned tag = 0;
    if (pw > 0) { mbar_wait(bars + 8 * B_EP); tag = lds32(sb + EP_OFF + 20); }
    if (pw == 0) {
      if (elect_one()) {
#pragma unroll 1
        for (int l = 0; l < 2; l++) {
          const uint32_t fb0 = bars + 8 * (B_G1FULL + 10 * l), wb = bars + 8 * (B_G1DONE + 9 * l - S1);
          const uint32_t free0 = bars + 8 * (has2 ? B_G2DONE + 19 : B_G1DONE + 9);
          uint32_t dst = sb;
#pragma unroll 1
          for (int k = l == 0 ? S1 : 0; k < 10; k++) {
            mbar_wait(k >= S1 + l ? wb + 8 * k : (k < WPF1 || !has2 ? free0 : bars + 8 * (B_GO + 1)));
            mbar_expect_tx(fb0 + 8 * k, 16384);
            tma5(dst, &p.mB, 64 * k, 0, 0, 4 * side, 2 * GP, fb0 + 8 * k);
            dst += G1_STAGE; if (dst == sb + (S1 + l) * G1_STAGE) dst = sb;
          }
          if (has2) {
            const uint32_t fb2 = bars + 8 * (B_G2FULL + 20 * l), wb2 = bars + 8 * (B_G2DONE + 19 * l - 6);
            dst = sb + G2_WOFF;
            int kc = 0;
#pragma unroll 1
            for (int k = 0; k < 20; k++) {
              mbar_wait(k >= 6 + l ? wb2 + 8 * k : (k == 5 ? bars + 8 * B_XFREE : (k < WPF2 ? bars + 8 * (B_G1DONE + 10 * l + 9) : bars + 8 * (B_GO + 2 * l))));
              mbar_expect_tx(fb2 + 8 * k, G2_WB);
              tma5(dst, &p.mCre + (k & 1), kc, 0, 0, 0, 10 * dg, fb2 + 8 * k);
              kc += (k & 1) << 7; if (k == 9) kc = 64;
              dst += G2_WB; if (dst == sb + G2_WOFF + (6 + l) * G2_WB) dst = sb + G2_WOFF;
            }
          }
        }
      }
    } else if (pw == 1) {
#pragma unroll 1
      for (int l = 0; l < 2; l++) {
        if (l == 0) {
          if (elect_one()) {
            uint32_t dst = sb + G1_XOFF;
#pragma unroll 1
            for (int k = S1; k < 10; k++) {
              mbar_wait(bars + 8 * (B_G1DONE + k - S1));
              mbar_expect_tx(bars + 8 * (B_G1FULL + k), 20480);
              tma4(dst, last ? &p.mXl : &p.mX, 64 * k, 0, 0, last ? 0 : 80 * T1, bars + 8 * (B_G1FULL + k));
              dst += G1_STAGE; if (k == 2 * S1 - 1) dst = sb + G1_XOFF;
              if (has2 && k - S1 + KV0 < 5) kv_issue(p, k - S1 + KV0, m2, dg);
            }
          }
        } else {
          mbar_wait(bars + 8 * (has2 ? B_G2DONE + 19 : B_G1DONE + 9));
          const int mlo = (160 * T1) >> 6, nf = last ? 8 : 12;
          flag_poll(&g_uflag[(4 * mlo + min(lane, nf - 1)) * 8], tag);
          fence_async_global();
          if (elect_one()) {
            TS(20);
            const int bytes = last ? 16384 : 20480;
            const uint8_t* src = g_u + T1 * 204800;
            uint32_t dst = sb + G1_XOFF;
#pragma unroll 1
            for (int k = 0; k < 10; k++) {
              if (k > S1) mbar_wait(bars + 8 * (B_G1DONE + 9 - S1 + k));
              mbar_expect_tx(bars + 8 * (B_G1FULL + 10 + k), bytes);
              bulk_g2s(dst, src, bytes, bars + 8 * (B_G1FULL + 10 + k));
              src += 20480; dst += G1_STAGE; if (k == S1) dst = sb + G1_XOFF;
            }
          }
        }
        __syncwarp();
        if (has2) {
          mbar_wait(bars + 8 * (B_G1DONE + 10 * l + 9));
          const int Tlo = (64 * m2) / 160, Thi = (64 * m2 + 63) / 160;
          flag_poll(&g_hflag[(((l * NT1 + (lane < 16 ? Tlo : Thi)) * 2) * 16 + min(lane & 15, 9)) * 8], tag);
          fence_async_global();
          if (elect_one()) {
            TS(21 + 2 * l);
            const uint32_t fb2 = bars + 8 * (B_G2FULL + 20 * l), wb2 = bars + 8 * (B_G2DONE + 18 * l - SX2);
            const uint8_t* src = g_h + (l * 32 + m2) * 163840;
            uint32_t dst = sb;
#pragma unroll 1
            for (int k = 0; k < 20; k++) {
              if (k >= SX2 + 2 * l) mbar_wait(wb2 + 8 * k);
              if (k == 10) { mbar_wait(bars + 8 * (B_H1 + l)); fence_async_global(); }
              mbar_expect_tx(fb2 + 8 * k, G2_XB);
              bulk_g2s(dst, src, G2_XB, fb2 + 8 * k);
              src += 8192; dst += G2_XB; if (dst == sb + (SX2 + 2 * l) * G2_XB) dst = sb;
            }
          }
          __syncwarp();
        }
      }
    } else if (pw == 2) {
#pragma unroll 1
      for (int l = 0; l < 2; l++) {
        mbar_wait(bars + 8 * (B_HST + 2 * l));
        mbar_wait(bars + 8 * (B_HST + 2 * l + 1));
        __syncwarp();
        if (lane < 2) st_rel(&g_hflag[(((l * NT1 + T1) * 2 + lane) * 16 + 2 * GP + side) * 8], tag);
        if (lane == 0) TS(6 + 8 * l);
        __syncwarp();
        if (l == 0 && has2 && elect_one()) {
#pragma unroll 1
          for (int c = 0; c < 5; c++) {
            mbar_wait(bars + 8 * (B_CVDONE + c));
            bulk_s2g(g_G + (cch0 + 32 * c) * 4096, cv_stage(c), 4096);
          }
          asm volatile("cp.async.bulk.commit_group;" ::: "memory");
          asm volatile("cp.async.bulk.wait_group 0;" ::: "memory");
          fence_async_global();
          st_rel(&g_gflag[(dg * 32 + m2) * 8], tag);
        }
        __syncwarp();
      }
    } else if (has2) {
#pragma unroll 1
      for (int c = 0; c < 5; c++) {
        mbar_wait(bars + 8 * (B_PD + c));
        const uint32_t cb = sb + CV_OFF + c * CV_B;
        sts128(lane < 8 ? cb + 16 * lane : (lane < 20 ? cb + CV_U + 16 * (lane - 8) : cb + CV_U + CV_PL + 16 * (lane - 20)), make_uint4(0, 0, 0, 0));
        fence_async_smem();
        __syncwarp();
        if (c < TAP0 && elect_one()) {
          mbar_expect_tx(bars + 8 * (B_TAPS + c), 4096);
          bulk_g2s(cb + CV_K, p.ssmk + (cch0 + 32 * c) * SEQ, 4096, bars + 8 * (B_TAPS + c));
        }
      }
      mbar_wait(bars + 8 * B_PUB);
      flag_poll(&g_kvflag[(dg * 32 + lane) * 8], tag);
      fence_async_global();
      if (elect_one()) {
        TS(28);
#pragma unroll 1
        for (int c = 0; c < 5; c++) {
          const uint32_t fb = bars + 8 * (B_CVFULL + c), cb = sb + CV_OFF + c * CV_B;
          mbar_expect_tx(fb, 4096);
          bulk_g2s(cb + CV_U + 192, g_kv + (cch0 + 32 * c) * 4096, 2048, fb);
          bulk_g2s(cb + CV_U + 192 + CV_PL, g_kv + (cch0 + 32 * c) * 4096 + 2048, 2048, fb);
          if (c >= TAP0) {
            mbar_expect_tx(bars + 8 * (B_TAPS + c), 4096);
            bulk_g2s(cb + CV_K, p.ssmk + (cch0 + 32 * c) * SEQ, 4096, bars + 8 * (B_TAPS + c));
          }
        }
#pragma unroll 1
        for (int c = 0; c < 5; c++) {
          mbar_wait(bars + 8 * (B_TAPS + c));
          const uint32_t a = sb + CV_OFF + c * CV_B + CV_K, w0 = lds32(a);
          sts32(a, (w0 & 0xffff0000u) | (pack_bf16(bf_lo(w0) + __uint_as_float(lds32(sb + EP_OFF + 4 * c)), 0.f) & 0xffffu));
          mbar_arrive(bars + 8 * (B_CVFULL + c));
        }
        TS(54);
        asm volatile("prefetch.tensormap [%0];" ::"l"(&p.mCre) : "memory");
        asm volatile("prefetch.tensormap [%0];" ::"l"(&p.mCim) : "memory");
        asm volatile("prefetch.tensormap [%0];" ::"l"(&p.mG) : "memory");
      }
      __syncwarp();
      const unsigned* hf = &g_hflag[(((lane < 16 ? (64 * m2) / 160 : (64 * m2 + 63) / 160) * 2 + 1) * 16 + min(lane & 15, 9)) * 8];
      mbar_wait(bars + 8 * (B_CVDONE + 0));
      if (elect_one()) { l2_prefetch(p.cre + (160 * dg + 5 * m2) * DM, 6400); l2_prefetch(p.cim + (160 * dg + 5 * m2) * DM, 6400); }
      flag_poll(hf, tag);
      __syncwarp();
      if (lane == 0) { mbar_arrive(bars + 8 * B_H1); TS(22); }
      mbar_wait(bars + 8 * (B_CVDONE + 4));
      flag_poll(&g_gflag[(dg * 32 + lane) * 8], tag);
      __syncwarp();
      fence_async_global();
      if (lane == 0) TS(29);
      if (elect_one()) {
        mbar_expect_tx(bars + 8 * B_GFULL, 20480);
        tma5(sb + G_OFF, &p.mG, 64 * m2, 0, 0, 0, 10 * dg, bars + 8 * B_GFULL);
      }
      mbar_wait(bars + 8 * (B_G1DONE + 19));
      flag_poll(hf + NT1 * 256, tag);
      __syncwarp();
      if (lane == 0) { mbar_arrive(bars + 8 * (B_H1 + 1)); TS(24); }
    }
  } else {
    const int w = wid & 3;
    if (wg == 2 && !(role >> 16)) { mbar_wait(bars + 8 * (B_G1FULL + 11)); stat_table(role & 15, lds32(sb + EP_OFF + 20), 1, w); }
#pragma unroll 1
    for (int l = 0; l < 2; l++) {
      if (wg < 2) {
        float acc[80];
#pragma unroll
        for (int i = 0; i < 80; i++) acc[i] = 0.f;
        ROLE(role)
        const int tid = tid_opaque(), r = (tid & 31) >> 2, q = tid & 3;
        const int ch = 128 * GP + 64 * wg + 32 * side + 8 * w + r;
        const uint32_t ca = sb + CTAB_OFF + (32 * wg + 8 * w + r) * 24;
        float2 lam = make_float2(0.f, 0.f), p8 = lam, p16 = lam, pL = lam, p2L = lam;
        fence_regs(acc);
        {
          uint32_t alo = desc_lo(sb, 16) + wg * 512, blo = l == 0 ? desc_lo(sb + G1_XOFF, 16) : desc_lo(sb + G1_XOFF, 128);
          const uint32_t bhi = l == 0 ? desc_hi(1024, 1) : desc_hi(1024, 0), xstep = l == 0 ? 2 : 16;
          const uint32_t aend = desc_lo(sb, 16) + (S1 + l) * (G1_STAGE >> 4);
          uint32_t fb = bars + 8 * (B_G1FULL + 10 * l);
          mbar_wait(fb);
          if (tid == 0) TS(1 + 8 * l);
#pragma unroll 1
          for (int k = 0; k < 10; k++) {
            uint32_t ok; const uint32_t nb = k < 9 ? fb + 8 : fb;
            wgmma_fence();
#pragma unroll
            for (int kk = 0; kk < 4; kk++) {
              wgmma_n160<0>(acc, alo + kk * 2, desc_hi(1024, 1), blo + kk * xstep, bhi);
              if (kk == 0) ok = mbar_test(nb);
            }
            wgmma_commit();
            alo += G1_STAGE >> 4; blo += G1_STAGE >> 4;
            if (alo >= aend) { alo -= (S1 + l) * (G1_STAGE >> 4); blo -= (S1 + l) * (G1_STAGE >> 4); }
            wgmma_wait<1>();
            if (k > 0 && (tid & 127) == 0) mbar_arrive(fb + 8 * (B_G1DONE - B_G1FULL - 1));
            if (!ok) mbar_wait(nb);
            if (k == PAUSE_K) {
              mbar_wait(bars + 8 * B_CTAB);
              lam = lds64f(ca);
              if (p.swap) lam.y = -lam.y;
              const float2 p2 = cmul(lam, lam), p4 = cmul(p2, p2);
              p8 = cmul(p4, p4); p16 = cmul(p8, p8);
              pL = cmul(p16, p16);
              if (!last) pL = cmul(pL, p8);
              p2L = cmul(pL, pL);
              if (has2) mbar_wait(bars + 8 * B_PREP);
            }
            fb += 8;
          }
        }
        mbar_wait(bars + 8 * (B_STAB + l));
        const float2 sB = lds64f(ca + 16);
        const unsigned tag = lds32(sb + EP_OFF + 20);
        wgmma_wait<0>();
        fence_regs(acc);
        if ((tid & 127) == 0) { mbar_arrive(bars + 8 * (B_G1DONE + 10 * l + 9)); if (wg == 0) TS(2 + 8 * l); }
        float2 ec[3];
#pragma unroll
        for (int jj = 0; jj < 8; jj++)
#pragma unroll
          for (int y = 0; y < 3; y++) {
            if (y == 2 && (jj & 1)) continue;
            const int j = y == 2 ? 16 + (jj >> 1) : 8 * y + jj;
            const float4 st = lds128f(sb + STAB_OFF + (8 * j + 2 * q) * 8);
            acc[4 * j + 0] = fmaf(acc[4 * j + 0], st.x, st.y * sB.x);
            acc[4 * j + 2] = fmaf(acc[4 * j + 2], st.x, st.y * sB.y);
            acc[4 * j + 1] = fmaf(acc[4 * j + 1], st.z, st.w * sB.x);
            acc[4 * j + 3] = fmaf(acc[4 * j + 3], st.z, st.w * sB.y);
            ec[y] = jj == 0 ? make_float2(acc[4 * j + 0], acc[4 * j + 2]) : cfma(lam, ec[y], make_float2(acc[4 * j + 0], acc[4 * j + 2]));
            ec[y] = cfma(lam, ec[y], make_float2(acc[4 * j + 1], acc[4 * j + 3]));
          }
        float2 e = cfma(p16, ec[0], ec[1]);
        if (!last) e = cfma(p8, e, ec[2]);
        {
          float2 v = make_float2(__shfl_up_sync(0xffffffffu, e.x, 1, 4), __shfl_up_sync(0xffffffffu, e.y, 1, 4));
          if (q >= 1) e = cfma(pL, v, e);
          v = make_float2(__shfl_up_sync(0xffffffffu, e.x, 2, 4), __shfl_up_sync(0xffffffffu, e.y, 2, 4));
          if (q >= 2) e = cfma(p2L, v, e);
        }
        if (!last && (q == 3 || (q == 2 && l == 0))) rec_st(&g_E[((q == 3 ? l : 1) * NT1 + T1) * DM + ch], e.x, e.y, q == 3 ? tag : tag - 1);
        if (tid == 0) TS(3 + 8 * l);
        float2 ex = make_float2(__shfl_up_sync(0xffffffffu, e.x, 1, 4), __shfl_up_sync(0xffffffffu, e.y, 1, 4));
        if (q == 0) ex = make_float2(0.f, 0.f);
        const float2 coef = lds64f(ca + 8), lamc = make_float2(lam.x, p.swap ? lam.y : -lam.y);
        float m00 = coef.x, m01 = -coef.y, m10 = -coef.y, m11 = -coef.x;
        if (p.swap) { m00 = -coef.y; m01 = coef.x; m10 = -coef.x; m11 = -coef.y; }
        float2 pLq, p160q, p640;
        {
          const float2 p80 = last ? cmul(p2L, p16) : p2L, p160 = cmul(p80, p80), p320 = cmul(p160, p160), one = make_float2(1.f, 0.f);
          p640 = cmul(p320, p320);
          pLq = cmul((q & 1) ? pL : one, (q & 2) ? p2L : one);
          p160q = cmul((q & 1) ? p160 : one, (q & 2) ? p320 : one);
        }
        float2 c, ev[3];
        unsigned tg[3];
        const uint4* ep = &g_E[(l * NT1 + T1 - 1 - q) * DM + ch];
#pragma unroll
        for (int j = 0; j < 20; j++) {
          if (j == CPOLL) {
#pragma unroll
            for (int i = 0; i < 3; i++) {
              ev[i] = make_float2(0.f, 0.f); tg[i] = tag;
              if (T1 - 1 - q - 4 * i >= 0) tg[i] = rec_ld(ep - 4 * i * DM, ev[i].x, ev[i].y);
            }
          }
#pragma unroll
          for (int x = 0; x < 2; x++) {
            const float b0 = acc[4 * j + x], b1 = acc[4 * j + 2 + x];
            acc[4 * j + x] = fmaf(b0, m00, b1 * m01);
            acc[4 * j + 2 + x] = fmaf(b0, m10, b1 * m11);
          }
          if (j == CPOLL - 1 || j == 19) asm volatile("" : "+f"(acc[4 * j]), "+f"(acc[4 * j + 1]), "+f"(acc[4 * j + 2]), "+f"(acc[4 * j + 3])::"memory");
        }
        {
          uint32_t it = 0;
          while (__any_sync(0xffffffffu, tg[0] != tag || tg[1] != tag || tg[2] != tag)) {
#pragma unroll
            for (int i = 0; i < 3; i++)
              if (tg[i] != tag) tg[i] = rec_ld(ep - 4 * i * DM, ev[i].x, ev[i].y);
            trap_if(++it > SPIN_LIMIT);
          }
          c = cfma(p640, cfma(p640, ev[2], ev[1]), ev[0]);
          c = cmul(c, p160q);
          c.x += __shfl_xor_sync(0xffffffffu, c.x, 1); c.y += __shfl_xor_sync(0xffffffffu, c.y, 1);
          c.x += __shfl_xor_sync(0xffffffffu, c.x, 2); c.y += __shfl_xor_sync(0xffffffffu, c.y, 2);
        }
        if (tid == 0) TS(4 + 8 * l);
        if (tid == 128) mbar_arrive(bars + 8 * (B_GO + 2 * l));
        c = cfma(pLq, c, ex);
        float2 hh = make_float2(fmaf(c.x, m00, c.y * m01), fmaf(c.x, m10, c.y * m11));
        uint8_t* hb = g_h + (size_t)l * (32 * 20 * 8192) + (10 * wg + 2 * GP) * 8192 + (4 * side + w) * 1024 + (tid_opaque() & 31) * 4;
#pragma unroll
        for (int j4 = 0; j4 < 5; j4++) {
          const int ng = 20 * T1 + 4 * j4;
          uint8_t* hp = hb + (size_t)(ng >> 3) * 163840 + (ng & 7) * 128;
#pragma unroll
          for (int jj = 0; jj < 4; jj++) {
            const int j = 4 * j4 + jj;
            const float2 h0 = cfma(lamc, hh, make_float2(acc[4 * j + 0], acc[4 * j + 2]));
            hh = cfma(lamc, h0, make_float2(acc[4 * j + 1], acc[4 * j + 3]));
            if (j4 < 4 || !last) {
              *(uint32_t*)(hp + jj * 128) = pack_bf16(h0.x, hh.x);
              *(uint32_t*)(hp + jj * 128 + 8192) = pack_bf16(h0.y, hh.y);
            }
          }
        }
        mbar_arrive(bars + 8 * (B_HST + 2 * l + wg));
        if (tid == 0) TS(5 + 8 * l);
      }
      if (l == 0) {
        ROLE(role)
        if (has2) {
          CvCtx cc;
          cv_setup(cc);
          mbar_wait(bars + 8 * (B_G1DONE + 9));
#pragma unroll 1
          for (int c = wg == 2 ? 0 : 2 + wg; c < (wg == 2 ? 2 : 5); c += wg == 2 ? 1 : 2) conv_channel(c, cc);
          if ((tid & 127) == 0) TS(wg == 2 ? 32 : 7 + wg);
        }
      }
      if (wg == 2) break;
    }
    if (wg == 2 && (role >> 16)) {
      float acc[80];
      float off[2] = {0.f, 0.f};
      const unsigned tag = lds32(sb + EP_OFF + 20);
      x0_load(acc);
      mbar_arrive(bars + 8 * B_XFREE);
#pragma unroll 1
      for (int l = 0; l < 2; l++) {
        float mean[2], rstd[2];
        {
          ROLE(role)
          const int lane = tid_opaque() & 31;
          stats_get(2 * l, 64 * m2 + 16 * w + (lane >> 2), tag, mean, rstd);
          off[0] += mean[0]; off[1] += mean[1];
          mbar_wait(bars + 8 * (l == 0 ? B_CTAB : B_HST + 3));
#pragma unroll
          for (int J = 0; J < 10; J++) {
            const float2 dw = lds64f(sb + DTAB_OFF + 2 * (16 * J + 4 * (lane & 3)));
#pragma unroll
            for (int x = 0; x < 8; x++) {
              const int h = (x >> 1) & 1;
              const uint32_t gwd = __float_as_uint(x < 4 ? dw.x : dw.y);
              const float t = fmaf(rstd[h], (x & 1) ? bf_hi(gwd) : bf_lo(gwd), 1.f);
              acc[8 * J + x] = fmaf(acc[8 * J + x], t, -mean[h] * t);
            }
          }
        }
        {
          const uint32_t aend = desc_lo(sb + SX2 * G2_XB, 1024) + l * (G2_XB >> 3), bend = desc_lo(sb + G2_WOFF + 6 * G2_WB, 16) + l * (G2_WB >> 4);
          uint32_t alo = desc_lo(sb, 1024), blo = desc_lo(sb + G2_WOFF, 16);
          uint32_t fb = bars + 8 * (B_G2FULL + 20 * l);
          fence_regs(acc);
          mbar_wait(fb);
          if (tid == 256) TS(33 + 6 * l);
#pragma unroll 1
          for (int k = 0; k < 20; k++) {
            if (l == 1 && (k & 3) == 3 && tid == 256) TS(56 + (k >> 2));
            uint32_t ok; const uint32_t nb = k < 19 ? fb + 8 : fb;
            wgmma_fence();
#pragma unroll
            for (int kk = 0; kk < 4; kk++) {
              wgmma_n160<1>(acc, alo + kk * 128, desc_hi(128, 0), blo + kk * 2, desc_hi(1024, 1));
              if (kk == 0) ok = mbar_test(nb);
            }
            wgmma_commit();
            alo += G2_XB >> 4; if (alo == aend) alo = desc_lo(sb, 1024);
            blo += G2_WB >> 4; if (blo == bend) blo = desc_lo(sb + G2_WOFF, 16);
            wgmma_wait<1>();
            if (k > 0 && tid == 256) mbar_arrive(fb + 8 * (B_G2DONE - B_G2FULL - 1));
            if (!ok) mbar_wait(nb);
            fb += 8;
          }
          wgmma_wait<0>();
          fence_regs(acc);
          if (tid == 256) TS(34 + 6 * l);
          if (tid == 256) mbar_arrive(bars + 8 * (B_G2DONE + 20 * l + 19));
        }
        ROLE(role)
        const int tq = tid_opaque() & 31, n0 = 64 * m2 + 16 * w + (tq >> 2);
        stats_publish<false>(2 * l + 1, n0, dg, tag, acc);
        uint32_t gf[10][4];
        mbar_wait(bars + 8 * B_GFULL);
        const uint32_t ga = sb + G_OFF + (8 * (tq >> 4) + (tq & 7)) * 128 + (((2 * w + ((tq >> 3) & 1)) ^ ((2 * m2) & 6) ^ (tq & 7)) << 4);
#pragma unroll
        for (int J = 0; J < 2; J++) ldsm4t(gf[J], ga + J * 2048);
        if (tid == 256) TS(35 + 6 * l);
        uint8_t* dst[2][2];
#pragma unroll
        for (int h = 0; h < 2; h++) {
          if (l == 0) {
            const int ng = 8 * m2 + 2 * w + h, T = ng / 20;
            uint8_t* ub = g_u + (T * 204800 + (ng - 20 * T) * 1024 + (tq & 2) * 64 + (tq & 28) * 4 + (tq & 1) * 8 + (5 * dg >> 1) * 20480);
            dst[h][1] = ub + ((dg & 1) ? 20480 - 512 : 0);
            dst[h][0] = ub + (dg & 1) * 512;
          } else {
            dst[h][0] = dst[h][1] = (uint8_t*)(p.out + (n_to_t(n0 + 8 * h) * DM + 160 * dg + 4 * (tq & 3)));
          }
        }
        stats_get(2 * l + 1, n0, tag, mean, rstd);
        if (tid == 256) { TS(36 + 6 * l); if (l == 0) mbar_arrive(bars + 8 * (B_GO + 1)); }
        off[0] += mean[0]; off[1] += mean[1];
        const float ov[2] = {l ? off[0] : 0.f, l ? off[1] : 0.f};
#pragma unroll
        for (int J = 0; J < 10; J++) {
          if (J + 2 < 10) ldsm4t(gf[J + 2 < 10 ? J + 2 : 0], ga + (J + 2) * 2048);
#pragma unroll
          for (int x = 0; x < 8; x++) {
            const int h = (x >> 1) & 1;
            const uint32_t gwd = gf[J][x >> 1];
            const float t = fmaf(rstd[h], (x & 1) ? bf_hi(gwd) : bf_lo(gwd), 1.f);
            acc[8 * J + x] = fmaf(acc[8 * J + x], t, fmaf(-mean[h], t, ov[h]));
          }
#pragma unroll
          for (int h = 0; h < 2; h++) {
            if (l == 0)
              *(uint2*)(dst[h][(J >> 1) & 1] + (J >> 2) * 20480 + (J & 3) * 256) =
                  make_uint2(pack_bf16(acc[8 * J + 2 * h], acc[8 * J + 2 * h + 1]), pack_bf16(acc[8 * J + 4 + 2 * h], acc[8 * J + 5 + 2 * h]));
            else
              *(float4*)(dst[h][0] + 64 * J) = make_float4(acc[8 * J + 2 * h], acc[8 * J + 2 * h + 1], acc[8 * J + 4 + 2 * h], acc[8 * J + 5 + 2 * h]);
          }
          __syncwarp();
        }
        if (l == 0) {
          bar_sync(3, 128);
          if (tid == 256) { TS(37); st_rel(&g_uflag[(4 * m2 + dg) * 8], tag); TS(38); }
          stats_publish<false>(2, n0, dg, tag, acc);
          mbar_wait(bars + 8 * (B_G1FULL + 11));
          stat_table(T1, tag, 1, w);
          if (tid == 256) TS(27);
        } else {
          if (tid == 256) {
            TS(43);
            if (m2 == 31 && dg == 3) asm volatile("st.relaxed.gpu.global.u32 [%0], %1;" ::"l"(g_epoch), "r"(tag + 1) : "memory");
          }
        }
      }
    }
  }
}

typedef CUresult (*EncFn)(CUtensorMap*, CUtensorMapDataType, cuuint32_t, void*, const cuuint64_t*, const cuuint64_t*,
                          const cuuint32_t*, const cuuint32_t*, CUtensorMapInterleave, CUtensorMapSwizzle,
                          CUtensorMapL2promotion, CUtensorMapFloatOOBfill);

void encode(EncFn fn, CUtensorMap* m, const void* ptr, int rank, const cuuint64_t* dims, const cuuint64_t* strides, const cuuint32_t* box,
            CUtensorMapSwizzle swz = CU_TENSOR_MAP_SWIZZLE_128B) {
  cuuint32_t es[5] = {1, 1, 1, 1, 1};
  fn(m, CU_TENSOR_MAP_DATA_TYPE_BFLOAT16, rank, (void*)ptr, dims, strides, box, es, CU_TENSOR_MAP_INTERLEAVE_NONE,
     swz, swz == CU_TENSOR_MAP_SWIZZLE_128B ? CU_TENSOR_MAP_L2_PROMOTION_L2_128B : CU_TENSOR_MAP_L2_PROMOTION_L2_64B, CU_TENSOR_MAP_FLOAT_OOB_FILL_NONE);
}

}

extern "C" void kernel_launch(void* const* d_in, const int* in_sizes, int n_in, void* d_out, int out_size) {
  (void)in_sizes; (void)n_in; (void)out_size;
  Params p;
  typedef const __nv_bfloat16* BP;
  p.x = (BP)d_in[0]; p.lre = (BP)d_in[1]; p.lim = (BP)d_in[2]; p.bre = (BP)d_in[3]; p.bim = (BP)d_in[4];
  p.cre = (BP)d_in[5]; p.cim = (BP)d_in[6]; p.logdt = (BP)d_in[7]; p.dskip = (BP)d_in[8];
  p.k = (BP)d_in[10]; p.v = (BP)d_in[11]; p.shiftk = (BP)d_in[12]; p.ssmk = (BP)d_in[13]; p.ssmD = (BP)d_in[14];
  p.out = (float*)d_out;
  for (int sm = 0; sm < 132; sm++) {
    const int tpc = sm >> 1, side = sm & 1;
    int gpc, gi;
    if (tpc < 32) { gpc = tpc & 7; gi = tpc >> 3; }
    else if (tpc < 60) { gpc = 1 + (tpc - 32) % 7; gi = 4 + (tpc - 32) / 7; }
    else if (tpc < 62) { gpc = tpc - 54; gi = 8; }
    else { gpc = 0; gi = tpc - 58; }
    const int pos = 8 * gpc + gi + (gpc == 7 ? 1 : 0);
    int T1, GP;
    if (pos < 52) { const int hh = pos / 26, x = pos - 26 * hh; T1 = x >> 1; GP = 2 * hh + (x & 1); }
    else { T1 = pos - 52; GP = 4; }
    const int m2 = 8 * (gpc >> 1) + gi, dg = 2 * (gpc & 1) + side;
    p.role[sm] = pos == 65 ? -1 : (T1 | (GP << 4) | (side << 7) | (m2 << 8) | (dg << 14) | ((gi < 8) << 16));
  }
  void* fnp = nullptr;
  cudaDriverEntryPointQueryResult qr;
  cudaGetDriverEntryPoint("cuTensorMapEncodeTiled", &fnp, cudaEnableDefault, &qr);
  EncFn fn = (EncFn)fnp;
  void* gG = nullptr;
  cudaGetSymbolAddress(&gG, g_G);
  const cuuint64_t RB = DM * 2;
  {
    p.swap = p.bim < p.bre;
    const char* lo = (const char*)(p.swap ? p.bim : p.bre); const char* hi = (const char*)(p.swap ? p.bre : p.bim);
    cuuint64_t dims[5] = {640, 8, 2, 8, 10}, st[4] = {RB, (cuuint64_t)(hi - lo), 8 * RB, 64 * RB}; cuuint32_t box[5] = {64, 8, 2, 4, 2};
    encode(fn, &p.mB, lo, 5, dims, st, box);
  }
  {
    cuuint64_t dims[5] = {640, 2, 4, 2, 40}, st[4] = {RB, 4 * RB, 2 * RB, 16 * RB}; cuuint32_t box[5] = {64, 2, 4, 2, 10};
    encode(fn, &p.mCre, p.cre, 5, dims, st, box); encode(fn, &p.mCim, p.cim, 5, dims, st, box);
    cuuint64_t dimg[5] = {2048, 2, 4, 2, 40}, stg[4] = {4096, 4 * 4096, 2 * 4096, 16 * 4096};
    encode(fn, &p.mG, gG, 5, dimg, stg, box);
  }
  {
    cuuint64_t dims[4] = {640, 2, 4, 900}, st[3] = {RB, 40 * RB, 2 * RB}; cuuint32_t box[4] = {64, 2, 4, 20};
    encode(fn, &p.mX, p.x, 4, dims, st, box);
    cuuint64_t diml[4] = {640, 2, 4, 16}, stl[3] = {RB, 32 * RB, 2 * RB};
    encode(fn, &p.mXl, p.x + (size_t)1920 * DM, 4, diml, stl, box);
    cuuint32_t boxt[4] = {160, 2, 4, 4};
    encode(fn, &p.mXt, p.x, 4, dims, st, boxt, CU_TENSOR_MAP_SWIZZLE_NONE);
    encode(fn, &p.mXtl, p.x + (size_t)1920 * DM, 4, diml, stl, boxt, CU_TENSOR_MAP_SWIZZLE_NONE);
    cuuint64_t dk[3] = {640, 2000, 4}, sk[2] = {RB, 16 * RB}; cuuint32_t bk[3] = {32, 19, 4}, bv[3] = {32, 17, 4};
    encode(fn, &p.mK, p.k, 3, dk, sk, bk, CU_TENSOR_MAP_SWIZZLE_NONE);
    encode(fn, &p.mV, p.v, 3, dk, sk, bv, CU_TENSOR_MAP_SWIZZLE_NONE);
  }
  cudaFuncSetAttribute(fused_kernel, cudaFuncAttributeMaxDynamicSharedMemorySize, SMEM_BYTES);
  cudaLaunchConfig_t cfg = {};
  cfg.gridDim = dim3(132); cfg.blockDim = dim3(512); cfg.dynamicSmemBytes = SMEM_BYTES; cfg.stream = cudaStreamPerThread;
  cudaLaunchKernelEx(&cfg, fused_kernel, p);
}
```

```cpp
#include <cuda_runtime.h>
#include <cuda.h>
#include <cuda_bf16.h>
#include <stdint.h>

namespace {

constexpr int SEQ = 2048, DM = 640;
constexpr int NT1 = 13;
#define EXP 0
#define WPF1 1
#define WPF2 2
#define CPOLL 10
#define KV0 5
#define TAP0 2
#define PROM_A 2
#define PROM_B 2
#define XFIRST 0
#define TAPLATE 1
#define PAUSE_K 3
constexpr uint32_t SPIN_LIMIT = 1u << 22;

__device__ __align__(1024) uint8_t g_h[2 * 32 * 20 * 8192];
__device__ __align__(1024) uint8_t g_u[NT1 * 10 * 20480];
__device__ __align__(1024) uint8_t g_kv[DM * 4096];
__device__ __align__(1024) uint8_t g_G[DM * 4096];
__device__ __align__(128) uint4 g_E[2 * NT1 * DM];
__device__ __align__(128) uint4 g_stats[4 * 4 * SEQ];
__device__ __align__(128) uint4 g_sB[DM * 2];
__device__ __align__(128) unsigned g_hflag[2 * NT1 * 2 * 16 * 8];
__device__ __align__(128) unsigned g_uflag[32 * 4 * 8];
__device__ __align__(128) unsigned g_kvflag[4 * 32 * 8];
__device__ __align__(128) unsigned g_gflag[4 * 32 * 8];
__device__ __align__(128) unsigned g_epoch[32] = {1};
#define TS(i) do {} while (0)

struct Params {
  CUtensorMap mB, mCre, mCim, mX, mXl, mG, mK, mV, mXt, mXtl;
  const __nv_bfloat16 *x, *lre, *lim, *bre, *bim, *cre, *cim, *logdt, *dskip, *k, *v, *shiftk, *ssmk, *ssmD;
  float* out;
  int swap;
  int role[132];
};

constexpr uint32_t sb = 1024;
constexpr uint32_t G1_STAGE = 36864, G1_XOFF = 16384;
constexpr int S1 = 4;
constexpr uint32_t XT_OFF = 159744, KS_OFF = 180224, KV_PIECE = 9216;
constexpr uint32_t G2_XB = 8192, G2_WB = 20480, G2_WOFF = 57344, G_OFF = 200704;
constexpr int SX2 = 5;
constexpr uint32_t CV_OFF = KS_OFF, CV_K = 128, CV_PL = 2240, CV_U = CV_K + 4096, CV_B = KV_PIECE;
constexpr uint32_t MISC = 226304;
constexpr uint32_t BAR_OFF = MISC;
constexpr int B_G1FULL = 0, B_G1DONE = 20, B_G2FULL = 40, B_CVFULL = 80  ,
              B_G2DONE = 85, B_GFULL = 125, B_EP = 126, B_H1 = 127  , B_TAPS = 129  ,
              B_GO = 139  , B_PD = 142  , B_PUB = 147,
              B_CVDONE = 148  , B_STAB = 153  , B_XFREE = 155, B_HST = 156  ,
              B_CTAB = 160, B_PREP = 161, B_XT = 162, B_KV = 163  ;
constexpr uint32_t bars = sb + BAR_OFF;
constexpr uint32_t STAB_OFF = MISC + 1344;
constexpr uint32_t CTAB_OFF = STAB_OFF + 1280;
constexpr uint32_t DTAB_OFF = CTAB_OFF + 1536;
constexpr uint32_t EP_OFF = DTAB_OFF + 320;
constexpr uint32_t TAP_OFF = 147456;
constexpr uint32_t SMEM_BYTES = 232448;
static_assert(EP_OFF + 32 <= SMEM_BYTES, "smem");

__device__ __forceinline__ void trap_if(bool c) { asm volatile("{\n.reg .pred p;\nsetp.ne.u32 p, %0, 0;\n@p trap;\n}\n" ::"r"((uint32_t)c)); }
__device__ __forceinline__ uint32_t smem_u32(const void* p) { return (uint32_t)__cvta_generic_to_shared(p); }
__device__ __forceinline__ void mbar_init(uint32_t bar, int cnt) { asm volatile("mbarrier.init.shared::cta.b64 [%0], %1;" ::"r"(bar), "r"(cnt) : "memory"); }
__device__ __forceinline__ void mbar_expect_tx(uint32_t bar, int bytes) { asm volatile("mbarrier.arrive.expect_tx.shared::cta.b64 _, [%0], %1;" ::"r"(bar), "r"(bytes) : "memory"); }
__device__ __forceinline__ void mbar_arrive(uint32_t bar) { asm volatile("mbarrier.arrive.shared::cta.b64 _, [%0];" ::"r"(bar) : "memory"); }
__device__ __forceinline__ void mbar_wait(uint32_t bar) {
  asm volatile(
      "{\n.reg .pred p;\n.reg .u32 c;\nmov.u32 c, 0;\n"
      "W_%=:\nmbarrier.try_wait.parity.shared::cta.b64 p, [%0], 0;\n@p bra D_%=;\n"
      "add.u32 c, c, 1;\nsetp.lt.u32 p, c, %1;\n@p bra W_%=;\ntrap;\nD_%=:\n}\n" ::"r"(bar), "n"(SPIN_LIMIT) : "memory");
}
__device__ __forceinline__ uint32_t mbar_test(uint32_t bar) {
  uint32_t ok;
  asm volatile("{\n.reg .pred p;\nmbarrier.test_wait.parity.shared::cta.b64 p, [%1], 0;\nselp.u32 %0, 1, 0, p;\n}\n" : "=r"(ok) : "r"(bar) : "memory");
  return ok;
}
__device__ __forceinline__ void tma3(uint32_t dst, const CUtensorMap* m, int c0, int c1, int c2, uint32_t bar) {
  asm volatile("cp.async.bulk.tensor.3d.shared::cluster.global.mbarrier::complete_tx::bytes [%0], [%1, {%3,%4,%5}], [%2];"
               ::"r"(dst), "l"(m), "r"(bar), "r"(c0), "r"(c1), "r"(c2) : "memory");
}
__device__ __forceinline__ void tma4(uint32_t dst, const CUtensorMap* m, int c0, int c1, int c2, int c3, uint32_t bar) {
  asm volatile("cp.async.bulk.tensor.4d.shared::cluster.global.mbarrier::complete_tx::bytes [%0], [%1, {%3,%4,%5,%6}], [%2];"
               ::"r"(dst), "l"(m), "r"(bar), "r"(c0), "r"(c1), "r"(c2), "r"(c3) : "memory");
}
__device__ __forceinline__ void tma5(uint32_t dst, const CUtensorMap* m, int c0, int c1, int c2, int c3, int c4, uint32_t bar) {
  asm volatile("cp.async.bulk.tensor.5d.shared::cluster.global.mbarrier::complete_tx::bytes [%0], [%1, {%3,%4,%5,%6,%7}], [%2];"
               ::"r"(dst), "l"(m), "r"(bar), "r"(c0), "r"(c1), "r"(c2), "r"(c3), "r"(c4) : "memory");
}
__device__ __forceinline__ void bulk_g2s(uint32_t dst, const void* src, int bytes, uint32_t bar) {
  asm volatile("cp.async.bulk.shared::cluster.global.mbarrier::complete_tx::bytes [%0], [%1], %2, [%3];"
               ::"r"(dst), "l"(src), "r"(bytes), "r"(bar) : "memory");
}
__device__ __forceinline__ void bulk_s2g(void* dst, uint32_t src, int bytes) {
  asm volatile("cp.async.bulk.global.shared::cta.bulk_group [%0], [%1], %2;" ::"l"(dst), "r"(src), "r"(bytes) : "memory");
}
__device__ __forceinline__ void l2_prefetch(const void* src, int bytes) {
  asm volatile("cp.async.bulk.prefetch.L2.global [%0], %1;" ::"l"(src), "r"(bytes) : "memory");
}
__device__ __forceinline__ void wgmma_fence() { asm volatile("wgmma.fence.sync.aligned;" ::: "memory"); }
__device__ __forceinline__ void wgmma_commit() { asm volatile("wgmma.commit_group.sync.aligned;" ::: "memory"); }
template <int N> __device__ __forceinline__ void wgmma_wait() { asm volatile("wgmma.wait_group.sync.aligned %0;" ::"n"(N) : "memory"); }
__host__ __device__ constexpr uint32_t desc_lo(uint32_t addr, uint32_t lbo) { return ((addr & 0x3FFFF) >> 4) | ((lbo >> 4) << 16); }
__host__ __device__ constexpr uint32_t desc_hi(uint32_t sbo, uint32_t swz) { return (sbo >> 4) | (swz << 30); }
__device__ __forceinline__ void bar_sync(int id, int n) { asm volatile("bar.sync %0, %1;" ::"r"(id), "r"(n) : "memory"); }
__device__ __forceinline__ uint32_t lds32(uint32_t a) { uint32_t v; asm volatile("ld.shared.u32 %0, [%1];" : "=r"(v) : "r"(a) : "memory"); return v; }
__device__ __forceinline__ float2 lds64f(uint32_t a) { float2 v; asm volatile("ld.shared.v2.f32 {%0,%1}, [%2];" : "=f"(v.x), "=f"(v.y) : "r"(a) : "memory"); return v; }
__device__ __forceinline__ float4 lds128f(uint32_t a) { float4 v; asm volatile("ld.shared.v4.f32 {%0,%1,%2,%3}, [%4];" : "=f"(v.x), "=f"(v.y), "=f"(v.z), "=f"(v.w) : "r"(a) : "memory"); return v; }
__device__ __forceinline__ void ldsm4t(uint32_t (&r)[4], uint32_t a) {
  asm volatile("ldmatrix.sync.aligned.m8n8.x4.trans.shared.b16 {%0,%1,%2,%3}, [%4];" : "=r"(r[0]), "=r"(r[1]), "=r"(r[2]), "=r"(r[3]) : "r"(a) : "memory");
}
__device__ __forceinline__ uint4 ldv128(const void* a) { uint4 v; asm volatile("ld.global.nc.v4.u32 {%0,%1,%2,%3}, [%4];" : "=r"(v.x), "=r"(v.y), "=r"(v.z), "=r"(v.w) : "l"(a) : "memory"); return v; }
__device__ __forceinline__ uint2 ldv64(const void* a) { uint2 v; asm volatile("ld.global.nc.v2.u32 {%0,%1}, [%2];" : "=r"(v.x), "=r"(v.y) : "l"(a) : "memory"); return v; }
__device__ __forceinline__ uint32_t ldv16(const void* a) { uint32_t v; asm volatile("ld.global.nc.u16 %0, [%1];" : "=r"(v) : "l"(a) : "memory"); return v; }
__device__ __forceinline__ void sts128(uint32_t a, uint4 v) { asm volatile("st.shared.v4.u32 [%0], {%1,%2,%3,%4};" ::"r"(a), "r"(v.x), "r"(v.y), "r"(v.z), "r"(v.w) : "memory"); }
__device__ __forceinline__ void sts32(uint32_t a, uint32_t v) { asm volatile("st.shared.u32 [%0], %1;" ::"r"(a), "r"(v) : "memory"); }
__device__ __forceinline__ void sts64f(uint32_t a, float x, float y) { asm volatile("st.shared.v2.f32 [%0], {%1,%2};" ::"r"(a), "f"(x), "f"(y) : "memory"); }
__device__ __forceinline__ void st_rel(unsigned* p, unsigned v) { asm volatile("st.release.gpu.global.u32 [%0], %1;" ::"l"(p), "r"(v) : "memory"); }
__device__ __forceinline__ void fence_async_global() { asm volatile("fence.proxy.async.global;" ::: "memory"); }
__device__ __forceinline__ void fence_async_smem() { asm volatile("fence.proxy.async.shared::cta;" ::: "memory"); }
__device__ __forceinline__ void rec_st(uint4* p, float a, float b, unsigned tag) {
  asm volatile("{\n.reg .b128 t;\n.reg .b64 lo, hi;\nmov.b64 lo, {%1,%2};\nmov.b64 hi, {%3,%3};\nmov.b128 t, {lo,hi};\n"
               "st.relaxed.gpu.global.b128 [%0], t;\n}\n" ::"l"(p), "r"(__float_as_uint(a)), "r"(__float_as_uint(b)), "r"(tag) : "memory");
}
__device__ __forceinline__ unsigned rec_ld(const uint4* p, float& a, float& b) {
  unsigned x, y, t;
  asm volatile("{\n.reg .b128 t;\n.reg .b64 lo, hi;\n.reg .b32 u;\nld.relaxed.gpu.global.b128 t, [%3];\nmov.b128 {lo,hi}, t;\n"
               "mov.b64 {%0,%1}, lo;\nmov.b64 {%2,u}, hi;\n}\n" : "=r"(x), "=r"(y), "=r"(t) : "l"(p) : "memory");
  a = __uint_as_float(x); b = __uint_as_float(y);
  return t;
}
__device__ __forceinline__ void rec_poll(const uint4* p, unsigned tag, float& a, float& b) {
  uint32_t it = 0;
  while (!__all_sync(0xffffffffu, rec_ld(p, a, b) == tag)) { trap_if(++it > SPIN_LIMIT); }
}
__device__ __forceinline__ unsigned ld_rlx(const unsigned* p) { unsigned v; asm volatile("ld.relaxed.gpu.global.u32 %0, [%1];" : "=r"(v) : "l"(p) : "memory"); return v; }
__device__ __forceinline__ void flag_poll(const unsigned* p, unsigned target) {
  uint32_t it = 0;
  while (!__all_sync(0xffffffffu, (int)(ld_rlx(p) - target) >= 0)) { trap_if(++it > SPIN_LIMIT); }
  asm volatile("fence.acquire.gpu;" ::: "memory");
}
__device__ __forceinline__ uint32_t pack_bf16(float lo, float hi) {
  uint32_t r; asm("cvt.rn.bf16x2.f32 %0, %1, %2;" : "=r"(r) : "f"(hi), "f"(lo)); return r;
}
__device__ __forceinline__ float bf_lo(uint32_t w) { return __uint_as_float(w << 16); }
__device__ __forceinline__ float bf_hi(uint32_t w) { return __uint_as_float(w & 0xffff0000u); }
__device__ __forceinline__ uint32_t hmul2(uint32_t a, uint32_t b) {
  __nv_bfloat162 r = __hmul2_rn(*(__nv_bfloat162*)&a, *(__nv_bfloat162*)&b); return *(uint32_t*)&r;
}
__device__ __forceinline__ uint32_t hadd2(uint32_t a, uint32_t b) {
  __nv_bfloat162 r = __hadd2_rn(*(__nv_bfloat162*)&a, *(__nv_bfloat162*)&b); return *(uint32_t*)&r;
}
__device__ __forceinline__ float2 cmul(float2 a, float2 b) { return make_float2(a.x * b.x - a.y * b.y, a.x * b.y + a.y * b.x); }
__device__ __forceinline__ float2 cfma(float2 a, float2 b, float2 c) {
  return make_float2(fmaf(a.x, b.x, fmaf(-a.y, b.y, c.x)), fmaf(a.x, b.y, fmaf(a.y, b.x, c.y)));
}
template <int N> __device__ __forceinline__ void fence_regs(float (&a)[N]) {
#pragma unroll
  for (int i = 0; i < N; i++) asm volatile("" : "+f"(a[i])::"memory");
}
__device__ __forceinline__ bool elect_one() {
  uint32_t e; asm volatile("{\n.reg .pred P;\nelect.sync _|P, 0xffffffff;\nselp.u32 %0, 1, 0, P;\n}\n" : "=r"(e)); return e != 0;
}
__device__ __forceinline__ int tid_opaque() { int t; asm volatile("mov.u32 %0, %%tid.x;" : "=r"(t)); return t; }
struct Role { int T1, GP, side, m2, dg, cch0; bool last, has2; };
__device__ __forceinline__ Role unpack_role(int x) {
  Role r; r.T1 = x & 15; r.GP = (x >> 4) & 7; r.side = (x >> 7) & 1; r.m2 = (x >> 8) & 63; r.dg = (x >> 14) & 3;
  r.has2 = (x >> 16) & 1; r.last = r.T1 == NT1 - 1; r.cch0 = 160 * r.dg + r.m2; return r;
}
__device__ __forceinline__ Role fresh_role(int x) { asm volatile("" : "+r"(x)); return unpack_role(__shfl_sync(0xffffffffu, x, 0)); }
#define ROLE(x) const Role R_ = fresh_role(x); const int T1 = R_.T1, GP = R_.GP, side = R_.side, m2 = R_.m2, dg = R_.dg, cch0 = R_.cch0; \
  const bool last = R_.last, has2 = R_.has2; (void)T1; (void)GP; (void)side; (void)m2; (void)dg; (void)cch0; (void)last; (void)has2;
__device__ __forceinline__ int n_to_t(int n) {
  int T = n / 160, nl = n - T * 160;
  int L = (T == NT1 - 1) ? 32 : 40;
  return T * 160 + L * ((nl & 7) >> 1) + 2 * (nl >> 3) + (nl & 1);
}

template<int TA> __device__ __forceinline__ void wgmma_n160(float (&d)[80], uint32_t alo, uint32_t ahi, uint32_t blo, uint32_t bhi){
  asm volatile("{\n.reg .b64 da, db;\nmov.b64 da, {%80,%81};\nmov.b64 db, {%82,%83};\n"
    "wgmma.mma_async.sync.aligned.m64n160k16.f32.bf16.bf16 {%0, %1, %2, %3, %4, %5, %6, %7, %8, %9, %10, %11, %12, %13, %14, %15, %16, %17, %18, %19, %20, %21, %22, %23, %24, %25, %26, %27, %28, %29, %30, %31, %32, %33, %34, %35, %36, %37, %38, %39, %40, %41, %42, %43, %44, %45, %46, %47, %48, %49, %50, %51, %52, %53, %54, %55, %56, %57, %58, %59, %60, %61, %62, %63, %64, %65, %66, %67, %68, %69, %70, %71, %72, %73, %74, %75, %76, %77, %78, %79}, da, db, 1, 1, 1, %84, 0;\n}\n"
    : "+f"(d[0]), "+f"(d[1]), "+f"(d[2]), "+f"(d[3]), "+f"(d[4]), "+f"(d[5]), "+f"(d[6]), "+f"(d[7]), "+f"(d[8]), "+f"(d[9]), "+f"(d[10]), "+f"(d[11]), "+f"(d[12]), "+f"(d[13]), "+f"(d[14]), "+f"(d[15]), "+f"(d[16]), "+f"(d[17]), "+f"(d[18]), "+f"(d[19]), "+f"(d[20]), "+f"(d[21]), "+f"(d[22]), "+f"(d[23]), "+f"(d[24]), "+f"(d[25]), "+f"(d[26]), "+f"(d[27]), "+f"(d[28]), "+f"(d[29]), "+f"(d[30]), "+f"(d[31]), "+f"(d[32]), "+f"(d[33]), "+f"(d[34]), "+f"(d[35]), "+f"(d[36]), "+f"(d[37]), "+f"(d[38]), "+f"(d[39]), "+f"(d[40]), "+f"(d[41]), "+f"(d[42]), "+f"(d[43]), "+f"(d[44]), "+f"(d[45]), "+f"(d[46]), "+f"(d[47]), "+f"(d[48]), "+f"(d[49]), "+f"(d[50]), "+f"(d[51]), "+f"(d[52]), "+f"(d[53]), "+f"(d[54]), "+f"(d[55]), "+f"(d[56]), "+f"(d[57]), "+f"(d[58]), "+f"(d[59]), "+f"(d[60]), "+f"(d[61]), "+f"(d[62]), "+f"(d[63]), "+f"(d[64]), "+f"(d[65]), "+f"(d[66]), "+f"(d[67]), "+f"(d[68]), "+f"(d[69]), "+f"(d[70]), "+f"(d[71]), "+f"(d[72]), "+f"(d[73]), "+f"(d[74]), "+f"(d[75]), "+f"(d[76]), "+f"(d[77]), "+f"(d[78]), "+f"(d[79])
    : "r"(alo), "r"(ahi), "r"(blo), "r"(bhi), "n"(TA));
}
template<int N> __device__ __forceinline__ void wgmma_rs_hi(float (&d)[64], uint32_t a0, uint32_t a1, uint32_t a2, uint32_t a3, uint32_t blo);
template<> __device__ __forceinline__ void wgmma_rs_hi<16>(float (&d)[64], uint32_t a0, uint32_t a1, uint32_t a2, uint32_t a3, uint32_t blo){
  asm volatile("{\n.reg .b64 db;\nmov.b64 db, {%12,8};\nwgmma.mma_async.sync.aligned.m64n16k16.f32.bf16.bf16 {%0, %1, %2, %3, %4, %5, %6, %7}, {%8,%9,%10,%11}, db, 1, 1, 1, 0;\n}\n"
    : "+f"(d[56]), "+f"(d[57]), "+f"(d[58]), "+f"(d[59]), "+f"(d[60]), "+f"(d[61]), "+f"(d[62]), "+f"(d[63])
    : "r"(a0), "r"(a1), "r"(a2), "r"(a3), "r"(blo));
}
template<> __device__ __forceinline__ void wgmma_rs_hi<32>(float (&d)[64], uint32_t a0, uint32_t a1, uint32_t a2, uint32_t a3, uint32_t blo){
  asm volatile("{\n.reg .b64 db;\nmov.b64 db, {%20,8};\nwgmma.mma_async.sync.aligned.m64n32k16.f32.bf16.bf16 {%0, %1, %2, %3, %4, %5, %6, %7, %8, %9, %10, %11, %12, %13, %14, %15}, {%16,%17,%18,%19}, db, 1, 1, 1, 0;\n}\n"
    : "+f"(d[48]), "+f"(d[49]), "+f"(d[50]), "+f"(d[51]), "+f"(d[52]), "+f"(d[53]), "+f"(d[54]), "+f"(d[55]), "+f"(d[56]), "+f"(d[57]), "+f"(d[58]), "+f"(d[59]), "+f"(d[60]), "+f"(d[61]), "+f"(d[62]), "+f"(d[63])
    : "r"(a0), "r"(a1), "r"(a2), "r"(a3), "r"(blo));
}
template<> __device__ __forceinline__ void wgmma_rs_hi<48>(float (&d)[64], uint32_t a0, uint32_t a1, uint32_t a2, uint32_t a3, uint32_t blo){
  asm volatile("{\n.reg .b64 db;\nmov.b64 db, {%28,8};\nwgmma.mma_async.sync.aligned.m64n48k16.f32.bf16.bf16 {%0, %1, %2, %3, %4, %5, %6, %7, %8, %9, %10, %11, %12, %13, %14, %15, %16, %17, %18, %19, %20, %21, %22, %23}, {%24,%25,%26,%27}, db, 1, 1, 1, 0;\n}\n"
    : "+f"(d[40]), "+f"(d[41]), "+f"(d[42]), "+f"(d[43]), "+f"(d[44]), "+f"(d[45]), "+f"(d[46]), "+f"(d[47]), "+f"(d[48]), "+f"(d[49]), "+f"(d[50]), "+f"(d[51]), "+f"(d[52]), "+f"(d[53]), "+f"(d[54]), "+f"(d[55]), "+f"(d[56]), "+f"(d[57]), "+f"(d[58]), "+f"(d[59]), "+f"(d[60]), "+f"(d[61]), "+f"(d[62]), "+f"(d[63])
    : "r"(a0), "r"(a1), "r"(a2), "r"(a3), "r"(blo));
}
template<> __device__ __forceinline__ void wgmma_rs_hi<64>(float (&d)[64], uint32_t a0, uint32_t a1, uint32_t a2, uint32_t a3, uint32_t blo){
  asm volatile("{\n.reg .b64 db;\nmov.b64 db, {%36,8};\nwgmma.mma_async.sync.aligned.m64n64k16.f32.bf16.bf16 {%0, %1, %2, %3, %4, %5, %6, %7, %8, %9, %10, %11, %12, %13, %14, %15, %16, %17, %18, %19, %20, %21, %22, %23, %24, %25, %26, %27, %28, %29, %30, %31}, {%32,%33,%34,%35}, db, 1, 1, 1, 0;\n}\n"
    : "+f"(d[32]), "+f"(d[33]), "+f"(d[34]), "+f"(d[35]), "+f"(d[36]), "+f"(d[37]), "+f"(d[38]), "+f"(d[39]), "+f"(d[40]), "+f"(d[41]), "+f"(d[42]), "+f"(d[43]), "+f"(d[44]), "+f"(d[45]), "+f"(d[46]), "+f"(d[47]), "+f"(d[48]), "+f"(d[49]), "+f"(d[50]), "+f"(d[51]), "+f"(d[52]), "+f"(d[53]), "+f"(d[54]), "+f"(d[55]), "+f"(d[56]), "+f"(d[57]), "+f"(d[58]), "+f"(d[59]), "+f"(d[60]), "+f"(d[61]), "+f"(d[62]), "+f"(d[63])
    : "r"(a0), "r"(a1), "r"(a2), "r"(a3), "r"(blo));
}
template<> __device__ __forceinline__ void wgmma_rs_hi<80>(float (&d)[64], uint32_t a0, uint32_t a1, uint32_t a2, uint32_t a3, uint32_t blo){
  asm volatile("{\n.reg .b64 db;\nmov.b64 db, {%44,8};\nwgmma.mma_async.sync.aligned.m64n80k16.f32.bf16.bf16 {%0, %1, %2, %3, %4, %5, %6, %7, %8, %9, %10, %11, %12, %13, %14, %15, %16, %17, %18, %19, %20, %21, %22, %23, %24, %25, %26, %27, %28, %29, %30, %31, %32, %33, %34, %35, %36, %37, %38, %39}, {%40,%41,%42,%43}, db, 1, 1, 1, 0;\n}\n"
    : "+f"(d[24]), "+f"(d[25]), "+f"(d[26]), "+f"(d[27]), "+f"(d[28]), "+f"(d[29]), "+f"(d[30]), "+f"(d[31]), "+f"(d[32]), "+f"(d[33]), "+f"(d[34]), "+f"(d[35]), "+f"(d[36]), "+f"(d[37]), "+f"(d[38]), "+f"(d[39]), "+f"(d[40]), "+f"(d[41]), "+f"(d[42]), "+f"(d[43]), "+f"(d[44]), "+f"(d[45]), "+f"(d[46]), "+f"(d[47]), "+f"(d[48]), "+f"(d[49]), "+f"(d[50]), "+f"(d[51]), "+f"(d[52]), "+f"(d[53]), "+f"(d[54]), "+f"(d[55]), "+f"(d[56]), "+f"(d[57]), "+f"(d[58]), "+f"(d[59]), "+f"(d[60]), "+f"(d[61]), "+f"(d[62]), "+f"(d[63])
    : "r"(a0), "r"(a1), "r"(a2), "r"(a3), "r"(blo));
}
template<> __device__ __forceinline__ void wgmma_rs_hi<96>(float (&d)[64], uint32_t a0, uint32_t a1, uint32_t a2, uint32_t a3, uint32_t blo){
  asm volatile("{\n.reg .b64 db;\nmov.b64 db, {%52,8};\nwgmma.mma_async.sync.aligned.m64n96k16.f32.bf16.bf16 {%0, %1, %2, %3, %4, %5, %6, %7, %8, %9, %10, %11, %12, %13, %14, %15, %16, %17, %18, %19, %20, %21, %22, %23, %24, %25, %26, %27, %28, %29, %30, %31, %32, %33, %34, %35, %36, %37, %38, %39, %40, %41, %42, %43, %44, %45, %46, %47}, {%48,%49,%50,%51}, db, 1, 1, 1, 0;\n}\n"
    : "+f"(d[16]), "+f"(d[17]), "+f"(d[18]), "+f"(d[19]), "+f"(d[20]), "+f"(d[21]), "+f"(d[22]), "+f"(d[23]), "+f"(d[24]), "+f"(d[25]), "+f"(d[26]), "+f"(d[27]), "+f"(d[28]), "+f"(d[29]), "+f"(d[30]), "+f"(d[31]), "+f"(d[32]), "+f"(d[33]), "+f"(d[34]), "+f"(d[35]), "+f"(d[36]), "+f"(d[37]), "+f"(d[38]), "+f"(d[39]), "+f"(d[40]), "+f"(d[41]), "+f"(d[42]), "+f"(d[43]), "+f"(d[44]), "+f"(d[45]), "+f"(d[46]), "+f"(d[47]), "+f"(d[48]), "+f"(d[49]), "+f"(d[50]), "+f"(d[51]), "+f"(d[52]), "+f"(d[53]), "+f"(d[54]), "+f"(d[55]), "+f"(d[56]), "+f"(d[57]), "+f"(d[58]), "+f"(d[59]), "+f"(d[60]), "+f"(d[61]), "+f"(d[62]), "+f"(d[63])
    : "r"(a0), "r"(a1), "r"(a2), "r"(a3), "r"(blo));
}
template<> __device__ __forceinline__ void wgmma_rs_hi<112>(float (&d)[64], uint32_t a0, uint32_t a1, uint32_t a2, uint32_t a3, uint32_t blo){
  asm volatile("{\n.reg .b64 db;\nmov.b64 db, {%60,8};\nwgmma.mma_async.sync.aligned.m64n112k16.f32.bf16.bf16 {%0, %1, %2, %3, %4, %5, %6, %7, %8, %9, %10, %11, %12, %13, %14, %15, %16, %17, %18, %19, %20, %21, %22, %23, %24, %25, %26, %27, %28, %29, %30, %31, %32, %33, %34, %35, %36, %37, %38, %39, %40, %41, %42, %43, %44, %45, %46, %47, %48, %49, %50, %51, %52, %53, %54, %55}, {%56,%57,%58,%59}, db, 1, 1, 1, 0;\n}\n"
    : "+f"(d[8]), "+f"(d[9]), "+f"(d[10]), "+f"(d[11]), "+f"(d[12]), "+f"(d[13]), "+f"(d[14]), "+f"(d[15]), "+f"(d[16]), "+f"(d[17]), "+f"(d[18]), "+f"(d[19]), "+f"(d[20]), "+f"(d[21]), "+f"(d[22]), "+f"(d[23]), "+f"(d[24]), "+f"(d[25]), "+f"(d[26]), "+f"(d[27]), "+f"(d[28]), "+f"(d[29]), "+f"(d[30]), "+f"(d[31]), "+f"(d[32]), "+f"(d[33]), "+f"(d[34]), "+f"(d[35]), "+f"(d[36]), "+f"(d[37]), "+f"(d[38]), "+f"(d[39]), "+f"(d[40]), "+f"(d[41]), "+f"(d[42]), "+f"(d[43]), "+f"(d[44]), "+f"(d[45]), "+f"(d[46]), "+f"(d[47]), "+f"(d[48]), "+f"(d[49]), "+f"(d[50]), "+f"(d[51]), "+f"(d[52]), "+f"(d[53]), "+f"(d[54]), "+f"(d[55]), "+f"(d[56]), "+f"(d[57]), "+f"(d[58]), "+f"(d[59]), "+f"(d[60]), "+f"(d[61]), "+f"(d[62]), "+f"(d[63])
    : "r"(a0), "r"(a1), "r"(a2), "r"(a3), "r"(blo));
}
template<> __device__ __forceinline__ void wgmma_rs_hi<128>(float (&d)[64], uint32_t a0, uint32_t a1, uint32_t a2, uint32_t a3, uint32_t blo){
  asm volatile("{\n.reg .b64 db;\nmov.b64 db, {%68,8};\nwgmma.mma_async.sync.aligned.m64n128k16.f32.bf16.bf16 {%0, %1, %2, %3, %4, %5, %6, %7, %8, %9, %10, %11, %12, %13, %14, %15, %16, %17, %18, %19, %20, %21, %22, %23, %24, %25, %26, %27, %28, %29, %30, %31, %32, %33, %34, %35, %36, %37, %38, %39, %40, %41, %42, %43, %44, %45, %46, %47, %48, %49, %50, %51, %52, %53, %54, %55, %56, %57, %58, %59, %60, %61, %62, %63}, {%64,%65,%66,%67}, db, 1, 1, 1, 0;\n}\n"
    : "+f"(d[0]), "+f"(d[1]), "+f"(d[2]), "+f"(d[3]), "+f"(d[4]), "+f"(d[5]), "+f"(d[6]), "+f"(d[7]), "+f"(d[8]), "+f"(d[9]), "+f"(d[10]), "+f"(d[11]), "+f"(d[12]), "+f"(d[13]), "+f"(d[14]), "+f"(d[15]), "+f"(d[16]), "+f"(d[17]), "+f"(d[18]), "+f"(d[19]), "+f"(d[20]), "+f"(d[21]), "+f"(d[22]), "+f"(d[23]), "+f"(d[24]), "+f"(d[25]), "+f"(d[26]), "+f"(d[27]), "+f"(d[28]), "+f"(d[29]), "+f"(d[30]), "+f"(d[31]), "+f"(d[32]), "+f"(d[33]), "+f"(d[34]), "+f"(d[35]), "+f"(d[36]), "+f"(d[37]), "+f"(d[38]), "+f"(d[39]), "+f"(d[40]), "+f"(d[41]), "+f"(d[42]), "+f"(d[43]), "+f"(d[44]), "+f"(d[45]), "+f"(d[46]), "+f"(d[47]), "+f"(d[48]), "+f"(d[49]), "+f"(d[50]), "+f"(d[51]), "+f"(d[52]), "+f"(d[53]), "+f"(d[54]), "+f"(d[55]), "+f"(d[56]), "+f"(d[57]), "+f"(d[58]), "+f"(d[59]), "+f"(d[60]), "+f"(d[61]), "+f"(d[62]), "+f"(d[63])
    : "r"(a0), "r"(a1), "r"(a2), "r"(a3), "r"(blo));
}

__device__ __forceinline__ float shfl_sel(float a, float b, bool p, int src) {
  float r;
  asm volatile("{\n.reg .pred P;\n.reg .f32 t;\nsetp.ne.u32 P, %3, 0;\nselp.f32 t, %1, %2, P;\nshfl.sync.idx.b32 %0, t, %4, 0x1f, 0xffffffff;\n}\n"
               : "=f"(r) : "f"(a), "f"(b), "r"((uint32_t)p), "r"(src));
  return r;
}
struct CvCtx {
  uint32_t koff, zero, so[4];
  int srcA, srcB;
  bool wrapA, s3, kodd;
};
struct CvPipe { float Ep[2], keep[2], send[2]; };
template <int LO> __device__ __forceinline__ void cv_copy(float (&acc)[64]) {
#pragma unroll
  for (int i = LO; i < 64; i++) { float t; asm volatile("mov.b32 %0, %1;" : "=f"(t) : "f"(acc[i]) : "memory"); acc[i] = t; }
}
template <int G> __device__ __forceinline__ void cv_raw(uint32_t (&A)[4][4], uint32_t kaddr) {
#pragma unroll
  for (int i = 0; i < 4; i++) {
    const uint32_t a = kaddr + (4 * G + i) * 128;
    A[i][0] = lds32(a); A[i][1] = lds32(a + 4); A[i][3] = lds32(a + 8);
  }
}
__device__ __forceinline__ void cv_form(uint32_t (&A)[4][4], uint32_t sel) {
#pragma unroll
  for (int i = 0; i < 4; i++) {
    asm volatile("prmt.b32 %0, %0, %1, %2;" : "+r"(A[i][0]) : "r"(A[i][1]), "r"(sel));
    asm volatile("prmt.b32 %0, %1, %2, %3;" : "=r"(A[i][2]) : "r"(A[i][1]), "r"(A[i][3]), "r"(sel));
  }
}
#define CVV 2
template <int G> __device__ __forceinline__ void cv_step(float (&acc)[64], uint32_t (&A)[4][4], CvPipe& s, const CvCtx& c, uint32_t cb, uint32_t stg) {
  constexpr int JA = G - 1, JB = G - 2, NH = CVV == 1 ? 4 : (CVV == 3 ? 2 : 1);
  const uint32_t db0 = desc_lo(cb + CV_U + 192, CV_PL);
  uint32_t B[4][4];
  float ra[4], rb[2];
  if constexpr (G < 8) {
    wgmma_fence();
#pragma unroll
    for (int i = 0; i < NH; i++) wgmma_rs_hi<128 - 16 * (G & 7)>(acc, A[i][0], A[i][1], A[i][2], A[i][3], db0 - 4 * i);
    wgmma_commit();
    __syncwarp();
  }
  if constexpr (JA >= 0 && JA < 8) {
#pragma unroll
    for (int x = 0; x < 4; x++) {
      const int i = 8 * JA + 4 * (x >> 1) + 2 * (x & 1) + 1;
      ra[x] = shfl_sel(i >= 4 ? acc[i >= 4 ? i - 4 : 0] : 0.f, acc[i], c.wrapA, c.srcA);
    }
  }
  if constexpr (JB >= 0) {
#pragma unroll
    for (int h = 0; h < 2; h++) rb[h] = __shfl_sync(0xffffffffu, s.send[h], c.srcB);
  }
  if constexpr (G < 7) cv_raw<G + 1>(B, cb + c.koff);
  uint32_t z = 0;
  if constexpr (G < 8 && NH < 4) {
    __syncwarp();
    wgmma_fence();
#pragma unroll
    for (int i = NH; i < 4; i++) wgmma_rs_hi<128 - 16 * (G & 7)>(acc, A[i][0], A[i][1], A[i][2], A[i][3], db0 - 4 * i);
    wgmma_commit();
    asm volatile("mov.u32 %0, %%clock;" : "=r"(z)::"memory");
    z &= c.zero;
  }
  const float one = __uint_as_float(0x3f800000u | z);
  if constexpr (G < 7) cv_form(B, 0x5432u | z);
  if constexpr (JB >= 0) sts32(stg + ((JB & 1) ? c.so[JB >> 1] >> 16 : c.so[JB >> 1] & 0xffff), pack_bf16(fmaf(rb[0], one, s.keep[0]), fmaf(rb[1], one, s.keep[1])));
  if constexpr (JA >= 0 && JA < 8) {
#pragma unroll
    for (int h = 0; h < 2; h++) {
      const float ev = fmaf(ra[h], one, acc[8 * JA + 2 * h]), od = fmaf(ra[2 + h], one, acc[8 * JA + 4 + 2 * h]);
      s.send[h] = c.kodd ? ev : (c.s3 ? s.Ep[h] : od);
      s.keep[h] = c.kodd ? od : ev;
      s.Ep[h] = od;
    }
  }
  if constexpr (G < 8) { __syncwarp(); wgmma_wait<0>(); cv_copy<8 * (G & 7)>(acc); }
  if constexpr (G < 9) cv_step<G + 1>(acc, B, s, c, cb, stg);
}
__device__ __forceinline__ uint32_t cv_stage(int slot) { return sb + (slot < 4 ? 40960 + slot * 4096 : CV_OFF + CV_K); }
__device__ __forceinline__ void cv_setup(CvCtx& c) {
  const int tid = tid_opaque() & 127, w = tid >> 5, lane = tid & 31, r = lane >> 2, q = lane & 3;
  const int i0 = (r >> 1) & 1, i1 = r >> 2;
  c.koff = CV_K - 32 + 4 * (8 * (r >> 1) + 2 * w + (r & 1) + 2 * q);
  c.srcA = i0 ? lane - 8 : lane + 8 - q + ((q + 3) & 3);
  c.wrapA = i0 && q == 3;
  c.srcB = i1 == 0 ? (lane - q + 16 + ((q + 3) & 3)) : (lane - q - 16 + ((q + 1) & 3));
  c.s3 = (i1 == 1 && q == 3); c.kodd = (i1 == 1 && q < 3);
  c.zero = lds32(sb + EP_OFF + 24);
  const int tb = 16 * (2 * (i1 == 0 ? q : 4 + ((q + 1) & 3)) + i0) + 4 * w + 2 * (r & 1);
#pragma unroll
  for (int J = 0; J < 8; J++) {
    const int t = 256 * J + tb, T = t / 160, tl = t - T * 160;
    const int qq = (T == NT1 - 1) ? (tl >> 5) : (tl / 40);
    int ck = 20 * T + ((tl - qq * ((T == NT1 - 1) ? 32 : 40)) >> 1);
    ck ^= (ck >> 2) & 6;
    const uint32_t o = ck * 16 + qq * 4;
    if (J & 1) c.so[J >> 1] |= o << 16; else c.so[J >> 1] = o;
  }
}
__device__ __forceinline__ void conv_channel(int slot, const CvCtx& c) {
  const uint32_t cb = sb + CV_OFF + slot * CV_B;
  float acc[64];
  CvPipe s;
  s.Ep[0] = s.Ep[1] = 0.f;
  uint32_t A[4][4];
#pragma unroll
  for (int i = 0; i < 64; i++) acc[i] = 0.f;
  if (slot == 4) mbar_wait(bars + 8 * B_CVDONE);
  mbar_wait(bars + 8 * (B_CVFULL + slot));
  cv_raw<0>(A, cb + c.koff);
  cv_form(A, 0x5432u);
  cv_copy<0>(acc);
  cv_step<0>(acc, A, s, c, cb, cv_stage(slot));
  fence_async_smem();
  mbar_arrive(bars + 8 * (B_CVDONE + slot));
}

__device__ __forceinline__ void tap_patch(int c) {
  mbar_wait(bars + 8 * (B_TAPS + c));
  const uint32_t a = sb + CV_OFF + c * CV_B + CV_K, w0 = lds32(a);
  sts32(a, (w0 & 0xffff0000u) | (pack_bf16(bf_lo(w0) + __uint_as_float(lds32(sb + EP_OFF + 4 * c)), 0.f) & 0xffffu));
  mbar_arrive(bars + 8 * (B_CVFULL + c));
}
__device__ __forceinline__ void kv_issue(const Params& p, int c, int m2, int dg) {
  const uint32_t fb = bars + 8 * (B_KV + c);
  mbar_expect_tx(fb, KV_PIECE);
  tma3(sb + KS_OFF + c * KV_PIECE, &p.mK, 160 * dg + 32 * c, 64 * m2 - 3, 0, fb);
  tma3(sb + KS_OFF + c * KV_PIECE + 4864, &p.mV, 160 * dg + 32 * c, 64 * m2 - 1, 0, fb);
}
__device__ __forceinline__ void kv_tile(int m, int dg, int c, int y) {
  const int lane = tid_opaque() & 31, tg = lane >> 3;
  const uint32_t pb = sb + KS_OFF + c * KV_PIECE + 32 * y + 4 * (lane & 7);
  const uint32_t ka = pb + tg * 1216, va = pb + 4864 + tg * 1088 + 64;
  const uint32_t kh = (m == 0 && tg > 0) ? ka - 192 : ka;
  uint32_t kk[19], u[16];
  const float4 t = lds128f(sb + TAP_OFF + 256 * c + 128 * y + 16 * (lane & 7));
#pragma unroll
  for (int i = 0; i < 19; i++) { kk[i] = lds32((i < 3 ? kh : ka) + i * 64); if (i >= 3) u[i - 3] = lds32(va + (i - 3) * 64); }
  uint8_t* dst = g_kv + ((160 * dg + 32 * c + 16 * y + 2 * (lane & 7)) * 4096 + (4 * m + tg) * 16);
  const uint32_t w0 = __byte_perm(__float_as_uint(t.x), __float_as_uint(t.z), 0x5410), w1 = __byte_perm(__float_as_uint(t.x), __float_as_uint(t.z), 0x7632);
  const uint32_t w2 = __byte_perm(__float_as_uint(t.y), __float_as_uint(t.w), 0x5410), w3 = __byte_perm(__float_as_uint(t.y), __float_as_uint(t.w), 0x7632);
#pragma unroll
  for (int i = 0; i < 16; i++) {
    uint32_t a = hmul2(kk[i], w3);
    a = hadd2(a, hmul2(kk[i + 1], w2)); a = hadd2(a, hmul2(kk[i + 2], w1)); a = hadd2(a, hmul2(kk[i + 3], w0));
    u[i] = hmul2(a, u[i]);
  }
#pragma unroll
  for (int e = 0; e < 2; e++)
#pragma unroll
    for (int f = 0; f < 2; f++) {
      uint32_t o[4];
#pragma unroll
      for (int qq = 0; qq < 4; qq++) o[qq] = __byte_perm(u[15 - 4 * qq - 2 * f], u[14 - 4 * qq - 2 * f], e ? 0x7632 : 0x5410);
      *(uint4*)(dst + e * 4096 + f * 2048) = make_uint4(o[0], o[1], o[2], o[3]);
    }
}
__device__ __forceinline__ void ln_finish(float s1, float s2, float& mean, float& rstd) {
  mean = s1 * (1.f / 640.f);
  const float v = fmaxf(fmaf(-mean, mean, s2 * (1.f / 640.f)), 0.f) + 1e-5f;
  asm("rsqrt.approx.ftz.f32 %0, %1;" : "=f"(rstd) : "f"(v));
}
__device__ __forceinline__ void stat_table(int T1, unsigned want, int l, int w) {
#pragma unroll 1
  for (int g = w; g < (T1 == NT1 - 1 ? 4 : 5); g += 4) {
    const int n = 32 * g + (tid_opaque() & 31);
    const uint4* rp = &g_stats[8 * l * SEQ + 160 * T1 + n];
    float a[4], b[4];
    uint32_t it = 0;
    while (true) {
      bool ok = true;
#pragma unroll
      for (int i = 0; i < 4; i++) ok &= (rec_ld(rp + SEQ * i, a[i], b[i]) == want);
      if (__all_sync(0xffffffffu, ok)) break;
      trap_if(++it > SPIN_LIMIT);
    }
    float m, rs;
    ln_finish((a[0] + a[1]) + (a[2] + a[3]), (b[0] + b[1]) + (b[2] + b[3]), m, rs);
    sts64f(sb + STAB_OFF + n * 8, rs, -m * rs);
  }
  mbar_arrive(bars + 8 * (B_STAB + l));
}

template <bool FIRST>
__device__ __forceinline__ void stats_publish(int which, int n0, int dg, unsigned tag, const float (&acc)[80]) {
  const int q = tid_opaque() & 3, h = q & 1;
  float s1[2] = {0.f, 0.f}, s2[2] = {0.f, 0.f}, t1[2] = {0.f, 0.f}, t2[2] = {0.f, 0.f};
#pragma unroll
  for (int j = 0; j < 20; j++)
#pragma unroll
    for (int y = 0; y < 2; y++) {
      const float a = acc[4 * j + 2 * y], b = acc[4 * j + 2 * y + 1];
      s1[y] += a; t1[y] += b; s2[y] = fmaf(a, a, s2[y]); t2[y] = fmaf(b, b, t2[y]);
    }
#pragma unroll
  for (int y = 0; y < 2; y++) { s1[y] += t1[y]; s2[y] += t2[y]; }
  float a = (h ? s1[1] : s1[0]) + __shfl_xor_sync(0xffffffffu, h ? s1[0] : s1[1], 1);
  float b = (h ? s2[1] : s2[0]) + __shfl_xor_sync(0xffffffffu, h ? s2[0] : s2[1], 1);
  a += __shfl_xor_sync(0xffffffffu, a, 2);
  b += __shfl_xor_sync(0xffffffffu, b, 2);
  if (FIRST) {
    rec_st(&g_stats[((q >> 1) * 4 + dg) * SEQ + n0 + 8 * h], a, b, q < 2 ? tag : tag - 1);
    rec_st(&g_stats[((q >> 1) * 4 + 8 + dg) * SEQ + n0 + 8 * h], a, b, tag - 1);
  } else if (q < 2) rec_st(&g_stats[(which * 4 + dg) * SEQ + n0 + 8 * h], a, b, tag);
}
__device__ __forceinline__ void stats_get(int which, int n0, unsigned tag, float (&mean)[2], float (&rstd)[2]) {
  const uint4* p0 = &g_stats[(which * 4 + (tid_opaque() & 3)) * SEQ + n0];
  float a[2], b[2];
  uint32_t it = 0;
  while (true) {
    const unsigned t0 = rec_ld(p0, a[0], b[0]), t1 = rec_ld(p0 + 8, a[1], b[1]);
    if (__all_sync(0xffffffffu, t0 == tag && t1 == tag)) break;
    trap_if(++it > SPIN_LIMIT);
  }
#pragma unroll
  for (int o = 1; o < 4; o <<= 1)
#pragma unroll
    for (int h = 0; h < 2; h++) { a[h] += __shfl_xor_sync(0xffffffffu, a[h], o); b[h] += __shfl_xor_sync(0xffffffffu, b[h], o); }
#pragma unroll
  for (int h = 0; h < 2; h++) ln_finish(a[h], b[h], mean[h], rstd[h]);
}
__device__ __forceinline__ void x0_load(float (&acc)[80]) {
  const int t = tid_opaque() & 127;
  const uint32_t xa = sb + XT_OFF + (16 * (t >> 5) + ((t & 31) >> 2)) * 320 + 8 * (t & 3);
  mbar_wait(bars + 8 * B_XT);
#pragma unroll
  for (int h = 0; h < 2; h++)
#pragma unroll
    for (int J = 0; J < 10; J++) {
      const float2 v = lds64f(xa + h * 2560 + 32 * J);
      const uint32_t x = __float_as_uint(v.x), y = __float_as_uint(v.y);
      acc[8 * J + 2 * h] = bf_lo(x); acc[8 * J + 2 * h + 1] = bf_hi(x);
      acc[8 * J + 4 + 2 * h] = bf_lo(y); acc[8 * J + 4 + 2 * h + 1] = bf_hi(y);
    }
}

template <bool FROM_X0>
__device__ __forceinline__ void dskip_init(float (&acc)[80], const float (&mean)[2], const float (&rstd)[2]) {
  const int t = tid_opaque() & 127;
  const uint32_t xa = sb + XT_OFF + (16 * (t >> 5) + ((t & 31) >> 2)) * 320 + 8 * (t & 3), da = sb + DTAB_OFF + 8 * (t & 3);
  float2 dw[10], xv[10][2];
#pragma unroll
  for (int J = 0; J < 2; J++) { dw[J] = lds64f(da + 32 * J); if (FROM_X0) { xv[J][0] = lds64f(xa + 32 * J); xv[J][1] = lds64f(xa + 2560 + 32 * J); } }
#pragma unroll
  for (int J = 0; J < 10; J++) {
    if (J + 2 < 10) { dw[J + 2] = lds64f(da + 32 * (J + 2)); if (FROM_X0) { xv[J + 2][0] = lds64f(xa + 32 * (J + 2)); xv[J + 2][1] = lds64f(xa + 2560 + 32 * (J + 2)); } }
#pragma unroll
    for (int x = 0; x < 8; x++) {
      const int h = (x >> 1) & 1;
      const uint32_t dwd = __float_as_uint(x < 4 ? dw[J].x : dw[J].y);
      const float tt = fmaf(rstd[h], (x & 1) ? bf_hi(dwd) : bf_lo(dwd), 1.f);
      float a = acc[8 * J + x];
      if (FROM_X0) { const uint32_t xw = __float_as_uint(x < 4 ? xv[J][h].x : xv[J][h].y); a = (x & 1) ? bf_hi(xw) : bf_lo(xw); }
      acc[8 * J + x] = FROM_X0 ? (a - mean[h]) * tt : fmaf(a, tt, -mean[h] * tt);
    }
  }
}

__global__ void __launch_bounds__(512, 1) fused_kernel(const __grid_constant__ Params p) {
  extern __shared__ __align__(1024) uint8_t smem_raw[];
  const int tid = threadIdx.x, lane = tid & 31;
  const int wid = __shfl_sync(0xffffffffu, tid >> 5, 0), wg = wid >> 2;
  unsigned smid; asm volatile("mov.u32 %0, %%smid;" : "=r"(smid));
  const int role = p.role[min(smid, 131u)];
  if (wid == 12) {
    const bool el = elect_one();
    if (el) {
      asm volatile("prefetch.tensormap [%0];" ::"l"(&p.mX) : "memory");
      asm volatile("prefetch.tensormap [%0];" ::"l"(&p.mB) : "memory");
#pragma unroll
      for (int k = 0; k < S1; k++) mbar_init(bars + 8 * (B_G1FULL + k), 1);
#pragma unroll
      for (int k = 0; k < 6; k++) mbar_init(bars + 8 * (B_XT + k), 1);
      asm volatile("fence.mbarrier_init.release.cluster;" ::: "memory");
    }
    if (role >= 0) {
      __syncwarp();
      asm volatile("bar.arrive 5, 288;" ::: "memory");
      const Role R = unpack_role(role);
      if (elect_one()) {
        TS(45);
#pragma unroll 1
        for (int k = 0; k < S1; k++) {
          const uint32_t fb = bars + 8 * (B_G1FULL + k);
          mbar_expect_tx(fb, G1_STAGE);
          tma4(sb + k * G1_STAGE + G1_XOFF, R.last ? &p.mXl : &p.mX, 64 * k, 0, 0, R.last ? 0 : 80 * R.T1, fb);
          tma5(sb + k * G1_STAGE, &p.mB, 64 * k, 0, 0, 4 * R.side, 2 * R.GP, fb);
        }
        if (R.has2) {
#pragma unroll 1
          for (int c = 0; c < KV0; c++) kv_issue(p, c, R.m2, R.dg);
          mbar_expect_tx(bars + 8 * B_XT, 20480);
#pragma unroll 1
          for (int h = 0; h < 2; h++) {
            const int ng = 8 * R.m2 + 4 * h, T = ng / 20;
            tma4(sb + XT_OFF + h * 10240, T == NT1 - 1 ? &p.mXtl : &p.mXt, 160 * R.dg, 0, 0, T == NT1 - 1 ? ng - 240 : ng + 60 * T, bars + 8 * B_XT);
          }
        }
        TS(44);
      }
      __syncwarp();
      bar_sync(6, 64);
    }
  }
  trap_if(smid >= 132 || smem_u32(smem_raw) != sb);
  if (role < 0) {
    if (wid == 0) {
      const unsigned tag = ld_rlx(g_epoch);
#pragma unroll 1
      for (int i = 0; i < NT1; i++) {
        uint32_t it = 0;
        while (!__all_sync(0xffffffffu, (int)(ld_rlx(&g_hflag[(i * 32 + min(lane, 9)) * 8]) - tag) >= 0)) { __nanosleep(500); trap_if(++it > SPIN_LIMIT); }
      }
    }
    return;
  }
  if (wg == 2 || wid == 14) {
    ROLE(role)
    const int c = wid == 14 ? 4 : wid - 8;
    const unsigned tag = ld_rlx(g_epoch);
    if (has2) {
      uint2 bv[2][5];
#pragma unroll
      for (int x = 0; x < 2; x++)
#pragma unroll
        for (int i = 0; i < 5; i++) bv[x][i] = ldv64((const uint2*)((x ? p.bim : p.bre) + (cch0 + 32 * c) * DM) + lane + 32 * i);
      float sv[2];
#pragma unroll
      for (int x = 0; x < 2; x++) {
        float a = 0.f;
#pragma unroll
        for (int i = 0; i < 5; i++) a += (bf_lo(bv[x][i].x) + bf_hi(bv[x][i].x)) + (bf_lo(bv[x][i].y) + bf_hi(bv[x][i].y));
        sv[x] = a;
      }
#pragma unroll
      for (int o = 16; o > 0; o >>= 1) { sv[0] += __shfl_xor_sync(0xffffffffu, sv[0], o); sv[1] += __shfl_xor_sync(0xffffffffu, sv[1], o); }
      if (lane < 2) rec_st(&g_sB[(cch0 + 32 * c) * 2 + lane], sv[0], sv[1], tag);
      if (tid == 256) TS(47);
      __syncwarp();
      bar_sync(8, 192);
      mbar_wait(bars + 8 * B_EP);
      mbar_wait(bars + 8 * (B_KV + c));
#pragma unroll 1
      for (int y = 0; y < 2; y++) kv_tile(m2, dg, c, y);
      __syncwarp();
      if (lane == 0) { mbar_arrive(bars + 8 * (B_PD + c)); mbar_arrive(bars + 8 * B_PREP); }
      if (tid == 256) TS(48);
      if (tid == 352) TS(52);
      if (tid == 448) TS(51);
      if (wg == 2) {
        float xs[80];
        x0_load(xs);
        stats_publish<true>(0, 64 * m2 + 16 * c + (lane >> 2), dg, tag, xs);
        if (tid == 256) TS(31);
        mbar_wait(bars + 8 * B_PUB);
      } else {
        mbar_wait(bars + 8 * B_PREP);
        if (lane == 0) { st_rel(&g_kvflag[(dg * 32 + m2) * 8], tag); mbar_arrive(bars + 8 * B_PUB); TS(30); }
        __syncwarp();
      }
    } else bar_sync(8, 192);
    if (wg == 2) {
      if (c == 1 || c == 2) {
        float a, b;
        rec_poll(&g_sB[(128 * GP + 64 * (c - 1) + 32 * side + lane) * 2], tag, a, b);
        sts64f(sb + CTAB_OFF + (32 * (c - 1) + lane) * 24 + 16, p.swap ? b : a, p.swap ? a : b);
      }
      stat_table(T1, tag, 0, c);
      if (tid == 256) TS(26);
    }
  } else if (wid == 15) {
    ROLE(role)
    const int ch = 128 * GP + 32 * side + lane;
    uint32_t r0 = ldv16(p.lre + ch), r1 = ldv16(p.lim + ch), r2 = ldv16(p.logdt + ch);
    const uint32_t r3 = ldv16(p.lre + ch + 64), r4 = ldv16(p.lim + ch + 64), r5 = ldv16(p.logdt + ch + 64);
#pragma unroll 1
    for (int i = 0; i < 2; i++) {
      const float lr = bf_lo(r0), li = bf_lo(r1);
      const float dt = __bfloat162float(__float2bfloat16_rn(expf(bf_lo(r2))));
      const float mag = expf(dt * lr);
      float sn, cs; sincospif(dt * li * 0.31830988618379067f, &sn, &cs);
      const float ar = mag * cs, ai = mag * sn;
      const float inv = 2.f / (lr * lr + li * li);
      const uint32_t ad = sb + CTAB_OFF + (32 * i + lane) * 24;
      sts64f(ad, ar, ai);
      sts64f(ad + 8, ((ar - 1.f) * lr + ai * li) * inv, (ai * lr - (ar - 1.f) * li) * inv);
      r0 = r3; r1 = r4; r2 = r5;
    }
    if (lane == 0) TS(46);
    __syncwarp();
    bar_sync(7, 64);
    mbar_arrive(bars + 8 * B_CTAB);
  } else if (wid == 13) {
    ROLE(role)
    uint4 tv[3];
    const uint32_t e0 = ld_rlx(g_epoch);
    const uint32_t e1 = ldv16(p.ssmD + min(cch0 + 32 * lane, 639));
    const uint4 dv = ldv128((const uint4*)(p.dskip + 160 * dg) + min(lane, 19));
#pragma unroll
    for (int i = 0; i < 3; i++) tv[i] = ldv128((const uint4*)(p.shiftk + 640 * dg) + min(lane + 32 * i, 79));
    sts128(sb + DTAB_OFF + 16 * min(lane, 19), dv);
#pragma unroll
    for (int i = 0; i < 3; i++) sts128(sb + TAP_OFF + 16 * min(lane + 32 * i, 79), tv[i]);
    if (lane < 7) sts32(sb + EP_OFF + 4 * lane, lane < 5 ? e1 << 16 : (lane == 5 ? e0 : 0u));
    __syncwarp();
    bar_sync(9, 64);
    mbar_arrive(bars + 8 * B_CTAB);
    if (lane == 0) { mbar_arrive(bars + 8 * B_EP); TS(53); }
  } else if (wid != 12) {
    if (elect_one()) {
      if (wid < 7) {
        const int b0 = wid < 4 ? 4 + 20 * wid : 85 + 21 * (wid - 4), cnt = wid < 4 ? 2 : 1;
#pragma unroll
        for (int i = 0; i < 21; i++) mbar_init(bars + 8 * (b0 + i), cnt);
      } else {
#pragma unroll
        for (int i = 0; i < 12; i++) mbar_init(bars + 8 * (B_CVDONE + i), 128);
        mbar_init(bars + 8 * B_CTAB, 64); mbar_init(bars + 8 * B_PREP, 5);
      }
      asm volatile("fence.mbarrier_init.release.cluster;" ::: "memory");
    }
    __syncwarp();
    bar_sync(5, 288);
    if (wid == 2) asm volatile("bar.arrive 8, 192;\nbar.arrive 6, 64;\nbar.arrive 9, 64;\nbar.arrive 7, 64;" ::: "memory");
    if (tid == 128) TS(0);
  }

  if (wg == 3) {
    ROLE(role)
    const int pw = wid & 3;
    unsigned tag = 0;
    if (pw > 0) { mbar_wait(bars + 8 * B_EP); tag = lds32(sb + EP_OFF + 20); }
    if (pw == 0) {
      if (elect_one()) {
#pragma unroll 1
        for (int l = 0; l < 2; l++) {
          const uint32_t fb0 = bars + 8 * (B_G1FULL + 10 * l), wb = bars + 8 * (B_G1DONE + 9 * l - S1);
          const uint32_t free0 = bars + 8 * (has2 ? B_G2DONE + 19 : B_G1DONE + 9);
          uint32_t dst = sb;
#pragma unroll 1
          for (int k = l == 0 ? S1 : 0; k < 10; k++) {
            mbar_wait(k >= S1 + l ? wb + 8 * k : (k < WPF1 || !has2 ? free0 : bars + 8 * (B_GO + 1)));
            mbar_expect_tx(fb0 + 8 * k, 16384);
            tma5(dst, &p.mB, 64 * k, 0, 0, 4 * side, 2 * GP, fb0 + 8 * k);
            dst += G1_STAGE; if (dst == sb + (S1 + l) * G1_STAGE) dst = sb;
          }
          if (has2) {
            const uint32_t fb2 = bars + 8 * (B_G2FULL + 20 * l), wb2 = bars + 8 * (B_G2DONE + 19 * l - 6);
            dst = sb + G2_WOFF;
            int kc = 0;
#pragma unroll 1
            for (int k = 0; k < 20; k++) {
              mbar_wait(k >= 6 + l ? wb2 + 8 * k : (k == 5 ? bars + 8 * B_XFREE : (k < WPF2 ? bars + 8 * (B_G1DONE + 10 * l + 9) : bars + 8 * (B_GO + 2 * l))));
              mbar_expect_tx(fb2 + 8 * k, G2_WB);
              tma5(dst, &p.mCre + (k & 1), kc, 0, 0, 0, 10 * dg, fb2 + 8 * k);
              kc += (k & 1) << 7; if (k == 9) kc = 64;
              dst += G2_WB; if (dst == sb + G2_WOFF + (6 + l) * G2_WB) dst = sb + G2_WOFF;
            }
          }
        }
      }
    } else if (pw == 1) {
#pragma unroll 1
      for (int l = 0; l < 2; l++) {
        if (l == 0) {
          if (elect_one()) {
            uint32_t dst = sb + G1_XOFF;
#pragma unroll 1
            for (int k = S1; k < 10; k++) {
              mbar_wait(bars + 8 * (B_G1DONE + k - S1));
              mbar_expect_tx(bars + 8 * (B_G1FULL + k), 20480);
              tma4(dst, last ? &p.mXl : &p.mX, 64 * k, 0, 0, last ? 0 : 80 * T1, bars + 8 * (B_G1FULL + k));
              dst += G1_STAGE; if (k == 2 * S1 - 1) dst = sb + G1_XOFF;
              if (has2 && k - S1 + KV0 < 5) kv_issue(p, k - S1 + KV0, m2, dg);
            }
          }
        } else {
          mbar_wait(bars + 8 * (has2 ? B_G2DONE + 19 : B_G1DONE + 9));
          const int mlo = (160 * T1) >> 6, nf = last ? 8 : 12;
          flag_poll(&g_uflag[(4 * mlo + min(lane, nf - 1)) * 8], tag);
          fence_async_global();
          if (elect_one()) {
            TS(20);
            const int bytes = last ? 16384 : 20480;
            const uint8_t* src = g_u + T1 * 204800;
            uint32_t dst = sb + G1_XOFF;
#pragma unroll 1
            for (int k = 0; k < 10; k++) {
              if (k > S1) mbar_wait(bars + 8 * (B_G1DONE + 9 - S1 + k));
              mbar_expect_tx(bars + 8 * (B_G1FULL + 10 + k), bytes);
              bulk_g2s(dst, src, bytes, bars + 8 * (B_G1FULL + 10 + k));
              src += 20480; dst += G1_STAGE; if (k == S1) dst = sb + G1_XOFF;
            }
          }
        }
        __syncwarp();
        if (has2) {
          mbar_wait(bars + 8 * (B_G1DONE + 10 * l + 9));
          const int Tlo = (64 * m2) / 160, Thi = (64 * m2 + 63) / 160;
          flag_poll(&g_hflag[(((l * NT1 + (lane < 16 ? Tlo : Thi)) * 2) * 16 + min(lane & 15, 9)) * 8], tag);
          fence_async_global();
          if (elect_one()) {
            TS(21 + 2 * l);
            const uint32_t fb2 = bars + 8 * (B_G2FULL + 20 * l), wb2 = bars + 8 * (B_G2DONE + 18 * l - SX2);
            const uint8_t* src = g_h + (l * 32 + m2) * 163840;
            uint32_t dst = sb;
#pragma unroll 1
            for (int k = 0; k < 20; k++) {
              if (k >= SX2 + 2 * l) mbar_wait(wb2 + 8 * k);
              if (k == 10) { mbar_wait(bars + 8 * (B_H1 + l)); fence_async_global(); }
              mbar_expect_tx(fb2 + 8 * k, G2_XB);
              bulk_g2s(dst, src, G2_XB, fb2 + 8 * k);
              src += 8192; dst += G2_XB; if (dst == sb + (SX2 + 2 * l) * G2_XB) dst = sb;
            }
          }
          __syncwarp();
        }
      }
    } else if (pw == 2) {
#pragma unroll 1
      for (int l = 0; l < 2; l++) {
        mbar_wait(bars + 8 * (B_HST + 2 * l));
        mbar_wait(bars + 8 * (B_HST + 2 * l + 1));
        __syncwarp();
        if (lane < 2) st_rel(&g_hflag[(((l * NT1 + T1) * 2 + lane) * 16 + 2 * GP + side) * 8], tag);
        if (lane == 0) TS(6 + 8 * l);
        __syncwarp();
        if (l == 0 && has2 && elect_one()) {
#pragma unroll 1
          for (int c = 0; c < 5; c++) {
            mbar_wait(bars + 8 * (B_CVDONE + c));
            bulk_s2g(g_G + (cch0 + 32 * c) * 4096, cv_stage(c), 4096);
          }
          asm volatile("cp.async.bulk.commit_group;" ::: "memory");
          asm volatile("cp.async.bulk.wait_group 0;" ::: "memory");
          fence_async_global();
          st_rel(&g_gflag[(dg * 32 + m2) * 8], tag);
        }
        __syncwarp();
      }
    } else if (has2) {
#pragma unroll 1
      for (int c = 0; c < 5; c++) {
        mbar_wait(bars + 8 * (B_PD + c));
        const uint32_t cb = sb + CV_OFF + c * CV_B;
        sts128(lane < 8 ? cb + 16 * lane : (lane < 20 ? cb + CV_U + 16 * (lane - 8) : cb + CV_U + CV_PL + 16 * (lane - 20)), make_uint4(0, 0, 0, 0));
        fence_async_smem();
        __syncwarp();
        if (!TAPLATE && c < TAP0 && elect_one()) {
          mbar_expect_tx(bars + 8 * (B_TAPS + c), 4096);
          bulk_g2s(cb + CV_K, p.ssmk + (cch0 + 32 * c) * SEQ, 4096, bars + 8 * (B_TAPS + c));
        }
      }
      mbar_wait(bars + 8 * B_PUB);
      if (TAPLATE && elect_one()) {
#pragma unroll
        for (int c = 0; c < TAP0; c++) {
          mbar_expect_tx(bars + 8 * (B_TAPS + c), 4096);
          bulk_g2s(sb + CV_OFF + c * CV_B + CV_K, p.ssmk + (cch0 + 32 * c) * SEQ, 4096, bars + 8 * (B_TAPS + c));
        }
      }
      flag_poll(&g_kvflag[(dg * 32 + lane) * 8], tag);
      fence_async_global();
      if (elect_one()) {
        TS(28);
#pragma unroll 1
        for (int c = 0; c < 5; c++) {
          const uint32_t fb = bars + 8 * (B_CVFULL + c), cb = sb + CV_OFF + c * CV_B;
          if (c == 1) tap_patch(0);
          mbar_expect_tx(fb, 4096);
          bulk_g2s(cb + CV_U + 192, g_kv + (cch0 + 32 * c) * 4096, 2048, fb);
          bulk_g2s(cb + CV_U + 192 + CV_PL, g_kv + (cch0 + 32 * c) * 4096 + 2048, 2048, fb);
          if (c >= TAP0) {
            mbar_expect_tx(bars + 8 * (B_TAPS + c), 4096);
            bulk_g2s(cb + CV_K, p.ssmk + (cch0 + 32 * c) * SEQ, 4096, bars + 8 * (B_TAPS + c));
          }
        }
#pragma unroll 1
        for (int c = 1; c < 5; c++) tap_patch(c);
        TS(54);
        asm volatile("prefetch.tensormap [%0];" ::"l"(&p.mCre) : "memory");
        asm volatile("prefetch.tensormap [%0];" ::"l"(&p.mCim) : "memory");
        asm volatile("prefetch.tensormap [%0];" ::"l"(&p.mG) : "memory");
      }
      __syncwarp();
      const unsigned* hf = &g_hflag[(((lane < 16 ? (64 * m2) / 160 : (64 * m2 + 63) / 160) * 2 + 1) * 16 + min(lane & 15, 9)) * 8];
      mbar_wait(bars + 8 * (B_CVDONE + 0));
      if (elect_one()) { l2_prefetch(p.cre + (160 * dg + 5 * m2) * DM, 6400); l2_prefetch(p.cim + (160 * dg + 5 * m2) * DM, 6400); }
      flag_poll(hf, tag);
      __syncwarp();
      if (lane == 0) { mbar_arrive(bars + 8 * B_H1); TS(22); }
      mbar_wait(bars + 8 * (B_CVDONE + 4));
      flag_poll(&g_gflag[(dg * 32 + lane) * 8], tag);
      __syncwarp();
      fence_async_global();
      if (lane == 0) TS(29);
      if (elect_one()) {
        mbar_expect_tx(bars + 8 * B_GFULL, 20480);
        tma5(sb + G_OFF, &p.mG, 64 * m2, 0, 0, 0, 10 * dg, bars + 8 * B_GFULL);
      }
      mbar_wait(bars + 8 * (B_G1DONE + 19));
      flag_poll(hf + NT1 * 256, tag);
      __syncwarp();
      if (lane == 0) { mbar_arrive(bars + 8 * (B_H1 + 1)); TS(24); }
    }
  } else {
    const int w = wid & 3;
    if (wg == 2 && !(role >> 16)) { mbar_wait(bars + 8 * (B_G1FULL + 11)); stat_table(role & 15, lds32(sb + EP_OFF + 20), 1, w); }
    float mean0[2] = {0.f, 0.f}, rstd0[2] = {0.f, 0.f};
    if (wg == 2 && (role >> 16)) stats_get(0, 64 * ((role >> 8) & 63) + 16 * w + (lane >> 2), lds32(sb + EP_OFF + 20), mean0, rstd0);
#pragma unroll 1
    for (int l = 0; l < 2; l++) {
      if (wg < 2) {
        float acc[80];
#pragma unroll
        for (int i = 0; i < 80; i++) acc[i] = 0.f;
        ROLE(role)
        const int tid = tid_opaque(), r = (tid & 31) >> 2, q = tid & 3;
        const int ch = 128 * GP + 64 * wg + 32 * side + 8 * w + r;
        const uint32_t ca = sb + CTAB_OFF + (32 * wg + 8 * w + r) * 24;
        float2 lam = make_float2(0.f, 0.f), p8 = lam, p16 = lam, pL = lam, p2L = lam;
        fence_regs(acc);
        {
          uint32_t alo = desc_lo(sb, 16) + wg * 512, blo = l == 0 ? desc_lo(sb + G1_XOFF, 16) : desc_lo(sb + G1_XOFF, 128);
          const uint32_t bhi = l == 0 ? desc_hi(1024, 1) : desc_hi(1024, 0), xstep = l == 0 ? 2 : 16;
          const uint32_t aend = desc_lo(sb, 16) + (S1 + l) * (G1_STAGE >> 4);
          uint32_t fb = bars + 8 * (B_G1FULL + 10 * l);
          mbar_wait(fb);
          if (tid == 0) TS(1 + 8 * l);
#pragma unroll 1
          for (int k = 0; k < 10; k++) {
            uint32_t ok; const uint32_t nb = k < 9 ? fb + 8 : fb;
            wgmma_fence();
#pragma unroll
            for (int kk = 0; kk < 4; kk++) {
              wgmma_n160<0>(acc, alo + kk * 2, desc_hi(1024, 1), blo + kk * xstep, bhi);
              if (kk == 0) ok = mbar_test(nb);
            }
            wgmma_commit();
            alo += G1_STAGE >> 4; blo += G1_STAGE >> 4;
            if (alo >= aend) { alo -= (S1 + l) * (G1_STAGE >> 4); blo -= (S1 + l) * (G1_STAGE >> 4); }
            wgmma_wait<1>();
            if (k > 0 && (tid & 127) == 0) mbar_arrive(fb + 8 * (B_G1DONE - B_G1FULL - 1));
            if (!ok) mbar_wait(nb);
            if (k == PAUSE_K) {
              mbar_wait(bars + 8 * B_CTAB);
              lam = lds64f(ca);
              if (p.swap) lam.y = -lam.y;
              const float2 p2 = cmul(lam, lam), p4 = cmul(p2, p2);
              p8 = cmul(p4, p4); p16 = cmul(p8, p8);
              pL = cmul(p16, p16);
              if (!last) pL = cmul(pL, p8);
              p2L = cmul(pL, pL);
              if (has2) mbar_wait(bars + 8 * B_PREP);
            }
            fb += 8;
          }
        }
        mbar_wait(bars + 8 * (B_STAB + l));
        const float2 sB = lds64f(ca + 16);
        const unsigned tag = lds32(sb + EP_OFF + 20);
        wgmma_wait<0>();
        fence_regs(acc);
        if ((tid & 127) == 0) { mbar_arrive(bars + 8 * (B_G1DONE + 10 * l + 9)); if (wg == 0) TS(2 + 8 * l); }
        float2 ec[3];
#pragma unroll
        for (int jj = 0; jj < 8; jj++)
#pragma unroll
          for (int y = 0; y < 3; y++) {
            if (y == 2 && (jj & 1)) continue;
            const int j = y == 2 ? 16 + (jj >> 1) : 8 * y + jj;
            const float4 st = lds128f(sb + STAB_OFF + (8 * j + 2 * q) * 8);
            acc[4 * j + 0] = fmaf(acc[4 * j + 0], st.x, st.y * sB.x);
            acc[4 * j + 2] = fmaf(acc[4 * j + 2], st.x, st.y * sB.y);
            acc[4 * j + 1] = fmaf(acc[4 * j + 1], st.z, st.w * sB.x);
            acc[4 * j + 3] = fmaf(acc[4 * j + 3], st.z, st.w * sB.y);
            ec[y] = jj == 0 ? make_float2(acc[4 * j + 0], acc[4 * j + 2]) : cfma(lam, ec[y], make_float2(acc[4 * j + 0], acc[4 * j + 2]));
            ec[y] = cfma(lam, ec[y], make_float2(acc[4 * j + 1], acc[4 * j + 3]));
          }
        float2 e = cfma(p16, ec[0], ec[1]);
        if (!last) e = cfma(p8, e, ec[2]);
        {
          float2 v = make_float2(__shfl_up_sync(0xffffffffu, e.x, 1, 4), __shfl_up_sync(0xffffffffu, e.y, 1, 4));
          if (q >= 1) e = cfma(pL, v, e);
          v = make_float2(__shfl_up_sync(0xffffffffu, e.x, 2, 4), __shfl_up_sync(0xffffffffu, e.y, 2, 4));
          if (q >= 2) e = cfma(p2L, v, e);
        }
        if (!last && (q == 3 || (q == 2 && l == 0))) rec_st(&g_E[((q == 3 ? l : 1) * NT1 + T1) * DM + ch], e.x, e.y, q == 3 ? tag : tag - 1);
        if (tid == 0) TS(3 + 8 * l);
        float2 ex = make_float2(__shfl_up_sync(0xffffffffu, e.x, 1, 4), __shfl_up_sync(0xffffffffu, e.y, 1, 4));
        if (q == 0) ex = make_float2(0.f, 0.f);
        const float2 coef = lds64f(ca + 8), lamc = make_float2(lam.x, p.swap ? lam.y : -lam.y);
        float m00 = coef.x, m01 = -coef.y, m10 = -coef.y, m11 = -coef.x;
        if (p.swap) { m00 = -coef.y; m01 = coef.x; m10 = -coef.x; m11 = -coef.y; }
        float2 pLq, p160q, p640;
        {
          const float2 p80 = last ? cmul(p2L, p16) : p2L, p160 = cmul(p80, p80), p320 = cmul(p160, p160), one = make_float2(1.f, 0.f);
          p640 = cmul(p320, p320);
          pLq = cmul((q & 1) ? pL : one, (q & 2) ? p2L : one);
          p160q = cmul((q & 1) ? p160 : one, (q & 2) ? p320 : one);
        }
        float2 c, ev[3];
        unsigned tg[3];
        const uint4* ep = &g_E[(l * NT1 + T1 - 1 - q) * DM + ch];
#pragma unroll
        for (int j = 0; j < 20; j++) {
          if (j == CPOLL) {
#pragma unroll
            for (int i = 0; i < 3; i++) {
              ev[i] = make_float2(0.f, 0.f); tg[i] = tag;
              if (T1 - 1 - q - 4 * i >= 0) tg[i] = rec_ld(ep - 4 * i * DM, ev[i].x, ev[i].y);
            }
          }
#pragma unroll
          for (int x = 0; x < 2; x++) {
            const float b0 = acc[4 * j + x], b1 = acc[4 * j + 2 + x];
            acc[4 * j + x] = fmaf(b0, m00, b1 * m01);
            acc[4 * j + 2 + x] = fmaf(b0, m10, b1 * m11);
          }
          if (j == CPOLL - 1 || j == 19) asm volatile("" : "+f"(acc[4 * j]), "+f"(acc[4 * j + 1]), "+f"(acc[4 * j + 2]), "+f"(acc[4 * j + 3])::"memory");
        }
        {
          uint32_t it = 0;
          while (__any_sync(0xffffffffu, tg[0] != tag || tg[1] != tag || tg[2] != tag)) {
#pragma unroll
            for (int i = 0; i < 3; i++)
              if (tg[i] != tag) tg[i] = rec_ld(ep - 4 * i * DM, ev[i].x, ev[i].y);
            trap_if(++it > SPIN_LIMIT);
          }
          c = cfma(p640, cfma(p640, ev[2], ev[1]), ev[0]);
          c = cmul(c, p160q);
          c.x += __shfl_xor_sync(0xffffffffu, c.x, 1); c.y += __shfl_xor_sync(0xffffffffu, c.y, 1);
          c.x += __shfl_xor_sync(0xffffffffu, c.x, 2); c.y += __shfl_xor_sync(0xffffffffu, c.y, 2);
        }
        if (tid == 0) TS(4 + 8 * l);
        if (tid == 128) mbar_arrive(bars + 8 * (B_GO + 2 * l));
        c = cfma(pLq, c, ex);
        float2 hh = make_float2(fmaf(c.x, m00, c.y * m01), fmaf(c.x, m10, c.y * m11));
        uint8_t* hb = g_h + (size_t)l * (32 * 20 * 8192) + (10 * wg + 2 * GP) * 8192 + (4 * side + w) * 1024 + (tid_opaque() & 31) * 4;
#pragma unroll
        for (int j4 = 0; j4 < 5; j4++) {
          const int ng = 20 * T1 + 4 * j4;
          uint8_t* hp = hb + (size_t)(ng >> 3) * 163840 + (ng & 7) * 128;
#pragma unroll
          for (int jj = 0; jj < 4; jj++) {
            const int j = 4 * j4 + jj;
            const float2 h0 = cfma(lamc, hh, make_float2(acc[4 * j + 0], acc[4 * j + 2]));
            hh = cfma(lamc, h0, make_float2(acc[4 * j + 1], acc[4 * j + 3]));
            if (j4 < 4 || !last) {
              *(uint32_t*)(hp + jj * 128) = pack_bf16(h0.x, hh.x);
              *(uint32_t*)(hp + jj * 128 + 8192) = pack_bf16(h0.y, hh.y);
            }
          }
        }
        mbar_arrive(bars + 8 * (B_HST + 2 * l + wg));
        if (tid == 0) TS(5 + 8 * l);
      }
      if (l == 0) {
        ROLE(role)
        if (has2) {
          CvCtx cc;
          cv_setup(cc);
          mbar_wait(bars + 8 * (B_G1DONE + 9));
#pragma unroll 1
          for (int c = wg == 2 ? 0 : 2 + wg; c < (wg == 2 ? 2 : 5); c += wg == 2 ? 1 : 2) conv_channel(c, cc);
          if ((tid & 127) == 0) TS(wg == 2 ? 32 : 7 + wg);
        }
      }
      if (wg == 2) break;
    }
    if (wg == 2 && (role >> 16)) {
      float acc[80];
      float off[2] = {mean0[0], mean0[1]};
      const unsigned tag = lds32(sb + EP_OFF + 20);
      dskip_init<true>(acc, mean0, rstd0);
      mbar_arrive(bars + 8 * B_XFREE);
#pragma unroll 1
      for (int l = 0; l < 2; l++) {
        float mean[2], rstd[2];
        {
          const uint32_t aend = desc_lo(sb + SX2 * G2_XB, 1024) + l * (G2_XB >> 3), bend = desc_lo(sb + G2_WOFF + 6 * G2_WB, 16) + l * (G2_WB >> 4);
          uint32_t alo = desc_lo(sb, 1024), blo = desc_lo(sb + G2_WOFF, 16);
          uint32_t fb = bars + 8 * (B_G2FULL + 20 * l);
          fence_regs(acc);
          mbar_wait(fb);
          if (tid == 256) TS(33 + 6 * l);
#pragma unroll 1
          for (int k = 0; k < 20; k++) {
            if (l == 1 && (k & 3) == 3 && tid == 256) TS(56 + (k >> 2));
            uint32_t ok; const uint32_t nb = k < 19 ? fb + 8 : fb;
            wgmma_fence();
#pragma unroll
            for (int kk = 0; kk < 4; kk++) {
              wgmma_n160<1>(acc, alo + kk * 128, desc_hi(128, 0), blo + kk * 2, desc_hi(1024, 1));
              if (kk == 0) ok = mbar_test(nb);
            }
            wgmma_commit();
            alo += G2_XB >> 4; if (alo == aend) alo = desc_lo(sb, 1024);
            blo += G2_WB >> 4; if (blo == bend) blo = desc_lo(sb + G2_WOFF, 16);
            wgmma_wait<1>();
            if (k > 0 && tid == 256) mbar_arrive(fb + 8 * (B_G2DONE - B_G2FULL - 1));
            if (!ok) mbar_wait(nb);
            fb += 8;
          }
          wgmma_wait<0>();
          fence_regs(acc);
          if (tid == 256) TS(34 + 6 * l);
          if (tid == 256) mbar_arrive(bars + 8 * (B_G2DONE + 20 * l + 19));
        }
        ROLE(role)
        const int tq = tid_opaque() & 31, n0 = 64 * m2 + 16 * w + (tq >> 2);
        stats_publish<false>(2 * l + 1, n0, dg, tag, acc);
        uint32_t gf[10][4];
        mbar_wait(bars + 8 * B_GFULL);
        const uint32_t ga = sb + G_OFF + (8 * (tq >> 4) + (tq & 7)) * 128 + (((2 * w + ((tq >> 3) & 1)) ^ ((2 * m2) & 6) ^ (tq & 7)) << 4);
#pragma unroll
        for (int J = 0; J < 2; J++) ldsm4t(gf[J], ga + J * 2048);
        if (tid == 256) TS(35 + 6 * l);
        uint8_t* dst[2][2];
#pragma unroll
        for (int h = 0; h < 2; h++) {
          if (l == 0) {
            const int ng = 8 * m2 + 2 * w + h, T = ng / 20;
            uint8_t* ub = g_u + (T * 204800 + (ng - 20 * T) * 1024 + (tq & 2) * 64 + (tq & 28) * 4 + (tq & 1) * 8 + (5 * dg >> 1) * 20480);
            dst[h][1] = ub + ((dg & 1) ? 20480 - 512 : 0);
            dst[h][0] = ub + (dg & 1) * 512;
          } else {
            dst[h][0] = dst[h][1] = (uint8_t*)(p.out + (n_to_t(n0 + 8 * h) * DM + 160 * dg + 4 * (tq & 3)));
          }
        }
        stats_get(2 * l + 1, n0, tag, mean, rstd);
        if (tid == 256) { TS(36 + 6 * l); if (l == 0) mbar_arrive(bars + 8 * (B_GO + 1)); }
        off[0] += mean[0]; off[1] += mean[1];
        const float ov[2] = {l ? off[0] : 0.f, l ? off[1] : 0.f};
#pragma unroll
        for (int J = 0; J < 10; J++) {
          if (J + 2 < 10) ldsm4t(gf[J + 2 < 10 ? J + 2 : 0], ga + (J + 2) * 2048);
#pragma unroll
          for (int x = 0; x < 8; x++) {
            const int h = (x >> 1) & 1;
            const uint32_t gwd = gf[J][x >> 1];
            const float t = fmaf(rstd[h], (x & 1) ? bf_hi(gwd) : bf_lo(gwd), 1.f);
            acc[8 * J + x] = fmaf(acc[8 * J + x], t, fmaf(-mean[h], t, ov[h]));
          }
#pragma unroll
          for (int h = 0; h < 2; h++) {
            if (l == 0)
              *(uint2*)(dst[h][(J >> 1) & 1] + (J >> 2) * 20480 + (J & 3) * 256) =
                  make_uint2(pack_bf16(acc[8 * J + 2 * h], acc[8 * J + 2 * h + 1]), pack_bf16(acc[8 * J + 4 + 2 * h], acc[8 * J + 5 + 2 * h]));
            else
              *(float4*)(dst[h][0] + 64 * J) = make_float4(acc[8 * J + 2 * h], acc[8 * J + 2 * h + 1], acc[8 * J + 4 + 2 * h], acc[8 * J + 5 + 2 * h]);
          }
          __syncwarp();
        }
        if (l == 0) {
          bar_sync(3, 128);
          if (tid == 256) { TS(37); st_rel(&g_uflag[(4 * m2 + dg) * 8], tag); TS(38); }
          stats_publish<false>(2, n0, dg, tag, acc);
          mbar_wait(bars + 8 * (B_G1FULL + 11));
          stat_table(T1, tag, 1, w);
          if (tid == 256) TS(27);
          stats_get(2, n0, tag, mean, rstd);
          off[0] += mean[0]; off[1] += mean[1];
          mbar_wait(bars + 8 * (B_HST + 3));
          dskip_init<false>(acc, mean, rstd);
        } else {
          if (tid == 256) {
            TS(43);
            if (m2 == 31 && dg == 3) asm volatile("st.relaxed.gpu.global.u32 [%0], %1;" ::"l"(g_epoch), "r"(tag + 1) : "memory");
          }
        }
      }
    }
  }
}

typedef CUresult (*EncFn)(CUtensorMap*, CUtensorMapDataType, cuuint32_t, void*, const cuuint64_t*, const cuuint64_t*,
                          const cuuint32_t*, const cuuint32_t*, CUtensorMapInterleave, CUtensorMapSwizzle,
                          CUtensorMapL2promotion, CUtensorMapFloatOOBfill);

void encode(EncFn fn, CUtensorMap* m, const void* ptr, int rank, const cuuint64_t* dims, const cuuint64_t* strides, const cuuint32_t* box,
            CUtensorMapSwizzle swz = CU_TENSOR_MAP_SWIZZLE_128B) {
  cuuint32_t es[5] = {1, 1, 1, 1, 1};
  fn(m, CU_TENSOR_MAP_DATA_TYPE_BFLOAT16, rank, (void*)ptr, dims, strides, box, es, CU_TENSOR_MAP_INTERLEAVE_NONE,
     swz, (CUtensorMapL2promotion)(swz == CU_TENSOR_MAP_SWIZZLE_128B ? PROM_A : PROM_B), CU_TENSOR_MAP_FLOAT_OOB_FILL_NONE);
}

}

extern "C" void kernel_launch(void* const* d_in, const int* in_sizes, int n_in, void* d_out, int out_size) {
  (void)in_sizes; (void)n_in; (void)out_size;
  Params p;
  typedef const __nv_bfloat16* BP;
  p.x = (BP)d_in[0]; p.lre = (BP)d_in[1]; p.lim = (BP)d_in[2]; p.bre = (BP)d_in[3]; p.bim = (BP)d_in[4];
  p.cre = (BP)d_in[5]; p.cim = (BP)d_in[6]; p.logdt = (BP)d_in[7]; p.dskip = (BP)d_in[8];
  p.k = (BP)d_in[10]; p.v = (BP)d_in[11]; p.shiftk = (BP)d_in[12]; p.ssmk = (BP)d_in[13]; p.ssmD = (BP)d_in[14];
  p.out = (float*)d_out;
  for (int sm = 0; sm < 132; sm++) {
    const int tpc = sm >> 1, side = sm & 1;
    int gpc, gi;
    if (tpc < 32) { gpc = tpc & 7; gi = tpc >> 3; }
    else if (tpc < 60) { gpc = 1 + (tpc - 32) % 7; gi = 4 + (tpc - 32) / 7; }
    else if (tpc < 62) { gpc = tpc - 54; gi = 8; }
    else { gpc = 0; gi = tpc - 58; }
    const int pos = 8 * gpc + gi + (gpc == 7 ? 1 : 0);
    int T1, GP;
    if (pos < 52) { const int hh = pos / 26, x = pos - 26 * hh; T1 = x >> 1; GP = 2 * hh + (x & 1); }
    else { T1 = pos - 52; GP = 4; }
    const int m2 = 8 * (gpc >> 1) + gi, dg = 2 * (gpc & 1) + side;
    p.role[sm] = pos == 65 ? -1 : (T1 | (GP << 4) | (side << 7) | (m2 << 8) | (dg << 14) | ((gi < 8) << 16));
  }
  void* fnp = nullptr;
  cudaDriverEntryPointQueryResult qr;
  cudaGetDriverEntryPoint("cuTensorMapEncodeTiled", &fnp, cudaEnableDefault, &qr);
  EncFn fn = (EncFn)fnp;
  void* gG = nullptr;
  cudaGetSymbolAddress(&gG, g_G);
  const cuuint64_t RB = DM * 2;
  {
    p.swap = p.bim < p.bre;
    const char* lo = (const char*)(p.swap ? p.bim : p.bre); const char* hi = (const char*)(p.swap ? p.bre : p.bim);
    cuuint64_t dims[5] = {640, 8, 2, 8, 10}, st[4] = {RB, (cuuint64_t)(hi - lo), 8 * RB, 64 * RB}; cuuint32_t box[5] = {64, 8, 2, 4, 2};
    encode(fn, &p.mB, lo, 5, dims, st, box);
  }
  {
    cuuint64_t dims[5] = {640, 2, 4, 2, 40}, st[4] = {RB, 4 * RB, 2 * RB, 16 * RB}; cuuint32_t box[5] = {64, 2, 4, 2, 10};
    encode(fn, &p.mCre, p.cre, 5, dims, st, box); encode(fn, &p.mCim, p.cim, 5, dims, st, box);
    cuuint64_t dimg[5] = {2048, 2, 4, 2, 40}, stg[4] = {4096, 4 * 4096, 2 * 4096, 16 * 4096};
    encode(fn, &p.mG, gG, 5, dimg, stg, box);
  }
  {
    cuuint64_t dims[4] = {640, 2, 4, 900}, st[3] = {RB, 40 * RB, 2 * RB}; cuuint32_t box[4] = {64, 2, 4, 20};
    encode(fn, &p.mX, p.x, 4, dims, st, box);
    cuuint64_t diml[4] = {640, 2, 4, 16}, stl[3] = {RB, 32 * RB, 2 * RB};
    encode(fn, &p.mXl, p.x + (size_t)1920 * DM, 4, diml, stl, box);
    cuuint32_t boxt[4] = {160, 2, 4, 4};
    encode(fn, &p.mXt, p.x, 4, dims, st, boxt, CU_TENSOR_MAP_SWIZZLE_NONE);
    encode(fn, &p.mXtl, p.x + (size_t)1920 * DM, 4, diml, stl, boxt, CU_TENSOR_MAP_SWIZZLE_NONE);
    cuuint64_t dk[3] = {640, 2000, 4}, sk[2] = {RB, 16 * RB}; cuuint32_t bk[3] = {32, 19, 4}, bv[3] = {32, 17, 4};
    encode(fn, &p.mK, p.k, 3, dk, sk, bk, CU_TENSOR_MAP_SWIZZLE_NONE);
    encode(fn, &p.mV, p.v, 3, dk, sk, bv, CU_TENSOR_MAP_SWIZZLE_NONE);
  }
  cudaFuncSetAttribute(fused_kernel, cudaFuncAttributeMaxDynamicSharedMemorySize, SMEM_BYTES);
  cudaLaunchConfig_t cfg = {};
  cfg.gridDim = dim3(132); cfg.blockDim = dim3(512); cfg.dynamicSmemBytes = SMEM_BYTES; cfg.stream = cudaStreamPerThread;
  cudaLaunchKernelEx(&cfg, fused_kernel, p);
}
```

```cpp
#include <cuda_runtime.h>
#include <cuda.h>
#include <cuda_bf16.h>
#include <stdint.h>

namespace {

constexpr int SEQ = 2048, DM = 640;
constexpr int NT1 = 13;
#define EXP 0
#define WPF1 1
#define WPF2 2
#define CPOLL 10
#define KV0 5
#define TAP0 2
#define PROM_A 2
#define PROM_B 2
#define XFIRST 0
#define TAPLATE 1
#define PAUSE_K 3
constexpr uint32_t SPIN_LIMIT = 1u << 22;

__device__ __align__(1024) uint8_t g_h[2 * 32 * 20 * 8192];
__device__ __align__(1024) uint8_t g_u[NT1 * 10 * 20480];
__device__ __align__(1024) uint8_t g_kv[DM * 4096];
__device__ __align__(1024) uint8_t g_G[DM * 4096];
__device__ __align__(128) uint4 g_E[2 * NT1 * DM];
__device__ __align__(128) uint4 g_stats[4 * 4 * SEQ];
__device__ __align__(128) uint4 g_sB[DM * 2];
__device__ __align__(128) unsigned g_hflag[2 * NT1 * 2 * 16 * 8];
__device__ __align__(128) unsigned g_uflag[32 * 4 * 8];
__device__ __align__(128) unsigned g_kvflag[4 * 32 * 8];
__device__ __align__(128) unsigned g_gflag[4 * 32 * 8];
__device__ __align__(128) unsigned g_epoch[32] = {1};
#define TS(i) do {} while (0)

struct Params {
  CUtensorMap mB, mCre, mCim, mX, mXl, mG, mK, mV, mXt, mXtl;
  const __nv_bfloat16 *x, *lre, *lim, *bre, *bim, *cre, *cim, *logdt, *dskip, *k, *v, *shiftk, *ssmk, *ssmD;
  float* out;
  int swap;
  int role[132];
};

constexpr uint32_t sb = 1024;
constexpr uint32_t G1_STAGE = 36864, G1_XOFF = 16384;
constexpr int S1 = 4;
constexpr uint32_t XT_OFF = 159744, KS_OFF = 180224, KV_PIECE = 9216;
constexpr uint32_t G2_XB = 8192, G2_WB = 20480, G2_WOFF = 57344, G_OFF = 200704;
constexpr int SX2 = 5;
constexpr uint32_t CV_OFF = KS_OFF, CV_K = 128, CV_PL = 2240, CV_U = CV_K + 4096, CV_B = KV_PIECE;
constexpr uint32_t MISC = 226304;
constexpr uint32_t BAR_OFF = MISC;
constexpr int B_G1FULL = 0, B_G1DONE = 20, B_G2FULL = 40, B_CVFULL = 80  ,
              B_G2DONE = 85, B_GFULL = 125, B_EP = 126, B_H1 = 127  , B_TAPS = 129  ,
              B_GO = 139  , B_PD = 142  , B_PUB = 147,
              B_CVDONE = 148  , B_STAB = 153  , B_XFREE = 155, B_HST = 156  ,
              B_CTAB = 160, B_PREP = 161, B_XT = 162, B_KV = 163  ;
constexpr uint32_t bars = sb + BAR_OFF;
constexpr uint32_t STAB_OFF = MISC + 1344;
constexpr uint32_t CTAB_OFF = STAB_OFF + 1280;
constexpr uint32_t DTAB_OFF = CTAB_OFF + 1536;
constexpr uint32_t EP_OFF = DTAB_OFF + 320;
constexpr uint32_t SO_OFF = EP_OFF + 32;
constexpr uint32_t TAP_OFF = 147456;
constexpr uint32_t SMEM_BYTES = 232448;
static_assert(SO_OFF + 1536 <= SMEM_BYTES, "smem");

__device__ __forceinline__ void trap_if(bool c) { asm volatile("{\n.reg .pred p;\nsetp.ne.u32 p, %0, 0;\n@p trap;\n}\n" ::"r"((uint32_t)c)); }
__device__ __forceinline__ uint32_t smem_u32(const void* p) { return (uint32_t)__cvta_generic_to_shared(p); }
__device__ __forceinline__ void mbar_init(uint32_t bar, int cnt) { asm volatile("mbarrier.init.shared::cta.b64 [%0], %1;" ::"r"(bar), "r"(cnt) : "memory"); }
__device__ __forceinline__ void mbar_expect_tx(uint32_t bar, int bytes) { asm volatile("mbarrier.arrive.expect_tx.shared::cta.b64 _, [%0], %1;" ::"r"(bar), "r"(bytes) : "memory"); }
__device__ __forceinline__ void mbar_arrive(uint32_t bar) { asm volatile("mbarrier.arrive.shared::cta.b64 _, [%0];" ::"r"(bar) : "memory"); }
__device__ __forceinline__ void mbar_wait(uint32_t bar) {
  asm volatile(
      "{\n.reg .pred p;\n.reg .u32 c;\nmov.u32 c, 0;\n"
      "W_%=:\nmbarrier.try_wait.parity.shared::cta.b64 p, [%0], 0;\n@p bra D_%=;\n"
      "add.u32 c, c, 1;\nsetp.lt.u32 p, c, %1;\n@p bra W_%=;\ntrap;\nD_%=:\n}\n" ::"r"(bar), "n"(SPIN_LIMIT) : "memory");
}
__device__ __forceinline__ uint32_t mbar_test(uint32_t bar) {
  uint32_t ok;
  asm volatile("{\n.reg .pred p;\nmbarrier.test_wait.parity.shared::cta.b64 p, [%1], 0;\nselp.u32 %0, 1, 0, p;\n}\n" : "=r"(ok) : "r"(bar) : "memory");
  return ok;
}
__device__ __forceinline__ void tma3(uint32_t dst, const CUtensorMap* m, int c0, int c1, int c2, uint32_t bar) {
  asm volatile("cp.async.bulk.tensor.3d.shared::cluster.global.mbarrier::complete_tx::bytes [%0], [%1, {%3,%4,%5}], [%2];"
               ::"r"(dst), "l"(m), "r"(bar), "r"(c0), "r"(c1), "r"(c2) : "memory");
}
__device__ __forceinline__ void tma4(uint32_t dst, const CUtensorMap* m, int c0, int c1, int c2, int c3, uint32_t bar) {
  asm volatile("cp.async.bulk.tensor.4d.shared::cluster.global.mbarrier::complete_tx::bytes [%0], [%1, {%3,%4,%5,%6}], [%2];"
               ::"r"(dst), "l"(m), "r"(bar), "r"(c0), "r"(c1), "r"(c2), "r"(c3) : "memory");
}
__device__ __forceinline__ void tma5(uint32_t dst, const CUtensorMap* m, int c0, int c1, int c2, int c3, int c4, uint32_t bar) {
  asm volatile("cp.async.bulk.tensor.5d.shared::cluster.global.mbarrier::complete_tx::bytes [%0], [%1, {%3,%4,%5,%6,%7}], [%2];"
               ::"r"(dst), "l"(m), "r"(bar), "r"(c0), "r"(c1), "r"(c2), "r"(c3), "r"(c4) : "memory");
}
__device__ __forceinline__ void bulk_g2s(uint32_t dst, const void* src, int bytes, uint32_t bar) {
  asm volatile("cp.async.bulk.shared::cluster.global.mbarrier::complete_tx::bytes [%0], [%1], %2, [%3];"
               ::"r"(dst), "l"(src), "r"(bytes), "r"(bar) : "memory");
}
__device__ __forceinline__ void bulk_s2g(void* dst, uint32_t src, int bytes) {
  asm volatile("cp.async.bulk.global.shared::cta.bulk_group [%0], [%1], %2;" ::"l"(dst), "r"(src), "r"(bytes) : "memory");
}
__device__ __forceinline__ void l2_prefetch(const void* src, int bytes) {
  asm volatile("cp.async.bulk.prefetch.L2.global [%0], %1;" ::"l"(src), "r"(bytes) : "memory");
}
__device__ __forceinline__ void wgmma_fence() { asm volatile("wgmma.fence.sync.aligned;" ::: "memory"); }
__device__ __forceinline__ void wgmma_commit() { asm volatile("wgmma.commit_group.sync.aligned;" ::: "memory"); }
template <int N> __device__ __forceinline__ void wgmma_wait() { asm volatile("wgmma.wait_group.sync.aligned %0;" ::"n"(N) : "memory"); }
__host__ __device__ constexpr uint32_t desc_lo(uint32_t addr, uint32_t lbo) { return ((addr & 0x3FFFF) >> 4) | ((lbo >> 4) << 16); }
__host__ __device__ constexpr uint32_t desc_hi(uint32_t sbo, uint32_t swz) { return (sbo >> 4) | (swz << 30); }
__device__ __forceinline__ void bar_sync(int id, int n) { asm volatile("bar.sync %0, %1;" ::"r"(id), "r"(n) : "memory"); }
__device__ __forceinline__ uint32_t lds32(uint32_t a) { uint32_t v; asm volatile("ld.shared.u32 %0, [%1];" : "=r"(v) : "r"(a) : "memory"); return v; }
__device__ __forceinline__ float2 lds64f(uint32_t a) { float2 v; asm volatile("ld.shared.v2.f32 {%0,%1}, [%2];" : "=f"(v.x), "=f"(v.y) : "r"(a) : "memory"); return v; }
__device__ __forceinline__ float4 lds128f(uint32_t a) { float4 v; asm volatile("ld.shared.v4.f32 {%0,%1,%2,%3}, [%4];" : "=f"(v.x), "=f"(v.y), "=f"(v.z), "=f"(v.w) : "r"(a) : "memory"); return v; }
__device__ __forceinline__ void ldsm4t(uint32_t (&r)[4], uint32_t a) {
  asm volatile("ldmatrix.sync.aligned.m8n8.x4.trans.shared.b16 {%0,%1,%2,%3}, [%4];" : "=r"(r[0]), "=r"(r[1]), "=r"(r[2]), "=r"(r[3]) : "r"(a) : "memory");
}
__device__ __forceinline__ uint4 ldv128(const void* a) { uint4 v; asm volatile("ld.global.nc.v4.u32 {%0,%1,%2,%3}, [%4];" : "=r"(v.x), "=r"(v.y), "=r"(v.z), "=r"(v.w) : "l"(a) : "memory"); return v; }
__device__ __forceinline__ uint2 ldv64(const void* a) { uint2 v; asm volatile("ld.global.nc.v2.u32 {%0,%1}, [%2];" : "=r"(v.x), "=r"(v.y) : "l"(a) : "memory"); return v; }
__device__ __forceinline__ uint32_t ldv16(const void* a) { uint32_t v; asm volatile("ld.global.nc.u16 %0, [%1];" : "=r"(v) : "l"(a) : "memory"); return v; }
__device__ __forceinline__ void sts128(uint32_t a, uint4 v) { asm volatile("st.shared.v4.u32 [%0], {%1,%2,%3,%4};" ::"r"(a), "r"(v.x), "r"(v.y), "r"(v.z), "r"(v.w) : "memory"); }
__device__ __forceinline__ void sts32(uint32_t a, uint32_t v) { asm volatile("st.shared.u32 [%0], %1;" ::"r"(a), "r"(v) : "memory"); }
__device__ __forceinline__ void sts64f(uint32_t a, float x, float y) { asm volatile("st.shared.v2.f32 [%0], {%1,%2};" ::"r"(a), "f"(x), "f"(y) : "memory"); }
__device__ __forceinline__ void st_rel(unsigned* p, unsigned v) { asm volatile("st.release.gpu.global.u32 [%0], %1;" ::"l"(p), "r"(v) : "memory"); }
__device__ __forceinline__ void fence_async_global() { asm volatile("fence.proxy.async.global;" ::: "memory"); }
__device__ __forceinline__ void fence_async_smem() { asm volatile("fence.proxy.async.shared::cta;" ::: "memory"); }
__device__ __forceinline__ void rec_st(uint4* p, float a, float b, unsigned tag) {
  asm volatile("{\n.reg .b128 t;\n.reg .b64 lo, hi;\nmov.b64 lo, {%1,%2};\nmov.b64 hi, {%3,%3};\nmov.b128 t, {lo,hi};\n"
               "st.relaxed.gpu.global.b128 [%0], t;\n}\n" ::"l"(p), "r"(__float_as_uint(a)), "r"(__float_as_uint(b)), "r"(tag) : "memory");
}
__device__ __forceinline__ unsigned rec_ld(const uint4* p, float& a, float& b) {
  unsigned x, y, t;
  asm volatile("{\n.reg .b128 t;\n.reg .b64 lo, hi;\n.reg .b32 u;\nld.relaxed.gpu.global.b128 t, [%3];\nmov.b128 {lo,hi}, t;\n"
               "mov.b64 {%0,%1}, lo;\nmov.b64 {%2,u}, hi;\n}\n" : "=r"(x), "=r"(y), "=r"(t) : "l"(p) : "memory");
  a = __uint_as_float(x); b = __uint_as_float(y);
  return t;
}
__device__ __forceinline__ void rec_poll(const uint4* p, unsigned tag, float& a, float& b) {
  uint32_t it = 0;
  while (!__all_sync(0xffffffffu, rec_ld(p, a, b) == tag)) { trap_if(++it > SPIN_LIMIT); }
}
__device__ __forceinline__ unsigned ld_rlx(const unsigned* p) { unsigned v; asm volatile("ld.relaxed.gpu.global.u32 %0, [%1];" : "=r"(v) : "l"(p) : "memory"); return v; }
__device__ __forceinline__ void flag_poll(const unsigned* p, unsigned target) {
  uint32_t it = 0;
  while (!__all_sync(0xffffffffu, (int)(ld_rlx(p) - target) >= 0)) { trap_if(++it > SPIN_LIMIT); }
  asm volatile("fence.acquire.gpu;" ::: "memory");
}
__device__ __forceinline__ uint32_t pack_bf16(float lo, float hi) {
  uint32_t r; asm("cvt.rn.bf16x2.f32 %0, %1, %2;" : "=r"(r) : "f"(hi), "f"(lo)); return r;
}
__device__ __forceinline__ float bf_lo(uint32_t w) { return __uint_as_float(w << 16); }
__device__ __forceinline__ float bf_hi(uint32_t w) { return __uint_as_float(w & 0xffff0000u); }
__device__ __forceinline__ uint32_t hmul2(uint32_t a, uint32_t b) {
  __nv_bfloat162 r = __hmul2_rn(*(__nv_bfloat162*)&a, *(__nv_bfloat162*)&b); return *(uint32_t*)&r;
}
__device__ __forceinline__ uint32_t hadd2(uint32_t a, uint32_t b) {
  __nv_bfloat162 r = __hadd2_rn(*(__nv_bfloat162*)&a, *(__nv_bfloat162*)&b); return *(uint32_t*)&r;
}
__device__ __forceinline__ float2 cmul(float2 a, float2 b) { return make_float2(a.x * b.x - a.y * b.y, a.x * b.y + a.y * b.x); }
__device__ __forceinline__ float2 cfma(float2 a, float2 b, float2 c) {
  return make_float2(fmaf(a.x, b.x, fmaf(-a.y, b.y, c.x)), fmaf(a.x, b.y, fmaf(a.y, b.x, c.y)));
}
template <int N> __device__ __forceinline__ void fence_regs(float (&a)[N]) {
#pragma unroll
  for (int i = 0; i < N; i++) asm volatile("" : "+f"(a[i])::"memory");
}
__device__ __forceinline__ bool elect_one() {
  uint32_t e; asm volatile("{\n.reg .pred P;\nelect.sync _|P, 0xffffffff;\nselp.u32 %0, 1, 0, P;\n}\n" : "=r"(e)); return e != 0;
}
__device__ __forceinline__ int tid_opaque() { int t; asm volatile("mov.u32 %0, %%tid.x;" : "=r"(t)); return t; }
struct Role { int T1, GP, side, m2, dg, cch0; bool last, has2; };
__device__ __forceinline__ Role unpack_role(int x) {
  Role r; r.T1 = x & 15; r.GP = (x >> 4) & 7; r.side = (x >> 7) & 1; r.m2 = (x >> 8) & 63; r.dg = (x >> 14) & 3;
  r.has2 = (x >> 16) & 1; r.last = r.T1 == NT1 - 1; r.cch0 = 160 * r.dg + r.m2; return r;
}
__device__ __forceinline__ Role fresh_role(int x) { asm volatile("" : "+r"(x)); return unpack_role(__shfl_sync(0xffffffffu, x, 0)); }
#define ROLE(x) const Role R_ = fresh_role(x); const int T1 = R_.T1, GP = R_.GP, side = R_.side, m2 = R_.m2, dg = R_.dg, cch0 = R_.cch0; \
  const bool last = R_.last, has2 = R_.has2; (void)T1; (void)GP; (void)side; (void)m2; (void)dg; (void)cch0; (void)last; (void)has2;
__device__ __forceinline__ int n_to_t(int n) {
  int T = n / 160, nl = n - T * 160;
  int L = (T == NT1 - 1) ? 32 : 40;
  return T * 160 + L * ((nl & 7) >> 1) + 2 * (nl >> 3) + (nl & 1);
}

template<int TA> __device__ __forceinline__ void wgmma_n160(float (&d)[80], uint32_t alo, uint32_t ahi, uint32_t blo, uint32_t bhi){
  asm volatile("{\n.reg .b64 da, db;\nmov.b64 da, {%80,%81};\nmov.b64 db, {%82,%83};\n"
    "wgmma.mma_async.sync.aligned.m64n160k16.f32.bf16.bf16 {%0, %1, %2, %3, %4, %5, %6, %7, %8, %9, %10, %11, %12, %13, %14, %15, %16, %17, %18, %19, %20, %21, %22, %23, %24, %25, %26, %27, %28, %29, %30, %31, %32, %33, %34, %35, %36, %37, %38, %39, %40, %41, %42, %43, %44, %45, %46, %47, %48, %49, %50, %51, %52, %53, %54, %55, %56, %57, %58, %59, %60, %61, %62, %63, %64, %65, %66, %67, %68, %69, %70, %71, %72, %73, %74, %75, %76, %77, %78, %79}, da, db, 1, 1, 1, %84, 0;\n}\n"
    : "+f"(d[0]), "+f"(d[1]), "+f"(d[2]), "+f"(d[3]), "+f"(d[4]), "+f"(d[5]), "+f"(d[6]), "+f"(d[7]), "+f"(d[8]), "+f"(d[9]), "+f"(d[10]), "+f"(d[11]), "+f"(d[12]), "+f"(d[13]), "+f"(d[14]), "+f"(d[15]), "+f"(d[16]), "+f"(d[17]), "+f"(d[18]), "+f"(d[19]), "+f"(d[20]), "+f"(d[21]), "+f"(d[22]), "+f"(d[23]), "+f"(d[24]), "+f"(d[25]), "+f"(d[26]), "+f"(d[27]), "+f"(d[28]), "+f"(d[29]), "+f"(d[30]), "+f"(d[31]), "+f"(d[32]), "+f"(d[33]), "+f"(d[34]), "+f"(d[35]), "+f"(d[36]), "+f"(d[37]), "+f"(d[38]), "+f"(d[39]), "+f"(d[40]), "+f"(d[41]), "+f"(d[42]), "+f"(d[43]), "+f"(d[44]), "+f"(d[45]), "+f"(d[46]), "+f"(d[47]), "+f"(d[48]), "+f"(d[49]), "+f"(d[50]), "+f"(d[51]), "+f"(d[52]), "+f"(d[53]), "+f"(d[54]), "+f"(d[55]), "+f"(d[56]), "+f"(d[57]), "+f"(d[58]), "+f"(d[59]), "+f"(d[60]), "+f"(d[61]), "+f"(d[62]), "+f"(d[63]), "+f"(d[64]), "+f"(d[65]), "+f"(d[66]), "+f"(d[67]), "+f"(d[68]), "+f"(d[69]), "+f"(d[70]), "+f"(d[71]), "+f"(d[72]), "+f"(d[73]), "+f"(d[74]), "+f"(d[75]), "+f"(d[76]), "+f"(d[77]), "+f"(d[78]), "+f"(d[79])
    : "r"(alo), "r"(ahi), "r"(blo), "r"(bhi), "n"(TA));
}
template<int N> __device__ __forceinline__ void wgmma_rs_hi(float (&d)[64], uint32_t a0, uint32_t a1, uint32_t a2, uint32_t a3, uint32_t blo);
template<> __device__ __forceinline__ void wgmma_rs_hi<16>(float (&d)[64], uint32_t a0, uint32_t a1, uint32_t a2, uint32_t a3, uint32_t blo){
  asm volatile("{\n.reg .b64 db;\nmov.b64 db, {%12,8};\nwgmma.mma_async.sync.aligned.m64n16k16.f32.bf16.bf16 {%0, %1, %2, %3, %4, %5, %6, %7}, {%8,%9,%10,%11}, db, 1, 1, 1, 0;\n}\n"
    : "+f"(d[56]), "+f"(d[57]), "+f"(d[58]), "+f"(d[59]), "+f"(d[60]), "+f"(d[61]), "+f"(d[62]), "+f"(d[63])
    : "r"(a0), "r"(a1), "r"(a2), "r"(a3), "r"(blo));
}
template<> __device__ __forceinline__ void wgmma_rs_hi<32>(float (&d)[64], uint32_t a0, uint32_t a1, uint32_t a2, uint32_t a3, uint32_t blo){
  asm volatile("{\n.reg .b64 db;\nmov.b64 db, {%20,8};\nwgmma.mma_async.sync.aligned.m64n32k16.f32.bf16.bf16 {%0, %1, %2, %3, %4, %5, %6, %7, %8, %9, %10, %11, %12, %13, %14, %15}, {%16,%17,%18,%19}, db, 1, 1, 1, 0;\n}\n"
    : "+f"(d[48]), "+f"(d[49]), "+f"(d[50]), "+f"(d[51]), "+f"(d[52]), "+f"(d[53]), "+f"(d[54]), "+f"(d[55]), "+f"(d[56]), "+f"(d[57]), "+f"(d[58]), "+f"(d[59]), "+f"(d[60]), "+f"(d[61]), "+f"(d[62]), "+f"(d[63])
    : "r"(a0), "r"(a1), "r"(a2), "r"(a3), "r"(blo));
}
template<> __device__ __forceinline__ void wgmma_rs_hi<48>(float (&d)[64], uint32_t a0, uint32_t a1, uint32_t a2, uint32_t a3, uint32_t blo){
  asm volatile("{\n.reg .b64 db;\nmov.b64 db, {%28,8};\nwgmma.mma_async.sync.aligned.m64n48k16.f32.bf16.bf16 {%0, %1, %2, %3, %4, %5, %6, %7, %8, %9, %10, %11, %12, %13, %14, %15, %16, %17, %18, %19, %20, %21, %22, %23}, {%24,%25,%26,%27}, db, 1, 1, 1, 0;\n}\n"
    : "+f"(d[40]), "+f"(d[41]), "+f"(d[42]), "+f"(d[43]), "+f"(d[44]), "+f"(d[45]), "+f"(d[46]), "+f"(d[47]), "+f"(d[48]), "+f"(d[49]), "+f"(d[50]), "+f"(d[51]), "+f"(d[52]), "+f"(d[53]), "+f"(d[54]), "+f"(d[55]), "+f"(d[56]), "+f"(d[57]), "+f"(d[58]), "+f"(d[59]), "+f"(d[60]), "+f"(d[61]), "+f"(d[62]), "+f"(d[63])
    : "r"(a0), "r"(a1), "r"(a2), "r"(a3), "r"(blo));
}
template<> __device__ __forceinline__ void wgmma_rs_hi<64>(float (&d)[64], uint32_t a0, uint32_t a1, uint32_t a2, uint32_t a3, uint32_t blo){
  asm volatile("{\n.reg .b64 db;\nmov.b64 db, {%36,8};\nwgmma.mma_async.sync.aligned.m64n64k16.f32.bf16.bf16 {%0, %1, %2, %3, %4, %5, %6, %7, %8, %9, %10, %11, %12, %13, %14, %15, %16, %17, %18, %19, %20, %21, %22, %23, %24, %25, %26, %27, %28, %29, %30, %31}, {%32,%33,%34,%35}, db, 1, 1, 1, 0;\n}\n"
    : "+f"(d[32]), "+f"(d[33]), "+f"(d[34]), "+f"(d[35]), "+f"(d[36]), "+f"(d[37]), "+f"(d[38]), "+f"(d[39]), "+f"(d[40]), "+f"(d[41]), "+f"(d[42]), "+f"(d[43]), "+f"(d[44]), "+f"(d[45]), "+f"(d[46]), "+f"(d[47]), "+f"(d[48]), "+f"(d[49]), "+f"(d[50]), "+f"(d[51]), "+f"(d[52]), "+f"(d[53]), "+f"(d[54]), "+f"(d[55]), "+f"(d[56]), "+f"(d[57]), "+f"(d[58]), "+f"(d[59]), "+f"(d[60]), "+f"(d[61]), "+f"(d[62]), "+f"(d[63])
    : "r"(a0), "r"(a1), "r"(a2), "r"(a3), "r"(blo));
}
template<> __device__ __forceinline__ void wgmma_rs_hi<80>(float (&d)[64], uint32_t a0, uint32_t a1, uint32_t a2, uint32_t a3, uint32_t blo){
  asm volatile("{\n.reg .b64 db;\nmov.b64 db, {%44,8};\nwgmma.mma_async.sync.aligned.m64n80k16.f32.bf16.bf16 {%0, %1, %2, %3, %4, %5, %6, %7, %8, %9, %10, %11, %12, %13, %14, %15, %16, %17, %18, %19, %20, %21, %22, %23, %24, %25, %26, %27, %28, %29, %30, %31, %32, %33, %34, %35, %36, %37, %38, %39}, {%40,%41,%42,%43}, db, 1, 1, 1, 0;\n}\n"
    : "+f"(d[24]), "+f"(d[25]), "+f"(d[26]), "+f"(d[27]), "+f"(d[28]), "+f"(d[29]), "+f"(d[30]), "+f"(d[31]), "+f"(d[32]), "+f"(d[33]), "+f"(d[34]), "+f"(d[35]), "+f"(d[36]), "+f"(d[37]), "+f"(d[38]), "+f"(d[39]), "+f"(d[40]), "+f"(d[41]), "+f"(d[42]), "+f"(d[43]), "+f"(d[44]), "+f"(d[45]), "+f"(d[46]), "+f"(d[47]), "+f"(d[48]), "+f"(d[49]), "+f"(d[50]), "+f"(d[51]), "+f"(d[52]), "+f"(d[53]), "+f"(d[54]), "+f"(d[55]), "+f"(d[56]), "+f"(d[57]), "+f"(d[58]), "+f"(d[59]), "+f"(d[60]), "+f"(d[61]), "+f"(d[62]), "+f"(d[63])
    : "r"(a0), "r"(a1), "r"(a2), "r"(a3), "r"(blo));
}
template<> __device__ __forceinline__ void wgmma_rs_hi<96>(float (&d)[64], uint32_t a0, uint32_t a1, uint32_t a2, uint32_t a3, uint32_t blo){
  asm volatile("{\n.reg .b64 db;\nmov.b64 db, {%52,8};\nwgmma.mma_async.sync.aligned.m64n96k16.f32.bf16.bf16 {%0, %1, %2, %3, %4, %5, %6, %7, %8, %9, %10, %11, %12, %13, %14, %15, %16, %17, %18, %19, %20, %21, %22, %23, %24, %25, %26, %27, %28, %29, %30, %31, %32, %33, %34, %35, %36, %37, %38, %39, %40, %41, %42, %43, %44, %45, %46, %47}, {%48,%49,%50,%51}, db, 1, 1, 1, 0;\n}\n"
    : "+f"(d[16]), "+f"(d[17]), "+f"(d[18]), "+f"(d[19]), "+f"(d[20]), "+f"(d[21]), "+f"(d[22]), "+f"(d[23]), "+f"(d[24]), "+f"(d[25]), "+f"(d[26]), "+f"(d[27]), "+f"(d[28]), "+f"(d[29]), "+f"(d[30]), "+f"(d[31]), "+f"(d[32]), "+f"(d[33]), "+f"(d[34]), "+f"(d[35]), "+f"(d[36]), "+f"(d[37]), "+f"(d[38]), "+f"(d[39]), "+f"(d[40]), "+f"(d[41]), "+f"(d[42]), "+f"(d[43]), "+f"(d[44]), "+f"(d[45]), "+f"(d[46]), "+f"(d[47]), "+f"(d[48]), "+f"(d[49]), "+f"(d[50]), "+f"(d[51]), "+f"(d[52]), "+f"(d[53]), "+f"(d[54]), "+f"(d[55]), "+f"(d[56]), "+f"(d[57]), "+f"(d[58]), "+f"(d[59]), "+f"(d[60]), "+f"(d[61]), "+f"(d[62]), "+f"(d[63])
    : "r"(a0), "r"(a1), "r"(a2), "r"(a3), "r"(blo));
}
template<> __device__ __forceinline__ void wgmma_rs_hi<112>(float (&d)[64], uint32_t a0, uint32_t a1, uint32_t a2, uint32_t a3, uint32_t blo){
  asm volatile("{\n.reg .b64 db;\nmov.b64 db, {%60,8};\nwgmma.mma_async.sync.aligned.m64n112k16.f32.bf16.bf16 {%0, %1, %2, %3, %4, %5, %6, %7, %8, %9, %10, %11, %12, %13, %14, %15, %16, %17, %18, %19, %20, %21, %22, %23, %24, %25, %26, %27, %28, %29, %30, %31, %32, %33, %34, %35, %36, %37, %38, %39, %40, %41, %42, %43, %44, %45, %46, %47, %48, %49, %50, %51, %52, %53, %54, %55}, {%56,%57,%58,%59}, db, 1, 1, 1, 0;\n}\n"
    : "+f"(d[8]), "+f"(d[9]), "+f"(d[10]), "+f"(d[11]), "+f"(d[12]), "+f"(d[13]), "+f"(d[14]), "+f"(d[15]), "+f"(d[16]), "+f"(d[17]), "+f"(d[18]), "+f"(d[19]), "+f"(d[20]), "+f"(d[21]), "+f"(d[22]), "+f"(d[23]), "+f"(d[24]), "+f"(d[25]), "+f"(d[26]), "+f"(d[27]), "+f"(d[28]), "+f"(d[29]), "+f"(d[30]), "+f"(d[31]), "+f"(d[32]), "+f"(d[33]), "+f"(d[34]), "+f"(d[35]), "+f"(d[36]), "+f"(d[37]), "+f"(d[38]), "+f"(d[39]), "+f"(d[40]), "+f"(d[41]), "+f"(d[42]), "+f"(d[43]), "+f"(d[44]), "+f"(d[45]), "+f"(d[46]), "+f"(d[47]), "+f"(d[48]), "+f"(d[49]), "+f"(d[50]), "+f"(d[51]), "+f"(d[52]), "+f"(d[53]), "+f"(d[54]), "+f"(d[55]), "+f"(d[56]), "+f"(d[57]), "+f"(d[58]), "+f"(d[59]), "+f"(d[60]), "+f"(d[61]), "+f"(d[62]), "+f"(d[63])
    : "r"(a0), "r"(a1), "r"(a2), "r"(a3), "r"(blo));
}
template<> __device__ __forceinline__ void wgmma_rs_hi<128>(float (&d)[64], uint32_t a0, uint32_t a1, uint32_t a2, uint32_t a3, uint32_t blo){
  asm volatile("{\n.reg .b64 db;\nmov.b64 db, {%68,8};\nwgmma.mma_async.sync.aligned.m64n128k16.f32.bf16.bf16 {%0, %1, %2, %3, %4, %5, %6, %7, %8, %9, %10, %11, %12, %13, %14, %15, %16, %17, %18, %19, %20, %21, %22, %23, %24, %25, %26, %27, %28, %29, %30, %31, %32, %33, %34, %35, %36, %37, %38, %39, %40, %41, %42, %43, %44, %45, %46, %47, %48, %49, %50, %51, %52, %53, %54, %55, %56, %57, %58, %59, %60, %61, %62, %63}, {%64,%65,%66,%67}, db, 1, 1, 1, 0;\n}\n"
    : "+f"(d[0]), "+f"(d[1]), "+f"(d[2]), "+f"(d[3]), "+f"(d[4]), "+f"(d[5]), "+f"(d[6]), "+f"(d[7]), "+f"(d[8]), "+f"(d[9]), "+f"(d[10]), "+f"(d[11]), "+f"(d[12]), "+f"(d[13]), "+f"(d[14]), "+f"(d[15]), "+f"(d[16]), "+f"(d[17]), "+f"(d[18]), "+f"(d[19]), "+f"(d[20]), "+f"(d[21]), "+f"(d[22]), "+f"(d[23]), "+f"(d[24]), "+f"(d[25]), "+f"(d[26]), "+f"(d[27]), "+f"(d[28]), "+f"(d[29]), "+f"(d[30]), "+f"(d[31]), "+f"(d[32]), "+f"(d[33]), "+f"(d[34]), "+f"(d[35]), "+f"(d[36]), "+f"(d[37]), "+f"(d[38]), "+f"(d[39]), "+f"(d[40]), "+f"(d[41]), "+f"(d[42]), "+f"(d[43]), "+f"(d[44]), "+f"(d[45]), "+f"(d[46]), "+f"(d[47]), "+f"(d[48]), "+f"(d[49]), "+f"(d[50]), "+f"(d[51]), "+f"(d[52]), "+f"(d[53]), "+f"(d[54]), "+f"(d[55]), "+f"(d[56]), "+f"(d[57]), "+f"(d[58]), "+f"(d[59]), "+f"(d[60]), "+f"(d[61]), "+f"(d[62]), "+f"(d[63])
    : "r"(a0), "r"(a1), "r"(a2), "r"(a3), "r"(blo));
}

__device__ __forceinline__ float shfl_sel(float a, float b, bool p, int src) {
  float r;
  asm volatile("{\n.reg .pred P;\n.reg .f32 t;\nsetp.ne.u32 P, %3, 0;\nselp.f32 t, %1, %2, P;\nshfl.sync.idx.b32 %0, t, %4, 0x1f, 0xffffffff;\n}\n"
               : "=f"(r) : "f"(a), "f"(b), "r"((uint32_t)p), "r"(src));
  return r;
}
struct CvCtx {
  uint32_t koff, zero, so[3];
  int srcA, srcB;
  bool wrapA, s3, kodd;
};
struct CvPipe { float Ep[2], keep[2], send[2]; };
template <int LO> __device__ __forceinline__ void cv_copy(float (&acc)[64]) {
#pragma unroll
  for (int i = LO; i < 64; i++) { float t; asm volatile("mov.b32 %0, %1;" : "=f"(t) : "f"(acc[i]) : "memory"); acc[i] = t; }
}
template <int G> __device__ __forceinline__ void cv_raw(uint32_t (&A)[4][4], uint32_t kaddr) {
#pragma unroll
  for (int i = 0; i < 4; i++) {
    const uint32_t a = kaddr + (4 * G + i) * 128;
    A[i][0] = lds32(a); A[i][1] = lds32(a + 4); A[i][3] = lds32(a + 8);
  }
}
__device__ __forceinline__ void cv_form(uint32_t (&A)[4][4], uint32_t sel) {
#pragma unroll
  for (int i = 0; i < 4; i++) {
    asm volatile("prmt.b32 %0, %0, %1, %2;" : "+r"(A[i][0]) : "r"(A[i][1]), "r"(sel));
    asm volatile("prmt.b32 %0, %1, %2, %3;" : "=r"(A[i][2]) : "r"(A[i][1]), "r"(A[i][3]), "r"(sel));
  }
}
#define CVV 2
template <int G> __device__ __forceinline__ void cv_step(float (&acc)[64], uint32_t (&A)[4][4], CvPipe& s, const CvCtx& c, uint32_t cb, uint32_t stg) {
  constexpr int JA = G - 1, JB = G - 2, NH = CVV == 1 ? 4 : (CVV == 3 ? 2 : 1);
  const uint32_t db0 = desc_lo(cb + CV_U + 192, CV_PL);
  uint32_t B[4][4];
  float ra[4], rb[2];
  if constexpr (G < 8) {
    wgmma_fence();
#pragma unroll
    for (int i = 0; i < NH; i++) wgmma_rs_hi<128 - 16 * (G & 7)>(acc, A[i][0], A[i][1], A[i][2], A[i][3], db0 - 4 * i);
    wgmma_commit();
    __syncwarp();
  }
  if constexpr (JA >= 0 && JA < 8) {
#pragma unroll
    for (int x = 0; x < 4; x++) {
      const int i = 8 * JA + 4 * (x >> 1) + 2 * (x & 1) + 1;
      ra[x] = shfl_sel(i >= 4 ? acc[i >= 4 ? i - 4 : 0] : 0.f, acc[i], c.wrapA, c.srcA);
    }
  }
  if constexpr (JB >= 0) {
#pragma unroll
    for (int h = 0; h < 2; h++) rb[h] = __shfl_sync(0xffffffffu, s.send[h], c.srcB);
  }
  if constexpr (G < 7) cv_raw<G + 1>(B, cb + c.koff);
  uint32_t z = 0;
  if constexpr (G < 8 && NH < 4) {
    __syncwarp();
    wgmma_fence();
#pragma unroll
    for (int i = NH; i < 4; i++) wgmma_rs_hi<128 - 16 * (G & 7)>(acc, A[i][0], A[i][1], A[i][2], A[i][3], db0 - 4 * i);
    wgmma_commit();
    asm volatile("mov.u32 %0, %%clock;" : "=r"(z)::"memory");
    z &= c.zero;
  }
  const float one = __uint_as_float(0x3f800000u | z);
  if constexpr (G < 7) cv_form(B, 0x5432u | z);
  if constexpr (JB >= 0) sts32(stg + ((c.so[JB / 3] >> (10 * (JB % 3))) & 0xffc), pack_bf16(fmaf(rb[0], one, s.keep[0]), fmaf(rb[1], one, s.keep[1])));
  if constexpr (JA >= 0 && JA < 8) {
#pragma unroll
    for (int h = 0; h < 2; h++) {
      const float ev = fmaf(ra[h], one, acc[8 * JA + 2 * h]), od = fmaf(ra[2 + h], one, acc[8 * JA + 4 + 2 * h]);
      s.send[h] = c.kodd ? ev : (c.s3 ? s.Ep[h] : od);
      s.keep[h] = c.kodd ? od : ev;
      s.Ep[h] = od;
    }
  }
  if constexpr (G < 8) { __syncwarp(); wgmma_wait<0>(); cv_copy<8 * (G & 7)>(acc); }
  if constexpr (G < 9) cv_step<G + 1>(acc, B, s, c, cb, stg);
}
__device__ __forceinline__ uint32_t cv_stage(int slot) { return sb + (slot < 4 ? 40960 + slot * 4096 : CV_OFF + CV_K); }
__device__ __forceinline__ void cv_setup(CvCtx& c) {
  const int tid = tid_opaque() & 127, w = tid >> 5, lane = tid & 31, r = lane >> 2, q = lane & 3;
  const int i0 = (r >> 1) & 1, i1 = r >> 2;
  c.koff = CV_K - 32 + 4 * (8 * (r >> 1) + 2 * w + (r & 1) + 2 * q);
  c.srcA = i0 ? lane - 8 : lane + 8 - q + ((q + 3) & 3);
  c.wrapA = i0 && q == 3;
  c.srcB = i1 == 0 ? (lane - q + 16 + ((q + 3) & 3)) : (lane - q - 16 + ((q + 1) & 3));
  c.s3 = (i1 == 1 && q == 3); c.kodd = (i1 == 1 && q < 3);
  c.zero = lds32(sb + EP_OFF + 24);
#pragma unroll
  for (int i = 0; i < 3; i++) c.so[i] = lds32(sb + SO_OFF + 512 * i + 4 * tid);
}
__device__ __forceinline__ void cv_table() {
  const int tid = tid_opaque() & 127, r = (tid & 31) >> 2, q = tid & 3;
  int t = 16 * (2 * (r < 4 ? q : 4 + ((q + 1) & 3)) + ((r >> 1) & 1)) + 4 * (tid >> 5) + 2 * (r & 1);
#pragma unroll 1
  for (int i = 0; i < 3; i++) {
    uint32_t v = 0;
#pragma unroll 1
    for (int x = 0; x < 3; x++, t += 256) {
      const int T = t / 160, tl = t - T * 160;
      const int qq = (T >= NT1 - 1) ? (tl >> 5) : (tl / 40);
      int ck = 20 * T + ((tl - qq * ((T >= NT1 - 1) ? 32 : 40)) >> 1);
      ck ^= (ck >> 2) & 6;
      v |= (uint32_t)((ck * 4 + qq) & 1023) << (10 * x + 2);
    }
    sts32(sb + SO_OFF + 512 * i + 4 * tid, v);
  }
}
__device__ __forceinline__ void conv_channel(int slot, const CvCtx& c) {
  const uint32_t cb = sb + CV_OFF + slot * CV_B;
  float acc[64];
  CvPipe s;
  s.Ep[0] = s.Ep[1] = 0.f;
  uint32_t A[4][4];
#pragma unroll
  for (int i = 0; i < 64; i++) acc[i] = 0.f;
  if (slot == 4) mbar_wait(bars + 8 * B_CVDONE);
  mbar_wait(bars + 8 * (B_CVFULL + slot));
  cv_raw<0>(A, cb + c.koff);
  cv_form(A, 0x5432u);
  cv_copy<0>(acc);
  cv_step<0>(acc, A, s, c, cb, cv_stage(slot));
  fence_async_smem();
  mbar_arrive(bars + 8 * (B_CVDONE + slot));
}

__device__ __forceinline__ void tap_patch(int c) {
  mbar_wait(bars + 8 * (B_TAPS + c));
  const uint32_t a = sb + CV_OFF + c * CV_B + CV_K, w0 = lds32(a);
  sts32(a, (w0 & 0xffff0000u) | (pack_bf16(bf_lo(w0) + __uint_as_float(lds32(sb + EP_OFF + 4 * c)), 0.f) & 0xffffu));
  mbar_arrive(bars + 8 * (B_CVFULL + c));
}
__device__ __forceinline__ void kv_issue(const Params& p, int c, int m2, int dg) {
  const uint32_t fb = bars + 8 * (B_KV + c);
  mbar_expect_tx(fb, KV_PIECE);
  tma3(sb + KS_OFF + c * KV_PIECE, &p.mK, 160 * dg + 32 * c, 64 * m2 - 3, 0, fb);
  tma3(sb + KS_OFF + c * KV_PIECE + 4864, &p.mV, 160 * dg + 32 * c, 64 * m2 - 1, 0, fb);
}
__device__ __forceinline__ void kv_tile(int m, int dg, int c, int y) {
  const int lane = tid_opaque() & 31, tg = lane >> 3;
  const uint32_t pb = sb + KS_OFF + c * KV_PIECE + 32 * y + 4 * (lane & 7);
  const uint32_t ka = pb + tg * 1216, va = pb + 4864 + tg * 1088 + 64;
  const uint32_t kh = (m == 0 && tg > 0) ? ka - 192 : ka;
  uint32_t kk[19], u[16];
  const float4 t = lds128f(sb + TAP_OFF + 256 * c + 128 * y + 16 * (lane & 7));
#pragma unroll
  for (int i = 0; i < 19; i++) { kk[i] = lds32((i < 3 ? kh : ka) + i * 64); if (i >= 3) u[i - 3] = lds32(va + (i - 3) * 64); }
  uint8_t* dst = g_kv + ((160 * dg + 32 * c + 16 * y + 2 * (lane & 7)) * 4096 + (4 * m + tg) * 16);
  const uint32_t w0 = __byte_perm(__float_as_uint(t.x), __float_as_uint(t.z), 0x5410), w1 = __byte_perm(__float_as_uint(t.x), __float_as_uint(t.z), 0x7632);
  const uint32_t w2 = __byte_perm(__float_as_uint(t.y), __float_as_uint(t.w), 0x5410), w3 = __byte_perm(__float_as_uint(t.y), __float_as_uint(t.w), 0x7632);
#pragma unroll
  for (int i = 0; i < 16; i++) {
    uint32_t a = hmul2(kk[i], w3);
    a = hadd2(a, hmul2(kk[i + 1], w2)); a = hadd2(a, hmul2(kk[i + 2], w1)); a = hadd2(a, hmul2(kk[i + 3], w0));
    u[i] = hmul2(a, u[i]);
  }
#pragma unroll
  for (int e = 0; e < 2; e++)
#pragma unroll
    for (int f = 0; f < 2; f++) {
      uint32_t o[4];
#pragma unroll
      for (int qq = 0; qq < 4; qq++) o[qq] = __byte_perm(u[15 - 4 * qq - 2 * f], u[14 - 4 * qq - 2 * f], e ? 0x7632 : 0x5410);
      *(uint4*)(dst + e * 4096 + f * 2048) = make_uint4(o[0], o[1], o[2], o[3]);
    }
}
__device__ __forceinline__ void ln_finish(float s1, float s2, float& mean, float& rstd) {
  mean = s1 * (1.f / 640.f);
  const float v = fmaxf(fmaf(-mean, mean, s2 * (1.f / 640.f)), 0.f) + 1e-5f;
  asm("rsqrt.approx.ftz.f32 %0, %1;" : "=f"(rstd) : "f"(v));
}
__device__ __forceinline__ void stat_table(int T1, unsigned want, int l, int g, const uint4* x0, const uint4* x1, float (&xa)[2], float (&xb)[2]) {
  const int n = 32 * g + (tid_opaque() & 31);
  const uint4* rp = &g_stats[8 * l * SEQ + min(160 * T1 + n, SEQ - 1)];
  float a[4], b[4];
  uint32_t it = 0;
  while (true) {
    bool ok = true;
#pragma unroll
    for (int i = 0; i < 4; i++) ok &= (rec_ld(rp + SEQ * i, a[i], b[i]) == want);
    ok &= rec_ld(x0, xa[0], xb[0]) == want;
    ok &= rec_ld(x1, xa[1], xb[1]) == want;
    if (__all_sync(0xffffffffu, ok)) break;
    trap_if(++it > SPIN_LIMIT);
  }
  float m, rs;
  ln_finish((a[0] + a[1]) + (a[2] + a[3]), (b[0] + b[1]) + (b[2] + b[3]), m, rs);
  sts64f(sb + STAB_OFF + n * 8, rs, -m * rs);
}
__device__ __forceinline__ void stats_reduce(float (&a)[2], float (&b)[2], float (&mean)[2], float (&rstd)[2]) {
#pragma unroll
  for (int o = 1; o < 4; o <<= 1)
#pragma unroll
    for (int h = 0; h < 2; h++) { a[h] += __shfl_xor_sync(0xffffffffu, a[h], o); b[h] += __shfl_xor_sync(0xffffffffu, b[h], o); }
#pragma unroll
  for (int h = 0; h < 2; h++) ln_finish(a[h], b[h], mean[h], rstd[h]);
}

template <bool FIRST>
__device__ __forceinline__ void stats_publish(int which, int n0, int dg, unsigned tag, const float (&acc)[80]) {
  const int q = tid_opaque() & 3, h = q & 1;
  float s1[2] = {0.f, 0.f}, s2[2] = {0.f, 0.f}, t1[2] = {0.f, 0.f}, t2[2] = {0.f, 0.f};
#pragma unroll
  for (int j = 0; j < 20; j++)
#pragma unroll
    for (int y = 0; y < 2; y++) {
      const float a = acc[4 * j + 2 * y], b = acc[4 * j + 2 * y + 1];
      s1[y] += a; t1[y] += b; s2[y] = fmaf(a, a, s2[y]); t2[y] = fmaf(b, b, t2[y]);
    }
#pragma unroll
  for (int y = 0; y < 2; y++) { s1[y] += t1[y]; s2[y] += t2[y]; }
  float a = (h ? s1[1] : s1[0]) + __shfl_xor_sync(0xffffffffu, h ? s1[0] : s1[1], 1);
  float b = (h ? s2[1] : s2[0]) + __shfl_xor_sync(0xffffffffu, h ? s2[0] : s2[1], 1);
  a += __shfl_xor_sync(0xffffffffu, a, 2);
  b += __shfl_xor_sync(0xffffffffu, b, 2);
  if (FIRST) {
    rec_st(&g_stats[((q >> 1) * 4 + dg) * SEQ + n0 + 8 * h], a, b, q < 2 ? tag : tag - 1);
    rec_st(&g_stats[((q >> 1) * 4 + 8 + dg) * SEQ + n0 + 8 * h], a, b, tag - 1);
  } else if (q < 2) rec_st(&g_stats[(which * 4 + dg) * SEQ + n0 + 8 * h], a, b, tag);
}
__device__ __forceinline__ void stats_get(int which, int n0, unsigned tag, float (&mean)[2], float (&rstd)[2]) {
  const uint4* p0 = &g_stats[(which * 4 + (tid_opaque() & 3)) * SEQ + n0];
  float a[2], b[2];
  uint32_t it = 0;
  while (true) {
    const unsigned t0 = rec_ld(p0, a[0], b[0]), t1 = rec_ld(p0 + 8, a[1], b[1]);
    if (__all_sync(0xffffffffu, t0 == tag && t1 == tag)) break;
    trap_if(++it > SPIN_LIMIT);
  }
  stats_reduce(a, b, mean, rstd);
}
__device__ __forceinline__ void x0_load(float (&acc)[80]) {
  const int t = tid_opaque() & 127;
  const uint32_t xa = sb + XT_OFF + (16 * (t >> 5) + ((t & 31) >> 2)) * 320 + 8 * (t & 3);
  mbar_wait(bars + 8 * B_XT);
#pragma unroll
  for (int h = 0; h < 2; h++)
#pragma unroll
    for (int J = 0; J < 10; J++) {
      const float2 v = lds64f(xa + h * 2560 + 32 * J);
      const uint32_t x = __float_as_uint(v.x), y = __float_as_uint(v.y);
      acc[8 * J + 2 * h] = bf_lo(x); acc[8 * J + 2 * h + 1] = bf_hi(x);
      acc[8 * J + 4 + 2 * h] = bf_lo(y); acc[8 * J + 4 + 2 * h + 1] = bf_hi(y);
    }
}

template <bool FROM_X0>
__device__ __forceinline__ void dskip_init(float (&acc)[80], const float (&mean)[2], const float (&rstd)[2]) {
  const int t = tid_opaque() & 127;
  const uint32_t xa = sb + XT_OFF + (16 * (t >> 5) + ((t & 31) >> 2)) * 320 + 8 * (t & 3), da = sb + DTAB_OFF + 8 * (t & 3);
  float2 dw[10], xv[10][2];
#pragma unroll
  for (int J = 0; J < 2; J++) { dw[J] = lds64f(da + 32 * J); if (FROM_X0) { xv[J][0] = lds64f(xa + 32 * J); xv[J][1] = lds64f(xa + 2560 + 32 * J); } }
#pragma unroll
  for (int J = 0; J < 10; J++) {
    if (J + 2 < 10) { dw[J + 2] = lds64f(da + 32 * (J + 2)); if (FROM_X0) { xv[J + 2][0] = lds64f(xa + 32 * (J + 2)); xv[J + 2][1] = lds64f(xa + 2560 + 32 * (J + 2)); } }
#pragma unroll
    for (int x = 0; x < 8; x++) {
      const int h = (x >> 1) & 1;
      const uint32_t dwd = __float_as_uint(x < 4 ? dw[J].x : dw[J].y);
      const float tt = fmaf(rstd[h], (x & 1) ? bf_hi(dwd) : bf_lo(dwd), 1.f);
      float a = acc[8 * J + x];
      if (FROM_X0) { const uint32_t xw = __float_as_uint(x < 4 ? xv[J][h].x : xv[J][h].y); a = (x & 1) ? bf_hi(xw) : bf_lo(xw); }
      acc[8 * J + x] = FROM_X0 ? (a - mean[h]) * tt : fmaf(a, tt, -mean[h] * tt);
    }
  }
}

__global__ void __launch_bounds__(512, 1) fused_kernel(const __grid_constant__ Params p) {
  extern __shared__ __align__(1024) uint8_t smem_raw[];
  const int tid = threadIdx.x, lane = tid & 31;
  const int wid = __shfl_sync(0xffffffffu, tid >> 5, 0), wg = wid >> 2;
  unsigned smid; asm volatile("mov.u32 %0, %%smid;" : "=r"(smid));
  const int role = p.role[min(smid, 131u)];
  if (wid == 12) {
    const bool el = elect_one();
    if (el) {
      asm volatile("prefetch.tensormap [%0];" ::"l"(&p.mX) : "memory");
      asm volatile("prefetch.tensormap [%0];" ::"l"(&p.mB) : "memory");
#pragma unroll
      for (int k = 0; k < S1; k++) mbar_init(bars + 8 * (B_G1FULL + k), 1);
#pragma unroll
      for (int k = 0; k < 6; k++) mbar_init(bars + 8 * (B_XT + k), 1);
      asm volatile("fence.mbarrier_init.release.cluster;" ::: "memory");
    }
    if (role >= 0) {
      __syncwarp();
      asm volatile("bar.arrive 5, 288;" ::: "memory");
      const Role R = unpack_role(role);
      if (elect_one()) {
        TS(45);
#pragma unroll 1
        for (int k = 0; k < S1; k++) {
          const uint32_t fb = bars + 8 * (B_G1FULL + k);
          mbar_expect_tx(fb, G1_STAGE);
          tma4(sb + k * G1_STAGE + G1_XOFF, R.last ? &p.mXl : &p.mX, 64 * k, 0, 0, R.last ? 0 : 80 * R.T1, fb);
          tma5(sb + k * G1_STAGE, &p.mB, 64 * k, 0, 0, 4 * R.side, 2 * R.GP, fb);
        }
        if (R.has2) {
#pragma unroll 1
          for (int c = 0; c < KV0; c++) kv_issue(p, c, R.m2, R.dg);
          mbar_expect_tx(bars + 8 * B_XT, 20480);
#pragma unroll 1
          for (int h = 0; h < 2; h++) {
            const int ng = 8 * R.m2 + 4 * h, T = ng / 20;
            tma4(sb + XT_OFF + h * 10240, T == NT1 - 1 ? &p.mXtl : &p.mXt, 160 * R.dg, 0, 0, T == NT1 - 1 ? ng - 240 : ng + 60 * T, bars + 8 * B_XT);
          }
        }
        TS(44);
      }
      __syncwarp();
      bar_sync(6, 64);
    }
  }
  trap_if(smid >= 132 || smem_u32(smem_raw) != sb);
  if (role < 0) {
    if (wid == 0) {
      const unsigned tag = ld_rlx(g_epoch);
#pragma unroll 1
      for (int i = 0; i < NT1; i++) {
        uint32_t it = 0;
        while (!__all_sync(0xffffffffu, (int)(ld_rlx(&g_hflag[(i * 32 + min(lane, 9)) * 8]) - tag) >= 0)) { __nanosleep(500); trap_if(++it > SPIN_LIMIT); }
      }
    }
    return;
  }
  float mean0[2] = {0.f, 0.f}, rstd0[2] = {0.f, 0.f};
  if (wg == 2 || wid == 14) {
    ROLE(role)
    const int c = wid == 14 ? 4 : wid - 8;
    const unsigned tag = ld_rlx(g_epoch);
    if (has2) {
      uint2 bv[2][5];
#pragma unroll
      for (int x = 0; x < 2; x++)
#pragma unroll
        for (int i = 0; i < 5; i++) bv[x][i] = ldv64((const uint2*)((x ? p.bim : p.bre) + (cch0 + 32 * c) * DM) + lane + 32 * i);
      float sv[2];
#pragma unroll
      for (int x = 0; x < 2; x++) {
        float a = 0.f;
#pragma unroll
        for (int i = 0; i < 5; i++) a += (bf_lo(bv[x][i].x) + bf_hi(bv[x][i].x)) + (bf_lo(bv[x][i].y) + bf_hi(bv[x][i].y));
        sv[x] = a;
      }
#pragma unroll
      for (int o = 16; o > 0; o >>= 1) { sv[0] += __shfl_xor_sync(0xffffffffu, sv[0], o); sv[1] += __shfl_xor_sync(0xffffffffu, sv[1], o); }
      if (lane < 2) rec_st(&g_sB[(cch0 + 32 * c) * 2 + lane], sv[0], sv[1], tag);
      if (tid == 256) TS(47);
      __syncwarp();
      bar_sync(8, 192);
      mbar_wait(bars + 8 * B_EP);
      mbar_wait(bars + 8 * (B_KV + c));
#pragma unroll 1
      for (int y = 0; y < 2; y++) kv_tile(m2, dg, c, y);
      __syncwarp();
      if (lane == 0) { mbar_arrive(bars + 8 * (B_PD + c)); mbar_arrive(bars + 8 * B_PREP); }
      if (tid == 256) TS(48);
      if (tid == 352) TS(52);
      if (tid == 448) TS(51);
      if (wg == 2) {
        float xs[80];
        x0_load(xs);
        stats_publish<true>(0, 64 * m2 + 16 * c + (lane >> 2), dg, tag, xs);
        if (tid == 256) TS(31);
        mbar_wait(bars + 8 * B_PUB);
      } else {
        mbar_wait(bars + 8 * B_PREP);
        if (lane == 0) { st_rel(&g_kvflag[(dg * 32 + m2) * 8], tag); mbar_arrive(bars + 8 * B_PUB); TS(30); }
        __syncwarp();
      }
    } else bar_sync(8, 192);
    {
      const uint4* x0 = wg == 2 ? &g_stats[(lane & 3) * SEQ + (has2 ? 64 * m2 : 0) + 16 * c + (lane >> 2)] : &g_sB[(128 * GP + 32 * side + lane) * 2];
      float xa[2], xb[2];
      stat_table(T1, tag, 0, c, x0, x0 + (wg == 2 ? 8 : 128), xa, xb);
      if (wg == 2) stats_reduce(xa, xb, mean0, rstd0);
      else {
#pragma unroll
        for (int i = 0; i < 2; i++) sts64f(sb + CTAB_OFF + (32 * i + lane) * 24 + 16, p.swap ? xb[i] : xa[i], p.swap ? xa[i] : xb[i]);
      }
      mbar_arrive(bars + 8 * B_STAB);
      if (tid == 256) TS(26);
    }
  } else if (wid == 15) {
    ROLE(role)
    const int ch = 128 * GP + 32 * side + lane;
    uint32_t r0 = ldv16(p.lre + ch), r1 = ldv16(p.lim + ch), r2 = ldv16(p.logdt + ch);
    const uint32_t r3 = ldv16(p.lre + ch + 64), r4 = ldv16(p.lim + ch + 64), r5 = ldv16(p.logdt + ch + 64);
#pragma unroll 1
    for (int i = 0; i < 2; i++) {
      const float lr = bf_lo(r0), li = bf_lo(r1);
      const float dt = __bfloat162float(__float2bfloat16_rn(expf(bf_lo(r2))));
      const float mag = expf(dt * lr);
      float sn, cs; sincospif(dt * li * 0.31830988618379067f, &sn, &cs);
      const float ar = mag * cs, ai = mag * sn;
      const float inv = 2.f / (lr * lr + li * li);
      const uint32_t ad = sb + CTAB_OFF + (32 * i + lane) * 24;
      sts64f(ad, ar, ai);
      sts64f(ad + 8, ((ar - 1.f) * lr + ai * li) * inv, (ai * lr - (ar - 1.f) * li) * inv);
      r0 = r3; r1 = r4; r2 = r5;
    }
    if (lane == 0) TS(46);
    __syncwarp();
    bar_sync(7, 64);
    mbar_arrive(bars + 8 * B_CTAB);
  } else if (wid == 13) {
    ROLE(role)
    uint4 tv[3];
    const uint32_t e0 = ld_rlx(g_epoch);
    const uint32_t e1 = ldv16(p.ssmD + min(cch0 + 32 * lane, 639));
    const uint4 dv = ldv128((const uint4*)(p.dskip + 160 * dg) + min(lane, 19));
#pragma unroll
    for (int i = 0; i < 3; i++) tv[i] = ldv128((const uint4*)(p.shiftk + 640 * dg) + min(lane + 32 * i, 79));
    sts128(sb + DTAB_OFF + 16 * min(lane, 19), dv);
#pragma unroll
    for (int i = 0; i < 3; i++) sts128(sb + TAP_OFF + 16 * min(lane + 32 * i, 79), tv[i]);
    if (lane < 7) sts32(sb + EP_OFF + 4 * lane, lane < 5 ? e1 << 16 : (lane == 5 ? e0 : 0u));
    __syncwarp();
    bar_sync(9, 64);
    mbar_arrive(bars + 8 * B_CTAB);
    if (lane == 0) { mbar_arrive(bars + 8 * B_EP); TS(53); }
  } else if (wid != 12) {
    if (elect_one()) {
      if (wid < 7) {
        const int b0 = wid < 4 ? 4 + 20 * wid : 85 + 21 * (wid - 4), cnt = wid < 4 ? 2 : 1;
#pragma unroll
        for (int i = 0; i < 21; i++) mbar_init(bars + 8 * (b0 + i), cnt);
      } else {
#pragma unroll
        for (int i = 0; i < 12; i++) mbar_init(bars + 8 * (B_CVDONE + i), (i == 5 || i == 6) ? 160 : 128);
        mbar_init(bars + 8 * B_CTAB, 192); mbar_init(bars + 8 * B_PREP, 5);
      }
      asm volatile("fence.mbarrier_init.release.cluster;" ::: "memory");
    }
    __syncwarp();
    bar_sync(5, 288);
    if (wid == 2) asm volatile("bar.arrive 8, 192;\nbar.arrive 6, 64;\nbar.arrive 9, 64;\nbar.arrive 7, 64;" ::: "memory");
    if (tid == 128) TS(0);
    if (wg == 1) { cv_table(); mbar_arrive(bars + 8 * B_CTAB); }
  }

  if (wg == 3) {
    ROLE(role)
    const int pw = wid & 3;
    unsigned tag = 0;
    if (pw > 0) { mbar_wait(bars + 8 * B_EP); tag = lds32(sb + EP_OFF + 20); }
    if (pw == 0) {
      if (elect_one()) {
#pragma unroll 1
        for (int l = 0; l < 2; l++) {
          const uint32_t fb0 = bars + 8 * (B_G1FULL + 10 * l), wb = bars + 8 * (B_G1DONE + 9 * l - S1);
          const uint32_t free0 = bars + 8 * (has2 ? B_G2DONE + 19 : B_G1DONE + 9);
          uint32_t dst = sb;
#pragma unroll 1
          for (int k = l == 0 ? S1 : 0; k < 10; k++) {
            mbar_wait(k >= S1 + l ? wb + 8 * k : (k < WPF1 || !has2 ? free0 : bars + 8 * (B_GO + 1)));
            mbar_expect_tx(fb0 + 8 * k, 16384);
            tma5(dst, &p.mB, 64 * k, 0, 0, 4 * side, 2 * GP, fb0 + 8 * k);
            dst += G1_STAGE; if (dst == sb + (S1 + l) * G1_STAGE) dst = sb;
          }
          if (has2) {
            const uint32_t fb2 = bars + 8 * (B_G2FULL + 20 * l), wb2 = bars + 8 * (B_G2DONE + 19 * l - 6);
            dst = sb + G2_WOFF;
            int kc = 0;
#pragma unroll 1
            for (int k = 0; k < 20; k++) {
              mbar_wait(k >= 6 + l ? wb2 + 8 * k : (k == 5 ? bars + 8 * B_XFREE : (k < WPF2 ? bars + 8 * (B_G1DONE + 10 * l + 9) : bars + 8 * (B_GO + 2 * l))));
              mbar_expect_tx(fb2 + 8 * k, G2_WB);
              tma5(dst, &p.mCre + (k & 1), kc, 0, 0, 0, 10 * dg, fb2 + 8 * k);
              kc += (k & 1) << 7; if (k == 9) kc = 64;
              dst += G2_WB; if (dst == sb + G2_WOFF + (6 + l) * G2_WB) dst = sb + G2_WOFF;
            }
          }
        }
      }
    } else if (pw == 1) {
#pragma unroll 1
      for (int l = 0; l < 2; l++) {
        if (l == 0) {
          if (elect_one()) {
            uint32_t dst = sb + G1_XOFF;
#pragma unroll 1
            for (int k = S1; k < 10; k++) {
              mbar_wait(bars + 8 * (B_G1DONE + k - S1));
              mbar_expect_tx(bars + 8 * (B_G1FULL + k), 20480);
              tma4(dst, last ? &p.mXl : &p.mX, 64 * k, 0, 0, last ? 0 : 80 * T1, bars + 8 * (B_G1FULL + k));
              dst += G1_STAGE; if (k == 2 * S1 - 1) dst = sb + G1_XOFF;
              if (has2 && k - S1 + KV0 < 5) kv_issue(p, k - S1 + KV0, m2, dg);
            }
          }
        } else {
          mbar_wait(bars + 8 * (has2 ? B_G2DONE + 19 : B_G1DONE + 9));
          const int mlo = (160 * T1) >> 6, nf = last ? 8 : 12;
          flag_poll(&g_uflag[(4 * mlo + min(lane, nf - 1)) * 8], tag);
          fence_async_global();
          if (elect_one()) {
            TS(20);
            const int bytes = last ? 16384 : 20480;
            const uint8_t* src = g_u + T1 * 204800;
            uint32_t dst = sb + G1_XOFF;
#pragma unroll 1
            for (int k = 0; k < 10; k++) {
              if (k > S1) mbar_wait(bars + 8 * (B_G1DONE + 9 - S1 + k));
              mbar_expect_tx(bars + 8 * (B_G1FULL + 10 + k), bytes);
              bulk_g2s(dst, src, bytes, bars + 8 * (B_G1FULL + 10 + k));
              src += 20480; dst += G1_STAGE; if (k == S1) dst = sb + G1_XOFF;
            }
          }
        }
        __syncwarp();
        if (has2) {
          mbar_wait(bars + 8 * (B_G1DONE + 10 * l + 9));
          const int Tlo = (64 * m2) / 160, Thi = (64 * m2 + 63) / 160;
          flag_poll(&g_hflag[(((l * NT1 + (lane < 16 ? Tlo : Thi)) * 2) * 16 + min(lane & 15, 9)) * 8], tag);
          fence_async_global();
          if (elect_one()) {
            TS(21 + 2 * l);
            const uint32_t fb2 = bars + 8 * (B_G2FULL + 20 * l), wb2 = bars + 8 * (B_G2DONE + 18 * l - SX2);
            const uint8_t* src = g_h + (l * 32 + m2) * 163840;
            uint32_t dst = sb;
#pragma unroll 1
            for (int k = 0; k < 20; k++) {
              if (k >= SX2 + 2 * l) mbar_wait(wb2 + 8 * k);
              if (k == 10) { mbar_wait(bars + 8 * (B_H1 + l)); fence_async_global(); }
              mbar_expect_tx(fb2 + 8 * k, G2_XB);
              bulk_g2s(dst, src, G2_XB, fb2 + 8 * k);
              src += 8192; dst += G2_XB; if (dst == sb + (SX2 + 2 * l) * G2_XB) dst = sb;
            }
          }
          __syncwarp();
        }
      }
    } else if (pw == 2) {
#pragma unroll 1
      for (int l = 0; l < 2; l++) {
        if (l == 1) {
          float xa[2], xb[2];
          mbar_wait(bars + 8 * (B_G1FULL + 11));
          stat_table(T1, tag, 1, 4, g_stats, g_stats, xa, xb);
          mbar_arrive(bars + 8 * (B_STAB + 1));
        }
        mbar_wait(bars + 8 * (B_HST + 2 * l));
        mbar_wait(bars + 8 * (B_HST + 2 * l + 1));
        __syncwarp();
        if (lane < 2) st_rel(&g_hflag[(((l * NT1 + T1) * 2 + lane) * 16 + 2 * GP + side) * 8], tag);
        if (lane == 0) TS(6 + 8 * l);
        __syncwarp();
        if (l == 0 && has2 && elect_one()) {
#pragma unroll 1
          for (int c = 0; c < 5; c++) {
            mbar_wait(bars + 8 * (B_CVDONE + c));
            bulk_s2g(g_G + (cch0 + 32 * c) * 4096, cv_stage(c), 4096);
          }
          asm volatile("cp.async.bulk.commit_group;" ::: "memory");
          asm volatile("cp.async.bulk.wait_group 0;" ::: "memory");
          fence_async_global();
          st_rel(&g_gflag[(dg * 32 + m2) * 8], tag);
        }
        __syncwarp();
      }
    } else if (has2) {
#pragma unroll 1
      for (int c = 0; c < 5; c++) {
        mbar_wait(bars + 8 * (B_PD + c));
        const uint32_t cb = sb + CV_OFF + c * CV_B;
        sts128(lane < 8 ? cb + 16 * lane : (lane < 20 ? cb + CV_U + 16 * (lane - 8) : cb + CV_U + CV_PL + 16 * (lane - 20)), make_uint4(0, 0, 0, 0));
        fence_async_smem();
        __syncwarp();
        if (!TAPLATE && c < TAP0 && elect_one()) {
          mbar_expect_tx(bars + 8 * (B_TAPS + c), 4096);
          bulk_g2s(cb + CV_K, p.ssmk + (cch0 + 32 * c) * SEQ, 4096, bars + 8 * (B_TAPS + c));
        }
      }
      mbar_wait(bars + 8 * B_PUB);
      if (TAPLATE && elect_one()) {
#pragma unroll
        for (int c = 0; c < TAP0; c++) {
          mbar_expect_tx(bars + 8 * (B_TAPS + c), 4096);
          bulk_g2s(sb + CV_OFF + c * CV_B + CV_K, p.ssmk + (cch0 + 32 * c) * SEQ, 4096, bars + 8 * (B_TAPS + c));
        }
      }
      flag_poll(&g_kvflag[(dg * 32 + lane) * 8], tag);
      fence_async_global();
      if (elect_one()) {
        TS(28);
#pragma unroll 1
        for (int c = 0; c < 5; c++) {
          const uint32_t fb = bars + 8 * (B_CVFULL + c), cb = sb + CV_OFF + c * CV_B;
          if (c == 1) tap_patch(0);
          mbar_expect_tx(fb, 4096);
          bulk_g2s(cb + CV_U + 192, g_kv + (cch0 + 32 * c) * 4096, 2048, fb);
          bulk_g2s(cb + CV_U + 192 + CV_PL, g_kv + (cch0 + 32 * c) * 4096 + 2048, 2048, fb);
          if (c >= TAP0) {
            mbar_expect_tx(bars + 8 * (B_TAPS + c), 4096);
            bulk_g2s(cb + CV_K, p.ssmk + (cch0 + 32 * c) * SEQ, 4096, bars + 8 * (B_TAPS + c));
          }
        }
#pragma unroll 1
        for (int c = 1; c < 5; c++) tap_patch(c);
        TS(54);
        asm volatile("prefetch.tensormap [%0];" ::"l"(&p.mCre) : "memory");
        asm volatile("prefetch.tensormap [%0];" ::"l"(&p.mCim) : "memory");
        asm volatile("prefetch.tensormap [%0];" ::"l"(&p.mG) : "memory");
      }
      __syncwarp();
      const unsigned* hf = &g_hflag[(((lane < 16 ? (64 * m2) / 160 : (64 * m2 + 63) / 160) * 2 + 1) * 16 + min(lane & 15, 9)) * 8];
      mbar_wait(bars + 8 * (B_CVDONE + 0));
      if (elect_one()) { l2_prefetch(p.cre + (160 * dg + 5 * m2) * DM, 6400); l2_prefetch(p.cim + (160 * dg + 5 * m2) * DM, 6400); }
      flag_poll(hf, tag);
      __syncwarp();
      if (lane == 0) { mbar_arrive(bars + 8 * B_H1); TS(22); }
      mbar_wait(bars + 8 * (B_CVDONE + 4));
      flag_poll(&g_gflag[(dg * 32 + lane) * 8], tag);
      __syncwarp();
      fence_async_global();
      if (lane == 0) TS(29);
      if (elect_one()) {
        mbar_expect_tx(bars + 8 * B_GFULL, 20480);
        tma5(sb + G_OFF, &p.mG, 64 * m2, 0, 0, 0, 10 * dg, bars + 8 * B_GFULL);
      }
      mbar_wait(bars + 8 * (B_G1DONE + 19));
      flag_poll(hf + NT1 * 256, tag);
      __syncwarp();
      if (lane == 0) { mbar_arrive(bars + 8 * (B_H1 + 1)); TS(24); }
    }
  } else {
    const int w = wid & 3;
    if (wg == 2 && !(role >> 16)) {
      float xa[2], xb[2];
      mbar_wait(bars + 8 * (B_G1FULL + 11));
      stat_table(role & 15, lds32(sb + EP_OFF + 20), 1, w, g_stats, g_stats, xa, xb);
      mbar_arrive(bars + 8 * (B_STAB + 1));
    }
#pragma unroll 1
    for (int l = 0; l < 2; l++) {
      if (wg < 2) {
        float acc[80];
#pragma unroll
        for (int i = 0; i < 80; i++) acc[i] = 0.f;
        ROLE(role)
        const int tid = tid_opaque(), r = (tid & 31) >> 2, q = tid & 3;
        const int ch = 128 * GP + 64 * wg + 32 * side + 8 * w + r;
        const uint32_t ca = sb + CTAB_OFF + (32 * wg + 8 * w + r) * 24;
        float2 lam = make_float2(0.f, 0.f), p8 = lam, p16 = lam, pL = lam, p2L = lam;
        fence_regs(acc);
        {
          uint32_t alo = desc_lo(sb, 16) + wg * 512, blo = l == 0 ? desc_lo(sb + G1_XOFF, 16) : desc_lo(sb + G1_XOFF, 128);
          const uint32_t bhi = l == 0 ? desc_hi(1024, 1) : desc_hi(1024, 0), xstep = l == 0 ? 2 : 16;
          const uint32_t aend = desc_lo(sb, 16) + (S1 + l) * (G1_STAGE >> 4);
          uint32_t fb = bars + 8 * (B_G1FULL + 10 * l);
          mbar_wait(fb);
          if (tid == 0) TS(1 + 8 * l);
#pragma unroll 1
          for (int k = 0; k < 10; k++) {
            uint32_t ok; const uint32_t nb = k < 9 ? fb + 8 : fb;
            wgmma_fence();
#pragma unroll
            for (int kk = 0; kk < 4; kk++) {
              wgmma_n160<0>(acc, alo + kk * 2, desc_hi(1024, 1), blo + kk * xstep, bhi);
              if (kk == 0) ok = mbar_test(nb);
            }
            wgmma_commit();
            alo += G1_STAGE >> 4; blo += G1_STAGE >> 4;
            if (alo >= aend) { alo -= (S1 + l) * (G1_STAGE >> 4); blo -= (S1 + l) * (G1_STAGE >> 4); }
            wgmma_wait<1>();
            if (k > 0 && (tid & 127) == 0) mbar_arrive(fb + 8 * (B_G1DONE - B_G1FULL - 1));
            if (!ok) mbar_wait(nb);
            if (k == PAUSE_K) {
              mbar_wait(bars + 8 * B_CTAB);
              lam = lds64f(ca);
              if (p.swap) lam.y = -lam.y;
              const float2 p2 = cmul(lam, lam), p4 = cmul(p2, p2);
              p8 = cmul(p4, p4); p16 = cmul(p8, p8);
              pL = cmul(p16, p16);
              if (!last) pL = cmul(pL, p8);
              p2L = cmul(pL, pL);
              if (has2) mbar_wait(bars + 8 * B_PREP);
            }
            fb += 8;
          }
        }
        mbar_wait(bars + 8 * (B_STAB + l));
        const float2 sB = lds64f(ca + 16);
        const unsigned tag = lds32(sb + EP_OFF + 20);
        wgmma_wait<0>();
        fence_regs(acc);
        if ((tid & 127) == 0) { mbar_arrive(bars + 8 * (B_G1DONE + 10 * l + 9)); if (wg == 0) TS(2 + 8 * l); }
        float2 ec[3];
#pragma unroll
        for (int jj = 0; jj < 8; jj++)
#pragma unroll
          for (int y = 0; y < 3; y++) {
            if (y == 2 && (jj & 1)) continue;
            const int j = y == 2 ? 16 + (jj >> 1) : 8 * y + jj;
            const float4 st = lds128f(sb + STAB_OFF + (8 * j + 2 * q) * 8);
            acc[4 * j + 0] = fmaf(acc[4 * j + 0], st.x, st.y * sB.x);
            acc[4 * j + 2] = fmaf(acc[4 * j + 2], st.x, st.y * sB.y);
            acc[4 * j + 1] = fmaf(acc[4 * j + 1], st.z, st.w * sB.x);
            acc[4 * j + 3] = fmaf(acc[4 * j + 3], st.z, st.w * sB.y);
            ec[y] = jj == 0 ? make_float2(acc[4 * j + 0], acc[4 * j + 2]) : cfma(lam, ec[y], make_float2(acc[4 * j + 0], acc[4 * j + 2]));
            ec[y] = cfma(lam, ec[y], make_float2(acc[4 * j + 1], acc[4 * j + 3]));
          }
        float2 e = cfma(p16, ec[0], ec[1]);
        if (!last) e = cfma(p8, e, ec[2]);
        {
          float2 v = make_float2(__shfl_up_sync(0xffffffffu, e.x, 1, 4), __shfl_up_sync(0xffffffffu, e.y, 1, 4));
          if (q >= 1) e = cfma(pL, v, e);
          v = make_float2(__shfl_up_sync(0xffffffffu, e.x, 2, 4), __shfl_up_sync(0xffffffffu, e.y, 2, 4));
          if (q >= 2) e = cfma(p2L, v, e);
        }
        if (!last && (q == 3 || (q == 2 && l == 0))) rec_st(&g_E[((q == 3 ? l : 1) * NT1 + T1) * DM + ch], e.x, e.y, q == 3 ? tag : tag - 1);
        if (tid == 0) TS(3 + 8 * l);
        float2 ex = make_float2(__shfl_up_sync(0xffffffffu, e.x, 1, 4), __shfl_up_sync(0xffffffffu, e.y, 1, 4));
        if (q == 0) ex = make_float2(0.f, 0.f);
        const float2 coef = lds64f(ca + 8), lamc = make_float2(lam.x, p.swap ? lam.y : -lam.y);
        float m00 = coef.x, m01 = -coef.y, m10 = -coef.y, m11 = -coef.x;
        if (p.swap) { m00 = -coef.y; m01 = coef.x; m10 = -coef.x; m11 = -coef.y; }
        float2 pLq, p160q, p640;
        {
          const float2 p80 = last ? cmul(p2L, p16) : p2L, p160 = cmul(p80, p80), p320 = cmul(p160, p160), one = make_float2(1.f, 0.f);
          p640 = cmul(p320, p320);
          pLq = cmul((q & 1) ? pL : one, (q & 2) ? p2L : one);
          p160q = cmul((q & 1) ? p160 : one, (q & 2) ? p320 : one);
        }
        float2 c, ev[3];
        unsigned tg[3];
        const uint4* ep = &g_E[(l * NT1 + T1 - 1 - q) * DM + ch];
#pragma unroll
        for (int j = 0; j < 20; j++) {
          if (j == CPOLL) {
#pragma unroll
            for (int i = 0; i < 3; i++) {
              ev[i] = make_float2(0.f, 0.f); tg[i] = tag;
              if (T1 - 1 - q - 4 * i >= 0) tg[i] = rec_ld(ep - 4 * i * DM, ev[i].x, ev[i].y);
            }
          }
#pragma unroll
          for (int x = 0; x < 2; x++) {
            const float b0 = acc[4 * j + x], b1 = acc[4 * j + 2 + x];
            acc[4 * j + x] = fmaf(b0, m00, b1 * m01);
            acc[4 * j + 2 + x] = fmaf(b0, m10, b1 * m11);
          }
          if (j == CPOLL - 1 || j == 19) asm volatile("" : "+f"(acc[4 * j]), "+f"(acc[4 * j + 1]), "+f"(acc[4 * j + 2]), "+f"(acc[4 * j + 3])::"memory");
        }
        {
          uint32_t it = 0;
          while (__any_sync(0xffffffffu, tg[0] != tag || tg[1] != tag || tg[2] != tag)) {
#pragma unroll
            for (int i = 0; i < 3; i++)
              if (tg[i] != tag) tg[i] = rec_ld(ep - 4 * i * DM, ev[i].x, ev[i].y);
            trap_if(++it > SPIN_LIMIT);
          }
          c = cfma(p640, cfma(p640, ev[2], ev[1]), ev[0]);
          c = cmul(c, p160q);
          c.x += __shfl_xor_sync(0xffffffffu, c.x, 1); c.y += __shfl_xor_sync(0xffffffffu, c.y, 1);
          c.x += __shfl_xor_sync(0xffffffffu, c.x, 2); c.y += __shfl_xor_sync(0xffffffffu, c.y, 2);
        }
        if (tid == 0) TS(4 + 8 * l);
        if (tid == 128) mbar_arrive(bars + 8 * (B_GO + 2 * l));
        c = cfma(pLq, c, ex);
        float2 hh = make_float2(fmaf(c.x, m00, c.y * m01), fmaf(c.x, m10, c.y * m11));
        uint8_t* hb = g_h + (size_t)l * (32 * 20 * 8192) + (10 * wg + 2 * GP) * 8192 + (4 * side + w) * 1024 + (tid_opaque() & 31) * 4;
#pragma unroll
        for (int j4 = 0; j4 < 5; j4++) {
          const int ng = 20 * T1 + 4 * j4;
          uint8_t* hp = hb + (size_t)(ng >> 3) * 163840 + (ng & 7) * 128;
#pragma unroll
          for (int jj = 0; jj < 4; jj++) {
            const int j = 4 * j4 + jj;
            const float2 h0 = cfma(lamc, hh, make_float2(acc[4 * j + 0], acc[4 * j + 2]));
            hh = cfma(lamc, h0, make_float2(acc[4 * j + 1], acc[4 * j + 3]));
            if (j4 < 4 || !last) {
              *(uint32_t*)(hp + jj * 128) = pack_bf16(h0.x, hh.x);
              *(uint32_t*)(hp + jj * 128 + 8192) = pack_bf16(h0.y, hh.y);
            }
          }
        }
        mbar_arrive(bars + 8 * (B_HST + 2 * l + wg));
        if (tid == 0) TS(5 + 8 * l);
      }
      if (l == 0) {
        ROLE(role)
        if (has2) {
          CvCtx cc;
          mbar_wait(bars + 8 * B_CTAB);
          cv_setup(cc);
          mbar_wait(bars + 8 * (B_G1DONE + 9));
#pragma unroll 1
          for (int c = wg == 2 ? 0 : 2 + wg; c < (wg == 2 ? 2 : 5); c += wg == 2 ? 1 : 2) conv_channel(c, cc);
          if ((tid & 127) == 0) TS(wg == 2 ? 32 : 7 + wg);
        }
      }
      if (wg == 2) break;
    }
    if (wg == 2 && (role >> 16)) {
      float acc[80];
      float off[2] = {mean0[0], mean0[1]};
      const unsigned tag = lds32(sb + EP_OFF + 20);
      dskip_init<true>(acc, mean0, rstd0);
      mbar_arrive(bars + 8 * B_XFREE);
#pragma unroll 1
      for (int l = 0; l < 2; l++) {
        float mean[2], rstd[2];
        {
          const uint32_t aend = desc_lo(sb + SX2 * G2_XB, 1024) + l * (G2_XB >> 3), bend = desc_lo(sb + G2_WOFF + 6 * G2_WB, 16) + l * (G2_WB >> 4);
          uint32_t alo = desc_lo(sb, 1024), blo = desc_lo(sb + G2_WOFF, 16);
          uint32_t fb = bars + 8 * (B_G2FULL + 20 * l);
          fence_regs(acc);
          mbar_wait(fb);
          if (tid == 256) TS(33 + 6 * l);
#pragma unroll 1
          for (int k = 0; k < 20; k++) {
            if (l == 1 && (k & 3) == 3 && tid == 256) TS(56 + (k >> 2));
            uint32_t ok; const uint32_t nb = k < 19 ? fb + 8 : fb;
            wgmma_fence();
#pragma unroll
            for (int kk = 0; kk < 4; kk++) {
              wgmma_n160<1>(acc, alo + kk * 128, desc_hi(128, 0), blo + kk * 2, desc_hi(1024, 1));
              if (kk == 0) ok = mbar_test(nb);
            }
            wgmma_commit();
            alo += G2_XB >> 4; if (alo == aend) alo = desc_lo(sb, 1024);
            blo += G2_WB >> 4; if (blo == bend) blo = desc_lo(sb + G2_WOFF, 16);
            wgmma_wait<1>();
            if (k > 0 && tid == 256) mbar_arrive(fb + 8 * (B_G2DONE - B_G2FULL - 1));
            if (!ok) mbar_wait(nb);
            fb += 8;
          }
          wgmma_wait<0>();
          fence_regs(acc);
          if (tid == 256) TS(34 + 6 * l);
          if (tid == 256) mbar_arrive(bars + 8 * (B_G2DONE + 20 * l + 19));
        }
        ROLE(role)
        const int tq = tid_opaque() & 31, n0 = 64 * m2 + 16 * w + (tq >> 2);
        stats_publish<false>(2 * l + 1, n0, dg, tag, acc);
        uint32_t gf[10][4];
        mbar_wait(bars + 8 * B_GFULL);
        const uint32_t ga = sb + G_OFF + (8 * (tq >> 4) + (tq & 7)) * 128 + (((2 * w + ((tq >> 3) & 1)) ^ ((2 * m2) & 6) ^ (tq & 7)) << 4);
#pragma unroll
        for (int J = 0; J < 2; J++) ldsm4t(gf[J], ga + J * 2048);
        if (tid == 256) TS(35 + 6 * l);
        uint8_t* dst[2][2];
#pragma unroll
        for (int h = 0; h < 2; h++) {
          if (l == 0) {
            const int ng = 8 * m2 + 2 * w + h, T = ng / 20;
            uint8_t* ub = g_u + (T * 204800 + (ng - 20 * T) * 1024 + (tq & 2) * 64 + (tq & 28) * 4 + (tq & 1) * 8 + (5 * dg >> 1) * 20480);
            dst[h][1] = ub + ((dg & 1) ? 20480 - 512 : 0);
            dst[h][0] = ub + (dg & 1) * 512;
          } else {
            dst[h][0] = dst[h][1] = (uint8_t*)(p.out + (n_to_t(n0 + 8 * h) * DM + 160 * dg + 4 * (tq & 3)));
          }
        }
        stats_get(2 * l + 1, n0, tag, mean, rstd);
        if (tid == 256) { TS(36 + 6 * l); if (l == 0) mbar_arrive(bars + 8 * (B_GO + 1)); }
        off[0] += mean[0]; off[1] += mean[1];
        const float ov[2] = {l ? off[0] : 0.f, l ? off[1] : 0.f};
#pragma unroll
        for (int J = 0; J < 10; J++) {
          if (J + 2 < 10) ldsm4t(gf[J + 2 < 10 ? J + 2 : 0], ga + (J + 2) * 2048);
#pragma unroll
          for (int x = 0; x < 8; x++) {
            const int h = (x >> 1) & 1;
            const uint32_t gwd = gf[J][x >> 1];
            const float t = fmaf(rstd[h], (x & 1) ? bf_hi(gwd) : bf_lo(gwd), 1.f);
            acc[8 * J + x] = fmaf(acc[8 * J + x], t, fmaf(-mean[h], t, ov[h]));
          }
#pragma unroll
          for (int h = 0; h < 2; h++) {
            if (l == 0)
              *(uint2*)(dst[h][(J >> 1) & 1] + (J >> 2) * 20480 + (J & 3) * 256) =
                  make_uint2(pack_bf16(acc[8 * J + 2 * h], acc[8 * J + 2 * h + 1]), pack_bf16(acc[8 * J + 4 + 2 * h], acc[8 * J + 5 + 2 * h]));
            else
              *(float4*)(dst[h][0] + 64 * J) = make_float4(acc[8 * J + 2 * h], acc[8 * J + 2 * h + 1], acc[8 * J + 4 + 2 * h], acc[8 * J + 5 + 2 * h]);
          }
          __syncwarp();
        }
        if (l == 0) {
          bar_sync(3, 128);
          if (tid == 256) { TS(37); st_rel(&g_uflag[(4 * m2 + dg) * 8], tag); TS(38); }
          stats_publish<false>(2, n0, dg, tag, acc);
          mbar_wait(bars + 8 * (B_G1FULL + 11));
          float xa[2], xb[2];
          const uint4* x0 = &g_stats[(8 + (tq & 3)) * SEQ + n0];
          stat_table(T1, tag, 1, w, x0, x0 + 8, xa, xb);
          mbar_arrive(bars + 8 * (B_STAB + 1));
          if (tid == 256) TS(27);
          stats_reduce(xa, xb, mean, rstd);
          off[0] += mean[0]; off[1] += mean[1];
          mbar_wait(bars + 8 * (B_HST + 3));
          dskip_init<false>(acc, mean, rstd);
        } else {
          if (tid == 256) {
            TS(43);
            if (m2 == 31 && dg == 3) asm volatile("st.relaxed.gpu.global.u32 [%0], %1;" ::"l"(g_epoch), "r"(tag + 1) : "memory");
          }
        }
      }
    }
  }
}

typedef CUresult (*EncFn)(CUtensorMap*, CUtensorMapDataType, cuuint32_t, void*, const cuuint64_t*, const cuuint64_t*,
                          const cuuint32_t*, const cuuint32_t*, CUtensorMapInterleave, CUtensorMapSwizzle,
                          CUtensorMapL2promotion, CUtensorMapFloatOOBfill);

void encode(EncFn fn, CUtensorMap* m, const void* ptr, int rank, const cuuint64_t* dims, const cuuint64_t* strides, const cuuint32_t* box,
            CUtensorMapSwizzle swz = CU_TENSOR_MAP_SWIZZLE_128B) {
  cuuint32_t es[5] = {1, 1, 1, 1, 1};
  fn(m, CU_TENSOR_MAP_DATA_TYPE_BFLOAT16, rank, (void*)ptr, dims, strides, box, es, CU_TENSOR_MAP_INTERLEAVE_NONE,
     swz, (CUtensorMapL2promotion)(swz == CU_TENSOR_MAP_SWIZZLE_128B ? PROM_A : PROM_B), CU_TENSOR_MAP_FLOAT_OOB_FILL_NONE);
}

}

extern "C" void kernel_launch(void* const* d_in, const int* in_sizes, int n_in, void* d_out, int out_size) {
  (void)in_sizes; (void)n_in; (void)out_size;
  Params p;
  typedef const __nv_bfloat16* BP;
  p.x = (BP)d_in[0]; p.lre = (BP)d_in[1]; p.lim = (BP)d_in[2]; p.bre = (BP)d_in[3]; p.bim = (BP)d_in[4];
  p.cre = (BP)d_in[5]; p.cim = (BP)d_in[6]; p.logdt = (BP)d_in[7]; p.dskip = (BP)d_in[8];
  p.k = (BP)d_in[10]; p.v = (BP)d_in[11]; p.shiftk = (BP)d_in[12]; p.ssmk = (BP)d_in[13]; p.ssmD = (BP)d_in[14];
  p.out = (float*)d_out;
  for (int sm = 0; sm < 132; sm++) {
    const int tpc = sm >> 1, side = sm & 1;
    int gpc, gi;
    if (tpc < 32) { gpc = tpc & 7; gi = tpc >> 3; }
    else if (tpc < 60) { gpc = 1 + (tpc - 32) % 7; gi = 4 + (tpc - 32) / 7; }
    else if (tpc < 62) { gpc = tpc - 54; gi = 8; }
    else { gpc = 0; gi = tpc - 58; }
    const int pos = 8 * gpc + gi + (gpc == 7 ? 1 : 0);
    int T1, GP;
    if (pos < 52) { const int hh = pos / 26, x = pos - 26 * hh; T1 = x >> 1; GP = 2 * hh + (x & 1); }
    else { T1 = pos - 52; GP = 4; }
    const int m2 = 8 * (gpc >> 1) + gi, dg = 2 * (gpc & 1) + side;
    p.role[sm] = pos == 65 ? -1 : (T1 | (GP << 4) | (side << 7) | (m2 << 8) | (dg << 14) | ((gi < 8) << 16));
  }
  void* fnp = nullptr;
  cudaDriverEntryPointQueryResult qr;
  cudaGetDriverEntryPoint("cuTensorMapEncodeTiled", &fnp, cudaEnableDefault, &qr);
  EncFn fn = (EncFn)fnp;
  void* gG = nullptr;
  cudaGetSymbolAddress(&gG, g_G);
  const cuuint64_t RB = DM * 2;
  {
    p.swap = p.bim < p.bre;
    const char* lo = (const char*)(p.swap ? p.bim : p.bre); const char* hi = (const char*)(p.swap ? p.bre : p.bim);
    cuuint64_t dims[5] = {640, 8, 2, 8, 10}, st[4] = {RB, (cuuint64_t)(hi - lo), 8 * RB, 64 * RB}; cuuint32_t box[5] = {64, 8, 2, 4, 2};
    encode(fn, &p.mB, lo, 5, dims, st, box);
  }
  {
    cuuint64_t dims[5] = {640, 2, 4, 2, 40}, st[4] = {RB, 4 * RB, 2 * RB, 16 * RB}; cuuint32_t box[5] = {64, 2, 4, 2, 10};
    encode(fn, &p.mCre, p.cre, 5, dims, st, box); encode(fn, &p.mCim, p.cim, 5, dims, st, box);
    cuuint64_t dimg[5] = {2048, 2, 4, 2, 40}, stg[4] = {4096, 4 * 4096, 2 * 4096, 16 * 4096};
    encode(fn, &p.mG, gG, 5, dimg, stg, box);
  }
  {
    cuuint64_t dims[4] = {640, 2, 4, 900}, st[3] = {RB, 40 * RB, 2 * RB}; cuuint32_t box[4] = {64, 2, 4, 20};
    encode(fn, &p.mX, p.x, 4, dims, st, box);
    cuuint64_t diml[4] = {640, 2, 4, 16}, stl[3] = {RB, 32 * RB, 2 * RB};
    encode(fn, &p.mXl, p.x + (size_t)1920 * DM, 4, diml, stl, box);
    cuuint32_t boxt[4] = {160, 2, 4, 4};
    encode(fn, &p.mXt, p.x, 4, dims, st, boxt, CU_TENSOR_MAP_SWIZZLE_NONE);
    encode(fn, &p.mXtl, p.x + (size_t)1920 * DM, 4, diml, stl, boxt, CU_TENSOR_MAP_SWIZZLE_NONE);
    cuuint64_t dk[3] = {640, 2000, 4}, sk[2] = {RB, 16 * RB}; cuuint32_t bk[3] = {32, 19, 4}, bv[3] = {32, 17, 4};
    encode(fn, &p.mK, p.k, 3, dk, sk, bk, CU_TENSOR_MAP_SWIZZLE_NONE);
    encode(fn, &p.mV, p.v, 3, dk, sk, bv, CU_TENSOR_MAP_SWIZZLE_NONE);
  }
  cudaFuncSetAttribute(fused_kernel, cudaFuncAttributeMaxDynamicSharedMemorySize, SMEM_BYTES);
  cudaLaunchConfig_t cfg = {};
  cfg.gridDim = dim3(132); cfg.blockDim = dim3(512); cfg.dynamicSmemBytes = SMEM_BYTES; cfg.stream = cudaStreamPerThread;
  cudaLaunchKernelEx(&cfg, fused_kernel, p);
}
```

```cpp
#include <cuda_runtime.h>
#include <cuda.h>
#include <cuda_bf16.h>
#include <stdint.h>

namespace {

constexpr int SEQ = 2048, DM = 640;
constexpr int NT1 = 13;
#define EXP 0
#define WPF1 1
#define WPF2 2
#define CPOLL 10
#define KV0 5
#define TAP0 2
#define PROM_A 2
#define PROM_B 2
#define XFIRST 0
#define TAPLATE 1
#define STG_D 3
#define STG_KK 1
#define PAUSE_K 3
constexpr uint32_t SPIN_LIMIT = 1u << 22;

__device__ __align__(1024) uint8_t g_h[2 * 32 * 20 * 8192];
__device__ __align__(1024) uint8_t g_u[NT1 * 10 * 20480];
__device__ __align__(1024) uint8_t g_kv[DM * 4096];
__device__ __align__(1024) uint8_t g_G[DM * 4096];
__device__ __align__(128) uint4 g_E[2 * NT1 * DM];
__device__ __align__(128) uint4 g_stats[4 * 4 * SEQ];
__device__ __align__(128) uint4 g_sB[DM * 2];
__device__ __align__(128) unsigned g_hflag[2 * NT1 * 2 * 16 * 8];
__device__ __align__(128) unsigned g_uflag[32 * 4 * 8];
__device__ __align__(128) unsigned g_kvflag[4 * 32 * 8];
__device__ __align__(128) unsigned g_gflag[4 * 32 * 8];
__device__ __align__(128) unsigned g_epoch[32] = {1};
#define TS(i) do {} while (0)

struct Params {
  CUtensorMap mB, mCre, mCim, mX, mXl, mG, mK, mV, mXt, mXtl;
  const __nv_bfloat16 *x, *lre, *lim, *bre, *bim, *cre, *cim, *logdt, *dskip, *k, *v, *shiftk, *ssmk, *ssmD;
  float* out;
  int swap;
  int role[132];
};

constexpr uint32_t sb = 1024;
constexpr uint32_t G1_STAGE = 36864, G1_XOFF = 16384;
constexpr int S1 = 4;
constexpr uint32_t XT_OFF = 159744, KS_OFF = 180224, KV_PIECE = 9216;
constexpr uint32_t G2_XB = 8192, G2_WB = 20480, G2_WOFF = 57344, G_OFF = 200704;
constexpr int SX2 = 5;
constexpr uint32_t CV_OFF = KS_OFF, CV_K = 128, CV_PL = 2240, CV_U = CV_K + 4096, CV_B = KV_PIECE;
constexpr uint32_t MISC = 226304;
constexpr uint32_t BAR_OFF = MISC;
constexpr int B_G1FULL = 0, B_G1DONE = 20, B_G2FULL = 40, B_CVFULL = 80  ,
              B_G2DONE = 85, B_GFULL = 125, B_EP = 126, B_H1 = 127  , B_TAPS = 129  , B_STG = 134  ,
              B_GO = 139  , B_PD = 142  , B_PUB = 147,
              B_CVDONE = 148  , B_STAB = 153  , B_XFREE = 155, B_HST = 156  ,
              B_CTAB = 160, B_PREP = 161, B_XT = 162, B_KV = 163  ;
constexpr uint32_t bars = sb + BAR_OFF;
constexpr uint32_t STAB_OFF = MISC + 1344;
constexpr uint32_t CTAB_OFF = STAB_OFF + 1280;
constexpr uint32_t DTAB_OFF = CTAB_OFF + 1536;
constexpr uint32_t EP_OFF = DTAB_OFF + 320;
constexpr uint32_t SO_OFF = EP_OFF + 32;
constexpr uint32_t TAP_OFF = 147456;
constexpr uint32_t SMEM_BYTES = 232448;
static_assert(SO_OFF + 1536 <= SMEM_BYTES, "smem");

__device__ __forceinline__ void trap_if(bool c) { asm volatile("{\n.reg .pred p;\nsetp.ne.u32 p, %0, 0;\n@p trap;\n}\n" ::"r"((uint32_t)c)); }
__device__ __forceinline__ uint32_t smem_u32(const void* p) { return (uint32_t)__cvta_generic_to_shared(p); }
__device__ __forceinline__ void mbar_init(uint32_t bar, int cnt) { asm volatile("mbarrier.init.shared::cta.b64 [%0], %1;" ::"r"(bar), "r"(cnt) : "memory"); }
__device__ __forceinline__ void mbar_expect_tx(uint32_t bar, int bytes) { asm volatile("mbarrier.arrive.expect_tx.shared::cta.b64 _, [%0], %1;" ::"r"(bar), "r"(bytes) : "memory"); }
__device__ __forceinline__ void mbar_arrive(uint32_t bar) { asm volatile("mbarrier.arrive.shared::cta.b64 _, [%0];" ::"r"(bar) : "memory"); }
__device__ __forceinline__ void mbar_wait(uint32_t bar) {
  asm volatile(
      "{\n.reg .pred p;\n.reg .u32 c;\nmov.u32 c, 0;\n"
      "W_%=:\nmbarrier.try_wait.parity.shared::cta.b64 p, [%0], 0;\n@p bra D_%=;\n"
      "add.u32 c, c, 1;\nsetp.lt.u32 p, c, %1;\n@p bra W_%=;\ntrap;\nD_%=:\n}\n" ::"r"(bar), "n"(SPIN_LIMIT) : "memory");
}
__device__ __forceinline__ uint32_t mbar_test(uint32_t bar) {
  uint32_t ok;
  asm volatile("{\n.reg .pred p;\nmbarrier.test_wait.parity.shared::cta.b64 p, [%1], 0;\nselp.u32 %0, 1, 0, p;\n}\n" : "=r"(ok) : "r"(bar) : "memory");
  return ok;
}
__device__ __forceinline__ void tma3(uint32_t dst, const CUtensorMap* m, int c0, int c1, int c2, uint32_t bar) {
  asm volatile("cp.async.bulk.tensor.3d.shared::cluster.global.mbarrier::complete_tx::bytes [%0], [%1, {%3,%4,%5}], [%2];"
               ::"r"(dst), "l"(m), "r"(bar), "r"(c0), "r"(c1), "r"(c2) : "memory");
}
__device__ __forceinline__ void tma4(uint32_t dst, const CUtensorMap* m, int c0, int c1, int c2, int c3, uint32_t bar) {
  asm volatile("cp.async.bulk.tensor.4d.shared::cluster.global.mbarrier::complete_tx::bytes [%0], [%1, {%3,%4,%5,%6}], [%2];"
               ::"r"(dst), "l"(m), "r"(bar), "r"(c0), "r"(c1), "r"(c2), "r"(c3) : "memory");
}
__device__ __forceinline__ void tma5(uint32_t dst, const CUtensorMap* m, int c0, int c1, int c2, int c3, int c4, uint32_t bar) {
  asm volatile("cp.async.bulk.tensor.5d.shared::cluster.global.mbarrier::complete_tx::bytes [%0], [%1, {%3,%4,%5,%6,%7}], [%2];"
               ::"r"(dst), "l"(m), "r"(bar), "r"(c0), "r"(c1), "r"(c2), "r"(c3), "r"(c4) : "memory");
}
__device__ __forceinline__ void bulk_g2s(uint32_t dst, const void* src, int bytes, uint32_t bar) {
  asm volatile("cp.async.bulk.shared::cluster.global.mbarrier::complete_tx::bytes [%0], [%1], %2, [%3];"
               ::"r"(dst), "l"(src), "r"(bytes), "r"(bar) : "memory");
}
__device__ __forceinline__ void bulk_s2g(void* dst, uint32_t src, int bytes) {
  asm volatile("cp.async.bulk.global.shared::cta.bulk_group [%0], [%1], %2;" ::"l"(dst), "r"(src), "r"(bytes) : "memory");
}
__device__ __forceinline__ void l2_prefetch(const void* src, int bytes) {
  asm volatile("cp.async.bulk.prefetch.L2.global [%0], %1;" ::"l"(src), "r"(bytes) : "memory");
}
__device__ __forceinline__ void wgmma_fence() { asm volatile("wgmma.fence.sync.aligned;" ::: "memory"); }
__device__ __forceinline__ void wgmma_commit() { asm volatile("wgmma.commit_group.sync.aligned;" ::: "memory"); }
template <int N> __device__ __forceinline__ void wgmma_wait() { asm volatile("wgmma.wait_group.sync.aligned %0;" ::"n"(N) : "memory"); }
__host__ __device__ constexpr uint32_t desc_lo(uint32_t addr, uint32_t lbo) { return ((addr & 0x3FFFF) >> 4) | ((lbo >> 4) << 16); }
__host__ __device__ constexpr uint32_t desc_hi(uint32_t sbo, uint32_t swz) { return (sbo >> 4) | (swz << 30); }
__device__ __forceinline__ void bar_sync(int id, int n) { asm volatile("bar.sync %0, %1;" ::"r"(id), "r"(n) : "memory"); }
__device__ __forceinline__ uint32_t lds32(uint32_t a) { uint32_t v; asm volatile("ld.shared.u32 %0, [%1];" : "=r"(v) : "r"(a) : "memory"); return v; }
__device__ __forceinline__ float2 lds64f(uint32_t a) { float2 v; asm volatile("ld.shared.v2.f32 {%0,%1}, [%2];" : "=f"(v.x), "=f"(v.y) : "r"(a) : "memory"); return v; }
__device__ __forceinline__ float4 lds128f(uint32_t a) { float4 v; asm volatile("ld.shared.v4.f32 {%0,%1,%2,%3}, [%4];" : "=f"(v.x), "=f"(v.y), "=f"(v.z), "=f"(v.w) : "r"(a) : "memory"); return v; }
__device__ __forceinline__ void ldsm4t(uint32_t (&r)[4], uint32_t a) {
  asm volatile("ldmatrix.sync.aligned.m8n8.x4.trans.shared.b16 {%0,%1,%2,%3}, [%4];" : "=r"(r[0]), "=r"(r[1]), "=r"(r[2]), "=r"(r[3]) : "r"(a) : "memory");
}
__device__ __forceinline__ uint4 ldv128(const void* a) { uint4 v; asm volatile("ld.global.nc.v4.u32 {%0,%1,%2,%3}, [%4];" : "=r"(v.x), "=r"(v.y), "=r"(v.z), "=r"(v.w) : "l"(a) : "memory"); return v; }
__device__ __forceinline__ uint2 ldv64(const void* a) { uint2 v; asm volatile("ld.global.nc.v2.u32 {%0,%1}, [%2];" : "=r"(v.x), "=r"(v.y) : "l"(a) : "memory"); return v; }
__device__ __forceinline__ uint32_t ldv16(const void* a) { uint32_t v; asm volatile("ld.global.nc.u16 %0, [%1];" : "=r"(v) : "l"(a) : "memory"); return v; }
__device__ __forceinline__ void sts128(uint32_t a, uint4 v) { asm volatile("st.shared.v4.u32 [%0], {%1,%2,%3,%4};" ::"r"(a), "r"(v.x), "r"(v.y), "r"(v.z), "r"(v.w) : "memory"); }
__device__ __forceinline__ void sts32(uint32_t a, uint32_t v) { asm volatile("st.shared.u32 [%0], %1;" ::"r"(a), "r"(v) : "memory"); }
__device__ __forceinline__ void sts64f(uint32_t a, float x, float y) { asm volatile("st.shared.v2.f32 [%0], {%1,%2};" ::"r"(a), "f"(x), "f"(y) : "memory"); }
__device__ __forceinline__ void st_rel(unsigned* p, unsigned v) { asm volatile("st.release.gpu.global.u32 [%0], %1;" ::"l"(p), "r"(v) : "memory"); }
__device__ __forceinline__ void fence_async_global() { asm volatile("fence.proxy.async.global;" ::: "memory"); }
__device__ __forceinline__ void fence_async_smem() { asm volatile("fence.proxy.async.shared::cta;" ::: "memory"); }
__device__ __forceinline__ void rec_st(uint4* p, float a, float b, unsigned tag) {
  asm volatile("{\n.reg .b128 t;\n.reg .b64 lo, hi;\nmov.b64 lo, {%1,%2};\nmov.b64 hi, {%3,%3};\nmov.b128 t, {lo,hi};\n"
               "st.relaxed.gpu.global.b128 [%0], t;\n}\n" ::"l"(p), "r"(__float_as_uint(a)), "r"(__float_as_uint(b)), "r"(tag) : "memory");
}
__device__ __forceinline__ unsigned rec_ld(const uint4* p, float& a, float& b) {
  unsigned x, y, t;
  asm volatile("{\n.reg .b128 t;\n.reg .b64 lo, hi;\n.reg .b32 u;\nld.relaxed.gpu.global.b128 t, [%3];\nmov.b128 {lo,hi}, t;\n"
               "mov.b64 {%0,%1}, lo;\nmov.b64 {%2,u}, hi;\n}\n" : "=r"(x), "=r"(y), "=r"(t) : "l"(p) : "memory");
  a = __uint_as_float(x); b = __uint_as_float(y);
  return t;
}
__device__ __forceinline__ void rec_poll(const uint4* p, unsigned tag, float& a, float& b) {
  uint32_t it = 0;
  while (!__all_sync(0xffffffffu, rec_ld(p, a, b) == tag)) { trap_if(++it > SPIN_LIMIT); }
}
__device__ __forceinline__ unsigned ld_rlx(const unsigned* p) { unsigned v; asm volatile("ld.relaxed.gpu.global.u32 %0, [%1];" : "=r"(v) : "l"(p) : "memory"); return v; }
__device__ __forceinline__ void flag_poll(const unsigned* p, unsigned target) {
  uint32_t it = 0;
  while (!__all_sync(0xffffffffu, (int)(ld_rlx(p) - target) >= 0)) { trap_if(++it > SPIN_LIMIT); }
  asm volatile("fence.acquire.gpu;" ::: "memory");
}
__device__ __forceinline__ uint32_t pack_bf16(float lo, float hi) {
  uint32_t r; asm("cvt.rn.bf16x2.f32 %0, %1, %2;" : "=r"(r) : "f"(hi), "f"(lo)); return r;
}
__device__ __forceinline__ float bf_lo(uint32_t w) { return __uint_as_float(w << 16); }
__device__ __forceinline__ float bf_hi(uint32_t w) { return __uint_as_float(w & 0xffff0000u); }
__device__ __forceinline__ uint32_t hmul2(uint32_t a, uint32_t b) {
  __nv_bfloat162 r = __hmul2_rn(*(__nv_bfloat162*)&a, *(__nv_bfloat162*)&b); return *(uint32_t*)&r;
}
__device__ __forceinline__ uint32_t hadd2(uint32_t a, uint32_t b) {
  __nv_bfloat162 r = __hadd2_rn(*(__nv_bfloat162*)&a, *(__nv_bfloat162*)&b); return *(uint32_t*)&r;
}
__device__ __forceinline__ float2 cmul(float2 a, float2 b) { return make_float2(a.x * b.x - a.y * b.y, a.x * b.y + a.y * b.x); }
__device__ __forceinline__ float2 cfma(float2 a, float2 b, float2 c) {
  return make_float2(fmaf(a.x, b.x, fmaf(-a.y, b.y, c.x)), fmaf(a.x, b.y, fmaf(a.y, b.x, c.y)));
}
template <int N> __device__ __forceinline__ void fence_regs(float (&a)[N]) {
#pragma unroll
  for (int i = 0; i < N; i++) asm volatile("" : "+f"(a[i])::"memory");
}
__device__ __forceinline__ bool elect_one() {
  uint32_t e; asm volatile("{\n.reg .pred P;\nelect.sync _|P, 0xffffffff;\nselp.u32 %0, 1, 0, P;\n}\n" : "=r"(e)); return e != 0;
}
__device__ __forceinline__ int tid_opaque() { int t; asm volatile("mov.u32 %0, %%tid.x;" : "=r"(t)); return t; }
struct Role { int T1, GP, side, m2, dg, cch0; bool last, has2; };
__device__ __forceinline__ Role unpack_role(int x) {
  Role r; r.T1 = x & 15; r.GP = (x >> 4) & 7; r.side = (x >> 7) & 1; r.m2 = (x >> 8) & 63; r.dg = (x >> 14) & 3;
  r.has2 = (x >> 16) & 1; r.last = r.T1 == NT1 - 1; r.cch0 = 160 * r.dg + r.m2; return r;
}
__device__ __forceinline__ Role fresh_role(int x) { asm volatile("" : "+r"(x)); return unpack_role(__shfl_sync(0xffffffffu, x, 0)); }
#define ROLE(x) const Role R_ = fresh_role(x); const int T1 = R_.T1, GP = R_.GP, side = R_.side, m2 = R_.m2, dg = R_.dg, cch0 = R_.cch0; \
  const bool last = R_.last, has2 = R_.has2; (void)T1; (void)GP; (void)side; (void)m2; (void)dg; (void)cch0; (void)last; (void)has2;
__device__ __forceinline__ int n_to_t(int n) {
  int T = n / 160, nl = n - T * 160;
  int L = (T == NT1 - 1) ? 32 : 40;
  return T * 160 + L * ((nl & 7) >> 1) + 2 * (nl >> 3) + (nl & 1);
}

template<int TA> __device__ __forceinline__ void wgmma_n160(float (&d)[80], uint32_t alo, uint32_t ahi, uint32_t blo, uint32_t bhi){
  asm volatile("{\n.reg .b64 da, db;\nmov.b64 da, {%80,%81};\nmov.b64 db, {%82,%83};\n"
    "wgmma.mma_async.sync.aligned.m64n160k16.f32.bf16.bf16 {%0, %1, %2, %3, %4, %5, %6, %7, %8, %9, %10, %11, %12, %13, %14, %15, %16, %17, %18, %19, %20, %21, %22, %23, %24, %25, %26, %27, %28, %29, %30, %31, %32, %33, %34, %35, %36, %37, %38, %39, %40, %41, %42, %43, %44, %45, %46, %47, %48, %49, %50, %51, %52, %53, %54, %55, %56, %57, %58, %59, %60, %61, %62, %63, %64, %65, %66, %67, %68, %69, %70, %71, %72, %73, %74, %75, %76, %77, %78, %79}, da, db, 1, 1, 1, %84, 0;\n}\n"
    : "+f"(d[0]), "+f"(d[1]), "+f"(d[2]), "+f"(d[3]), "+f"(d[4]), "+f"(d[5]), "+f"(d[6]), "+f"(d[7]), "+f"(d[8]), "+f"(d[9]), "+f"(d[10]), "+f"(d[11]), "+f"(d[12]), "+f"(d[13]), "+f"(d[14]), "+f"(d[15]), "+f"(d[16]), "+f"(d[17]), "+f"(d[18]), "+f"(d[19]), "+f"(d[20]), "+f"(d[21]), "+f"(d[22]), "+f"(d[23]), "+f"(d[24]), "+f"(d[25]), "+f"(d[26]), "+f"(d[27]), "+f"(d[28]), "+f"(d[29]), "+f"(d[30]), "+f"(d[31]), "+f"(d[32]), "+f"(d[33]), "+f"(d[34]), "+f"(d[35]), "+f"(d[36]), "+f"(d[37]), "+f"(d[38]), "+f"(d[39]), "+f"(d[40]), "+f"(d[41]), "+f"(d[42]), "+f"(d[43]), "+f"(d[44]), "+f"(d[45]), "+f"(d[46]), "+f"(d[47]), "+f"(d[48]), "+f"(d[49]), "+f"(d[50]), "+f"(d[51]), "+f"(d[52]), "+f"(d[53]), "+f"(d[54]), "+f"(d[55]), "+f"(d[56]), "+f"(d[57]), "+f"(d[58]), "+f"(d[59]), "+f"(d[60]), "+f"(d[61]), "+f"(d[62]), "+f"(d[63]), "+f"(d[64]), "+f"(d[65]), "+f"(d[66]), "+f"(d[67]), "+f"(d[68]), "+f"(d[69]), "+f"(d[70]), "+f"(d[71]), "+f"(d[72]), "+f"(d[73]), "+f"(d[74]), "+f"(d[75]), "+f"(d[76]), "+f"(d[77]), "+f"(d[78]), "+f"(d[79])
    : "r"(alo), "r"(ahi), "r"(blo), "r"(bhi), "n"(TA));
}
template<int N> __device__ __forceinline__ void wgmma_rs_hi(float (&d)[64], uint32_t a0, uint32_t a1, uint32_t a2, uint32_t a3, uint32_t blo);
template<> __device__ __forceinline__ void wgmma_rs_hi<16>(float (&d)[64], uint32_t a0, uint32_t a1, uint32_t a2, uint32_t a3, uint32_t blo){
  asm volatile("{\n.reg .b64 db;\nmov.b64 db, {%12,8};\nwgmma.mma_async.sync.aligned.m64n16k16.f32.bf16.bf16 {%0, %1, %2, %3, %4, %5, %6, %7}, {%8,%9,%10,%11}, db, 1, 1, 1, 0;\n}\n"
    : "+f"(d[56]), "+f"(d[57]), "+f"(d[58]), "+f"(d[59]), "+f"(d[60]), "+f"(d[61]), "+f"(d[62]), "+f"(d[63])
    : "r"(a0), "r"(a1), "r"(a2), "r"(a3), "r"(blo));
}
template<> __device__ __forceinline__ void wgmma_rs_hi<32>(float (&d)[64], uint32_t a0, uint32_t a1, uint32_t a2, uint32_t a3, uint32_t blo){
  asm volatile("{\n.reg .b64 db;\nmov.b64 db, {%20,8};\nwgmma.mma_async.sync.aligned.m64n32k16.f32.bf16.bf16 {%0, %1, %2, %3, %4, %5, %6, %7, %8, %9, %10, %11, %12, %13, %14, %15}, {%16,%17,%18,%19}, db, 1, 1, 1, 0;\n}\n"
    : "+f"(d[48]), "+f"(d[49]), "+f"(d[50]), "+f"(d[51]), "+f"(d[52]), "+f"(d[53]), "+f"(d[54]), "+f"(d[55]), "+f"(d[56]), "+f"(d[57]), "+f"(d[58]), "+f"(d[59]), "+f"(d[60]), "+f"(d[61]), "+f"(d[62]), "+f"(d[63])
    : "r"(a0), "r"(a1), "r"(a2), "r"(a3), "r"(blo));
}
template<> __device__ __forceinline__ void wgmma_rs_hi<48>(float (&d)[64], uint32_t a0, uint32_t a1, uint32_t a2, uint32_t a3, uint32_t blo){
  asm volatile("{\n.reg .b64 db;\nmov.b64 db, {%28,8};\nwgmma.mma_async.sync.aligned.m64n48k16.f32.bf16.bf16 {%0, %1, %2, %3, %4, %5, %6, %7, %8, %9, %10, %11, %12, %13, %14, %15, %16, %17, %18, %19, %20, %21, %22, %23}, {%24,%25,%26,%27}, db, 1, 1, 1, 0;\n}\n"
    : "+f"(d[40]), "+f"(d[41]), "+f"(d[42]), "+f"(d[43]), "+f"(d[44]), "+f"(d[45]), "+f"(d[46]), "+f"(d[47]), "+f"(d[48]), "+f"(d[49]), "+f"(d[50]), "+f"(d[51]), "+f"(d[52]), "+f"(d[53]), "+f"(d[54]), "+f"(d[55]), "+f"(d[56]), "+f"(d[57]), "+f"(d[58]), "+f"(d[59]), "+f"(d[60]), "+f"(d[61]), "+f"(d[62]), "+f"(d[63])
    : "r"(a0), "r"(a1), "r"(a2), "r"(a3), "r"(blo));
}
template<> __device__ __forceinline__ void wgmma_rs_hi<64>(float (&d)[64], uint32_t a0, uint32_t a1, uint32_t a2, uint32_t a3, uint32_t blo){
  asm volatile("{\n.reg .b64 db;\nmov.b64 db, {%36,8};\nwgmma.mma_async.sync.aligned.m64n64k16.f32.bf16.bf16 {%0, %1, %2, %3, %4, %5, %6, %7, %8, %9, %10, %11, %12, %13, %14, %15, %16, %17, %18, %19, %20, %21, %22, %23, %24, %25, %26, %27, %28, %29, %30, %31}, {%32,%33,%34,%35}, db, 1, 1, 1, 0;\n}\n"
    : "+f"(d[32]), "+f"(d[33]), "+f"(d[34]), "+f"(d[35]), "+f"(d[36]), "+f"(d[37]), "+f"(d[38]), "+f"(d[39]), "+f"(d[40]), "+f"(d[41]), "+f"(d[42]), "+f"(d[43]), "+f"(d[44]), "+f"(d[45]), "+f"(d[46]), "+f"(d[47]), "+f"(d[48]), "+f"(d[49]), "+f"(d[50]), "+f"(d[51]), "+f"(d[52]), "+f"(d[53]), "+f"(d[54]), "+f"(d[55]), "+f"(d[56]), "+f"(d[57]), "+f"(d[58]), "+f"(d[59]), "+f"(d[60]), "+f"(d[61]), "+f"(d[62]), "+f"(d[63])
    : "r"(a0), "r"(a1), "r"(a2), "r"(a3), "r"(blo));
}
template<> __device__ __forceinline__ void wgmma_rs_hi<80>(float (&d)[64], uint32_t a0, uint32_t a1, uint32_t a2, uint32_t a3, uint32_t blo){
  asm volatile("{\n.reg .b64 db;\nmov.b64 db, {%44,8};\nwgmma.mma_async.sync.aligned.m64n80k16.f32.bf16.bf16 {%0, %1, %2, %3, %4, %5, %6, %7, %8, %9, %10, %11, %12, %13, %14, %15, %16, %17, %18, %19, %20, %21, %22, %23, %24, %25, %26, %27, %28, %29, %30, %31, %32, %33, %34, %35, %36, %37, %38, %39}, {%40,%41,%42,%43}, db, 1, 1, 1, 0;\n}\n"
    : "+f"(d[24]), "+f"(d[25]), "+f"(d[26]), "+f"(d[27]), "+f"(d[28]), "+f"(d[29]), "+f"(d[30]), "+f"(d[31]), "+f"(d[32]), "+f"(d[33]), "+f"(d[34]), "+f"(d[35]), "+f"(d[36]), "+f"(d[37]), "+f"(d[38]), "+f"(d[39]), "+f"(d[40]), "+f"(d[41]), "+f"(d[42]), "+f"(d[43]), "+f"(d[44]), "+f"(d[45]), "+f"(d[46]), "+f"(d[47]), "+f"(d[48]), "+f"(d[49]), "+f"(d[50]), "+f"(d[51]), "+f"(d[52]), "+f"(d[53]), "+f"(d[54]), "+f"(d[55]), "+f"(d[56]), "+f"(d[57]), "+f"(d[58]), "+f"(d[59]), "+f"(d[60]), "+f"(d[61]), "+f"(d[62]), "+f"(d[63])
    : "r"(a0), "r"(a1), "r"(a2), "r"(a3), "r"(blo));
}
template<> __device__ __forceinline__ void wgmma_rs_hi<96>(float (&d)[64], uint32_t a0, uint32_t a1, uint32_t a2, uint32_t a3, uint32_t blo){
  asm volatile("{\n.reg .b64 db;\nmov.b64 db, {%52,8};\nwgmma.mma_async.sync.aligned.m64n96k16.f32.bf16.bf16 {%0, %1, %2, %3, %4, %5, %6, %7, %8, %9, %10, %11, %12, %13, %14, %15, %16, %17, %18, %19, %20, %21, %22, %23, %24, %25, %26, %27, %28, %29, %30, %31, %32, %33, %34, %35, %36, %37, %38, %39, %40, %41, %42, %43, %44, %45, %46, %47}, {%48,%49,%50,%51}, db, 1, 1, 1, 0;\n}\n"
    : "+f"(d[16]), "+f"(d[17]), "+f"(d[18]), "+f"(d[19]), "+f"(d[20]), "+f"(d[21]), "+f"(d[22]), "+f"(d[23]), "+f"(d[24]), "+f"(d[25]), "+f"(d[26]), "+f"(d[27]), "+f"(d[28]), "+f"(d[29]), "+f"(d[30]), "+f"(d[31]), "+f"(d[32]), "+f"(d[33]), "+f"(d[34]), "+f"(d[35]), "+f"(d[36]), "+f"(d[37]), "+f"(d[38]), "+f"(d[39]), "+f"(d[40]), "+f"(d[41]), "+f"(d[42]), "+f"(d[43]), "+f"(d[44]), "+f"(d[45]), "+f"(d[46]), "+f"(d[47]), "+f"(d[48]), "+f"(d[49]), "+f"(d[50]), "+f"(d[51]), "+f"(d[52]), "+f"(d[53]), "+f"(d[54]), "+f"(d[55]), "+f"(d[56]), "+f"(d[57]), "+f"(d[58]), "+f"(d[59]), "+f"(d[60]), "+f"(d[61]), "+f"(d[62]), "+f"(d[63])
    : "r"(a0), "r"(a1), "r"(a2), "r"(a3), "r"(blo));
}
template<> __device__ __forceinline__ void wgmma_rs_hi<112>(float (&d)[64], uint32_t a0, uint32_t a1, uint32_t a2, uint32_t a3, uint32_t blo){
  asm volatile("{\n.reg .b64 db;\nmov.b64 db, {%60,8};\nwgmma.mma_async.sync.aligned.m64n112k16.f32.bf16.bf16 {%0, %1, %2, %3, %4, %5, %6, %7, %8, %9, %10, %11, %12, %13, %14, %15, %16, %17, %18, %19, %20, %21, %22, %23, %24, %25, %26, %27, %28, %29, %30, %31, %32, %33, %34, %35, %36, %37, %38, %39, %40, %41, %42, %43, %44, %45, %46, %47, %48, %49, %50, %51, %52, %53, %54, %55}, {%56,%57,%58,%59}, db, 1, 1, 1, 0;\n}\n"
    : "+f"(d[8]), "+f"(d[9]), "+f"(d[10]), "+f"(d[11]), "+f"(d[12]), "+f"(d[13]), "+f"(d[14]), "+f"(d[15]), "+f"(d[16]), "+f"(d[17]), "+f"(d[18]), "+f"(d[19]), "+f"(d[20]), "+f"(d[21]), "+f"(d[22]), "+f"(d[23]), "+f"(d[24]), "+f"(d[25]), "+f"(d[26]), "+f"(d[27]), "+f"(d[28]), "+f"(d[29]), "+f"(d[30]), "+f"(d[31]), "+f"(d[32]), "+f"(d[33]), "+f"(d[34]), "+f"(d[35]), "+f"(d[36]), "+f"(d[37]), "+f"(d[38]), "+f"(d[39]), "+f"(d[40]), "+f"(d[41]), "+f"(d[42]), "+f"(d[43]), "+f"(d[44]), "+f"(d[45]), "+f"(d[46]), "+f"(d[47]), "+f"(d[48]), "+f"(d[49]), "+f"(d[50]), "+f"(d[51]), "+f"(d[52]), "+f"(d[53]), "+f"(d[54]), "+f"(d[55]), "+f"(d[56]), "+f"(d[57]), "+f"(d[58]), "+f"(d[59]), "+f"(d[60]), "+f"(d[61]), "+f"(d[62]), "+f"(d[63])
    : "r"(a0), "r"(a1), "r"(a2), "r"(a3), "r"(blo));
}
template<> __device__ __forceinline__ void wgmma_rs_hi<128>(float (&d)[64], uint32_t a0, uint32_t a1, uint32_t a2, uint32_t a3, uint32_t blo){
  asm volatile("{\n.reg .b64 db;\nmov.b64 db, {%68,8};\nwgmma.mma_async.sync.aligned.m64n128k16.f32.bf16.bf16 {%0, %1, %2, %3, %4, %5, %6, %7, %8, %9, %10, %11, %12, %13, %14, %15, %16, %17, %18, %19, %20, %21, %22, %23, %24, %25, %26, %27, %28, %29, %30, %31, %32, %33, %34, %35, %36, %37, %38, %39, %40, %41, %42, %43, %44, %45, %46, %47, %48, %49, %50, %51, %52, %53, %54, %55, %56, %57, %58, %59, %60, %61, %62, %63}, {%64,%65,%66,%67}, db, 1, 1, 1, 0;\n}\n"
    : "+f"(d[0]), "+f"(d[1]), "+f"(d[2]), "+f"(d[3]), "+f"(d[4]), "+f"(d[5]), "+f"(d[6]), "+f"(d[7]), "+f"(d[8]), "+f"(d[9]), "+f"(d[10]), "+f"(d[11]), "+f"(d[12]), "+f"(d[13]), "+f"(d[14]), "+f"(d[15]), "+f"(d[16]), "+f"(d[17]), "+f"(d[18]), "+f"(d[19]), "+f"(d[20]), "+f"(d[21]), "+f"(d[22]), "+f"(d[23]), "+f"(d[24]), "+f"(d[25]), "+f"(d[26]), "+f"(d[27]), "+f"(d[28]), "+f"(d[29]), "+f"(d[30]), "+f"(d[31]), "+f"(d[32]), "+f"(d[33]), "+f"(d[34]), "+f"(d[35]), "+f"(d[36]), "+f"(d[37]), "+f"(d[38]), "+f"(d[39]), "+f"(d[40]), "+f"(d[41]), "+f"(d[42]), "+f"(d[43]), "+f"(d[44]), "+f"(d[45]), "+f"(d[46]), "+f"(d[47]), "+f"(d[48]), "+f"(d[49]), "+f"(d[50]), "+f"(d[51]), "+f"(d[52]), "+f"(d[53]), "+f"(d[54]), "+f"(d[55]), "+f"(d[56]), "+f"(d[57]), "+f"(d[58]), "+f"(d[59]), "+f"(d[60]), "+f"(d[61]), "+f"(d[62]), "+f"(d[63])
    : "r"(a0), "r"(a1), "r"(a2), "r"(a3), "r"(blo));
}

__device__ __forceinline__ float shfl_sel(float a, float b, bool p, int src) {
  float r;
  asm volatile("{\n.reg .pred P;\n.reg .f32 t;\nsetp.ne.u32 P, %3, 0;\nselp.f32 t, %1, %2, P;\nshfl.sync.idx.b32 %0, t, %4, 0x1f, 0xffffffff;\n}\n"
               : "=f"(r) : "f"(a), "f"(b), "r"((uint32_t)p), "r"(src));
  return r;
}
struct CvCtx {
  uint32_t koff, zero, so[3];
  int srcA, srcB;
  bool wrapA, s3, kodd;
};
struct CvPipe { float Ep[2], keep[2], send[2]; };
template <int LO> __device__ __forceinline__ void cv_copy(float (&acc)[64]) {
#pragma unroll
  for (int i = LO; i < 64; i++) { float t; asm volatile("mov.b32 %0, %1;" : "=f"(t) : "f"(acc[i]) : "memory"); acc[i] = t; }
}
template <int G> __device__ __forceinline__ void cv_raw(uint32_t (&A)[4][4], uint32_t kaddr) {
#pragma unroll
  for (int i = 0; i < 4; i++) {
    const uint32_t a = kaddr + (4 * G + i) * 128;
    A[i][0] = lds32(a); A[i][1] = lds32(a + 4); A[i][3] = lds32(a + 8);
  }
}
__device__ __forceinline__ void cv_form(uint32_t (&A)[4][4], uint32_t sel) {
#pragma unroll
  for (int i = 0; i < 4; i++) {
    asm volatile("prmt.b32 %0, %0, %1, %2;" : "+r"(A[i][0]) : "r"(A[i][1]), "r"(sel));
    asm volatile("prmt.b32 %0, %1, %2, %3;" : "=r"(A[i][2]) : "r"(A[i][1]), "r"(A[i][3]), "r"(sel));
  }
}
#define CVV 2
template <int G> __device__ __forceinline__ void cv_step(float (&acc)[64], uint32_t (&A)[4][4], CvPipe& s, const CvCtx& c, uint32_t cb, uint32_t stg) {
  constexpr int JA = G - 1, JB = G - 2, NH = CVV == 1 ? 4 : (CVV == 3 ? 2 : 1);
  const uint32_t db0 = desc_lo(cb + CV_U + 192, CV_PL);
  uint32_t B[4][4];
  float ra[4], rb[2];
  if constexpr (G < 8) {
    wgmma_fence();
#pragma unroll
    for (int i = 0; i < NH; i++) wgmma_rs_hi<128 - 16 * (G & 7)>(acc, A[i][0], A[i][1], A[i][2], A[i][3], db0 - 4 * i);
    wgmma_commit();
    __syncwarp();
  }
  if constexpr (JA >= 0 && JA < 8) {
#pragma unroll
    for (int x = 0; x < 4; x++) {
      const int i = 8 * JA + 4 * (x >> 1) + 2 * (x & 1) + 1;
      ra[x] = shfl_sel(i >= 4 ? acc[i >= 4 ? i - 4 : 0] : 0.f, acc[i], c.wrapA, c.srcA);
    }
  }
  if constexpr (JB >= 0) {
#pragma unroll
    for (int h = 0; h < 2; h++) rb[h] = __shfl_sync(0xffffffffu, s.send[h], c.srcB);
  }
  if constexpr (G < 7) cv_raw<G + 1>(B, cb + c.koff);
  uint32_t z = 0;
  if constexpr (G < 8 && NH < 4) {
    __syncwarp();
    wgmma_fence();
#pragma unroll
    for (int i = NH; i < 4; i++) wgmma_rs_hi<128 - 16 * (G & 7)>(acc, A[i][0], A[i][1], A[i][2], A[i][3], db0 - 4 * i);
    wgmma_commit();
    asm volatile("mov.u32 %0, %%clock;" : "=r"(z)::"memory");
    z &= c.zero;
  }
  const float one = __uint_as_float(0x3f800000u | z);
  if constexpr (G < 7) cv_form(B, 0x5432u | z);
  if constexpr (JB >= 0) sts32(stg + ((c.so[JB / 3] >> (10 * (JB % 3))) & 0xffc), pack_bf16(fmaf(rb[0], one, s.keep[0]), fmaf(rb[1], one, s.keep[1])));
  if constexpr (JA >= 0 && JA < 8) {
#pragma unroll
    for (int h = 0; h < 2; h++) {
      const float ev = fmaf(ra[h], one, acc[8 * JA + 2 * h]), od = fmaf(ra[2 + h], one, acc[8 * JA + 4 + 2 * h]);
      s.send[h] = c.kodd ? ev : (c.s3 ? s.Ep[h] : od);
      s.keep[h] = c.kodd ? od : ev;
      s.Ep[h] = od;
    }
  }
  if constexpr (G < 8) { __syncwarp(); wgmma_wait<0>(); cv_copy<8 * (G & 7)>(acc); }
  if constexpr (G < 9) cv_step<G + 1>(acc, B, s, c, cb, stg);
}
__device__ __forceinline__ uint32_t cv_stage(int slot) { return sb + (slot < 4 ? 40960 + slot * 4096 : CV_OFF + CV_K); }
__device__ __forceinline__ void cv_setup(CvCtx& c) {
  const int tid = tid_opaque() & 127, w = tid >> 5, lane = tid & 31, r = lane >> 2, q = lane & 3;
  const int i0 = (r >> 1) & 1, i1 = r >> 2;
  c.koff = CV_K - 32 + 4 * (8 * (r >> 1) + 2 * w + (r & 1) + 2 * q);
  c.srcA = i0 ? lane - 8 : lane + 8 - q + ((q + 3) & 3);
  c.wrapA = i0 && q == 3;
  c.srcB = i1 == 0 ? (lane - q + 16 + ((q + 3) & 3)) : (lane - q - 16 + ((q + 1) & 3));
  c.s3 = (i1 == 1 && q == 3); c.kodd = (i1 == 1 && q < 3);
  c.zero = lds32(sb + EP_OFF + 24);
#pragma unroll
  for (int i = 0; i < 3; i++) c.so[i] = lds32(sb + SO_OFF + 512 * i + 4 * tid);
}
__device__ __forceinline__ void cv_table() {
  const int tid = tid_opaque() & 127, r = (tid & 31) >> 2, q = tid & 3;
  int t = 16 * (2 * (r < 4 ? q : 4 + ((q + 1) & 3)) + ((r >> 1) & 1)) + 4 * (tid >> 5) + 2 * (r & 1);
#pragma unroll 1
  for (int i = 0; i < 3; i++) {
    uint32_t v = 0;
#pragma unroll 1
    for (int x = 0; x < 3; x++, t += 256) {
      const int T = t / 160, tl = t - T * 160;
      const int qq = (T >= NT1 - 1) ? (tl >> 5) : (tl / 40);
      int ck = 20 * T + ((tl - qq * ((T >= NT1 - 1) ? 32 : 40)) >> 1);
      ck ^= (ck >> 2) & 6;
      v |= (uint32_t)((ck * 4 + qq) & 1023) << (10 * x + 2);
    }
    sts32(sb + SO_OFF + 512 * i + 4 * tid, v);
  }
}
__device__ __forceinline__ void conv_channel(int slot, const CvCtx& c) {
  const uint32_t cb = sb + CV_OFF + slot * CV_B;
  float acc[64];
  CvPipe s;
  s.Ep[0] = s.Ep[1] = 0.f;
  uint32_t A[4][4];
#pragma unroll
  for (int i = 0; i < 64; i++) acc[i] = 0.f;
  if (slot == 4) mbar_wait(bars + 8 * B_CVDONE);
  mbar_wait(bars + 8 * (B_CVFULL + slot));
  cv_raw<0>(A, cb + c.koff);
  cv_form(A, 0x5432u);
  cv_copy<0>(acc);
  cv_step<0>(acc, A, s, c, cb, cv_stage(slot));
  fence_async_smem();
  mbar_arrive(bars + 8 * (B_CVDONE + slot));
}

__device__ __forceinline__ void tap_patch(int c) {
  mbar_wait(bars + 8 * (B_TAPS + c));
  const uint32_t a = sb + CV_OFF + c * CV_B + CV_K, w0 = lds32(a);
  sts32(a, (w0 & 0xffff0000u) | (pack_bf16(bf_lo(w0) + __uint_as_float(lds32(sb + EP_OFF + 4 * c)), 0.f) & 0xffffu));
  mbar_arrive(bars + 8 * (B_CVFULL + c));
}
__device__ __forceinline__ void kv_issue(const Params& p, int c, int m2, int dg) {
  const uint32_t fb = bars + 8 * (B_KV + c);
  mbar_expect_tx(fb, KV_PIECE);
  tma3(sb + KS_OFF + c * KV_PIECE, &p.mK, 160 * dg + 32 * c, 64 * m2 - 3, 0, fb);
  tma3(sb + KS_OFF + c * KV_PIECE + 4864, &p.mV, 160 * dg + 32 * c, 64 * m2 - 1, 0, fb);
}
__device__ __forceinline__ void kv_tile(int m, int dg, int c, int y) {
  const int lane = tid_opaque() & 31, tg = lane >> 3;
  const uint32_t pb = sb + KS_OFF + c * KV_PIECE + 32 * y + 4 * (lane & 7);
  const uint32_t ka = pb + tg * 1216, va = pb + 4864 + tg * 1088 + 64;
  const uint32_t kh = (m == 0 && tg > 0) ? ka - 192 : ka;
  uint32_t kk[19], u[16];
  const float4 t = lds128f(sb + TAP_OFF + 256 * c + 128 * y + 16 * (lane & 7));
#pragma unroll
  for (int i = 0; i < 19; i++) { kk[i] = lds32((i < 3 ? kh : ka) + i * 64); if (i >= 3) u[i - 3] = lds32(va + (i - 3) * 64); }
  uint8_t* dst = g_kv + ((160 * dg + 32 * c + 16 * y + 2 * (lane & 7)) * 4096 + (4 * m + tg) * 16);
  const uint32_t w0 = __byte_perm(__float_as_uint(t.x), __float_as_uint(t.z), 0x5410), w1 = __byte_perm(__float_as_uint(t.x), __float_as_uint(t.z), 0x7632);
  const uint32_t w2 = __byte_perm(__float_as_uint(t.y), __float_as_uint(t.w), 0x5410), w3 = __byte_perm(__float_as_uint(t.y), __float_as_uint(t.w), 0x7632);
#pragma unroll
  for (int i = 0; i < 16; i++) {
    uint32_t a = hmul2(kk[i], w3);
    a = hadd2(a, hmul2(kk[i + 1], w2)); a = hadd2(a, hmul2(kk[i + 2], w1)); a = hadd2(a, hmul2(kk[i + 3], w0));
    u[i] = hmul2(a, u[i]);
  }
#pragma unroll
  for (int e = 0; e < 2; e++)
#pragma unroll
    for (int f = 0; f < 2; f++) {
      uint32_t o[4];
#pragma unroll
      for (int qq = 0; qq < 4; qq++) o[qq] = __byte_perm(u[15 - 4 * qq - 2 * f], u[14 - 4 * qq - 2 * f], e ? 0x7632 : 0x5410);
      *(uint4*)(dst + e * 4096 + f * 2048) = make_uint4(o[0], o[1], o[2], o[3]);
    }
}
__device__ __forceinline__ void ln_finish(float s1, float s2, float& mean, float& rstd) {
  mean = s1 * (1.f / 640.f);
  const float v = fmaxf(fmaf(-mean, mean, s2 * (1.f / 640.f)), 0.f) + 1e-5f;
  asm("rsqrt.approx.ftz.f32 %0, %1;" : "=f"(rstd) : "f"(v));
}
__device__ __forceinline__ void stat_table(int T1, unsigned want, int l, int g, const uint4* x0, const uint4* x1, float (&xa)[2], float (&xb)[2]) {
  const int n = 32 * g + (tid_opaque() & 31);
  const uint4* rp = &g_stats[8 * l * SEQ + min(160 * T1 + n, SEQ - 1)];
  float a[4], b[4];
  uint32_t it = 0;
  while (true) {
    bool ok = true;
#pragma unroll
    for (int i = 0; i < 4; i++) ok &= (rec_ld(rp + SEQ * i, a[i], b[i]) == want);
    ok &= rec_ld(x0, xa[0], xb[0]) == want;
    ok &= rec_ld(x1, xa[1], xb[1]) == want;
    if (__all_sync(0xffffffffu, ok)) break;
    trap_if(++it > SPIN_LIMIT);
  }
  float m, rs;
  ln_finish((a[0] + a[1]) + (a[2] + a[3]), (b[0] + b[1]) + (b[2] + b[3]), m, rs);
  sts64f(sb + STAB_OFF + n * 8, rs, -m * rs);
}
__device__ __forceinline__ void stats_reduce(float (&a)[2], float (&b)[2], float (&mean)[2], float (&rstd)[2]) {
#pragma unroll
  for (int o = 1; o < 4; o <<= 1)
#pragma unroll
    for (int h = 0; h < 2; h++) { a[h] += __shfl_xor_sync(0xffffffffu, a[h], o); b[h] += __shfl_xor_sync(0xffffffffu, b[h], o); }
#pragma unroll
  for (int h = 0; h < 2; h++) ln_finish(a[h], b[h], mean[h], rstd[h]);
}

template <bool FIRST>
__device__ __forceinline__ void stats_publish(int which, int n0, int dg, unsigned tag, const float (&acc)[80]) {
  const int q = tid_opaque() & 3, h = q & 1;
  float s1[2] = {0.f, 0.f}, s2[2] = {0.f, 0.f}, t1[2] = {0.f, 0.f}, t2[2] = {0.f, 0.f};
#pragma unroll
  for (int j = 0; j < 20; j++)
#pragma unroll
    for (int y = 0; y < 2; y++) {
      const float a = acc[4 * j + 2 * y], b = acc[4 * j + 2 * y + 1];
      s1[y] += a; t1[y] += b; s2[y] = fmaf(a, a, s2[y]); t2[y] = fmaf(b, b, t2[y]);
    }
#pragma unroll
  for (int y = 0; y < 2; y++) { s1[y] += t1[y]; s2[y] += t2[y]; }
  float a = (h ? s1[1] : s1[0]) + __shfl_xor_sync(0xffffffffu, h ? s1[0] : s1[1], 1);
  float b = (h ? s2[1] : s2[0]) + __shfl_xor_sync(0xffffffffu, h ? s2[0] : s2[1], 1);
  a += __shfl_xor_sync(0xffffffffu, a, 2);
  b += __shfl_xor_sync(0xffffffffu, b, 2);
  if (FIRST) {
    rec_st(&g_stats[((q >> 1) * 4 + dg) * SEQ + n0 + 8 * h], a, b, q < 2 ? tag : tag - 1);
    rec_st(&g_stats[((q >> 1) * 4 + 8 + dg) * SEQ + n0 + 8 * h], a, b, tag - 1);
  } else if (q < 2) rec_st(&g_stats[(which * 4 + dg) * SEQ + n0 + 8 * h], a, b, tag);
}
__device__ __forceinline__ void stats_get(int which, int n0, unsigned tag, float (&mean)[2], float (&rstd)[2]) {
  const uint4* p0 = &g_stats[(which * 4 + (tid_opaque() & 3)) * SEQ + n0];
  float a[2], b[2];
  uint32_t it = 0;
  while (true) {
    const unsigned t0 = rec_ld(p0, a[0], b[0]), t1 = rec_ld(p0 + 8, a[1], b[1]);
    if (__all_sync(0xffffffffu, t0 == tag && t1 == tag)) break;
    trap_if(++it > SPIN_LIMIT);
  }
  stats_reduce(a, b, mean, rstd);
}
__device__ __forceinline__ void x0_load(float (&acc)[80]) {
  const int t = tid_opaque() & 127;
  const uint32_t xa = sb + XT_OFF + (16 * (t >> 5) + ((t & 31) >> 2)) * 320 + 8 * (t & 3);
  mbar_wait(bars + 8 * B_XT);
#pragma unroll
  for (int h = 0; h < 2; h++)
#pragma unroll
    for (int J = 0; J < 10; J++) {
      const float2 v = lds64f(xa + h * 2560 + 32 * J);
      const uint32_t x = __float_as_uint(v.x), y = __float_as_uint(v.y);
      acc[8 * J + 2 * h] = bf_lo(x); acc[8 * J + 2 * h + 1] = bf_hi(x);
      acc[8 * J + 4 + 2 * h] = bf_lo(y); acc[8 * J + 4 + 2 * h + 1] = bf_hi(y);
    }
}

template <bool FROM_X0>
__device__ __forceinline__ void dskip_init(float (&acc)[80], const float (&mean)[2], const float (&rstd)[2]) {
  const int t = tid_opaque() & 127;
  const uint32_t xa = sb + XT_OFF + (16 * (t >> 5) + ((t & 31) >> 2)) * 320 + 8 * (t & 3), da = sb + DTAB_OFF + 8 * (t & 3);
  float2 dw[10], xv[10][2];
#pragma unroll
  for (int J = 0; J < 2; J++) { dw[J] = lds64f(da + 32 * J); if (FROM_X0) { xv[J][0] = lds64f(xa + 32 * J); xv[J][1] = lds64f(xa + 2560 + 32 * J); } }
#pragma unroll
  for (int J = 0; J < 10; J++) {
    if (J + 2 < 10) { dw[J + 2] = lds64f(da + 32 * (J + 2)); if (FROM_X0) { xv[J + 2][0] = lds64f(xa + 32 * (J + 2)); xv[J + 2][1] = lds64f(xa + 2560 + 32 * (J + 2)); } }
#pragma unroll
    for (int x = 0; x < 8; x++) {
      const int h = (x >> 1) & 1;
      const uint32_t dwd = __float_as_uint(x < 4 ? dw[J].x : dw[J].y);
      const float tt = fmaf(rstd[h], (x & 1) ? bf_hi(dwd) : bf_lo(dwd), 1.f);
      float a = acc[8 * J + x];
      if (FROM_X0) { const uint32_t xw = __float_as_uint(x < 4 ? xv[J][h].x : xv[J][h].y); a = (x & 1) ? bf_hi(xw) : bf_lo(xw); }
      acc[8 * J + x] = FROM_X0 ? (a - mean[h]) * tt : fmaf(a, tt, -mean[h] * tt);
    }
  }
}

__global__ void __launch_bounds__(512, 1) fused_kernel(const __grid_constant__ Params p) {
  extern __shared__ __align__(1024) uint8_t smem_raw[];
  const int tid = threadIdx.x, lane = tid & 31;
  const int wid = __shfl_sync(0xffffffffu, tid >> 5, 0), wg = wid >> 2;
  unsigned smid; asm volatile("mov.u32 %0, %%smid;" : "=r"(smid));
  const int role = p.role[min(smid, 131u)];
  if (wid == 12) {
    const bool el = elect_one();
    if (el) {
      asm volatile("prefetch.tensormap [%0];" ::"l"(&p.mX) : "memory");
      asm volatile("prefetch.tensormap [%0];" ::"l"(&p.mB) : "memory");
#pragma unroll
      for (int k = 0; k < S1; k++) mbar_init(bars + 8 * (B_G1FULL + k), 1);
#pragma unroll
      for (int k = 0; k < 6; k++) mbar_init(bars + 8 * (B_XT + k), 1);
      asm volatile("fence.mbarrier_init.release.cluster;" ::: "memory");
    }
    if (role >= 0) {
      __syncwarp();
      asm volatile("bar.arrive 5, 288;" ::: "memory");
      const Role R = unpack_role(role);
      if (elect_one()) {
        TS(45);
#pragma unroll 1
        for (int k = 0; k < S1; k++) {
          const uint32_t fb = bars + 8 * (B_G1FULL + k);
          mbar_expect_tx(fb, G1_STAGE);
          tma4(sb + k * G1_STAGE + G1_XOFF, R.last ? &p.mXl : &p.mX, 64 * k, 0, 0, R.last ? 0 : 80 * R.T1, fb);
          tma5(sb + k * G1_STAGE, &p.mB, 64 * k, 0, 0, 4 * R.side, 2 * R.GP, fb);
        }
        if (R.has2) {
#pragma unroll 1
          for (int c = 0; c < KV0; c++) kv_issue(p, c, R.m2, R.dg);
          mbar_expect_tx(bars + 8 * B_XT, 20480);
#pragma unroll 1
          for (int h = 0; h < 2; h++) {
            const int ng = 8 * R.m2 + 4 * h, T = ng / 20;
            tma4(sb + XT_OFF + h * 10240, T == NT1 - 1 ? &p.mXtl : &p.mXt, 160 * R.dg, 0, 0, T == NT1 - 1 ? ng - 240 : ng + 60 * T, bars + 8 * B_XT);
          }
        }
        TS(44);
      }
      __syncwarp();
      bar_sync(6, 64);
    }
  }
  trap_if(smid >= 132 || smem_u32(smem_raw) != sb);
  if (role < 0) {
    if (wid == 0) {
      const unsigned tag = ld_rlx(g_epoch);
#pragma unroll 1
      for (int i = 0; i < NT1; i++) {
        uint32_t it = 0;
        while (!__all_sync(0xffffffffu, (int)(ld_rlx(&g_hflag[(i * 32 + min(lane, 9)) * 8]) - tag) >= 0)) { __nanosleep(500); trap_if(++it > SPIN_LIMIT); }
      }
    }
    return;
  }
  float mean0[2] = {0.f, 0.f}, rstd0[2] = {0.f, 0.f};
  if (wg == 2 || wid == 14) {
    ROLE(role)
    const int c = wid == 14 ? 4 : wid - 8;
    const unsigned tag = ld_rlx(g_epoch);
    if (has2) {
      uint2 bv[2][5];
#pragma unroll
      for (int x = 0; x < 2; x++)
#pragma unroll
        for (int i = 0; i < 5; i++) bv[x][i] = ldv64((const uint2*)((x ? p.bim : p.bre) + (cch0 + 32 * c) * DM) + lane + 32 * i);
      float sv[2];
#pragma unroll
      for (int x = 0; x < 2; x++) {
        float a = 0.f;
#pragma unroll
        for (int i = 0; i < 5; i++) a += (bf_lo(bv[x][i].x) + bf_hi(bv[x][i].x)) + (bf_lo(bv[x][i].y) + bf_hi(bv[x][i].y));
        sv[x] = a;
      }
#pragma unroll
      for (int o = 16; o > 0; o >>= 1) { sv[0] += __shfl_xor_sync(0xffffffffu, sv[0], o); sv[1] += __shfl_xor_sync(0xffffffffu, sv[1], o); }
      if (lane < 2) rec_st(&g_sB[(cch0 + 32 * c) * 2 + lane], sv[0], sv[1], tag);
      if (tid == 256) TS(47);
      __syncwarp();
      bar_sync(8, 192);
      mbar_wait(bars + 8 * B_EP);
      mbar_wait(bars + 8 * (B_KV + c));
#pragma unroll 1
      for (int y = 0; y < 2; y++) kv_tile(m2, dg, c, y);
      __syncwarp();
      if (lane == 0) { mbar_arrive(bars + 8 * (B_PD + c)); mbar_arrive(bars + 8 * B_PREP); }
      if (tid == 256) TS(48);
      if (tid == 352) TS(52);
      if (tid == 448) TS(51);
      if (wg == 2) {
        float xs[80];
        x0_load(xs);
        stats_publish<true>(0, 64 * m2 + 16 * c + (lane >> 2), dg, tag, xs);
        if (tid == 256) TS(31);
        mbar_wait(bars + 8 * B_PUB);
      } else {
        mbar_wait(bars + 8 * B_PREP);
        if (lane == 0) { st_rel(&g_kvflag[(dg * 32 + m2) * 8], tag); mbar_arrive(bars + 8 * B_PUB); TS(30); }
        __syncwarp();
      }
    } else bar_sync(8, 192);
    {
      const uint4* x0 = wg == 2 ? &g_stats[(lane & 3) * SEQ + (has2 ? 64 * m2 : 0) + 16 * c + (lane >> 2)] : &g_sB[(128 * GP + 32 * side + lane) * 2];
      float xa[2], xb[2];
      stat_table(T1, tag, 0, c, x0, x0 + (wg == 2 ? 8 : 128), xa, xb);
      if (wg == 2) stats_reduce(xa, xb, mean0, rstd0);
      else {
#pragma unroll
        for (int i = 0; i < 2; i++) sts64f(sb + CTAB_OFF + (32 * i + lane) * 24 + 16, p.swap ? xb[i] : xa[i], p.swap ? xa[i] : xb[i]);
      }
      mbar_arrive(bars + 8 * B_STAB);
      if (tid == 256) TS(26);
    }
  } else if (wid == 15) {
    ROLE(role)
    const int ch = 128 * GP + 32 * side + lane;
    uint32_t r0 = ldv16(p.lre + ch), r1 = ldv16(p.lim + ch), r2 = ldv16(p.logdt + ch);
    const uint32_t r3 = ldv16(p.lre + ch + 64), r4 = ldv16(p.lim + ch + 64), r5 = ldv16(p.logdt + ch + 64);
#pragma unroll 1
    for (int i = 0; i < 2; i++) {
      const float lr = bf_lo(r0), li = bf_lo(r1);
      const float dt = __bfloat162float(__float2bfloat16_rn(expf(bf_lo(r2))));
      const float mag = expf(dt * lr);
      float sn, cs; sincospif(dt * li * 0.31830988618379067f, &sn, &cs);
      const float ar = mag * cs, ai = mag * sn;
      const float inv = 2.f / (lr * lr + li * li);
      const uint32_t ad = sb + CTAB_OFF + (32 * i + lane) * 24;
      sts64f(ad, ar, ai);
      sts64f(ad + 8, ((ar - 1.f) * lr + ai * li) * inv, (ai * lr - (ar - 1.f) * li) * inv);
      r0 = r3; r1 = r4; r2 = r5;
    }
    if (lane == 0) TS(46);
    __syncwarp();
    bar_sync(7, 64);
    mbar_arrive(bars + 8 * B_CTAB);
  } else if (wid == 13) {
    ROLE(role)
    uint4 tv[3];
    const uint32_t e0 = ld_rlx(g_epoch);
    const uint32_t e1 = ldv16(p.ssmD + min(cch0 + 32 * lane, 639));
    const uint4 dv = ldv128((const uint4*)(p.dskip + 160 * dg) + min(lane, 19));
#pragma unroll
    for (int i = 0; i < 3; i++) tv[i] = ldv128((const uint4*)(p.shiftk + 640 * dg) + min(lane + 32 * i, 79));
    sts128(sb + DTAB_OFF + 16 * min(lane, 19), dv);
#pragma unroll
    for (int i = 0; i < 3; i++) sts128(sb + TAP_OFF + 16 * min(lane + 32 * i, 79), tv[i]);
    if (lane < 7) sts32(sb + EP_OFF + 4 * lane, lane < 5 ? e1 << 16 : (lane == 5 ? e0 : 0u));
    __syncwarp();
    bar_sync(9, 64);
    mbar_arrive(bars + 8 * B_CTAB);
    if (lane == 0) { mbar_arrive(bars + 8 * B_EP); TS(53); }
  } else if (wid != 12) {
    if (elect_one()) {
      if (wid < 7) {
        const int b0 = wid < 4 ? 4 + 20 * wid : 85 + 21 * (wid - 4), cnt = wid < 4 ? 2 : 1;
#pragma unroll
        for (int i = 0; i < 21; i++) mbar_init(bars + 8 * (b0 + i), cnt);
      } else {
#pragma unroll
        for (int i = 0; i < 12; i++) mbar_init(bars + 8 * (B_CVDONE + i), (i == 5 || i == 6) ? 160 : 128);
        mbar_init(bars + 8 * B_CTAB, 192); mbar_init(bars + 8 * B_PREP, 5);
      }
      asm volatile("fence.mbarrier_init.release.cluster;" ::: "memory");
    }
    __syncwarp();
    bar_sync(5, 288);
    if (wid == 2) asm volatile("bar.arrive 8, 192;\nbar.arrive 6, 64;\nbar.arrive 9, 64;\nbar.arrive 7, 64;" ::: "memory");
    if (tid == 128) TS(0);
    if (wg == 1) { cv_table(); mbar_arrive(bars + 8 * B_CTAB); }
  }

  if (wg == 3) {
    ROLE(role)
    const int pw = wid & 3;
    unsigned tag = 0;
    if (pw > 0) { mbar_wait(bars + 8 * B_EP); tag = lds32(sb + EP_OFF + 20); }
    if (pw == 0) {
      if (elect_one()) {
#pragma unroll 1
        for (int l = 0; l < 2; l++) {
          const uint32_t fb0 = bars + 8 * (B_G1FULL + 10 * l), wb = bars + 8 * (B_G1DONE + 9 * l - S1);
          const uint32_t free0 = bars + 8 * (has2 ? B_G2DONE + 19 : B_G1DONE + 9);
          uint32_t dst = sb;
#pragma unroll 1
          for (int k = l == 0 ? S1 : 0; k < 10; k++) {
            mbar_wait(k >= S1 + l ? wb + 8 * k : (k < WPF1 || !has2 ? free0 : bars + 8 * (B_GO + 1)));
            mbar_expect_tx(fb0 + 8 * k, 16384);
            tma5(dst, &p.mB, 64 * k, 0, 0, 4 * side, 2 * GP, fb0 + 8 * k);
            dst += G1_STAGE; if (dst == sb + (S1 + l) * G1_STAGE) dst = sb;
          }
          if (has2) {
            const uint32_t fb2 = bars + 8 * (B_G2FULL + 20 * l), wb2 = bars + 8 * (B_G2DONE + 19 * l - 6);
            dst = sb + G2_WOFF;
            int kc = 0;
#pragma unroll 1
            for (int k = 0; k < 20; k++) {
              mbar_wait(k >= 6 + l ? wb2 + 8 * k : (k == 5 ? bars + 8 * B_XFREE : (k < WPF2 ? bars + 8 * (B_G1DONE + 10 * l + 9) : bars + 8 * (B_GO + 2 * l))));
              mbar_expect_tx(fb2 + 8 * k, G2_WB);
              tma5(dst, &p.mCre + (k & 1), kc, 0, 0, 0, 10 * dg, fb2 + 8 * k);
              kc += (k & 1) << 7; if (k == 9) kc = 64;
              dst += G2_WB; if (dst == sb + G2_WOFF + (6 + l) * G2_WB) dst = sb + G2_WOFF;
            }
          }
        }
      }
    } else if (pw == 1) {
#pragma unroll 1
      for (int l = 0; l < 2; l++) {
        if (l == 0) {
          if (elect_one()) {
            uint32_t dst = sb + G1_XOFF;
#pragma unroll 1
            for (int k = S1; k < 10; k++) {
              mbar_wait(bars + 8 * (B_G1DONE + k - S1));
              mbar_expect_tx(bars + 8 * (B_G1FULL + k), 20480);
              tma4(dst, last ? &p.mXl : &p.mX, 64 * k, 0, 0, last ? 0 : 80 * T1, bars + 8 * (B_G1FULL + k));
              dst += G1_STAGE; if (k == 2 * S1 - 1) dst = sb + G1_XOFF;
              if (has2 && k - S1 + KV0 < 5) kv_issue(p, k - S1 + KV0, m2, dg);
            }
          }
        } else {
          mbar_wait(bars + 8 * (has2 ? B_G2DONE + 19 : B_G1DONE + 9));
          const int mlo = (160 * T1) >> 6, nf = last ? 8 : 12;
          flag_poll(&g_uflag[(4 * mlo + min(lane, nf - 1)) * 8], tag);
          fence_async_global();
          if (elect_one()) {
            TS(20);
            const int bytes = last ? 16384 : 20480;
            const uint8_t* src = g_u + T1 * 204800;
            uint32_t dst = sb + G1_XOFF;
#pragma unroll 1
            for (int k = 0; k < 10; k++) {
              if (k > S1) mbar_wait(bars + 8 * (B_G1DONE + 9 - S1 + k));
              mbar_expect_tx(bars + 8 * (B_G1FULL + 10 + k), bytes);
              bulk_g2s(dst, src, bytes, bars + 8 * (B_G1FULL + 10 + k));
              src += 20480; dst += G1_STAGE; if (k == S1) dst = sb + G1_XOFF;
            }
          }
        }
        __syncwarp();
        if (has2) {
          mbar_wait(bars + 8 * (B_G1DONE + 10 * l + 9));
          const int Tlo = (64 * m2) / 160, Thi = (64 * m2 + 63) / 160;
          flag_poll(&g_hflag[(((l * NT1 + (lane < 16 ? Tlo : Thi)) * 2) * 16 + min(lane & 15, 9)) * 8], tag);
          fence_async_global();
          if (elect_one()) {
            TS(21 + 2 * l);
            const uint32_t fb2 = bars + 8 * (B_G2FULL + 20 * l), wb2 = bars + 8 * (B_G2DONE + 18 * l - SX2);
            const uint8_t* src = g_h + (l * 32 + m2) * 163840;
            uint32_t dst = sb;
#pragma unroll 1
            for (int k = 0; k < 20; k++) {
              if (k >= SX2 + 2 * l) mbar_wait(wb2 + 8 * k);
              if (k == 10) { mbar_wait(bars + 8 * (B_H1 + l)); fence_async_global(); }
              mbar_expect_tx(fb2 + 8 * k, G2_XB);
              bulk_g2s(dst, src, G2_XB, fb2 + 8 * k);
              src += 8192; dst += G2_XB; if (dst == sb + (SX2 + 2 * l) * G2_XB) dst = sb;
            }
          }
          __syncwarp();
        }
      }
    } else if (pw == 2) {
#pragma unroll 1
      for (int l = 0; l < 2; l++) {
        if (l == 1) {
          float xa[2], xb[2];
          mbar_wait(bars + 8 * (B_G1FULL + 11));
          stat_table(T1, tag, 1, 4, g_stats, g_stats, xa, xb);
          mbar_arrive(bars + 8 * (B_STAB + 1));
        }
#pragma unroll 1
        for (int w = 0; w < 2; w++) {
          mbar_wait(bars + 8 * (B_HST + 2 * l + w));
          if (lane == 0) { st_rel(&g_hflag[(((l * NT1 + T1) * 2 + w) * 16 + 2 * GP + side) * 8], tag); TS(w ? 15 + l : 6 + 8 * l); }
          __syncwarp();
        }
        if (l == 0 && has2 && elect_one()) {
#pragma unroll 1
          for (int c = 0; c < 5; c++) {
            mbar_wait(bars + 8 * (B_CVDONE + c));
            bulk_s2g(g_G + (cch0 + 32 * c) * 4096, cv_stage(c), 4096);
          }
          asm volatile("cp.async.bulk.commit_group;" ::: "memory");
          asm volatile("cp.async.bulk.wait_group 0;" ::: "memory");
          fence_async_global();
          st_rel(&g_gflag[(dg * 32 + m2) * 8], tag);
        }
        __syncwarp();
      }
    } else if (has2) {
#pragma unroll 1
      for (int c = 0; c < 5; c++) {
        mbar_wait(bars + 8 * (B_PD + c));
        const uint32_t cb = sb + CV_OFF + c * CV_B;
        sts128(lane < 8 ? cb + 16 * lane : (lane < 20 ? cb + CV_U + 16 * (lane - 8) : cb + CV_U + CV_PL + 16 * (lane - 20)), make_uint4(0, 0, 0, 0));
        fence_async_smem();
        __syncwarp();
        if (!TAPLATE && c < TAP0 && elect_one()) {
          mbar_expect_tx(bars + 8 * (B_TAPS + c), 4096);
          bulk_g2s(cb + CV_K, p.ssmk + (cch0 + 32 * c) * SEQ, 4096, bars + 8 * (B_TAPS + c));
        }
      }
      mbar_wait(bars + 8 * B_PUB);
      if (TAPLATE && elect_one()) {
#pragma unroll
        for (int c = 0; c < TAP0; c++) {
          mbar_expect_tx(bars + 8 * (B_TAPS + c), 4096);
          bulk_g2s(sb + CV_OFF + c * CV_B + CV_K, p.ssmk + (cch0 + 32 * c) * SEQ, 4096, bars + 8 * (B_TAPS + c));
        }
      }
      flag_poll(&g_kvflag[(dg * 32 + lane) * 8], tag);
      fence_async_global();
      if (elect_one()) {
        TS(28);
#pragma unroll 1
        for (int c = 0; c < 5; c++) {
          const uint32_t fb = bars + 8 * (B_CVFULL + c), cb = sb + CV_OFF + c * CV_B;
          if (c == 1) tap_patch(0);
          mbar_expect_tx(fb, 4096);
          bulk_g2s(cb + CV_U + 192, g_kv + (cch0 + 32 * c) * 4096, 2048, fb);
          bulk_g2s(cb + CV_U + 192 + CV_PL, g_kv + (cch0 + 32 * c) * 4096 + 2048, 2048, fb);
          if (c >= TAP0) {
            mbar_expect_tx(bars + 8 * (B_TAPS + c), 4096);
            bulk_g2s(cb + CV_K, p.ssmk + (cch0 + 32 * c) * SEQ, 4096, bars + 8 * (B_TAPS + c));
          }
        }
#pragma unroll 1
        for (int c = 1; c < 5; c++) tap_patch(c);
        TS(54);
        asm volatile("prefetch.tensormap [%0];" ::"l"(&p.mCre) : "memory");
        asm volatile("prefetch.tensormap [%0];" ::"l"(&p.mCim) : "memory");
        asm volatile("prefetch.tensormap [%0];" ::"l"(&p.mG) : "memory");
      }
      __syncwarp();
      const unsigned* hf = &g_hflag[(((lane < 16 ? (64 * m2) / 160 : (64 * m2 + 63) / 160) * 2 + 1) * 16 + min(lane & 15, 9)) * 8];
      mbar_wait(bars + 8 * (B_CVDONE + 0));
      if (elect_one()) { l2_prefetch(p.cre + (160 * dg + 5 * m2) * DM, 6400); l2_prefetch(p.cim + (160 * dg + 5 * m2) * DM, 6400); }
      flag_poll(hf, tag);
      __syncwarp();
      if (lane == 0) { mbar_arrive(bars + 8 * B_H1); TS(22); }
      mbar_wait(bars + 8 * (B_CVDONE + 4));
      flag_poll(&g_gflag[(dg * 32 + lane) * 8], tag);
      __syncwarp();
      fence_async_global();
      if (lane == 0) TS(29);
      if (elect_one()) {
        mbar_expect_tx(bars + 8 * B_GFULL, 20480);
        tma5(sb + G_OFF, &p.mG, 64 * m2, 0, 0, 0, 10 * dg, bars + 8 * B_GFULL);
      }
      mbar_wait(bars + 8 * (B_G1DONE + 19));
      flag_poll(hf + NT1 * 256, tag);
      __syncwarp();
      if (lane == 0) { mbar_arrive(bars + 8 * (B_H1 + 1)); TS(24); }
    }
  } else {
    const int w = wid & 3;
    if (wg == 2 && !(role >> 16)) {
      float xa[2], xb[2];
      mbar_wait(bars + 8 * (B_G1FULL + 11));
      stat_table(role & 15, lds32(sb + EP_OFF + 20), 1, w, g_stats, g_stats, xa, xb);
      mbar_arrive(bars + 8 * (B_STAB + 1));
    }
#pragma unroll 1
    for (int l = 0; l < 2; l++) {
      if (wg < 2) {
        float acc[80];
#pragma unroll
        for (int i = 0; i < 80; i++) acc[i] = 0.f;
        ROLE(role)
        const int tid = tid_opaque(), r = (tid & 31) >> 2, q = tid & 3;
        const int ch = 128 * GP + 64 * wg + 32 * side + 8 * w + r;
        const uint32_t ca = sb + CTAB_OFF + (32 * wg + 8 * w + r) * 24;
        float2 lam = make_float2(0.f, 0.f), p8 = lam, p16 = lam, pL = lam, p2L = lam;
        fence_regs(acc);
        {
          uint32_t alo = desc_lo(sb, 16) + wg * 512, blo = l == 0 ? desc_lo(sb + G1_XOFF, 16) : desc_lo(sb + G1_XOFF, 128);
          const uint32_t bhi = l == 0 ? desc_hi(1024, 1) : desc_hi(1024, 0), xstep = l == 0 ? 2 : 16;
          const uint32_t aend = desc_lo(sb, 16) + (S1 + l) * (G1_STAGE >> 4);
          uint32_t fb = bars + 8 * (B_G1FULL + 10 * l);
          mbar_wait(fb);
          if (tid == 0) TS(1 + 8 * l);
#pragma unroll 1
          for (int k = 0; k < 10; k++) {
            uint32_t ok; const uint32_t nb = k < 9 ? fb + 8 : fb;
            wgmma_fence();
#pragma unroll
            for (int kk = 0; kk < 4; kk++) {
              wgmma_n160<0>(acc, alo + kk * 2, desc_hi(1024, 1), blo + kk * xstep, bhi);
              if (kk == 0) ok = mbar_test(nb);
              if (kk == STG_KK && k == 9 && tid == 0) mbar_arrive(bars + 8 * (B_STG + l));
            }
            wgmma_commit();
            alo += G1_STAGE >> 4; blo += G1_STAGE >> 4;
            if (alo >= aend) { alo -= (S1 + l) * (G1_STAGE >> 4); blo -= (S1 + l) * (G1_STAGE >> 4); }
            wgmma_wait<1>();
            if (k > 0 && (tid & 127) == 0) mbar_arrive(fb + 8 * (B_G1DONE - B_G1FULL - 1));
            if (!ok) mbar_wait(nb);
            if (wg == 1 && k == 9 - STG_D - l) mbar_wait(bars + 8 * (B_STG + l));
            if (k == PAUSE_K) {
              mbar_wait(bars + 8 * B_CTAB);
              lam = lds64f(ca);
              if (p.swap) lam.y = -lam.y;
              const float2 p2 = cmul(lam, lam), p4 = cmul(p2, p2);
              p8 = cmul(p4, p4); p16 = cmul(p8, p8);
              pL = cmul(p16, p16);
              if (!last) pL = cmul(pL, p8);
              p2L = cmul(pL, pL);
              if (has2) mbar_wait(bars + 8 * B_PREP);
            }
            fb += 8;
          }
        }
        mbar_wait(bars + 8 * (B_STAB + l));
        const float2 sB = lds64f(ca + 16);
        const unsigned tag = lds32(sb + EP_OFF + 20);
        wgmma_wait<0>();
        fence_regs(acc);
        if ((tid & 127) == 0) { mbar_arrive(bars + 8 * (B_G1DONE + 10 * l + 9)); TS(wg ? 17 + l : 2 + 8 * l); }
        float2 ec[3];
#pragma unroll
        for (int jj = 0; jj < 8; jj++)
#pragma unroll
          for (int y = 0; y < 3; y++) {
            if (y == 2 && (jj & 1)) continue;
            const int j = y == 2 ? 16 + (jj >> 1) : 8 * y + jj;
            const float4 st = lds128f(sb + STAB_OFF + (8 * j + 2 * q) * 8);
            acc[4 * j + 0] = fmaf(acc[4 * j + 0], st.x, st.y * sB.x);
            acc[4 * j + 2] = fmaf(acc[4 * j + 2], st.x, st.y * sB.y);
            acc[4 * j + 1] = fmaf(acc[4 * j + 1], st.z, st.w * sB.x);
            acc[4 * j + 3] = fmaf(acc[4 * j + 3], st.z, st.w * sB.y);
            ec[y] = jj == 0 ? make_float2(acc[4 * j + 0], acc[4 * j + 2]) : cfma(lam, ec[y], make_float2(acc[4 * j + 0], acc[4 * j + 2]));
            ec[y] = cfma(lam, ec[y], make_float2(acc[4 * j + 1], acc[4 * j + 3]));
          }
        float2 e = cfma(p16, ec[0], ec[1]);
        if (!last) e = cfma(p8, e, ec[2]);
        {
          float2 v = make_float2(__shfl_up_sync(0xffffffffu, e.x, 1, 4), __shfl_up_sync(0xffffffffu, e.y, 1, 4));
          if (q >= 1) e = cfma(pL, v, e);
          v = make_float2(__shfl_up_sync(0xffffffffu, e.x, 2, 4), __shfl_up_sync(0xffffffffu, e.y, 2, 4));
          if (q >= 2) e = cfma(p2L, v, e);
        }
        if (!last && (q == 3 || (q == 2 && l == 0))) rec_st(&g_E[((q == 3 ? l : 1) * NT1 + T1) * DM + ch], e.x, e.y, q == 3 ? tag : tag - 1);
        if (tid == 0) TS(3 + 8 * l);
        float2 ex = make_float2(__shfl_up_sync(0xffffffffu, e.x, 1, 4), __shfl_up_sync(0xffffffffu, e.y, 1, 4));
        if (q == 0) ex = make_float2(0.f, 0.f);
        const float2 coef = lds64f(ca + 8), lamc = make_float2(lam.x, p.swap ? lam.y : -lam.y);
        float m00 = coef.x, m01 = -coef.y, m10 = -coef.y, m11 = -coef.x;
        if (p.swap) { m00 = -coef.y; m01 = coef.x; m10 = -coef.x; m11 = -coef.y; }
        float2 pLq, p160q, p640;
        {
          const float2 p80 = last ? cmul(p2L, p16) : p2L, p160 = cmul(p80, p80), p320 = cmul(p160, p160), one = make_float2(1.f, 0.f);
          p640 = cmul(p320, p320);
          pLq = cmul((q & 1) ? pL : one, (q & 2) ? p2L : one);
          p160q = cmul((q & 1) ? p160 : one, (q & 2) ? p320 : one);
        }
        float2 c, ev[3];
        unsigned tg[3];
        const uint4* ep = &g_E[(l * NT1 + T1 - 1 - q) * DM + ch];
#pragma unroll
        for (int j = 0; j < 20; j++) {
          if (j == CPOLL) {
#pragma unroll
            for (int i = 0; i < 3; i++) {
              ev[i] = make_float2(0.f, 0.f); tg[i] = tag;
              if (T1 - 1 - q - 4 * i >= 0) tg[i] = rec_ld(ep - 4 * i * DM, ev[i].x, ev[i].y);
            }
          }
#pragma unroll
          for (int x = 0; x < 2; x++) {
            const float b0 = acc[4 * j + x], b1 = acc[4 * j + 2 + x];
            acc[4 * j + x] = fmaf(b0, m00, b1 * m01);
            acc[4 * j + 2 + x] = fmaf(b0, m10, b1 * m11);
          }
          if (j == CPOLL - 1 || j == 19) asm volatile("" : "+f"(acc[4 * j]), "+f"(acc[4 * j + 1]), "+f"(acc[4 * j + 2]), "+f"(acc[4 * j + 3])::"memory");
        }
        {
          uint32_t it = 0;
          while (__any_sync(0xffffffffu, tg[0] != tag || tg[1] != tag || tg[2] != tag)) {
#pragma unroll
            for (int i = 0; i < 3; i++)
              if (tg[i] != tag) tg[i] = rec_ld(ep - 4 * i * DM, ev[i].x, ev[i].y);
            trap_if(++it > SPIN_LIMIT);
          }
          c = cfma(p640, cfma(p640, ev[2], ev[1]), ev[0]);
          c = cmul(c, p160q);
          c.x += __shfl_xor_sync(0xffffffffu, c.x, 1); c.y += __shfl_xor_sync(0xffffffffu, c.y, 1);
          c.x += __shfl_xor_sync(0xffffffffu, c.x, 2); c.y += __shfl_xor_sync(0xffffffffu, c.y, 2);
        }
        if (tid == 0) TS(4 + 8 * l);
        if (tid == 128) mbar_arrive(bars + 8 * (B_GO + 2 * l));
        c = cfma(pLq, c, ex);
        float2 hh = make_float2(fmaf(c.x, m00, c.y * m01), fmaf(c.x, m10, c.y * m11));
        uint8_t* hb = g_h + (size_t)l * (32 * 20 * 8192) + (10 * wg + 2 * GP) * 8192 + (4 * side + w) * 1024 + (tid_opaque() & 31) * 4;
#pragma unroll
        for (int j4 = 0; j4 < 5; j4++) {
          const int ng = 20 * T1 + 4 * j4;
          uint8_t* hp = hb + (size_t)(ng >> 3) * 163840 + (ng & 7) * 128;
#pragma unroll
          for (int jj = 0; jj < 4; jj++) {
            const int j = 4 * j4 + jj;
            const float2 h0 = cfma(lamc, hh, make_float2(acc[4 * j + 0], acc[4 * j + 2]));
            hh = cfma(lamc, h0, make_float2(acc[4 * j + 1], acc[4 * j + 3]));
            if (j4 < 4 || !last) {
              *(uint32_t*)(hp + jj * 128) = pack_bf16(h0.x, hh.x);
              *(uint32_t*)(hp + jj * 128 + 8192) = pack_bf16(h0.y, hh.y);
            }
          }
        }
        mbar_arrive(bars + 8 * (B_HST + 2 * l + wg));
        if (tid == 0) TS(5 + 8 * l);
        if (tid == 128) TS(l ? 25 : 19);
      }
      if (l == 0) {
        ROLE(role)
        if (has2) {
          CvCtx cc;
          mbar_wait(bars + 8 * B_CTAB);
          cv_setup(cc);
          mbar_wait(bars + 8 * (B_G1DONE + 9));
#pragma unroll 1
          for (int c = wg == 2 ? 0 : 2 + wg; c < (wg == 2 ? 2 : 5); c += wg == 2 ? 1 : 2) conv_channel(c, cc);
          if ((tid & 127) == 0) TS(wg == 2 ? 32 : 7 + wg);
        }
      }
      if (wg == 2) break;
    }
    if (wg == 2 && (role >> 16)) {
      float acc[80];
      float off[2] = {mean0[0], mean0[1]};
      const unsigned tag = lds32(sb + EP_OFF + 20);
      dskip_init<true>(acc, mean0, rstd0);
      mbar_arrive(bars + 8 * B_XFREE);
#pragma unroll 1
      for (int l = 0; l < 2; l++) {
        float mean[2], rstd[2];
        {
          const uint32_t aend = desc_lo(sb + SX2 * G2_XB, 1024) + l * (G2_XB >> 3), bend = desc_lo(sb + G2_WOFF + 6 * G2_WB, 16) + l * (G2_WB >> 4);
          uint32_t alo = desc_lo(sb, 1024), blo = desc_lo(sb + G2_WOFF, 16);
          uint32_t fb = bars + 8 * (B_G2FULL + 20 * l);
          fence_regs(acc);
          mbar_wait(fb);
          if (tid == 256) TS(33 + 6 * l);
#pragma unroll 1
          for (int k = 0; k < 20; k++) {
            if (l == 1 && (k & 3) == 3 && tid == 256) TS(56 + (k >> 2));
            uint32_t ok; const uint32_t nb = k < 19 ? fb + 8 : fb;
            wgmma_fence();
#pragma unroll
            for (int kk = 0; kk < 4; kk++) {
              wgmma_n160<1>(acc, alo + kk * 128, desc_hi(128, 0), blo + kk * 2, desc_hi(1024, 1));
              if (kk == 0) ok = mbar_test(nb);
            }
            wgmma_commit();
            alo += G2_XB >> 4; if (alo == aend) alo = desc_lo(sb, 1024);
            blo += G2_WB >> 4; if (blo == bend) blo = desc_lo(sb + G2_WOFF, 16);
            wgmma_wait<1>();
            if (k > 0 && tid == 256) mbar_arrive(fb + 8 * (B_G2DONE - B_G2FULL - 1));
            if (!ok) mbar_wait(nb);
            fb += 8;
          }
          wgmma_wait<0>();
          fence_regs(acc);
          if (tid == 256) TS(34 + 6 * l);
          if (tid == 256) mbar_arrive(bars + 8 * (B_G2DONE + 20 * l + 19));
        }
        ROLE(role)
        const int tq = tid_opaque() & 31, n0 = 64 * m2 + 16 * w + (tq >> 2);
        stats_publish<false>(2 * l + 1, n0, dg, tag, acc);
        uint32_t gf[10][4];
        mbar_wait(bars + 8 * B_GFULL);
        const uint32_t ga = sb + G_OFF + (8 * (tq >> 4) + (tq & 7)) * 128 + (((2 * w + ((tq >> 3) & 1)) ^ ((2 * m2) & 6) ^ (tq & 7)) << 4);
#pragma unroll
        for (int J = 0; J < 2; J++) ldsm4t(gf[J], ga + J * 2048);
        if (tid == 256) TS(35 + 6 * l);
        uint8_t* dst[2][2];
#pragma unroll
        for (int h = 0; h < 2; h++) {
          if (l == 0) {
            const int ng = 8 * m2 + 2 * w + h, T = ng / 20;
            uint8_t* ub = g_u + (T * 204800 + (ng - 20 * T) * 1024 + (tq & 2) * 64 + (tq & 28) * 4 + (tq & 1) * 8 + (5 * dg >> 1) * 20480);
            dst[h][1] = ub + ((dg & 1) ? 20480 - 512 : 0);
            dst[h][0] = ub + (dg & 1) * 512;
          } else {
            dst[h][0] = dst[h][1] = (uint8_t*)(p.out + (n_to_t(n0 + 8 * h) * DM + 160 * dg + 4 * (tq & 3)));
          }
        }
        stats_get(2 * l + 1, n0, tag, mean, rstd);
        if (tid == 256) { TS(36 + 6 * l); if (l == 0) mbar_arrive(bars + 8 * (B_GO + 1)); }
        off[0] += mean[0]; off[1] += mean[1];
        const float ov[2] = {l ? off[0] : 0.f, l ? off[1] : 0.f};
#pragma unroll
        for (int J = 0; J < 10; J++) {
          if (J + 2 < 10) ldsm4t(gf[J + 2 < 10 ? J + 2 : 0], ga + (J + 2) * 2048);
#pragma unroll
          for (int x = 0; x < 8; x++) {
            const int h = (x >> 1) & 1;
            const uint32_t gwd = gf[J][x >> 1];
            const float t = fmaf(rstd[h], (x & 1) ? bf_hi(gwd) : bf_lo(gwd), 1.f);
            acc[8 * J + x] = fmaf(acc[8 * J + x], t, fmaf(-mean[h], t, ov[h]));
          }
#pragma unroll
          for (int h = 0; h < 2; h++) {
            if (l == 0)
              *(uint2*)(dst[h][(J >> 1) & 1] + (J >> 2) * 20480 + (J & 3) * 256) =
                  make_uint2(pack_bf16(acc[8 * J + 2 * h], acc[8 * J + 2 * h + 1]), pack_bf16(acc[8 * J + 4 + 2 * h], acc[8 * J + 5 + 2 * h]));
            else
              *(float4*)(dst[h][0] + 64 * J) = make_float4(acc[8 * J + 2 * h], acc[8 * J + 2 * h + 1], acc[8 * J + 4 + 2 * h], acc[8 * J + 5 + 2 * h]);
          }
          __syncwarp();
        }
        if (l == 0) {
          bar_sync(3, 128);
          if (tid == 256) { TS(37); st_rel(&g_uflag[(4 * m2 + dg) * 8], tag); TS(38); }
          stats_publish<false>(2, n0, dg, tag, acc);
          mbar_wait(bars + 8 * (B_G1FULL + 11));
          float xa[2], xb[2];
          const uint4* x0 = &g_stats[(8 + (tq & 3)) * SEQ + n0];
          stat_table(T1, tag, 1, w, x0, x0 + 8, xa, xb);
          mbar_arrive(bars + 8 * (B_STAB + 1));
          if (tid == 256) TS(27);
          stats_reduce(xa, xb, mean, rstd);
          off[0] += mean[0]; off[1] += mean[1];
          mbar_wait(bars + 8 * (B_HST + 3));
          dskip_init<false>(acc, mean, rstd);
        } else {
          if (tid == 256) {
            TS(43);
            if (m2 == 31 && dg == 3) asm volatile("st.relaxed.gpu.global.u32 [%0], %1;" ::"l"(g_epoch), "r"(tag + 1) : "memory");
          }
        }
      }
    }
  }
}

typedef CUresult (*EncFn)(CUtensorMap*, CUtensorMapDataType, cuuint32_t, void*, const cuuint64_t*, const cuuint64_t*,
                          const cuuint32_t*, const cuuint32_t*, CUtensorMapInterleave, CUtensorMapSwizzle,
                          CUtensorMapL2promotion, CUtensorMapFloatOOBfill);

void encode(EncFn fn, CUtensorMap* m, const void* ptr, int rank, const cuuint64_t* dims, const cuuint64_t* strides, const cuuint32_t* box,
            CUtensorMapSwizzle swz = CU_TENSOR_MAP_SWIZZLE_128B) {
  cuuint32_t es[5] = {1, 1, 1, 1, 1};
  fn(m, CU_TENSOR_MAP_DATA_TYPE_BFLOAT16, rank, (void*)ptr, dims, strides, box, es, CU_TENSOR_MAP_INTERLEAVE_NONE,
     swz, (CUtensorMapL2promotion)(swz == CU_TENSOR_MAP_SWIZZLE_128B ? PROM_A : PROM_B), CU_TENSOR_MAP_FLOAT_OOB_FILL_NONE);
}

}

extern "C" void kernel_launch(void* const* d_in, const int* in_sizes, int n_in, void* d_out, int out_size) {
  (void)in_sizes; (void)n_in; (void)out_size;
  Params p;
  typedef const __nv_bfloat16* BP;
  p.x = (BP)d_in[0]; p.lre = (BP)d_in[1]; p.lim = (BP)d_in[2]; p.bre = (BP)d_in[3]; p.bim = (BP)d_in[4];
  p.cre = (BP)d_in[5]; p.cim = (BP)d_in[6]; p.logdt = (BP)d_in[7]; p.dskip = (BP)d_in[8];
  p.k = (BP)d_in[10]; p.v = (BP)d_in[11]; p.shiftk = (BP)d_in[12]; p.ssmk = (BP)d_in[13]; p.ssmD = (BP)d_in[14];
  p.out = (float*)d_out;
  for (int sm = 0; sm < 132; sm++) {
    const int tpc = sm >> 1, side = sm & 1;
    int gpc, gi;
    if (tpc < 32) { gpc = tpc & 7; gi = tpc >> 3; }
    else if (tpc < 60) { gpc = 1 + (tpc - 32) % 7; gi = 4 + (tpc - 32) / 7; }
    else if (tpc < 62) { gpc = tpc - 54; gi = 8; }
    else { gpc = 0; gi = tpc - 58; }
    const int pos = 8 * gpc + gi + (gpc == 7 ? 1 : 0);
    int T1, GP;
    if (pos < 52) { const int hh = pos / 26, x = pos - 26 * hh; T1 = x >> 1; GP = 2 * hh + (x & 1); }
    else { T1 = pos - 52; GP = 4; }
    const int m2 = 8 * (gpc >> 1) + gi, dg = 2 * (gpc & 1) + side;
    p.role[sm] = pos == 65 ? -1 : (T1 | (GP << 4) | (side << 7) | (m2 << 8) | (dg << 14) | ((gi < 8) << 16));
  }
  void* fnp = nullptr;
  cudaDriverEntryPointQueryResult qr;
  cudaGetDriverEntryPoint("cuTensorMapEncodeTiled", &fnp, cudaEnableDefault, &qr);
  EncFn fn = (EncFn)fnp;
  void* gG = nullptr;
  cudaGetSymbolAddress(&gG, g_G);
  const cuuint64_t RB = DM * 2;
  {
    p.swap = p.bim < p.bre;
    const char* lo = (const char*)(p.swap ? p.bim : p.bre); const char* hi = (const char*)(p.swap ? p.bre : p.bim);
    cuuint64_t dims[5] = {640, 8, 2, 8, 10}, st[4] = {RB, (cuuint64_t)(hi - lo), 8 * RB, 64 * RB}; cuuint32_t box[5] = {64, 8, 2, 4, 2};
    encode(fn, &p.mB, lo, 5, dims, st, box);
  }
  {
    cuuint64_t dims[5] = {640, 2, 4, 2, 40}, st[4] = {RB, 4 * RB, 2 * RB, 16 * RB}; cuuint32_t box[5] = {64, 2, 4, 2, 10};
    encode(fn, &p.mCre, p.cre, 5, dims, st, box); encode(fn, &p.mCim, p.cim, 5, dims, st, box);
    cuuint64_t dimg[5] = {2048, 2, 4, 2, 40}, stg[4] = {4096, 4 * 4096, 2 * 4096, 16 * 4096};
    encode(fn, &p.mG, gG, 5, dimg, stg, box);
  }
  {
    cuuint64_t dims[4] = {640, 2, 4, 900}, st[3] = {RB, 40 * RB, 2 * RB}; cuuint32_t box[4] = {64, 2, 4, 20};
    encode(fn, &p.mX, p.x, 4, dims, st, box);
    cuuint64_t diml[4] = {640, 2, 4, 16}, stl[3] = {RB, 32 * RB, 2 * RB};
    encode(fn, &p.mXl, p.x + (size_t)1920 * DM, 4, diml, stl, box);
    cuuint32_t boxt[4] = {160, 2, 4, 4};
    encode(fn, &p.mXt, p.x, 4, dims, st, boxt, CU_TENSOR_MAP_SWIZZLE_NONE);
    encode(fn, &p.mXtl, p.x + (size_t)1920 * DM, 4, diml, stl, boxt, CU_TENSOR_MAP_SWIZZLE_NONE);
    cuuint64_t dk[3] = {640, 2000, 4}, sk[2] = {RB, 16 * RB}; cuuint32_t bk[3] = {32, 19, 4}, bv[3] = {32, 17, 4};
    encode(fn, &p.mK, p.k, 3, dk, sk, bk, CU_TENSOR_MAP_SWIZZLE_NONE);
    encode(fn, &p.mV, p.v, 3, dk, sk, bv, CU_TENSOR_MAP_SWIZZLE_NONE);
  }
  cudaFuncSetAttribute(fused_kernel, cudaFuncAttributeMaxDynamicSharedMemorySize, SMEM_BYTES);
  cudaLaunchConfig_t cfg = {};
  cfg.gridDim = dim3(132); cfg.blockDim = dim3(512); cfg.dynamicSmemBytes = SMEM_BYTES; cfg.stream = cudaStreamPerThread;
  cudaLaunchKernelEx(&cfg, fused_kernel, p);
}
```

```cpp
#include <cuda_runtime.h>
#include <cuda.h>
#include <cuda_bf16.h>
#include <stdint.h>

namespace {

constexpr int SEQ = 2048, DM = 640;
constexpr int NT1 = 13;
#define EXP 0
#define WPF1 3
#define WPF2 7
#define CPOLL 10
#define KV0 5
#define TAP0 2
#define PROM_A 2
#define PROM_B 2
#define XFIRST 0
#define TAPLATE 1
#define STG_D 3
#define STG_KK 1
#define HOLD0 1
#define WREL 0
#define UREL 1
#define PAUSE_K 3
constexpr uint32_t SPIN_LIMIT = 1u << 22;

__device__ __align__(1024) uint8_t g_h[2 * 32 * 20 * 8192];
__device__ __align__(1024) uint8_t g_u[NT1 * 10 * 20480];
__device__ __align__(1024) uint8_t g_kv[DM * 4096];
__device__ __align__(1024) uint8_t g_G[DM * 4096];
__device__ __align__(128) uint4 g_E[2 * NT1 * DM];
__device__ __align__(128) uint4 g_stats[4 * 4 * SEQ];
__device__ __align__(128) uint4 g_sB[DM * 2];
__device__ __align__(128) unsigned g_hflag[2 * NT1 * 2 * 16 * 8];
__device__ __align__(128) unsigned g_uflag[32 * 4 * 8];
__device__ __align__(128) unsigned g_kvflag[4 * 32 * 8];
__device__ __align__(128) unsigned g_gflag[4 * 32 * 8];
__device__ __align__(128) unsigned g_epoch[32] = {1};
#define TS(i) do {} while (0)

struct Params {
  CUtensorMap mB, mCre, mCim, mX, mXl, mG, mK, mV, mXt, mXtl;
  const __nv_bfloat16 *x, *lre, *lim, *bre, *bim, *cre, *cim, *logdt, *dskip, *k, *v, *shiftk, *ssmk, *ssmD;
  float* out;
  int swap;
  int role[132];
};

constexpr uint32_t sb = 1024;
constexpr uint32_t G1_STAGE = 36864, G1_XOFF = 16384;
constexpr int S1 = 4;
constexpr uint32_t XT_OFF = 159744, KS_OFF = 180224, KV_PIECE = 9216;
constexpr uint32_t G2_XB = 8192, G2_WB = 20480, G2_WOFF = 57344, G_OFF = 200704;
constexpr int SX2 = 5;
constexpr uint32_t CV_OFF = KS_OFF, CV_K = 128, CV_PL = 2240, CV_U = CV_K + 4096, CV_B = KV_PIECE;
constexpr uint32_t MISC = 226304;
constexpr uint32_t BAR_OFF = MISC;
constexpr int B_G1FULL = 0, B_G1DONE = 20, B_G2FULL = 40, B_CVFULL = 80  ,
              B_G2DONE = 85, B_GFULL = 125, B_EP = 126, B_H1 = 127  , B_TAPS = 129  , B_STG = 134  , B_REL = 136  ,
              B_GO = 139  , B_PD = 142  , B_PUB = 147,
              B_CVDONE = 148  , B_STAB = 153  , B_XFREE = 155, B_HST = 156  ,
              B_CTAB = 160, B_PREP = 161, B_XT = 162, B_KV = 163  ;
constexpr uint32_t bars = sb + BAR_OFF;
constexpr uint32_t STAB_OFF = MISC + 1344;
constexpr uint32_t CTAB_OFF = STAB_OFF + 1280;
constexpr uint32_t DTAB_OFF = CTAB_OFF + 1536;
constexpr uint32_t EP_OFF = DTAB_OFF + 320;
constexpr uint32_t SO_OFF = EP_OFF + 32;
constexpr uint32_t TAP_OFF = 147456;
constexpr uint32_t SMEM_BYTES = 232448;
static_assert(SO_OFF + 1536 <= SMEM_BYTES, "smem");

__device__ __forceinline__ void trap_if(bool c) { asm volatile("{\n.reg .pred p;\nsetp.ne.u32 p, %0, 0;\n@p trap;\n}\n" ::"r"((uint32_t)c)); }
__device__ __forceinline__ uint32_t smem_u32(const void* p) { return (uint32_t)__cvta_generic_to_shared(p); }
__device__ __forceinline__ void mbar_init(uint32_t bar, int cnt) { asm volatile("mbarrier.init.shared::cta.b64 [%0], %1;" ::"r"(bar), "r"(cnt) : "memory"); }
__device__ __forceinline__ void mbar_expect_tx(uint32_t bar, int bytes) { asm volatile("mbarrier.arrive.expect_tx.shared::cta.b64 _, [%0], %1;" ::"r"(bar), "r"(bytes) : "memory"); }
__device__ __forceinline__ void mbar_arrive(uint32_t bar) { asm volatile("mbarrier.arrive.shared::cta.b64 _, [%0];" ::"r"(bar) : "memory"); }
__device__ __forceinline__ void mbar_wait(uint32_t bar) {
  asm volatile(
      "{\n.reg .pred p;\n.reg .u32 c;\nmov.u32 c, 0;\n"
      "W_%=:\nmbarrier.try_wait.parity.shared::cta.b64 p, [%0], 0;\n@p bra D_%=;\n"
      "add.u32 c, c, 1;\nsetp.lt.u32 p, c, %1;\n@p bra W_%=;\ntrap;\nD_%=:\n}\n" ::"r"(bar), "n"(SPIN_LIMIT) : "memory");
}
__device__ __forceinline__ uint32_t mbar_test(uint32_t bar) {
  uint32_t ok;
  asm volatile("{\n.reg .pred p;\nmbarrier.test_wait.parity.shared::cta.b64 p, [%1], 0;\nselp.u32 %0, 1, 0, p;\n}\n" : "=r"(ok) : "r"(bar) : "memory");
  return ok;
}
__device__ __forceinline__ void tma3(uint32_t dst, const CUtensorMap* m, int c0, int c1, int c2, uint32_t bar) {
  asm volatile("cp.async.bulk.tensor.3d.shared::cluster.global.mbarrier::complete_tx::bytes [%0], [%1, {%3,%4,%5}], [%2];"
               ::"r"(dst), "l"(m), "r"(bar), "r"(c0), "r"(c1), "r"(c2) : "memory");
}
__device__ __forceinline__ void tma4(uint32_t dst, const CUtensorMap* m, int c0, int c1, int c2, int c3, uint32_t bar) {
  asm volatile("cp.async.bulk.tensor.4d.shared::cluster.global.mbarrier::complete_tx::bytes [%0], [%1, {%3,%4,%5,%6}], [%2];"
               ::"r"(dst), "l"(m), "r"(bar), "r"(c0), "r"(c1), "r"(c2), "r"(c3) : "memory");
}
__device__ __forceinline__ void tma5(uint32_t dst, const CUtensorMap* m, int c0, int c1, int c2, int c3, int c4, uint32_t bar) {
  asm volatile("cp.async.bulk.tensor.5d.shared::cluster.global.mbarrier::complete_tx::bytes [%0], [%1, {%3,%4,%5,%6,%7}], [%2];"
               ::"r"(dst), "l"(m), "r"(bar), "r"(c0), "r"(c1), "r"(c2), "r"(c3), "r"(c4) : "memory");
}
__device__ __forceinline__ void bulk_g2s(uint32_t dst, const void* src, int bytes, uint32_t bar) {
  asm volatile("cp.async.bulk.shared::cluster.global.mbarrier::complete_tx::bytes [%0], [%1], %2, [%3];"
               ::"r"(dst), "l"(src), "r"(bytes), "r"(bar) : "memory");
}
__device__ __forceinline__ void bulk_s2g(void* dst, uint32_t src, int bytes) {
  asm volatile("cp.async.bulk.global.shared::cta.bulk_group [%0], [%1], %2;" ::"l"(dst), "r"(src), "r"(bytes) : "memory");
}
__device__ __forceinline__ void l2_prefetch(const void* src, int bytes) {
  asm volatile("cp.async.bulk.prefetch.L2.global [%0], %1;" ::"l"(src), "r"(bytes) : "memory");
}
__device__ __forceinline__ void wgmma_fence() { asm volatile("wgmma.fence.sync.aligned;" ::: "memory"); }
__device__ __forceinline__ void wgmma_commit() { asm volatile("wgmma.commit_group.sync.aligned;" ::: "memory"); }
template <int N> __device__ __forceinline__ void wgmma_wait() { asm volatile("wgmma.wait_group.sync.aligned %0;" ::"n"(N) : "memory"); }
__host__ __device__ constexpr uint32_t desc_lo(uint32_t addr, uint32_t lbo) { return ((addr & 0x3FFFF) >> 4) | ((lbo >> 4) << 16); }
__host__ __device__ constexpr uint32_t desc_hi(uint32_t sbo, uint32_t swz) { return (sbo >> 4) | (swz << 30); }
__device__ __forceinline__ void bar_sync(int id, int n) { asm volatile("bar.sync %0, %1;" ::"r"(id), "r"(n) : "memory"); }
__device__ __forceinline__ uint32_t lds32(uint32_t a) { uint32_t v; asm volatile("ld.shared.u32 %0, [%1];" : "=r"(v) : "r"(a) : "memory"); return v; }
__device__ __forceinline__ float2 lds64f(uint32_t a) { float2 v; asm volatile("ld.shared.v2.f32 {%0,%1}, [%2];" : "=f"(v.x), "=f"(v.y) : "r"(a) : "memory"); return v; }
__device__ __forceinline__ float4 lds128f(uint32_t a) { float4 v; asm volatile("ld.shared.v4.f32 {%0,%1,%2,%3}, [%4];" : "=f"(v.x), "=f"(v.y), "=f"(v.z), "=f"(v.w) : "r"(a) : "memory"); return v; }
__device__ __forceinline__ void ldsm4t(uint32_t (&r)[4], uint32_t a) {
  asm volatile("ldmatrix.sync.aligned.m8n8.x4.trans.shared.b16 {%0,%1,%2,%3}, [%4];" : "=r"(r[0]), "=r"(r[1]), "=r"(r[2]), "=r"(r[3]) : "r"(a) : "memory");
}
__device__ __forceinline__ uint4 ldv128(const void* a) { uint4 v; asm volatile("ld.global.nc.v4.u32 {%0,%1,%2,%3}, [%4];" : "=r"(v.x), "=r"(v.y), "=r"(v.z), "=r"(v.w) : "l"(a) : "memory"); return v; }
__device__ __forceinline__ uint2 ldv64(const void* a) { uint2 v; asm volatile("ld.global.nc.v2.u32 {%0,%1}, [%2];" : "=r"(v.x), "=r"(v.y) : "l"(a) : "memory"); return v; }
__device__ __forceinline__ uint32_t ldv16(const void* a) { uint32_t v; asm volatile("ld.global.nc.u16 %0, [%1];" : "=r"(v) : "l"(a) : "memory"); return v; }
__device__ __forceinline__ void sts128(uint32_t a, uint4 v) { asm volatile("st.shared.v4.u32 [%0], {%1,%2,%3,%4};" ::"r"(a), "r"(v.x), "r"(v.y), "r"(v.z), "r"(v.w) : "memory"); }
__device__ __forceinline__ void sts32(uint32_t a, uint32_t v) { asm volatile("st.shared.u32 [%0], %1;" ::"r"(a), "r"(v) : "memory"); }
__device__ __forceinline__ void sts64f(uint32_t a, float x, float y) { asm volatile("st.shared.v2.f32 [%0], {%1,%2};" ::"r"(a), "f"(x), "f"(y) : "memory"); }
__device__ __forceinline__ void st_rel(unsigned* p, unsigned v) { asm volatile("st.release.gpu.global.u32 [%0], %1;" ::"l"(p), "r"(v) : "memory"); }
__device__ __forceinline__ void fence_async_global() { asm volatile("fence.proxy.async.global;" ::: "memory"); }
__device__ __forceinline__ void fence_async_smem() { asm volatile("fence.proxy.async.shared::cta;" ::: "memory"); }
__device__ __forceinline__ void rec_st(uint4* p, float a, float b, unsigned tag) {
  asm volatile("{\n.reg .b128 t;\n.reg .b64 lo, hi;\nmov.b64 lo, {%1,%2};\nmov.b64 hi, {%3,%3};\nmov.b128 t, {lo,hi};\n"
               "st.relaxed.gpu.global.b128 [%0], t;\n}\n" ::"l"(p), "r"(__float_as_uint(a)), "r"(__float_as_uint(b)), "r"(tag) : "memory");
}
__device__ __forceinline__ unsigned rec_ld(const uint4* p, float& a, float& b) {
  unsigned x, y, t;
  asm volatile("{\n.reg .b128 t;\n.reg .b64 lo, hi;\n.reg .b32 u;\nld.relaxed.gpu.global.b128 t, [%3];\nmov.b128 {lo,hi}, t;\n"
               "mov.b64 {%0,%1}, lo;\nmov.b64 {%2,u}, hi;\n}\n" : "=r"(x), "=r"(y), "=r"(t) : "l"(p) : "memory");
  a = __uint_as_float(x); b = __uint_as_float(y);
  return t;
}
__device__ __forceinline__ void rec_poll(const uint4* p, unsigned tag, float& a, float& b) {
  uint32_t it = 0;
  while (!__all_sync(0xffffffffu, rec_ld(p, a, b) == tag)) { trap_if(++it > SPIN_LIMIT); }
}
__device__ __forceinline__ unsigned ld_rlx(const unsigned* p) { unsigned v; asm volatile("ld.relaxed.gpu.global.u32 %0, [%1];" : "=r"(v) : "l"(p) : "memory"); return v; }
__device__ __forceinline__ void flag_poll(const unsigned* p, unsigned target) {
  uint32_t it = 0;
  while (!__all_sync(0xffffffffu, (int)(ld_rlx(p) - target) >= 0)) { trap_if(++it > SPIN_LIMIT); }
  asm volatile("fence.acquire.gpu;" ::: "memory");
}
__device__ __forceinline__ uint32_t pack_bf16(float lo, float hi) {
  uint32_t r; asm("cvt.rn.bf16x2.f32 %0, %1, %2;" : "=r"(r) : "f"(hi), "f"(lo)); return r;
}
__device__ __forceinline__ float bf_lo(uint32_t w) { return __uint_as_float(w << 16); }
__device__ __forceinline__ float bf_hi(uint32_t w) { return __uint_as_float(w & 0xffff0000u); }
__device__ __forceinline__ uint32_t hmul2(uint32_t a, uint32_t b) {
  __nv_bfloat162 r = __hmul2_rn(*(__nv_bfloat162*)&a, *(__nv_bfloat162*)&b); return *(uint32_t*)&r;
}
__device__ __forceinline__ uint32_t hadd2(uint32_t a, uint32_t b) {
  __nv_bfloat162 r = __hadd2_rn(*(__nv_bfloat162*)&a, *(__nv_bfloat162*)&b); return *(uint32_t*)&r;
}
__device__ __forceinline__ float2 cmul(float2 a, float2 b) { return make_float2(a.x * b.x - a.y * b.y, a.x * b.y + a.y * b.x); }
__device__ __forceinline__ float2 cfma(float2 a, float2 b, float2 c) {
  return make_float2(fmaf(a.x, b.x, fmaf(-a.y, b.y, c.x)), fmaf(a.x, b.y, fmaf(a.y, b.x, c.y)));
}
template <int N> __device__ __forceinline__ void fence_regs(float (&a)[N]) {
#pragma unroll
  for (int i = 0; i < N; i++) asm volatile("" : "+f"(a[i])::"memory");
}
__device__ __forceinline__ bool elect_one() {
  uint32_t e; asm volatile("{\n.reg .pred P;\nelect.sync _|P, 0xffffffff;\nselp.u32 %0, 1, 0, P;\n}\n" : "=r"(e)); return e != 0;
}
__device__ __forceinline__ int tid_opaque() { int t; asm volatile("mov.u32 %0, %%tid.x;" : "=r"(t)); return t; }
struct Role { int T1, GP, side, m2, dg, cch0; bool last, has2; };
__device__ __forceinline__ Role unpack_role(int x) {
  Role r; r.T1 = x & 15; r.GP = (x >> 4) & 7; r.side = (x >> 7) & 1; r.m2 = (x >> 8) & 63; r.dg = (x >> 14) & 3;
  r.has2 = (x >> 16) & 1; r.last = r.T1 == NT1 - 1; r.cch0 = 160 * r.dg + r.m2; return r;
}
__device__ __forceinline__ Role fresh_role(int x) { asm volatile("" : "+r"(x)); return unpack_role(__shfl_sync(0xffffffffu, x, 0)); }
#define ROLE(x) const Role R_ = fresh_role(x); const int T1 = R_.T1, GP = R_.GP, side = R_.side, m2 = R_.m2, dg = R_.dg, cch0 = R_.cch0; \
  const bool last = R_.last, has2 = R_.has2; (void)T1; (void)GP; (void)side; (void)m2; (void)dg; (void)cch0; (void)last; (void)has2;
__device__ __forceinline__ int n_to_t(int n) {
  int T = n / 160, nl = n - T * 160;
  int L = (T == NT1 - 1) ? 32 : 40;
  return T * 160 + L * ((nl & 7) >> 1) + 2 * (nl >> 3) + (nl & 1);
}

template<int TA> __device__ __forceinline__ void wgmma_n160(float (&d)[80], uint32_t alo, uint32_t ahi, uint32_t blo, uint32_t bhi){
  asm volatile("{\n.reg .b64 da, db;\nmov.b64 da, {%80,%81};\nmov.b64 db, {%82,%83};\n"
    "wgmma.mma_async.sync.aligned.m64n160k16.f32.bf16.bf16 {%0, %1, %2, %3, %4, %5, %6, %7, %8, %9, %10, %11, %12, %13, %14, %15, %16, %17, %18, %19, %20, %21, %22, %23, %24, %25, %26, %27, %28, %29, %30, %31, %32, %33, %34, %35, %36, %37, %38, %39, %40, %41, %42, %43, %44, %45, %46, %47, %48, %49, %50, %51, %52, %53, %54, %55, %56, %57, %58, %59, %60, %61, %62, %63, %64, %65, %66, %67, %68, %69, %70, %71, %72, %73, %74, %75, %76, %77, %78, %79}, da, db, 1, 1, 1, %84, 0;\n}\n"
    : "+f"(d[0]), "+f"(d[1]), "+f"(d[2]), "+f"(d[3]), "+f"(d[4]), "+f"(d[5]), "+f"(d[6]), "+f"(d[7]), "+f"(d[8]), "+f"(d[9]), "+f"(d[10]), "+f"(d[11]), "+f"(d[12]), "+f"(d[13]), "+f"(d[14]), "+f"(d[15]), "+f"(d[16]), "+f"(d[17]), "+f"(d[18]), "+f"(d[19]), "+f"(d[20]), "+f"(d[21]), "+f"(d[22]), "+f"(d[23]), "+f"(d[24]), "+f"(d[25]), "+f"(d[26]), "+f"(d[27]), "+f"(d[28]), "+f"(d[29]), "+f"(d[30]), "+f"(d[31]), "+f"(d[32]), "+f"(d[33]), "+f"(d[34]), "+f"(d[35]), "+f"(d[36]), "+f"(d[37]), "+f"(d[38]), "+f"(d[39]), "+f"(d[40]), "+f"(d[41]), "+f"(d[42]), "+f"(d[43]), "+f"(d[44]), "+f"(d[45]), "+f"(d[46]), "+f"(d[47]), "+f"(d[48]), "+f"(d[49]), "+f"(d[50]), "+f"(d[51]), "+f"(d[52]), "+f"(d[53]), "+f"(d[54]), "+f"(d[55]), "+f"(d[56]), "+f"(d[57]), "+f"(d[58]), "+f"(d[59]), "+f"(d[60]), "+f"(d[61]), "+f"(d[62]), "+f"(d[63]), "+f"(d[64]), "+f"(d[65]), "+f"(d[66]), "+f"(d[67]), "+f"(d[68]), "+f"(d[69]), "+f"(d[70]), "+f"(d[71]), "+f"(d[72]), "+f"(d[73]), "+f"(d[74]), "+f"(d[75]), "+f"(d[76]), "+f"(d[77]), "+f"(d[78]), "+f"(d[79])
    : "r"(alo), "r"(ahi), "r"(blo), "r"(bhi), "n"(TA));
}
template<int N> __device__ __forceinline__ void wgmma_rs_hi(float (&d)[64], uint32_t a0, uint32_t a1, uint32_t a2, uint32_t a3, uint32_t blo);
template<> __device__ __forceinline__ void wgmma_rs_hi<16>(float (&d)[64], uint32_t a0, uint32_t a1, uint32_t a2, uint32_t a3, uint32_t blo){
  asm volatile("{\n.reg .b64 db;\nmov.b64 db, {%12,8};\nwgmma.mma_async.sync.aligned.m64n16k16.f32.bf16.bf16 {%0, %1, %2, %3, %4, %5, %6, %7}, {%8,%9,%10,%11}, db, 1, 1, 1, 0;\n}\n"
    : "+f"(d[56]), "+f"(d[57]), "+f"(d[58]), "+f"(d[59]), "+f"(d[60]), "+f"(d[61]), "+f"(d[62]), "+f"(d[63])
    : "r"(a0), "r"(a1), "r"(a2), "r"(a3), "r"(blo));
}
template<> __device__ __forceinline__ void wgmma_rs_hi<32>(float (&d)[64], uint32_t a0, uint32_t a1, uint32_t a2, uint32_t a3, uint32_t blo){
  asm volatile("{\n.reg .b64 db;\nmov.b64 db, {%20,8};\nwgmma.mma_async.sync.aligned.m64n32k16.f32.bf16.bf16 {%0, %1, %2, %3, %4, %5, %6, %7, %8, %9, %10, %11, %12, %13, %14, %15}, {%16,%17,%18,%19}, db, 1, 1, 1, 0;\n}\n"
    : "+f"(d[48]), "+f"(d[49]), "+f"(d[50]), "+f"(d[51]), "+f"(d[52]), "+f"(d[53]), "+f"(d[54]), "+f"(d[55]), "+f"(d[56]), "+f"(d[57]), "+f"(d[58]), "+f"(d[59]), "+f"(d[60]), "+f"(d[61]), "+f"(d[62]), "+f"(d[63])
    : "r"(a0), "r"(a1), "r"(a2), "r"(a3), "r"(blo));
}
template<> __device__ __forceinline__ void wgmma_rs_hi<48>(float (&d)[64], uint32_t a0, uint32_t a1, uint32_t a2, uint32_t a3, uint32_t blo){
  asm volatile("{\n.reg .b64 db;\nmov.b64 db, {%28,8};\nwgmma.mma_async.sync.aligned.m64n48k16.f32.bf16.bf16 {%0, %1, %2, %3, %4, %5, %6, %7, %8, %9, %10, %11, %12, %13, %14, %15, %16, %17, %18, %19, %20, %21, %22, %23}, {%24,%25,%26,%27}, db, 1, 1, 1, 0;\n}\n"
    : "+f"(d[40]), "+f"(d[41]), "+f"(d[42]), "+f"(d[43]), "+f"(d[44]), "+f"(d[45]), "+f"(d[46]), "+f"(d[47]), "+f"(d[48]), "+f"(d[49]), "+f"(d[50]), "+f"(d[51]), "+f"(d[52]), "+f"(d[53]), "+f"(d[54]), "+f"(d[55]), "+f"(d[56]), "+f"(d[57]), "+f"(d[58]), "+f"(d[59]), "+f"(d[60]), "+f"(d[61]), "+f"(d[62]), "+f"(d[63])
    : "r"(a0), "r"(a1), "r"(a2), "r"(a3), "r"(blo));
}
template<> __device__ __forceinline__ void wgmma_rs_hi<64>(float (&d)[64], uint32_t a0, uint32_t a1, uint32_t a2, uint32_t a3, uint32_t blo){
  asm volatile("{\n.reg .b64 db;\nmov.b64 db, {%36,8};\nwgmma.mma_async.sync.aligned.m64n64k16.f32.bf16.bf16 {%0, %1, %2, %3, %4, %5, %6, %7, %8, %9, %10, %11, %12, %13, %14, %15, %16, %17, %18, %19, %20, %21, %22, %23, %24, %25, %26, %27, %28, %29, %30, %31}, {%32,%33,%34,%35}, db, 1, 1, 1, 0;\n}\n"
    : "+f"(d[32]), "+f"(d[33]), "+f"(d[34]), "+f"(d[35]), "+f"(d[36]), "+f"(d[37]), "+f"(d[38]), "+f"(d[39]), "+f"(d[40]), "+f"(d[41]), "+f"(d[42]), "+f"(d[43]), "+f"(d[44]), "+f"(d[45]), "+f"(d[46]), "+f"(d[47]), "+f"(d[48]), "+f"(d[49]), "+f"(d[50]), "+f"(d[51]), "+f"(d[52]), "+f"(d[53]), "+f"(d[54]), "+f"(d[55]), "+f"(d[56]), "+f"(d[57]), "+f"(d[58]), "+f"(d[59]), "+f"(d[60]), "+f"(d[61]), "+f"(d[62]), "+f"(d[63])
    : "r"(a0), "r"(a1), "r"(a2), "r"(a3), "r"(blo));
}
template<> __device__ __forceinline__ void wgmma_rs_hi<80>(float (&d)[64], uint32_t a0, uint32_t a1, uint32_t a2, uint32_t a3, uint32_t blo){
  asm volatile("{\n.reg .b64 db;\nmov.b64 db, {%44,8};\nwgmma.mma_async.sync.aligned.m64n80k16.f32.bf16.bf16 {%0, %1, %2, %3, %4, %5, %6, %7, %8, %9, %10, %11, %12, %13, %14, %15, %16, %17, %18, %19, %20, %21, %22, %23, %24, %25, %26, %27, %28, %29, %30, %31, %32, %33, %34, %35, %36, %37, %38, %39}, {%40,%41,%42,%43}, db, 1, 1, 1, 0;\n}\n"
    : "+f"(d[24]), "+f"(d[25]), "+f"(d[26]), "+f"(d[27]), "+f"(d[28]), "+f"(d[29]), "+f"(d[30]), "+f"(d[31]), "+f"(d[32]), "+f"(d[33]), "+f"(d[34]), "+f"(d[35]), "+f"(d[36]), "+f"(d[37]), "+f"(d[38]), "+f"(d[39]), "+f"(d[40]), "+f"(d[41]), "+f"(d[42]), "+f"(d[43]), "+f"(d[44]), "+f"(d[45]), "+f"(d[46]), "+f"(d[47]), "+f"(d[48]), "+f"(d[49]), "+f"(d[50]), "+f"(d[51]), "+f"(d[52]), "+f"(d[53]), "+f"(d[54]), "+f"(d[55]), "+f"(d[56]), "+f"(d[57]), "+f"(d[58]), "+f"(d[59]), "+f"(d[60]), "+f"(d[61]), "+f"(d[62]), "+f"(d[63])
    : "r"(a0), "r"(a1), "r"(a2), "r"(a3), "r"(blo));
}
template<> __device__ __forceinline__ void wgmma_rs_hi<96>(float (&d)[64], uint32_t a0, uint32_t a1, uint32_t a2, uint32_t a3, uint32_t blo){
  asm volatile("{\n.reg .b64 db;\nmov.b64 db, {%52,8};\nwgmma.mma_async.sync.aligned.m64n96k16.f32.bf16.bf16 {%0, %1, %2, %3, %4, %5, %6, %7, %8, %9, %10, %11, %12, %13, %14, %15, %16, %17, %18, %19, %20, %21, %22, %23, %24, %25, %26, %27, %28, %29, %30, %31, %32, %33, %34, %35, %36, %37, %38, %39, %40, %41, %42, %43, %44, %45, %46, %47}, {%48,%49,%50,%51}, db, 1, 1, 1, 0;\n}\n"
    : "+f"(d[16]), "+f"(d[17]), "+f"(d[18]), "+f"(d[19]), "+f"(d[20]), "+f"(d[21]), "+f"(d[22]), "+f"(d[23]), "+f"(d[24]), "+f"(d[25]), "+f"(d[26]), "+f"(d[27]), "+f"(d[28]), "+f"(d[29]), "+f"(d[30]), "+f"(d[31]), "+f"(d[32]), "+f"(d[33]), "+f"(d[34]), "+f"(d[35]), "+f"(d[36]), "+f"(d[37]), "+f"(d[38]), "+f"(d[39]), "+f"(d[40]), "+f"(d[41]), "+f"(d[42]), "+f"(d[43]), "+f"(d[44]), "+f"(d[45]), "+f"(d[46]), "+f"(d[47]), "+f"(d[48]), "+f"(d[49]), "+f"(d[50]), "+f"(d[51]), "+f"(d[52]), "+f"(d[53]), "+f"(d[54]), "+f"(d[55]), "+f"(d[56]), "+f"(d[57]), "+f"(d[58]), "+f"(d[59]), "+f"(d[60]), "+f"(d[61]), "+f"(d[62]), "+f"(d[63])
    : "r"(a0), "r"(a1), "r"(a2), "r"(a3), "r"(blo));
}
template<> __device__ __forceinline__ void wgmma_rs_hi<112>(float (&d)[64], uint32_t a0, uint32_t a1, uint32_t a2, uint32_t a3, uint32_t blo){
  asm volatile("{\n.reg .b64 db;\nmov.b64 db, {%60,8};\nwgmma.mma_async.sync.aligned.m64n112k16.f32.bf16.bf16 {%0, %1, %2, %3, %4, %5, %6, %7, %8, %9, %10, %11, %12, %13, %14, %15, %16, %17, %18, %19, %20, %21, %22, %23, %24, %25, %26, %27, %28, %29, %30, %31, %32, %33, %34, %35, %36, %37, %38, %39, %40, %41, %42, %43, %44, %45, %46, %47, %48, %49, %50, %51, %52, %53, %54, %55}, {%56,%57,%58,%59}, db, 1, 1, 1, 0;\n}\n"
    : "+f"(d[8]), "+f"(d[9]), "+f"(d[10]), "+f"(d[11]), "+f"(d[12]), "+f"(d[13]), "+f"(d[14]), "+f"(d[15]), "+f"(d[16]), "+f"(d[17]), "+f"(d[18]), "+f"(d[19]), "+f"(d[20]), "+f"(d[21]), "+f"(d[22]), "+f"(d[23]), "+f"(d[24]), "+f"(d[25]), "+f"(d[26]), "+f"(d[27]), "+f"(d[28]), "+f"(d[29]), "+f"(d[30]), "+f"(d[31]), "+f"(d[32]), "+f"(d[33]), "+f"(d[34]), "+f"(d[35]), "+f"(d[36]), "+f"(d[37]), "+f"(d[38]), "+f"(d[39]), "+f"(d[40]), "+f"(d[41]), "+f"(d[42]), "+f"(d[43]), "+f"(d[44]), "+f"(d[45]), "+f"(d[46]), "+f"(d[47]), "+f"(d[48]), "+f"(d[49]), "+f"(d[50]), "+f"(d[51]), "+f"(d[52]), "+f"(d[53]), "+f"(d[54]), "+f"(d[55]), "+f"(d[56]), "+f"(d[57]), "+f"(d[58]), "+f"(d[59]), "+f"(d[60]), "+f"(d[61]), "+f"(d[62]), "+f"(d[63])
    : "r"(a0), "r"(a1), "r"(a2), "r"(a3), "r"(blo));
}
template<> __device__ __forceinline__ void wgmma_rs_hi<128>(float (&d)[64], uint32_t a0, uint32_t a1, uint32_t a2, uint32_t a3, uint32_t blo){
  asm volatile("{\n.reg .b64 db;\nmov.b64 db, {%68,8};\nwgmma.mma_async.sync.aligned.m64n128k16.f32.bf16.bf16 {%0, %1, %2, %3, %4, %5, %6, %7, %8, %9, %10, %11, %12, %13, %14, %15, %16, %17, %18, %19, %20, %21, %22, %23, %24, %25, %26, %27, %28, %29, %30, %31, %32, %33, %34, %35, %36, %37, %38, %39, %40, %41, %42, %43, %44, %45, %46, %47, %48, %49, %50, %51, %52, %53, %54, %55, %56, %57, %58, %59, %60, %61, %62, %63}, {%64,%65,%66,%67}, db, 1, 1, 1, 0;\n}\n"
    : "+f"(d[0]), "+f"(d[1]), "+f"(d[2]), "+f"(d[3]), "+f"(d[4]), "+f"(d[5]), "+f"(d[6]), "+f"(d[7]), "+f"(d[8]), "+f"(d[9]), "+f"(d[10]), "+f"(d[11]), "+f"(d[12]), "+f"(d[13]), "+f"(d[14]), "+f"(d[15]), "+f"(d[16]), "+f"(d[17]), "+f"(d[18]), "+f"(d[19]), "+f"(d[20]), "+f"(d[21]), "+f"(d[22]), "+f"(d[23]), "+f"(d[24]), "+f"(d[25]), "+f"(d[26]), "+f"(d[27]), "+f"(d[28]), "+f"(d[29]), "+f"(d[30]), "+f"(d[31]), "+f"(d[32]), "+f"(d[33]), "+f"(d[34]), "+f"(d[35]), "+f"(d[36]), "+f"(d[37]), "+f"(d[38]), "+f"(d[39]), "+f"(d[40]), "+f"(d[41]), "+f"(d[42]), "+f"(d[43]), "+f"(d[44]), "+f"(d[45]), "+f"(d[46]), "+f"(d[47]), "+f"(d[48]), "+f"(d[49]), "+f"(d[50]), "+f"(d[51]), "+f"(d[52]), "+f"(d[53]), "+f"(d[54]), "+f"(d[55]), "+f"(d[56]), "+f"(d[57]), "+f"(d[58]), "+f"(d[59]), "+f"(d[60]), "+f"(d[61]), "+f"(d[62]), "+f"(d[63])
    : "r"(a0), "r"(a1), "r"(a2), "r"(a3), "r"(blo));
}

__device__ __forceinline__ float shfl_sel(float a, float b, bool p, int src) {
  float r;
  asm volatile("{\n.reg .pred P;\n.reg .f32 t;\nsetp.ne.u32 P, %3, 0;\nselp.f32 t, %1, %2, P;\nshfl.sync.idx.b32 %0, t, %4, 0x1f, 0xffffffff;\n}\n"
               : "=f"(r) : "f"(a), "f"(b), "r"((uint32_t)p), "r"(src));
  return r;
}
struct CvCtx {
  uint32_t koff, zero, so[3];
  int srcA, srcB;
  bool wrapA, s3, kodd;
};
struct CvPipe { float Ep[2], keep[2], send[2]; };
template <int LO> __device__ __forceinline__ void cv_copy(float (&acc)[64]) {
#pragma unroll
  for (int i = LO; i < 64; i++) { float t; asm volatile("mov.b32 %0, %1;" : "=f"(t) : "f"(acc[i]) : "memory"); acc[i] = t; }
}
template <int G> __device__ __forceinline__ void cv_raw(uint32_t (&A)[4][4], uint32_t kaddr) {
#pragma unroll
  for (int i = 0; i < 4; i++) {
    const uint32_t a = kaddr + (4 * G + i) * 128;
    A[i][0] = lds32(a); A[i][1] = lds32(a + 4); A[i][3] = lds32(a + 8);
  }
}
__device__ __forceinline__ void cv_form(uint32_t (&A)[4][4], uint32_t sel) {
#pragma unroll
  for (int i = 0; i < 4; i++) {
    asm volatile("prmt.b32 %0, %0, %1, %2;" : "+r"(A[i][0]) : "r"(A[i][1]), "r"(sel));
    asm volatile("prmt.b32 %0, %1, %2, %3;" : "=r"(A[i][2]) : "r"(A[i][1]), "r"(A[i][3]), "r"(sel));
  }
}
#define CVV 2
template <int G> __device__ __forceinline__ void cv_step(float (&acc)[64], uint32_t (&A)[4][4], CvPipe& s, const CvCtx& c, uint32_t cb, uint32_t stg) {
  constexpr int JA = G - 1, JB = G - 2, NH = CVV == 1 ? 4 : (CVV == 3 ? 2 : 1);
  const uint32_t db0 = desc_lo(cb + CV_U + 192, CV_PL);
  uint32_t B[4][4];
  float ra[4], rb[2];
  if constexpr (G < 8) {
    wgmma_fence();
#pragma unroll
    for (int i = 0; i < NH; i++) wgmma_rs_hi<128 - 16 * (G & 7)>(acc, A[i][0], A[i][1], A[i][2], A[i][3], db0 - 4 * i);
    wgmma_commit();
    __syncwarp();
  }
  if constexpr (JA >= 0 && JA < 8) {
#pragma unroll
    for (int x = 0; x < 4; x++) {
      const int i = 8 * JA + 4 * (x >> 1) + 2 * (x & 1) + 1;
      ra[x] = shfl_sel(i >= 4 ? acc[i >= 4 ? i - 4 : 0] : 0.f, acc[i], c.wrapA, c.srcA);
    }
  }
  if constexpr (JB >= 0) {
#pragma unroll
    for (int h = 0; h < 2; h++) rb[h] = __shfl_sync(0xffffffffu, s.send[h], c.srcB);
  }
  if constexpr (G < 7) cv_raw<G + 1>(B, cb + c.koff);
  uint32_t z = 0;
  if constexpr (G < 8 && NH < 4) {
    __syncwarp();
    wgmma_fence();
#pragma unroll
    for (int i = NH; i < 4; i++) wgmma_rs_hi<128 - 16 * (G & 7)>(acc, A[i][0], A[i][1], A[i][2], A[i][3], db0 - 4 * i);
    wgmma_commit();
    asm volatile("mov.u32 %0, %%clock;" : "=r"(z)::"memory");
    z &= c.zero;
  }
  const float one = __uint_as_float(0x3f800000u | z);
  if constexpr (G < 7) cv_form(B, 0x5432u | z);
  if constexpr (JB >= 0) sts32(stg + ((c.so[JB / 3] >> (10 * (JB % 3))) & 0xffc), pack_bf16(fmaf(rb[0], one, s.keep[0]), fmaf(rb[1], one, s.keep[1])));
  if constexpr (JA >= 0 && JA < 8) {
#pragma unroll
    for (int h = 0; h < 2; h++) {
      const float ev = fmaf(ra[h], one, acc[8 * JA + 2 * h]), od = fmaf(ra[2 + h], one, acc[8 * JA + 4 + 2 * h]);
      s.send[h] = c.kodd ? ev : (c.s3 ? s.Ep[h] : od);
      s.keep[h] = c.kodd ? od : ev;
      s.Ep[h] = od;
    }
  }
  if constexpr (G < 8) { __syncwarp(); wgmma_wait<0>(); cv_copy<8 * (G & 7)>(acc); }
  if constexpr (G < 9) cv_step<G + 1>(acc, B, s, c, cb, stg);
}
__device__ __forceinline__ uint32_t cv_stage(int slot) { return sb + (slot < 4 ? 40960 + slot * 4096 : CV_OFF + CV_K); }
__device__ __forceinline__ void cv_setup(CvCtx& c) {
  const int tid = tid_opaque() & 127, w = tid >> 5, lane = tid & 31, r = lane >> 2, q = lane & 3;
  const int i0 = (r >> 1) & 1, i1 = r >> 2;
  c.koff = CV_K - 32 + 4 * (8 * (r >> 1) + 2 * w + (r & 1) + 2 * q);
  c.srcA = i0 ? lane - 8 : lane + 8 - q + ((q + 3) & 3);
  c.wrapA = i0 && q == 3;
  c.srcB = i1 == 0 ? (lane - q + 16 + ((q + 3) & 3)) : (lane - q - 16 + ((q + 1) & 3));
  c.s3 = (i1 == 1 && q == 3); c.kodd = (i1 == 1 && q < 3);
  c.zero = lds32(sb + EP_OFF + 24);
#pragma unroll
  for (int i = 0; i < 3; i++) c.so[i] = lds32(sb + SO_OFF + 512 * i + 4 * tid);
}
__device__ __forceinline__ void cv_table() {
  const int tid = tid_opaque() & 127, r = (tid & 31) >> 2, q = tid & 3;
  int t = 16 * (2 * (r < 4 ? q : 4 + ((q + 1) & 3)) + ((r >> 1) & 1)) + 4 * (tid >> 5) + 2 * (r & 1);
#pragma unroll 1
  for (int i = 0; i < 3; i++) {
    uint32_t v = 0;
#pragma unroll 1
    for (int x = 0; x < 3; x++, t += 256) {
      const int T = t / 160, tl = t - T * 160;
      const int qq = (T >= NT1 - 1) ? (tl >> 5) : (tl / 40);
      int ck = 20 * T + ((tl - qq * ((T >= NT1 - 1) ? 32 : 40)) >> 1);
      ck ^= (ck >> 2) & 6;
      v |= (uint32_t)((ck * 4 + qq) & 1023) << (10 * x + 2);
    }
    sts32(sb + SO_OFF + 512 * i + 4 * tid, v);
  }
}
__device__ __forceinline__ void conv_channel(int slot, const CvCtx& c) {
  const uint32_t cb = sb + CV_OFF + slot * CV_B;
  float acc[64];
  CvPipe s;
  s.Ep[0] = s.Ep[1] = 0.f;
  uint32_t A[4][4];
#pragma unroll
  for (int i = 0; i < 64; i++) acc[i] = 0.f;
  if (slot == 4) mbar_wait(bars + 8 * B_CVDONE);
  mbar_wait(bars + 8 * (B_CVFULL + slot));
  cv_raw<0>(A, cb + c.koff);
  {
    const uint32_t w0 = lds32(cb + CV_K);
    const uint32_t wp = __byte_perm(pack_bf16(bf_lo(w0) + __uint_as_float(lds32(sb + EP_OFF + 4 * slot)), 0.f), w0, 0x7610);
    if (c.koff == CV_K) A[0][0] = wp;
    if (c.koff == CV_K - 4) A[0][1] = wp;
    if (c.koff == CV_K - 8) A[0][3] = wp;
  }
  cv_form(A, 0x5432u);
  cv_copy<0>(acc);
  cv_step<0>(acc, A, s, c, cb, cv_stage(slot));
  fence_async_smem();
  mbar_arrive(bars + 8 * (B_CVDONE + slot));
}

__device__ __forceinline__ void kv_issue(const Params& p, int c, int m2, int dg) {
  const uint32_t fb = bars + 8 * (B_KV + c);
  mbar_expect_tx(fb, KV_PIECE);
  tma3(sb + KS_OFF + c * KV_PIECE, &p.mK, 160 * dg + 32 * c, 64 * m2 - 3, 0, fb);
  tma3(sb + KS_OFF + c * KV_PIECE + 4864, &p.mV, 160 * dg + 32 * c, 64 * m2 - 1, 0, fb);
}
__device__ __forceinline__ void kv_tile(int m, int dg, int c, int y) {
  const int lane = tid_opaque() & 31, tg = lane >> 3;
  const uint32_t pb = sb + KS_OFF + c * KV_PIECE + 32 * y + 4 * (lane & 7);
  const uint32_t ka = pb + tg * 1216, va = pb + 4864 + tg * 1088 + 64;
  const uint32_t kh = (m == 0 && tg > 0) ? ka - 192 : ka;
  uint32_t kk[19], u[16];
  const float4 t = lds128f(sb + TAP_OFF + 256 * c + 128 * y + 16 * (lane & 7));
#pragma unroll
  for (int i = 0; i < 19; i++) { kk[i] = lds32((i < 3 ? kh : ka) + i * 64); if (i >= 3) u[i - 3] = lds32(va + (i - 3) * 64); }
  uint8_t* dst = g_kv + ((160 * dg + 32 * c + 16 * y + 2 * (lane & 7)) * 4096 + (4 * m + tg) * 16);
  const uint32_t w0 = __byte_perm(__float_as_uint(t.x), __float_as_uint(t.z), 0x5410), w1 = __byte_perm(__float_as_uint(t.x), __float_as_uint(t.z), 0x7632);
  const uint32_t w2 = __byte_perm(__float_as_uint(t.y), __float_as_uint(t.w), 0x5410), w3 = __byte_perm(__float_as_uint(t.y), __float_as_uint(t.w), 0x7632);
#pragma unroll
  for (int i = 0; i < 16; i++) {
    uint32_t a = hmul2(kk[i], w3);
    a = hadd2(a, hmul2(kk[i + 1], w2)); a = hadd2(a, hmul2(kk[i + 2], w1)); a = hadd2(a, hmul2(kk[i + 3], w0));
    u[i] = hmul2(a, u[i]);
  }
#pragma unroll
  for (int e = 0; e < 2; e++)
#pragma unroll
    for (int f = 0; f < 2; f++) {
      uint32_t o[4];
#pragma unroll
      for (int qq = 0; qq < 4; qq++) o[qq] = __byte_perm(u[15 - 4 * qq - 2 * f], u[14 - 4 * qq - 2 * f], e ? 0x7632 : 0x5410);
      *(uint4*)(dst + e * 4096 + f * 2048) = make_uint4(o[0], o[1], o[2], o[3]);
    }
}
__device__ __forceinline__ void ln_finish(float s1, float s2, float& mean, float& rstd) {
  mean = s1 * (1.f / 640.f);
  const float v = fmaxf(fmaf(-mean, mean, s2 * (1.f / 640.f)), 0.f) + 1e-5f;
  asm("rsqrt.approx.ftz.f32 %0, %1;" : "=f"(rstd) : "f"(v));
}
__device__ __forceinline__ void stat_table(int T1, unsigned want, int l, int g, const uint4* x0, const uint4* x1, float (&xa)[2], float (&xb)[2]) {
  const int n = 32 * g + (tid_opaque() & 31);
  const uint4* rp = &g_stats[8 * l * SEQ + min(160 * T1 + n, SEQ - 1)];
  float a[4], b[4];
  uint32_t it = 0;
  while (true) {
    bool ok = true;
#pragma unroll
    for (int i = 0; i < 4; i++) ok &= (rec_ld(rp + SEQ * i, a[i], b[i]) == want);
    ok &= rec_ld(x0, xa[0], xb[0]) == want;
    ok &= rec_ld(x1, xa[1], xb[1]) == want;
    if (__all_sync(0xffffffffu, ok)) break;
    trap_if(++it > SPIN_LIMIT);
  }
  float m, rs;
  ln_finish((a[0] + a[1]) + (a[2] + a[3]), (b[0] + b[1]) + (b[2] + b[3]), m, rs);
  sts64f(sb + STAB_OFF + n * 8, rs, -m * rs);
}
__device__ __forceinline__ void stats_reduce(float (&a)[2], float (&b)[2], float (&mean)[2], float (&rstd)[2]) {
#pragma unroll
  for (int o = 1; o < 4; o <<= 1)
#pragma unroll
    for (int h = 0; h < 2; h++) { a[h] += __shfl_xor_sync(0xffffffffu, a[h], o); b[h] += __shfl_xor_sync(0xffffffffu, b[h], o); }
#pragma unroll
  for (int h = 0; h < 2; h++) ln_finish(a[h], b[h], mean[h], rstd[h]);
}

template <bool FIRST>
__device__ __forceinline__ void stats_publish(int which, int n0, int dg, unsigned tag, const float (&acc)[80]) {
  const int q = tid_opaque() & 3, h = q & 1;
  float s1[2] = {0.f, 0.f}, s2[2] = {0.f, 0.f}, t1[2] = {0.f, 0.f}, t2[2] = {0.f, 0.f};
#pragma unroll
  for (int j = 0; j < 20; j++)
#pragma unroll
    for (int y = 0; y < 2; y++) {
      const float a = acc[4 * j + 2 * y], b = acc[4 * j + 2 * y + 1];
      s1[y] += a; t1[y] += b; s2[y] = fmaf(a, a, s2[y]); t2[y] = fmaf(b, b, t2[y]);
    }
#pragma unroll
  for (int y = 0; y < 2; y++) { s1[y] += t1[y]; s2[y] += t2[y]; }
  float a = (h ? s1[1] : s1[0]) + __shfl_xor_sync(0xffffffffu, h ? s1[0] : s1[1], 1);
  float b = (h ? s2[1] : s2[0]) + __shfl_xor_sync(0xffffffffu, h ? s2[0] : s2[1], 1);
  a += __shfl_xor_sync(0xffffffffu, a, 2);
  b += __shfl_xor_sync(0xffffffffu, b, 2);
  if (FIRST) {
    rec_st(&g_stats[((q >> 1) * 4 + dg) * SEQ + n0 + 8 * h], a, b, q < 2 ? tag : tag - 1);
    rec_st(&g_stats[((q >> 1) * 4 + 8 + dg) * SEQ + n0 + 8 * h], a, b, tag - 1);
  } else if (q < 2) rec_st(&g_stats[(which * 4 + dg) * SEQ + n0 + 8 * h], a, b, tag);
}
__device__ __forceinline__ void stats_get(int which, int n0, unsigned tag, float (&mean)[2], float (&rstd)[2]) {
  const uint4* p0 = &g_stats[(which * 4 + (tid_opaque() & 3)) * SEQ + n0];
  float a[2], b[2];
  uint32_t it = 0;
  while (true) {
    const unsigned t0 = rec_ld(p0, a[0], b[0]), t1 = rec_ld(p0 + 8, a[1], b[1]);
    if (__all_sync(0xffffffffu, t0 == tag && t1 == tag)) break;
    trap_if(++it > SPIN_LIMIT);
  }
  stats_reduce(a, b, mean, rstd);
}
__device__ __forceinline__ void x0_load(float (&acc)[80]) {
  const int t = tid_opaque() & 127;
  const uint32_t xa = sb + XT_OFF + (16 * (t >> 5) + ((t & 31) >> 2)) * 320 + 8 * (t & 3);
  mbar_wait(bars + 8 * B_XT);
#pragma unroll
  for (int h = 0; h < 2; h++)
#pragma unroll
    for (int J = 0; J < 10; J++) {
      const float2 v = lds64f(xa + h * 2560 + 32 * J);
      const uint32_t x = __float_as_uint(v.x), y = __float_as_uint(v.y);
      acc[8 * J + 2 * h] = bf_lo(x); acc[8 * J + 2 * h + 1] = bf_hi(x);
      acc[8 * J + 4 + 2 * h] = bf_lo(y); acc[8 * J + 4 + 2 * h + 1] = bf_hi(y);
    }
}

template <bool FROM_X0>
__device__ __forceinline__ void dskip_init(float (&acc)[80], const float (&mean)[2], const float (&rstd)[2]) {
  const int t = tid_opaque() & 127;
  const uint32_t xa = sb + XT_OFF + (16 * (t >> 5) + ((t & 31) >> 2)) * 320 + 8 * (t & 3), da = sb + DTAB_OFF + 8 * (t & 3);
  float2 dw[10], xv[10][2];
#pragma unroll
  for (int J = 0; J < 2; J++) { dw[J] = lds64f(da + 32 * J); if (FROM_X0) { xv[J][0] = lds64f(xa + 32 * J); xv[J][1] = lds64f(xa + 2560 + 32 * J); } }
#pragma unroll
  for (int J = 0; J < 10; J++) {
    if (J + 2 < 10) { dw[J + 2] = lds64f(da + 32 * (J + 2)); if (FROM_X0) { xv[J + 2][0] = lds64f(xa + 32 * (J + 2)); xv[J + 2][1] = lds64f(xa + 2560 + 32 * (J + 2)); } }
#pragma unroll
    for (int x = 0; x < 8; x++) {
      const int h = (x >> 1) & 1;
      const uint32_t dwd = __float_as_uint(x < 4 ? dw[J].x : dw[J].y);
      const float tt = fmaf(rstd[h], (x & 1) ? bf_hi(dwd) : bf_lo(dwd), 1.f);
      float a = acc[8 * J + x];
      if (FROM_X0) { const uint32_t xw = __float_as_uint(x < 4 ? xv[J][h].x : xv[J][h].y); a = (x & 1) ? bf_hi(xw) : bf_lo(xw); }
      acc[8 * J + x] = FROM_X0 ? (a - mean[h]) * tt : fmaf(a, tt, -mean[h] * tt);
    }
  }
}

__global__ void __launch_bounds__(512, 1) fused_kernel(const __grid_constant__ Params p) {
  extern __shared__ __align__(1024) uint8_t smem_raw[];
  const int tid = threadIdx.x, lane = tid & 31;
  const int wid = __shfl_sync(0xffffffffu, tid >> 5, 0), wg = wid >> 2;
  unsigned smid; asm volatile("mov.u32 %0, %%smid;" : "=r"(smid));
  const int role = p.role[min(smid, 131u)];
  if (wid == 12) {
    const bool el = elect_one();
    if (el) {
      asm volatile("prefetch.tensormap [%0];" ::"l"(&p.mX) : "memory");
      asm volatile("prefetch.tensormap [%0];" ::"l"(&p.mB) : "memory");
#pragma unroll
      for (int k = 0; k < S1; k++) mbar_init(bars + 8 * (B_G1FULL + k), 1);
#pragma unroll
      for (int k = 0; k < 6; k++) mbar_init(bars + 8 * (B_XT + k), 1);
      asm volatile("fence.mbarrier_init.release.cluster;" ::: "memory");
    }
    if (role >= 0) {
      __syncwarp();
      asm volatile("bar.arrive 5, 288;" ::: "memory");
      const Role R = unpack_role(role);
      if (elect_one()) {
        TS(45);
#pragma unroll 1
        for (int k = 0; k < S1; k++) {
          const uint32_t fb = bars + 8 * (B_G1FULL + k);
          mbar_expect_tx(fb, G1_STAGE);
          tma4(sb + k * G1_STAGE + G1_XOFF, R.last ? &p.mXl : &p.mX, 64 * k, 0, 0, R.last ? 0 : 80 * R.T1, fb);
          tma5(sb + k * G1_STAGE, &p.mB, 64 * k, 0, 0, 4 * R.side, 2 * R.GP, fb);
        }
        if (R.has2) {
#pragma unroll 1
          for (int c = 0; c < KV0; c++) kv_issue(p, c, R.m2, R.dg);
          mbar_expect_tx(bars + 8 * B_XT, 20480);
#pragma unroll 1
          for (int h = 0; h < 2; h++) {
            const int ng = 8 * R.m2 + 4 * h, T = ng / 20;
            tma4(sb + XT_OFF + h * 10240, T == NT1 - 1 ? &p.mXtl : &p.mXt, 160 * R.dg, 0, 0, T == NT1 - 1 ? ng - 240 : ng + 60 * T, bars + 8 * B_XT);
          }
        }
        TS(44);
      }
      __syncwarp();
      bar_sync(6, 64);
    }
  }
  trap_if(smid >= 132 || smem_u32(smem_raw) != sb);
  if (role < 0) {
    if (wid == 0) {
      const unsigned tag = ld_rlx(g_epoch);
#pragma unroll 1
      for (int i = 0; i < NT1; i++) {
        uint32_t it = 0;
        while (!__all_sync(0xffffffffu, (int)(ld_rlx(&g_hflag[(i * 32 + min(lane, 9)) * 8]) - tag) >= 0)) { __nanosleep(500); trap_if(++it > SPIN_LIMIT); }
      }
    }
    return;
  }
  float mean0[2] = {0.f, 0.f}, rstd0[2] = {0.f, 0.f};
  if (wg == 2 || wid == 14) {
    ROLE(role)
    const int c = wid == 14 ? 4 : wid - 8;
    const unsigned tag = ld_rlx(g_epoch);
    if (has2) {
      uint2 bv[2][5];
#pragma unroll
      for (int x = 0; x < 2; x++)
#pragma unroll
        for (int i = 0; i < 5; i++) bv[x][i] = ldv64((const uint2*)((x ? p.bim : p.bre) + (cch0 + 32 * c) * DM) + lane + 32 * i);
      float sv[2];
#pragma unroll
      for (int x = 0; x < 2; x++) {
        float a = 0.f;
#pragma unroll
        for (int i = 0; i < 5; i++) a += (bf_lo(bv[x][i].x) + bf_hi(bv[x][i].x)) + (bf_lo(bv[x][i].y) + bf_hi(bv[x][i].y));
        sv[x] = a;
      }
#pragma unroll
      for (int o = 16; o > 0; o >>= 1) { sv[0] += __shfl_xor_sync(0xffffffffu, sv[0], o); sv[1] += __shfl_xor_sync(0xffffffffu, sv[1], o); }
      if (lane < 2) rec_st(&g_sB[(cch0 + 32 * c) * 2 + lane], sv[0], sv[1], tag);
      if (tid == 256) TS(47);
      __syncwarp();
      bar_sync(8, 192);
      mbar_wait(bars + 8 * B_EP);
      mbar_wait(bars + 8 * (B_KV + c));
#pragma unroll 1
      for (int y = 0; y < 2; y++) kv_tile(m2, dg, c, y);
      __syncwarp();
      if (lane == 0) mbar_arrive(bars + 8 * B_PREP);
      if (tid == 256) TS(48);
      if (tid == 352) TS(52);
      if (tid == 448) TS(51);
      if (wg == 2) {
        float xs[80];
        x0_load(xs);
        stats_publish<true>(0, 64 * m2 + 16 * c + (lane >> 2), dg, tag, xs);
        if (tid == 256) TS(31);
        mbar_wait(bars + 8 * B_PUB);
      } else {
        mbar_wait(bars + 8 * B_PREP);
        if (lane == 0) { st_rel(&g_kvflag[(dg * 32 + m2) * 8], tag); mbar_arrive(bars + 8 * B_PUB); TS(30); }
        __syncwarp();
      }
    } else bar_sync(8, 192);
    {
      const uint4* x0 = wg == 2 ? &g_stats[(lane & 3) * SEQ + (has2 ? 64 * m2 : 0) + 16 * c + (lane >> 2)] : &g_sB[(128 * GP + 32 * side + lane) * 2];
      float xa[2], xb[2];
      stat_table(T1, tag, 0, c, x0, x0 + (wg == 2 ? 8 : 128), xa, xb);
      if (wg == 2) stats_reduce(xa, xb, mean0, rstd0);
      else {
#pragma unroll
        for (int i = 0; i < 2; i++) sts64f(sb + CTAB_OFF + (32 * i + lane) * 24 + 16, p.swap ? xb[i] : xa[i], p.swap ? xa[i] : xb[i]);
      }
      mbar_arrive(bars + 8 * B_STAB);
      if (tid == 256) TS(26);
    }
  } else if (wid == 15) {
    ROLE(role)
    const int ch = 128 * GP + 32 * side + lane;
    uint32_t r0 = ldv16(p.lre + ch), r1 = ldv16(p.lim + ch), r2 = ldv16(p.logdt + ch);
    const uint32_t r3 = ldv16(p.lre + ch + 64), r4 = ldv16(p.lim + ch + 64), r5 = ldv16(p.logdt + ch + 64);
#pragma unroll 1
    for (int i = 0; i < 2; i++) {
      const float lr = bf_lo(r0), li = bf_lo(r1);
      const float dt = __bfloat162float(__float2bfloat16_rn(expf(bf_lo(r2))));
      const float mag = expf(dt * lr);
      float sn, cs; sincospif(dt * li * 0.31830988618379067f, &sn, &cs);
      const float ar = mag * cs, ai = mag * sn;
      const float inv = 2.f / (lr * lr + li * li);
      const uint32_t ad = sb + CTAB_OFF + (32 * i + lane) * 24;
      sts64f(ad, ar, ai);
      sts64f(ad + 8, ((ar - 1.f) * lr + ai * li) * inv, (ai * lr - (ar - 1.f) * li) * inv);
      r0 = r3; r1 = r4; r2 = r5;
    }
    if (lane == 0) TS(46);
    __syncwarp();
    bar_sync(7, 64);
    mbar_arrive(bars + 8 * B_CTAB);
  } else if (wid == 13) {
    ROLE(role)
    uint4 tv[3];
    const uint32_t e0 = ld_rlx(g_epoch);
    const uint32_t e1 = ldv16(p.ssmD + min(cch0 + 32 * lane, 639));
    const uint4 dv = ldv128((const uint4*)(p.dskip + 160 * dg) + min(lane, 19));
#pragma unroll
    for (int i = 0; i < 3; i++) tv[i] = ldv128((const uint4*)(p.shiftk + 640 * dg) + min(lane + 32 * i, 79));
    sts128(sb + DTAB_OFF + 16 * min(lane, 19), dv);
#pragma unroll
    for (int i = 0; i < 3; i++) sts128(sb + TAP_OFF + 16 * min(lane + 32 * i, 79), tv[i]);
    if (lane < 7) sts32(sb + EP_OFF + 4 * lane, lane < 5 ? e1 << 16 : (lane == 5 ? e0 : 0u));
    __syncwarp();
    bar_sync(9, 64);
    mbar_arrive(bars + 8 * B_CTAB);
    if (lane == 0) { mbar_arrive(bars + 8 * B_EP); TS(53); }
  } else if (wid != 12) {
    if (elect_one()) {
      if (wid < 7) {
        const int b0 = wid < 4 ? 4 + 20 * wid : 85 + 21 * (wid - 4), cnt = wid < 4 ? 2 : 1;
#pragma unroll
        for (int i = 0; i < 21; i++) mbar_init(bars + 8 * (b0 + i), cnt);
      } else {
#pragma unroll
        for (int i = 0; i < 12; i++) mbar_init(bars + 8 * (B_CVDONE + i), (i == 5 || i == 6) ? 160 : 128);
        mbar_init(bars + 8 * B_CTAB, 192); mbar_init(bars + 8 * B_PREP, 5);
      }
      asm volatile("fence.mbarrier_init.release.cluster;" ::: "memory");
    }
    __syncwarp();
    bar_sync(5, 288);
    if (wid == 2) asm volatile("bar.arrive 8, 192;\nbar.arrive 6, 64;\nbar.arrive 9, 64;\nbar.arrive 7, 64;" ::: "memory");
    if (tid == 128) TS(0);
    if (wg == 1) { cv_table(); mbar_arrive(bars + 8 * B_CTAB); }
  }

  if (wid == 12) {
    ROLE(role)
    uint32_t dst = sb;
#pragma unroll 1
    for (int k = S1; k < 10; k++) {
      const uint32_t fb = bars + 8 * (B_G1FULL + k);
      mbar_wait(bars + 8 * (B_G1DONE + k - S1));
      if (elect_one()) {
        mbar_expect_tx(fb, 20480);
        tma4(dst + G1_XOFF, last ? &p.mXl : &p.mX, 64 * k, 0, 0, last ? 0 : 80 * T1, fb);
        mbar_expect_tx(fb, 16384);
        tma5(dst, &p.mB, 64 * k, 0, 0, 4 * side, 2 * GP, fb);
      }
      dst += G1_STAGE; if (k == 2 * S1 - 1) dst = sb;
    }
  } else if (wid == 15 && (role >> 16)) {
    ROLE(role)
    mbar_wait(bars + 8 * B_PREP);
#pragma unroll
    for (int c = 0; c < 5; c++) {
      const uint32_t cb = sb + CV_OFF + c * CV_B;
      sts128(lane < 8 ? cb + 16 * lane : (lane < 20 ? cb + CV_U + 16 * (lane - 8) : cb + CV_U + CV_PL + 16 * (lane - 20)), make_uint4(0, 0, 0, 0));
    }
    fence_async_smem();
    __syncwarp();
    const unsigned tag = lds32(sb + EP_OFF + 20);
    mbar_wait(bars + 8 * B_PUB);
    if (elect_one()) {
#pragma unroll
      for (int c = 0; c < TAP0; c++) {
        mbar_expect_tx(bars + 8 * (B_CVFULL + c), 4096);
        bulk_g2s(sb + CV_OFF + c * CV_B + CV_K, p.ssmk + (cch0 + 32 * c) * SEQ, 4096, bars + 8 * (B_CVFULL + c));
      }
    }
    flag_poll(&g_kvflag[(dg * 32 + lane) * 8], tag);
    fence_async_global();
    if (elect_one()) {
      TS(28);
#pragma unroll 1
      for (int c = 0; c < 5; c++) {
        const uint32_t fb = bars + 8 * (B_CVFULL + c), cb = sb + CV_OFF + c * CV_B;
        mbar_expect_tx(fb, 4096);
        bulk_g2s(cb + CV_U + 192, g_kv + (cch0 + 32 * c) * 4096, 2048, fb);
        bulk_g2s(cb + CV_U + 192 + CV_PL, g_kv + (cch0 + 32 * c) * 4096 + 2048, 2048, fb);
        if (c >= TAP0) {
          mbar_expect_tx(fb, 4096);
          bulk_g2s(cb + CV_K, p.ssmk + (cch0 + 32 * c) * SEQ, 4096, fb);
        }
      }
      TS(54);
    }
    __syncwarp();
  }
  {
    const int w = wid & 3;
    if (wg == 2 && !(role >> 16)) {
      float xa[2], xb[2];
      mbar_wait(bars + 8 * (B_G1FULL + 11));
      stat_table(role & 15, lds32(sb + EP_OFF + 20), 1, w, g_stats, g_stats, xa, xb);
      mbar_arrive(bars + 8 * (B_STAB + 1));
    }
#pragma unroll 1
    for (int l = 0; l < 2; l++) {
      if (wg < 2) {
        float acc[80];
#pragma unroll
        for (int i = 0; i < 80; i++) acc[i] = 0.f;
        ROLE(role)
        const int tid = tid_opaque(), r = (tid & 31) >> 2, q = tid & 3;
        const int ch = 128 * GP + 64 * wg + 32 * side + 8 * w + r;
        const uint32_t ca = sb + CTAB_OFF + (32 * wg + 8 * w + r) * 24;
        float2 lam = make_float2(0.f, 0.f), p8 = lam, p16 = lam, pL = lam, p2L = lam;
        fence_regs(acc);
        {
          uint32_t alo = desc_lo(sb, 16) + wg * 512, blo = l == 0 ? desc_lo(sb + G1_XOFF, 16) : desc_lo(sb + G1_XOFF, 128);
          const uint32_t bhi = l == 0 ? desc_hi(1024, 1) : desc_hi(1024, 0), xstep = l == 0 ? 2 : 16;
          const uint32_t aend = desc_lo(sb, 16) + (S1 + l) * (G1_STAGE >> 4);
          uint32_t fb = bars + 8 * (B_G1FULL + 10 * l);
          mbar_wait(fb);
          if (tid == 0) TS(1 + 8 * l);
#pragma unroll 1
          for (int k = 0; k < 10; k++) {
            uint32_t ok; const uint32_t nb = k < 9 ? fb + 8 : fb;
            wgmma_fence();
#pragma unroll
            for (int kk = 0; kk < 4; kk++) {
              wgmma_n160<0>(acc, alo + kk * 2, desc_hi(1024, 1), blo + kk * xstep, bhi);
              if (kk == 0) ok = mbar_test(nb);
              if (kk == STG_KK && k == 9 && tid == 0) mbar_arrive(bars + 8 * (B_STG + l));
            }
            wgmma_commit();
            alo += G1_STAGE >> 4; blo += G1_STAGE >> 4;
            if (alo >= aend) { alo -= (S1 + l) * (G1_STAGE >> 4); blo -= (S1 + l) * (G1_STAGE >> 4); }
            wgmma_wait<1>();
            if (k > 0 && (tid & 127) == 0) mbar_arrive(fb + 8 * (B_G1DONE - B_G1FULL - 1));
            if (!ok) mbar_wait(nb);
            if (wg == 1 && k == 9 - STG_D - l) mbar_wait(bars + 8 * (B_STG + l));
            if (k == PAUSE_K) {
              mbar_wait(bars + 8 * B_CTAB);
              lam = lds64f(ca);
              if (p.swap) lam.y = -lam.y;
              const float2 p2 = cmul(lam, lam), p4 = cmul(p2, p2);
              p8 = cmul(p4, p4); p16 = cmul(p8, p8);
              pL = cmul(p16, p16);
              if (!last) pL = cmul(pL, p8);
              p2L = cmul(pL, pL);
              if (has2) mbar_wait(bars + 8 * B_PREP);
            }
            fb += 8;
          }
        }
        mbar_wait(bars + 8 * (B_STAB + l));
        const float2 sB = lds64f(ca + 16);
        const unsigned tag = lds32(sb + EP_OFF + 20);
        wgmma_wait<0>();
        fence_regs(acc);
        if ((tid & 127) == 0) { mbar_arrive(bars + 8 * (B_G1DONE + 10 * l + 9)); TS(wg ? 17 + l : 2 + 8 * l); }
        float2 ec[3];
#pragma unroll
        for (int jj = 0; jj < 8; jj++)
#pragma unroll
          for (int y = 0; y < 3; y++) {
            if (y == 2 && (jj & 1)) continue;
            const int j = y == 2 ? 16 + (jj >> 1) : 8 * y + jj;
            const float4 st = lds128f(sb + STAB_OFF + (8 * j + 2 * q) * 8);
            acc[4 * j + 0] = fmaf(acc[4 * j + 0], st.x, st.y * sB.x);
            acc[4 * j + 2] = fmaf(acc[4 * j + 2], st.x, st.y * sB.y);
            acc[4 * j + 1] = fmaf(acc[4 * j + 1], st.z, st.w * sB.x);
            acc[4 * j + 3] = fmaf(acc[4 * j + 3], st.z, st.w * sB.y);
            ec[y] = jj == 0 ? make_float2(acc[4 * j + 0], acc[4 * j + 2]) : cfma(lam, ec[y], make_float2(acc[4 * j + 0], acc[4 * j + 2]));
            ec[y] = cfma(lam, ec[y], make_float2(acc[4 * j + 1], acc[4 * j + 3]));
          }
        float2 e = cfma(p16, ec[0], ec[1]);
        if (!last) e = cfma(p8, e, ec[2]);
        {
          float2 v = make_float2(__shfl_up_sync(0xffffffffu, e.x, 1, 4), __shfl_up_sync(0xffffffffu, e.y, 1, 4));
          if (q >= 1) e = cfma(pL, v, e);
          v = make_float2(__shfl_up_sync(0xffffffffu, e.x, 2, 4), __shfl_up_sync(0xffffffffu, e.y, 2, 4));
          if (q >= 2) e = cfma(p2L, v, e);
        }
        if (!last && (q == 3 || (q == 2 && l == 0))) rec_st(&g_E[((q == 3 ? l : 1) * NT1 + T1) * DM + ch], e.x, e.y, q == 3 ? tag : tag - 1);
        if (tid == 0) TS(3 + 8 * l);
        float2 ex = make_float2(__shfl_up_sync(0xffffffffu, e.x, 1, 4), __shfl_up_sync(0xffffffffu, e.y, 1, 4));
        if (q == 0) ex = make_float2(0.f, 0.f);
        const float2 coef = lds64f(ca + 8), lamc = make_float2(lam.x, p.swap ? lam.y : -lam.y);
        float m00 = coef.x, m01 = -coef.y, m10 = -coef.y, m11 = -coef.x;
        if (p.swap) { m00 = -coef.y; m01 = coef.x; m10 = -coef.x; m11 = -coef.y; }
        float2 pLq, p160q, p640;
        {
          const float2 p80 = last ? cmul(p2L, p16) : p2L, p160 = cmul(p80, p80), p320 = cmul(p160, p160), one = make_float2(1.f, 0.f);
          p640 = cmul(p320, p320);
          pLq = cmul((q & 1) ? pL : one, (q & 2) ? p2L : one);
          p160q = cmul((q & 1) ? p160 : one, (q & 2) ? p320 : one);
        }
        float2 c, ev[3];
        unsigned tg[3];
        const uint4* ep = &g_E[(l * NT1 + T1 - 1 - q) * DM + ch];
#pragma unroll
        for (int j = 0; j < 20; j++) {
          if (j == CPOLL) {
#pragma unroll
            for (int i = 0; i < 3; i++) {
              ev[i] = make_float2(0.f, 0.f); tg[i] = tag;
              if (T1 - 1 - q - 4 * i >= 0) tg[i] = rec_ld(ep - 4 * i * DM, ev[i].x, ev[i].y);
            }
          }
#pragma unroll
          for (int x = 0; x < 2; x++) {
            const float b0 = acc[4 * j + x], b1 = acc[4 * j + 2 + x];
            acc[4 * j + x] = fmaf(b0, m00, b1 * m01);
            acc[4 * j + 2 + x] = fmaf(b0, m10, b1 * m11);
          }
          if (j == CPOLL - 1 || j == 19) asm volatile("" : "+f"(acc[4 * j]), "+f"(acc[4 * j + 1]), "+f"(acc[4 * j + 2]), "+f"(acc[4 * j + 3])::"memory");
        }
        {
          uint32_t it = 0;
          while (__any_sync(0xffffffffu, tg[0] != tag || tg[1] != tag || tg[2] != tag)) {
#pragma unroll
            for (int i = 0; i < 3; i++)
              if (tg[i] != tag) tg[i] = rec_ld(ep - 4 * i * DM, ev[i].x, ev[i].y);
            trap_if(++it > SPIN_LIMIT);
          }
          c = cfma(p640, cfma(p640, ev[2], ev[1]), ev[0]);
          c = cmul(c, p160q);
          c.x += __shfl_xor_sync(0xffffffffu, c.x, 1); c.y += __shfl_xor_sync(0xffffffffu, c.y, 1);
          c.x += __shfl_xor_sync(0xffffffffu, c.x, 2); c.y += __shfl_xor_sync(0xffffffffu, c.y, 2);
        }
        if (tid == 0) TS(4 + 8 * l);
        if (wg == 1 && l >= HOLD0) mbar_wait(bars + 8 * (B_REL + l));
        c = cfma(pLq, c, ex);
        float2 hh = make_float2(fmaf(c.x, m00, c.y * m01), fmaf(c.x, m10, c.y * m11));
        uint8_t* hb = g_h + (size_t)l * (32 * 20 * 8192) + (10 * wg + 2 * GP) * 8192 + (4 * side + w) * 1024 + (tid_opaque() & 31) * 4;
#pragma unroll
        for (int j4 = 0; j4 < 5; j4++) {
          const int ng = 20 * T1 + 4 * j4;
          uint8_t* hp = hb + (size_t)(ng >> 3) * 163840 + (ng & 7) * 128;
#pragma unroll
          for (int jj = 0; jj < 4; jj++) {
            const int j = 4 * j4 + jj;
            const float2 h0 = cfma(lamc, hh, make_float2(acc[4 * j + 0], acc[4 * j + 2]));
            hh = cfma(lamc, h0, make_float2(acc[4 * j + 1], acc[4 * j + 3]));
            if (j4 < 4 || !last) {
              *(uint32_t*)(hp + jj * 128) = pack_bf16(h0.x, hh.x);
              *(uint32_t*)(hp + jj * 128 + 8192) = pack_bf16(h0.y, hh.y);
            }
          }
        }
        mbar_arrive(bars + 8 * (B_HST + 2 * l + wg));
        if (tid == 0) TS(5 + 8 * l);
        if (tid == 128) TS(l ? 25 : 19);
      }
      if (l == 0) {
        ROLE(role)
        if (has2) {
          CvCtx cc;
          mbar_wait(bars + 8 * B_CTAB);
          cv_setup(cc);
          mbar_wait(bars + 8 * (B_G1DONE + 9));
#pragma unroll 1
          for (int c = (wg + 2) & 3; c < 5; c += 4) conv_channel(c, cc);
          if ((tid & 127) == 0) TS(wg == 2 ? 32 : (wg == 3 ? 50 : 7 + wg));
        }
      }
      if (wg >= 2) break;
    }
    if (wg == 3) {
    ROLE(role)
    const int pw = wid & 3;
    mbar_wait(bars + 8 * B_EP);
    const unsigned tag = lds32(sb + EP_OFF + 20);
    if (pw == 0) {
      if (elect_one()) {
#pragma unroll 1
        for (int l = 0; l < 2; l++) {
          uint32_t dst = sb;
          if (l == 1) {
            const uint32_t free0 = bars + 8 * (has2 ? B_G2DONE + 19 : B_G1DONE + 9);
#pragma unroll 1
            for (int k = 0; k < 10; k++) {
              mbar_wait(k > S1 ? bars + 8 * (B_G1DONE + 9 - S1 + k) : (k < WPF1 || !has2 ? free0 : bars + 8 * B_GO));
              mbar_expect_tx(bars + 8 * (B_G1FULL + 10 + k), 16384);
              tma5(dst, &p.mB, 64 * k, 0, 0, 4 * side, 2 * GP, bars + 8 * (B_G1FULL + 10 + k));
              dst += G1_STAGE; if (k == S1) dst = sb;
            }
          }
          if (has2) {
            const uint32_t fb2 = bars + 8 * (B_G2FULL + 20 * l), wb2 = bars + 8 * (B_G2DONE + 19 * l - 6);
            dst = sb + G2_WOFF;
            int kc = 0;
#pragma unroll 1
            for (int k = 0; k < 20; k++) {
              mbar_wait(k >= 6 + l ? wb2 + 8 * k : (k == 5 ? bars + 8 * B_XFREE : bars + 8 * (B_G1DONE + 10 * l + 9)));
              mbar_expect_tx(fb2 + 8 * k, G2_WB);
              tma5(dst, &p.mCre + (k & 1), kc, 0, 0, 0, 10 * dg, fb2 + 8 * k);
              kc += (k & 1) << 7; if (k == 9) kc = 64;
              dst += G2_WB; if (dst == sb + G2_WOFF + (6 + l) * G2_WB) dst = sb + G2_WOFF;
            }
          }
        }
      }
    } else if (pw == 1) {
#pragma unroll 1
      for (int l = 0; l < 2; l++) {
        if (l == 1) {
          mbar_wait(bars + 8 * (has2 ? B_G2DONE + 19 : B_G1DONE + 9));
          const int mlo = (160 * T1) >> 6, nf = last ? 8 : 12;
          flag_poll(&g_uflag[(4 * mlo + min(lane, nf - 1)) * 8], tag);
          fence_async_global();
          if (elect_one()) {
            TS(20);
            const int bytes = last ? 16384 : 20480;
            const uint8_t* src = g_u + T1 * 204800;
            uint32_t dst = sb + G1_XOFF;
#pragma unroll 1
            for (int k = 0; k < 10; k++) {
              if (k > S1) mbar_wait(bars + 8 * (B_G1DONE + 9 - S1 + k));
              mbar_expect_tx(bars + 8 * (B_G1FULL + 10 + k), bytes);
              bulk_g2s(dst, src, bytes, bars + 8 * (B_G1FULL + 10 + k));
              src += 20480; dst += G1_STAGE; if (k == S1) dst = sb + G1_XOFF;
            }
          }
          __syncwarp();
        }
        if (has2) {
          mbar_wait(bars + 8 * (B_HST + 2 * l));
          mbar_wait(bars + 8 * (B_G1DONE + 10 * l + 9));
          const int Tlo = (64 * m2) / 160, Thi = (64 * m2 + 63) / 160;
          flag_poll(&g_hflag[(((l * NT1 + (lane < 16 ? Tlo : Thi)) * 2) * 16 + min(lane & 15, 9)) * 8], tag);
          fence_async_global();
          if (elect_one()) {
            TS(21 + 2 * l);
            const uint32_t fb2 = bars + 8 * (B_G2FULL + 20 * l), wb2 = bars + 8 * (B_G2DONE + 18 * l - SX2);
            const uint8_t* src = g_h + (l * 32 + m2) * 163840;
            uint32_t dst = sb;
#pragma unroll 1
            for (int k = 0; k < 20; k++) {
              if (k >= SX2 + 2 * l) mbar_wait(wb2 + 8 * k);
              if (k == 10) { mbar_wait(bars + 8 * (B_H1 + l)); fence_async_global(); }
              mbar_expect_tx(fb2 + 8 * k, G2_XB);
              bulk_g2s(dst, src, G2_XB, fb2 + 8 * k);
              src += 8192; dst += G2_XB; if (dst == sb + (SX2 + 2 * l) * G2_XB) dst = sb;
            }
          }
          __syncwarp();
        }
      }
    } else if (pw == 2) {
#pragma unroll 1
      for (int l = 0; l < 2; l++) {
        if (l == 1) {
          float xa[2], xb[2];
          mbar_wait(bars + 8 * (B_G1FULL + 11));
          stat_table(T1, tag, 1, 4, g_stats, g_stats, xa, xb);
          mbar_arrive(bars + 8 * (B_STAB + 1));
        }
#pragma unroll 1
        for (int w = 0; w < 2; w++) {
          mbar_wait(bars + 8 * (B_HST + 2 * l + w));
          if (lane == 0) { st_rel(&g_hflag[(((l * NT1 + T1) * 2 + w) * 16 + 2 * GP + side) * 8], tag); if (w == 0) mbar_arrive(bars + 8 * (B_REL + l)); TS(w ? 15 + l : 6 + 8 * l); }
          __syncwarp();
        }
        if (l == 0 && has2 && elect_one()) {
#pragma unroll 1
          for (int c = 0; c < 5; c++) {
            mbar_wait(bars + 8 * (B_CVDONE + c));
            bulk_s2g(g_G + (cch0 + 32 * c) * 4096, cv_stage(c), 4096);
          }
          asm volatile("cp.async.bulk.commit_group;" ::: "memory");
          asm volatile("cp.async.bulk.wait_group 0;" ::: "memory");
          fence_async_global();
          st_rel(&g_gflag[(dg * 32 + m2) * 8], tag);
          mbar_arrive(bars + 8 * (B_GO + 1));
        }
        __syncwarp();
      }
    } else if (has2) {
      if (elect_one()) {
        l2_prefetch(p.cre + (160 * dg + 5 * m2) * DM, 6400); l2_prefetch(p.cim + (160 * dg + 5 * m2) * DM, 6400);
        asm volatile("prefetch.tensormap [%0];" ::"l"(&p.mG) : "memory");
      }
      const unsigned* hf = &g_hflag[(((lane < 16 ? (64 * m2) / 160 : (64 * m2 + 63) / 160) * 2 + 1) * 16 + min(lane & 15, 9)) * 8];
      mbar_wait(bars + 8 * (B_HST + 1));
      flag_poll(hf, tag);
      if (lane == 0) { mbar_arrive(bars + 8 * B_H1); TS(22); }
      mbar_wait(bars + 8 * (B_GO + 1));
      flag_poll(&g_gflag[(dg * 32 + lane) * 8], tag);
      fence_async_global();
      if (elect_one()) {
        TS(29);
        mbar_expect_tx(bars + 8 * B_GFULL, 20480);
        tma5(sb + G_OFF, &p.mG, 64 * m2, 0, 0, 0, 10 * dg, bars + 8 * B_GFULL);
      }
      mbar_wait(bars + 8 * (B_HST + 3));
      flag_poll(hf + NT1 * 256, tag);
      if (lane == 0) { mbar_arrive(bars + 8 * (B_H1 + 1)); TS(24); }
    }
    } else if (wg == 2 && (role >> 16)) {
      float acc[80];
      float off[2] = {mean0[0], mean0[1]};
      const unsigned tag = lds32(sb + EP_OFF + 20);
      dskip_init<true>(acc, mean0, rstd0);
      mbar_arrive(bars + 8 * B_XFREE);
#pragma unroll 1
      for (int l = 0; l < 2; l++) {
        float mean[2], rstd[2];
        {
          const uint32_t aend = desc_lo(sb + SX2 * G2_XB, 1024) + l * (G2_XB >> 3), bend = desc_lo(sb + G2_WOFF + 6 * G2_WB, 16) + l * (G2_WB >> 4);
          uint32_t alo = desc_lo(sb, 1024), blo = desc_lo(sb + G2_WOFF, 16);
          uint32_t fb = bars + 8 * (B_G2FULL + 20 * l);
          fence_regs(acc);
          mbar_wait(fb);
          if (tid == 256) TS(33 + 6 * l);
#pragma unroll 1
          for (int k = 0; k < 20; k++) {
            if (l == 1 && (k & 3) == 3 && tid == 256) TS(56 + (k >> 2));
            uint32_t ok; const uint32_t nb = k < 19 ? fb + 8 : fb;
            wgmma_fence();
#pragma unroll
            for (int kk = 0; kk < 4; kk++) {
              wgmma_n160<1>(acc, alo + kk * 128, desc_hi(128, 0), blo + kk * 2, desc_hi(1024, 1));
              if (kk == 0) ok = mbar_test(nb);
            }
            wgmma_commit();
            alo += G2_XB >> 4; if (alo == aend) alo = desc_lo(sb, 1024);
            blo += G2_WB >> 4; if (blo == bend) blo = desc_lo(sb + G2_WOFF, 16);
            wgmma_wait<1>();
            if (k > 0 && tid == 256) mbar_arrive(fb + 8 * (B_G2DONE - B_G2FULL - 1));
            if (!ok) mbar_wait(nb);
            fb += 8;
          }
          wgmma_wait<0>();
          fence_regs(acc);
          if (tid == 256) TS(34 + 6 * l);
          if (tid == 256) mbar_arrive(bars + 8 * (B_G2DONE + 20 * l + 19));
        }
        ROLE(role)
        const int tq = tid_opaque() & 31, n0 = 64 * m2 + 16 * w + (tq >> 2);
        stats_publish<false>(2 * l + 1, n0, dg, tag, acc);
        uint32_t gf[10][4];
        mbar_wait(bars + 8 * B_GFULL);
        const uint32_t ga = sb + G_OFF + (8 * (tq >> 4) + (tq & 7)) * 128 + (((2 * w + ((tq >> 3) & 1)) ^ ((2 * m2) & 6) ^ (tq & 7)) << 4);
#pragma unroll
        for (int J = 0; J < 2; J++) ldsm4t(gf[J], ga + J * 2048);
        if (tid == 256) TS(35 + 6 * l);
        uint8_t* dst[2][2];
#pragma unroll
        for (int h = 0; h < 2; h++) {
          if (l == 0) {
            const int ng = 8 * m2 + 2 * w + h, T = ng / 20;
            uint8_t* ub = g_u + (T * 204800 + (ng - 20 * T) * 1024 + (tq & 2) * 64 + (tq & 28) * 4 + (tq & 1) * 8 + (5 * dg >> 1) * 20480);
            dst[h][1] = ub + ((dg & 1) ? 20480 - 512 : 0);
            dst[h][0] = ub + (dg & 1) * 512;
          } else {
            dst[h][0] = dst[h][1] = (uint8_t*)(p.out + (n_to_t(n0 + 8 * h) * DM + 160 * dg + 4 * (tq & 3)));
          }
        }
        stats_get(2 * l + 1, n0, tag, mean, rstd);
        if (tid == 256) TS(36 + 6 * l);
        off[0] += mean[0]; off[1] += mean[1];
        const float ov[2] = {l ? off[0] : 0.f, l ? off[1] : 0.f};
#pragma unroll
        for (int J = 0; J < 10; J++) {
          if (J + 2 < 10) ldsm4t(gf[J + 2 < 10 ? J + 2 : 0], ga + (J + 2) * 2048);
#pragma unroll
          for (int x = 0; x < 8; x++) {
            const int h = (x >> 1) & 1;
            const uint32_t gwd = gf[J][x >> 1];
            const float t = fmaf(rstd[h], (x & 1) ? bf_hi(gwd) : bf_lo(gwd), 1.f);
            acc[8 * J + x] = fmaf(acc[8 * J + x], t, fmaf(-mean[h], t, ov[h]));
          }
#pragma unroll
          for (int h = 0; h < 2; h++) {
            if (l == 0)
              *(uint2*)(dst[h][(J >> 1) & 1] + (J >> 2) * 20480 + (J & 3) * 256) =
                  make_uint2(pack_bf16(acc[8 * J + 2 * h], acc[8 * J + 2 * h + 1]), pack_bf16(acc[8 * J + 4 + 2 * h], acc[8 * J + 5 + 2 * h]));
            else
              *(float4*)(dst[h][0] + 64 * J) = make_float4(acc[8 * J + 2 * h], acc[8 * J + 2 * h + 1], acc[8 * J + 4 + 2 * h], acc[8 * J + 5 + 2 * h]);
          }
          __syncwarp();
        }
        if (l == 0) {
          bar_sync(3, 128);
          if (tid == 256) { TS(37); st_rel(&g_uflag[(4 * m2 + dg) * 8], tag); mbar_arrive(bars + 8 * B_GO); TS(38); }
          stats_publish<false>(2, n0, dg, tag, acc);
          mbar_wait(bars + 8 * (B_G1FULL + 11));
          float xa[2], xb[2];
          const uint4* x0 = &g_stats[(8 + (tq & 3)) * SEQ + n0];
          stat_table(T1, tag, 1, w, x0, x0 + 8, xa, xb);
          mbar_arrive(bars + 8 * (B_STAB + 1));
          if (tid == 256) TS(27);
          stats_reduce(xa, xb, mean, rstd);
          off[0] += mean[0]; off[1] += mean[1];
          mbar_wait(bars + 8 * (B_HST + 2));
          dskip_init<false>(acc, mean, rstd);
        } else {
          if (tid == 256) {
            TS(43);
            if (m2 == 31 && dg == 3) asm volatile("st.relaxed.gpu.global.u32 [%0], %1;" ::"l"(g_epoch), "r"(tag + 1) : "memory");
          }
        }
      }
    }
  }
}

typedef CUresult (*EncFn)(CUtensorMap*, CUtensorMapDataType, cuuint32_t, void*, const cuuint64_t*, const cuuint64_t*,
                          const cuuint32_t*, const cuuint32_t*, CUtensorMapInterleave, CUtensorMapSwizzle,
                          CUtensorMapL2promotion, CUtensorMapFloatOOBfill);

void encode(EncFn fn, CUtensorMap* m, const void* ptr, int rank, const cuuint64_t* dims, const cuuint64_t* strides, const cuuint32_t* box,
            CUtensorMapSwizzle swz = CU_TENSOR_MAP_SWIZZLE_128B) {
  cuuint32_t es[5] = {1, 1, 1, 1, 1};
  fn(m, CU_TENSOR_MAP_DATA_TYPE_BFLOAT16, rank, (void*)ptr, dims, strides, box, es, CU_TENSOR_MAP_INTERLEAVE_NONE,
     swz, (CUtensorMapL2promotion)(swz == CU_TENSOR_MAP_SWIZZLE_128B ? PROM_A : PROM_B), CU_TENSOR_MAP_FLOAT_OOB_FILL_NONE);
}

}

extern "C" void kernel_launch(void* const* d_in, const int* in_sizes, int n_in, void* d_out, int out_size) {
  (void)in_sizes; (void)n_in; (void)out_size;
  Params p;
  typedef const __nv_bfloat16* BP;
  p.x = (BP)d_in[0]; p.lre = (BP)d_in[1]; p.lim = (BP)d_in[2]; p.bre = (BP)d_in[3]; p.bim = (BP)d_in[4];
  p.cre = (BP)d_in[5]; p.cim = (BP)d_in[6]; p.logdt = (BP)d_in[7]; p.dskip = (BP)d_in[8];
  p.k = (BP)d_in[10]; p.v = (BP)d_in[11]; p.shiftk = (BP)d_in[12]; p.ssmk = (BP)d_in[13]; p.ssmD = (BP)d_in[14];
  p.out = (float*)d_out;
  for (int sm = 0; sm < 132; sm++) {
    const int tpc = sm >> 1, side = sm & 1;
    int gpc, gi;
    if (tpc < 32) { gpc = tpc & 7; gi = tpc >> 3; }
    else if (tpc < 60) { gpc = 1 + (tpc - 32) % 7; gi = 4 + (tpc - 32) / 7; }
    else if (tpc < 62) { gpc = tpc - 54; gi = 8; }
    else { gpc = 0; gi = tpc - 58; }
    const int pos = 8 * gpc + gi + (gpc == 7 ? 1 : 0);
    int T1, GP;
    if (pos < 52) { const int hh = pos / 26, x = pos - 26 * hh; T1 = x >> 1; GP = 2 * hh + (x & 1); }
    else { T1 = pos - 52; GP = 4; }
    const int m2 = 8 * (gpc >> 1) + gi, dg = 2 * (gpc & 1) + side;
    p.role[sm] = pos == 65 ? -1 : (T1 | (GP << 4) | (side << 7) | (m2 << 8) | (dg << 14) | ((gi < 8) << 16));
  }
  void* fnp = nullptr;
  cudaDriverEntryPointQueryResult qr;
  cudaGetDriverEntryPoint("cuTensorMapEncodeTiled", &fnp, cudaEnableDefault, &qr);
  EncFn fn = (EncFn)fnp;
  void* gG = nullptr;
  cudaGetSymbolAddress(&gG, g_G);
  const cuuint64_t RB = DM * 2;
  {
    p.swap = p.bim < p.bre;
    const char* lo = (const char*)(p.swap ? p.bim : p.bre); const char* hi = (const char*)(p.swap ? p.bre : p.bim);
    cuuint64_t dims[5] = {640, 8, 2, 8, 10}, st[4] = {RB, (cuuint64_t)(hi - lo), 8 * RB, 64 * RB}; cuuint32_t box[5] = {64, 8, 2, 4, 2};
    encode(fn, &p.mB, lo, 5, dims, st, box);
  }
  {
    cuuint64_t dims[5] = {640, 2, 4, 2, 40}, st[4] = {RB, 4 * RB, 2 * RB, 16 * RB}; cuuint32_t box[5] = {64, 2, 4, 2, 10};
    encode(fn, &p.mCre, p.cre, 5, dims, st, box); encode(fn, &p.mCim, p.cim, 5, dims, st, box);
    cuuint64_t dimg[5] = {2048, 2, 4, 2, 40}, stg[4] = {4096, 4 * 4096, 2 * 4096, 16 * 4096};
    encode(fn, &p.mG, gG, 5, dimg, stg, box);
  }
  {
    cuuint64_t dims[4] = {640, 2, 4, 900}, st[3] = {RB, 40 * RB, 2 * RB}; cuuint32_t box[4] = {64, 2, 4, 20};
    encode(fn, &p.mX, p.x, 4, dims, st, box);
    cuuint64_t diml[4] = {640, 2, 4, 16}, stl[3] = {RB, 32 * RB, 2 * RB};
    encode(fn, &p.mXl, p.x + (size_t)1920 * DM, 4, diml, stl, box);
    cuuint32_t boxt[4] = {160, 2, 4, 4};
    encode(fn, &p.mXt, p.x, 4, dims, st, boxt, CU_TENSOR_MAP_SWIZZLE_NONE);
    encode(fn, &p.mXtl, p.x + (size_t)1920 * DM, 4, diml, stl, boxt, CU_TENSOR_MAP_SWIZZLE_NONE);
    cuuint64_t dk[3] = {640, 2000, 4}, sk[2] = {RB, 16 * RB}; cuuint32_t bk[3] = {32, 19, 4}, bv[3] = {32, 17, 4};
    encode(fn, &p.mK, p.k, 3, dk, sk, bk, CU_TENSOR_MAP_SWIZZLE_NONE);
    encode(fn, &p.mV, p.v, 3, dk, sk, bv, CU_TENSOR_MAP_SWIZZLE_NONE);
  }
  cudaFuncSetAttribute(fused_kernel, cudaFuncAttributeMaxDynamicSharedMemorySize, SMEM_BYTES);
  cudaLaunchConfig_t cfg = {};
  cfg.gridDim = dim3(132); cfg.blockDim = dim3(512); cfg.dynamicSmemBytes = SMEM_BYTES; cfg.stream = cudaStreamPerThread;
  cudaLaunchKernelEx(&cfg, fused_kernel, p);
}
```

```cpp
#include <cuda_runtime.h>
#include <cuda.h>
#include <cuda_bf16.h>
#include <stdint.h>

namespace {

constexpr int SEQ = 2048, DM = 640;
constexpr int NT1 = 13;
#define EXP 0
#define WPF1 3
#define WPF2 7
#define CPOLL 10
#define KV0 5
#define TAP0 2
#define PROM_A 2
#define PROM_B 2
#define XFIRST 0
#define TAPLATE 1
#define STG_D 3
#define STG_KK 1
#define HOLD0 1
#define WREL 0
#define UREL 1
#define TSL 1
#define PAUSE_K 3
constexpr uint32_t SPIN_LIMIT = 1u << 22;

__device__ __align__(1024) uint8_t g_h[2 * 32 * 20 * 8192];
__device__ __align__(1024) uint8_t g_u[NT1 * 10 * 20480];
__device__ __align__(1024) uint8_t g_kv[DM * 4096];
__device__ __align__(1024) uint8_t g_G[DM * 4096];
__device__ __align__(128) uint4 g_E[2 * NT1 * DM];
__device__ __align__(128) uint4 g_stats[4 * 4 * SEQ];
__device__ __align__(128) uint4 g_sB[DM * 2];
__device__ __align__(128) unsigned g_hflag[2 * NT1 * 2 * 16 * 8];
__device__ __align__(128) unsigned g_uflag[32 * 4 * 8];
__device__ __align__(128) unsigned g_kvflag[4 * 32 * 8];
__device__ __align__(128) unsigned g_gflag[4 * 32 * 8];
__device__ __align__(128) unsigned g_epoch[32] = {1};
#define TS(i) do {} while (0)

struct Params {
  CUtensorMap mB, mCre, mCim, mX, mXl, mG, mK, mV, mXt, mXtl;
  const __nv_bfloat16 *x, *lre, *lim, *bre, *bim, *cre, *cim, *logdt, *dskip, *k, *v, *shiftk, *ssmk, *ssmD;
  float* out;
  int swap;
  int role[132];
};

constexpr uint32_t sb = 1024;
constexpr uint32_t G1_STAGE = 36864, G1_XOFF = 16384;
constexpr int S1 = 4;
constexpr uint32_t XT_OFF = 159744, KS_OFF = 180224, KV_PIECE = 9216;
constexpr uint32_t G2_XB = 8192, G2_WB = 20480, G2_WOFF = 57344, G_OFF = 200704;
constexpr int S2 = 7;
constexpr uint32_t CV_OFF = KS_OFF, CV_K = 128, CV_PL = 2240, CV_U = CV_K + 4096, CV_B = KV_PIECE;
constexpr uint32_t MISC = 226304;
constexpr uint32_t BAR_OFF = MISC;
constexpr int B_G1FULL = 0, B_G1DONE = 20, B_G2FULL = 40, B_CVFULL = 80  ,
              B_G2DONE = 85, B_GFULL = 125, B_EP = 126, B_H1 = 127  , B_STG = 134  , B_REL = 136  , B_SFREE = 138,
              B_GO = 139  , B_PUB = 147,
              B_CVDONE = 148  , B_STAB = 153  , B_XFREE = 155, B_HST = 156  ,
              B_CTAB = 160, B_PREP = 161, B_XT = 162, B_KV = 163  ;
constexpr uint32_t bars = sb + BAR_OFF;
constexpr uint32_t STAB_OFF = MISC + 1344;
constexpr uint32_t CTAB_OFF = STAB_OFF + 1280;
constexpr uint32_t DTAB_OFF = CTAB_OFF + 1536;
constexpr uint32_t EP_OFF = DTAB_OFF + 320;
constexpr uint32_t SO_OFF = EP_OFF + 32;
constexpr uint32_t TAP_OFF = 147456;
constexpr uint32_t SMEM_BYTES = 232448;
static_assert(SO_OFF + 1536 <= SMEM_BYTES, "smem");

__device__ __forceinline__ void trap_if(bool c) { asm volatile("{\n.reg .pred p;\nsetp.ne.u32 p, %0, 0;\n@p trap;\n}\n" ::"r"((uint32_t)c)); }
__device__ __forceinline__ uint32_t smem_u32(const void* p) { return (uint32_t)__cvta_generic_to_shared(p); }
__device__ __forceinline__ void mbar_init(uint32_t bar, int cnt) { asm volatile("mbarrier.init.shared::cta.b64 [%0], %1;" ::"r"(bar), "r"(cnt) : "memory"); }
__device__ __forceinline__ void mbar_expect_tx(uint32_t bar, int bytes) { asm volatile("mbarrier.arrive.expect_tx.shared::cta.b64 _, [%0], %1;" ::"r"(bar), "r"(bytes) : "memory"); }
__device__ __forceinline__ void mbar_arrive(uint32_t bar) { asm volatile("mbarrier.arrive.shared::cta.b64 _, [%0];" ::"r"(bar) : "memory"); }
__device__ __forceinline__ void mbar_wait(uint32_t bar) {
  asm volatile(
      "{\n.reg .pred p;\n.reg .u32 c;\nmov.u32 c, 0;\n"
      "W_%=:\nmbarrier.try_wait.parity.shared::cta.b64 p, [%0], 0;\n@p bra D_%=;\n"
      "add.u32 c, c, 1;\nsetp.lt.u32 p, c, %1;\n@p bra W_%=;\ntrap;\nD_%=:\n}\n" ::"r"(bar), "n"(SPIN_LIMIT) : "memory");
}
__device__ __forceinline__ uint32_t mbar_test(uint32_t bar) {
  uint32_t ok;
  asm volatile("{\n.reg .pred p;\nmbarrier.test_wait.parity.shared::cta.b64 p, [%1], 0;\nselp.u32 %0, 1, 0, p;\n}\n" : "=r"(ok) : "r"(bar) : "memory");
  return ok;
}
__device__ __forceinline__ void tma3(uint32_t dst, const CUtensorMap* m, int c0, int c1, int c2, uint32_t bar) {
  asm volatile("cp.async.bulk.tensor.3d.shared::cluster.global.mbarrier::complete_tx::bytes [%0], [%1, {%3,%4,%5}], [%2];"
               ::"r"(dst), "l"(m), "r"(bar), "r"(c0), "r"(c1), "r"(c2) : "memory");
}
__device__ __forceinline__ void tma4(uint32_t dst, const CUtensorMap* m, int c0, int c1, int c2, int c3, uint32_t bar) {
  asm volatile("cp.async.bulk.tensor.4d.shared::cluster.global.mbarrier::complete_tx::bytes [%0], [%1, {%3,%4,%5,%6}], [%2];"
               ::"r"(dst), "l"(m), "r"(bar), "r"(c0), "r"(c1), "r"(c2), "r"(c3) : "memory");
}
__device__ __forceinline__ void tma5(uint32_t dst, const CUtensorMap* m, int c0, int c1, int c2, int c3, int c4, uint32_t bar) {
  asm volatile("cp.async.bulk.tensor.5d.shared::cluster.global.mbarrier::complete_tx::bytes [%0], [%1, {%3,%4,%5,%6,%7}], [%2];"
               ::"r"(dst), "l"(m), "r"(bar), "r"(c0), "r"(c1), "r"(c2), "r"(c3), "r"(c4) : "memory");
}
__device__ __forceinline__ void bulk_g2s(uint32_t dst, const void* src, int bytes, uint32_t bar) {
  asm volatile("cp.async.bulk.shared::cluster.global.mbarrier::complete_tx::bytes [%0], [%1], %2, [%3];"
               ::"r"(dst), "l"(src), "r"(bytes), "r"(bar) : "memory");
}
__device__ __forceinline__ void bulk_s2g(void* dst, uint32_t src, int bytes) {
  asm volatile("cp.async.bulk.global.shared::cta.bulk_group [%0], [%1], %2;" ::"l"(dst), "r"(src), "r"(bytes) : "memory");
}
__device__ __forceinline__ void l2_prefetch(const void* src, int bytes) {
  asm volatile("cp.async.bulk.prefetch.L2.global [%0], %1;" ::"l"(src), "r"(bytes) : "memory");
}
__device__ __forceinline__ void wgmma_fence() { asm volatile("wgmma.fence.sync.aligned;" ::: "memory"); }
__device__ __forceinline__ void wgmma_commit() { asm volatile("wgmma.commit_group.sync.aligned;" ::: "memory"); }
template <int N> __device__ __forceinline__ void wgmma_wait() { asm volatile("wgmma.wait_group.sync.aligned %0;" ::"n"(N) : "memory"); }
__host__ __device__ constexpr uint32_t desc_lo(uint32_t addr, uint32_t lbo) { return ((addr & 0x3FFFF) >> 4) | ((lbo >> 4) << 16); }
__host__ __device__ constexpr uint32_t desc_hi(uint32_t sbo, uint32_t swz) { return (sbo >> 4) | (swz << 30); }
__device__ __forceinline__ void bar_sync(int id, int n) { asm volatile("bar.sync %0, %1;" ::"r"(id), "r"(n) : "memory"); }
__device__ __forceinline__ uint32_t lds32(uint32_t a) { uint32_t v; asm volatile("ld.shared.u32 %0, [%1];" : "=r"(v) : "r"(a) : "memory"); return v; }
__device__ __forceinline__ float2 lds64f(uint32_t a) { float2 v; asm volatile("ld.shared.v2.f32 {%0,%1}, [%2];" : "=f"(v.x), "=f"(v.y) : "r"(a) : "memory"); return v; }
__device__ __forceinline__ float4 lds128f(uint32_t a) { float4 v; asm volatile("ld.shared.v4.f32 {%0,%1,%2,%3}, [%4];" : "=f"(v.x), "=f"(v.y), "=f"(v.z), "=f"(v.w) : "r"(a) : "memory"); return v; }
__device__ __forceinline__ void ldsm4t(uint32_t (&r)[4], uint32_t a) {
  asm volatile("ldmatrix.sync.aligned.m8n8.x4.trans.shared.b16 {%0,%1,%2,%3}, [%4];" : "=r"(r[0]), "=r"(r[1]), "=r"(r[2]), "=r"(r[3]) : "r"(a) : "memory");
}
__device__ __forceinline__ uint4 ldv128(const void* a) { uint4 v; asm volatile("ld.global.nc.v4.u32 {%0,%1,%2,%3}, [%4];" : "=r"(v.x), "=r"(v.y), "=r"(v.z), "=r"(v.w) : "l"(a) : "memory"); return v; }
__device__ __forceinline__ uint2 ldv64(const void* a) { uint2 v; asm volatile("ld.global.nc.v2.u32 {%0,%1}, [%2];" : "=r"(v.x), "=r"(v.y) : "l"(a) : "memory"); return v; }
__device__ __forceinline__ uint32_t ldv16(const void* a) { uint32_t v; asm volatile("ld.global.nc.u16 %0, [%1];" : "=r"(v) : "l"(a) : "memory"); return v; }
__device__ __forceinline__ void sts128(uint32_t a, uint4 v) { asm volatile("st.shared.v4.u32 [%0], {%1,%2,%3,%4};" ::"r"(a), "r"(v.x), "r"(v.y), "r"(v.z), "r"(v.w) : "memory"); }
__device__ __forceinline__ void sts32(uint32_t a, uint32_t v) { asm volatile("st.shared.u32 [%0], %1;" ::"r"(a), "r"(v) : "memory"); }
__device__ __forceinline__ void sts64f(uint32_t a, float x, float y) { asm volatile("st.shared.v2.f32 [%0], {%1,%2};" ::"r"(a), "f"(x), "f"(y) : "memory"); }
__device__ __forceinline__ void st_rel(unsigned* p, unsigned v) { asm volatile("st.release.gpu.global.u32 [%0], %1;" ::"l"(p), "r"(v) : "memory"); }
__device__ __forceinline__ void fence_async_global() { asm volatile("fence.proxy.async.global;" ::: "memory"); }
__device__ __forceinline__ void fence_async_smem() { asm volatile("fence.proxy.async.shared::cta;" ::: "memory"); }
__device__ __forceinline__ void rec_st(uint4* p, float a, float b, unsigned tag) {
  asm volatile("{\n.reg .b128 t;\n.reg .b64 lo, hi;\nmov.b64 lo, {%1,%2};\nmov.b64 hi, {%3,%3};\nmov.b128 t, {lo,hi};\n"
               "st.relaxed.gpu.global.b128 [%0], t;\n}\n" ::"l"(p), "r"(__float_as_uint(a)), "r"(__float_as_uint(b)), "r"(tag) : "memory");
}
__device__ __forceinline__ unsigned rec_ld(const uint4* p, float& a, float& b) {
  unsigned x, y, t;
  asm volatile("{\n.reg .b128 t;\n.reg .b64 lo, hi;\n.reg .b32 u;\nld.relaxed.gpu.global.b128 t, [%3];\nmov.b128 {lo,hi}, t;\n"
               "mov.b64 {%0,%1}, lo;\nmov.b64 {%2,u}, hi;\n}\n" : "=r"(x), "=r"(y), "=r"(t) : "l"(p) : "memory");
  a = __uint_as_float(x); b = __uint_as_float(y);
  return t;
}
__device__ __forceinline__ unsigned ld_rlx(const unsigned* p) { unsigned v; asm volatile("ld.relaxed.gpu.global.u32 %0, [%1];" : "=r"(v) : "l"(p) : "memory"); return v; }
__device__ __forceinline__ void flag_poll(const unsigned* p, unsigned target) {
  uint32_t it = 0;
  while (!__all_sync(0xffffffffu, (int)(ld_rlx(p) - target) >= 0)) { trap_if(++it > SPIN_LIMIT); }
  asm volatile("fence.acquire.gpu;" ::: "memory");
}
__device__ __forceinline__ uint32_t pack_bf16(float lo, float hi) {
  uint32_t r; asm("cvt.rn.bf16x2.f32 %0, %1, %2;" : "=r"(r) : "f"(hi), "f"(lo)); return r;
}
__device__ __forceinline__ float bf_lo(uint32_t w) { return __uint_as_float(w << 16); }
__device__ __forceinline__ float bf_hi(uint32_t w) { return __uint_as_float(w & 0xffff0000u); }
__device__ __forceinline__ uint32_t hmul2(uint32_t a, uint32_t b) {
  __nv_bfloat162 r = __hmul2_rn(*(__nv_bfloat162*)&a, *(__nv_bfloat162*)&b); return *(uint32_t*)&r;
}
__device__ __forceinline__ uint32_t hadd2(uint32_t a, uint32_t b) {
  __nv_bfloat162 r = __hadd2_rn(*(__nv_bfloat162*)&a, *(__nv_bfloat162*)&b); return *(uint32_t*)&r;
}
__device__ __forceinline__ float2 cmul(float2 a, float2 b) { return make_float2(a.x * b.x - a.y * b.y, a.x * b.y + a.y * b.x); }
__device__ __forceinline__ float2 cfma(float2 a, float2 b, float2 c) {
  return make_float2(fmaf(a.x, b.x, fmaf(-a.y, b.y, c.x)), fmaf(a.x, b.y, fmaf(a.y, b.x, c.y)));
}
template <int N> __device__ __forceinline__ void fence_regs(float (&a)[N]) {
#pragma unroll
  for (int i = 0; i < N; i++) asm volatile("" : "+f"(a[i])::"memory");
}
__device__ __forceinline__ bool elect_one() {
  uint32_t e; asm volatile("{\n.reg .pred P;\nelect.sync _|P, 0xffffffff;\nselp.u32 %0, 1, 0, P;\n}\n" : "=r"(e)); return e != 0;
}
__device__ __forceinline__ int tid_opaque() { int t; asm volatile("mov.u32 %0, %%tid.x;" : "=r"(t)); return t; }
struct Role { int T1, GP, side, m2, dg, cch0; bool last, has2; };
__device__ __forceinline__ Role unpack_role(int x) {
  Role r; r.T1 = x & 15; r.GP = (x >> 4) & 7; r.side = (x >> 7) & 1; r.m2 = (x >> 8) & 63; r.dg = (x >> 14) & 3;
  r.has2 = (x >> 16) & 1; r.last = r.T1 == NT1 - 1; r.cch0 = 160 * r.dg + r.m2; return r;
}
__device__ __forceinline__ Role fresh_role(int x) { asm volatile("" : "+r"(x)); return unpack_role(__shfl_sync(0xffffffffu, x, 0)); }
#define ROLE(x) const Role R_ = fresh_role(x); const int T1 = R_.T1, GP = R_.GP, side = R_.side, m2 = R_.m2, dg = R_.dg, cch0 = R_.cch0; \
  const bool last = R_.last, has2 = R_.has2; (void)T1; (void)GP; (void)side; (void)m2; (void)dg; (void)cch0; (void)last; (void)has2;
__device__ __forceinline__ int n_to_t(int n) {
  int T = n / 160, nl = n - T * 160;
  int L = (T == NT1 - 1) ? 32 : 40;
  return T * 160 + L * ((nl & 7) >> 1) + 2 * (nl >> 3) + (nl & 1);
}

template<int TA> __device__ __forceinline__ void wgmma_n160(float (&d)[80], uint32_t alo, uint32_t ahi, uint32_t blo, uint32_t bhi){
  asm volatile("{\n.reg .b64 da, db;\nmov.b64 da, {%80,%81};\nmov.b64 db, {%82,%83};\n"
    "wgmma.mma_async.sync.aligned.m64n160k16.f32.bf16.bf16 {%0, %1, %2, %3, %4, %5, %6, %7, %8, %9, %10, %11, %12, %13, %14, %15, %16, %17, %18, %19, %20, %21, %22, %23, %24, %25, %26, %27, %28, %29, %30, %31, %32, %33, %34, %35, %36, %37, %38, %39, %40, %41, %42, %43, %44, %45, %46, %47, %48, %49, %50, %51, %52, %53, %54, %55, %56, %57, %58, %59, %60, %61, %62, %63, %64, %65, %66, %67, %68, %69, %70, %71, %72, %73, %74, %75, %76, %77, %78, %79}, da, db, 1, 1, 1, %84, 0;\n}\n"
    : "+f"(d[0]), "+f"(d[1]), "+f"(d[2]), "+f"(d[3]), "+f"(d[4]), "+f"(d[5]), "+f"(d[6]), "+f"(d[7]), "+f"(d[8]), "+f"(d[9]), "+f"(d[10]), "+f"(d[11]), "+f"(d[12]), "+f"(d[13]), "+f"(d[14]), "+f"(d[15]), "+f"(d[16]), "+f"(d[17]), "+f"(d[18]), "+f"(d[19]), "+f"(d[20]), "+f"(d[21]), "+f"(d[22]), "+f"(d[23]), "+f"(d[24]), "+f"(d[25]), "+f"(d[26]), "+f"(d[27]), "+f"(d[28]), "+f"(d[29]), "+f"(d[30]), "+f"(d[31]), "+f"(d[32]), "+f"(d[33]), "+f"(d[34]), "+f"(d[35]), "+f"(d[36]), "+f"(d[37]), "+f"(d[38]), "+f"(d[39]), "+f"(d[40]), "+f"(d[41]), "+f"(d[42]), "+f"(d[43]), "+f"(d[44]), "+f"(d[45]), "+f"(d[46]), "+f"(d[47]), "+f"(d[48]), "+f"(d[49]), "+f"(d[50]), "+f"(d[51]), "+f"(d[52]), "+f"(d[53]), "+f"(d[54]), "+f"(d[55]), "+f"(d[56]), "+f"(d[57]), "+f"(d[58]), "+f"(d[59]), "+f"(d[60]), "+f"(d[61]), "+f"(d[62]), "+f"(d[63]), "+f"(d[64]), "+f"(d[65]), "+f"(d[66]), "+f"(d[67]), "+f"(d[68]), "+f"(d[69]), "+f"(d[70]), "+f"(d[71]), "+f"(d[72]), "+f"(d[73]), "+f"(d[74]), "+f"(d[75]), "+f"(d[76]), "+f"(d[77]), "+f"(d[78]), "+f"(d[79])
    : "r"(alo), "r"(ahi), "r"(blo), "r"(bhi), "n"(TA));
}
template<int N> __device__ __forceinline__ void wgmma_rs_hi(float (&d)[64], uint32_t a0, uint32_t a1, uint32_t a2, uint32_t a3, uint32_t blo);
template<> __device__ __forceinline__ void wgmma_rs_hi<16>(float (&d)[64], uint32_t a0, uint32_t a1, uint32_t a2, uint32_t a3, uint32_t blo){
  asm volatile("{\n.reg .b64 db;\nmov.b64 db, {%12,8};\nwgmma.mma_async.sync.aligned.m64n16k16.f32.bf16.bf16 {%0, %1, %2, %3, %4, %5, %6, %7}, {%8,%9,%10,%11}, db, 1, 1, 1, 0;\n}\n"
    : "+f"(d[56]), "+f"(d[57]), "+f"(d[58]), "+f"(d[59]), "+f"(d[60]), "+f"(d[61]), "+f"(d[62]), "+f"(d[63])
    : "r"(a0), "r"(a1), "r"(a2), "r"(a3), "r"(blo));
}
template<> __device__ __forceinline__ void wgmma_rs_hi<32>(float (&d)[64], uint32_t a0, uint32_t a1, uint32_t a2, uint32_t a3, uint32_t blo){
  asm volatile("{\n.reg .b64 db;\nmov.b64 db, {%20,8};\nwgmma.mma_async.sync.aligned.m64n32k16.f32.bf16.bf16 {%0, %1, %2, %3, %4, %5, %6, %7, %8, %9, %10, %11, %12, %13, %14, %15}, {%16,%17,%18,%19}, db, 1, 1, 1, 0;\n}\n"
    : "+f"(d[48]), "+f"(d[49]), "+f"(d[50]), "+f"(d[51]), "+f"(d[52]), "+f"(d[53]), "+f"(d[54]), "+f"(d[55]), "+f"(d[56]), "+f"(d[57]), "+f"(d[58]), "+f"(d[59]), "+f"(d[60]), "+f"(d[61]), "+f"(d[62]), "+f"(d[63])
    : "r"(a0), "r"(a1), "r"(a2), "r"(a3), "r"(blo));
}
template<> __device__ __forceinline__ void wgmma_rs_hi<48>(float (&d)[64], uint32_t a0, uint32_t a1, uint32_t a2, uint32_t a3, uint32_t blo){
  asm volatile("{\n.reg .b64 db;\nmov.b64 db, {%28,8};\nwgmma.mma_async.sync.aligned.m64n48k16.f32.bf16.bf16 {%0, %1, %2, %3, %4, %5, %6, %7, %8, %9, %10, %11, %12, %13, %14, %15, %16, %17, %18, %19, %20, %21, %22, %23}, {%24,%25,%26,%27}, db, 1, 1, 1, 0;\n}\n"
    : "+f"(d[40]), "+f"(d[41]), "+f"(d[42]), "+f"(d[43]), "+f"(d[44]), "+f"(d[45]), "+f"(d[46]), "+f"(d[47]), "+f"(d[48]), "+f"(d[49]), "+f"(d[50]), "+f"(d[51]), "+f"(d[52]), "+f"(d[53]), "+f"(d[54]), "+f"(d[55]), "+f"(d[56]), "+f"(d[57]), "+f"(d[58]), "+f"(d[59]), "+f"(d[60]), "+f"(d[61]), "+f"(d[62]), "+f"(d[63])
    : "r"(a0), "r"(a1), "r"(a2), "r"(a3), "r"(blo));
}
template<> __device__ __forceinline__ void wgmma_rs_hi<64>(float (&d)[64], uint32_t a0, uint32_t a1, uint32_t a2, uint32_t a3, uint32_t blo){
  asm volatile("{\n.reg .b64 db;\nmov.b64 db, {%36,8};\nwgmma.mma_async.sync.aligned.m64n64k16.f32.bf16.bf16 {%0, %1, %2, %3, %4, %5, %6, %7, %8, %9, %10, %11, %12, %13, %14, %15, %16, %17, %18, %19, %20, %21, %22, %23, %24, %25, %26, %27, %28, %29, %30, %31}, {%32,%33,%34,%35}, db, 1, 1, 1, 0;\n}\n"
    : "+f"(d[32]), "+f"(d[33]), "+f"(d[34]), "+f"(d[35]), "+f"(d[36]), "+f"(d[37]), "+f"(d[38]), "+f"(d[39]), "+f"(d[40]), "+f"(d[41]), "+f"(d[42]), "+f"(d[43]), "+f"(d[44]), "+f"(d[45]), "+f"(d[46]), "+f"(d[47]), "+f"(d[48]), "+f"(d[49]), "+f"(d[50]), "+f"(d[51]), "+f"(d[52]), "+f"(d[53]), "+f"(d[54]), "+f"(d[55]), "+f"(d[56]), "+f"(d[57]), "+f"(d[58]), "+f"(d[59]), "+f"(d[60]), "+f"(d[61]), "+f"(d[62]), "+f"(d[63])
    : "r"(a0), "r"(a1), "r"(a2), "r"(a3), "r"(blo));
}
template<> __device__ __forceinline__ void wgmma_rs_hi<80>(float (&d)[64], uint32_t a0, uint32_t a1, uint32_t a2, uint32_t a3, uint32_t blo){
  asm volatile("{\n.reg .b64 db;\nmov.b64 db, {%44,8};\nwgmma.mma_async.sync.aligned.m64n80k16.f32.bf16.bf16 {%0, %1, %2, %3, %4, %5, %6, %7, %8, %9, %10, %11, %12, %13, %14, %15, %16, %17, %18, %19, %20, %21, %22, %23, %24, %25, %26, %27, %28, %29, %30, %31, %32, %33, %34, %35, %36, %37, %38, %39}, {%40,%41,%42,%43}, db, 1, 1, 1, 0;\n}\n"
    : "+f"(d[24]), "+f"(d[25]), "+f"(d[26]), "+f"(d[27]), "+f"(d[28]), "+f"(d[29]), "+f"(d[30]), "+f"(d[31]), "+f"(d[32]), "+f"(d[33]), "+f"(d[34]), "+f"(d[35]), "+f"(d[36]), "+f"(d[37]), "+f"(d[38]), "+f"(d[39]), "+f"(d[40]), "+f"(d[41]), "+f"(d[42]), "+f"(d[43]), "+f"(d[44]), "+f"(d[45]), "+f"(d[46]), "+f"(d[47]), "+f"(d[48]), "+f"(d[49]), "+f"(d[50]), "+f"(d[51]), "+f"(d[52]), "+f"(d[53]), "+f"(d[54]), "+f"(d[55]), "+f"(d[56]), "+f"(d[57]), "+f"(d[58]), "+f"(d[59]), "+f"(d[60]), "+f"(d[61]), "+f"(d[62]), "+f"(d[63])
    : "r"(a0), "r"(a1), "r"(a2), "r"(a3), "r"(blo));
}
template<> __device__ __forceinline__ void wgmma_rs_hi<96>(float (&d)[64], uint32_t a0, uint32_t a1, uint32_t a2, uint32_t a3, uint32_t blo){
  asm volatile("{\n.reg .b64 db;\nmov.b64 db, {%52,8};\nwgmma.mma_async.sync.aligned.m64n96k16.f32.bf16.bf16 {%0, %1, %2, %3, %4, %5, %6, %7, %8, %9, %10, %11, %12, %13, %14, %15, %16, %17, %18, %19, %20, %21, %22, %23, %24, %25, %26, %27, %28, %29, %30, %31, %32, %33, %34, %35, %36, %37, %38, %39, %40, %41, %42, %43, %44, %45, %46, %47}, {%48,%49,%50,%51}, db, 1, 1, 1, 0;\n}\n"
    : "+f"(d[16]), "+f"(d[17]), "+f"(d[18]), "+f"(d[19]), "+f"(d[20]), "+f"(d[21]), "+f"(d[22]), "+f"(d[23]), "+f"(d[24]), "+f"(d[25]), "+f"(d[26]), "+f"(d[27]), "+f"(d[28]), "+f"(d[29]), "+f"(d[30]), "+f"(d[31]), "+f"(d[32]), "+f"(d[33]), "+f"(d[34]), "+f"(d[35]), "+f"(d[36]), "+f"(d[37]), "+f"(d[38]), "+f"(d[39]), "+f"(d[40]), "+f"(d[41]), "+f"(d[42]), "+f"(d[43]), "+f"(d[44]), "+f"(d[45]), "+f"(d[46]), "+f"(d[47]), "+f"(d[48]), "+f"(d[49]), "+f"(d[50]), "+f"(d[51]), "+f"(d[52]), "+f"(d[53]), "+f"(d[54]), "+f"(d[55]), "+f"(d[56]), "+f"(d[57]), "+f"(d[58]), "+f"(d[59]), "+f"(d[60]), "+f"(d[61]), "+f"(d[62]), "+f"(d[63])
    : "r"(a0), "r"(a1), "r"(a2), "r"(a3), "r"(blo));
}
template<> __device__ __forceinline__ void wgmma_rs_hi<112>(float (&d)[64], uint32_t a0, uint32_t a1, uint32_t a2, uint32_t a3, uint32_t blo){
  asm volatile("{\n.reg .b64 db;\nmov.b64 db, {%60,8};\nwgmma.mma_async.sync.aligned.m64n112k16.f32.bf16.bf16 {%0, %1, %2, %3, %4, %5, %6, %7, %8, %9, %10, %11, %12, %13, %14, %15, %16, %17, %18, %19, %20, %21, %22, %23, %24, %25, %26, %27, %28, %29, %30, %31, %32, %33, %34, %35, %36, %37, %38, %39, %40, %41, %42, %43, %44, %45, %46, %47, %48, %49, %50, %51, %52, %53, %54, %55}, {%56,%57,%58,%59}, db, 1, 1, 1, 0;\n}\n"
    : "+f"(d[8]), "+f"(d[9]), "+f"(d[10]), "+f"(d[11]), "+f"(d[12]), "+f"(d[13]), "+f"(d[14]), "+f"(d[15]), "+f"(d[16]), "+f"(d[17]), "+f"(d[18]), "+f"(d[19]), "+f"(d[20]), "+f"(d[21]), "+f"(d[22]), "+f"(d[23]), "+f"(d[24]), "+f"(d[25]), "+f"(d[26]), "+f"(d[27]), "+f"(d[28]), "+f"(d[29]), "+f"(d[30]), "+f"(d[31]), "+f"(d[32]), "+f"(d[33]), "+f"(d[34]), "+f"(d[35]), "+f"(d[36]), "+f"(d[37]), "+f"(d[38]), "+f"(d[39]), "+f"(d[40]), "+f"(d[41]), "+f"(d[42]), "+f"(d[43]), "+f"(d[44]), "+f"(d[45]), "+f"(d[46]), "+f"(d[47]), "+f"(d[48]), "+f"(d[49]), "+f"(d[50]), "+f"(d[51]), "+f"(d[52]), "+f"(d[53]), "+f"(d[54]), "+f"(d[55]), "+f"(d[56]), "+f"(d[57]), "+f"(d[58]), "+f"(d[59]), "+f"(d[60]), "+f"(d[61]), "+f"(d[62]), "+f"(d[63])
    : "r"(a0), "r"(a1), "r"(a2), "r"(a3), "r"(blo));
}
template<> __device__ __forceinline__ void wgmma_rs_hi<128>(float (&d)[64], uint32_t a0, uint32_t a1, uint32_t a2, uint32_t a3, uint32_t blo){
  asm volatile("{\n.reg .b64 db;\nmov.b64 db, {%68,8};\nwgmma.mma_async.sync.aligned.m64n128k16.f32.bf16.bf16 {%0, %1, %2, %3, %4, %5, %6, %7, %8, %9, %10, %11, %12, %13, %14, %15, %16, %17, %18, %19, %20, %21, %22, %23, %24, %25, %26, %27, %28, %29, %30, %31, %32, %33, %34, %35, %36, %37, %38, %39, %40, %41, %42, %43, %44, %45, %46, %47, %48, %49, %50, %51, %52, %53, %54, %55, %56, %57, %58, %59, %60, %61, %62, %63}, {%64,%65,%66,%67}, db, 1, 1, 1, 0;\n}\n"
    : "+f"(d[0]), "+f"(d[1]), "+f"(d[2]), "+f"(d[3]), "+f"(d[4]), "+f"(d[5]), "+f"(d[6]), "+f"(d[7]), "+f"(d[8]), "+f"(d[9]), "+f"(d[10]), "+f"(d[11]), "+f"(d[12]), "+f"(d[13]), "+f"(d[14]), "+f"(d[15]), "+f"(d[16]), "+f"(d[17]), "+f"(d[18]), "+f"(d[19]), "+f"(d[20]), "+f"(d[21]), "+f"(d[22]), "+f"(d[23]), "+f"(d[24]), "+f"(d[25]), "+f"(d[26]), "+f"(d[27]), "+f"(d[28]), "+f"(d[29]), "+f"(d[30]), "+f"(d[31]), "+f"(d[32]), "+f"(d[33]), "+f"(d[34]), "+f"(d[35]), "+f"(d[36]), "+f"(d[37]), "+f"(d[38]), "+f"(d[39]), "+f"(d[40]), "+f"(d[41]), "+f"(d[42]), "+f"(d[43]), "+f"(d[44]), "+f"(d[45]), "+f"(d[46]), "+f"(d[47]), "+f"(d[48]), "+f"(d[49]), "+f"(d[50]), "+f"(d[51]), "+f"(d[52]), "+f"(d[53]), "+f"(d[54]), "+f"(d[55]), "+f"(d[56]), "+f"(d[57]), "+f"(d[58]), "+f"(d[59]), "+f"(d[60]), "+f"(d[61]), "+f"(d[62]), "+f"(d[63])
    : "r"(a0), "r"(a1), "r"(a2), "r"(a3), "r"(blo));
}

__device__ __forceinline__ float shfl_sel(float a, float b, bool p, int src) {
  float r;
  asm volatile("{\n.reg .pred P;\n.reg .f32 t;\nsetp.ne.u32 P, %3, 0;\nselp.f32 t, %1, %2, P;\nshfl.sync.idx.b32 %0, t, %4, 0x1f, 0xffffffff;\n}\n"
               : "=f"(r) : "f"(a), "f"(b), "r"((uint32_t)p), "r"(src));
  return r;
}
struct CvCtx {
  uint32_t koff, zero, so[3];
  int srcA, srcB;
  bool wrapA, s3, kodd;
};
struct CvPipe { float Ep[2], keep[2], send[2]; };
template <int LO> __device__ __forceinline__ void cv_copy(float (&acc)[64]) {
#pragma unroll
  for (int i = LO; i < 64; i++) { float t; asm volatile("mov.b32 %0, %1;" : "=f"(t) : "f"(acc[i]) : "memory"); acc[i] = t; }
}
template <int G> __device__ __forceinline__ void cv_raw(uint32_t (&A)[4][4], uint32_t kaddr) {
#pragma unroll
  for (int i = 0; i < 4; i++) {
    const uint32_t a = kaddr + (4 * G + i) * 128;
    A[i][0] = lds32(a); A[i][1] = lds32(a + 4); A[i][3] = lds32(a + 8);
  }
}
__device__ __forceinline__ void cv_form(uint32_t (&A)[4][4], uint32_t sel) {
#pragma unroll
  for (int i = 0; i < 4; i++) {
    asm volatile("prmt.b32 %0, %0, %1, %2;" : "+r"(A[i][0]) : "r"(A[i][1]), "r"(sel));
    asm volatile("prmt.b32 %0, %1, %2, %3;" : "=r"(A[i][2]) : "r"(A[i][1]), "r"(A[i][3]), "r"(sel));
  }
}
#define CVV 2
template <int G> __device__ __forceinline__ void cv_step(float (&acc)[64], uint32_t (&A)[4][4], CvPipe& s, const CvCtx& c, uint32_t cb, uint32_t stg) {
  constexpr int JA = G - 1, JB = G - 2, NH = CVV == 1 ? 4 : (CVV == 3 ? 2 : 1);
  const uint32_t db0 = desc_lo(cb + CV_U + 192, CV_PL);
  uint32_t B[4][4];
  float ra[4], rb[2];
  if constexpr (G < 8) {
    wgmma_fence();
#pragma unroll
    for (int i = 0; i < NH; i++) wgmma_rs_hi<128 - 16 * (G & 7)>(acc, A[i][0], A[i][1], A[i][2], A[i][3], db0 - 4 * i);
    wgmma_commit();
    __syncwarp();
  }
  if constexpr (JA >= 0 && JA < 8) {
#pragma unroll
    for (int x = 0; x < 4; x++) {
      const int i = 8 * JA + 4 * (x >> 1) + 2 * (x & 1) + 1;
      ra[x] = shfl_sel(i >= 4 ? acc[i >= 4 ? i - 4 : 0] : 0.f, acc[i], c.wrapA, c.srcA);
    }
  }
  if constexpr (JB >= 0) {
#pragma unroll
    for (int h = 0; h < 2; h++) rb[h] = __shfl_sync(0xffffffffu, s.send[h], c.srcB);
  }
  if constexpr (G < 7) cv_raw<G + 1>(B, cb + c.koff);
  uint32_t z = 0;
  if constexpr (G < 8 && NH < 4) {
    __syncwarp();
    wgmma_fence();
#pragma unroll
    for (int i = NH; i < 4; i++) wgmma_rs_hi<128 - 16 * (G & 7)>(acc, A[i][0], A[i][1], A[i][2], A[i][3], db0 - 4 * i);
    wgmma_commit();
    asm volatile("mov.u32 %0, %%clock;" : "=r"(z)::"memory");
    z &= c.zero;
  }
  const float one = __uint_as_float(0x3f800000u | z);
  if constexpr (G < 7) cv_form(B, 0x5432u | z);
  if constexpr (JB >= 0) sts32(stg + ((c.so[JB / 3] >> (10 * (JB % 3))) & 0xffc), pack_bf16(fmaf(rb[0], one, s.keep[0]), fmaf(rb[1], one, s.keep[1])));
  if constexpr (JA >= 0 && JA < 8) {
#pragma unroll
    for (int h = 0; h < 2; h++) {
      const float ev = fmaf(ra[h], one, acc[8 * JA + 2 * h]), od = fmaf(ra[2 + h], one, acc[8 * JA + 4 + 2 * h]);
      s.send[h] = c.kodd ? ev : (c.s3 ? s.Ep[h] : od);
      s.keep[h] = c.kodd ? od : ev;
      s.Ep[h] = od;
    }
  }
  if constexpr (G < 8) { __syncwarp(); wgmma_wait<0>(); cv_copy<8 * (G & 7)>(acc); }
  if constexpr (G < 9) cv_step<G + 1>(acc, B, s, c, cb, stg);
}
__device__ __forceinline__ uint32_t cv_stage(int slot) { return sb + (slot < 4 ? 40960 + slot * 4096 : CV_OFF + CV_K); }
__device__ __forceinline__ void cv_setup(CvCtx& c) {
  const int tid = tid_opaque() & 127, w = tid >> 5, lane = tid & 31, r = lane >> 2, q = lane & 3;
  const int i0 = (r >> 1) & 1, i1 = r >> 2;
  c.koff = CV_K - 32 + 4 * (8 * (r >> 1) + 2 * w + (r & 1) + 2 * q);
  c.srcA = i0 ? lane - 8 : lane + 8 - q + ((q + 3) & 3);
  c.wrapA = i0 && q == 3;
  c.srcB = i1 == 0 ? (lane - q + 16 + ((q + 3) & 3)) : (lane - q - 16 + ((q + 1) & 3));
  c.s3 = (i1 == 1 && q == 3); c.kodd = (i1 == 1 && q < 3);
  c.zero = lds32(sb + EP_OFF + 24);
#pragma unroll
  for (int i = 0; i < 3; i++) c.so[i] = lds32(sb + SO_OFF + 512 * i + 4 * tid);
}
__device__ __forceinline__ void cv_table() {
  const int tid = tid_opaque() & 127, r = (tid & 31) >> 2, q = tid & 3;
  int t = 16 * (2 * (r < 4 ? q : 4 + ((q + 1) & 3)) + ((r >> 1) & 1)) + 4 * (tid >> 5) + 2 * (r & 1);
#pragma unroll 1
  for (int i = 0; i < 3; i++) {
    uint32_t v = 0;
#pragma unroll 1
    for (int x = 0; x < 3; x++, t += 256) {
      const int T = t / 160, tl = t - T * 160;
      const int qq = (T >= NT1 - 1) ? (tl >> 5) : (tl / 40);
      int ck = 20 * T + ((tl - qq * ((T >= NT1 - 1) ? 32 : 40)) >> 1);
      ck ^= (ck >> 2) & 6;
      v |= (uint32_t)((ck * 4 + qq) & 1023) << (10 * x + 2);
    }
    sts32(sb + SO_OFF + 512 * i + 4 * tid, v);
  }
}
__device__ __forceinline__ void conv_channel(int slot, const CvCtx& c) {
  const uint32_t cb = sb + CV_OFF + slot * CV_B;
  float acc[64];
  CvPipe s;
  s.Ep[0] = s.Ep[1] = 0.f;
  uint32_t A[4][4];
#pragma unroll
  for (int i = 0; i < 64; i++) acc[i] = 0.f;
  if (slot == 4) mbar_wait(bars + 8 * B_CVDONE);
  mbar_wait(bars + 8 * (B_CVFULL + slot));
  cv_raw<0>(A, cb + c.koff);
  {
    const uint32_t w0 = lds32(cb + CV_K);
    const uint32_t wp = __byte_perm(pack_bf16(bf_lo(w0) + __uint_as_float(lds32(sb + EP_OFF + 4 * slot)), 0.f), w0, 0x7610);
    if (c.koff == CV_K) A[0][0] = wp;
    if (c.koff == CV_K - 4) A[0][1] = wp;
    if (c.koff == CV_K - 8) A[0][3] = wp;
  }
  cv_form(A, 0x5432u);
  cv_copy<0>(acc);
  cv_step<0>(acc, A, s, c, cb, cv_stage(slot));
  fence_async_smem();
  mbar_arrive(bars + 8 * (B_CVDONE + slot));
}

__device__ __forceinline__ void kv_issue(const Params& p, int c, int m2, int dg) {
  const uint32_t fb = bars + 8 * (B_KV + c);
  mbar_expect_tx(fb, KV_PIECE);
  tma3(sb + KS_OFF + c * KV_PIECE, &p.mK, 160 * dg + 32 * c, 64 * m2 - 3, 0, fb);
  tma3(sb + KS_OFF + c * KV_PIECE + 4864, &p.mV, 160 * dg + 32 * c, 64 * m2 - 1, 0, fb);
}
__device__ __forceinline__ void kv_tile(int m, int dg, int c, int y) {
  const int lane = tid_opaque() & 31, tg = lane >> 3;
  const uint32_t pb = sb + KS_OFF + c * KV_PIECE + 32 * y + 4 * (lane & 7);
  const uint32_t ka = pb + tg * 1216, va = pb + 4864 + tg * 1088 + 64;
  const uint32_t kh = (m == 0 && tg > 0) ? ka - 192 : ka;
  uint32_t kk[19], u[16];
  const float4 t = lds128f(sb + TAP_OFF + 256 * c + 128 * y + 16 * (lane & 7));
#pragma unroll
  for (int i = 0; i < 19; i++) { kk[i] = lds32((i < 3 ? kh : ka) + i * 64); if (i >= 3) u[i - 3] = lds32(va + (i - 3) * 64); }
  uint8_t* dst = g_kv + ((160 * dg + 32 * c + 16 * y + 2 * (lane & 7)) * 4096 + (4 * m + tg) * 16);
  const uint32_t w0 = __byte_perm(__float_as_uint(t.x), __float_as_uint(t.z), 0x5410), w1 = __byte_perm(__float_as_uint(t.x), __float_as_uint(t.z), 0x7632);
  const uint32_t w2 = __byte_perm(__float_as_uint(t.y), __float_as_uint(t.w), 0x5410), w3 = __byte_perm(__float_as_uint(t.y), __float_as_uint(t.w), 0x7632);
#pragma unroll
  for (int i = 0; i < 16; i++) {
    uint32_t a = hmul2(kk[i], w3);
    a = hadd2(a, hmul2(kk[i + 1], w2)); a = hadd2(a, hmul2(kk[i + 2], w1)); a = hadd2(a, hmul2(kk[i + 3], w0));
    u[i] = hmul2(a, u[i]);
  }
#pragma unroll
  for (int e = 0; e < 2; e++)
#pragma unroll
    for (int f = 0; f < 2; f++) {
      uint32_t o[4];
#pragma unroll
      for (int qq = 0; qq < 4; qq++) o[qq] = __byte_perm(u[15 - 4 * qq - 2 * f], u[14 - 4 * qq - 2 * f], e ? 0x7632 : 0x5410);
      *(uint4*)(dst + e * 4096 + f * 2048) = make_uint4(o[0], o[1], o[2], o[3]);
    }
}
__device__ __forceinline__ void ln_finish(float s1, float s2, float& mean, float& rstd) {
  mean = s1 * (1.f / 640.f);
  const float v = fmaxf(fmaf(-mean, mean, s2 * (1.f / 640.f)), 0.f) + 1e-5f;
  asm("rsqrt.approx.ftz.f32 %0, %1;" : "=f"(rstd) : "f"(v));
}
__device__ __forceinline__ void stat_table(int T1, unsigned want, int l, int g, const uint4* x0, const uint4* x1, float (&xa)[2], float (&xb)[2]) {
  const int n = 32 * g + (tid_opaque() & 31);
  const uint4* rp = &g_stats[8 * l * SEQ + min(160 * T1 + n, SEQ - 1)];
  float a[4], b[4];
  uint32_t it = 0;
  while (true) {
    bool ok = true;
#pragma unroll
    for (int i = 0; i < 4; i++) ok &= (rec_ld(rp + SEQ * i, a[i], b[i]) == want);
    ok &= rec_ld(x0, xa[0], xb[0]) == want;
    ok &= rec_ld(x1, xa[1], xb[1]) == want;
    if (__all_sync(0xffffffffu, ok)) break;
    trap_if(++it > SPIN_LIMIT);
  }
  float m, rs;
  ln_finish((a[0] + a[1]) + (a[2] + a[3]), (b[0] + b[1]) + (b[2] + b[3]), m, rs);
  sts64f(sb + STAB_OFF + n * 8, rs, -m * rs);
}
__device__ __forceinline__ void stats_reduce(float (&a)[2], float (&b)[2], float (&mean)[2], float (&rstd)[2]) {
#pragma unroll
  for (int o = 1; o < 4; o <<= 1)
#pragma unroll
    for (int h = 0; h < 2; h++) { a[h] += __shfl_xor_sync(0xffffffffu, a[h], o); b[h] += __shfl_xor_sync(0xffffffffu, b[h], o); }
#pragma unroll
  for (int h = 0; h < 2; h++) ln_finish(a[h], b[h], mean[h], rstd[h]);
}

template <bool FIRST>
__device__ __forceinline__ void stats_publish(int which, int n0, int dg, unsigned tag, const float (&acc)[80]) {
  const int q = tid_opaque() & 3, h = q & 1;
  float s1[2] = {0.f, 0.f}, s2[2] = {0.f, 0.f}, t1[2] = {0.f, 0.f}, t2[2] = {0.f, 0.f};
#pragma unroll
  for (int j = 0; j < 20; j++)
#pragma unroll
    for (int y = 0; y < 2; y++) {
      const float a = acc[4 * j + 2 * y], b = acc[4 * j + 2 * y + 1];
      s1[y] += a; t1[y] += b; s2[y] = fmaf(a, a, s2[y]); t2[y] = fmaf(b, b, t2[y]);
    }
#pragma unroll
  for (int y = 0; y < 2; y++) { s1[y] += t1[y]; s2[y] += t2[y]; }
  float a = (h ? s1[1] : s1[0]) + __shfl_xor_sync(0xffffffffu, h ? s1[0] : s1[1], 1);
  float b = (h ? s2[1] : s2[0]) + __shfl_xor_sync(0xffffffffu, h ? s2[0] : s2[1], 1);
  a += __shfl_xor_sync(0xffffffffu, a, 2);
  b += __shfl_xor_sync(0xffffffffu, b, 2);
  if (FIRST) {
    rec_st(&g_stats[((q >> 1) * 4 + dg) * SEQ + n0 + 8 * h], a, b, q < 2 ? tag : tag - 1);
    rec_st(&g_stats[((q >> 1) * 4 + 8 + dg) * SEQ + n0 + 8 * h], a, b, tag - 1);
  } else if (q < 2) rec_st(&g_stats[(which * 4 + dg) * SEQ + n0 + 8 * h], a, b, tag);
}
__device__ __forceinline__ void stats_get(int which, int n0, unsigned tag, float (&mean)[2], float (&rstd)[2]) {
  const uint4* p0 = &g_stats[(which * 4 + (tid_opaque() & 3)) * SEQ + n0];
  float a[2], b[2];
  uint32_t it = 0;
  while (true) {
    const unsigned t0 = rec_ld(p0, a[0], b[0]), t1 = rec_ld(p0 + 8, a[1], b[1]);
    if (__all_sync(0xffffffffu, t0 == tag && t1 == tag)) break;
    trap_if(++it > SPIN_LIMIT);
  }
  stats_reduce(a, b, mean, rstd);
}
__device__ __forceinline__ void x0_load(float (&acc)[80]) {
  const int t = tid_opaque() & 127;
  const uint32_t xa = sb + XT_OFF + (16 * (t >> 5) + ((t & 31) >> 2)) * 320 + 8 * (t & 3);
  mbar_wait(bars + 8 * B_XT);
#pragma unroll
  for (int h = 0; h < 2; h++)
#pragma unroll
    for (int J = 0; J < 10; J++) {
      const float2 v = lds64f(xa + h * 2560 + 32 * J);
      const uint32_t x = __float_as_uint(v.x), y = __float_as_uint(v.y);
      acc[8 * J + 2 * h] = bf_lo(x); acc[8 * J + 2 * h + 1] = bf_hi(x);
      acc[8 * J + 4 + 2 * h] = bf_lo(y); acc[8 * J + 4 + 2 * h + 1] = bf_hi(y);
    }
}

template <bool FROM_X0>
__device__ __forceinline__ void dskip_init(float (&acc)[80], const float (&mean)[2], const float (&rstd)[2]) {
  const int t = tid_opaque() & 127;
  const uint32_t xa = sb + XT_OFF + (16 * (t >> 5) + ((t & 31) >> 2)) * 320 + 8 * (t & 3), da = sb + DTAB_OFF + 8 * (t & 3);
  float2 dw[10], xv[10][2];
#pragma unroll
  for (int J = 0; J < 2; J++) { dw[J] = lds64f(da + 32 * J); if (FROM_X0) { xv[J][0] = lds64f(xa + 32 * J); xv[J][1] = lds64f(xa + 2560 + 32 * J); } }
#pragma unroll
  for (int J = 0; J < 10; J++) {
    if (J + 2 < 10) { dw[J + 2] = lds64f(da + 32 * (J + 2)); if (FROM_X0) { xv[J + 2][0] = lds64f(xa + 32 * (J + 2)); xv[J + 2][1] = lds64f(xa + 2560 + 32 * (J + 2)); } }
#pragma unroll
    for (int x = 0; x < 8; x++) {
      const int h = (x >> 1) & 1;
      const uint32_t dwd = __float_as_uint(x < 4 ? dw[J].x : dw[J].y);
      const float tt = fmaf(rstd[h], (x & 1) ? bf_hi(dwd) : bf_lo(dwd), 1.f);
      float a = acc[8 * J + x];
      if (FROM_X0) { const uint32_t xw = __float_as_uint(x < 4 ? xv[J][h].x : xv[J][h].y); a = (x & 1) ? bf_hi(xw) : bf_lo(xw); }
      acc[8 * J + x] = FROM_X0 ? (a - mean[h]) * tt : fmaf(a, tt, -mean[h] * tt);
    }
  }
}

__global__ void __launch_bounds__(512, 1) fused_kernel(const __grid_constant__ Params p) {
  extern __shared__ __align__(1024) uint8_t smem_raw[];
  const int tid = threadIdx.x, lane = tid & 31;
  const int wid = __shfl_sync(0xffffffffu, tid >> 5, 0), wg = wid >> 2;
  unsigned smid; asm volatile("mov.u32 %0, %%smid;" : "=r"(smid));
  const int role = p.role[min(smid, 131u)];
  if (wid == 12) {
    const bool el = elect_one();
    if (el) {
      asm volatile("prefetch.tensormap [%0];" ::"l"(&p.mX) : "memory");
      asm volatile("prefetch.tensormap [%0];" ::"l"(&p.mB) : "memory");
#pragma unroll
      for (int k = 0; k < S1; k++) mbar_init(bars + 8 * (B_G1FULL + k), 1);
#pragma unroll
      for (int k = 0; k < 6; k++) mbar_init(bars + 8 * (B_XT + k), 1);
      asm volatile("fence.mbarrier_init.release.cluster;" ::: "memory");
    }
    if (role >= 0) {
      __syncwarp();
      asm volatile("bar.arrive 5, 288;" ::: "memory");
      const Role R = unpack_role(role);
      if (elect_one()) {
        TS(45);
#pragma unroll 1
        for (int k = 0; k < S1; k++) {
          const uint32_t fb = bars + 8 * (B_G1FULL + k);
          mbar_expect_tx(fb, G1_STAGE);
          tma4(sb + k * G1_STAGE + G1_XOFF, R.last ? &p.mXl : &p.mX, 64 * k, 0, 0, R.last ? 0 : 80 * R.T1, fb);
          tma5(sb + k * G1_STAGE, &p.mB, 64 * k, 0, 0, 4 * R.side, 2 * R.GP, fb);
        }
        if (R.has2) {
#pragma unroll 1
          for (int c = 0; c < KV0; c++) kv_issue(p, c, R.m2, R.dg);
          mbar_expect_tx(bars + 8 * B_XT, 20480);
#pragma unroll 1
          for (int h = 0; h < 2; h++) {
            const int ng = 8 * R.m2 + 4 * h, T = ng / 20;
            tma4(sb + XT_OFF + h * 10240, T == NT1 - 1 ? &p.mXtl : &p.mXt, 160 * R.dg, 0, 0, T == NT1 - 1 ? ng - 240 : ng + 60 * T, bars + 8 * B_XT);
          }
        }
        TS(44);
      }
      __syncwarp();
      bar_sync(6, 64);
    }
  }
  trap_if(smid >= 132 || smem_u32(smem_raw) != sb);
  if (role < 0) {
    if (wid == 0) {
      const unsigned tag = ld_rlx(g_epoch);
#pragma unroll 1
      for (int i = 0; i < NT1; i++) {
        uint32_t it = 0;
        while (!__all_sync(0xffffffffu, (int)(ld_rlx(&g_hflag[(i * 32 + min(lane, 9)) * 8]) - tag) >= 0)) { __nanosleep(500); trap_if(++it > SPIN_LIMIT); }
      }
    }
    return;
  }
  float mean0[2] = {0.f, 0.f}, rstd0[2] = {0.f, 0.f};
  if (wg == 2 || wid == 14) {
    ROLE(role)
    const int c = wid == 14 ? 4 : wid - 8;
    const unsigned tag = ld_rlx(g_epoch);
    if (has2) {
      uint2 bv[2][5];
#pragma unroll
      for (int x = 0; x < 2; x++)
#pragma unroll
        for (int i = 0; i < 5; i++) bv[x][i] = ldv64((const uint2*)((x ? p.bim : p.bre) + (cch0 + 32 * c) * DM) + lane + 32 * i);
      float sv[2];
#pragma unroll
      for (int x = 0; x < 2; x++) {
        float a = 0.f;
#pragma unroll
        for (int i = 0; i < 5; i++) a += (bf_lo(bv[x][i].x) + bf_hi(bv[x][i].x)) + (bf_lo(bv[x][i].y) + bf_hi(bv[x][i].y));
        sv[x] = a;
      }
#pragma unroll
      for (int o = 16; o > 0; o >>= 1) { sv[0] += __shfl_xor_sync(0xffffffffu, sv[0], o); sv[1] += __shfl_xor_sync(0xffffffffu, sv[1], o); }
      if (lane < 2) rec_st(&g_sB[(cch0 + 32 * c) * 2 + lane], sv[0], sv[1], tag);
      if (tid == 256) TS(47);
      __syncwarp();
      bar_sync(8, 192);
      mbar_wait(bars + 8 * B_EP);
      mbar_wait(bars + 8 * (B_KV + c));
#pragma unroll 1
      for (int y = 0; y < 2; y++) kv_tile(m2, dg, c, y);
      __syncwarp();
      if (lane == 0) mbar_arrive(bars + 8 * B_PREP);
      if (tid == 352) TS(52);
      if (tid == 448) TS(51);
      if (wg == 2) {
        float xs[80];
        x0_load(xs);
        stats_publish<true>(0, 64 * m2 + 16 * c + (lane >> 2), dg, tag, xs);
        if (tid == 256) TS(31);
        mbar_wait(bars + 8 * B_PUB);
      } else {
        mbar_wait(bars + 8 * B_PREP);
        if (lane == 0) { st_rel(&g_kvflag[(dg * 32 + m2) * 8], tag); mbar_arrive(bars + 8 * B_PUB); TS(30); }
        __syncwarp();
      }
    } else bar_sync(8, 192);
    {
      const uint4* x0 = wg == 2 ? &g_stats[(lane & 3) * SEQ + (has2 ? 64 * m2 : 0) + 16 * c + (lane >> 2)] : &g_sB[(128 * GP + 32 * side + lane) * 2];
      float xa[2], xb[2];
      stat_table(T1, tag, 0, c, x0, x0 + (wg == 2 ? 8 : 128), xa, xb);
      if (wg == 2) stats_reduce(xa, xb, mean0, rstd0);
      else {
#pragma unroll
        for (int i = 0; i < 2; i++) sts64f(sb + CTAB_OFF + (32 * i + lane) * 24 + 16, p.swap ? xb[i] : xa[i], p.swap ? xa[i] : xb[i]);
      }
      mbar_arrive(bars + 8 * B_STAB);
      if (tid == 256) TS(26);
    }
  } else if (wid == 15) {
    ROLE(role)
    const int ch = 128 * GP + 32 * side + lane;
    uint32_t r0 = ldv16(p.lre + ch), r1 = ldv16(p.lim + ch), r2 = ldv16(p.logdt + ch);
    const uint32_t r3 = ldv16(p.lre + ch + 64), r4 = ldv16(p.lim + ch + 64), r5 = ldv16(p.logdt + ch + 64);
#pragma unroll 1
    for (int i = 0; i < 2; i++) {
      const float lr = bf_lo(r0), li = bf_lo(r1);
      const float dt = __bfloat162float(__float2bfloat16_rn(expf(bf_lo(r2))));
      const float mag = expf(dt * lr);
      float sn, cs; sincospif(dt * li * 0.31830988618379067f, &sn, &cs);
      const float ar = mag * cs, ai = mag * sn;
      const float inv = 2.f / (lr * lr + li * li);
      const uint32_t ad = sb + CTAB_OFF + (32 * i + lane) * 24;
      sts64f(ad, ar, ai);
      sts64f(ad + 8, ((ar - 1.f) * lr + ai * li) * inv, (ai * lr - (ar - 1.f) * li) * inv);
      r0 = r3; r1 = r4; r2 = r5;
    }
    if (lane == 0) TS(46);
    __syncwarp();
    bar_sync(7, 64);
    mbar_arrive(bars + 8 * B_CTAB);
  } else if (wid == 13) {
    ROLE(role)
    uint4 tv[3];
    const uint32_t e0 = ld_rlx(g_epoch);
    const uint32_t e1 = ldv16(p.ssmD + min(cch0 + 32 * lane, 639));
    const uint4 dv = ldv128((const uint4*)(p.dskip + 160 * dg) + min(lane, 19));
#pragma unroll
    for (int i = 0; i < 3; i++) tv[i] = ldv128((const uint4*)(p.shiftk + 640 * dg) + min(lane + 32 * i, 79));
    sts128(sb + DTAB_OFF + 16 * min(lane, 19), dv);
#pragma unroll
    for (int i = 0; i < 3; i++) sts128(sb + TAP_OFF + 16 * min(lane + 32 * i, 79), tv[i]);
    if (lane < 7) sts32(sb + EP_OFF + 4 * lane, lane < 5 ? e1 << 16 : (lane == 5 ? e0 : 0u));
    __syncwarp();
    bar_sync(9, 64);
    mbar_arrive(bars + 8 * B_CTAB);
    if (lane == 0) { mbar_arrive(bars + 8 * B_EP); TS(53); }
  } else if (wid != 12) {
    if (elect_one()) {
      if (wid < 7) {
        const int b0 = wid < 4 ? 4 + 20 * wid : 85 + 21 * (wid - 4), cnt = wid < 4 ? 2 : 1;
#pragma unroll
        for (int i = 0; i < 21; i++) mbar_init(bars + 8 * (b0 + i), cnt);
      } else {
#pragma unroll
        for (int i = 0; i < 12; i++) mbar_init(bars + 8 * (B_CVDONE + i), (i == 5 || i == 6) ? 160 : 128);
        mbar_init(bars + 8 * B_CTAB, 192); mbar_init(bars + 8 * B_PREP, 5);
      }
      asm volatile("fence.mbarrier_init.release.cluster;" ::: "memory");
    }
    __syncwarp();
    bar_sync(5, 288);
    if (wid == 2) asm volatile("bar.arrive 8, 192;\nbar.arrive 6, 64;\nbar.arrive 9, 64;\nbar.arrive 7, 64;" ::: "memory");
    if (tid == 128) TS(0);
    if (wg == 1) { cv_table(); mbar_arrive(bars + 8 * B_CTAB); }
  }

  if (wid == 12) {
    ROLE(role)
    uint32_t dst = sb;
#pragma unroll 1
    for (int k = S1; k < 10; k++) {
      const uint32_t fb = bars + 8 * (B_G1FULL + k);
      mbar_wait(bars + 8 * (B_G1DONE + k - S1));
      if (elect_one()) {
        mbar_expect_tx(fb, 20480);
        tma4(dst + G1_XOFF, last ? &p.mXl : &p.mX, 64 * k, 0, 0, last ? 0 : 80 * T1, fb);
        mbar_expect_tx(fb, 16384);
        tma5(dst, &p.mB, 64 * k, 0, 0, 4 * side, 2 * GP, fb);
      }
      dst += G1_STAGE; if (k == 2 * S1 - 1) dst = sb;
    }
  } else if (wid == 15 && (role >> 16)) {
    ROLE(role)
    mbar_wait(bars + 8 * B_PREP);
#pragma unroll
    for (int c = 0; c < 5; c++) {
      const uint32_t cb = sb + CV_OFF + c * CV_B;
      sts128(lane < 8 ? cb + 16 * lane : (lane < 20 ? cb + CV_U + 16 * (lane - 8) : cb + CV_U + CV_PL + 16 * (lane - 20)), make_uint4(0, 0, 0, 0));
    }
    fence_async_smem();
    __syncwarp();
    const unsigned tag = lds32(sb + EP_OFF + 20);
    mbar_wait(bars + 8 * B_PUB);
    if (elect_one()) {
#pragma unroll
      for (int c = 0; c < TAP0; c++) {
        mbar_expect_tx(bars + 8 * (B_CVFULL + c), 4096);
        bulk_g2s(sb + CV_OFF + c * CV_B + CV_K, p.ssmk + (cch0 + 32 * c) * SEQ, 4096, bars + 8 * (B_CVFULL + c));
      }
    }
    flag_poll(&g_kvflag[(dg * 32 + lane) * 8], tag);
    fence_async_global();
    if (elect_one()) {
      TS(28);
#pragma unroll 1
      for (int c = 0; c < 5; c++) {
        const uint32_t fb = bars + 8 * (B_CVFULL + c), cb = sb + CV_OFF + c * CV_B;
        mbar_expect_tx(fb, 4096);
        bulk_g2s(cb + CV_U + 192, g_kv + (cch0 + 32 * c) * 4096, 2048, fb);
        bulk_g2s(cb + CV_U + 192 + CV_PL, g_kv + (cch0 + 32 * c) * 4096 + 2048, 2048, fb);
        if (c >= TAP0) {
          mbar_expect_tx(fb, 4096);
          bulk_g2s(cb + CV_K, p.ssmk + (cch0 + 32 * c) * SEQ, 4096, fb);
        }
      }
      TS(54);
    }
    __syncwarp();
  }
  {
    const int w = wid & 3;
    if (wg == 2 && !(role >> 16)) {
      float xa[2], xb[2];
      mbar_wait(bars + 8 * (B_G1FULL + 11));
      stat_table(role & 15, lds32(sb + EP_OFF + 20), 1, w, g_stats, g_stats, xa, xb);
      mbar_arrive(bars + 8 * (B_STAB + 1));
    }
#pragma unroll 1
    for (int l = 0; l < 2; l++) {
      if (wg < 2) {
        float acc[80];
#pragma unroll
        for (int i = 0; i < 80; i++) acc[i] = 0.f;
        ROLE(role)
        const int tid = tid_opaque(), r = (tid & 31) >> 2, q = tid & 3;
        const int ch = 128 * GP + 64 * wg + 32 * side + 8 * w + r;
        const uint32_t ca = sb + CTAB_OFF + (32 * wg + 8 * w + r) * 24;
        float2 lam = make_float2(0.f, 0.f), p8 = lam, p16 = lam, pL = lam, p2L = lam;
        fence_regs(acc);
        {
          uint32_t alo = desc_lo(sb, 16) + wg * 512, blo = l == 0 ? desc_lo(sb + G1_XOFF, 16) : desc_lo(sb + G1_XOFF, 128);
          const uint32_t bhi = l == 0 ? desc_hi(1024, 1) : desc_hi(1024, 0), xstep = l == 0 ? 2 : 16;
          const uint32_t aend = desc_lo(sb, 16) + (S1 + l) * (G1_STAGE >> 4);
          uint32_t fb = bars + 8 * (B_G1FULL + 10 * l);
          mbar_wait(fb);
          if (tid == 0) TS(1 + 8 * l);
#pragma unroll 1
          for (int k = 0; k < 10; k++) {
            uint32_t ok; const uint32_t nb = k < 9 ? fb + 8 : fb;
            wgmma_fence();
#pragma unroll
            for (int kk = 0; kk < 4; kk++) {
              wgmma_n160<0>(acc, alo + kk * 2, desc_hi(1024, 1), blo + kk * xstep, bhi);
              if (kk == 0) ok = mbar_test(nb);
              if (kk == STG_KK && k == 9 && tid == 0) mbar_arrive(bars + 8 * (B_STG + l));
            }
            wgmma_commit();
            alo += G1_STAGE >> 4; blo += G1_STAGE >> 4;
            if (alo >= aend) { alo -= (S1 + l) * (G1_STAGE >> 4); blo -= (S1 + l) * (G1_STAGE >> 4); }
            wgmma_wait<1>();
            if (k > 0 && (tid & 127) == 0) mbar_arrive(fb + 8 * (B_G1DONE - B_G1FULL - 1));
            if (!ok) mbar_wait(nb);
            if (wg == 1 && k == 9 - STG_D - l) mbar_wait(bars + 8 * (B_STG + l));
            if (k == PAUSE_K) {
              mbar_wait(bars + 8 * B_CTAB);
              lam = lds64f(ca);
              if (p.swap) lam.y = -lam.y;
              const float2 p2 = cmul(lam, lam), p4 = cmul(p2, p2);
              p8 = cmul(p4, p4); p16 = cmul(p8, p8);
              pL = cmul(p16, p16);
              if (!last) pL = cmul(pL, p8);
              p2L = cmul(pL, pL);
              if (has2) mbar_wait(bars + 8 * B_PREP);
            }
            fb += 8;
          }
        }
        mbar_wait(bars + 8 * (B_STAB + l));
        const float2 sB = lds64f(ca + 16);
        const unsigned tag = lds32(sb + EP_OFF + 20);
        wgmma_wait<0>();
        fence_regs(acc);
        if ((tid & 127) == 0) { mbar_arrive(bars + 8 * (B_G1DONE + 10 * l + 9)); TS(wg ? 17 + l : 2 + 8 * l); }
        float2 ec[3];
#pragma unroll
        for (int jj = 0; jj < 8; jj++)
#pragma unroll
          for (int y = 0; y < 3; y++) {
            if (y == 2 && (jj & 1)) continue;
            const int j = y == 2 ? 16 + (jj >> 1) : 8 * y + jj;
            const float4 st = lds128f(sb + STAB_OFF + (8 * j + 2 * q) * 8);
            acc[4 * j + 0] = fmaf(acc[4 * j + 0], st.x, st.y * sB.x);
            acc[4 * j + 2] = fmaf(acc[4 * j + 2], st.x, st.y * sB.y);
            acc[4 * j + 1] = fmaf(acc[4 * j + 1], st.z, st.w * sB.x);
            acc[4 * j + 3] = fmaf(acc[4 * j + 3], st.z, st.w * sB.y);
            ec[y] = jj == 0 ? make_float2(acc[4 * j + 0], acc[4 * j + 2]) : cfma(lam, ec[y], make_float2(acc[4 * j + 0], acc[4 * j + 2]));
            ec[y] = cfma(lam, ec[y], make_float2(acc[4 * j + 1], acc[4 * j + 3]));
          }
        float2 e = cfma(p16, ec[0], ec[1]);
        if (!last) e = cfma(p8, e, ec[2]);
        {
          float2 v = make_float2(__shfl_up_sync(0xffffffffu, e.x, 1, 4), __shfl_up_sync(0xffffffffu, e.y, 1, 4));
          if (q >= 1) e = cfma(pL, v, e);
          v = make_float2(__shfl_up_sync(0xffffffffu, e.x, 2, 4), __shfl_up_sync(0xffffffffu, e.y, 2, 4));
          if (q >= 2) e = cfma(p2L, v, e);
        }
        if (!last && (q == 3 || (q == 2 && l == 0))) rec_st(&g_E[((q == 3 ? l : 1) * NT1 + T1) * DM + ch], e.x, e.y, q == 3 ? tag : tag - 1);
        if (tid == 0) TS(3 + 8 * l);
        float2 ex = make_float2(__shfl_up_sync(0xffffffffu, e.x, 1, 4), __shfl_up_sync(0xffffffffu, e.y, 1, 4));
        if (q == 0) ex = make_float2(0.f, 0.f);
        const float2 coef = lds64f(ca + 8), lamc = make_float2(lam.x, p.swap ? lam.y : -lam.y);
        float m00 = coef.x, m01 = -coef.y, m10 = -coef.y, m11 = -coef.x;
        if (p.swap) { m00 = -coef.y; m01 = coef.x; m10 = -coef.x; m11 = -coef.y; }
        float2 pLq, p160q, p640;
        {
          const float2 p80 = last ? cmul(p2L, p16) : p2L, p160 = cmul(p80, p80), p320 = cmul(p160, p160), one = make_float2(1.f, 0.f);
          p640 = cmul(p320, p320);
          pLq = cmul((q & 1) ? pL : one, (q & 2) ? p2L : one);
          p160q = cmul((q & 1) ? p160 : one, (q & 2) ? p320 : one);
        }
        float2 c, ev[3];
        unsigned tg[3];
        const uint4* ep = &g_E[(l * NT1 + T1 - 1 - q) * DM + ch];
#pragma unroll
        for (int j = 0; j < 20; j++) {
          if (j == CPOLL) {
#pragma unroll
            for (int i = 0; i < 3; i++) {
              ev[i] = make_float2(0.f, 0.f); tg[i] = tag;
              if (T1 - 1 - q - 4 * i >= 0) tg[i] = rec_ld(ep - 4 * i * DM, ev[i].x, ev[i].y);
            }
          }
#pragma unroll
          for (int x = 0; x < 2; x++) {
            const float b0 = acc[4 * j + x], b1 = acc[4 * j + 2 + x];
            acc[4 * j + x] = fmaf(b0, m00, b1 * m01);
            acc[4 * j + 2 + x] = fmaf(b0, m10, b1 * m11);
          }
          if (j == CPOLL - 1 || j == 19) asm volatile("" : "+f"(acc[4 * j]), "+f"(acc[4 * j + 1]), "+f"(acc[4 * j + 2]), "+f"(acc[4 * j + 3])::"memory");
        }
        {
          uint32_t it = 0;
          while (__any_sync(0xffffffffu, tg[0] != tag || tg[1] != tag || tg[2] != tag)) {
#pragma unroll
            for (int i = 0; i < 3; i++)
              if (tg[i] != tag) tg[i] = rec_ld(ep - 4 * i * DM, ev[i].x, ev[i].y);
            trap_if(++it > SPIN_LIMIT);
          }
          c = cfma(p640, cfma(p640, ev[2], ev[1]), ev[0]);
          c = cmul(c, p160q);
          c.x += __shfl_xor_sync(0xffffffffu, c.x, 1); c.y += __shfl_xor_sync(0xffffffffu, c.y, 1);
          c.x += __shfl_xor_sync(0xffffffffu, c.x, 2); c.y += __shfl_xor_sync(0xffffffffu, c.y, 2);
        }
        if (tid == 0) TS(4 + 8 * l);
        if (wg == 1 && l >= HOLD0) mbar_wait(bars + 8 * (B_REL + l));
        c = cfma(pLq, c, ex);
        float2 hh = make_float2(fmaf(c.x, m00, c.y * m01), fmaf(c.x, m10, c.y * m11));
        uint8_t* hb = g_h + (size_t)l * (32 * 20 * 8192) + (10 * wg + 2 * GP) * 8192 + (4 * side + w) * 1024 + (tid_opaque() & 31) * 4;
#pragma unroll
        for (int j4 = 0; j4 < 5; j4++) {
          const int ng = 20 * T1 + 4 * j4;
          uint8_t* hp = hb + (size_t)(ng >> 3) * 163840 + (ng & 7) * 128;
#pragma unroll
          for (int jj = 0; jj < 4; jj++) {
            const int j = 4 * j4 + jj;
            const float2 h0 = cfma(lamc, hh, make_float2(acc[4 * j + 0], acc[4 * j + 2]));
            hh = cfma(lamc, h0, make_float2(acc[4 * j + 1], acc[4 * j + 3]));
            if (j4 < 4 || !last) {
              *(uint32_t*)(hp + jj * 128) = pack_bf16(h0.x, hh.x);
              *(uint32_t*)(hp + jj * 128 + 8192) = pack_bf16(h0.y, hh.y);
            }
          }
        }
        mbar_arrive(bars + 8 * (B_HST + 2 * l + wg));
        if (tid == 0) TS(5 + 8 * l);
        if (tid == 128) TS(l ? 25 : 19);
      }
      if (l == 0) {
        ROLE(role)
        if (has2) {
          CvCtx cc;
          mbar_wait(bars + 8 * B_CTAB);
          cv_setup(cc);
          mbar_wait(bars + 8 * (B_G1DONE + 9));
#pragma unroll 1
          for (int c = (wg + 2) & 3; c < 5; c += 4) conv_channel(c, cc);
          if ((tid & 127) == 0) TS(wg == 2 ? 32 : (wg == 3 ? 50 : 7 + wg));
        }
      }
      if (wg >= 2) break;
    }
    if (wg == 3) {
    ROLE(role)
    const int pw = wid & 3;
    mbar_wait(bars + 8 * B_EP);
    const unsigned tag = lds32(sb + EP_OFF + 20);
    if (pw == 0) {
      if (elect_one()) {
#pragma unroll 1
        for (int l = 0; l < 2; l++) {
          uint32_t dst = sb;
          if (l == 1) {
            const uint32_t free0 = bars + 8 * (has2 ? B_G2DONE + 19 : B_G1DONE + 9);
#pragma unroll 1
            for (int k = 0; k < 10; k++) {
              mbar_wait(k > S1 ? bars + 8 * (B_G1DONE + 9 - S1 + k) : (k < WPF1 || !has2 ? free0 : bars + 8 * B_GO));
              mbar_expect_tx(bars + 8 * (B_G1FULL + 10 + k), 16384);
              tma5(dst, &p.mB, 64 * k, 0, 0, 4 * side, 2 * GP, bars + 8 * (B_G1FULL + 10 + k));
              dst += G1_STAGE; if (k == S1) dst = sb;
            }
          }
          if (has2) {
            const uint32_t fb2 = bars + 8 * (B_G2FULL + 20 * l), wb2 = bars + 8 * (B_G2DONE + 20 * l - S2);
            dst = sb + G2_WOFF;
            int kc = 0;
#pragma unroll 1
            for (int k = 0; k < 20; k++) {
              mbar_wait(k >= S2 ? wb2 + 8 * k : (k == 5 ? bars + 8 * B_XFREE : (k == 6 ? bars + 8 * B_SFREE : bars + 8 * (B_G1DONE + 10 * l + 9))));
              mbar_expect_tx(fb2 + 8 * k, G2_WB);
              tma5(dst, &p.mCre + (k & 1), kc, 0, 0, 0, 10 * dg, fb2 + 8 * k);
              kc += (k & 1) << 7; if (k == 9) kc = 64;
              dst += G2_WB; if (dst == sb + G2_WOFF + S2 * G2_WB) dst = sb + G2_WOFF;
            }
          }
        }
      }
    } else if (pw == 1) {
#pragma unroll 1
      for (int l = 0; l < 2; l++) {
        if (l == 1) {
          mbar_wait(bars + 8 * (has2 ? B_G2DONE + 19 : B_G1DONE + 9));
          const int mlo = (160 * T1) >> 6, nf = last ? 8 : 12;
          flag_poll(&g_uflag[(4 * mlo + min(lane, nf - 1)) * 8], tag);
          fence_async_global();
          if (elect_one()) {
            TS(20);
            const int bytes = last ? 16384 : 20480;
            const uint8_t* src = g_u + T1 * 204800;
            uint32_t dst = sb + G1_XOFF;
#pragma unroll 1
            for (int k = 0; k < 10; k++) {
              if (k > S1) mbar_wait(bars + 8 * (B_G1DONE + 9 - S1 + k));
              mbar_expect_tx(bars + 8 * (B_G1FULL + 10 + k), bytes);
              bulk_g2s(dst, src, bytes, bars + 8 * (B_G1FULL + 10 + k));
              src += 20480; dst += G1_STAGE; if (k == S1) dst = sb + G1_XOFF;
            }
          }
          __syncwarp();
        }
        if (has2) {
          mbar_wait(bars + 8 * (B_HST + 2 * l));
          mbar_wait(bars + 8 * (B_G1DONE + 10 * l + 9));
          const int Tlo = (64 * m2) / 160, Thi = (64 * m2 + 63) / 160;
          flag_poll(&g_hflag[(((l * NT1 + (lane < 16 ? Tlo : Thi)) * 2) * 16 + min(lane & 15, 9)) * 8], tag);
          fence_async_global();
          if (elect_one()) {
            TS(21 + 2 * l);
            const uint32_t fb2 = bars + 8 * (B_G2FULL + 20 * l), wb2 = bars + 8 * (B_G2DONE + 20 * l - S2);
            const uint8_t* src = g_h + (l * 32 + m2) * 163840;
            uint32_t dst = sb;
#pragma unroll 1
            for (int k = 0; k < 20; k++) {
              if (k >= 5) mbar_wait(k >= S2 ? wb2 + 8 * k : bars + 8 * B_SFREE);
              if (k == 10) { mbar_wait(bars + 8 * (B_H1 + l)); fence_async_global(); }
              mbar_expect_tx(fb2 + 8 * k, G2_XB);
              bulk_g2s(dst, src, G2_XB, fb2 + 8 * k);
              src += 8192; dst += G2_XB; if (dst == sb + S2 * G2_XB) dst = sb;
            }
          }
          __syncwarp();
        }
      }
    } else if (pw == 2) {
#pragma unroll 1
      for (int l = 0; l < 2; l++) {
        if (l == 1) {
          float xa[2], xb[2];
          mbar_wait(bars + 8 * (B_G1FULL + 11));
          stat_table(T1, tag, 1, 4, g_stats, g_stats, xa, xb);
          mbar_arrive(bars + 8 * (B_STAB + 1));
        }
#pragma unroll 1
        for (int w = 0; w <= l; w++) {
          mbar_wait(bars + 8 * (B_HST + 2 * l + w));
          if (l == 0) mbar_wait(bars + 8 * (B_HST + 1));
          if (lane < 2 - l) st_rel(&g_hflag[(((l * NT1 + T1) * 2 + w + lane) * 16 + 2 * GP + side) * 8], tag);
          if (lane == 0) { if (w == 0) mbar_arrive(bars + 8 * (B_REL + l)); TS(w ? 15 + l : 6 + 8 * l); }
          __syncwarp();
        }
        if (l == 0 && has2 && elect_one()) {
#pragma unroll 1
          for (int c = 0; c < 5; c++) {
            mbar_wait(bars + 8 * (B_CVDONE + c));
            bulk_s2g(g_G + (cch0 + 32 * c) * 4096, cv_stage(c), 4096);
          }
          asm volatile("cp.async.bulk.commit_group;" ::: "memory");
          asm volatile("cp.async.bulk.wait_group.read 0;" ::: "memory");
          mbar_arrive(bars + 8 * B_SFREE);
          asm volatile("cp.async.bulk.wait_group 0;" ::: "memory");
          TS(48);
          fence_async_global();
          st_rel(&g_gflag[(dg * 32 + m2) * 8], tag);
          TS(49);
          mbar_arrive(bars + 8 * (B_GO + 1));
        }
        __syncwarp();
      }
    } else if (has2) {
      if (elect_one()) {
        l2_prefetch(p.cre + (160 * dg + 5 * m2) * DM, 6400); l2_prefetch(p.cim + (160 * dg + 5 * m2) * DM, 6400);
        asm volatile("prefetch.tensormap [%0];" ::"l"(&p.mG) : "memory");
      }
      const unsigned* hf = &g_hflag[(((lane < 16 ? (64 * m2) / 160 : (64 * m2 + 63) / 160) * 2 + 1) * 16 + min(lane & 15, 9)) * 8];
      mbar_wait(bars + 8 * (B_HST + 1));
      flag_poll(hf, tag);
      if (lane == 0) { mbar_arrive(bars + 8 * B_H1); TS(22); }
      mbar_wait(bars + 8 * (B_GO + 1));
      flag_poll(&g_gflag[(dg * 32 + lane) * 8], tag);
      fence_async_global();
      if (elect_one()) {
        TS(29);
        mbar_expect_tx(bars + 8 * B_GFULL, 20480);
        tma5(sb + G_OFF, &p.mG, 64 * m2, 0, 0, 0, 10 * dg, bars + 8 * B_GFULL);
      }
      mbar_wait(bars + 8 * (B_HST + 3));
      flag_poll(hf + NT1 * 256, tag);
      if (lane == 0) { mbar_arrive(bars + 8 * (B_H1 + 1)); TS(24); }
    }
    } else if (wg == 2 && (role >> 16)) {
      float acc[80];
      float off[2] = {mean0[0], mean0[1]};
      const unsigned tag = lds32(sb + EP_OFF + 20);
      dskip_init<true>(acc, mean0, rstd0);
      mbar_arrive(bars + 8 * B_XFREE);
#pragma unroll 1
      for (int l = 0; l < 2; l++) {
        float mean[2], rstd[2];
        {
          uint32_t alo = desc_lo(sb, 1024), blo = desc_lo(sb + G2_WOFF, 16);
          uint32_t fb = bars + 8 * (B_G2FULL + 20 * l);
          fence_regs(acc);
          mbar_wait(fb);
          if (tid == 256) TS(33 + 6 * l);
#pragma unroll 1
          for (int k = 0; k < 20; k++) {
            if (l == TSL && (k & 3) == 3 && tid == 256) TS(56 + (k >> 2));
            uint32_t ok; const uint32_t nb = k < 19 ? fb + 8 : fb;
            wgmma_fence();
#pragma unroll
            for (int kk = 0; kk < 4; kk++) {
              wgmma_n160<1>(acc, alo + kk * 128, desc_hi(128, 0), blo + kk * 2, desc_hi(1024, 1));
              if (kk == 0) ok = mbar_test(nb);
            }
            wgmma_commit();
            alo += G2_XB >> 4; blo += G2_WB >> 4;
            if (alo == desc_lo(sb + S2 * G2_XB, 1024)) { alo = desc_lo(sb, 1024); blo = desc_lo(sb + G2_WOFF, 16); }
            wgmma_wait<1>();
            if (k > 0 && tid == 256) mbar_arrive(fb + 8 * (B_G2DONE - B_G2FULL - 1));
            if (!ok) mbar_wait(nb);
            fb += 8;
          }
          wgmma_wait<0>();
          fence_regs(acc);
          if (tid == 256) TS(34 + 6 * l);
          if (tid == 256) mbar_arrive(bars + 8 * (B_G2DONE + 20 * l + 19));
        }
        ROLE(role)
        const int tq = tid_opaque() & 31, n0 = 64 * m2 + 16 * w + (tq >> 2);
        stats_publish<false>(2 * l + 1, n0, dg, tag, acc);
        uint32_t gf[10][4];
        mbar_wait(bars + 8 * B_GFULL);
        const uint32_t ga = sb + G_OFF + (8 * (tq >> 4) + (tq & 7)) * 128 + (((2 * w + ((tq >> 3) & 1)) ^ ((2 * m2) & 6) ^ (tq & 7)) << 4);
#pragma unroll
        for (int J = 0; J < 2; J++) ldsm4t(gf[J], ga + J * 2048);
        if (tid == 256) TS(35 + 6 * l);
        uint8_t* dst[2][2];
#pragma unroll
        for (int h = 0; h < 2; h++) {
          if (l == 0) {
            const int ng = 8 * m2 + 2 * w + h, T = ng / 20;
            uint8_t* ub = g_u + (T * 204800 + (ng - 20 * T) * 1024 + (tq & 2) * 64 + (tq & 28) * 4 + (tq & 1) * 8 + (5 * dg >> 1) * 20480);
            dst[h][1] = ub + ((dg & 1) ? 20480 - 512 : 0);
            dst[h][0] = ub + (dg & 1) * 512;
          } else {
            dst[h][0] = dst[h][1] = (uint8_t*)(p.out + (n_to_t(n0 + 8 * h) * DM + 160 * dg + 4 * (tq & 3)));
          }
        }
        stats_get(2 * l + 1, n0, tag, mean, rstd);
        if (tid == 256) TS(36 + 6 * l);
        off[0] += mean[0]; off[1] += mean[1];
        const float ov[2] = {l ? off[0] : 0.f, l ? off[1] : 0.f};
#pragma unroll
        for (int J = 0; J < 10; J++) {
          if (J + 2 < 10) ldsm4t(gf[J + 2 < 10 ? J + 2 : 0], ga + (J + 2) * 2048);
#pragma unroll
          for (int x = 0; x < 8; x++) {
            const int h = (x >> 1) & 1;
            const uint32_t gwd = gf[J][x >> 1];
            const float t = fmaf(rstd[h], (x & 1) ? bf_hi(gwd) : bf_lo(gwd), 1.f);
            acc[8 * J + x] = fmaf(acc[8 * J + x], t, fmaf(-mean[h], t, ov[h]));
          }
#pragma unroll
          for (int h = 0; h < 2; h++) {
            if (l == 0)
              *(uint2*)(dst[h][(J >> 1) & 1] + (J >> 2) * 20480 + (J & 3) * 256) =
                  make_uint2(pack_bf16(acc[8 * J + 2 * h], acc[8 * J + 2 * h + 1]), pack_bf16(acc[8 * J + 4 + 2 * h], acc[8 * J + 5 + 2 * h]));
            else
              *(float4*)(dst[h][0] + 64 * J) = make_float4(acc[8 * J + 2 * h], acc[8 * J + 2 * h + 1], acc[8 * J + 4 + 2 * h], acc[8 * J + 5 + 2 * h]);
          }
          __syncwarp();
        }
        if (l == 0) {
          bar_sync(3, 128);
          if (tid == 256) { TS(37); st_rel(&g_uflag[(4 * m2 + dg) * 8], tag); mbar_arrive(bars + 8 * B_GO); TS(38); }
          stats_publish<false>(2, n0, dg, tag, acc);
          mbar_wait(bars + 8 * (B_G1FULL + 11));
          float xa[2], xb[2];
          const uint4* x0 = &g_stats[(8 + (tq & 3)) * SEQ + n0];
          stat_table(T1, tag, 1, w, x0, x0 + 8, xa, xb);
          mbar_arrive(bars + 8 * (B_STAB + 1));
          if (tid == 256) TS(27);
          stats_reduce(xa, xb, mean, rstd);
          off[0] += mean[0]; off[1] += mean[1];
          mbar_wait(bars + 8 * (B_HST + 2));
          dskip_init<false>(acc, mean, rstd);
        } else {
          if (tid == 256) {
            TS(43);
            if (m2 == 31 && dg == 3) asm volatile("st.relaxed.gpu.global.u32 [%0], %1;" ::"l"(g_epoch), "r"(tag + 1) : "memory");
          }
        }
      }
    }
  }
}

typedef CUresult (*EncFn)(CUtensorMap*, CUtensorMapDataType, cuuint32_t, void*, const cuuint64_t*, const cuuint64_t*,
                          const cuuint32_t*, const cuuint32_t*, CUtensorMapInterleave, CUtensorMapSwizzle,
                          CUtensorMapL2promotion, CUtensorMapFloatOOBfill);

void encode(EncFn fn, CUtensorMap* m, const void* ptr, int rank, const cuuint64_t* dims, const cuuint64_t* strides, const cuuint32_t* box,
            CUtensorMapSwizzle swz = CU_TENSOR_MAP_SWIZZLE_128B) {
  cuuint32_t es[5] = {1, 1, 1, 1, 1};
  fn(m, CU_TENSOR_MAP_DATA_TYPE_BFLOAT16, rank, (void*)ptr, dims, strides, box, es, CU_TENSOR_MAP_INTERLEAVE_NONE,
     swz, (CUtensorMapL2promotion)(swz == CU_TENSOR_MAP_SWIZZLE_128B ? PROM_A : PROM_B), CU_TENSOR_MAP_FLOAT_OOB_FILL_NONE);
}

}

extern "C" void kernel_launch(void* const* d_in, const int* in_sizes, int n_in, void* d_out, int out_size) {
  (void)in_sizes; (void)n_in; (void)out_size;
  Params p;
  typedef const __nv_bfloat16* BP;
  p.x = (BP)d_in[0]; p.lre = (BP)d_in[1]; p.lim = (BP)d_in[2]; p.bre = (BP)d_in[3]; p.bim = (BP)d_in[4];
  p.cre = (BP)d_in[5]; p.cim = (BP)d_in[6]; p.logdt = (BP)d_in[7]; p.dskip = (BP)d_in[8];
  p.k = (BP)d_in[10]; p.v = (BP)d_in[11]; p.shiftk = (BP)d_in[12]; p.ssmk = (BP)d_in[13]; p.ssmD = (BP)d_in[14];
  p.out = (float*)d_out;
  for (int sm = 0; sm < 132; sm++) {
    const int tpc = sm >> 1, side = sm & 1;
    int gpc, gi;
    if (tpc < 32) { gpc = tpc & 7; gi = tpc >> 3; }
    else if (tpc < 60) { gpc = 1 + (tpc - 32) % 7; gi = 4 + (tpc - 32) / 7; }
    else if (tpc < 62) { gpc = tpc - 54; gi = 8; }
    else { gpc = 0; gi = tpc - 58; }
    const int pos = 8 * gpc + gi + (gpc == 7 ? 1 : 0);
    int T1, GP;
    if (pos < 52) { const int hh = pos / 26, x = pos - 26 * hh; T1 = x >> 1; GP = 2 * hh + (x & 1); }
    else { T1 = pos - 52; GP = 4; }
    const int m2 = 8 * (gpc >> 1) + gi, dg = 2 * (gpc & 1) + side;
    p.role[sm] = pos == 65 ? -1 : (T1 | (GP << 4) | (side << 7) | (m2 << 8) | (dg << 14) | ((gi < 8) << 16));
  }
  void* fnp = nullptr;
  cudaDriverEntryPointQueryResult qr;
  cudaGetDriverEntryPoint("cuTensorMapEncodeTiled", &fnp, cudaEnableDefault, &qr);
  EncFn fn = (EncFn)fnp;
  void* gG = nullptr;
  cudaGetSymbolAddress(&gG, g_G);
  const cuuint64_t RB = DM * 2;
  {
    p.swap = p.bim < p.bre;
    const char* lo = (const char*)(p.swap ? p.bim : p.bre); const char* hi = (const char*)(p.swap ? p.bre : p.bim);
    cuuint64_t dims[5] = {640, 8, 2, 8, 10}, st[4] = {RB, (cuuint64_t)(hi - lo), 8 * RB, 64 * RB}; cuuint32_t box[5] = {64, 8, 2, 4, 2};
    encode(fn, &p.mB, lo, 5, dims, st, box);
  }
  {
    cuuint64_t dims[5] = {640, 2, 4, 2, 40}, st[4] = {RB, 4 * RB, 2 * RB, 16 * RB}; cuuint32_t box[5] = {64, 2, 4, 2, 10};
    encode(fn, &p.mCre, p.cre, 5, dims, st, box); encode(fn, &p.mCim, p.cim, 5, dims, st, box);
    cuuint64_t dimg[5] = {2048, 2, 4, 2, 40}, stg[4] = {4096, 4 * 4096, 2 * 4096, 16 * 4096};
    encode(fn, &p.mG, gG, 5, dimg, stg, box);
  }
  {
    cuuint64_t dims[4] = {640, 2, 4, 900}, st[3] = {RB, 40 * RB, 2 * RB}; cuuint32_t box[4] = {64, 2, 4, 20};
    encode(fn, &p.mX, p.x, 4, dims, st, box);
    cuuint64_t diml[4] = {640, 2, 4, 16}, stl[3] = {RB, 32 * RB, 2 * RB};
    encode(fn, &p.mXl, p.x + (size_t)1920 * DM, 4, diml, stl, box);
    cuuint32_t boxt[4] = {160, 2, 4, 4};
    encode(fn, &p.mXt, p.x, 4, dims, st, boxt, CU_TENSOR_MAP_SWIZZLE_NONE);
    encode(fn, &p.mXtl, p.x + (size_t)1920 * DM, 4, diml, stl, boxt, CU_TENSOR_MAP_SWIZZLE_NONE);
    cuuint64_t dk[3] = {640, 2000, 4}, sk[2] = {RB, 16 * RB}; cuuint32_t bk[3] = {32, 19, 4}, bv[3] = {32, 17, 4};
    encode(fn, &p.mK, p.k, 3, dk, sk, bk, CU_TENSOR_MAP_SWIZZLE_NONE);
    encode(fn, &p.mV, p.v, 3, dk, sk, bv, CU_TENSOR_MAP_SWIZZLE_NONE);
  }
  cudaFuncSetAttribute(fused_kernel, cudaFuncAttributeMaxDynamicSharedMemorySize, SMEM_BYTES);
  cudaLaunchConfig_t cfg = {};
  cfg.gridDim = dim3(132); cfg.blockDim = dim3(512); cfg.dynamicSmemBytes = SMEM_BYTES; cfg.stream = cudaStreamPerThread;
  cudaLaunchKernelEx(&cfg, fused_kernel, p);
}
```

```cpp
#include <cuda_runtime.h>
#include <cuda.h>
#include <cuda_bf16.h>
#include <stdint.h>

namespace {

constexpr int SEQ = 2048, DM = 640;
constexpr int NT1 = 13;
#define EXP 0
#define WPF1 3
#define WPF2 7
#define CPOLL 10
#define KV0 5
#define TAP0 2
#define PROM_A 2
#define PROM_B 2
#define XFIRST 0
#define TAPLATE 1
#define STG_D 3
#define STG_KK 1
#define HOLD0 1
#define WREL 0
#define UREL 1
#define TSL 1
#define TABW 0
#define STG0 3
#define PAUSE_K 4
constexpr uint32_t SPIN_LIMIT = 1u << 22;

__device__ __align__(1024) uint8_t g_h[2 * 32 * 20 * 8192];
__device__ __align__(1024) uint8_t g_u[NT1 * 10 * 20480];
__device__ __align__(1024) uint8_t g_kv[DM * 4096];
__device__ __align__(1024) uint8_t g_G[DM * 4096];
__device__ __align__(128) uint4 g_E[2 * NT1 * DM];
__device__ __align__(128) uint4 g_stats[4 * 4 * SEQ];
__device__ __align__(128) uint4 g_sB[DM * 2];
__device__ __align__(128) unsigned g_hflag[2 * NT1 * 2 * 16 * 8];
__device__ __align__(128) unsigned g_uflag[32 * 4 * 8];
__device__ __align__(128) unsigned g_kvflag[4 * 32 * 8];
__device__ __align__(128) unsigned g_gflag[4 * 32 * 8];
__device__ __align__(128) unsigned g_epoch[32] = {1};
#define TS(i) do {} while (0)

struct Params {
  CUtensorMap mB, mCre, mCim, mX, mXl, mG, mK, mV, mXt, mXtl;
  const __nv_bfloat16 *x, *lre, *lim, *bre, *bim, *cre, *cim, *logdt, *dskip, *k, *v, *shiftk, *ssmk, *ssmD;
  float* out;
  int swap;
  int role[132];
};

constexpr uint32_t sb = 1024;
constexpr uint32_t G1_STAGE = 36864, G1_XOFF = 16384;
constexpr int S1 = 4;
constexpr uint32_t XT_OFF = 159744, KS_OFF = 180224, KV_PIECE = 9216;
constexpr uint32_t G2_XB = 8192, G2_WB = 20480, G2_WOFF = 57344, G_OFF = 200704;
constexpr int S2 = 7;
constexpr uint32_t CV_OFF = KS_OFF, CV_K = 128, CV_PL = 2240, CV_U = CV_K + 4096, CV_B = KV_PIECE;
constexpr uint32_t MISC = 226304;
constexpr uint32_t BAR_OFF = MISC;
constexpr int B_G1FULL = 0, B_G1DONE = 20, B_G2FULL = 40, B_CVFULL = 80  ,
              B_G2DONE = 85, B_GFULL = 125, B_EP = 126, B_H1 = 127  , B_STG = 134  , B_REL = 136  , B_SFREE = 138,
              B_GO = 139  , B_PUB = 147,
              B_CVDONE = 148  , B_STAB = 153  , B_XFREE = 155, B_HST = 156  ,
              B_CTAB = 160, B_PREP = 161, B_XT = 162, B_KV = 163  ;
constexpr uint32_t bars = sb + BAR_OFF;
constexpr uint32_t STAB_OFF = MISC + 1344;
constexpr uint32_t CTAB_OFF = STAB_OFF + 1280;
constexpr uint32_t DTAB_OFF = CTAB_OFF + 1536;
constexpr uint32_t EP_OFF = DTAB_OFF + 320;
constexpr uint32_t SO_OFF = EP_OFF + 32;
constexpr uint32_t TAP_OFF = 147456;
constexpr uint32_t SMEM_BYTES = 232448;
static_assert(SO_OFF + 1536 <= SMEM_BYTES, "smem");

__device__ __forceinline__ void trap_if(bool c) { asm volatile("{\n.reg .pred p;\nsetp.ne.u32 p, %0, 0;\n@p trap;\n}\n" ::"r"((uint32_t)c)); }
__device__ __forceinline__ uint32_t smem_u32(const void* p) { return (uint32_t)__cvta_generic_to_shared(p); }
__device__ __forceinline__ void mbar_init(uint32_t bar, int cnt) { asm volatile("mbarrier.init.shared::cta.b64 [%0], %1;" ::"r"(bar), "r"(cnt) : "memory"); }
__device__ __forceinline__ void mbar_expect_tx(uint32_t bar, int bytes) { asm volatile("mbarrier.arrive.expect_tx.shared::cta.b64 _, [%0], %1;" ::"r"(bar), "r"(bytes) : "memory"); }
__device__ __forceinline__ void mbar_arrive(uint32_t bar) { asm volatile("mbarrier.arrive.shared::cta.b64 _, [%0];" ::"r"(bar) : "memory"); }
__device__ __forceinline__ void mbar_wait(uint32_t bar) {
  asm volatile(
      "{\n.reg .pred p;\n.reg .u32 c;\nmov.u32 c, 0;\n"
      "W_%=:\nmbarrier.try_wait.parity.shared::cta.b64 p, [%0], 0;\n@p bra D_%=;\n"
      "add.u32 c, c, 1;\nsetp.lt.u32 p, c, %1;\n@p bra W_%=;\ntrap;\nD_%=:\n}\n" ::"r"(bar), "n"(SPIN_LIMIT) : "memory");
}
__device__ __forceinline__ uint32_t mbar_test(uint32_t bar) {
  uint32_t ok;
  asm volatile("{\n.reg .pred p;\nmbarrier.test_wait.parity.shared::cta.b64 p, [%1], 0;\nselp.u32 %0, 1, 0, p;\n}\n" : "=r"(ok) : "r"(bar) : "memory");
  return ok;
}
__device__ __forceinline__ void tma3(uint32_t dst, const CUtensorMap* m, int c0, int c1, int c2, uint32_t bar) {
  asm volatile("cp.async.bulk.tensor.3d.shared::cluster.global.mbarrier::complete_tx::bytes [%0], [%1, {%3,%4,%5}], [%2];"
               ::"r"(dst), "l"(m), "r"(bar), "r"(c0), "r"(c1), "r"(c2) : "memory");
}
__device__ __forceinline__ void tma4(uint32_t dst, const CUtensorMap* m, int c0, int c1, int c2, int c3, uint32_t bar) {
  asm volatile("cp.async.bulk.tensor.4d.shared::cluster.global.mbarrier::complete_tx::bytes [%0], [%1, {%3,%4,%5,%6}], [%2];"
               ::"r"(dst), "l"(m), "r"(bar), "r"(c0), "r"(c1), "r"(c2), "r"(c3) : "memory");
}
__device__ __forceinline__ void tma5(uint32_t dst, const CUtensorMap* m, int c0, int c1, int c2, int c3, int c4, uint32_t bar) {
  asm volatile("cp.async.bulk.tensor.5d.shared::cluster.global.mbarrier::complete_tx::bytes [%0], [%1, {%3,%4,%5,%6,%7}], [%2];"
               ::"r"(dst), "l"(m), "r"(bar), "r"(c0), "r"(c1), "r"(c2), "r"(c3), "r"(c4) : "memory");
}
__device__ __forceinline__ void bulk_g2s(uint32_t dst, const void* src, int bytes, uint32_t bar) {
  asm volatile("cp.async.bulk.shared::cluster.global.mbarrier::complete_tx::bytes [%0], [%1], %2, [%3];"
               ::"r"(dst), "l"(src), "r"(bytes), "r"(bar) : "memory");
}
__device__ __forceinline__ void bulk_s2g(void* dst, uint32_t src, int bytes) {
  asm volatile("cp.async.bulk.global.shared::cta.bulk_group [%0], [%1], %2;" ::"l"(dst), "r"(src), "r"(bytes) : "memory");
}
__device__ __forceinline__ void l2_prefetch(const void* src, int bytes) {
  asm volatile("cp.async.bulk.prefetch.L2.global [%0], %1;" ::"l"(src), "r"(bytes) : "memory");
}
__device__ __forceinline__ void wgmma_fence() { asm volatile("wgmma.fence.sync.aligned;" ::: "memory"); }
__device__ __forceinline__ void wgmma_commit() { asm volatile("wgmma.commit_group.sync.aligned;" ::: "memory"); }
template <int N> __device__ __forceinline__ void wgmma_wait() { asm volatile("wgmma.wait_group.sync.aligned %0;" ::"n"(N) : "memory"); }
__host__ __device__ constexpr uint32_t desc_lo(uint32_t addr, uint32_t lbo) { return ((addr & 0x3FFFF) >> 4) | ((lbo >> 4) << 16); }
__host__ __device__ constexpr uint32_t desc_hi(uint32_t sbo, uint32_t swz) { return (sbo >> 4) | (swz << 30); }
__device__ __forceinline__ void bar_sync(int id, int n) { asm volatile("bar.sync %0, %1;" ::"r"(id), "r"(n) : "memory"); }
__device__ __forceinline__ uint32_t lds32(uint32_t a) { uint32_t v; asm volatile("ld.shared.u32 %0, [%1];" : "=r"(v) : "r"(a) : "memory"); return v; }
__device__ __forceinline__ float2 lds64f(uint32_t a) { float2 v; asm volatile("ld.shared.v2.f32 {%0,%1}, [%2];" : "=f"(v.x), "=f"(v.y) : "r"(a) : "memory"); return v; }
__device__ __forceinline__ float4 lds128f(uint32_t a) { float4 v; asm volatile("ld.shared.v4.f32 {%0,%1,%2,%3}, [%4];" : "=f"(v.x), "=f"(v.y), "=f"(v.z), "=f"(v.w) : "r"(a) : "memory"); return v; }
__device__ __forceinline__ void ldsm4t(uint32_t (&r)[4], uint32_t a) {
  asm volatile("ldmatrix.sync.aligned.m8n8.x4.trans.shared.b16 {%0,%1,%2,%3}, [%4];" : "=r"(r[0]), "=r"(r[1]), "=r"(r[2]), "=r"(r[3]) : "r"(a) : "memory");
}
__device__ __forceinline__ uint4 ldv128(const void* a) { uint4 v; asm volatile("ld.global.nc.v4.u32 {%0,%1,%2,%3}, [%4];" : "=r"(v.x), "=r"(v.y), "=r"(v.z), "=r"(v.w) : "l"(a) : "memory"); return v; }
__device__ __forceinline__ uint2 ldv64(const void* a) { uint2 v; asm volatile("ld.global.nc.v2.u32 {%0,%1}, [%2];" : "=r"(v.x), "=r"(v.y) : "l"(a) : "memory"); return v; }
__device__ __forceinline__ uint32_t ldv16(const void* a) { uint32_t v; asm volatile("ld.global.nc.u16 %0, [%1];" : "=r"(v) : "l"(a) : "memory"); return v; }
__device__ __forceinline__ void sts128(uint32_t a, uint4 v) { asm volatile("st.shared.v4.u32 [%0], {%1,%2,%3,%4};" ::"r"(a), "r"(v.x), "r"(v.y), "r"(v.z), "r"(v.w) : "memory"); }
__device__ __forceinline__ void sts32(uint32_t a, uint32_t v) { asm volatile("st.shared.u32 [%0], %1;" ::"r"(a), "r"(v) : "memory"); }
__device__ __forceinline__ void sts64f(uint32_t a, float x, float y) { asm volatile("st.shared.v2.f32 [%0], {%1,%2};" ::"r"(a), "f"(x), "f"(y) : "memory"); }
__device__ __forceinline__ void st_rel(unsigned* p, unsigned v) { asm volatile("st.release.gpu.global.u32 [%0], %1;" ::"l"(p), "r"(v) : "memory"); }
__device__ __forceinline__ void fence_async_global() { asm volatile("fence.proxy.async.global;" ::: "memory"); }
__device__ __forceinline__ void fence_async_smem() { asm volatile("fence.proxy.async.shared::cta;" ::: "memory"); }
__device__ __forceinline__ void rec_st(uint4* p, float a, float b, unsigned tag) {
  asm volatile("{\n.reg .b128 t;\n.reg .b64 lo, hi;\nmov.b64 lo, {%1,%2};\nmov.b64 hi, {%3,%3};\nmov.b128 t, {lo,hi};\n"
               "st.relaxed.gpu.global.b128 [%0], t;\n}\n" ::"l"(p), "r"(__float_as_uint(a)), "r"(__float_as_uint(b)), "r"(tag) : "memory");
}
__device__ __forceinline__ unsigned rec_ld(const uint4* p, float& a, float& b) {
  unsigned x, y, t;
  asm volatile("{\n.reg .b128 t;\n.reg .b64 lo, hi;\n.reg .b32 u;\nld.relaxed.gpu.global.b128 t, [%3];\nmov.b128 {lo,hi}, t;\n"
               "mov.b64 {%0,%1}, lo;\nmov.b64 {%2,u}, hi;\n}\n" : "=r"(x), "=r"(y), "=r"(t) : "l"(p) : "memory");
  a = __uint_as_float(x); b = __uint_as_float(y);
  return t;
}
__device__ __forceinline__ unsigned ld_rlx(const unsigned* p) { unsigned v; asm volatile("ld.relaxed.gpu.global.u32 %0, [%1];" : "=r"(v) : "l"(p) : "memory"); return v; }
__device__ __forceinline__ void flag_poll(const unsigned* p, unsigned target) {
  uint32_t it = 0;
  while (!__all_sync(0xffffffffu, (int)(ld_rlx(p) - target) >= 0)) { trap_if(++it > SPIN_LIMIT); }
  asm volatile("fence.acquire.gpu;" ::: "memory");
}
__device__ __forceinline__ uint32_t pack_bf16(float lo, float hi) {
  uint32_t r; asm("cvt.rn.bf16x2.f32 %0, %1, %2;" : "=r"(r) : "f"(hi), "f"(lo)); return r;
}
__device__ __forceinline__ float bf_lo(uint32_t w) { return __uint_as_float(w << 16); }
__device__ __forceinline__ float bf_hi(uint32_t w) { return __uint_as_float(w & 0xffff0000u); }
__device__ __forceinline__ uint32_t hmul2(uint32_t a, uint32_t b) {
  __nv_bfloat162 r = __hmul2_rn(*(__nv_bfloat162*)&a, *(__nv_bfloat162*)&b); return *(uint32_t*)&r;
}
__device__ __forceinline__ uint32_t hadd2(uint32_t a, uint32_t b) {
  __nv_bfloat162 r = __hadd2_rn(*(__nv_bfloat162*)&a, *(__nv_bfloat162*)&b); return *(uint32_t*)&r;
}
__device__ __forceinline__ float2 cmul(float2 a, float2 b) { return make_float2(a.x * b.x - a.y * b.y, a.x * b.y + a.y * b.x); }
__device__ __forceinline__ float2 cfma(float2 a, float2 b, float2 c) {
  return make_float2(fmaf(a.x, b.x, fmaf(-a.y, b.y, c.x)), fmaf(a.x, b.y, fmaf(a.y, b.x, c.y)));
}
template <int N> __device__ __forceinline__ void fence_regs(float (&a)[N]) {
#pragma unroll
  for (int i = 0; i < N; i++) asm volatile("" : "+f"(a[i])::"memory");
}
__device__ __forceinline__ bool elect_one() {
  uint32_t e; asm volatile("{\n.reg .pred P;\nelect.sync _|P, 0xffffffff;\nselp.u32 %0, 1, 0, P;\n}\n" : "=r"(e)); return e != 0;
}
__device__ __forceinline__ int tid_opaque() { int t; asm volatile("mov.u32 %0, %%tid.x;" : "=r"(t)); return t; }
struct Role { int T1, GP, side, m2, dg, cch0; bool last, has2; };
__device__ __forceinline__ Role unpack_role(int x) {
  Role r; r.T1 = x & 15; r.GP = (x >> 4) & 7; r.side = (x >> 7) & 1; r.m2 = (x >> 8) & 63; r.dg = (x >> 14) & 3;
  r.has2 = (x >> 16) & 1; r.last = r.T1 == NT1 - 1; r.cch0 = 160 * r.dg + r.m2; return r;
}
__device__ __forceinline__ Role fresh_role(int x) { asm volatile("" : "+r"(x)); return unpack_role(__shfl_sync(0xffffffffu, x, 0)); }
#define ROLE(x) const Role R_ = fresh_role(x); const int T1 = R_.T1, GP = R_.GP, side = R_.side, m2 = R_.m2, dg = R_.dg, cch0 = R_.cch0; \
  const bool last = R_.last, has2 = R_.has2; (void)T1; (void)GP; (void)side; (void)m2; (void)dg; (void)cch0; (void)last; (void)has2;
__device__ __forceinline__ int n_to_t(int n) {
  int T = n / 160, nl = n - T * 160;
  int L = (T == NT1 - 1) ? 32 : 40;
  return T * 160 + L * ((nl & 7) >> 1) + 2 * (nl >> 3) + (nl & 1);
}

template<int TA> __device__ __forceinline__ void wgmma_n160(float (&d)[80], uint32_t alo, uint32_t ahi, uint32_t blo, uint32_t bhi){
  asm volatile("{\n.reg .b64 da, db;\nmov.b64 da, {%80,%81};\nmov.b64 db, {%82,%83};\n"
    "wgmma.mma_async.sync.aligned.m64n160k16.f32.bf16.bf16 {%0, %1, %2, %3, %4, %5, %6, %7, %8, %9, %10, %11, %12, %13, %14, %15, %16, %17, %18, %19, %20, %21, %22, %23, %24, %25, %26, %27, %28, %29, %30, %31, %32, %33, %34, %35, %36, %37, %38, %39, %40, %41, %42, %43, %44, %45, %46, %47, %48, %49, %50, %51, %52, %53, %54, %55, %56, %57, %58, %59, %60, %61, %62, %63, %64, %65, %66, %67, %68, %69, %70, %71, %72, %73, %74, %75, %76, %77, %78, %79}, da, db, 1, 1, 1, %84, 0;\n}\n"
    : "+f"(d[0]), "+f"(d[1]), "+f"(d[2]), "+f"(d[3]), "+f"(d[4]), "+f"(d[5]), "+f"(d[6]), "+f"(d[7]), "+f"(d[8]), "+f"(d[9]), "+f"(d[10]), "+f"(d[11]), "+f"(d[12]), "+f"(d[13]), "+f"(d[14]), "+f"(d[15]), "+f"(d[16]), "+f"(d[17]), "+f"(d[18]), "+f"(d[19]), "+f"(d[20]), "+f"(d[21]), "+f"(d[22]), "+f"(d[23]), "+f"(d[24]), "+f"(d[25]), "+f"(d[26]), "+f"(d[27]), "+f"(d[28]), "+f"(d[29]), "+f"(d[30]), "+f"(d[31]), "+f"(d[32]), "+f"(d[33]), "+f"(d[34]), "+f"(d[35]), "+f"(d[36]), "+f"(d[37]), "+f"(d[38]), "+f"(d[39]), "+f"(d[40]), "+f"(d[41]), "+f"(d[42]), "+f"(d[43]), "+f"(d[44]), "+f"(d[45]), "+f"(d[46]), "+f"(d[47]), "+f"(d[48]), "+f"(d[49]), "+f"(d[50]), "+f"(d[51]), "+f"(d[52]), "+f"(d[53]), "+f"(d[54]), "+f"(d[55]), "+f"(d[56]), "+f"(d[57]), "+f"(d[58]), "+f"(d[59]), "+f"(d[60]), "+f"(d[61]), "+f"(d[62]), "+f"(d[63]), "+f"(d[64]), "+f"(d[65]), "+f"(d[66]), "+f"(d[67]), "+f"(d[68]), "+f"(d[69]), "+f"(d[70]), "+f"(d[71]), "+f"(d[72]), "+f"(d[73]), "+f"(d[74]), "+f"(d[75]), "+f"(d[76]), "+f"(d[77]), "+f"(d[78]), "+f"(d[79])
    : "r"(alo), "r"(ahi), "r"(blo), "r"(bhi), "n"(TA));
}
template<int N> __device__ __forceinline__ void wgmma_rs_hi(float (&d)[64], uint32_t a0, uint32_t a1, uint32_t a2, uint32_t a3, uint32_t blo);
template<> __device__ __forceinline__ void wgmma_rs_hi<16>(float (&d)[64], uint32_t a0, uint32_t a1, uint32_t a2, uint32_t a3, uint32_t blo){
  asm volatile("{\n.reg .b64 db;\nmov.b64 db, {%12,8};\nwgmma.mma_async.sync.aligned.m64n16k16.f32.bf16.bf16 {%0, %1, %2, %3, %4, %5, %6, %7}, {%8,%9,%10,%11}, db, 1, 1, 1, 0;\n}\n"
    : "+f"(d[56]), "+f"(d[57]), "+f"(d[58]), "+f"(d[59]), "+f"(d[60]), "+f"(d[61]), "+f"(d[62]), "+f"(d[63])
    : "r"(a0), "r"(a1), "r"(a2), "r"(a3), "r"(blo));
}
template<> __device__ __forceinline__ void wgmma_rs_hi<32>(float (&d)[64], uint32_t a0, uint32_t a1, uint32_t a2, uint32_t a3, uint32_t blo){
  asm volatile("{\n.reg .b64 db;\nmov.b64 db, {%20,8};\nwgmma.mma_async.sync.aligned.m64n32k16.f32.bf16.bf16 {%0, %1, %2, %3, %4, %5, %6, %7, %8, %9, %10, %11, %12, %13, %14, %15}, {%16,%17,%18,%19}, db, 1, 1, 1, 0;\n}\n"
    : "+f"(d[48]), "+f"(d[49]), "+f"(d[50]), "+f"(d[51]), "+f"(d[52]), "+f"(d[53]), "+f"(d[54]), "+f"(d[55]), "+f"(d[56]), "+f"(d[57]), "+f"(d[58]), "+f"(d[59]), "+f"(d[60]), "+f"(d[61]), "+f"(d[62]), "+f"(d[63])
    : "r"(a0), "r"(a1), "r"(a2), "r"(a3), "r"(blo));
}
template<> __device__ __forceinline__ void wgmma_rs_hi<48>(float (&d)[64], uint32_t a0, uint32_t a1, uint32_t a2, uint32_t a3, uint32_t blo){
  asm volatile("{\n.reg .b64 db;\nmov.b64 db, {%28,8};\nwgmma.mma_async.sync.aligned.m64n48k16.f32.bf16.bf16 {%0, %1, %2, %3, %4, %5, %6, %7, %8, %9, %10, %11, %12, %13, %14, %15, %16, %17, %18, %19, %20, %21, %22, %23}, {%24,%25,%26,%27}, db, 1, 1, 1, 0;\n}\n"
    : "+f"(d[40]), "+f"(d[41]), "+f"(d[42]), "+f"(d[43]), "+f"(d[44]), "+f"(d[45]), "+f"(d[46]), "+f"(d[47]), "+f"(d[48]), "+f"(d[49]), "+f"(d[50]), "+f"(d[51]), "+f"(d[52]), "+f"(d[53]), "+f"(d[54]), "+f"(d[55]), "+f"(d[56]), "+f"(d[57]), "+f"(d[58]), "+f"(d[59]), "+f"(d[60]), "+f"(d[61]), "+f"(d[62]), "+f"(d[63])
    : "r"(a0), "r"(a1), "r"(a2), "r"(a3), "r"(blo));
}
template<> __device__ __forceinline__ void wgmma_rs_hi<64>(float (&d)[64], uint32_t a0, uint32_t a1, uint32_t a2, uint32_t a3, uint32_t blo){
  asm volatile("{\n.reg .b64 db;\nmov.b64 db, {%36,8};\nwgmma.mma_async.sync.aligned.m64n64k16.f32.bf16.bf16 {%0, %1, %2, %3, %4, %5, %6, %7, %8, %9, %10, %11, %12, %13, %14, %15, %16, %17, %18, %19, %20, %21, %22, %23, %24, %25, %26, %27, %28, %29, %30, %31}, {%32,%33,%34,%35}, db, 1, 1, 1, 0;\n}\n"
    : "+f"(d[32]), "+f"(d[33]), "+f"(d[34]), "+f"(d[35]), "+f"(d[36]), "+f"(d[37]), "+f"(d[38]), "+f"(d[39]), "+f"(d[40]), "+f"(d[41]), "+f"(d[42]), "+f"(d[43]), "+f"(d[44]), "+f"(d[45]), "+f"(d[46]), "+f"(d[47]), "+f"(d[48]), "+f"(d[49]), "+f"(d[50]), "+f"(d[51]), "+f"(d[52]), "+f"(d[53]), "+f"(d[54]), "+f"(d[55]), "+f"(d[56]), "+f"(d[57]), "+f"(d[58]), "+f"(d[59]), "+f"(d[60]), "+f"(d[61]), "+f"(d[62]), "+f"(d[63])
    : "r"(a0), "r"(a1), "r"(a2), "r"(a3), "r"(blo));
}
template<> __device__ __forceinline__ void wgmma_rs_hi<80>(float (&d)[64], uint32_t a0, uint32_t a1, uint32_t a2, uint32_t a3, uint32_t blo){
  asm volatile("{\n.reg .b64 db;\nmov.b64 db, {%44,8};\nwgmma.mma_async.sync.aligned.m64n80k16.f32.bf16.bf16 {%0, %1, %2, %3, %4, %5, %6, %7, %8, %9, %10, %11, %12, %13, %14, %15, %16, %17, %18, %19, %20, %21, %22, %23, %24, %25, %26, %27, %28, %29, %30, %31, %32, %33, %34, %35, %36, %37, %38, %39}, {%40,%41,%42,%43}, db, 1, 1, 1, 0;\n}\n"
    : "+f"(d[24]), "+f"(d[25]), "+f"(d[26]), "+f"(d[27]), "+f"(d[28]), "+f"(d[29]), "+f"(d[30]), "+f"(d[31]), "+f"(d[32]), "+f"(d[33]), "+f"(d[34]), "+f"(d[35]), "+f"(d[36]), "+f"(d[37]), "+f"(d[38]), "+f"(d[39]), "+f"(d[40]), "+f"(d[41]), "+f"(d[42]), "+f"(d[43]), "+f"(d[44]), "+f"(d[45]), "+f"(d[46]), "+f"(d[47]), "+f"(d[48]), "+f"(d[49]), "+f"(d[50]), "+f"(d[51]), "+f"(d[52]), "+f"(d[53]), "+f"(d[54]), "+f"(d[55]), "+f"(d[56]), "+f"(d[57]), "+f"(d[58]), "+f"(d[59]), "+f"(d[60]), "+f"(d[61]), "+f"(d[62]), "+f"(d[63])
    : "r"(a0), "r"(a1), "r"(a2), "r"(a3), "r"(blo));
}
template<> __device__ __forceinline__ void wgmma_rs_hi<96>(float (&d)[64], uint32_t a0, uint32_t a1, uint32_t a2, uint32_t a3, uint32_t blo){
  asm volatile("{\n.reg .b64 db;\nmov.b64 db, {%52,8};\nwgmma.mma_async.sync.aligned.m64n96k16.f32.bf16.bf16 {%0, %1, %2, %3, %4, %5, %6, %7, %8, %9, %10, %11, %12, %13, %14, %15, %16, %17, %18, %19, %20, %21, %22, %23, %24, %25, %26, %27, %28, %29, %30, %31, %32, %33, %34, %35, %36, %37, %38, %39, %40, %41, %42, %43, %44, %45, %46, %47}, {%48,%49,%50,%51}, db, 1, 1, 1, 0;\n}\n"
    : "+f"(d[16]), "+f"(d[17]), "+f"(d[18]), "+f"(d[19]), "+f"(d[20]), "+f"(d[21]), "+f"(d[22]), "+f"(d[23]), "+f"(d[24]), "+f"(d[25]), "+f"(d[26]), "+f"(d[27]), "+f"(d[28]), "+f"(d[29]), "+f"(d[30]), "+f"(d[31]), "+f"(d[32]), "+f"(d[33]), "+f"(d[34]), "+f"(d[35]), "+f"(d[36]), "+f"(d[37]), "+f"(d[38]), "+f"(d[39]), "+f"(d[40]), "+f"(d[41]), "+f"(d[42]), "+f"(d[43]), "+f"(d[44]), "+f"(d[45]), "+f"(d[46]), "+f"(d[47]), "+f"(d[48]), "+f"(d[49]), "+f"(d[50]), "+f"(d[51]), "+f"(d[52]), "+f"(d[53]), "+f"(d[54]), "+f"(d[55]), "+f"(d[56]), "+f"(d[57]), "+f"(d[58]), "+f"(d[59]), "+f"(d[60]), "+f"(d[61]), "+f"(d[62]), "+f"(d[63])
    : "r"(a0), "r"(a1), "r"(a2), "r"(a3), "r"(blo));
}
template<> __device__ __forceinline__ void wgmma_rs_hi<112>(float (&d)[64], uint32_t a0, uint32_t a1, uint32_t a2, uint32_t a3, uint32_t blo){
  asm volatile("{\n.reg .b64 db;\nmov.b64 db, {%60,8};\nwgmma.mma_async.sync.aligned.m64n112k16.f32.bf16.bf16 {%0, %1, %2, %3, %4, %5, %6, %7, %8, %9, %10, %11, %12, %13, %14, %15, %16, %17, %18, %19, %20, %21, %22, %23, %24, %25, %26, %27, %28, %29, %30, %31, %32, %33, %34, %35, %36, %37, %38, %39, %40, %41, %42, %43, %44, %45, %46, %47, %48, %49, %50, %51, %52, %53, %54, %55}, {%56,%57,%58,%59}, db, 1, 1, 1, 0;\n}\n"
    : "+f"(d[8]), "+f"(d[9]), "+f"(d[10]), "+f"(d[11]), "+f"(d[12]), "+f"(d[13]), "+f"(d[14]), "+f"(d[15]), "+f"(d[16]), "+f"(d[17]), "+f"(d[18]), "+f"(d[19]), "+f"(d[20]), "+f"(d[21]), "+f"(d[22]), "+f"(d[23]), "+f"(d[24]), "+f"(d[25]), "+f"(d[26]), "+f"(d[27]), "+f"(d[28]), "+f"(d[29]), "+f"(d[30]), "+f"(d[31]), "+f"(d[32]), "+f"(d[33]), "+f"(d[34]), "+f"(d[35]), "+f"(d[36]), "+f"(d[37]), "+f"(d[38]), "+f"(d[39]), "+f"(d[40]), "+f"(d[41]), "+f"(d[42]), "+f"(d[43]), "+f"(d[44]), "+f"(d[45]), "+f"(d[46]), "+f"(d[47]), "+f"(d[48]), "+f"(d[49]), "+f"(d[50]), "+f"(d[51]), "+f"(d[52]), "+f"(d[53]), "+f"(d[54]), "+f"(d[55]), "+f"(d[56]), "+f"(d[57]), "+f"(d[58]), "+f"(d[59]), "+f"(d[60]), "+f"(d[61]), "+f"(d[62]), "+f"(d[63])
    : "r"(a0), "r"(a1), "r"(a2), "r"(a3), "r"(blo));
}
template<> __device__ __forceinline__ void wgmma_rs_hi<128>(float (&d)[64], uint32_t a0, uint32_t a1, uint32_t a2, uint32_t a3, uint32_t blo){
  asm volatile("{\n.reg .b64 db;\nmov.b64 db, {%68,8};\nwgmma.mma_async.sync.aligned.m64n128k16.f32.bf16.bf16 {%0, %1, %2, %3, %4, %5, %6, %7, %8, %9, %10, %11, %12, %13, %14, %15, %16, %17, %18, %19, %20, %21, %22, %23, %24, %25, %26, %27, %28, %29, %30, %31, %32, %33, %34, %35, %36, %37, %38, %39, %40, %41, %42, %43, %44, %45, %46, %47, %48, %49, %50, %51, %52, %53, %54, %55, %56, %57, %58, %59, %60, %61, %62, %63}, {%64,%65,%66,%67}, db, 1, 1, 1, 0;\n}\n"
    : "+f"(d[0]), "+f"(d[1]), "+f"(d[2]), "+f"(d[3]), "+f"(d[4]), "+f"(d[5]), "+f"(d[6]), "+f"(d[7]), "+f"(d[8]), "+f"(d[9]), "+f"(d[10]), "+f"(d[11]), "+f"(d[12]), "+f"(d[13]), "+f"(d[14]), "+f"(d[15]), "+f"(d[16]), "+f"(d[17]), "+f"(d[18]), "+f"(d[19]), "+f"(d[20]), "+f"(d[21]), "+f"(d[22]), "+f"(d[23]), "+f"(d[24]), "+f"(d[25]), "+f"(d[26]), "+f"(d[27]), "+f"(d[28]), "+f"(d[29]), "+f"(d[30]), "+f"(d[31]), "+f"(d[32]), "+f"(d[33]), "+f"(d[34]), "+f"(d[35]), "+f"(d[36]), "+f"(d[37]), "+f"(d[38]), "+f"(d[39]), "+f"(d[40]), "+f"(d[41]), "+f"(d[42]), "+f"(d[43]), "+f"(d[44]), "+f"(d[45]), "+f"(d[46]), "+f"(d[47]), "+f"(d[48]), "+f"(d[49]), "+f"(d[50]), "+f"(d[51]), "+f"(d[52]), "+f"(d[53]), "+f"(d[54]), "+f"(d[55]), "+f"(d[56]), "+f"(d[57]), "+f"(d[58]), "+f"(d[59]), "+f"(d[60]), "+f"(d[61]), "+f"(d[62]), "+f"(d[63])
    : "r"(a0), "r"(a1), "r"(a2), "r"(a3), "r"(blo));
}

__device__ __forceinline__ float shfl_sel(float a, float b, bool p, int src) {
  float r;
  asm volatile("{\n.reg .pred P;\n.reg .f32 t;\nsetp.ne.u32 P, %3, 0;\nselp.f32 t, %1, %2, P;\nshfl.sync.idx.b32 %0, t, %4, 0x1f, 0xffffffff;\n}\n"
               : "=f"(r) : "f"(a), "f"(b), "r"((uint32_t)p), "r"(src));
  return r;
}
struct CvCtx {
  uint32_t koff, zero, so[3];
  int srcA, srcB;
  bool wrapA, s3, kodd;
};
struct CvPipe { float Ep[2], keep[2], send[2]; };
template <int LO> __device__ __forceinline__ void cv_copy(float (&acc)[64]) {
#pragma unroll
  for (int i = LO; i < 64; i++) { float t; asm volatile("mov.b32 %0, %1;" : "=f"(t) : "f"(acc[i]) : "memory"); acc[i] = t; }
}
template <int G> __device__ __forceinline__ void cv_raw(uint32_t (&A)[4][4], uint32_t kaddr) {
#pragma unroll
  for (int i = 0; i < 4; i++) {
    const uint32_t a = kaddr + (4 * G + i) * 128;
    A[i][0] = lds32(a); A[i][1] = lds32(a + 4); A[i][3] = lds32(a + 8);
  }
}
__device__ __forceinline__ void cv_form(uint32_t (&A)[4][4], uint32_t sel) {
#pragma unroll
  for (int i = 0; i < 4; i++) {
    asm volatile("prmt.b32 %0, %0, %1, %2;" : "+r"(A[i][0]) : "r"(A[i][1]), "r"(sel));
    asm volatile("prmt.b32 %0, %1, %2, %3;" : "=r"(A[i][2]) : "r"(A[i][1]), "r"(A[i][3]), "r"(sel));
  }
}
#define CVV 2
template <int G> __device__ __forceinline__ void cv_step(float (&acc)[64], uint32_t (&A)[4][4], CvPipe& s, const CvCtx& c, uint32_t cb, uint32_t stg) {
  constexpr int JA = G - 1, JB = G - 2, NH = CVV == 1 ? 4 : (CVV == 3 ? 2 : 1);
  const uint32_t db0 = desc_lo(cb + CV_U + 192, CV_PL);
  uint32_t B[4][4];
  float ra[4], rb[2];
  if constexpr (G < 8) {
    wgmma_fence();
#pragma unroll
    for (int i = 0; i < NH; i++) wgmma_rs_hi<128 - 16 * (G & 7)>(acc, A[i][0], A[i][1], A[i][2], A[i][3], db0 - 4 * i);
    wgmma_commit();
    __syncwarp();
  }
  if constexpr (JA >= 0 && JA < 8) {
#pragma unroll
    for (int x = 0; x < 4; x++) {
      const int i = 8 * JA + 4 * (x >> 1) + 2 * (x & 1) + 1;
      ra[x] = shfl_sel(i >= 4 ? acc[i >= 4 ? i - 4 : 0] : 0.f, acc[i], c.wrapA, c.srcA);
    }
  }
  if constexpr (JB >= 0) {
#pragma unroll
    for (int h = 0; h < 2; h++) rb[h] = __shfl_sync(0xffffffffu, s.send[h], c.srcB);
  }
  if constexpr (G < 7) cv_raw<G + 1>(B, cb + c.koff);
  uint32_t z = 0;
  if constexpr (G < 8 && NH < 4) {
    __syncwarp();
    wgmma_fence();
#pragma unroll
    for (int i = NH; i < 4; i++) wgmma_rs_hi<128 - 16 * (G & 7)>(acc, A[i][0], A[i][1], A[i][2], A[i][3], db0 - 4 * i);
    wgmma_commit();
    asm volatile("mov.u32 %0, %%clock;" : "=r"(z)::"memory");
    z &= c.zero;
  }
  const float one = __uint_as_float(0x3f800000u | z);
  if constexpr (G < 7) cv_form(B, 0x5432u | z);
  if constexpr (JB >= 0) sts32(stg + ((c.so[JB / 3] >> (10 * (JB % 3))) & 0xffc), pack_bf16(fmaf(rb[0], one, s.keep[0]), fmaf(rb[1], one, s.keep[1])));
  if constexpr (JA >= 0 && JA < 8) {
#pragma unroll
    for (int h = 0; h < 2; h++) {
      const float ev = fmaf(ra[h], one, acc[8 * JA + 2 * h]), od = fmaf(ra[2 + h], one, acc[8 * JA + 4 + 2 * h]);
      s.send[h] = c.kodd ? ev : (c.s3 ? s.Ep[h] : od);
      s.keep[h] = c.kodd ? od : ev;
      s.Ep[h] = od;
    }
  }
  if constexpr (G < 8) { __syncwarp(); wgmma_wait<0>(); cv_copy<8 * (G & 7)>(acc); }
  if constexpr (G < 9) cv_step<G + 1>(acc, B, s, c, cb, stg);
}
__device__ __forceinline__ uint32_t cv_stage(int slot) { return sb + (slot < 4 ? 40960 + slot * 4096 : CV_OFF + CV_K); }
__device__ __forceinline__ void cv_setup(CvCtx& c) {
  const int tid = tid_opaque() & 127, w = tid >> 5, lane = tid & 31, r = lane >> 2, q = lane & 3;
  const int i0 = (r >> 1) & 1, i1 = r >> 2;
  c.koff = CV_K - 32 + 4 * (8 * (r >> 1) + 2 * w + (r & 1) + 2 * q);
  c.srcA = i0 ? lane - 8 : lane + 8 - q + ((q + 3) & 3);
  c.wrapA = i0 && q == 3;
  c.srcB = i1 == 0 ? (lane - q + 16 + ((q + 3) & 3)) : (lane - q - 16 + ((q + 1) & 3));
  c.s3 = (i1 == 1 && q == 3); c.kodd = (i1 == 1 && q < 3);
  c.zero = lds32(sb + EP_OFF + 24);
#pragma unroll
  for (int i = 0; i < 3; i++) c.so[i] = lds32(sb + SO_OFF + 512 * i + 4 * tid);
}
__device__ __forceinline__ void cv_table() {
  const int tid = tid_opaque() & 127, r = (tid & 31) >> 2, q = tid & 3;
  int t = 16 * (2 * (r < 4 ? q : 4 + ((q + 1) & 3)) + ((r >> 1) & 1)) + 4 * (tid >> 5) + 2 * (r & 1);
#pragma unroll 1
  for (int i = 0; i < 3; i++) {
    uint32_t v = 0;
#pragma unroll 1
    for (int x = 0; x < 3; x++, t += 256) {
      const int T = t / 160, tl = t - T * 160;
      const int qq = (T >= NT1 - 1) ? (tl >> 5) : (tl / 40);
      int ck = 20 * T + ((tl - qq * ((T >= NT1 - 1) ? 32 : 40)) >> 1);
      ck ^= (ck >> 2) & 6;
      v |= (uint32_t)((ck * 4 + qq) & 1023) << (10 * x + 2);
    }
    sts32(sb + SO_OFF + 512 * i + 4 * tid, v);
  }
}
__device__ __forceinline__ void conv_channel(int slot, const CvCtx& c) {
  const uint32_t cb = sb + CV_OFF + slot * CV_B;
  float acc[64];
  CvPipe s;
  s.Ep[0] = s.Ep[1] = 0.f;
  uint32_t A[4][4];
#pragma unroll
  for (int i = 0; i < 64; i++) acc[i] = 0.f;
  if (slot == 4) mbar_wait(bars + 8 * B_CVDONE);
  mbar_wait(bars + 8 * (B_CVFULL + slot));
  cv_raw<0>(A, cb + c.koff);
  {
    const uint32_t w0 = lds32(cb + CV_K);
    const uint32_t wp = __byte_perm(pack_bf16(bf_lo(w0) + __uint_as_float(lds32(sb + EP_OFF + 4 * slot)), 0.f), w0, 0x7610);
    if (c.koff == CV_K) A[0][0] = wp;
    if (c.koff == CV_K - 4) A[0][1] = wp;
    if (c.koff == CV_K - 8) A[0][3] = wp;
  }
  cv_form(A, 0x5432u);
  cv_copy<0>(acc);
  cv_step<0>(acc, A, s, c, cb, cv_stage(slot));
  fence_async_smem();
  mbar_arrive(bars + 8 * (B_CVDONE + slot));
}

__device__ __forceinline__ void kv_issue(const Params& p, int c, int m2, int dg) {
  const uint32_t fb = bars + 8 * (B_KV + c);
  mbar_expect_tx(fb, KV_PIECE);
  tma3(sb + KS_OFF + c * KV_PIECE, &p.mK, 160 * dg + 32 * c, 64 * m2 - 3, 0, fb);
  tma3(sb + KS_OFF + c * KV_PIECE + 4864, &p.mV, 160 * dg + 32 * c, 64 * m2 - 1, 0, fb);
}
__device__ __forceinline__ void kv_tile(int m, int dg, int c, int y) {
  const int lane = tid_opaque() & 31, tg = lane >> 3;
  const uint32_t pb = sb + KS_OFF + c * KV_PIECE + 32 * y + 4 * (lane & 7);
  const uint32_t ka = pb + tg * 1216, va = pb + 4864 + tg * 1088 + 64;
  const uint32_t kh = (m == 0 && tg > 0) ? ka - 192 : ka;
  uint32_t kk[19], u[16];
  const float4 t = lds128f(sb + TAP_OFF + 256 * c + 128 * y + 16 * (lane & 7));
#pragma unroll
  for (int i = 0; i < 19; i++) { kk[i] = lds32((i < 3 ? kh : ka) + i * 64); if (i >= 3) u[i - 3] = lds32(va + (i - 3) * 64); }
  uint8_t* dst = g_kv + ((160 * dg + 32 * c + 16 * y + 2 * (lane & 7)) * 4096 + (4 * m + tg) * 16);
  const uint32_t w0 = __byte_perm(__float_as_uint(t.x), __float_as_uint(t.z), 0x5410), w1 = __byte_perm(__float_as_uint(t.x), __float_as_uint(t.z), 0x7632);
  const uint32_t w2 = __byte_perm(__float_as_uint(t.y), __float_as_uint(t.w), 0x5410), w3 = __byte_perm(__float_as_uint(t.y), __float_as_uint(t.w), 0x7632);
#pragma unroll
  for (int i = 0; i < 16; i++) {
    uint32_t a = hmul2(kk[i], w3);
    a = hadd2(a, hmul2(kk[i + 1], w2)); a = hadd2(a, hmul2(kk[i + 2], w1)); a = hadd2(a, hmul2(kk[i + 3], w0));
    u[i] = hmul2(a, u[i]);
  }
#pragma unroll
  for (int e = 0; e < 2; e++)
#pragma unroll
    for (int f = 0; f < 2; f++) {
      uint32_t o[4];
#pragma unroll
      for (int qq = 0; qq < 4; qq++) o[qq] = __byte_perm(u[15 - 4 * qq - 2 * f], u[14 - 4 * qq - 2 * f], e ? 0x7632 : 0x5410);
      *(uint4*)(dst + e * 4096 + f * 2048) = make_uint4(o[0], o[1], o[2], o[3]);
    }
}
__device__ __forceinline__ void ln_finish(float s1, float s2, float& mean, float& rstd) {
  mean = s1 * (1.f / 640.f);
  const float v = fmaxf(fmaf(-mean, mean, s2 * (1.f / 640.f)), 0.f) + 1e-5f;
  asm("rsqrt.approx.ftz.f32 %0, %1;" : "=f"(rstd) : "f"(v));
}
__device__ __forceinline__ void stat_table(int T1, unsigned want, int l, int g, const uint4* x0, const uint4* x1, float (&xa)[2], float (&xb)[2]) {
  const int n = 32 * g + (tid_opaque() & 31);
  const uint4* rp = &g_stats[8 * l * SEQ + min(160 * T1 + n, SEQ - 1)];
  float a[4], b[4];
  uint32_t it = 0;
  while (true) {
    bool ok = true;
#pragma unroll
    for (int i = 0; i < 4; i++) ok &= (rec_ld(rp + SEQ * i, a[i], b[i]) == want);
    ok &= rec_ld(x0, xa[0], xb[0]) == want;
    ok &= rec_ld(x1, xa[1], xb[1]) == want;
    if (__all_sync(0xffffffffu, ok)) break;
    trap_if(++it > SPIN_LIMIT);
  }
  float m, rs;
  ln_finish((a[0] + a[1]) + (a[2] + a[3]), (b[0] + b[1]) + (b[2] + b[3]), m, rs);
  sts64f(sb + STAB_OFF + n * 8, rs, -m * rs);
}
__device__ __forceinline__ void stats_reduce(float (&a)[2], float (&b)[2], float (&mean)[2], float (&rstd)[2]) {
#pragma unroll
  for (int o = 1; o < 4; o <<= 1)
#pragma unroll
    for (int h = 0; h < 2; h++) { a[h] += __shfl_xor_sync(0xffffffffu, a[h], o); b[h] += __shfl_xor_sync(0xffffffffu, b[h], o); }
#pragma unroll
  for (int h = 0; h < 2; h++) ln_finish(a[h], b[h], mean[h], rstd[h]);
}

template <bool FIRST>
__device__ __forceinline__ void stats_publish(int which, int n0, int dg, unsigned tag, const float (&acc)[80]) {
  const int q = tid_opaque() & 3, h = q & 1;
  float s1[2] = {0.f, 0.f}, s2[2] = {0.f, 0.f}, t1[2] = {0.f, 0.f}, t2[2] = {0.f, 0.f};
#pragma unroll
  for (int j = 0; j < 20; j++)
#pragma unroll
    for (int y = 0; y < 2; y++) {
      const float a = acc[4 * j + 2 * y], b = acc[4 * j + 2 * y + 1];
      s1[y] += a; t1[y] += b; s2[y] = fmaf(a, a, s2[y]); t2[y] = fmaf(b, b, t2[y]);
    }
#pragma unroll
  for (int y = 0; y < 2; y++) { s1[y] += t1[y]; s2[y] += t2[y]; }
  float a = (h ? s1[1] : s1[0]) + __shfl_xor_sync(0xffffffffu, h ? s1[0] : s1[1], 1);
  float b = (h ? s2[1] : s2[0]) + __shfl_xor_sync(0xffffffffu, h ? s2[0] : s2[1], 1);
  a += __shfl_xor_sync(0xffffffffu, a, 2);
  b += __shfl_xor_sync(0xffffffffu, b, 2);
  if (FIRST) {
    rec_st(&g_stats[((q >> 1) * 4 + dg) * SEQ + n0 + 8 * h], a, b, q < 2 ? tag : tag - 1);
    rec_st(&g_stats[((q >> 1) * 4 + 8 + dg) * SEQ + n0 + 8 * h], a, b, tag - 1);
  } else if (q < 2) rec_st(&g_stats[(which * 4 + dg) * SEQ + n0 + 8 * h], a, b, tag);
}
__device__ __forceinline__ void stats_get(int which, int n0, unsigned tag, float (&mean)[2], float (&rstd)[2]) {
  const uint4* p0 = &g_stats[(which * 4 + (tid_opaque() & 3)) * SEQ + n0];
  float a[2], b[2];
  uint32_t it = 0;
  while (true) {
    const unsigned t0 = rec_ld(p0, a[0], b[0]), t1 = rec_ld(p0 + 8, a[1], b[1]);
    if (__all_sync(0xffffffffu, t0 == tag && t1 == tag)) break;
    trap_if(++it > SPIN_LIMIT);
  }
  stats_reduce(a, b, mean, rstd);
}
__device__ __forceinline__ void x0_load(float (&acc)[80]) {
  const int t = tid_opaque() & 127;
  const uint32_t xa = sb + XT_OFF + (16 * (t >> 5) + ((t & 31) >> 2)) * 320 + 8 * (t & 3);
  mbar_wait(bars + 8 * B_XT);
#pragma unroll
  for (int h = 0; h < 2; h++)
#pragma unroll
    for (int J = 0; J < 10; J++) {
      const float2 v = lds64f(xa + h * 2560 + 32 * J);
      const uint32_t x = __float_as_uint(v.x), y = __float_as_uint(v.y);
      acc[8 * J + 2 * h] = bf_lo(x); acc[8 * J + 2 * h + 1] = bf_hi(x);
      acc[8 * J + 4 + 2 * h] = bf_lo(y); acc[8 * J + 4 + 2 * h + 1] = bf_hi(y);
    }
}

template <bool FROM_X0>
__device__ __forceinline__ void dskip_init(float (&acc)[80], const float (&mean)[2], const float (&rstd)[2]) {
  const int t = tid_opaque() & 127;
  const uint32_t xa = sb + XT_OFF + (16 * (t >> 5) + ((t & 31) >> 2)) * 320 + 8 * (t & 3), da = sb + DTAB_OFF + 8 * (t & 3);
  float2 dw[10], xv[10][2];
#pragma unroll
  for (int J = 0; J < 2; J++) { dw[J] = lds64f(da + 32 * J); if (FROM_X0) { xv[J][0] = lds64f(xa + 32 * J); xv[J][1] = lds64f(xa + 2560 + 32 * J); } }
#pragma unroll
  for (int J = 0; J < 10; J++) {
    if (J + 2 < 10) { dw[J + 2] = lds64f(da + 32 * (J + 2)); if (FROM_X0) { xv[J + 2][0] = lds64f(xa + 32 * (J + 2)); xv[J + 2][1] = lds64f(xa + 2560 + 32 * (J + 2)); } }
#pragma unroll
    for (int x = 0; x < 8; x++) {
      const int h = (x >> 1) & 1;
      const uint32_t dwd = __float_as_uint(x < 4 ? dw[J].x : dw[J].y);
      const float tt = fmaf(rstd[h], (x & 1) ? bf_hi(dwd) : bf_lo(dwd), 1.f);
      float a = acc[8 * J + x];
      if (FROM_X0) { const uint32_t xw = __float_as_uint(x < 4 ? xv[J][h].x : xv[J][h].y); a = (x & 1) ? bf_hi(xw) : bf_lo(xw); }
      acc[8 * J + x] = FROM_X0 ? (a - mean[h]) * tt : fmaf(a, tt, -mean[h] * tt);
    }
  }
}

__global__ void __launch_bounds__(512, 1) fused_kernel(const __grid_constant__ Params p) {
  extern __shared__ __align__(1024) uint8_t smem_raw[];
  const int tid = threadIdx.x, lane = tid & 31;
  const int wid = __shfl_sync(0xffffffffu, tid >> 5, 0), wg = wid >> 2;
  unsigned smid; asm volatile("mov.u32 %0, %%smid;" : "=r"(smid));
  const int role = p.role[min(smid, 131u)];
  if (wid == 12) {
    const bool el = elect_one();
    if (el) {
      asm volatile("prefetch.tensormap [%0];" ::"l"(&p.mX) : "memory");
      asm volatile("prefetch.tensormap [%0];" ::"l"(&p.mB) : "memory");
#pragma unroll
      for (int k = 0; k < S1; k++) mbar_init(bars + 8 * (B_G1FULL + k), 1);
#pragma unroll
      for (int k = 0; k < 6; k++) mbar_init(bars + 8 * (B_XT + k), 1);
      asm volatile("fence.mbarrier_init.release.cluster;" ::: "memory");
    }
    if (role >= 0) {
      __syncwarp();
      asm volatile("bar.arrive 5, 288;" ::: "memory");
      const Role R = unpack_role(role);
      if (elect_one()) {
        TS(45);
#pragma unroll 1
        for (int k = 0; k < S1; k++) {
          const uint32_t fb = bars + 8 * (B_G1FULL + k);
          mbar_expect_tx(fb, G1_STAGE);
          tma4(sb + k * G1_STAGE + G1_XOFF, R.last ? &p.mXl : &p.mX, 64 * k, 0, 0, R.last ? 0 : 80 * R.T1, fb);
          tma5(sb + k * G1_STAGE, &p.mB, 64 * k, 0, 0, 4 * R.side, 2 * R.GP, fb);
        }
        if (R.has2) {
#pragma unroll 1
          for (int c = 0; c < KV0; c++) kv_issue(p, c, R.m2, R.dg);
          mbar_expect_tx(bars + 8 * B_XT, 20480);
#pragma unroll 1
          for (int h = 0; h < 2; h++) {
            const int ng = 8 * R.m2 + 4 * h, T = ng / 20;
            tma4(sb + XT_OFF + h * 10240, T == NT1 - 1 ? &p.mXtl : &p.mXt, 160 * R.dg, 0, 0, T == NT1 - 1 ? ng - 240 : ng + 60 * T, bars + 8 * B_XT);
          }
        }
        TS(44);
      }
      __syncwarp();
      bar_sync(6, 64);
    }
  }
  trap_if(smid >= 132 || smem_u32(smem_raw) != sb);
  if (role < 0) {
    if (wid == 0) {
      const unsigned tag = ld_rlx(g_epoch);
#pragma unroll 1
      for (int i = 0; i < NT1; i++) {
        uint32_t it = 0;
        while (!__all_sync(0xffffffffu, (int)(ld_rlx(&g_hflag[(i * 32 + min(lane, 9)) * 8]) - tag) >= 0)) { __nanosleep(500); trap_if(++it > SPIN_LIMIT); }
      }
    }
    return;
  }
  float mean0[2] = {0.f, 0.f}, rstd0[2] = {0.f, 0.f};
  if (wg == 2 || wid == 14) {
    ROLE(role)
    const int c = wid == 14 ? 4 : wid - 8;
    const unsigned tag = ld_rlx(g_epoch);
    if (has2) {
      uint2 bv[2][5];
#pragma unroll
      for (int x = 0; x < 2; x++)
#pragma unroll
        for (int i = 0; i < 5; i++) bv[x][i] = ldv64((const uint2*)((x ? p.bim : p.bre) + (cch0 + 32 * c) * DM) + lane + 32 * i);
      float sv[2];
#pragma unroll
      for (int x = 0; x < 2; x++) {
        float a = 0.f;
#pragma unroll
        for (int i = 0; i < 5; i++) a += (bf_lo(bv[x][i].x) + bf_hi(bv[x][i].x)) + (bf_lo(bv[x][i].y) + bf_hi(bv[x][i].y));
        sv[x] = a;
      }
#pragma unroll
      for (int o = 16; o > 0; o >>= 1) { sv[0] += __shfl_xor_sync(0xffffffffu, sv[0], o); sv[1] += __shfl_xor_sync(0xffffffffu, sv[1], o); }
      if (lane < 2) rec_st(&g_sB[(cch0 + 32 * c) * 2 + lane], sv[0], sv[1], tag);
      if (tid == 256) TS(47);
      __syncwarp();
      bar_sync(8, 192);
      mbar_wait(bars + 8 * B_EP);
      mbar_wait(bars + 8 * (B_KV + c));
#pragma unroll 1
      for (int y = 0; y < 2; y++) kv_tile(m2, dg, c, y);
      __syncwarp();
      if (lane == 0) mbar_arrive(bars + 8 * B_PREP);
      if (tid == 352) TS(52);
      if (tid == 448) TS(51);
      if (wg == 2) {
        float xs[80];
        x0_load(xs);
        stats_publish<true>(0, 64 * m2 + 16 * c + (lane >> 2), dg, tag, xs);
        if (tid == 256) TS(31);
        mbar_wait(bars + 8 * (TABW ? B_PUB : B_PREP));
      } else {
        mbar_wait(bars + 8 * B_PREP);
        if (lane == 0) { st_rel(&g_kvflag[(dg * 32 + m2) * 8], tag); mbar_arrive(bars + 8 * B_PUB); TS(30); }
        __syncwarp();
      }
    } else bar_sync(8, 192);
    {
      const uint4* x0 = wg == 2 ? &g_stats[(lane & 3) * SEQ + (has2 ? 64 * m2 : 0) + 16 * c + (lane >> 2)] : &g_sB[(128 * GP + 32 * side + lane) * 2];
      float xa[2], xb[2];
      stat_table(T1, tag, 0, c, x0, x0 + (wg == 2 ? 8 : 128), xa, xb);
      if (wg == 2) stats_reduce(xa, xb, mean0, rstd0);
      else {
#pragma unroll
        for (int i = 0; i < 2; i++) sts64f(sb + CTAB_OFF + (32 * i + lane) * 24 + 16, p.swap ? xb[i] : xa[i], p.swap ? xa[i] : xb[i]);
      }
      mbar_arrive(bars + 8 * B_STAB);
      if (tid == 448) TS(26);
    }
  } else if (wid == 15) {
    ROLE(role)
    const int ch = 128 * GP + 32 * side + lane;
    uint32_t r0 = ldv16(p.lre + ch), r1 = ldv16(p.lim + ch), r2 = ldv16(p.logdt + ch);
    const uint32_t r3 = ldv16(p.lre + ch + 64), r4 = ldv16(p.lim + ch + 64), r5 = ldv16(p.logdt + ch + 64);
#pragma unroll 1
    for (int i = 0; i < 2; i++) {
      const float lr = bf_lo(r0), li = bf_lo(r1);
      const float dt = __bfloat162float(__float2bfloat16_rn(expf(bf_lo(r2))));
      const float mag = expf(dt * lr);
      float sn, cs; sincospif(dt * li * 0.31830988618379067f, &sn, &cs);
      const float ar = mag * cs, ai = mag * sn;
      const float inv = 2.f / (lr * lr + li * li);
      const uint32_t ad = sb + CTAB_OFF + (32 * i + lane) * 24;
      sts64f(ad, ar, ai);
      sts64f(ad + 8, ((ar - 1.f) * lr + ai * li) * inv, (ai * lr - (ar - 1.f) * li) * inv);
      r0 = r3; r1 = r4; r2 = r5;
    }
    if (lane == 0) TS(46);
    __syncwarp();
    bar_sync(7, 64);
    mbar_arrive(bars + 8 * B_CTAB);
  } else if (wid == 13) {
    ROLE(role)
    uint4 tv[3];
    const uint32_t e0 = ld_rlx(g_epoch);
    const uint32_t e1 = ldv16(p.ssmD + min(cch0 + 32 * lane, 639));
    const uint4 dv = ldv128((const uint4*)(p.dskip + 160 * dg) + min(lane, 19));
#pragma unroll
    for (int i = 0; i < 3; i++) tv[i] = ldv128((const uint4*)(p.shiftk + 640 * dg) + min(lane + 32 * i, 79));
    sts128(sb + DTAB_OFF + 16 * min(lane, 19), dv);
#pragma unroll
    for (int i = 0; i < 3; i++) sts128(sb + TAP_OFF + 16 * min(lane + 32 * i, 79), tv[i]);
    if (lane < 7) sts32(sb + EP_OFF + 4 * lane, lane < 5 ? e1 << 16 : (lane == 5 ? e0 : 0u));
    __syncwarp();
    bar_sync(9, 64);
    mbar_arrive(bars + 8 * B_CTAB);
    if (lane == 0) { mbar_arrive(bars + 8 * B_EP); TS(53); }
  } else if (wid != 12) {
    if (elect_one()) {
      if (wid < 7) {
        const int b0 = wid < 4 ? 4 + 20 * wid : 85 + 21 * (wid - 4), cnt = wid < 4 ? 2 : 1;
#pragma unroll
        for (int i = 0; i < 21; i++) mbar_init(bars + 8 * (b0 + i), cnt);
      } else {
#pragma unroll
        for (int i = 0; i < 12; i++) mbar_init(bars + 8 * (B_CVDONE + i), (i == 5 || i == 6) ? 160 : 128);
        mbar_init(bars + 8 * B_CTAB, 192); mbar_init(bars + 8 * B_PREP, 5);
      }
      asm volatile("fence.mbarrier_init.release.cluster;" ::: "memory");
    }
    __syncwarp();
    bar_sync(5, 288);
    if (wid == 2) asm volatile("bar.arrive 8, 192;\nbar.arrive 6, 64;\nbar.arrive 9, 64;\nbar.arrive 7, 64;" ::: "memory");
    if (tid == 128) TS(0);
    if (wg == 1) { cv_table(); mbar_arrive(bars + 8 * B_CTAB); }
  }

  if (wid == 12) {
    ROLE(role)
    uint32_t dst = sb;
#pragma unroll 1
    for (int k = S1; k < 10; k++) {
      const uint32_t fb = bars + 8 * (B_G1FULL + k);
      mbar_wait(bars + 8 * (B_G1DONE + k - S1));
      if (elect_one()) {
        mbar_expect_tx(fb, 20480);
        tma4(dst + G1_XOFF, last ? &p.mXl : &p.mX, 64 * k, 0, 0, last ? 0 : 80 * T1, fb);
        mbar_expect_tx(fb, 16384);
        tma5(dst, &p.mB, 64 * k, 0, 0, 4 * side, 2 * GP, fb);
        if (has2 && k - S1 + KV0 < 5) kv_issue(p, k - S1 + KV0, m2, dg);
      }
      dst += G1_STAGE; if (k == 2 * S1 - 1) dst = sb;
    }
  } else if (wid == 15 && (role >> 16)) {
    ROLE(role)
    mbar_wait(bars + 8 * B_PREP);
#pragma unroll
    for (int c = 0; c < 5; c++) {
      const uint32_t cb = sb + CV_OFF + c * CV_B;
      sts128(lane < 8 ? cb + 16 * lane : (lane < 20 ? cb + CV_U + 16 * (lane - 8) : cb + CV_U + CV_PL + 16 * (lane - 20)), make_uint4(0, 0, 0, 0));
    }
    fence_async_smem();
    __syncwarp();
    const unsigned tag = lds32(sb + EP_OFF + 20);
    mbar_wait(bars + 8 * B_PUB);
    if (elect_one()) {
#pragma unroll
      for (int c = 0; c < TAP0; c++) {
        mbar_expect_tx(bars + 8 * (B_CVFULL + c), 4096);
        bulk_g2s(sb + CV_OFF + c * CV_B + CV_K, p.ssmk + (cch0 + 32 * c) * SEQ, 4096, bars + 8 * (B_CVFULL + c));
      }
    }
    flag_poll(&g_kvflag[(dg * 32 + lane) * 8], tag);
    fence_async_global();
    if (elect_one()) {
      TS(28);
#pragma unroll 1
      for (int c = 0; c < 5; c++) {
        const uint32_t fb = bars + 8 * (B_CVFULL + c), cb = sb + CV_OFF + c * CV_B;
        mbar_expect_tx(fb, 4096);
        bulk_g2s(cb + CV_U + 192, g_kv + (cch0 + 32 * c) * 4096, 2048, fb);
        bulk_g2s(cb + CV_U + 192 + CV_PL, g_kv + (cch0 + 32 * c) * 4096 + 2048, 2048, fb);
        if (c >= TAP0) {
          mbar_expect_tx(fb, 4096);
          bulk_g2s(cb + CV_K, p.ssmk + (cch0 + 32 * c) * SEQ, 4096, fb);
        }
      }
      TS(54);
    }
    __syncwarp();
  }
  {
    const int w = wid & 3;
    if (wg == 2 && !(role >> 16)) {
      float xa[2], xb[2];
      mbar_wait(bars + 8 * (B_G1FULL + 11));
      stat_table(role & 15, lds32(sb + EP_OFF + 20), 1, w, g_stats, g_stats, xa, xb);
      mbar_arrive(bars + 8 * (B_STAB + 1));
    }
#pragma unroll 1
    for (int l = 0; l < 2; l++) {
      if (wg < 2) {
        float acc[80];
#pragma unroll
        for (int i = 0; i < 80; i++) acc[i] = 0.f;
        ROLE(role)
        const int tid = tid_opaque(), r = (tid & 31) >> 2, q = tid & 3;
        const int ch = 128 * GP + 64 * wg + 32 * side + 8 * w + r;
        const uint32_t ca = sb + CTAB_OFF + (32 * wg + 8 * w + r) * 24;
        float2 lam = make_float2(0.f, 0.f), p8 = lam, p16 = lam, pL = lam, p2L = lam;
        fence_regs(acc);
        {
          uint32_t alo = desc_lo(sb, 16) + wg * 512, blo = l == 0 ? desc_lo(sb + G1_XOFF, 16) : desc_lo(sb + G1_XOFF, 128);
          const uint32_t bhi = l == 0 ? desc_hi(1024, 1) : desc_hi(1024, 0), xstep = l == 0 ? 2 : 16;
          const uint32_t aend = desc_lo(sb, 16) + (S1 + l) * (G1_STAGE >> 4);
          uint32_t fb = bars + 8 * (B_G1FULL + 10 * l);
          mbar_wait(fb);
          if (tid == 0) TS(1 + 8 * l);
#pragma unroll 1
          for (int k = 0; k < 10; k++) {
            uint32_t ok; const uint32_t nb = k < 9 ? fb + 8 : fb;
            wgmma_fence();
#pragma unroll
            for (int kk = 0; kk < 4; kk++) {
              wgmma_n160<0>(acc, alo + kk * 2, desc_hi(1024, 1), blo + kk * xstep, bhi);
              if (kk == 0) ok = mbar_test(nb);
              if (kk == STG_KK && k == 9 && tid == 0) mbar_arrive(bars + 8 * (B_STG + l));
            }
            wgmma_commit();
            alo += G1_STAGE >> 4; blo += G1_STAGE >> 4;
            if (alo >= aend) { alo -= (S1 + l) * (G1_STAGE >> 4); blo -= (S1 + l) * (G1_STAGE >> 4); }
            wgmma_wait<1>();
            if (k > 0 && (tid & 127) == 0) mbar_arrive(fb + 8 * (B_G1DONE - B_G1FULL - 1));
            if (!ok) mbar_wait(nb);
            if (wg == 1 && k == (l ? 8 - STG_D : 9 - STG0)) mbar_wait(bars + 8 * (B_STG + l));
            if (k == 3) {
              mbar_wait(bars + 8 * B_CTAB);
              lam = lds64f(ca);
              if (p.swap) lam.y = -lam.y;
              const float2 p2 = cmul(lam, lam), p4 = cmul(p2, p2);
              p8 = cmul(p4, p4); p16 = cmul(p8, p8);
              pL = cmul(p16, p16);
              if (!last) pL = cmul(pL, p8);
              p2L = cmul(pL, pL);
            }
            if (k == PAUSE_K && has2) mbar_wait(bars + 8 * B_PREP);
            fb += 8;
          }
        }
        mbar_wait(bars + 8 * (B_STAB + l));
        const float2 sB = lds64f(ca + 16);
        const unsigned tag = lds32(sb + EP_OFF + 20);
        wgmma_wait<0>();
        fence_regs(acc);
        if ((tid & 127) == 0) { mbar_arrive(bars + 8 * (B_G1DONE + 10 * l + 9)); TS(wg ? 17 + l : 2 + 8 * l); }
        float2 ec[3];
#pragma unroll
        for (int jj = 0; jj < 8; jj++)
#pragma unroll
          for (int y = 0; y < 3; y++) {
            if (y == 2 && (jj & 1)) continue;
            const int j = y == 2 ? 16 + (jj >> 1) : 8 * y + jj;
            const float4 st = lds128f(sb + STAB_OFF + (8 * j + 2 * q) * 8);
            acc[4 * j + 0] = fmaf(acc[4 * j + 0], st.x, st.y * sB.x);
            acc[4 * j + 2] = fmaf(acc[4 * j + 2], st.x, st.y * sB.y);
            acc[4 * j + 1] = fmaf(acc[4 * j + 1], st.z, st.w * sB.x);
            acc[4 * j + 3] = fmaf(acc[4 * j + 3], st.z, st.w * sB.y);
            ec[y] = jj == 0 ? make_float2(acc[4 * j + 0], acc[4 * j + 2]) : cfma(lam, ec[y], make_float2(acc[4 * j + 0], acc[4 * j + 2]));
            ec[y] = cfma(lam, ec[y], make_float2(acc[4 * j + 1], acc[4 * j + 3]));
          }
        float2 e = cfma(p16, ec[0], ec[1]);
        if (!last) e = cfma(p8, e, ec[2]);
        {
          float2 v = make_float2(__shfl_up_sync(0xffffffffu, e.x, 1, 4), __shfl_up_sync(0xffffffffu, e.y, 1, 4));
          if (q >= 1) e = cfma(pL, v, e);
          v = make_float2(__shfl_up_sync(0xffffffffu, e.x, 2, 4), __shfl_up_sync(0xffffffffu, e.y, 2, 4));
          if (q >= 2) e = cfma(p2L, v, e);
        }
        if (!last && (q == 3 || (q == 2 && l == 0))) rec_st(&g_E[((q == 3 ? l : 1) * NT1 + T1) * DM + ch], e.x, e.y, q == 3 ? tag : tag - 1);
        if (tid == 0) TS(3 + 8 * l);
        float2 ex = make_float2(__shfl_up_sync(0xffffffffu, e.x, 1, 4), __shfl_up_sync(0xffffffffu, e.y, 1, 4));
        if (q == 0) ex = make_float2(0.f, 0.f);
        const float2 coef = lds64f(ca + 8), lamc = make_float2(lam.x, p.swap ? lam.y : -lam.y);
        float m00 = coef.x, m01 = -coef.y, m10 = -coef.y, m11 = -coef.x;
        if (p.swap) { m00 = -coef.y; m01 = coef.x; m10 = -coef.x; m11 = -coef.y; }
        float2 pLq, p160q, p640;
        {
          const float2 p80 = last ? cmul(p2L, p16) : p2L, p160 = cmul(p80, p80), p320 = cmul(p160, p160), one = make_float2(1.f, 0.f);
          p640 = cmul(p320, p320);
          pLq = cmul((q & 1) ? pL : one, (q & 2) ? p2L : one);
          p160q = cmul((q & 1) ? p160 : one, (q & 2) ? p320 : one);
        }
        float2 c, ev[3];
        unsigned tg[3];
        const uint4* ep = &g_E[(l * NT1 + T1 - 1 - q) * DM + ch];
#pragma unroll
        for (int j = 0; j < 20; j++) {
          if (j == CPOLL) {
#pragma unroll
            for (int i = 0; i < 3; i++) {
              ev[i] = make_float2(0.f, 0.f); tg[i] = tag;
              if (T1 - 1 - q - 4 * i >= 0) tg[i] = rec_ld(ep - 4 * i * DM, ev[i].x, ev[i].y);
            }
          }
#pragma unroll
          for (int x = 0; x < 2; x++) {
            const float b0 = acc[4 * j + x], b1 = acc[4 * j + 2 + x];
            acc[4 * j + x] = fmaf(b0, m00, b1 * m01);
            acc[4 * j + 2 + x] = fmaf(b0, m10, b1 * m11);
          }
          if (j == CPOLL - 1 || j == 19) asm volatile("" : "+f"(acc[4 * j]), "+f"(acc[4 * j + 1]), "+f"(acc[4 * j + 2]), "+f"(acc[4 * j + 3])::"memory");
        }
        {
          uint32_t it = 0;
          while (__any_sync(0xffffffffu, tg[0] != tag || tg[1] != tag || tg[2] != tag)) {
#pragma unroll
            for (int i = 0; i < 3; i++)
              if (tg[i] != tag) tg[i] = rec_ld(ep - 4 * i * DM, ev[i].x, ev[i].y);
            trap_if(++it > SPIN_LIMIT);
          }
          c = cfma(p640, cfma(p640, ev[2], ev[1]), ev[0]);
          c = cmul(c, p160q);
          c.x += __shfl_xor_sync(0xffffffffu, c.x, 1); c.y += __shfl_xor_sync(0xffffffffu, c.y, 1);
          c.x += __shfl_xor_sync(0xffffffffu, c.x, 2); c.y += __shfl_xor_sync(0xffffffffu, c.y, 2);
        }
        if (tid == 0) TS(4 + 8 * l);
        if (wg == 1 && l >= HOLD0) mbar_wait(bars + 8 * (B_REL + l));
        c = cfma(pLq, c, ex);
        float2 hh = make_float2(fmaf(c.x, m00, c.y * m01), fmaf(c.x, m10, c.y * m11));
        uint8_t* hb = g_h + (size_t)l * (32 * 20 * 8192) + (10 * wg + 2 * GP) * 8192 + (4 * side + w) * 1024 + (tid_opaque() & 31) * 4;
#pragma unroll
        for (int j4 = 0; j4 < 5; j4++) {
          const int ng = 20 * T1 + 4 * j4;
          uint8_t* hp = hb + (size_t)(ng >> 3) * 163840 + (ng & 7) * 128;
#pragma unroll
          for (int jj = 0; jj < 4; jj++) {
            const int j = 4 * j4 + jj;
            const float2 h0 = cfma(lamc, hh, make_float2(acc[4 * j + 0], acc[4 * j + 2]));
            hh = cfma(lamc, h0, make_float2(acc[4 * j + 1], acc[4 * j + 3]));
            if (j4 < 4 || !last) {
              *(uint32_t*)(hp + jj * 128) = pack_bf16(h0.x, hh.x);
              *(uint32_t*)(hp + jj * 128 + 8192) = pack_bf16(h0.y, hh.y);
            }
          }
        }
        mbar_arrive(bars + 8 * (B_HST + 2 * l + wg));
        if (tid == 0) TS(5 + 8 * l);
        if (tid == 128) TS(l ? 25 : 19);
        if (l == 0 && wid == 4) {
          mbar_wait(bars + 8 * B_HST);
          mbar_wait(bars + 8 * (B_HST + 1));
          if ((tid & 31) < 2) st_rel(&g_hflag[((T1 * 2 + (tid & 31)) * 16 + 2 * GP + side) * 8], tag);
          if (tid == 128) { mbar_arrive(bars + 8 * B_REL); TS(6); }
          __syncwarp();
        }
      }
      if (l == 0) {
        ROLE(role)
        if (has2) {
          CvCtx cc;
          mbar_wait(bars + 8 * B_CTAB);
          cv_setup(cc);
          mbar_wait(bars + 8 * (B_G1DONE + 9));
#pragma unroll 1
          for (int c = (wg + 2) & 3; c < 5; c += 4) conv_channel(c, cc);
          if ((tid & 127) == 0) TS(wg == 2 ? 32 : (wg == 3 ? 50 : 7 + wg));
        }
      }
      if (wg >= 2) break;
    }
    if (wg == 3) {
    ROLE(role)
    const int pw = wid & 3;
    mbar_wait(bars + 8 * B_EP);
    const unsigned tag = lds32(sb + EP_OFF + 20);
    if (pw == 0) {
      if (elect_one()) {
#pragma unroll 1
        for (int l = 0; l < 2; l++) {
          uint32_t dst = sb;
          if (l == 1) {
            const uint32_t free0 = bars + 8 * (has2 ? B_G2DONE + 19 : B_G1DONE + 9);
#pragma unroll 1
            for (int k = 0; k < 10; k++) {
              mbar_wait(k > S1 ? bars + 8 * (B_G1DONE + 9 - S1 + k) : (k < WPF1 || !has2 ? free0 : bars + 8 * B_GO));
              mbar_expect_tx(bars + 8 * (B_G1FULL + 10 + k), 16384);
              tma5(dst, &p.mB, 64 * k, 0, 0, 4 * side, 2 * GP, bars + 8 * (B_G1FULL + 10 + k));
              dst += G1_STAGE; if (k == S1) dst = sb;
            }
          }
          if (has2) {
            const uint32_t fb2 = bars + 8 * (B_G2FULL + 20 * l), wb2 = bars + 8 * (B_G2DONE + 20 * l - S2);
            dst = sb + G2_WOFF;
            int kc = 0;
#pragma unroll 1
            for (int k = 0; k < 20; k++) {
              mbar_wait(k >= S2 ? wb2 + 8 * k : (k == 5 ? bars + 8 * B_XFREE : (k == 6 ? bars + 8 * B_SFREE : bars + 8 * (l ? B_G1DONE + 19 : B_REL))));
              mbar_expect_tx(fb2 + 8 * k, G2_WB);
              tma5(dst, &p.mCre + (k & 1), kc, 0, 0, 0, 10 * dg, fb2 + 8 * k);
              kc += (k & 1) << 7; if (k == 9) kc = 64;
              dst += G2_WB; if (dst == sb + G2_WOFF + S2 * G2_WB) dst = sb + G2_WOFF;
            }
          }
        }
      }
    } else if (pw == 1) {
#pragma unroll 1
      for (int l = 0; l < 2; l++) {
        if (l == 1) {
          mbar_wait(bars + 8 * (has2 ? B_G2DONE + 19 : B_G1DONE + 9));
          const int mlo = (160 * T1) >> 6, nf = last ? 8 : 12;
          flag_poll(&g_uflag[(4 * mlo + min(lane, nf - 1)) * 8], tag);
          fence_async_global();
          if (elect_one()) {
            TS(20);
            const int bytes = last ? 16384 : 20480;
            const uint8_t* src = g_u + T1 * 204800;
            uint32_t dst = sb + G1_XOFF;
#pragma unroll 1
            for (int k = 0; k < 10; k++) {
              if (k > S1) mbar_wait(bars + 8 * (B_G1DONE + 9 - S1 + k));
              mbar_expect_tx(bars + 8 * (B_G1FULL + 10 + k), bytes);
              bulk_g2s(dst, src, bytes, bars + 8 * (B_G1FULL + 10 + k));
              src += 20480; dst += G1_STAGE; if (k == S1) dst = sb + G1_XOFF;
            }
          }
          __syncwarp();
        }
        if (has2) {
          mbar_wait(bars + 8 * (B_HST + 2 * l));
          mbar_wait(bars + 8 * (B_G1DONE + 10 * l + 9));
          const int Tlo = (64 * m2) / 160, Thi = (64 * m2 + 63) / 160;
          flag_poll(&g_hflag[(((l * NT1 + (lane < 16 ? Tlo : Thi)) * 2) * 16 + min(lane & 15, 9)) * 8], tag);
          fence_async_global();
          if (elect_one()) {
            TS(21 + 2 * l);
            const uint32_t fb2 = bars + 8 * (B_G2FULL + 20 * l), wb2 = bars + 8 * (B_G2DONE + 20 * l - S2);
            const uint8_t* src = g_h + (l * 32 + m2) * 163840;
            uint32_t dst = sb;
#pragma unroll 1
            for (int k = 0; k < 20; k++) {
              if (k >= 5) mbar_wait(k >= S2 ? wb2 + 8 * k : bars + 8 * B_SFREE);
              if (k == 10) { mbar_wait(bars + 8 * (B_H1 + l)); fence_async_global(); }
              mbar_expect_tx(fb2 + 8 * k, G2_XB);
              bulk_g2s(dst, src, G2_XB, fb2 + 8 * k);
              src += 8192; dst += G2_XB; if (dst == sb + S2 * G2_XB) dst = sb;
            }
          }
          __syncwarp();
        }
      }
    } else if (pw == 2) {
#pragma unroll 1
      for (int l = 0; l < 2; l++) {
        if (l == 1) {
          float xa[2], xb[2];
          mbar_wait(bars + 8 * (B_G1FULL + 11));
          stat_table(T1, tag, 1, 4, g_stats, g_stats, xa, xb);
          mbar_arrive(bars + 8 * (B_STAB + 1));
        }
#pragma unroll 1
        for (int w = 0; w < 2 * l; w++) {
          mbar_wait(bars + 8 * (B_HST + 2 + w));
          if (lane == 0) { st_rel(&g_hflag[(((NT1 + T1) * 2 + w) * 16 + 2 * GP + side) * 8], tag); if (w == 0) mbar_arrive(bars + 8 * (B_REL + 1)); TS(w ? 16 : 14); }
          __syncwarp();
        }
        if (l == 0 && has2 && elect_one()) {
#pragma unroll 1
          for (int c = 0; c < 5; c++) {
            mbar_wait(bars + 8 * (B_CVDONE + c));
            bulk_s2g(g_G + (cch0 + 32 * c) * 4096, cv_stage(c), 4096);
          }
          asm volatile("cp.async.bulk.commit_group;" ::: "memory");
          asm volatile("cp.async.bulk.wait_group.read 0;" ::: "memory");
          mbar_arrive(bars + 8 * B_SFREE);
          asm volatile("cp.async.bulk.wait_group 0;" ::: "memory");
          TS(48);
          fence_async_global();
          st_rel(&g_gflag[(dg * 32 + m2) * 8], tag);
          TS(49);
          mbar_arrive(bars + 8 * (B_GO + 1));
        }
        __syncwarp();
      }
    } else if (has2) {
      mbar_wait(bars + 8 * B_REL);
      if (elect_one()) {
        l2_prefetch(p.cre + (160 * dg + 5 * m2) * DM, 6400); l2_prefetch(p.cim + (160 * dg + 5 * m2) * DM, 6400);
        asm volatile("prefetch.tensormap [%0];" ::"l"(&p.mG) : "memory");
      }
      const unsigned* hf = &g_hflag[(((lane < 16 ? (64 * m2) / 160 : (64 * m2 + 63) / 160) * 2 + 1) * 16 + min(lane & 15, 9)) * 8];
      mbar_wait(bars + 8 * (B_HST + 1));
      flag_poll(hf, tag);
      if (lane == 0) { mbar_arrive(bars + 8 * B_H1); TS(22); }
      mbar_wait(bars + 8 * (B_GO + 1));
      flag_poll(&g_gflag[(dg * 32 + lane) * 8], tag);
      fence_async_global();
      if (elect_one()) {
        TS(29);
        mbar_expect_tx(bars + 8 * B_GFULL, 20480);
        tma5(sb + G_OFF, &p.mG, 64 * m2, 0, 0, 0, 10 * dg, bars + 8 * B_GFULL);
      }
      mbar_wait(bars + 8 * (B_HST + 3));
      flag_poll(hf + NT1 * 256, tag);
      if (lane == 0) { mbar_arrive(bars + 8 * (B_H1 + 1)); TS(24); }
    }
    } else if (wg == 2 && (role >> 16)) {
      float acc[80];
      float off[2] = {mean0[0], mean0[1]};
      const unsigned tag = lds32(sb + EP_OFF + 20);
      dskip_init<true>(acc, mean0, rstd0);
      mbar_arrive(bars + 8 * B_XFREE);
#pragma unroll 1
      for (int l = 0; l < 2; l++) {
        float mean[2], rstd[2];
        {
          uint32_t alo = desc_lo(sb, 1024), blo = desc_lo(sb + G2_WOFF, 16);
          uint32_t fb = bars + 8 * (B_G2FULL + 20 * l);
          fence_regs(acc);
          mbar_wait(fb);
          if (tid == 256) TS(33 + 6 * l);
#pragma unroll 1
          for (int k = 0; k < 20; k++) {
            if (l == TSL && (k & 3) == 3 && tid == 256) TS(56 + (k >> 2));
            uint32_t ok; const uint32_t nb = k < 19 ? fb + 8 : fb;
            wgmma_fence();
#pragma unroll
            for (int kk = 0; kk < 4; kk++) {
              wgmma_n160<1>(acc, alo + kk * 128, desc_hi(128, 0), blo + kk * 2, desc_hi(1024, 1));
              if (kk == 0) ok = mbar_test(nb);
            }
            wgmma_commit();
            alo += G2_XB >> 4; blo += G2_WB >> 4;
            if (alo == desc_lo(sb + S2 * G2_XB, 1024)) { alo = desc_lo(sb, 1024); blo = desc_lo(sb + G2_WOFF, 16); }
            wgmma_wait<1>();
            if (k > 0 && tid == 256) mbar_arrive(fb + 8 * (B_G2DONE - B_G2FULL - 1));
            if (!ok) mbar_wait(nb);
            fb += 8;
          }
          wgmma_wait<0>();
          fence_regs(acc);
          if (tid == 256) TS(34 + 6 * l);
          if (tid == 256) mbar_arrive(bars + 8 * (B_G2DONE + 20 * l + 19));
        }
        ROLE(role)
        const int tq = tid_opaque() & 31, n0 = 64 * m2 + 16 * w + (tq >> 2);
        stats_publish<false>(2 * l + 1, n0, dg, tag, acc);
        uint32_t gf[10][4];
        mbar_wait(bars + 8 * B_GFULL);
        const uint32_t ga = sb + G_OFF + (8 * (tq >> 4) + (tq & 7)) * 128 + (((2 * w + ((tq >> 3) & 1)) ^ ((2 * m2) & 6) ^ (tq & 7)) << 4);
#pragma unroll
        for (int J = 0; J < 2; J++) ldsm4t(gf[J], ga + J * 2048);
        if (tid == 256) TS(35 + 6 * l);
        uint8_t* dst[2][2];
#pragma unroll
        for (int h = 0; h < 2; h++) {
          if (l == 0) {
            const int ng = 8 * m2 + 2 * w + h, T = ng / 20;
            uint8_t* ub = g_u + (T * 204800 + (ng - 20 * T) * 1024 + (tq & 2) * 64 + (tq & 28) * 4 + (tq & 1) * 8 + (5 * dg >> 1) * 20480);
            dst[h][1] = ub + ((dg & 1) ? 20480 - 512 : 0);
            dst[h][0] = ub + (dg & 1) * 512;
          } else {
            dst[h][0] = dst[h][1] = (uint8_t*)(p.out + (n_to_t(n0 + 8 * h) * DM + 160 * dg + 4 * (tq & 3)));
          }
        }
        stats_get(2 * l + 1, n0, tag, mean, rstd);
        if (tid == 256) TS(36 + 6 * l);
        off[0] += mean[0]; off[1] += mean[1];
        const float ov[2] = {l ? off[0] : 0.f, l ? off[1] : 0.f};
#pragma unroll
        for (int J = 0; J < 10; J++) {
          if (J + 2 < 10) ldsm4t(gf[J + 2 < 10 ? J + 2 : 0], ga + (J + 2) * 2048);
#pragma unroll
          for (int x = 0; x < 8; x++) {
            const int h = (x >> 1) & 1;
            const uint32_t gwd = gf[J][x >> 1];
            const float t = fmaf(rstd[h], (x & 1) ? bf_hi(gwd) : bf_lo(gwd), 1.f);
            acc[8 * J + x] = fmaf(acc[8 * J + x], t, fmaf(-mean[h], t, ov[h]));
          }
#pragma unroll
          for (int h = 0; h < 2; h++) {
            if (l == 0)
              *(uint2*)(dst[h][(J >> 1) & 1] + (J >> 2) * 20480 + (J & 3) * 256) =
                  make_uint2(pack_bf16(acc[8 * J + 2 * h], acc[8 * J + 2 * h + 1]), pack_bf16(acc[8 * J + 4 + 2 * h], acc[8 * J + 5 + 2 * h]));
            else
              *(float4*)(dst[h][0] + 64 * J) = make_float4(acc[8 * J + 2 * h], acc[8 * J + 2 * h + 1], acc[8 * J + 4 + 2 * h], acc[8 * J + 5 + 2 * h]);
          }
          __syncwarp();
        }
        if (l == 0) {
          bar_sync(3, 128);
          if (tid == 256) { TS(37); st_rel(&g_uflag[(4 * m2 + dg) * 8], tag); mbar_arrive(bars + 8 * B_GO); TS(38); }
          stats_publish<false>(2, n0, dg, tag, acc);
          mbar_wait(bars + 8 * (B_G1FULL + 11));
          float xa[2], xb[2];
          const uint4* x0 = &g_stats[(8 + (tq & 3)) * SEQ + n0];
          stat_table(T1, tag, 1, w, x0, x0 + 8, xa, xb);
          mbar_arrive(bars + 8 * (B_STAB + 1));
          if (tid == 256) TS(27);
          stats_reduce(xa, xb, mean, rstd);
          off[0] += mean[0]; off[1] += mean[1];
          mbar_wait(bars + 8 * (B_HST + 2));
          dskip_init<false>(acc, mean, rstd);
        } else {
          if (tid == 256) {
            TS(43);
            if (m2 == 31 && dg == 3) asm volatile("st.relaxed.gpu.global.u32 [%0], %1;" ::"l"(g_epoch), "r"(tag + 1) : "memory");
          }
        }
      }
    }
  }
}

typedef CUresult (*EncFn)(CUtensorMap*, CUtensorMapDataType, cuuint32_t, void*, const cuuint64_t*, const cuuint64_t*,
                          const cuuint32_t*, const cuuint32_t*, CUtensorMapInterleave, CUtensorMapSwizzle,
                          CUtensorMapL2promotion, CUtensorMapFloatOOBfill);

void encode(EncFn fn, CUtensorMap* m, const void* ptr, int rank, const cuuint64_t* dims, const cuuint64_t* strides, const cuuint32_t* box,
            CUtensorMapSwizzle swz = CU_TENSOR_MAP_SWIZZLE_128B) {
  cuuint32_t es[5] = {1, 1, 1, 1, 1};
  fn(m, CU_TENSOR_MAP_DATA_TYPE_BFLOAT16, rank, (void*)ptr, dims, strides, box, es, CU_TENSOR_MAP_INTERLEAVE_NONE,
     swz, (CUtensorMapL2promotion)(swz == CU_TENSOR_MAP_SWIZZLE_128B ? PROM_A : PROM_B), CU_TENSOR_MAP_FLOAT_OOB_FILL_NONE);
}

}

extern "C" void kernel_launch(void* const* d_in, const int* in_sizes, int n_in, void* d_out, int out_size) {
  (void)in_sizes; (void)n_in; (void)out_size;
  Params p;
  typedef const __nv_bfloat16* BP;
  p.x = (BP)d_in[0]; p.lre = (BP)d_in[1]; p.lim = (BP)d_in[2]; p.bre = (BP)d_in[3]; p.bim = (BP)d_in[4];
  p.cre = (BP)d_in[5]; p.cim = (BP)d_in[6]; p.logdt = (BP)d_in[7]; p.dskip = (BP)d_in[8];
  p.k = (BP)d_in[10]; p.v = (BP)d_in[11]; p.shiftk = (BP)d_in[12]; p.ssmk = (BP)d_in[13]; p.ssmD = (BP)d_in[14];
  p.out = (float*)d_out;
  for (int sm = 0; sm < 132; sm++) {
    const int tpc = sm >> 1, side = sm & 1;
    int gpc, gi;
    if (tpc < 32) { gpc = tpc & 7; gi = tpc >> 3; }
    else if (tpc < 60) { gpc = 1 + (tpc - 32) % 7; gi = 4 + (tpc - 32) / 7; }
    else if (tpc < 62) { gpc = tpc - 54; gi = 8; }
    else { gpc = 0; gi = tpc - 58; }
    const int pos = 8 * gpc + gi + (gpc == 7 ? 1 : 0);
    int T1, GP;
    if (pos < 52) { const int hh = pos / 26, x = pos - 26 * hh; T1 = x >> 1; GP = 2 * hh + (x & 1); }
    else { T1 = pos - 52; GP = 4; }
    const int m2 = 8 * (gpc >> 1) + gi, dg = 2 * (gpc & 1) + side;
    p.role[sm] = pos == 65 ? -1 : (T1 | (GP << 4) | (side << 7) | (m2 << 8) | (dg << 14) | ((gi < 8) << 16));
  }
  void* fnp = nullptr;
  cudaDriverEntryPointQueryResult qr;
  cudaGetDriverEntryPoint("cuTensorMapEncodeTiled", &fnp, cudaEnableDefault, &qr);
  EncFn fn = (EncFn)fnp;
  void* gG = nullptr;
  cudaGetSymbolAddress(&gG, g_G);
  const cuuint64_t RB = DM * 2;
  {
    p.swap = p.bim < p.bre;
    const char* lo = (const char*)(p.swap ? p.bim : p.bre); const char* hi = (const char*)(p.swap ? p.bre : p.bim);
    cuuint64_t dims[5] = {640, 8, 2, 8, 10}, st[4] = {RB, (cuuint64_t)(hi - lo), 8 * RB, 64 * RB}; cuuint32_t box[5] = {64, 8, 2, 4, 2};
    encode(fn, &p.mB, lo, 5, dims, st, box);
  }
  {
    cuuint64_t dims[5] = {640, 2, 4, 2, 40}, st[4] = {RB, 4 * RB, 2 * RB, 16 * RB}; cuuint32_t box[5] = {64, 2, 4, 2, 10};
    encode(fn, &p.mCre, p.cre, 5, dims, st, box); encode(fn, &p.mCim, p.cim, 5, dims, st, box);
    cuuint64_t dimg[5] = {2048, 2, 4, 2, 40}, stg[4] = {4096, 4 * 4096, 2 * 4096, 16 * 4096};
    encode(fn, &p.mG, gG, 5, dimg, stg, box);
  }
  {
    cuuint64_t dims[4] = {640, 2, 4, 900}, st[3] = {RB, 40 * RB, 2 * RB}; cuuint32_t box[4] = {64, 2, 4, 20};
    encode(fn, &p.mX, p.x, 4, dims, st, box);
    cuuint64_t diml[4] = {640, 2, 4, 16}, stl[3] = {RB, 32 * RB, 2 * RB};
    encode(fn, &p.mXl, p.x + (size_t)1920 * DM, 4, diml, stl, box);
    cuuint32_t boxt[4] = {160, 2, 4, 4};
    encode(fn, &p.mXt, p.x, 4, dims, st, boxt, CU_TENSOR_MAP_SWIZZLE_NONE);
    encode(fn, &p.mXtl, p.x + (size_t)1920 * DM, 4, diml, stl, boxt, CU_TENSOR_MAP_SWIZZLE_NONE);
    cuuint64_t dk[3] = {640, 2000, 4}, sk[2] = {RB, 16 * RB}; cuuint32_t bk[3] = {32, 19, 4}, bv[3] = {32, 17, 4};
    encode(fn, &p.mK, p.k, 3, dk, sk, bk, CU_TENSOR_MAP_SWIZZLE_NONE);
    encode(fn, &p.mV, p.v, 3, dk, sk, bv, CU_TENSOR_MAP_SWIZZLE_NONE);
  }
  cudaFuncSetAttribute(fused_kernel, cudaFuncAttributeMaxDynamicSharedMemorySize, SMEM_BYTES);
  cudaLaunchConfig_t cfg = {};
  cfg.gridDim = dim3(132); cfg.blockDim = dim3(512); cfg.dynamicSmemBytes = SMEM_BYTES; cfg.stream = cudaStreamPerThread;
  cudaLaunchKernelEx(&cfg, fused_kernel, p);
}
```

```cpp
#include <cuda_runtime.h>
#include <cuda.h>
#include <cuda_bf16.h>
#include <stdint.h>

namespace {

constexpr int SEQ = 2048, DM = 640;
constexpr int NT1 = 13;
#define EXP 0
#define WPF1 3
#define WPF2 7
#define CPOLL 10
#define KV0 5
#define TAP0 2
#define PROM_A 2
#define PROM_B 2
#define XFIRST 0
#define TAPLATE 1
#define STG_D 3
#define STG_KK 1
#define HOLD0 1
#define WREL 0
#define UREL 1
#define TSL 1
#define TABW 0
#define STG0 3
#define SYNCW 0
#define PAUSE_K 4
constexpr uint32_t SPIN_LIMIT = 1u << 22;

__device__ __align__(1024) uint8_t g_h[2 * 32 * 20 * 8192];
__device__ __align__(1024) uint8_t g_u[NT1 * 10 * 20480];
__device__ __align__(1024) uint8_t g_kv[DM * 4096];
__device__ __align__(1024) uint8_t g_G[DM * 4096];
__device__ __align__(128) uint4 g_E[2 * NT1 * DM];
__device__ __align__(128) uint4 g_stats[4 * 4 * SEQ];
__device__ __align__(128) uint4 g_sB[DM * 2];
__device__ __align__(128) unsigned g_hflag[2 * NT1 * 2 * 16 * 8];
__device__ __align__(128) unsigned g_uflag[32 * 4 * 8];
__device__ __align__(128) unsigned g_kvflag[4 * 32 * 8];
__device__ __align__(128) unsigned g_gflag[4 * 32 * 8];
__device__ __align__(128) unsigned g_rflag[128 * 8];
__device__ __align__(128) unsigned g_epoch[32] = {1};
#define TS(i) do {} while (0)

struct Params {
  CUtensorMap mB, mCre, mCim, mX, mXl, mG, mK, mV, mXt, mXtl;
  const __nv_bfloat16 *x, *lre, *lim, *bre, *bim, *cre, *cim, *logdt, *dskip, *k, *v, *shiftk, *ssmk, *ssmD;
  float* out;
  int swap;
  int role[132];
};

constexpr uint32_t sb = 1024;
constexpr uint32_t G1_STAGE = 36864, G1_XOFF = 16384;
constexpr int S1 = 4;
constexpr uint32_t XT_OFF = 159744, KS_OFF = 180224, KV_PIECE = 9216;
constexpr uint32_t G2_XB = 8192, G2_WB = 20480, G2_WOFF = 57344, G_OFF = 200704;
constexpr int S2 = 7;
constexpr uint32_t CV_OFF = KS_OFF, CV_K = 128, CV_PL = 2240, CV_U = CV_K + 4096, CV_B = KV_PIECE;
constexpr uint32_t MISC = 226304;
constexpr uint32_t BAR_OFF = MISC;
constexpr int B_G1FULL = 0, B_G1DONE = 20, B_G2FULL = 40, B_CVFULL = 80  ,
              B_G2DONE = 85, B_GFULL = 125, B_EP = 126, B_H1 = 127  , B_STG = 134  , B_REL = 136  , B_SFREE = 138,
              B_GO = 139  , B_PUB = 147,
              B_CVDONE = 148  , B_STAB = 153  , B_XFREE = 155, B_HST = 156  ,
              B_CTAB = 160, B_PREP = 161, B_XT = 162, B_KV = 163  ;
constexpr uint32_t bars = sb + BAR_OFF;
constexpr uint32_t STAB_OFF = MISC + 1344;
constexpr uint32_t CTAB_OFF = STAB_OFF + 1280;
constexpr uint32_t DTAB_OFF = CTAB_OFF + 1536;
constexpr uint32_t EP_OFF = DTAB_OFF + 320;
constexpr uint32_t SO_OFF = EP_OFF + 32;
constexpr uint32_t TAP_OFF = 147456;
constexpr uint32_t SMEM_BYTES = 232448;
static_assert(SO_OFF + 1536 <= SMEM_BYTES, "smem");

__device__ __forceinline__ void trap_if(bool c) { asm volatile("{\n.reg .pred p;\nsetp.ne.u32 p, %0, 0;\n@p trap;\n}\n" ::"r"((uint32_t)c)); }
__device__ __forceinline__ uint32_t smem_u32(const void* p) { return (uint32_t)__cvta_generic_to_shared(p); }
__device__ __forceinline__ void mbar_init(uint32_t bar, int cnt) { asm volatile("mbarrier.init.shared::cta.b64 [%0], %1;" ::"r"(bar), "r"(cnt) : "memory"); }
__device__ __forceinline__ void mbar_expect_tx(uint32_t bar, int bytes) { asm volatile("mbarrier.arrive.expect_tx.shared::cta.b64 _, [%0], %1;" ::"r"(bar), "r"(bytes) : "memory"); }
__device__ __forceinline__ void mbar_arrive(uint32_t bar) { asm volatile("mbarrier.arrive.shared::cta.b64 _, [%0];" ::"r"(bar) : "memory"); }
__device__ __forceinline__ void mbar_wait(uint32_t bar) {
  asm volatile(
      "{\n.reg .pred p;\n.reg .u32 c;\nmov.u32 c, 0;\n"
      "W_%=:\nmbarrier.try_wait.parity.shared::cta.b64 p, [%0], 0;\n@p bra D_%=;\n"
      "add.u32 c, c, 1;\nsetp.lt.u32 p, c, %1;\n@p bra W_%=;\ntrap;\nD_%=:\n}\n" ::"r"(bar), "n"(SPIN_LIMIT) : "memory");
}
__device__ __forceinline__ uint32_t mbar_test(uint32_t bar) {
  uint32_t ok;
  asm volatile("{\n.reg .pred p;\nmbarrier.test_wait.parity.shared::cta.b64 p, [%1], 0;\nselp.u32 %0, 1, 0, p;\n}\n" : "=r"(ok) : "r"(bar) : "memory");
  return ok;
}
__device__ __forceinline__ void tma3(uint32_t dst, const CUtensorMap* m, int c0, int c1, int c2, uint32_t bar) {
  asm volatile("cp.async.bulk.tensor.3d.shared::cluster.global.mbarrier::complete_tx::bytes [%0], [%1, {%3,%4,%5}], [%2];"
               ::"r"(dst), "l"(m), "r"(bar), "r"(c0), "r"(c1), "r"(c2) : "memory");
}
__device__ __forceinline__ void tma4(uint32_t dst, const CUtensorMap* m, int c0, int c1, int c2, int c3, uint32_t bar) {
  asm volatile("cp.async.bulk.tensor.4d.shared::cluster.global.mbarrier::complete_tx::bytes [%0], [%1, {%3,%4,%5,%6}], [%2];"
               ::"r"(dst), "l"(m), "r"(bar), "r"(c0), "r"(c1), "r"(c2), "r"(c3) : "memory");
}
__device__ __forceinline__ void tma5(uint32_t dst, const CUtensorMap* m, int c0, int c1, int c2, int c3, int c4, uint32_t bar) {
  asm volatile("cp.async.bulk.tensor.5d.shared::cluster.global.mbarrier::complete_tx::bytes [%0], [%1, {%3,%4,%5,%6,%7}], [%2];"
               ::"r"(dst), "l"(m), "r"(bar), "r"(c0), "r"(c1), "r"(c2), "r"(c3), "r"(c4) : "memory");
}
__device__ __forceinline__ void bulk_g2s(uint32_t dst, const void* src, int bytes, uint32_t bar) {
  asm volatile("cp.async.bulk.shared::cluster.global.mbarrier::complete_tx::bytes [%0], [%1], %2, [%3];"
               ::"r"(dst), "l"(src), "r"(bytes), "r"(bar) : "memory");
}
__device__ __forceinline__ void bulk_s2g(void* dst, uint32_t src, int bytes) {
  asm volatile("cp.async.bulk.global.shared::cta.bulk_group [%0], [%1], %2;" ::"l"(dst), "r"(src), "r"(bytes) : "memory");
}
__device__ __forceinline__ void l2_prefetch(const void* src, int bytes) {
  asm volatile("cp.async.bulk.prefetch.L2.global [%0], %1;" ::"l"(src), "r"(bytes) : "memory");
}
__device__ __forceinline__ void wgmma_fence() { asm volatile("wgmma.fence.sync.aligned;" ::: "memory"); }
__device__ __forceinline__ void wgmma_commit() { asm volatile("wgmma.commit_group.sync.aligned;" ::: "memory"); }
template <int N> __device__ __forceinline__ void wgmma_wait() { asm volatile("wgmma.wait_group.sync.aligned %0;" ::"n"(N) : "memory"); }
__host__ __device__ constexpr uint32_t desc_lo(uint32_t addr, uint32_t lbo) { return ((addr & 0x3FFFF) >> 4) | ((lbo >> 4) << 16); }
__host__ __device__ constexpr uint32_t desc_hi(uint32_t sbo, uint32_t swz) { return (sbo >> 4) | (swz << 30); }
__device__ __forceinline__ void bar_sync(int id, int n) { asm volatile("bar.sync %0, %1;" ::"r"(id), "r"(n) : "memory"); }
__device__ __forceinline__ uint32_t lds32(uint32_t a) { uint32_t v; asm volatile("ld.shared.u32 %0, [%1];" : "=r"(v) : "r"(a) : "memory"); return v; }
__device__ __forceinline__ float2 lds64f(uint32_t a) { float2 v; asm volatile("ld.shared.v2.f32 {%0,%1}, [%2];" : "=f"(v.x), "=f"(v.y) : "r"(a) : "memory"); return v; }
__device__ __forceinline__ float4 lds128f(uint32_t a) { float4 v; asm volatile("ld.shared.v4.f32 {%0,%1,%2,%3}, [%4];" : "=f"(v.x), "=f"(v.y), "=f"(v.z), "=f"(v.w) : "r"(a) : "memory"); return v; }
__device__ __forceinline__ void ldsm4t(uint32_t (&r)[4], uint32_t a) {
  asm volatile("ldmatrix.sync.aligned.m8n8.x4.trans.shared.b16 {%0,%1,%2,%3}, [%4];" : "=r"(r[0]), "=r"(r[1]), "=r"(r[2]), "=r"(r[3]) : "r"(a) : "memory");
}
__device__ __forceinline__ uint4 ldv128(const void* a) { uint4 v; asm volatile("ld.global.nc.v4.u32 {%0,%1,%2,%3}, [%4];" : "=r"(v.x), "=r"(v.y), "=r"(v.z), "=r"(v.w) : "l"(a) : "memory"); return v; }
__device__ __forceinline__ uint2 ldv64(const void* a) { uint2 v; asm volatile("ld.global.nc.v2.u32 {%0,%1}, [%2];" : "=r"(v.x), "=r"(v.y) : "l"(a) : "memory"); return v; }
__device__ __forceinline__ uint32_t ldv16(const void* a) { uint32_t v; asm volatile("ld.global.nc.u16 %0, [%1];" : "=r"(v) : "l"(a) : "memory"); return v; }
__device__ __forceinline__ void sts128(uint32_t a, uint4 v) { asm volatile("st.shared.v4.u32 [%0], {%1,%2,%3,%4};" ::"r"(a), "r"(v.x), "r"(v.y), "r"(v.z), "r"(v.w) : "memory"); }
__device__ __forceinline__ void sts32(uint32_t a, uint32_t v) { asm volatile("st.shared.u32 [%0], %1;" ::"r"(a), "r"(v) : "memory"); }
__device__ __forceinline__ void sts64f(uint32_t a, float x, float y) { asm volatile("st.shared.v2.f32 [%0], {%1,%2};" ::"r"(a), "f"(x), "f"(y) : "memory"); }
__device__ __forceinline__ void st_rel(unsigned* p, unsigned v) { asm volatile("st.release.gpu.global.u32 [%0], %1;" ::"l"(p), "r"(v) : "memory"); }
__device__ __forceinline__ void fence_async_global() { asm volatile("fence.proxy.async.global;" ::: "memory"); }
__device__ __forceinline__ void fence_async_smem() { asm volatile("fence.proxy.async.shared::cta;" ::: "memory"); }
__device__ __forceinline__ void rec_st(uint4* p, float a, float b, unsigned tag) {
  asm volatile("{\n.reg .b128 t;\n.reg .b64 lo, hi;\nmov.b64 lo, {%1,%2};\nmov.b64 hi, {%3,%3};\nmov.b128 t, {lo,hi};\n"
               "st.relaxed.gpu.global.b128 [%0], t;\n}\n" ::"l"(p), "r"(__float_as_uint(a)), "r"(__float_as_uint(b)), "r"(tag) : "memory");
}
__device__ __forceinline__ unsigned rec_ld(const uint4* p, float& a, float& b) {
  unsigned x, y, t;
  asm volatile("{\n.reg .b128 t;\n.reg .b64 lo, hi;\n.reg .b32 u;\nld.relaxed.gpu.global.b128 t, [%3];\nmov.b128 {lo,hi}, t;\n"
               "mov.b64 {%0,%1}, lo;\nmov.b64 {%2,u}, hi;\n}\n" : "=r"(x), "=r"(y), "=r"(t) : "l"(p) : "memory");
  a = __uint_as_float(x); b = __uint_as_float(y);
  return t;
}
__device__ __forceinline__ unsigned ld_rlx(const unsigned* p) { unsigned v; asm volatile("ld.relaxed.gpu.global.u32 %0, [%1];" : "=r"(v) : "l"(p) : "memory"); return v; }
__device__ __forceinline__ void flag_poll(const unsigned* p, unsigned target) {
  uint32_t it = 0;
  while (!__all_sync(0xffffffffu, (int)(ld_rlx(p) - target) >= 0)) { trap_if(++it > SPIN_LIMIT); }
  asm volatile("fence.acquire.gpu;" ::: "memory");
}
__device__ __forceinline__ uint32_t pack_bf16(float lo, float hi) {
  uint32_t r; asm("cvt.rn.bf16x2.f32 %0, %1, %2;" : "=r"(r) : "f"(hi), "f"(lo)); return r;
}
__device__ __forceinline__ float bf_lo(uint32_t w) { return __uint_as_float(w << 16); }
__device__ __forceinline__ float bf_hi(uint32_t w) { return __uint_as_float(w & 0xffff0000u); }
__device__ __forceinline__ uint32_t hmul2(uint32_t a, uint32_t b) {
  __nv_bfloat162 r = __hmul2_rn(*(__nv_bfloat162*)&a, *(__nv_bfloat162*)&b); return *(uint32_t*)&r;
}
__device__ __forceinline__ uint32_t hadd2(uint32_t a, uint32_t b) {
  __nv_bfloat162 r = __hadd2_rn(*(__nv_bfloat162*)&a, *(__nv_bfloat162*)&b); return *(uint32_t*)&r;
}
__device__ __forceinline__ float2 cmul(float2 a, float2 b) { return make_float2(a.x * b.x - a.y * b.y, a.x * b.y + a.y * b.x); }
__device__ __forceinline__ float2 cfma(float2 a, float2 b, float2 c) {
  return make_float2(fmaf(a.x, b.x, fmaf(-a.y, b.y, c.x)), fmaf(a.x, b.y, fmaf(a.y, b.x, c.y)));
}
template <int N> __device__ __forceinline__ void fence_regs(float (&a)[N]) {
#pragma unroll
  for (int i = 0; i < N; i++) asm volatile("" : "+f"(a[i])::"memory");
}
__device__ __forceinline__ bool elect_one() {
  uint32_t e; asm volatile("{\n.reg .pred P;\nelect.sync _|P, 0xffffffff;\nselp.u32 %0, 1, 0, P;\n}\n" : "=r"(e)); return e != 0;
}
__device__ __forceinline__ int tid_opaque() { int t; asm volatile("mov.u32 %0, %%tid.x;" : "=r"(t)); return t; }
struct Role { int T1, GP, side, m2, dg, cch0; bool last, has2; };
__device__ __forceinline__ Role unpack_role(int x) {
  Role r; r.T1 = x & 15; r.GP = (x >> 4) & 7; r.side = (x >> 7) & 1; r.m2 = (x >> 8) & 63; r.dg = (x >> 14) & 3;
  r.has2 = (x >> 16) & 1; r.last = r.T1 == NT1 - 1; r.cch0 = 160 * r.dg + r.m2; return r;
}
__device__ __forceinline__ Role fresh_role(int x) { asm volatile("" : "+r"(x)); return unpack_role(__shfl_sync(0xffffffffu, x, 0)); }
#define ROLE(x) const Role R_ = fresh_role(x); const int T1 = R_.T1, GP = R_.GP, side = R_.side, m2 = R_.m2, dg = R_.dg, cch0 = R_.cch0; \
  const bool last = R_.last, has2 = R_.has2; (void)T1; (void)GP; (void)side; (void)m2; (void)dg; (void)cch0; (void)last; (void)has2;
__device__ __forceinline__ int n_to_t(int n) {
  int T = n / 160, nl = n - T * 160;
  int L = (T == NT1 - 1) ? 32 : 40;
  return T * 160 + L * ((nl & 7) >> 1) + 2 * (nl >> 3) + (nl & 1);
}

template<int TA> __device__ __forceinline__ void wgmma_n160(float (&d)[80], uint32_t alo, uint32_t ahi, uint32_t blo, uint32_t bhi){
  asm volatile("{\n.reg .b64 da, db;\nmov.b64 da, {%80,%81};\nmov.b64 db, {%82,%83};\n"
    "wgmma.mma_async.sync.aligned.m64n160k16.f32.bf16.bf16 {%0, %1, %2, %3, %4, %5, %6, %7, %8, %9, %10, %11, %12, %13, %14, %15, %16, %17, %18, %19, %20, %21, %22, %23, %24, %25, %26, %27, %28, %29, %30, %31, %32, %33, %34, %35, %36, %37, %38, %39, %40, %41, %42, %43, %44, %45, %46, %47, %48, %49, %50, %51, %52, %53, %54, %55, %56, %57, %58, %59, %60, %61, %62, %63, %64, %65, %66, %67, %68, %69, %70, %71, %72, %73, %74, %75, %76, %77, %78, %79}, da, db, 1, 1, 1, %84, 0;\n}\n"
    : "+f"(d[0]), "+f"(d[1]), "+f"(d[2]), "+f"(d[3]), "+f"(d[4]), "+f"(d[5]), "+f"(d[6]), "+f"(d[7]), "+f"(d[8]), "+f"(d[9]), "+f"(d[10]), "+f"(d[11]), "+f"(d[12]), "+f"(d[13]), "+f"(d[14]), "+f"(d[15]), "+f"(d[16]), "+f"(d[17]), "+f"(d[18]), "+f"(d[19]), "+f"(d[20]), "+f"(d[21]), "+f"(d[22]), "+f"(d[23]), "+f"(d[24]), "+f"(d[25]), "+f"(d[26]), "+f"(d[27]), "+f"(d[28]), "+f"(d[29]), "+f"(d[30]), "+f"(d[31]), "+f"(d[32]), "+f"(d[33]), "+f"(d[34]), "+f"(d[35]), "+f"(d[36]), "+f"(d[37]), "+f"(d[38]), "+f"(d[39]), "+f"(d[40]), "+f"(d[41]), "+f"(d[42]), "+f"(d[43]), "+f"(d[44]), "+f"(d[45]), "+f"(d[46]), "+f"(d[47]), "+f"(d[48]), "+f"(d[49]), "+f"(d[50]), "+f"(d[51]), "+f"(d[52]), "+f"(d[53]), "+f"(d[54]), "+f"(d[55]), "+f"(d[56]), "+f"(d[57]), "+f"(d[58]), "+f"(d[59]), "+f"(d[60]), "+f"(d[61]), "+f"(d[62]), "+f"(d[63]), "+f"(d[64]), "+f"(d[65]), "+f"(d[66]), "+f"(d[67]), "+f"(d[68]), "+f"(d[69]), "+f"(d[70]), "+f"(d[71]), "+f"(d[72]), "+f"(d[73]), "+f"(d[74]), "+f"(d[75]), "+f"(d[76]), "+f"(d[77]), "+f"(d[78]), "+f"(d[79])
    : "r"(alo), "r"(ahi), "r"(blo), "r"(bhi), "n"(TA));
}
template<int N> __device__ __forceinline__ void wgmma_rs_hi(float (&d)[64], uint32_t a0, uint32_t a1, uint32_t a2, uint32_t a3, uint32_t blo);
template<> __device__ __forceinline__ void wgmma_rs_hi<16>(float (&d)[64], uint32_t a0, uint32_t a1, uint32_t a2, uint32_t a3, uint32_t blo){
  asm volatile("{\n.reg .b64 db;\nmov.b64 db, {%12,8};\nwgmma.mma_async.sync.aligned.m64n16k16.f32.bf16.bf16 {%0, %1, %2, %3, %4, %5, %6, %7}, {%8,%9,%10,%11}, db, 1, 1, 1, 0;\n}\n"
    : "+f"(d[56]), "+f"(d[57]), "+f"(d[58]), "+f"(d[59]), "+f"(d[60]), "+f"(d[61]), "+f"(d[62]), "+f"(d[63])
    : "r"(a0), "r"(a1), "r"(a2), "r"(a3), "r"(blo));
}
template<> __device__ __forceinline__ void wgmma_rs_hi<32>(float (&d)[64], uint32_t a0, uint32_t a1, uint32_t a2, uint32_t a3, uint32_t blo){
  asm volatile("{\n.reg .b64 db;\nmov.b64 db, {%20,8};\nwgmma.mma_async.sync.aligned.m64n32k16.f32.bf16.bf16 {%0, %1, %2, %3, %4, %5, %6, %7, %8, %9, %10, %11, %12, %13, %14, %15}, {%16,%17,%18,%19}, db, 1, 1, 1, 0;\n}\n"
    : "+f"(d[48]), "+f"(d[49]), "+f"(d[50]), "+f"(d[51]), "+f"(d[52]), "+f"(d[53]), "+f"(d[54]), "+f"(d[55]), "+f"(d[56]), "+f"(d[57]), "+f"(d[58]), "+f"(d[59]), "+f"(d[60]), "+f"(d[61]), "+f"(d[62]), "+f"(d[63])
    : "r"(a0), "r"(a1), "r"(a2), "r"(a3), "r"(blo));
}
template<> __device__ __forceinline__ void wgmma_rs_hi<48>(float (&d)[64], uint32_t a0, uint32_t a1, uint32_t a2, uint32_t a3, uint32_t blo){
  asm volatile("{\n.reg .b64 db;\nmov.b64 db, {%28,8};\nwgmma.mma_async.sync.aligned.m64n48k16.f32.bf16.bf16 {%0, %1, %2, %3, %4, %5, %6, %7, %8, %9, %10, %11, %12, %13, %14, %15, %16, %17, %18, %19, %20, %21, %22, %23}, {%24,%25,%26,%27}, db, 1, 1, 1, 0;\n}\n"
    : "+f"(d[40]), "+f"(d[41]), "+f"(d[42]), "+f"(d[43]), "+f"(d[44]), "+f"(d[45]), "+f"(d[46]), "+f"(d[47]), "+f"(d[48]), "+f"(d[49]), "+f"(d[50]), "+f"(d[51]), "+f"(d[52]), "+f"(d[53]), "+f"(d[54]), "+f"(d[55]), "+f"(d[56]), "+f"(d[57]), "+f"(d[58]), "+f"(d[59]), "+f"(d[60]), "+f"(d[61]), "+f"(d[62]), "+f"(d[63])
    : "r"(a0), "r"(a1), "r"(a2), "r"(a3), "r"(blo));
}
template<> __device__ __forceinline__ void wgmma_rs_hi<64>(float (&d)[64], uint32_t a0, uint32_t a1, uint32_t a2, uint32_t a3, uint32_t blo){
  asm volatile("{\n.reg .b64 db;\nmov.b64 db, {%36,8};\nwgmma.mma_async.sync.aligned.m64n64k16.f32.bf16.bf16 {%0, %1, %2, %3, %4, %5, %6, %7, %8, %9, %10, %11, %12, %13, %14, %15, %16, %17, %18, %19, %20, %21, %22, %23, %24, %25, %26, %27, %28, %29, %30, %31}, {%32,%33,%34,%35}, db, 1, 1, 1, 0;\n}\n"
    : "+f"(d[32]), "+f"(d[33]), "+f"(d[34]), "+f"(d[35]), "+f"(d[36]), "+f"(d[37]), "+f"(d[38]), "+f"(d[39]), "+f"(d[40]), "+f"(d[41]), "+f"(d[42]), "+f"(d[43]), "+f"(d[44]), "+f"(d[45]), "+f"(d[46]), "+f"(d[47]), "+f"(d[48]), "+f"(d[49]), "+f"(d[50]), "+f"(d[51]), "+f"(d[52]), "+f"(d[53]), "+f"(d[54]), "+f"(d[55]), "+f"(d[56]), "+f"(d[57]), "+f"(d[58]), "+f"(d[59]), "+f"(d[60]), "+f"(d[61]), "+f"(d[62]), "+f"(d[63])
    : "r"(a0), "r"(a1), "r"(a2), "r"(a3), "r"(blo));
}
template<> __device__ __forceinline__ void wgmma_rs_hi<80>(float (&d)[64], uint32_t a0, uint32_t a1, uint32_t a2, uint32_t a3, uint32_t blo){
  asm volatile("{\n.reg .b64 db;\nmov.b64 db, {%44,8};\nwgmma.mma_async.sync.aligned.m64n80k16.f32.bf16.bf16 {%0, %1, %2, %3, %4, %5, %6, %7, %8, %9, %10, %11, %12, %13, %14, %15, %16, %17, %18, %19, %20, %21, %22, %23, %24, %25, %26, %27, %28, %29, %30, %31, %32, %33, %34, %35, %36, %37, %38, %39}, {%40,%41,%42,%43}, db, 1, 1, 1, 0;\n}\n"
    : "+f"(d[24]), "+f"(d[25]), "+f"(d[26]), "+f"(d[27]), "+f"(d[28]), "+f"(d[29]), "+f"(d[30]), "+f"(d[31]), "+f"(d[32]), "+f"(d[33]), "+f"(d[34]), "+f"(d[35]), "+f"(d[36]), "+f"(d[37]), "+f"(d[38]), "+f"(d[39]), "+f"(d[40]), "+f"(d[41]), "+f"(d[42]), "+f"(d[43]), "+f"(d[44]), "+f"(d[45]), "+f"(d[46]), "+f"(d[47]), "+f"(d[48]), "+f"(d[49]), "+f"(d[50]), "+f"(d[51]), "+f"(d[52]), "+f"(d[53]), "+f"(d[54]), "+f"(d[55]), "+f"(d[56]), "+f"(d[57]), "+f"(d[58]), "+f"(d[59]), "+f"(d[60]), "+f"(d[61]), "+f"(d[62]), "+f"(d[63])
    : "r"(a0), "r"(a1), "r"(a2), "r"(a3), "r"(blo));
}
template<> __device__ __forceinline__ void wgmma_rs_hi<96>(float (&d)[64], uint32_t a0, uint32_t a1, uint32_t a2, uint32_t a3, uint32_t blo){
  asm volatile("{\n.reg .b64 db;\nmov.b64 db, {%52,8};\nwgmma.mma_async.sync.aligned.m64n96k16.f32.bf16.bf16 {%0, %1, %2, %3, %4, %5, %6, %7, %8, %9, %10, %11, %12, %13, %14, %15, %16, %17, %18, %19, %20, %21, %22, %23, %24, %25, %26, %27, %28, %29, %30, %31, %32, %33, %34, %35, %36, %37, %38, %39, %40, %41, %42, %43, %44, %45, %46, %47}, {%48,%49,%50,%51}, db, 1, 1, 1, 0;\n}\n"
    : "+f"(d[16]), "+f"(d[17]), "+f"(d[18]), "+f"(d[19]), "+f"(d[20]), "+f"(d[21]), "+f"(d[22]), "+f"(d[23]), "+f"(d[24]), "+f"(d[25]), "+f"(d[26]), "+f"(d[27]), "+f"(d[28]), "+f"(d[29]), "+f"(d[30]), "+f"(d[31]), "+f"(d[32]), "+f"(d[33]), "+f"(d[34]), "+f"(d[35]), "+f"(d[36]), "+f"(d[37]), "+f"(d[38]), "+f"(d[39]), "+f"(d[40]), "+f"(d[41]), "+f"(d[42]), "+f"(d[43]), "+f"(d[44]), "+f"(d[45]), "+f"(d[46]), "+f"(d[47]), "+f"(d[48]), "+f"(d[49]), "+f"(d[50]), "+f"(d[51]), "+f"(d[52]), "+f"(d[53]), "+f"(d[54]), "+f"(d[55]), "+f"(d[56]), "+f"(d[57]), "+f"(d[58]), "+f"(d[59]), "+f"(d[60]), "+f"(d[61]), "+f"(d[62]), "+f"(d[63])
    : "r"(a0), "r"(a1), "r"(a2), "r"(a3), "r"(blo));
}
template<> __device__ __forceinline__ void wgmma_rs_hi<112>(float (&d)[64], uint32_t a0, uint32_t a1, uint32_t a2, uint32_t a3, uint32_t blo){
  asm volatile("{\n.reg .b64 db;\nmov.b64 db, {%60,8};\nwgmma.mma_async.sync.aligned.m64n112k16.f32.bf16.bf16 {%0, %1, %2, %3, %4, %5, %6, %7, %8, %9, %10, %11, %12, %13, %14, %15, %16, %17, %18, %19, %20, %21, %22, %23, %24, %25, %26, %27, %28, %29, %30, %31, %32, %33, %34, %35, %36, %37, %38, %39, %40, %41, %42, %43, %44, %45, %46, %47, %48, %49, %50, %51, %52, %53, %54, %55}, {%56,%57,%58,%59}, db, 1, 1, 1, 0;\n}\n"
    : "+f"(d[8]), "+f"(d[9]), "+f"(d[10]), "+f"(d[11]), "+f"(d[12]), "+f"(d[13]), "+f"(d[14]), "+f"(d[15]), "+f"(d[16]), "+f"(d[17]), "+f"(d[18]), "+f"(d[19]), "+f"(d[20]), "+f"(d[21]), "+f"(d[22]), "+f"(d[23]), "+f"(d[24]), "+f"(d[25]), "+f"(d[26]), "+f"(d[27]), "+f"(d[28]), "+f"(d[29]), "+f"(d[30]), "+f"(d[31]), "+f"(d[32]), "+f"(d[33]), "+f"(d[34]), "+f"(d[35]), "+f"(d[36]), "+f"(d[37]), "+f"(d[38]), "+f"(d[39]), "+f"(d[40]), "+f"(d[41]), "+f"(d[42]), "+f"(d[43]), "+f"(d[44]), "+f"(d[45]), "+f"(d[46]), "+f"(d[47]), "+f"(d[48]), "+f"(d[49]), "+f"(d[50]), "+f"(d[51]), "+f"(d[52]), "+f"(d[53]), "+f"(d[54]), "+f"(d[55]), "+f"(d[56]), "+f"(d[57]), "+f"(d[58]), "+f"(d[59]), "+f"(d[60]), "+f"(d[61]), "+f"(d[62]), "+f"(d[63])
    : "r"(a0), "r"(a1), "r"(a2), "r"(a3), "r"(blo));
}
template<> __device__ __forceinline__ void wgmma_rs_hi<128>(float (&d)[64], uint32_t a0, uint32_t a1, uint32_t a2, uint32_t a3, uint32_t blo){
  asm volatile("{\n.reg .b64 db;\nmov.b64 db, {%68,8};\nwgmma.mma_async.sync.aligned.m64n128k16.f32.bf16.bf16 {%0, %1, %2, %3, %4, %5, %6, %7, %8, %9, %10, %11, %12, %13, %14, %15, %16, %17, %18, %19, %20, %21, %22, %23, %24, %25, %26, %27, %28, %29, %30, %31, %32, %33, %34, %35, %36, %37, %38, %39, %40, %41, %42, %43, %44, %45, %46, %47, %48, %49, %50, %51, %52, %53, %54, %55, %56, %57, %58, %59, %60, %61, %62, %63}, {%64,%65,%66,%67}, db, 1, 1, 1, 0;\n}\n"
    : "+f"(d[0]), "+f"(d[1]), "+f"(d[2]), "+f"(d[3]), "+f"(d[4]), "+f"(d[5]), "+f"(d[6]), "+f"(d[7]), "+f"(d[8]), "+f"(d[9]), "+f"(d[10]), "+f"(d[11]), "+f"(d[12]), "+f"(d[13]), "+f"(d[14]), "+f"(d[15]), "+f"(d[16]), "+f"(d[17]), "+f"(d[18]), "+f"(d[19]), "+f"(d[20]), "+f"(d[21]), "+f"(d[22]), "+f"(d[23]), "+f"(d[24]), "+f"(d[25]), "+f"(d[26]), "+f"(d[27]), "+f"(d[28]), "+f"(d[29]), "+f"(d[30]), "+f"(d[31]), "+f"(d[32]), "+f"(d[33]), "+f"(d[34]), "+f"(d[35]), "+f"(d[36]), "+f"(d[37]), "+f"(d[38]), "+f"(d[39]), "+f"(d[40]), "+f"(d[41]), "+f"(d[42]), "+f"(d[43]), "+f"(d[44]), "+f"(d[45]), "+f"(d[46]), "+f"(d[47]), "+f"(d[48]), "+f"(d[49]), "+f"(d[50]), "+f"(d[51]), "+f"(d[52]), "+f"(d[53]), "+f"(d[54]), "+f"(d[55]), "+f"(d[56]), "+f"(d[57]), "+f"(d[58]), "+f"(d[59]), "+f"(d[60]), "+f"(d[61]), "+f"(d[62]), "+f"(d[63])
    : "r"(a0), "r"(a1), "r"(a2), "r"(a3), "r"(blo));
}

__device__ __forceinline__ float shfl_sel(float a, float b, bool p, int src) {
  float r;
  asm volatile("{\n.reg .pred P;\n.reg .f32 t;\nsetp.ne.u32 P, %3, 0;\nselp.f32 t, %1, %2, P;\nshfl.sync.idx.b32 %0, t, %4, 0x1f, 0xffffffff;\n}\n"
               : "=f"(r) : "f"(a), "f"(b), "r"((uint32_t)p), "r"(src));
  return r;
}
struct CvCtx {
  uint32_t koff, zero, so[3];
  int srcA, srcB;
  bool wrapA, s3, kodd;
};
struct CvPipe { float Ep[2], keep[2], send[2]; };
template <int LO> __device__ __forceinline__ void cv_copy(float (&acc)[64]) {
#pragma unroll
  for (int i = LO; i < 64; i++) { float t; asm volatile("mov.b32 %0, %1;" : "=f"(t) : "f"(acc[i]) : "memory"); acc[i] = t; }
}
template <int G> __device__ __forceinline__ void cv_raw(uint32_t (&A)[4][4], uint32_t kaddr) {
#pragma unroll
  for (int i = 0; i < 4; i++) {
    const uint32_t a = kaddr + (4 * G + i) * 128;
    A[i][0] = lds32(a); A[i][1] = lds32(a + 4); A[i][3] = lds32(a + 8);
  }
}
__device__ __forceinline__ void cv_form(uint32_t (&A)[4][4], uint32_t sel) {
#pragma unroll
  for (int i = 0; i < 4; i++) {
    asm volatile("prmt.b32 %0, %0, %1, %2;" : "+r"(A[i][0]) : "r"(A[i][1]), "r"(sel));
    asm volatile("prmt.b32 %0, %1, %2, %3;" : "=r"(A[i][2]) : "r"(A[i][1]), "r"(A[i][3]), "r"(sel));
  }
}
#define CVV 2
template <int G> __device__ __forceinline__ void cv_step(float (&acc)[64], uint32_t (&A)[4][4], CvPipe& s, const CvCtx& c, uint32_t cb, uint32_t stg) {
  constexpr int JA = G - 1, JB = G - 2, NH = CVV == 1 ? 4 : (CVV == 3 ? 2 : 1);
  const uint32_t db0 = desc_lo(cb + CV_U + 192, CV_PL);
  uint32_t B[4][4];
  float ra[4], rb[2];
  if constexpr (G < 8) {
    wgmma_fence();
#pragma unroll
    for (int i = 0; i < NH; i++) wgmma_rs_hi<128 - 16 * (G & 7)>(acc, A[i][0], A[i][1], A[i][2], A[i][3], db0 - 4 * i);
    wgmma_commit();
    __syncwarp();
  }
  if constexpr (JA >= 0 && JA < 8) {
#pragma unroll
    for (int x = 0; x < 4; x++) {
      const int i = 8 * JA + 4 * (x >> 1) + 2 * (x & 1) + 1;
      ra[x] = shfl_sel(i >= 4 ? acc[i >= 4 ? i - 4 : 0] : 0.f, acc[i], c.wrapA, c.srcA);
    }
  }
  if constexpr (JB >= 0) {
#pragma unroll
    for (int h = 0; h < 2; h++) rb[h] = __shfl_sync(0xffffffffu, s.send[h], c.srcB);
  }
  if constexpr (G < 7) cv_raw<G + 1>(B, cb + c.koff);
  uint32_t z = 0;
  if constexpr (G < 8 && NH < 4) {
    __syncwarp();
    wgmma_fence();
#pragma unroll
    for (int i = NH; i < 4; i++) wgmma_rs_hi<128 - 16 * (G & 7)>(acc, A[i][0], A[i][1], A[i][2], A[i][3], db0 - 4 * i);
    wgmma_commit();
    asm volatile("mov.u32 %0, %%clock;" : "=r"(z)::"memory");
    z &= c.zero;
  }
  const float one = __uint_as_float(0x3f800000u | z);
  if constexpr (G < 7) cv_form(B, 0x5432u | z);
  if constexpr (JB >= 0) sts32(stg + ((c.so[JB / 3] >> (10 * (JB % 3))) & 0xffc), pack_bf16(fmaf(rb[0], one, s.keep[0]), fmaf(rb[1], one, s.keep[1])));
  if constexpr (JA >= 0 && JA < 8) {
#pragma unroll
    for (int h = 0; h < 2; h++) {
      const float ev = fmaf(ra[h], one, acc[8 * JA + 2 * h]), od = fmaf(ra[2 + h], one, acc[8 * JA + 4 + 2 * h]);
      s.send[h] = c.kodd ? ev : (c.s3 ? s.Ep[h] : od);
      s.keep[h] = c.kodd ? od : ev;
      s.Ep[h] = od;
    }
  }
  if constexpr (G < 8) { __syncwarp(); wgmma_wait<0>(); cv_copy<8 * (G & 7)>(acc); }
  if constexpr (G < 9) cv_step<G + 1>(acc, B, s, c, cb, stg);
}
__device__ __forceinline__ uint32_t cv_stage(int slot) { return sb + (slot < 4 ? 40960 + slot * 4096 : CV_OFF + CV_K); }
__device__ __forceinline__ void cv_setup(CvCtx& c) {
  const int tid = tid_opaque() & 127, w = tid >> 5, lane = tid & 31, r = lane >> 2, q = lane & 3;
  const int i0 = (r >> 1) & 1, i1 = r >> 2;
  c.koff = CV_K - 32 + 4 * (8 * (r >> 1) + 2 * w + (r & 1) + 2 * q);
  c.srcA = i0 ? lane - 8 : lane + 8 - q + ((q + 3) & 3);
  c.wrapA = i0 && q == 3;
  c.srcB = i1 == 0 ? (lane - q + 16 + ((q + 3) & 3)) : (lane - q - 16 + ((q + 1) & 3));
  c.s3 = (i1 == 1 && q == 3); c.kodd = (i1 == 1 && q < 3);
  c.zero = lds32(sb + EP_OFF + 24);
#pragma unroll
  for (int i = 0; i < 3; i++) c.so[i] = lds32(sb + SO_OFF + 512 * i + 4 * tid);
}
__device__ __forceinline__ void cv_table() {
  const int tid = tid_opaque() & 127, r = (tid & 31) >> 2, q = tid & 3;
  int t = 16 * (2 * (r < 4 ? q : 4 + ((q + 1) & 3)) + ((r >> 1) & 1)) + 4 * (tid >> 5) + 2 * (r & 1);
#pragma unroll 1
  for (int i = 0; i < 3; i++) {
    uint32_t v = 0;
#pragma unroll 1
    for (int x = 0; x < 3; x++, t += 256) {
      const int T = t / 160, tl = t - T * 160;
      const int qq = (T >= NT1 - 1) ? (tl >> 5) : (tl / 40);
      int ck = 20 * T + ((tl - qq * ((T >= NT1 - 1) ? 32 : 40)) >> 1);
      ck ^= (ck >> 2) & 6;
      v |= (uint32_t)((ck * 4 + qq) & 1023) << (10 * x + 2);
    }
    sts32(sb + SO_OFF + 512 * i + 4 * tid, v);
  }
}
__device__ __forceinline__ void conv_channel(int slot, const CvCtx& c) {
  const uint32_t cb = sb + CV_OFF + slot * CV_B;
  float acc[64];
  CvPipe s;
  s.Ep[0] = s.Ep[1] = 0.f;
  uint32_t A[4][4];
#pragma unroll
  for (int i = 0; i < 64; i++) acc[i] = 0.f;
  if (slot == 4) mbar_wait(bars + 8 * B_CVDONE);
  mbar_wait(bars + 8 * (B_CVFULL + slot));
  cv_raw<0>(A, cb + c.koff);
  {
    const uint32_t w0 = lds32(cb + CV_K);
    const uint32_t wp = __byte_perm(pack_bf16(bf_lo(w0) + __uint_as_float(lds32(sb + EP_OFF + 4 * slot)), 0.f), w0, 0x7610);
    if (c.koff == CV_K) A[0][0] = wp;
    if (c.koff == CV_K - 4) A[0][1] = wp;
    if (c.koff == CV_K - 8) A[0][3] = wp;
  }
  cv_form(A, 0x5432u);
  cv_copy<0>(acc);
  cv_step<0>(acc, A, s, c, cb, cv_stage(slot));
  fence_async_smem();
  mbar_arrive(bars + 8 * (B_CVDONE + slot));
}

__device__ __forceinline__ void kv_issue(const Params& p, int c, int m2, int dg) {
  const uint32_t fb = bars + 8 * (B_KV + c);
  mbar_expect_tx(fb, KV_PIECE);
  tma3(sb + KS_OFF + c * KV_PIECE, &p.mK, 160 * dg + 32 * c, 64 * m2 - 3, 0, fb);
  tma3(sb + KS_OFF + c * KV_PIECE + 4864, &p.mV, 160 * dg + 32 * c, 64 * m2 - 1, 0, fb);
}
__device__ __forceinline__ void kv_tile(int m, int dg, int c, int y) {
  const int lane = tid_opaque() & 31, tg = lane >> 3;
  const uint32_t pb = sb + KS_OFF + c * KV_PIECE + 32 * y + 4 * (lane & 7);
  const uint32_t ka = pb + tg * 1216, va = pb + 4864 + tg * 1088 + 64;
  const uint32_t kh = (m == 0 && tg > 0) ? ka - 192 : ka;
  uint32_t kk[19], u[16];
  const float4 t = lds128f(sb + TAP_OFF + 256 * c + 128 * y + 16 * (lane & 7));
#pragma unroll
  for (int i = 0; i < 19; i++) { kk[i] = lds32((i < 3 ? kh : ka) + i * 64); if (i >= 3) u[i - 3] = lds32(va + (i - 3) * 64); }
  uint8_t* dst = g_kv + ((160 * dg + 32 * c + 16 * y + 2 * (lane & 7)) * 4096 + (4 * m + tg) * 16);
  const uint32_t w0 = __byte_perm(__float_as_uint(t.x), __float_as_uint(t.z), 0x5410), w1 = __byte_perm(__float_as_uint(t.x), __float_as_uint(t.z), 0x7632);
  const uint32_t w2 = __byte_perm(__float_as_uint(t.y), __float_as_uint(t.w), 0x5410), w3 = __byte_perm(__float_as_uint(t.y), __float_as_uint(t.w), 0x7632);
#pragma unroll
  for (int i = 0; i < 16; i++) {
    uint32_t a = hmul2(kk[i], w3);
    a = hadd2(a, hmul2(kk[i + 1], w2)); a = hadd2(a, hmul2(kk[i + 2], w1)); a = hadd2(a, hmul2(kk[i + 3], w0));
    u[i] = hmul2(a, u[i]);
  }
#pragma unroll
  for (int e = 0; e < 2; e++)
#pragma unroll
    for (int f = 0; f < 2; f++) {
      uint32_t o[4];
#pragma unroll
      for (int qq = 0; qq < 4; qq++) o[qq] = __byte_perm(u[15 - 4 * qq - 2 * f], u[14 - 4 * qq - 2 * f], e ? 0x7632 : 0x5410);
      *(uint4*)(dst + e * 4096 + f * 2048) = make_uint4(o[0], o[1], o[2], o[3]);
    }
}
__device__ __forceinline__ void ln_finish(float s1, float s2, float& mean, float& rstd) {
  mean = s1 * (1.f / 640.f);
  const float v = fmaxf(fmaf(-mean, mean, s2 * (1.f / 640.f)), 0.f) + 1e-5f;
  asm("rsqrt.approx.ftz.f32 %0, %1;" : "=f"(rstd) : "f"(v));
}
__device__ __forceinline__ void stat_table(int T1, unsigned want, int l, int g, const uint4* x0, const uint4* x1, float (&xa)[2], float (&xb)[2]) {
  const int n = 32 * g + (tid_opaque() & 31);
  const uint4* rp = &g_stats[8 * l * SEQ + min(160 * T1 + n, SEQ - 1)];
  float a[4], b[4];
  uint32_t it = 0;
  while (true) {
    bool ok = true;
#pragma unroll
    for (int i = 0; i < 4; i++) ok &= (rec_ld(rp + SEQ * i, a[i], b[i]) == want);
    ok &= rec_ld(x0, xa[0], xb[0]) == want;
    ok &= rec_ld(x1, xa[1], xb[1]) == want;
    if (__all_sync(0xffffffffu, ok)) break;
    trap_if(++it > SPIN_LIMIT);
  }
  float m, rs;
  ln_finish((a[0] + a[1]) + (a[2] + a[3]), (b[0] + b[1]) + (b[2] + b[3]), m, rs);
  sts64f(sb + STAB_OFF + n * 8, rs, -m * rs);
}
__device__ __forceinline__ void stats_reduce(float (&a)[2], float (&b)[2], float (&mean)[2], float (&rstd)[2]) {
#pragma unroll
  for (int o = 1; o < 4; o <<= 1)
#pragma unroll
    for (int h = 0; h < 2; h++) { a[h] += __shfl_xor_sync(0xffffffffu, a[h], o); b[h] += __shfl_xor_sync(0xffffffffu, b[h], o); }
#pragma unroll
  for (int h = 0; h < 2; h++) ln_finish(a[h], b[h], mean[h], rstd[h]);
}

template <bool FIRST>
__device__ __forceinline__ void stats_publish(int which, int n0, int dg, unsigned tag, const float (&acc)[80]) {
  const int q = tid_opaque() & 3, h = q & 1;
  float s1[2] = {0.f, 0.f}, s2[2] = {0.f, 0.f}, t1[2] = {0.f, 0.f}, t2[2] = {0.f, 0.f};
#pragma unroll
  for (int j = 0; j < 20; j++)
#pragma unroll
    for (int y = 0; y < 2; y++) {
      const float a = acc[4 * j + 2 * y], b = acc[4 * j + 2 * y + 1];
      s1[y] += a; t1[y] += b; s2[y] = fmaf(a, a, s2[y]); t2[y] = fmaf(b, b, t2[y]);
    }
#pragma unroll
  for (int y = 0; y < 2; y++) { s1[y] += t1[y]; s2[y] += t2[y]; }
  float a = (h ? s1[1] : s1[0]) + __shfl_xor_sync(0xffffffffu, h ? s1[0] : s1[1], 1);
  float b = (h ? s2[1] : s2[0]) + __shfl_xor_sync(0xffffffffu, h ? s2[0] : s2[1], 1);
  a += __shfl_xor_sync(0xffffffffu, a, 2);
  b += __shfl_xor_sync(0xffffffffu, b, 2);
  if (FIRST) {
    rec_st(&g_stats[((q >> 1) * 4 + dg) * SEQ + n0 + 8 * h], a, b, q < 2 ? tag : tag - 1);
    rec_st(&g_stats[((q >> 1) * 4 + 8 + dg) * SEQ + n0 + 8 * h], a, b, tag - 1);
  } else if (q < 2) rec_st(&g_stats[(which * 4 + dg) * SEQ + n0 + 8 * h], a, b, tag);
}
__device__ __forceinline__ void stats_get(int which, int n0, unsigned tag, float (&mean)[2], float (&rstd)[2]) {
  const uint4* p0 = &g_stats[(which * 4 + (tid_opaque() & 3)) * SEQ + n0];
  float a[2], b[2];
  uint32_t it = 0;
  while (true) {
    const unsigned t0 = rec_ld(p0, a[0], b[0]), t1 = rec_ld(p0 + 8, a[1], b[1]);
    if (__all_sync(0xffffffffu, t0 == tag && t1 == tag)) break;
    trap_if(++it > SPIN_LIMIT);
  }
  stats_reduce(a, b, mean, rstd);
}
__device__ __forceinline__ void x0_load(float (&acc)[80]) {
  const int t = tid_opaque() & 127;
  const uint32_t xa = sb + XT_OFF + (16 * (t >> 5) + ((t & 31) >> 2)) * 320 + 8 * (t & 3);
  mbar_wait(bars + 8 * B_XT);
#pragma unroll
  for (int h = 0; h < 2; h++)
#pragma unroll
    for (int J = 0; J < 10; J++) {
      const float2 v = lds64f(xa + h * 2560 + 32 * J);
      const uint32_t x = __float_as_uint(v.x), y = __float_as_uint(v.y);
      acc[8 * J + 2 * h] = bf_lo(x); acc[8 * J + 2 * h + 1] = bf_hi(x);
      acc[8 * J + 4 + 2 * h] = bf_lo(y); acc[8 * J + 4 + 2 * h + 1] = bf_hi(y);
    }
}

template <bool FROM_X0>
__device__ __forceinline__ void dskip_init(float (&acc)[80], const float (&mean)[2], const float (&rstd)[2]) {
  const int t = tid_opaque() & 127;
  const uint32_t xa = sb + XT_OFF + (16 * (t >> 5) + ((t & 31) >> 2)) * 320 + 8 * (t & 3), da = sb + DTAB_OFF + 8 * (t & 3);
  float2 dw[10], xv[10][2];
#pragma unroll
  for (int J = 0; J < 2; J++) { dw[J] = lds64f(da + 32 * J); if (FROM_X0) { xv[J][0] = lds64f(xa + 32 * J); xv[J][1] = lds64f(xa + 2560 + 32 * J); } }
#pragma unroll
  for (int J = 0; J < 10; J++) {
    if (J + 2 < 10) { dw[J + 2] = lds64f(da + 32 * (J + 2)); if (FROM_X0) { xv[J + 2][0] = lds64f(xa + 32 * (J + 2)); xv[J + 2][1] = lds64f(xa + 2560 + 32 * (J + 2)); } }
#pragma unroll
    for (int x = 0; x < 8; x++) {
      const int h = (x >> 1) & 1;
      const uint32_t dwd = __float_as_uint(x < 4 ? dw[J].x : dw[J].y);
      const float tt = fmaf(rstd[h], (x & 1) ? bf_hi(dwd) : bf_lo(dwd), 1.f);
      float a = acc[8 * J + x];
      if (FROM_X0) { const uint32_t xw = __float_as_uint(x < 4 ? xv[J][h].x : xv[J][h].y); a = (x & 1) ? bf_hi(xw) : bf_lo(xw); }
      acc[8 * J + x] = FROM_X0 ? (a - mean[h]) * tt : fmaf(a, tt, -mean[h] * tt);
    }
  }
}

__global__ void __launch_bounds__(512, 1) fused_kernel(const __grid_constant__ Params p) {
  extern __shared__ __align__(1024) uint8_t smem_raw[];
  const int tid = threadIdx.x, lane = tid & 31;
  const int wid = __shfl_sync(0xffffffffu, tid >> 5, 0), wg = wid >> 2;
  unsigned smid; asm volatile("mov.u32 %0, %%smid;" : "=r"(smid));
  const int role = p.role[min(smid, 131u)];
  if (wid == 12) {
    const bool el = elect_one();
    if (el) {
      asm volatile("prefetch.tensormap [%0];" ::"l"(&p.mX) : "memory");
      asm volatile("prefetch.tensormap [%0];" ::"l"(&p.mB) : "memory");
#pragma unroll
      for (int k = 0; k < S1; k++) mbar_init(bars + 8 * (B_G1FULL + k), 1);
#pragma unroll
      for (int k = 0; k < 6; k++) mbar_init(bars + 8 * (B_XT + k), 1);
      asm volatile("fence.mbarrier_init.release.cluster;" ::: "memory");
    }
    if (role >= 0) {
      __syncwarp();
      asm volatile("bar.arrive 5, 288;" ::: "memory");
      const Role R = unpack_role(role);
      if (elect_one()) {
        TS(45);
#pragma unroll 1
        for (int k = 0; k < S1; k++) {
          const uint32_t fb = bars + 8 * (B_G1FULL + k);
          mbar_expect_tx(fb, G1_STAGE);
          tma4(sb + k * G1_STAGE + G1_XOFF, R.last ? &p.mXl : &p.mX, 64 * k, 0, 0, R.last ? 0 : 80 * R.T1, fb);
          tma5(sb + k * G1_STAGE, &p.mB, 64 * k, 0, 0, 4 * R.side, 2 * R.GP, fb);
        }
        if (R.has2) {
#pragma unroll 1
          for (int c = 0; c < KV0; c++) kv_issue(p, c, R.m2, R.dg);
          mbar_expect_tx(bars + 8 * B_XT, 20480);
#pragma unroll 1
          for (int h = 0; h < 2; h++) {
            const int ng = 8 * R.m2 + 4 * h, T = ng / 20;
            tma4(sb + XT_OFF + h * 10240, T == NT1 - 1 ? &p.mXtl : &p.mXt, 160 * R.dg, 0, 0, T == NT1 - 1 ? ng - 240 : ng + 60 * T, bars + 8 * B_XT);
          }
        }
        TS(44);
      }
      __syncwarp();
      bar_sync(6, 64);
    }
  }
  trap_if(smid >= 132 || smem_u32(smem_raw) != sb);
  if (role < 0) {
    if (wid == 0) {
      const unsigned tag = ld_rlx(g_epoch);
#pragma unroll 1
      for (int i = 0; i < NT1; i++) {
        uint32_t it = 0;
        while (!__all_sync(0xffffffffu, (int)(ld_rlx(&g_hflag[(i * 32 + min(lane, 9)) * 8]) - tag) >= 0)) { __nanosleep(500); trap_if(++it > SPIN_LIMIT); }
      }
    }
    return;
  }
  float mean0[2] = {0.f, 0.f}, rstd0[2] = {0.f, 0.f};
  if (wg == 2 || wid == 14) {
    ROLE(role)
    const int c = wid == 14 ? 4 : wid - 8;
    const unsigned tag = ld_rlx(g_epoch);
    if (has2) {
      uint2 bv[2][5];
#pragma unroll
      for (int x = 0; x < 2; x++)
#pragma unroll
        for (int i = 0; i < 5; i++) bv[x][i] = ldv64((const uint2*)((x ? p.bim : p.bre) + (cch0 + 32 * c) * DM) + lane + 32 * i);
      float sv[2];
#pragma unroll
      for (int x = 0; x < 2; x++) {
        float a = 0.f;
#pragma unroll
        for (int i = 0; i < 5; i++) a += (bf_lo(bv[x][i].x) + bf_hi(bv[x][i].x)) + (bf_lo(bv[x][i].y) + bf_hi(bv[x][i].y));
        sv[x] = a;
      }
#pragma unroll
      for (int o = 16; o > 0; o >>= 1) { sv[0] += __shfl_xor_sync(0xffffffffu, sv[0], o); sv[1] += __shfl_xor_sync(0xffffffffu, sv[1], o); }
      if (lane < 2) rec_st(&g_sB[(cch0 + 32 * c) * 2 + lane], sv[0], sv[1], tag);
      if (tid == 256) TS(47);
      __syncwarp();
      bar_sync(8, 192);
      mbar_wait(bars + 8 * B_EP);
      mbar_wait(bars + 8 * (B_KV + c));
#pragma unroll 1
      for (int y = 0; y < 2; y++) kv_tile(m2, dg, c, y);
      __syncwarp();
      if (lane == 0) mbar_arrive(bars + 8 * B_PREP);
      if (tid == 352) TS(52);
      if (tid == 448) TS(51);
      if (wg == 2) {
        float xs[80];
        x0_load(xs);
        stats_publish<true>(0, 64 * m2 + 16 * c + (lane >> 2), dg, tag, xs);
        if (tid == 256) TS(31);
        mbar_wait(bars + 8 * (TABW ? B_PUB : B_PREP));
      } else {
        mbar_wait(bars + 8 * B_PREP);
        if (lane == 0) { st_rel(&g_kvflag[(dg * 32 + m2) * 8], tag); mbar_arrive(bars + 8 * B_PUB); TS(30); }
        __syncwarp();
      }
    } else bar_sync(8, 192);
    {
      const uint4* x0 = wg == 2 ? &g_stats[(lane & 3) * SEQ + (has2 ? 64 * m2 : 0) + 16 * c + (lane >> 2)] : &g_sB[(128 * GP + 32 * side + lane) * 2];
      float xa[2], xb[2];
      stat_table(T1, tag, 0, c, x0, x0 + (wg == 2 ? 8 : 128), xa, xb);
      if (wg == 2) stats_reduce(xa, xb, mean0, rstd0);
      else {
#pragma unroll
        for (int i = 0; i < 2; i++) sts64f(sb + CTAB_OFF + (32 * i + lane) * 24 + 16, p.swap ? xb[i] : xa[i], p.swap ? xa[i] : xb[i]);
      }
      mbar_arrive(bars + 8 * B_STAB);
      if (tid == 448) TS(26);
    }
  } else if (wid == 15) {
    ROLE(role)
    const int ch = 128 * GP + 32 * side + lane;
    uint32_t r0 = ldv16(p.lre + ch), r1 = ldv16(p.lim + ch), r2 = ldv16(p.logdt + ch);
    const uint32_t r3 = ldv16(p.lre + ch + 64), r4 = ldv16(p.lim + ch + 64), r5 = ldv16(p.logdt + ch + 64);
#pragma unroll 1
    for (int i = 0; i < 2; i++) {
      const float lr = bf_lo(r0), li = bf_lo(r1);
      const float dt = __bfloat162float(__float2bfloat16_rn(expf(bf_lo(r2))));
      const float mag = expf(dt * lr);
      float sn, cs; sincospif(dt * li * 0.31830988618379067f, &sn, &cs);
      const float ar = mag * cs, ai = mag * sn;
      const float inv = 2.f / (lr * lr + li * li);
      const uint32_t ad = sb + CTAB_OFF + (32 * i + lane) * 24;
      sts64f(ad, ar, ai);
      sts64f(ad + 8, ((ar - 1.f) * lr + ai * li) * inv, (ai * lr - (ar - 1.f) * li) * inv);
      r0 = r3; r1 = r4; r2 = r5;
    }
    if (lane == 0) TS(46);
    __syncwarp();
    bar_sync(7, 64);
    mbar_arrive(bars + 8 * B_CTAB);
  } else if (wid == 13) {
    ROLE(role)
    uint4 tv[3];
    const uint32_t e0 = ld_rlx(g_epoch);
    const uint32_t e1 = ldv16(p.ssmD + min(cch0 + 32 * lane, 639));
    const uint4 dv = ldv128((const uint4*)(p.dskip + 160 * dg) + min(lane, 19));
#pragma unroll
    for (int i = 0; i < 3; i++) tv[i] = ldv128((const uint4*)(p.shiftk + 640 * dg) + min(lane + 32 * i, 79));
    sts128(sb + DTAB_OFF + 16 * min(lane, 19), dv);
#pragma unroll
    for (int i = 0; i < 3; i++) sts128(sb + TAP_OFF + 16 * min(lane + 32 * i, 79), tv[i]);
    if (lane < 7) sts32(sb + EP_OFF + 4 * lane, lane < 5 ? e1 << 16 : (lane == 5 ? e0 : 0u));
    __syncwarp();
    bar_sync(9, 64);
    mbar_arrive(bars + 8 * B_CTAB);
    if (lane == 0) { mbar_arrive(bars + 8 * B_EP); TS(53); }
  } else if (wid != 12) {
    if (elect_one()) {
      if (wid < 7) {
        const int b0 = wid < 4 ? 4 + 20 * wid : 85 + 21 * (wid - 4), cnt = wid < 4 ? 2 : 1;
#pragma unroll
        for (int i = 0; i < 21; i++) mbar_init(bars + 8 * (b0 + i), cnt);
      } else {
#pragma unroll
        for (int i = 0; i < 12; i++) mbar_init(bars + 8 * (B_CVDONE + i), (i == 5 || i == 6) ? 160 : 128);
        mbar_init(bars + 8 * B_CTAB, 192); mbar_init(bars + 8 * B_PREP, 5);
      }
      asm volatile("fence.mbarrier_init.release.cluster;" ::: "memory");
    }
    __syncwarp();
    bar_sync(5, 288);
    if (wid == 2) asm volatile("bar.arrive 8, 192;\nbar.arrive 6, 64;\nbar.arrive 9, 64;\nbar.arrive 7, 64;" ::: "memory");
    if (tid == 128) TS(0);
    if (wg == 1) { cv_table(); mbar_arrive(bars + 8 * B_CTAB); }
  }

  if (wid == 12) {
    ROLE(role)
    uint32_t dst = sb;
#pragma unroll 1
    for (int k = S1; k < 10; k++) {
      const uint32_t fb = bars + 8 * (B_G1FULL + k);
      mbar_wait(bars + 8 * (B_G1DONE + k - S1));
      if (elect_one()) {
        mbar_expect_tx(fb, 20480);
        tma4(dst + G1_XOFF, last ? &p.mXl : &p.mX, 64 * k, 0, 0, last ? 0 : 80 * T1, fb);
        mbar_expect_tx(fb, 16384);
        tma5(dst, &p.mB, 64 * k, 0, 0, 4 * side, 2 * GP, fb);
        if (has2 && k - S1 + KV0 < 5) kv_issue(p, k - S1 + KV0, m2, dg);
      }
      dst += G1_STAGE; if (k == 2 * S1 - 1) dst = sb;
    }
  } else if (wid == 15 && (role >> 16)) {
    ROLE(role)
    mbar_wait(bars + 8 * B_PREP);
#pragma unroll
    for (int c = 0; c < 5; c++) {
      const uint32_t cb = sb + CV_OFF + c * CV_B;
      sts128(lane < 8 ? cb + 16 * lane : (lane < 20 ? cb + CV_U + 16 * (lane - 8) : cb + CV_U + CV_PL + 16 * (lane - 20)), make_uint4(0, 0, 0, 0));
    }
    fence_async_smem();
    __syncwarp();
    const unsigned tag = lds32(sb + EP_OFF + 20);
    mbar_wait(bars + 8 * B_PUB);
    if (elect_one()) {
#pragma unroll
      for (int c = 0; c < TAP0; c++) {
        mbar_expect_tx(bars + 8 * (B_CVFULL + c), 4096);
        bulk_g2s(sb + CV_OFF + c * CV_B + CV_K, p.ssmk + (cch0 + 32 * c) * SEQ, 4096, bars + 8 * (B_CVFULL + c));
      }
    }
    flag_poll(&g_kvflag[(dg * 32 + lane) * 8], tag);
    fence_async_global();
    if (elect_one()) {
      TS(28);
#pragma unroll 1
      for (int c = 0; c < 5; c++) {
        const uint32_t fb = bars + 8 * (B_CVFULL + c), cb = sb + CV_OFF + c * CV_B;
        mbar_expect_tx(fb, 4096);
        bulk_g2s(cb + CV_U + 192, g_kv + (cch0 + 32 * c) * 4096, 2048, fb);
        bulk_g2s(cb + CV_U + 192 + CV_PL, g_kv + (cch0 + 32 * c) * 4096 + 2048, 2048, fb);
        if (c >= TAP0) {
          mbar_expect_tx(fb, 4096);
          bulk_g2s(cb + CV_K, p.ssmk + (cch0 + 32 * c) * SEQ, 4096, fb);
        }
      }
      TS(54);
    }
    __syncwarp();
  }
  {
    const int w = wid & 3;
    if (wg == 2 && !(role >> 16)) {
      float xa[2], xb[2];
      mbar_wait(bars + 8 * (B_G1FULL + 11));
      stat_table(role & 15, lds32(sb + EP_OFF + 20), 1, w, g_stats, g_stats, xa, xb);
      mbar_arrive(bars + 8 * (B_STAB + 1));
    }
#pragma unroll 1
    for (int l = 0; l < 2; l++) {
      if (wg < 2) {
        float acc[80];
#pragma unroll
        for (int i = 0; i < 80; i++) acc[i] = 0.f;
        ROLE(role)
        const int tid = tid_opaque(), r = (tid & 31) >> 2, q = tid & 3;
        const int ch = 128 * GP + 64 * wg + 32 * side + 8 * w + r;
        const uint32_t ca = sb + CTAB_OFF + (32 * wg + 8 * w + r) * 24;
        float2 lam = make_float2(0.f, 0.f), p8 = lam, p16 = lam, pL = lam, p2L = lam;
        fence_regs(acc);
        {
          uint32_t alo = desc_lo(sb, 16) + wg * 512, blo = l == 0 ? desc_lo(sb + G1_XOFF, 16) : desc_lo(sb + G1_XOFF, 128);
          const uint32_t bhi = l == 0 ? desc_hi(1024, 1) : desc_hi(1024, 0), xstep = l == 0 ? 2 : 16;
          const uint32_t aend = desc_lo(sb, 16) + (S1 + l) * (G1_STAGE >> 4);
          uint32_t fb = bars + 8 * (B_G1FULL + 10 * l);
          mbar_wait(fb);
          if (tid == 0) TS(1 + 8 * l);
#pragma unroll 1
          for (int k = 0; k < 10; k++) {
            uint32_t ok; const uint32_t nb = k < 9 ? fb + 8 : fb;
            wgmma_fence();
#pragma unroll
            for (int kk = 0; kk < 4; kk++) {
              wgmma_n160<0>(acc, alo + kk * 2, desc_hi(1024, 1), blo + kk * xstep, bhi);
              if (kk == 0) ok = mbar_test(nb);
              if (kk == STG_KK && k == 9 && tid == 0) mbar_arrive(bars + 8 * (B_STG + l));
            }
            wgmma_commit();
            alo += G1_STAGE >> 4; blo += G1_STAGE >> 4;
            if (alo >= aend) { alo -= (S1 + l) * (G1_STAGE >> 4); blo -= (S1 + l) * (G1_STAGE >> 4); }
            wgmma_wait<1>();
            if (k > 0 && (tid & 127) == 0) mbar_arrive(fb + 8 * (B_G1DONE - B_G1FULL - 1));
            if (!ok) mbar_wait(nb);
            if (wg == 1 && k == (l ? 8 - STG_D : 9 - STG0)) mbar_wait(bars + 8 * (B_STG + l));
            if (k == 3) {
              mbar_wait(bars + 8 * B_CTAB);
              lam = lds64f(ca);
              if (p.swap) lam.y = -lam.y;
              const float2 p2 = cmul(lam, lam), p4 = cmul(p2, p2);
              p8 = cmul(p4, p4); p16 = cmul(p8, p8);
              pL = cmul(p16, p16);
              if (!last) pL = cmul(pL, p8);
              p2L = cmul(pL, pL);
            }
            if (k == PAUSE_K && has2) mbar_wait(bars + 8 * B_PREP);
            fb += 8;
          }
        }
        mbar_wait(bars + 8 * (B_STAB + l));
        const float2 sB = lds64f(ca + 16);
        const unsigned tag = lds32(sb + EP_OFF + 20);
        wgmma_wait<0>();
        fence_regs(acc);
        if ((tid & 127) == 0) { mbar_arrive(bars + 8 * (B_G1DONE + 10 * l + 9)); TS(wg ? 17 + l : 2 + 8 * l); }
        float2 ec[3];
#pragma unroll
        for (int jj = 0; jj < 8; jj++)
#pragma unroll
          for (int y = 0; y < 3; y++) {
            if (y == 2 && (jj & 1)) continue;
            const int j = y == 2 ? 16 + (jj >> 1) : 8 * y + jj;
            const float4 st = lds128f(sb + STAB_OFF + (8 * j + 2 * q) * 8);
            acc[4 * j + 0] = fmaf(acc[4 * j + 0], st.x, st.y * sB.x);
            acc[4 * j + 2] = fmaf(acc[4 * j + 2], st.x, st.y * sB.y);
            acc[4 * j + 1] = fmaf(acc[4 * j + 1], st.z, st.w * sB.x);
            acc[4 * j + 3] = fmaf(acc[4 * j + 3], st.z, st.w * sB.y);
            ec[y] = jj == 0 ? make_float2(acc[4 * j + 0], acc[4 * j + 2]) : cfma(lam, ec[y], make_float2(acc[4 * j + 0], acc[4 * j + 2]));
            ec[y] = cfma(lam, ec[y], make_float2(acc[4 * j + 1], acc[4 * j + 3]));
          }
        float2 e = cfma(p16, ec[0], ec[1]);
        if (!last) e = cfma(p8, e, ec[2]);
        {
          float2 v = make_float2(__shfl_up_sync(0xffffffffu, e.x, 1, 4), __shfl_up_sync(0xffffffffu, e.y, 1, 4));
          if (q >= 1) e = cfma(pL, v, e);
          v = make_float2(__shfl_up_sync(0xffffffffu, e.x, 2, 4), __shfl_up_sync(0xffffffffu, e.y, 2, 4));
          if (q >= 2) e = cfma(p2L, v, e);
        }
        if (!last && (q == 3 || (q == 2 && l == 0))) rec_st(&g_E[((q == 3 ? l : 1) * NT1 + T1) * DM + ch], e.x, e.y, q == 3 ? tag : tag - 1);
        if (tid == 0) TS(3 + 8 * l);
        float2 ex = make_float2(__shfl_up_sync(0xffffffffu, e.x, 1, 4), __shfl_up_sync(0xffffffffu, e.y, 1, 4));
        if (q == 0) ex = make_float2(0.f, 0.f);
        const float2 coef = lds64f(ca + 8), lamc = make_float2(lam.x, p.swap ? lam.y : -lam.y);
        float m00 = coef.x, m01 = -coef.y, m10 = -coef.y, m11 = -coef.x;
        if (p.swap) { m00 = -coef.y; m01 = coef.x; m10 = -coef.x; m11 = -coef.y; }
        float2 pLq, p160q, p640;
        {
          const float2 p80 = last ? cmul(p2L, p16) : p2L, p160 = cmul(p80, p80), p320 = cmul(p160, p160), one = make_float2(1.f, 0.f);
          p640 = cmul(p320, p320);
          pLq = cmul((q & 1) ? pL : one, (q & 2) ? p2L : one);
          p160q = cmul((q & 1) ? p160 : one, (q & 2) ? p320 : one);
        }
        float2 c, ev[3];
        unsigned tg[3];
        const uint4* ep = &g_E[(l * NT1 + T1 - 1 - q) * DM + ch];
#pragma unroll
        for (int j = 0; j < 20; j++) {
          if (j == CPOLL) {
#pragma unroll
            for (int i = 0; i < 3; i++) {
              ev[i] = make_float2(0.f, 0.f); tg[i] = tag;
              if (T1 - 1 - q - 4 * i >= 0) tg[i] = rec_ld(ep - 4 * i * DM, ev[i].x, ev[i].y);
            }
          }
#pragma unroll
          for (int x = 0; x < 2; x++) {
            const float b0 = acc[4 * j + x], b1 = acc[4 * j + 2 + x];
            acc[4 * j + x] = fmaf(b0, m00, b1 * m01);
            acc[4 * j + 2 + x] = fmaf(b0, m10, b1 * m11);
          }
          if (j == CPOLL - 1 || j == 19) asm volatile("" : "+f"(acc[4 * j]), "+f"(acc[4 * j + 1]), "+f"(acc[4 * j + 2]), "+f"(acc[4 * j + 3])::"memory");
        }
        {
          uint32_t it = 0;
          while (__any_sync(0xffffffffu, tg[0] != tag || tg[1] != tag || tg[2] != tag)) {
#pragma unroll
            for (int i = 0; i < 3; i++)
              if (tg[i] != tag) tg[i] = rec_ld(ep - 4 * i * DM, ev[i].x, ev[i].y);
            trap_if(++it > SPIN_LIMIT);
          }
          c = cfma(p640, cfma(p640, ev[2], ev[1]), ev[0]);
          c = cmul(c, p160q);
          c.x += __shfl_xor_sync(0xffffffffu, c.x, 1); c.y += __shfl_xor_sync(0xffffffffu, c.y, 1);
          c.x += __shfl_xor_sync(0xffffffffu, c.x, 2); c.y += __shfl_xor_sync(0xffffffffu, c.y, 2);
        }
        if (tid == 0) TS(4 + 8 * l);
        if (wg == 1 && l >= HOLD0) mbar_wait(bars + 8 * (B_REL + l));
        c = cfma(pLq, c, ex);
        float2 hh = make_float2(fmaf(c.x, m00, c.y * m01), fmaf(c.x, m10, c.y * m11));
        uint8_t* hb = g_h + (size_t)l * (32 * 20 * 8192) + (10 * wg + 2 * GP) * 8192 + (4 * side + w) * 1024 + (tid_opaque() & 31) * 4;
#pragma unroll
        for (int j4 = 0; j4 < 5; j4++) {
          const int ng = 20 * T1 + 4 * j4;
          uint8_t* hp = hb + (size_t)(ng >> 3) * 163840 + (ng & 7) * 128;
#pragma unroll
          for (int jj = 0; jj < 4; jj++) {
            const int j = 4 * j4 + jj;
            const float2 h0 = cfma(lamc, hh, make_float2(acc[4 * j + 0], acc[4 * j + 2]));
            hh = cfma(lamc, h0, make_float2(acc[4 * j + 1], acc[4 * j + 3]));
            if (j4 < 4 || !last) {
              *(uint32_t*)(hp + jj * 128) = pack_bf16(h0.x, hh.x);
              *(uint32_t*)(hp + jj * 128 + 8192) = pack_bf16(h0.y, hh.y);
            }
          }
        }
        mbar_arrive(bars + 8 * (B_HST + 2 * l + wg));
        if (tid == 0) TS(5 + 8 * l);
        if (tid == 128) TS(l ? 25 : 19);
        if (l == 0 && wid == 4) {
          mbar_wait(bars + 8 * B_HST);
          mbar_wait(bars + 8 * (B_HST + 1));
          if ((tid & 31) < 2) st_rel(&g_hflag[((T1 * 2 + (tid & 31)) * 16 + 2 * GP + side) * 8], tag);
          if (tid == 128) { mbar_arrive(bars + 8 * B_REL); TS(6); }
          __syncwarp();
        }
      }
      if (l == 0) {
        ROLE(role)
        if (has2) {
          CvCtx cc;
          mbar_wait(bars + 8 * B_CTAB);
          cv_setup(cc);
          mbar_wait(bars + 8 * (B_G1DONE + 9));
#pragma unroll 1
          for (int c = (wg + 2) & 3; c < 5; c += 4) conv_channel(c, cc);
          if ((tid & 127) == 0) TS(wg == 2 ? 32 : (wg == 3 ? 50 : 7 + wg));
        }
      }
      if (wg >= 2) break;
    }
    if (wg == 3) {
    ROLE(role)
    const int pw = wid & 3;
    mbar_wait(bars + 8 * B_EP);
    const unsigned tag = lds32(sb + EP_OFF + 20);
    if (pw == 0) {
      if (elect_one()) {
#pragma unroll 1
        for (int l = 0; l < 2; l++) {
          uint32_t dst = sb;
          if (l == 1) {
            const uint32_t free0 = bars + 8 * (has2 ? B_G2DONE + 19 : B_G1DONE + 9);
#pragma unroll 1
            for (int k = 0; k < 10; k++) {
              mbar_wait(k > S1 ? bars + 8 * (B_G1DONE + 9 - S1 + k) : (k < WPF1 || !has2 ? free0 : bars + 8 * B_GO));
              mbar_expect_tx(bars + 8 * (B_G1FULL + 10 + k), 16384);
              tma5(dst, &p.mB, 64 * k, 0, 0, 4 * side, 2 * GP, bars + 8 * (B_G1FULL + 10 + k));
              dst += G1_STAGE; if (k == S1) dst = sb;
            }
          }
          if (has2) {
            const uint32_t fb2 = bars + 8 * (B_G2FULL + 20 * l), wb2 = bars + 8 * (B_G2DONE + 20 * l - S2);
            dst = sb + G2_WOFF;
            int kc = 0;
#pragma unroll 1
            for (int k = 0; k < 20; k++) {
              mbar_wait(k >= S2 ? wb2 + 8 * k : (k == 5 ? bars + 8 * B_XFREE : (k == 6 ? bars + 8 * B_SFREE : bars + 8 * (l ? B_G1DONE + 19 : B_REL))));
              mbar_expect_tx(fb2 + 8 * k, G2_WB);
              tma5(dst, &p.mCre + (k & 1), kc, 0, 0, 0, 10 * dg, fb2 + 8 * k);
              kc += (k & 1) << 7; if (k == 9) kc = 64;
              dst += G2_WB; if (dst == sb + G2_WOFF + S2 * G2_WB) dst = sb + G2_WOFF;
            }
          }
        }
      }
    } else if (pw == 1) {
#pragma unroll 1
      for (int l = 0; l < 2; l++) {
        if (l == 1) {
          mbar_wait(bars + 8 * (has2 ? B_G2DONE + 19 : B_G1DONE + 9));
          const int mlo = (160 * T1) >> 6, nf = last ? 8 : 12;
          flag_poll(&g_uflag[(4 * mlo + min(lane, nf - 1)) * 8], tag);
          fence_async_global();
          if (elect_one()) {
            TS(20);
            const int bytes = last ? 16384 : 20480;
            const uint8_t* src = g_u + T1 * 204800;
            uint32_t dst = sb + G1_XOFF;
#pragma unroll 1
            for (int k = 0; k < 10; k++) {
              if (k > S1) mbar_wait(bars + 8 * (B_G1DONE + 9 - S1 + k));
              mbar_expect_tx(bars + 8 * (B_G1FULL + 10 + k), bytes);
              bulk_g2s(dst, src, bytes, bars + 8 * (B_G1FULL + 10 + k));
              src += 20480; dst += G1_STAGE; if (k == S1) dst = sb + G1_XOFF;
            }
          }
          __syncwarp();
        }
        if (has2) {
          mbar_wait(bars + 8 * (B_HST + 2 * l));
          mbar_wait(bars + 8 * (B_G1DONE + 10 * l + 9));
          const int Tlo = (64 * m2) / 160, Thi = (64 * m2 + 63) / 160;
          flag_poll(&g_hflag[(((l * NT1 + (lane < 16 ? Tlo : Thi)) * 2) * 16 + min(lane & 15, 9)) * 8], tag);
          fence_async_global();
          if (elect_one()) {
            TS(21 + 2 * l);
            const uint32_t fb2 = bars + 8 * (B_G2FULL + 20 * l), wb2 = bars + 8 * (B_G2DONE + 20 * l - S2);
            const uint8_t* src = g_h + (l * 32 + m2) * 163840;
            uint32_t dst = sb;
#pragma unroll 1
            for (int k = 0; k < 20; k++) {
              if (k >= 5) mbar_wait(k >= S2 ? wb2 + 8 * k : bars + 8 * B_SFREE);
              if (k == 10) { mbar_wait(bars + 8 * (B_H1 + l)); fence_async_global(); }
              mbar_expect_tx(fb2 + 8 * k, G2_XB);
              bulk_g2s(dst, src, G2_XB, fb2 + 8 * k);
              src += 8192; dst += G2_XB; if (dst == sb + S2 * G2_XB) dst = sb;
            }
          }
          __syncwarp();
        }
      }
    } else if (pw == 2) {
#pragma unroll 1
      for (int l = 0; l < 2; l++) {
        if (l == 1) {
          float xa[2], xb[2];
          mbar_wait(bars + 8 * (B_G1FULL + 11));
          stat_table(T1, tag, 1, 4, g_stats, g_stats, xa, xb);
          mbar_arrive(bars + 8 * (B_STAB + 1));
        }
#pragma unroll 1
        for (int w = 0; w < 2 * l; w++) {
          mbar_wait(bars + 8 * (B_HST + 2 + w));
          if (lane == 0) { st_rel(&g_hflag[(((NT1 + T1) * 2 + w) * 16 + 2 * GP + side) * 8], tag); if (w == 0) mbar_arrive(bars + 8 * (B_REL + 1)); TS(w ? 16 : 14); }
          __syncwarp();
        }
        if (l == 0 && has2 && elect_one()) {
#pragma unroll 1
          for (int c = 0; c < 5; c++) {
            mbar_wait(bars + 8 * (B_CVDONE + c));
            bulk_s2g(g_G + (cch0 + 32 * c) * 4096, cv_stage(c), 4096);
          }
          asm volatile("cp.async.bulk.commit_group;" ::: "memory");
          asm volatile("cp.async.bulk.wait_group.read 0;" ::: "memory");
          mbar_arrive(bars + 8 * B_SFREE);
          asm volatile("cp.async.bulk.wait_group 0;" ::: "memory");
          TS(48);
          fence_async_global();
          st_rel(&g_gflag[(dg * 32 + m2) * 8], tag);
          TS(49);
          mbar_arrive(bars + 8 * (B_GO + 1));
        }
        __syncwarp();
      }
    } else if (has2) {
      mbar_wait(bars + 8 * B_REL);
      if (elect_one()) {
        l2_prefetch(p.cre + (160 * dg + 5 * m2) * DM, 6400); l2_prefetch(p.cim + (160 * dg + 5 * m2) * DM, 6400);
        asm volatile("prefetch.tensormap [%0];" ::"l"(&p.mG) : "memory");
      }
      const unsigned* hf = &g_hflag[(((lane < 16 ? (64 * m2) / 160 : (64 * m2 + 63) / 160) * 2 + 1) * 16 + min(lane & 15, 9)) * 8];
      mbar_wait(bars + 8 * (B_HST + 1));
      flag_poll(hf, tag);
      if (lane == 0) { mbar_arrive(bars + 8 * B_H1); TS(22); }
      if (SYNCW) {
        mbar_wait(bars + 8 * (B_CVDONE + 4));
        flag_poll(&g_rflag[((m2 & ~7) * 4 + (SYNCW == 2 ? lane : (lane & ~2) | (dg & 2))) * 8], tag);
        if (lane == 0) { mbar_arrive(bars + 8 * (B_GO + 2)); TS(15); }
      }
      mbar_wait(bars + 8 * (B_GO + 1));
      flag_poll(&g_gflag[(dg * 32 + lane) * 8], tag);
      fence_async_global();
      if (elect_one()) {
        TS(29);
        mbar_expect_tx(bars + 8 * B_GFULL, 20480);
        tma5(sb + G_OFF, &p.mG, 64 * m2, 0, 0, 0, 10 * dg, bars + 8 * B_GFULL);
      }
      mbar_wait(bars + 8 * (B_HST + 3));
      flag_poll(hf + NT1 * 256, tag);
      if (lane == 0) { mbar_arrive(bars + 8 * (B_H1 + 1)); TS(24); }
    }
    } else if (wg == 2 && (role >> 16)) {
      float acc[80];
      float off[2] = {mean0[0], mean0[1]};
      const unsigned tag = lds32(sb + EP_OFF + 20);
      if (tid == 256) asm volatile("st.relaxed.gpu.global.u32 [%0], %1;" ::"l"(&g_rflag[(((role >> 8) & 63) * 4 + ((role >> 14) & 3)) * 8]), "r"(tag) : "memory");
      dskip_init<true>(acc, mean0, rstd0);
      mbar_arrive(bars + 8 * B_XFREE);
#pragma unroll 1
      for (int l = 0; l < 2; l++) {
        float mean[2], rstd[2];
        {
          uint32_t alo = desc_lo(sb, 1024), blo = desc_lo(sb + G2_WOFF, 16);
          uint32_t fb = bars + 8 * (B_G2FULL + 20 * l);
          fence_regs(acc);
          if (SYNCW) mbar_wait(bars + 8 * (B_GO + 2));
          mbar_wait(fb);
          if (tid == 256) TS(33 + 6 * l);
#pragma unroll 1
          for (int k = 0; k < 20; k++) {
            if (l == TSL && (k & 3) == 3 && tid == 256) TS(56 + (k >> 2));
            uint32_t ok; const uint32_t nb = k < 19 ? fb + 8 : fb;
            wgmma_fence();
#pragma unroll
            for (int kk = 0; kk < 4; kk++) {
              wgmma_n160<1>(acc, alo + kk * 128, desc_hi(128, 0), blo + kk * 2, desc_hi(1024, 1));
              if (kk == 0) ok = mbar_test(nb);
            }
            wgmma_commit();
            alo += G2_XB >> 4; blo += G2_WB >> 4;
            if (alo == desc_lo(sb + S2 * G2_XB, 1024)) { alo = desc_lo(sb, 1024); blo = desc_lo(sb + G2_WOFF, 16); }
            wgmma_wait<1>();
            if (k > 0 && tid == 256) mbar_arrive(fb + 8 * (B_G2DONE - B_G2FULL - 1));
            if (!ok) mbar_wait(nb);
            fb += 8;
          }
          wgmma_wait<0>();
          fence_regs(acc);
          if (tid == 256) TS(34 + 6 * l);
          if (tid == 256) mbar_arrive(bars + 8 * (B_G2DONE + 20 * l + 19));
        }
        ROLE(role)
        const int tq = tid_opaque() & 31, n0 = 64 * m2 + 16 * w + (tq >> 2);
        stats_publish<false>(2 * l + 1, n0, dg, tag, acc);
        uint32_t gf[10][4];
        mbar_wait(bars + 8 * B_GFULL);
        const uint32_t ga = sb + G_OFF + (8 * (tq >> 4) + (tq & 7)) * 128 + (((2 * w + ((tq >> 3) & 1)) ^ ((2 * m2) & 6) ^ (tq & 7)) << 4);
#pragma unroll
        for (int J = 0; J < 2; J++) ldsm4t(gf[J], ga + J * 2048);
        if (tid == 256) TS(35 + 6 * l);
        uint8_t* dst[2][2];
#pragma unroll
        for (int h = 0; h < 2; h++) {
          if (l == 0) {
            const int ng = 8 * m2 + 2 * w + h, T = ng / 20;
            uint8_t* ub = g_u + (T * 204800 + (ng - 20 * T) * 1024 + (tq & 2) * 64 + (tq & 28) * 4 + (tq & 1) * 8 + (5 * dg >> 1) * 20480);
            dst[h][1] = ub + ((dg & 1) ? 20480 - 512 : 0);
            dst[h][0] = ub + (dg & 1) * 512;
          } else {
            dst[h][0] = dst[h][1] = (uint8_t*)(p.out + (n_to_t(n0 + 8 * h) * DM + 160 * dg + 4 * (tq & 3)));
          }
        }
        stats_get(2 * l + 1, n0, tag, mean, rstd);
        if (tid == 256) TS(36 + 6 * l);
        off[0] += mean[0]; off[1] += mean[1];
        const float ov[2] = {l ? off[0] : 0.f, l ? off[1] : 0.f};
#pragma unroll
        for (int J = 0; J < 10; J++) {
          if (J + 2 < 10) ldsm4t(gf[J + 2 < 10 ? J + 2 : 0], ga + (J + 2) * 2048);
#pragma unroll
          for (int x = 0; x < 8; x++) {
            const int h = (x >> 1) & 1;
            const uint32_t gwd = gf[J][x >> 1];
            const float t = fmaf(rstd[h], (x & 1) ? bf_hi(gwd) : bf_lo(gwd), 1.f);
            acc[8 * J + x] = fmaf(acc[8 * J + x], t, fmaf(-mean[h], t, ov[h]));
          }
#pragma unroll
          for (int h = 0; h < 2; h++) {
            if (l == 0)
              *(uint2*)(dst[h][(J >> 1) & 1] + (J >> 2) * 20480 + (J & 3) * 256) =
                  make_uint2(pack_bf16(acc[8 * J + 2 * h], acc[8 * J + 2 * h + 1]), pack_bf16(acc[8 * J + 4 + 2 * h], acc[8 * J + 5 + 2 * h]));
            else
              *(float4*)(dst[h][0] + 64 * J) = make_float4(acc[8 * J + 2 * h], acc[8 * J + 2 * h + 1], acc[8 * J + 4 + 2 * h], acc[8 * J + 5 + 2 * h]);
          }
          __syncwarp();
        }
        if (l == 0) {
          bar_sync(3, 128);
          if (tid == 256) { TS(37); st_rel(&g_uflag[(4 * m2 + dg) * 8], tag); mbar_arrive(bars + 8 * B_GO); TS(38); }
          stats_publish<false>(2, n0, dg, tag, acc);
          mbar_wait(bars + 8 * (B_G1FULL + 11));
          float xa[2], xb[2];
          const uint4* x0 = &g_stats[(8 + (tq & 3)) * SEQ + n0];
          stat_table(T1, tag, 1, w, x0, x0 + 8, xa, xb);
          mbar_arrive(bars + 8 * (B_STAB + 1));
          if (tid == 256) TS(27);
          stats_reduce(xa, xb, mean, rstd);
          off[0] += mean[0]; off[1] += mean[1];
          mbar_wait(bars + 8 * (B_HST + 2));
          dskip_init<false>(acc, mean, rstd);
        } else {
          if (tid == 256) {
            TS(43);
            if (m2 == 31 && dg == 3) asm volatile("st.relaxed.gpu.global.u32 [%0], %1;" ::"l"(g_epoch), "r"(tag + 1) : "memory");
          }
        }
      }
    }
  }
}

typedef CUresult (*EncFn)(CUtensorMap*, CUtensorMapDataType, cuuint32_t, void*, const cuuint64_t*, const cuuint64_t*,
                          const cuuint32_t*, const cuuint32_t*, CUtensorMapInterleave, CUtensorMapSwizzle,
                          CUtensorMapL2promotion, CUtensorMapFloatOOBfill);

void encode(EncFn fn, CUtensorMap* m, const void* ptr, int rank, const cuuint64_t* dims, const cuuint64_t* strides, const cuuint32_t* box,
            CUtensorMapSwizzle swz = CU_TENSOR_MAP_SWIZZLE_128B) {
  cuuint32_t es[5] = {1, 1, 1, 1, 1};
  fn(m, CU_TENSOR_MAP_DATA_TYPE_BFLOAT16, rank, (void*)ptr, dims, strides, box, es, CU_TENSOR_MAP_INTERLEAVE_NONE,
     swz, (CUtensorMapL2promotion)(swz == CU_TENSOR_MAP_SWIZZLE_128B ? PROM_A : PROM_B), CU_TENSOR_MAP_FLOAT_OOB_FILL_NONE);
}

}

extern "C" void kernel_launch(void* const* d_in, const int* in_sizes, int n_in, void* d_out, int out_size) {
  (void)in_sizes; (void)n_in; (void)out_size;
  Params p;
  typedef const __nv_bfloat16* BP;
  p.x = (BP)d_in[0]; p.lre = (BP)d_in[1]; p.lim = (BP)d_in[2]; p.bre = (BP)d_in[3]; p.bim = (BP)d_in[4];
  p.cre = (BP)d_in[5]; p.cim = (BP)d_in[6]; p.logdt = (BP)d_in[7]; p.dskip = (BP)d_in[8];
  p.k = (BP)d_in[10]; p.v = (BP)d_in[11]; p.shiftk = (BP)d_in[12]; p.ssmk = (BP)d_in[13]; p.ssmD = (BP)d_in[14];
  p.out = (float*)d_out;
  for (int sm = 0; sm < 132; sm++) {
    const int tpc = sm >> 1, side = sm & 1;
    int gpc, gi;
    if (tpc < 32) { gpc = tpc & 7; gi = tpc >> 3; }
    else if (tpc < 60) { gpc = 1 + (tpc - 32) % 7; gi = 4 + (tpc - 32) / 7; }
    else if (tpc < 62) { gpc = tpc - 54; gi = 8; }
    else { gpc = 0; gi = tpc - 58; }
    const int pos = 8 * gpc + gi + (gpc == 7 ? 1 : 0);
    int T1, GP;
    if (pos < 52) { const int hh = pos / 26, x = pos - 26 * hh; T1 = x >> 1; GP = 2 * hh + (x & 1); }
    else { T1 = pos - 52; GP = 4; }
    const int m2 = 8 * (gpc >> 1) + gi, dg = 2 * (gpc & 1) + side;
    p.role[sm] = pos == 65 ? -1 : (T1 | (GP << 4) | (side << 7) | (m2 << 8) | (dg << 14) | ((gi < 8) << 16));
  }
  void* fnp = nullptr;
  cudaDriverEntryPointQueryResult qr;
  cudaGetDriverEntryPoint("cuTensorMapEncodeTiled", &fnp, cudaEnableDefault, &qr);
  EncFn fn = (EncFn)fnp;
  void* gG = nullptr;
  cudaGetSymbolAddress(&gG, g_G);
  const cuuint64_t RB = DM * 2;
  {
    p.swap = p.bim < p.bre;
    const char* lo = (const char*)(p.swap ? p.bim : p.bre); const char* hi = (const char*)(p.swap ? p.bre : p.bim);
    cuuint64_t dims[5] = {640, 8, 2, 8, 10}, st[4] = {RB, (cuuint64_t)(hi - lo), 8 * RB, 64 * RB}; cuuint32_t box[5] = {64, 8, 2, 4, 2};
    encode(fn, &p.mB, lo, 5, dims, st, box);
  }
  {
    cuuint64_t dims[5] = {640, 2, 4, 2, 40}, st[4] = {RB, 4 * RB, 2 * RB, 16 * RB}; cuuint32_t box[5] = {64, 2, 4, 2, 10};
    encode(fn, &p.mCre, p.cre, 5, dims, st, box); encode(fn, &p.mCim, p.cim, 5, dims, st, box);
    cuuint64_t dimg[5] = {2048, 2, 4, 2, 40}, stg[4] = {4096, 4 * 4096, 2 * 4096, 16 * 4096};
    encode(fn, &p.mG, gG, 5, dimg, stg, box);
  }
  {
    cuuint64_t dims[4] = {640, 2, 4, 900}, st[3] = {RB, 40 * RB, 2 * RB}; cuuint32_t box[4] = {64, 2, 4, 20};
    encode(fn, &p.mX, p.x, 4, dims, st, box);
    cuuint64_t diml[4] = {640, 2, 4, 16}, stl[3] = {RB, 32 * RB, 2 * RB};
    encode(fn, &p.mXl, p.x + (size_t)1920 * DM, 4, diml, stl, box);
    cuuint32_t boxt[4] = {160, 2, 4, 4};
    encode(fn, &p.mXt, p.x, 4, dims, st, boxt, CU_TENSOR_MAP_SWIZZLE_NONE);
    encode(fn, &p.mXtl, p.x + (size_t)1920 * DM, 4, diml, stl, boxt, CU_TENSOR_MAP_SWIZZLE_NONE);
    cuuint64_t dk[3] = {640, 2000, 4}, sk[2] = {RB, 16 * RB}; cuuint32_t bk[3] = {32, 19, 4}, bv[3] = {32, 17, 4};
    encode(fn, &p.mK, p.k, 3, dk, sk, bk, CU_TENSOR_MAP_SWIZZLE_NONE);
    encode(fn, &p.mV, p.v, 3, dk, sk, bv, CU_TENSOR_MAP_SWIZZLE_NONE);
  }
  cudaFuncSetAttribute(fused_kernel, cudaFuncAttributeMaxDynamicSharedMemorySize, SMEM_BYTES);
  cudaLaunchConfig_t cfg = {};
  cfg.gridDim = dim3(132); cfg.blockDim = dim3(512); cfg.dynamicSmemBytes = SMEM_BYTES; cfg.stream = cudaStreamPerThread;
  cudaLaunchKernelEx(&cfg, fused_kernel, p);
}
```

```cpp
#include <cuda_runtime.h>
#include <cuda.h>
#include <cuda_bf16.h>
#include <stdint.h>

namespace {

constexpr int SEQ = 2048, DM = 640;
constexpr int NT1 = 13;
#define EXP 0
#define WPF1 3
#define WPF2 7
#define CPOLL 10
#define KV0 5
#define TAP0 2
#define PROM_A 2
#define PROM_B 2
#define XFIRST 0
#define TAPLATE 1
#define STG_D 3
#define STG_KK 1
#define HOLD0 1
#define WREL 0
#define UREL 1
#define TSL 1
#define TABW 0
#define STG0 3
#define SYNCW 0
#define PAUSE_K 4
constexpr uint32_t SPIN_LIMIT = 1u << 22;

__device__ __align__(1024) uint8_t g_h[2 * 32 * 20 * 8192];
__device__ __align__(1024) uint8_t g_u[NT1 * 10 * 20480];
__device__ __align__(1024) uint8_t g_kv[DM * 4096];
__device__ __align__(1024) uint8_t g_G[DM * 4096];
__device__ __align__(128) uint4 g_E[2 * NT1 * DM];
__device__ __align__(128) uint4 g_stats[4 * 4 * SEQ];
__device__ __align__(128) uint4 g_sB[DM * 2];
__device__ __align__(128) unsigned g_hcnt[2 * 2 * 8 * 32];
__device__ __align__(128) unsigned g_ucnt[8 * 32];
__device__ __align__(128) unsigned g_kvflag[4 * 32 * 8];
__device__ __align__(128) unsigned g_gflag[4 * 32 * 8];
__device__ __align__(128) unsigned g_rflag[128 * 8];
__device__ __align__(128) unsigned g_epoch[32] = {1};
#define TS(i) do {} while (0)

struct Params {
  CUtensorMap mB, mCre, mCim, mX, mXl, mG, mK, mV, mXt, mXtl;
  const __nv_bfloat16 *x, *lre, *lim, *bre, *bim, *cre, *cim, *logdt, *dskip, *k, *v, *shiftk, *ssmk, *ssmD;
  float* out;
  int swap;
  int role[132];
};

constexpr uint32_t sb = 1024;
constexpr uint32_t G1_STAGE = 36864, G1_XOFF = 16384;
constexpr int S1 = 4;
constexpr uint32_t XT_OFF = 159744, KS_OFF = 180224, KV_PIECE = 9216;
constexpr uint32_t G2_XB = 8192, G2_WB = 20480, G2_WOFF = 57344, G_OFF = 200704;
constexpr int S2 = 7;
constexpr uint32_t CV_OFF = KS_OFF, CV_K = 128, CV_PL = 2240, CV_U = CV_K + 4096, CV_B = KV_PIECE;
constexpr uint32_t MISC = 226304;
constexpr uint32_t BAR_OFF = MISC;
constexpr int B_G1FULL = 0, B_G1DONE = 20, B_G2FULL = 40, B_CVFULL = 80  ,
              B_G2DONE = 85, B_GFULL = 125, B_EP = 126, B_H1 = 127  , B_STG = 134  , B_REL = 136  , B_SFREE = 138, B_UST = 142,
              B_GO = 139  , B_PUB = 147,
              B_CVDONE = 148  , B_STAB = 153  , B_XFREE = 155, B_HST = 156  ,
              B_CTAB = 160, B_PREP = 161, B_XT = 162, B_KV = 163  ;
constexpr uint32_t bars = sb + BAR_OFF;
constexpr uint32_t STAB_OFF = MISC + 1344;
constexpr uint32_t CTAB_OFF = STAB_OFF + 1280;
constexpr uint32_t DTAB_OFF = CTAB_OFF + 1536;
constexpr uint32_t EP_OFF = DTAB_OFF + 320;
constexpr uint32_t SO_OFF = EP_OFF + 32;
constexpr uint32_t TAP_OFF = 147456;
constexpr uint32_t SMEM_BYTES = 232448;
static_assert(SO_OFF + 1536 <= SMEM_BYTES, "smem");

__device__ __forceinline__ void trap_if(bool c) { asm volatile("{\n.reg .pred p;\nsetp.ne.u32 p, %0, 0;\n@p trap;\n}\n" ::"r"((uint32_t)c)); }
__device__ __forceinline__ uint32_t smem_u32(const void* p) { return (uint32_t)__cvta_generic_to_shared(p); }
__device__ __forceinline__ void mbar_init(uint32_t bar, int cnt) { asm volatile("mbarrier.init.shared::cta.b64 [%0], %1;" ::"r"(bar), "r"(cnt) : "memory"); }
__device__ __forceinline__ void mbar_expect_tx(uint32_t bar, int bytes) { asm volatile("mbarrier.arrive.expect_tx.shared::cta.b64 _, [%0], %1;" ::"r"(bar), "r"(bytes) : "memory"); }
__device__ __forceinline__ void mbar_arrive(uint32_t bar) { asm volatile("mbarrier.arrive.shared::cta.b64 _, [%0];" ::"r"(bar) : "memory"); }
__device__ __forceinline__ void mbar_wait(uint32_t bar) {
  asm volatile(
      "{\n.reg .pred p;\n.reg .u32 c;\nmov.u32 c, 0;\n"
      "W_%=:\nmbarrier.try_wait.parity.shared::cta.b64 p, [%0], 0;\n@p bra D_%=;\n"
      "add.u32 c, c, 1;\nsetp.lt.u32 p, c, %1;\n@p bra W_%=;\ntrap;\nD_%=:\n}\n" ::"r"(bar), "n"(SPIN_LIMIT) : "memory");
}
__device__ __forceinline__ uint32_t mbar_test(uint32_t bar) {
  uint32_t ok;
  asm volatile("{\n.reg .pred p;\nmbarrier.test_wait.parity.shared::cta.b64 p, [%1], 0;\nselp.u32 %0, 1, 0, p;\n}\n" : "=r"(ok) : "r"(bar) : "memory");
  return ok;
}
__device__ __forceinline__ void tma3(uint32_t dst, const CUtensorMap* m, int c0, int c1, int c2, uint32_t bar) {
  asm volatile("cp.async.bulk.tensor.3d.shared::cluster.global.mbarrier::complete_tx::bytes [%0], [%1, {%3,%4,%5}], [%2];"
               ::"r"(dst), "l"(m), "r"(bar), "r"(c0), "r"(c1), "r"(c2) : "memory");
}
__device__ __forceinline__ void tma4(uint32_t dst, const CUtensorMap* m, int c0, int c1, int c2, int c3, uint32_t bar) {
  asm volatile("cp.async.bulk.tensor.4d.shared::cluster.global.mbarrier::complete_tx::bytes [%0], [%1, {%3,%4,%5,%6}], [%2];"
               ::"r"(dst), "l"(m), "r"(bar), "r"(c0), "r"(c1), "r"(c2), "r"(c3) : "memory");
}
__device__ __forceinline__ void tma5(uint32_t dst, const CUtensorMap* m, int c0, int c1, int c2, int c3, int c4, uint32_t bar) {
  asm volatile("cp.async.bulk.tensor.5d.shared::cluster.global.mbarrier::complete_tx::bytes [%0], [%1, {%3,%4,%5,%6,%7}], [%2];"
               ::"r"(dst), "l"(m), "r"(bar), "r"(c0), "r"(c1), "r"(c2), "r"(c3), "r"(c4) : "memory");
}
__device__ __forceinline__ void bulk_g2s(uint32_t dst, const void* src, int bytes, uint32_t bar) {
  asm volatile("cp.async.bulk.shared::cluster.global.mbarrier::complete_tx::bytes [%0], [%1], %2, [%3];"
               ::"r"(dst), "l"(src), "r"(bytes), "r"(bar) : "memory");
}
__device__ __forceinline__ void bulk_s2g(void* dst, uint32_t src, int bytes) {
  asm volatile("cp.async.bulk.global.shared::cta.bulk_group [%0], [%1], %2;" ::"l"(dst), "r"(src), "r"(bytes) : "memory");
}
__device__ __forceinline__ void l2_prefetch(const void* src, int bytes) {
  asm volatile("cp.async.bulk.prefetch.L2.global [%0], %1;" ::"l"(src), "r"(bytes) : "memory");
}
__device__ __forceinline__ void wgmma_fence() { asm volatile("wgmma.fence.sync.aligned;" ::: "memory"); }
__device__ __forceinline__ void wgmma_commit() { asm volatile("wgmma.commit_group.sync.aligned;" ::: "memory"); }
template <int N> __device__ __forceinline__ void wgmma_wait() { asm volatile("wgmma.wait_group.sync.aligned %0;" ::"n"(N) : "memory"); }
__host__ __device__ constexpr uint32_t desc_lo(uint32_t addr, uint32_t lbo) { return ((addr & 0x3FFFF) >> 4) | ((lbo >> 4) << 16); }
__host__ __device__ constexpr uint32_t desc_hi(uint32_t sbo, uint32_t swz) { return (sbo >> 4) | (swz << 30); }
__device__ __forceinline__ void bar_sync(int id, int n) { asm volatile("bar.sync %0, %1;" ::"r"(id), "r"(n) : "memory"); }
__device__ __forceinline__ uint32_t lds32(uint32_t a) { uint32_t v; asm volatile("ld.shared.u32 %0, [%1];" : "=r"(v) : "r"(a) : "memory"); return v; }
__device__ __forceinline__ float2 lds64f(uint32_t a) { float2 v; asm volatile("ld.shared.v2.f32 {%0,%1}, [%2];" : "=f"(v.x), "=f"(v.y) : "r"(a) : "memory"); return v; }
__device__ __forceinline__ float4 lds128f(uint32_t a) { float4 v; asm volatile("ld.shared.v4.f32 {%0,%1,%2,%3}, [%4];" : "=f"(v.x), "=f"(v.y), "=f"(v.z), "=f"(v.w) : "r"(a) : "memory"); return v; }
__device__ __forceinline__ void ldsm4t(uint32_t (&r)[4], uint32_t a) {
  asm volatile("ldmatrix.sync.aligned.m8n8.x4.trans.shared.b16 {%0,%1,%2,%3}, [%4];" : "=r"(r[0]), "=r"(r[1]), "=r"(r[2]), "=r"(r[3]) : "r"(a) : "memory");
}
__device__ __forceinline__ uint4 ldv128(const void* a) { uint4 v; asm volatile("ld.global.nc.v4.u32 {%0,%1,%2,%3}, [%4];" : "=r"(v.x), "=r"(v.y), "=r"(v.z), "=r"(v.w) : "l"(a) : "memory"); return v; }
__device__ __forceinline__ uint2 ldv64(const void* a) { uint2 v; asm volatile("ld.global.nc.v2.u32 {%0,%1}, [%2];" : "=r"(v.x), "=r"(v.y) : "l"(a) : "memory"); return v; }
__device__ __forceinline__ uint32_t ldv16(const void* a) { uint32_t v; asm volatile("ld.global.nc.u16 %0, [%1];" : "=r"(v) : "l"(a) : "memory"); return v; }
__device__ __forceinline__ void sts128(uint32_t a, uint4 v) { asm volatile("st.shared.v4.u32 [%0], {%1,%2,%3,%4};" ::"r"(a), "r"(v.x), "r"(v.y), "r"(v.z), "r"(v.w) : "memory"); }
__device__ __forceinline__ void sts32(uint32_t a, uint32_t v) { asm volatile("st.shared.u32 [%0], %1;" ::"r"(a), "r"(v) : "memory"); }
__device__ __forceinline__ void sts64f(uint32_t a, float x, float y) { asm volatile("st.shared.v2.f32 [%0], {%1,%2};" ::"r"(a), "f"(x), "f"(y) : "memory"); }
__device__ __forceinline__ void st_rel(unsigned* p, unsigned v) { asm volatile("st.release.gpu.global.u32 [%0], %1;" ::"l"(p), "r"(v) : "memory"); }
__device__ __forceinline__ void red_rel(unsigned* p) { asm volatile("red.release.gpu.global.add.u32 [%0], 1;" ::"l"(p) : "memory"); }
__device__ __forceinline__ void fence_async_global() { asm volatile("fence.proxy.async.global;" ::: "memory"); }
__device__ __forceinline__ void fence_async_smem() { asm volatile("fence.proxy.async.shared::cta;" ::: "memory"); }
__device__ __forceinline__ void rec_st(uint4* p, float a, float b, unsigned tag) {
  asm volatile("{\n.reg .b128 t;\n.reg .b64 lo, hi;\nmov.b64 lo, {%1,%2};\nmov.b64 hi, {%3,%3};\nmov.b128 t, {lo,hi};\n"
               "st.relaxed.gpu.global.b128 [%0], t;\n}\n" ::"l"(p), "r"(__float_as_uint(a)), "r"(__float_as_uint(b)), "r"(tag) : "memory");
}
__device__ __forceinline__ unsigned rec_ld(const uint4* p, float& a, float& b) {
  unsigned x, y, t;
  asm volatile("{\n.reg .b128 t;\n.reg .b64 lo, hi;\n.reg .b32 u;\nld.relaxed.gpu.global.b128 t, [%3];\nmov.b128 {lo,hi}, t;\n"
               "mov.b64 {%0,%1}, lo;\nmov.b64 {%2,u}, hi;\n}\n" : "=r"(x), "=r"(y), "=r"(t) : "l"(p) : "memory");
  a = __uint_as_float(x); b = __uint_as_float(y);
  return t;
}
__device__ __forceinline__ unsigned ld_rlx(const unsigned* p) { unsigned v; asm volatile("ld.relaxed.gpu.global.u32 %0, [%1];" : "=r"(v) : "l"(p) : "memory"); return v; }
__device__ __forceinline__ void flag_poll(const unsigned* p, unsigned target) {
  uint32_t it = 0;
  while (!__all_sync(0xffffffffu, (int)(ld_rlx(p) - target) >= 0)) { trap_if(++it > SPIN_LIMIT); }
  asm volatile("fence.acquire.gpu;" ::: "memory");
}
__device__ __forceinline__ void cnt_poll(const unsigned* p, unsigned target) {
  unsigned a = ld_rlx(p); __nanosleep(100);
  unsigned b = ld_rlx(p); __nanosleep(100);
  unsigned c = ld_rlx(p);
  uint32_t it = 0;
  while (true) {
    if (__all_sync(0xffffffffu, (int)(a - target) >= 0)) break;
    a = ld_rlx(p);
    if (__all_sync(0xffffffffu, (int)(b - target) >= 0)) break;
    b = ld_rlx(p);
    if (__all_sync(0xffffffffu, (int)(c - target) >= 0)) break;
    c = ld_rlx(p);
    trap_if(++it > SPIN_LIMIT);
  }
  asm volatile("fence.acquire.gpu;" ::: "memory");
}
__device__ __forceinline__ void h_release(int idx, int T, int i) {
  const int Q = (i & 2) ? (T + 2) / 3 - 1 : T / 3;
  if (Q >= 0 && Q < 4 && ((i & 2) == 0 || T % 3 == 0)) red_rel(&g_hcnt[(idx * 8 + 2 * Q + (i & 1)) * 32]);
}
__device__ __forceinline__ uint32_t pack_bf16(float lo, float hi) {
  uint32_t r; asm("cvt.rn.bf16x2.f32 %0, %1, %2;" : "=r"(r) : "f"(hi), "f"(lo)); return r;
}
__device__ __forceinline__ float bf_lo(uint32_t w) { return __uint_as_float(w << 16); }
__device__ __forceinline__ float bf_hi(uint32_t w) { return __uint_as_float(w & 0xffff0000u); }
__device__ __forceinline__ uint32_t hmul2(uint32_t a, uint32_t b) {
  __nv_bfloat162 r = __hmul2_rn(*(__nv_bfloat162*)&a, *(__nv_bfloat162*)&b); return *(uint32_t*)&r;
}
__device__ __forceinline__ uint32_t hadd2(uint32_t a, uint32_t b) {
  __nv_bfloat162 r = __hadd2_rn(*(__nv_bfloat162*)&a, *(__nv_bfloat162*)&b); return *(uint32_t*)&r;
}
__device__ __forceinline__ float2 cmul(float2 a, float2 b) { return make_float2(a.x * b.x - a.y * b.y, a.x * b.y + a.y * b.x); }
__device__ __forceinline__ float2 cfma(float2 a, float2 b, float2 c) {
  return make_float2(fmaf(a.x, b.x, fmaf(-a.y, b.y, c.x)), fmaf(a.x, b.y, fmaf(a.y, b.x, c.y)));
}
template <int N> __device__ __forceinline__ void fence_regs(float (&a)[N]) {
#pragma unroll
  for (int i = 0; i < N; i++) asm volatile("" : "+f"(a[i])::"memory");
}
__device__ __forceinline__ bool elect_one() {
  uint32_t e; asm volatile("{\n.reg .pred P;\nelect.sync _|P, 0xffffffff;\nselp.u32 %0, 1, 0, P;\n}\n" : "=r"(e)); return e != 0;
}
__device__ __forceinline__ int tid_opaque() { int t; asm volatile("mov.u32 %0, %%tid.x;" : "=r"(t)); return t; }
struct Role { int T1, GP, side, m2, dg, cch0; bool last, has2; };
__device__ __forceinline__ Role unpack_role(int x) {
  Role r; r.T1 = x & 15; r.GP = (x >> 4) & 7; r.side = (x >> 7) & 1; r.m2 = (x >> 8) & 63; r.dg = (x >> 14) & 3;
  r.has2 = (x >> 16) & 1; r.last = r.T1 == NT1 - 1; r.cch0 = 160 * r.dg + r.m2; return r;
}
__device__ __forceinline__ Role fresh_role(int x) { asm volatile("" : "+r"(x)); return unpack_role(__shfl_sync(0xffffffffu, x, 0)); }
#define ROLE(x) const Role R_ = fresh_role(x); const int T1 = R_.T1, GP = R_.GP, side = R_.side, m2 = R_.m2, dg = R_.dg, cch0 = R_.cch0; \
  const bool last = R_.last, has2 = R_.has2; (void)T1; (void)GP; (void)side; (void)m2; (void)dg; (void)cch0; (void)last; (void)has2;
__device__ __forceinline__ int n_to_t(int n) {
  int T = n / 160, nl = n - T * 160;
  int L = (T == NT1 - 1) ? 32 : 40;
  return T * 160 + L * ((nl & 7) >> 1) + 2 * (nl >> 3) + (nl & 1);
}

template<int TA> __device__ __forceinline__ void wgmma_n160(float (&d)[80], uint32_t alo, uint32_t ahi, uint32_t blo, uint32_t bhi){
  asm volatile("{\n.reg .b64 da, db;\nmov.b64 da, {%80,%81};\nmov.b64 db, {%82,%83};\n"
    "wgmma.mma_async.sync.aligned.m64n160k16.f32.bf16.bf16 {%0, %1, %2, %3, %4, %5, %6, %7, %8, %9, %10, %11, %12, %13, %14, %15, %16, %17, %18, %19, %20, %21, %22, %23, %24, %25, %26, %27, %28, %29, %30, %31, %32, %33, %34, %35, %36, %37, %38, %39, %40, %41, %42, %43, %44, %45, %46, %47, %48, %49, %50, %51, %52, %53, %54, %55, %56, %57, %58, %59, %60, %61, %62, %63, %64, %65, %66, %67, %68, %69, %70, %71, %72, %73, %74, %75, %76, %77, %78, %79}, da, db, 1, 1, 1, %84, 0;\n}\n"
    : "+f"(d[0]), "+f"(d[1]), "+f"(d[2]), "+f"(d[3]), "+f"(d[4]), "+f"(d[5]), "+f"(d[6]), "+f"(d[7]), "+f"(d[8]), "+f"(d[9]), "+f"(d[10]), "+f"(d[11]), "+f"(d[12]), "+f"(d[13]), "+f"(d[14]), "+f"(d[15]), "+f"(d[16]), "+f"(d[17]), "+f"(d[18]), "+f"(d[19]), "+f"(d[20]), "+f"(d[21]), "+f"(d[22]), "+f"(d[23]), "+f"(d[24]), "+f"(d[25]), "+f"(d[26]), "+f"(d[27]), "+f"(d[28]), "+f"(d[29]), "+f"(d[30]), "+f"(d[31]), "+f"(d[32]), "+f"(d[33]), "+f"(d[34]), "+f"(d[35]), "+f"(d[36]), "+f"(d[37]), "+f"(d[38]), "+f"(d[39]), "+f"(d[40]), "+f"(d[41]), "+f"(d[42]), "+f"(d[43]), "+f"(d[44]), "+f"(d[45]), "+f"(d[46]), "+f"(d[47]), "+f"(d[48]), "+f"(d[49]), "+f"(d[50]), "+f"(d[51]), "+f"(d[52]), "+f"(d[53]), "+f"(d[54]), "+f"(d[55]), "+f"(d[56]), "+f"(d[57]), "+f"(d[58]), "+f"(d[59]), "+f"(d[60]), "+f"(d[61]), "+f"(d[62]), "+f"(d[63]), "+f"(d[64]), "+f"(d[65]), "+f"(d[66]), "+f"(d[67]), "+f"(d[68]), "+f"(d[69]), "+f"(d[70]), "+f"(d[71]), "+f"(d[72]), "+f"(d[73]), "+f"(d[74]), "+f"(d[75]), "+f"(d[76]), "+f"(d[77]), "+f"(d[78]), "+f"(d[79])
    : "r"(alo), "r"(ahi), "r"(blo), "r"(bhi), "n"(TA));
}
template<int N> __device__ __forceinline__ void wgmma_rs_hi(float (&d)[64], uint32_t a0, uint32_t a1, uint32_t a2, uint32_t a3, uint32_t blo);
template<> __device__ __forceinline__ void wgmma_rs_hi<16>(float (&d)[64], uint32_t a0, uint32_t a1, uint32_t a2, uint32_t a3, uint32_t blo){
  asm volatile("{\n.reg .b64 db;\nmov.b64 db, {%12,8};\nwgmma.mma_async.sync.aligned.m64n16k16.f32.bf16.bf16 {%0, %1, %2, %3, %4, %5, %6, %7}, {%8,%9,%10,%11}, db, 1, 1, 1, 0;\n}\n"
    : "+f"(d[56]), "+f"(d[57]), "+f"(d[58]), "+f"(d[59]), "+f"(d[60]), "+f"(d[61]), "+f"(d[62]), "+f"(d[63])
    : "r"(a0), "r"(a1), "r"(a2), "r"(a3), "r"(blo));
}
template<> __device__ __forceinline__ void wgmma_rs_hi<32>(float (&d)[64], uint32_t a0, uint32_t a1, uint32_t a2, uint32_t a3, uint32_t blo){
  asm volatile("{\n.reg .b64 db;\nmov.b64 db, {%20,8};\nwgmma.mma_async.sync.aligned.m64n32k16.f32.bf16.bf16 {%0, %1, %2, %3, %4, %5, %6, %7, %8, %9, %10, %11, %12, %13, %14, %15}, {%16,%17,%18,%19}, db, 1, 1, 1, 0;\n}\n"
    : "+f"(d[48]), "+f"(d[49]), "+f"(d[50]), "+f"(d[51]), "+f"(d[52]), "+f"(d[53]), "+f"(d[54]), "+f"(d[55]), "+f"(d[56]), "+f"(d[57]), "+f"(d[58]), "+f"(d[59]), "+f"(d[60]), "+f"(d[61]), "+f"(d[62]), "+f"(d[63])
    : "r"(a0), "r"(a1), "r"(a2), "r"(a3), "r"(blo));
}
template<> __device__ __forceinline__ void wgmma_rs_hi<48>(float (&d)[64], uint32_t a0, uint32_t a1, uint32_t a2, uint32_t a3, uint32_t blo){
  asm volatile("{\n.reg .b64 db;\nmov.b64 db, {%28,8};\nwgmma.mma_async.sync.aligned.m64n48k16.f32.bf16.bf16 {%0, %1, %2, %3, %4, %5, %6, %7, %8, %9, %10, %11, %12, %13, %14, %15, %16, %17, %18, %19, %20, %21, %22, %23}, {%24,%25,%26,%27}, db, 1, 1, 1, 0;\n}\n"
    : "+f"(d[40]), "+f"(d[41]), "+f"(d[42]), "+f"(d[43]), "+f"(d[44]), "+f"(d[45]), "+f"(d[46]), "+f"(d[47]), "+f"(d[48]), "+f"(d[49]), "+f"(d[50]), "+f"(d[51]), "+f"(d[52]), "+f"(d[53]), "+f"(d[54]), "+f"(d[55]), "+f"(d[56]), "+f"(d[57]), "+f"(d[58]), "+f"(d[59]), "+f"(d[60]), "+f"(d[61]), "+f"(d[62]), "+f"(d[63])
    : "r"(a0), "r"(a1), "r"(a2), "r"(a3), "r"(blo));
}
template<> __device__ __forceinline__ void wgmma_rs_hi<64>(float (&d)[64], uint32_t a0, uint32_t a1, uint32_t a2, uint32_t a3, uint32_t blo){
  asm volatile("{\n.reg .b64 db;\nmov.b64 db, {%36,8};\nwgmma.mma_async.sync.aligned.m64n64k16.f32.bf16.bf16 {%0, %1, %2, %3, %4, %5, %6, %7, %8, %9, %10, %11, %12, %13, %14, %15, %16, %17, %18, %19, %20, %21, %22, %23, %24, %25, %26, %27, %28, %29, %30, %31}, {%32,%33,%34,%35}, db, 1, 1, 1, 0;\n}\n"
    : "+f"(d[32]), "+f"(d[33]), "+f"(d[34]), "+f"(d[35]), "+f"(d[36]), "+f"(d[37]), "+f"(d[38]), "+f"(d[39]), "+f"(d[40]), "+f"(d[41]), "+f"(d[42]), "+f"(d[43]), "+f"(d[44]), "+f"(d[45]), "+f"(d[46]), "+f"(d[47]), "+f"(d[48]), "+f"(d[49]), "+f"(d[50]), "+f"(d[51]), "+f"(d[52]), "+f"(d[53]), "+f"(d[54]), "+f"(d[55]), "+f"(d[56]), "+f"(d[57]), "+f"(d[58]), "+f"(d[59]), "+f"(d[60]), "+f"(d[61]), "+f"(d[62]), "+f"(d[63])
    : "r"(a0), "r"(a1), "r"(a2), "r"(a3), "r"(blo));
}
template<> __device__ __forceinline__ void wgmma_rs_hi<80>(float (&d)[64], uint32_t a0, uint32_t a1, uint32_t a2, uint32_t a3, uint32_t blo){
  asm volatile("{\n.reg .b64 db;\nmov.b64 db, {%44,8};\nwgmma.mma_async.sync.aligned.m64n80k16.f32.bf16.bf16 {%0, %1, %2, %3, %4, %5, %6, %7, %8, %9, %10, %11, %12, %13, %14, %15, %16, %17, %18, %19, %20, %21, %22, %23, %24, %25, %26, %27, %28, %29, %30, %31, %32, %33, %34, %35, %36, %37, %38, %39}, {%40,%41,%42,%43}, db, 1, 1, 1, 0;\n}\n"
    : "+f"(d[24]), "+f"(d[25]), "+f"(d[26]), "+f"(d[27]), "+f"(d[28]), "+f"(d[29]), "+f"(d[30]), "+f"(d[31]), "+f"(d[32]), "+f"(d[33]), "+f"(d[34]), "+f"(d[35]), "+f"(d[36]), "+f"(d[37]), "+f"(d[38]), "+f"(d[39]), "+f"(d[40]), "+f"(d[41]), "+f"(d[42]), "+f"(d[43]), "+f"(d[44]), "+f"(d[45]), "+f"(d[46]), "+f"(d[47]), "+f"(d[48]), "+f"(d[49]), "+f"(d[50]), "+f"(d[51]), "+f"(d[52]), "+f"(d[53]), "+f"(d[54]), "+f"(d[55]), "+f"(d[56]), "+f"(d[57]), "+f"(d[58]), "+f"(d[59]), "+f"(d[60]), "+f"(d[61]), "+f"(d[62]), "+f"(d[63])
    : "r"(a0), "r"(a1), "r"(a2), "r"(a3), "r"(blo));
}
template<> __device__ __forceinline__ void wgmma_rs_hi<96>(float (&d)[64], uint32_t a0, uint32_t a1, uint32_t a2, uint32_t a3, uint32_t blo){
  asm volatile("{\n.reg .b64 db;\nmov.b64 db, {%52,8};\nwgmma.mma_async.sync.aligned.m64n96k16.f32.bf16.bf16 {%0, %1, %2, %3, %4, %5, %6, %7, %8, %9, %10, %11, %12, %13, %14, %15, %16, %17, %18, %19, %20, %21, %22, %23, %24, %25, %26, %27, %28, %29, %30, %31, %32, %33, %34, %35, %36, %37, %38, %39, %40, %41, %42, %43, %44, %45, %46, %47}, {%48,%49,%50,%51}, db, 1, 1, 1, 0;\n}\n"
    : "+f"(d[16]), "+f"(d[17]), "+f"(d[18]), "+f"(d[19]), "+f"(d[20]), "+f"(d[21]), "+f"(d[22]), "+f"(d[23]), "+f"(d[24]), "+f"(d[25]), "+f"(d[26]), "+f"(d[27]), "+f"(d[28]), "+f"(d[29]), "+f"(d[30]), "+f"(d[31]), "+f"(d[32]), "+f"(d[33]), "+f"(d[34]), "+f"(d[35]), "+f"(d[36]), "+f"(d[37]), "+f"(d[38]), "+f"(d[39]), "+f"(d[40]), "+f"(d[41]), "+f"(d[42]), "+f"(d[43]), "+f"(d[44]), "+f"(d[45]), "+f"(d[46]), "+f"(d[47]), "+f"(d[48]), "+f"(d[49]), "+f"(d[50]), "+f"(d[51]), "+f"(d[52]), "+f"(d[53]), "+f"(d[54]), "+f"(d[55]), "+f"(d[56]), "+f"(d[57]), "+f"(d[58]), "+f"(d[59]), "+f"(d[60]), "+f"(d[61]), "+f"(d[62]), "+f"(d[63])
    : "r"(a0), "r"(a1), "r"(a2), "r"(a3), "r"(blo));
}
template<> __device__ __forceinline__ void wgmma_rs_hi<112>(float (&d)[64], uint32_t a0, uint32_t a1, uint32_t a2, uint32_t a3, uint32_t blo){
  asm volatile("{\n.reg .b64 db;\nmov.b64 db, {%60,8};\nwgmma.mma_async.sync.aligned.m64n112k16.f32.bf16.bf16 {%0, %1, %2, %3, %4, %5, %6, %7, %8, %9, %10, %11, %12, %13, %14, %15, %16, %17, %18, %19, %20, %21, %22, %23, %24, %25, %26, %27, %28, %29, %30, %31, %32, %33, %34, %35, %36, %37, %38, %39, %40, %41, %42, %43, %44, %45, %46, %47, %48, %49, %50, %51, %52, %53, %54, %55}, {%56,%57,%58,%59}, db, 1, 1, 1, 0;\n}\n"
    : "+f"(d[8]), "+f"(d[9]), "+f"(d[10]), "+f"(d[11]), "+f"(d[12]), "+f"(d[13]), "+f"(d[14]), "+f"(d[15]), "+f"(d[16]), "+f"(d[17]), "+f"(d[18]), "+f"(d[19]), "+f"(d[20]), "+f"(d[21]), "+f"(d[22]), "+f"(d[23]), "+f"(d[24]), "+f"(d[25]), "+f"(d[26]), "+f"(d[27]), "+f"(d[28]), "+f"(d[29]), "+f"(d[30]), "+f"(d[31]), "+f"(d[32]), "+f"(d[33]), "+f"(d[34]), "+f"(d[35]), "+f"(d[36]), "+f"(d[37]), "+f"(d[38]), "+f"(d[39]), "+f"(d[40]), "+f"(d[41]), "+f"(d[42]), "+f"(d[43]), "+f"(d[44]), "+f"(d[45]), "+f"(d[46]), "+f"(d[47]), "+f"(d[48]), "+f"(d[49]), "+f"(d[50]), "+f"(d[51]), "+f"(d[52]), "+f"(d[53]), "+f"(d[54]), "+f"(d[55]), "+f"(d[56]), "+f"(d[57]), "+f"(d[58]), "+f"(d[59]), "+f"(d[60]), "+f"(d[61]), "+f"(d[62]), "+f"(d[63])
    : "r"(a0), "r"(a1), "r"(a2), "r"(a3), "r"(blo));
}
template<> __device__ __forceinline__ void wgmma_rs_hi<128>(float (&d)[64], uint32_t a0, uint32_t a1, uint32_t a2, uint32_t a3, uint32_t blo){
  asm volatile("{\n.reg .b64 db;\nmov.b64 db, {%68,8};\nwgmma.mma_async.sync.aligned.m64n128k16.f32.bf16.bf16 {%0, %1, %2, %3, %4, %5, %6, %7, %8, %9, %10, %11, %12, %13, %14, %15, %16, %17, %18, %19, %20, %21, %22, %23, %24, %25, %26, %27, %28, %29, %30, %31, %32, %33, %34, %35, %36, %37, %38, %39, %40, %41, %42, %43, %44, %45, %46, %47, %48, %49, %50, %51, %52, %53, %54, %55, %56, %57, %58, %59, %60, %61, %62, %63}, {%64,%65,%66,%67}, db, 1, 1, 1, 0;\n}\n"
    : "+f"(d[0]), "+f"(d[1]), "+f"(d[2]), "+f"(d[3]), "+f"(d[4]), "+f"(d[5]), "+f"(d[6]), "+f"(d[7]), "+f"(d[8]), "+f"(d[9]), "+f"(d[10]), "+f"(d[11]), "+f"(d[12]), "+f"(d[13]), "+f"(d[14]), "+f"(d[15]), "+f"(d[16]), "+f"(d[17]), "+f"(d[18]), "+f"(d[19]), "+f"(d[20]), "+f"(d[21]), "+f"(d[22]), "+f"(d[23]), "+f"(d[24]), "+f"(d[25]), "+f"(d[26]), "+f"(d[27]), "+f"(d[28]), "+f"(d[29]), "+f"(d[30]), "+f"(d[31]), "+f"(d[32]), "+f"(d[33]), "+f"(d[34]), "+f"(d[35]), "+f"(d[36]), "+f"(d[37]), "+f"(d[38]), "+f"(d[39]), "+f"(d[40]), "+f"(d[41]), "+f"(d[42]), "+f"(d[43]), "+f"(d[44]), "+f"(d[45]), "+f"(d[46]), "+f"(d[47]), "+f"(d[48]), "+f"(d[49]), "+f"(d[50]), "+f"(d[51]), "+f"(d[52]), "+f"(d[53]), "+f"(d[54]), "+f"(d[55]), "+f"(d[56]), "+f"(d[57]), "+f"(d[58]), "+f"(d[59]), "+f"(d[60]), "+f"(d[61]), "+f"(d[62]), "+f"(d[63])
    : "r"(a0), "r"(a1), "r"(a2), "r"(a3), "r"(blo));
}

__device__ __forceinline__ float shfl_sel(float a, float b, bool p, int src) {
  float r;
  asm volatile("{\n.reg .pred P;\n.reg .f32 t;\nsetp.ne.u32 P, %3, 0;\nselp.f32 t, %1, %2, P;\nshfl.sync.idx.b32 %0, t, %4, 0x1f, 0xffffffff;\n}\n"
               : "=f"(r) : "f"(a), "f"(b), "r"((uint32_t)p), "r"(src));
  return r;
}
struct CvCtx {
  uint32_t koff, zero, so[3];
  int srcA, srcB;
  bool wrapA, s3, kodd;
};
struct CvPipe { float Ep[2], keep[2], send[2]; };
template <int LO> __device__ __forceinline__ void cv_copy(float (&acc)[64]) {
#pragma unroll
  for (int i = LO; i < 64; i++) { float t; asm volatile("mov.b32 %0, %1;" : "=f"(t) : "f"(acc[i]) : "memory"); acc[i] = t; }
}
template <int G> __device__ __forceinline__ void cv_raw(uint32_t (&A)[4][4], uint32_t kaddr) {
#pragma unroll
  for (int i = 0; i < 4; i++) {
    const uint32_t a = kaddr + (4 * G + i) * 128;
    A[i][0] = lds32(a); A[i][1] = lds32(a + 4); A[i][3] = lds32(a + 8);
  }
}
__device__ __forceinline__ void cv_form(uint32_t (&A)[4][4], uint32_t sel) {
#pragma unroll
  for (int i = 0; i < 4; i++) {
    asm volatile("prmt.b32 %0, %0, %1, %2;" : "+r"(A[i][0]) : "r"(A[i][1]), "r"(sel));
    asm volatile("prmt.b32 %0, %1, %2, %3;" : "=r"(A[i][2]) : "r"(A[i][1]), "r"(A[i][3]), "r"(sel));
  }
}
#define CVV 2
template <int G> __device__ __forceinline__ void cv_step(float (&acc)[64], uint32_t (&A)[4][4], CvPipe& s, const CvCtx& c, uint32_t cb, uint32_t stg) {
  constexpr int JA = G - 1, JB = G - 2, NH = CVV == 1 ? 4 : (CVV == 3 ? 2 : 1);
  const uint32_t db0 = desc_lo(cb + CV_U + 192, CV_PL);
  uint32_t B[4][4];
  float ra[4], rb[2];
  if constexpr (G < 8) {
    wgmma_fence();
#pragma unroll
    for (int i = 0; i < NH; i++) wgmma_rs_hi<128 - 16 * (G & 7)>(acc, A[i][0], A[i][1], A[i][2], A[i][3], db0 - 4 * i);
    wgmma_commit();
    __syncwarp();
  }
  if constexpr (JA >= 0 && JA < 8) {
#pragma unroll
    for (int x = 0; x < 4; x++) {
      const int i = 8 * JA + 4 * (x >> 1) + 2 * (x & 1) + 1;
      ra[x] = shfl_sel(i >= 4 ? acc[i >= 4 ? i - 4 : 0] : 0.f, acc[i], c.wrapA, c.srcA);
    }
  }
  if constexpr (JB >= 0) {
#pragma unroll
    for (int h = 0; h < 2; h++) rb[h] = __shfl_sync(0xffffffffu, s.send[h], c.srcB);
  }
  if constexpr (G < 7) cv_raw<G + 1>(B, cb + c.koff);
  uint32_t z = 0;
  if constexpr (G < 8 && NH < 4) {
    __syncwarp();
    wgmma_fence();
#pragma unroll
    for (int i = NH; i < 4; i++) wgmma_rs_hi<128 - 16 * (G & 7)>(acc, A[i][0], A[i][1], A[i][2], A[i][3], db0 - 4 * i);
    wgmma_commit();
    asm volatile("mov.u32 %0, %%clock;" : "=r"(z)::"memory");
    z &= c.zero;
  }
  const float one = __uint_as_float(0x3f800000u | z);
  if constexpr (G < 7) cv_form(B, 0x5432u | z);
  if constexpr (JB >= 0) sts32(stg + ((c.so[JB / 3] >> (10 * (JB % 3))) & 0xffc), pack_bf16(fmaf(rb[0], one, s.keep[0]), fmaf(rb[1], one, s.keep[1])));
  if constexpr (JA >= 0 && JA < 8) {
#pragma unroll
    for (int h = 0; h < 2; h++) {
      const float ev = fmaf(ra[h], one, acc[8 * JA + 2 * h]), od = fmaf(ra[2 + h], one, acc[8 * JA + 4 + 2 * h]);
      s.send[h] = c.kodd ? ev : (c.s3 ? s.Ep[h] : od);
      s.keep[h] = c.kodd ? od : ev;
      s.Ep[h] = od;
    }
  }
  if constexpr (G < 8) { __syncwarp(); wgmma_wait<0>(); cv_copy<8 * (G & 7)>(acc); }
  if constexpr (G < 9) cv_step<G + 1>(acc, B, s, c, cb, stg);
}
__device__ __forceinline__ uint32_t cv_stage(int slot) { return sb + (slot < 4 ? 40960 + slot * 4096 : CV_OFF + CV_K); }
__device__ __forceinline__ void cv_setup(CvCtx& c) {
  const int tid = tid_opaque() & 127, w = tid >> 5, lane = tid & 31, r = lane >> 2, q = lane & 3;
  const int i0 = (r >> 1) & 1, i1 = r >> 2;
  c.koff = CV_K - 32 + 4 * (8 * (r >> 1) + 2 * w + (r & 1) + 2 * q);
  c.srcA = i0 ? lane - 8 : lane + 8 - q + ((q + 3) & 3);
  c.wrapA = i0 && q == 3;
  c.srcB = i1 == 0 ? (lane - q + 16 + ((q + 3) & 3)) : (lane - q - 16 + ((q + 1) & 3));
  c.s3 = (i1 == 1 && q == 3); c.kodd = (i1 == 1 && q < 3);
  c.zero = lds32(sb + EP_OFF + 24);
#pragma unroll
  for (int i = 0; i < 3; i++) c.so[i] = lds32(sb + SO_OFF + 512 * i + 4 * tid);
}
__device__ __forceinline__ void cv_table() {
  const int tid = tid_opaque() & 127, r = (tid & 31) >> 2, q = tid & 3;
  int t = 16 * (2 * (r < 4 ? q : 4 + ((q + 1) & 3)) + ((r >> 1) & 1)) + 4 * (tid >> 5) + 2 * (r & 1);
#pragma unroll 1
  for (int i = 0; i < 3; i++) {
    uint32_t v = 0;
#pragma unroll 1
    for (int x = 0; x < 3; x++, t += 256) {
      const int T = t / 160, tl = t - T * 160;
      const int qq = (T >= NT1 - 1) ? (tl >> 5) : (tl / 40);
      int ck = 20 * T + ((tl - qq * ((T >= NT1 - 1) ? 32 : 40)) >> 1);
      ck ^= (ck >> 2) & 6;
      v |= (uint32_t)((ck * 4 + qq) & 1023) << (10 * x + 2);
    }
    sts32(sb + SO_OFF + 512 * i + 4 * tid, v);
  }
}
__device__ __forceinline__ void conv_channel(int slot, const CvCtx& c) {
  const uint32_t cb = sb + CV_OFF + slot * CV_B;
  float acc[64];
  CvPipe s;
  s.Ep[0] = s.Ep[1] = 0.f;
  uint32_t A[4][4];
#pragma unroll
  for (int i = 0; i < 64; i++) acc[i] = 0.f;
  if (slot == 4) mbar_wait(bars + 8 * B_CVDONE);
  mbar_wait(bars + 8 * (B_CVFULL + slot));
  cv_raw<0>(A, cb + c.koff);
  {
    const uint32_t w0 = lds32(cb + CV_K);
    const uint32_t wp = __byte_perm(pack_bf16(bf_lo(w0) + __uint_as_float(lds32(sb + EP_OFF + 4 * slot)), 0.f), w0, 0x7610);
    if (c.koff == CV_K) A[0][0] = wp;
    if (c.koff == CV_K - 4) A[0][1] = wp;
    if (c.koff == CV_K - 8) A[0][3] = wp;
  }
  cv_form(A, 0x5432u);
  cv_copy<0>(acc);
  cv_step<0>(acc, A, s, c, cb, cv_stage(slot));
  fence_async_smem();
  mbar_arrive(bars + 8 * (B_CVDONE + slot));
}

__device__ __forceinline__ void kv_issue(const Params& p, int c, int m2, int dg) {
  const uint32_t fb = bars + 8 * (B_KV + c);
  mbar_expect_tx(fb, KV_PIECE);
  tma3(sb + KS_OFF + c * KV_PIECE, &p.mK, 160 * dg + 32 * c, 64 * m2 - 3, 0, fb);
  tma3(sb + KS_OFF + c * KV_PIECE + 4864, &p.mV, 160 * dg + 32 * c, 64 * m2 - 1, 0, fb);
}
__device__ __forceinline__ void kv_tile(int m, int dg, int c, int y) {
  const int lane = tid_opaque() & 31, tg = lane >> 3;
  const uint32_t pb = sb + KS_OFF + c * KV_PIECE + 32 * y + 4 * (lane & 7);
  const uint32_t ka = pb + tg * 1216, va = pb + 4864 + tg * 1088 + 64;
  const uint32_t kh = (m == 0 && tg > 0) ? ka - 192 : ka;
  uint32_t kk[19], u[16];
  const float4 t = lds128f(sb + TAP_OFF + 256 * c + 128 * y + 16 * (lane & 7));
#pragma unroll
  for (int i = 0; i < 19; i++) { kk[i] = lds32((i < 3 ? kh : ka) + i * 64); if (i >= 3) u[i - 3] = lds32(va + (i - 3) * 64); }
  uint8_t* dst = g_kv + ((160 * dg + 32 * c + 16 * y + 2 * (lane & 7)) * 4096 + (4 * m + tg) * 16);
  const uint32_t w0 = __byte_perm(__float_as_uint(t.x), __float_as_uint(t.z), 0x5410), w1 = __byte_perm(__float_as_uint(t.x), __float_as_uint(t.z), 0x7632);
  const uint32_t w2 = __byte_perm(__float_as_uint(t.y), __float_as_uint(t.w), 0x5410), w3 = __byte_perm(__float_as_uint(t.y), __float_as_uint(t.w), 0x7632);
#pragma unroll
  for (int i = 0; i < 16; i++) {
    uint32_t a = hmul2(kk[i], w3);
    a = hadd2(a, hmul2(kk[i + 1], w2)); a = hadd2(a, hmul2(kk[i + 2], w1)); a = hadd2(a, hmul2(kk[i + 3], w0));
    u[i] = hmul2(a, u[i]);
  }
#pragma unroll
  for (int e = 0; e < 2; e++)
#pragma unroll
    for (int f = 0; f < 2; f++) {
      uint32_t o[4];
#pragma unroll
      for (int qq = 0; qq < 4; qq++) o[qq] = __byte_perm(u[15 - 4 * qq - 2 * f], u[14 - 4 * qq - 2 * f], e ? 0x7632 : 0x5410);
      *(uint4*)(dst + e * 4096 + f * 2048) = make_uint4(o[0], o[1], o[2], o[3]);
    }
}
__device__ __forceinline__ void ln_finish(float s1, float s2, float& mean, float& rstd) {
  mean = s1 * (1.f / 640.f);
  const float v = fmaxf(fmaf(-mean, mean, s2 * (1.f / 640.f)), 0.f) + 1e-5f;
  asm("rsqrt.approx.ftz.f32 %0, %1;" : "=f"(rstd) : "f"(v));
}
__device__ __forceinline__ void stat_table(int T1, unsigned want, int l, int g, const uint4* x0, const uint4* x1, float (&xa)[2], float (&xb)[2]) {
  const int n = 32 * g + (tid_opaque() & 31);
  const uint4* rp = &g_stats[8 * l * SEQ + min(160 * T1 + n, SEQ - 1)];
  float a[4], b[4];
  uint32_t it = 0;
  while (true) {
    bool ok = true;
#pragma unroll
    for (int i = 0; i < 4; i++) ok &= (rec_ld(rp + SEQ * i, a[i], b[i]) == want);
    ok &= rec_ld(x0, xa[0], xb[0]) == want;
    ok &= rec_ld(x1, xa[1], xb[1]) == want;
    if (__all_sync(0xffffffffu, ok)) break;
    trap_if(++it > SPIN_LIMIT);
  }
  float m, rs;
  ln_finish((a[0] + a[1]) + (a[2] + a[3]), (b[0] + b[1]) + (b[2] + b[3]), m, rs);
  sts64f(sb + STAB_OFF + n * 8, rs, -m * rs);
}
__device__ __forceinline__ void stats_reduce(float (&a)[2], float (&b)[2], float (&mean)[2], float (&rstd)[2]) {
#pragma unroll
  for (int o = 1; o < 4; o <<= 1)
#pragma unroll
    for (int h = 0; h < 2; h++) { a[h] += __shfl_xor_sync(0xffffffffu, a[h], o); b[h] += __shfl_xor_sync(0xffffffffu, b[h], o); }
#pragma unroll
  for (int h = 0; h < 2; h++) ln_finish(a[h], b[h], mean[h], rstd[h]);
}

template <bool FIRST>
__device__ __forceinline__ void stats_publish(int which, int n0, int dg, unsigned tag, const float (&acc)[80]) {
  const int q = tid_opaque() & 3, h = q & 1;
  float s1[2] = {0.f, 0.f}, s2[2] = {0.f, 0.f}, t1[2] = {0.f, 0.f}, t2[2] = {0.f, 0.f};
#pragma unroll
  for (int j = 0; j < 20; j++)
#pragma unroll
    for (int y = 0; y < 2; y++) {
      const float a = acc[4 * j + 2 * y], b = acc[4 * j + 2 * y + 1];
      s1[y] += a; t1[y] += b; s2[y] = fmaf(a, a, s2[y]); t2[y] = fmaf(b, b, t2[y]);
    }
#pragma unroll
  for (int y = 0; y < 2; y++) { s1[y] += t1[y]; s2[y] += t2[y]; }
  float a = (h ? s1[1] : s1[0]) + __shfl_xor_sync(0xffffffffu, h ? s1[0] : s1[1], 1);
  float b = (h ? s2[1] : s2[0]) + __shfl_xor_sync(0xffffffffu, h ? s2[0] : s2[1], 1);
  a += __shfl_xor_sync(0xffffffffu, a, 2);
  b += __shfl_xor_sync(0xffffffffu, b, 2);
  if (FIRST) {
    rec_st(&g_stats[((q >> 1) * 4 + dg) * SEQ + n0 + 8 * h], a, b, q < 2 ? tag : tag - 1);
    rec_st(&g_stats[((q >> 1) * 4 + 8 + dg) * SEQ + n0 + 8 * h], a, b, tag - 1);
  } else if (q < 2) rec_st(&g_stats[(which * 4 + dg) * SEQ + n0 + 8 * h], a, b, tag);
}
__device__ __forceinline__ void stats_get(int which, int n0, unsigned tag, float (&mean)[2], float (&rstd)[2]) {
  const uint4* p0 = &g_stats[(which * 4 + (tid_opaque() & 3)) * SEQ + n0];
  float a[2], b[2];
  uint32_t it = 0;
  while (true) {
    const unsigned t0 = rec_ld(p0, a[0], b[0]), t1 = rec_ld(p0 + 8, a[1], b[1]);
    if (__all_sync(0xffffffffu, t0 == tag && t1 == tag)) break;
    trap_if(++it > SPIN_LIMIT);
  }
  stats_reduce(a, b, mean, rstd);
}
__device__ __forceinline__ void x0_load(float (&acc)[80]) {
  const int t = tid_opaque() & 127;
  const uint32_t xa = sb + XT_OFF + (16 * (t >> 5) + ((t & 31) >> 2)) * 320 + 8 * (t & 3);
  mbar_wait(bars + 8 * B_XT);
#pragma unroll
  for (int h = 0; h < 2; h++)
#pragma unroll
    for (int J = 0; J < 10; J++) {
      const float2 v = lds64f(xa + h * 2560 + 32 * J);
      const uint32_t x = __float_as_uint(v.x), y = __float_as_uint(v.y);
      acc[8 * J + 2 * h] = bf_lo(x); acc[8 * J + 2 * h + 1] = bf_hi(x);
      acc[8 * J + 4 + 2 * h] = bf_lo(y); acc[8 * J + 4 + 2 * h + 1] = bf_hi(y);
    }
}

template <bool FROM_X0>
__device__ __forceinline__ void dskip_init(float (&acc)[80], const float (&mean)[2], const float (&rstd)[2]) {
  const int t = tid_opaque() & 127;
  const uint32_t xa = sb + XT_OFF + (16 * (t >> 5) + ((t & 31) >> 2)) * 320 + 8 * (t & 3), da = sb + DTAB_OFF + 8 * (t & 3);
  float2 dw[10], xv[10][2];
#pragma unroll
  for (int J = 0; J < 2; J++) { dw[J] = lds64f(da + 32 * J); if (FROM_X0) { xv[J][0] = lds64f(xa + 32 * J); xv[J][1] = lds64f(xa + 2560 + 32 * J); } }
#pragma unroll
  for (int J = 0; J < 10; J++) {
    if (J + 2 < 10) { dw[J + 2] = lds64f(da + 32 * (J + 2)); if (FROM_X0) { xv[J + 2][0] = lds64f(xa + 32 * (J + 2)); xv[J + 2][1] = lds64f(xa + 2560 + 32 * (J + 2)); } }
#pragma unroll
    for (int x = 0; x < 8; x++) {
      const int h = (x >> 1) & 1;
      const uint32_t dwd = __float_as_uint(x < 4 ? dw[J].x : dw[J].y);
      const float tt = fmaf(rstd[h], (x & 1) ? bf_hi(dwd) : bf_lo(dwd), 1.f);
      float a = acc[8 * J + x];
      if (FROM_X0) { const uint32_t xw = __float_as_uint(x < 4 ? xv[J][h].x : xv[J][h].y); a = (x & 1) ? bf_hi(xw) : bf_lo(xw); }
      acc[8 * J + x] = FROM_X0 ? (a - mean[h]) * tt : fmaf(a, tt, -mean[h] * tt);
    }
  }
}

__global__ void __launch_bounds__(512, 1) fused_kernel(const __grid_constant__ Params p) {
  extern __shared__ __align__(1024) uint8_t smem_raw[];
  const int tid = threadIdx.x, lane = tid & 31;
  const int wid = __shfl_sync(0xffffffffu, tid >> 5, 0), wg = wid >> 2;
  unsigned smid; asm volatile("mov.u32 %0, %%smid;" : "=r"(smid));
  const int role = p.role[min(smid, 131u)];
  if (wid == 12) {
    const bool el = elect_one();
    if (el) {
      asm volatile("prefetch.tensormap [%0];" ::"l"(&p.mX) : "memory");
      asm volatile("prefetch.tensormap [%0];" ::"l"(&p.mB) : "memory");
#pragma unroll
      for (int k = 0; k < S1; k++) mbar_init(bars + 8 * (B_G1FULL + k), 1);
#pragma unroll
      for (int k = 0; k < 6; k++) mbar_init(bars + 8 * (B_XT + k), 1);
      asm volatile("fence.mbarrier_init.release.cluster;" ::: "memory");
    }
    if (role >= 0) {
      __syncwarp();
      asm volatile("bar.arrive 5, 288;" ::: "memory");
      const Role R = unpack_role(role);
      if (elect_one()) {
        TS(45);
#pragma unroll 1
        for (int k = 0; k < S1; k++) {
          const uint32_t fb = bars + 8 * (B_G1FULL + k);
          mbar_expect_tx(fb, G1_STAGE);
          tma4(sb + k * G1_STAGE + G1_XOFF, R.last ? &p.mXl : &p.mX, 64 * k, 0, 0, R.last ? 0 : 80 * R.T1, fb);
          tma5(sb + k * G1_STAGE, &p.mB, 64 * k, 0, 0, 4 * R.side, 2 * R.GP, fb);
        }
        if (R.has2) {
#pragma unroll 1
          for (int c = 0; c < KV0; c++) kv_issue(p, c, R.m2, R.dg);
          mbar_expect_tx(bars + 8 * B_XT, 20480);
#pragma unroll 1
          for (int h = 0; h < 2; h++) {
            const int ng = 8 * R.m2 + 4 * h, T = ng / 20;
            tma4(sb + XT_OFF + h * 10240, T == NT1 - 1 ? &p.mXtl : &p.mXt, 160 * R.dg, 0, 0, T == NT1 - 1 ? ng - 240 : ng + 60 * T, bars + 8 * B_XT);
          }
        }
        TS(44);
      }
      __syncwarp();
      bar_sync(6, 64);
    }
  }
  trap_if(smid >= 132 || smem_u32(smem_raw) != sb);
  if (role < 0) {
    if (wid == 0) {
      const unsigned tag = ld_rlx(g_epoch);
      uint32_t it = 0;
      while (!__all_sync(0xffffffffu, (int)(ld_rlx(&g_hcnt[(lane & 7) * 32]) - 40 * tag) >= 0)) { __nanosleep(500); trap_if(++it > SPIN_LIMIT); }
    }
    return;
  }
  float mean0[2] = {0.f, 0.f}, rstd0[2] = {0.f, 0.f};
  if (wg == 2 || wid == 14) {
    ROLE(role)
    const int c = wid == 14 ? 4 : wid - 8;
    const unsigned tag = ld_rlx(g_epoch);
    if (has2) {
      uint2 bv[2][5];
#pragma unroll
      for (int x = 0; x < 2; x++)
#pragma unroll
        for (int i = 0; i < 5; i++) bv[x][i] = ldv64((const uint2*)((x ? p.bim : p.bre) + (cch0 + 32 * c) * DM) + lane + 32 * i);
      float sv[2];
#pragma unroll
      for (int x = 0; x < 2; x++) {
        float a = 0.f;
#pragma unroll
        for (int i = 0; i < 5; i++) a += (bf_lo(bv[x][i].x) + bf_hi(bv[x][i].x)) + (bf_lo(bv[x][i].y) + bf_hi(bv[x][i].y));
        sv[x] = a;
      }
#pragma unroll
      for (int o = 16; o > 0; o >>= 1) { sv[0] += __shfl_xor_sync(0xffffffffu, sv[0], o); sv[1] += __shfl_xor_sync(0xffffffffu, sv[1], o); }
      if (lane < 2) rec_st(&g_sB[(cch0 + 32 * c) * 2 + lane], sv[0], sv[1], tag);
      if (tid == 256) TS(47);
      __syncwarp();
      bar_sync(8, 192);
      mbar_wait(bars + 8 * B_EP);
      mbar_wait(bars + 8 * (B_KV + c));
#pragma unroll 1
      for (int y = 0; y < 2; y++) kv_tile(m2, dg, c, y);
      __syncwarp();
      if (lane == 0) mbar_arrive(bars + 8 * B_PREP);
      if (tid == 352) TS(52);
      if (tid == 448) TS(51);
      if (wg == 2) {
        float xs[80];
        x0_load(xs);
        stats_publish<true>(0, 64 * m2 + 16 * c + (lane >> 2), dg, tag, xs);
        if (tid == 256) TS(31);
        mbar_wait(bars + 8 * (TABW ? B_PUB : B_PREP));
      } else {
        mbar_wait(bars + 8 * B_PREP);
        if (lane == 0) { st_rel(&g_kvflag[(dg * 32 + m2) * 8], tag); mbar_arrive(bars + 8 * B_PUB); TS(30); }
        __syncwarp();
      }
    } else bar_sync(8, 192);
    {
      const uint4* x0 = wg == 2 ? &g_stats[(lane & 3) * SEQ + (has2 ? 64 * m2 : 0) + 16 * c + (lane >> 2)] : &g_sB[(128 * GP + 32 * side + lane) * 2];
      float xa[2], xb[2];
      stat_table(T1, tag, 0, c, x0, x0 + (wg == 2 ? 8 : 128), xa, xb);
      if (wg == 2) stats_reduce(xa, xb, mean0, rstd0);
      else {
#pragma unroll
        for (int i = 0; i < 2; i++) sts64f(sb + CTAB_OFF + (32 * i + lane) * 24 + 16, p.swap ? xb[i] : xa[i], p.swap ? xa[i] : xb[i]);
      }
      mbar_arrive(bars + 8 * B_STAB);
      if (tid == 448) TS(26);
    }
  } else if (wid == 15) {
    ROLE(role)
    const int ch = 128 * GP + 32 * side + lane;
    uint32_t r0 = ldv16(p.lre + ch), r1 = ldv16(p.lim + ch), r2 = ldv16(p.logdt + ch);
    const uint32_t r3 = ldv16(p.lre + ch + 64), r4 = ldv16(p.lim + ch + 64), r5 = ldv16(p.logdt + ch + 64);
#pragma unroll 1
    for (int i = 0; i < 2; i++) {
      const float lr = bf_lo(r0), li = bf_lo(r1);
      const float dt = __bfloat162float(__float2bfloat16_rn(expf(bf_lo(r2))));
      const float mag = expf(dt * lr);
      float sn, cs; sincospif(dt * li * 0.31830988618379067f, &sn, &cs);
      const float ar = mag * cs, ai = mag * sn;
      const float inv = 2.f / (lr * lr + li * li);
      const uint32_t ad = sb + CTAB_OFF + (32 * i + lane) * 24;
      sts64f(ad, ar, ai);
      sts64f(ad + 8, ((ar - 1.f) * lr + ai * li) * inv, (ai * lr - (ar - 1.f) * li) * inv);
      r0 = r3; r1 = r4; r2 = r5;
    }
    if (lane == 0) TS(46);
    __syncwarp();
    bar_sync(7, 64);
    mbar_arrive(bars + 8 * B_CTAB);
  } else if (wid == 13) {
    ROLE(role)
    uint4 tv[3];
    const uint32_t e0 = ld_rlx(g_epoch);
    const uint32_t e1 = ldv16(p.ssmD + min(cch0 + 32 * lane, 639));
    const uint4 dv = ldv128((const uint4*)(p.dskip + 160 * dg) + min(lane, 19));
#pragma unroll
    for (int i = 0; i < 3; i++) tv[i] = ldv128((const uint4*)(p.shiftk + 640 * dg) + min(lane + 32 * i, 79));
    sts128(sb + DTAB_OFF + 16 * min(lane, 19), dv);
#pragma unroll
    for (int i = 0; i < 3; i++) sts128(sb + TAP_OFF + 16 * min(lane + 32 * i, 79), tv[i]);
    if (lane < 7) sts32(sb + EP_OFF + 4 * lane, lane < 5 ? e1 << 16 : (lane == 5 ? e0 : 0u));
    __syncwarp();
    bar_sync(9, 64);
    mbar_arrive(bars + 8 * B_CTAB);
    if (lane == 0) { mbar_arrive(bars + 8 * B_EP); TS(53); }
  } else if (wid != 12) {
    if (elect_one()) {
      if (wid < 7) {
        const int b0 = wid < 4 ? 4 + 20 * wid : 85 + 21 * (wid - 4), cnt = wid < 4 ? 2 : 1;
#pragma unroll
        for (int i = 0; i < 21; i++) mbar_init(bars + 8 * (b0 + i), cnt);
      } else {
#pragma unroll
        for (int i = 0; i < 12; i++) mbar_init(bars + 8 * (B_CVDONE + i), (i == 5 || i == 6) ? 160 : 128);
        mbar_init(bars + 8 * B_CTAB, 192); mbar_init(bars + 8 * B_PREP, 5);
      }
      asm volatile("fence.mbarrier_init.release.cluster;" ::: "memory");
    }
    __syncwarp();
    bar_sync(5, 288);
    if (wid == 2) asm volatile("bar.arrive 8, 192;\nbar.arrive 6, 64;\nbar.arrive 9, 64;\nbar.arrive 7, 64;" ::: "memory");
    if (tid == 128) TS(0);
    if (wg == 1) { cv_table(); mbar_arrive(bars + 8 * B_CTAB); }
  }

  if (wid == 12) {
    ROLE(role)
    uint32_t dst = sb;
#pragma unroll 1
    for (int k = S1; k < 10; k++) {
      const uint32_t fb = bars + 8 * (B_G1FULL + k);
      mbar_wait(bars + 8 * (B_G1DONE + k - S1));
      if (elect_one()) {
        mbar_expect_tx(fb, 20480);
        tma4(dst + G1_XOFF, last ? &p.mXl : &p.mX, 64 * k, 0, 0, last ? 0 : 80 * T1, fb);
        mbar_expect_tx(fb, 16384);
        tma5(dst, &p.mB, 64 * k, 0, 0, 4 * side, 2 * GP, fb);
        if (has2 && k - S1 + KV0 < 5) kv_issue(p, k - S1 + KV0, m2, dg);
      }
      dst += G1_STAGE; if (k == 2 * S1 - 1) dst = sb;
    }
  } else if (wid == 15 && (role >> 16)) {
    ROLE(role)
    mbar_wait(bars + 8 * B_PREP);
#pragma unroll
    for (int c = 0; c < 5; c++) {
      const uint32_t cb = sb + CV_OFF + c * CV_B;
      sts128(lane < 8 ? cb + 16 * lane : (lane < 20 ? cb + CV_U + 16 * (lane - 8) : cb + CV_U + CV_PL + 16 * (lane - 20)), make_uint4(0, 0, 0, 0));
    }
    fence_async_smem();
    __syncwarp();
    const unsigned tag = lds32(sb + EP_OFF + 20);
    mbar_wait(bars + 8 * B_PUB);
    if (elect_one()) {
#pragma unroll
      for (int c = 0; c < TAP0; c++) {
        mbar_expect_tx(bars + 8 * (B_CVFULL + c), 4096);
        bulk_g2s(sb + CV_OFF + c * CV_B + CV_K, p.ssmk + (cch0 + 32 * c) * SEQ, 4096, bars + 8 * (B_CVFULL + c));
      }
    }
    flag_poll(&g_kvflag[(dg * 32 + lane) * 8], tag);
    fence_async_global();
    if (elect_one()) {
      TS(28);
#pragma unroll 1
      for (int c = 0; c < 5; c++) {
        const uint32_t fb = bars + 8 * (B_CVFULL + c), cb = sb + CV_OFF + c * CV_B;
        mbar_expect_tx(fb, 4096);
        bulk_g2s(cb + CV_U + 192, g_kv + (cch0 + 32 * c) * 4096, 2048, fb);
        bulk_g2s(cb + CV_U + 192 + CV_PL, g_kv + (cch0 + 32 * c) * 4096 + 2048, 2048, fb);
        if (c >= TAP0) {
          mbar_expect_tx(fb, 4096);
          bulk_g2s(cb + CV_K, p.ssmk + (cch0 + 32 * c) * SEQ, 4096, fb);
        }
      }
      TS(54);
    }
    __syncwarp();
  }
  {
    const int w = wid & 3;
    if (wg == 2 && !(role >> 16)) {
      float xa[2], xb[2];
      mbar_wait(bars + 8 * (B_G1FULL + 11));
      stat_table(role & 15, lds32(sb + EP_OFF + 20), 1, w, g_stats, g_stats, xa, xb);
      mbar_arrive(bars + 8 * (B_STAB + 1));
    }
#pragma unroll 1
    for (int l = 0; l < 2; l++) {
      if (wg < 2) {
        float acc[80];
#pragma unroll
        for (int i = 0; i < 80; i++) acc[i] = 0.f;
        ROLE(role)
        const int tid = tid_opaque(), r = (tid & 31) >> 2, q = tid & 3;
        const int ch = 128 * GP + 64 * wg + 32 * side + 8 * w + r;
        const uint32_t ca = sb + CTAB_OFF + (32 * wg + 8 * w + r) * 24;
        float2 lam = make_float2(0.f, 0.f), p8 = lam, p16 = lam, pL = lam, p2L = lam;
        fence_regs(acc);
        {
          uint32_t alo = desc_lo(sb, 16) + wg * 512, blo = l == 0 ? desc_lo(sb + G1_XOFF, 16) : desc_lo(sb + G1_XOFF, 128);
          const uint32_t bhi = l == 0 ? desc_hi(1024, 1) : desc_hi(1024, 0), xstep = l == 0 ? 2 : 16;
          const uint32_t aend = desc_lo(sb, 16) + (S1 + l) * (G1_STAGE >> 4);
          uint32_t fb = bars + 8 * (B_G1FULL + 10 * l);
          mbar_wait(fb);
          if (tid == 0) TS(1 + 8 * l);
#pragma unroll 1
          for (int k = 0; k < 10; k++) {
            uint32_t ok; const uint32_t nb = k < 9 ? fb + 8 : fb;
            wgmma_fence();
#pragma unroll
            for (int kk = 0; kk < 4; kk++) {
              wgmma_n160<0>(acc, alo + kk * 2, desc_hi(1024, 1), blo + kk * xstep, bhi);
              if (kk == 0) ok = mbar_test(nb);
              if (kk == STG_KK && k == 9 && tid == 0) mbar_arrive(bars + 8 * (B_STG + l));
            }
            wgmma_commit();
            alo += G1_STAGE >> 4; blo += G1_STAGE >> 4;
            if (alo >= aend) { alo -= (S1 + l) * (G1_STAGE >> 4); blo -= (S1 + l) * (G1_STAGE >> 4); }
            wgmma_wait<1>();
            if (k > 0 && (tid & 127) == 0) mbar_arrive(fb + 8 * (B_G1DONE - B_G1FULL - 1));
            if (!ok) mbar_wait(nb);
            if (wg == 1 && k == (l ? 8 - STG_D : 9 - STG0)) mbar_wait(bars + 8 * (B_STG + l));
            if (k == 3) {
              mbar_wait(bars + 8 * B_CTAB);
              lam = lds64f(ca);
              if (p.swap) lam.y = -lam.y;
              const float2 p2 = cmul(lam, lam), p4 = cmul(p2, p2);
              p8 = cmul(p4, p4); p16 = cmul(p8, p8);
              pL = cmul(p16, p16);
              if (!last) pL = cmul(pL, p8);
              p2L = cmul(pL, pL);
            }
            if (k == PAUSE_K && has2) mbar_wait(bars + 8 * B_PREP);
            fb += 8;
          }
        }
        mbar_wait(bars + 8 * (B_STAB + l));
        const float2 sB = lds64f(ca + 16);
        const unsigned tag = lds32(sb + EP_OFF + 20);
        wgmma_wait<0>();
        fence_regs(acc);
        if ((tid & 127) == 0) { mbar_arrive(bars + 8 * (B_G1DONE + 10 * l + 9)); TS(wg ? 17 + l : 2 + 8 * l); }
        float2 ec[3];
#pragma unroll
        for (int jj = 0; jj < 8; jj++)
#pragma unroll
          for (int y = 0; y < 3; y++) {
            if (y == 2 && (jj & 1)) continue;
            const int j = y == 2 ? 16 + (jj >> 1) : 8 * y + jj;
            const float4 st = lds128f(sb + STAB_OFF + (8 * j + 2 * q) * 8);
            acc[4 * j + 0] = fmaf(acc[4 * j + 0], st.x, st.y * sB.x);
            acc[4 * j + 2] = fmaf(acc[4 * j + 2], st.x, st.y * sB.y);
            acc[4 * j + 1] = fmaf(acc[4 * j + 1], st.z, st.w * sB.x);
            acc[4 * j + 3] = fmaf(acc[4 * j + 3], st.z, st.w * sB.y);
            ec[y] = jj == 0 ? make_float2(acc[4 * j + 0], acc[4 * j + 2]) : cfma(lam, ec[y], make_float2(acc[4 * j + 0], acc[4 * j + 2]));
            ec[y] = cfma(lam, ec[y], make_float2(acc[4 * j + 1], acc[4 * j + 3]));
          }
        float2 e = cfma(p16, ec[0], ec[1]);
        if (!last) e = cfma(p8, e, ec[2]);
        {
          float2 v = make_float2(__shfl_up_sync(0xffffffffu, e.x, 1, 4), __shfl_up_sync(0xffffffffu, e.y, 1, 4));
          if (q >= 1) e = cfma(pL, v, e);
          v = make_float2(__shfl_up_sync(0xffffffffu, e.x, 2, 4), __shfl_up_sync(0xffffffffu, e.y, 2, 4));
          if (q >= 2) e = cfma(p2L, v, e);
        }
        if (!last && (q == 3 || (q == 2 && l == 0))) rec_st(&g_E[((q == 3 ? l : 1) * NT1 + T1) * DM + ch], e.x, e.y, q == 3 ? tag : tag - 1);
        if (tid == 0) TS(3 + 8 * l);
        float2 ex = make_float2(__shfl_up_sync(0xffffffffu, e.x, 1, 4), __shfl_up_sync(0xffffffffu, e.y, 1, 4));
        if (q == 0) ex = make_float2(0.f, 0.f);
        const float2 coef = lds64f(ca + 8), lamc = make_float2(lam.x, p.swap ? lam.y : -lam.y);
        float m00 = coef.x, m01 = -coef.y, m10 = -coef.y, m11 = -coef.x;
        if (p.swap) { m00 = -coef.y; m01 = coef.x; m10 = -coef.x; m11 = -coef.y; }
        float2 pLq, p160q, p640;
        {
          const float2 p80 = last ? cmul(p2L, p16) : p2L, p160 = cmul(p80, p80), p320 = cmul(p160, p160), one = make_float2(1.f, 0.f);
          p640 = cmul(p320, p320);
          pLq = cmul((q & 1) ? pL : one, (q & 2) ? p2L : one);
          p160q = cmul((q & 1) ? p160 : one, (q & 2) ? p320 : one);
        }
        float2 c, ev[3];
        unsigned tg[3];
        const uint4* ep = &g_E[(l * NT1 + T1 - 1 - q) * DM + ch];
#pragma unroll
        for (int j = 0; j < 20; j++) {
          if (j == CPOLL) {
#pragma unroll
            for (int i = 0; i < 3; i++) {
              ev[i] = make_float2(0.f, 0.f); tg[i] = tag;
              if (T1 - 1 - q - 4 * i >= 0) tg[i] = rec_ld(ep - 4 * i * DM, ev[i].x, ev[i].y);
            }
          }
#pragma unroll
          for (int x = 0; x < 2; x++) {
            const float b0 = acc[4 * j + x], b1 = acc[4 * j + 2 + x];
            acc[4 * j + x] = fmaf(b0, m00, b1 * m01);
            acc[4 * j + 2 + x] = fmaf(b0, m10, b1 * m11);
          }
          if (j == CPOLL - 1 || j == 19) asm volatile("" : "+f"(acc[4 * j]), "+f"(acc[4 * j + 1]), "+f"(acc[4 * j + 2]), "+f"(acc[4 * j + 3])::"memory");
        }
        {
          uint32_t it = 0;
          while (__any_sync(0xffffffffu, tg[0] != tag || tg[1] != tag || tg[2] != tag)) {
#pragma unroll
            for (int i = 0; i < 3; i++)
              if (tg[i] != tag) tg[i] = rec_ld(ep - 4 * i * DM, ev[i].x, ev[i].y);
            trap_if(++it > SPIN_LIMIT);
          }
          c = cfma(p640, cfma(p640, ev[2], ev[1]), ev[0]);
          c = cmul(c, p160q);
          c.x += __shfl_xor_sync(0xffffffffu, c.x, 1); c.y += __shfl_xor_sync(0xffffffffu, c.y, 1);
          c.x += __shfl_xor_sync(0xffffffffu, c.x, 2); c.y += __shfl_xor_sync(0xffffffffu, c.y, 2);
        }
        if (tid == 0) TS(4 + 8 * l);
        if (wg == 1 && l >= HOLD0) mbar_wait(bars + 8 * (B_REL + l));
        c = cfma(pLq, c, ex);
        float2 hh = make_float2(fmaf(c.x, m00, c.y * m01), fmaf(c.x, m10, c.y * m11));
        uint8_t* hb = g_h + (size_t)l * (32 * 20 * 8192) + (10 * wg + 2 * GP) * 8192 + (4 * side + w) * 1024 + (tid_opaque() & 31) * 4;
#pragma unroll
        for (int j4 = 0; j4 < 5; j4++) {
          const int ng = 20 * T1 + 4 * j4;
          uint8_t* hp = hb + (size_t)(ng >> 3) * 163840 + (ng & 7) * 128;
#pragma unroll
          for (int jj = 0; jj < 4; jj++) {
            const int j = 4 * j4 + jj;
            const float2 h0 = cfma(lamc, hh, make_float2(acc[4 * j + 0], acc[4 * j + 2]));
            hh = cfma(lamc, h0, make_float2(acc[4 * j + 1], acc[4 * j + 3]));
            if (j4 < 4 || !last) {
              *(uint32_t*)(hp + jj * 128) = pack_bf16(h0.x, hh.x);
              *(uint32_t*)(hp + jj * 128 + 8192) = pack_bf16(h0.y, hh.y);
            }
          }
        }
        mbar_arrive(bars + 8 * (B_HST + 2 * l + wg));
        if (tid == 0) TS(5 + 8 * l);
        if (tid == 128) TS(l ? 25 : 19);
        if (l == 0 && wid == 4) {
          mbar_wait(bars + 8 * B_HST);
          mbar_wait(bars + 8 * (B_HST + 1));
          if ((tid & 31) < 8) h_release((tid >> 2) & 1, T1, tid & 3);
          __syncwarp();
          if (tid == 128) { mbar_arrive(bars + 8 * B_REL); TS(6); }
        }
      }
      if (l == 0) {
        ROLE(role)
        if (has2) {
          CvCtx cc;
          mbar_wait(bars + 8 * B_CTAB);
          cv_setup(cc);
          mbar_wait(bars + 8 * (B_G1DONE + 9));
#pragma unroll 1
          for (int c = (wg + 2) & 3; c < 5; c += 4) conv_channel(c, cc);
          if ((tid & 127) == 0) TS(wg == 2 ? 32 : (wg == 3 ? 50 : 7 + wg));
        }
      }
      if (wg >= 2) break;
    }
    if (wg == 3) {
    ROLE(role)
    const int pw = wid & 3, gpc = 2 * min(m2 >> 3, 3) + (dg >> 1);
    mbar_wait(bars + 8 * B_EP);
    const unsigned tag = lds32(sb + EP_OFF + 20);
    if (pw == 0) {
      if (elect_one()) {
#pragma unroll 1
        for (int l = 0; l < 2; l++) {
          uint32_t dst = sb;
          if (l == 1) {
            const uint32_t free0 = bars + 8 * (has2 ? B_G2DONE + 19 : B_G1DONE + 9);
#pragma unroll 1
            for (int k = 0; k < 10; k++) {
              mbar_wait(k > S1 ? bars + 8 * (B_G1DONE + 9 - S1 + k) : (k < WPF1 || !has2 ? free0 : bars + 8 * B_GO));
              mbar_expect_tx(bars + 8 * (B_G1FULL + 10 + k), 16384);
              tma5(dst, &p.mB, 64 * k, 0, 0, 4 * side, 2 * GP, bars + 8 * (B_G1FULL + 10 + k));
              dst += G1_STAGE; if (k == S1) dst = sb;
            }
          }
          if (has2) {
            const uint32_t fb2 = bars + 8 * (B_G2FULL + 20 * l), wb2 = bars + 8 * (B_G2DONE + 20 * l - S2);
            dst = sb + G2_WOFF;
            int kc = 0;
#pragma unroll 1
            for (int k = 0; k < 20; k++) {
              mbar_wait(k >= S2 ? wb2 + 8 * k : (k == 5 ? bars + 8 * B_XFREE : (k == 6 ? bars + 8 * B_SFREE : bars + 8 * (l ? B_G1DONE + 19 : B_REL))));
              mbar_expect_tx(fb2 + 8 * k, G2_WB);
              tma5(dst, &p.mCre + (k & 1), kc, 0, 0, 0, 10 * dg, fb2 + 8 * k);
              kc += (k & 1) << 7; if (k == 9) kc = 64;
              dst += G2_WB; if (dst == sb + G2_WOFF + S2 * G2_WB) dst = sb + G2_WOFF;
            }
          }
        }
      }
    } else if (pw == 1) {
#pragma unroll 1
      for (int l = 0; l < 2; l++) {
        if (l == 1) {
          mbar_wait(bars + 8 * (has2 ? B_G2DONE + 19 : B_G1DONE + 9));
          if (has2) mbar_wait(bars + 8 * B_UST);
          cnt_poll(&g_ucnt[gpc * 32], 128 * tag);
          fence_async_global();
          if (elect_one()) {
            TS(20);
            const int bytes = last ? 16384 : 20480;
            const uint8_t* src = g_u + T1 * 204800;
            uint32_t dst = sb + G1_XOFF;
#pragma unroll 1
            for (int k = 0; k < 10; k++) {
              if (k > S1) mbar_wait(bars + 8 * (B_G1DONE + 9 - S1 + k));
              mbar_expect_tx(bars + 8 * (B_G1FULL + 10 + k), bytes);
              bulk_g2s(dst, src, bytes, bars + 8 * (B_G1FULL + 10 + k));
              src += 20480; dst += G1_STAGE; if (k == S1) dst = sb + G1_XOFF;
            }
          }
          __syncwarp();
        }
        if (has2) {
          mbar_wait(bars + 8 * (B_HST + 2 * l));
          mbar_wait(bars + 8 * (B_G1DONE + 10 * l + 9));
          cnt_poll(&g_hcnt[(l * 16 + gpc) * 32], 40 * tag);
          fence_async_global();
          if (elect_one()) {
            TS(21 + 2 * l);
            const uint32_t fb2 = bars + 8 * (B_G2FULL + 20 * l), wb2 = bars + 8 * (B_G2DONE + 20 * l - S2);
            const uint8_t* src = g_h + (l * 32 + m2) * 163840;
            uint32_t dst = sb;
#pragma unroll 1
            for (int k = 0; k < 20; k++) {
              if (k >= 5) mbar_wait(k >= S2 ? wb2 + 8 * k : bars + 8 * B_SFREE);
              if (k == 10) { mbar_wait(bars + 8 * (B_H1 + l)); fence_async_global(); }
              mbar_expect_tx(fb2 + 8 * k, G2_XB);
              bulk_g2s(dst, src, G2_XB, fb2 + 8 * k);
              src += 8192; dst += G2_XB; if (dst == sb + S2 * G2_XB) dst = sb;
            }
          }
          __syncwarp();
        }
      }
    } else if (pw == 2) {
#pragma unroll 1
      for (int l = 0; l < 2; l++) {
        if (l == 1) {
          float xa[2], xb[2];
          mbar_wait(bars + 8 * (B_G1FULL + 11));
          stat_table(T1, tag, 1, 4, g_stats, g_stats, xa, xb);
          mbar_arrive(bars + 8 * (B_STAB + 1));
        }
#pragma unroll 1
        for (int w = 0; w < 2 * l; w++) {
          mbar_wait(bars + 8 * (B_HST + 2 + w));
          if (lane < 4) h_release(2 + w, T1, lane);
          __syncwarp();
          if (lane == 0) { if (w == 0) mbar_arrive(bars + 8 * (B_REL + 1)); TS(w ? 16 : 14); }
        }
        if (l == 0 && has2 && elect_one()) {
#pragma unroll 1
          for (int c = 0; c < 5; c++) {
            mbar_wait(bars + 8 * (B_CVDONE + c));
            bulk_s2g(g_G + (cch0 + 32 * c) * 4096, cv_stage(c), 4096);
          }
          asm volatile("cp.async.bulk.commit_group;" ::: "memory");
          asm volatile("cp.async.bulk.wait_group.read 0;" ::: "memory");
          mbar_arrive(bars + 8 * B_SFREE);
          asm volatile("cp.async.bulk.wait_group 0;" ::: "memory");
          TS(48);
          fence_async_global();
          st_rel(&g_gflag[(dg * 32 + m2) * 8], tag);
          TS(49);
          mbar_arrive(bars + 8 * (B_GO + 1));
        }
        __syncwarp();
      }
    } else if (has2) {
      mbar_wait(bars + 8 * B_REL);
      if (elect_one()) {
        l2_prefetch(p.cre + (160 * dg + 5 * m2) * DM, 6400); l2_prefetch(p.cim + (160 * dg + 5 * m2) * DM, 6400);
        asm volatile("prefetch.tensormap [%0];" ::"l"(&p.mG) : "memory");
      }
      mbar_wait(bars + 8 * (B_HST + 1));
      flag_poll(&g_hcnt[(8 + gpc) * 32], 40 * tag);
      if (lane == 0) { mbar_arrive(bars + 8 * B_H1); TS(22); }
      if (SYNCW) {
        mbar_wait(bars + 8 * (B_CVDONE + 4));
        flag_poll(&g_rflag[((m2 & ~7) * 4 + (SYNCW == 2 ? lane : (lane & ~2) | (dg & 2))) * 8], tag);
        if (lane == 0) { mbar_arrive(bars + 8 * (B_GO + 2)); TS(15); }
      }
      mbar_wait(bars + 8 * (B_GO + 1));
      flag_poll(&g_gflag[(dg * 32 + lane) * 8], tag);
      fence_async_global();
      if (elect_one()) {
        TS(29);
        mbar_expect_tx(bars + 8 * B_GFULL, 20480);
        tma5(sb + G_OFF, &p.mG, 64 * m2, 0, 0, 0, 10 * dg, bars + 8 * B_GFULL);
      }
      mbar_wait(bars + 8 * (B_HST + 3));
      cnt_poll(&g_hcnt[(24 + gpc) * 32], 40 * tag);
      if (lane == 0) { mbar_arrive(bars + 8 * (B_H1 + 1)); TS(24); }
    }
    } else if (wg == 2 && (role >> 16)) {
      float acc[80];
      float off[2] = {mean0[0], mean0[1]};
      const unsigned tag = lds32(sb + EP_OFF + 20);
      if (tid == 256) asm volatile("st.relaxed.gpu.global.u32 [%0], %1;" ::"l"(&g_rflag[(((role >> 8) & 63) * 4 + ((role >> 14) & 3)) * 8]), "r"(tag) : "memory");
      dskip_init<true>(acc, mean0, rstd0);
      mbar_arrive(bars + 8 * B_XFREE);
#pragma unroll 1
      for (int l = 0; l < 2; l++) {
        float mean[2], rstd[2];
        {
          uint32_t alo = desc_lo(sb, 1024), blo = desc_lo(sb + G2_WOFF, 16);
          uint32_t fb = bars + 8 * (B_G2FULL + 20 * l);
          fence_regs(acc);
          if (SYNCW) mbar_wait(bars + 8 * (B_GO + 2));
          mbar_wait(fb);
          if (tid == 256) TS(33 + 6 * l);
#pragma unroll 1
          for (int k = 0; k < 20; k++) {
            if (l == TSL && (k & 3) == 3 && tid == 256) TS(56 + (k >> 2));
            uint32_t ok; const uint32_t nb = k < 19 ? fb + 8 : fb;
            wgmma_fence();
#pragma unroll
            for (int kk = 0; kk < 4; kk++) {
              wgmma_n160<1>(acc, alo + kk * 128, desc_hi(128, 0), blo + kk * 2, desc_hi(1024, 1));
              if (kk == 0) ok = mbar_test(nb);
            }
            wgmma_commit();
            alo += G2_XB >> 4; blo += G2_WB >> 4;
            if (alo == desc_lo(sb + S2 * G2_XB, 1024)) { alo = desc_lo(sb, 1024); blo = desc_lo(sb + G2_WOFF, 16); }
            wgmma_wait<1>();
            if (k > 0 && tid == 256) mbar_arrive(fb + 8 * (B_G2DONE - B_G2FULL - 1));
            if (!ok) mbar_wait(nb);
            fb += 8;
          }
          wgmma_wait<0>();
          fence_regs(acc);
          if (tid == 256) TS(34 + 6 * l);
          if (tid == 256) mbar_arrive(bars + 8 * (B_G2DONE + 20 * l + 19));
        }
        ROLE(role)
        const int tq = tid_opaque() & 31, n0 = 64 * m2 + 16 * w + (tq >> 2);
        stats_publish<false>(2 * l + 1, n0, dg, tag, acc);
        uint32_t gf[10][4];
        mbar_wait(bars + 8 * B_GFULL);
        const uint32_t ga = sb + G_OFF + (8 * (tq >> 4) + (tq & 7)) * 128 + (((2 * w + ((tq >> 3) & 1)) ^ ((2 * m2) & 6) ^ (tq & 7)) << 4);
#pragma unroll
        for (int J = 0; J < 2; J++) ldsm4t(gf[J], ga + J * 2048);
        if (tid == 256) TS(35 + 6 * l);
        uint8_t* dst[2][2];
#pragma unroll
        for (int h = 0; h < 2; h++) {
          if (l == 0) {
            const int ng = 8 * m2 + 2 * w + h, T = ng / 20;
            uint8_t* ub = g_u + (T * 204800 + (ng - 20 * T) * 1024 + (tq & 2) * 64 + (tq & 28) * 4 + (tq & 1) * 8 + (5 * dg >> 1) * 20480);
            dst[h][1] = ub + ((dg & 1) ? 20480 - 512 : 0);
            dst[h][0] = ub + (dg & 1) * 512;
          } else {
            dst[h][0] = dst[h][1] = (uint8_t*)(p.out + (n_to_t(n0 + 8 * h) * DM + 160 * dg + 4 * (tq & 3)));
          }
        }
        stats_get(2 * l + 1, n0, tag, mean, rstd);
        if (tid == 256) TS(36 + 6 * l);
        off[0] += mean[0]; off[1] += mean[1];
        const float ov[2] = {l ? off[0] : 0.f, l ? off[1] : 0.f};
#pragma unroll
        for (int J = 0; J < 10; J++) {
          if (J + 2 < 10) ldsm4t(gf[J + 2 < 10 ? J + 2 : 0], ga + (J + 2) * 2048);
#pragma unroll
          for (int x = 0; x < 8; x++) {
            const int h = (x >> 1) & 1;
            const uint32_t gwd = gf[J][x >> 1];
            const float t = fmaf(rstd[h], (x & 1) ? bf_hi(gwd) : bf_lo(gwd), 1.f);
            acc[8 * J + x] = fmaf(acc[8 * J + x], t, fmaf(-mean[h], t, ov[h]));
          }
#pragma unroll
          for (int h = 0; h < 2; h++) {
            if (l == 0)
              *(uint2*)(dst[h][(J >> 1) & 1] + (J >> 2) * 20480 + (J & 3) * 256) =
                  make_uint2(pack_bf16(acc[8 * J + 2 * h], acc[8 * J + 2 * h + 1]), pack_bf16(acc[8 * J + 4 + 2 * h], acc[8 * J + 5 + 2 * h]));
            else
              *(float4*)(dst[h][0] + 64 * J) = make_float4(acc[8 * J + 2 * h], acc[8 * J + 2 * h + 1], acc[8 * J + 4 + 2 * h], acc[8 * J + 5 + 2 * h]);
          }
          __syncwarp();
        }
        if (l == 0) {
          bar_sync(3, 128);
          if (tid == 288) { TS(37); mbar_arrive(bars + 8 * B_UST); }
          if (tid < 264) red_rel(&g_ucnt[(tid & 7) * 32]);
          __syncwarp();
          if (tid == 256) { mbar_arrive(bars + 8 * B_GO); TS(38); }
          stats_publish<false>(2, n0, dg, tag, acc);
          mbar_wait(bars + 8 * (B_G1FULL + 11));
          float xa[2], xb[2];
          const uint4* x0 = &g_stats[(8 + (tq & 3)) * SEQ + n0];
          stat_table(T1, tag, 1, w, x0, x0 + 8, xa, xb);
          mbar_arrive(bars + 8 * (B_STAB + 1));
          if (tid == 256) TS(27);
          stats_reduce(xa, xb, mean, rstd);
          off[0] += mean[0]; off[1] += mean[1];
          mbar_wait(bars + 8 * (B_HST + 2));
          dskip_init<false>(acc, mean, rstd);
        } else {
          if (tid == 256) {
            TS(43);
            if (m2 == 31 && dg == 3) asm volatile("st.relaxed.gpu.global.u32 [%0], %1;" ::"l"(g_epoch), "r"(tag + 1) : "memory");
          }
        }
      }
    }
  }
}

typedef CUresult (*EncFn)(CUtensorMap*, CUtensorMapDataType, cuuint32_t, void*, const cuuint64_t*, const cuuint64_t*,
                          const cuuint32_t*, const cuuint32_t*, CUtensorMapInterleave, CUtensorMapSwizzle,
                          CUtensorMapL2promotion, CUtensorMapFloatOOBfill);

void encode(EncFn fn, CUtensorMap* m, const void* ptr, int rank, const cuuint64_t* dims, const cuuint64_t* strides, const cuuint32_t* box,
            CUtensorMapSwizzle swz = CU_TENSOR_MAP_SWIZZLE_128B) {
  cuuint32_t es[5] = {1, 1, 1, 1, 1};
  fn(m, CU_TENSOR_MAP_DATA_TYPE_BFLOAT16, rank, (void*)ptr, dims, strides, box, es, CU_TENSOR_MAP_INTERLEAVE_NONE,
     swz, (CUtensorMapL2promotion)(swz == CU_TENSOR_MAP_SWIZZLE_128B ? PROM_A : PROM_B), CU_TENSOR_MAP_FLOAT_OOB_FILL_NONE);
}

}

extern "C" void kernel_launch(void* const* d_in, const int* in_sizes, int n_in, void* d_out, int out_size) {
  (void)in_sizes; (void)n_in; (void)out_size;
  Params p;
  typedef const __nv_bfloat16* BP;
  p.x = (BP)d_in[0]; p.lre = (BP)d_in[1]; p.lim = (BP)d_in[2]; p.bre = (BP)d_in[3]; p.bim = (BP)d_in[4];
  p.cre = (BP)d_in[5]; p.cim = (BP)d_in[6]; p.logdt = (BP)d_in[7]; p.dskip = (BP)d_in[8];
  p.k = (BP)d_in[10]; p.v = (BP)d_in[11]; p.shiftk = (BP)d_in[12]; p.ssmk = (BP)d_in[13]; p.ssmD = (BP)d_in[14];
  p.out = (float*)d_out;
  for (int sm = 0; sm < 132; sm++) {
    const int tpc = sm >> 1, side = sm & 1;
    int gpc, gi;
    if (tpc < 32) { gpc = tpc & 7; gi = tpc >> 3; }
    else if (tpc < 60) { gpc = 1 + (tpc - 32) % 7; gi = 4 + (tpc - 32) / 7; }
    else if (tpc < 62) { gpc = tpc - 54; gi = 8; }
    else { gpc = 0; gi = tpc - 58; }
    const int pos = 8 * gpc + gi + (gpc == 7 ? 1 : 0);
    int T1, GP;
    if (pos < 52) { const int hh = pos / 26, x = pos - 26 * hh; T1 = x >> 1; GP = 2 * hh + (x & 1); }
    else { T1 = pos - 52; GP = 4; }
    const int m2 = 8 * (gpc >> 1) + gi, dg = 2 * (gpc & 1) + side;
    p.role[sm] = pos == 65 ? -1 : (T1 | (GP << 4) | (side << 7) | (m2 << 8) | (dg << 14) | ((gi < 8) << 16));
  }
  void* fnp = nullptr;
  cudaDriverEntryPointQueryResult qr;
  cudaGetDriverEntryPoint("cuTensorMapEncodeTiled", &fnp, cudaEnableDefault, &qr);
  EncFn fn = (EncFn)fnp;
  void* gG = nullptr;
  cudaGetSymbolAddress(&gG, g_G);
  const cuuint64_t RB = DM * 2;
  {
    p.swap = p.bim < p.bre;
    const char* lo = (const char*)(p.swap ? p.bim : p.bre); const char* hi = (const char*)(p.swap ? p.bre : p.bim);
    cuuint64_t dims[5] = {640, 8, 2, 8, 10}, st[4] = {RB, (cuuint64_t)(hi - lo), 8 * RB, 64 * RB}; cuuint32_t box[5] = {64, 8, 2, 4, 2};
    encode(fn, &p.mB, lo, 5, dims, st, box);
  }
  {
    cuuint64_t dims[5] = {640, 2, 4, 2, 40}, st[4] = {RB, 4 * RB, 2 * RB, 16 * RB}; cuuint32_t box[5] = {64, 2, 4, 2, 10};
    encode(fn, &p.mCre, p.cre, 5, dims, st, box); encode(fn, &p.mCim, p.cim, 5, dims, st, box);
    cuuint64_t dimg[5] = {2048, 2, 4, 2, 40}, stg[4] = {4096, 4 * 4096, 2 * 4096, 16 * 4096};
    encode(fn, &p.mG, gG, 5, dimg, stg, box);
  }
  {
    cuuint64_t dims[4] = {640, 2, 4, 900}, st[3] = {RB, 40 * RB, 2 * RB}; cuuint32_t box[4] = {64, 2, 4, 20};
    encode(fn, &p.mX, p.x, 4, dims, st, box);
    cuuint64_t diml[4] = {640, 2, 4, 16}, stl[3] = {RB, 32 * RB, 2 * RB};
    encode(fn, &p.mXl, p.x + (size_t)1920 * DM, 4, diml, stl, box);
    cuuint32_t boxt[4] = {160, 2, 4, 4};
    encode(fn, &p.mXt, p.x, 4, dims, st, boxt, CU_TENSOR_MAP_SWIZZLE_NONE);
    encode(fn, &p.mXtl, p.x + (size_t)1920 * DM, 4, diml, stl, boxt, CU_TENSOR_MAP_SWIZZLE_NONE);
    cuuint64_t dk[3] = {640, 2000, 4}, sk[2] = {RB, 16 * RB}; cuuint32_t bk[3] = {32, 19, 4}, bv[3] = {32, 17, 4};
    encode(fn, &p.mK, p.k, 3, dk, sk, bk, CU_TENSOR_MAP_SWIZZLE_NONE);
    encode(fn, &p.mV, p.v, 3, dk, sk, bv, CU_TENSOR_MAP_SWIZZLE_NONE);
  }
  cudaFuncSetAttribute(fused_kernel, cudaFuncAttributeMaxDynamicSharedMemorySize, SMEM_BYTES);
  cudaLaunchConfig_t cfg = {};
  cfg.gridDim = dim3(132); cfg.blockDim = dim3(512); cfg.dynamicSmemBytes = SMEM_BYTES; cfg.stream = cudaStreamPerThread;
  cudaLaunchKernelEx(&cfg, fused_kernel, p);
}
```

```cpp
#include <cuda_runtime.h>
#include <cuda.h>
#include <cuda_bf16.h>
#include <stdint.h>

namespace {

constexpr int SEQ = 2048, DM = 640;
constexpr int NT1 = 13;
#define EXP 0
#define WPF1 3
#define WPF2 7
#define CPOLL 10
#define KV0 5
#define TAP0 2
#define PROM_A 2
#define PROM_B 2
#define XFIRST 0
#define TAPLATE 1
#define STG_D 3
#define STG_KK 1
#define HOLD0 1
#define WREL 0
#define UREL 1
#define TSL 1
#define TABW 0
#define STG0 3
#define SYNCW 0
#define WTAIL 1
#define PAUSE_K 4
constexpr uint32_t SPIN_LIMIT = 1u << 22;

__device__ __align__(1024) uint8_t g_h[2 * 32 * 20 * 8192];
__device__ __align__(1024) uint8_t g_u[NT1 * 10 * 20480];
__device__ __align__(1024) uint8_t g_kv[DM * 4096];
__device__ __align__(1024) uint8_t g_G[DM * 4096];
__device__ __align__(128) uint4 g_E[2 * NT1 * DM];
__device__ __align__(128) uint4 g_stats[4 * 4 * SEQ];
__device__ __align__(128) uint4 g_sB[DM * 2];
__device__ __align__(128) unsigned g_hcnt[2 * 2 * 8 * 32];
__device__ __align__(128) unsigned g_ucnt[8 * 32];
__device__ __align__(128) unsigned g_kvcnt[16 * 32];
__device__ __align__(128) unsigned g_gcnt[16 * 32];
__device__ __align__(128) unsigned g_rcnt[8 * 32];
__device__ __align__(128) unsigned g_epoch[32] = {1};
#define TS(i) do {} while (0)

struct Params {
  CUtensorMap mB, mCre, mCim, mX, mXl, mG, mK, mV, mXt, mXtl;
  const __nv_bfloat16 *x, *lre, *lim, *bre, *bim, *cre, *cim, *logdt, *dskip, *k, *v, *shiftk, *ssmk, *ssmD;
  float* out;
  int swap;
  int role[132];
};

constexpr uint32_t sb = 1024;
constexpr uint32_t G1_STAGE = 36864, G1_XOFF = 16384;
constexpr int S1 = 4;
constexpr uint32_t XT_OFF = 159744, KS_OFF = 180224, KV_PIECE = 9216;
constexpr uint32_t G2_XB = 8192, G2_WB = 20480, G2_WOFF = 57344, G_OFF = 200704;
constexpr uint32_t X1_OFF = 139264;
constexpr int S2 = 7;
constexpr uint32_t CV_OFF = KS_OFF, CV_K = 128, CV_PL = 2240, CV_U = CV_K + 4096, CV_B = KV_PIECE;
constexpr uint32_t MISC = 226304;
constexpr uint32_t BAR_OFF = MISC;
constexpr int B_G1FULL = 0, B_G1DONE = 20, B_G2FULL = 40, B_CVFULL = 80  ,
              B_G2DONE = 85, B_GFULL = 125, B_EP = 126, B_H1 = 127  , B_STG = 134  , B_REL = 136  , B_SFREE = 138, B_UST = 142,
              B_GO = 139  , B_PUB = 147,
              B_CVDONE = 148  , B_STAB = 153  , B_XFREE = 155, B_HST = 156  ,
              B_CTAB = 160, B_PREP = 161, B_XT = 162, B_KV = 163  ;
constexpr uint32_t bars = sb + BAR_OFF;
constexpr uint32_t STAB_OFF = MISC + 1344;
constexpr uint32_t CTAB_OFF = STAB_OFF + 1280;
constexpr uint32_t DTAB_OFF = CTAB_OFF + 1536;
constexpr uint32_t EP_OFF = DTAB_OFF + 320;
constexpr uint32_t SO_OFF = EP_OFF + 32;
constexpr uint32_t TAP_OFF = 147456;
constexpr uint32_t SMEM_BYTES = 232448;
static_assert(SO_OFF + 1536 <= SMEM_BYTES, "smem");

__device__ __forceinline__ void trap_if(bool c) { asm volatile("{\n.reg .pred p;\nsetp.ne.u32 p, %0, 0;\n@p trap;\n}\n" ::"r"((uint32_t)c)); }
__device__ __forceinline__ uint32_t smem_u32(const void* p) { return (uint32_t)__cvta_generic_to_shared(p); }
__device__ __forceinline__ void mbar_init(uint32_t bar, int cnt) { asm volatile("mbarrier.init.shared::cta.b64 [%0], %1;" ::"r"(bar), "r"(cnt) : "memory"); }
__device__ __forceinline__ void mbar_expect_tx(uint32_t bar, int bytes) { asm volatile("mbarrier.arrive.expect_tx.shared::cta.b64 _, [%0], %1;" ::"r"(bar), "r"(bytes) : "memory"); }
__device__ __forceinline__ void mbar_arrive(uint32_t bar) { asm volatile("mbarrier.arrive.shared::cta.b64 _, [%0];" ::"r"(bar) : "memory"); }
__device__ __forceinline__ void mbar_wait(uint32_t bar) {
  asm volatile(
      "{\n.reg .pred p;\n.reg .u32 c;\nmov.u32 c, 0;\n"
      "W_%=:\nmbarrier.try_wait.parity.shared::cta.b64 p, [%0], 0;\n@p bra D_%=;\n"
      "add.u32 c, c, 1;\nsetp.lt.u32 p, c, %1;\n@p bra W_%=;\ntrap;\nD_%=:\n}\n" ::"r"(bar), "n"(SPIN_LIMIT) : "memory");
}
__device__ __forceinline__ uint32_t mbar_test(uint32_t bar) {
  uint32_t ok;
  asm volatile("{\n.reg .pred p;\nmbarrier.test_wait.parity.shared::cta.b64 p, [%1], 0;\nselp.u32 %0, 1, 0, p;\n}\n" : "=r"(ok) : "r"(bar) : "memory");
  return ok;
}
__device__ __forceinline__ void tma3(uint32_t dst, const CUtensorMap* m, int c0, int c1, int c2, uint32_t bar) {
  asm volatile("cp.async.bulk.tensor.3d.shared::cluster.global.mbarrier::complete_tx::bytes [%0], [%1, {%3,%4,%5}], [%2];"
               ::"r"(dst), "l"(m), "r"(bar), "r"(c0), "r"(c1), "r"(c2) : "memory");
}
__device__ __forceinline__ void tma4(uint32_t dst, const CUtensorMap* m, int c0, int c1, int c2, int c3, uint32_t bar) {
  asm volatile("cp.async.bulk.tensor.4d.shared::cluster.global.mbarrier::complete_tx::bytes [%0], [%1, {%3,%4,%5,%6}], [%2];"
               ::"r"(dst), "l"(m), "r"(bar), "r"(c0), "r"(c1), "r"(c2), "r"(c3) : "memory");
}
__device__ __forceinline__ void tma5(uint32_t dst, const CUtensorMap* m, int c0, int c1, int c2, int c3, int c4, uint32_t bar) {
  asm volatile("cp.async.bulk.tensor.5d.shared::cluster.global.mbarrier::complete_tx::bytes [%0], [%1, {%3,%4,%5,%6,%7}], [%2];"
               ::"r"(dst), "l"(m), "r"(bar), "r"(c0), "r"(c1), "r"(c2), "r"(c3), "r"(c4) : "memory");
}
__device__ __forceinline__ void bulk_g2s(uint32_t dst, const void* src, int bytes, uint32_t bar) {
  asm volatile("cp.async.bulk.shared::cluster.global.mbarrier::complete_tx::bytes [%0], [%1], %2, [%3];"
               ::"r"(dst), "l"(src), "r"(bytes), "r"(bar) : "memory");
}
__device__ __forceinline__ void bulk_s2g(void* dst, uint32_t src, int bytes) {
  asm volatile("cp.async.bulk.global.shared::cta.bulk_group [%0], [%1], %2;" ::"l"(dst), "r"(src), "r"(bytes) : "memory");
}
__device__ __forceinline__ void l2_prefetch(const void* src, int bytes) {
  asm volatile("cp.async.bulk.prefetch.L2.global [%0], %1;" ::"l"(src), "r"(bytes) : "memory");
}
__device__ __forceinline__ void wgmma_fence() { asm volatile("wgmma.fence.sync.aligned;" ::: "memory"); }
__device__ __forceinline__ void wgmma_commit() { asm volatile("wgmma.commit_group.sync.aligned;" ::: "memory"); }
template <int N> __device__ __forceinline__ void wgmma_wait() { asm volatile("wgmma.wait_group.sync.aligned %0;" ::"n"(N) : "memory"); }
__host__ __device__ constexpr uint32_t desc_lo(uint32_t addr, uint32_t lbo) { return ((addr & 0x3FFFF) >> 4) | ((lbo >> 4) << 16); }
__host__ __device__ constexpr uint32_t desc_hi(uint32_t sbo, uint32_t swz) { return (sbo >> 4) | (swz << 30); }
__device__ __forceinline__ void bar_sync(int id, int n) { asm volatile("bar.sync %0, %1;" ::"r"(id), "r"(n) : "memory"); }
__device__ __forceinline__ uint32_t lds32(uint32_t a) { uint32_t v; asm volatile("ld.shared.u32 %0, [%1];" : "=r"(v) : "r"(a) : "memory"); return v; }
__device__ __forceinline__ float2 lds64f(uint32_t a) { float2 v; asm volatile("ld.shared.v2.f32 {%0,%1}, [%2];" : "=f"(v.x), "=f"(v.y) : "r"(a) : "memory"); return v; }
__device__ __forceinline__ float4 lds128f(uint32_t a) { float4 v; asm volatile("ld.shared.v4.f32 {%0,%1,%2,%3}, [%4];" : "=f"(v.x), "=f"(v.y), "=f"(v.z), "=f"(v.w) : "r"(a) : "memory"); return v; }
__device__ __forceinline__ void ldsm4t(uint32_t (&r)[4], uint32_t a) {
  asm volatile("ldmatrix.sync.aligned.m8n8.x4.trans.shared.b16 {%0,%1,%2,%3}, [%4];" : "=r"(r[0]), "=r"(r[1]), "=r"(r[2]), "=r"(r[3]) : "r"(a) : "memory");
}
__device__ __forceinline__ uint4 ldv128(const void* a) { uint4 v; asm volatile("ld.global.nc.v4.u32 {%0,%1,%2,%3}, [%4];" : "=r"(v.x), "=r"(v.y), "=r"(v.z), "=r"(v.w) : "l"(a) : "memory"); return v; }
__device__ __forceinline__ uint2 ldv64(const void* a) { uint2 v; asm volatile("ld.global.nc.v2.u32 {%0,%1}, [%2];" : "=r"(v.x), "=r"(v.y) : "l"(a) : "memory"); return v; }
__device__ __forceinline__ uint32_t ldv16(const void* a) { uint32_t v; asm volatile("ld.global.nc.u16 %0, [%1];" : "=r"(v) : "l"(a) : "memory"); return v; }
__device__ __forceinline__ void sts128(uint32_t a, uint4 v) { asm volatile("st.shared.v4.u32 [%0], {%1,%2,%3,%4};" ::"r"(a), "r"(v.x), "r"(v.y), "r"(v.z), "r"(v.w) : "memory"); }
__device__ __forceinline__ void sts32(uint32_t a, uint32_t v) { asm volatile("st.shared.u32 [%0], %1;" ::"r"(a), "r"(v) : "memory"); }
__device__ __forceinline__ void sts64f(uint32_t a, float x, float y) { asm volatile("st.shared.v2.f32 [%0], {%1,%2};" ::"r"(a), "f"(x), "f"(y) : "memory"); }
__device__ __forceinline__ void red_rlx(unsigned* p) { asm volatile("red.relaxed.gpu.global.add.u32 [%0], 1;" ::"l"(p) : "memory"); }
__device__ __forceinline__ void red_rel(unsigned* p) { asm volatile("red.release.gpu.global.add.u32 [%0], 1;" ::"l"(p) : "memory"); }
__device__ __forceinline__ void fence_async_global() { asm volatile("fence.proxy.async.global;" ::: "memory"); }
__device__ __forceinline__ void fence_async_smem() { asm volatile("fence.proxy.async.shared::cta;" ::: "memory"); }
__device__ __forceinline__ void rec_st(uint4* p, float a, float b, unsigned tag) {
  asm volatile("{\n.reg .b128 t;\n.reg .b64 lo, hi;\nmov.b64 lo, {%1,%2};\nmov.b64 hi, {%3,%3};\nmov.b128 t, {lo,hi};\n"
               "st.relaxed.gpu.global.b128 [%0], t;\n}\n" ::"l"(p), "r"(__float_as_uint(a)), "r"(__float_as_uint(b)), "r"(tag) : "memory");
}
__device__ __forceinline__ unsigned rec_ld(const uint4* p, float& a, float& b) {
  unsigned x, y, t;
  asm volatile("{\n.reg .b128 t;\n.reg .b64 lo, hi;\n.reg .b32 u;\nld.relaxed.gpu.global.b128 t, [%3];\nmov.b128 {lo,hi}, t;\n"
               "mov.b64 {%0,%1}, lo;\nmov.b64 {%2,u}, hi;\n}\n" : "=r"(x), "=r"(y), "=r"(t) : "l"(p) : "memory");
  a = __uint_as_float(x); b = __uint_as_float(y);
  return t;
}
__device__ __forceinline__ unsigned ld_rlx(const unsigned* p) { unsigned v; asm volatile("ld.relaxed.gpu.global.u32 %0, [%1];" : "=r"(v) : "l"(p) : "memory"); return v; }
__device__ __forceinline__ void flag_poll(const unsigned* p, unsigned target) {
  uint32_t it = 0;
  while (!__all_sync(0xffffffffu, (int)(ld_rlx(p) - target) >= 0)) { trap_if(++it > SPIN_LIMIT); }
  asm volatile("fence.acquire.gpu;" ::: "memory");
}
__device__ __forceinline__ void cnt_poll(const unsigned* p, unsigned target) {
  unsigned a = ld_rlx(p); __nanosleep(100);
  unsigned b = ld_rlx(p); __nanosleep(100);
  unsigned c = ld_rlx(p);
  uint32_t it = 0;
  while (true) {
    if (__all_sync(0xffffffffu, (int)(a - target) >= 0)) break;
    a = ld_rlx(p);
    if (__all_sync(0xffffffffu, (int)(b - target) >= 0)) break;
    b = ld_rlx(p);
    if (__all_sync(0xffffffffu, (int)(c - target) >= 0)) break;
    c = ld_rlx(p);
    trap_if(++it > SPIN_LIMIT);
  }
  asm volatile("fence.acquire.gpu;" ::: "memory");
}
__device__ __forceinline__ void h_release(int idx, int T, int i) {
  const int Q = (i & 2) ? (T + 2) / 3 - 1 : T / 3;
  if (Q >= 0 && Q < 4 && ((i & 2) == 0 || T % 3 == 0)) red_rel(&g_hcnt[(idx * 8 + 2 * Q + (i & 1)) * 32]);
}
__device__ __forceinline__ uint32_t pack_bf16(float lo, float hi) {
  uint32_t r; asm("cvt.rn.bf16x2.f32 %0, %1, %2;" : "=r"(r) : "f"(hi), "f"(lo)); return r;
}
__device__ __forceinline__ float bf_lo(uint32_t w) { return __uint_as_float(w << 16); }
__device__ __forceinline__ float bf_hi(uint32_t w) { return __uint_as_float(w & 0xffff0000u); }
__device__ __forceinline__ uint32_t hmul2(uint32_t a, uint32_t b) {
  __nv_bfloat162 r = __hmul2_rn(*(__nv_bfloat162*)&a, *(__nv_bfloat162*)&b); return *(uint32_t*)&r;
}
__device__ __forceinline__ uint32_t hadd2(uint32_t a, uint32_t b) {
  __nv_bfloat162 r = __hadd2_rn(*(__nv_bfloat162*)&a, *(__nv_bfloat162*)&b); return *(uint32_t*)&r;
}
__device__ __forceinline__ float2 cmul(float2 a, float2 b) { return make_float2(a.x * b.x - a.y * b.y, a.x * b.y + a.y * b.x); }
__device__ __forceinline__ float2 cfma(float2 a, float2 b, float2 c) {
  return make_float2(fmaf(a.x, b.x, fmaf(-a.y, b.y, c.x)), fmaf(a.x, b.y, fmaf(a.y, b.x, c.y)));
}
template <int N> __device__ __forceinline__ void fence_regs(float (&a)[N]) {
#pragma unroll
  for (int i = 0; i < N; i++) asm volatile("" : "+f"(a[i])::"memory");
}
__device__ __forceinline__ bool elect_one() {
  uint32_t e; asm volatile("{\n.reg .pred P;\nelect.sync _|P, 0xffffffff;\nselp.u32 %0, 1, 0, P;\n}\n" : "=r"(e)); return e != 0;
}
__device__ __forceinline__ int tid_opaque() { int t; asm volatile("mov.u32 %0, %%tid.x;" : "=r"(t)); return t; }
struct Role { int T1, GP, side, m2, dg, cch0; bool last, has2; };
__device__ __forceinline__ Role unpack_role(int x) {
  Role r; r.T1 = x & 15; r.GP = (x >> 4) & 7; r.side = (x >> 7) & 1; r.m2 = (x >> 8) & 63; r.dg = (x >> 14) & 3;
  r.has2 = (x >> 16) & 1; r.last = r.T1 == NT1 - 1; r.cch0 = 160 * r.dg + r.m2; return r;
}
__device__ __forceinline__ Role fresh_role(int x) { asm volatile("" : "+r"(x)); return unpack_role(__shfl_sync(0xffffffffu, x, 0)); }
#define ROLE(x) const Role R_ = fresh_role(x); const int T1 = R_.T1, GP = R_.GP, side = R_.side, m2 = R_.m2, dg = R_.dg, cch0 = R_.cch0; \
  const bool last = R_.last, has2 = R_.has2; (void)T1; (void)GP; (void)side; (void)m2; (void)dg; (void)cch0; (void)last; (void)has2;
__device__ __forceinline__ int n_to_t(int n) {
  int T = n / 160, nl = n - T * 160;
  int L = (T == NT1 - 1) ? 32 : 40;
  return T * 160 + L * ((nl & 7) >> 1) + 2 * (nl >> 3) + (nl & 1);
}

template<int TA> __device__ __forceinline__ void wgmma_n160(float (&d)[80], uint32_t alo, uint32_t ahi, uint32_t blo, uint32_t bhi){
  asm volatile("{\n.reg .b64 da, db;\nmov.b64 da, {%80,%81};\nmov.b64 db, {%82,%83};\n"
    "wgmma.mma_async.sync.aligned.m64n160k16.f32.bf16.bf16 {%0, %1, %2, %3, %4, %5, %6, %7, %8, %9, %10, %11, %12, %13, %14, %15, %16, %17, %18, %19, %20, %21, %22, %23, %24, %25, %26, %27, %28, %29, %30, %31, %32, %33, %34, %35, %36, %37, %38, %39, %40, %41, %42, %43, %44, %45, %46, %47, %48, %49, %50, %51, %52, %53, %54, %55, %56, %57, %58, %59, %60, %61, %62, %63, %64, %65, %66, %67, %68, %69, %70, %71, %72, %73, %74, %75, %76, %77, %78, %79}, da, db, 1, 1, 1, %84, 0;\n}\n"
    : "+f"(d[0]), "+f"(d[1]), "+f"(d[2]), "+f"(d[3]), "+f"(d[4]), "+f"(d[5]), "+f"(d[6]), "+f"(d[7]), "+f"(d[8]), "+f"(d[9]), "+f"(d[10]), "+f"(d[11]), "+f"(d[12]), "+f"(d[13]), "+f"(d[14]), "+f"(d[15]), "+f"(d[16]), "+f"(d[17]), "+f"(d[18]), "+f"(d[19]), "+f"(d[20]), "+f"(d[21]), "+f"(d[22]), "+f"(d[23]), "+f"(d[24]), "+f"(d[25]), "+f"(d[26]), "+f"(d[27]), "+f"(d[28]), "+f"(d[29]), "+f"(d[30]), "+f"(d[31]), "+f"(d[32]), "+f"(d[33]), "+f"(d[34]), "+f"(d[35]), "+f"(d[36]), "+f"(d[37]), "+f"(d[38]), "+f"(d[39]), "+f"(d[40]), "+f"(d[41]), "+f"(d[42]), "+f"(d[43]), "+f"(d[44]), "+f"(d[45]), "+f"(d[46]), "+f"(d[47]), "+f"(d[48]), "+f"(d[49]), "+f"(d[50]), "+f"(d[51]), "+f"(d[52]), "+f"(d[53]), "+f"(d[54]), "+f"(d[55]), "+f"(d[56]), "+f"(d[57]), "+f"(d[58]), "+f"(d[59]), "+f"(d[60]), "+f"(d[61]), "+f"(d[62]), "+f"(d[63]), "+f"(d[64]), "+f"(d[65]), "+f"(d[66]), "+f"(d[67]), "+f"(d[68]), "+f"(d[69]), "+f"(d[70]), "+f"(d[71]), "+f"(d[72]), "+f"(d[73]), "+f"(d[74]), "+f"(d[75]), "+f"(d[76]), "+f"(d[77]), "+f"(d[78]), "+f"(d[79])
    : "r"(alo), "r"(ahi), "r"(blo), "r"(bhi), "n"(TA));
}
template<int N> __device__ __forceinline__ void wgmma_rs_hi(float (&d)[64], uint32_t a0, uint32_t a1, uint32_t a2, uint32_t a3, uint32_t blo);
template<> __device__ __forceinline__ void wgmma_rs_hi<16>(float (&d)[64], uint32_t a0, uint32_t a1, uint32_t a2, uint32_t a3, uint32_t blo){
  asm volatile("{\n.reg .b64 db;\nmov.b64 db, {%12,8};\nwgmma.mma_async.sync.aligned.m64n16k16.f32.bf16.bf16 {%0, %1, %2, %3, %4, %5, %6, %7}, {%8,%9,%10,%11}, db, 1, 1, 1, 0;\n}\n"
    : "+f"(d[56]), "+f"(d[57]), "+f"(d[58]), "+f"(d[59]), "+f"(d[60]), "+f"(d[61]), "+f"(d[62]), "+f"(d[63])
    : "r"(a0), "r"(a1), "r"(a2), "r"(a3), "r"(blo));
}
template<> __device__ __forceinline__ void wgmma_rs_hi<32>(float (&d)[64], uint32_t a0, uint32_t a1, uint32_t a2, uint32_t a3, uint32_t blo){
  asm volatile("{\n.reg .b64 db;\nmov.b64 db, {%20,8};\nwgmma.mma_async.sync.aligned.m64n32k16.f32.bf16.bf16 {%0, %1, %2, %3, %4, %5, %6, %7, %8, %9, %10, %11, %12, %13, %14, %15}, {%16,%17,%18,%19}, db, 1, 1, 1, 0;\n}\n"
    : "+f"(d[48]), "+f"(d[49]), "+f"(d[50]), "+f"(d[51]), "+f"(d[52]), "+f"(d[53]), "+f"(d[54]), "+f"(d[55]), "+f"(d[56]), "+f"(d[57]), "+f"(d[58]), "+f"(d[59]), "+f"(d[60]), "+f"(d[61]), "+f"(d[62]), "+f"(d[63])
    : "r"(a0), "r"(a1), "r"(a2), "r"(a3), "r"(blo));
}
template<> __device__ __forceinline__ void wgmma_rs_hi<48>(float (&d)[64], uint32_t a0, uint32_t a1, uint32_t a2, uint32_t a3, uint32_t blo){
  asm volatile("{\n.reg .b64 db;\nmov.b64 db, {%28,8};\nwgmma.mma_async.sync.aligned.m64n48k16.f32.bf16.bf16 {%0, %1, %2, %3, %4, %5, %6, %7, %8, %9, %10, %11, %12, %13, %14, %15, %16, %17, %18, %19, %20, %21, %22, %23}, {%24,%25,%26,%27}, db, 1, 1, 1, 0;\n}\n"
    : "+f"(d[40]), "+f"(d[41]), "+f"(d[42]), "+f"(d[43]), "+f"(d[44]), "+f"(d[45]), "+f"(d[46]), "+f"(d[47]), "+f"(d[48]), "+f"(d[49]), "+f"(d[50]), "+f"(d[51]), "+f"(d[52]), "+f"(d[53]), "+f"(d[54]), "+f"(d[55]), "+f"(d[56]), "+f"(d[57]), "+f"(d[58]), "+f"(d[59]), "+f"(d[60]), "+f"(d[61]), "+f"(d[62]), "+f"(d[63])
    : "r"(a0), "r"(a1), "r"(a2), "r"(a3), "r"(blo));
}
template<> __device__ __forceinline__ void wgmma_rs_hi<64>(float (&d)[64], uint32_t a0, uint32_t a1, uint32_t a2, uint32_t a3, uint32_t blo){
  asm volatile("{\n.reg .b64 db;\nmov.b64 db, {%36,8};\nwgmma.mma_async.sync.aligned.m64n64k16.f32.bf16.bf16 {%0, %1, %2, %3, %4, %5, %6, %7, %8, %9, %10, %11, %12, %13, %14, %15, %16, %17, %18, %19, %20, %21, %22, %23, %24, %25, %26, %27, %28, %29, %30, %31}, {%32,%33,%34,%35}, db, 1, 1, 1, 0;\n}\n"
    : "+f"(d[32]), "+f"(d[33]), "+f"(d[34]), "+f"(d[35]), "+f"(d[36]), "+f"(d[37]), "+f"(d[38]), "+f"(d[39]), "+f"(d[40]), "+f"(d[41]), "+f"(d[42]), "+f"(d[43]), "+f"(d[44]), "+f"(d[45]), "+f"(d[46]), "+f"(d[47]), "+f"(d[48]), "+f"(d[49]), "+f"(d[50]), "+f"(d[51]), "+f"(d[52]), "+f"(d[53]), "+f"(d[54]), "+f"(d[55]), "+f"(d[56]), "+f"(d[57]), "+f"(d[58]), "+f"(d[59]), "+f"(d[60]), "+f"(d[61]), "+f"(d[62]), "+f"(d[63])
    : "r"(a0), "r"(a1), "r"(a2), "r"(a3), "r"(blo));
}
template<> __device__ __forceinline__ void wgmma_rs_hi<80>(float (&d)[64], uint32_t a0, uint32_t a1, uint32_t a2, uint32_t a3, uint32_t blo){
  asm volatile("{\n.reg .b64 db;\nmov.b64 db, {%44,8};\nwgmma.mma_async.sync.aligned.m64n80k16.f32.bf16.bf16 {%0, %1, %2, %3, %4, %5, %6, %7, %8, %9, %10, %11, %12, %13, %14, %15, %16, %17, %18, %19, %20, %21, %22, %23, %24, %25, %26, %27, %28, %29, %30, %31, %32, %33, %34, %35, %36, %37, %38, %39}, {%40,%41,%42,%43}, db, 1, 1, 1, 0;\n}\n"
    : "+f"(d[24]), "+f"(d[25]), "+f"(d[26]), "+f"(d[27]), "+f"(d[28]), "+f"(d[29]), "+f"(d[30]), "+f"(d[31]), "+f"(d[32]), "+f"(d[33]), "+f"(d[34]), "+f"(d[35]), "+f"(d[36]), "+f"(d[37]), "+f"(d[38]), "+f"(d[39]), "+f"(d[40]), "+f"(d[41]), "+f"(d[42]), "+f"(d[43]), "+f"(d[44]), "+f"(d[45]), "+f"(d[46]), "+f"(d[47]), "+f"(d[48]), "+f"(d[49]), "+f"(d[50]), "+f"(d[51]), "+f"(d[52]), "+f"(d[53]), "+f"(d[54]), "+f"(d[55]), "+f"(d[56]), "+f"(d[57]), "+f"(d[58]), "+f"(d[59]), "+f"(d[60]), "+f"(d[61]), "+f"(d[62]), "+f"(d[63])
    : "r"(a0), "r"(a1), "r"(a2), "r"(a3), "r"(blo));
}
template<> __device__ __forceinline__ void wgmma_rs_hi<96>(float (&d)[64], uint32_t a0, uint32_t a1, uint32_t a2, uint32_t a3, uint32_t blo){
  asm volatile("{\n.reg .b64 db;\nmov.b64 db, {%52,8};\nwgmma.mma_async.sync.aligned.m64n96k16.f32.bf16.bf16 {%0, %1, %2, %3, %4, %5, %6, %7, %8, %9, %10, %11, %12, %13, %14, %15, %16, %17, %18, %19, %20, %21, %22, %23, %24, %25, %26, %27, %28, %29, %30, %31, %32, %33, %34, %35, %36, %37, %38, %39, %40, %41, %42, %43, %44, %45, %46, %47}, {%48,%49,%50,%51}, db, 1, 1, 1, 0;\n}\n"
    : "+f"(d[16]), "+f"(d[17]), "+f"(d[18]), "+f"(d[19]), "+f"(d[20]), "+f"(d[21]), "+f"(d[22]), "+f"(d[23]), "+f"(d[24]), "+f"(d[25]), "+f"(d[26]), "+f"(d[27]), "+f"(d[28]), "+f"(d[29]), "+f"(d[30]), "+f"(d[31]), "+f"(d[32]), "+f"(d[33]), "+f"(d[34]), "+f"(d[35]), "+f"(d[36]), "+f"(d[37]), "+f"(d[38]), "+f"(d[39]), "+f"(d[40]), "+f"(d[41]), "+f"(d[42]), "+f"(d[43]), "+f"(d[44]), "+f"(d[45]), "+f"(d[46]), "+f"(d[47]), "+f"(d[48]), "+f"(d[49]), "+f"(d[50]), "+f"(d[51]), "+f"(d[52]), "+f"(d[53]), "+f"(d[54]), "+f"(d[55]), "+f"(d[56]), "+f"(d[57]), "+f"(d[58]), "+f"(d[59]), "+f"(d[60]), "+f"(d[61]), "+f"(d[62]), "+f"(d[63])
    : "r"(a0), "r"(a1), "r"(a2), "r"(a3), "r"(blo));
}
template<> __device__ __forceinline__ void wgmma_rs_hi<112>(float (&d)[64], uint32_t a0, uint32_t a1, uint32_t a2, uint32_t a3, uint32_t blo){
  asm volatile("{\n.reg .b64 db;\nmov.b64 db, {%60,8};\nwgmma.mma_async.sync.aligned.m64n112k16.f32.bf16.bf16 {%0, %1, %2, %3, %4, %5, %6, %7, %8, %9, %10, %11, %12, %13, %14, %15, %16, %17, %18, %19, %20, %21, %22, %23, %24, %25, %26, %27, %28, %29, %30, %31, %32, %33, %34, %35, %36, %37, %38, %39, %40, %41, %42, %43, %44, %45, %46, %47, %48, %49, %50, %51, %52, %53, %54, %55}, {%56,%57,%58,%59}, db, 1, 1, 1, 0;\n}\n"
    : "+f"(d[8]), "+f"(d[9]), "+f"(d[10]), "+f"(d[11]), "+f"(d[12]), "+f"(d[13]), "+f"(d[14]), "+f"(d[15]), "+f"(d[16]), "+f"(d[17]), "+f"(d[18]), "+f"(d[19]), "+f"(d[20]), "+f"(d[21]), "+f"(d[22]), "+f"(d[23]), "+f"(d[24]), "+f"(d[25]), "+f"(d[26]), "+f"(d[27]), "+f"(d[28]), "+f"(d[29]), "+f"(d[30]), "+f"(d[31]), "+f"(d[32]), "+f"(d[33]), "+f"(d[34]), "+f"(d[35]), "+f"(d[36]), "+f"(d[37]), "+f"(d[38]), "+f"(d[39]), "+f"(d[40]), "+f"(d[41]), "+f"(d[42]), "+f"(d[43]), "+f"(d[44]), "+f"(d[45]), "+f"(d[46]), "+f"(d[47]), "+f"(d[48]), "+f"(d[49]), "+f"(d[50]), "+f"(d[51]), "+f"(d[52]), "+f"(d[53]), "+f"(d[54]), "+f"(d[55]), "+f"(d[56]), "+f"(d[57]), "+f"(d[58]), "+f"(d[59]), "+f"(d[60]), "+f"(d[61]), "+f"(d[62]), "+f"(d[63])
    : "r"(a0), "r"(a1), "r"(a2), "r"(a3), "r"(blo));
}
template<> __device__ __forceinline__ void wgmma_rs_hi<128>(float (&d)[64], uint32_t a0, uint32_t a1, uint32_t a2, uint32_t a3, uint32_t blo){
  asm volatile("{\n.reg .b64 db;\nmov.b64 db, {%68,8};\nwgmma.mma_async.sync.aligned.m64n128k16.f32.bf16.bf16 {%0, %1, %2, %3, %4, %5, %6, %7, %8, %9, %10, %11, %12, %13, %14, %15, %16, %17, %18, %19, %20, %21, %22, %23, %24, %25, %26, %27, %28, %29, %30, %31, %32, %33, %34, %35, %36, %37, %38, %39, %40, %41, %42, %43, %44, %45, %46, %47, %48, %49, %50, %51, %52, %53, %54, %55, %56, %57, %58, %59, %60, %61, %62, %63}, {%64,%65,%66,%67}, db, 1, 1, 1, 0;\n}\n"
    : "+f"(d[0]), "+f"(d[1]), "+f"(d[2]), "+f"(d[3]), "+f"(d[4]), "+f"(d[5]), "+f"(d[6]), "+f"(d[7]), "+f"(d[8]), "+f"(d[9]), "+f"(d[10]), "+f"(d[11]), "+f"(d[12]), "+f"(d[13]), "+f"(d[14]), "+f"(d[15]), "+f"(d[16]), "+f"(d[17]), "+f"(d[18]), "+f"(d[19]), "+f"(d[20]), "+f"(d[21]), "+f"(d[22]), "+f"(d[23]), "+f"(d[24]), "+f"(d[25]), "+f"(d[26]), "+f"(d[27]), "+f"(d[28]), "+f"(d[29]), "+f"(d[30]), "+f"(d[31]), "+f"(d[32]), "+f"(d[33]), "+f"(d[34]), "+f"(d[35]), "+f"(d[36]), "+f"(d[37]), "+f"(d[38]), "+f"(d[39]), "+f"(d[40]), "+f"(d[41]), "+f"(d[42]), "+f"(d[43]), "+f"(d[44]), "+f"(d[45]), "+f"(d[46]), "+f"(d[47]), "+f"(d[48]), "+f"(d[49]), "+f"(d[50]), "+f"(d[51]), "+f"(d[52]), "+f"(d[53]), "+f"(d[54]), "+f"(d[55]), "+f"(d[56]), "+f"(d[57]), "+f"(d[58]), "+f"(d[59]), "+f"(d[60]), "+f"(d[61]), "+f"(d[62]), "+f"(d[63])
    : "r"(a0), "r"(a1), "r"(a2), "r"(a3), "r"(blo));
}

__device__ __forceinline__ float shfl_sel(float a, float b, bool p, int src) {
  float r;
  asm volatile("{\n.reg .pred P;\n.reg .f32 t;\nsetp.ne.u32 P, %3, 0;\nselp.f32 t, %1, %2, P;\nshfl.sync.idx.b32 %0, t, %4, 0x1f, 0xffffffff;\n}\n"
               : "=f"(r) : "f"(a), "f"(b), "r"((uint32_t)p), "r"(src));
  return r;
}
struct CvCtx {
  uint32_t koff, zero, so[3];
  int srcA, srcB;
  bool wrapA, s3, kodd;
};
struct CvPipe { float Ep[2], keep[2], send[2]; };
template <int LO> __device__ __forceinline__ void cv_copy(float (&acc)[64]) {
#pragma unroll
  for (int i = LO; i < 64; i++) { float t; asm volatile("mov.b32 %0, %1;" : "=f"(t) : "f"(acc[i]) : "memory"); acc[i] = t; }
}
template <int G> __device__ __forceinline__ void cv_raw(uint32_t (&A)[4][4], uint32_t kaddr) {
#pragma unroll
  for (int i = 0; i < 4; i++) {
    const uint32_t a = kaddr + (4 * G + i) * 128;
    A[i][0] = lds32(a); A[i][1] = lds32(a + 4); A[i][3] = lds32(a + 8);
  }
}
__device__ __forceinline__ void cv_form(uint32_t (&A)[4][4], uint32_t sel) {
#pragma unroll
  for (int i = 0; i < 4; i++) {
    asm volatile("prmt.b32 %0, %0, %1, %2;" : "+r"(A[i][0]) : "r"(A[i][1]), "r"(sel));
    asm volatile("prmt.b32 %0, %1, %2, %3;" : "=r"(A[i][2]) : "r"(A[i][1]), "r"(A[i][3]), "r"(sel));
  }
}
#define CVV 2
template <int G> __device__ __forceinline__ void cv_step(float (&acc)[64], uint32_t (&A)[4][4], CvPipe& s, const CvCtx& c, uint32_t cb, uint32_t stg) {
  constexpr int JA = G - 1, JB = G - 2, NH = CVV == 1 ? 4 : (CVV == 3 ? 2 : 1);
  const uint32_t db0 = desc_lo(cb + CV_U + 192, CV_PL);
  uint32_t B[4][4];
  float ra[4], rb[2];
  if constexpr (G < 8) {
    wgmma_fence();
#pragma unroll
    for (int i = 0; i < NH; i++) wgmma_rs_hi<128 - 16 * (G & 7)>(acc, A[i][0], A[i][1], A[i][2], A[i][3], db0 - 4 * i);
    wgmma_commit();
    __syncwarp();
  }
  if constexpr (JA >= 0 && JA < 8) {
#pragma unroll
    for (int x = 0; x < 4; x++) {
      const int i = 8 * JA + 4 * (x >> 1) + 2 * (x & 1) + 1;
      ra[x] = shfl_sel(i >= 4 ? acc[i >= 4 ? i - 4 : 0] : 0.f, acc[i], c.wrapA, c.srcA);
    }
  }
  if constexpr (JB >= 0) {
#pragma unroll
    for (int h = 0; h < 2; h++) rb[h] = __shfl_sync(0xffffffffu, s.send[h], c.srcB);
  }
  if constexpr (G < 7) cv_raw<G + 1>(B, cb + c.koff);
  uint32_t z = 0;
  if constexpr (G < 8 && NH < 4) {
    __syncwarp();
    wgmma_fence();
#pragma unroll
    for (int i = NH; i < 4; i++) wgmma_rs_hi<128 - 16 * (G & 7)>(acc, A[i][0], A[i][1], A[i][2], A[i][3], db0 - 4 * i);
    wgmma_commit();
    asm volatile("mov.u32 %0, %%clock;" : "=r"(z)::"memory");
    z &= c.zero;
  }
  const float one = __uint_as_float(0x3f800000u | z);
  if constexpr (G < 7) cv_form(B, 0x5432u | z);
  if constexpr (JB >= 0) sts32(stg + ((c.so[JB / 3] >> (10 * (JB % 3))) & 0xffc), pack_bf16(fmaf(rb[0], one, s.keep[0]), fmaf(rb[1], one, s.keep[1])));
  if constexpr (JA >= 0 && JA < 8) {
#pragma unroll
    for (int h = 0; h < 2; h++) {
      const float ev = fmaf(ra[h], one, acc[8 * JA + 2 * h]), od = fmaf(ra[2 + h], one, acc[8 * JA + 4 + 2 * h]);
      s.send[h] = c.kodd ? ev : (c.s3 ? s.Ep[h] : od);
      s.keep[h] = c.kodd ? od : ev;
      s.Ep[h] = od;
    }
  }
  if constexpr (G < 8) { __syncwarp(); wgmma_wait<0>(); cv_copy<8 * (G & 7)>(acc); }
  if constexpr (G < 9) cv_step<G + 1>(acc, B, s, c, cb, stg);
}
__device__ __forceinline__ uint32_t cv_stage(int slot) { return sb + (slot < 4 ? 40960 + slot * 4096 : CV_OFF + CV_K); }
__device__ __forceinline__ void cv_setup(CvCtx& c) {
  const int tid = tid_opaque() & 127, w = tid >> 5, lane = tid & 31, r = lane >> 2, q = lane & 3;
  const int i0 = (r >> 1) & 1, i1 = r >> 2;
  c.koff = CV_K - 32 + 4 * (8 * (r >> 1) + 2 * w + (r & 1) + 2 * q);
  c.srcA = i0 ? lane - 8 : lane + 8 - q + ((q + 3) & 3);
  c.wrapA = i0 && q == 3;
  c.srcB = i1 == 0 ? (lane - q + 16 + ((q + 3) & 3)) : (lane - q - 16 + ((q + 1) & 3));
  c.s3 = (i1 == 1 && q == 3); c.kodd = (i1 == 1 && q < 3);
  c.zero = lds32(sb + EP_OFF + 24);
#pragma unroll
  for (int i = 0; i < 3; i++) c.so[i] = lds32(sb + SO_OFF + 512 * i + 4 * tid);
}
__device__ __forceinline__ void cv_table() {
  const int tid = tid_opaque() & 127, r = (tid & 31) >> 2, q = tid & 3;
  int t = 16 * (2 * (r < 4 ? q : 4 + ((q + 1) & 3)) + ((r >> 1) & 1)) + 4 * (tid >> 5) + 2 * (r & 1);
#pragma unroll 1
  for (int i = 0; i < 3; i++) {
    uint32_t v = 0;
#pragma unroll 1
    for (int x = 0; x < 3; x++, t += 256) {
      const int T = t / 160, tl = t - T * 160;
      const int qq = (T >= NT1 - 1) ? (tl >> 5) : (tl / 40);
      int ck = 20 * T + ((tl - qq * ((T >= NT1 - 1) ? 32 : 40)) >> 1);
      ck ^= (ck >> 2) & 6;
      v |= (uint32_t)((ck * 4 + qq) & 1023) << (10 * x + 2);
    }
    sts32(sb + SO_OFF + 512 * i + 4 * tid, v);
  }
}
__device__ __forceinline__ void conv_channel(int slot, const CvCtx& c) {
  const uint32_t cb = sb + CV_OFF + slot * CV_B;
  float acc[64];
  CvPipe s;
  s.Ep[0] = s.Ep[1] = 0.f;
  uint32_t A[4][4];
#pragma unroll
  for (int i = 0; i < 64; i++) acc[i] = 0.f;
  if (slot == 4) mbar_wait(bars + 8 * B_CVDONE);
  mbar_wait(bars + 8 * (B_CVFULL + slot));
  cv_raw<0>(A, cb + c.koff);
  {
    const uint32_t w0 = lds32(cb + CV_K);
    const uint32_t wp = __byte_perm(pack_bf16(bf_lo(w0) + __uint_as_float(lds32(sb + EP_OFF + 4 * slot)), 0.f), w0, 0x7610);
    if (c.koff == CV_K) A[0][0] = wp;
    if (c.koff == CV_K - 4) A[0][1] = wp;
    if (c.koff == CV_K - 8) A[0][3] = wp;
  }
  cv_form(A, 0x5432u);
  cv_copy<0>(acc);
  cv_step<0>(acc, A, s, c, cb, cv_stage(slot));
  fence_async_smem();
  mbar_arrive(bars + 8 * (B_CVDONE + slot));
}

__device__ __forceinline__ void kv_issue(const Params& p, int c, int m2, int dg) {
  const uint32_t fb = bars + 8 * (B_KV + c);
  mbar_expect_tx(fb, KV_PIECE);
  tma3(sb + KS_OFF + c * KV_PIECE, &p.mK, 160 * dg + 32 * c, 64 * m2 - 3, 0, fb);
  tma3(sb + KS_OFF + c * KV_PIECE + 4864, &p.mV, 160 * dg + 32 * c, 64 * m2 - 1, 0, fb);
}
__device__ __forceinline__ void kv_tile(int m, int dg, int c, int y) {
  const int lane = tid_opaque() & 31, tg = lane >> 3;
  const uint32_t pb = sb + KS_OFF + c * KV_PIECE + 32 * y + 4 * (lane & 7);
  const uint32_t ka = pb + tg * 1216, va = pb + 4864 + tg * 1088 + 64;
  const uint32_t kh = (m == 0 && tg > 0) ? ka - 192 : ka;
  uint32_t kk[19], u[16];
  const float4 t = lds128f(sb + TAP_OFF + 256 * c + 128 * y + 16 * (lane & 7));
#pragma unroll
  for (int i = 0; i < 19; i++) { kk[i] = lds32((i < 3 ? kh : ka) + i * 64); if (i >= 3) u[i - 3] = lds32(va + (i - 3) * 64); }
  uint8_t* dst = g_kv + ((160 * dg + 32 * c + 16 * y + 2 * (lane & 7)) * 4096 + (4 * m + tg) * 16);
  const uint32_t w0 = __byte_perm(__float_as_uint(t.x), __float_as_uint(t.z), 0x5410), w1 = __byte_perm(__float_as_uint(t.x), __float_as_uint(t.z), 0x7632);
  const uint32_t w2 = __byte_perm(__float_as_uint(t.y), __float_as_uint(t.w), 0x5410), w3 = __byte_perm(__float_as_uint(t.y), __float_as_uint(t.w), 0x7632);
#pragma unroll
  for (int i = 0; i < 16; i++) {
    uint32_t a = hmul2(kk[i], w3);
    a = hadd2(a, hmul2(kk[i + 1], w2)); a = hadd2(a, hmul2(kk[i + 2], w1)); a = hadd2(a, hmul2(kk[i + 3], w0));
    u[i] = hmul2(a, u[i]);
  }
#pragma unroll
  for (int e = 0; e < 2; e++)
#pragma unroll
    for (int f = 0; f < 2; f++) {
      uint32_t o[4];
#pragma unroll
      for (int qq = 0; qq < 4; qq++) o[qq] = __byte_perm(u[15 - 4 * qq - 2 * f], u[14 - 4 * qq - 2 * f], e ? 0x7632 : 0x5410);
      *(uint4*)(dst + e * 4096 + f * 2048) = make_uint4(o[0], o[1], o[2], o[3]);
    }
}
__device__ __forceinline__ void ln_finish(float s1, float s2, float& mean, float& rstd) {
  mean = s1 * (1.f / 640.f);
  const float v = fmaxf(fmaf(-mean, mean, s2 * (1.f / 640.f)), 0.f) + 1e-5f;
  asm("rsqrt.approx.ftz.f32 %0, %1;" : "=f"(rstd) : "f"(v));
}
__device__ __forceinline__ void stat_table(int T1, unsigned want, int l, int g, const uint4* x0, const uint4* x1, float (&xa)[2], float (&xb)[2]) {
  const int n = 32 * g + (tid_opaque() & 31);
  const uint4* rp = &g_stats[8 * l * SEQ + min(160 * T1 + n, SEQ - 1)];
  float a[4], b[4];
  uint32_t it = 0;
  while (true) {
    bool ok = true;
#pragma unroll
    for (int i = 0; i < 4; i++) ok &= (rec_ld(rp + SEQ * i, a[i], b[i]) == want);
    ok &= rec_ld(x0, xa[0], xb[0]) == want;
    ok &= rec_ld(x1, xa[1], xb[1]) == want;
    if (__all_sync(0xffffffffu, ok)) break;
    trap_if(++it > SPIN_LIMIT);
  }
  float m, rs;
  ln_finish((a[0] + a[1]) + (a[2] + a[3]), (b[0] + b[1]) + (b[2] + b[3]), m, rs);
  sts64f(sb + STAB_OFF + n * 8, rs, -m * rs);
}
__device__ __forceinline__ void stats_reduce(float (&a)[2], float (&b)[2], float (&mean)[2], float (&rstd)[2]) {
#pragma unroll
  for (int o = 1; o < 4; o <<= 1)
#pragma unroll
    for (int h = 0; h < 2; h++) { a[h] += __shfl_xor_sync(0xffffffffu, a[h], o); b[h] += __shfl_xor_sync(0xffffffffu, b[h], o); }
#pragma unroll
  for (int h = 0; h < 2; h++) ln_finish(a[h], b[h], mean[h], rstd[h]);
}

template <bool FIRST>
__device__ __forceinline__ void stats_publish(int which, int n0, int dg, unsigned tag, const float (&acc)[80]) {
  const int q = tid_opaque() & 3, h = q & 1;
  float s1[2] = {0.f, 0.f}, s2[2] = {0.f, 0.f}, t1[2] = {0.f, 0.f}, t2[2] = {0.f, 0.f};
#pragma unroll
  for (int j = 0; j < 20; j++)
#pragma unroll
    for (int y = 0; y < 2; y++) {
      const float a = acc[4 * j + 2 * y], b = acc[4 * j + 2 * y + 1];
      s1[y] += a; t1[y] += b; s2[y] = fmaf(a, a, s2[y]); t2[y] = fmaf(b, b, t2[y]);
    }
#pragma unroll
  for (int y = 0; y < 2; y++) { s1[y] += t1[y]; s2[y] += t2[y]; }
  float a = (h ? s1[1] : s1[0]) + __shfl_xor_sync(0xffffffffu, h ? s1[0] : s1[1], 1);
  float b = (h ? s2[1] : s2[0]) + __shfl_xor_sync(0xffffffffu, h ? s2[0] : s2[1], 1);
  a += __shfl_xor_sync(0xffffffffu, a, 2);
  b += __shfl_xor_sync(0xffffffffu, b, 2);
  if (FIRST) {
    rec_st(&g_stats[((q >> 1) * 4 + dg) * SEQ + n0 + 8 * h], a, b, q < 2 ? tag : tag - 1);
    rec_st(&g_stats[((q >> 1) * 4 + 8 + dg) * SEQ + n0 + 8 * h], a, b, tag - 1);
  } else if (q < 2) rec_st(&g_stats[(which * 4 + dg) * SEQ + n0 + 8 * h], a, b, tag);
}
__device__ __forceinline__ void stats_get(int which, int n0, unsigned tag, float (&mean)[2], float (&rstd)[2]) {
  const uint4* p0 = &g_stats[(which * 4 + (tid_opaque() & 3)) * SEQ + n0];
  float a[2], b[2];
  uint32_t it = 0;
  while (true) {
    const unsigned t0 = rec_ld(p0, a[0], b[0]), t1 = rec_ld(p0 + 8, a[1], b[1]);
    if (__all_sync(0xffffffffu, t0 == tag && t1 == tag)) break;
    trap_if(++it > SPIN_LIMIT);
  }
  stats_reduce(a, b, mean, rstd);
}
__device__ __forceinline__ void x0_load(float (&acc)[80]) {
  const int t = tid_opaque() & 127;
  const uint32_t xa = sb + XT_OFF + (16 * (t >> 5) + ((t & 31) >> 2)) * 320 + 8 * (t & 3);
  mbar_wait(bars + 8 * B_XT);
#pragma unroll
  for (int h = 0; h < 2; h++)
#pragma unroll
    for (int J = 0; J < 10; J++) {
      const float2 v = lds64f(xa + h * 2560 + 32 * J);
      const uint32_t x = __float_as_uint(v.x), y = __float_as_uint(v.y);
      acc[8 * J + 2 * h] = bf_lo(x); acc[8 * J + 2 * h + 1] = bf_hi(x);
      acc[8 * J + 4 + 2 * h] = bf_lo(y); acc[8 * J + 4 + 2 * h + 1] = bf_hi(y);
    }
}

template <bool FROM_X0>
__device__ __forceinline__ void dskip_init(float (&acc)[80], const float (&mean)[2], const float (&rstd)[2]) {
  const int t = tid_opaque() & 127;
  const uint32_t xa = sb + XT_OFF + (16 * (t >> 5) + ((t & 31) >> 2)) * 320 + 8 * (t & 3), da = sb + DTAB_OFF + 8 * (t & 3);
  float2 dw[10], xv[10][2];
#pragma unroll
  for (int J = 0; J < 2; J++) { dw[J] = lds64f(da + 32 * J); if (FROM_X0) { xv[J][0] = lds64f(xa + 32 * J); xv[J][1] = lds64f(xa + 2560 + 32 * J); } }
#pragma unroll
  for (int J = 0; J < 10; J++) {
    if (J + 2 < 10) { dw[J + 2] = lds64f(da + 32 * (J + 2)); if (FROM_X0) { xv[J + 2][0] = lds64f(xa + 32 * (J + 2)); xv[J + 2][1] = lds64f(xa + 2560 + 32 * (J + 2)); } }
#pragma unroll
    for (int x = 0; x < 8; x++) {
      const int h = (x >> 1) & 1;
      const uint32_t dwd = __float_as_uint(x < 4 ? dw[J].x : dw[J].y);
      const float tt = fmaf(rstd[h], (x & 1) ? bf_hi(dwd) : bf_lo(dwd), 1.f);
      float a = acc[8 * J + x];
      if (FROM_X0) { const uint32_t xw = __float_as_uint(x < 4 ? xv[J][h].x : xv[J][h].y); a = (x & 1) ? bf_hi(xw) : bf_lo(xw); }
      acc[8 * J + x] = FROM_X0 ? (a - mean[h]) * tt : fmaf(a, tt, -mean[h] * tt);
    }
  }
}

__global__ void __launch_bounds__(512, 1) fused_kernel(const __grid_constant__ Params p) {
  extern __shared__ __align__(1024) uint8_t smem_raw[];
  const int tid = threadIdx.x, lane = tid & 31;
  const int wid = __shfl_sync(0xffffffffu, tid >> 5, 0), wg = wid >> 2;
  unsigned smid; asm volatile("mov.u32 %0, %%smid;" : "=r"(smid));
  const int role = p.role[min(smid, 131u)];
  if (wid == 12) {
    const bool el = elect_one();
    if (el) {
      asm volatile("prefetch.tensormap [%0];" ::"l"(&p.mX) : "memory");
      asm volatile("prefetch.tensormap [%0];" ::"l"(&p.mB) : "memory");
#pragma unroll
      for (int k = 0; k < S1; k++) mbar_init(bars + 8 * (B_G1FULL + k), 1);
#pragma unroll
      for (int k = 0; k < 6; k++) mbar_init(bars + 8 * (B_XT + k), 1);
      asm volatile("fence.mbarrier_init.release.cluster;" ::: "memory");
    }
    if (role >= 0) {
      __syncwarp();
      asm volatile("bar.arrive 5, 288;" ::: "memory");
      const Role R = unpack_role(role);
      if (elect_one()) {
        TS(45);
#pragma unroll 1
        for (int k = 0; k < S1; k++) {
          const uint32_t fb = bars + 8 * (B_G1FULL + k);
          mbar_expect_tx(fb, G1_STAGE);
          tma4(sb + k * G1_STAGE + G1_XOFF, R.last ? &p.mXl : &p.mX, 64 * k, 0, 0, R.last ? 0 : 80 * R.T1, fb);
          tma5(sb + k * G1_STAGE, &p.mB, 64 * k, 0, 0, 4 * R.side, 2 * R.GP, fb);
        }
        if (R.has2) {
#pragma unroll 1
          for (int c = 0; c < KV0; c++) kv_issue(p, c, R.m2, R.dg);
          mbar_expect_tx(bars + 8 * B_XT, 20480);
#pragma unroll 1
          for (int h = 0; h < 2; h++) {
            const int ng = 8 * R.m2 + 4 * h, T = ng / 20;
            tma4(sb + XT_OFF + h * 10240, T == NT1 - 1 ? &p.mXtl : &p.mXt, 160 * R.dg, 0, 0, T == NT1 - 1 ? ng - 240 : ng + 60 * T, bars + 8 * B_XT);
          }
        }
        TS(44);
      }
      __syncwarp();
      bar_sync(6, 64);
    }
  }
  trap_if(smid >= 132 || smem_u32(smem_raw) != sb);
  if (role < 0) {
    if (wid == 0) {
      const unsigned tag = ld_rlx(g_epoch);
      uint32_t it = 0;
      while (!__all_sync(0xffffffffu, (int)(ld_rlx(&g_hcnt[(lane & 7) * 32]) - 40 * tag) >= 0)) { __nanosleep(500); trap_if(++it > SPIN_LIMIT); }
    }
    return;
  }
  float mean0[2] = {0.f, 0.f}, rstd0[2] = {0.f, 0.f};
  if (wg == 2 || wid == 14) {
    ROLE(role)
    const int c = wid == 14 ? 4 : wid - 8;
    const unsigned tag = ld_rlx(g_epoch);
    if (has2) {
      uint2 bv[2][5];
#pragma unroll
      for (int x = 0; x < 2; x++)
#pragma unroll
        for (int i = 0; i < 5; i++) bv[x][i] = ldv64((const uint2*)((x ? p.bim : p.bre) + (cch0 + 32 * c) * DM) + lane + 32 * i);
      float sv[2];
#pragma unroll
      for (int x = 0; x < 2; x++) {
        float a = 0.f;
#pragma unroll
        for (int i = 0; i < 5; i++) a += (bf_lo(bv[x][i].x) + bf_hi(bv[x][i].x)) + (bf_lo(bv[x][i].y) + bf_hi(bv[x][i].y));
        sv[x] = a;
      }
#pragma unroll
      for (int o = 16; o > 0; o >>= 1) { sv[0] += __shfl_xor_sync(0xffffffffu, sv[0], o); sv[1] += __shfl_xor_sync(0xffffffffu, sv[1], o); }
      if (lane < 2) rec_st(&g_sB[(cch0 + 32 * c) * 2 + lane], sv[0], sv[1], tag);
      if (tid == 256) TS(47);
      __syncwarp();
      bar_sync(8, 192);
      mbar_wait(bars + 8 * B_EP);
      mbar_wait(bars + 8 * (B_KV + c));
#pragma unroll 1
      for (int y = 0; y < 2; y++) kv_tile(m2, dg, c, y);
      __syncwarp();
      if (lane == 0) mbar_arrive(bars + 8 * B_PREP);
      if (tid == 352) TS(52);
      if (tid == 448) TS(51);
      if (wg == 2) {
        float xs[80];
        x0_load(xs);
        stats_publish<true>(0, 64 * m2 + 16 * c + (lane >> 2), dg, tag, xs);
        if (tid == 256) TS(31);
        mbar_wait(bars + 8 * (TABW ? B_PUB : B_PREP));
      } else {
        mbar_wait(bars + 8 * B_PREP);
        if (lane < 4) red_rel(&g_kvcnt[(dg * 4 + lane) * 32]);
        __syncwarp();
        if (lane == 0) { mbar_arrive(bars + 8 * B_PUB); TS(30); }
      }
    } else bar_sync(8, 192);
    {
      const uint4* x0 = wg == 2 ? &g_stats[(lane & 3) * SEQ + (has2 ? 64 * m2 : 0) + 16 * c + (lane >> 2)] : &g_sB[(128 * GP + 32 * side + lane) * 2];
      float xa[2], xb[2];
      stat_table(T1, tag, 0, c, x0, x0 + (wg == 2 ? 8 : 128), xa, xb);
      if (wg == 2) stats_reduce(xa, xb, mean0, rstd0);
      else {
#pragma unroll
        for (int i = 0; i < 2; i++) sts64f(sb + CTAB_OFF + (32 * i + lane) * 24 + 16, p.swap ? xb[i] : xa[i], p.swap ? xa[i] : xb[i]);
      }
      mbar_arrive(bars + 8 * B_STAB);
      if (tid == 448) TS(26);
    }
  } else if (wid == 15) {
    ROLE(role)
    const int ch = 128 * GP + 32 * side + lane;
    uint32_t r0 = ldv16(p.lre + ch), r1 = ldv16(p.lim + ch), r2 = ldv16(p.logdt + ch);
    const uint32_t r3 = ldv16(p.lre + ch + 64), r4 = ldv16(p.lim + ch + 64), r5 = ldv16(p.logdt + ch + 64);
#pragma unroll 1
    for (int i = 0; i < 2; i++) {
      const float lr = bf_lo(r0), li = bf_lo(r1);
      const float dt = __bfloat162float(__float2bfloat16_rn(expf(bf_lo(r2))));
      const float mag = expf(dt * lr);
      float sn, cs; sincospif(dt * li * 0.31830988618379067f, &sn, &cs);
      const float ar = mag * cs, ai = mag * sn;
      const float inv = 2.f / (lr * lr + li * li);
      const uint32_t ad = sb + CTAB_OFF + (32 * i + lane) * 24;
      sts64f(ad, ar, ai);
      sts64f(ad + 8, ((ar - 1.f) * lr + ai * li) * inv, (ai * lr - (ar - 1.f) * li) * inv);
      r0 = r3; r1 = r4; r2 = r5;
    }
    if (lane == 0) TS(46);
    __syncwarp();
    bar_sync(7, 64);
    mbar_arrive(bars + 8 * B_CTAB);
  } else if (wid == 13) {
    ROLE(role)
    uint4 tv[3];
    const uint32_t e0 = ld_rlx(g_epoch);
    const uint32_t e1 = ldv16(p.ssmD + min(cch0 + 32 * lane, 639));
    const uint4 dv = ldv128((const uint4*)(p.dskip + 160 * dg) + min(lane, 19));
#pragma unroll
    for (int i = 0; i < 3; i++) tv[i] = ldv128((const uint4*)(p.shiftk + 640 * dg) + min(lane + 32 * i, 79));
    sts128(sb + DTAB_OFF + 16 * min(lane, 19), dv);
#pragma unroll
    for (int i = 0; i < 3; i++) sts128(sb + TAP_OFF + 16 * min(lane + 32 * i, 79), tv[i]);
    if (lane < 7) sts32(sb + EP_OFF + 4 * lane, lane < 5 ? e1 << 16 : (lane == 5 ? e0 : 0u));
    __syncwarp();
    bar_sync(9, 64);
    mbar_arrive(bars + 8 * B_CTAB);
    if (lane == 0) { mbar_arrive(bars + 8 * B_EP); TS(53); }
  } else if (wid != 12) {
    if (elect_one()) {
      if (wid < 7) {
        const int b0 = wid < 4 ? 4 + 20 * wid : 85 + 21 * (wid - 4), cnt = wid < 4 ? 2 : 1;
#pragma unroll
        for (int i = 0; i < 21; i++) mbar_init(bars + 8 * (b0 + i), cnt);
      } else {
#pragma unroll
        for (int i = 0; i < 12; i++) mbar_init(bars + 8 * (B_CVDONE + i), (i == 5 || i == 6) ? 160 : 128);
        mbar_init(bars + 8 * B_CTAB, 192); mbar_init(bars + 8 * B_PREP, 5);
      }
      asm volatile("fence.mbarrier_init.release.cluster;" ::: "memory");
    }
    __syncwarp();
    bar_sync(5, 288);
    if (wid == 2) asm volatile("bar.arrive 8, 192;\nbar.arrive 6, 64;\nbar.arrive 9, 64;\nbar.arrive 7, 64;" ::: "memory");
    if (tid == 128) TS(0);
    if (wg == 1) { cv_table(); mbar_arrive(bars + 8 * B_CTAB); }
  }

  if (wid == 12) {
    ROLE(role)
    uint32_t dst = sb;
#pragma unroll 1
    for (int k = S1; k < 10; k++) {
      const uint32_t fb = bars + 8 * (B_G1FULL + k);
      mbar_wait(bars + 8 * (B_G1DONE + k - S1));
      if (elect_one()) {
        mbar_expect_tx(fb, 20480);
        tma4(dst + G1_XOFF, last ? &p.mXl : &p.mX, 64 * k, 0, 0, last ? 0 : 80 * T1, fb);
        mbar_expect_tx(fb, 16384);
        tma5(dst, &p.mB, 64 * k, 0, 0, 4 * side, 2 * GP, fb);
        if (has2 && k - S1 + KV0 < 5) kv_issue(p, k - S1 + KV0, m2, dg);
      }
      dst += G1_STAGE; if (k == 2 * S1 - 1) dst = sb;
    }
  } else if (wid == 15 && (role >> 16)) {
    ROLE(role)
    mbar_wait(bars + 8 * B_PREP);
#pragma unroll
    for (int c = 0; c < 5; c++) {
      const uint32_t cb = sb + CV_OFF + c * CV_B;
      sts128(lane < 8 ? cb + 16 * lane : (lane < 20 ? cb + CV_U + 16 * (lane - 8) : cb + CV_U + CV_PL + 16 * (lane - 20)), make_uint4(0, 0, 0, 0));
    }
    fence_async_smem();
    __syncwarp();
    const unsigned tag = lds32(sb + EP_OFF + 20);
    mbar_wait(bars + 8 * B_PUB);
    if (elect_one()) {
#pragma unroll
      for (int c = 0; c < TAP0; c++) {
        mbar_expect_tx(bars + 8 * (B_CVFULL + c), 4096);
        bulk_g2s(sb + CV_OFF + c * CV_B + CV_K, p.ssmk + (cch0 + 32 * c) * SEQ, 4096, bars + 8 * (B_CVFULL + c));
      }
    }
    cnt_poll(&g_kvcnt[(dg * 4 + (m2 >> 3)) * 32], 32 * tag);
    fence_async_global();
    if (elect_one()) {
      TS(28);
#pragma unroll 1
      for (int c = 0; c < 5; c++) {
        const uint32_t fb = bars + 8 * (B_CVFULL + c), cb = sb + CV_OFF + c * CV_B;
        mbar_expect_tx(fb, 4096);
        bulk_g2s(cb + CV_U + 192, g_kv + (cch0 + 32 * c) * 4096, 2048, fb);
        bulk_g2s(cb + CV_U + 192 + CV_PL, g_kv + (cch0 + 32 * c) * 4096 + 2048, 2048, fb);
        if (c >= TAP0) {
          mbar_expect_tx(fb, 4096);
          bulk_g2s(cb + CV_K, p.ssmk + (cch0 + 32 * c) * SEQ, 4096, fb);
        }
      }
      TS(54);
    }
    __syncwarp();
  }
  {
    const int w = wid & 3;
    if (wg == 2 && !(role >> 16)) {
      float xa[2], xb[2];
      mbar_wait(bars + 8 * (B_G1FULL + 11));
      stat_table(role & 15, lds32(sb + EP_OFF + 20), 1, w, g_stats, g_stats, xa, xb);
      mbar_arrive(bars + 8 * (B_STAB + 1));
    }
#pragma unroll 1
    for (int l = 0; l < 2; l++) {
      if (wg < 2) {
        float acc[80];
#pragma unroll
        for (int i = 0; i < 80; i++) acc[i] = 0.f;
        ROLE(role)
        const int tid = tid_opaque(), r = (tid & 31) >> 2, q = tid & 3;
        const int ch = 128 * GP + 64 * wg + 32 * side + 8 * w + r;
        const uint32_t ca = sb + CTAB_OFF + (32 * wg + 8 * w + r) * 24;
        float2 lam = make_float2(0.f, 0.f), p8 = lam, p16 = lam, pL = lam, p2L = lam;
        fence_regs(acc);
        {
          const uint32_t alo0 = (l == 0 ? desc_lo(sb, 16) : desc_lo(sb + G2_WOFF, 16)) + wg * 512;
          const uint32_t blo0 = l == 0 ? desc_lo(sb + G1_XOFF, 16) : desc_lo(sb + X1_OFF, 128);
          const uint32_t bhi = l == 0 ? desc_hi(1024, 1) : desc_hi(1024, 0), xstep = l == 0 ? 2 : 16;
          const uint32_t astep = l == 0 ? G1_STAGE >> 4 : 1024, bstep = l == 0 ? G1_STAGE >> 4 : 1280, aend = alo0 + (S1 + l) * astep;
          uint32_t alo = alo0, blo = blo0;
          uint32_t fb = bars + 8 * (B_G1FULL + 10 * l);
          mbar_wait(fb);
          if (tid == 0) TS(1 + 8 * l);
#pragma unroll 1
          for (int k = 0; k < 10; k++) {
            uint32_t ok; const uint32_t nb = k < 9 ? fb + 8 : fb;
            wgmma_fence();
#pragma unroll
            for (int kk = 0; kk < 4; kk++) {
              wgmma_n160<0>(acc, alo + kk * 2, desc_hi(1024, 1), blo + kk * xstep, bhi);
              if (kk == 0) ok = mbar_test(nb);
              if (kk == STG_KK && k == 9 && tid == 0) mbar_arrive(bars + 8 * (B_STG + l));
            }
            wgmma_commit();
            alo += astep; blo += bstep;
            if (blo == desc_lo(sb + G_OFF, 128)) blo = desc_lo(sb, 128);
            if (alo == aend) { alo = alo0; blo = blo0; }
            wgmma_wait<1>();
            if (k > 0 && (tid & 127) == 0) mbar_arrive(fb + 8 * (B_G1DONE - B_G1FULL - 1));
            if (!ok) mbar_wait(nb);
            if (wg == 1 && k == (l ? 8 - STG_D : 9 - STG0)) mbar_wait(bars + 8 * (B_STG + l));
            if (k == 3) {
              mbar_wait(bars + 8 * B_CTAB);
              lam = lds64f(ca);
              if (p.swap) lam.y = -lam.y;
              const float2 p2 = cmul(lam, lam), p4 = cmul(p2, p2);
              p8 = cmul(p4, p4); p16 = cmul(p8, p8);
              pL = cmul(p16, p16);
              if (!last) pL = cmul(pL, p8);
              p2L = cmul(pL, pL);
            }
            if (k == PAUSE_K && has2) mbar_wait(bars + 8 * B_PREP);
            fb += 8;
          }
        }
        mbar_wait(bars + 8 * (B_STAB + l));
        const float2 sB = lds64f(ca + 16);
        const unsigned tag = lds32(sb + EP_OFF + 20);
        wgmma_wait<0>();
        fence_regs(acc);
        if ((tid & 127) == 0) { mbar_arrive(bars + 8 * (B_G1DONE + 10 * l + 9)); TS(wg ? 17 + l : 2 + 8 * l); }
        float2 ec[3];
#pragma unroll
        for (int jj = 0; jj < 8; jj++)
#pragma unroll
          for (int y = 0; y < 3; y++) {
            if (y == 2 && (jj & 1)) continue;
            const int j = y == 2 ? 16 + (jj >> 1) : 8 * y + jj;
            const float4 st = lds128f(sb + STAB_OFF + (8 * j + 2 * q) * 8);
            acc[4 * j + 0] = fmaf(acc[4 * j + 0], st.x, st.y * sB.x);
            acc[4 * j + 2] = fmaf(acc[4 * j + 2], st.x, st.y * sB.y);
            acc[4 * j + 1] = fmaf(acc[4 * j + 1], st.z, st.w * sB.x);
            acc[4 * j + 3] = fmaf(acc[4 * j + 3], st.z, st.w * sB.y);
            ec[y] = jj == 0 ? make_float2(acc[4 * j + 0], acc[4 * j + 2]) : cfma(lam, ec[y], make_float2(acc[4 * j + 0], acc[4 * j + 2]));
            ec[y] = cfma(lam, ec[y], make_float2(acc[4 * j + 1], acc[4 * j + 3]));
          }
        float2 e = cfma(p16, ec[0], ec[1]);
        if (!last) e = cfma(p8, e, ec[2]);
        {
          float2 v = make_float2(__shfl_up_sync(0xffffffffu, e.x, 1, 4), __shfl_up_sync(0xffffffffu, e.y, 1, 4));
          if (q >= 1) e = cfma(pL, v, e);
          v = make_float2(__shfl_up_sync(0xffffffffu, e.x, 2, 4), __shfl_up_sync(0xffffffffu, e.y, 2, 4));
          if (q >= 2) e = cfma(p2L, v, e);
        }
        if (!last && (q == 3 || (q == 2 && l == 0))) rec_st(&g_E[((q == 3 ? l : 1) * NT1 + T1) * DM + ch], e.x, e.y, q == 3 ? tag : tag - 1);
        if (tid == 0) TS(3 + 8 * l);
        float2 ex = make_float2(__shfl_up_sync(0xffffffffu, e.x, 1, 4), __shfl_up_sync(0xffffffffu, e.y, 1, 4));
        if (q == 0) ex = make_float2(0.f, 0.f);
        const float2 coef = lds64f(ca + 8), lamc = make_float2(lam.x, p.swap ? lam.y : -lam.y);
        float m00 = coef.x, m01 = -coef.y, m10 = -coef.y, m11 = -coef.x;
        if (p.swap) { m00 = -coef.y; m01 = coef.x; m10 = -coef.x; m11 = -coef.y; }
        float2 pLq, p160q, p640;
        {
          const float2 p80 = last ? cmul(p2L, p16) : p2L, p160 = cmul(p80, p80), p320 = cmul(p160, p160), one = make_float2(1.f, 0.f);
          p640 = cmul(p320, p320);
          pLq = cmul((q & 1) ? pL : one, (q & 2) ? p2L : one);
          p160q = cmul((q & 1) ? p160 : one, (q & 2) ? p320 : one);
        }
        float2 c, ev[3];
        unsigned tg[3];
        const uint4* ep = &g_E[(l * NT1 + T1 - 1 - q) * DM + ch];
#pragma unroll
        for (int j = 0; j < 20; j++) {
          if (j == CPOLL) {
#pragma unroll
            for (int i = 0; i < 3; i++) {
              ev[i] = make_float2(0.f, 0.f); tg[i] = tag;
              if (T1 - 1 - q - 4 * i >= 0) tg[i] = rec_ld(ep - 4 * i * DM, ev[i].x, ev[i].y);
            }
          }
#pragma unroll
          for (int x = 0; x < 2; x++) {
            const float b0 = acc[4 * j + x], b1 = acc[4 * j + 2 + x];
            acc[4 * j + x] = fmaf(b0, m00, b1 * m01);
            acc[4 * j + 2 + x] = fmaf(b0, m10, b1 * m11);
          }
          if (j == CPOLL - 1 || j == 19) asm volatile("" : "+f"(acc[4 * j]), "+f"(acc[4 * j + 1]), "+f"(acc[4 * j + 2]), "+f"(acc[4 * j + 3])::"memory");
        }
        {
          uint32_t it = 0;
          while (__any_sync(0xffffffffu, tg[0] != tag || tg[1] != tag || tg[2] != tag)) {
#pragma unroll
            for (int i = 0; i < 3; i++)
              if (tg[i] != tag) tg[i] = rec_ld(ep - 4 * i * DM, ev[i].x, ev[i].y);
            trap_if(++it > SPIN_LIMIT);
          }
          c = cfma(p640, cfma(p640, ev[2], ev[1]), ev[0]);
          c = cmul(c, p160q);
          c.x += __shfl_xor_sync(0xffffffffu, c.x, 1); c.y += __shfl_xor_sync(0xffffffffu, c.y, 1);
          c.x += __shfl_xor_sync(0xffffffffu, c.x, 2); c.y += __shfl_xor_sync(0xffffffffu, c.y, 2);
        }
        if (tid == 0) TS(4 + 8 * l);
        if (wg == 1 && l >= HOLD0) mbar_wait(bars + 8 * (B_REL + l));
        c = cfma(pLq, c, ex);
        float2 hh = make_float2(fmaf(c.x, m00, c.y * m01), fmaf(c.x, m10, c.y * m11));
        uint8_t* hb = g_h + (size_t)l * (32 * 20 * 8192) + (10 * wg + 2 * GP) * 8192 + (4 * side + w) * 1024 + (tid_opaque() & 31) * 4;
#pragma unroll
        for (int j4 = 0; j4 < 5; j4++) {
          const int ng = 20 * T1 + 4 * j4;
          uint8_t* hp = hb + (size_t)(ng >> 3) * 163840 + (ng & 7) * 128;
#pragma unroll
          for (int jj = 0; jj < 4; jj++) {
            const int j = 4 * j4 + jj;
            const float2 h0 = cfma(lamc, hh, make_float2(acc[4 * j + 0], acc[4 * j + 2]));
            hh = cfma(lamc, h0, make_float2(acc[4 * j + 1], acc[4 * j + 3]));
            if (j4 < 4 || !last) {
              *(uint32_t*)(hp + jj * 128) = pack_bf16(h0.x, hh.x);
              *(uint32_t*)(hp + jj * 128 + 8192) = pack_bf16(h0.y, hh.y);
            }
          }
        }
        mbar_arrive(bars + 8 * (B_HST + 2 * l + wg));
        if (tid == 0) TS(5 + 8 * l);
        if (tid == 128) TS(l ? 25 : 19);
        if (l == 0 && wid == 4) {
          mbar_wait(bars + 8 * B_HST);
          mbar_wait(bars + 8 * (B_HST + 1));
          if ((tid & 31) < 8) h_release((tid >> 2) & 1, T1, tid & 3);
          __syncwarp();
          if (tid == 128) { mbar_arrive(bars + 8 * B_REL); TS(6); }
        }
      }
      if (l == 0) {
        ROLE(role)
        if (has2) {
          CvCtx cc;
          mbar_wait(bars + 8 * B_CTAB);
          cv_setup(cc);
          mbar_wait(bars + 8 * (B_G1DONE + 9));
#pragma unroll 1
          for (int c = (wg + 2) & 3; c < 5; c += 4) conv_channel(c, cc);
          if ((tid & 127) == 0) TS(wg == 2 ? 32 : (wg == 3 ? 50 : 7 + wg));
        }
      }
      if (wg >= 2) break;
    }
    if (wg == 3) {
    ROLE(role)
    const int pw = wid & 3, gpc = 2 * min(m2 >> 3, 3) + (dg >> 1);
    mbar_wait(bars + 8 * B_EP);
    const unsigned tag = lds32(sb + EP_OFF + 20);
    if (pw == 0) {
      if (elect_one()) {
#pragma unroll 1
        for (int l = 0; l < 2; l++) {
          uint32_t dst = sb;
          if (l == 1) {
            dst = sb + G2_WOFF;
#pragma unroll 1
            for (int k = 0; k < 10; k++) {
              mbar_wait(k > 4 ? bars + 8 * (B_G1DONE + 5 + k) : (has2 ? bars + 8 * (B_G2DONE + 14 + min(k, 3)) : bars + 8 * (B_G1DONE + 9)));
              mbar_expect_tx(bars + 8 * (B_G1FULL + 10 + k), 16384);
              tma5(dst, &p.mB, 64 * k, 0, 0, 4 * side, 2 * GP, bars + 8 * (B_G1FULL + 10 + k));
              dst += 16384; if (k == 4) dst = sb + G2_WOFF;
            }
          }
          if (has2) {
            const uint32_t fb2 = bars + 8 * (B_G2FULL + 20 * l), wb2 = bars + 8 * (B_G2DONE + 20 * l - S2);
            dst = sb + G2_WOFF + (WTAIL ? 4 * l * G2_WB : 0);
            int kc = 0;
#pragma unroll 1
            for (int k = 0; k < 20; k++) {
              mbar_wait(k >= S2 ? wb2 + 8 * k : bars + 8 * (l ? B_G1DONE + (WTAIL ? (k < 3 ? 15 + k : 13 + k) : 19) : (k == 5 ? B_XFREE : (k == 6 ? B_SFREE : B_REL))));
              mbar_expect_tx(fb2 + 8 * k, G2_WB);
              tma5(dst, &p.mCre + (k & 1), kc, 0, 0, 0, 10 * dg, fb2 + 8 * k);
              kc += (k & 1) << 7; if (k == 9) kc = 64;
              dst += G2_WB; if (dst == sb + G2_WOFF + S2 * G2_WB) dst = sb + G2_WOFF;
            }
          }
        }
      }
    } else if (pw == 1) {
#pragma unroll 1
      for (int l = 0; l < 2; l++) {
        if (l == 1) {
          mbar_wait(bars + 8 * (has2 ? B_G2DONE + 19 : B_G1DONE + 9));
          if (has2) mbar_wait(bars + 8 * B_UST);
          cnt_poll(&g_ucnt[gpc * 32], 128 * tag);
          fence_async_global();
          if (elect_one()) {
            TS(20);
            const int bytes = last ? 16384 : 20480;
            const uint8_t* src = g_u + T1 * 204800;
            uint32_t dst = sb + X1_OFF;
#pragma unroll 1
            for (int k = 0; k < 10; k++) {
              if (k > 4) mbar_wait(bars + 8 * (B_G1DONE + 5 + k));
              mbar_expect_tx(bars + 8 * (B_G1FULL + 10 + k), bytes);
              bulk_g2s(dst, src, bytes, bars + 8 * (B_G1FULL + 10 + k));
              src += 20480; dst += 20480; if (dst == sb + G_OFF) dst = sb; if (k == 4) dst = sb + X1_OFF;
            }
          }
          __syncwarp();
        }
        if (has2) {
          mbar_wait(bars + 8 * (B_HST + 2 * l));
          mbar_wait(bars + 8 * (B_G1DONE + 10 * l + 9));
          cnt_poll(&g_hcnt[(l * 16 + gpc) * 32], 40 * tag);
          fence_async_global();
          if (elect_one()) {
            TS(21 + 2 * l);
            const uint32_t fb2 = bars + 8 * (B_G2FULL + 20 * l), wb2 = bars + 8 * (B_G2DONE + 20 * l - S2);
            const uint8_t* src = g_h + (l * 32 + m2) * 163840;
            uint32_t dst = sb;
#pragma unroll 1
            for (int k = 0; k < 20; k++) {
              if (k >= 5) mbar_wait(k >= S2 ? wb2 + 8 * k : bars + 8 * B_SFREE);
              if (k == 10) { mbar_wait(bars + 8 * (B_H1 + l)); fence_async_global(); }
              mbar_expect_tx(fb2 + 8 * k, G2_XB);
              bulk_g2s(dst, src, G2_XB, fb2 + 8 * k);
              src += 8192; dst += G2_XB; if (dst == sb + S2 * G2_XB) dst = sb;
            }
          }
          __syncwarp();
        }
      }
    } else if (pw == 2) {
#pragma unroll 1
      for (int l = 0; l < 2; l++) {
        if (l == 1) {
          float xa[2], xb[2];
          mbar_wait(bars + 8 * (B_G1FULL + 11));
          stat_table(T1, tag, 1, 4, g_stats, g_stats, xa, xb);
          mbar_arrive(bars + 8 * (B_STAB + 1));
        }
#pragma unroll 1
        for (int w = 0; w < 2 * l; w++) {
          mbar_wait(bars + 8 * (B_HST + 2 + w));
          if (lane < 4) h_release(2 + w, T1, lane);
          __syncwarp();
          if (lane == 0) { if (w == 0) mbar_arrive(bars + 8 * (B_REL + 1)); TS(w ? 16 : 14); }
        }
        if (l == 0 && has2 && elect_one()) {
#pragma unroll 1
          for (int c = 0; c < 5; c++) {
            mbar_wait(bars + 8 * (B_CVDONE + c));
            bulk_s2g(g_G + (cch0 + 32 * c) * 4096, cv_stage(c), 4096);
          }
          asm volatile("cp.async.bulk.commit_group;" ::: "memory");
          asm volatile("cp.async.bulk.wait_group.read 0;" ::: "memory");
          mbar_arrive(bars + 8 * B_SFREE);
          asm volatile("cp.async.bulk.wait_group 0;" ::: "memory");
          TS(48);
          fence_async_global();
          asm volatile("fence.acq_rel.gpu;" ::: "memory");
#pragma unroll
          for (int i = 0; i < 4; i++) red_rlx(&g_gcnt[(dg * 4 + i) * 32]);
          TS(49);
          mbar_arrive(bars + 8 * (B_GO + 1));
        }
        __syncwarp();
      }
    } else if (has2) {
      mbar_wait(bars + 8 * B_REL);
      if (elect_one()) {
        l2_prefetch(p.cre + (160 * dg + 5 * m2) * DM, 6400); l2_prefetch(p.cim + (160 * dg + 5 * m2) * DM, 6400);
        asm volatile("prefetch.tensormap [%0];" ::"l"(&p.mG) : "memory");
      }
      mbar_wait(bars + 8 * (B_HST + 1));
      flag_poll(&g_hcnt[(8 + gpc) * 32], 40 * tag);
      if (lane == 0) { mbar_arrive(bars + 8 * B_H1); TS(22); }
      if (SYNCW) {
        cnt_poll(&g_rcnt[gpc * 32], 16 * tag);
        if (lane == 0) { mbar_arrive(bars + 8 * (B_GO + 2)); TS(15); }
      }
      mbar_wait(bars + 8 * (B_GO + 1));
      flag_poll(&g_gcnt[(dg * 4 + (m2 >> 3)) * 32], 32 * tag);
      fence_async_global();
      if (elect_one()) {
        TS(29);
        mbar_expect_tx(bars + 8 * B_GFULL, 20480);
        tma5(sb + G_OFF, &p.mG, 64 * m2, 0, 0, 0, 10 * dg, bars + 8 * B_GFULL);
      }
      mbar_wait(bars + 8 * (B_HST + 3));
      cnt_poll(&g_hcnt[(24 + gpc) * 32], 40 * tag);
      if (lane == 0) { mbar_arrive(bars + 8 * (B_H1 + 1)); TS(24); }
    }
    } else if (wg == 2 && (role >> 16)) {
      float acc[80];
      float off[2] = {mean0[0], mean0[1]};
      const unsigned tag = lds32(sb + EP_OFF + 20);
      if (SYNCW && tid == 256) red_rlx(&g_rcnt[(2 * ((role >> 11) & 3) + ((role >> 15) & 1)) * 32]);
      dskip_init<true>(acc, mean0, rstd0);
      mbar_arrive(bars + 8 * B_XFREE);
#pragma unroll 1
      for (int l = 0; l < 2; l++) {
        float mean[2], rstd[2];
        {
          uint32_t alo = desc_lo(sb, 1024), blo = desc_lo(sb + G2_WOFF, 16) + (WTAIL ? l * (G2_WB >> 2) : 0);
          uint32_t fb = bars + 8 * (B_G2FULL + 20 * l);
          fence_regs(acc);
          if (SYNCW) mbar_wait(bars + 8 * (B_GO + 2));
          mbar_wait(fb);
          if (tid == 256) TS(33 + 6 * l);
#pragma unroll 1
          for (int k = 0; k < 20; k++) {
            if (l == TSL && (k & 3) == 3 && tid == 256) TS(56 + (k >> 2));
            uint32_t ok; const uint32_t nb = k < 19 ? fb + 8 : fb;
            wgmma_fence();
#pragma unroll
            for (int kk = 0; kk < 4; kk++) {
              wgmma_n160<1>(acc, alo + kk * 128, desc_hi(128, 0), blo + kk * 2, desc_hi(1024, 1));
              if (kk == 0) ok = mbar_test(nb);
            }
            wgmma_commit();
            alo += G2_XB >> 4; blo += G2_WB >> 4;
            if (alo == desc_lo(sb + S2 * G2_XB, 1024)) alo = desc_lo(sb, 1024);
            if (blo == desc_lo(sb + G_OFF, 16)) blo = desc_lo(sb + G2_WOFF, 16);
            wgmma_wait<1>();
            if (k > 0 && tid == 256) mbar_arrive(fb + 8 * (B_G2DONE - B_G2FULL - 1));
            if (!ok) mbar_wait(nb);
            fb += 8;
          }
          wgmma_wait<0>();
          fence_regs(acc);
          if (tid == 256) TS(34 + 6 * l);
          if (tid == 256) mbar_arrive(bars + 8 * (B_G2DONE + 20 * l + 19));
        }
        ROLE(role)
        const int tq = tid_opaque() & 31, n0 = 64 * m2 + 16 * w + (tq >> 2);
        stats_publish<false>(2 * l + 1, n0, dg, tag, acc);
        uint32_t gf[10][4];
        mbar_wait(bars + 8 * B_GFULL);
        const uint32_t ga = sb + G_OFF + (8 * (tq >> 4) + (tq & 7)) * 128 + (((2 * w + ((tq >> 3) & 1)) ^ ((2 * m2) & 6) ^ (tq & 7)) << 4);
#pragma unroll
        for (int J = 0; J < 2; J++) ldsm4t(gf[J], ga + J * 2048);
        if (tid == 256) TS(35 + 6 * l);
        uint8_t* dst[2][2];
#pragma unroll
        for (int h = 0; h < 2; h++) {
          if (l == 0) {
            const int ng = 8 * m2 + 2 * w + h, T = ng / 20;
            uint8_t* ub = g_u + (T * 204800 + (ng - 20 * T) * 1024 + (tq & 2) * 64 + (tq & 28) * 4 + (tq & 1) * 8 + (5 * dg >> 1) * 20480);
            dst[h][1] = ub + ((dg & 1) ? 20480 - 512 : 0);
            dst[h][0] = ub + (dg & 1) * 512;
          } else {
            dst[h][0] = dst[h][1] = (uint8_t*)(p.out + (n_to_t(n0 + 8 * h) * DM + 160 * dg + 4 * (tq & 3)));
          }
        }
        stats_get(2 * l + 1, n0, tag, mean, rstd);
        if (tid == 256) TS(36 + 6 * l);
        off[0] += mean[0]; off[1] += mean[1];
        const float ov[2] = {l ? off[0] : 0.f, l ? off[1] : 0.f};
#pragma unroll
        for (int J = 0; J < 10; J++) {
          if (J + 2 < 10) ldsm4t(gf[J + 2 < 10 ? J + 2 : 0], ga + (J + 2) * 2048);
#pragma unroll
          for (int x = 0; x < 8; x++) {
            const int h = (x >> 1) & 1;
            const uint32_t gwd = gf[J][x >> 1];
            const float t = fmaf(rstd[h], (x & 1) ? bf_hi(gwd) : bf_lo(gwd), 1.f);
            acc[8 * J + x] = fmaf(acc[8 * J + x], t, fmaf(-mean[h], t, ov[h]));
          }
#pragma unroll
          for (int h = 0; h < 2; h++) {
            if (l == 0)
              *(uint2*)(dst[h][(J >> 1) & 1] + (J >> 2) * 20480 + (J & 3) * 256) =
                  make_uint2(pack_bf16(acc[8 * J + 2 * h], acc[8 * J + 2 * h + 1]), pack_bf16(acc[8 * J + 4 + 2 * h], acc[8 * J + 5 + 2 * h]));
            else
              *(float4*)(dst[h][0] + 64 * J) = make_float4(acc[8 * J + 2 * h], acc[8 * J + 2 * h + 1], acc[8 * J + 4 + 2 * h], acc[8 * J + 5 + 2 * h]);
          }
          __syncwarp();
        }
        if (l == 0) {
          bar_sync(3, 128);
          if (tid == 288) { TS(37); mbar_arrive(bars + 8 * B_UST); }
          if (tid < 264) red_rel(&g_ucnt[(tid & 7) * 32]);
          __syncwarp();
          if (tid == 256) TS(38);
          stats_publish<false>(2, n0, dg, tag, acc);
          mbar_wait(bars + 8 * (B_G1FULL + 11));
          float xa[2], xb[2];
          const uint4* x0 = &g_stats[(8 + (tq & 3)) * SEQ + n0];
          stat_table(T1, tag, 1, w, x0, x0 + 8, xa, xb);
          mbar_arrive(bars + 8 * (B_STAB + 1));
          if (tid == 256) TS(27);
          stats_reduce(xa, xb, mean, rstd);
          off[0] += mean[0]; off[1] += mean[1];
          mbar_wait(bars + 8 * (B_HST + 2));
          dskip_init<false>(acc, mean, rstd);
        } else {
          if (tid == 256) {
            TS(43);
            if (m2 == 31 && dg == 3) asm volatile("st.relaxed.gpu.global.u32 [%0], %1;" ::"l"(g_epoch), "r"(tag + 1) : "memory");
          }
        }
      }
    }
  }
}

typedef CUresult (*EncFn)(CUtensorMap*, CUtensorMapDataType, cuuint32_t, void*, const cuuint64_t*, const cuuint64_t*,
                          const cuuint32_t*, const cuuint32_t*, CUtensorMapInterleave, CUtensorMapSwizzle,
                          CUtensorMapL2promotion, CUtensorMapFloatOOBfill);

void encode(EncFn fn, CUtensorMap* m, const void* ptr, int rank, const cuuint64_t* dims, const cuuint64_t* strides, const cuuint32_t* box,
            CUtensorMapSwizzle swz = CU_TENSOR_MAP_SWIZZLE_128B) {
  cuuint32_t es[5] = {1, 1, 1, 1, 1};
  fn(m, CU_TENSOR_MAP_DATA_TYPE_BFLOAT16, rank, (void*)ptr, dims, strides, box, es, CU_TENSOR_MAP_INTERLEAVE_NONE,
     swz, (CUtensorMapL2promotion)(swz == CU_TENSOR_MAP_SWIZZLE_128B ? PROM_A : PROM_B), CU_TENSOR_MAP_FLOAT_OOB_FILL_NONE);
}

}

extern "C" void kernel_launch(void* const* d_in, const int* in_sizes, int n_in, void* d_out, int out_size) {
  (void)in_sizes; (void)n_in; (void)out_size;
  Params p;
  typedef const __nv_bfloat16* BP;
  p.x = (BP)d_in[0]; p.lre = (BP)d_in[1]; p.lim = (BP)d_in[2]; p.bre = (BP)d_in[3]; p.bim = (BP)d_in[4];
  p.cre = (BP)d_in[5]; p.cim = (BP)d_in[6]; p.logdt = (BP)d_in[7]; p.dskip = (BP)d_in[8];
  p.k = (BP)d_in[10]; p.v = (BP)d_in[11]; p.shiftk = (BP)d_in[12]; p.ssmk = (BP)d_in[13]; p.ssmD = (BP)d_in[14];
  p.out = (float*)d_out;
  for (int sm = 0; sm < 132; sm++) {
    const int tpc = sm >> 1, side = sm & 1;
    int gpc, gi;
    if (tpc < 32) { gpc = tpc & 7; gi = tpc >> 3; }
    else if (tpc < 60) { gpc = 1 + (tpc - 32) % 7; gi = 4 + (tpc - 32) / 7; }
    else if (tpc < 62) { gpc = tpc - 54; gi = 8; }
    else { gpc = 0; gi = tpc - 58; }
    const int pos = 8 * gpc + gi + (gpc == 7 ? 1 : 0);
    int T1, GP;
    if (pos < 52) { const int hh = pos / 26, x = pos - 26 * hh; T1 = x >> 1; GP = 2 * hh + (x & 1); }
    else { T1 = pos - 52; GP = 4; }
    const int m2 = 8 * (gpc >> 1) + gi, dg = 2 * (gpc & 1) + side;
    p.role[sm] = pos == 65 ? -1 : (T1 | (GP << 4) | (side << 7) | (m2 << 8) | (dg << 14) | ((gi < 8) << 16));
  }
  void* fnp = nullptr;
  cudaDriverEntryPointQueryResult qr;
  cudaGetDriverEntryPoint("cuTensorMapEncodeTiled", &fnp, cudaEnableDefault, &qr);
  EncFn fn = (EncFn)fnp;
  void* gG = nullptr;
  cudaGetSymbolAddress(&gG, g_G);
  const cuuint64_t RB = DM * 2;
  {
    p.swap = p.bim < p.bre;
    const char* lo = (const char*)(p.swap ? p.bim : p.bre); const char* hi = (const char*)(p.swap ? p.bre : p.bim);
    cuuint64_t dims[5] = {640, 8, 2, 8, 10}, st[4] = {RB, (cuuint64_t)(hi - lo), 8 * RB, 64 * RB}; cuuint32_t box[5] = {64, 8, 2, 4, 2};
    encode(fn, &p.mB, lo, 5, dims, st, box);
  }
  {
    cuuint64_t dims[5] = {640, 2, 4, 2, 40}, st[4] = {RB, 4 * RB, 2 * RB, 16 * RB}; cuuint32_t box[5] = {64, 2, 4, 2, 10};
    encode(fn, &p.mCre, p.cre, 5, dims, st, box); encode(fn, &p.mCim, p.cim, 5, dims, st, box);
    cuuint64_t dimg[5] = {2048, 2, 4, 2, 40}, stg[4] = {4096, 4 * 4096, 2 * 4096, 16 * 4096};
    encode(fn, &p.mG, gG, 5, dimg, stg, box);
  }
  {
    cuuint64_t dims[4] = {640, 2, 4, 900}, st[3] = {RB, 40 * RB, 2 * RB}; cuuint32_t box[4] = {64, 2, 4, 20};
    encode(fn, &p.mX, p.x, 4, dims, st, box);
    cuuint64_t diml[4] = {640, 2, 4, 16}, stl[3] = {RB, 32 * RB, 2 * RB};
    encode(fn, &p.mXl, p.x + (size_t)1920 * DM, 4, diml, stl, box);
    cuuint32_t boxt[4] = {160, 2, 4, 4};
    encode(fn, &p.mXt, p.x, 4, dims, st, boxt, CU_TENSOR_MAP_SWIZZLE_NONE);
    encode(fn, &p.mXtl, p.x + (size_t)1920 * DM, 4, diml, stl, boxt, CU_TENSOR_MAP_SWIZZLE_NONE);
    cuuint64_t dk[3] = {640, 2000, 4}, sk[2] = {RB, 16 * RB}; cuuint32_t bk[3] = {32, 19, 4}, bv[3] = {32, 17, 4};
    encode(fn, &p.mK, p.k, 3, dk, sk, bk, CU_TENSOR_MAP_SWIZZLE_NONE);
    encode(fn, &p.mV, p.v, 3, dk, sk, bv, CU_TENSOR_MAP_SWIZZLE_NONE);
  }
  cudaFuncSetAttribute(fused_kernel, cudaFuncAttributeMaxDynamicSharedMemorySize, SMEM_BYTES);
  cudaLaunchConfig_t cfg = {};
  cfg.gridDim = dim3(132); cfg.blockDim = dim3(512); cfg.dynamicSmemBytes = SMEM_BYTES; cfg.stream = cudaStreamPerThread;
  cudaLaunchKernelEx(&cfg, fused_kernel, p);
}
```

```cpp
#include <cuda_runtime.h>
#include <cuda.h>
#include <cuda_bf16.h>
#include <stdint.h>

namespace {

constexpr int SEQ = 2048, DM = 640;
constexpr int NT1 = 13;
#define EXP 0
#define WPF1 3
#define WPF2 7
#define CPOLL 10
#define KV0 5
#define TAP0 2
#define PROM_A 2
#define PROM_B 2
#define XFIRST 0
#define TAPLATE 1
#define STG_D 3
#define STG_KK 1
#define HOLD0 1
#define WREL 0
#define UREL 1
#define TSL 1
#define TABW 0
#define STG0 3
#define WTAIL 1
#define PAUSE_K 4
constexpr uint32_t SPIN_LIMIT = 1u << 22;

__device__ __align__(1024) uint8_t g_h[2 * 32 * 20 * 8192];
__device__ __align__(1024) uint8_t g_u[NT1 * 10 * 20480];
__device__ __align__(1024) uint8_t g_kv[DM * 4096];
__device__ __align__(1024) uint8_t g_G[DM * 4096];
__device__ __align__(128) uint4 g_E[2 * NT1 * DM];
__device__ __align__(128) uint4 g_stats[4 * 4 * SEQ];
__device__ __align__(128) uint4 g_sB[DM * 2];
__device__ __align__(128) unsigned g_hcnt[2 * 2 * 8 * 32];
__device__ __align__(128) unsigned g_ucnt[8 * 32];
__device__ __align__(128) unsigned g_kvcnt[16 * 32];
__device__ __align__(128) unsigned g_gcnt[16 * 32];
__device__ __align__(128) unsigned g_epoch[32] = {1};
#define TS(i) do {} while (0)

struct Params {
  CUtensorMap mB, mCre, mCim, mX, mXl, mG, mK, mV, mXt, mXtl;
  const __nv_bfloat16 *x, *lre, *lim, *bre, *bim, *cre, *cim, *logdt, *dskip, *k, *v, *shiftk, *ssmk, *ssmD;
  float* out;
  int swap;
  int role[132];
};

constexpr uint32_t sb = 1024;
constexpr uint32_t G1_STAGE = 36864, G1_XOFF = 16384;
constexpr int S1 = 4;
constexpr uint32_t XT_OFF = 159744, KS_OFF = 180224, KV_PIECE = 9216;
constexpr uint32_t G2_XB = 8192, G2_WB = 20480, G2_WOFF = 57344, G_OFF = 200704;
constexpr uint32_t X1_OFF = 139264;
constexpr int S2 = 7;
constexpr uint32_t CV_OFF = KS_OFF, CV_K = 128, CV_PL = 2240, CV_U = CV_K + 4096, CV_B = KV_PIECE;
constexpr uint32_t MISC = 226304;
constexpr uint32_t BAR_OFF = MISC;
constexpr int B_G1FULL = 0, B_G1DONE = 20, B_G2FULL = 40, B_CVFULL = 80  ,
              B_G2DONE = 85, B_GFULL = 125, B_EP = 126, B_H1 = 127  , B_STG = 134  , B_REL = 136  , B_SFREE = 138, B_UST = 142,
              B_GO = 139  , B_PUB = 147,
              B_CVDONE = 148  , B_STAB = 153  , B_XFREE = 155, B_HST = 156  ,
              B_CTAB = 160, B_PREP = 161, B_XT = 162, B_KV = 163  ;
constexpr uint32_t bars = sb + BAR_OFF;
constexpr uint32_t STAB_OFF = MISC + 1344;
constexpr uint32_t CTAB_OFF = STAB_OFF + 1280;
constexpr uint32_t DTAB_OFF = CTAB_OFF + 1536;
constexpr uint32_t EP_OFF = DTAB_OFF + 320;
constexpr uint32_t SO_OFF = EP_OFF + 32;
constexpr uint32_t TAP_OFF = 147456;
constexpr uint32_t SMEM_BYTES = 232448;
static_assert(SO_OFF + 1536 <= SMEM_BYTES, "smem");

__device__ __forceinline__ void trap_if(bool c) { asm volatile("{\n.reg .pred p;\nsetp.ne.u32 p, %0, 0;\n@p trap;\n}\n" ::"r"((uint32_t)c)); }
__device__ __forceinline__ uint32_t smem_u32(const void* p) { return (uint32_t)__cvta_generic_to_shared(p); }
__device__ __forceinline__ void mbar_init(uint32_t bar, int cnt) { asm volatile("mbarrier.init.shared::cta.b64 [%0], %1;" ::"r"(bar), "r"(cnt) : "memory"); }
__device__ __forceinline__ void mbar_expect_tx(uint32_t bar, int bytes) { asm volatile("mbarrier.arrive.expect_tx.shared::cta.b64 _, [%0], %1;" ::"r"(bar), "r"(bytes) : "memory"); }
__device__ __forceinline__ void mbar_arrive(uint32_t bar) { asm volatile("mbarrier.arrive.shared::cta.b64 _, [%0];" ::"r"(bar) : "memory"); }
__device__ __forceinline__ void mbar_wait(uint32_t bar) {
  asm volatile(
      "{\n.reg .pred p;\n.reg .u32 c;\nmov.u32 c, 0;\n"
      "W_%=:\nmbarrier.try_wait.parity.shared::cta.b64 p, [%0], 0;\n@p bra D_%=;\n"
      "add.u32 c, c, 1;\nsetp.lt.u32 p, c, %1;\n@p bra W_%=;\ntrap;\nD_%=:\n}\n" ::"r"(bar), "n"(SPIN_LIMIT) : "memory");
}
__device__ __forceinline__ uint32_t mbar_test(uint32_t bar) {
  uint32_t ok;
  asm volatile("{\n.reg .pred p;\nmbarrier.test_wait.parity.shared::cta.b64 p, [%1], 0;\nselp.u32 %0, 1, 0, p;\n}\n" : "=r"(ok) : "r"(bar) : "memory");
  return ok;
}
__device__ __forceinline__ void tma3(uint32_t dst, const CUtensorMap* m, int c0, int c1, int c2, uint32_t bar) {
  asm volatile("cp.async.bulk.tensor.3d.shared::cluster.global.mbarrier::complete_tx::bytes [%0], [%1, {%3,%4,%5}], [%2];"
               ::"r"(dst), "l"(m), "r"(bar), "r"(c0), "r"(c1), "r"(c2) : "memory");
}
__device__ __forceinline__ void tma4(uint32_t dst, const CUtensorMap* m, int c0, int c1, int c2, int c3, uint32_t bar) {
  asm volatile("cp.async.bulk.tensor.4d.shared::cluster.global.mbarrier::complete_tx::bytes [%0], [%1, {%3,%4,%5,%6}], [%2];"
               ::"r"(dst), "l"(m), "r"(bar), "r"(c0), "r"(c1), "r"(c2), "r"(c3) : "memory");
}
__device__ __forceinline__ void tma5(uint32_t dst, const CUtensorMap* m, int c0, int c1, int c2, int c3, int c4, uint32_t bar) {
  asm volatile("cp.async.bulk.tensor.5d.shared::cluster.global.mbarrier::complete_tx::bytes [%0], [%1, {%3,%4,%5,%6,%7}], [%2];"
               ::"r"(dst), "l"(m), "r"(bar), "r"(c0), "r"(c1), "r"(c2), "r"(c3), "r"(c4) : "memory");
}
__device__ __forceinline__ void bulk_g2s(uint32_t dst, const void* src, int bytes, uint32_t bar) {
  asm volatile("cp.async.bulk.shared::cluster.global.mbarrier::complete_tx::bytes [%0], [%1], %2, [%3];"
               ::"r"(dst), "l"(src), "r"(bytes), "r"(bar) : "memory");
}
__device__ __forceinline__ void bulk_s2g(void* dst, uint32_t src, int bytes) {
  asm volatile("cp.async.bulk.global.shared::cta.bulk_group [%0], [%1], %2;" ::"l"(dst), "r"(src), "r"(bytes) : "memory");
}
__device__ __forceinline__ void l2_prefetch(const void* src, int bytes) {
  asm volatile("cp.async.bulk.prefetch.L2.global [%0], %1;" ::"l"(src), "r"(bytes) : "memory");
}
__device__ __forceinline__ void wgmma_fence() { asm volatile("wgmma.fence.sync.aligned;" ::: "memory"); }
__device__ __forceinline__ void wgmma_commit() { asm volatile("wgmma.commit_group.sync.aligned;" ::: "memory"); }
template <int N> __device__ __forceinline__ void wgmma_wait() { asm volatile("wgmma.wait_group.sync.aligned %0;" ::"n"(N) : "memory"); }
__host__ __device__ constexpr uint32_t desc_lo(uint32_t addr, uint32_t lbo) { return ((addr & 0x3FFFF) >> 4) | ((lbo >> 4) << 16); }
__host__ __device__ constexpr uint32_t desc_hi(uint32_t sbo, uint32_t swz) { return (sbo >> 4) | (swz << 30); }
__device__ __forceinline__ void bar_sync(int id, int n) { asm volatile("bar.sync %0, %1;" ::"r"(id), "r"(n) : "memory"); }
__device__ __forceinline__ uint32_t lds32(uint32_t a) { uint32_t v; asm volatile("ld.shared.u32 %0, [%1];" : "=r"(v) : "r"(a) : "memory"); return v; }
__device__ __forceinline__ float2 lds64f(uint32_t a) { float2 v; asm volatile("ld.shared.v2.f32 {%0,%1}, [%2];" : "=f"(v.x), "=f"(v.y) : "r"(a) : "memory"); return v; }
__device__ __forceinline__ float4 lds128f(uint32_t a) { float4 v; asm volatile("ld.shared.v4.f32 {%0,%1,%2,%3}, [%4];" : "=f"(v.x), "=f"(v.y), "=f"(v.z), "=f"(v.w) : "r"(a) : "memory"); return v; }
__device__ __forceinline__ void ldsm4t(uint32_t (&r)[4], uint32_t a) {
  asm volatile("ldmatrix.sync.aligned.m8n8.x4.trans.shared.b16 {%0,%1,%2,%3}, [%4];" : "=r"(r[0]), "=r"(r[1]), "=r"(r[2]), "=r"(r[3]) : "r"(a) : "memory");
}
__device__ __forceinline__ uint4 ldv128(const void* a) { uint4 v; asm volatile("ld.global.nc.v4.u32 {%0,%1,%2,%3}, [%4];" : "=r"(v.x), "=r"(v.y), "=r"(v.z), "=r"(v.w) : "l"(a) : "memory"); return v; }
__device__ __forceinline__ uint2 ldv64(const void* a) { uint2 v; asm volatile("ld.global.nc.v2.u32 {%0,%1}, [%2];" : "=r"(v.x), "=r"(v.y) : "l"(a) : "memory"); return v; }
__device__ __forceinline__ uint32_t ldv16(const void* a) { uint32_t v; asm volatile("ld.global.nc.u16 %0, [%1];" : "=r"(v) : "l"(a) : "memory"); return v; }
__device__ __forceinline__ void sts128(uint32_t a, uint4 v) { asm volatile("st.shared.v4.u32 [%0], {%1,%2,%3,%4};" ::"r"(a), "r"(v.x), "r"(v.y), "r"(v.z), "r"(v.w) : "memory"); }
__device__ __forceinline__ void sts32(uint32_t a, uint32_t v) { asm volatile("st.shared.u32 [%0], %1;" ::"r"(a), "r"(v) : "memory"); }
__device__ __forceinline__ void sts64f(uint32_t a, float x, float y) { asm volatile("st.shared.v2.f32 [%0], {%1,%2};" ::"r"(a), "f"(x), "f"(y) : "memory"); }
__device__ __forceinline__ void red_rlx(unsigned* p) { asm volatile("red.relaxed.gpu.global.add.u32 [%0], 1;" ::"l"(p) : "memory"); }
__device__ __forceinline__ void red_rel(unsigned* p) { asm volatile("red.release.gpu.global.add.u32 [%0], 1;" ::"l"(p) : "memory"); }
__device__ __forceinline__ void fence_async_global() { asm volatile("fence.proxy.async.global;" ::: "memory"); }
__device__ __forceinline__ void fence_async_smem() { asm volatile("fence.proxy.async.shared::cta;" ::: "memory"); }
__device__ __forceinline__ void rec_st(uint4* p, float a, float b, unsigned tag) {
  asm volatile("{\n.reg .b128 t;\n.reg .b64 lo, hi;\nmov.b64 lo, {%1,%2};\nmov.b64 hi, {%3,%3};\nmov.b128 t, {lo,hi};\n"
               "st.relaxed.gpu.global.b128 [%0], t;\n}\n" ::"l"(p), "r"(__float_as_uint(a)), "r"(__float_as_uint(b)), "r"(tag) : "memory");
}
__device__ __forceinline__ unsigned rec_ld(const uint4* p, float& a, float& b) {
  unsigned x, y, t;
  asm volatile("{\n.reg .b128 t;\n.reg .b64 lo, hi;\n.reg .b32 u;\nld.relaxed.gpu.global.b128 t, [%3];\nmov.b128 {lo,hi}, t;\n"
               "mov.b64 {%0,%1}, lo;\nmov.b64 {%2,u}, hi;\n}\n" : "=r"(x), "=r"(y), "=r"(t) : "l"(p) : "memory");
  a = __uint_as_float(x); b = __uint_as_float(y);
  return t;
}
__device__ __forceinline__ unsigned ld_rlx(const unsigned* p) { unsigned v; asm volatile("ld.relaxed.gpu.global.u32 %0, [%1];" : "=r"(v) : "l"(p) : "memory"); return v; }
__device__ __forceinline__ void flag_poll(const unsigned* p, unsigned target) {
  uint32_t it = 0;
  while (!__all_sync(0xffffffffu, (int)(ld_rlx(p) - target) >= 0)) { trap_if(++it > SPIN_LIMIT); }
  asm volatile("fence.acquire.gpu;" ::: "memory");
}
__device__ __forceinline__ void cnt_poll(const unsigned* p, unsigned target) {
  unsigned a = ld_rlx(p); __nanosleep(100);
  unsigned b = ld_rlx(p); __nanosleep(100);
  unsigned c = ld_rlx(p);
  uint32_t it = 0;
  while (true) {
    if (__all_sync(0xffffffffu, (int)(a - target) >= 0)) break;
    a = ld_rlx(p);
    if (__all_sync(0xffffffffu, (int)(b - target) >= 0)) break;
    b = ld_rlx(p);
    if (__all_sync(0xffffffffu, (int)(c - target) >= 0)) break;
    c = ld_rlx(p);
    trap_if(++it > SPIN_LIMIT);
  }
  asm volatile("fence.acquire.gpu;" ::: "memory");
}
__device__ __forceinline__ void h_release(int idx, int T, int i) {
  const int Q = (i & 2) ? (T + 2) / 3 - 1 : T / 3;
  if (Q >= 0 && Q < 4 && ((i & 2) == 0 || T % 3 == 0)) red_rel(&g_hcnt[(idx * 8 + 2 * Q + (i & 1)) * 32]);
}
__device__ __forceinline__ uint32_t pack_bf16(float lo, float hi) {
  uint32_t r; asm("cvt.rn.bf16x2.f32 %0, %1, %2;" : "=r"(r) : "f"(hi), "f"(lo)); return r;
}
__device__ __forceinline__ float bf_lo(uint32_t w) { return __uint_as_float(w << 16); }
__device__ __forceinline__ float bf_hi(uint32_t w) { return __uint_as_float(w & 0xffff0000u); }
__device__ __forceinline__ uint32_t hmul2(uint32_t a, uint32_t b) {
  __nv_bfloat162 r = __hmul2_rn(*(__nv_bfloat162*)&a, *(__nv_bfloat162*)&b); return *(uint32_t*)&r;
}
__device__ __forceinline__ uint32_t hadd2(uint32_t a, uint32_t b) {
  __nv_bfloat162 r = __hadd2_rn(*(__nv_bfloat162*)&a, *(__nv_bfloat162*)&b); return *(uint32_t*)&r;
}
__device__ __forceinline__ float2 cmul(float2 a, float2 b) { return make_float2(a.x * b.x - a.y * b.y, a.x * b.y + a.y * b.x); }
__device__ __forceinline__ float2 cfma(float2 a, float2 b, float2 c) {
  return make_float2(fmaf(a.x, b.x, fmaf(-a.y, b.y, c.x)), fmaf(a.x, b.y, fmaf(a.y, b.x, c.y)));
}
template <int N> __device__ __forceinline__ void fence_regs(float (&a)[N]) {
#pragma unroll
  for (int i = 0; i < N; i++) asm volatile("" : "+f"(a[i])::"memory");
}
__device__ __forceinline__ bool elect_one() {
  uint32_t e; asm volatile("{\n.reg .pred P;\nelect.sync _|P, 0xffffffff;\nselp.u32 %0, 1, 0, P;\n}\n" : "=r"(e)); return e != 0;
}
__device__ __forceinline__ int tid_opaque() { int t; asm volatile("mov.u32 %0, %%tid.x;" : "=r"(t)); return t; }
struct Role { int T1, GP, side, m2, dg, cch0; bool last, has2; };
__device__ __forceinline__ Role unpack_role(int x) {
  Role r; r.T1 = x & 15; r.GP = (x >> 4) & 7; r.side = (x >> 7) & 1; r.m2 = (x >> 8) & 63; r.dg = (x >> 14) & 3;
  r.has2 = (x >> 16) & 1; r.last = r.T1 == NT1 - 1; r.cch0 = 160 * r.dg + r.m2; return r;
}
__device__ __forceinline__ Role fresh_role(int x) { asm volatile("" : "+r"(x)); return unpack_role(__shfl_sync(0xffffffffu, x, 0)); }
#define ROLE(x) const Role R_ = fresh_role(x); const int T1 = R_.T1, GP = R_.GP, side = R_.side, m2 = R_.m2, dg = R_.dg, cch0 = R_.cch0; \
  const bool last = R_.last, has2 = R_.has2; (void)T1; (void)GP; (void)side; (void)m2; (void)dg; (void)cch0; (void)last; (void)has2;
__device__ __forceinline__ int n_to_t(int n) {
  int T = n / 160, nl = n - T * 160;
  int L = (T == NT1 - 1) ? 32 : 40;
  return T * 160 + L * ((nl & 7) >> 1) + 2 * (nl >> 3) + (nl & 1);
}

template<int TA> __device__ __forceinline__ void wgmma_n160(float (&d)[80], uint32_t alo, uint32_t ahi, uint32_t blo, uint32_t bhi){
  asm volatile("{\n.reg .b64 da, db;\nmov.b64 da, {%80,%81};\nmov.b64 db, {%82,%83};\n"
    "wgmma.mma_async.sync.aligned.m64n160k16.f32.bf16.bf16 {%0, %1, %2, %3, %4, %5, %6, %7, %8, %9, %10, %11, %12, %13, %14, %15, %16, %17, %18, %19, %20, %21, %22, %23, %24, %25, %26, %27, %28, %29, %30, %31, %32, %33, %34, %35, %36, %37, %38, %39, %40, %41, %42, %43, %44, %45, %46, %47, %48, %49, %50, %51, %52, %53, %54, %55, %56, %57, %58, %59, %60, %61, %62, %63, %64, %65, %66, %67, %68, %69, %70, %71, %72, %73, %74, %75, %76, %77, %78, %79}, da, db, 1, 1, 1, %84, 0;\n}\n"
    : "+f"(d[0]), "+f"(d[1]), "+f"(d[2]), "+f"(d[3]), "+f"(d[4]), "+f"(d[5]), "+f"(d[6]), "+f"(d[7]), "+f"(d[8]), "+f"(d[9]), "+f"(d[10]), "+f"(d[11]), "+f"(d[12]), "+f"(d[13]), "+f"(d[14]), "+f"(d[15]), "+f"(d[16]), "+f"(d[17]), "+f"(d[18]), "+f"(d[19]), "+f"(d[20]), "+f"(d[21]), "+f"(d[22]), "+f"(d[23]), "+f"(d[24]), "+f"(d[25]), "+f"(d[26]), "+f"(d[27]), "+f"(d[28]), "+f"(d[29]), "+f"(d[30]), "+f"(d[31]), "+f"(d[32]), "+f"(d[33]), "+f"(d[34]), "+f"(d[35]), "+f"(d[36]), "+f"(d[37]), "+f"(d[38]), "+f"(d[39]), "+f"(d[40]), "+f"(d[41]), "+f"(d[42]), "+f"(d[43]), "+f"(d[44]), "+f"(d[45]), "+f"(d[46]), "+f"(d[47]), "+f"(d[48]), "+f"(d[49]), "+f"(d[50]), "+f"(d[51]), "+f"(d[52]), "+f"(d[53]), "+f"(d[54]), "+f"(d[55]), "+f"(d[56]), "+f"(d[57]), "+f"(d[58]), "+f"(d[59]), "+f"(d[60]), "+f"(d[61]), "+f"(d[62]), "+f"(d[63]), "+f"(d[64]), "+f"(d[65]), "+f"(d[66]), "+f"(d[67]), "+f"(d[68]), "+f"(d[69]), "+f"(d[70]), "+f"(d[71]), "+f"(d[72]), "+f"(d[73]), "+f"(d[74]), "+f"(d[75]), "+f"(d[76]), "+f"(d[77]), "+f"(d[78]), "+f"(d[79])
    : "r"(alo), "r"(ahi), "r"(blo), "r"(bhi), "n"(TA));
}
template<int N> __device__ __forceinline__ void wgmma_rs_hi(float (&d)[64], uint32_t a0, uint32_t a1, uint32_t a2, uint32_t a3, uint32_t blo);
template<> __device__ __forceinline__ void wgmma_rs_hi<16>(float (&d)[64], uint32_t a0, uint32_t a1, uint32_t a2, uint32_t a3, uint32_t blo){
  asm volatile("{\n.reg .b64 db;\nmov.b64 db, {%12,8};\nwgmma.mma_async.sync.aligned.m64n16k16.f32.bf16.bf16 {%0, %1, %2, %3, %4, %5, %6, %7}, {%8,%9,%10,%11}, db, 1, 1, 1, 0;\n}\n"
    : "+f"(d[56]), "+f"(d[57]), "+f"(d[58]), "+f"(d[59]), "+f"(d[60]), "+f"(d[61]), "+f"(d[62]), "+f"(d[63])
    : "r"(a0), "r"(a1), "r"(a2), "r"(a3), "r"(blo));
}
template<> __device__ __forceinline__ void wgmma_rs_hi<32>(float (&d)[64], uint32_t a0, uint32_t a1, uint32_t a2, uint32_t a3, uint32_t blo){
  asm volatile("{\n.reg .b64 db;\nmov.b64 db, {%20,8};\nwgmma.mma_async.sync.aligned.m64n32k16.f32.bf16.bf16 {%0, %1, %2, %3, %4, %5, %6, %7, %8, %9, %10, %11, %12, %13, %14, %15}, {%16,%17,%18,%19}, db, 1, 1, 1, 0;\n}\n"
    : "+f"(d[48]), "+f"(d[49]), "+f"(d[50]), "+f"(d[51]), "+f"(d[52]), "+f"(d[53]), "+f"(d[54]), "+f"(d[55]), "+f"(d[56]), "+f"(d[57]), "+f"(d[58]), "+f"(d[59]), "+f"(d[60]), "+f"(d[61]), "+f"(d[62]), "+f"(d[63])
    : "r"(a0), "r"(a1), "r"(a2), "r"(a3), "r"(blo));
}
template<> __device__ __forceinline__ void wgmma_rs_hi<48>(float (&d)[64], uint32_t a0, uint32_t a1, uint32_t a2, uint32_t a3, uint32_t blo){
  asm volatile("{\n.reg .b64 db;\nmov.b64 db, {%28,8};\nwgmma.mma_async.sync.aligned.m64n48k16.f32.bf16.bf16 {%0, %1, %2, %3, %4, %5, %6, %7, %8, %9, %10, %11, %12, %13, %14, %15, %16, %17, %18, %19, %20, %21, %22, %23}, {%24,%25,%26,%27}, db, 1, 1, 1, 0;\n}\n"
    : "+f"(d[40]), "+f"(d[41]), "+f"(d[42]), "+f"(d[43]), "+f"(d[44]), "+f"(d[45]), "+f"(d[46]), "+f"(d[47]), "+f"(d[48]), "+f"(d[49]), "+f"(d[50]), "+f"(d[51]), "+f"(d[52]), "+f"(d[53]), "+f"(d[54]), "+f"(d[55]), "+f"(d[56]), "+f"(d[57]), "+f"(d[58]), "+f"(d[59]), "+f"(d[60]), "+f"(d[61]), "+f"(d[62]), "+f"(d[63])
    : "r"(a0), "r"(a1), "r"(a2), "r"(a3), "r"(blo));
}
template<> __device__ __forceinline__ void wgmma_rs_hi<64>(float (&d)[64], uint32_t a0, uint32_t a1, uint32_t a2, uint32_t a3, uint32_t blo){
  asm volatile("{\n.reg .b64 db;\nmov.b64 db, {%36,8};\nwgmma.mma_async.sync.aligned.m64n64k16.f32.bf16.bf16 {%0, %1, %2, %3, %4, %5, %6, %7, %8, %9, %10, %11, %12, %13, %14, %15, %16, %17, %18, %19, %20, %21, %22, %23, %24, %25, %26, %27, %28, %29, %30, %31}, {%32,%33,%34,%35}, db, 1, 1, 1, 0;\n}\n"
    : "+f"(d[32]), "+f"(d[33]), "+f"(d[34]), "+f"(d[35]), "+f"(d[36]), "+f"(d[37]), "+f"(d[38]), "+f"(d[39]), "+f"(d[40]), "+f"(d[41]), "+f"(d[42]), "+f"(d[43]), "+f"(d[44]), "+f"(d[45]), "+f"(d[46]), "+f"(d[47]), "+f"(d[48]), "+f"(d[49]), "+f"(d[50]), "+f"(d[51]), "+f"(d[52]), "+f"(d[53]), "+f"(d[54]), "+f"(d[55]), "+f"(d[56]), "+f"(d[57]), "+f"(d[58]), "+f"(d[59]), "+f"(d[60]), "+f"(d[61]), "+f"(d[62]), "+f"(d[63])
    : "r"(a0), "r"(a1), "r"(a2), "r"(a3), "r"(blo));
}
template<> __device__ __forceinline__ void wgmma_rs_hi<80>(float (&d)[64], uint32_t a0, uint32_t a1, uint32_t a2, uint32_t a3, uint32_t blo){
  asm volatile("{\n.reg .b64 db;\nmov.b64 db, {%44,8};\nwgmma.mma_async.sync.aligned.m64n80k16.f32.bf16.bf16 {%0, %1, %2, %3, %4, %5, %6, %7, %8, %9, %10, %11, %12, %13, %14, %15, %16, %17, %18, %19, %20, %21, %22, %23, %24, %25, %26, %27, %28, %29, %30, %31, %32, %33, %34, %35, %36, %37, %38, %39}, {%40,%41,%42,%43}, db, 1, 1, 1, 0;\n}\n"
    : "+f"(d[24]), "+f"(d[25]), "+f"(d[26]), "+f"(d[27]), "+f"(d[28]), "+f"(d[29]), "+f"(d[30]), "+f"(d[31]), "+f"(d[32]), "+f"(d[33]), "+f"(d[34]), "+f"(d[35]), "+f"(d[36]), "+f"(d[37]), "+f"(d[38]), "+f"(d[39]), "+f"(d[40]), "+f"(d[41]), "+f"(d[42]), "+f"(d[43]), "+f"(d[44]), "+f"(d[45]), "+f"(d[46]), "+f"(d[47]), "+f"(d[48]), "+f"(d[49]), "+f"(d[50]), "+f"(d[51]), "+f"(d[52]), "+f"(d[53]), "+f"(d[54]), "+f"(d[55]), "+f"(d[56]), "+f"(d[57]), "+f"(d[58]), "+f"(d[59]), "+f"(d[60]), "+f"(d[61]), "+f"(d[62]), "+f"(d[63])
    : "r"(a0), "r"(a1), "r"(a2), "r"(a3), "r"(blo));
}
template<> __device__ __forceinline__ void wgmma_rs_hi<96>(float (&d)[64], uint32_t a0, uint32_t a1, uint32_t a2, uint32_t a3, uint32_t blo){
  asm volatile("{\n.reg .b64 db;\nmov.b64 db, {%52,8};\nwgmma.mma_async.sync.aligned.m64n96k16.f32.bf16.bf16 {%0, %1, %2, %3, %4, %5, %6, %7, %8, %9, %10, %11, %12, %13, %14, %15, %16, %17, %18, %19, %20, %21, %22, %23, %24, %25, %26, %27, %28, %29, %30, %31, %32, %33, %34, %35, %36, %37, %38, %39, %40, %41, %42, %43, %44, %45, %46, %47}, {%48,%49,%50,%51}, db, 1, 1, 1, 0;\n}\n"
    : "+f"(d[16]), "+f"(d[17]), "+f"(d[18]), "+f"(d[19]), "+f"(d[20]), "+f"(d[21]), "+f"(d[22]), "+f"(d[23]), "+f"(d[24]), "+f"(d[25]), "+f"(d[26]), "+f"(d[27]), "+f"(d[28]), "+f"(d[29]), "+f"(d[30]), "+f"(d[31]), "+f"(d[32]), "+f"(d[33]), "+f"(d[34]), "+f"(d[35]), "+f"(d[36]), "+f"(d[37]), "+f"(d[38]), "+f"(d[39]), "+f"(d[40]), "+f"(d[41]), "+f"(d[42]), "+f"(d[43]), "+f"(d[44]), "+f"(d[45]), "+f"(d[46]), "+f"(d[47]), "+f"(d[48]), "+f"(d[49]), "+f"(d[50]), "+f"(d[51]), "+f"(d[52]), "+f"(d[53]), "+f"(d[54]), "+f"(d[55]), "+f"(d[56]), "+f"(d[57]), "+f"(d[58]), "+f"(d[59]), "+f"(d[60]), "+f"(d[61]), "+f"(d[62]), "+f"(d[63])
    : "r"(a0), "r"(a1), "r"(a2), "r"(a3), "r"(blo));
}
template<> __device__ __forceinline__ void wgmma_rs_hi<112>(float (&d)[64], uint32_t a0, uint32_t a1, uint32_t a2, uint32_t a3, uint32_t blo){
  asm volatile("{\n.reg .b64 db;\nmov.b64 db, {%60,8};\nwgmma.mma_async.sync.aligned.m64n112k16.f32.bf16.bf16 {%0, %1, %2, %3, %4, %5, %6, %7, %8, %9, %10, %11, %12, %13, %14, %15, %16, %17, %18, %19, %20, %21, %22, %23, %24, %25, %26, %27, %28, %29, %30, %31, %32, %33, %34, %35, %36, %37, %38, %39, %40, %41, %42, %43, %44, %45, %46, %47, %48, %49, %50, %51, %52, %53, %54, %55}, {%56,%57,%58,%59}, db, 1, 1, 1, 0;\n}\n"
    : "+f"(d[8]), "+f"(d[9]), "+f"(d[10]), "+f"(d[11]), "+f"(d[12]), "+f"(d[13]), "+f"(d[14]), "+f"(d[15]), "+f"(d[16]), "+f"(d[17]), "+f"(d[18]), "+f"(d[19]), "+f"(d[20]), "+f"(d[21]), "+f"(d[22]), "+f"(d[23]), "+f"(d[24]), "+f"(d[25]), "+f"(d[26]), "+f"(d[27]), "+f"(d[28]), "+f"(d[29]), "+f"(d[30]), "+f"(d[31]), "+f"(d[32]), "+f"(d[33]), "+f"(d[34]), "+f"(d[35]), "+f"(d[36]), "+f"(d[37]), "+f"(d[38]), "+f"(d[39]), "+f"(d[40]), "+f"(d[41]), "+f"(d[42]), "+f"(d[43]), "+f"(d[44]), "+f"(d[45]), "+f"(d[46]), "+f"(d[47]), "+f"(d[48]), "+f"(d[49]), "+f"(d[50]), "+f"(d[51]), "+f"(d[52]), "+f"(d[53]), "+f"(d[54]), "+f"(d[55]), "+f"(d[56]), "+f"(d[57]), "+f"(d[58]), "+f"(d[59]), "+f"(d[60]), "+f"(d[61]), "+f"(d[62]), "+f"(d[63])
    : "r"(a0), "r"(a1), "r"(a2), "r"(a3), "r"(blo));
}
template<> __device__ __forceinline__ void wgmma_rs_hi<128>(float (&d)[64], uint32_t a0, uint32_t a1, uint32_t a2, uint32_t a3, uint32_t blo){
  asm volatile("{\n.reg .b64 db;\nmov.b64 db, {%68,8};\nwgmma.mma_async.sync.aligned.m64n128k16.f32.bf16.bf16 {%0, %1, %2, %3, %4, %5, %6, %7, %8, %9, %10, %11, %12, %13, %14, %15, %16, %17, %18, %19, %20, %21, %22, %23, %24, %25, %26, %27, %28, %29, %30, %31, %32, %33, %34, %35, %36, %37, %38, %39, %40, %41, %42, %43, %44, %45, %46, %47, %48, %49, %50, %51, %52, %53, %54, %55, %56, %57, %58, %59, %60, %61, %62, %63}, {%64,%65,%66,%67}, db, 1, 1, 1, 0;\n}\n"
    : "+f"(d[0]), "+f"(d[1]), "+f"(d[2]), "+f"(d[3]), "+f"(d[4]), "+f"(d[5]), "+f"(d[6]), "+f"(d[7]), "+f"(d[8]), "+f"(d[9]), "+f"(d[10]), "+f"(d[11]), "+f"(d[12]), "+f"(d[13]), "+f"(d[14]), "+f"(d[15]), "+f"(d[16]), "+f"(d[17]), "+f"(d[18]), "+f"(d[19]), "+f"(d[20]), "+f"(d[21]), "+f"(d[22]), "+f"(d[23]), "+f"(d[24]), "+f"(d[25]), "+f"(d[26]), "+f"(d[27]), "+f"(d[28]), "+f"(d[29]), "+f"(d[30]), "+f"(d[31]), "+f"(d[32]), "+f"(d[33]), "+f"(d[34]), "+f"(d[35]), "+f"(d[36]), "+f"(d[37]), "+f"(d[38]), "+f"(d[39]), "+f"(d[40]), "+f"(d[41]), "+f"(d[42]), "+f"(d[43]), "+f"(d[44]), "+f"(d[45]), "+f"(d[46]), "+f"(d[47]), "+f"(d[48]), "+f"(d[49]), "+f"(d[50]), "+f"(d[51]), "+f"(d[52]), "+f"(d[53]), "+f"(d[54]), "+f"(d[55]), "+f"(d[56]), "+f"(d[57]), "+f"(d[58]), "+f"(d[59]), "+f"(d[60]), "+f"(d[61]), "+f"(d[62]), "+f"(d[63])
    : "r"(a0), "r"(a1), "r"(a2), "r"(a3), "r"(blo));
}

__device__ __forceinline__ float shfl_sel(float a, float b, bool p, int src) {
  float r;
  asm volatile("{\n.reg .pred P;\n.reg .f32 t;\nsetp.ne.u32 P, %3, 0;\nselp.f32 t, %1, %2, P;\nshfl.sync.idx.b32 %0, t, %4, 0x1f, 0xffffffff;\n}\n"
               : "=f"(r) : "f"(a), "f"(b), "r"((uint32_t)p), "r"(src));
  return r;
}
struct CvCtx {
  uint32_t koff, zero, so[3];
  int srcA, srcB;
  bool wrapA, s3, kodd;
};
struct CvPipe { float Ep[2], keep[2], send[2]; };
template <int LO> __device__ __forceinline__ void cv_copy(float (&acc)[64]) {
#pragma unroll
  for (int i = LO; i < 64; i++) { float t; asm volatile("mov.b32 %0, %1;" : "=f"(t) : "f"(acc[i]) : "memory"); acc[i] = t; }
}
template <int G> __device__ __forceinline__ void cv_raw(uint32_t (&A)[4][4], uint32_t kaddr) {
#pragma unroll
  for (int i = 0; i < 4; i++) {
    const uint32_t a = kaddr + (4 * G + i) * 128;
    A[i][0] = lds32(a); A[i][1] = lds32(a + 4); A[i][3] = lds32(a + 8);
  }
}
__device__ __forceinline__ void cv_form(uint32_t (&A)[4][4], uint32_t sel) {
#pragma unroll
  for (int i = 0; i < 4; i++) {
    asm volatile("prmt.b32 %0, %0, %1, %2;" : "+r"(A[i][0]) : "r"(A[i][1]), "r"(sel));
    asm volatile("prmt.b32 %0, %1, %2, %3;" : "=r"(A[i][2]) : "r"(A[i][1]), "r"(A[i][3]), "r"(sel));
  }
}
#define CVV 2
template <int G> __device__ __forceinline__ void cv_step(float (&acc)[64], uint32_t (&A)[4][4], CvPipe& s, const CvCtx& c, uint32_t cb, uint32_t stg) {
  constexpr int JA = G - 1, JB = G - 2, NH = CVV == 1 ? 4 : (CVV == 3 ? 2 : 1);
  const uint32_t db0 = desc_lo(cb + CV_U + 192, CV_PL);
  uint32_t B[4][4];
  float ra[4], rb[2];
  if constexpr (G < 8) {
    wgmma_fence();
#pragma unroll
    for (int i = 0; i < NH; i++) wgmma_rs_hi<128 - 16 * (G & 7)>(acc, A[i][0], A[i][1], A[i][2], A[i][3], db0 - 4 * i);
    wgmma_commit();
    __syncwarp();
  }
  if constexpr (JA >= 0 && JA < 8) {
#pragma unroll
    for (int x = 0; x < 4; x++) {
      const int i = 8 * JA + 4 * (x >> 1) + 2 * (x & 1) + 1;
      ra[x] = shfl_sel(i >= 4 ? acc[i >= 4 ? i - 4 : 0] : 0.f, acc[i], c.wrapA, c.srcA);
    }
  }
  if constexpr (JB >= 0) {
#pragma unroll
    for (int h = 0; h < 2; h++) rb[h] = __shfl_sync(0xffffffffu, s.send[h], c.srcB);
  }
  if constexpr (G < 7) cv_raw<G + 1>(B, cb + c.koff);
  uint32_t z = 0;
  if constexpr (G < 8 && NH < 4) {
    __syncwarp();
    wgmma_fence();
#pragma unroll
    for (int i = NH; i < 4; i++) wgmma_rs_hi<128 - 16 * (G & 7)>(acc, A[i][0], A[i][1], A[i][2], A[i][3], db0 - 4 * i);
    wgmma_commit();
    asm volatile("mov.u32 %0, %%clock;" : "=r"(z)::"memory");
    z &= c.zero;
  }
  const float one = __uint_as_float(0x3f800000u | z);
  if constexpr (G < 7) cv_form(B, 0x5432u | z);
  if constexpr (JB >= 0) sts32(stg + ((c.so[JB / 3] >> (10 * (JB % 3))) & 0xffc), pack_bf16(fmaf(rb[0], one, s.keep[0]), fmaf(rb[1], one, s.keep[1])));
  if constexpr (JA >= 0 && JA < 8) {
#pragma unroll
    for (int h = 0; h < 2; h++) {
      const float ev = fmaf(ra[h], one, acc[8 * JA + 2 * h]), od = fmaf(ra[2 + h], one, acc[8 * JA + 4 + 2 * h]);
      s.send[h] = c.kodd ? ev : (c.s3 ? s.Ep[h] : od);
      s.keep[h] = c.kodd ? od : ev;
      s.Ep[h] = od;
    }
  }
  if constexpr (G < 8) { __syncwarp(); wgmma_wait<0>(); cv_copy<8 * (G & 7)>(acc); }
  if constexpr (G < 9) cv_step<G + 1>(acc, B, s, c, cb, stg);
}
__device__ __forceinline__ uint32_t cv_stage(int slot) { return sb + (slot < 4 ? 40960 + slot * 4096 : CV_OFF + CV_K); }
__device__ __forceinline__ void cv_setup(CvCtx& c) {
  const int tid = tid_opaque() & 127, w = tid >> 5, lane = tid & 31, r = lane >> 2, q = lane & 3;
  const int i0 = (r >> 1) & 1, i1 = r >> 2;
  c.koff = CV_K - 32 + 4 * (8 * (r >> 1) + 2 * w + (r & 1) + 2 * q);
  c.srcA = i0 ? lane - 8 : lane + 8 - q + ((q + 3) & 3);
  c.wrapA = i0 && q == 3;
  c.srcB = i1 == 0 ? (lane - q + 16 + ((q + 3) & 3)) : (lane - q - 16 + ((q + 1) & 3));
  c.s3 = (i1 == 1 && q == 3); c.kodd = (i1 == 1 && q < 3);
  c.zero = lds32(sb + EP_OFF + 24);
#pragma unroll
  for (int i = 0; i < 3; i++) c.so[i] = lds32(sb + SO_OFF + 512 * i + 4 * tid);
}
__device__ __forceinline__ void cv_table() {
  const int tid = tid_opaque() & 127, r = (tid & 31) >> 2, q = tid & 3;
  int t = 16 * (2 * (r < 4 ? q : 4 + ((q + 1) & 3)) + ((r >> 1) & 1)) + 4 * (tid >> 5) + 2 * (r & 1);
#pragma unroll 1
  for (int i = 0; i < 3; i++) {
    uint32_t v = 0;
#pragma unroll 1
    for (int x = 0; x < 3; x++, t += 256) {
      const int T = t / 160, tl = t - T * 160;
      const int qq = (T >= NT1 - 1) ? (tl >> 5) : (tl / 40);
      int ck = 20 * T + ((tl - qq * ((T >= NT1 - 1) ? 32 : 40)) >> 1);
      ck ^= (ck >> 2) & 6;
      v |= (uint32_t)((ck * 4 + qq) & 1023) << (10 * x + 2);
    }
    sts32(sb + SO_OFF + 512 * i + 4 * tid, v);
  }
}
__device__ __forceinline__ void conv_channel(int slot, const CvCtx& c) {
  const uint32_t cb = sb + CV_OFF + slot * CV_B;
  float acc[64];
  CvPipe s;
  s.Ep[0] = s.Ep[1] = 0.f;
  uint32_t A[4][4];
#pragma unroll
  for (int i = 0; i < 64; i++) acc[i] = 0.f;
  if (slot == 4) mbar_wait(bars + 8 * B_CVDONE);
  mbar_wait(bars + 8 * (B_CVFULL + slot));
  cv_raw<0>(A, cb + c.koff);
  {
    const uint32_t w0 = lds32(cb + CV_K);
    const uint32_t wp = __byte_perm(pack_bf16(bf_lo(w0) + __uint_as_float(lds32(sb + EP_OFF + 4 * slot)), 0.f), w0, 0x7610);
    if (c.koff == CV_K) A[0][0] = wp;
    if (c.koff == CV_K - 4) A[0][1] = wp;
    if (c.koff == CV_K - 8) A[0][3] = wp;
  }
  cv_form(A, 0x5432u);
  cv_copy<0>(acc);
  cv_step<0>(acc, A, s, c, cb, cv_stage(slot));
  fence_async_smem();
  mbar_arrive(bars + 8 * (B_CVDONE + slot));
}

__device__ __forceinline__ void kv_issue(const Params& p, int c, int m2, int dg) {
  const uint32_t fb = bars + 8 * (B_KV + c);
  mbar_expect_tx(fb, KV_PIECE);
  tma3(sb + KS_OFF + c * KV_PIECE, &p.mK, 160 * dg + 32 * c, 64 * m2 - 3, 0, fb);
  tma3(sb + KS_OFF + c * KV_PIECE + 4864, &p.mV, 160 * dg + 32 * c, 64 * m2 - 1, 0, fb);
}
__device__ __forceinline__ void kv_tile(int m, int dg, int c, int y) {
  const int lane = tid_opaque() & 31, tg = lane >> 3;
  const uint32_t pb = sb + KS_OFF + c * KV_PIECE + 32 * y + 4 * (lane & 7);
  const uint32_t ka = pb + tg * 1216, va = pb + 4864 + tg * 1088 + 64;
  const uint32_t kh = (m == 0 && tg > 0) ? ka - 192 : ka;
  uint32_t kk[19], u[16];
  const float4 t = lds128f(sb + TAP_OFF + 256 * c + 128 * y + 16 * (lane & 7));
#pragma unroll
  for (int i = 0; i < 19; i++) { kk[i] = lds32((i < 3 ? kh : ka) + i * 64); if (i >= 3) u[i - 3] = lds32(va + (i - 3) * 64); }
  uint8_t* dst = g_kv + ((160 * dg + 32 * c + 16 * y + 2 * (lane & 7)) * 4096 + (4 * m + tg) * 16);
  const uint32_t w0 = __byte_perm(__float_as_uint(t.x), __float_as_uint(t.z), 0x5410), w1 = __byte_perm(__float_as_uint(t.x), __float_as_uint(t.z), 0x7632);
  const uint32_t w2 = __byte_perm(__float_as_uint(t.y), __float_as_uint(t.w), 0x5410), w3 = __byte_perm(__float_as_uint(t.y), __float_as_uint(t.w), 0x7632);
#pragma unroll
  for (int i = 0; i < 16; i++) {
    uint32_t a = hmul2(kk[i], w3);
    a = hadd2(a, hmul2(kk[i + 1], w2)); a = hadd2(a, hmul2(kk[i + 2], w1)); a = hadd2(a, hmul2(kk[i + 3], w0));
    u[i] = hmul2(a, u[i]);
  }
#pragma unroll
  for (int e = 0; e < 2; e++)
#pragma unroll
    for (int f = 0; f < 2; f++) {
      uint32_t o[4];
#pragma unroll
      for (int qq = 0; qq < 4; qq++) o[qq] = __byte_perm(u[15 - 4 * qq - 2 * f], u[14 - 4 * qq - 2 * f], e ? 0x7632 : 0x5410);
      *(uint4*)(dst + e * 4096 + f * 2048) = make_uint4(o[0], o[1], o[2], o[3]);
    }
}
__device__ __forceinline__ void ln_finish(float s1, float s2, float& mean, float& rstd) {
  mean = s1 * (1.f / 640.f);
  const float v = fmaxf(fmaf(-mean, mean, s2 * (1.f / 640.f)), 0.f) + 1e-5f;
  asm("rsqrt.approx.ftz.f32 %0, %1;" : "=f"(rstd) : "f"(v));
}
__device__ __forceinline__ void stat_table(int T1, unsigned want, int l, int g, const uint4* x0, const uint4* x1, float (&xa)[2], float (&xb)[2]) {
  const int n = 32 * g + (tid_opaque() & 31);
  const uint4* rp = &g_stats[8 * l * SEQ + min(160 * T1 + n, SEQ - 1)];
  float a[4], b[4];
  uint32_t it = 0;
  while (true) {
    bool ok = true;
#pragma unroll
    for (int i = 0; i < 4; i++) ok &= (rec_ld(rp + SEQ * i, a[i], b[i]) == want);
    ok &= rec_ld(x0, xa[0], xb[0]) == want;
    ok &= rec_ld(x1, xa[1], xb[1]) == want;
    if (__all_sync(0xffffffffu, ok)) break;
    trap_if(++it > SPIN_LIMIT);
  }
  float m, rs;
  ln_finish((a[0] + a[1]) + (a[2] + a[3]), (b[0] + b[1]) + (b[2] + b[3]), m, rs);
  sts64f(sb + STAB_OFF + n * 8, rs, -m * rs);
}
__device__ __forceinline__ void stats_reduce(float (&a)[2], float (&b)[2], float (&mean)[2], float (&rstd)[2]) {
#pragma unroll
  for (int o = 1; o < 4; o <<= 1)
#pragma unroll
    for (int h = 0; h < 2; h++) { a[h] += __shfl_xor_sync(0xffffffffu, a[h], o); b[h] += __shfl_xor_sync(0xffffffffu, b[h], o); }
#pragma unroll
  for (int h = 0; h < 2; h++) ln_finish(a[h], b[h], mean[h], rstd[h]);
}

template <bool FIRST>
__device__ __forceinline__ void stats_publish(int which, int n0, int dg, unsigned tag, const float (&acc)[80]) {
  const int q = tid_opaque() & 3, h = q & 1;
  float s1[2] = {0.f, 0.f}, s2[2] = {0.f, 0.f}, t1[2] = {0.f, 0.f}, t2[2] = {0.f, 0.f};
#pragma unroll
  for (int j = 0; j < 20; j++)
#pragma unroll
    for (int y = 0; y < 2; y++) {
      const float a = acc[4 * j + 2 * y], b = acc[4 * j + 2 * y + 1];
      s1[y] += a; t1[y] += b; s2[y] = fmaf(a, a, s2[y]); t2[y] = fmaf(b, b, t2[y]);
    }
#pragma unroll
  for (int y = 0; y < 2; y++) { s1[y] += t1[y]; s2[y] += t2[y]; }
  float a = (h ? s1[1] : s1[0]) + __shfl_xor_sync(0xffffffffu, h ? s1[0] : s1[1], 1);
  float b = (h ? s2[1] : s2[0]) + __shfl_xor_sync(0xffffffffu, h ? s2[0] : s2[1], 1);
  a += __shfl_xor_sync(0xffffffffu, a, 2);
  b += __shfl_xor_sync(0xffffffffu, b, 2);
  if (FIRST) {
    rec_st(&g_stats[((q >> 1) * 4 + dg) * SEQ + n0 + 8 * h], a, b, q < 2 ? tag : tag - 1);
    rec_st(&g_stats[((q >> 1) * 4 + 8 + dg) * SEQ + n0 + 8 * h], a, b, tag - 1);
  } else if (q < 2) rec_st(&g_stats[(which * 4 + dg) * SEQ + n0 + 8 * h], a, b, tag);
}
__device__ __forceinline__ void stats_get(int which, int n0, unsigned tag, float (&mean)[2], float (&rstd)[2]) {
  const uint4* p0 = &g_stats[(which * 4 + (tid_opaque() & 3)) * SEQ + n0];
  float a[2], b[2];
  uint32_t it = 0;
  while (true) {
    const unsigned t0 = rec_ld(p0, a[0], b[0]), t1 = rec_ld(p0 + 8, a[1], b[1]);
    if (__all_sync(0xffffffffu, t0 == tag && t1 == tag)) break;
    trap_if(++it > SPIN_LIMIT);
  }
  stats_reduce(a, b, mean, rstd);
}
__device__ __forceinline__ void x0_load(float (&acc)[80]) {
  const int t = tid_opaque() & 127;
  const uint32_t xa = sb + XT_OFF + (16 * (t >> 5) + ((t & 31) >> 2)) * 320 + 8 * (t & 3);
  mbar_wait(bars + 8 * B_XT);
#pragma unroll
  for (int h = 0; h < 2; h++)
#pragma unroll
    for (int J = 0; J < 10; J++) {
      const float2 v = lds64f(xa + h * 2560 + 32 * J);
      const uint32_t x = __float_as_uint(v.x), y = __float_as_uint(v.y);
      acc[8 * J + 2 * h] = bf_lo(x); acc[8 * J + 2 * h + 1] = bf_hi(x);
      acc[8 * J + 4 + 2 * h] = bf_lo(y); acc[8 * J + 4 + 2 * h + 1] = bf_hi(y);
    }
}

template <bool FROM_X0>
__device__ __forceinline__ void dskip_init(float (&acc)[80], const float (&mean)[2], const float (&rstd)[2]) {
  const int t = tid_opaque() & 127;
  const uint32_t xa = sb + XT_OFF + (16 * (t >> 5) + ((t & 31) >> 2)) * 320 + 8 * (t & 3), da = sb + DTAB_OFF + 8 * (t & 3);
  float2 dw[10], xv[10][2];
#pragma unroll
  for (int J = 0; J < 2; J++) { dw[J] = lds64f(da + 32 * J); if (FROM_X0) { xv[J][0] = lds64f(xa + 32 * J); xv[J][1] = lds64f(xa + 2560 + 32 * J); } }
#pragma unroll
  for (int J = 0; J < 10; J++) {
    if (J + 2 < 10) { dw[J + 2] = lds64f(da + 32 * (J + 2)); if (FROM_X0) { xv[J + 2][0] = lds64f(xa + 32 * (J + 2)); xv[J + 2][1] = lds64f(xa + 2560 + 32 * (J + 2)); } }
#pragma unroll
    for (int x = 0; x < 8; x++) {
      const int h = (x >> 1) & 1;
      const uint32_t dwd = __float_as_uint(x < 4 ? dw[J].x : dw[J].y);
      const float tt = fmaf(rstd[h], (x & 1) ? bf_hi(dwd) : bf_lo(dwd), 1.f);
      float a = acc[8 * J + x];
      if (FROM_X0) { const uint32_t xw = __float_as_uint(x < 4 ? xv[J][h].x : xv[J][h].y); a = (x & 1) ? bf_hi(xw) : bf_lo(xw); }
      acc[8 * J + x] = FROM_X0 ? (a - mean[h]) * tt : fmaf(a, tt, -mean[h] * tt);
    }
  }
}

__global__ void __launch_bounds__(512, 1) fused_kernel(const __grid_constant__ Params p) {
  extern __shared__ __align__(1024) uint8_t smem_raw[];
  const int tid = threadIdx.x, lane = tid & 31;
  const int wid = __shfl_sync(0xffffffffu, tid >> 5, 0), wg = wid >> 2;
  unsigned smid; asm volatile("mov.u32 %0, %%smid;" : "=r"(smid));
  const int role = p.role[min(smid, 131u)];
  if (wid == 12) {
    const bool el = elect_one();
    if (el) {
      asm volatile("prefetch.tensormap [%0];" ::"l"(&p.mX) : "memory");
      asm volatile("prefetch.tensormap [%0];" ::"l"(&p.mB) : "memory");
#pragma unroll
      for (int k = 0; k < S1; k++) mbar_init(bars + 8 * (B_G1FULL + k), 1);
#pragma unroll
      for (int k = 0; k < 6; k++) mbar_init(bars + 8 * (B_XT + k), 1);
      asm volatile("fence.mbarrier_init.release.cluster;" ::: "memory");
    }
    if (role >= 0) {
      __syncwarp();
      asm volatile("bar.arrive 5, 288;" ::: "memory");
      const Role R = unpack_role(role);
      if (elect_one()) {
        TS(45);
#pragma unroll 1
        for (int k = 0; k < S1; k++) {
          const uint32_t fb = bars + 8 * (B_G1FULL + k);
          mbar_expect_tx(fb, G1_STAGE);
          tma4(sb + k * G1_STAGE + G1_XOFF, R.last ? &p.mXl : &p.mX, 64 * k, 0, 0, R.last ? 0 : 80 * R.T1, fb);
          tma5(sb + k * G1_STAGE, &p.mB, 64 * k, 0, 0, 4 * R.side, 2 * R.GP, fb);
        }
        if (R.has2) {
#pragma unroll 1
          for (int c = 0; c < KV0; c++) kv_issue(p, c, R.m2, R.dg);
          mbar_expect_tx(bars + 8 * B_XT, 20480);
#pragma unroll 1
          for (int h = 0; h < 2; h++) {
            const int ng = 8 * R.m2 + 4 * h, T = ng / 20;
            tma4(sb + XT_OFF + h * 10240, T == NT1 - 1 ? &p.mXtl : &p.mXt, 160 * R.dg, 0, 0, T == NT1 - 1 ? ng - 240 : ng + 60 * T, bars + 8 * B_XT);
          }
        }
        TS(44);
      }
      __syncwarp();
      bar_sync(6, 64);
    }
  }
  trap_if(smid >= 132 || smem_u32(smem_raw) != sb);
  if (role < 0) {
    if (wid == 0) {
      const unsigned tag = ld_rlx(g_epoch);
      uint32_t it = 0;
      while (!__all_sync(0xffffffffu, (int)(ld_rlx(&g_hcnt[(lane & 7) * 32]) - 40 * tag) >= 0)) { __nanosleep(500); trap_if(++it > SPIN_LIMIT); }
    }
    return;
  }
  float mean0[2] = {0.f, 0.f}, rstd0[2] = {0.f, 0.f};
  if (wg == 2 || wid == 14) {
    ROLE(role)
    const int c = wid == 14 ? 4 : wid - 8;
    const unsigned tag = ld_rlx(g_epoch);
    if (has2) {
      uint2 bv[2][5];
#pragma unroll
      for (int x = 0; x < 2; x++)
#pragma unroll
        for (int i = 0; i < 5; i++) bv[x][i] = ldv64((const uint2*)((x ? p.bim : p.bre) + (cch0 + 32 * c) * DM) + lane + 32 * i);
      float sv[2];
#pragma unroll
      for (int x = 0; x < 2; x++) {
        float a = 0.f;
#pragma unroll
        for (int i = 0; i < 5; i++) a += (bf_lo(bv[x][i].x) + bf_hi(bv[x][i].x)) + (bf_lo(bv[x][i].y) + bf_hi(bv[x][i].y));
        sv[x] = a;
      }
#pragma unroll
      for (int o = 16; o > 0; o >>= 1) { sv[0] += __shfl_xor_sync(0xffffffffu, sv[0], o); sv[1] += __shfl_xor_sync(0xffffffffu, sv[1], o); }
      if (lane < 2) rec_st(&g_sB[(cch0 + 32 * c) * 2 + lane], sv[0], sv[1], tag);
      if (tid == 256) TS(47);
      __syncwarp();
      bar_sync(8, 192);
      mbar_wait(bars + 8 * B_EP);
      mbar_wait(bars + 8 * (B_KV + c));
#pragma unroll 1
      for (int y = 0; y < 2; y++) kv_tile(m2, dg, c, y);
      __syncwarp();
      if (lane == 0) mbar_arrive(bars + 8 * B_PREP);
      if (tid == 352) TS(52);
      if (tid == 448) TS(51);
      if (wg == 2) {
        float xs[80];
        x0_load(xs);
        stats_publish<true>(0, 64 * m2 + 16 * c + (lane >> 2), dg, tag, xs);
        if (tid == 256) TS(31);
        mbar_wait(bars + 8 * (TABW ? B_PUB : B_PREP));
      } else {
        mbar_wait(bars + 8 * B_PREP);
        if (lane < 4) red_rel(&g_kvcnt[(dg * 4 + lane) * 32]);
        __syncwarp();
        if (lane == 0) { mbar_arrive(bars + 8 * B_PUB); TS(30); }
      }
    } else bar_sync(8, 192);
    {
      const uint4* x0 = wg == 2 ? &g_stats[(lane & 3) * SEQ + (has2 ? 64 * m2 : 0) + 16 * c + (lane >> 2)] : &g_sB[(128 * GP + 32 * side + lane) * 2];
      float xa[2], xb[2];
      stat_table(T1, tag, 0, c, x0, x0 + (wg == 2 ? 8 : 128), xa, xb);
      if (wg == 2) stats_reduce(xa, xb, mean0, rstd0);
      else {
#pragma unroll
        for (int i = 0; i < 2; i++) sts64f(sb + CTAB_OFF + (32 * i + lane) * 24 + 16, p.swap ? xb[i] : xa[i], p.swap ? xa[i] : xb[i]);
      }
      mbar_arrive(bars + 8 * B_STAB);
      if (tid == 448) TS(26);
    }
  } else if (wid == 15) {
    ROLE(role)
    const int ch = 128 * GP + 32 * side + lane;
    uint32_t r0 = ldv16(p.lre + ch), r1 = ldv16(p.lim + ch), r2 = ldv16(p.logdt + ch);
    const uint32_t r3 = ldv16(p.lre + ch + 64), r4 = ldv16(p.lim + ch + 64), r5 = ldv16(p.logdt + ch + 64);
#pragma unroll 1
    for (int i = 0; i < 2; i++) {
      const float lr = bf_lo(r0), li = bf_lo(r1);
      const float dt = __bfloat162float(__float2bfloat16_rn(expf(bf_lo(r2))));
      const float mag = expf(dt * lr);
      float sn, cs; sincospif(dt * li * 0.31830988618379067f, &sn, &cs);
      const float ar = mag * cs, ai = mag * sn;
      const float inv = 2.f / (lr * lr + li * li);
      const uint32_t ad = sb + CTAB_OFF + (32 * i + lane) * 24;
      sts64f(ad, ar, ai);
      sts64f(ad + 8, ((ar - 1.f) * lr + ai * li) * inv, (ai * lr - (ar - 1.f) * li) * inv);
      r0 = r3; r1 = r4; r2 = r5;
    }
    if (lane == 0) TS(46);
    __syncwarp();
    bar_sync(7, 64);
    mbar_arrive(bars + 8 * B_CTAB);
  } else if (wid == 13) {
    ROLE(role)
    uint4 tv[3];
    const uint32_t e0 = ld_rlx(g_epoch);
    const uint32_t e1 = ldv16(p.ssmD + min(cch0 + 32 * lane, 639));
    const uint4 dv = ldv128((const uint4*)(p.dskip + 160 * dg) + min(lane, 19));
#pragma unroll
    for (int i = 0; i < 3; i++) tv[i] = ldv128((const uint4*)(p.shiftk + 640 * dg) + min(lane + 32 * i, 79));
    sts128(sb + DTAB_OFF + 16 * min(lane, 19), dv);
#pragma unroll
    for (int i = 0; i < 3; i++) sts128(sb + TAP_OFF + 16 * min(lane + 32 * i, 79), tv[i]);
    if (lane < 7) sts32(sb + EP_OFF + 4 * lane, lane < 5 ? e1 << 16 : (lane == 5 ? e0 : 0u));
    __syncwarp();
    bar_sync(9, 64);
    mbar_arrive(bars + 8 * B_CTAB);
    if (lane == 0) { mbar_arrive(bars + 8 * B_EP); TS(53); }
  } else if (wid != 12) {
    if (elect_one()) {
      if (wid < 7) {
        const int b0 = wid < 4 ? 4 + 20 * wid : 85 + 21 * (wid - 4), cnt = wid < 4 ? 2 : 1;
#pragma unroll
        for (int i = 0; i < 21; i++) mbar_init(bars + 8 * (b0 + i), cnt);
      } else {
#pragma unroll
        for (int i = 0; i < 12; i++) mbar_init(bars + 8 * (B_CVDONE + i), (i == 5 || i == 6) ? 160 : 128);
        mbar_init(bars + 8 * B_CTAB, 192); mbar_init(bars + 8 * B_PREP, 5);
      }
      asm volatile("fence.mbarrier_init.release.cluster;" ::: "memory");
    }
    __syncwarp();
    bar_sync(5, 288);
    if (wid == 2) asm volatile("bar.arrive 8, 192;\nbar.arrive 6, 64;\nbar.arrive 9, 64;\nbar.arrive 7, 64;" ::: "memory");
    if (tid == 128) TS(0);
    if (wg == 1) { cv_table(); mbar_arrive(bars + 8 * B_CTAB); }
  }

  if (wid == 12) {
    ROLE(role)
    uint32_t dst = sb;
#pragma unroll 1
    for (int k = S1; k < 10; k++) {
      const uint32_t fb = bars + 8 * (B_G1FULL + k);
      mbar_wait(bars + 8 * (B_G1DONE + k - S1));
      if (elect_one()) {
        mbar_expect_tx(fb, 20480);
        tma4(dst + G1_XOFF, last ? &p.mXl : &p.mX, 64 * k, 0, 0, last ? 0 : 80 * T1, fb);
        mbar_expect_tx(fb, 16384);
        tma5(dst, &p.mB, 64 * k, 0, 0, 4 * side, 2 * GP, fb);
        if (has2 && k - S1 + KV0 < 5) kv_issue(p, k - S1 + KV0, m2, dg);
      }
      dst += G1_STAGE; if (k == 2 * S1 - 1) dst = sb;
    }
  } else if (wid == 15 && (role >> 16)) {
    ROLE(role)
    mbar_wait(bars + 8 * B_PREP);
#pragma unroll
    for (int c = 0; c < 5; c++) {
      const uint32_t cb = sb + CV_OFF + c * CV_B;
      sts128(lane < 8 ? cb + 16 * lane : (lane < 20 ? cb + CV_U + 16 * (lane - 8) : cb + CV_U + CV_PL + 16 * (lane - 20)), make_uint4(0, 0, 0, 0));
    }
    fence_async_smem();
    __syncwarp();
    const unsigned tag = lds32(sb + EP_OFF + 20);
    mbar_wait(bars + 8 * B_PUB);
    if (elect_one()) {
#pragma unroll
      for (int c = 0; c < TAP0; c++) {
        mbar_expect_tx(bars + 8 * (B_CVFULL + c), 4096);
        bulk_g2s(sb + CV_OFF + c * CV_B + CV_K, p.ssmk + (cch0 + 32 * c) * SEQ, 4096, bars + 8 * (B_CVFULL + c));
      }
    }
    cnt_poll(&g_kvcnt[(dg * 4 + (m2 >> 3)) * 32], 32 * tag);
    fence_async_global();
    if (elect_one()) {
      TS(28);
#pragma unroll 1
      for (int c = 0; c < 5; c++) {
        const uint32_t fb = bars + 8 * (B_CVFULL + c), cb = sb + CV_OFF + c * CV_B;
        mbar_expect_tx(fb, 4096);
        bulk_g2s(cb + CV_U + 192, g_kv + (cch0 + 32 * c) * 4096, 2048, fb);
        bulk_g2s(cb + CV_U + 192 + CV_PL, g_kv + (cch0 + 32 * c) * 4096 + 2048, 2048, fb);
        if (c >= TAP0) {
          mbar_expect_tx(fb, 4096);
          bulk_g2s(cb + CV_K, p.ssmk + (cch0 + 32 * c) * SEQ, 4096, fb);
        }
      }
      TS(54);
    }
    __syncwarp();
  }
  {
    const int w = wid & 3;
    if (wg == 2 && !(role >> 16)) {
      float xa[2], xb[2];
      mbar_wait(bars + 8 * (B_G1FULL + 11));
      stat_table(role & 15, lds32(sb + EP_OFF + 20), 1, w, g_stats, g_stats, xa, xb);
      mbar_arrive(bars + 8 * (B_STAB + 1));
    }
#pragma unroll 1
    for (int l = 0; l < 2; l++) {
      if (wg < 2) {
        float acc[80];
#pragma unroll
        for (int i = 0; i < 80; i++) acc[i] = 0.f;
        ROLE(role)
        const int tid = tid_opaque(), r = (tid & 31) >> 2, q = tid & 3;
        const int ch = 128 * GP + 64 * wg + 32 * side + 8 * w + r;
        const uint32_t ca = sb + CTAB_OFF + (32 * wg + 8 * w + r) * 24;
        float2 lam = make_float2(0.f, 0.f), p8 = lam, p16 = lam, pL = lam, p2L = lam;
        fence_regs(acc);
        {
          const uint32_t alo0 = (l == 0 ? desc_lo(sb, 16) : desc_lo(sb + G2_WOFF, 16)) + wg * 512;
          const uint32_t blo0 = l == 0 ? desc_lo(sb + G1_XOFF, 16) : desc_lo(sb + X1_OFF, 128);
          const uint32_t bhi = l == 0 ? desc_hi(1024, 1) : desc_hi(1024, 0), xstep = l == 0 ? 2 : 16;
          const uint32_t astep = l == 0 ? G1_STAGE >> 4 : 1024, bstep = l == 0 ? G1_STAGE >> 4 : 1280, aend = alo0 + (S1 + l) * astep;
          uint32_t alo = alo0, blo = blo0;
          uint32_t fb = bars + 8 * (B_G1FULL + 10 * l);
          mbar_wait(fb);
          if (tid == 0) TS(1 + 8 * l);
#pragma unroll 1
          for (int k = 0; k < 10; k++) {
            uint32_t ok; const uint32_t nb = k < 9 ? fb + 8 : fb;
            wgmma_fence();
#pragma unroll
            for (int kk = 0; kk < 4; kk++) {
              wgmma_n160<0>(acc, alo + kk * 2, desc_hi(1024, 1), blo + kk * xstep, bhi);
              if (kk == 0) ok = mbar_test(nb);
              if (kk == STG_KK && k == 9 && tid == 0) mbar_arrive(bars + 8 * (B_STG + l));
            }
            wgmma_commit();
            alo += astep; blo += bstep;
            if (blo == desc_lo(sb + G_OFF, 128)) blo = desc_lo(sb, 128);
            if (alo == aend) { alo = alo0; blo = blo0; }
            wgmma_wait<1>();
            if (k > 0 && (tid & 127) == 0) mbar_arrive(fb + 8 * (B_G1DONE - B_G1FULL - 1));
            if (!ok) mbar_wait(nb);
            if (wg == 1 && k == (l ? 8 - STG_D : 9 - STG0)) mbar_wait(bars + 8 * (B_STG + l));
            if (k == 3) {
              mbar_wait(bars + 8 * B_CTAB);
              lam = lds64f(ca);
              if (p.swap) lam.y = -lam.y;
              const float2 p2 = cmul(lam, lam), p4 = cmul(p2, p2);
              p8 = cmul(p4, p4); p16 = cmul(p8, p8);
              pL = cmul(p16, p16);
              if (!last) pL = cmul(pL, p8);
              p2L = cmul(pL, pL);
            }
            if (k == PAUSE_K && has2) mbar_wait(bars + 8 * B_PREP);
            fb += 8;
          }
        }
        mbar_wait(bars + 8 * (B_STAB + l));
        const float2 sB = lds64f(ca + 16);
        const unsigned tag = lds32(sb + EP_OFF + 20);
        wgmma_wait<0>();
        fence_regs(acc);
        if ((tid & 127) == 0) { mbar_arrive(bars + 8 * (B_G1DONE + 10 * l + 9)); TS(wg ? 17 + l : 2 + 8 * l); }
        float2 ec[3];
#pragma unroll
        for (int jj = 0; jj < 8; jj++)
#pragma unroll
          for (int y = 0; y < 3; y++) {
            if (y == 2 && (jj & 1)) continue;
            const int j = y == 2 ? 16 + (jj >> 1) : 8 * y + jj;
            const float4 st = lds128f(sb + STAB_OFF + (8 * j + 2 * q) * 8);
            acc[4 * j + 0] = fmaf(acc[4 * j + 0], st.x, st.y * sB.x);
            acc[4 * j + 2] = fmaf(acc[4 * j + 2], st.x, st.y * sB.y);
            acc[4 * j + 1] = fmaf(acc[4 * j + 1], st.z, st.w * sB.x);
            acc[4 * j + 3] = fmaf(acc[4 * j + 3], st.z, st.w * sB.y);
            ec[y] = jj == 0 ? make_float2(acc[4 * j + 0], acc[4 * j + 2]) : cfma(lam, ec[y], make_float2(acc[4 * j + 0], acc[4 * j + 2]));
            ec[y] = cfma(lam, ec[y], make_float2(acc[4 * j + 1], acc[4 * j + 3]));
          }
        float2 e = cfma(p16, ec[0], ec[1]);
        if (!last) e = cfma(p8, e, ec[2]);
        {
          float2 v = make_float2(__shfl_up_sync(0xffffffffu, e.x, 1, 4), __shfl_up_sync(0xffffffffu, e.y, 1, 4));
          if (q >= 1) e = cfma(pL, v, e);
          v = make_float2(__shfl_up_sync(0xffffffffu, e.x, 2, 4), __shfl_up_sync(0xffffffffu, e.y, 2, 4));
          if (q >= 2) e = cfma(p2L, v, e);
        }
        if (!last && (q == 3 || (q == 2 && l == 0))) rec_st(&g_E[((q == 3 ? l : 1) * NT1 + T1) * DM + ch], e.x, e.y, q == 3 ? tag : tag - 1);
        if (tid == 0) TS(3 + 8 * l);
        float2 ex = make_float2(__shfl_up_sync(0xffffffffu, e.x, 1, 4), __shfl_up_sync(0xffffffffu, e.y, 1, 4));
        if (q == 0) ex = make_float2(0.f, 0.f);
        const float2 coef = lds64f(ca + 8), lamc = make_float2(lam.x, p.swap ? lam.y : -lam.y);
        float m00 = coef.x, m01 = -coef.y, m10 = -coef.y, m11 = -coef.x;
        if (p.swap) { m00 = -coef.y; m01 = coef.x; m10 = -coef.x; m11 = -coef.y; }
        float2 pLq, p160q, p640;
        {
          const float2 p80 = last ? cmul(p2L, p16) : p2L, p160 = cmul(p80, p80), p320 = cmul(p160, p160), one = make_float2(1.f, 0.f);
          p640 = cmul(p320, p320);
          pLq = cmul((q & 1) ? pL : one, (q & 2) ? p2L : one);
          p160q = cmul((q & 1) ? p160 : one, (q & 2) ? p320 : one);
        }
        float2 c, ev[3];
        unsigned tg[3];
        const uint4* ep = &g_E[(l * NT1 + T1 - 1 - q) * DM + ch];
#pragma unroll
        for (int j = 0; j < 20; j++) {
          if (j == CPOLL) {
#pragma unroll
            for (int i = 0; i < 3; i++) {
              ev[i] = make_float2(0.f, 0.f); tg[i] = tag;
              if (T1 - 1 - q - 4 * i >= 0) tg[i] = rec_ld(ep - 4 * i * DM, ev[i].x, ev[i].y);
            }
          }
#pragma unroll
          for (int x = 0; x < 2; x++) {
            const float b0 = acc[4 * j + x], b1 = acc[4 * j + 2 + x];
            acc[4 * j + x] = fmaf(b0, m00, b1 * m01);
            acc[4 * j + 2 + x] = fmaf(b0, m10, b1 * m11);
          }
          if (j == CPOLL - 1 || j == 19) asm volatile("" : "+f"(acc[4 * j]), "+f"(acc[4 * j + 1]), "+f"(acc[4 * j + 2]), "+f"(acc[4 * j + 3])::"memory");
        }
        {
          uint32_t it = 0;
          while (__any_sync(0xffffffffu, tg[0] != tag || tg[1] != tag || tg[2] != tag)) {
#pragma unroll
            for (int i = 0; i < 3; i++)
              if (tg[i] != tag) tg[i] = rec_ld(ep - 4 * i * DM, ev[i].x, ev[i].y);
            trap_if(++it > SPIN_LIMIT);
          }
          c = cfma(p640, cfma(p640, ev[2], ev[1]), ev[0]);
          c = cmul(c, p160q);
          c.x += __shfl_xor_sync(0xffffffffu, c.x, 1); c.y += __shfl_xor_sync(0xffffffffu, c.y, 1);
          c.x += __shfl_xor_sync(0xffffffffu, c.x, 2); c.y += __shfl_xor_sync(0xffffffffu, c.y, 2);
        }
        if (tid == 0) TS(4 + 8 * l);
        if (wg == 1 && l >= HOLD0) mbar_wait(bars + 8 * (B_REL + l));
        c = cfma(pLq, c, ex);
        float2 hh = make_float2(fmaf(c.x, m00, c.y * m01), fmaf(c.x, m10, c.y * m11));
        uint8_t* hb = g_h + (size_t)l * (32 * 20 * 8192) + (10 * wg + 2 * GP) * 8192 + (4 * side + w) * 1024 + (tid_opaque() & 31) * 4;
#pragma unroll
        for (int j4 = 0; j4 < 5; j4++) {
          const int ng = 20 * T1 + 4 * j4;
          uint8_t* hp = hb + (size_t)(ng >> 3) * 163840 + (ng & 7) * 128;
#pragma unroll
          for (int jj = 0; jj < 4; jj++) {
            const int j = 4 * j4 + jj;
            const float2 h0 = cfma(lamc, hh, make_float2(acc[4 * j + 0], acc[4 * j + 2]));
            hh = cfma(lamc, h0, make_float2(acc[4 * j + 1], acc[4 * j + 3]));
            if (j4 < 4 || !last) {
              *(uint32_t*)(hp + jj * 128) = pack_bf16(h0.x, hh.x);
              *(uint32_t*)(hp + jj * 128 + 8192) = pack_bf16(h0.y, hh.y);
            }
          }
        }
        mbar_arrive(bars + 8 * (B_HST + 2 * l + wg));
        if (tid == 0) TS(5 + 8 * l);
        if (tid == 128) TS(l ? 25 : 19);
        if (l == 0 && wid == 4) {
          mbar_wait(bars + 8 * B_HST);
          mbar_wait(bars + 8 * (B_HST + 1));
          if ((tid & 31) < 8) h_release((tid >> 2) & 1, T1, tid & 3);
          __syncwarp();
          if (tid == 128) { mbar_arrive(bars + 8 * B_REL); TS(6); }
        }
      }
      if (l == 0) {
        ROLE(role)
        if (has2) {
          CvCtx cc;
          mbar_wait(bars + 8 * B_CTAB);
          cv_setup(cc);
          mbar_wait(bars + 8 * (B_G1DONE + 9));
#pragma unroll 1
          for (int c = (wg + 2) & 3; c < 5; c += 4) conv_channel(c, cc);
          if ((tid & 127) == 0) TS(wg == 2 ? 32 : (wg == 3 ? 50 : 7 + wg));
        }
      }
      if (wg >= 2) break;
    }
    if (wg == 3) {
    ROLE(role)
    const int pw = wid & 3, gpc = 2 * min(m2 >> 3, 3) + (dg >> 1);
    mbar_wait(bars + 8 * B_EP);
    const unsigned tag = lds32(sb + EP_OFF + 20);
    if (pw == 0) {
      if (elect_one()) {
#pragma unroll 1
        for (int l = 0; l < 2; l++) {
          uint32_t dst = sb;
          if (l == 1) {
            dst = sb + G2_WOFF;
#pragma unroll 1
            for (int k = 0; k < 10; k++) {
              mbar_wait(k > 4 ? bars + 8 * (B_G1DONE + 5 + k) : (has2 ? bars + 8 * (B_G2DONE + 14 + min(k, 3)) : bars + 8 * (B_G1DONE + 9)));
              mbar_expect_tx(bars + 8 * (B_G1FULL + 10 + k), 16384);
              tma5(dst, &p.mB, 64 * k, 0, 0, 4 * side, 2 * GP, bars + 8 * (B_G1FULL + 10 + k));
              dst += 16384; if (k == 4) dst = sb + G2_WOFF;
            }
          }
          if (has2) {
            const uint32_t fb2 = bars + 8 * (B_G2FULL + 20 * l), wb2 = bars + 8 * (B_G2DONE + 20 * l - S2);
            dst = sb + G2_WOFF + (WTAIL ? 4 * l * G2_WB : 0);
            int kc = 0;
#pragma unroll 1
            for (int k = 0; k < 20; k++) {
              mbar_wait(k >= S2 ? wb2 + 8 * k : bars + 8 * (l ? B_G1DONE + (WTAIL ? (k < 3 ? 15 + k : 13 + k) : 19) : (k == 5 ? B_XFREE : (k == 6 ? B_SFREE : B_REL))));
              mbar_expect_tx(fb2 + 8 * k, G2_WB);
              tma5(dst, &p.mCre + (k & 1), kc, 0, 0, 0, 10 * dg, fb2 + 8 * k);
              kc += (k & 1) << 7; if (k == 9) kc = 64;
              dst += G2_WB; if (dst == sb + G2_WOFF + S2 * G2_WB) dst = sb + G2_WOFF;
            }
          }
        }
      }
    } else if (pw == 1) {
#pragma unroll 1
      for (int l = 0; l < 2; l++) {
        if (l == 1) {
          mbar_wait(bars + 8 * (has2 ? B_G2DONE + 19 : B_G1DONE + 9));
          if (has2) mbar_wait(bars + 8 * B_UST);
          cnt_poll(&g_ucnt[gpc * 32], 128 * tag);
          fence_async_global();
          if (elect_one()) {
            TS(20);
            const int bytes = last ? 16384 : 20480;
            const uint8_t* src = g_u + T1 * 204800;
            uint32_t dst = sb + X1_OFF;
#pragma unroll 1
            for (int k = 0; k < 10; k++) {
              if (k > 4) mbar_wait(bars + 8 * (B_G1DONE + 5 + k));
              mbar_expect_tx(bars + 8 * (B_G1FULL + 10 + k), bytes);
              bulk_g2s(dst, src, bytes, bars + 8 * (B_G1FULL + 10 + k));
              src += 20480; dst += 20480; if (dst == sb + G_OFF) dst = sb; if (k == 4) dst = sb + X1_OFF;
            }
          }
          __syncwarp();
        }
        if (has2) {
          mbar_wait(bars + 8 * (B_HST + 2 * l));
          mbar_wait(bars + 8 * (B_G1DONE + 10 * l + 9));
          cnt_poll(&g_hcnt[(l * 16 + gpc) * 32], 40 * tag);
          fence_async_global();
          if (elect_one()) {
            TS(21 + 2 * l);
            const uint32_t fb2 = bars + 8 * (B_G2FULL + 20 * l), wb2 = bars + 8 * (B_G2DONE + 20 * l - S2);
            const uint8_t* src = g_h + (l * 32 + m2) * 163840;
            uint32_t dst = sb;
#pragma unroll 1
            for (int k = 0; k < 20; k++) {
              if (k >= 5) mbar_wait(k >= S2 ? wb2 + 8 * k : bars + 8 * B_SFREE);
              if (k == 10) { mbar_wait(bars + 8 * (B_H1 + l)); fence_async_global(); }
              mbar_expect_tx(fb2 + 8 * k, G2_XB);
              bulk_g2s(dst, src, G2_XB, fb2 + 8 * k);
              src += 8192; dst += G2_XB; if (dst == sb + S2 * G2_XB) dst = sb;
            }
          }
          __syncwarp();
        }
      }
    } else if (pw == 2) {
#pragma unroll 1
      for (int l = 0; l < 2; l++) {
        if (l == 1) {
          float xa[2], xb[2];
          mbar_wait(bars + 8 * (B_G1FULL + 11));
          stat_table(T1, tag, 1, 4, g_stats, g_stats, xa, xb);
          mbar_arrive(bars + 8 * (B_STAB + 1));
        }
#pragma unroll 1
        for (int w = 0; w < 2 * l; w++) {
          mbar_wait(bars + 8 * (B_HST + 2 + w));
          if (lane < 4) h_release(2 + w, T1, lane);
          __syncwarp();
          if (lane == 0) { if (w == 0) mbar_arrive(bars + 8 * (B_REL + 1)); TS(w ? 16 : 14); }
        }
        if (l == 0 && has2 && elect_one()) {
#pragma unroll 1
          for (int i = 0; i < 5; i++) {
            const int c = i < 3 ? i : 7 - i;
            mbar_wait(bars + 8 * (B_CVDONE + c));
            bulk_s2g(g_G + (cch0 + 32 * c) * 4096, cv_stage(c), 4096);
          }
          asm volatile("cp.async.bulk.commit_group;" ::: "memory");
          asm volatile("cp.async.bulk.wait_group.read 0;" ::: "memory");
          mbar_arrive(bars + 8 * B_SFREE);
          asm volatile("cp.async.bulk.wait_group 0;" ::: "memory");
          TS(48);
          fence_async_global();
          asm volatile("fence.acq_rel.gpu;" ::: "memory");
#pragma unroll
          for (int i = 0; i < 4; i++) red_rlx(&g_gcnt[(dg * 4 + i) * 32]);
          TS(49);
          mbar_arrive(bars + 8 * (B_GO + 1));
        }
        __syncwarp();
      }
    } else if (has2) {
      mbar_wait(bars + 8 * B_REL);
      if (elect_one()) {
        l2_prefetch(p.cre + (160 * dg + 5 * m2) * DM, 6400); l2_prefetch(p.cim + (160 * dg + 5 * m2) * DM, 6400);
        asm volatile("prefetch.tensormap [%0];" ::"l"(&p.mG) : "memory");
      }
      mbar_wait(bars + 8 * (B_HST + 1));
      flag_poll(&g_hcnt[(8 + gpc) * 32], 40 * tag);
      if (lane == 0) { mbar_arrive(bars + 8 * B_H1); TS(22); }
      mbar_wait(bars + 8 * (B_GO + 1));
      flag_poll(&g_gcnt[(dg * 4 + (m2 >> 3)) * 32], 32 * tag);
      fence_async_global();
      if (elect_one()) {
        TS(29);
        mbar_expect_tx(bars + 8 * B_GFULL, 20480);
        tma5(sb + G_OFF, &p.mG, 64 * m2, 0, 0, 0, 10 * dg, bars + 8 * B_GFULL);
      }
      mbar_wait(bars + 8 * (B_HST + 3));
      cnt_poll(&g_hcnt[(24 + gpc) * 32], 40 * tag);
      if (lane == 0) { mbar_arrive(bars + 8 * (B_H1 + 1)); TS(24); }
    }
    } else if (wg == 2 && (role >> 16)) {
      float acc[80];
      float off[2] = {mean0[0], mean0[1]};
      const unsigned tag = lds32(sb + EP_OFF + 20);
      dskip_init<true>(acc, mean0, rstd0);
      mbar_arrive(bars + 8 * B_XFREE);
#pragma unroll 1
      for (int l = 0; l < 2; l++) {
        float mean[2], rstd[2];
        {
          uint32_t alo = desc_lo(sb, 1024), blo = desc_lo(sb + G2_WOFF, 16) + (WTAIL ? l * (G2_WB >> 2) : 0);
          uint32_t fb = bars + 8 * (B_G2FULL + 20 * l);
          fence_regs(acc);
          mbar_wait(bars + 8 * (B_CVDONE + 2));
          mbar_wait(bars + 8 * (B_CVDONE + 3));
          mbar_wait(fb);
          if (tid == 256) TS(33 + 6 * l);
#pragma unroll 1
          for (int k = 0; k < 20; k++) {
            if (l == TSL && (k & 3) == 3 && tid == 256) TS(56 + (k >> 2));
            uint32_t ok; const uint32_t nb = k < 19 ? fb + 8 : fb;
            wgmma_fence();
#pragma unroll
            for (int kk = 0; kk < 4; kk++) {
              wgmma_n160<1>(acc, alo + kk * 128, desc_hi(128, 0), blo + kk * 2, desc_hi(1024, 1));
              if (kk == 0) ok = mbar_test(nb);
            }
            wgmma_commit();
            alo += G2_XB >> 4; blo += G2_WB >> 4;
            if (alo == desc_lo(sb + S2 * G2_XB, 1024)) alo = desc_lo(sb, 1024);
            if (blo == desc_lo(sb + G_OFF, 16)) blo = desc_lo(sb + G2_WOFF, 16);
            wgmma_wait<1>();
            if (k > 0 && tid == 256) mbar_arrive(fb + 8 * (B_G2DONE - B_G2FULL - 1));
            if (!ok) mbar_wait(nb);
            fb += 8;
          }
          wgmma_wait<0>();
          fence_regs(acc);
          if (tid == 256) TS(34 + 6 * l);
          if (tid == 256) mbar_arrive(bars + 8 * (B_G2DONE + 20 * l + 19));
        }
        ROLE(role)
        const int tq = tid_opaque() & 31, n0 = 64 * m2 + 16 * w + (tq >> 2);
        stats_publish<false>(2 * l + 1, n0, dg, tag, acc);
        uint32_t gf[10][4];
        mbar_wait(bars + 8 * B_GFULL);
        const uint32_t ga = sb + G_OFF + (8 * (tq >> 4) + (tq & 7)) * 128 + (((2 * w + ((tq >> 3) & 1)) ^ ((2 * m2) & 6) ^ (tq & 7)) << 4);
#pragma unroll
        for (int J = 0; J < 2; J++) ldsm4t(gf[J], ga + J * 2048);
        if (tid == 256) TS(35 + 6 * l);
        uint8_t* dst[2][2];
#pragma unroll
        for (int h = 0; h < 2; h++) {
          if (l == 0) {
            const int ng = 8 * m2 + 2 * w + h, T = ng / 20;
            uint8_t* ub = g_u + (T * 204800 + (ng - 20 * T) * 1024 + (tq & 2) * 64 + (tq & 28) * 4 + (tq & 1) * 8 + (5 * dg >> 1) * 20480);
            dst[h][1] = ub + ((dg & 1) ? 20480 - 512 : 0);
            dst[h][0] = ub + (dg & 1) * 512;
          } else {
            dst[h][0] = dst[h][1] = (uint8_t*)(p.out + (n_to_t(n0 + 8 * h) * DM + 160 * dg + 4 * (tq & 3)));
          }
        }
        stats_get(2 * l + 1, n0, tag, mean, rstd);
        if (tid == 256) TS(36 + 6 * l);
        off[0] += mean[0]; off[1] += mean[1];
        const float ov[2] = {l ? off[0] : 0.f, l ? off[1] : 0.f};
#pragma unroll
        for (int J = 0; J < 10; J++) {
          if (J + 2 < 10) ldsm4t(gf[J + 2 < 10 ? J + 2 : 0], ga + (J + 2) * 2048);
#pragma unroll
          for (int x = 0; x < 8; x++) {
            const int h = (x >> 1) & 1;
            const uint32_t gwd = gf[J][x >> 1];
            const float t = fmaf(rstd[h], (x & 1) ? bf_hi(gwd) : bf_lo(gwd), 1.f);
            acc[8 * J + x] = fmaf(acc[8 * J + x], t, fmaf(-mean[h], t, ov[h]));
          }
#pragma unroll
          for (int h = 0; h < 2; h++) {
            if (l == 0)
              *(uint2*)(dst[h][(J >> 1) & 1] + (J >> 2) * 20480 + (J & 3) * 256) =
                  make_uint2(pack_bf16(acc[8 * J + 2 * h], acc[8 * J + 2 * h + 1]), pack_bf16(acc[8 * J + 4 + 2 * h], acc[8 * J + 5 + 2 * h]));
            else
              *(float4*)(dst[h][0] + 64 * J) = make_float4(acc[8 * J + 2 * h], acc[8 * J + 2 * h + 1], acc[8 * J + 4 + 2 * h], acc[8 * J + 5 + 2 * h]);
          }
          __syncwarp();
        }
        if (l == 0) {
          bar_sync(3, 128);
          if (tid == 288) { TS(37); mbar_arrive(bars + 8 * B_UST); }
          if (tid < 264) red_rel(&g_ucnt[(tid & 7) * 32]);
          __syncwarp();
          if (tid == 256) TS(38);
          stats_publish<false>(2, n0, dg, tag, acc);
          mbar_wait(bars + 8 * (B_G1FULL + 11));
          float xa[2], xb[2];
          const uint4* x0 = &g_stats[(8 + (tq & 3)) * SEQ + n0];
          stat_table(T1, tag, 1, w, x0, x0 + 8, xa, xb);
          mbar_arrive(bars + 8 * (B_STAB + 1));
          if (tid == 256) TS(27);
          stats_reduce(xa, xb, mean, rstd);
          off[0] += mean[0]; off[1] += mean[1];
          mbar_wait(bars + 8 * (B_HST + 2));
          dskip_init<false>(acc, mean, rstd);
        } else {
          if (tid == 256) {
            TS(43);
            if (m2 == 31 && dg == 3) asm volatile("st.relaxed.gpu.global.u32 [%0], %1;" ::"l"(g_epoch), "r"(tag + 1) : "memory");
          }
        }
      }
    }
  }
}

typedef CUresult (*EncFn)(CUtensorMap*, CUtensorMapDataType, cuuint32_t, void*, const cuuint64_t*, const cuuint64_t*,
                          const cuuint32_t*, const cuuint32_t*, CUtensorMapInterleave, CUtensorMapSwizzle,
                          CUtensorMapL2promotion, CUtensorMapFloatOOBfill);

void encode(EncFn fn, CUtensorMap* m, const void* ptr, int rank, const cuuint64_t* dims, const cuuint64_t* strides, const cuuint32_t* box,
            CUtensorMapSwizzle swz = CU_TENSOR_MAP_SWIZZLE_128B) {
  cuuint32_t es[5] = {1, 1, 1, 1, 1};
  fn(m, CU_TENSOR_MAP_DATA_TYPE_BFLOAT16, rank, (void*)ptr, dims, strides, box, es, CU_TENSOR_MAP_INTERLEAVE_NONE,
     swz, (CUtensorMapL2promotion)(swz == CU_TENSOR_MAP_SWIZZLE_128B ? PROM_A : PROM_B), CU_TENSOR_MAP_FLOAT_OOB_FILL_NONE);
}

}

extern "C" void kernel_launch(void* const* d_in, const int* in_sizes, int n_in, void* d_out, int out_size) {
  (void)in_sizes; (void)n_in; (void)out_size;
  Params p;
  typedef const __nv_bfloat16* BP;
  p.x = (BP)d_in[0]; p.lre = (BP)d_in[1]; p.lim = (BP)d_in[2]; p.bre = (BP)d_in[3]; p.bim = (BP)d_in[4];
  p.cre = (BP)d_in[5]; p.cim = (BP)d_in[6]; p.logdt = (BP)d_in[7]; p.dskip = (BP)d_in[8];
  p.k = (BP)d_in[10]; p.v = (BP)d_in[11]; p.shiftk = (BP)d_in[12]; p.ssmk = (BP)d_in[13]; p.ssmD = (BP)d_in[14];
  p.out = (float*)d_out;
  for (int sm = 0; sm < 132; sm++) {
    const int tpc = sm >> 1, side = sm & 1;
    int gpc, gi;
    if (tpc < 32) { gpc = tpc & 7; gi = tpc >> 3; }
    else if (tpc < 60) { gpc = 1 + (tpc - 32) % 7; gi = 4 + (tpc - 32) / 7; }
    else if (tpc < 62) { gpc = tpc - 54; gi = 8; }
    else { gpc = 0; gi = tpc - 58; }
    const int pos = 8 * gpc + gi + (gpc == 7 ? 1 : 0);
    int T1, GP;
    if (pos < 52) { const int hh = pos / 26, x = pos - 26 * hh; T1 = x >> 1; GP = 2 * hh + (x & 1); }
    else { T1 = pos - 52; GP = 4; }
    const int m2 = 8 * (gpc >> 1) + gi, dg = 2 * (gpc & 1) + side;
    p.role[sm] = pos == 65 ? -1 : (T1 | (GP << 4) | (side << 7) | (m2 << 8) | (dg << 14) | ((gi < 8) << 16));
  }
  void* fnp = nullptr;
  cudaDriverEntryPointQueryResult qr;
  cudaGetDriverEntryPoint("cuTensorMapEncodeTiled", &fnp, cudaEnableDefault, &qr);
  EncFn fn = (EncFn)fnp;
  void* gG = nullptr;
  cudaGetSymbolAddress(&gG, g_G);
  const cuuint64_t RB = DM * 2;
  {
    p.swap = p.bim < p.bre;
    const char* lo = (const char*)(p.swap ? p.bim : p.bre); const char* hi = (const char*)(p.swap ? p.bre : p.bim);
    cuuint64_t dims[5] = {640, 8, 2, 8, 10}, st[4] = {RB, (cuuint64_t)(hi - lo), 8 * RB, 64 * RB}; cuuint32_t box[5] = {64, 8, 2, 4, 2};
    encode(fn, &p.mB, lo, 5, dims, st, box);
  }
  {
    cuuint64_t dims[5] = {640, 2, 4, 2, 40}, st[4] = {RB, 4 * RB, 2 * RB, 16 * RB}; cuuint32_t box[5] = {64, 2, 4, 2, 10};
    encode(fn, &p.mCre, p.cre, 5, dims, st, box); encode(fn, &p.mCim, p.cim, 5, dims, st, box);
    cuuint64_t dimg[5] = {2048, 2, 4, 2, 40}, stg[4] = {4096, 4 * 4096, 2 * 4096, 16 * 4096};
    encode(fn, &p.mG, gG, 5, dimg, stg, box);
  }
  {
    cuuint64_t dims[4] = {640, 2, 4, 900}, st[3] = {RB, 40 * RB, 2 * RB}; cuuint32_t box[4] = {64, 2, 4, 20};
    encode(fn, &p.mX, p.x, 4, dims, st, box);
    cuuint64_t diml[4] = {640, 2, 4, 16}, stl[3] = {RB, 32 * RB, 2 * RB};
    encode(fn, &p.mXl, p.x + (size_t)1920 * DM, 4, diml, stl, box);
    cuuint32_t boxt[4] = {160, 2, 4, 4};
    encode(fn, &p.mXt, p.x, 4, dims, st, boxt, CU_TENSOR_MAP_SWIZZLE_NONE);
    encode(fn, &p.mXtl, p.x + (size_t)1920 * DM, 4, diml, stl, boxt, CU_TENSOR_MAP_SWIZZLE_NONE);
    cuuint64_t dk[3] = {640, 2000, 4}, sk[2] = {RB, 16 * RB}; cuuint32_t bk[3] = {32, 19, 4}, bv[3] = {32, 17, 4};
    encode(fn, &p.mK, p.k, 3, dk, sk, bk, CU_TENSOR_MAP_SWIZZLE_NONE);
    encode(fn, &p.mV, p.v, 3, dk, sk, bv, CU_TENSOR_MAP_SWIZZLE_NONE);
  }
  cudaFuncSetAttribute(fused_kernel, cudaFuncAttributeMaxDynamicSharedMemorySize, SMEM_BYTES);
  cudaLaunchConfig_t cfg = {};
  cfg.gridDim = dim3(132); cfg.blockDim = dim3(512); cfg.dynamicSmemBytes = SMEM_BYTES; cfg.stream = cudaStreamPerThread;
  cudaLaunchKernelEx(&cfg, fused_kernel, p);
}
```

```cpp
#include <cuda_runtime.h>
#include <cuda.h>
#include <cuda_bf16.h>
#include <stdint.h>

namespace {

constexpr int SEQ = 2048, DM = 640;
constexpr int NT1 = 13;
#define EXP 0
#define WPF1 3
#define WPF2 7
#define CPOLL 10
#define KV0 5
#define TAP0 2
#define PROM_A 2
#define PROM_B 2
#define XFIRST 0
#define TAPLATE 1
#define STG_D 3
#define STG_KK 1
#define HOLD0 1
#define WREL 0
#define UREL 1
#define TSL 1
#define TABW 0
#define STG0 3
#define WTAIL 1
#define PAUSE_K 4
constexpr uint32_t SPIN_LIMIT = 1u << 22;

__device__ __align__(1024) uint8_t g_h[2 * 32 * 20 * 8192];
__device__ __align__(1024) uint8_t g_u[NT1 * 10 * 20480];
__device__ __align__(1024) uint8_t g_kv[DM * 4096];
__device__ __align__(1024) uint8_t g_G[DM * 4096];
__device__ __align__(128) uint4 g_E[2 * NT1 * DM];
__device__ __align__(128) uint4 g_stats[4 * 4 * SEQ];
__device__ __align__(128) uint4 g_sB[DM * 2];
__device__ __align__(128) unsigned g_hcnt[2 * 2 * 8 * 32];
__device__ __align__(128) unsigned g_ucnt[8 * 32];
__device__ __align__(128) unsigned g_kvcnt[16 * 32];
__device__ __align__(128) unsigned g_gcnt[16 * 32];
__device__ __align__(128) unsigned g_epoch[32] = {1};
#define TS(i) do {} while (0)

struct Params {
  CUtensorMap mB, mCre, mCim, mX, mXl, mG, mK, mV, mXt, mXtl;
  const __nv_bfloat16 *x, *lre, *lim, *bre, *bim, *cre, *cim, *logdt, *dskip, *k, *v, *shiftk, *ssmk, *ssmD;
  float* out;
  int swap;
  int role[132];
};

constexpr uint32_t sb = 1024;
constexpr uint32_t G1_STAGE = 36864, G1_XOFF = 16384;
constexpr int S1 = 4;
constexpr uint32_t XT_OFF = 159744, KS_OFF = 180224, KV_PIECE = 9216;
constexpr uint32_t G2_XB = 8192, G2_WB = 20480, G2_WOFF = 57344, G_OFF = 200704;
constexpr uint32_t X1_OFF = 139264;
constexpr int S2 = 7;
constexpr uint32_t CV_OFF = KS_OFF, CV_K = 128, CV_PL = 2240, CV_U = CV_K + 4096, CV_B = KV_PIECE;
constexpr uint32_t MISC = 226304;
constexpr uint32_t BAR_OFF = MISC;
constexpr int B_G1FULL = 0, B_G1DONE = 20, B_G2FULL = 40, B_CVFULL = 80  ,
              B_G2DONE = 85, B_GFULL = 125, B_EP = 126, B_H1 = 127  , B_STG = 134  , B_REL = 136  , B_SFREE = 138, B_UST = 142,
              B_GO = 139  , B_PUB = 147,
              B_CVDONE = 148  , B_STAB = 153  , B_XFREE = 155, B_HST = 156  ,
              B_CTAB = 160, B_PREP = 161, B_XT = 162, B_KV = 163  ;
constexpr uint32_t bars = sb + BAR_OFF;
constexpr uint32_t STAB_OFF = MISC + 1344;
constexpr uint32_t CTAB_OFF = STAB_OFF + 1280;
constexpr uint32_t DTAB_OFF = CTAB_OFF + 1536;
constexpr uint32_t EP_OFF = DTAB_OFF + 320;
constexpr uint32_t SO_OFF = EP_OFF + 32;
constexpr uint32_t TAP_OFF = 147456;
constexpr uint32_t SMEM_BYTES = 232448;
static_assert(SO_OFF + 1536 <= SMEM_BYTES, "smem");

__device__ __forceinline__ void trap_if(bool c) { asm volatile("{\n.reg .pred p;\nsetp.ne.u32 p, %0, 0;\n@p trap;\n}\n" ::"r"((uint32_t)c)); }
__device__ __forceinline__ uint32_t smem_u32(const void* p) { return (uint32_t)__cvta_generic_to_shared(p); }
__device__ __forceinline__ void mbar_init(uint32_t bar, int cnt) { asm volatile("mbarrier.init.shared::cta.b64 [%0], %1;" ::"r"(bar), "r"(cnt) : "memory"); }
__device__ __forceinline__ void mbar_expect_tx(uint32_t bar, int bytes) { asm volatile("mbarrier.arrive.expect_tx.shared::cta.b64 _, [%0], %1;" ::"r"(bar), "r"(bytes) : "memory"); }
__device__ __forceinline__ void mbar_arrive(uint32_t bar) { asm volatile("mbarrier.arrive.shared::cta.b64 _, [%0];" ::"r"(bar) : "memory"); }
__device__ __forceinline__ void mbar_wait(uint32_t bar) {
  asm volatile(
      "{\n.reg .pred p;\n.reg .u32 c;\nmov.u32 c, 0;\n"
      "W_%=:\nmbarrier.try_wait.parity.shared::cta.b64 p, [%0], 0;\n@p bra D_%=;\n"
      "add.u32 c, c, 1;\nsetp.lt.u32 p, c, %1;\n@p bra W_%=;\ntrap;\nD_%=:\n}\n" ::"r"(bar), "n"(SPIN_LIMIT) : "memory");
}
__device__ __forceinline__ uint32_t mbar_test(uint32_t bar) {
  uint32_t ok;
  asm volatile("{\n.reg .pred p;\nmbarrier.test_wait.parity.shared::cta.b64 p, [%1], 0;\nselp.u32 %0, 1, 0, p;\n}\n" : "=r"(ok) : "r"(bar) : "memory");
  return ok;
}
__device__ __forceinline__ void tma3(uint32_t dst, const CUtensorMap* m, int c0, int c1, int c2, uint32_t bar) {
  asm volatile("cp.async.bulk.tensor.3d.shared::cluster.global.mbarrier::complete_tx::bytes [%0], [%1, {%3,%4,%5}], [%2];"
               ::"r"(dst), "l"(m), "r"(bar), "r"(c0), "r"(c1), "r"(c2) : "memory");
}
__device__ __forceinline__ void tma4(uint32_t dst, const CUtensorMap* m, int c0, int c1, int c2, int c3, uint32_t bar) {
  asm volatile("cp.async.bulk.tensor.4d.shared::cluster.global.mbarrier::complete_tx::bytes [%0], [%1, {%3,%4,%5,%6}], [%2];"
               ::"r"(dst), "l"(m), "r"(bar), "r"(c0), "r"(c1), "r"(c2), "r"(c3) : "memory");
}
__device__ __forceinline__ void tma5(uint32_t dst, const CUtensorMap* m, int c0, int c1, int c2, int c3, int c4, uint32_t bar) {
  asm volatile("cp.async.bulk.tensor.5d.shared::cluster.global.mbarrier::complete_tx::bytes [%0], [%1, {%3,%4,%5,%6,%7}], [%2];"
               ::"r"(dst), "l"(m), "r"(bar), "r"(c0), "r"(c1), "r"(c2), "r"(c3), "r"(c4) : "memory");
}
__device__ __forceinline__ void bulk_g2s(uint32_t dst, const void* src, int bytes, uint32_t bar) {
  asm volatile("cp.async.bulk.shared::cluster.global.mbarrier::complete_tx::bytes [%0], [%1], %2, [%3];"
               ::"r"(dst), "l"(src), "r"(bytes), "r"(bar) : "memory");
}
__device__ __forceinline__ void bulk_s2g(void* dst, uint32_t src, int bytes) {
  asm volatile("cp.async.bulk.global.shared::cta.bulk_group [%0], [%1], %2;" ::"l"(dst), "r"(src), "r"(bytes) : "memory");
}
__device__ __forceinline__ void l2_prefetch(const void* src, int bytes) {
  asm volatile("cp.async.bulk.prefetch.L2.global [%0], %1;" ::"l"(src), "r"(bytes) : "memory");
}
__device__ __forceinline__ void wgmma_fence() { asm volatile("wgmma.fence.sync.aligned;" ::: "memory"); }
__device__ __forceinline__ void wgmma_commit() { asm volatile("wgmma.commit_group.sync.aligned;" ::: "memory"); }
template <int N> __device__ __forceinline__ void wgmma_wait() { asm volatile("wgmma.wait_group.sync.aligned %0;" ::"n"(N) : "memory"); }
__host__ __device__ constexpr uint32_t desc_lo(uint32_t addr, uint32_t lbo) { return ((addr & 0x3FFFF) >> 4) | ((lbo >> 4) << 16); }
__host__ __device__ constexpr uint32_t desc_hi(uint32_t sbo, uint32_t swz) { return (sbo >> 4) | (swz << 30); }
__device__ __forceinline__ void bar_sync(int id, int n) { asm volatile("bar.sync %0, %1;" ::"r"(id), "r"(n) : "memory"); }
__device__ __forceinline__ uint32_t lds32(uint32_t a) { uint32_t v; asm volatile("ld.shared.u32 %0, [%1];" : "=r"(v) : "r"(a) : "memory"); return v; }
__device__ __forceinline__ float2 lds64f(uint32_t a) { float2 v; asm volatile("ld.shared.v2.f32 {%0,%1}, [%2];" : "=f"(v.x), "=f"(v.y) : "r"(a) : "memory"); return v; }
__device__ __forceinline__ float4 lds128f(uint32_t a) { float4 v; asm volatile("ld.shared.v4.f32 {%0,%1,%2,%3}, [%4];" : "=f"(v.x), "=f"(v.y), "=f"(v.z), "=f"(v.w) : "r"(a) : "memory"); return v; }
__device__ __forceinline__ void ldsm4t(uint32_t (&r)[4], uint32_t a) {
  asm volatile("ldmatrix.sync.aligned.m8n8.x4.trans.shared.b16 {%0,%1,%2,%3}, [%4];" : "=r"(r[0]), "=r"(r[1]), "=r"(r[2]), "=r"(r[3]) : "r"(a) : "memory");
}
__device__ __forceinline__ uint4 ldv128(const void* a) { uint4 v; asm volatile("ld.global.nc.v4.u32 {%0,%1,%2,%3}, [%4];" : "=r"(v.x), "=r"(v.y), "=r"(v.z), "=r"(v.w) : "l"(a) : "memory"); return v; }
__device__ __forceinline__ uint2 ldv64(const void* a) { uint2 v; asm volatile("ld.global.nc.v2.u32 {%0,%1}, [%2];" : "=r"(v.x), "=r"(v.y) : "l"(a) : "memory"); return v; }
__device__ __forceinline__ uint32_t ldv16(const void* a) { uint32_t v; asm volatile("ld.global.nc.u16 %0, [%1];" : "=r"(v) : "l"(a) : "memory"); return v; }
__device__ __forceinline__ void sts128(uint32_t a, uint4 v) { asm volatile("st.shared.v4.u32 [%0], {%1,%2,%3,%4};" ::"r"(a), "r"(v.x), "r"(v.y), "r"(v.z), "r"(v.w) : "memory"); }
__device__ __forceinline__ void sts32(uint32_t a, uint32_t v) { asm volatile("st.shared.u32 [%0], %1;" ::"r"(a), "r"(v) : "memory"); }
__device__ __forceinline__ void sts64f(uint32_t a, float x, float y) { asm volatile("st.shared.v2.f32 [%0], {%1,%2};" ::"r"(a), "f"(x), "f"(y) : "memory"); }
__device__ __forceinline__ void red_rlx(unsigned* p) { asm volatile("red.relaxed.gpu.global.add.u32 [%0], 1;" ::"l"(p) : "memory"); }
__device__ __forceinline__ void red_rel(unsigned* p) { asm volatile("red.release.gpu.global.add.u32 [%0], 1;" ::"l"(p) : "memory"); }
__device__ __forceinline__ void fence_async_global() { asm volatile("fence.proxy.async.global;" ::: "memory"); }
__device__ __forceinline__ void fence_async_smem() { asm volatile("fence.proxy.async.shared::cta;" ::: "memory"); }
__device__ __forceinline__ void rec_st(uint4* p, float a, float b, unsigned tag) {
  asm volatile("{\n.reg .b128 t;\n.reg .b64 lo, hi;\nmov.b64 lo, {%1,%2};\nmov.b64 hi, {%3,%3};\nmov.b128 t, {lo,hi};\n"
               "st.relaxed.gpu.global.b128 [%0], t;\n}\n" ::"l"(p), "r"(__float_as_uint(a)), "r"(__float_as_uint(b)), "r"(tag) : "memory");
}
__device__ __forceinline__ unsigned rec_ld(const uint4* p, float& a, float& b) {
  unsigned x, y, t;
  asm volatile("{\n.reg .b128 t;\n.reg .b64 lo, hi;\n.reg .b32 u;\nld.relaxed.gpu.global.b128 t, [%3];\nmov.b128 {lo,hi}, t;\n"
               "mov.b64 {%0,%1}, lo;\nmov.b64 {%2,u}, hi;\n}\n" : "=r"(x), "=r"(y), "=r"(t) : "l"(p) : "memory");
  a = __uint_as_float(x); b = __uint_as_float(y);
  return t;
}
__device__ __forceinline__ unsigned ld_rlx(const unsigned* p) { unsigned v; asm volatile("ld.relaxed.gpu.global.u32 %0, [%1];" : "=r"(v) : "l"(p) : "memory"); return v; }
__device__ __forceinline__ void flag_poll(const unsigned* p, unsigned target) {
  uint32_t it = 0;
  while (!__all_sync(0xffffffffu, (int)(ld_rlx(p) - target) >= 0)) { trap_if(++it > SPIN_LIMIT); }
  asm volatile("fence.acquire.gpu;" ::: "memory");
}
__device__ __forceinline__ void cnt_poll(const unsigned* p, unsigned target) {
  unsigned a = ld_rlx(p); __nanosleep(100);
  unsigned b = ld_rlx(p); __nanosleep(100);
  unsigned c = ld_rlx(p);
  uint32_t it = 0;
  while (true) {
    if (__all_sync(0xffffffffu, (int)(a - target) >= 0)) break;
    a = ld_rlx(p);
    if (__all_sync(0xffffffffu, (int)(b - target) >= 0)) break;
    b = ld_rlx(p);
    if (__all_sync(0xffffffffu, (int)(c - target) >= 0)) break;
    c = ld_rlx(p);
    trap_if(++it > SPIN_LIMIT);
  }
  asm volatile("fence.acquire.gpu;" ::: "memory");
}
__device__ __forceinline__ void h_release(int idx, int T, int i) {
  const int Q = (i & 2) ? (T + 2) / 3 - 1 : T / 3;
  if (Q >= 0 && Q < 4 && ((i & 2) == 0 || T % 3 == 0)) red_rel(&g_hcnt[(idx * 8 + 2 * Q + (i & 1)) * 32]);
}
__device__ __forceinline__ uint32_t pack_bf16(float lo, float hi) {
  uint32_t r; asm("cvt.rn.bf16x2.f32 %0, %1, %2;" : "=r"(r) : "f"(hi), "f"(lo)); return r;
}
__device__ __forceinline__ float bf_lo(uint32_t w) { return __uint_as_float(w << 16); }
__device__ __forceinline__ float bf_hi(uint32_t w) { return __uint_as_float(w & 0xffff0000u); }
__device__ __forceinline__ uint32_t hmul2(uint32_t a, uint32_t b) {
  __nv_bfloat162 r = __hmul2_rn(*(__nv_bfloat162*)&a, *(__nv_bfloat162*)&b); return *(uint32_t*)&r;
}
__device__ __forceinline__ uint32_t hadd2(uint32_t a, uint32_t b) {
  __nv_bfloat162 r = __hadd2_rn(*(__nv_bfloat162*)&a, *(__nv_bfloat162*)&b); return *(uint32_t*)&r;
}
__device__ __forceinline__ float2 cmul(float2 a, float2 b) { return make_float2(a.x * b.x - a.y * b.y, a.x * b.y + a.y * b.x); }
__device__ __forceinline__ float2 cfma(float2 a, float2 b, float2 c) {
  return make_float2(fmaf(a.x, b.x, fmaf(-a.y, b.y, c.x)), fmaf(a.x, b.y, fmaf(a.y, b.x, c.y)));
}
template <int N> __device__ __forceinline__ void fence_regs(float (&a)[N]) {
#pragma unroll
  for (int i = 0; i < N; i++) asm volatile("" : "+f"(a[i])::"memory");
}
__device__ __forceinline__ bool elect_one() {
  uint32_t e; asm volatile("{\n.reg .pred P;\nelect.sync _|P, 0xffffffff;\nselp.u32 %0, 1, 0, P;\n}\n" : "=r"(e)); return e != 0;
}
__device__ __forceinline__ int tid_opaque() { int t; asm volatile("mov.u32 %0, %%tid.x;" : "=r"(t)); return t; }
struct Role { int T1, GP, side, m2, dg, cch0; bool last, has2; };
__device__ __forceinline__ Role unpack_role(int x) {
  Role r; r.T1 = x & 15; r.GP = (x >> 4) & 7; r.side = (x >> 7) & 1; r.m2 = (x >> 8) & 63; r.dg = (x >> 14) & 3;
  r.has2 = (x >> 16) & 1; r.last = r.T1 == NT1 - 1; r.cch0 = 160 * r.dg + r.m2; return r;
}
__device__ __forceinline__ Role fresh_role(int x) { asm volatile("" : "+r"(x)); return unpack_role(__shfl_sync(0xffffffffu, x, 0)); }
#define ROLE(x) const Role R_ = fresh_role(x); const int T1 = R_.T1, GP = R_.GP, side = R_.side, m2 = R_.m2, dg = R_.dg, cch0 = R_.cch0; \
  const bool last = R_.last, has2 = R_.has2; (void)T1; (void)GP; (void)side; (void)m2; (void)dg; (void)cch0; (void)last; (void)has2;
__device__ __forceinline__ int n_to_t(int n) {
  int T = n / 160, nl = n - T * 160;
  int L = (T == NT1 - 1) ? 32 : 40;
  return T * 160 + L * ((nl & 7) >> 1) + 2 * (nl >> 3) + (nl & 1);
}

template<int TA> __device__ __forceinline__ void wgmma_n160(float (&d)[80], uint32_t alo, uint32_t ahi, uint32_t blo, uint32_t bhi){
  asm volatile("{\n.reg .b64 da, db;\nmov.b64 da, {%80,%81};\nmov.b64 db, {%82,%83};\n"
    "wgmma.mma_async.sync.aligned.m64n160k16.f32.bf16.bf16 {%0, %1, %2, %3, %4, %5, %6, %7, %8, %9, %10, %11, %12, %13, %14, %15, %16, %17, %18, %19, %20, %21, %22, %23, %24, %25, %26, %27, %28, %29, %30, %31, %32, %33, %34, %35, %36, %37, %38, %39, %40, %41, %42, %43, %44, %45, %46, %47, %48, %49, %50, %51, %52, %53, %54, %55, %56, %57, %58, %59, %60, %61, %62, %63, %64, %65, %66, %67, %68, %69, %70, %71, %72, %73, %74, %75, %76, %77, %78, %79}, da, db, 1, 1, 1, %84, 0;\n}\n"
    : "+f"(d[0]), "+f"(d[1]), "+f"(d[2]), "+f"(d[3]), "+f"(d[4]), "+f"(d[5]), "+f"(d[6]), "+f"(d[7]), "+f"(d[8]), "+f"(d[9]), "+f"(d[10]), "+f"(d[11]), "+f"(d[12]), "+f"(d[13]), "+f"(d[14]), "+f"(d[15]), "+f"(d[16]), "+f"(d[17]), "+f"(d[18]), "+f"(d[19]), "+f"(d[20]), "+f"(d[21]), "+f"(d[22]), "+f"(d[23]), "+f"(d[24]), "+f"(d[25]), "+f"(d[26]), "+f"(d[27]), "+f"(d[28]), "+f"(d[29]), "+f"(d[30]), "+f"(d[31]), "+f"(d[32]), "+f"(d[33]), "+f"(d[34]), "+f"(d[35]), "+f"(d[36]), "+f"(d[37]), "+f"(d[38]), "+f"(d[39]), "+f"(d[40]), "+f"(d[41]), "+f"(d[42]), "+f"(d[43]), "+f"(d[44]), "+f"(d[45]), "+f"(d[46]), "+f"(d[47]), "+f"(d[48]), "+f"(d[49]), "+f"(d[50]), "+f"(d[51]), "+f"(d[52]), "+f"(d[53]), "+f"(d[54]), "+f"(d[55]), "+f"(d[56]), "+f"(d[57]), "+f"(d[58]), "+f"(d[59]), "+f"(d[60]), "+f"(d[61]), "+f"(d[62]), "+f"(d[63]), "+f"(d[64]), "+f"(d[65]), "+f"(d[66]), "+f"(d[67]), "+f"(d[68]), "+f"(d[69]), "+f"(d[70]), "+f"(d[71]), "+f"(d[72]), "+f"(d[73]), "+f"(d[74]), "+f"(d[75]), "+f"(d[76]), "+f"(d[77]), "+f"(d[78]), "+f"(d[79])
    : "r"(alo), "r"(ahi), "r"(blo), "r"(bhi), "n"(TA));
}
template<int N> __device__ __forceinline__ void wgmma_rs_hi(float (&d)[64], uint32_t a0, uint32_t a1, uint32_t a2, uint32_t a3, uint32_t blo);
template<> __device__ __forceinline__ void wgmma_rs_hi<16>(float (&d)[64], uint32_t a0, uint32_t a1, uint32_t a2, uint32_t a3, uint32_t blo){
  asm volatile("{\n.reg .b64 db;\nmov.b64 db, {%12,8};\nwgmma.mma_async.sync.aligned.m64n16k16.f32.bf16.bf16 {%0, %1, %2, %3, %4, %5, %6, %7}, {%8,%9,%10,%11}, db, 1, 1, 1, 0;\n}\n"
    : "+f"(d[56]), "+f"(d[57]), "+f"(d[58]), "+f"(d[59]), "+f"(d[60]), "+f"(d[61]), "+f"(d[62]), "+f"(d[63])
    : "r"(a0), "r"(a1), "r"(a2), "r"(a3), "r"(blo));
}
template<> __device__ __forceinline__ void wgmma_rs_hi<32>(float (&d)[64], uint32_t a0, uint32_t a1, uint32_t a2, uint32_t a3, uint32_t blo){
  asm volatile("{\n.reg .b64 db;\nmov.b64 db, {%20,8};\nwgmma.mma_async.sync.aligned.m64n32k16.f32.bf16.bf16 {%0, %1, %2, %3, %4, %5, %6, %7, %8, %9, %10, %11, %12, %13, %14, %15}, {%16,%17,%18,%19}, db, 1, 1, 1, 0;\n}\n"
    : "+f"(d[48]), "+f"(d[49]), "+f"(d[50]), "+f"(d[51]), "+f"(d[52]), "+f"(d[53]), "+f"(d[54]), "+f"(d[55]), "+f"(d[56]), "+f"(d[57]), "+f"(d[58]), "+f"(d[59]), "+f"(d[60]), "+f"(d[61]), "+f"(d[62]), "+f"(d[63])
    : "r"(a0), "r"(a1), "r"(a2), "r"(a3), "r"(blo));
}
template<> __device__ __forceinline__ void wgmma_rs_hi<48>(float (&d)[64], uint32_t a0, uint32_t a1, uint32_t a2, uint32_t a3, uint32_t blo){
  asm volatile("{\n.reg .b64 db;\nmov.b64 db, {%28,8};\nwgmma.mma_async.sync.aligned.m64n48k16.f32.bf16.bf16 {%0, %1, %2, %3, %4, %5, %6, %7, %8, %9, %10, %11, %12, %13, %14, %15, %16, %17, %18, %19, %20, %21, %22, %23}, {%24,%25,%26,%27}, db, 1, 1, 1, 0;\n}\n"
    : "+f"(d[40]), "+f"(d[41]), "+f"(d[42]), "+f"(d[43]), "+f"(d[44]), "+f"(d[45]), "+f"(d[46]), "+f"(d[47]), "+f"(d[48]), "+f"(d[49]), "+f"(d[50]), "+f"(d[51]), "+f"(d[52]), "+f"(d[53]), "+f"(d[54]), "+f"(d[55]), "+f"(d[56]), "+f"(d[57]), "+f"(d[58]), "+f"(d[59]), "+f"(d[60]), "+f"(d[61]), "+f"(d[62]), "+f"(d[63])
    : "r"(a0), "r"(a1), "r"(a2), "r"(a3), "r"(blo));
}
template<> __device__ __forceinline__ void wgmma_rs_hi<64>(float (&d)[64], uint32_t a0, uint32_t a1, uint32_t a2, uint32_t a3, uint32_t blo){
  asm volatile("{\n.reg .b64 db;\nmov.b64 db, {%36,8};\nwgmma.mma_async.sync.aligned.m64n64k16.f32.bf16.bf16 {%0, %1, %2, %3, %4, %5, %6, %7, %8, %9, %10, %11, %12, %13, %14, %15, %16, %17, %18, %19, %20, %21, %22, %23, %24, %25, %26, %27, %28, %29, %30, %31}, {%32,%33,%34,%35}, db, 1, 1, 1, 0;\n}\n"
    : "+f"(d[32]), "+f"(d[33]), "+f"(d[34]), "+f"(d[35]), "+f"(d[36]), "+f"(d[37]), "+f"(d[38]), "+f"(d[39]), "+f"(d[40]), "+f"(d[41]), "+f"(d[42]), "+f"(d[43]), "+f"(d[44]), "+f"(d[45]), "+f"(d[46]), "+f"(d[47]), "+f"(d[48]), "+f"(d[49]), "+f"(d[50]), "+f"(d[51]), "+f"(d[52]), "+f"(d[53]), "+f"(d[54]), "+f"(d[55]), "+f"(d[56]), "+f"(d[57]), "+f"(d[58]), "+f"(d[59]), "+f"(d[60]), "+f"(d[61]), "+f"(d[62]), "+f"(d[63])
    : "r"(a0), "r"(a1), "r"(a2), "r"(a3), "r"(blo));
}
template<> __device__ __forceinline__ void wgmma_rs_hi<80>(float (&d)[64], uint32_t a0, uint32_t a1, uint32_t a2, uint32_t a3, uint32_t blo){
  asm volatile("{\n.reg .b64 db;\nmov.b64 db, {%44,8};\nwgmma.mma_async.sync.aligned.m64n80k16.f32.bf16.bf16 {%0, %1, %2, %3, %4, %5, %6, %7, %8, %9, %10, %11, %12, %13, %14, %15, %16, %17, %18, %19, %20, %21, %22, %23, %24, %25, %26, %27, %28, %29, %30, %31, %32, %33, %34, %35, %36, %37, %38, %39}, {%40,%41,%42,%43}, db, 1, 1, 1, 0;\n}\n"
    : "+f"(d[24]), "+f"(d[25]), "+f"(d[26]), "+f"(d[27]), "+f"(d[28]), "+f"(d[29]), "+f"(d[30]), "+f"(d[31]), "+f"(d[32]), "+f"(d[33]), "+f"(d[34]), "+f"(d[35]), "+f"(d[36]), "+f"(d[37]), "+f"(d[38]), "+f"(d[39]), "+f"(d[40]), "+f"(d[41]), "+f"(d[42]), "+f"(d[43]), "+f"(d[44]), "+f"(d[45]), "+f"(d[46]), "+f"(d[47]), "+f"(d[48]), "+f"(d[49]), "+f"(d[50]), "+f"(d[51]), "+f"(d[52]), "+f"(d[53]), "+f"(d[54]), "+f"(d[55]), "+f"(d[56]), "+f"(d[57]), "+f"(d[58]), "+f"(d[59]), "+f"(d[60]), "+f"(d[61]), "+f"(d[62]), "+f"(d[63])
    : "r"(a0), "r"(a1), "r"(a2), "r"(a3), "r"(blo));
}
template<> __device__ __forceinline__ void wgmma_rs_hi<96>(float (&d)[64], uint32_t a0, uint32_t a1, uint32_t a2, uint32_t a3, uint32_t blo){
  asm volatile("{\n.reg .b64 db;\nmov.b64 db, {%52,8};\nwgmma.mma_async.sync.aligned.m64n96k16.f32.bf16.bf16 {%0, %1, %2, %3, %4, %5, %6, %7, %8, %9, %10, %11, %12, %13, %14, %15, %16, %17, %18, %19, %20, %21, %22, %23, %24, %25, %26, %27, %28, %29, %30, %31, %32, %33, %34, %35, %36, %37, %38, %39, %40, %41, %42, %43, %44, %45, %46, %47}, {%48,%49,%50,%51}, db, 1, 1, 1, 0;\n}\n"
    : "+f"(d[16]), "+f"(d[17]), "+f"(d[18]), "+f"(d[19]), "+f"(d[20]), "+f"(d[21]), "+f"(d[22]), "+f"(d[23]), "+f"(d[24]), "+f"(d[25]), "+f"(d[26]), "+f"(d[27]), "+f"(d[28]), "+f"(d[29]), "+f"(d[30]), "+f"(d[31]), "+f"(d[32]), "+f"(d[33]), "+f"(d[34]), "+f"(d[35]), "+f"(d[36]), "+f"(d[37]), "+f"(d[38]), "+f"(d[39]), "+f"(d[40]), "+f"(d[41]), "+f"(d[42]), "+f"(d[43]), "+f"(d[44]), "+f"(d[45]), "+f"(d[46]), "+f"(d[47]), "+f"(d[48]), "+f"(d[49]), "+f"(d[50]), "+f"(d[51]), "+f"(d[52]), "+f"(d[53]), "+f"(d[54]), "+f"(d[55]), "+f"(d[56]), "+f"(d[57]), "+f"(d[58]), "+f"(d[59]), "+f"(d[60]), "+f"(d[61]), "+f"(d[62]), "+f"(d[63])
    : "r"(a0), "r"(a1), "r"(a2), "r"(a3), "r"(blo));
}
template<> __device__ __forceinline__ void wgmma_rs_hi<112>(float (&d)[64], uint32_t a0, uint32_t a1, uint32_t a2, uint32_t a3, uint32_t blo){
  asm volatile("{\n.reg .b64 db;\nmov.b64 db, {%60,8};\nwgmma.mma_async.sync.aligned.m64n112k16.f32.bf16.bf16 {%0, %1, %2, %3, %4, %5, %6, %7, %8, %9, %10, %11, %12, %13, %14, %15, %16, %17, %18, %19, %20, %21, %22, %23, %24, %25, %26, %27, %28, %29, %30, %31, %32, %33, %34, %35, %36, %37, %38, %39, %40, %41, %42, %43, %44, %45, %46, %47, %48, %49, %50, %51, %52, %53, %54, %55}, {%56,%57,%58,%59}, db, 1, 1, 1, 0;\n}\n"
    : "+f"(d[8]), "+f"(d[9]), "+f"(d[10]), "+f"(d[11]), "+f"(d[12]), "+f"(d[13]), "+f"(d[14]), "+f"(d[15]), "+f"(d[16]), "+f"(d[17]), "+f"(d[18]), "+f"(d[19]), "+f"(d[20]), "+f"(d[21]), "+f"(d[22]), "+f"(d[23]), "+f"(d[24]), "+f"(d[25]), "+f"(d[26]), "+f"(d[27]), "+f"(d[28]), "+f"(d[29]), "+f"(d[30]), "+f"(d[31]), "+f"(d[32]), "+f"(d[33]), "+f"(d[34]), "+f"(d[35]), "+f"(d[36]), "+f"(d[37]), "+f"(d[38]), "+f"(d[39]), "+f"(d[40]), "+f"(d[41]), "+f"(d[42]), "+f"(d[43]), "+f"(d[44]), "+f"(d[45]), "+f"(d[46]), "+f"(d[47]), "+f"(d[48]), "+f"(d[49]), "+f"(d[50]), "+f"(d[51]), "+f"(d[52]), "+f"(d[53]), "+f"(d[54]), "+f"(d[55]), "+f"(d[56]), "+f"(d[57]), "+f"(d[58]), "+f"(d[59]), "+f"(d[60]), "+f"(d[61]), "+f"(d[62]), "+f"(d[63])
    : "r"(a0), "r"(a1), "r"(a2), "r"(a3), "r"(blo));
}
template<> __device__ __forceinline__ void wgmma_rs_hi<128>(float (&d)[64], uint32_t a0, uint32_t a1, uint32_t a2, uint32_t a3, uint32_t blo){
  asm volatile("{\n.reg .b64 db;\nmov.b64 db, {%68,8};\nwgmma.mma_async.sync.aligned.m64n128k16.f32.bf16.bf16 {%0, %1, %2, %3, %4, %5, %6, %7, %8, %9, %10, %11, %12, %13, %14, %15, %16, %17, %18, %19, %20, %21, %22, %23, %24, %25, %26, %27, %28, %29, %30, %31, %32, %33, %34, %35, %36, %37, %38, %39, %40, %41, %42, %43, %44, %45, %46, %47, %48, %49, %50, %51, %52, %53, %54, %55, %56, %57, %58, %59, %60, %61, %62, %63}, {%64,%65,%66,%67}, db, 1, 1, 1, 0;\n}\n"
    : "+f"(d[0]), "+f"(d[1]), "+f"(d[2]), "+f"(d[3]), "+f"(d[4]), "+f"(d[5]), "+f"(d[6]), "+f"(d[7]), "+f"(d[8]), "+f"(d[9]), "+f"(d[10]), "+f"(d[11]), "+f"(d[12]), "+f"(d[13]), "+f"(d[14]), "+f"(d[15]), "+f"(d[16]), "+f"(d[17]), "+f"(d[18]), "+f"(d[19]), "+f"(d[20]), "+f"(d[21]), "+f"(d[22]), "+f"(d[23]), "+f"(d[24]), "+f"(d[25]), "+f"(d[26]), "+f"(d[27]), "+f"(d[28]), "+f"(d[29]), "+f"(d[30]), "+f"(d[31]), "+f"(d[32]), "+f"(d[33]), "+f"(d[34]), "+f"(d[35]), "+f"(d[36]), "+f"(d[37]), "+f"(d[38]), "+f"(d[39]), "+f"(d[40]), "+f"(d[41]), "+f"(d[42]), "+f"(d[43]), "+f"(d[44]), "+f"(d[45]), "+f"(d[46]), "+f"(d[47]), "+f"(d[48]), "+f"(d[49]), "+f"(d[50]), "+f"(d[51]), "+f"(d[52]), "+f"(d[53]), "+f"(d[54]), "+f"(d[55]), "+f"(d[56]), "+f"(d[57]), "+f"(d[58]), "+f"(d[59]), "+f"(d[60]), "+f"(d[61]), "+f"(d[62]), "+f"(d[63])
    : "r"(a0), "r"(a1), "r"(a2), "r"(a3), "r"(blo));
}

struct CvCtx {
  uint32_t koff, zero, so[3];
  int srcA, srcB;
  bool wrapA, s3, kodd;
};
struct CvPipe { uint32_t Ap, Ep, keep, send; };
template <int LO> __device__ __forceinline__ void cv_copy(float (&acc)[64]) {
#pragma unroll
  for (int i = LO; i < 64; i++) { float t; asm volatile("mov.b32 %0, %1;" : "=f"(t) : "f"(acc[i]) : "memory"); acc[i] = t; }
}
template <int G> __device__ __forceinline__ void cv_raw(uint32_t (&A)[4][4], uint32_t kaddr) {
#pragma unroll
  for (int i = 0; i < 4; i++) {
    const uint32_t a = kaddr + (4 * G + i) * 128;
    A[i][0] = lds32(a); A[i][1] = lds32(a + 4); A[i][3] = lds32(a + 8);
  }
}
__device__ __forceinline__ void cv_form(uint32_t (&A)[4][4], uint32_t sel) {
#pragma unroll
  for (int i = 0; i < 4; i++) {
    asm volatile("prmt.b32 %0, %0, %1, %2;" : "+r"(A[i][0]) : "r"(A[i][1]), "r"(sel));
    asm volatile("prmt.b32 %0, %1, %2, %3;" : "=r"(A[i][2]) : "r"(A[i][1]), "r"(A[i][3]), "r"(sel));
  }
}
#define CVV 2
template <int G> __device__ __forceinline__ void cv_step(float (&acc)[64], uint32_t (&A)[4][4], CvPipe& s, const CvCtx& c, uint32_t cb, uint32_t stg) {
  constexpr int JA = G - 1, JB = G - 2, NH = CVV == 1 ? 4 : (CVV == 3 ? 2 : 1);
  const uint32_t db0 = desc_lo(cb + CV_U + 192, CV_PL);
  uint32_t B[4][4];
  uint32_t ra[2], rb;
  if constexpr (G < 8) {
    wgmma_fence();
#pragma unroll
    for (int i = 0; i < NH; i++) wgmma_rs_hi<128 - 16 * (G & 7)>(acc, A[i][0], A[i][1], A[i][2], A[i][3], db0 - 4 * i);
    wgmma_commit();
    __syncwarp();
  }
  if constexpr (JA >= 0 && JA < 8) {
    const uint32_t p0 = pack_bf16(acc[8 * JA + 1], acc[8 * JA + 3]), p1 = pack_bf16(acc[8 * JA + 5], acc[8 * JA + 7]);
    ra[0] = __shfl_sync(0xffffffffu, c.wrapA ? s.Ap : p0, c.srcA);
    ra[1] = __shfl_sync(0xffffffffu, c.wrapA ? p0 : p1, c.srcA);
    s.Ap = p1;
  }
  if constexpr (JB >= 0) rb = __shfl_sync(0xffffffffu, s.send, c.srcB);
  if constexpr (G < 7) cv_raw<G + 1>(B, cb + c.koff);
  uint32_t z = 0;
  if constexpr (G < 8 && NH < 4) {
    __syncwarp();
    wgmma_fence();
#pragma unroll
    for (int i = NH; i < 4; i++) wgmma_rs_hi<128 - 16 * (G & 7)>(acc, A[i][0], A[i][1], A[i][2], A[i][3], db0 - 4 * i);
    wgmma_commit();
    asm volatile("mov.u32 %0, %%clock;" : "=r"(z)::"memory");
    z &= c.zero;
  }
  if constexpr (G < 7) cv_form(B, 0x5432u | z);
  if constexpr (JB >= 0) sts32(stg + ((c.so[JB / 3] >> (10 * (JB % 3))) & 0xffc), hadd2(rb | z, s.keep));
  if constexpr (JA >= 0 && JA < 8) {
    const uint32_t sh = 16 | z, mk = 0xffff0000u | z;
    const uint32_t ev = pack_bf16(acc[8 * JA] + __uint_as_float(ra[0] << sh), acc[8 * JA + 2] + __uint_as_float(ra[0] & mk));
    const uint32_t od = pack_bf16(acc[8 * JA + 4] + __uint_as_float(ra[1] << sh), acc[8 * JA + 6] + __uint_as_float(ra[1] & mk));
    s.send = c.kodd ? ev : (c.s3 ? s.Ep : od);
    s.keep = c.kodd ? od : ev;
    s.Ep = od;
  }
  if constexpr (G < 8) { __syncwarp(); wgmma_wait<0>(); cv_copy<8 * (G & 7)>(acc); }
  if constexpr (G < 9) cv_step<G + 1>(acc, B, s, c, cb, stg);
}
__device__ __forceinline__ uint32_t cv_stage(int slot) { return sb + (slot < 4 ? 40960 + slot * 4096 : CV_OFF + CV_K); }
__device__ __forceinline__ void cv_setup(CvCtx& c) {
  const int tid = tid_opaque() & 127, w = tid >> 5, lane = tid & 31, r = lane >> 2, q = lane & 3;
  const int i0 = (r >> 1) & 1, i1 = r >> 2;
  c.koff = CV_K - 32 + 4 * (8 * (r >> 1) + 2 * w + (r & 1) + 2 * q);
  c.srcA = i0 ? lane - 8 : lane + 8 - q + ((q + 3) & 3);
  c.wrapA = i0 && q == 3;
  c.srcB = i1 == 0 ? (lane - q + 16 + ((q + 3) & 3)) : (lane - q - 16 + ((q + 1) & 3));
  c.s3 = (i1 == 1 && q == 3); c.kodd = (i1 == 1 && q < 3);
  c.zero = lds32(sb + EP_OFF + 24);
#pragma unroll
  for (int i = 0; i < 3; i++) c.so[i] = lds32(sb + SO_OFF + 512 * i + 4 * tid);
}
__device__ __forceinline__ void cv_table() {
  const int tid = tid_opaque() & 127, r = (tid & 31) >> 2, q = tid & 3;
  int t = 16 * (2 * (r < 4 ? q : 4 + ((q + 1) & 3)) + ((r >> 1) & 1)) + 4 * (tid >> 5) + 2 * (r & 1);
#pragma unroll 1
  for (int i = 0; i < 3; i++) {
    uint32_t v = 0;
#pragma unroll 1
    for (int x = 0; x < 3; x++, t += 256) {
      const int T = t / 160, tl = t - T * 160;
      const int qq = (T >= NT1 - 1) ? (tl >> 5) : (tl / 40);
      int ck = 20 * T + ((tl - qq * ((T >= NT1 - 1) ? 32 : 40)) >> 1);
      ck ^= (ck >> 2) & 6;
      v |= (uint32_t)((ck * 4 + qq) & 1023) << (10 * x + 2);
    }
    sts32(sb + SO_OFF + 512 * i + 4 * tid, v);
  }
}
__device__ __forceinline__ void conv_channel(int slot, const CvCtx& c) {
  const uint32_t cb = sb + CV_OFF + slot * CV_B;
  float acc[64];
  CvPipe s;
  s.Ap = s.Ep = 0u;
  uint32_t A[4][4];
#pragma unroll
  for (int i = 0; i < 64; i++) acc[i] = 0.f;
  if (slot == 4) mbar_wait(bars + 8 * B_CVDONE);
  mbar_wait(bars + 8 * (B_CVFULL + slot));
  cv_raw<0>(A, cb + c.koff);
  {
    const uint32_t w0 = lds32(cb + CV_K);
    const uint32_t wp = __byte_perm(pack_bf16(bf_lo(w0) + __uint_as_float(lds32(sb + EP_OFF + 4 * slot)), 0.f), w0, 0x7610);
    if (c.koff == CV_K) A[0][0] = wp;
    if (c.koff == CV_K - 4) A[0][1] = wp;
    if (c.koff == CV_K - 8) A[0][3] = wp;
  }
  cv_form(A, 0x5432u);
  cv_copy<0>(acc);
  cv_step<0>(acc, A, s, c, cb, cv_stage(slot));
  fence_async_smem();
  mbar_arrive(bars + 8 * (B_CVDONE + slot));
}

__device__ __forceinline__ void kv_issue(const Params& p, int c, int m2, int dg) {
  const uint32_t fb = bars + 8 * (B_KV + c);
  mbar_expect_tx(fb, KV_PIECE);
  tma3(sb + KS_OFF + c * KV_PIECE, &p.mK, 160 * dg + 32 * c, 64 * m2 - 3, 0, fb);
  tma3(sb + KS_OFF + c * KV_PIECE + 4864, &p.mV, 160 * dg + 32 * c, 64 * m2 - 1, 0, fb);
}
__device__ __forceinline__ void kv_tile(int m, int dg, int c, int y) {
  const int lane = tid_opaque() & 31, tg = lane >> 3;
  const uint32_t pb = sb + KS_OFF + c * KV_PIECE + 32 * y + 4 * (lane & 7);
  const uint32_t ka = pb + tg * 1216, va = pb + 4864 + tg * 1088 + 64;
  const uint32_t kh = (m == 0 && tg > 0) ? ka - 192 : ka;
  uint32_t kk[19], u[16];
  const float4 t = lds128f(sb + TAP_OFF + 256 * c + 128 * y + 16 * (lane & 7));
#pragma unroll
  for (int i = 0; i < 19; i++) { kk[i] = lds32((i < 3 ? kh : ka) + i * 64); if (i >= 3) u[i - 3] = lds32(va + (i - 3) * 64); }
  uint8_t* dst = g_kv + ((160 * dg + 32 * c + 16 * y + 2 * (lane & 7)) * 4096 + (4 * m + tg) * 16);
  const uint32_t w0 = __byte_perm(__float_as_uint(t.x), __float_as_uint(t.z), 0x5410), w1 = __byte_perm(__float_as_uint(t.x), __float_as_uint(t.z), 0x7632);
  const uint32_t w2 = __byte_perm(__float_as_uint(t.y), __float_as_uint(t.w), 0x5410), w3 = __byte_perm(__float_as_uint(t.y), __float_as_uint(t.w), 0x7632);
#pragma unroll
  for (int i = 0; i < 16; i++) {
    uint32_t a = hmul2(kk[i], w3);
    a = hadd2(a, hmul2(kk[i + 1], w2)); a = hadd2(a, hmul2(kk[i + 2], w1)); a = hadd2(a, hmul2(kk[i + 3], w0));
    u[i] = hmul2(a, u[i]);
  }
#pragma unroll
  for (int e = 0; e < 2; e++)
#pragma unroll
    for (int f = 0; f < 2; f++) {
      uint32_t o[4];
#pragma unroll
      for (int qq = 0; qq < 4; qq++) o[qq] = __byte_perm(u[15 - 4 * qq - 2 * f], u[14 - 4 * qq - 2 * f], e ? 0x7632 : 0x5410);
      *(uint4*)(dst + e * 4096 + f * 2048) = make_uint4(o[0], o[1], o[2], o[3]);
    }
}
__device__ __forceinline__ void ln_finish(float s1, float s2, float& mean, float& rstd) {
  mean = s1 * (1.f / 640.f);
  const float v = fmaxf(fmaf(-mean, mean, s2 * (1.f / 640.f)), 0.f) + 1e-5f;
  asm("rsqrt.approx.ftz.f32 %0, %1;" : "=f"(rstd) : "f"(v));
}
__device__ __forceinline__ void stat_table(int T1, unsigned want, int l, int g, const uint4* x0, const uint4* x1, float (&xa)[2], float (&xb)[2]) {
  const int n = 32 * g + (tid_opaque() & 31);
  const uint4* rp = &g_stats[8 * l * SEQ + min(160 * T1 + n, SEQ - 1)];
  float a[4], b[4];
  uint32_t it = 0;
  while (true) {
    bool ok = true;
#pragma unroll
    for (int i = 0; i < 4; i++) ok &= (rec_ld(rp + SEQ * i, a[i], b[i]) == want);
    ok &= rec_ld(x0, xa[0], xb[0]) == want;
    ok &= rec_ld(x1, xa[1], xb[1]) == want;
    if (__all_sync(0xffffffffu, ok)) break;
    trap_if(++it > SPIN_LIMIT);
  }
  float m, rs;
  ln_finish((a[0] + a[1]) + (a[2] + a[3]), (b[0] + b[1]) + (b[2] + b[3]), m, rs);
  sts64f(sb + STAB_OFF + n * 8, rs, -m * rs);
}
__device__ __forceinline__ void stats_reduce(float (&a)[2], float (&b)[2], float (&mean)[2], float (&rstd)[2]) {
#pragma unroll
  for (int o = 1; o < 4; o <<= 1)
#pragma unroll
    for (int h = 0; h < 2; h++) { a[h] += __shfl_xor_sync(0xffffffffu, a[h], o); b[h] += __shfl_xor_sync(0xffffffffu, b[h], o); }
#pragma unroll
  for (int h = 0; h < 2; h++) ln_finish(a[h], b[h], mean[h], rstd[h]);
}

template <bool FIRST>
__device__ __forceinline__ void stats_publish(int which, int n0, int dg, unsigned tag, const float (&acc)[80]) {
  const int q = tid_opaque() & 3, h = q & 1;
  float s1[2] = {0.f, 0.f}, s2[2] = {0.f, 0.f}, t1[2] = {0.f, 0.f}, t2[2] = {0.f, 0.f};
#pragma unroll
  for (int j = 0; j < 20; j++)
#pragma unroll
    for (int y = 0; y < 2; y++) {
      const float a = acc[4 * j + 2 * y], b = acc[4 * j + 2 * y + 1];
      s1[y] += a; t1[y] += b; s2[y] = fmaf(a, a, s2[y]); t2[y] = fmaf(b, b, t2[y]);
    }
#pragma unroll
  for (int y = 0; y < 2; y++) { s1[y] += t1[y]; s2[y] += t2[y]; }
  float a = (h ? s1[1] : s1[0]) + __shfl_xor_sync(0xffffffffu, h ? s1[0] : s1[1], 1);
  float b = (h ? s2[1] : s2[0]) + __shfl_xor_sync(0xffffffffu, h ? s2[0] : s2[1], 1);
  a += __shfl_xor_sync(0xffffffffu, a, 2);
  b += __shfl_xor_sync(0xffffffffu, b, 2);
  if (FIRST) {
    rec_st(&g_stats[((q >> 1) * 4 + dg) * SEQ + n0 + 8 * h], a, b, q < 2 ? tag : tag - 1);
    rec_st(&g_stats[((q >> 1) * 4 + 8 + dg) * SEQ + n0 + 8 * h], a, b, tag - 1);
  } else if (q < 2) rec_st(&g_stats[(which * 4 + dg) * SEQ + n0 + 8 * h], a, b, tag);
}
__device__ __forceinline__ void stats_get(int which, int n0, unsigned tag, float (&mean)[2], float (&rstd)[2]) {
  const uint4* p0 = &g_stats[(which * 4 + (tid_opaque() & 3)) * SEQ + n0];
  float a[2], b[2];
  uint32_t it = 0;
  while (true) {
    const unsigned t0 = rec_ld(p0, a[0], b[0]), t1 = rec_ld(p0 + 8, a[1], b[1]);
    if (__all_sync(0xffffffffu, t0 == tag && t1 == tag)) break;
    trap_if(++it > SPIN_LIMIT);
  }
  stats_reduce(a, b, mean, rstd);
}
__device__ __forceinline__ void x0_load(float (&acc)[80]) {
  const int t = tid_opaque() & 127;
  const uint32_t xa = sb + XT_OFF + (16 * (t >> 5) + ((t & 31) >> 2)) * 320 + 8 * (t & 3);
  mbar_wait(bars + 8 * B_XT);
#pragma unroll
  for (int h = 0; h < 2; h++)
#pragma unroll
    for (int J = 0; J < 10; J++) {
      const float2 v = lds64f(xa + h * 2560 + 32 * J);
      const uint32_t x = __float_as_uint(v.x), y = __float_as_uint(v.y);
      acc[8 * J + 2 * h] = bf_lo(x); acc[8 * J + 2 * h + 1] = bf_hi(x);
      acc[8 * J + 4 + 2 * h] = bf_lo(y); acc[8 * J + 4 + 2 * h + 1] = bf_hi(y);
    }
}

template <bool FROM_X0>
__device__ __forceinline__ void dskip_init(float (&acc)[80], const float (&mean)[2], const float (&rstd)[2]) {
  const int t = tid_opaque() & 127;
  const uint32_t xa = sb + XT_OFF + (16 * (t >> 5) + ((t & 31) >> 2)) * 320 + 8 * (t & 3), da = sb + DTAB_OFF + 8 * (t & 3);
  float2 dw[10], xv[10][2];
#pragma unroll
  for (int J = 0; J < 2; J++) { dw[J] = lds64f(da + 32 * J); if (FROM_X0) { xv[J][0] = lds64f(xa + 32 * J); xv[J][1] = lds64f(xa + 2560 + 32 * J); } }
#pragma unroll
  for (int J = 0; J < 10; J++) {
    if (J + 2 < 10) { dw[J + 2] = lds64f(da + 32 * (J + 2)); if (FROM_X0) { xv[J + 2][0] = lds64f(xa + 32 * (J + 2)); xv[J + 2][1] = lds64f(xa + 2560 + 32 * (J + 2)); } }
#pragma unroll
    for (int x = 0; x < 8; x++) {
      const int h = (x >> 1) & 1;
      const uint32_t dwd = __float_as_uint(x < 4 ? dw[J].x : dw[J].y);
      const float tt = fmaf(rstd[h], (x & 1) ? bf_hi(dwd) : bf_lo(dwd), 1.f);
      float a = acc[8 * J + x];
      if (FROM_X0) { const uint32_t xw = __float_as_uint(x < 4 ? xv[J][h].x : xv[J][h].y); a = (x & 1) ? bf_hi(xw) : bf_lo(xw); }
      acc[8 * J + x] = FROM_X0 ? (a - mean[h]) * tt : fmaf(a, tt, -mean[h] * tt);
    }
  }
}

__global__ void __launch_bounds__(512, 1) fused_kernel(const __grid_constant__ Params p) {
  extern __shared__ __align__(1024) uint8_t smem_raw[];
  const int tid = threadIdx.x, lane = tid & 31;
  const int wid = __shfl_sync(0xffffffffu, tid >> 5, 0), wg = wid >> 2;
  unsigned smid; asm volatile("mov.u32 %0, %%smid;" : "=r"(smid));
  const int role = p.role[min(smid, 131u)];
  if (wid == 12) {
    const bool el = elect_one();
    if (el) {
      asm volatile("prefetch.tensormap [%0];" ::"l"(&p.mX) : "memory");
      asm volatile("prefetch.tensormap [%0];" ::"l"(&p.mB) : "memory");
#pragma unroll
      for (int k = 0; k < S1; k++) mbar_init(bars + 8 * (B_G1FULL + k), 1);
#pragma unroll
      for (int k = 0; k < 6; k++) mbar_init(bars + 8 * (B_XT + k), 1);
      asm volatile("fence.mbarrier_init.release.cluster;" ::: "memory");
    }
    if (role >= 0) {
      __syncwarp();
      asm volatile("bar.arrive 5, 288;" ::: "memory");
      const Role R = unpack_role(role);
      if (elect_one()) {
        TS(45);
#pragma unroll 1
        for (int k = 0; k < S1; k++) {
          const uint32_t fb = bars + 8 * (B_G1FULL + k);
          mbar_expect_tx(fb, G1_STAGE);
          tma4(sb + k * G1_STAGE + G1_XOFF, R.last ? &p.mXl : &p.mX, 64 * k, 0, 0, R.last ? 0 : 80 * R.T1, fb);
          tma5(sb + k * G1_STAGE, &p.mB, 64 * k, 0, 0, 4 * R.side, 2 * R.GP, fb);
        }
        if (R.has2) {
#pragma unroll 1
          for (int c = 0; c < KV0; c++) kv_issue(p, c, R.m2, R.dg);
          mbar_expect_tx(bars + 8 * B_XT, 20480);
#pragma unroll 1
          for (int h = 0; h < 2; h++) {
            const int ng = 8 * R.m2 + 4 * h, T = ng / 20;
            tma4(sb + XT_OFF + h * 10240, T == NT1 - 1 ? &p.mXtl : &p.mXt, 160 * R.dg, 0, 0, T == NT1 - 1 ? ng - 240 : ng + 60 * T, bars + 8 * B_XT);
          }
        }
        TS(44);
      }
      __syncwarp();
      bar_sync(6, 64);
    }
  }
  trap_if(smid >= 132 || smem_u32(smem_raw) != sb);
  if (role < 0) {
    if (wid == 0) {
      const unsigned tag = ld_rlx(g_epoch);
      uint32_t it = 0;
      while (!__all_sync(0xffffffffu, (int)(ld_rlx(&g_hcnt[(lane & 7) * 32]) - 40 * tag) >= 0)) { __nanosleep(500); trap_if(++it > SPIN_LIMIT); }
    }
    return;
  }
  float mean0[2] = {0.f, 0.f}, rstd0[2] = {0.f, 0.f};
  if (wg == 2 || wid == 14) {
    ROLE(role)
    const int c = wid == 14 ? 4 : wid - 8;
    const unsigned tag = ld_rlx(g_epoch);
    if (has2) {
      uint2 bv[2][5];
#pragma unroll
      for (int x = 0; x < 2; x++)
#pragma unroll
        for (int i = 0; i < 5; i++) bv[x][i] = ldv64((const uint2*)((x ? p.bim : p.bre) + (cch0 + 32 * c) * DM) + lane + 32 * i);
      float sv[2];
#pragma unroll
      for (int x = 0; x < 2; x++) {
        float a = 0.f;
#pragma unroll
        for (int i = 0; i < 5; i++) a += (bf_lo(bv[x][i].x) + bf_hi(bv[x][i].x)) + (bf_lo(bv[x][i].y) + bf_hi(bv[x][i].y));
        sv[x] = a;
      }
#pragma unroll
      for (int o = 16; o > 0; o >>= 1) { sv[0] += __shfl_xor_sync(0xffffffffu, sv[0], o); sv[1] += __shfl_xor_sync(0xffffffffu, sv[1], o); }
      if (lane < 2) rec_st(&g_sB[(cch0 + 32 * c) * 2 + lane], sv[0], sv[1], tag);
      if (tid == 256) TS(47);
      __syncwarp();
      bar_sync(8, 192);
      mbar_wait(bars + 8 * B_EP);
      mbar_wait(bars + 8 * (B_KV + c));
#pragma unroll 1
      for (int y = 0; y < 2; y++) kv_tile(m2, dg, c, y);
      __syncwarp();
      if (lane == 0) mbar_arrive(bars + 8 * B_PREP);
      if (tid == 352) TS(52);
      if (tid == 448) TS(51);
      if (wg == 2) {
        float xs[80];
        x0_load(xs);
        stats_publish<true>(0, 64 * m2 + 16 * c + (lane >> 2), dg, tag, xs);
        if (tid == 256) TS(31);
        mbar_wait(bars + 8 * (TABW ? B_PUB : B_PREP));
      } else {
        mbar_wait(bars + 8 * B_PREP);
        if (lane < 4) red_rel(&g_kvcnt[(dg * 4 + lane) * 32]);
        __syncwarp();
        if (lane == 0) { mbar_arrive(bars + 8 * B_PUB); TS(30); }
      }
    } else bar_sync(8, 192);
    {
      const uint4* x0 = wg == 2 ? &g_stats[(lane & 3) * SEQ + (has2 ? 64 * m2 : 0) + 16 * c + (lane >> 2)] : &g_sB[(128 * GP + 32 * side + lane) * 2];
      float xa[2], xb[2];
      stat_table(T1, tag, 0, c, x0, x0 + (wg == 2 ? 8 : 128), xa, xb);
      if (wg == 2) stats_reduce(xa, xb, mean0, rstd0);
      else {
#pragma unroll
        for (int i = 0; i < 2; i++) sts64f(sb + CTAB_OFF + (32 * i + lane) * 24 + 16, p.swap ? xb[i] : xa[i], p.swap ? xa[i] : xb[i]);
      }
      mbar_arrive(bars + 8 * B_STAB);
      if (tid == 448) TS(26);
    }
  } else if (wid == 15) {
    ROLE(role)
    const int ch = 128 * GP + 32 * side + lane;
    uint32_t r0 = ldv16(p.lre + ch), r1 = ldv16(p.lim + ch), r2 = ldv16(p.logdt + ch);
    const uint32_t r3 = ldv16(p.lre + ch + 64), r4 = ldv16(p.lim + ch + 64), r5 = ldv16(p.logdt + ch + 64);
#pragma unroll 1
    for (int i = 0; i < 2; i++) {
      const float lr = bf_lo(r0), li = bf_lo(r1);
      const float dt = __bfloat162float(__float2bfloat16_rn(expf(bf_lo(r2))));
      const float mag = expf(dt * lr);
      float sn, cs; sincospif(dt * li * 0.31830988618379067f, &sn, &cs);
      const float ar = mag * cs, ai = mag * sn;
      const float inv = 2.f / (lr * lr + li * li);
      const uint32_t ad = sb + CTAB_OFF + (32 * i + lane) * 24;
      sts64f(ad, ar, ai);
      sts64f(ad + 8, ((ar - 1.f) * lr + ai * li) * inv, (ai * lr - (ar - 1.f) * li) * inv);
      r0 = r3; r1 = r4; r2 = r5;
    }
    if (lane == 0) TS(46);
    __syncwarp();
    bar_sync(7, 64);
    mbar_arrive(bars + 8 * B_CTAB);
  } else if (wid == 13) {
    ROLE(role)
    uint4 tv[3];
    const uint32_t e0 = ld_rlx(g_epoch);
    const uint32_t e1 = ldv16(p.ssmD + min(cch0 + 32 * lane, 639));
    const uint4 dv = ldv128((const uint4*)(p.dskip + 160 * dg) + min(lane, 19));
#pragma unroll
    for (int i = 0; i < 3; i++) tv[i] = ldv128((const uint4*)(p.shiftk + 640 * dg) + min(lane + 32 * i, 79));
    sts128(sb + DTAB_OFF + 16 * min(lane, 19), dv);
#pragma unroll
    for (int i = 0; i < 3; i++) sts128(sb + TAP_OFF + 16 * min(lane + 32 * i, 79), tv[i]);
    if (lane < 7) sts32(sb + EP_OFF + 4 * lane, lane < 5 ? e1 << 16 : (lane == 5 ? e0 : 0u));
    __syncwarp();
    bar_sync(9, 64);
    mbar_arrive(bars + 8 * B_CTAB);
    if (lane == 0) { mbar_arrive(bars + 8 * B_EP); TS(53); }
  } else if (wid != 12) {
    if (elect_one()) {
      if (wid < 7) {
        const int b0 = wid < 4 ? 4 + 20 * wid : 85 + 21 * (wid - 4), cnt = wid < 4 ? 2 : 1;
#pragma unroll
        for (int i = 0; i < 21; i++) mbar_init(bars + 8 * (b0 + i), cnt);
      } else {
#pragma unroll
        for (int i = 0; i < 12; i++) mbar_init(bars + 8 * (B_CVDONE + i), (i == 5 || i == 6) ? 160 : 128);
        mbar_init(bars + 8 * B_CTAB, 192); mbar_init(bars + 8 * B_PREP, 5);
      }
      asm volatile("fence.mbarrier_init.release.cluster;" ::: "memory");
    }
    __syncwarp();
    bar_sync(5, 288);
    if (wid == 2) asm volatile("bar.arrive 8, 192;\nbar.arrive 6, 64;\nbar.arrive 9, 64;\nbar.arrive 7, 64;" ::: "memory");
    if (tid == 128) TS(0);
    if (wg == 1) { cv_table(); mbar_arrive(bars + 8 * B_CTAB); }
  }

  if (wid == 12) {
    ROLE(role)
    uint32_t dst = sb;
#pragma unroll 1
    for (int k = S1; k < 10; k++) {
      const uint32_t fb = bars + 8 * (B_G1FULL + k);
      mbar_wait(bars + 8 * (B_G1DONE + k - S1));
      if (elect_one()) {
        mbar_expect_tx(fb, 20480);
        tma4(dst + G1_XOFF, last ? &p.mXl : &p.mX, 64 * k, 0, 0, last ? 0 : 80 * T1, fb);
        mbar_expect_tx(fb, 16384);
        tma5(dst, &p.mB, 64 * k, 0, 0, 4 * side, 2 * GP, fb);
        if (has2 && k - S1 + KV0 < 5) kv_issue(p, k - S1 + KV0, m2, dg);
      }
      dst += G1_STAGE; if (k == 2 * S1 - 1) dst = sb;
    }
  } else if (wid == 15 && (role >> 16)) {
    ROLE(role)
    mbar_wait(bars + 8 * B_PREP);
#pragma unroll
    for (int c = 0; c < 5; c++) {
      const uint32_t cb = sb + CV_OFF + c * CV_B;
      sts128(lane < 8 ? cb + 16 * lane : (lane < 20 ? cb + CV_U + 16 * (lane - 8) : cb + CV_U + CV_PL + 16 * (lane - 20)), make_uint4(0, 0, 0, 0));
    }
    fence_async_smem();
    __syncwarp();
    const unsigned tag = lds32(sb + EP_OFF + 20);
    mbar_wait(bars + 8 * B_PUB);
    if (elect_one()) {
#pragma unroll
      for (int c = 0; c < TAP0; c++) {
        mbar_expect_tx(bars + 8 * (B_CVFULL + c), 4096);
        bulk_g2s(sb + CV_OFF + c * CV_B + CV_K, p.ssmk + (cch0 + 32 * c) * SEQ, 4096, bars + 8 * (B_CVFULL + c));
      }
    }
    cnt_poll(&g_kvcnt[(dg * 4 + (m2 >> 3)) * 32], 32 * tag);
    fence_async_global();
    if (elect_one()) {
      TS(28);
#pragma unroll 1
      for (int c = 0; c < 5; c++) {
        const uint32_t fb = bars + 8 * (B_CVFULL + c), cb = sb + CV_OFF + c * CV_B;
        mbar_expect_tx(fb, 4096);
        bulk_g2s(cb + CV_U + 192, g_kv + (cch0 + 32 * c) * 4096, 2048, fb);
        bulk_g2s(cb + CV_U + 192 + CV_PL, g_kv + (cch0 + 32 * c) * 4096 + 2048, 2048, fb);
        if (c >= TAP0) {
          mbar_expect_tx(fb, 4096);
          bulk_g2s(cb + CV_K, p.ssmk + (cch0 + 32 * c) * SEQ, 4096, fb);
        }
      }
      TS(54);
    }
    __syncwarp();
  }
  {
    const int w = wid & 3;
    if (wg == 2 && !(role >> 16)) {
      float xa[2], xb[2];
      mbar_wait(bars + 8 * (B_G1FULL + 11));
      stat_table(role & 15, lds32(sb + EP_OFF + 20), 1, w, g_stats, g_stats, xa, xb);
      mbar_arrive(bars + 8 * (B_STAB + 1));
    }
#pragma unroll 1
    for (int l = 0; l < 2; l++) {
      if (wg < 2) {
        float acc[80];
#pragma unroll
        for (int i = 0; i < 80; i++) acc[i] = 0.f;
        ROLE(role)
        const int tid = tid_opaque(), r = (tid & 31) >> 2, q = tid & 3;
        const int ch = 128 * GP + 64 * wg + 32 * side + 8 * w + r;
        const uint32_t ca = sb + CTAB_OFF + (32 * wg + 8 * w + r) * 24;
        float2 lam = make_float2(0.f, 0.f), p8 = lam, p16 = lam, pL = lam, p2L = lam;
        fence_regs(acc);
        {
          const uint32_t alo0 = (l == 0 ? desc_lo(sb, 16) : desc_lo(sb + G2_WOFF, 16)) + wg * 512;
          const uint32_t blo0 = l == 0 ? desc_lo(sb + G1_XOFF, 16) : desc_lo(sb + X1_OFF, 128);
          const uint32_t bhi = l == 0 ? desc_hi(1024, 1) : desc_hi(1024, 0), xstep = l == 0 ? 2 : 16;
          const uint32_t astep = l == 0 ? G1_STAGE >> 4 : 1024, bstep = l == 0 ? G1_STAGE >> 4 : 1280, aend = alo0 + (S1 + l) * astep;
          uint32_t alo = alo0, blo = blo0;
          uint32_t fb = bars + 8 * (B_G1FULL + 10 * l);
          mbar_wait(fb);
          if (tid == 0) TS(1 + 8 * l);
#pragma unroll 1
          for (int k = 0; k < 10; k++) {
            uint32_t ok; const uint32_t nb = k < 9 ? fb + 8 : fb;
            wgmma_fence();
#pragma unroll
            for (int kk = 0; kk < 4; kk++) {
              wgmma_n160<0>(acc, alo + kk * 2, desc_hi(1024, 1), blo + kk * xstep, bhi);
              if (kk == 0) ok = mbar_test(nb);
              if (kk == STG_KK && k == 9 && tid == 0) mbar_arrive(bars + 8 * (B_STG + l));
            }
            wgmma_commit();
            alo += astep; blo += bstep;
            if (blo == desc_lo(sb + G_OFF, 128)) blo = desc_lo(sb, 128);
            if (alo == aend) { alo = alo0; blo = blo0; }
            wgmma_wait<1>();
            if (k > 0 && (tid & 127) == 0) mbar_arrive(fb + 8 * (B_G1DONE - B_G1FULL - 1));
            if (!ok) mbar_wait(nb);
            if (wg == 1 && k == (l ? 8 - STG_D : 9 - STG0)) mbar_wait(bars + 8 * (B_STG + l));
            if (k == 3) {
              mbar_wait(bars + 8 * B_CTAB);
              lam = lds64f(ca);
              if (p.swap) lam.y = -lam.y;
              const float2 p2 = cmul(lam, lam), p4 = cmul(p2, p2);
              p8 = cmul(p4, p4); p16 = cmul(p8, p8);
              pL = cmul(p16, p16);
              if (!last) pL = cmul(pL, p8);
              p2L = cmul(pL, pL);
            }
            if (k == PAUSE_K && has2) mbar_wait(bars + 8 * B_PREP);
            fb += 8;
          }
        }
        mbar_wait(bars + 8 * (B_STAB + l));
        const float2 sB = lds64f(ca + 16);
        const unsigned tag = lds32(sb + EP_OFF + 20);
        wgmma_wait<0>();
        fence_regs(acc);
        if ((tid & 127) == 0) { mbar_arrive(bars + 8 * (B_G1DONE + 10 * l + 9)); TS(wg ? 17 + l : 2 + 8 * l); }
        float2 ec[3];
#pragma unroll
        for (int jj = 0; jj < 8; jj++)
#pragma unroll
          for (int y = 0; y < 3; y++) {
            if (y == 2 && (jj & 1)) continue;
            const int j = y == 2 ? 16 + (jj >> 1) : 8 * y + jj;
            const float4 st = lds128f(sb + STAB_OFF + (8 * j + 2 * q) * 8);
            acc[4 * j + 0] = fmaf(acc[4 * j + 0], st.x, st.y * sB.x);
            acc[4 * j + 2] = fmaf(acc[4 * j + 2], st.x, st.y * sB.y);
            acc[4 * j + 1] = fmaf(acc[4 * j + 1], st.z, st.w * sB.x);
            acc[4 * j + 3] = fmaf(acc[4 * j + 3], st.z, st.w * sB.y);
            ec[y] = jj == 0 ? make_float2(acc[4 * j + 0], acc[4 * j + 2]) : cfma(lam, ec[y], make_float2(acc[4 * j + 0], acc[4 * j + 2]));
            ec[y] = cfma(lam, ec[y], make_float2(acc[4 * j + 1], acc[4 * j + 3]));
          }
        float2 e = cfma(p16, ec[0], ec[1]);
        if (!last) e = cfma(p8, e, ec[2]);
        {
          float2 v = make_float2(__shfl_up_sync(0xffffffffu, e.x, 1, 4), __shfl_up_sync(0xffffffffu, e.y, 1, 4));
          if (q >= 1) e = cfma(pL, v, e);
          v = make_float2(__shfl_up_sync(0xffffffffu, e.x, 2, 4), __shfl_up_sync(0xffffffffu, e.y, 2, 4));
          if (q >= 2) e = cfma(p2L, v, e);
        }
        if (!last && (q == 3 || (q == 2 && l == 0))) rec_st(&g_E[((q == 3 ? l : 1) * NT1 + T1) * DM + ch], e.x, e.y, q == 3 ? tag : tag - 1);
        if (tid == 0) TS(3 + 8 * l);
        float2 ex = make_float2(__shfl_up_sync(0xffffffffu, e.x, 1, 4), __shfl_up_sync(0xffffffffu, e.y, 1, 4));
        if (q == 0) ex = make_float2(0.f, 0.f);
        const float2 coef = lds64f(ca + 8), lamc = make_float2(lam.x, p.swap ? lam.y : -lam.y);
        float m00 = coef.x, m01 = -coef.y, m10 = -coef.y, m11 = -coef.x;
        if (p.swap) { m00 = -coef.y; m01 = coef.x; m10 = -coef.x; m11 = -coef.y; }
        float2 pLq, p160q, p640;
        {
          const float2 p80 = last ? cmul(p2L, p16) : p2L, p160 = cmul(p80, p80), p320 = cmul(p160, p160), one = make_float2(1.f, 0.f);
          p640 = cmul(p320, p320);
          pLq = cmul((q & 1) ? pL : one, (q & 2) ? p2L : one);
          p160q = cmul((q & 1) ? p160 : one, (q & 2) ? p320 : one);
        }
        float2 c, ev[3];
        unsigned tg[3];
        const uint4* ep = &g_E[(l * NT1 + T1 - 1 - q) * DM + ch];
#pragma unroll
        for (int j = 0; j < 20; j++) {
          if (j == CPOLL) {
#pragma unroll
            for (int i = 0; i < 3; i++) {
              ev[i] = make_float2(0.f, 0.f); tg[i] = tag;
              if (T1 - 1 - q - 4 * i >= 0) tg[i] = rec_ld(ep - 4 * i * DM, ev[i].x, ev[i].y);
            }
          }
#pragma unroll
          for (int x = 0; x < 2; x++) {
            const float b0 = acc[4 * j + x], b1 = acc[4 * j + 2 + x];
            acc[4 * j + x] = fmaf(b0, m00, b1 * m01);
            acc[4 * j + 2 + x] = fmaf(b0, m10, b1 * m11);
          }
          if (j == CPOLL - 1 || j == 19) asm volatile("" : "+f"(acc[4 * j]), "+f"(acc[4 * j + 1]), "+f"(acc[4 * j + 2]), "+f"(acc[4 * j + 3])::"memory");
        }
        {
          uint32_t it = 0;
          while (__any_sync(0xffffffffu, tg[0] != tag || tg[1] != tag || tg[2] != tag)) {
#pragma unroll
            for (int i = 0; i < 3; i++)
              if (tg[i] != tag) tg[i] = rec_ld(ep - 4 * i * DM, ev[i].x, ev[i].y);
            trap_if(++it > SPIN_LIMIT);
          }
          c = cfma(p640, cfma(p640, ev[2], ev[1]), ev[0]);
          c = cmul(c, p160q);
          c.x += __shfl_xor_sync(0xffffffffu, c.x, 1); c.y += __shfl_xor_sync(0xffffffffu, c.y, 1);
          c.x += __shfl_xor_sync(0xffffffffu, c.x, 2); c.y += __shfl_xor_sync(0xffffffffu, c.y, 2);
        }
        if (tid == 0) TS(4 + 8 * l);
        if (wg == 1 && l >= HOLD0) mbar_wait(bars + 8 * (B_REL + l));
        c = cfma(pLq, c, ex);
        float2 hh = make_float2(fmaf(c.x, m00, c.y * m01), fmaf(c.x, m10, c.y * m11));
        uint8_t* hb = g_h + (size_t)l * (32 * 20 * 8192) + (10 * wg + 2 * GP) * 8192 + (4 * side + w) * 1024 + (tid_opaque() & 31) * 4;
#pragma unroll
        for (int j4 = 0; j4 < 5; j4++) {
          const int ng = 20 * T1 + 4 * j4;
          uint8_t* hp = hb + (size_t)(ng >> 3) * 163840 + (ng & 7) * 128;
#pragma unroll
          for (int jj = 0; jj < 4; jj++) {
            const int j = 4 * j4 + jj;
            const float2 h0 = cfma(lamc, hh, make_float2(acc[4 * j + 0], acc[4 * j + 2]));
            hh = cfma(lamc, h0, make_float2(acc[4 * j + 1], acc[4 * j + 3]));
            if (j4 < 4 || !last) {
              *(uint32_t*)(hp + jj * 128) = pack_bf16(h0.x, hh.x);
              *(uint32_t*)(hp + jj * 128 + 8192) = pack_bf16(h0.y, hh.y);
            }
          }
        }
        mbar_arrive(bars + 8 * (B_HST + 2 * l + wg));
        if (tid == 0) TS(5 + 8 * l);
        if (tid == 128) TS(l ? 25 : 19);
        if (l == 0 && wid == 4) {
          mbar_wait(bars + 8 * B_HST);
          mbar_wait(bars + 8 * (B_HST + 1));
          if ((tid & 31) < 8) h_release((tid >> 2) & 1, T1, tid & 3);
          __syncwarp();
          if (tid == 128) { mbar_arrive(bars + 8 * B_REL); TS(6); }
        }
      }
      if (l == 0) {
        ROLE(role)
        if (has2) {
          CvCtx cc;
          mbar_wait(bars + 8 * B_CTAB);
          cv_setup(cc);
          mbar_wait(bars + 8 * (B_G1DONE + 9));
#pragma unroll 1
          for (int c = (wg + 2) & 3; c < 5; c += 4) conv_channel(c, cc);
          if ((tid & 127) == 0) TS(wg == 2 ? 32 : (wg == 3 ? 50 : 7 + wg));
        }
      }
      if (wg >= 2) break;
    }
    if (wg == 3) {
    ROLE(role)
    const int pw = wid & 3, gpc = 2 * min(m2 >> 3, 3) + (dg >> 1);
    mbar_wait(bars + 8 * B_EP);
    const unsigned tag = lds32(sb + EP_OFF + 20);
    if (pw == 0) {
      if (elect_one()) {
#pragma unroll 1
        for (int l = 0; l < 2; l++) {
          uint32_t dst = sb;
          if (l == 1) {
            dst = sb + G2_WOFF;
#pragma unroll 1
            for (int k = 0; k < 10; k++) {
              mbar_wait(k > 4 ? bars + 8 * (B_G1DONE + 5 + k) : (has2 ? bars + 8 * (B_G2DONE + 14 + min(k, 3)) : bars + 8 * (B_G1DONE + 9)));
              mbar_expect_tx(bars + 8 * (B_G1FULL + 10 + k), 16384);
              tma5(dst, &p.mB, 64 * k, 0, 0, 4 * side, 2 * GP, bars + 8 * (B_G1FULL + 10 + k));
              dst += 16384; if (k == 4) dst = sb + G2_WOFF;
            }
          }
          if (has2) {
            const uint32_t fb2 = bars + 8 * (B_G2FULL + 20 * l), wb2 = bars + 8 * (B_G2DONE + 20 * l - S2);
            dst = sb + G2_WOFF + (WTAIL ? 4 * l * G2_WB : 0);
            int kc = 0;
#pragma unroll 1
            for (int k = 0; k < 20; k++) {
              mbar_wait(k >= S2 ? wb2 + 8 * k : bars + 8 * (l ? B_G1DONE + (WTAIL ? (k < 3 ? 15 + k : 13 + k) : 19) : (k == 5 ? B_XFREE : (k == 6 ? B_SFREE : B_REL))));
              mbar_expect_tx(fb2 + 8 * k, G2_WB);
              tma5(dst, &p.mCre + (k & 1), kc, 0, 0, 0, 10 * dg, fb2 + 8 * k);
              kc += (k & 1) << 7; if (k == 9) kc = 64;
              dst += G2_WB; if (dst == sb + G2_WOFF + S2 * G2_WB) dst = sb + G2_WOFF;
            }
          }
        }
      }
    } else if (pw == 1) {
#pragma unroll 1
      for (int l = 0; l < 2; l++) {
        if (l == 1) {
          mbar_wait(bars + 8 * (has2 ? B_G2DONE + 19 : B_G1DONE + 9));
          if (has2) mbar_wait(bars + 8 * B_UST);
          cnt_poll(&g_ucnt[gpc * 32], 128 * tag);
          fence_async_global();
          if (elect_one()) {
            TS(20);
            const int bytes = last ? 16384 : 20480;
            const uint8_t* src = g_u + T1 * 204800;
            uint32_t dst = sb + X1_OFF;
#pragma unroll 1
            for (int k = 0; k < 10; k++) {
              if (k > 4) mbar_wait(bars + 8 * (B_G1DONE + 5 + k));
              mbar_expect_tx(bars + 8 * (B_G1FULL + 10 + k), bytes);
              bulk_g2s(dst, src, bytes, bars + 8 * (B_G1FULL + 10 + k));
              src += 20480; dst += 20480; if (dst == sb + G_OFF) dst = sb; if (k == 4) dst = sb + X1_OFF;
            }
          }
          __syncwarp();
        }
        if (has2) {
          mbar_wait(bars + 8 * (B_HST + 2 * l));
          mbar_wait(bars + 8 * (B_G1DONE + 10 * l + 9));
          cnt_poll(&g_hcnt[(l * 16 + gpc) * 32], 40 * tag);
          fence_async_global();
          if (elect_one()) {
            TS(21 + 2 * l);
            const uint32_t fb2 = bars + 8 * (B_G2FULL + 20 * l), wb2 = bars + 8 * (B_G2DONE + 20 * l - S2);
            const uint8_t* src = g_h + (l * 32 + m2) * 163840;
            uint32_t dst = sb;
#pragma unroll 1
            for (int k = 0; k < 20; k++) {
              if (k >= 5) mbar_wait(k >= S2 ? wb2 + 8 * k : bars + 8 * B_SFREE);
              if (k == 10) { mbar_wait(bars + 8 * (B_H1 + l)); fence_async_global(); }
              mbar_expect_tx(fb2 + 8 * k, G2_XB);
              bulk_g2s(dst, src, G2_XB, fb2 + 8 * k);
              src += 8192; dst += G2_XB; if (dst == sb + S2 * G2_XB) dst = sb;
            }
          }
          __syncwarp();
        }
      }
    } else if (pw == 2) {
#pragma unroll 1
      for (int l = 0; l < 2; l++) {
        if (l == 1) {
          float xa[2], xb[2];
          mbar_wait(bars + 8 * (B_G1FULL + 11));
          stat_table(T1, tag, 1, 4, g_stats, g_stats, xa, xb);
          mbar_arrive(bars + 8 * (B_STAB + 1));
        }
#pragma unroll 1
        for (int w = 0; w < 2 * l; w++) {
          mbar_wait(bars + 8 * (B_HST + 2 + w));
          if (lane < 4) h_release(2 + w, T1, lane);
          __syncwarp();
          if (lane == 0) { if (w == 0) mbar_arrive(bars + 8 * (B_REL + 1)); TS(w ? 16 : 14); }
        }
        if (l == 0 && has2 && elect_one()) {
#pragma unroll 1
          for (int i = 0; i < 5; i++) {
            const int c = i < 3 ? i : 7 - i;
            mbar_wait(bars + 8 * (B_CVDONE + c));
            bulk_s2g(g_G + (cch0 + 32 * c) * 4096, cv_stage(c), 4096);
          }
          asm volatile("cp.async.bulk.commit_group;" ::: "memory");
          asm volatile("cp.async.bulk.wait_group.read 0;" ::: "memory");
          mbar_arrive(bars + 8 * B_SFREE);
          asm volatile("cp.async.bulk.wait_group 0;" ::: "memory");
          TS(48);
          fence_async_global();
          asm volatile("fence.acq_rel.gpu;" ::: "memory");
#pragma unroll
          for (int i = 0; i < 4; i++) red_rlx(&g_gcnt[(dg * 4 + i) * 32]);
          TS(49);
          mbar_arrive(bars + 8 * (B_GO + 1));
        }
        __syncwarp();
      }
    } else if (has2) {
      mbar_wait(bars + 8 * B_REL);
      if (elect_one()) {
        l2_prefetch(p.cre + (160 * dg + 5 * m2) * DM, 6400); l2_prefetch(p.cim + (160 * dg + 5 * m2) * DM, 6400);
        asm volatile("prefetch.tensormap [%0];" ::"l"(&p.mG) : "memory");
      }
      mbar_wait(bars + 8 * (B_HST + 1));
      flag_poll(&g_hcnt[(8 + gpc) * 32], 40 * tag);
      if (lane == 0) { mbar_arrive(bars + 8 * B_H1); TS(22); }
      mbar_wait(bars + 8 * (B_GO + 1));
      flag_poll(&g_gcnt[(dg * 4 + (m2 >> 3)) * 32], 32 * tag);
      fence_async_global();
      if (elect_one()) {
        TS(29);
        mbar_expect_tx(bars + 8 * B_GFULL, 20480);
        tma5(sb + G_OFF, &p.mG, 64 * m2, 0, 0, 0, 10 * dg, bars + 8 * B_GFULL);
      }
      mbar_wait(bars + 8 * (B_HST + 3));
      cnt_poll(&g_hcnt[(24 + gpc) * 32], 40 * tag);
      if (lane == 0) { mbar_arrive(bars + 8 * (B_H1 + 1)); TS(24); }
    }
    } else if (wg == 2 && (role >> 16)) {
      float acc[80];
      float off[2] = {mean0[0], mean0[1]};
      const unsigned tag = lds32(sb + EP_OFF + 20);
      dskip_init<true>(acc, mean0, rstd0);
      mbar_arrive(bars + 8 * B_XFREE);
#pragma unroll 1
      for (int l = 0; l < 2; l++) {
        float mean[2], rstd[2];
        {
          uint32_t alo = desc_lo(sb, 1024), blo = desc_lo(sb + G2_WOFF, 16) + (WTAIL ? l * (G2_WB >> 2) : 0);
          uint32_t fb = bars + 8 * (B_G2FULL + 20 * l);
          fence_regs(acc);
          mbar_wait(bars + 8 * (B_CVDONE + 2));
          mbar_wait(bars + 8 * (B_CVDONE + 3));
          mbar_wait(fb);
          if (tid == 256) TS(33 + 6 * l);
#pragma unroll 1
          for (int k = 0; k < 20; k++) {
            if (l == TSL && (k & 3) == 3 && tid == 256) TS(56 + (k >> 2));
            uint32_t ok; const uint32_t nb = k < 19 ? fb + 8 : fb;
            wgmma_fence();
#pragma unroll
            for (int kk = 0; kk < 4; kk++) {
              wgmma_n160<1>(acc, alo + kk * 128, desc_hi(128, 0), blo + kk * 2, desc_hi(1024, 1));
              if (kk == 0) ok = mbar_test(nb);
            }
            wgmma_commit();
            alo += G2_XB >> 4; blo += G2_WB >> 4;
            if (alo == desc_lo(sb + S2 * G2_XB, 1024)) alo = desc_lo(sb, 1024);
            if (blo == desc_lo(sb + G_OFF, 16)) blo = desc_lo(sb + G2_WOFF, 16);
            wgmma_wait<1>();
            if (k > 0 && tid == 256) mbar_arrive(fb + 8 * (B_G2DONE - B_G2FULL - 1));
            if (!ok) mbar_wait(nb);
            fb += 8;
          }
          wgmma_wait<0>();
          fence_regs(acc);
          if (tid == 256) TS(34 + 6 * l);
          if (tid == 256) mbar_arrive(bars + 8 * (B_G2DONE + 20 * l + 19));
        }
        ROLE(role)
        const int tq = tid_opaque() & 31, n0 = 64 * m2 + 16 * w + (tq >> 2);
        stats_publish<false>(2 * l + 1, n0, dg, tag, acc);
        uint32_t gf[10][4];
        mbar_wait(bars + 8 * B_GFULL);
        const uint32_t ga = sb + G_OFF + (8 * (tq >> 4) + (tq & 7)) * 128 + (((2 * w + ((tq >> 3) & 1)) ^ ((2 * m2) & 6) ^ (tq & 7)) << 4);
#pragma unroll
        for (int J = 0; J < 2; J++) ldsm4t(gf[J], ga + J * 2048);
        if (tid == 256) TS(35 + 6 * l);
        uint8_t* dst[2][2];
#pragma unroll
        for (int h = 0; h < 2; h++) {
          if (l == 0) {
            const int ng = 8 * m2 + 2 * w + h, T = ng / 20;
            uint8_t* ub = g_u + (T * 204800 + (ng - 20 * T) * 1024 + (tq & 2) * 64 + (tq & 28) * 4 + (tq & 1) * 8 + (5 * dg >> 1) * 20480);
            dst[h][1] = ub + ((dg & 1) ? 20480 - 512 : 0);
            dst[h][0] = ub + (dg & 1) * 512;
          } else {
            dst[h][0] = dst[h][1] = (uint8_t*)(p.out + (n_to_t(n0 + 8 * h) * DM + 160 * dg + 4 * (tq & 3)));
          }
        }
        stats_get(2 * l + 1, n0, tag, mean, rstd);
        if (tid == 256) TS(36 + 6 * l);
        off[0] += mean[0]; off[1] += mean[1];
        const float ov[2] = {l ? off[0] : 0.f, l ? off[1] : 0.f};
#pragma unroll
        for (int J = 0; J < 10; J++) {
          if (J + 2 < 10) ldsm4t(gf[J + 2 < 10 ? J + 2 : 0], ga + (J + 2) * 2048);
#pragma unroll
          for (int x = 0; x < 8; x++) {
            const int h = (x >> 1) & 1;
            const uint32_t gwd = gf[J][x >> 1];
            const float t = fmaf(rstd[h], (x & 1) ? bf_hi(gwd) : bf_lo(gwd), 1.f);
            acc[8 * J + x] = fmaf(acc[8 * J + x], t, fmaf(-mean[h], t, ov[h]));
          }
#pragma unroll
          for (int h = 0; h < 2; h++) {
            if (l == 0)
              *(uint2*)(dst[h][(J >> 1) & 1] + (J >> 2) * 20480 + (J & 3) * 256) =
                  make_uint2(pack_bf16(acc[8 * J + 2 * h], acc[8 * J + 2 * h + 1]), pack_bf16(acc[8 * J + 4 + 2 * h], acc[8 * J + 5 + 2 * h]));
            else
              *(float4*)(dst[h][0] + 64 * J) = make_float4(acc[8 * J + 2 * h], acc[8 * J + 2 * h + 1], acc[8 * J + 4 + 2 * h], acc[8 * J + 5 + 2 * h]);
          }
          __syncwarp();
        }
        if (l == 0) {
          bar_sync(3, 128);
          if (tid == 288) { TS(37); mbar_arrive(bars + 8 * B_UST); }
          if (tid < 264) red_rel(&g_ucnt[(tid & 7) * 32]);
          __syncwarp();
          if (tid == 256) TS(38);
          stats_publish<false>(2, n0, dg, tag, acc);
          mbar_wait(bars + 8 * (B_G1FULL + 11));
          float xa[2], xb[2];
          const uint4* x0 = &g_stats[(8 + (tq & 3)) * SEQ + n0];
          stat_table(T1, tag, 1, w, x0, x0 + 8, xa, xb);
          mbar_arrive(bars + 8 * (B_STAB + 1));
          if (tid == 256) TS(27);
          stats_reduce(xa, xb, mean, rstd);
          off[0] += mean[0]; off[1] += mean[1];
          mbar_wait(bars + 8 * (B_HST + 2));
          dskip_init<false>(acc, mean, rstd);
        } else {
          if (tid == 256) {
            TS(43);
            if (m2 == 31 && dg == 3) asm volatile("st.relaxed.gpu.global.u32 [%0], %1;" ::"l"(g_epoch), "r"(tag + 1) : "memory");
          }
        }
      }
    }
  }
}

typedef CUresult (*EncFn)(CUtensorMap*, CUtensorMapDataType, cuuint32_t, void*, const cuuint64_t*, const cuuint64_t*,
                          const cuuint32_t*, const cuuint32_t*, CUtensorMapInterleave, CUtensorMapSwizzle,
                          CUtensorMapL2promotion, CUtensorMapFloatOOBfill);

void encode(EncFn fn, CUtensorMap* m, const void* ptr, int rank, const cuuint64_t* dims, const cuuint64_t* strides, const cuuint32_t* box,
            CUtensorMapSwizzle swz = CU_TENSOR_MAP_SWIZZLE_128B) {
  cuuint32_t es[5] = {1, 1, 1, 1, 1};
  fn(m, CU_TENSOR_MAP_DATA_TYPE_BFLOAT16, rank, (void*)ptr, dims, strides, box, es, CU_TENSOR_MAP_INTERLEAVE_NONE,
     swz, (CUtensorMapL2promotion)(swz == CU_TENSOR_MAP_SWIZZLE_128B ? PROM_A : PROM_B), CU_TENSOR_MAP_FLOAT_OOB_FILL_NONE);
}

}

extern "C" void kernel_launch(void* const* d_in, const int* in_sizes, int n_in, void* d_out, int out_size) {
  (void)in_sizes; (void)n_in; (void)out_size;
  Params p;
  typedef const __nv_bfloat16* BP;
  p.x = (BP)d_in[0]; p.lre = (BP)d_in[1]; p.lim = (BP)d_in[2]; p.bre = (BP)d_in[3]; p.bim = (BP)d_in[4];
  p.cre = (BP)d_in[5]; p.cim = (BP)d_in[6]; p.logdt = (BP)d_in[7]; p.dskip = (BP)d_in[8];
  p.k = (BP)d_in[10]; p.v = (BP)d_in[11]; p.shiftk = (BP)d_in[12]; p.ssmk = (BP)d_in[13]; p.ssmD = (BP)d_in[14];
  p.out = (float*)d_out;
  for (int sm = 0; sm < 132; sm++) {
    const int tpc = sm >> 1, side = sm & 1;
    int gpc, gi;
    if (tpc < 32) { gpc = tpc & 7; gi = tpc >> 3; }
    else if (tpc < 60) { gpc = 1 + (tpc - 32) % 7; gi = 4 + (tpc - 32) / 7; }
    else if (tpc < 62) { gpc = tpc - 54; gi = 8; }
    else { gpc = 0; gi = tpc - 58; }
    const int pos = 8 * gpc + gi + (gpc == 7 ? 1 : 0);
    int T1, GP;
    if (pos < 52) { const int hh = pos / 26, x = pos - 26 * hh; T1 = x >> 1; GP = 2 * hh + (x & 1); }
    else { T1 = pos - 52; GP = 4; }
    const int m2 = 8 * (gpc >> 1) + gi, dg = 2 * (gpc & 1) + side;
    p.role[sm] = pos == 65 ? -1 : (T1 | (GP << 4) | (side << 7) | (m2 << 8) | (dg << 14) | ((gi < 8) << 16));
  }
  void* fnp = nullptr;
  cudaDriverEntryPointQueryResult qr;
  cudaGetDriverEntryPoint("cuTensorMapEncodeTiled", &fnp, cudaEnableDefault, &qr);
  EncFn fn = (EncFn)fnp;
  void* gG = nullptr;
  cudaGetSymbolAddress(&gG, g_G);
  const cuuint64_t RB = DM * 2;
  {
    p.swap = p.bim < p.bre;
    const char* lo = (const char*)(p.swap ? p.bim : p.bre); const char* hi = (const char*)(p.swap ? p.bre : p.bim);
    cuuint64_t dims[5] = {640, 8, 2, 8, 10}, st[4] = {RB, (cuuint64_t)(hi - lo), 8 * RB, 64 * RB}; cuuint32_t box[5] = {64, 8, 2, 4, 2};
    encode(fn, &p.mB, lo, 5, dims, st, box);
  }
  {
    cuuint64_t dims[5] = {640, 2, 4, 2, 40}, st[4] = {RB, 4 * RB, 2 * RB, 16 * RB}; cuuint32_t box[5] = {64, 2, 4, 2, 10};
    encode(fn, &p.mCre, p.cre, 5, dims, st, box); encode(fn, &p.mCim, p.cim, 5, dims, st, box);
    cuuint64_t dimg[5] = {2048, 2, 4, 2, 40}, stg[4] = {4096, 4 * 4096, 2 * 4096, 16 * 4096};
    encode(fn, &p.mG, gG, 5, dimg, stg, box);
  }
  {
    cuuint64_t dims[4] = {640, 2, 4, 900}, st[3] = {RB, 40 * RB, 2 * RB}; cuuint32_t box[4] = {64, 2, 4, 20};
    encode(fn, &p.mX, p.x, 4, dims, st, box);
    cuuint64_t diml[4] = {640, 2, 4, 16}, stl[3] = {RB, 32 * RB, 2 * RB};
    encode(fn, &p.mXl, p.x + (size_t)1920 * DM, 4, diml, stl, box);
    cuuint32_t boxt[4] = {160, 2, 4, 4};
    encode(fn, &p.mXt, p.x, 4, dims, st, boxt, CU_TENSOR_MAP_SWIZZLE_NONE);
    encode(fn, &p.mXtl, p.x + (size_t)1920 * DM, 4, diml, stl, boxt, CU_TENSOR_MAP_SWIZZLE_NONE);
    cuuint64_t dk[3] = {640, 2000, 4}, sk[2] = {RB, 16 * RB}; cuuint32_t bk[3] = {32, 19, 4}, bv[3] = {32, 17, 4};
    encode(fn, &p.mK, p.k, 3, dk, sk, bk, CU_TENSOR_MAP_SWIZZLE_NONE);
    encode(fn, &p.mV, p.v, 3, dk, sk, bv, CU_TENSOR_MAP_SWIZZLE_NONE);
  }
  cudaFuncSetAttribute(fused_kernel, cudaFuncAttributeMaxDynamicSharedMemorySize, SMEM_BYTES);
  cudaLaunchConfig_t cfg = {};
  cfg.gridDim = dim3(132); cfg.blockDim = dim3(512); cfg.dynamicSmemBytes = SMEM_BYTES; cfg.stream = cudaStreamPerThread;
  cudaLaunchKernelEx(&cfg, fused_kernel, p);
}
```

```cpp
#include <cuda_runtime.h>
#include <cuda.h>
#include <cuda_bf16.h>
#include <stdint.h>

namespace {

constexpr int SEQ = 2048, DM = 640;
constexpr int NT1 = 13;
#define EXP 0
#define WPF1 3
#define WPF2 7
#define CPOLL 10
#define KV0 5
#define RGATE 20
#define PROM_A 2
#define PROM_B 2
#define XFIRST 0
#define TAPLATE 1
#define STG_D 3
#define STG_KK 1
#define HOLD0 1
#define WREL 0
#define UREL 1
#define TSL 1
#define TABW 0
#define STG0 3
#define WTAIL 1
#define PAUSE_K 4
constexpr uint32_t SPIN_LIMIT = 1u << 22;

__device__ __align__(1024) uint8_t g_h[2 * 32 * 20 * 8192];
__device__ __align__(1024) uint8_t g_u[NT1 * 10 * 20480];
__device__ __align__(1024) uint8_t g_kv[DM * 4096];
__device__ __align__(1024) uint8_t g_G[DM * 4096];
__device__ __align__(128) uint4 g_E[2 * NT1 * DM];
__device__ __align__(128) uint4 g_stats[4 * 4 * SEQ];
__device__ __align__(128) uint4 g_sB[DM * 2];
__device__ __align__(128) unsigned g_hcnt[2 * 2 * 8 * 32];
__device__ __align__(128) unsigned g_ucnt[8 * 32];
__device__ __align__(128) unsigned g_kvcnt[16 * 32];
__device__ __align__(128) unsigned g_gcnt[16 * 32];
__device__ __align__(128) unsigned g_epoch[32] = {1};
#define TS(i) do {} while (0)

struct Params {
  CUtensorMap mB, mCre, mCim, mX, mXl, mG, mK, mV, mXt, mXtl;
  const __nv_bfloat16 *x, *lre, *lim, *bre, *bim, *cre, *cim, *logdt, *dskip, *k, *v, *shiftk, *ssmk, *ssmD;
  float* out;
  int swap;
  int role[132];
};

constexpr uint32_t sb = 1024;
constexpr uint32_t G1_STAGE = 36864, G1_XOFF = 16384;
constexpr int S1 = 4;
constexpr uint32_t XT_OFF = 159744, KS_OFF = 180224, KV_PIECE = 9216;
constexpr uint32_t G2_XB = 8192, G2_WB = 20480, G2_WOFF = 57344, G_OFF = 200704;
constexpr uint32_t X1_OFF = 139264;
constexpr int S2 = 7;
constexpr uint32_t CV_OFF = KS_OFF, CV_K = 128, CV_PL = 2240, CV_U = CV_K + 4096, CV_B = KV_PIECE;
constexpr uint32_t MISC = 226304;
constexpr uint32_t BAR_OFF = MISC;
constexpr int B_G1FULL = 0, B_G1DONE = 20, B_G2FULL = 40,
              B_G2DONE = 85, B_GFULL = 125, B_EP = 126, B_H1 = 127  , B_CVFULL = 129  , B_STG = 134  , B_REL = 136  , B_SFREE = 138, B_UST = 142,
              B_GO = 139  , B_PUB = 147,
              B_CVDONE = 148  , B_STAB = 153  , B_XFREE = 155, B_HST = 156  ,
              B_CTAB = 160, B_PREP = 161, B_XT = 162, B_KV = 163  ;
constexpr uint32_t bars = sb + BAR_OFF;
constexpr uint32_t STAB_OFF = MISC + 1344;
constexpr uint32_t CTAB_OFF = STAB_OFF + 1280;
constexpr uint32_t DTAB_OFF = CTAB_OFF + 1536;
constexpr uint32_t EP_OFF = DTAB_OFF + 320;
constexpr uint32_t SO_OFF = EP_OFF + 32;
constexpr uint32_t TAP_OFF = 147456;
constexpr uint32_t SMEM_BYTES = 232448;
static_assert(SO_OFF + 1536 <= SMEM_BYTES, "smem");

__device__ __forceinline__ void trap_if(bool c) { asm volatile("{\n.reg .pred p;\nsetp.ne.u32 p, %0, 0;\n@p trap;\n}\n" ::"r"((uint32_t)c)); }
__device__ __forceinline__ uint32_t smem_u32(const void* p) { return (uint32_t)__cvta_generic_to_shared(p); }
__device__ __forceinline__ void mbar_init(uint32_t bar, int cnt) { asm volatile("mbarrier.init.shared::cta.b64 [%0], %1;" ::"r"(bar), "r"(cnt) : "memory"); }
__device__ __forceinline__ void mbar_expect_tx(uint32_t bar, int bytes) { asm volatile("mbarrier.arrive.expect_tx.shared::cta.b64 _, [%0], %1;" ::"r"(bar), "r"(bytes) : "memory"); }
__device__ __forceinline__ void mbar_arrive(uint32_t bar) { asm volatile("mbarrier.arrive.shared::cta.b64 _, [%0];" ::"r"(bar) : "memory"); }
__device__ __forceinline__ void mbar_wait(uint32_t bar) {
  asm volatile(
      "{\n.reg .pred p;\n.reg .u32 c;\nmov.u32 c, 0;\n"
      "W_%=:\nmbarrier.try_wait.parity.shared::cta.b64 p, [%0], 0;\n@p bra D_%=;\n"
      "add.u32 c, c, 1;\nsetp.lt.u32 p, c, %1;\n@p bra W_%=;\ntrap;\nD_%=:\n}\n" ::"r"(bar), "n"(SPIN_LIMIT) : "memory");
}
__device__ __forceinline__ uint32_t mbar_test(uint32_t bar) {
  uint32_t ok;
  asm volatile("{\n.reg .pred p;\nmbarrier.test_wait.parity.shared::cta.b64 p, [%1], 0;\nselp.u32 %0, 1, 0, p;\n}\n" : "=r"(ok) : "r"(bar) : "memory");
  return ok;
}
__device__ __forceinline__ void tma3(uint32_t dst, const CUtensorMap* m, int c0, int c1, int c2, uint32_t bar) {
  asm volatile("cp.async.bulk.tensor.3d.shared::cluster.global.mbarrier::complete_tx::bytes [%0], [%1, {%3,%4,%5}], [%2];"
               ::"r"(dst), "l"(m), "r"(bar), "r"(c0), "r"(c1), "r"(c2) : "memory");
}
__device__ __forceinline__ void tma4(uint32_t dst, const CUtensorMap* m, int c0, int c1, int c2, int c3, uint32_t bar) {
  asm volatile("cp.async.bulk.tensor.4d.shared::cluster.global.mbarrier::complete_tx::bytes [%0], [%1, {%3,%4,%5,%6}], [%2];"
               ::"r"(dst), "l"(m), "r"(bar), "r"(c0), "r"(c1), "r"(c2), "r"(c3) : "memory");
}
__device__ __forceinline__ void tma5(uint32_t dst, const CUtensorMap* m, int c0, int c1, int c2, int c3, int c4, uint32_t bar) {
  asm volatile("cp.async.bulk.tensor.5d.shared::cluster.global.mbarrier::complete_tx::bytes [%0], [%1, {%3,%4,%5,%6,%7}], [%2];"
               ::"r"(dst), "l"(m), "r"(bar), "r"(c0), "r"(c1), "r"(c2), "r"(c3), "r"(c4) : "memory");
}
__device__ __forceinline__ void bulk_g2s(uint32_t dst, const void* src, int bytes, uint32_t bar) {
  asm volatile("cp.async.bulk.shared::cluster.global.mbarrier::complete_tx::bytes [%0], [%1], %2, [%3];"
               ::"r"(dst), "l"(src), "r"(bytes), "r"(bar) : "memory");
}
__device__ __forceinline__ void bulk_s2g(void* dst, uint32_t src, int bytes) {
  asm volatile("cp.async.bulk.global.shared::cta.bulk_group [%0], [%1], %2;" ::"l"(dst), "r"(src), "r"(bytes) : "memory");
}
__device__ __forceinline__ void l2_prefetch(const void* src, int bytes) {
  asm volatile("cp.async.bulk.prefetch.L2.global [%0], %1;" ::"l"(src), "r"(bytes) : "memory");
}
__device__ __forceinline__ void wgmma_fence() { asm volatile("wgmma.fence.sync.aligned;" ::: "memory"); }
__device__ __forceinline__ void wgmma_commit() { asm volatile("wgmma.commit_group.sync.aligned;" ::: "memory"); }
template <int N> __device__ __forceinline__ void wgmma_wait() { asm volatile("wgmma.wait_group.sync.aligned %0;" ::"n"(N) : "memory"); }
__host__ __device__ constexpr uint32_t desc_lo(uint32_t addr, uint32_t lbo) { return ((addr & 0x3FFFF) >> 4) | ((lbo >> 4) << 16); }
__host__ __device__ constexpr uint32_t desc_hi(uint32_t sbo, uint32_t swz) { return (sbo >> 4) | (swz << 30); }
__device__ __forceinline__ void bar_sync(int id, int n) { asm volatile("bar.sync %0, %1;" ::"r"(id), "r"(n) : "memory"); }
__device__ __forceinline__ uint32_t lds32(uint32_t a) { uint32_t v; asm volatile("ld.shared.u32 %0, [%1];" : "=r"(v) : "r"(a) : "memory"); return v; }
__device__ __forceinline__ float2 lds64f(uint32_t a) { float2 v; asm volatile("ld.shared.v2.f32 {%0,%1}, [%2];" : "=f"(v.x), "=f"(v.y) : "r"(a) : "memory"); return v; }
__device__ __forceinline__ float4 lds128f(uint32_t a) { float4 v; asm volatile("ld.shared.v4.f32 {%0,%1,%2,%3}, [%4];" : "=f"(v.x), "=f"(v.y), "=f"(v.z), "=f"(v.w) : "r"(a) : "memory"); return v; }
__device__ __forceinline__ void ldsm4t(uint32_t (&r)[4], uint32_t a) {
  asm volatile("ldmatrix.sync.aligned.m8n8.x4.trans.shared.b16 {%0,%1,%2,%3}, [%4];" : "=r"(r[0]), "=r"(r[1]), "=r"(r[2]), "=r"(r[3]) : "r"(a) : "memory");
}
__device__ __forceinline__ uint4 ldv128(const void* a) { uint4 v; asm volatile("ld.global.nc.v4.u32 {%0,%1,%2,%3}, [%4];" : "=r"(v.x), "=r"(v.y), "=r"(v.z), "=r"(v.w) : "l"(a) : "memory"); return v; }
__device__ __forceinline__ uint2 ldv64(const void* a) { uint2 v; asm volatile("ld.global.nc.v2.u32 {%0,%1}, [%2];" : "=r"(v.x), "=r"(v.y) : "l"(a) : "memory"); return v; }
__device__ __forceinline__ uint32_t ldv16(const void* a) { uint32_t v; asm volatile("ld.global.nc.u16 %0, [%1];" : "=r"(v) : "l"(a) : "memory"); return v; }
__device__ __forceinline__ void sts128(uint32_t a, uint4 v) { asm volatile("st.shared.v4.u32 [%0], {%1,%2,%3,%4};" ::"r"(a), "r"(v.x), "r"(v.y), "r"(v.z), "r"(v.w) : "memory"); }
__device__ __forceinline__ void sts32(uint32_t a, uint32_t v) { asm volatile("st.shared.u32 [%0], %1;" ::"r"(a), "r"(v) : "memory"); }
__device__ __forceinline__ void sts64f(uint32_t a, float x, float y) { asm volatile("st.shared.v2.f32 [%0], {%1,%2};" ::"r"(a), "f"(x), "f"(y) : "memory"); }
__device__ __forceinline__ void red_rlx(unsigned* p) { asm volatile("red.relaxed.gpu.global.add.u32 [%0], 1;" ::"l"(p) : "memory"); }
__device__ __forceinline__ void red_rel(unsigned* p) { asm volatile("red.release.gpu.global.add.u32 [%0], 1;" ::"l"(p) : "memory"); }
__device__ __forceinline__ void fence_async_global() { asm volatile("fence.proxy.async.global;" ::: "memory"); }
__device__ __forceinline__ void fence_async_smem() { asm volatile("fence.proxy.async.shared::cta;" ::: "memory"); }
__device__ __forceinline__ void rec_st(uint4* p, float a, float b, unsigned tag) {
  asm volatile("{\n.reg .b128 t;\n.reg .b64 lo, hi;\nmov.b64 lo, {%1,%2};\nmov.b64 hi, {%3,%3};\nmov.b128 t, {lo,hi};\n"
               "st.relaxed.gpu.global.b128 [%0], t;\n}\n" ::"l"(p), "r"(__float_as_uint(a)), "r"(__float_as_uint(b)), "r"(tag) : "memory");
}
__device__ __forceinline__ unsigned rec_ld(const uint4* p, float& a, float& b) {
  unsigned x, y, t;
  asm volatile("{\n.reg .b128 t;\n.reg .b64 lo, hi;\n.reg .b32 u;\nld.relaxed.gpu.global.b128 t, [%3];\nmov.b128 {lo,hi}, t;\n"
               "mov.b64 {%0,%1}, lo;\nmov.b64 {%2,u}, hi;\n}\n" : "=r"(x), "=r"(y), "=r"(t) : "l"(p) : "memory");
  a = __uint_as_float(x); b = __uint_as_float(y);
  return t;
}
__device__ __forceinline__ unsigned ld_rlx(const unsigned* p) { unsigned v; asm volatile("ld.relaxed.gpu.global.u32 %0, [%1];" : "=r"(v) : "l"(p) : "memory"); return v; }
__device__ __forceinline__ void flag_poll(const unsigned* p, unsigned target) {
  uint32_t it = 0;
  while (!__all_sync(0xffffffffu, (int)(ld_rlx(p) - target) >= 0)) { trap_if(++it > SPIN_LIMIT); }
  asm volatile("fence.acquire.gpu;" ::: "memory");
}
__device__ __forceinline__ void cnt_poll(const unsigned* p, unsigned target) {
  unsigned a = ld_rlx(p); __nanosleep(100);
  unsigned b = ld_rlx(p); __nanosleep(100);
  unsigned c = ld_rlx(p);
  uint32_t it = 0;
  while (true) {
    if (__all_sync(0xffffffffu, (int)(a - target) >= 0)) break;
    a = ld_rlx(p);
    if (__all_sync(0xffffffffu, (int)(b - target) >= 0)) break;
    b = ld_rlx(p);
    if (__all_sync(0xffffffffu, (int)(c - target) >= 0)) break;
    c = ld_rlx(p);
    trap_if(++it > SPIN_LIMIT);
  }
  asm volatile("fence.acquire.gpu;" ::: "memory");
}
__device__ __forceinline__ void h_release(int idx, int T, int i) {
  const int Q = (i & 2) ? (T + 2) / 3 - 1 : T / 3;
  if (Q >= 0 && Q < 4 && ((i & 2) == 0 || T % 3 == 0)) red_rel(&g_hcnt[(idx * 8 + 2 * Q + (i & 1)) * 32]);
}
__device__ __forceinline__ uint32_t pack_bf16(float lo, float hi) {
  uint32_t r; asm("cvt.rn.bf16x2.f32 %0, %1, %2;" : "=r"(r) : "f"(hi), "f"(lo)); return r;
}
__device__ __forceinline__ float bf_lo(uint32_t w) { return __uint_as_float(w << 16); }
__device__ __forceinline__ float bf_hi(uint32_t w) { return __uint_as_float(w & 0xffff0000u); }
__device__ __forceinline__ uint32_t hmul2(uint32_t a, uint32_t b) {
  __nv_bfloat162 r = __hmul2_rn(*(__nv_bfloat162*)&a, *(__nv_bfloat162*)&b); return *(uint32_t*)&r;
}
__device__ __forceinline__ uint32_t hadd2(uint32_t a, uint32_t b) {
  __nv_bfloat162 r = __hadd2_rn(*(__nv_bfloat162*)&a, *(__nv_bfloat162*)&b); return *(uint32_t*)&r;
}
__device__ __forceinline__ float2 cmul(float2 a, float2 b) { return make_float2(a.x * b.x - a.y * b.y, a.x * b.y + a.y * b.x); }
__device__ __forceinline__ float2 cfma(float2 a, float2 b, float2 c) {
  return make_float2(fmaf(a.x, b.x, fmaf(-a.y, b.y, c.x)), fmaf(a.x, b.y, fmaf(a.y, b.x, c.y)));
}
template <int N> __device__ __forceinline__ void fence_regs(float (&a)[N]) {
#pragma unroll
  for (int i = 0; i < N; i++) asm volatile("" : "+f"(a[i])::"memory");
}
__device__ __forceinline__ bool elect_one() {
  uint32_t e; asm volatile("{\n.reg .pred P;\nelect.sync _|P, 0xffffffff;\nselp.u32 %0, 1, 0, P;\n}\n" : "=r"(e)); return e != 0;
}
__device__ __forceinline__ int tid_opaque() { int t; asm volatile("mov.u32 %0, %%tid.x;" : "=r"(t)); return t; }
struct Role { int T1, GP, side, m2, dg, cch0; bool last, has2; };
__device__ __forceinline__ Role unpack_role(int x) {
  Role r; r.T1 = x & 15; r.GP = (x >> 4) & 7; r.side = (x >> 7) & 1; r.m2 = (x >> 8) & 63; r.dg = (x >> 14) & 3;
  r.has2 = (x >> 16) & 1; r.last = r.T1 == NT1 - 1; r.cch0 = 160 * r.dg + r.m2; return r;
}
__device__ __forceinline__ Role fresh_role(int x) { asm volatile("" : "+r"(x)); return unpack_role(__shfl_sync(0xffffffffu, x, 0)); }
#define ROLE(x) const Role R_ = fresh_role(x); const int T1 = R_.T1, GP = R_.GP, side = R_.side, m2 = R_.m2, dg = R_.dg, cch0 = R_.cch0; \
  const bool last = R_.last, has2 = R_.has2; (void)T1; (void)GP; (void)side; (void)m2; (void)dg; (void)cch0; (void)last; (void)has2;
__device__ __forceinline__ int n_to_t(int n) {
  int T = n / 160, nl = n - T * 160;
  int L = (T == NT1 - 1) ? 32 : 40;
  return T * 160 + L * ((nl & 7) >> 1) + 2 * (nl >> 3) + (nl & 1);
}

template<int TA> __device__ __forceinline__ void wgmma_n160(float (&d)[80], uint32_t alo, uint32_t ahi, uint32_t blo, uint32_t bhi){
  asm volatile("{\n.reg .b64 da, db;\nmov.b64 da, {%80,%81};\nmov.b64 db, {%82,%83};\n"
    "wgmma.mma_async.sync.aligned.m64n160k16.f32.bf16.bf16 {%0, %1, %2, %3, %4, %5, %6, %7, %8, %9, %10, %11, %12, %13, %14, %15, %16, %17, %18, %19, %20, %21, %22, %23, %24, %25, %26, %27, %28, %29, %30, %31, %32, %33, %34, %35, %36, %37, %38, %39, %40, %41, %42, %43, %44, %45, %46, %47, %48, %49, %50, %51, %52, %53, %54, %55, %56, %57, %58, %59, %60, %61, %62, %63, %64, %65, %66, %67, %68, %69, %70, %71, %72, %73, %74, %75, %76, %77, %78, %79}, da, db, 1, 1, 1, %84, 0;\n}\n"
    : "+f"(d[0]), "+f"(d[1]), "+f"(d[2]), "+f"(d[3]), "+f"(d[4]), "+f"(d[5]), "+f"(d[6]), "+f"(d[7]), "+f"(d[8]), "+f"(d[9]), "+f"(d[10]), "+f"(d[11]), "+f"(d[12]), "+f"(d[13]), "+f"(d[14]), "+f"(d[15]), "+f"(d[16]), "+f"(d[17]), "+f"(d[18]), "+f"(d[19]), "+f"(d[20]), "+f"(d[21]), "+f"(d[22]), "+f"(d[23]), "+f"(d[24]), "+f"(d[25]), "+f"(d[26]), "+f"(d[27]), "+f"(d[28]), "+f"(d[29]), "+f"(d[30]), "+f"(d[31]), "+f"(d[32]), "+f"(d[33]), "+f"(d[34]), "+f"(d[35]), "+f"(d[36]), "+f"(d[37]), "+f"(d[38]), "+f"(d[39]), "+f"(d[40]), "+f"(d[41]), "+f"(d[42]), "+f"(d[43]), "+f"(d[44]), "+f"(d[45]), "+f"(d[46]), "+f"(d[47]), "+f"(d[48]), "+f"(d[49]), "+f"(d[50]), "+f"(d[51]), "+f"(d[52]), "+f"(d[53]), "+f"(d[54]), "+f"(d[55]), "+f"(d[56]), "+f"(d[57]), "+f"(d[58]), "+f"(d[59]), "+f"(d[60]), "+f"(d[61]), "+f"(d[62]), "+f"(d[63]), "+f"(d[64]), "+f"(d[65]), "+f"(d[66]), "+f"(d[67]), "+f"(d[68]), "+f"(d[69]), "+f"(d[70]), "+f"(d[71]), "+f"(d[72]), "+f"(d[73]), "+f"(d[74]), "+f"(d[75]), "+f"(d[76]), "+f"(d[77]), "+f"(d[78]), "+f"(d[79])
    : "r"(alo), "r"(ahi), "r"(blo), "r"(bhi), "n"(TA));
}
template<int N> __device__ __forceinline__ void wgmma_rs_hi(float (&d)[64], uint32_t a0, uint32_t a1, uint32_t a2, uint32_t a3, uint32_t blo);
template<> __device__ __forceinline__ void wgmma_rs_hi<16>(float (&d)[64], uint32_t a0, uint32_t a1, uint32_t a2, uint32_t a3, uint32_t blo){
  asm volatile("{\n.reg .b64 db;\nmov.b64 db, {%12,8};\nwgmma.mma_async.sync.aligned.m64n16k16.f32.bf16.bf16 {%0, %1, %2, %3, %4, %5, %6, %7}, {%8,%9,%10,%11}, db, 1, 1, 1, 0;\n}\n"
    : "+f"(d[56]), "+f"(d[57]), "+f"(d[58]), "+f"(d[59]), "+f"(d[60]), "+f"(d[61]), "+f"(d[62]), "+f"(d[63])
    : "r"(a0), "r"(a1), "r"(a2), "r"(a3), "r"(blo));
}
template<> __device__ __forceinline__ void wgmma_rs_hi<32>(float (&d)[64], uint32_t a0, uint32_t a1, uint32_t a2, uint32_t a3, uint32_t blo){
  asm volatile("{\n.reg .b64 db;\nmov.b64 db, {%20,8};\nwgmma.mma_async.sync.aligned.m64n32k16.f32.bf16.bf16 {%0, %1, %2, %3, %4, %5, %6, %7, %8, %9, %10, %11, %12, %13, %14, %15}, {%16,%17,%18,%19}, db, 1, 1, 1, 0;\n}\n"
    : "+f"(d[48]), "+f"(d[49]), "+f"(d[50]), "+f"(d[51]), "+f"(d[52]), "+f"(d[53]), "+f"(d[54]), "+f"(d[55]), "+f"(d[56]), "+f"(d[57]), "+f"(d[58]), "+f"(d[59]), "+f"(d[60]), "+f"(d[61]), "+f"(d[62]), "+f"(d[63])
    : "r"(a0), "r"(a1), "r"(a2), "r"(a3), "r"(blo));
}
template<> __device__ __forceinline__ void wgmma_rs_hi<48>(float (&d)[64], uint32_t a0, uint32_t a1, uint32_t a2, uint32_t a3, uint32_t blo){
  asm volatile("{\n.reg .b64 db;\nmov.b64 db, {%28,8};\nwgmma.mma_async.sync.aligned.m64n48k16.f32.bf16.bf16 {%0, %1, %2, %3, %4, %5, %6, %7, %8, %9, %10, %11, %12, %13, %14, %15, %16, %17, %18, %19, %20, %21, %22, %23}, {%24,%25,%26,%27}, db, 1, 1, 1, 0;\n}\n"
    : "+f"(d[40]), "+f"(d[41]), "+f"(d[42]), "+f"(d[43]), "+f"(d[44]), "+f"(d[45]), "+f"(d[46]), "+f"(d[47]), "+f"(d[48]), "+f"(d[49]), "+f"(d[50]), "+f"(d[51]), "+f"(d[52]), "+f"(d[53]), "+f"(d[54]), "+f"(d[55]), "+f"(d[56]), "+f"(d[57]), "+f"(d[58]), "+f"(d[59]), "+f"(d[60]), "+f"(d[61]), "+f"(d[62]), "+f"(d[63])
    : "r"(a0), "r"(a1), "r"(a2), "r"(a3), "r"(blo));
}
template<> __device__ __forceinline__ void wgmma_rs_hi<64>(float (&d)[64], uint32_t a0, uint32_t a1, uint32_t a2, uint32_t a3, uint32_t blo){
  asm volatile("{\n.reg .b64 db;\nmov.b64 db, {%36,8};\nwgmma.mma_async.sync.aligned.m64n64k16.f32.bf16.bf16 {%0, %1, %2, %3, %4, %5, %6, %7, %8, %9, %10, %11, %12, %13, %14, %15, %16, %17, %18, %19, %20, %21, %22, %23, %24, %25, %26, %27, %28, %29, %30, %31}, {%32,%33,%34,%35}, db, 1, 1, 1, 0;\n}\n"
    : "+f"(d[32]), "+f"(d[33]), "+f"(d[34]), "+f"(d[35]), "+f"(d[36]), "+f"(d[37]), "+f"(d[38]), "+f"(d[39]), "+f"(d[40]), "+f"(d[41]), "+f"(d[42]), "+f"(d[43]), "+f"(d[44]), "+f"(d[45]), "+f"(d[46]), "+f"(d[47]), "+f"(d[48]), "+f"(d[49]), "+f"(d[50]), "+f"(d[51]), "+f"(d[52]), "+f"(d[53]), "+f"(d[54]), "+f"(d[55]), "+f"(d[56]), "+f"(d[57]), "+f"(d[58]), "+f"(d[59]), "+f"(d[60]), "+f"(d[61]), "+f"(d[62]), "+f"(d[63])
    : "r"(a0), "r"(a1), "r"(a2), "r"(a3), "r"(blo));
}
template<> __device__ __forceinline__ void wgmma_rs_hi<80>(float (&d)[64], uint32_t a0, uint32_t a1, uint32_t a2, uint32_t a3, uint32_t blo){
  asm volatile("{\n.reg .b64 db;\nmov.b64 db, {%44,8};\nwgmma.mma_async.sync.aligned.m64n80k16.f32.bf16.bf16 {%0, %1, %2, %3, %4, %5, %6, %7, %8, %9, %10, %11, %12, %13, %14, %15, %16, %17, %18, %19, %20, %21, %22, %23, %24, %25, %26, %27, %28, %29, %30, %31, %32, %33, %34, %35, %36, %37, %38, %39}, {%40,%41,%42,%43}, db, 1, 1, 1, 0;\n}\n"
    : "+f"(d[24]), "+f"(d[25]), "+f"(d[26]), "+f"(d[27]), "+f"(d[28]), "+f"(d[29]), "+f"(d[30]), "+f"(d[31]), "+f"(d[32]), "+f"(d[33]), "+f"(d[34]), "+f"(d[35]), "+f"(d[36]), "+f"(d[37]), "+f"(d[38]), "+f"(d[39]), "+f"(d[40]), "+f"(d[41]), "+f"(d[42]), "+f"(d[43]), "+f"(d[44]), "+f"(d[45]), "+f"(d[46]), "+f"(d[47]), "+f"(d[48]), "+f"(d[49]), "+f"(d[50]), "+f"(d[51]), "+f"(d[52]), "+f"(d[53]), "+f"(d[54]), "+f"(d[55]), "+f"(d[56]), "+f"(d[57]), "+f"(d[58]), "+f"(d[59]), "+f"(d[60]), "+f"(d[61]), "+f"(d[62]), "+f"(d[63])
    : "r"(a0), "r"(a1), "r"(a2), "r"(a3), "r"(blo));
}
template<> __device__ __forceinline__ void wgmma_rs_hi<96>(float (&d)[64], uint32_t a0, uint32_t a1, uint32_t a2, uint32_t a3, uint32_t blo){
  asm volatile("{\n.reg .b64 db;\nmov.b64 db, {%52,8};\nwgmma.mma_async.sync.aligned.m64n96k16.f32.bf16.bf16 {%0, %1, %2, %3, %4, %5, %6, %7, %8, %9, %10, %11, %12, %13, %14, %15, %16, %17, %18, %19, %20, %21, %22, %23, %24, %25, %26, %27, %28, %29, %30, %31, %32, %33, %34, %35, %36, %37, %38, %39, %40, %41, %42, %43, %44, %45, %46, %47}, {%48,%49,%50,%51}, db, 1, 1, 1, 0;\n}\n"
    : "+f"(d[16]), "+f"(d[17]), "+f"(d[18]), "+f"(d[19]), "+f"(d[20]), "+f"(d[21]), "+f"(d[22]), "+f"(d[23]), "+f"(d[24]), "+f"(d[25]), "+f"(d[26]), "+f"(d[27]), "+f"(d[28]), "+f"(d[29]), "+f"(d[30]), "+f"(d[31]), "+f"(d[32]), "+f"(d[33]), "+f"(d[34]), "+f"(d[35]), "+f"(d[36]), "+f"(d[37]), "+f"(d[38]), "+f"(d[39]), "+f"(d[40]), "+f"(d[41]), "+f"(d[42]), "+f"(d[43]), "+f"(d[44]), "+f"(d[45]), "+f"(d[46]), "+f"(d[47]), "+f"(d[48]), "+f"(d[49]), "+f"(d[50]), "+f"(d[51]), "+f"(d[52]), "+f"(d[53]), "+f"(d[54]), "+f"(d[55]), "+f"(d[56]), "+f"(d[57]), "+f"(d[58]), "+f"(d[59]), "+f"(d[60]), "+f"(d[61]), "+f"(d[62]), "+f"(d[63])
    : "r"(a0), "r"(a1), "r"(a2), "r"(a3), "r"(blo));
}
template<> __device__ __forceinline__ void wgmma_rs_hi<112>(float (&d)[64], uint32_t a0, uint32_t a1, uint32_t a2, uint32_t a3, uint32_t blo){
  asm volatile("{\n.reg .b64 db;\nmov.b64 db, {%60,8};\nwgmma.mma_async.sync.aligned.m64n112k16.f32.bf16.bf16 {%0, %1, %2, %3, %4, %5, %6, %7, %8, %9, %10, %11, %12, %13, %14, %15, %16, %17, %18, %19, %20, %21, %22, %23, %24, %25, %26, %27, %28, %29, %30, %31, %32, %33, %34, %35, %36, %37, %38, %39, %40, %41, %42, %43, %44, %45, %46, %47, %48, %49, %50, %51, %52, %53, %54, %55}, {%56,%57,%58,%59}, db, 1, 1, 1, 0;\n}\n"
    : "+f"(d[8]), "+f"(d[9]), "+f"(d[10]), "+f"(d[11]), "+f"(d[12]), "+f"(d[13]), "+f"(d[14]), "+f"(d[15]), "+f"(d[16]), "+f"(d[17]), "+f"(d[18]), "+f"(d[19]), "+f"(d[20]), "+f"(d[21]), "+f"(d[22]), "+f"(d[23]), "+f"(d[24]), "+f"(d[25]), "+f"(d[26]), "+f"(d[27]), "+f"(d[28]), "+f"(d[29]), "+f"(d[30]), "+f"(d[31]), "+f"(d[32]), "+f"(d[33]), "+f"(d[34]), "+f"(d[35]), "+f"(d[36]), "+f"(d[37]), "+f"(d[38]), "+f"(d[39]), "+f"(d[40]), "+f"(d[41]), "+f"(d[42]), "+f"(d[43]), "+f"(d[44]), "+f"(d[45]), "+f"(d[46]), "+f"(d[47]), "+f"(d[48]), "+f"(d[49]), "+f"(d[50]), "+f"(d[51]), "+f"(d[52]), "+f"(d[53]), "+f"(d[54]), "+f"(d[55]), "+f"(d[56]), "+f"(d[57]), "+f"(d[58]), "+f"(d[59]), "+f"(d[60]), "+f"(d[61]), "+f"(d[62]), "+f"(d[63])
    : "r"(a0), "r"(a1), "r"(a2), "r"(a3), "r"(blo));
}
template<> __device__ __forceinline__ void wgmma_rs_hi<128>(float (&d)[64], uint32_t a0, uint32_t a1, uint32_t a2, uint32_t a3, uint32_t blo){
  asm volatile("{\n.reg .b64 db;\nmov.b64 db, {%68,8};\nwgmma.mma_async.sync.aligned.m64n128k16.f32.bf16.bf16 {%0, %1, %2, %3, %4, %5, %6, %7, %8, %9, %10, %11, %12, %13, %14, %15, %16, %17, %18, %19, %20, %21, %22, %23, %24, %25, %26, %27, %28, %29, %30, %31, %32, %33, %34, %35, %36, %37, %38, %39, %40, %41, %42, %43, %44, %45, %46, %47, %48, %49, %50, %51, %52, %53, %54, %55, %56, %57, %58, %59, %60, %61, %62, %63}, {%64,%65,%66,%67}, db, 1, 1, 1, 0;\n}\n"
    : "+f"(d[0]), "+f"(d[1]), "+f"(d[2]), "+f"(d[3]), "+f"(d[4]), "+f"(d[5]), "+f"(d[6]), "+f"(d[7]), "+f"(d[8]), "+f"(d[9]), "+f"(d[10]), "+f"(d[11]), "+f"(d[12]), "+f"(d[13]), "+f"(d[14]), "+f"(d[15]), "+f"(d[16]), "+f"(d[17]), "+f"(d[18]), "+f"(d[19]), "+f"(d[20]), "+f"(d[21]), "+f"(d[22]), "+f"(d[23]), "+f"(d[24]), "+f"(d[25]), "+f"(d[26]), "+f"(d[27]), "+f"(d[28]), "+f"(d[29]), "+f"(d[30]), "+f"(d[31]), "+f"(d[32]), "+f"(d[33]), "+f"(d[34]), "+f"(d[35]), "+f"(d[36]), "+f"(d[37]), "+f"(d[38]), "+f"(d[39]), "+f"(d[40]), "+f"(d[41]), "+f"(d[42]), "+f"(d[43]), "+f"(d[44]), "+f"(d[45]), "+f"(d[46]), "+f"(d[47]), "+f"(d[48]), "+f"(d[49]), "+f"(d[50]), "+f"(d[51]), "+f"(d[52]), "+f"(d[53]), "+f"(d[54]), "+f"(d[55]), "+f"(d[56]), "+f"(d[57]), "+f"(d[58]), "+f"(d[59]), "+f"(d[60]), "+f"(d[61]), "+f"(d[62]), "+f"(d[63])
    : "r"(a0), "r"(a1), "r"(a2), "r"(a3), "r"(blo));
}

struct CvCtx {
  uint32_t koff, zero, so[3];
  int srcA, srcB;
  bool wrapA, s3, kodd;
};
struct CvPipe { uint32_t Ap, Ep, keep, send; };
template <int LO> __device__ __forceinline__ void cv_copy(float (&acc)[64]) {
#pragma unroll
  for (int i = LO; i < 64; i++) { float t; asm volatile("mov.b32 %0, %1;" : "=f"(t) : "f"(acc[i]) : "memory"); acc[i] = t; }
}
template <int G> __device__ __forceinline__ void cv_raw(uint32_t (&A)[4][4], uint32_t kaddr) {
#pragma unroll
  for (int i = 0; i < 4; i++) {
    const uint32_t a = kaddr + (4 * G + i) * 128;
    A[i][0] = lds32(a); A[i][1] = lds32(a + 4); A[i][3] = lds32(a + 8);
  }
}
__device__ __forceinline__ void cv_form(uint32_t (&A)[4][4], uint32_t sel) {
#pragma unroll
  for (int i = 0; i < 4; i++) {
    asm volatile("prmt.b32 %0, %0, %1, %2;" : "+r"(A[i][0]) : "r"(A[i][1]), "r"(sel));
    asm volatile("prmt.b32 %0, %1, %2, %3;" : "=r"(A[i][2]) : "r"(A[i][1]), "r"(A[i][3]), "r"(sel));
  }
}
#define CVV 2
template <int G> __device__ __forceinline__ void cv_step(float (&acc)[64], uint32_t (&A)[4][4], CvPipe& s, const CvCtx& c, uint32_t cb, uint32_t stg) {
  constexpr int JA = G - 1, JB = G - 2, NH = CVV == 1 ? 4 : (CVV == 3 ? 2 : 1);
  const uint32_t db0 = desc_lo(cb + CV_U + 192, CV_PL);
  uint32_t B[4][4];
  uint32_t ra[2], rb;
  if constexpr (G < 8) {
    wgmma_fence();
#pragma unroll
    for (int i = 0; i < NH; i++) wgmma_rs_hi<128 - 16 * (G & 7)>(acc, A[i][0], A[i][1], A[i][2], A[i][3], db0 - 4 * i);
    wgmma_commit();
    __syncwarp();
  }
  if constexpr (JA >= 0 && JA < 8) {
    const uint32_t p0 = pack_bf16(acc[8 * JA + 1], acc[8 * JA + 3]), p1 = pack_bf16(acc[8 * JA + 5], acc[8 * JA + 7]);
    ra[0] = __shfl_sync(0xffffffffu, c.wrapA ? s.Ap : p0, c.srcA);
    ra[1] = __shfl_sync(0xffffffffu, c.wrapA ? p0 : p1, c.srcA);
    s.Ap = p1;
  }
  if constexpr (JB >= 0) rb = __shfl_sync(0xffffffffu, s.send, c.srcB);
  if constexpr (G < 7) cv_raw<G + 1>(B, cb + c.koff);
  uint32_t z = 0;
  if constexpr (G < 8 && NH < 4) {
    __syncwarp();
    wgmma_fence();
#pragma unroll
    for (int i = NH; i < 4; i++) wgmma_rs_hi<128 - 16 * (G & 7)>(acc, A[i][0], A[i][1], A[i][2], A[i][3], db0 - 4 * i);
    wgmma_commit();
    asm volatile("mov.u32 %0, %%clock;" : "=r"(z)::"memory");
    z &= c.zero;
  }
  if constexpr (G < 7) cv_form(B, 0x5432u | z);
  if constexpr (JB >= 0) sts32(stg + ((c.so[JB / 3] >> (10 * (JB % 3))) & 0xffc), hadd2(rb | z, s.keep));
  if constexpr (JA >= 0 && JA < 8) {
    const uint32_t sh = 16 | z, mk = 0xffff0000u | z;
    const uint32_t ev = pack_bf16(acc[8 * JA] + __uint_as_float(ra[0] << sh), acc[8 * JA + 2] + __uint_as_float(ra[0] & mk));
    const uint32_t od = pack_bf16(acc[8 * JA + 4] + __uint_as_float(ra[1] << sh), acc[8 * JA + 6] + __uint_as_float(ra[1] & mk));
    s.send = c.kodd ? ev : (c.s3 ? s.Ep : od);
    s.keep = c.kodd ? od : ev;
    s.Ep = od;
  }
  if constexpr (G < 8) { __syncwarp(); wgmma_wait<0>(); cv_copy<8 * (G & 7)>(acc); }
  if constexpr (G < 9) cv_step<G + 1>(acc, B, s, c, cb, stg);
}
__device__ __forceinline__ uint32_t cv_stage(int slot) { return sb + (slot < 4 ? 40960 + slot * 4096 : CV_OFF + CV_K); }
__device__ __forceinline__ void cv_setup(CvCtx& c) {
  const int tid = tid_opaque() & 127, w = tid >> 5, lane = tid & 31, r = lane >> 2, q = lane & 3;
  const int i0 = (r >> 1) & 1, i1 = r >> 2;
  c.koff = CV_K - 32 + 4 * (8 * (r >> 1) + 2 * w + (r & 1) + 2 * q);
  c.srcA = i0 ? lane - 8 : lane + 8 - q + ((q + 3) & 3);
  c.wrapA = i0 && q == 3;
  c.srcB = i1 == 0 ? (lane - q + 16 + ((q + 3) & 3)) : (lane - q - 16 + ((q + 1) & 3));
  c.s3 = (i1 == 1 && q == 3); c.kodd = (i1 == 1 && q < 3);
  c.zero = lds32(sb + EP_OFF + 24);
#pragma unroll
  for (int i = 0; i < 3; i++) c.so[i] = lds32(sb + SO_OFF + 512 * i + 4 * tid);
}
__device__ __forceinline__ void cv_table() {
  const int tid = tid_opaque() & 127, r = (tid & 31) >> 2, q = tid & 3;
  int t = 16 * (2 * (r < 4 ? q : 4 + ((q + 1) & 3)) + ((r >> 1) & 1)) + 4 * (tid >> 5) + 2 * (r & 1);
#pragma unroll 1
  for (int i = 0; i < 3; i++) {
    uint32_t v = 0;
#pragma unroll 1
    for (int x = 0; x < 3; x++, t += 256) {
      const int T = t / 160, tl = t - T * 160;
      const int qq = (T >= NT1 - 1) ? (tl >> 5) : (tl / 40);
      int ck = 20 * T + ((tl - qq * ((T >= NT1 - 1) ? 32 : 40)) >> 1);
      ck ^= (ck >> 2) & 6;
      v |= (uint32_t)((ck * 4 + qq) & 1023) << (10 * x + 2);
    }
    sts32(sb + SO_OFF + 512 * i + 4 * tid, v);
  }
}
__device__ __forceinline__ void conv_channel(int slot, const CvCtx& c) {
  const uint32_t cb = sb + CV_OFF + slot * CV_B;
  float acc[64];
  CvPipe s;
  s.Ap = s.Ep = 0u;
  uint32_t A[4][4];
#pragma unroll
  for (int i = 0; i < 64; i++) acc[i] = 0.f;
  if (slot == 4) mbar_wait(bars + 8 * B_CVDONE);
  mbar_wait(bars + 8 * (B_CVFULL + slot));
  cv_raw<0>(A, cb + c.koff);
  {
    const uint32_t w0 = lds32(cb + CV_K);
    const uint32_t wp = __byte_perm(pack_bf16(bf_lo(w0) + __uint_as_float(lds32(sb + EP_OFF + 4 * slot)), 0.f), w0, 0x7610);
    if (c.koff == CV_K) A[0][0] = wp;
    if (c.koff == CV_K - 4) A[0][1] = wp;
    if (c.koff == CV_K - 8) A[0][3] = wp;
  }
  cv_form(A, 0x5432u);
  cv_copy<0>(acc);
  cv_step<0>(acc, A, s, c, cb, cv_stage(slot));
  fence_async_smem();
  mbar_arrive(bars + 8 * (B_CVDONE + slot));
}

__device__ __forceinline__ void kv_issue(const Params& p, int c, int m2, int dg) {
  const uint32_t fb = bars + 8 * (B_KV + c);
  mbar_expect_tx(fb, KV_PIECE);
  tma3(sb + KS_OFF + c * KV_PIECE, &p.mK, 160 * dg + 32 * c, 64 * m2 - 3, 0, fb);
  tma3(sb + KS_OFF + c * KV_PIECE + 4864, &p.mV, 160 * dg + 32 * c, 64 * m2 - 1, 0, fb);
}
__device__ __forceinline__ void kv_tile(int m, int dg, int c, int y) {
  const int lane = tid_opaque() & 31, tg = lane >> 3;
  const uint32_t pb = sb + KS_OFF + c * KV_PIECE + 32 * y + 4 * (lane & 7);
  const uint32_t ka = pb + tg * 1216, va = pb + 4864 + tg * 1088 + 64;
  const uint32_t kh = (m == 0 && tg > 0) ? ka - 192 : ka;
  uint32_t kk[19], u[16];
  const float4 t = lds128f(sb + TAP_OFF + 256 * c + 128 * y + 16 * (lane & 7));
#pragma unroll
  for (int i = 0; i < 19; i++) { kk[i] = lds32((i < 3 ? kh : ka) + i * 64); if (i >= 3) u[i - 3] = lds32(va + (i - 3) * 64); }
  uint8_t* dst = g_kv + ((160 * dg + 32 * c + 16 * y + 2 * (lane & 7)) * 4096 + (4 * m + tg) * 16);
  const uint32_t w0 = __byte_perm(__float_as_uint(t.x), __float_as_uint(t.z), 0x5410), w1 = __byte_perm(__float_as_uint(t.x), __float_as_uint(t.z), 0x7632);
  const uint32_t w2 = __byte_perm(__float_as_uint(t.y), __float_as_uint(t.w), 0x5410), w3 = __byte_perm(__float_as_uint(t.y), __float_as_uint(t.w), 0x7632);
#pragma unroll
  for (int i = 0; i < 16; i++) {
    uint32_t a = hmul2(kk[i], w3);
    a = hadd2(a, hmul2(kk[i + 1], w2)); a = hadd2(a, hmul2(kk[i + 2], w1)); a = hadd2(a, hmul2(kk[i + 3], w0));
    u[i] = hmul2(a, u[i]);
  }
#pragma unroll
  for (int e = 0; e < 2; e++)
#pragma unroll
    for (int f = 0; f < 2; f++) {
      uint32_t o[4];
#pragma unroll
      for (int qq = 0; qq < 4; qq++) o[qq] = __byte_perm(u[15 - 4 * qq - 2 * f], u[14 - 4 * qq - 2 * f], e ? 0x7632 : 0x5410);
      *(uint4*)(dst + e * 4096 + f * 2048) = make_uint4(o[0], o[1], o[2], o[3]);
    }
}
__device__ __forceinline__ void ln_finish(float s1, float s2, float& mean, float& rstd) {
  mean = s1 * (1.f / 640.f);
  const float v = fmaxf(fmaf(-mean, mean, s2 * (1.f / 640.f)), 0.f) + 1e-5f;
  asm("rsqrt.approx.ftz.f32 %0, %1;" : "=f"(rstd) : "f"(v));
}
__device__ __forceinline__ void stat_table(int T1, unsigned want, int l, int g, const uint4* x0, const uint4* x1, float (&xa)[2], float (&xb)[2]) {
  const int n = 32 * g + (tid_opaque() & 31);
  const uint4* rp = &g_stats[8 * l * SEQ + min(160 * T1 + n, SEQ - 1)];
  float a[4], b[4];
  uint32_t it = 0;
  while (true) {
    bool ok = true;
#pragma unroll
    for (int i = 0; i < 4; i++) ok &= (rec_ld(rp + SEQ * i, a[i], b[i]) == want);
    ok &= rec_ld(x0, xa[0], xb[0]) == want;
    ok &= rec_ld(x1, xa[1], xb[1]) == want;
    if (__all_sync(0xffffffffu, ok)) break;
    trap_if(++it > SPIN_LIMIT);
  }
  float m, rs;
  ln_finish((a[0] + a[1]) + (a[2] + a[3]), (b[0] + b[1]) + (b[2] + b[3]), m, rs);
  sts64f(sb + STAB_OFF + n * 8, rs, -m * rs);
}
__device__ __forceinline__ void stats_reduce(float (&a)[2], float (&b)[2], float (&mean)[2], float (&rstd)[2]) {
#pragma unroll
  for (int o = 1; o < 4; o <<= 1)
#pragma unroll
    for (int h = 0; h < 2; h++) { a[h] += __shfl_xor_sync(0xffffffffu, a[h], o); b[h] += __shfl_xor_sync(0xffffffffu, b[h], o); }
#pragma unroll
  for (int h = 0; h < 2; h++) ln_finish(a[h], b[h], mean[h], rstd[h]);
}

template <bool FIRST>
__device__ __forceinline__ void stats_publish(int which, int n0, int dg, unsigned tag, const float (&acc)[80]) {
  const int q = tid_opaque() & 3, h = q & 1;
  float s1[2] = {0.f, 0.f}, s2[2] = {0.f, 0.f}, t1[2] = {0.f, 0.f}, t2[2] = {0.f, 0.f};
#pragma unroll
  for (int j = 0; j < 20; j++)
#pragma unroll
    for (int y = 0; y < 2; y++) {
      const float a = acc[4 * j + 2 * y], b = acc[4 * j + 2 * y + 1];
      s1[y] += a; t1[y] += b; s2[y] = fmaf(a, a, s2[y]); t2[y] = fmaf(b, b, t2[y]);
    }
#pragma unroll
  for (int y = 0; y < 2; y++) { s1[y] += t1[y]; s2[y] += t2[y]; }
  float a = (h ? s1[1] : s1[0]) + __shfl_xor_sync(0xffffffffu, h ? s1[0] : s1[1], 1);
  float b = (h ? s2[1] : s2[0]) + __shfl_xor_sync(0xffffffffu, h ? s2[0] : s2[1], 1);
  a += __shfl_xor_sync(0xffffffffu, a, 2);
  b += __shfl_xor_sync(0xffffffffu, b, 2);
  if (FIRST) {
    rec_st(&g_stats[((q >> 1) * 4 + dg) * SEQ + n0 + 8 * h], a, b, q < 2 ? tag : tag - 1);
    rec_st(&g_stats[((q >> 1) * 4 + 8 + dg) * SEQ + n0 + 8 * h], a, b, tag - 1);
  } else if (q < 2) rec_st(&g_stats[(which * 4 + dg) * SEQ + n0 + 8 * h], a, b, tag);
}
__device__ __forceinline__ void stats_get(int which, int n0, unsigned tag, float (&mean)[2], float (&rstd)[2]) {
  const uint4* p0 = &g_stats[(which * 4 + (tid_opaque() & 3)) * SEQ + n0];
  float a[2], b[2];
  uint32_t it = 0;
  while (true) {
    const unsigned t0 = rec_ld(p0, a[0], b[0]), t1 = rec_ld(p0 + 8, a[1], b[1]);
    if (__all_sync(0xffffffffu, t0 == tag && t1 == tag)) break;
    trap_if(++it > SPIN_LIMIT);
  }
  stats_reduce(a, b, mean, rstd);
}
__device__ __forceinline__ void x0_load(float (&acc)[80]) {
  const int t = tid_opaque() & 127;
  const uint32_t xa = sb + XT_OFF + (16 * (t >> 5) + ((t & 31) >> 2)) * 320 + 8 * (t & 3);
  mbar_wait(bars + 8 * B_XT);
#pragma unroll
  for (int h = 0; h < 2; h++)
#pragma unroll
    for (int J = 0; J < 10; J++) {
      const float2 v = lds64f(xa + h * 2560 + 32 * J);
      const uint32_t x = __float_as_uint(v.x), y = __float_as_uint(v.y);
      acc[8 * J + 2 * h] = bf_lo(x); acc[8 * J + 2 * h + 1] = bf_hi(x);
      acc[8 * J + 4 + 2 * h] = bf_lo(y); acc[8 * J + 4 + 2 * h + 1] = bf_hi(y);
    }
}

template <bool FROM_X0>
__device__ __forceinline__ void dskip_init(float (&acc)[80], const float (&mean)[2], const float (&rstd)[2]) {
  const int t = tid_opaque() & 127;
  const uint32_t xa = sb + XT_OFF + (16 * (t >> 5) + ((t & 31) >> 2)) * 320 + 8 * (t & 3), da = sb + DTAB_OFF + 8 * (t & 3);
  float2 dw[10], xv[10][2];
#pragma unroll
  for (int J = 0; J < 2; J++) { dw[J] = lds64f(da + 32 * J); if (FROM_X0) { xv[J][0] = lds64f(xa + 32 * J); xv[J][1] = lds64f(xa + 2560 + 32 * J); } }
#pragma unroll
  for (int J = 0; J < 10; J++) {
    if (J + 2 < 10) { dw[J + 2] = lds64f(da + 32 * (J + 2)); if (FROM_X0) { xv[J + 2][0] = lds64f(xa + 32 * (J + 2)); xv[J + 2][1] = lds64f(xa + 2560 + 32 * (J + 2)); } }
#pragma unroll
    for (int x = 0; x < 8; x++) {
      const int h = (x >> 1) & 1;
      const uint32_t dwd = __float_as_uint(x < 4 ? dw[J].x : dw[J].y);
      const float tt = fmaf(rstd[h], (x & 1) ? bf_hi(dwd) : bf_lo(dwd), 1.f);
      float a = acc[8 * J + x];
      if (FROM_X0) { const uint32_t xw = __float_as_uint(x < 4 ? xv[J][h].x : xv[J][h].y); a = (x & 1) ? bf_hi(xw) : bf_lo(xw); }
      acc[8 * J + x] = FROM_X0 ? (a - mean[h]) * tt : fmaf(a, tt, -mean[h] * tt);
    }
  }
}

__global__ void __launch_bounds__(512, 1) fused_kernel(const __grid_constant__ Params p) {
  extern __shared__ __align__(1024) uint8_t smem_raw[];
  const int tid = threadIdx.x, lane = tid & 31;
  const int wid = __shfl_sync(0xffffffffu, tid >> 5, 0), wg = wid >> 2;
  unsigned smid; asm volatile("mov.u32 %0, %%smid;" : "=r"(smid));
  const int role = p.role[min(smid, 131u)];
  if (wid == 12) {
    const bool el = elect_one();
    if (el) {
      asm volatile("prefetch.tensormap [%0];" ::"l"(&p.mX) : "memory");
      asm volatile("prefetch.tensormap [%0];" ::"l"(&p.mB) : "memory");
#pragma unroll
      for (int k = 0; k < S1; k++) mbar_init(bars + 8 * (B_G1FULL + k), 1);
#pragma unroll
      for (int k = 0; k < 6; k++) mbar_init(bars + 8 * (B_XT + k), 1);
      asm volatile("fence.mbarrier_init.release.cluster;" ::: "memory");
    }
    if (role >= 0) {
      __syncwarp();
      asm volatile("bar.arrive 5, 288;" ::: "memory");
      const Role R = unpack_role(role);
      if (elect_one()) {
        TS(45);
#pragma unroll 1
        for (int k = 0; k < S1; k++) {
          const uint32_t fb = bars + 8 * (B_G1FULL + k);
          mbar_expect_tx(fb, G1_STAGE);
          tma4(sb + k * G1_STAGE + G1_XOFF, R.last ? &p.mXl : &p.mX, 64 * k, 0, 0, R.last ? 0 : 80 * R.T1, fb);
          tma5(sb + k * G1_STAGE, &p.mB, 64 * k, 0, 0, 4 * R.side, 2 * R.GP, fb);
        }
        if (R.has2) {
#pragma unroll 1
          for (int c = 0; c < KV0; c++) kv_issue(p, c, R.m2, R.dg);
          mbar_expect_tx(bars + 8 * B_XT, 20480);
#pragma unroll 1
          for (int h = 0; h < 2; h++) {
            const int ng = 8 * R.m2 + 4 * h, T = ng / 20;
            tma4(sb + XT_OFF + h * 10240, T == NT1 - 1 ? &p.mXtl : &p.mXt, 160 * R.dg, 0, 0, T == NT1 - 1 ? ng - 240 : ng + 60 * T, bars + 8 * B_XT);
          }
        }
        TS(44);
      }
      __syncwarp();
      bar_sync(6, 64);
    }
  }
  trap_if(smid >= 132 || smem_u32(smem_raw) != sb);
  if (role < 0) {
    if (wid == 0) {
      const unsigned tag = ld_rlx(g_epoch);
      uint32_t it = 0;
      while (!__all_sync(0xffffffffu, (int)(ld_rlx(&g_hcnt[(lane & 7) * 32]) - 40 * tag) >= 0)) { __nanosleep(500); trap_if(++it > SPIN_LIMIT); }
    }
    return;
  }
  float mean0[2] = {0.f, 0.f}, rstd0[2] = {0.f, 0.f};
  if (wg == 2 || wid == 14) {
    ROLE(role)
    const int c = wid == 14 ? 4 : wid - 8;
    const unsigned tag = ld_rlx(g_epoch);
    if (has2) {
      uint2 bv[2][5];
#pragma unroll
      for (int x = 0; x < 2; x++)
#pragma unroll
        for (int i = 0; i < 5; i++) bv[x][i] = ldv64((const uint2*)((x ? p.bim : p.bre) + (cch0 + 32 * c) * DM) + lane + 32 * i);
      float sv[2];
#pragma unroll
      for (int x = 0; x < 2; x++) {
        float a = 0.f;
#pragma unroll
        for (int i = 0; i < 5; i++) a += (bf_lo(bv[x][i].x) + bf_hi(bv[x][i].x)) + (bf_lo(bv[x][i].y) + bf_hi(bv[x][i].y));
        sv[x] = a;
      }
#pragma unroll
      for (int o = 16; o > 0; o >>= 1) { sv[0] += __shfl_xor_sync(0xffffffffu, sv[0], o); sv[1] += __shfl_xor_sync(0xffffffffu, sv[1], o); }
      if (lane < 2) rec_st(&g_sB[(cch0 + 32 * c) * 2 + lane], sv[0], sv[1], tag);
      if (tid == 256) TS(47);
      __syncwarp();
      bar_sync(8, 192);
      mbar_wait(bars + 8 * B_EP);
      mbar_wait(bars + 8 * (B_KV + c));
#pragma unroll 1
      for (int y = 0; y < 2; y++) kv_tile(m2, dg, c, y);
      __syncwarp();
      if (lane == 0) mbar_arrive(bars + 8 * B_PREP);
      if (tid == 352) TS(52);
      if (tid == 448) TS(51);
      if (wg == 2) {
        float xs[80];
        x0_load(xs);
        stats_publish<true>(0, 64 * m2 + 16 * c + (lane >> 2), dg, tag, xs);
        if (tid == 256) TS(31);
      }
      mbar_wait(bars + 8 * (TABW ? B_PUB : B_PREP));
    } else bar_sync(8, 192);
    {
      const uint4* x0 = wg == 2 ? &g_stats[(lane & 3) * SEQ + (has2 ? 64 * m2 : 0) + 16 * c + (lane >> 2)] : &g_sB[(128 * GP + 32 * side + lane) * 2];
      float xa[2], xb[2];
      stat_table(T1, tag, 0, c, x0, x0 + (wg == 2 ? 8 : 128), xa, xb);
      if (wg == 2) stats_reduce(xa, xb, mean0, rstd0);
      else {
#pragma unroll
        for (int i = 0; i < 2; i++) sts64f(sb + CTAB_OFF + (32 * i + lane) * 24 + 16, p.swap ? xb[i] : xa[i], p.swap ? xa[i] : xb[i]);
      }
      mbar_arrive(bars + 8 * B_STAB);
      if (tid == 448) TS(26);
    }
  } else if (wid == 15) {
    ROLE(role)
    const int ch = 128 * GP + 32 * side + lane;
    uint32_t r0 = ldv16(p.lre + ch), r1 = ldv16(p.lim + ch), r2 = ldv16(p.logdt + ch);
    const uint32_t r3 = ldv16(p.lre + ch + 64), r4 = ldv16(p.lim + ch + 64), r5 = ldv16(p.logdt + ch + 64);
#pragma unroll 1
    for (int i = 0; i < 2; i++) {
      const float lr = bf_lo(r0), li = bf_lo(r1);
      const float dt = __bfloat162float(__float2bfloat16_rn(expf(bf_lo(r2))));
      const float mag = expf(dt * lr);
      float sn, cs; sincospif(dt * li * 0.31830988618379067f, &sn, &cs);
      const float ar = mag * cs, ai = mag * sn;
      const float inv = 2.f / (lr * lr + li * li);
      const uint32_t ad = sb + CTAB_OFF + (32 * i + lane) * 24;
      sts64f(ad, ar, ai);
      sts64f(ad + 8, ((ar - 1.f) * lr + ai * li) * inv, (ai * lr - (ar - 1.f) * li) * inv);
      r0 = r3; r1 = r4; r2 = r5;
    }
    if (lane == 0) TS(46);
    __syncwarp();
    bar_sync(7, 64);
    mbar_arrive(bars + 8 * B_CTAB);
  } else if (wid == 13) {
    ROLE(role)
    uint4 tv[3];
    const uint32_t e0 = ld_rlx(g_epoch);
    const uint32_t e1 = ldv16(p.ssmD + min(cch0 + 32 * lane, 639));
    const uint4 dv = ldv128((const uint4*)(p.dskip + 160 * dg) + min(lane, 19));
#pragma unroll
    for (int i = 0; i < 3; i++) tv[i] = ldv128((const uint4*)(p.shiftk + 640 * dg) + min(lane + 32 * i, 79));
    sts128(sb + DTAB_OFF + 16 * min(lane, 19), dv);
#pragma unroll
    for (int i = 0; i < 3; i++) sts128(sb + TAP_OFF + 16 * min(lane + 32 * i, 79), tv[i]);
    if (lane < 7) sts32(sb + EP_OFF + 4 * lane, lane < 5 ? e1 << 16 : (lane == 5 ? e0 : 0u));
    __syncwarp();
    bar_sync(9, 64);
    mbar_arrive(bars + 8 * B_CTAB);
    if (lane == 0) { mbar_arrive(bars + 8 * B_EP); TS(53); }
    if (has2) {
      mbar_wait(bars + 8 * B_PREP);
      if (lane < 4) red_rel(&g_kvcnt[(dg * 4 + lane) * 32]);
      __syncwarp();
      if (lane == 0) { mbar_arrive(bars + 8 * B_PUB); TS(30); }
    }
  } else if (wid != 12) {
    if (elect_one()) {
      if (wid < 7) {
        const int b0 = wid < 4 ? 4 + 20 * wid : 85 + 21 * (wid - 4), cnt = wid < 4 ? 2 : 1;
#pragma unroll
        for (int i = 0; i < 21; i++) mbar_init(bars + 8 * (b0 + i), cnt);
      } else {
#pragma unroll
        for (int i = 0; i < 12; i++) mbar_init(bars + 8 * (B_CVDONE + i), (i == 5 || i == 6) ? 160 : 128);
        mbar_init(bars + 8 * B_CTAB, 192); mbar_init(bars + 8 * B_PREP, 5);
      }
      asm volatile("fence.mbarrier_init.release.cluster;" ::: "memory");
    }
    __syncwarp();
    bar_sync(5, 288);
    if (wid == 2) asm volatile("bar.arrive 8, 192;\nbar.arrive 6, 64;\nbar.arrive 9, 64;\nbar.arrive 7, 64;" ::: "memory");
    if (tid == 128) TS(0);
    if (wg == 1) { cv_table(); mbar_arrive(bars + 8 * B_CTAB); }
  }

  if (wid == 12) {
    ROLE(role)
    uint32_t dst = sb;
#pragma unroll 1
    for (int k = S1; k < 10; k++) {
      const uint32_t fb = bars + 8 * (B_G1FULL + k);
      mbar_wait(bars + 8 * (B_G1DONE + k - S1));
      if (k == RGATE && has2) mbar_wait(bars + 8 * B_PUB);
      if (elect_one()) {
        mbar_expect_tx(fb, 20480);
        tma4(dst + G1_XOFF, last ? &p.mXl : &p.mX, 64 * k, 0, 0, last ? 0 : 80 * T1, fb);
        mbar_expect_tx(fb, 16384);
        tma5(dst, &p.mB, 64 * k, 0, 0, 4 * side, 2 * GP, fb);
        if (has2 && k - S1 + KV0 < 5) kv_issue(p, k - S1 + KV0, m2, dg);
      }
      dst += G1_STAGE; if (k == 2 * S1 - 1) dst = sb;
    }
  } else if (wid == 15 && (role >> 16)) {
    ROLE(role)
    mbar_wait(bars + 8 * B_PREP);
#pragma unroll
    for (int c = 0; c < 5; c++) {
      const uint32_t cb = sb + CV_OFF + c * CV_B;
      sts128(lane < 8 ? cb + 16 * lane : (lane < 20 ? cb + CV_U + 16 * (lane - 8) : cb + CV_U + CV_PL + 16 * (lane - 20)), make_uint4(0, 0, 0, 0));
    }
    fence_async_smem();
    __syncwarp();
    const unsigned tag = lds32(sb + EP_OFF + 20);
    mbar_wait(bars + 8 * B_PUB);
    if (elect_one()) {
#pragma unroll 1
      for (int c = 0; c < 5; c++) {
        mbar_expect_tx(bars + 8 * (B_CVFULL + c), 8192);
        bulk_g2s(sb + CV_OFF + c * CV_B + CV_K, p.ssmk + (cch0 + 32 * c) * SEQ, 4096, bars + 8 * (B_CVFULL + c));
      }
    }
    cnt_poll(&g_kvcnt[(dg * 4 + (m2 >> 3)) * 32], 32 * tag);
    fence_async_global();
    if (elect_one()) {
      TS(28);
#pragma unroll
      for (int c = 0; c < 10; c++)
        bulk_g2s(sb + CV_OFF + (c >> 1) * CV_B + CV_U + 192 + (c & 1) * CV_PL, g_kv + cch0 * 4096 + (c >> 1) * 131072 + (c & 1) * 2048, 2048, bars + 8 * (B_CVFULL + (c >> 1)));
      TS(54);
    }
    __syncwarp();
  }
  {
    const int w = wid & 3;
    if (wg == 2 && !(role >> 16)) {
      float xa[2], xb[2];
      mbar_wait(bars + 8 * (B_G1FULL + 11));
      stat_table(role & 15, lds32(sb + EP_OFF + 20), 1, w, g_stats, g_stats, xa, xb);
      mbar_arrive(bars + 8 * (B_STAB + 1));
    }
#pragma unroll 1
    for (int l = 0; l < 2; l++) {
      if (wg < 2) {
        float acc[80];
#pragma unroll
        for (int i = 0; i < 80; i++) acc[i] = 0.f;
        ROLE(role)
        const int tid = tid_opaque(), r = (tid & 31) >> 2, q = tid & 3;
        const int ch = 128 * GP + 64 * wg + 32 * side + 8 * w + r;
        const uint32_t ca = sb + CTAB_OFF + (32 * wg + 8 * w + r) * 24;
        float2 lam = make_float2(0.f, 0.f), p8 = lam, p16 = lam, pL = lam, p2L = lam;
        fence_regs(acc);
        {
          const uint32_t alo0 = (l == 0 ? desc_lo(sb, 16) : desc_lo(sb + G2_WOFF, 16)) + wg * 512;
          const uint32_t blo0 = l == 0 ? desc_lo(sb + G1_XOFF, 16) : desc_lo(sb + X1_OFF, 128);
          const uint32_t bhi = l == 0 ? desc_hi(1024, 1) : desc_hi(1024, 0), xstep = l == 0 ? 2 : 16;
          const uint32_t astep = l == 0 ? G1_STAGE >> 4 : 1024, bstep = l == 0 ? G1_STAGE >> 4 : 1280, aend = alo0 + (S1 + l) * astep;
          uint32_t alo = alo0, blo = blo0;
          uint32_t fb = bars + 8 * (B_G1FULL + 10 * l);
          mbar_wait(fb);
          if (tid == 0) TS(1 + 8 * l);
#pragma unroll 1
          for (int k = 0; k < 10; k++) {
            uint32_t ok; const uint32_t nb = k < 9 ? fb + 8 : fb;
            wgmma_fence();
#pragma unroll
            for (int kk = 0; kk < 4; kk++) {
              wgmma_n160<0>(acc, alo + kk * 2, desc_hi(1024, 1), blo + kk * xstep, bhi);
              if (kk == 0) ok = mbar_test(nb);
              if (kk == STG_KK && k == 9 && tid == 0) mbar_arrive(bars + 8 * (B_STG + l));
            }
            wgmma_commit();
            alo += astep; blo += bstep;
            if (blo == desc_lo(sb + G_OFF, 128)) blo = desc_lo(sb, 128);
            if (alo == aend) { alo = alo0; blo = blo0; }
            wgmma_wait<1>();
            if (k > 0 && (tid & 127) == 0) mbar_arrive(fb + 8 * (B_G1DONE - B_G1FULL - 1));
            if (!ok) mbar_wait(nb);
            if (wg == 1 && k == (l ? 8 - STG_D : 9 - STG0)) mbar_wait(bars + 8 * (B_STG + l));
            if (k == 3) {
              mbar_wait(bars + 8 * B_CTAB);
              lam = lds64f(ca);
              if (p.swap) lam.y = -lam.y;
              const float2 p2 = cmul(lam, lam), p4 = cmul(p2, p2);
              p8 = cmul(p4, p4); p16 = cmul(p8, p8);
              pL = cmul(p16, p16);
              if (!last) pL = cmul(pL, p8);
              p2L = cmul(pL, pL);
            }
            if (k == PAUSE_K && has2) mbar_wait(bars + 8 * B_PREP);
            fb += 8;
          }
        }
        mbar_wait(bars + 8 * (B_STAB + l));
        const float2 sB = lds64f(ca + 16);
        const unsigned tag = lds32(sb + EP_OFF + 20);
        wgmma_wait<0>();
        fence_regs(acc);
        if ((tid & 127) == 0) { mbar_arrive(bars + 8 * (B_G1DONE + 10 * l + 9)); TS(wg ? 17 + l : 2 + 8 * l); }
        float2 ec[3];
#pragma unroll
        for (int jj = 0; jj < 8; jj++)
#pragma unroll
          for (int y = 0; y < 3; y++) {
            if (y == 2 && (jj & 1)) continue;
            const int j = y == 2 ? 16 + (jj >> 1) : 8 * y + jj;
            const float4 st = lds128f(sb + STAB_OFF + (8 * j + 2 * q) * 8);
            acc[4 * j + 0] = fmaf(acc[4 * j + 0], st.x, st.y * sB.x);
            acc[4 * j + 2] = fmaf(acc[4 * j + 2], st.x, st.y * sB.y);
            acc[4 * j + 1] = fmaf(acc[4 * j + 1], st.z, st.w * sB.x);
            acc[4 * j + 3] = fmaf(acc[4 * j + 3], st.z, st.w * sB.y);
            ec[y] = jj == 0 ? make_float2(acc[4 * j + 0], acc[4 * j + 2]) : cfma(lam, ec[y], make_float2(acc[4 * j + 0], acc[4 * j + 2]));
            ec[y] = cfma(lam, ec[y], make_float2(acc[4 * j + 1], acc[4 * j + 3]));
          }
        float2 e = cfma(p16, ec[0], ec[1]);
        if (!last) e = cfma(p8, e, ec[2]);
        {
          float2 v = make_float2(__shfl_up_sync(0xffffffffu, e.x, 1, 4), __shfl_up_sync(0xffffffffu, e.y, 1, 4));
          if (q >= 1) e = cfma(pL, v, e);
          v = make_float2(__shfl_up_sync(0xffffffffu, e.x, 2, 4), __shfl_up_sync(0xffffffffu, e.y, 2, 4));
          if (q >= 2) e = cfma(p2L, v, e);
        }
        if (!last && (q == 3 || (q == 2 && l == 0))) rec_st(&g_E[((q == 3 ? l : 1) * NT1 + T1) * DM + ch], e.x, e.y, q == 3 ? tag : tag - 1);
        if (tid == 0) TS(3 + 8 * l);
        float2 ex = make_float2(__shfl_up_sync(0xffffffffu, e.x, 1, 4), __shfl_up_sync(0xffffffffu, e.y, 1, 4));
        if (q == 0) ex = make_float2(0.f, 0.f);
        const float2 coef = lds64f(ca + 8), lamc = make_float2(lam.x, p.swap ? lam.y : -lam.y);
        float m00 = coef.x, m01 = -coef.y, m10 = -coef.y, m11 = -coef.x;
        if (p.swap) { m00 = -coef.y; m01 = coef.x; m10 = -coef.x; m11 = -coef.y; }
        float2 pLq, p160q, p640;
        {
          const float2 p80 = last ? cmul(p2L, p16) : p2L, p160 = cmul(p80, p80), p320 = cmul(p160, p160), one = make_float2(1.f, 0.f);
          p640 = cmul(p320, p320);
          pLq = cmul((q & 1) ? pL : one, (q & 2) ? p2L : one);
          p160q = cmul((q & 1) ? p160 : one, (q & 2) ? p320 : one);
        }
        float2 c, ev[3];
        unsigned tg[3];
        const uint4* ep = &g_E[(l * NT1 + T1 - 1 - q) * DM + ch];
#pragma unroll
        for (int j = 0; j < 20; j++) {
          if (j == CPOLL) {
#pragma unroll
            for (int i = 0; i < 3; i++) {
              ev[i] = make_float2(0.f, 0.f); tg[i] = tag;
              if (T1 - 1 - q - 4 * i >= 0) tg[i] = rec_ld(ep - 4 * i * DM, ev[i].x, ev[i].y);
            }
          }
#pragma unroll
          for (int x = 0; x < 2; x++) {
            const float b0 = acc[4 * j + x], b1 = acc[4 * j + 2 + x];
            acc[4 * j + x] = fmaf(b0, m00, b1 * m01);
            acc[4 * j + 2 + x] = fmaf(b0, m10, b1 * m11);
          }
          if (j == CPOLL - 1 || j == 19) asm volatile("" : "+f"(acc[4 * j]), "+f"(acc[4 * j + 1]), "+f"(acc[4 * j + 2]), "+f"(acc[4 * j + 3])::"memory");
        }
        {
          uint32_t it = 0;
          while (__any_sync(0xffffffffu, tg[0] != tag || tg[1] != tag || tg[2] != tag)) {
#pragma unroll
            for (int i = 0; i < 3; i++)
              if (tg[i] != tag) tg[i] = rec_ld(ep - 4 * i * DM, ev[i].x, ev[i].y);
            trap_if(++it > SPIN_LIMIT);
          }
          c = cfma(p640, cfma(p640, ev[2], ev[1]), ev[0]);
          c = cmul(c, p160q);
          c.x += __shfl_xor_sync(0xffffffffu, c.x, 1); c.y += __shfl_xor_sync(0xffffffffu, c.y, 1);
          c.x += __shfl_xor_sync(0xffffffffu, c.x, 2); c.y += __shfl_xor_sync(0xffffffffu, c.y, 2);
        }
        if (tid == 0) TS(4 + 8 * l);
        if (wg == 1 && l >= HOLD0) mbar_wait(bars + 8 * (B_REL + l));
        c = cfma(pLq, c, ex);
        float2 hh = make_float2(fmaf(c.x, m00, c.y * m01), fmaf(c.x, m10, c.y * m11));
        uint8_t* hb = g_h + (size_t)l * (32 * 20 * 8192) + (10 * wg + 2 * GP) * 8192 + (4 * side + w) * 1024 + (tid_opaque() & 31) * 4;
#pragma unroll
        for (int j4 = 0; j4 < 5; j4++) {
          const int ng = 20 * T1 + 4 * j4;
          uint8_t* hp = hb + (size_t)(ng >> 3) * 163840 + (ng & 7) * 128;
#pragma unroll
          for (int jj = 0; jj < 4; jj++) {
            const int j = 4 * j4 + jj;
            const float2 h0 = cfma(lamc, hh, make_float2(acc[4 * j + 0], acc[4 * j + 2]));
            hh = cfma(lamc, h0, make_float2(acc[4 * j + 1], acc[4 * j + 3]));
            if (j4 < 4 || !last) {
              *(uint32_t*)(hp + jj * 128) = pack_bf16(h0.x, hh.x);
              *(uint32_t*)(hp + jj * 128 + 8192) = pack_bf16(h0.y, hh.y);
            }
          }
        }
        mbar_arrive(bars + 8 * (B_HST + 2 * l + wg));
        if (tid == 0) TS(5 + 8 * l);
        if (tid == 128) TS(l ? 25 : 19);
        if (l == 0 && wid == 4) {
          mbar_wait(bars + 8 * B_HST);
          mbar_wait(bars + 8 * (B_HST + 1));
          if ((tid & 31) < 8) h_release((tid >> 2) & 1, T1, tid & 3);
          __syncwarp();
          if (tid == 128) { mbar_arrive(bars + 8 * B_REL); TS(6); }
        }
      }
      if (l == 0) {
        ROLE(role)
        if (has2) {
          CvCtx cc;
          mbar_wait(bars + 8 * B_CTAB);
          cv_setup(cc);
          mbar_wait(bars + 8 * (B_G1DONE + 9));
#pragma unroll 1
          for (int c = (wg + 2) & 3; c < 5; c += 4) conv_channel(c, cc);
          if ((tid & 127) == 0) TS(wg == 2 ? 32 : (wg == 3 ? 50 : 7 + wg));
        }
      }
      if (wg >= 2) break;
    }
    if (wg == 3) {
    ROLE(role)
    const int pw = wid & 3, gpc = 2 * min(m2 >> 3, 3) + (dg >> 1);
    mbar_wait(bars + 8 * B_EP);
    const unsigned tag = lds32(sb + EP_OFF + 20);
    if (pw == 0) {
      if (elect_one()) {
#pragma unroll 1
        for (int l = 0; l < 2; l++) {
          uint32_t dst = sb;
          if (l == 1) {
            dst = sb + G2_WOFF;
#pragma unroll 1
            for (int k = 0; k < 10; k++) {
              mbar_wait(k > 4 ? bars + 8 * (B_G1DONE + 5 + k) : (has2 ? bars + 8 * (B_G2DONE + 14 + min(k, 3)) : bars + 8 * (B_G1DONE + 9)));
              mbar_expect_tx(bars + 8 * (B_G1FULL + 10 + k), 16384);
              tma5(dst, &p.mB, 64 * k, 0, 0, 4 * side, 2 * GP, bars + 8 * (B_G1FULL + 10 + k));
              dst += 16384; if (k == 4) dst = sb + G2_WOFF;
            }
          }
          if (has2) {
            const uint32_t fb2 = bars + 8 * (B_G2FULL + 20 * l), wb2 = bars + 8 * (B_G2DONE + 20 * l - S2);
            dst = sb + G2_WOFF + (WTAIL ? 4 * l * G2_WB : 0);
            int kc = 0;
#pragma unroll 1
            for (int k = 0; k < 20; k++) {
              mbar_wait(k >= S2 ? wb2 + 8 * k : bars + 8 * (l ? B_G1DONE + (WTAIL ? (k < 3 ? 15 + k : 13 + k) : 19) : (k == 5 ? B_XFREE : (k == 6 ? B_SFREE : B_REL))));
              mbar_expect_tx(fb2 + 8 * k, G2_WB);
              tma5(dst, &p.mCre + (k & 1), kc, 0, 0, 0, 10 * dg, fb2 + 8 * k);
              kc += (k & 1) << 7; if (k == 9) kc = 64;
              dst += G2_WB; if (dst == sb + G2_WOFF + S2 * G2_WB) dst = sb + G2_WOFF;
            }
          }
        }
      }
    } else if (pw == 1) {
#pragma unroll 1
      for (int l = 0; l < 2; l++) {
        if (l == 1) {
          mbar_wait(bars + 8 * (has2 ? B_G2DONE + 19 : B_G1DONE + 9));
          if (has2) mbar_wait(bars + 8 * B_UST);
          cnt_poll(&g_ucnt[gpc * 32], 128 * tag);
          fence_async_global();
          if (elect_one()) {
            TS(20);
            const int bytes = last ? 16384 : 20480;
            const uint8_t* src = g_u + T1 * 204800;
            uint32_t dst = sb + X1_OFF;
#pragma unroll 1
            for (int k = 0; k < 10; k++) {
              if (k > 4) mbar_wait(bars + 8 * (B_G1DONE + 5 + k));
              mbar_expect_tx(bars + 8 * (B_G1FULL + 10 + k), bytes);
              bulk_g2s(dst, src, bytes, bars + 8 * (B_G1FULL + 10 + k));
              src += 20480; dst += 20480; if (dst == sb + G_OFF) dst = sb; if (k == 4) dst = sb + X1_OFF;
            }
          }
          __syncwarp();
        }
        if (has2) {
          mbar_wait(bars + 8 * (B_HST + 2 * l));
          mbar_wait(bars + 8 * (B_G1DONE + 10 * l + 9));
          cnt_poll(&g_hcnt[(l * 16 + gpc) * 32], 40 * tag);
          fence_async_global();
          if (elect_one()) {
            TS(21 + 2 * l);
            const uint32_t fb2 = bars + 8 * (B_G2FULL + 20 * l), wb2 = bars + 8 * (B_G2DONE + 20 * l - S2);
            const uint8_t* src = g_h + (l * 32 + m2) * 163840;
            uint32_t dst = sb;
#pragma unroll 1
            for (int k = 0; k < 20; k++) {
              if (k >= 5) mbar_wait(k >= S2 ? wb2 + 8 * k : bars + 8 * B_SFREE);
              if (k == 10) { mbar_wait(bars + 8 * (B_H1 + l)); fence_async_global(); }
              mbar_expect_tx(fb2 + 8 * k, G2_XB);
              bulk_g2s(dst, src, G2_XB, fb2 + 8 * k);
              src += 8192; dst += G2_XB; if (dst == sb + S2 * G2_XB) dst = sb;
            }
          }
          __syncwarp();
        }
      }
    } else if (pw == 2) {
#pragma unroll 1
      for (int l = 0; l < 2; l++) {
        if (l == 1) {
          float xa[2], xb[2];
          mbar_wait(bars + 8 * (B_G1FULL + 11));
          stat_table(T1, tag, 1, 4, g_stats, g_stats, xa, xb);
          mbar_arrive(bars + 8 * (B_STAB + 1));
        }
#pragma unroll 1
        for (int w = 0; w < 2 * l; w++) {
          mbar_wait(bars + 8 * (B_HST + 2 + w));
          if (lane < 4) h_release(2 + w, T1, lane);
          __syncwarp();
          if (lane == 0) { if (w == 0) mbar_arrive(bars + 8 * (B_REL + 1)); TS(w ? 16 : 14); }
        }
        if (l == 0 && has2 && elect_one()) {
#pragma unroll 1
          for (int i = 0; i < 5; i++) {
            const int c = i < 3 ? i : 7 - i;
            mbar_wait(bars + 8 * (B_CVDONE + c));
            bulk_s2g(g_G + (cch0 + 32 * c) * 4096, cv_stage(c), 4096);
          }
          asm volatile("cp.async.bulk.commit_group;" ::: "memory");
          asm volatile("cp.async.bulk.wait_group.read 0;" ::: "memory");
          mbar_arrive(bars + 8 * B_SFREE);
          asm volatile("cp.async.bulk.wait_group 0;" ::: "memory");
          TS(48);
          fence_async_global();
          asm volatile("fence.acq_rel.gpu;" ::: "memory");
#pragma unroll
          for (int i = 0; i < 4; i++) red_rlx(&g_gcnt[(dg * 4 + i) * 32]);
          TS(49);
          mbar_arrive(bars + 8 * (B_GO + 1));
        }
        __syncwarp();
      }
    } else if (has2) {
      mbar_wait(bars + 8 * B_REL);
      if (elect_one()) {
        l2_prefetch(p.cre + (160 * dg + 5 * m2) * DM, 6400); l2_prefetch(p.cim + (160 * dg + 5 * m2) * DM, 6400);
        asm volatile("prefetch.tensormap [%0];" ::"l"(&p.mG) : "memory");
      }
      mbar_wait(bars + 8 * (B_HST + 1));
      flag_poll(&g_hcnt[(8 + gpc) * 32], 40 * tag);
      if (lane == 0) { mbar_arrive(bars + 8 * B_H1); TS(22); }
      mbar_wait(bars + 8 * (B_GO + 1));
      flag_poll(&g_gcnt[(dg * 4 + (m2 >> 3)) * 32], 32 * tag);
      fence_async_global();
      if (elect_one()) {
        TS(29);
        mbar_expect_tx(bars + 8 * B_GFULL, 20480);
        tma5(sb + G_OFF, &p.mG, 64 * m2, 0, 0, 0, 10 * dg, bars + 8 * B_GFULL);
      }
      mbar_wait(bars + 8 * (B_HST + 3));
      cnt_poll(&g_hcnt[(24 + gpc) * 32], 40 * tag);
      if (lane == 0) { mbar_arrive(bars + 8 * (B_H1 + 1)); TS(24); }
    }
    } else if (wg == 2 && (role >> 16)) {
      float acc[80];
      float off[2] = {mean0[0], mean0[1]};
      const unsigned tag = lds32(sb + EP_OFF + 20);
      dskip_init<true>(acc, mean0, rstd0);
      mbar_arrive(bars + 8 * B_XFREE);
#pragma unroll 1
      for (int l = 0; l < 2; l++) {
        float mean[2], rstd[2];
        {
          uint32_t alo = desc_lo(sb, 1024), blo = desc_lo(sb + G2_WOFF, 16) + (WTAIL ? l * (G2_WB >> 2) : 0);
          uint32_t fb = bars + 8 * (B_G2FULL + 20 * l);
          fence_regs(acc);
          mbar_wait(bars + 8 * (B_CVDONE + 2));
          mbar_wait(bars + 8 * (B_CVDONE + 3));
          mbar_wait(fb);
          if (tid == 256) TS(33 + 6 * l);
#pragma unroll 1
          for (int k = 0; k < 20; k++) {
            if (l == TSL && (k & 3) == 3 && tid == 256) TS(56 + (k >> 2));
            uint32_t ok; const uint32_t nb = k < 19 ? fb + 8 : fb;
            wgmma_fence();
#pragma unroll
            for (int kk = 0; kk < 4; kk++) {
              wgmma_n160<1>(acc, alo + kk * 128, desc_hi(128, 0), blo + kk * 2, desc_hi(1024, 1));
              if (kk == 0) ok = mbar_test(nb);
            }
            wgmma_commit();
            alo += G2_XB >> 4; blo += G2_WB >> 4;
            if (alo == desc_lo(sb + S2 * G2_XB, 1024)) alo = desc_lo(sb, 1024);
            if (blo == desc_lo(sb + G_OFF, 16)) blo = desc_lo(sb + G2_WOFF, 16);
            wgmma_wait<1>();
            if (k > 0 && tid == 256) mbar_arrive(fb + 8 * (B_G2DONE - B_G2FULL - 1));
            if (!ok) mbar_wait(nb);
            fb += 8;
          }
          wgmma_wait<0>();
          fence_regs(acc);
          if (tid == 256) TS(34 + 6 * l);
          if (tid == 256) mbar_arrive(bars + 8 * (B_G2DONE + 20 * l + 19));
        }
        ROLE(role)
        const int tq = tid_opaque() & 31, n0 = 64 * m2 + 16 * w + (tq >> 2);
        stats_publish<false>(2 * l + 1, n0, dg, tag, acc);
        uint32_t gf[10][4];
        mbar_wait(bars + 8 * B_GFULL);
        const uint32_t ga = sb + G_OFF + (8 * (tq >> 4) + (tq & 7)) * 128 + (((2 * w + ((tq >> 3) & 1)) ^ ((2 * m2) & 6) ^ (tq & 7)) << 4);
#pragma unroll
        for (int J = 0; J < 2; J++) ldsm4t(gf[J], ga + J * 2048);
        if (tid == 256) TS(35 + 6 * l);
        uint8_t* dst[2][2];
#pragma unroll
        for (int h = 0; h < 2; h++) {
          if (l == 0) {
            const int ng = 8 * m2 + 2 * w + h, T = ng / 20;
            uint8_t* ub = g_u + (T * 204800 + (ng - 20 * T) * 1024 + (tq & 2) * 64 + (tq & 28) * 4 + (tq & 1) * 8 + (5 * dg >> 1) * 20480);
            dst[h][1] = ub + ((dg & 1) ? 20480 - 512 : 0);
            dst[h][0] = ub + (dg & 1) * 512;
          } else {
            dst[h][0] = dst[h][1] = (uint8_t*)(p.out + (n_to_t(n0 + 8 * h) * DM + 160 * dg + 4 * (tq & 3)));
          }
        }
        stats_get(2 * l + 1, n0, tag, mean, rstd);
        if (tid == 256) TS(36 + 6 * l);
        off[0] += mean[0]; off[1] += mean[1];
        const float ov[2] = {l ? off[0] : 0.f, l ? off[1] : 0.f};
#pragma unroll
        for (int J = 0; J < 10; J++) {
          if (J + 2 < 10) ldsm4t(gf[J + 2 < 10 ? J + 2 : 0], ga + (J + 2) * 2048);
#pragma unroll
          for (int x = 0; x < 8; x++) {
            const int h = (x >> 1) & 1;
            const uint32_t gwd = gf[J][x >> 1];
            const float t = fmaf(rstd[h], (x & 1) ? bf_hi(gwd) : bf_lo(gwd), 1.f);
            acc[8 * J + x] = fmaf(acc[8 * J + x], t, fmaf(-mean[h], t, ov[h]));
          }
#pragma unroll
          for (int h = 0; h < 2; h++) {
            if (l == 0)
              *(uint2*)(dst[h][(J >> 1) & 1] + (J >> 2) * 20480 + (J & 3) * 256) =
                  make_uint2(pack_bf16(acc[8 * J + 2 * h], acc[8 * J + 2 * h + 1]), pack_bf16(acc[8 * J + 4 + 2 * h], acc[8 * J + 5 + 2 * h]));
            else
              *(float4*)(dst[h][0] + 64 * J) = make_float4(acc[8 * J + 2 * h], acc[8 * J + 2 * h + 1], acc[8 * J + 4 + 2 * h], acc[8 * J + 5 + 2 * h]);
          }
          __syncwarp();
        }
        if (l == 0) {
          bar_sync(3, 128);
          if (tid == 288) { TS(37); mbar_arrive(bars + 8 * B_UST); }
          if (tid < 264) red_rel(&g_ucnt[(tid & 7) * 32]);
          __syncwarp();
          if (tid == 256) TS(38);
          stats_publish<false>(2, n0, dg, tag, acc);
          mbar_wait(bars + 8 * (B_G1FULL + 11));
          float xa[2], xb[2];
          const uint4* x0 = &g_stats[(8 + (tq & 3)) * SEQ + n0];
          stat_table(T1, tag, 1, w, x0, x0 + 8, xa, xb);
          mbar_arrive(bars + 8 * (B_STAB + 1));
          if (tid == 256) TS(27);
          stats_reduce(xa, xb, mean, rstd);
          off[0] += mean[0]; off[1] += mean[1];
          mbar_wait(bars + 8 * (B_HST + 2));
          dskip_init<false>(acc, mean, rstd);
        } else {
          if (tid == 256) {
            TS(43);
            if (m2 == 31 && dg == 3) asm volatile("st.relaxed.gpu.global.u32 [%0], %1;" ::"l"(g_epoch), "r"(tag + 1) : "memory");
          }
        }
      }
    }
  }
}

typedef CUresult (*EncFn)(CUtensorMap*, CUtensorMapDataType, cuuint32_t, void*, const cuuint64_t*, const cuuint64_t*,
                          const cuuint32_t*, const cuuint32_t*, CUtensorMapInterleave, CUtensorMapSwizzle,
                          CUtensorMapL2promotion, CUtensorMapFloatOOBfill);

void encode(EncFn fn, CUtensorMap* m, const void* ptr, int rank, const cuuint64_t* dims, const cuuint64_t* strides, const cuuint32_t* box,
            CUtensorMapSwizzle swz = CU_TENSOR_MAP_SWIZZLE_128B) {
  cuuint32_t es[5] = {1, 1, 1, 1, 1};
  fn(m, CU_TENSOR_MAP_DATA_TYPE_BFLOAT16, rank, (void*)ptr, dims, strides, box, es, CU_TENSOR_MAP_INTERLEAVE_NONE,
     swz, (CUtensorMapL2promotion)(swz == CU_TENSOR_MAP_SWIZZLE_128B ? PROM_A : PROM_B), CU_TENSOR_MAP_FLOAT_OOB_FILL_NONE);
}

}

extern "C" void kernel_launch(void* const* d_in, const int* in_sizes, int n_in, void* d_out, int out_size) {
  (void)in_sizes; (void)n_in; (void)out_size;
  Params p;
  typedef const __nv_bfloat16* BP;
  p.x = (BP)d_in[0]; p.lre = (BP)d_in[1]; p.lim = (BP)d_in[2]; p.bre = (BP)d_in[3]; p.bim = (BP)d_in[4];
  p.cre = (BP)d_in[5]; p.cim = (BP)d_in[6]; p.logdt = (BP)d_in[7]; p.dskip = (BP)d_in[8];
  p.k = (BP)d_in[10]; p.v = (BP)d_in[11]; p.shiftk = (BP)d_in[12]; p.ssmk = (BP)d_in[13]; p.ssmD = (BP)d_in[14];
  p.out = (float*)d_out;
  for (int sm = 0; sm < 132; sm++) {
    const int tpc = sm >> 1, side = sm & 1;
    int gpc, gi;
    if (tpc < 32) { gpc = tpc & 7; gi = tpc >> 3; }
    else if (tpc < 60) { gpc = 1 + (tpc - 32) % 7; gi = 4 + (tpc - 32) / 7; }
    else if (tpc < 62) { gpc = tpc - 54; gi = 8; }
    else { gpc = 0; gi = tpc - 58; }
    const int pos = 8 * gpc + gi + (gpc == 7 ? 1 : 0);
    int T1, GP;
    if (pos < 52) { const int hh = pos / 26, x = pos - 26 * hh; T1 = x >> 1; GP = 2 * hh + (x & 1); }
    else { T1 = pos - 52; GP = 4; }
    const int m2 = 8 * (gpc >> 1) + gi, dg = 2 * (gpc & 1) + side;
    p.role[sm] = pos == 65 ? -1 : (T1 | (GP << 4) | (side << 7) | (m2 << 8) | (dg << 14) | ((gi < 8) << 16));
  }
  void* fnp = nullptr;
  cudaDriverEntryPointQueryResult qr;
  cudaGetDriverEntryPoint("cuTensorMapEncodeTiled", &fnp, cudaEnableDefault, &qr);
  EncFn fn = (EncFn)fnp;
  void* gG = nullptr;
  cudaGetSymbolAddress(&gG, g_G);
  const cuuint64_t RB = DM * 2;
  {
    p.swap = p.bim < p.bre;
    const char* lo = (const char*)(p.swap ? p.bim : p.bre); const char* hi = (const char*)(p.swap ? p.bre : p.bim);
    cuuint64_t dims[5] = {640, 8, 2, 8, 10}, st[4] = {RB, (cuuint64_t)(hi - lo), 8 * RB, 64 * RB}; cuuint32_t box[5] = {64, 8, 2, 4, 2};
    encode(fn, &p.mB, lo, 5, dims, st, box);
  }
  {
    cuuint64_t dims[5] = {640, 2, 4, 2, 40}, st[4] = {RB, 4 * RB, 2 * RB, 16 * RB}; cuuint32_t box[5] = {64, 2, 4, 2, 10};
    encode(fn, &p.mCre, p.cre, 5, dims, st, box); encode(fn, &p.mCim, p.cim, 5, dims, st, box);
    cuuint64_t dimg[5] = {2048, 2, 4, 2, 40}, stg[4] = {4096, 4 * 4096, 2 * 4096, 16 * 4096};
    encode(fn, &p.mG, gG, 5, dimg, stg, box);
  }
  {
    cuuint64_t dims[4] = {640, 2, 4, 900}, st[3] = {RB, 40 * RB, 2 * RB}; cuuint32_t box[4] = {64, 2, 4, 20};
    encode(fn, &p.mX, p.x, 4, dims, st, box);
    cuuint64_t diml[4] = {640, 2, 4, 16}, stl[3] = {RB, 32 * RB, 2 * RB};
    encode(fn, &p.mXl, p.x + (size_t)1920 * DM, 4, diml, stl, box);
    cuuint32_t boxt[4] = {160, 2, 4, 4};
    encode(fn, &p.mXt, p.x, 4, dims, st, boxt, CU_TENSOR_MAP_SWIZZLE_NONE);
    encode(fn, &p.mXtl, p.x + (size_t)1920 * DM, 4, diml, stl, boxt, CU_TENSOR_MAP_SWIZZLE_NONE);
    cuuint64_t dk[3] = {640, 2000, 4}, sk[2] = {RB, 16 * RB}; cuuint32_t bk[3] = {32, 19, 4}, bv[3] = {32, 17, 4};
    encode(fn, &p.mK, p.k, 3, dk, sk, bk, CU_TENSOR_MAP_SWIZZLE_NONE);
    encode(fn, &p.mV, p.v, 3, dk, sk, bv, CU_TENSOR_MAP_SWIZZLE_NONE);
  }
  cudaFuncSetAttribute(fused_kernel, cudaFuncAttributeMaxDynamicSharedMemorySize, SMEM_BYTES);
  cudaLaunchConfig_t cfg = {};
  cfg.gridDim = dim3(132); cfg.blockDim = dim3(512); cfg.dynamicSmemBytes = SMEM_BYTES; cfg.stream = cudaStreamPerThread;
  cudaLaunchKernelEx(&cfg, fused_kernel, p);
}
```

```cpp
#include <cuda_runtime.h>
#include <cuda.h>
#include <cuda_bf16.h>
#include <stdint.h>

namespace {

constexpr int SEQ = 2048, DM = 640;
constexpr int NT1 = 13;
#define EXP 0
#define WPF1 3
#define WPF2 7
#define CPOLL 10
#define KV0 5
#define RGATE 20
#define PROM_A 2
#define PROM_B 2
#define XFIRST 0
#define TAPLATE 1
#define STG_D 3
#define STG_KK 1
#define HOLD0 1
#define WREL 0
#define UREL 1
#define TSL 1
#define TABW 0
#define STG0 3
#define WTAIL 1
#define PFD 1
#define PAUSE_K 4
constexpr uint32_t SPIN_LIMIT = 1u << 22;

__device__ __align__(1024) uint8_t g_h[2 * 32 * 20 * 8192];
__device__ __align__(1024) uint8_t g_u[NT1 * 10 * 20480];
__device__ __align__(1024) uint8_t g_kv[DM * 4096];
__device__ __align__(1024) uint8_t g_G[DM * 4096];
__device__ __align__(128) uint4 g_E[2 * NT1 * DM];
__device__ __align__(128) uint4 g_stats[4 * 4 * SEQ];
__device__ __align__(128) uint4 g_sB[DM * 2];
__device__ __align__(128) unsigned g_hcnt[2 * 2 * 8 * 32];
__device__ __align__(128) unsigned g_ucnt[8 * 32];
__device__ __align__(128) unsigned g_kvcnt[16 * 32];
__device__ __align__(128) unsigned g_gcnt[16 * 32];
__device__ __align__(128) unsigned g_epoch[32] = {1};
#define TS(i) do {} while (0)

struct Params {
  CUtensorMap mX, mB, mXl, mK, mV, mXt, mXtl, mCre, mCim, mG;
  const __nv_bfloat16 *x, *lre, *lim, *bre, *bim, *cre, *cim, *logdt, *dskip, *k, *v, *shiftk, *ssmk, *ssmD;
  float* out;
  int swap;
  int role[132];
};

constexpr uint32_t sb = 1024;
constexpr uint32_t G1_STAGE = 36864, G1_XOFF = 16384;
constexpr int S1 = 4;
constexpr uint32_t XT_OFF = 159744, KS_OFF = 180224, KV_PIECE = 9216;
constexpr uint32_t G2_XB = 8192, G2_WB = 20480, G2_WOFF = 57344, G_OFF = 200704;
constexpr uint32_t X1_OFF = 139264;
constexpr int S2 = 7;
constexpr uint32_t CV_OFF = KS_OFF, CV_K = 128, CV_PL = 2240, CV_U = CV_K + 4096, CV_B = KV_PIECE;
constexpr uint32_t MISC = 226304;
constexpr uint32_t BAR_OFF = MISC;
constexpr int B_G1FULL = 0, B_G1DONE = 20, B_G2FULL = 40,
              B_G2DONE = 85, B_GFULL = 125, B_EP = 126, B_H1 = 127  , B_CVFULL = 129  , B_STG = 134  , B_REL = 136  , B_SFREE = 138, B_UST = 142,
              B_GO = 139  , B_PUB = 147,
              B_CVDONE = 148  , B_STAB = 153  , B_XFREE = 155, B_HST = 156  ,
              B_CTAB = 160, B_PREP = 161, B_XT = 162, B_KV = 163  ;
constexpr uint32_t bars = sb + BAR_OFF;
constexpr uint32_t STAB_OFF = MISC + 1344;
constexpr uint32_t CTAB_OFF = STAB_OFF + 1280;
constexpr uint32_t DTAB_OFF = CTAB_OFF + 1536;
constexpr uint32_t EP_OFF = DTAB_OFF + 320;
constexpr uint32_t SO_OFF = EP_OFF + 32;
constexpr uint32_t TAP_OFF = 147456;
constexpr uint32_t SMEM_BYTES = 232448;
static_assert(SO_OFF + 1536 <= SMEM_BYTES, "smem");

__device__ __forceinline__ void trap_if(bool c) { asm volatile("{\n.reg .pred p;\nsetp.ne.u32 p, %0, 0;\n@p trap;\n}\n" ::"r"((uint32_t)c)); }
__device__ __forceinline__ uint32_t smem_u32(const void* p) { return (uint32_t)__cvta_generic_to_shared(p); }
__device__ __forceinline__ void mbar_init(uint32_t bar, int cnt) { asm volatile("mbarrier.init.shared::cta.b64 [%0], %1;" ::"r"(bar), "r"(cnt) : "memory"); }
__device__ __forceinline__ void mbar_expect_tx(uint32_t bar, int bytes) { asm volatile("mbarrier.arrive.expect_tx.shared::cta.b64 _, [%0], %1;" ::"r"(bar), "r"(bytes) : "memory"); }
__device__ __forceinline__ void mbar_arrive(uint32_t bar) { asm volatile("mbarrier.arrive.shared::cta.b64 _, [%0];" ::"r"(bar) : "memory"); }
__device__ __forceinline__ void mbar_wait(uint32_t bar) {
  asm volatile(
      "{\n.reg .pred p;\n.reg .u32 c;\nmov.u32 c, 0;\n"
      "W_%=:\nmbarrier.try_wait.parity.shared::cta.b64 p, [%0], 0;\n@p bra D_%=;\n"
      "add.u32 c, c, 1;\nsetp.lt.u32 p, c, %1;\n@p bra W_%=;\ntrap;\nD_%=:\n}\n" ::"r"(bar), "n"(SPIN_LIMIT) : "memory");
}
__device__ __forceinline__ uint32_t mbar_test(uint32_t bar) {
  uint32_t ok;
  asm volatile("{\n.reg .pred p;\nmbarrier.test_wait.parity.shared::cta.b64 p, [%1], 0;\nselp.u32 %0, 1, 0, p;\n}\n" : "=r"(ok) : "r"(bar) : "memory");
  return ok;
}
__device__ __forceinline__ void tma3(uint32_t dst, const CUtensorMap* m, int c0, int c1, int c2, uint32_t bar) {
  asm volatile("cp.async.bulk.tensor.3d.shared::cluster.global.mbarrier::complete_tx::bytes [%0], [%1, {%3,%4,%5}], [%2];"
               ::"r"(dst), "l"(m), "r"(bar), "r"(c0), "r"(c1), "r"(c2) : "memory");
}
__device__ __forceinline__ void tma4(uint32_t dst, const CUtensorMap* m, int c0, int c1, int c2, int c3, uint32_t bar) {
  asm volatile("cp.async.bulk.tensor.4d.shared::cluster.global.mbarrier::complete_tx::bytes [%0], [%1, {%3,%4,%5,%6}], [%2];"
               ::"r"(dst), "l"(m), "r"(bar), "r"(c0), "r"(c1), "r"(c2), "r"(c3) : "memory");
}
__device__ __forceinline__ void tma5(uint32_t dst, const CUtensorMap* m, int c0, int c1, int c2, int c3, int c4, uint32_t bar) {
  asm volatile("cp.async.bulk.tensor.5d.shared::cluster.global.mbarrier::complete_tx::bytes [%0], [%1, {%3,%4,%5,%6,%7}], [%2];"
               ::"r"(dst), "l"(m), "r"(bar), "r"(c0), "r"(c1), "r"(c2), "r"(c3), "r"(c4) : "memory");
}
__device__ __forceinline__ void bulk_g2s(uint32_t dst, const void* src, int bytes, uint32_t bar) {
  asm volatile("cp.async.bulk.shared::cluster.global.mbarrier::complete_tx::bytes [%0], [%1], %2, [%3];"
               ::"r"(dst), "l"(src), "r"(bytes), "r"(bar) : "memory");
}
__device__ __forceinline__ void bulk_s2g(void* dst, uint32_t src, int bytes) {
  asm volatile("cp.async.bulk.global.shared::cta.bulk_group [%0], [%1], %2;" ::"l"(dst), "r"(src), "r"(bytes) : "memory");
}
__device__ __forceinline__ void l2_prefetch(const void* src, int bytes) {
  asm volatile("cp.async.bulk.prefetch.L2.global [%0], %1;" ::"l"(src), "r"(bytes) : "memory");
}
__device__ __forceinline__ void wgmma_fence() { asm volatile("wgmma.fence.sync.aligned;" ::: "memory"); }
__device__ __forceinline__ void wgmma_commit() { asm volatile("wgmma.commit_group.sync.aligned;" ::: "memory"); }
template <int N> __device__ __forceinline__ void wgmma_wait() { asm volatile("wgmma.wait_group.sync.aligned %0;" ::"n"(N) : "memory"); }
__host__ __device__ constexpr uint32_t desc_lo(uint32_t addr, uint32_t lbo) { return ((addr & 0x3FFFF) >> 4) | ((lbo >> 4) << 16); }
__host__ __device__ constexpr uint32_t desc_hi(uint32_t sbo, uint32_t swz) { return (sbo >> 4) | (swz << 30); }
__device__ __forceinline__ void bar_sync(int id, int n) { asm volatile("bar.sync %0, %1;" ::"r"(id), "r"(n) : "memory"); }
__device__ __forceinline__ uint32_t lds32(uint32_t a) { uint32_t v; asm volatile("ld.shared.u32 %0, [%1];" : "=r"(v) : "r"(a) : "memory"); return v; }
__device__ __forceinline__ float2 lds64f(uint32_t a) { float2 v; asm volatile("ld.shared.v2.f32 {%0,%1}, [%2];" : "=f"(v.x), "=f"(v.y) : "r"(a) : "memory"); return v; }
__device__ __forceinline__ float4 lds128f(uint32_t a) { float4 v; asm volatile("ld.shared.v4.f32 {%0,%1,%2,%3}, [%4];" : "=f"(v.x), "=f"(v.y), "=f"(v.z), "=f"(v.w) : "r"(a) : "memory"); return v; }
__device__ __forceinline__ void ldsm4t(uint32_t (&r)[4], uint32_t a) {
  asm volatile("ldmatrix.sync.aligned.m8n8.x4.trans.shared.b16 {%0,%1,%2,%3}, [%4];" : "=r"(r[0]), "=r"(r[1]), "=r"(r[2]), "=r"(r[3]) : "r"(a) : "memory");
}
__device__ __forceinline__ uint4 ldv128(const void* a) { uint4 v; asm volatile("ld.global.nc.v4.u32 {%0,%1,%2,%3}, [%4];" : "=r"(v.x), "=r"(v.y), "=r"(v.z), "=r"(v.w) : "l"(a) : "memory"); return v; }
__device__ __forceinline__ uint2 ldv64(const void* a) { uint2 v; asm volatile("ld.global.nc.v2.u32 {%0,%1}, [%2];" : "=r"(v.x), "=r"(v.y) : "l"(a) : "memory"); return v; }
__device__ __forceinline__ uint32_t ldv16(const void* a) { uint32_t v; asm volatile("ld.global.nc.u16 %0, [%1];" : "=r"(v) : "l"(a) : "memory"); return v; }
__device__ __forceinline__ void sts128(uint32_t a, uint4 v) { asm volatile("st.shared.v4.u32 [%0], {%1,%2,%3,%4};" ::"r"(a), "r"(v.x), "r"(v.y), "r"(v.z), "r"(v.w) : "memory"); }
__device__ __forceinline__ void sts32(uint32_t a, uint32_t v) { asm volatile("st.shared.u32 [%0], %1;" ::"r"(a), "r"(v) : "memory"); }
__device__ __forceinline__ void sts64f(uint32_t a, float x, float y) { asm volatile("st.shared.v2.f32 [%0], {%1,%2};" ::"r"(a), "f"(x), "f"(y) : "memory"); }
__device__ __forceinline__ void red_rlx(unsigned* p) { asm volatile("red.relaxed.gpu.global.add.u32 [%0], 1;" ::"l"(p) : "memory"); }
__device__ __forceinline__ void red_rel(unsigned* p) { asm volatile("red.release.gpu.global.add.u32 [%0], 1;" ::"l"(p) : "memory"); }
__device__ __forceinline__ void fence_async_global() { asm volatile("fence.proxy.async.global;" ::: "memory"); }
__device__ __forceinline__ void fence_async_smem() { asm volatile("fence.proxy.async.shared::cta;" ::: "memory"); }
__device__ __forceinline__ void rec_st(uint4* p, float a, float b, unsigned tag) {
  asm volatile("{\n.reg .b128 t;\n.reg .b64 lo, hi;\nmov.b64 lo, {%1,%2};\nmov.b64 hi, {%3,%3};\nmov.b128 t, {lo,hi};\n"
               "st.relaxed.gpu.global.b128 [%0], t;\n}\n" ::"l"(p), "r"(__float_as_uint(a)), "r"(__float_as_uint(b)), "r"(tag) : "memory");
}
__device__ __forceinline__ unsigned rec_ld(const uint4* p, float& a, float& b) {
  unsigned x, y, t;
  asm volatile("{\n.reg .b128 t;\n.reg .b64 lo, hi;\n.reg .b32 u;\nld.relaxed.gpu.global.b128 t, [%3];\nmov.b128 {lo,hi}, t;\n"
               "mov.b64 {%0,%1}, lo;\nmov.b64 {%2,u}, hi;\n}\n" : "=r"(x), "=r"(y), "=r"(t) : "l"(p) : "memory");
  a = __uint_as_float(x); b = __uint_as_float(y);
  return t;
}
__device__ __forceinline__ unsigned ld_rlx(const unsigned* p) { unsigned v; asm volatile("ld.relaxed.gpu.global.u32 %0, [%1];" : "=r"(v) : "l"(p) : "memory"); return v; }
__device__ __forceinline__ void flag_poll(const unsigned* p, unsigned target) {
  uint32_t it = 0;
  while (!__all_sync(0xffffffffu, (int)(ld_rlx(p) - target) >= 0)) { trap_if(++it > SPIN_LIMIT); }
  asm volatile("fence.acquire.gpu;" ::: "memory");
}
__device__ __forceinline__ void cnt_poll(const unsigned* p, unsigned target) {
  unsigned a = ld_rlx(p); __nanosleep(100);
  unsigned b = ld_rlx(p); __nanosleep(100);
  unsigned c = ld_rlx(p);
  uint32_t it = 0;
  while (true) {
    if (__all_sync(0xffffffffu, (int)(a - target) >= 0)) break;
    a = ld_rlx(p);
    if (__all_sync(0xffffffffu, (int)(b - target) >= 0)) break;
    b = ld_rlx(p);
    if (__all_sync(0xffffffffu, (int)(c - target) >= 0)) break;
    c = ld_rlx(p);
    trap_if(++it > SPIN_LIMIT);
  }
  asm volatile("fence.acquire.gpu;" ::: "memory");
}
__device__ __forceinline__ void h_release(int idx, int T, int i) {
  const int Q = (i & 2) ? (T + 2) / 3 - 1 : T / 3;
  if (Q >= 0 && Q < 4 && ((i & 2) == 0 || T % 3 == 0)) red_rel(&g_hcnt[(idx * 8 + 2 * Q + (i & 1)) * 32]);
}
__device__ __forceinline__ uint32_t pack_bf16(float lo, float hi) {
  uint32_t r; asm("cvt.rn.bf16x2.f32 %0, %1, %2;" : "=r"(r) : "f"(hi), "f"(lo)); return r;
}
__device__ __forceinline__ float bf_lo(uint32_t w) { return __uint_as_float(w << 16); }
__device__ __forceinline__ float bf_hi(uint32_t w) { return __uint_as_float(w & 0xffff0000u); }
__device__ __forceinline__ uint32_t hmul2(uint32_t a, uint32_t b) {
  __nv_bfloat162 r = __hmul2_rn(*(__nv_bfloat162*)&a, *(__nv_bfloat162*)&b); return *(uint32_t*)&r;
}
__device__ __forceinline__ uint32_t hadd2(uint32_t a, uint32_t b) {
  __nv_bfloat162 r = __hadd2_rn(*(__nv_bfloat162*)&a, *(__nv_bfloat162*)&b); return *(uint32_t*)&r;
}
__device__ __forceinline__ float2 cmul(float2 a, float2 b) { return make_float2(a.x * b.x - a.y * b.y, a.x * b.y + a.y * b.x); }
__device__ __forceinline__ float2 cfma(float2 a, float2 b, float2 c) {
  return make_float2(fmaf(a.x, b.x, fmaf(-a.y, b.y, c.x)), fmaf(a.x, b.y, fmaf(a.y, b.x, c.y)));
}
template <int N> __device__ __forceinline__ void fence_regs(float (&a)[N]) {
#pragma unroll
  for (int i = 0; i < N; i++) asm volatile("" : "+f"(a[i])::"memory");
}
__device__ __forceinline__ bool elect_one() {
  uint32_t e; asm volatile("{\n.reg .pred P;\nelect.sync _|P, 0xffffffff;\nselp.u32 %0, 1, 0, P;\n}\n" : "=r"(e)); return e != 0;
}
__device__ __forceinline__ int tid_opaque() { int t; asm volatile("mov.u32 %0, %%tid.x;" : "=r"(t)); return t; }
struct Role { int T1, GP, side, m2, dg, cch0; bool last, has2; };
__device__ __forceinline__ Role unpack_role(int x) {
  Role r; r.T1 = x & 15; r.GP = (x >> 4) & 7; r.side = (x >> 7) & 1; r.m2 = (x >> 8) & 63; r.dg = (x >> 14) & 3;
  r.has2 = (x >> 16) & 1; r.last = r.T1 == NT1 - 1; r.cch0 = 160 * r.dg + r.m2; return r;
}
__device__ __forceinline__ Role fresh_role(int x) { asm volatile("" : "+r"(x)); return unpack_role(__shfl_sync(0xffffffffu, x, 0)); }
#define ROLE(x) const Role R_ = fresh_role(x); const int T1 = R_.T1, GP = R_.GP, side = R_.side, m2 = R_.m2, dg = R_.dg, cch0 = R_.cch0; \
  const bool last = R_.last, has2 = R_.has2; (void)T1; (void)GP; (void)side; (void)m2; (void)dg; (void)cch0; (void)last; (void)has2;
__device__ __forceinline__ int n_to_t(int n) {
  int T = n / 160, nl = n - T * 160;
  int L = (T == NT1 - 1) ? 32 : 40;
  return T * 160 + L * ((nl & 7) >> 1) + 2 * (nl >> 3) + (nl & 1);
}

template<int TA> __device__ __forceinline__ void wgmma_n160(float (&d)[80], uint32_t alo, uint32_t ahi, uint32_t blo, uint32_t bhi){
  asm volatile("{\n.reg .b64 da, db;\nmov.b64 da, {%80,%81};\nmov.b64 db, {%82,%83};\n"
    "wgmma.mma_async.sync.aligned.m64n160k16.f32.bf16.bf16 {%0, %1, %2, %3, %4, %5, %6, %7, %8, %9, %10, %11, %12, %13, %14, %15, %16, %17, %18, %19, %20, %21, %22, %23, %24, %25, %26, %27, %28, %29, %30, %31, %32, %33, %34, %35, %36, %37, %38, %39, %40, %41, %42, %43, %44, %45, %46, %47, %48, %49, %50, %51, %52, %53, %54, %55, %56, %57, %58, %59, %60, %61, %62, %63, %64, %65, %66, %67, %68, %69, %70, %71, %72, %73, %74, %75, %76, %77, %78, %79}, da, db, 1, 1, 1, %84, 0;\n}\n"
    : "+f"(d[0]), "+f"(d[1]), "+f"(d[2]), "+f"(d[3]), "+f"(d[4]), "+f"(d[5]), "+f"(d[6]), "+f"(d[7]), "+f"(d[8]), "+f"(d[9]), "+f"(d[10]), "+f"(d[11]), "+f"(d[12]), "+f"(d[13]), "+f"(d[14]), "+f"(d[15]), "+f"(d[16]), "+f"(d[17]), "+f"(d[18]), "+f"(d[19]), "+f"(d[20]), "+f"(d[21]), "+f"(d[22]), "+f"(d[23]), "+f"(d[24]), "+f"(d[25]), "+f"(d[26]), "+f"(d[27]), "+f"(d[28]), "+f"(d[29]), "+f"(d[30]), "+f"(d[31]), "+f"(d[32]), "+f"(d[33]), "+f"(d[34]), "+f"(d[35]), "+f"(d[36]), "+f"(d[37]), "+f"(d[38]), "+f"(d[39]), "+f"(d[40]), "+f"(d[41]), "+f"(d[42]), "+f"(d[43]), "+f"(d[44]), "+f"(d[45]), "+f"(d[46]), "+f"(d[47]), "+f"(d[48]), "+f"(d[49]), "+f"(d[50]), "+f"(d[51]), "+f"(d[52]), "+f"(d[53]), "+f"(d[54]), "+f"(d[55]), "+f"(d[56]), "+f"(d[57]), "+f"(d[58]), "+f"(d[59]), "+f"(d[60]), "+f"(d[61]), "+f"(d[62]), "+f"(d[63]), "+f"(d[64]), "+f"(d[65]), "+f"(d[66]), "+f"(d[67]), "+f"(d[68]), "+f"(d[69]), "+f"(d[70]), "+f"(d[71]), "+f"(d[72]), "+f"(d[73]), "+f"(d[74]), "+f"(d[75]), "+f"(d[76]), "+f"(d[77]), "+f"(d[78]), "+f"(d[79])
    : "r"(alo), "r"(ahi), "r"(blo), "r"(bhi), "n"(TA));
}
template<int N> __device__ __forceinline__ void wgmma_rs_hi(float (&d)[64], uint32_t a0, uint32_t a1, uint32_t a2, uint32_t a3, uint32_t blo);
template<> __device__ __forceinline__ void wgmma_rs_hi<16>(float (&d)[64], uint32_t a0, uint32_t a1, uint32_t a2, uint32_t a3, uint32_t blo){
  asm volatile("{\n.reg .b64 db;\nmov.b64 db, {%12,8};\nwgmma.mma_async.sync.aligned.m64n16k16.f32.bf16.bf16 {%0, %1, %2, %3, %4, %5, %6, %7}, {%8,%9,%10,%11}, db, 1, 1, 1, 0;\n}\n"
    : "+f"(d[56]), "+f"(d[57]), "+f"(d[58]), "+f"(d[59]), "+f"(d[60]), "+f"(d[61]), "+f"(d[62]), "+f"(d[63])
    : "r"(a0), "r"(a1), "r"(a2), "r"(a3), "r"(blo));
}
template<> __device__ __forceinline__ void wgmma_rs_hi<32>(float (&d)[64], uint32_t a0, uint32_t a1, uint32_t a2, uint32_t a3, uint32_t blo){
  asm volatile("{\n.reg .b64 db;\nmov.b64 db, {%20,8};\nwgmma.mma_async.sync.aligned.m64n32k16.f32.bf16.bf16 {%0, %1, %2, %3, %4, %5, %6, %7, %8, %9, %10, %11, %12, %13, %14, %15}, {%16,%17,%18,%19}, db, 1, 1, 1, 0;\n}\n"
    : "+f"(d[48]), "+f"(d[49]), "+f"(d[50]), "+f"(d[51]), "+f"(d[52]), "+f"(d[53]), "+f"(d[54]), "+f"(d[55]), "+f"(d[56]), "+f"(d[57]), "+f"(d[58]), "+f"(d[59]), "+f"(d[60]), "+f"(d[61]), "+f"(d[62]), "+f"(d[63])
    : "r"(a0), "r"(a1), "r"(a2), "r"(a3), "r"(blo));
}
template<> __device__ __forceinline__ void wgmma_rs_hi<48>(float (&d)[64], uint32_t a0, uint32_t a1, uint32_t a2, uint32_t a3, uint32_t blo){
  asm volatile("{\n.reg .b64 db;\nmov.b64 db, {%28,8};\nwgmma.mma_async.sync.aligned.m64n48k16.f32.bf16.bf16 {%0, %1, %2, %3, %4, %5, %6, %7, %8, %9, %10, %11, %12, %13, %14, %15, %16, %17, %18, %19, %20, %21, %22, %23}, {%24,%25,%26,%27}, db, 1, 1, 1, 0;\n}\n"
    : "+f"(d[40]), "+f"(d[41]), "+f"(d[42]), "+f"(d[43]), "+f"(d[44]), "+f"(d[45]), "+f"(d[46]), "+f"(d[47]), "+f"(d[48]), "+f"(d[49]), "+f"(d[50]), "+f"(d[51]), "+f"(d[52]), "+f"(d[53]), "+f"(d[54]), "+f"(d[55]), "+f"(d[56]), "+f"(d[57]), "+f"(d[58]), "+f"(d[59]), "+f"(d[60]), "+f"(d[61]), "+f"(d[62]), "+f"(d[63])
    : "r"(a0), "r"(a1), "r"(a2), "r"(a3), "r"(blo));
}
template<> __device__ __forceinline__ void wgmma_rs_hi<64>(float (&d)[64], uint32_t a0, uint32_t a1, uint32_t a2, uint32_t a3, uint32_t blo){
  asm volatile("{\n.reg .b64 db;\nmov.b64 db, {%36,8};\nwgmma.mma_async.sync.aligned.m64n64k16.f32.bf16.bf16 {%0, %1, %2, %3, %4, %5, %6, %7, %8, %9, %10, %11, %12, %13, %14, %15, %16, %17, %18, %19, %20, %21, %22, %23, %24, %25, %26, %27, %28, %29, %30, %31}, {%32,%33,%34,%35}, db, 1, 1, 1, 0;\n}\n"
    : "+f"(d[32]), "+f"(d[33]), "+f"(d[34]), "+f"(d[35]), "+f"(d[36]), "+f"(d[37]), "+f"(d[38]), "+f"(d[39]), "+f"(d[40]), "+f"(d[41]), "+f"(d[42]), "+f"(d[43]), "+f"(d[44]), "+f"(d[45]), "+f"(d[46]), "+f"(d[47]), "+f"(d[48]), "+f"(d[49]), "+f"(d[50]), "+f"(d[51]), "+f"(d[52]), "+f"(d[53]), "+f"(d[54]), "+f"(d[55]), "+f"(d[56]), "+f"(d[57]), "+f"(d[58]), "+f"(d[59]), "+f"(d[60]), "+f"(d[61]), "+f"(d[62]), "+f"(d[63])
    : "r"(a0), "r"(a1), "r"(a2), "r"(a3), "r"(blo));
}
template<> __device__ __forceinline__ void wgmma_rs_hi<80>(float (&d)[64], uint32_t a0, uint32_t a1, uint32_t a2, uint32_t a3, uint32_t blo){
  asm volatile("{\n.reg .b64 db;\nmov.b64 db, {%44,8};\nwgmma.mma_async.sync.aligned.m64n80k16.f32.bf16.bf16 {%0, %1, %2, %3, %4, %5, %6, %7, %8, %9, %10, %11, %12, %13, %14, %15, %16, %17, %18, %19, %20, %21, %22, %23, %24, %25, %26, %27, %28, %29, %30, %31, %32, %33, %34, %35, %36, %37, %38, %39}, {%40,%41,%42,%43}, db, 1, 1, 1, 0;\n}\n"
    : "+f"(d[24]), "+f"(d[25]), "+f"(d[26]), "+f"(d[27]), "+f"(d[28]), "+f"(d[29]), "+f"(d[30]), "+f"(d[31]), "+f"(d[32]), "+f"(d[33]), "+f"(d[34]), "+f"(d[35]), "+f"(d[36]), "+f"(d[37]), "+f"(d[38]), "+f"(d[39]), "+f"(d[40]), "+f"(d[41]), "+f"(d[42]), "+f"(d[43]), "+f"(d[44]), "+f"(d[45]), "+f"(d[46]), "+f"(d[47]), "+f"(d[48]), "+f"(d[49]), "+f"(d[50]), "+f"(d[51]), "+f"(d[52]), "+f"(d[53]), "+f"(d[54]), "+f"(d[55]), "+f"(d[56]), "+f"(d[57]), "+f"(d[58]), "+f"(d[59]), "+f"(d[60]), "+f"(d[61]), "+f"(d[62]), "+f"(d[63])
    : "r"(a0), "r"(a1), "r"(a2), "r"(a3), "r"(blo));
}
template<> __device__ __forceinline__ void wgmma_rs_hi<96>(float (&d)[64], uint32_t a0, uint32_t a1, uint32_t a2, uint32_t a3, uint32_t blo){
  asm volatile("{\n.reg .b64 db;\nmov.b64 db, {%52,8};\nwgmma.mma_async.sync.aligned.m64n96k16.f32.bf16.bf16 {%0, %1, %2, %3, %4, %5, %6, %7, %8, %9, %10, %11, %12, %13, %14, %15, %16, %17, %18, %19, %20, %21, %22, %23, %24, %25, %26, %27, %28, %29, %30, %31, %32, %33, %34, %35, %36, %37, %38, %39, %40, %41, %42, %43, %44, %45, %46, %47}, {%48,%49,%50,%51}, db, 1, 1, 1, 0;\n}\n"
    : "+f"(d[16]), "+f"(d[17]), "+f"(d[18]), "+f"(d[19]), "+f"(d[20]), "+f"(d[21]), "+f"(d[22]), "+f"(d[23]), "+f"(d[24]), "+f"(d[25]), "+f"(d[26]), "+f"(d[27]), "+f"(d[28]), "+f"(d[29]), "+f"(d[30]), "+f"(d[31]), "+f"(d[32]), "+f"(d[33]), "+f"(d[34]), "+f"(d[35]), "+f"(d[36]), "+f"(d[37]), "+f"(d[38]), "+f"(d[39]), "+f"(d[40]), "+f"(d[41]), "+f"(d[42]), "+f"(d[43]), "+f"(d[44]), "+f"(d[45]), "+f"(d[46]), "+f"(d[47]), "+f"(d[48]), "+f"(d[49]), "+f"(d[50]), "+f"(d[51]), "+f"(d[52]), "+f"(d[53]), "+f"(d[54]), "+f"(d[55]), "+f"(d[56]), "+f"(d[57]), "+f"(d[58]), "+f"(d[59]), "+f"(d[60]), "+f"(d[61]), "+f"(d[62]), "+f"(d[63])
    : "r"(a0), "r"(a1), "r"(a2), "r"(a3), "r"(blo));
}
template<> __device__ __forceinline__ void wgmma_rs_hi<112>(float (&d)[64], uint32_t a0, uint32_t a1, uint32_t a2, uint32_t a3, uint32_t blo){
  asm volatile("{\n.reg .b64 db;\nmov.b64 db, {%60,8};\nwgmma.mma_async.sync.aligned.m64n112k16.f32.bf16.bf16 {%0, %1, %2, %3, %4, %5, %6, %7, %8, %9, %10, %11, %12, %13, %14, %15, %16, %17, %18, %19, %20, %21, %22, %23, %24, %25, %26, %27, %28, %29, %30, %31, %32, %33, %34, %35, %36, %37, %38, %39, %40, %41, %42, %43, %44, %45, %46, %47, %48, %49, %50, %51, %52, %53, %54, %55}, {%56,%57,%58,%59}, db, 1, 1, 1, 0;\n}\n"
    : "+f"(d[8]), "+f"(d[9]), "+f"(d[10]), "+f"(d[11]), "+f"(d[12]), "+f"(d[13]), "+f"(d[14]), "+f"(d[15]), "+f"(d[16]), "+f"(d[17]), "+f"(d[18]), "+f"(d[19]), "+f"(d[20]), "+f"(d[21]), "+f"(d[22]), "+f"(d[23]), "+f"(d[24]), "+f"(d[25]), "+f"(d[26]), "+f"(d[27]), "+f"(d[28]), "+f"(d[29]), "+f"(d[30]), "+f"(d[31]), "+f"(d[32]), "+f"(d[33]), "+f"(d[34]), "+f"(d[35]), "+f"(d[36]), "+f"(d[37]), "+f"(d[38]), "+f"(d[39]), "+f"(d[40]), "+f"(d[41]), "+f"(d[42]), "+f"(d[43]), "+f"(d[44]), "+f"(d[45]), "+f"(d[46]), "+f"(d[47]), "+f"(d[48]), "+f"(d[49]), "+f"(d[50]), "+f"(d[51]), "+f"(d[52]), "+f"(d[53]), "+f"(d[54]), "+f"(d[55]), "+f"(d[56]), "+f"(d[57]), "+f"(d[58]), "+f"(d[59]), "+f"(d[60]), "+f"(d[61]), "+f"(d[62]), "+f"(d[63])
    : "r"(a0), "r"(a1), "r"(a2), "r"(a3), "r"(blo));
}
template<> __device__ __forceinline__ void wgmma_rs_hi<128>(float (&d)[64], uint32_t a0, uint32_t a1, uint32_t a2, uint32_t a3, uint32_t blo){
  asm volatile("{\n.reg .b64 db;\nmov.b64 db, {%68,8};\nwgmma.mma_async.sync.aligned.m64n128k16.f32.bf16.bf16 {%0, %1, %2, %3, %4, %5, %6, %7, %8, %9, %10, %11, %12, %13, %14, %15, %16, %17, %18, %19, %20, %21, %22, %23, %24, %25, %26, %27, %28, %29, %30, %31, %32, %33, %34, %35, %36, %37, %38, %39, %40, %41, %42, %43, %44, %45, %46, %47, %48, %49, %50, %51, %52, %53, %54, %55, %56, %57, %58, %59, %60, %61, %62, %63}, {%64,%65,%66,%67}, db, 1, 1, 1, 0;\n}\n"
    : "+f"(d[0]), "+f"(d[1]), "+f"(d[2]), "+f"(d[3]), "+f"(d[4]), "+f"(d[5]), "+f"(d[6]), "+f"(d[7]), "+f"(d[8]), "+f"(d[9]), "+f"(d[10]), "+f"(d[11]), "+f"(d[12]), "+f"(d[13]), "+f"(d[14]), "+f"(d[15]), "+f"(d[16]), "+f"(d[17]), "+f"(d[18]), "+f"(d[19]), "+f"(d[20]), "+f"(d[21]), "+f"(d[22]), "+f"(d[23]), "+f"(d[24]), "+f"(d[25]), "+f"(d[26]), "+f"(d[27]), "+f"(d[28]), "+f"(d[29]), "+f"(d[30]), "+f"(d[31]), "+f"(d[32]), "+f"(d[33]), "+f"(d[34]), "+f"(d[35]), "+f"(d[36]), "+f"(d[37]), "+f"(d[38]), "+f"(d[39]), "+f"(d[40]), "+f"(d[41]), "+f"(d[42]), "+f"(d[43]), "+f"(d[44]), "+f"(d[45]), "+f"(d[46]), "+f"(d[47]), "+f"(d[48]), "+f"(d[49]), "+f"(d[50]), "+f"(d[51]), "+f"(d[52]), "+f"(d[53]), "+f"(d[54]), "+f"(d[55]), "+f"(d[56]), "+f"(d[57]), "+f"(d[58]), "+f"(d[59]), "+f"(d[60]), "+f"(d[61]), "+f"(d[62]), "+f"(d[63])
    : "r"(a0), "r"(a1), "r"(a2), "r"(a3), "r"(blo));
}

struct CvCtx {
  uint32_t koff, zero, so[3];
  int srcA, srcB;
  bool wrapA, s3, kodd;
};
struct CvPipe { uint32_t Ap, Ep, keep, send; };
template <int LO> __device__ __forceinline__ void cv_copy(float (&acc)[64]) {
#pragma unroll
  for (int i = LO; i < 64; i++) { float t; asm volatile("mov.b32 %0, %1;" : "=f"(t) : "f"(acc[i]) : "memory"); acc[i] = t; }
}
template <int G> __device__ __forceinline__ void cv_raw(uint32_t (&A)[4][4], uint32_t kaddr) {
#pragma unroll
  for (int i = 0; i < 4; i++) {
    const uint32_t a = kaddr + (4 * G + i) * 128;
    A[i][0] = lds32(a); A[i][1] = lds32(a + 4); A[i][3] = lds32(a + 8);
  }
}
__device__ __forceinline__ void cv_form(uint32_t (&A)[4][4], uint32_t sel) {
#pragma unroll
  for (int i = 0; i < 4; i++) {
    asm volatile("prmt.b32 %0, %0, %1, %2;" : "+r"(A[i][0]) : "r"(A[i][1]), "r"(sel));
    asm volatile("prmt.b32 %0, %1, %2, %3;" : "=r"(A[i][2]) : "r"(A[i][1]), "r"(A[i][3]), "r"(sel));
  }
}
#define CVV 2
template <int G> __device__ __forceinline__ void cv_step(float (&acc)[64], uint32_t (&A)[4][4], CvPipe& s, const CvCtx& c, uint32_t cb, uint32_t stg) {
  constexpr int JA = G - 1, JB = G - 2, NH = CVV == 1 ? 4 : (CVV == 3 ? 2 : 1);
  const uint32_t db0 = desc_lo(cb + CV_U + 192, CV_PL);
  uint32_t B[4][4];
  uint32_t ra[2], rb;
  if constexpr (G < 8) {
    wgmma_fence();
#pragma unroll
    for (int i = 0; i < NH; i++) wgmma_rs_hi<128 - 16 * (G & 7)>(acc, A[i][0], A[i][1], A[i][2], A[i][3], db0 - 4 * i);
    wgmma_commit();
    __syncwarp();
  }
  if constexpr (JA >= 0 && JA < 8) {
    const uint32_t p0 = pack_bf16(acc[8 * JA + 1], acc[8 * JA + 3]), p1 = pack_bf16(acc[8 * JA + 5], acc[8 * JA + 7]);
    ra[0] = __shfl_sync(0xffffffffu, c.wrapA ? s.Ap : p0, c.srcA);
    ra[1] = __shfl_sync(0xffffffffu, c.wrapA ? p0 : p1, c.srcA);
    s.Ap = p1;
  }
  if constexpr (JB >= 0) rb = __shfl_sync(0xffffffffu, s.send, c.srcB);
  if constexpr (G < 7) cv_raw<G + 1>(B, cb + c.koff);
  uint32_t z = 0;
  if constexpr (G < 8 && NH < 4) {
    __syncwarp();
    wgmma_fence();
#pragma unroll
    for (int i = NH; i < 4; i++) wgmma_rs_hi<128 - 16 * (G & 7)>(acc, A[i][0], A[i][1], A[i][2], A[i][3], db0 - 4 * i);
    wgmma_commit();
    asm volatile("mov.u32 %0, %%clock;" : "=r"(z)::"memory");
    z &= c.zero;
  }
  if constexpr (G < 7) cv_form(B, 0x5432u | z);
  if constexpr (JB >= 0) sts32(stg + ((c.so[JB / 3] >> (10 * (JB % 3))) & 0xffc), hadd2(rb | z, s.keep));
  if constexpr (JA >= 0 && JA < 8) {
    const uint32_t sh = 16 | z, mk = 0xffff0000u | z;
    const uint32_t ev = pack_bf16(acc[8 * JA] + __uint_as_float(ra[0] << sh), acc[8 * JA + 2] + __uint_as_float(ra[0] & mk));
    const uint32_t od = pack_bf16(acc[8 * JA + 4] + __uint_as_float(ra[1] << sh), acc[8 * JA + 6] + __uint_as_float(ra[1] & mk));
    s.send = c.kodd ? ev : (c.s3 ? s.Ep : od);
    s.keep = c.kodd ? od : ev;
    s.Ep = od;
  }
  if constexpr (G < 8) { __syncwarp(); wgmma_wait<0>(); cv_copy<8 * (G & 7)>(acc); }
  if constexpr (G < 9) cv_step<G + 1>(acc, B, s, c, cb, stg);
}
__device__ __forceinline__ uint32_t cv_stage(int slot) { return sb + (slot < 4 ? 40960 + slot * 4096 : CV_OFF + CV_K); }
__device__ __forceinline__ void cv_setup(CvCtx& c) {
  const int tid = tid_opaque() & 127, w = tid >> 5, lane = tid & 31, r = lane >> 2, q = lane & 3;
  const int i0 = (r >> 1) & 1, i1 = r >> 2;
  c.koff = CV_K - 32 + 4 * (8 * (r >> 1) + 2 * w + (r & 1) + 2 * q);
  c.srcA = i0 ? lane - 8 : lane + 8 - q + ((q + 3) & 3);
  c.wrapA = i0 && q == 3;
  c.srcB = i1 == 0 ? (lane - q + 16 + ((q + 3) & 3)) : (lane - q - 16 + ((q + 1) & 3));
  c.s3 = (i1 == 1 && q == 3); c.kodd = (i1 == 1 && q < 3);
  c.zero = lds32(sb + EP_OFF + 24);
#pragma unroll
  for (int i = 0; i < 3; i++) c.so[i] = lds32(sb + SO_OFF + 512 * i + 4 * tid);
}
__device__ __forceinline__ void cv_table() {
  const int tid = tid_opaque() & 127, r = (tid & 31) >> 2, q = tid & 3;
  int t = 16 * (2 * (r < 4 ? q : 4 + ((q + 1) & 3)) + ((r >> 1) & 1)) + 4 * (tid >> 5) + 2 * (r & 1);
#pragma unroll 1
  for (int i = 0; i < 3; i++) {
    uint32_t v = 0;
#pragma unroll 1
    for (int x = 0; x < 3; x++, t += 256) {
      const int T = t / 160, tl = t - T * 160;
      const int qq = (T >= NT1 - 1) ? (tl >> 5) : (tl / 40);
      int ck = 20 * T + ((tl - qq * ((T >= NT1 - 1) ? 32 : 40)) >> 1);
      ck ^= (ck >> 2) & 6;
      v |= (uint32_t)((ck * 4 + qq) & 1023) << (10 * x + 2);
    }
    sts32(sb + SO_OFF + 512 * i + 4 * tid, v);
  }
}
__device__ __forceinline__ void conv_channel(int slot, const CvCtx& c) {
  const uint32_t cb = sb + CV_OFF + slot * CV_B;
  float acc[64];
  CvPipe s;
  s.Ap = s.Ep = 0u;
  uint32_t A[4][4];
#pragma unroll
  for (int i = 0; i < 64; i++) acc[i] = 0.f;
  if (slot == 4) mbar_wait(bars + 8 * B_CVDONE);
  mbar_wait(bars + 8 * (B_CVFULL + slot));
  cv_raw<0>(A, cb + c.koff);
  {
    const uint32_t w0 = lds32(cb + CV_K);
    const uint32_t wp = __byte_perm(pack_bf16(bf_lo(w0) + __uint_as_float(lds32(sb + EP_OFF + 4 * slot)), 0.f), w0, 0x7610);
    if (c.koff == CV_K) A[0][0] = wp;
    if (c.koff == CV_K - 4) A[0][1] = wp;
    if (c.koff == CV_K - 8) A[0][3] = wp;
  }
  cv_form(A, 0x5432u);
  cv_copy<0>(acc);
  cv_step<0>(acc, A, s, c, cb, cv_stage(slot));
  fence_async_smem();
  mbar_arrive(bars + 8 * (B_CVDONE + slot));
}

__device__ __forceinline__ void kv_issue(const Params& p, int c, int m2, int dg) {
  const uint32_t fb = bars + 8 * (B_KV + c);
  mbar_expect_tx(fb, KV_PIECE);
  tma3(sb + KS_OFF + c * KV_PIECE, &p.mK, 160 * dg + 32 * c, 64 * m2 - 3, 0, fb);
  tma3(sb + KS_OFF + c * KV_PIECE + 4864, &p.mV, 160 * dg + 32 * c, 64 * m2 - 1, 0, fb);
}
__device__ __forceinline__ void kv_tile(int m, int dg, int c, int y) {
  const int lane = tid_opaque() & 31, tg = lane >> 3;
  const uint32_t pb = sb + KS_OFF + c * KV_PIECE + 32 * y + 4 * (lane & 7);
  const uint32_t ka = pb + tg * 1216, va = pb + 4864 + tg * 1088 + 64;
  const uint32_t kh = (m == 0 && tg > 0) ? ka - 192 : ka;
  uint32_t kk[19], u[16];
  const float4 t = lds128f(sb + TAP_OFF + 256 * c + 128 * y + 16 * (lane & 7));
#pragma unroll
  for (int i = 0; i < 19; i++) { kk[i] = lds32((i < 3 ? kh : ka) + i * 64); if (i >= 3) u[i - 3] = lds32(va + (i - 3) * 64); }
  uint8_t* dst = g_kv + ((160 * dg + 32 * c + 16 * y + 2 * (lane & 7)) * 4096 + (4 * m + tg) * 16);
  const uint32_t w0 = __byte_perm(__float_as_uint(t.x), __float_as_uint(t.z), 0x5410), w1 = __byte_perm(__float_as_uint(t.x), __float_as_uint(t.z), 0x7632);
  const uint32_t w2 = __byte_perm(__float_as_uint(t.y), __float_as_uint(t.w), 0x5410), w3 = __byte_perm(__float_as_uint(t.y), __float_as_uint(t.w), 0x7632);
#pragma unroll
  for (int i = 0; i < 16; i++) {
    uint32_t a = hmul2(kk[i], w3);
    a = hadd2(a, hmul2(kk[i + 1], w2)); a = hadd2(a, hmul2(kk[i + 2], w1)); a = hadd2(a, hmul2(kk[i + 3], w0));
    u[i] = hmul2(a, u[i]);
  }
#pragma unroll
  for (int e = 0; e < 2; e++)
#pragma unroll
    for (int f = 0; f < 2; f++) {
      uint32_t o[4];
#pragma unroll
      for (int qq = 0; qq < 4; qq++) o[qq] = __byte_perm(u[15 - 4 * qq - 2 * f], u[14 - 4 * qq - 2 * f], e ? 0x7632 : 0x5410);
      *(uint4*)(dst + e * 4096 + f * 2048) = make_uint4(o[0], o[1], o[2], o[3]);
    }
}
__device__ __forceinline__ void ln_finish(float s1, float s2, float& mean, float& rstd) {
  mean = s1 * (1.f / 640.f);
  const float v = fmaxf(fmaf(-mean, mean, s2 * (1.f / 640.f)), 0.f) + 1e-5f;
  asm("rsqrt.approx.ftz.f32 %0, %1;" : "=f"(rstd) : "f"(v));
}
__device__ __forceinline__ void stat_table(int T1, unsigned want, int l, int g, const uint4* x0, const uint4* x1, float (&xa)[2], float (&xb)[2]) {
  const int n = 32 * g + (tid_opaque() & 31);
  const uint4* rp = &g_stats[8 * l * SEQ + min(160 * T1 + n, SEQ - 1)];
  float a[4], b[4];
  uint32_t it = 0;
  while (true) {
    bool ok = true;
#pragma unroll
    for (int i = 0; i < 4; i++) ok &= (rec_ld(rp + SEQ * i, a[i], b[i]) == want);
    ok &= rec_ld(x0, xa[0], xb[0]) == want;
    ok &= rec_ld(x1, xa[1], xb[1]) == want;
    if (__all_sync(0xffffffffu, ok)) break;
    trap_if(++it > SPIN_LIMIT);
  }
  float m, rs;
  ln_finish((a[0] + a[1]) + (a[2] + a[3]), (b[0] + b[1]) + (b[2] + b[3]), m, rs);
  sts64f(sb + STAB_OFF + n * 8, rs, -m * rs);
}
__device__ __forceinline__ void stats_reduce(float (&a)[2], float (&b)[2], float (&mean)[2], float (&rstd)[2]) {
#pragma unroll
  for (int o = 1; o < 4; o <<= 1)
#pragma unroll
    for (int h = 0; h < 2; h++) { a[h] += __shfl_xor_sync(0xffffffffu, a[h], o); b[h] += __shfl_xor_sync(0xffffffffu, b[h], o); }
#pragma unroll
  for (int h = 0; h < 2; h++) ln_finish(a[h], b[h], mean[h], rstd[h]);
}

template <bool FIRST>
__device__ __forceinline__ void stats_publish(int which, int n0, int dg, unsigned tag, const float (&acc)[80]) {
  const int q = tid_opaque() & 3, h = q & 1;
  float s1[2] = {0.f, 0.f}, s2[2] = {0.f, 0.f}, t1[2] = {0.f, 0.f}, t2[2] = {0.f, 0.f};
#pragma unroll
  for (int j = 0; j < 20; j++)
#pragma unroll
    for (int y = 0; y < 2; y++) {
      const float a = acc[4 * j + 2 * y], b = acc[4 * j + 2 * y + 1];
      s1[y] += a; t1[y] += b; s2[y] = fmaf(a, a, s2[y]); t2[y] = fmaf(b, b, t2[y]);
    }
#pragma unroll
  for (int y = 0; y < 2; y++) { s1[y] += t1[y]; s2[y] += t2[y]; }
  float a = (h ? s1[1] : s1[0]) + __shfl_xor_sync(0xffffffffu, h ? s1[0] : s1[1], 1);
  float b = (h ? s2[1] : s2[0]) + __shfl_xor_sync(0xffffffffu, h ? s2[0] : s2[1], 1);
  a += __shfl_xor_sync(0xffffffffu, a, 2);
  b += __shfl_xor_sync(0xffffffffu, b, 2);
  if (FIRST) {
    rec_st(&g_stats[((q >> 1) * 4 + dg) * SEQ + n0 + 8 * h], a, b, q < 2 ? tag : tag - 1);
    rec_st(&g_stats[((q >> 1) * 4 + 8 + dg) * SEQ + n0 + 8 * h], a, b, tag - 1);
  } else if (q < 2) rec_st(&g_stats[(which * 4 + dg) * SEQ + n0 + 8 * h], a, b, tag);
}
__device__ __forceinline__ void stats_get(int which, int n0, unsigned tag, float (&mean)[2], float (&rstd)[2]) {
  const uint4* p0 = &g_stats[(which * 4 + (tid_opaque() & 3)) * SEQ + n0];
  float a[2], b[2];
  uint32_t it = 0;
  while (true) {
    const unsigned t0 = rec_ld(p0, a[0], b[0]), t1 = rec_ld(p0 + 8, a[1], b[1]);
    if (__all_sync(0xffffffffu, t0 == tag && t1 == tag)) break;
    trap_if(++it > SPIN_LIMIT);
  }
  stats_reduce(a, b, mean, rstd);
}
__device__ __forceinline__ void x0_load(float (&acc)[80]) {
  const int t = tid_opaque() & 127;
  const uint32_t xa = sb + XT_OFF + (16 * (t >> 5) + ((t & 31) >> 2)) * 320 + 8 * (t & 3);
  mbar_wait(bars + 8 * B_XT);
#pragma unroll
  for (int h = 0; h < 2; h++)
#pragma unroll
    for (int J = 0; J < 10; J++) {
      const float2 v = lds64f(xa + h * 2560 + 32 * J);
      const uint32_t x = __float_as_uint(v.x), y = __float_as_uint(v.y);
      acc[8 * J + 2 * h] = bf_lo(x); acc[8 * J + 2 * h + 1] = bf_hi(x);
      acc[8 * J + 4 + 2 * h] = bf_lo(y); acc[8 * J + 4 + 2 * h + 1] = bf_hi(y);
    }
}

template <bool FROM_X0>
__device__ __forceinline__ void dskip_init(float (&acc)[80], const float (&mean)[2], const float (&rstd)[2]) {
  const int t = tid_opaque() & 127;
  const uint32_t xa = sb + XT_OFF + (16 * (t >> 5) + ((t & 31) >> 2)) * 320 + 8 * (t & 3), da = sb + DTAB_OFF + 8 * (t & 3);
  float2 dw[10], xv[10][2];
#pragma unroll
  for (int J = 0; J < 2; J++) { dw[J] = lds64f(da + 32 * J); if (FROM_X0) { xv[J][0] = lds64f(xa + 32 * J); xv[J][1] = lds64f(xa + 2560 + 32 * J); } }
#pragma unroll
  for (int J = 0; J < 10; J++) {
    if (J + 2 < 10) { dw[J + 2] = lds64f(da + 32 * (J + 2)); if (FROM_X0) { xv[J + 2][0] = lds64f(xa + 32 * (J + 2)); xv[J + 2][1] = lds64f(xa + 2560 + 32 * (J + 2)); } }
#pragma unroll
    for (int x = 0; x < 8; x++) {
      const int h = (x >> 1) & 1;
      const uint32_t dwd = __float_as_uint(x < 4 ? dw[J].x : dw[J].y);
      const float tt = fmaf(rstd[h], (x & 1) ? bf_hi(dwd) : bf_lo(dwd), 1.f);
      float a = acc[8 * J + x];
      if (FROM_X0) { const uint32_t xw = __float_as_uint(x < 4 ? xv[J][h].x : xv[J][h].y); a = (x & 1) ? bf_hi(xw) : bf_lo(xw); }
      acc[8 * J + x] = FROM_X0 ? (a - mean[h]) * tt : fmaf(a, tt, -mean[h] * tt);
    }
  }
}

__global__ void __launch_bounds__(512, 1) fused_kernel(const __grid_constant__ Params p) {
  extern __shared__ __align__(1024) uint8_t smem_raw[];
  const int tid = threadIdx.x, lane = tid & 31;
  const int wid = __shfl_sync(0xffffffffu, tid >> 5, 0), wg = wid >> 2;
  unsigned smid; asm volatile("mov.u32 %0, %%smid;" : "=r"(smid));
  const int role = p.role[min(smid, 131u)];
  if (wid == 12) {
    const bool el = elect_one();
    if (el) {
      asm volatile("prefetch.tensormap [%0];" ::"l"(&p.mB) : "memory");
      asm volatile("prefetch.tensormap [%0];" ::"l"((role & 15) == NT1 - 1 ? &p.mXl : &p.mX) : "memory");
#pragma unroll
      for (int k = 0; k < S1; k++) mbar_init(bars + 8 * (B_G1FULL + k), 1);
#pragma unroll
      for (int k = 0; k < 6; k++) mbar_init(bars + 8 * (B_XT + k), 1);
      asm volatile("fence.mbarrier_init.release.cluster;" ::: "memory");
    }
    if (role >= 0) {
      __syncwarp();
      asm volatile("bar.arrive 5, 288;" ::: "memory");
      const Role R = unpack_role(role);
      if (elect_one()) {
        TS(45);
#pragma unroll 1
        for (int k = 0; k < S1; k++) {
          const uint32_t fb = bars + 8 * (B_G1FULL + k);
          mbar_expect_tx(fb, G1_STAGE);
          tma4(sb + k * G1_STAGE + G1_XOFF, R.last ? &p.mXl : &p.mX, 64 * k, 0, 0, R.last ? 0 : 80 * R.T1, fb);
          tma5(sb + k * G1_STAGE, &p.mB, 64 * k, 0, 0, 4 * R.side, 2 * R.GP, fb);
          if (PFD) asm volatile("prefetch.tensormap [%0];" ::"l"(&p.mK + k) : "memory");
        }
        if (R.has2) {
#pragma unroll 1
          for (int c = 0; c < KV0; c++) kv_issue(p, c, R.m2, R.dg);
          mbar_expect_tx(bars + 8 * B_XT, 20480);
#pragma unroll 1
          for (int h = 0; h < 2; h++) {
            const int ng = 8 * R.m2 + 4 * h, T = ng / 20;
            tma4(sb + XT_OFF + h * 10240, T == NT1 - 1 ? &p.mXtl : &p.mXt, 160 * R.dg, 0, 0, T == NT1 - 1 ? ng - 240 : ng + 60 * T, bars + 8 * B_XT);
          }
        }
        TS(44);
      }
      __syncwarp();
      bar_sync(6, 64);
    }
  }
  trap_if(smid >= 132 || smem_u32(smem_raw) != sb);
  if (role < 0) {
    if (wid == 0) {
      const unsigned tag = ld_rlx(g_epoch);
      uint32_t it = 0;
      while (!__all_sync(0xffffffffu, (int)(ld_rlx(&g_hcnt[(lane & 7) * 32]) - 40 * tag) >= 0)) { __nanosleep(500); trap_if(++it > SPIN_LIMIT); }
    }
    return;
  }
  float mean0[2] = {0.f, 0.f}, rstd0[2] = {0.f, 0.f};
  if (wg == 2 || wid == 14) {
    ROLE(role)
    const int c = wid == 14 ? 4 : wid - 8;
    const unsigned tag = ld_rlx(g_epoch);
    if (has2) {
      uint2 bv[2][5];
#pragma unroll
      for (int x = 0; x < 2; x++)
#pragma unroll
        for (int i = 0; i < 5; i++) bv[x][i] = ldv64((const uint2*)((x ? p.bim : p.bre) + (cch0 + 32 * c) * DM) + lane + 32 * i);
      float sv[2];
#pragma unroll
      for (int x = 0; x < 2; x++) {
        float a = 0.f;
#pragma unroll
        for (int i = 0; i < 5; i++) a += (bf_lo(bv[x][i].x) + bf_hi(bv[x][i].x)) + (bf_lo(bv[x][i].y) + bf_hi(bv[x][i].y));
        sv[x] = a;
      }
#pragma unroll
      for (int o = 16; o > 0; o >>= 1) { sv[0] += __shfl_xor_sync(0xffffffffu, sv[0], o); sv[1] += __shfl_xor_sync(0xffffffffu, sv[1], o); }
      if (lane < 2) rec_st(&g_sB[(cch0 + 32 * c) * 2 + lane], sv[0], sv[1], tag);
      if (tid == 256) TS(47);
      __syncwarp();
      bar_sync(8, 192);
      mbar_wait(bars + 8 * B_EP);
      mbar_wait(bars + 8 * (B_KV + c));
#pragma unroll 1
      for (int y = 0; y < 2; y++) kv_tile(m2, dg, c, y);
      __syncwarp();
      if (lane == 0) mbar_arrive(bars + 8 * B_PREP);
      if (tid == 352) TS(52);
      if (tid == 448) TS(51);
      if (wg == 2) {
        float xs[80];
        x0_load(xs);
        stats_publish<true>(0, 64 * m2 + 16 * c + (lane >> 2), dg, tag, xs);
        if (tid == 256) TS(31);
      }
      mbar_wait(bars + 8 * (TABW ? B_PUB : B_PREP));
    } else bar_sync(8, 192);
    {
      const uint4* x0 = wg == 2 ? &g_stats[(lane & 3) * SEQ + (has2 ? 64 * m2 : 0) + 16 * c + (lane >> 2)] : &g_sB[(128 * GP + 32 * side + lane) * 2];
      float xa[2], xb[2];
      stat_table(T1, tag, 0, c, x0, x0 + (wg == 2 ? 8 : 128), xa, xb);
      if (wg == 2) stats_reduce(xa, xb, mean0, rstd0);
      else {
#pragma unroll
        for (int i = 0; i < 2; i++) sts64f(sb + CTAB_OFF + (32 * i + lane) * 24 + 16, p.swap ? xb[i] : xa[i], p.swap ? xa[i] : xb[i]);
      }
      mbar_arrive(bars + 8 * B_STAB);
      if (tid == 448) TS(26);
    }
  } else if (wid == 15) {
    ROLE(role)
    const int ch = 128 * GP + 32 * side + lane;
    uint32_t r0 = ldv16(p.lre + ch), r1 = ldv16(p.lim + ch), r2 = ldv16(p.logdt + ch);
    const uint32_t r3 = ldv16(p.lre + ch + 64), r4 = ldv16(p.lim + ch + 64), r5 = ldv16(p.logdt + ch + 64);
#pragma unroll 1
    for (int i = 0; i < 2; i++) {
      const float lr = bf_lo(r0), li = bf_lo(r1);
      const float dt = __bfloat162float(__float2bfloat16_rn(expf(bf_lo(r2))));
      const float mag = expf(dt * lr);
      float sn, cs; sincospif(dt * li * 0.31830988618379067f, &sn, &cs);
      const float ar = mag * cs, ai = mag * sn;
      const float inv = 2.f / (lr * lr + li * li);
      const uint32_t ad = sb + CTAB_OFF + (32 * i + lane) * 24;
      sts64f(ad, ar, ai);
      sts64f(ad + 8, ((ar - 1.f) * lr + ai * li) * inv, (ai * lr - (ar - 1.f) * li) * inv);
      r0 = r3; r1 = r4; r2 = r5;
    }
    if (lane == 0) TS(46);
    __syncwarp();
    bar_sync(7, 64);
    mbar_arrive(bars + 8 * B_CTAB);
  } else if (wid == 13) {
    ROLE(role)
    uint4 tv[3];
    const uint32_t e0 = ld_rlx(g_epoch);
    const uint32_t e1 = ldv16(p.ssmD + min(cch0 + 32 * lane, 639));
    const uint4 dv = ldv128((const uint4*)(p.dskip + 160 * dg) + min(lane, 19));
#pragma unroll
    for (int i = 0; i < 3; i++) tv[i] = ldv128((const uint4*)(p.shiftk + 640 * dg) + min(lane + 32 * i, 79));
    sts128(sb + DTAB_OFF + 16 * min(lane, 19), dv);
#pragma unroll
    for (int i = 0; i < 3; i++) sts128(sb + TAP_OFF + 16 * min(lane + 32 * i, 79), tv[i]);
    if (lane < 7) sts32(sb + EP_OFF + 4 * lane, lane < 5 ? e1 << 16 : (lane == 5 ? e0 : 0u));
    __syncwarp();
    bar_sync(9, 64);
    mbar_arrive(bars + 8 * B_CTAB);
    if (lane == 0) { mbar_arrive(bars + 8 * B_EP); TS(53); }
    if (has2) {
      mbar_wait(bars + 8 * B_PREP);
      if (lane < 4) red_rel(&g_kvcnt[(dg * 4 + lane) * 32]);
      __syncwarp();
      if (lane == 0) { mbar_arrive(bars + 8 * B_PUB); TS(30); }
    }
  } else if (wid != 12) {
    if (elect_one()) {
      if (wid < 7) {
        const int b0 = wid < 4 ? 4 + 20 * wid : 85 + 21 * (wid - 4), cnt = wid < 4 ? 2 : 1;
#pragma unroll
        for (int i = 0; i < 21; i++) mbar_init(bars + 8 * (b0 + i), cnt);
      } else {
#pragma unroll
        for (int i = 0; i < 12; i++) mbar_init(bars + 8 * (B_CVDONE + i), (i == 5 || i == 6) ? 160 : 128);
        mbar_init(bars + 8 * B_CTAB, 192); mbar_init(bars + 8 * B_PREP, 5);
      }
      asm volatile("fence.mbarrier_init.release.cluster;" ::: "memory");
    }
    __syncwarp();
    bar_sync(5, 288);
    if (wid == 2) asm volatile("bar.arrive 8, 192;\nbar.arrive 6, 64;\nbar.arrive 9, 64;\nbar.arrive 7, 64;" ::: "memory");
    if (tid == 128) TS(0);
    if (wg == 1) { cv_table(); mbar_arrive(bars + 8 * B_CTAB); }
  }

  if (wid == 12) {
    ROLE(role)
    uint32_t dst = sb;
#pragma unroll 1
    for (int k = S1; k < 10; k++) {
      const uint32_t fb = bars + 8 * (B_G1FULL + k);
      mbar_wait(bars + 8 * (B_G1DONE + k - S1));
      if (k == RGATE && has2) mbar_wait(bars + 8 * B_PUB);
      if (elect_one()) {
        mbar_expect_tx(fb, 20480);
        tma4(dst + G1_XOFF, last ? &p.mXl : &p.mX, 64 * k, 0, 0, last ? 0 : 80 * T1, fb);
        mbar_expect_tx(fb, 16384);
        tma5(dst, &p.mB, 64 * k, 0, 0, 4 * side, 2 * GP, fb);
        if (has2 && k - S1 + KV0 < 5) kv_issue(p, k - S1 + KV0, m2, dg);
      }
      dst += G1_STAGE; if (k == 2 * S1 - 1) dst = sb;
    }
  } else if (wid == 15 && (role >> 16)) {
    ROLE(role)
    mbar_wait(bars + 8 * B_PREP);
#pragma unroll
    for (int c = 0; c < 5; c++) {
      const uint32_t cb = sb + CV_OFF + c * CV_B;
      sts128(lane < 8 ? cb + 16 * lane : (lane < 20 ? cb + CV_U + 16 * (lane - 8) : cb + CV_U + CV_PL + 16 * (lane - 20)), make_uint4(0, 0, 0, 0));
    }
    fence_async_smem();
    __syncwarp();
    const unsigned tag = lds32(sb + EP_OFF + 20);
    mbar_wait(bars + 8 * B_PUB);
    if (elect_one()) {
#pragma unroll 1
      for (int c = 0; c < 5; c++) {
        mbar_expect_tx(bars + 8 * (B_CVFULL + c), 8192);
        bulk_g2s(sb + CV_OFF + c * CV_B + CV_K, p.ssmk + (cch0 + 32 * c) * SEQ, 4096, bars + 8 * (B_CVFULL + c));
      }
    }
    cnt_poll(&g_kvcnt[(dg * 4 + (m2 >> 3)) * 32], 32 * tag);
    fence_async_global();
    if (elect_one()) {
      TS(28);
#pragma unroll
      for (int c = 0; c < 10; c++)
        bulk_g2s(sb + CV_OFF + (c >> 1) * CV_B + CV_U + 192 + (c & 1) * CV_PL, g_kv + cch0 * 4096 + (c >> 1) * 131072 + (c & 1) * 2048, 2048, bars + 8 * (B_CVFULL + (c >> 1)));
#pragma unroll
      for (int i = 0; i < 3; i++) asm volatile("prefetch.tensormap [%0];" ::"l"(&p.mCre + i) : "memory");
      TS(54);
    }
    __syncwarp();
  }
  {
    const int w = wid & 3;
    if (wg == 2 && !(role >> 16)) {
      float xa[2], xb[2];
      mbar_wait(bars + 8 * (B_G1FULL + 11));
      stat_table(role & 15, lds32(sb + EP_OFF + 20), 1, w, g_stats, g_stats, xa, xb);
      mbar_arrive(bars + 8 * (B_STAB + 1));
    }
#pragma unroll 1
    for (int l = 0; l < 2; l++) {
      if (wg < 2) {
        float acc[80];
#pragma unroll
        for (int i = 0; i < 80; i++) acc[i] = 0.f;
        ROLE(role)
        const int tid = tid_opaque(), r = (tid & 31) >> 2, q = tid & 3;
        const int ch = 128 * GP + 64 * wg + 32 * side + 8 * w + r;
        const uint32_t ca = sb + CTAB_OFF + (32 * wg + 8 * w + r) * 24;
        float2 lam = make_float2(0.f, 0.f), p8 = lam, p16 = lam, pL = lam, p2L = lam;
        fence_regs(acc);
        {
          const uint32_t alo0 = (l == 0 ? desc_lo(sb, 16) : desc_lo(sb + G2_WOFF, 16)) + wg * 512;
          const uint32_t blo0 = l == 0 ? desc_lo(sb + G1_XOFF, 16) : desc_lo(sb + X1_OFF, 128);
          const uint32_t bhi = l == 0 ? desc_hi(1024, 1) : desc_hi(1024, 0), xstep = l == 0 ? 2 : 16;
          const uint32_t astep = l == 0 ? G1_STAGE >> 4 : 1024, bstep = l == 0 ? G1_STAGE >> 4 : 1280, aend = alo0 + (S1 + l) * astep;
          uint32_t alo = alo0, blo = blo0;
          uint32_t fb = bars + 8 * (B_G1FULL + 10 * l);
          mbar_wait(fb);
          if (tid == 0) TS(1 + 8 * l);
#pragma unroll 1
          for (int k = 0; k < 10; k++) {
            uint32_t ok; const uint32_t nb = k < 9 ? fb + 8 : fb;
            wgmma_fence();
#pragma unroll
            for (int kk = 0; kk < 4; kk++) {
              wgmma_n160<0>(acc, alo + kk * 2, desc_hi(1024, 1), blo + kk * xstep, bhi);
              if (kk == 0) ok = mbar_test(nb);
              if (kk == STG_KK && k == 9 && tid == 0) mbar_arrive(bars + 8 * (B_STG + l));
            }
            wgmma_commit();
            alo += astep; blo += bstep;
            if (blo == desc_lo(sb + G_OFF, 128)) blo = desc_lo(sb, 128);
            if (alo == aend) { alo = alo0; blo = blo0; }
            wgmma_wait<1>();
            if (k > 0 && (tid & 127) == 0) mbar_arrive(fb + 8 * (B_G1DONE - B_G1FULL - 1));
            if (!ok) mbar_wait(nb);
            if (wg == 1 && k == (l ? 8 - STG_D : 9 - STG0)) mbar_wait(bars + 8 * (B_STG + l));
            if (k == 3) {
              mbar_wait(bars + 8 * B_CTAB);
              lam = lds64f(ca);
              if (p.swap) lam.y = -lam.y;
              const float2 p2 = cmul(lam, lam), p4 = cmul(p2, p2);
              p8 = cmul(p4, p4); p16 = cmul(p8, p8);
              pL = cmul(p16, p16);
              if (!last) pL = cmul(pL, p8);
              p2L = cmul(pL, pL);
            }
            if (k == PAUSE_K && has2) mbar_wait(bars + 8 * B_PREP);
            fb += 8;
          }
        }
        mbar_wait(bars + 8 * (B_STAB + l));
        const float2 sB = lds64f(ca + 16);
        const unsigned tag = lds32(sb + EP_OFF + 20);
        wgmma_wait<0>();
        fence_regs(acc);
        if ((tid & 127) == 0) { mbar_arrive(bars + 8 * (B_G1DONE + 10 * l + 9)); TS(wg ? 17 + l : 2 + 8 * l); }
        float2 ec[3];
#pragma unroll
        for (int jj = 0; jj < 8; jj++)
#pragma unroll
          for (int y = 0; y < 3; y++) {
            if (y == 2 && (jj & 1)) continue;
            const int j = y == 2 ? 16 + (jj >> 1) : 8 * y + jj;
            const float4 st = lds128f(sb + STAB_OFF + (8 * j + 2 * q) * 8);
            acc[4 * j + 0] = fmaf(acc[4 * j + 0], st.x, st.y * sB.x);
            acc[4 * j + 2] = fmaf(acc[4 * j + 2], st.x, st.y * sB.y);
            acc[4 * j + 1] = fmaf(acc[4 * j + 1], st.z, st.w * sB.x);
            acc[4 * j + 3] = fmaf(acc[4 * j + 3], st.z, st.w * sB.y);
            ec[y] = jj == 0 ? make_float2(acc[4 * j + 0], acc[4 * j + 2]) : cfma(lam, ec[y], make_float2(acc[4 * j + 0], acc[4 * j + 2]));
            ec[y] = cfma(lam, ec[y], make_float2(acc[4 * j + 1], acc[4 * j + 3]));
          }
        float2 e = cfma(p16, ec[0], ec[1]);
        if (!last) e = cfma(p8, e, ec[2]);
        {
          float2 v = make_float2(__shfl_up_sync(0xffffffffu, e.x, 1, 4), __shfl_up_sync(0xffffffffu, e.y, 1, 4));
          if (q >= 1) e = cfma(pL, v, e);
          v = make_float2(__shfl_up_sync(0xffffffffu, e.x, 2, 4), __shfl_up_sync(0xffffffffu, e.y, 2, 4));
          if (q >= 2) e = cfma(p2L, v, e);
        }
        if (!last && (q == 3 || (q == 2 && l == 0))) rec_st(&g_E[((q == 3 ? l : 1) * NT1 + T1) * DM + ch], e.x, e.y, q == 3 ? tag : tag - 1);
        if (tid == 0) TS(3 + 8 * l);
        float2 ex = make_float2(__shfl_up_sync(0xffffffffu, e.x, 1, 4), __shfl_up_sync(0xffffffffu, e.y, 1, 4));
        if (q == 0) ex = make_float2(0.f, 0.f);
        const float2 coef = lds64f(ca + 8), lamc = make_float2(lam.x, p.swap ? lam.y : -lam.y);
        float m00 = coef.x, m01 = -coef.y, m10 = -coef.y, m11 = -coef.x;
        if (p.swap) { m00 = -coef.y; m01 = coef.x; m10 = -coef.x; m11 = -coef.y; }
        float2 pLq, p160q, p640;
        {
          const float2 p80 = last ? cmul(p2L, p16) : p2L, p160 = cmul(p80, p80), p320 = cmul(p160, p160), one = make_float2(1.f, 0.f);
          p640 = cmul(p320, p320);
          pLq = cmul((q & 1) ? pL : one, (q & 2) ? p2L : one);
          p160q = cmul((q & 1) ? p160 : one, (q & 2) ? p320 : one);
        }
        float2 c, ev[3];
        unsigned tg[3];
        const uint4* ep = &g_E[(l * NT1 + T1 - 1 - q) * DM + ch];
#pragma unroll
        for (int j = 0; j < 20; j++) {
          if (j == CPOLL) {
#pragma unroll
            for (int i = 0; i < 3; i++) {
              ev[i] = make_float2(0.f, 0.f); tg[i] = tag;
              if (T1 - 1 - q - 4 * i >= 0) tg[i] = rec_ld(ep - 4 * i * DM, ev[i].x, ev[i].y);
            }
          }
#pragma unroll
          for (int x = 0; x < 2; x++) {
            const float b0 = acc[4 * j + x], b1 = acc[4 * j + 2 + x];
            acc[4 * j + x] = fmaf(b0, m00, b1 * m01);
            acc[4 * j + 2 + x] = fmaf(b0, m10, b1 * m11);
          }
          if (j == CPOLL - 1 || j == 19) asm volatile("" : "+f"(acc[4 * j]), "+f"(acc[4 * j + 1]), "+f"(acc[4 * j + 2]), "+f"(acc[4 * j + 3])::"memory");
        }
        {
          uint32_t it = 0;
          while (__any_sync(0xffffffffu, tg[0] != tag || tg[1] != tag || tg[2] != tag)) {
#pragma unroll
            for (int i = 0; i < 3; i++)
              if (tg[i] != tag) tg[i] = rec_ld(ep - 4 * i * DM, ev[i].x, ev[i].y);
            trap_if(++it > SPIN_LIMIT);
          }
          c = cfma(p640, cfma(p640, ev[2], ev[1]), ev[0]);
          c = cmul(c, p160q);
          c.x += __shfl_xor_sync(0xffffffffu, c.x, 1); c.y += __shfl_xor_sync(0xffffffffu, c.y, 1);
          c.x += __shfl_xor_sync(0xffffffffu, c.x, 2); c.y += __shfl_xor_sync(0xffffffffu, c.y, 2);
        }
        if (tid == 0) TS(4 + 8 * l);
        if (wg == 1 && l >= HOLD0) mbar_wait(bars + 8 * (B_REL + l));
        c = cfma(pLq, c, ex);
        float2 hh = make_float2(fmaf(c.x, m00, c.y * m01), fmaf(c.x, m10, c.y * m11));
        uint8_t* hb = g_h + (size_t)l * (32 * 20 * 8192) + (10 * wg + 2 * GP) * 8192 + (4 * side + w) * 1024 + (tid_opaque() & 31) * 4;
#pragma unroll
        for (int j4 = 0; j4 < 5; j4++) {
          const int ng = 20 * T1 + 4 * j4;
          uint8_t* hp = hb + (size_t)(ng >> 3) * 163840 + (ng & 7) * 128;
#pragma unroll
          for (int jj = 0; jj < 4; jj++) {
            const int j = 4 * j4 + jj;
            const float2 h0 = cfma(lamc, hh, make_float2(acc[4 * j + 0], acc[4 * j + 2]));
            hh = cfma(lamc, h0, make_float2(acc[4 * j + 1], acc[4 * j + 3]));
            if (j4 < 4 || !last) {
              *(uint32_t*)(hp + jj * 128) = pack_bf16(h0.x, hh.x);
              *(uint32_t*)(hp + jj * 128 + 8192) = pack_bf16(h0.y, hh.y);
            }
          }
        }
        mbar_arrive(bars + 8 * (B_HST + 2 * l + wg));
        if (tid == 0) TS(5 + 8 * l);
        if (tid == 128) TS(l ? 25 : 19);
        if (l == 0 && wid == 4) {
          mbar_wait(bars + 8 * B_HST);
          mbar_wait(bars + 8 * (B_HST + 1));
          if ((tid & 31) < 8) h_release((tid >> 2) & 1, T1, tid & 3);
          __syncwarp();
          if (tid == 128) { mbar_arrive(bars + 8 * B_REL); TS(6); }
        }
      }
      if (l == 0) {
        ROLE(role)
        if (has2) {
          CvCtx cc;
          mbar_wait(bars + 8 * B_CTAB);
          cv_setup(cc);
          mbar_wait(bars + 8 * (B_G1DONE + 9));
#pragma unroll 1
          for (int c = (wg + 2) & 3; c < 5; c += 4) conv_channel(c, cc);
          if ((tid & 127) == 0) TS(wg == 2 ? 32 : (wg == 3 ? 50 : 7 + wg));
        }
      }
      if (wg >= 2) break;
    }
    if (wg == 3) {
    ROLE(role)
    const int pw = wid & 3, gpc = 2 * min(m2 >> 3, 3) + (dg >> 1);
    mbar_wait(bars + 8 * B_EP);
    const unsigned tag = lds32(sb + EP_OFF + 20);
    if (pw == 0) {
      if (elect_one()) {
#pragma unroll 1
        for (int l = 0; l < 2; l++) {
          uint32_t dst = sb;
          if (l == 1) {
            dst = sb + G2_WOFF;
#pragma unroll 1
            for (int k = 0; k < 10; k++) {
              mbar_wait(k > 4 ? bars + 8 * (B_G1DONE + 5 + k) : (has2 ? bars + 8 * (B_G2DONE + 14 + min(k, 3)) : bars + 8 * (B_G1DONE + 9)));
              mbar_expect_tx(bars + 8 * (B_G1FULL + 10 + k), 16384);
              tma5(dst, &p.mB, 64 * k, 0, 0, 4 * side, 2 * GP, bars + 8 * (B_G1FULL + 10 + k));
              dst += 16384; if (k == 4) dst = sb + G2_WOFF;
            }
          }
          if (has2) {
            const uint32_t fb2 = bars + 8 * (B_G2FULL + 20 * l), wb2 = bars + 8 * (B_G2DONE + 20 * l - S2);
            dst = sb + G2_WOFF + (WTAIL ? 4 * l * G2_WB : 0);
            int kc = 0;
#pragma unroll 1
            for (int k = 0; k < 20; k++) {
              mbar_wait(k >= S2 ? wb2 + 8 * k : bars + 8 * (l ? B_G1DONE + (WTAIL ? (k < 3 ? 15 + k : 13 + k) : 19) : (k == 5 ? B_XFREE : (k == 6 ? B_SFREE : B_REL))));
              mbar_expect_tx(fb2 + 8 * k, G2_WB);
              tma5(dst, &p.mCre + (k & 1), kc, 0, 0, 0, 10 * dg, fb2 + 8 * k);
              kc += (k & 1) << 7; if (k == 9) kc = 64;
              dst += G2_WB; if (dst == sb + G2_WOFF + S2 * G2_WB) dst = sb + G2_WOFF;
            }
          }
        }
      }
    } else if (pw == 1) {
#pragma unroll 1
      for (int l = 0; l < 2; l++) {
        if (l == 1) {
          mbar_wait(bars + 8 * (has2 ? B_G2DONE + 19 : B_G1DONE + 9));
          if (has2) mbar_wait(bars + 8 * B_UST);
          cnt_poll(&g_ucnt[gpc * 32], 128 * tag);
          fence_async_global();
          if (elect_one()) {
            TS(20);
            const int bytes = last ? 16384 : 20480;
            const uint8_t* src = g_u + T1 * 204800;
            uint32_t dst = sb + X1_OFF;
#pragma unroll 1
            for (int k = 0; k < 10; k++) {
              if (k > 4) mbar_wait(bars + 8 * (B_G1DONE + 5 + k));
              mbar_expect_tx(bars + 8 * (B_G1FULL + 10 + k), bytes);
              bulk_g2s(dst, src, bytes, bars + 8 * (B_G1FULL + 10 + k));
              src += 20480; dst += 20480; if (dst == sb + G_OFF) dst = sb; if (k == 4) dst = sb + X1_OFF;
            }
          }
          __syncwarp();
        }
        if (has2) {
          mbar_wait(bars + 8 * (B_HST + 2 * l));
          mbar_wait(bars + 8 * (B_G1DONE + 10 * l + 9));
          cnt_poll(&g_hcnt[(l * 16 + gpc) * 32], 40 * tag);
          fence_async_global();
          if (elect_one()) {
            TS(21 + 2 * l);
            const uint32_t fb2 = bars + 8 * (B_G2FULL + 20 * l), wb2 = bars + 8 * (B_G2DONE + 20 * l - S2);
            const uint8_t* src = g_h + (l * 32 + m2) * 163840;
            uint32_t dst = sb;
#pragma unroll 1
            for (int k = 0; k < 20; k++) {
              if (k >= 5) mbar_wait(k >= S2 ? wb2 + 8 * k : bars + 8 * B_SFREE);
              if (k == 10) { mbar_wait(bars + 8 * (B_H1 + l)); fence_async_global(); }
              mbar_expect_tx(fb2 + 8 * k, G2_XB);
              bulk_g2s(dst, src, G2_XB, fb2 + 8 * k);
              src += 8192; dst += G2_XB; if (dst == sb + S2 * G2_XB) dst = sb;
            }
          }
          __syncwarp();
        }
      }
    } else if (pw == 2) {
#pragma unroll 1
      for (int l = 0; l < 2; l++) {
        if (l == 1) {
          float xa[2], xb[2];
          mbar_wait(bars + 8 * (B_G1FULL + 11));
          stat_table(T1, tag, 1, 4, g_stats, g_stats, xa, xb);
          mbar_arrive(bars + 8 * (B_STAB + 1));
        }
#pragma unroll 1
        for (int w = 0; w < 2 * l; w++) {
          mbar_wait(bars + 8 * (B_HST + 2 + w));
          if (lane < 4) h_release(2 + w, T1, lane);
          __syncwarp();
          if (lane == 0) { if (w == 0) mbar_arrive(bars + 8 * (B_REL + 1)); TS(w ? 16 : 14); }
        }
        if (l == 0 && has2 && elect_one()) {
#pragma unroll 1
          for (int i = 0; i < 5; i++) {
            const int c = i < 3 ? i : 7 - i;
            mbar_wait(bars + 8 * (B_CVDONE + c));
            bulk_s2g(g_G + (cch0 + 32 * c) * 4096, cv_stage(c), 4096);
          }
          asm volatile("cp.async.bulk.commit_group;" ::: "memory");
          asm volatile("cp.async.bulk.wait_group.read 0;" ::: "memory");
          mbar_arrive(bars + 8 * B_SFREE);
          asm volatile("cp.async.bulk.wait_group 0;" ::: "memory");
          TS(48);
          fence_async_global();
          asm volatile("fence.acq_rel.gpu;" ::: "memory");
#pragma unroll
          for (int i = 0; i < 4; i++) red_rlx(&g_gcnt[(dg * 4 + i) * 32]);
          TS(49);
          mbar_arrive(bars + 8 * (B_GO + 1));
        }
        __syncwarp();
      }
    } else if (has2) {
      mbar_wait(bars + 8 * B_REL);
      if (elect_one()) {
        l2_prefetch(p.cre + (160 * dg + 5 * m2) * DM, 6400); l2_prefetch(p.cim + (160 * dg + 5 * m2) * DM, 6400);
      }
      mbar_wait(bars + 8 * (B_HST + 1));
      flag_poll(&g_hcnt[(8 + gpc) * 32], 40 * tag);
      if (lane == 0) { mbar_arrive(bars + 8 * B_H1); TS(22); }
      mbar_wait(bars + 8 * (B_GO + 1));
      flag_poll(&g_gcnt[(dg * 4 + (m2 >> 3)) * 32], 32 * tag);
      fence_async_global();
      if (elect_one()) {
        TS(29);
        mbar_expect_tx(bars + 8 * B_GFULL, 20480);
        tma5(sb + G_OFF, &p.mG, 64 * m2, 0, 0, 0, 10 * dg, bars + 8 * B_GFULL);
      }
      mbar_wait(bars + 8 * (B_HST + 3));
      cnt_poll(&g_hcnt[(24 + gpc) * 32], 40 * tag);
      if (lane == 0) { mbar_arrive(bars + 8 * (B_H1 + 1)); TS(24); }
    }
    } else if (wg == 2 && (role >> 16)) {
      float acc[80];
      float off[2] = {mean0[0], mean0[1]};
      const unsigned tag = lds32(sb + EP_OFF + 20);
      dskip_init<true>(acc, mean0, rstd0);
      mbar_arrive(bars + 8 * B_XFREE);
#pragma unroll 1
      for (int l = 0; l < 2; l++) {
        float mean[2], rstd[2];
        {
          uint32_t alo = desc_lo(sb, 1024), blo = desc_lo(sb + G2_WOFF, 16) + (WTAIL ? l * (G2_WB >> 2) : 0);
          uint32_t fb = bars + 8 * (B_G2FULL + 20 * l);
          fence_regs(acc);
          mbar_wait(bars + 8 * (B_CVDONE + 2));
          mbar_wait(bars + 8 * (B_CVDONE + 3));
          mbar_wait(fb);
          if (tid == 256) TS(33 + 6 * l);
#pragma unroll 1
          for (int k = 0; k < 20; k++) {
            if (l == TSL && (k & 3) == 3 && tid == 256) TS(56 + (k >> 2));
            uint32_t ok; const uint32_t nb = k < 19 ? fb + 8 : fb;
            wgmma_fence();
#pragma unroll
            for (int kk = 0; kk < 4; kk++) {
              wgmma_n160<1>(acc, alo + kk * 128, desc_hi(128, 0), blo + kk * 2, desc_hi(1024, 1));
              if (kk == 0) ok = mbar_test(nb);
            }
            wgmma_commit();
            alo += G2_XB >> 4; blo += G2_WB >> 4;
            if (alo == desc_lo(sb + S2 * G2_XB, 1024)) alo = desc_lo(sb, 1024);
            if (blo == desc_lo(sb + G_OFF, 16)) blo = desc_lo(sb + G2_WOFF, 16);
            wgmma_wait<1>();
            if (k > 0 && tid == 256) mbar_arrive(fb + 8 * (B_G2DONE - B_G2FULL - 1));
            if (!ok) mbar_wait(nb);
            fb += 8;
          }
          wgmma_wait<0>();
          fence_regs(acc);
          if (tid == 256) TS(34 + 6 * l);
          if (tid == 256) mbar_arrive(bars + 8 * (B_G2DONE + 20 * l + 19));
        }
        ROLE(role)
        const int tq = tid_opaque() & 31, n0 = 64 * m2 + 16 * w + (tq >> 2);
        stats_publish<false>(2 * l + 1, n0, dg, tag, acc);
        uint32_t gf[10][4];
        mbar_wait(bars + 8 * B_GFULL);
        const uint32_t ga = sb + G_OFF + (8 * (tq >> 4) + (tq & 7)) * 128 + (((2 * w + ((tq >> 3) & 1)) ^ ((2 * m2) & 6) ^ (tq & 7)) << 4);
#pragma unroll
        for (int J = 0; J < 2; J++) ldsm4t(gf[J], ga + J * 2048);
        if (tid == 256) TS(35 + 6 * l);
        uint8_t* dst[2][2];
#pragma unroll
        for (int h = 0; h < 2; h++) {
          if (l == 0) {
            const int ng = 8 * m2 + 2 * w + h, T = ng / 20;
            uint8_t* ub = g_u + (T * 204800 + (ng - 20 * T) * 1024 + (tq & 2) * 64 + (tq & 28) * 4 + (tq & 1) * 8 + (5 * dg >> 1) * 20480);
            dst[h][1] = ub + ((dg & 1) ? 20480 - 512 : 0);
            dst[h][0] = ub + (dg & 1) * 512;
          } else {
            dst[h][0] = dst[h][1] = (uint8_t*)(p.out + (n_to_t(n0 + 8 * h) * DM + 160 * dg + 4 * (tq & 3)));
          }
        }
        stats_get(2 * l + 1, n0, tag, mean, rstd);
        if (tid == 256) TS(36 + 6 * l);
        off[0] += mean[0]; off[1] += mean[1];
        const float ov[2] = {l ? off[0] : 0.f, l ? off[1] : 0.f};
#pragma unroll
        for (int J = 0; J < 10; J++) {
          if (J + 2 < 10) ldsm4t(gf[J + 2 < 10 ? J + 2 : 0], ga + (J + 2) * 2048);
#pragma unroll
          for (int x = 0; x < 8; x++) {
            const int h = (x >> 1) & 1;
            const uint32_t gwd = gf[J][x >> 1];
            const float t = fmaf(rstd[h], (x & 1) ? bf_hi(gwd) : bf_lo(gwd), 1.f);
            acc[8 * J + x] = fmaf(acc[8 * J + x], t, fmaf(-mean[h], t, ov[h]));
          }
#pragma unroll
          for (int h = 0; h < 2; h++) {
            if (l == 0)
              *(uint2*)(dst[h][(J >> 1) & 1] + (J >> 2) * 20480 + (J & 3) * 256) =
                  make_uint2(pack_bf16(acc[8 * J + 2 * h], acc[8 * J + 2 * h + 1]), pack_bf16(acc[8 * J + 4 + 2 * h], acc[8 * J + 5 + 2 * h]));
            else
              *(float4*)(dst[h][0] + 64 * J) = make_float4(acc[8 * J + 2 * h], acc[8 * J + 2 * h + 1], acc[8 * J + 4 + 2 * h], acc[8 * J + 5 + 2 * h]);
          }
          __syncwarp();
        }
        if (l == 0) {
          bar_sync(3, 128);
          if (tid == 288) { TS(37); mbar_arrive(bars + 8 * B_UST); }
          if (tid < 264) red_rel(&g_ucnt[(tid & 7) * 32]);
          __syncwarp();
          if (tid == 256) TS(38);
          stats_publish<false>(2, n0, dg, tag, acc);
          mbar_wait(bars + 8 * (B_G1FULL + 11));
          float xa[2], xb[2];
          const uint4* x0 = &g_stats[(8 + (tq & 3)) * SEQ + n0];
          stat_table(T1, tag, 1, w, x0, x0 + 8, xa, xb);
          mbar_arrive(bars + 8 * (B_STAB + 1));
          if (tid == 256) TS(27);
          stats_reduce(xa, xb, mean, rstd);
          off[0] += mean[0]; off[1] += mean[1];
          mbar_wait(bars + 8 * (B_HST + 2));
          dskip_init<false>(acc, mean, rstd);
        } else {
          if (tid == 256) {
            TS(43);
            if (m2 == 31 && dg == 3) asm volatile("st.relaxed.gpu.global.u32 [%0], %1;" ::"l"(g_epoch), "r"(tag + 1) : "memory");
          }
        }
      }
    }
  }
}

typedef CUresult (*EncFn)(CUtensorMap*, CUtensorMapDataType, cuuint32_t, void*, const cuuint64_t*, const cuuint64_t*,
                          const cuuint32_t*, const cuuint32_t*, CUtensorMapInterleave, CUtensorMapSwizzle,
                          CUtensorMapL2promotion, CUtensorMapFloatOOBfill);

void encode(EncFn fn, CUtensorMap* m, const void* ptr, int rank, const cuuint64_t* dims, const cuuint64_t* strides, const cuuint32_t* box,
            CUtensorMapSwizzle swz = CU_TENSOR_MAP_SWIZZLE_128B) {
  cuuint32_t es[5] = {1, 1, 1, 1, 1};
  fn(m, CU_TENSOR_MAP_DATA_TYPE_BFLOAT16, rank, (void*)ptr, dims, strides, box, es, CU_TENSOR_MAP_INTERLEAVE_NONE,
     swz, (CUtensorMapL2promotion)(swz == CU_TENSOR_MAP_SWIZZLE_128B ? PROM_A : PROM_B), CU_TENSOR_MAP_FLOAT_OOB_FILL_NONE);
}

}

extern "C" void kernel_launch(void* const* d_in, const int* in_sizes, int n_in, void* d_out, int out_size) {
  (void)in_sizes; (void)n_in; (void)out_size;
  Params p;
  typedef const __nv_bfloat16* BP;
  p.x = (BP)d_in[0]; p.lre = (BP)d_in[1]; p.lim = (BP)d_in[2]; p.bre = (BP)d_in[3]; p.bim = (BP)d_in[4];
  p.cre = (BP)d_in[5]; p.cim = (BP)d_in[6]; p.logdt = (BP)d_in[7]; p.dskip = (BP)d_in[8];
  p.k = (BP)d_in[10]; p.v = (BP)d_in[11]; p.shiftk = (BP)d_in[12]; p.ssmk = (BP)d_in[13]; p.ssmD = (BP)d_in[14];
  p.out = (float*)d_out;
  for (int sm = 0; sm < 132; sm++) {
    const int tpc = sm >> 1, side = sm & 1;
    int gpc, gi;
    if (tpc < 32) { gpc = tpc & 7; gi = tpc >> 3; }
    else if (tpc < 60) { gpc = 1 + (tpc - 32) % 7; gi = 4 + (tpc - 32) / 7; }
    else if (tpc < 62) { gpc = tpc - 54; gi = 8; }
    else { gpc = 0; gi = tpc - 58; }
    const int pos = 8 * gpc + gi + (gpc == 7 ? 1 : 0);
    int T1, GP;
    if (pos < 52) { const int hh = pos / 26, x = pos - 26 * hh; T1 = x >> 1; GP = 2 * hh + (x & 1); }
    else { T1 = pos - 52; GP = 4; }
    const int m2 = 8 * (gpc >> 1) + gi, dg = 2 * (gpc & 1) + side;
    p.role[sm] = pos == 65 ? -1 : (T1 | (GP << 4) | (side << 7) | (m2 << 8) | (dg << 14) | ((gi < 8) << 16));
  }
  void* fnp = nullptr;
  cudaDriverEntryPointQueryResult qr;
  cudaGetDriverEntryPoint("cuTensorMapEncodeTiled", &fnp, cudaEnableDefault, &qr);
  EncFn fn = (EncFn)fnp;
  void* gG = nullptr;
  cudaGetSymbolAddress(&gG, g_G);
  const cuuint64_t RB = DM * 2;
  {
    p.swap = p.bim < p.bre;
    const char* lo = (const char*)(p.swap ? p.bim : p.bre); const char* hi = (const char*)(p.swap ? p.bre : p.bim);
    cuuint64_t dims[5] = {640, 8, 2, 8, 10}, st[4] = {RB, (cuuint64_t)(hi - lo), 8 * RB, 64 * RB}; cuuint32_t box[5] = {64, 8, 2, 4, 2};
    encode(fn, &p.mB, lo, 5, dims, st, box);
  }
  {
    cuuint64_t dims[5] = {640, 2, 4, 2, 40}, st[4] = {RB, 4 * RB, 2 * RB, 16 * RB}; cuuint32_t box[5] = {64, 2, 4, 2, 10};
    encode(fn, &p.mCre, p.cre, 5, dims, st, box); encode(fn, &p.mCim, p.cim, 5, dims, st, box);
    cuuint64_t dimg[5] = {2048, 2, 4, 2, 40}, stg[4] = {4096, 4 * 4096, 2 * 4096, 16 * 4096};
    encode(fn, &p.mG, gG, 5, dimg, stg, box);
  }
  {
    cuuint64_t dims[4] = {640, 2, 4, 900}, st[3] = {RB, 40 * RB, 2 * RB}; cuuint32_t box[4] = {64, 2, 4, 20};
    encode(fn, &p.mX, p.x, 4, dims, st, box);
    cuuint64_t diml[4] = {640, 2, 4, 16}, stl[3] = {RB, 32 * RB, 2 * RB};
    encode(fn, &p.mXl, p.x + (size_t)1920 * DM, 4, diml, stl, box);
    cuuint32_t boxt[4] = {160, 2, 4, 4};
    encode(fn, &p.mXt, p.x, 4, dims, st, boxt, CU_TENSOR_MAP_SWIZZLE_NONE);
    encode(fn, &p.mXtl, p.x + (size_t)1920 * DM, 4, diml, stl, boxt, CU_TENSOR_MAP_SWIZZLE_NONE);
    cuuint64_t dk[3] = {640, 2000, 4}, sk[2] = {RB, 16 * RB}; cuuint32_t bk[3] = {32, 19, 4}, bv[3] = {32, 17, 4};
    encode(fn, &p.mK, p.k, 3, dk, sk, bk, CU_TENSOR_MAP_SWIZZLE_NONE);
    encode(fn, &p.mV, p.v, 3, dk, sk, bv, CU_TENSOR_MAP_SWIZZLE_NONE);
  }
  cudaFuncSetAttribute(fused_kernel, cudaFuncAttributeMaxDynamicSharedMemorySize, SMEM_BYTES);
  cudaLaunchConfig_t cfg = {};
  cfg.gridDim = dim3(132); cfg.blockDim = dim3(512); cfg.dynamicSmemBytes = SMEM_BYTES; cfg.stream = cudaStreamPerThread;
  cudaLaunchKernelEx(&cfg, fused_kernel, p);
}
```

```cpp
#include <cuda_runtime.h>
#include <cuda.h>
#include <cuda_bf16.h>
#include <stdint.h>

namespace {

constexpr int SEQ = 2048, DM = 640;
constexpr int NT1 = 13;
#define EXP 0
#define WPF1 3
#define WPF2 7
#define CPOLL 10
#define KV0 1
#define TAPLATE 1
#define STG_D 3
#define STG_KK 1
#define HOLD0 1
#define WREL 0
#define UREL 1
#define TSL 1
#define STG0 0
#define WTAIL 1
#define PFD 1
#define TAPW 1
#define PAUSE_K 5
constexpr uint32_t SPIN_LIMIT = 1u << 22;

__device__ __align__(1024) uint8_t g_h[2 * 32 * 20 * 8192];
__device__ __align__(1024) uint8_t g_u[NT1 * 10 * 20480];
__device__ __align__(1024) uint8_t g_kv[DM * 4096];
__device__ __align__(1024) uint8_t g_G[DM * 4096];
__device__ __align__(128) uint4 g_E[2 * NT1 * DM];
__device__ __align__(128) uint4 g_stats[4 * 4 * SEQ];
__device__ __align__(128) uint4 g_sB[DM * 2];
__device__ __align__(128) unsigned g_hcnt[2 * 2 * 8 * 32];
__device__ __align__(128) unsigned g_ucnt[8 * 32];
__device__ __align__(128) unsigned g_kvcnt[16 * 32];
__device__ __align__(128) unsigned g_gcnt[16 * 32];
__device__ __align__(128) unsigned g_epoch[32] = {1};
#define TS(i) do {} while (0)

struct Params {
  CUtensorMap mX, mB, mXl, mK, mV, mXt, mXtl, mCre, mCim, mG, mU;
  const __nv_bfloat16 *x, *lre, *lim, *bre, *bim, *cre, *cim, *logdt, *dskip, *k, *v, *shiftk, *ssmk, *ssmD;
  float* out;
  int swap;
  int role[132];
};

constexpr uint32_t sb = 1024;
constexpr uint32_t G1_STAGE = 36864, G1_XOFF = 16384;
constexpr int S1 = 4;
constexpr uint32_t XT_OFF = 159744, KS_OFF = 180224, KV_PIECE = 9216;
constexpr uint32_t G2_XB = 8192, G2_WB = 20480, G2_WOFF = 57344, G_OFF = 200704;
constexpr uint32_t X1_OFF = 139264;
constexpr int S2 = 7;
constexpr uint32_t CV_OFF = KS_OFF, CV_K = 128, CV_PL = 2240, CV_U = CV_K + 4096, CV_B = KV_PIECE;
constexpr uint32_t MISC = 226304;
constexpr uint32_t BAR_OFF = MISC;
constexpr int B_G1FULL = 0, B_G1DONE = 20, B_G2FULL = 40,
              B_G2DONE = 85, B_GFULL = 125, B_EP = 126, B_H1 = 127  , B_CVFULL = 129  , B_STG = 134  , B_REL = 136  , B_SFREE = 138, B_UST = 142,
              B_GO = 139  , B_PUB = 147,
              B_CVDONE = 148  , B_STAB = 153  , B_XFREE = 155, B_HST = 156  ,
              B_CTAB = 160, B_PREP = 161, B_XT = 162, B_KV = 163  , B_PREP2 = 84;
constexpr uint32_t bars = sb + BAR_OFF;
constexpr uint32_t STAB_OFF = MISC + 1344;
constexpr uint32_t CTAB_OFF = STAB_OFF + 1280;
constexpr uint32_t DTAB_OFF = CTAB_OFF + 1536;
constexpr uint32_t EP_OFF = DTAB_OFF + 320;
constexpr uint32_t SO_OFF = EP_OFF + 32;
constexpr uint32_t TAP_OFF = 147456;
constexpr uint32_t SMEM_BYTES = 232448;
static_assert(SO_OFF + 1536 <= SMEM_BYTES, "smem");

__device__ __forceinline__ void trap_if(bool c) { asm volatile("{\n.reg .pred p;\nsetp.ne.u32 p, %0, 0;\n@p trap;\n}\n" ::"r"((uint32_t)c)); }
__device__ __forceinline__ uint32_t smem_u32(const void* p) { return (uint32_t)__cvta_generic_to_shared(p); }
__device__ __forceinline__ void mbar_init(uint32_t bar, int cnt) { asm volatile("mbarrier.init.shared::cta.b64 [%0], %1;" ::"r"(bar), "r"(cnt) : "memory"); }
__device__ __forceinline__ void mbar_expect_tx(uint32_t bar, int bytes) { asm volatile("mbarrier.arrive.expect_tx.shared::cta.b64 _, [%0], %1;" ::"r"(bar), "r"(bytes) : "memory"); }
__device__ __forceinline__ void mbar_arrive(uint32_t bar) { asm volatile("mbarrier.arrive.shared::cta.b64 _, [%0];" ::"r"(bar) : "memory"); }
__device__ __forceinline__ void mbar_wait(uint32_t bar) {
  asm volatile(
      "{\n.reg .pred p;\n.reg .u32 c;\nmov.u32 c, 0;\n"
      "W_%=:\nmbarrier.try_wait.parity.shared::cta.b64 p, [%0], 0;\n@p bra D_%=;\n"
      "add.u32 c, c, 1;\nsetp.lt.u32 p, c, %1;\n@p bra W_%=;\ntrap;\nD_%=:\n}\n" ::"r"(bar), "n"(SPIN_LIMIT) : "memory");
}
__device__ __forceinline__ uint32_t mbar_test(uint32_t bar) {
  uint32_t ok;
  asm volatile("{\n.reg .pred p;\nmbarrier.test_wait.parity.shared::cta.b64 p, [%1], 0;\nselp.u32 %0, 1, 0, p;\n}\n" : "=r"(ok) : "r"(bar) : "memory");
  return ok;
}
__device__ __forceinline__ void tma3(uint32_t dst, const CUtensorMap* m, int c0, int c1, int c2, uint32_t bar) {
  asm volatile("cp.async.bulk.tensor.3d.shared::cluster.global.mbarrier::complete_tx::bytes [%0], [%1, {%3,%4,%5}], [%2];"
               ::"r"(dst), "l"(m), "r"(bar), "r"(c0), "r"(c1), "r"(c2) : "memory");
}
__device__ __forceinline__ void tma4(uint32_t dst, const CUtensorMap* m, int c0, int c1, int c2, int c3, uint32_t bar) {
  asm volatile("cp.async.bulk.tensor.4d.shared::cluster.global.mbarrier::complete_tx::bytes [%0], [%1, {%3,%4,%5,%6}], [%2];"
               ::"r"(dst), "l"(m), "r"(bar), "r"(c0), "r"(c1), "r"(c2), "r"(c3) : "memory");
}
__device__ __forceinline__ void tma5(uint32_t dst, const CUtensorMap* m, int c0, int c1, int c2, int c3, int c4, uint32_t bar) {
  asm volatile("cp.async.bulk.tensor.5d.shared::cluster.global.mbarrier::complete_tx::bytes [%0], [%1, {%3,%4,%5,%6,%7}], [%2];"
               ::"r"(dst), "l"(m), "r"(bar), "r"(c0), "r"(c1), "r"(c2), "r"(c3), "r"(c4) : "memory");
}
__device__ __forceinline__ void bulk_g2s(uint32_t dst, const void* src, int bytes, uint32_t bar) {
  asm volatile("cp.async.bulk.shared::cluster.global.mbarrier::complete_tx::bytes [%0], [%1], %2, [%3];"
               ::"r"(dst), "l"(src), "r"(bytes), "r"(bar) : "memory");
}
__device__ __forceinline__ void bulk_s2g(void* dst, uint32_t src, int bytes) {
  asm volatile("cp.async.bulk.global.shared::cta.bulk_group [%0], [%1], %2;" ::"l"(dst), "r"(src), "r"(bytes) : "memory");
}
__device__ __forceinline__ void l2_prefetch(const void* src, int bytes) {
  asm volatile("cp.async.bulk.prefetch.L2.global [%0], %1;" ::"l"(src), "r"(bytes) : "memory");
}
__device__ __forceinline__ void wgmma_fence() { asm volatile("wgmma.fence.sync.aligned;" ::: "memory"); }
__device__ __forceinline__ void wgmma_commit() { asm volatile("wgmma.commit_group.sync.aligned;" ::: "memory"); }
template <int N> __device__ __forceinline__ void wgmma_wait() { asm volatile("wgmma.wait_group.sync.aligned %0;" ::"n"(N) : "memory"); }
__host__ __device__ constexpr uint32_t desc_lo(uint32_t addr, uint32_t lbo) { return ((addr & 0x3FFFF) >> 4) | ((lbo >> 4) << 16); }
__host__ __device__ constexpr uint32_t desc_hi(uint32_t sbo, uint32_t swz) { return (sbo >> 4) | (swz << 30); }
__device__ __forceinline__ void bar_sync(int id, int n) { asm volatile("bar.sync %0, %1;" ::"r"(id), "r"(n) : "memory"); }
__device__ __forceinline__ uint32_t lds32(uint32_t a) { uint32_t v; asm volatile("ld.shared.u32 %0, [%1];" : "=r"(v) : "r"(a) : "memory"); return v; }
__device__ __forceinline__ float2 lds64f(uint32_t a) { float2 v; asm volatile("ld.shared.v2.f32 {%0,%1}, [%2];" : "=f"(v.x), "=f"(v.y) : "r"(a) : "memory"); return v; }
__device__ __forceinline__ float4 lds128f(uint32_t a) { float4 v; asm volatile("ld.shared.v4.f32 {%0,%1,%2,%3}, [%4];" : "=f"(v.x), "=f"(v.y), "=f"(v.z), "=f"(v.w) : "r"(a) : "memory"); return v; }
__device__ __forceinline__ void ldsm4t(uint32_t (&r)[4], uint32_t a) {
  asm volatile("ldmatrix.sync.aligned.m8n8.x4.trans.shared.b16 {%0,%1,%2,%3}, [%4];" : "=r"(r[0]), "=r"(r[1]), "=r"(r[2]), "=r"(r[3]) : "r"(a) : "memory");
}
__device__ __forceinline__ uint4 ldv128(const void* a) { uint4 v; asm volatile("ld.global.nc.v4.u32 {%0,%1,%2,%3}, [%4];" : "=r"(v.x), "=r"(v.y), "=r"(v.z), "=r"(v.w) : "l"(a) : "memory"); return v; }
__device__ __forceinline__ uint2 ldv64(const void* a) { uint2 v; asm volatile("ld.global.nc.v2.u32 {%0,%1}, [%2];" : "=r"(v.x), "=r"(v.y) : "l"(a) : "memory"); return v; }
__device__ __forceinline__ uint32_t ldv16(const void* a) { uint32_t v; asm volatile("ld.global.nc.u16 %0, [%1];" : "=r"(v) : "l"(a) : "memory"); return v; }
__device__ __forceinline__ void sts128(uint32_t a, uint4 v) { asm volatile("st.shared.v4.u32 [%0], {%1,%2,%3,%4};" ::"r"(a), "r"(v.x), "r"(v.y), "r"(v.z), "r"(v.w) : "memory"); }
__device__ __forceinline__ void sts32(uint32_t a, uint32_t v) { asm volatile("st.shared.u32 [%0], %1;" ::"r"(a), "r"(v) : "memory"); }
__device__ __forceinline__ void sts64f(uint32_t a, float x, float y) { asm volatile("st.shared.v2.f32 [%0], {%1,%2};" ::"r"(a), "f"(x), "f"(y) : "memory"); }
__device__ __forceinline__ void red_rlx(unsigned* p) { asm volatile("red.relaxed.gpu.global.add.u32 [%0], 1;" ::"l"(p) : "memory"); }
__device__ __forceinline__ void red_rel(unsigned* p) { asm volatile("red.release.gpu.global.add.u32 [%0], 1;" ::"l"(p) : "memory"); }
__device__ __forceinline__ void fence_async_global() { asm volatile("fence.proxy.async.global;" ::: "memory"); }
__device__ __forceinline__ void fence_async_smem() { asm volatile("fence.proxy.async.shared::cta;" ::: "memory"); }
__device__ __forceinline__ void rec_st(uint4* p, float a, float b, unsigned tag) {
  asm volatile("{\n.reg .b128 t;\n.reg .b64 lo, hi;\nmov.b64 lo, {%1,%2};\nmov.b64 hi, {%3,%3};\nmov.b128 t, {lo,hi};\n"
               "st.relaxed.gpu.global.b128 [%0], t;\n}\n" ::"l"(p), "r"(__float_as_uint(a)), "r"(__float_as_uint(b)), "r"(tag) : "memory");
}
__device__ __forceinline__ unsigned rec_ld(const uint4* p, float& a, float& b) {
  unsigned x, y, t;
  asm volatile("{\n.reg .b128 t;\n.reg .b64 lo, hi;\n.reg .b32 u;\nld.relaxed.gpu.global.b128 t, [%3];\nmov.b128 {lo,hi}, t;\n"
               "mov.b64 {%0,%1}, lo;\nmov.b64 {%2,u}, hi;\n}\n" : "=r"(x), "=r"(y), "=r"(t) : "l"(p) : "memory");
  a = __uint_as_float(x); b = __uint_as_float(y);
  return t;
}
__device__ __forceinline__ unsigned ld_rlx(const unsigned* p) { unsigned v; asm volatile("ld.relaxed.gpu.global.u32 %0, [%1];" : "=r"(v) : "l"(p) : "memory"); return v; }
__device__ __forceinline__ void flag_poll(const unsigned* p, unsigned target) {
  uint32_t it = 0;
  while (!__all_sync(0xffffffffu, (int)(ld_rlx(p) - target) >= 0)) { trap_if(++it > SPIN_LIMIT); }
  asm volatile("fence.acquire.gpu;" ::: "memory");
}
__device__ __forceinline__ void cnt_poll(const unsigned* p, unsigned target) {
  unsigned a = ld_rlx(p); __nanosleep(100);
  unsigned b = ld_rlx(p); __nanosleep(100);
  unsigned c = ld_rlx(p);
  uint32_t it = 0;
  while (true) {
    if (__all_sync(0xffffffffu, (int)(a - target) >= 0)) break;
    a = ld_rlx(p);
    if (__all_sync(0xffffffffu, (int)(b - target) >= 0)) break;
    b = ld_rlx(p);
    if (__all_sync(0xffffffffu, (int)(c - target) >= 0)) break;
    c = ld_rlx(p);
    trap_if(++it > SPIN_LIMIT);
  }
  asm volatile("fence.acquire.gpu;" ::: "memory");
}
__device__ __forceinline__ void h_release(int idx, int T, int i) {
  const int Q = (i & 2) ? (T + 2) / 3 - 1 : T / 3;
  if (Q >= 0 && Q < 4 && ((i & 2) == 0 || T % 3 == 0)) red_rel(&g_hcnt[(idx * 8 + 2 * Q + (i & 1)) * 32]);
}
__device__ __forceinline__ uint32_t pack_bf16(float lo, float hi) {
  uint32_t r; asm("cvt.rn.bf16x2.f32 %0, %1, %2;" : "=r"(r) : "f"(hi), "f"(lo)); return r;
}
__device__ __forceinline__ float bf_lo(uint32_t w) { return __uint_as_float(w << 16); }
__device__ __forceinline__ float bf_hi(uint32_t w) { return __uint_as_float(w & 0xffff0000u); }
__device__ __forceinline__ uint32_t hmul2(uint32_t a, uint32_t b) {
  __nv_bfloat162 r = __hmul2_rn(*(__nv_bfloat162*)&a, *(__nv_bfloat162*)&b); return *(uint32_t*)&r;
}
__device__ __forceinline__ uint32_t hadd2(uint32_t a, uint32_t b) {
  __nv_bfloat162 r = __hadd2_rn(*(__nv_bfloat162*)&a, *(__nv_bfloat162*)&b); return *(uint32_t*)&r;
}
__device__ __forceinline__ float2 cmul(float2 a, float2 b) { return make_float2(a.x * b.x - a.y * b.y, a.x * b.y + a.y * b.x); }
__device__ __forceinline__ float2 cfma(float2 a, float2 b, float2 c) {
  return make_float2(fmaf(a.x, b.x, fmaf(-a.y, b.y, c.x)), fmaf(a.x, b.y, fmaf(a.y, b.x, c.y)));
}
template <int N> __device__ __forceinline__ void fence_regs(float (&a)[N]) {
#pragma unroll
  for (int i = 0; i < N; i++) asm volatile("" : "+f"(a[i])::"memory");
}
__device__ __forceinline__ bool elect_one() {
  uint32_t e; asm volatile("{\n.reg .pred P;\nelect.sync _|P, 0xffffffff;\nselp.u32 %0, 1, 0, P;\n}\n" : "=r"(e)); return e != 0;
}
__device__ __forceinline__ int tid_opaque() { int t; asm volatile("mov.u32 %0, %%tid.x;" : "=r"(t)); return t; }
struct Role { int T1, GP, side, m2, dg, cch0; bool last, has2; };
__device__ __forceinline__ Role unpack_role(int x) {
  Role r; r.T1 = x & 15; r.GP = (x >> 4) & 7; r.side = (x >> 7) & 1; r.m2 = (x >> 8) & 63; r.dg = (x >> 14) & 3;
  r.has2 = (x >> 16) & 1; r.last = r.T1 == NT1 - 1; r.cch0 = 160 * r.dg + r.m2; return r;
}
__device__ __forceinline__ Role fresh_role(int x) { asm volatile("" : "+r"(x)); return unpack_role(__shfl_sync(0xffffffffu, x, 0)); }
#define ROLE(x) const Role R_ = fresh_role(x); const int T1 = R_.T1, GP = R_.GP, side = R_.side, m2 = R_.m2, dg = R_.dg, cch0 = R_.cch0; \
  const bool last = R_.last, has2 = R_.has2; (void)T1; (void)GP; (void)side; (void)m2; (void)dg; (void)cch0; (void)last; (void)has2;
__device__ __forceinline__ int n_to_t(int n) {
  int T = n / 160, nl = n - T * 160;
  int L = (T == NT1 - 1) ? 32 : 40;
  return T * 160 + L * ((nl & 7) >> 1) + 2 * (nl >> 3) + (nl & 1);
}

template<int TA> __device__ __forceinline__ void wgmma_n160(float (&d)[80], uint32_t alo, uint32_t ahi, uint32_t blo, uint32_t bhi){
  asm volatile("{\n.reg .b64 da, db;\nmov.b64 da, {%80,%81};\nmov.b64 db, {%82,%83};\n"
    "wgmma.mma_async.sync.aligned.m64n160k16.f32.bf16.bf16 {%0, %1, %2, %3, %4, %5, %6, %7, %8, %9, %10, %11, %12, %13, %14, %15, %16, %17, %18, %19, %20, %21, %22, %23, %24, %25, %26, %27, %28, %29, %30, %31, %32, %33, %34, %35, %36, %37, %38, %39, %40, %41, %42, %43, %44, %45, %46, %47, %48, %49, %50, %51, %52, %53, %54, %55, %56, %57, %58, %59, %60, %61, %62, %63, %64, %65, %66, %67, %68, %69, %70, %71, %72, %73, %74, %75, %76, %77, %78, %79}, da, db, 1, 1, 1, %84, 0;\n}\n"
    : "+f"(d[0]), "+f"(d[1]), "+f"(d[2]), "+f"(d[3]), "+f"(d[4]), "+f"(d[5]), "+f"(d[6]), "+f"(d[7]), "+f"(d[8]), "+f"(d[9]), "+f"(d[10]), "+f"(d[11]), "+f"(d[12]), "+f"(d[13]), "+f"(d[14]), "+f"(d[15]), "+f"(d[16]), "+f"(d[17]), "+f"(d[18]), "+f"(d[19]), "+f"(d[20]), "+f"(d[21]), "+f"(d[22]), "+f"(d[23]), "+f"(d[24]), "+f"(d[25]), "+f"(d[26]), "+f"(d[27]), "+f"(d[28]), "+f"(d[29]), "+f"(d[30]), "+f"(d[31]), "+f"(d[32]), "+f"(d[33]), "+f"(d[34]), "+f"(d[35]), "+f"(d[36]), "+f"(d[37]), "+f"(d[38]), "+f"(d[39]), "+f"(d[40]), "+f"(d[41]), "+f"(d[42]), "+f"(d[43]), "+f"(d[44]), "+f"(d[45]), "+f"(d[46]), "+f"(d[47]), "+f"(d[48]), "+f"(d[49]), "+f"(d[50]), "+f"(d[51]), "+f"(d[52]), "+f"(d[53]), "+f"(d[54]), "+f"(d[55]), "+f"(d[56]), "+f"(d[57]), "+f"(d[58]), "+f"(d[59]), "+f"(d[60]), "+f"(d[61]), "+f"(d[62]), "+f"(d[63]), "+f"(d[64]), "+f"(d[65]), "+f"(d[66]), "+f"(d[67]), "+f"(d[68]), "+f"(d[69]), "+f"(d[70]), "+f"(d[71]), "+f"(d[72]), "+f"(d[73]), "+f"(d[74]), "+f"(d[75]), "+f"(d[76]), "+f"(d[77]), "+f"(d[78]), "+f"(d[79])
    : "r"(alo), "r"(ahi), "r"(blo), "r"(bhi), "n"(TA));
}
template<int N> __device__ __forceinline__ void wgmma_rs_hi(float (&d)[64], uint32_t a0, uint32_t a1, uint32_t a2, uint32_t a3, uint32_t blo);
template<> __device__ __forceinline__ void wgmma_rs_hi<16>(float (&d)[64], uint32_t a0, uint32_t a1, uint32_t a2, uint32_t a3, uint32_t blo){
  asm volatile("{\n.reg .b64 db;\nmov.b64 db, {%12,8};\nwgmma.mma_async.sync.aligned.m64n16k16.f32.bf16.bf16 {%0, %1, %2, %3, %4, %5, %6, %7}, {%8,%9,%10,%11}, db, 1, 1, 1, 0;\n}\n"
    : "+f"(d[56]), "+f"(d[57]), "+f"(d[58]), "+f"(d[59]), "+f"(d[60]), "+f"(d[61]), "+f"(d[62]), "+f"(d[63])
    : "r"(a0), "r"(a1), "r"(a2), "r"(a3), "r"(blo));
}
template<> __device__ __forceinline__ void wgmma_rs_hi<32>(float (&d)[64], uint32_t a0, uint32_t a1, uint32_t a2, uint32_t a3, uint32_t blo){
  asm volatile("{\n.reg .b64 db;\nmov.b64 db, {%20,8};\nwgmma.mma_async.sync.aligned.m64n32k16.f32.bf16.bf16 {%0, %1, %2, %3, %4, %5, %6, %7, %8, %9, %10, %11, %12, %13, %14, %15}, {%16,%17,%18,%19}, db, 1, 1, 1, 0;\n}\n"
    : "+f"(d[48]), "+f"(d[49]), "+f"(d[50]), "+f"(d[51]), "+f"(d[52]), "+f"(d[53]), "+f"(d[54]), "+f"(d[55]), "+f"(d[56]), "+f"(d[57]), "+f"(d[58]), "+f"(d[59]), "+f"(d[60]), "+f"(d[61]), "+f"(d[62]), "+f"(d[63])
    : "r"(a0), "r"(a1), "r"(a2), "r"(a3), "r"(blo));
}
template<> __device__ __forceinline__ void wgmma_rs_hi<48>(float (&d)[64], uint32_t a0, uint32_t a1, uint32_t a2, uint32_t a3, uint32_t blo){
  asm volatile("{\n.reg .b64 db;\nmov.b64 db, {%28,8};\nwgmma.mma_async.sync.aligned.m64n48k16.f32.bf16.bf16 {%0, %1, %2, %3, %4, %5, %6, %7, %8, %9, %10, %11, %12, %13, %14, %15, %16, %17, %18, %19, %20, %21, %22, %23}, {%24,%25,%26,%27}, db, 1, 1, 1, 0;\n}\n"
    : "+f"(d[40]), "+f"(d[41]), "+f"(d[42]), "+f"(d[43]), "+f"(d[44]), "+f"(d[45]), "+f"(d[46]), "+f"(d[47]), "+f"(d[48]), "+f"(d[49]), "+f"(d[50]), "+f"(d[51]), "+f"(d[52]), "+f"(d[53]), "+f"(d[54]), "+f"(d[55]), "+f"(d[56]), "+f"(d[57]), "+f"(d[58]), "+f"(d[59]), "+f"(d[60]), "+f"(d[61]), "+f"(d[62]), "+f"(d[63])
    : "r"(a0), "r"(a1), "r"(a2), "r"(a3), "r"(blo));
}
template<> __device__ __forceinline__ void wgmma_rs_hi<64>(float (&d)[64], uint32_t a0, uint32_t a1, uint32_t a2, uint32_t a3, uint32_t blo){
  asm volatile("{\n.reg .b64 db;\nmov.b64 db, {%36,8};\nwgmma.mma_async.sync.aligned.m64n64k16.f32.bf16.bf16 {%0, %1, %2, %3, %4, %5, %6, %7, %8, %9, %10, %11, %12, %13, %14, %15, %16, %17, %18, %19, %20, %21, %22, %23, %24, %25, %26, %27, %28, %29, %30, %31}, {%32,%33,%34,%35}, db, 1, 1, 1, 0;\n}\n"
    : "+f"(d[32]), "+f"(d[33]), "+f"(d[34]), "+f"(d[35]), "+f"(d[36]), "+f"(d[37]), "+f"(d[38]), "+f"(d[39]), "+f"(d[40]), "+f"(d[41]), "+f"(d[42]), "+f"(d[43]), "+f"(d[44]), "+f"(d[45]), "+f"(d[46]), "+f"(d[47]), "+f"(d[48]), "+f"(d[49]), "+f"(d[50]), "+f"(d[51]), "+f"(d[52]), "+f"(d[53]), "+f"(d[54]), "+f"(d[55]), "+f"(d[56]), "+f"(d[57]), "+f"(d[58]), "+f"(d[59]), "+f"(d[60]), "+f"(d[61]), "+f"(d[62]), "+f"(d[63])
    : "r"(a0), "r"(a1), "r"(a2), "r"(a3), "r"(blo));
}
template<> __device__ __forceinline__ void wgmma_rs_hi<80>(float (&d)[64], uint32_t a0, uint32_t a1, uint32_t a2, uint32_t a3, uint32_t blo){
  asm volatile("{\n.reg .b64 db;\nmov.b64 db, {%44,8};\nwgmma.mma_async.sync.aligned.m64n80k16.f32.bf16.bf16 {%0, %1, %2, %3, %4, %5, %6, %7, %8, %9, %10, %11, %12, %13, %14, %15, %16, %17, %18, %19, %20, %21, %22, %23, %24, %25, %26, %27, %28, %29, %30, %31, %32, %33, %34, %35, %36, %37, %38, %39}, {%40,%41,%42,%43}, db, 1, 1, 1, 0;\n}\n"
    : "+f"(d[24]), "+f"(d[25]), "+f"(d[26]), "+f"(d[27]), "+f"(d[28]), "+f"(d[29]), "+f"(d[30]), "+f"(d[31]), "+f"(d[32]), "+f"(d[33]), "+f"(d[34]), "+f"(d[35]), "+f"(d[36]), "+f"(d[37]), "+f"(d[38]), "+f"(d[39]), "+f"(d[40]), "+f"(d[41]), "+f"(d[42]), "+f"(d[43]), "+f"(d[44]), "+f"(d[45]), "+f"(d[46]), "+f"(d[47]), "+f"(d[48]), "+f"(d[49]), "+f"(d[50]), "+f"(d[51]), "+f"(d[52]), "+f"(d[53]), "+f"(d[54]), "+f"(d[55]), "+f"(d[56]), "+f"(d[57]), "+f"(d[58]), "+f"(d[59]), "+f"(d[60]), "+f"(d[61]), "+f"(d[62]), "+f"(d[63])
    : "r"(a0), "r"(a1), "r"(a2), "r"(a3), "r"(blo));
}
template<> __device__ __forceinline__ void wgmma_rs_hi<96>(float (&d)[64], uint32_t a0, uint32_t a1, uint32_t a2, uint32_t a3, uint32_t blo){
  asm volatile("{\n.reg .b64 db;\nmov.b64 db, {%52,8};\nwgmma.mma_async.sync.aligned.m64n96k16.f32.bf16.bf16 {%0, %1, %2, %3, %4, %5, %6, %7, %8, %9, %10, %11, %12, %13, %14, %15, %16, %17, %18, %19, %20, %21, %22, %23, %24, %25, %26, %27, %28, %29, %30, %31, %32, %33, %34, %35, %36, %37, %38, %39, %40, %41, %42, %43, %44, %45, %46, %47}, {%48,%49,%50,%51}, db, 1, 1, 1, 0;\n}\n"
    : "+f"(d[16]), "+f"(d[17]), "+f"(d[18]), "+f"(d[19]), "+f"(d[20]), "+f"(d[21]), "+f"(d[22]), "+f"(d[23]), "+f"(d[24]), "+f"(d[25]), "+f"(d[26]), "+f"(d[27]), "+f"(d[28]), "+f"(d[29]), "+f"(d[30]), "+f"(d[31]), "+f"(d[32]), "+f"(d[33]), "+f"(d[34]), "+f"(d[35]), "+f"(d[36]), "+f"(d[37]), "+f"(d[38]), "+f"(d[39]), "+f"(d[40]), "+f"(d[41]), "+f"(d[42]), "+f"(d[43]), "+f"(d[44]), "+f"(d[45]), "+f"(d[46]), "+f"(d[47]), "+f"(d[48]), "+f"(d[49]), "+f"(d[50]), "+f"(d[51]), "+f"(d[52]), "+f"(d[53]), "+f"(d[54]), "+f"(d[55]), "+f"(d[56]), "+f"(d[57]), "+f"(d[58]), "+f"(d[59]), "+f"(d[60]), "+f"(d[61]), "+f"(d[62]), "+f"(d[63])
    : "r"(a0), "r"(a1), "r"(a2), "r"(a3), "r"(blo));
}
template<> __device__ __forceinline__ void wgmma_rs_hi<112>(float (&d)[64], uint32_t a0, uint32_t a1, uint32_t a2, uint32_t a3, uint32_t blo){
  asm volatile("{\n.reg .b64 db;\nmov.b64 db, {%60,8};\nwgmma.mma_async.sync.aligned.m64n112k16.f32.bf16.bf16 {%0, %1, %2, %3, %4, %5, %6, %7, %8, %9, %10, %11, %12, %13, %14, %15, %16, %17, %18, %19, %20, %21, %22, %23, %24, %25, %26, %27, %28, %29, %30, %31, %32, %33, %34, %35, %36, %37, %38, %39, %40, %41, %42, %43, %44, %45, %46, %47, %48, %49, %50, %51, %52, %53, %54, %55}, {%56,%57,%58,%59}, db, 1, 1, 1, 0;\n}\n"
    : "+f"(d[8]), "+f"(d[9]), "+f"(d[10]), "+f"(d[11]), "+f"(d[12]), "+f"(d[13]), "+f"(d[14]), "+f"(d[15]), "+f"(d[16]), "+f"(d[17]), "+f"(d[18]), "+f"(d[19]), "+f"(d[20]), "+f"(d[21]), "+f"(d[22]), "+f"(d[23]), "+f"(d[24]), "+f"(d[25]), "+f"(d[26]), "+f"(d[27]), "+f"(d[28]), "+f"(d[29]), "+f"(d[30]), "+f"(d[31]), "+f"(d[32]), "+f"(d[33]), "+f"(d[34]), "+f"(d[35]), "+f"(d[36]), "+f"(d[37]), "+f"(d[38]), "+f"(d[39]), "+f"(d[40]), "+f"(d[41]), "+f"(d[42]), "+f"(d[43]), "+f"(d[44]), "+f"(d[45]), "+f"(d[46]), "+f"(d[47]), "+f"(d[48]), "+f"(d[49]), "+f"(d[50]), "+f"(d[51]), "+f"(d[52]), "+f"(d[53]), "+f"(d[54]), "+f"(d[55]), "+f"(d[56]), "+f"(d[57]), "+f"(d[58]), "+f"(d[59]), "+f"(d[60]), "+f"(d[61]), "+f"(d[62]), "+f"(d[63])
    : "r"(a0), "r"(a1), "r"(a2), "r"(a3), "r"(blo));
}
template<> __device__ __forceinline__ void wgmma_rs_hi<128>(float (&d)[64], uint32_t a0, uint32_t a1, uint32_t a2, uint32_t a3, uint32_t blo){
  asm volatile("{\n.reg .b64 db;\nmov.b64 db, {%68,8};\nwgmma.mma_async.sync.aligned.m64n128k16.f32.bf16.bf16 {%0, %1, %2, %3, %4, %5, %6, %7, %8, %9, %10, %11, %12, %13, %14, %15, %16, %17, %18, %19, %20, %21, %22, %23, %24, %25, %26, %27, %28, %29, %30, %31, %32, %33, %34, %35, %36, %37, %38, %39, %40, %41, %42, %43, %44, %45, %46, %47, %48, %49, %50, %51, %52, %53, %54, %55, %56, %57, %58, %59, %60, %61, %62, %63}, {%64,%65,%66,%67}, db, 1, 1, 1, 0;\n}\n"
    : "+f"(d[0]), "+f"(d[1]), "+f"(d[2]), "+f"(d[3]), "+f"(d[4]), "+f"(d[5]), "+f"(d[6]), "+f"(d[7]), "+f"(d[8]), "+f"(d[9]), "+f"(d[10]), "+f"(d[11]), "+f"(d[12]), "+f"(d[13]), "+f"(d[14]), "+f"(d[15]), "+f"(d[16]), "+f"(d[17]), "+f"(d[18]), "+f"(d[19]), "+f"(d[20]), "+f"(d[21]), "+f"(d[22]), "+f"(d[23]), "+f"(d[24]), "+f"(d[25]), "+f"(d[26]), "+f"(d[27]), "+f"(d[28]), "+f"(d[29]), "+f"(d[30]), "+f"(d[31]), "+f"(d[32]), "+f"(d[33]), "+f"(d[34]), "+f"(d[35]), "+f"(d[36]), "+f"(d[37]), "+f"(d[38]), "+f"(d[39]), "+f"(d[40]), "+f"(d[41]), "+f"(d[42]), "+f"(d[43]), "+f"(d[44]), "+f"(d[45]), "+f"(d[46]), "+f"(d[47]), "+f"(d[48]), "+f"(d[49]), "+f"(d[50]), "+f"(d[51]), "+f"(d[52]), "+f"(d[53]), "+f"(d[54]), "+f"(d[55]), "+f"(d[56]), "+f"(d[57]), "+f"(d[58]), "+f"(d[59]), "+f"(d[60]), "+f"(d[61]), "+f"(d[62]), "+f"(d[63])
    : "r"(a0), "r"(a1), "r"(a2), "r"(a3), "r"(blo));
}

struct CvCtx {
  uint32_t koff, zero, so[3];
  int srcA, srcB;
  bool wrapA, s3, kodd;
};
struct CvPipe { uint32_t Ap, Ep, keep, send; };
template <int LO> __device__ __forceinline__ void cv_copy(float (&acc)[64]) {
#pragma unroll
  for (int i = LO; i < 64; i++) { float t; asm volatile("mov.b32 %0, %1;" : "=f"(t) : "f"(acc[i]) : "memory"); acc[i] = t; }
}
template <int G> __device__ __forceinline__ void cv_raw(uint32_t (&A)[4][4], uint32_t kaddr) {
#pragma unroll
  for (int i = 0; i < 4; i++) {
    const uint32_t a = kaddr + (4 * G + i) * 128;
    A[i][0] = lds32(a); A[i][1] = lds32(a + 4); A[i][3] = lds32(a + 8);
  }
}
__device__ __forceinline__ void cv_form(uint32_t (&A)[4][4], uint32_t sel) {
#pragma unroll
  for (int i = 0; i < 4; i++) {
    asm volatile("prmt.b32 %0, %0, %1, %2;" : "+r"(A[i][0]) : "r"(A[i][1]), "r"(sel));
    asm volatile("prmt.b32 %0, %1, %2, %3;" : "=r"(A[i][2]) : "r"(A[i][1]), "r"(A[i][3]), "r"(sel));
  }
}
#define CVV 2
template <int G> __device__ __forceinline__ void cv_step(float (&acc)[64], uint32_t (&A)[4][4], CvPipe& s, const CvCtx& c, uint32_t cb, uint32_t stg) {
  constexpr int JA = G - 1, JB = G - 2, NH = CVV == 1 ? 4 : (CVV == 3 ? 2 : 1);
  const uint32_t db0 = desc_lo(cb + CV_U + 192, CV_PL);
  uint32_t B[4][4];
  uint32_t ra[2], rb;
  if constexpr (G < 8) {
    wgmma_fence();
#pragma unroll
    for (int i = 0; i < NH; i++) wgmma_rs_hi<128 - 16 * (G & 7)>(acc, A[i][0], A[i][1], A[i][2], A[i][3], db0 - 4 * i);
    wgmma_commit();
    __syncwarp();
  }
  if constexpr (JA >= 0 && JA < 8) {
    const uint32_t p0 = pack_bf16(acc[8 * JA + 1], acc[8 * JA + 3]), p1 = pack_bf16(acc[8 * JA + 5], acc[8 * JA + 7]);
    ra[0] = __shfl_sync(0xffffffffu, c.wrapA ? s.Ap : p0, c.srcA);
    ra[1] = __shfl_sync(0xffffffffu, c.wrapA ? p0 : p1, c.srcA);
    s.Ap = p1;
  }
  if constexpr (JB >= 0) rb = __shfl_sync(0xffffffffu, s.send, c.srcB);
  if constexpr (G < 7) cv_raw<G + 1>(B, cb + c.koff);
  uint32_t z = 0;
  if constexpr (G < 8 && NH < 4) {
    __syncwarp();
    wgmma_fence();
#pragma unroll
    for (int i = NH; i < 4; i++) wgmma_rs_hi<128 - 16 * (G & 7)>(acc, A[i][0], A[i][1], A[i][2], A[i][3], db0 - 4 * i);
    wgmma_commit();
    asm volatile("mov.u32 %0, %%clock;" : "=r"(z)::"memory");
    z &= c.zero;
  }
  if constexpr (G < 7) cv_form(B, 0x5432u | z);
  if constexpr (JB >= 0) sts32(stg + ((c.so[JB / 3] >> (10 * (JB % 3))) & 0xffc), hadd2(rb | z, s.keep));
  if constexpr (JA >= 0 && JA < 8) {
    const uint32_t sh = 16 | z, mk = 0xffff0000u | z;
    const uint32_t ev = pack_bf16(acc[8 * JA] + __uint_as_float(ra[0] << sh), acc[8 * JA + 2] + __uint_as_float(ra[0] & mk));
    const uint32_t od = pack_bf16(acc[8 * JA + 4] + __uint_as_float(ra[1] << sh), acc[8 * JA + 6] + __uint_as_float(ra[1] & mk));
    s.send = c.kodd ? ev : (c.s3 ? s.Ep : od);
    s.keep = c.kodd ? od : ev;
    s.Ep = od;
  }
  if constexpr (G < 8) { __syncwarp(); wgmma_wait<0>(); cv_copy<8 * (G & 7)>(acc); }
  if constexpr (G < 9) cv_step<G + 1>(acc, B, s, c, cb, stg);
}
__device__ __forceinline__ uint32_t cv_stage(int slot) { return sb + (slot < 4 ? 40960 + slot * 4096 : CV_OFF + CV_K); }
__device__ __forceinline__ void cv_setup(CvCtx& c) {
  const int tid = tid_opaque() & 127, w = tid >> 5, lane = tid & 31, r = lane >> 2, q = lane & 3;
  const int i0 = (r >> 1) & 1, i1 = r >> 2;
  c.koff = CV_K - 32 + 4 * (8 * (r >> 1) + 2 * w + (r & 1) + 2 * q);
  c.srcA = i0 ? lane - 8 : lane + 8 - q + ((q + 3) & 3);
  c.wrapA = i0 && q == 3;
  c.srcB = i1 == 0 ? (lane - q + 16 + ((q + 3) & 3)) : (lane - q - 16 + ((q + 1) & 3));
  c.s3 = (i1 == 1 && q == 3); c.kodd = (i1 == 1 && q < 3);
  c.zero = lds32(sb + EP_OFF + 24);
#pragma unroll
  for (int i = 0; i < 3; i++) c.so[i] = lds32(sb + SO_OFF + 512 * i + 4 * tid);
}
__device__ __forceinline__ void cv_table() {
  const int tid = tid_opaque() & 127, r = (tid & 31) >> 2, q = tid & 3;
  int t = 16 * (2 * (r < 4 ? q : 4 + ((q + 1) & 3)) + ((r >> 1) & 1)) + 4 * (tid >> 5) + 2 * (r & 1);
#pragma unroll 1
  for (int i = 0; i < 3; i++) {
    uint32_t v = 0;
#pragma unroll 1
    for (int x = 0; x < 3; x++, t += 256) {
      const int T = t / 160, tl = t - T * 160;
      const int qq = (T >= NT1 - 1) ? (tl >> 5) : (tl / 40);
      int ck = 20 * T + ((tl - qq * ((T >= NT1 - 1) ? 32 : 40)) >> 1);
      ck ^= (ck >> 2) & 6;
      v |= (uint32_t)((ck * 4 + qq) & 1023) << (10 * x + 2);
    }
    sts32(sb + SO_OFF + 512 * i + 4 * tid, v);
  }
}
__device__ __forceinline__ void conv_channel(int slot, const CvCtx& c) {
  const uint32_t cb = sb + CV_OFF + slot * CV_B;
  float acc[64];
  CvPipe s;
  s.Ap = s.Ep = 0u;
  uint32_t A[4][4];
#pragma unroll
  for (int i = 0; i < 64; i++) acc[i] = 0.f;
  if (slot == 4) mbar_wait(bars + 8 * B_CVDONE);
  mbar_wait(bars + 8 * (B_CVFULL + slot));
  cv_raw<0>(A, cb + c.koff);
  {
    const uint32_t w0 = lds32(cb + CV_K);
    const uint32_t wp = __byte_perm(pack_bf16(bf_lo(w0) + __uint_as_float(lds32(sb + EP_OFF + 4 * slot)), 0.f), w0, 0x7610);
    if (c.koff == CV_K) A[0][0] = wp;
    if (c.koff == CV_K - 4) A[0][1] = wp;
    if (c.koff == CV_K - 8) A[0][3] = wp;
  }
  cv_form(A, 0x5432u);
  cv_copy<0>(acc);
  cv_step<0>(acc, A, s, c, cb, cv_stage(slot));
  fence_async_smem();
  mbar_arrive(bars + 8 * (B_CVDONE + slot));
}

__device__ __forceinline__ void kv_issue(const Params& p, int c, int m2, int dg) {
  const uint32_t fb = bars + 8 * (B_KV + c);
  mbar_expect_tx(fb, KV_PIECE);
  tma3(sb + KS_OFF + c * KV_PIECE, &p.mK, 160 * dg + 32 * c, 64 * m2 - 3, 0, fb);
  tma3(sb + KS_OFF + c * KV_PIECE + 4864, &p.mV, 160 * dg + 32 * c, 64 * m2 - 1, 0, fb);
}
__device__ __forceinline__ void kv_tile(int m, int c, int y, uint32_t (&o)[4][4]) {
  const int lane = tid_opaque() & 31, tg = lane & 3, pr = 8 * (y ^ (tg >> 1)) + (lane >> 2);
  const uint32_t pb = sb + KS_OFF + c * KV_PIECE + 4 * pr;
  const uint32_t ka = pb + tg * 1216, va = pb + 4864 + tg * 1088 + 64;
  const uint32_t kh = (m == 0 && tg > 0) ? ka - 192 : ka;
  uint32_t kk[19], u[16];
  const float4 t = lds128f(sb + TAP_OFF + 256 * c + 16 * pr);
#pragma unroll
  for (int i = 0; i < 19; i++) { kk[i] = lds32((i < 3 ? kh : ka) + i * 64); if (i >= 3) u[i - 3] = lds32(va + (i - 3) * 64); }
  const uint32_t dst = sb + KS_OFF + c * KV_PIECE + pr * 64 + tg * 16;
  if (y) {
    __syncwarp();
#pragma unroll
    for (int x = 0; x < 4; x++) sts128((dst ^ 512) + x * 1024, make_uint4(o[x][0], o[x][1], o[x][2], o[x][3]));
  }
  const uint32_t w0 = __byte_perm(__float_as_uint(t.x), __float_as_uint(t.z), 0x5410), w1 = __byte_perm(__float_as_uint(t.x), __float_as_uint(t.z), 0x7632);
  const uint32_t w2 = __byte_perm(__float_as_uint(t.y), __float_as_uint(t.w), 0x5410), w3 = __byte_perm(__float_as_uint(t.y), __float_as_uint(t.w), 0x7632);
#pragma unroll
  for (int i = 0; i < 16; i++) {
    uint32_t a = hmul2(kk[i], w3);
    a = hadd2(a, hmul2(kk[i + 1], w2)); a = hadd2(a, hmul2(kk[i + 2], w1)); a = hadd2(a, hmul2(kk[i + 3], w0));
    u[i] = hmul2(a, u[i]);
  }
#pragma unroll
  for (int x = 0; x < 4; x++) {
#pragma unroll
    for (int qq = 0; qq < 4; qq++) o[x][qq] = __byte_perm(u[15 - 4 * qq - (x & 2)], u[14 - 4 * qq - (x & 2)], (x & 1) ? 0x7632 : 0x5410);
    if (y) sts128(dst + x * 1024, make_uint4(o[x][0], o[x][1], o[x][2], o[x][3]));
  }
}
__device__ __forceinline__ void ln_finish(float s1, float s2, float& mean, float& rstd) {
  mean = s1 * (1.f / 640.f);
  const float v = fmaxf(fmaf(-mean, mean, s2 * (1.f / 640.f)), 0.f) + 1e-5f;
  asm("rsqrt.approx.ftz.f32 %0, %1;" : "=f"(rstd) : "f"(v));
}
__device__ __forceinline__ void stat_table(int T1, unsigned want, int l, int g, const uint4* x0, const uint4* x1, float (&xa)[2], float (&xb)[2]) {
  const int n = 32 * g + (tid_opaque() & 31);
  const uint4* rp = &g_stats[8 * l * SEQ + min(160 * T1 + n, SEQ - 1)];
  float a[4], b[4];
  uint32_t it = 0;
  while (true) {
    bool ok = true;
#pragma unroll
    for (int i = 0; i < 4; i++) ok &= (rec_ld(rp + SEQ * i, a[i], b[i]) == want);
    ok &= rec_ld(x0, xa[0], xb[0]) == want;
    ok &= rec_ld(x1, xa[1], xb[1]) == want;
    if (__all_sync(0xffffffffu, ok)) break;
    trap_if(++it > SPIN_LIMIT);
  }
  float m, rs;
  ln_finish((a[0] + a[1]) + (a[2] + a[3]), (b[0] + b[1]) + (b[2] + b[3]), m, rs);
  sts64f(sb + STAB_OFF + n * 8, rs, -m * rs);
}
__device__ __forceinline__ void stats_reduce(float (&a)[2], float (&b)[2], float (&mean)[2], float (&rstd)[2]) {
#pragma unroll
  for (int o = 1; o < 4; o <<= 1)
#pragma unroll
    for (int h = 0; h < 2; h++) { a[h] += __shfl_xor_sync(0xffffffffu, a[h], o); b[h] += __shfl_xor_sync(0xffffffffu, b[h], o); }
#pragma unroll
  for (int h = 0; h < 2; h++) ln_finish(a[h], b[h], mean[h], rstd[h]);
}

template <bool FIRST>
__device__ __forceinline__ void stats_publish(int which, int n0, int dg, unsigned tag, const float (&acc)[80]) {
  const int q = tid_opaque() & 3, h = q & 1;
  float s1[2] = {0.f, 0.f}, s2[2] = {0.f, 0.f}, t1[2] = {0.f, 0.f}, t2[2] = {0.f, 0.f};
#pragma unroll
  for (int j = 0; j < 20; j++)
#pragma unroll
    for (int y = 0; y < 2; y++) {
      const float a = acc[4 * j + 2 * y], b = acc[4 * j + 2 * y + 1];
      s1[y] += a; t1[y] += b; s2[y] = fmaf(a, a, s2[y]); t2[y] = fmaf(b, b, t2[y]);
    }
#pragma unroll
  for (int y = 0; y < 2; y++) { s1[y] += t1[y]; s2[y] += t2[y]; }
  float a = (h ? s1[1] : s1[0]) + __shfl_xor_sync(0xffffffffu, h ? s1[0] : s1[1], 1);
  float b = (h ? s2[1] : s2[0]) + __shfl_xor_sync(0xffffffffu, h ? s2[0] : s2[1], 1);
  a += __shfl_xor_sync(0xffffffffu, a, 2);
  b += __shfl_xor_sync(0xffffffffu, b, 2);
  if (FIRST) {
    rec_st(&g_stats[((q >> 1) * 4 + dg) * SEQ + n0 + 8 * h], a, b, q < 2 ? tag : tag - 1);
    rec_st(&g_stats[((q >> 1) * 4 + 8 + dg) * SEQ + n0 + 8 * h], a, b, tag - 1);
  } else if (q < 2) rec_st(&g_stats[(which * 4 + dg) * SEQ + n0 + 8 * h], a, b, tag);
}
__device__ __forceinline__ void stats_get(int which, int n0, unsigned tag, float (&mean)[2], float (&rstd)[2]) {
  const uint4* p0 = &g_stats[(which * 4 + (tid_opaque() & 3)) * SEQ + n0];
  float a[2], b[2];
  uint32_t it = 0;
  while (true) {
    const unsigned t0 = rec_ld(p0, a[0], b[0]), t1 = rec_ld(p0 + 8, a[1], b[1]);
    if (__all_sync(0xffffffffu, t0 == tag && t1 == tag)) break;
    trap_if(++it > SPIN_LIMIT);
  }
  stats_reduce(a, b, mean, rstd);
}
__device__ __forceinline__ void x0_load(float (&acc)[80]) {
  const int t = tid_opaque() & 127;
  const uint32_t xa = sb + XT_OFF + (16 * (t >> 5) + ((t & 31) >> 2)) * 320 + 8 * (t & 3);
  mbar_wait(bars + 8 * B_XT);
#pragma unroll
  for (int h = 0; h < 2; h++)
#pragma unroll
    for (int J = 0; J < 10; J++) {
      const float2 v = lds64f(xa + h * 2560 + 32 * J);
      const uint32_t x = __float_as_uint(v.x), y = __float_as_uint(v.y);
      acc[8 * J + 2 * h] = bf_lo(x); acc[8 * J + 2 * h + 1] = bf_hi(x);
      acc[8 * J + 4 + 2 * h] = bf_lo(y); acc[8 * J + 4 + 2 * h + 1] = bf_hi(y);
    }
}

template <bool FROM_X0>
__device__ __forceinline__ void dskip_init(float (&acc)[80], const float (&mean)[2], const float (&rstd)[2]) {
  const int t = tid_opaque() & 127;
  const uint32_t xa = sb + XT_OFF + (16 * (t >> 5) + ((t & 31) >> 2)) * 320 + 8 * (t & 3), da = sb + DTAB_OFF + 8 * (t & 3);
  float2 dw[10], xv[10][2];
#pragma unroll
  for (int J = 0; J < 2; J++) { dw[J] = lds64f(da + 32 * J); if (FROM_X0) { xv[J][0] = lds64f(xa + 32 * J); xv[J][1] = lds64f(xa + 2560 + 32 * J); } }
#pragma unroll
  for (int J = 0; J < 10; J++) {
    if (J + 2 < 10) { dw[J + 2] = lds64f(da + 32 * (J + 2)); if (FROM_X0) { xv[J + 2][0] = lds64f(xa + 32 * (J + 2)); xv[J + 2][1] = lds64f(xa + 2560 + 32 * (J + 2)); } }
#pragma unroll
    for (int x = 0; x < 8; x++) {
      const int h = (x >> 1) & 1;
      const uint32_t dwd = __float_as_uint(x < 4 ? dw[J].x : dw[J].y);
      const float tt = fmaf(rstd[h], (x & 1) ? bf_hi(dwd) : bf_lo(dwd), 1.f);
      float a = acc[8 * J + x];
      if (FROM_X0) { const uint32_t xw = __float_as_uint(x < 4 ? xv[J][h].x : xv[J][h].y); a = (x & 1) ? bf_hi(xw) : bf_lo(xw); }
      acc[8 * J + x] = FROM_X0 ? (a - mean[h]) * tt : fmaf(a, tt, -mean[h] * tt);
    }
  }
}

__global__ void __launch_bounds__(512, 1) fused_kernel(const __grid_constant__ Params p) {
  extern __shared__ __align__(1024) uint8_t smem_raw[];
  const int tid = threadIdx.x, lane = tid & 31;
  const int wid = __shfl_sync(0xffffffffu, tid >> 5, 0), wg = wid >> 2;
  unsigned smid; asm volatile("mov.u32 %0, %%smid;" : "=r"(smid));
  const int role = p.role[min(smid, 131u)];
  if (wid == 12) {
    const bool el = elect_one();
    if (el) {
      asm volatile("prefetch.tensormap [%0];" ::"l"(&p.mB) : "memory");
      asm volatile("prefetch.tensormap [%0];" ::"l"((role & 15) == NT1 - 1 ? &p.mXl : &p.mX) : "memory");
#pragma unroll
      for (int k = 0; k < S1; k++) mbar_init(bars + 8 * (B_G1FULL + k), 1);
#pragma unroll
      for (int k = 0; k < 6; k++) mbar_init(bars + 8 * (B_XT + k), 1);
      asm volatile("fence.mbarrier_init.release.cluster;" ::: "memory");
    }
    if (role >= 0) {
      __syncwarp();
      asm volatile("bar.arrive 5, 288;" ::: "memory");
      const Role R = unpack_role(role);
      if (elect_one()) {
        TS(45);
#pragma unroll 1
        for (int k = 0; k < S1; k++) {
          const uint32_t fb = bars + 8 * (B_G1FULL + k);
          mbar_expect_tx(fb, G1_STAGE);
          tma4(sb + k * G1_STAGE + G1_XOFF, R.last ? &p.mXl : &p.mX, 64 * k, 0, 0, R.last ? 0 : 80 * R.T1, fb);
          tma5(sb + k * G1_STAGE, &p.mB, 64 * k, 0, 0, 4 * R.side, 2 * R.GP, fb);
          if (PFD) asm volatile("prefetch.tensormap [%0];" ::"l"(&p.mK + k) : "memory");
        }
        if (R.has2) {
          mbar_expect_tx(bars + 8 * B_XT, 20480);
#pragma unroll 1
          for (int h = 0; h < 2; h++) {
            const int ng = 8 * R.m2 + 4 * h, T = ng / 20;
            tma4(sb + XT_OFF + h * 10240, T == NT1 - 1 ? &p.mXtl : &p.mXt, 160 * R.dg, 0, 0, T == NT1 - 1 ? ng - 240 : ng + 60 * T, bars + 8 * B_XT);
          }
#pragma unroll 1
          for (int c = 0; c < KV0; c++) kv_issue(p, c, R.m2, R.dg);
        }
        TS(44);
      }
      __syncwarp();
      bar_sync(6, 64);
    }
  }
  trap_if(smid >= 132 || smem_u32(smem_raw) != sb);
  if (role < 0) {
    if (wid == 0) {
      const unsigned tag = ld_rlx(g_epoch);
      uint32_t it = 0;
      while (!__all_sync(0xffffffffu, (int)(ld_rlx(&g_hcnt[(lane & 7) * 32]) - 40 * tag) >= 0)) { __nanosleep(500); trap_if(++it > SPIN_LIMIT); }
    }
    return;
  }
  float mean0[2] = {0.f, 0.f}, rstd0[2] = {0.f, 0.f};
  if (wg == 2 || wid == 14) {
    ROLE(role)
    const int c = wid == 14 ? 4 : wid - 8;
    const unsigned tag = ld_rlx(g_epoch);
    if (has2) {
      uint2 bv[2][5];
#pragma unroll
      for (int x = 0; x < 2; x++)
#pragma unroll
        for (int i = 0; i < 5; i++) bv[x][i] = ldv64((const uint2*)((x ? p.bim : p.bre) + (cch0 + 32 * c) * DM) + lane + 32 * i);
      float sv[2];
#pragma unroll
      for (int x = 0; x < 2; x++) {
        float a = 0.f;
#pragma unroll
        for (int i = 0; i < 5; i++) a += (bf_lo(bv[x][i].x) + bf_hi(bv[x][i].x)) + (bf_lo(bv[x][i].y) + bf_hi(bv[x][i].y));
        sv[x] = a;
      }
#pragma unroll
      for (int o = 16; o > 0; o >>= 1) { sv[0] += __shfl_xor_sync(0xffffffffu, sv[0], o); sv[1] += __shfl_xor_sync(0xffffffffu, sv[1], o); }
      if (lane < 2) rec_st(&g_sB[(cch0 + 32 * c) * 2 + lane], sv[0], sv[1], tag);
      if (tid == 256) TS(47);
      __syncwarp();
      bar_sync(8, 192);
      if (wg == 2) {
        float xs[80];
        x0_load(xs);
        stats_publish<true>(0, 64 * m2 + 16 * c + (lane >> 2), dg, tag, xs);
        if (tid == 256) TS(31);
      }
      mbar_wait(bars + 8 * B_EP);
      mbar_wait(bars + 8 * (B_KV + c));
      mbar_wait(bars + 8 * (B_G1DONE + PAUSE_K - 1));
      if (tid == 448) TS(52);
      uint32_t o[4][4] = {};
#pragma unroll 1
      for (int y = 0; y < 2; y++) kv_tile(m2, c, y, o);
      fence_async_smem();
      __syncwarp();
      if (lane == 0) {
        mbar_arrive(bars + 8 * B_PREP);
        bulk_s2g(g_kv + (dg * 32 + m2) * 20480 + c * 4096, sb + KS_OFF + c * KV_PIECE, 4096);
        asm volatile("cp.async.bulk.commit_group;" ::: "memory");
      }
      __syncwarp();
      if (tid == 448) TS(51);
    } else bar_sync(8, 192);
    {
      const uint4* x0 = wg == 2 ? &g_stats[(lane & 3) * SEQ + (has2 ? 64 * m2 : 0) + 16 * c + (lane >> 2)] : &g_sB[(128 * GP + 32 * side + lane) * 2];
      float xa[2], xb[2];
      stat_table(T1, tag, 0, c, x0, x0 + (wg == 2 ? 8 : 128), xa, xb);
      if (wg == 2) stats_reduce(xa, xb, mean0, rstd0);
      else {
#pragma unroll
        for (int i = 0; i < 2; i++) sts64f(sb + CTAB_OFF + (32 * i + lane) * 24 + 16, p.swap ? xb[i] : xa[i], p.swap ? xa[i] : xb[i]);
      }
      mbar_arrive(bars + 8 * B_STAB);
      if (tid == 448) TS(26);
    }
    if (has2) {
      if (lane == 0) {
        asm volatile("cp.async.bulk.wait_group 0;" ::: "memory");
        fence_async_global();
        mbar_arrive(bars + 8 * B_PREP2);
      }
      __syncwarp();
    }
  } else if (wid == 15) {
    ROLE(role)
    const int ch = 128 * GP + 32 * side + lane;
    uint32_t r0 = ldv16(p.lre + ch), r1 = ldv16(p.lim + ch), r2 = ldv16(p.logdt + ch);
    const uint32_t r3 = ldv16(p.lre + ch + 64), r4 = ldv16(p.lim + ch + 64), r5 = ldv16(p.logdt + ch + 64);
#pragma unroll 1
    for (int i = 0; i < 2; i++) {
      const float lr = bf_lo(r0), li = bf_lo(r1);
      const float dt = __bfloat162float(__float2bfloat16_rn(expf(bf_lo(r2))));
      const float mag = expf(dt * lr);
      float sn, cs; sincospif(dt * li * 0.31830988618379067f, &sn, &cs);
      const float ar = mag * cs, ai = mag * sn;
      const float inv = 2.f / (lr * lr + li * li);
      const uint32_t ad = sb + CTAB_OFF + (32 * i + lane) * 24;
      sts64f(ad, ar, ai);
      sts64f(ad + 8, ((ar - 1.f) * lr + ai * li) * inv, (ai * lr - (ar - 1.f) * li) * inv);
      r0 = r3; r1 = r4; r2 = r5;
    }
    if (lane == 0) TS(46);
    __syncwarp();
    bar_sync(7, 64);
    mbar_arrive(bars + 8 * B_CTAB);
  } else if (wid == 13) {
    ROLE(role)
    uint4 tv[3];
    const uint32_t e0 = ld_rlx(g_epoch);
    const uint32_t e1 = ldv16(p.ssmD + min(cch0 + 32 * lane, 639));
    const uint4 dv = ldv128((const uint4*)(p.dskip + 160 * dg) + min(lane, 19));
#pragma unroll
    for (int i = 0; i < 3; i++) tv[i] = ldv128((const uint4*)(p.shiftk + 640 * dg) + min(lane + 32 * i, 79));
    sts128(sb + DTAB_OFF + 16 * min(lane, 19), dv);
#pragma unroll
    for (int i = 0; i < 3; i++) sts128(sb + TAP_OFF + 16 * min(lane + 32 * i, 79), tv[i]);
    if (lane < 7) sts32(sb + EP_OFF + 4 * lane, lane < 5 ? e1 << 16 : (lane == 5 ? e0 : 0u));
    __syncwarp();
    bar_sync(9, 64);
    mbar_arrive(bars + 8 * B_CTAB);
    if (lane == 0) { mbar_arrive(bars + 8 * B_EP); TS(53); }
    if (has2) {
      mbar_wait(bars + 8 * B_PREP2);
      if (lane < 4) red_rel(&g_kvcnt[(dg * 4 + lane) * 32]);
      __syncwarp();
      if (lane == 0) { mbar_arrive(bars + 8 * B_PUB); TS(30); }
    }
  } else if (wid != 12) {
    if (elect_one()) {
      if (wid < 7) {
        const int b0 = wid < 4 ? 4 + 19 * wid : 85 + 21 * (wid - 4), cnt = wid < 4 ? 2 : 1;
#pragma unroll
        for (int i = 0; i < 21; i++) mbar_init(bars + 8 * (b0 + i), cnt);
      } else {
#pragma unroll
        for (int i = 0; i < 12; i++) mbar_init(bars + 8 * (B_CVDONE + i), (i == 5 || i == 6) ? 160 : 128);
        mbar_init(bars + 8 * B_CTAB, 192); mbar_init(bars + 8 * B_PREP, 5); mbar_init(bars + 8 * B_PREP2, 5);
      }
      asm volatile("fence.mbarrier_init.release.cluster;" ::: "memory");
    }
    __syncwarp();
    bar_sync(5, 288);
    if (wid == 2) asm volatile("bar.arrive 8, 192;\nbar.arrive 6, 64;\nbar.arrive 9, 64;\nbar.arrive 7, 64;" ::: "memory");
    if (tid == 128) TS(0);
    if (wg == 1) { cv_table(); mbar_arrive(bars + 8 * B_CTAB); }
  }

  if (wid == 12) {
    ROLE(role)
    uint32_t dst = sb;
#pragma unroll 1
    for (int k = S1; k < 10; k++) {
      const uint32_t fb = bars + 8 * (B_G1FULL + k);
      mbar_wait(bars + 8 * (B_G1DONE + k - S1));
      if (elect_one()) {
        mbar_expect_tx(fb, 20480);
        tma4(dst + G1_XOFF, last ? &p.mXl : &p.mX, 64 * k, 0, 0, last ? 0 : 80 * T1, fb);
        mbar_expect_tx(fb, 16384);
        tma5(dst, &p.mB, 64 * k, 0, 0, 4 * side, 2 * GP, fb);
        if (has2 && k - S1 + KV0 < 5) kv_issue(p, k - S1 + KV0, m2, dg);
      }
      dst += G1_STAGE; if (k == 2 * S1 - 1) dst = sb;
    }
  } else if (wid == 15 && (role >> 16)) {
    ROLE(role)
    mbar_wait(bars + 8 * B_PREP2);
    if (lane < 10) sts128(sb + CV_OFF + (lane >> 1) * CV_B + CV_K - 32 + 16 * (lane & 1), make_uint4(0, 0, 0, 0));
    fence_async_smem();
    __syncwarp();
    const unsigned tag = lds32(sb + EP_OFF + 20);
    if (TAPW) mbar_wait(bars + 8 * B_PUB);
    if (elect_one()) {
#pragma unroll 1
      for (int c = 0; c < 5; c++) {
        if (c == 0) asm volatile("prefetch.tensormap [%0];" ::"l"(&p.mU) : "memory");
        mbar_expect_tx(bars + 8 * (B_CVFULL + c), 4096 + 2 * CV_PL);
        bulk_g2s(sb + CV_OFF + c * CV_B + CV_K, p.ssmk + (cch0 + 32 * c) * SEQ, 4096, bars + 8 * (B_CVFULL + c));
      }
    }
    mbar_wait(bars + 8 * B_PUB);
    cnt_poll(&g_kvcnt[(dg * 4 + (m2 >> 3)) * 32], 32 * tag);
    fence_async_global();
    if (elect_one()) {
      TS(28);
#pragma unroll
      for (int c = 0; c < 5; c++)
        tma5(sb + CV_OFF + c * CV_B + CV_U, &p.mU, 0, -3, 2 * c, 16 * (m2 & 1) + (m2 >> 1), dg, bars + 8 * (B_CVFULL + c));
#pragma unroll
      for (int i = 0; i < 3; i++) asm volatile("prefetch.tensormap [%0];" ::"l"(&p.mCre + i) : "memory");
      TS(54);
    }
    __syncwarp();
  }
  {
    const int w = wid & 3;
    if (wg == 2 && !(role >> 16)) {
      float xa[2], xb[2];
      mbar_wait(bars + 8 * (B_G1FULL + 11));
      stat_table(role & 15, lds32(sb + EP_OFF + 20), 1, w, g_stats, g_stats, xa, xb);
      mbar_arrive(bars + 8 * (B_STAB + 1));
    }
#pragma unroll 1
    for (int l = 0; l < 2; l++) {
      if (wg < 2) {
        float acc[80];
#pragma unroll
        for (int i = 0; i < 80; i++) acc[i] = 0.f;
        ROLE(role)
        const int tid = tid_opaque(), r = (tid & 31) >> 2, q = tid & 3;
        const int ch = 128 * GP + 64 * wg + 32 * side + 8 * w + r;
        const uint32_t ca = sb + CTAB_OFF + (32 * wg + 8 * w + r) * 24;
        float2 lam = make_float2(0.f, 0.f), p8 = lam, p16 = lam, pL = lam, p2L = lam;
        fence_regs(acc);
        {
          const uint32_t alo0 = (l == 0 ? desc_lo(sb, 16) : desc_lo(sb + G2_WOFF, 16)) + wg * 512;
          const uint32_t blo0 = l == 0 ? desc_lo(sb + G1_XOFF, 16) : desc_lo(sb + X1_OFF, 128);
          const uint32_t bhi = l == 0 ? desc_hi(1024, 1) : desc_hi(1024, 0), xstep = l == 0 ? 2 : 16;
          const uint32_t astep = l == 0 ? G1_STAGE >> 4 : 1024, bstep = l == 0 ? G1_STAGE >> 4 : 1280, aend = alo0 + (S1 + l) * astep;
          uint32_t alo = alo0, blo = blo0;
          uint32_t fb = bars + 8 * (B_G1FULL + 10 * l);
          mbar_wait(fb);
          if (tid == 0) TS(1 + 8 * l);
#pragma unroll 1
          for (int k = 0; k < 10; k++) {
            uint32_t ok; const uint32_t nb = k < 9 ? fb + 8 : fb;
            wgmma_fence();
#pragma unroll
            for (int kk = 0; kk < 4; kk++) {
              wgmma_n160<0>(acc, alo + kk * 2, desc_hi(1024, 1), blo + kk * xstep, bhi);
              if (kk == 0) ok = mbar_test(nb);
              if (kk == STG_KK && k == 9 && tid == 0) mbar_arrive(bars + 8 * (B_STG + l));
            }
            wgmma_commit();
            alo += astep; blo += bstep;
            if (blo == desc_lo(sb + G_OFF, 128)) blo = desc_lo(sb, 128);
            if (alo == aend) { alo = alo0; blo = blo0; }
            wgmma_wait<1>();
            if (k > 0 && (tid & 127) == 0) mbar_arrive(fb + 8 * (B_G1DONE - B_G1FULL - 1));
            if (!ok) mbar_wait(nb);
            if (wg == 1 && k == (l ? 8 - STG_D : 9 - STG0)) mbar_wait(bars + 8 * (B_STG + l));
            if (k == 3) {
              mbar_wait(bars + 8 * B_CTAB);
              lam = lds64f(ca);
              if (p.swap) lam.y = -lam.y;
              const float2 p2 = cmul(lam, lam), p4 = cmul(p2, p2);
              p8 = cmul(p4, p4); p16 = cmul(p8, p8);
              pL = cmul(p16, p16);
              if (!last) pL = cmul(pL, p8);
              p2L = cmul(pL, pL);
            }
            if (k == PAUSE_K && has2) mbar_wait(bars + 8 * B_PREP);
            fb += 8;
          }
        }
        mbar_wait(bars + 8 * (B_STAB + l));
        const float2 sB = lds64f(ca + 16);
        const unsigned tag = lds32(sb + EP_OFF + 20);
        wgmma_wait<0>();
        fence_regs(acc);
        if ((tid & 127) == 0) { mbar_arrive(bars + 8 * (B_G1DONE + 10 * l + 9)); TS(wg ? 17 + l : 2 + 8 * l); }
        float2 ec[3];
#pragma unroll
        for (int jj = 0; jj < 8; jj++)
#pragma unroll
          for (int y = 0; y < 3; y++) {
            if (y == 2 && (jj & 1)) continue;
            const int j = y == 2 ? 16 + (jj >> 1) : 8 * y + jj;
            const float4 st = lds128f(sb + STAB_OFF + (8 * j + 2 * q) * 8);
            acc[4 * j + 0] = fmaf(acc[4 * j + 0], st.x, st.y * sB.x);
            acc[4 * j + 2] = fmaf(acc[4 * j + 2], st.x, st.y * sB.y);
            acc[4 * j + 1] = fmaf(acc[4 * j + 1], st.z, st.w * sB.x);
            acc[4 * j + 3] = fmaf(acc[4 * j + 3], st.z, st.w * sB.y);
            ec[y] = jj == 0 ? make_float2(acc[4 * j + 0], acc[4 * j + 2]) : cfma(lam, ec[y], make_float2(acc[4 * j + 0], acc[4 * j + 2]));
            ec[y] = cfma(lam, ec[y], make_float2(acc[4 * j + 1], acc[4 * j + 3]));
          }
        float2 e = cfma(p16, ec[0], ec[1]);
        if (!last) e = cfma(p8, e, ec[2]);
        {
          float2 v = make_float2(__shfl_up_sync(0xffffffffu, e.x, 1, 4), __shfl_up_sync(0xffffffffu, e.y, 1, 4));
          if (q >= 1) e = cfma(pL, v, e);
          v = make_float2(__shfl_up_sync(0xffffffffu, e.x, 2, 4), __shfl_up_sync(0xffffffffu, e.y, 2, 4));
          if (q >= 2) e = cfma(p2L, v, e);
        }
        if (!last && (q == 3 || (q == 2 && l == 0))) rec_st(&g_E[((q == 3 ? l : 1) * NT1 + T1) * DM + ch], e.x, e.y, q == 3 ? tag : tag - 1);
        if (tid == 0) TS(3 + 8 * l);
        float2 ex = make_float2(__shfl_up_sync(0xffffffffu, e.x, 1, 4), __shfl_up_sync(0xffffffffu, e.y, 1, 4));
        if (q == 0) ex = make_float2(0.f, 0.f);
        const float2 coef = lds64f(ca + 8), lamc = make_float2(lam.x, p.swap ? lam.y : -lam.y);
        float m00 = coef.x, m01 = -coef.y, m10 = -coef.y, m11 = -coef.x;
        if (p.swap) { m00 = -coef.y; m01 = coef.x; m10 = -coef.x; m11 = -coef.y; }
        float2 pLq, p160q, p640;
        {
          const float2 p80 = last ? cmul(p2L, p16) : p2L, p160 = cmul(p80, p80), p320 = cmul(p160, p160), one = make_float2(1.f, 0.f);
          p640 = cmul(p320, p320);
          pLq = cmul((q & 1) ? pL : one, (q & 2) ? p2L : one);
          p160q = cmul((q & 1) ? p160 : one, (q & 2) ? p320 : one);
        }
        float2 c, ev[3];
        unsigned tg[3];
        const uint4* ep = &g_E[(l * NT1 + T1 - 1 - q) * DM + ch];
#pragma unroll
        for (int j = 0; j < 20; j++) {
          if (j == CPOLL) {
#pragma unroll
            for (int i = 0; i < 3; i++) {
              ev[i] = make_float2(0.f, 0.f); tg[i] = tag;
              if (T1 - 1 - q - 4 * i >= 0) tg[i] = rec_ld(ep - 4 * i * DM, ev[i].x, ev[i].y);
            }
          }
#pragma unroll
          for (int x = 0; x < 2; x++) {
            const float b0 = acc[4 * j + x], b1 = acc[4 * j + 2 + x];
            acc[4 * j + x] = fmaf(b0, m00, b1 * m01);
            acc[4 * j + 2 + x] = fmaf(b0, m10, b1 * m11);
          }
          if (j == CPOLL - 1 || j == 19) asm volatile("" : "+f"(acc[4 * j]), "+f"(acc[4 * j + 1]), "+f"(acc[4 * j + 2]), "+f"(acc[4 * j + 3])::"memory");
        }
        {
          uint32_t it = 0;
          while (__any_sync(0xffffffffu, tg[0] != tag || tg[1] != tag || tg[2] != tag)) {
#pragma unroll
            for (int i = 0; i < 3; i++)
              if (tg[i] != tag) tg[i] = rec_ld(ep - 4 * i * DM, ev[i].x, ev[i].y);
            trap_if(++it > SPIN_LIMIT);
          }
          c = cfma(p640, cfma(p640, ev[2], ev[1]), ev[0]);
          c = cmul(c, p160q);
          c.x += __shfl_xor_sync(0xffffffffu, c.x, 1); c.y += __shfl_xor_sync(0xffffffffu, c.y, 1);
          c.x += __shfl_xor_sync(0xffffffffu, c.x, 2); c.y += __shfl_xor_sync(0xffffffffu, c.y, 2);
        }
        if (tid == 0) TS(4 + 8 * l);
        if (wg == 1 && l >= HOLD0) mbar_wait(bars + 8 * (B_REL + l));
        c = cfma(pLq, c, ex);
        float2 hh = make_float2(fmaf(c.x, m00, c.y * m01), fmaf(c.x, m10, c.y * m11));
        uint8_t* hb = g_h + (size_t)l * (32 * 20 * 8192) + (10 * wg + 2 * GP) * 8192 + (4 * side + w) * 1024 + (tid_opaque() & 31) * 4;
#pragma unroll
        for (int j4 = 0; j4 < 5; j4++) {
          const int ng = 20 * T1 + 4 * j4;
          uint8_t* hp = hb + (size_t)(ng >> 3) * 163840 + (ng & 7) * 128;
#pragma unroll
          for (int jj = 0; jj < 4; jj++) {
            const int j = 4 * j4 + jj;
            const float2 h0 = cfma(lamc, hh, make_float2(acc[4 * j + 0], acc[4 * j + 2]));
            hh = cfma(lamc, h0, make_float2(acc[4 * j + 1], acc[4 * j + 3]));
            if (j4 < 4 || !last) {
              *(uint32_t*)(hp + jj * 128) = pack_bf16(h0.x, hh.x);
              *(uint32_t*)(hp + jj * 128 + 8192) = pack_bf16(h0.y, hh.y);
            }
          }
        }
        mbar_arrive(bars + 8 * (B_HST + 2 * l + wg));
        if (tid == 0) TS(5 + 8 * l);
        if (tid == 128) TS(l ? 25 : 19);
        if (l == 0 && wid == 4) {
          mbar_wait(bars + 8 * B_HST);
          mbar_wait(bars + 8 * (B_HST + 1));
          if ((tid & 31) < 8) h_release((tid >> 2) & 1, T1, tid & 3);
          __syncwarp();
          if (tid == 128) { mbar_arrive(bars + 8 * B_REL); TS(6); }
        }
      }
      if (l == 0) {
        ROLE(role)
        if (has2) {
          CvCtx cc;
          mbar_wait(bars + 8 * B_CTAB);
          cv_setup(cc);
          mbar_wait(bars + 8 * (B_G1DONE + 9));
#pragma unroll 1
          for (int c = (wg + 2) & 3; c < 5; c += 4) conv_channel(c, cc);
          if ((tid & 127) == 0) TS(wg == 2 ? 32 : (wg == 3 ? 50 : 7 + wg));
        }
      }
      if (wg >= 2) break;
    }
    if (wg == 3) {
    ROLE(role)
    const int pw = wid & 3, gpc = 2 * min(m2 >> 3, 3) + (dg >> 1);
    mbar_wait(bars + 8 * B_EP);
    const unsigned tag = lds32(sb + EP_OFF + 20);
    if (pw == 0) {
      if (elect_one()) {
#pragma unroll 1
        for (int l = 0; l < 2; l++) {
          uint32_t dst = sb;
          if (l == 1) {
            dst = sb + G2_WOFF;
#pragma unroll 1
            for (int k = 0; k < 10; k++) {
              mbar_wait(k > 4 ? bars + 8 * (B_G1DONE + 5 + k) : (has2 ? bars + 8 * (B_G2DONE + 14 + min(k, 3)) : bars + 8 * (B_G1DONE + 9)));
              mbar_expect_tx(bars + 8 * (B_G1FULL + 10 + k), 16384);
              tma5(dst, &p.mB, 64 * k, 0, 0, 4 * side, 2 * GP, bars + 8 * (B_G1FULL + 10 + k));
              dst += 16384; if (k == 4) dst = sb + G2_WOFF;
            }
          }
          if (has2) {
            const uint32_t fb2 = bars + 8 * (B_G2FULL + 20 * l), wb2 = bars + 8 * (B_G2DONE + 20 * l - S2);
            dst = sb + G2_WOFF + (WTAIL ? 4 * l * G2_WB : 0);
            int kc = 0;
#pragma unroll 1
            for (int k = 0; k < 20; k++) {
              mbar_wait(k >= S2 ? wb2 + 8 * k : bars + 8 * (l ? B_G1DONE + (WTAIL ? (k < 3 ? 15 + k : 13 + k) : 19) : (k == 5 ? B_XFREE : (k == 6 ? B_SFREE : B_REL))));
              mbar_expect_tx(fb2 + 8 * k, G2_WB);
              tma5(dst, &p.mCre + (k & 1), kc, 0, 0, 0, 10 * dg, fb2 + 8 * k);
              kc += (k & 1) << 7; if (k == 9) kc = 64;
              dst += G2_WB; if (dst == sb + G2_WOFF + S2 * G2_WB) dst = sb + G2_WOFF;
            }
          }
        }
      }
    } else if (pw == 1) {
#pragma unroll 1
      for (int l = 0; l < 2; l++) {
        if (l == 1) {
          mbar_wait(bars + 8 * (has2 ? B_G2DONE + 19 : B_G1DONE + 9));
          if (has2) mbar_wait(bars + 8 * B_UST);
          cnt_poll(&g_ucnt[gpc * 32], 128 * tag);
          fence_async_global();
          if (elect_one()) {
            TS(20);
            const int bytes = last ? 16384 : 20480;
            const uint8_t* src = g_u + T1 * 204800;
            uint32_t dst = sb + X1_OFF;
#pragma unroll 1
            for (int k = 0; k < 10; k++) {
              if (k > 4) mbar_wait(bars + 8 * (B_G1DONE + 5 + k));
              mbar_expect_tx(bars + 8 * (B_G1FULL + 10 + k), bytes);
              bulk_g2s(dst, src, bytes, bars + 8 * (B_G1FULL + 10 + k));
              src += 20480; dst += 20480; if (dst == sb + G_OFF) dst = sb; if (k == 4) dst = sb + X1_OFF;
            }
          }
          __syncwarp();
        }
        if (has2) {
          mbar_wait(bars + 8 * (B_HST + 2 * l));
          mbar_wait(bars + 8 * (B_G1DONE + 10 * l + 9));
          cnt_poll(&g_hcnt[(l * 16 + gpc) * 32], 40 * tag);
          fence_async_global();
          if (elect_one()) {
            TS(21 + 2 * l);
            const uint32_t fb2 = bars + 8 * (B_G2FULL + 20 * l), wb2 = bars + 8 * (B_G2DONE + 20 * l - S2);
            const uint8_t* src = g_h + (l * 32 + m2) * 163840;
            uint32_t dst = sb;
#pragma unroll 1
            for (int k = 0; k < 20; k++) {
              if (k >= 5) mbar_wait(k >= S2 ? wb2 + 8 * k : bars + 8 * B_SFREE);
              if (k == 10) { mbar_wait(bars + 8 * (B_H1 + l)); fence_async_global(); }
              mbar_expect_tx(fb2 + 8 * k, G2_XB);
              bulk_g2s(dst, src, G2_XB, fb2 + 8 * k);
              src += 8192; dst += G2_XB; if (dst == sb + S2 * G2_XB) dst = sb;
            }
          }
          __syncwarp();
        }
      }
    } else if (pw == 2) {
#pragma unroll 1
      for (int l = 0; l < 2; l++) {
        if (l == 1) {
          float xa[2], xb[2];
          mbar_wait(bars + 8 * (B_G1FULL + 11));
          stat_table(T1, tag, 1, 4, g_stats, g_stats, xa, xb);
          mbar_arrive(bars + 8 * (B_STAB + 1));
        }
#pragma unroll 1
        for (int w = 0; w < 2 * l; w++) {
          mbar_wait(bars + 8 * (B_HST + 2 + w));
          if (lane < 4) h_release(2 + w, T1, lane);
          __syncwarp();
          if (lane == 0) { if (w == 0) mbar_arrive(bars + 8 * (B_REL + 1)); TS(w ? 16 : 14); }
        }
        if (l == 0 && has2 && elect_one()) {
#pragma unroll 1
          for (int i = 0; i < 5; i++) {
            const int c = i < 3 ? i : 7 - i;
            mbar_wait(bars + 8 * (B_CVDONE + c));
            bulk_s2g(g_G + (cch0 + 32 * c) * 4096, cv_stage(c), 4096);
          }
          asm volatile("cp.async.bulk.commit_group;" ::: "memory");
          asm volatile("cp.async.bulk.wait_group.read 0;" ::: "memory");
          mbar_arrive(bars + 8 * B_SFREE);
          asm volatile("cp.async.bulk.wait_group 0;" ::: "memory");
          TS(48);
          fence_async_global();
          asm volatile("fence.acq_rel.gpu;" ::: "memory");
#pragma unroll
          for (int i = 0; i < 4; i++) red_rlx(&g_gcnt[(dg * 4 + i) * 32]);
          TS(49);
          mbar_arrive(bars + 8 * (B_GO + 1));
        }
        __syncwarp();
      }
    } else if (has2) {
      mbar_wait(bars + 8 * B_REL);
      if (elect_one()) {
        l2_prefetch(p.cre + (160 * dg + 5 * m2) * DM, 6400); l2_prefetch(p.cim + (160 * dg + 5 * m2) * DM, 6400);
      }
      mbar_wait(bars + 8 * (B_HST + 1));
      flag_poll(&g_hcnt[(8 + gpc) * 32], 40 * tag);
      if (lane == 0) { mbar_arrive(bars + 8 * B_H1); TS(22); }
      mbar_wait(bars + 8 * (B_GO + 1));
      flag_poll(&g_gcnt[(dg * 4 + (m2 >> 3)) * 32], 32 * tag);
      fence_async_global();
      if (elect_one()) {
        TS(29);
        mbar_expect_tx(bars + 8 * B_GFULL, 20480);
        tma5(sb + G_OFF, &p.mG, 64 * m2, 0, 0, 0, 10 * dg, bars + 8 * B_GFULL);
      }
      mbar_wait(bars + 8 * (B_HST + 3));
      cnt_poll(&g_hcnt[(24 + gpc) * 32], 40 * tag);
      if (lane == 0) { mbar_arrive(bars + 8 * (B_H1 + 1)); TS(24); }
    }
    } else if (wg == 2 && (role >> 16)) {
      float acc[80];
      float off[2] = {mean0[0], mean0[1]};
      const unsigned tag = lds32(sb + EP_OFF + 20);
      dskip_init<true>(acc, mean0, rstd0);
      mbar_arrive(bars + 8 * B_XFREE);
#pragma unroll 1
      for (int l = 0; l < 2; l++) {
        float mean[2], rstd[2];
        {
          uint32_t alo = desc_lo(sb, 1024), blo = desc_lo(sb + G2_WOFF, 16) + (WTAIL ? l * (G2_WB >> 2) : 0);
          uint32_t fb = bars + 8 * (B_G2FULL + 20 * l);
          fence_regs(acc);
          mbar_wait(bars + 8 * (B_CVDONE + 2));
          mbar_wait(bars + 8 * (B_CVDONE + 3));
          mbar_wait(fb);
          if (tid == 256) TS(33 + 6 * l);
#pragma unroll 1
          for (int k = 0; k < 20; k++) {
            if (l == TSL && (k & 3) == 3 && tid == 256) TS(56 + (k >> 2));
            uint32_t ok; const uint32_t nb = k < 19 ? fb + 8 : fb;
            wgmma_fence();
#pragma unroll
            for (int kk = 0; kk < 4; kk++) {
              wgmma_n160<1>(acc, alo + kk * 128, desc_hi(128, 0), blo + kk * 2, desc_hi(1024, 1));
              if (kk == 0) ok = mbar_test(nb);
            }
            wgmma_commit();
            alo += G2_XB >> 4; blo += G2_WB >> 4;
            if (alo == desc_lo(sb + S2 * G2_XB, 1024)) alo = desc_lo(sb, 1024);
            if (blo == desc_lo(sb + G_OFF, 16)) blo = desc_lo(sb + G2_WOFF, 16);
            wgmma_wait<1>();
            if (k > 0 && tid == 256) mbar_arrive(fb + 8 * (B_G2DONE - B_G2FULL - 1));
            if (!ok) mbar_wait(nb);
            fb += 8;
          }
          wgmma_wait<0>();
          fence_regs(acc);
          if (tid == 256) TS(34 + 6 * l);
          if (tid == 256) mbar_arrive(bars + 8 * (B_G2DONE + 20 * l + 19));
        }
        ROLE(role)
        const int tq = tid_opaque() & 31, n0 = 64 * m2 + 16 * w + (tq >> 2);
        stats_publish<false>(2 * l + 1, n0, dg, tag, acc);
        uint32_t gf[10][4];
        mbar_wait(bars + 8 * B_GFULL);
        const uint32_t ga = sb + G_OFF + (8 * (tq >> 4) + (tq & 7)) * 128 + (((2 * w + ((tq >> 3) & 1)) ^ ((2 * m2) & 6) ^ (tq & 7)) << 4);
#pragma unroll
        for (int J = 0; J < 2; J++) ldsm4t(gf[J], ga + J * 2048);
        if (tid == 256) TS(35 + 6 * l);
        uint8_t* dst[2][2];
#pragma unroll
        for (int h = 0; h < 2; h++) {
          if (l == 0) {
            const int ng = 8 * m2 + 2 * w + h, T = ng / 20;
            uint8_t* ub = g_u + (T * 204800 + (ng - 20 * T) * 1024 + (tq & 2) * 64 + (tq & 28) * 4 + (tq & 1) * 8 + (5 * dg >> 1) * 20480);
            dst[h][1] = ub + ((dg & 1) ? 20480 - 512 : 0);
            dst[h][0] = ub + (dg & 1) * 512;
          } else {
            dst[h][0] = dst[h][1] = (uint8_t*)(p.out + (n_to_t(n0 + 8 * h) * DM + 160 * dg + 4 * (tq & 3)));
          }
        }
        stats_get(2 * l + 1, n0, tag, mean, rstd);
        if (tid == 256) TS(36 + 6 * l);
        off[0] += mean[0]; off[1] += mean[1];
        const float ov[2] = {l ? off[0] : 0.f, l ? off[1] : 0.f};
#pragma unroll
        for (int J = 0; J < 10; J++) {
          if (J + 2 < 10) ldsm4t(gf[J + 2 < 10 ? J + 2 : 0], ga + (J + 2) * 2048);
#pragma unroll
          for (int x = 0; x < 8; x++) {
            const int h = (x >> 1) & 1;
            const uint32_t gwd = gf[J][x >> 1];
            const float t = fmaf(rstd[h], (x & 1) ? bf_hi(gwd) : bf_lo(gwd), 1.f);
            acc[8 * J + x] = fmaf(acc[8 * J + x], t, fmaf(-mean[h], t, ov[h]));
          }
#pragma unroll
          for (int h = 0; h < 2; h++) {
            if (l == 0)
              *(uint2*)(dst[h][(J >> 1) & 1] + (J >> 2) * 20480 + (J & 3) * 256) =
                  make_uint2(pack_bf16(acc[8 * J + 2 * h], acc[8 * J + 2 * h + 1]), pack_bf16(acc[8 * J + 4 + 2 * h], acc[8 * J + 5 + 2 * h]));
            else
              *(float4*)(dst[h][0] + 64 * J) = make_float4(acc[8 * J + 2 * h], acc[8 * J + 2 * h + 1], acc[8 * J + 4 + 2 * h], acc[8 * J + 5 + 2 * h]);
          }
          __syncwarp();
        }
        if (l == 0) {
          bar_sync(3, 128);
          if (tid == 288) { TS(37); mbar_arrive(bars + 8 * B_UST); }
          if (tid < 264) red_rel(&g_ucnt[(tid & 7) * 32]);
          __syncwarp();
          if (tid == 256) TS(38);
          stats_publish<false>(2, n0, dg, tag, acc);
          mbar_wait(bars + 8 * (B_G1FULL + 11));
          float xa[2], xb[2];
          const uint4* x0 = &g_stats[(8 + (tq & 3)) * SEQ + n0];
          stat_table(T1, tag, 1, w, x0, x0 + 8, xa, xb);
          mbar_arrive(bars + 8 * (B_STAB + 1));
          if (tid == 256) TS(27);
          stats_reduce(xa, xb, mean, rstd);
          off[0] += mean[0]; off[1] += mean[1];
          mbar_wait(bars + 8 * (B_HST + 2));
          dskip_init<false>(acc, mean, rstd);
        } else {
          if (tid == 256) {
            TS(43);
            if (m2 == 31 && dg == 3) asm volatile("st.relaxed.gpu.global.u32 [%0], %1;" ::"l"(g_epoch), "r"(tag + 1) : "memory");
          }
        }
      }
    }
  }
}

typedef CUresult (*EncFn)(CUtensorMap*, CUtensorMapDataType, cuuint32_t, void*, const cuuint64_t*, const cuuint64_t*,
                          const cuuint32_t*, const cuuint32_t*, CUtensorMapInterleave, CUtensorMapSwizzle,
                          CUtensorMapL2promotion, CUtensorMapFloatOOBfill);

void encode(EncFn fn, CUtensorMap* m, const void* ptr, int rank, const cuuint64_t* dims, const cuuint64_t* strides, const cuuint32_t* box,
            CUtensorMapSwizzle swz = CU_TENSOR_MAP_SWIZZLE_128B, int prom = 2) {
  cuuint32_t es[5] = {1, 1, 1, 1, 1};
  fn(m, CU_TENSOR_MAP_DATA_TYPE_BFLOAT16, rank, (void*)ptr, dims, strides, box, es, CU_TENSOR_MAP_INTERLEAVE_NONE,
     swz, (CUtensorMapL2promotion)prom, CU_TENSOR_MAP_FLOAT_OOB_FILL_NONE);
}

}

extern "C" void kernel_launch(void* const* d_in, const int* in_sizes, int n_in, void* d_out, int out_size) {
  (void)in_sizes; (void)n_in; (void)out_size;
  Params p;
  typedef const __nv_bfloat16* BP;
  p.x = (BP)d_in[0]; p.lre = (BP)d_in[1]; p.lim = (BP)d_in[2]; p.bre = (BP)d_in[3]; p.bim = (BP)d_in[4];
  p.cre = (BP)d_in[5]; p.cim = (BP)d_in[6]; p.logdt = (BP)d_in[7]; p.dskip = (BP)d_in[8];
  p.k = (BP)d_in[10]; p.v = (BP)d_in[11]; p.shiftk = (BP)d_in[12]; p.ssmk = (BP)d_in[13]; p.ssmD = (BP)d_in[14];
  p.out = (float*)d_out;
  for (int sm = 0; sm < 132; sm++) {
    const int tpc = sm >> 1, side = sm & 1;
    int gpc, gi;
    if (tpc < 32) { gpc = tpc & 7; gi = tpc >> 3; }
    else if (tpc < 60) { gpc = 1 + (tpc - 32) % 7; gi = 4 + (tpc - 32) / 7; }
    else if (tpc < 62) { gpc = tpc - 54; gi = 8; }
    else { gpc = 0; gi = tpc - 58; }
    const int pos = 8 * gpc + gi + (gpc == 7 ? 1 : 0);
    int T1, GP;
    if (pos < 52) { const int hh = pos / 26, x = pos - 26 * hh; T1 = x >> 1; GP = 2 * hh + (x & 1); }
    else { T1 = pos - 52; GP = 4; }
    const int m2 = 8 * (gpc >> 1) + gi, dg = 2 * (gpc & 1) + side;
    p.role[sm] = pos == 65 ? -1 : (T1 | (GP << 4) | (side << 7) | (m2 << 8) | (dg << 14) | ((gi < 8) << 16));
  }
  void* fnp = nullptr;
  cudaDriverEntryPointQueryResult qr;
  cudaGetDriverEntryPoint("cuTensorMapEncodeTiled", &fnp, cudaEnableDefault, &qr);
  EncFn fn = (EncFn)fnp;
  void* gG = nullptr;
  cudaGetSymbolAddress(&gG, g_G);
  void* gKV = nullptr;
  cudaGetSymbolAddress(&gKV, g_kv);
  {
    cuuint64_t dims[5] = {32, 32, 10, 32, 4}, st[4] = {20480, 2048, 64, 655360}; cuuint32_t box[5] = {32, 35, 2, 1, 1};
    encode(fn, &p.mU, gKV, 5, dims, st, box, CU_TENSOR_MAP_SWIZZLE_NONE, 1);
  }
  const cuuint64_t RB = DM * 2;
  {
    p.swap = p.bim < p.bre;
    const char* lo = (const char*)(p.swap ? p.bim : p.bre); const char* hi = (const char*)(p.swap ? p.bre : p.bim);
    cuuint64_t dims[5] = {640, 8, 2, 8, 10}, st[4] = {RB, (cuuint64_t)(hi - lo), 8 * RB, 64 * RB}; cuuint32_t box[5] = {64, 8, 2, 4, 2};
    encode(fn, &p.mB, lo, 5, dims, st, box);
  }
  {
    cuuint64_t dims[5] = {640, 2, 4, 2, 40}, st[4] = {RB, 4 * RB, 2 * RB, 16 * RB}; cuuint32_t box[5] = {64, 2, 4, 2, 10};
    encode(fn, &p.mCre, p.cre, 5, dims, st, box); encode(fn, &p.mCim, p.cim, 5, dims, st, box);
    cuuint64_t dimg[5] = {2048, 2, 4, 2, 40}, stg[4] = {4096, 4 * 4096, 2 * 4096, 16 * 4096};
    encode(fn, &p.mG, gG, 5, dimg, stg, box);
  }
  {
    cuuint64_t dims[4] = {640, 2, 4, 900}, st[3] = {RB, 40 * RB, 2 * RB}; cuuint32_t box[4] = {64, 2, 4, 20};
    encode(fn, &p.mX, p.x, 4, dims, st, box);
    cuuint64_t diml[4] = {640, 2, 4, 16}, stl[3] = {RB, 32 * RB, 2 * RB};
    encode(fn, &p.mXl, p.x + (size_t)1920 * DM, 4, diml, stl, box);
    cuuint32_t boxt[4] = {160, 2, 4, 4};
    encode(fn, &p.mXt, p.x, 4, dims, st, boxt, CU_TENSOR_MAP_SWIZZLE_NONE);
    encode(fn, &p.mXtl, p.x + (size_t)1920 * DM, 4, diml, stl, boxt, CU_TENSOR_MAP_SWIZZLE_NONE);
    cuuint64_t dk[3] = {640, 2000, 4}, sk[2] = {RB, 16 * RB}; cuuint32_t bk[3] = {32, 19, 4}, bv[3] = {32, 17, 4};
    encode(fn, &p.mK, p.k, 3, dk, sk, bk, CU_TENSOR_MAP_SWIZZLE_NONE);
    encode(fn, &p.mV, p.v, 3, dk, sk, bv, CU_TENSOR_MAP_SWIZZLE_NONE);
  }
  cudaFuncSetAttribute(fused_kernel, cudaFuncAttributeMaxDynamicSharedMemorySize, SMEM_BYTES);
  cudaLaunchConfig_t cfg = {};
  cfg.gridDim = dim3(132); cfg.blockDim = dim3(512); cfg.dynamicSmemBytes = SMEM_BYTES; cfg.stream = cudaStreamPerThread;
  cudaLaunchKernelEx(&cfg, fused_kernel, p);
}
```

```cpp
#include <cuda_runtime.h>
#include <cuda.h>
#include <cuda_bf16.h>
#include <stdint.h>

namespace {

constexpr int SEQ = 2048, DM = 640;
constexpr int NT1 = 13;
#define EXP 0
#define WPF1 3
#define WPF2 7
#define CPOLL 10
#define KV0 1
#define TAPLATE 1
#define STG_D 3
#define STG_KK 1
#define HOLD0 1
#define WREL 0
#define UREL 1
#define TSL 1
#define STG0 0
#define WTAIL 1
#define PFD 1
#define TAPW 1
#define TPF 4
#define CPF 0
#define PAUSE_K 5
constexpr uint32_t SPIN_LIMIT = 1u << 22;

__device__ __align__(1024) uint8_t g_h[2 * 32 * 20 * 8192];
__device__ __align__(1024) uint8_t g_u[NT1 * 10 * 20480];
__device__ __align__(1024) uint8_t g_kv[DM * 4096];
__device__ __align__(1024) uint8_t g_G[DM * 4096];
__device__ __align__(128) uint4 g_E[2 * NT1 * DM];
__device__ __align__(128) uint4 g_stats[4 * 4 * SEQ];
__device__ __align__(128) uint4 g_sB[DM * 2];
__device__ __align__(128) unsigned g_hcnt[2 * 2 * 8 * 32];
__device__ __align__(128) unsigned g_ucnt[8 * 32];
__device__ __align__(128) unsigned g_kvcnt[16 * 32];
__device__ __align__(128) unsigned g_gcnt[16 * 32];
__device__ __align__(128) unsigned g_epoch[32] = {1};
#define TS(i) do {} while (0)

struct Params {
  CUtensorMap mX, mB, mXl, mK, mV, mXt, mXtl, mCre, mCim, mG, mU;
  const __nv_bfloat16 *x, *lre, *lim, *bre, *bim, *cre, *cim, *logdt, *dskip, *k, *v, *shiftk, *ssmk, *ssmD;
  float* out;
  int swap;
  int role[132];
};

constexpr uint32_t sb = 1024;
constexpr uint32_t G1_STAGE = 36864, G1_XOFF = 16384;
constexpr int S1 = 4;
constexpr uint32_t XT_OFF = 159744, KS_OFF = 180224, KV_PIECE = 9216;
constexpr uint32_t G2_XB = 8192, G2_WB = 20480, G2_WOFF = 57344, G_OFF = 200704;
constexpr uint32_t X1_OFF = 139264;
constexpr int S2 = 7;
constexpr uint32_t CV_OFF = KS_OFF, CV_K = 128, CV_PL = 2240, CV_U = CV_K + 4096, CV_B = KV_PIECE;
constexpr uint32_t MISC = 226304;
constexpr uint32_t BAR_OFF = MISC;
constexpr int B_G1FULL = 0, B_G1DONE = 20, B_G2FULL = 40,
              B_G2DONE = 85, B_GFULL = 125, B_EP = 126, B_H1 = 127  , B_CVFULL = 129  , B_STG = 134  , B_REL = 136  , B_SFREE = 138, B_UST = 142,
              B_GO = 139  , B_PUB = 147,
              B_CVDONE = 148  , B_STAB = 153  , B_XFREE = 155, B_HST = 156  ,
              B_CTAB = 160, B_PREP = 161, B_XT = 162, B_KV = 163  , B_PREP2 = 84;
constexpr uint32_t bars = sb + BAR_OFF;
constexpr uint32_t STAB_OFF = MISC + 1344;
constexpr uint32_t CTAB_OFF = STAB_OFF + 1280;
constexpr uint32_t DTAB_OFF = CTAB_OFF + 1536;
constexpr uint32_t EP_OFF = DTAB_OFF + 320;
constexpr uint32_t SO_OFF = EP_OFF + 32;
constexpr uint32_t TAP_OFF = 147456;
constexpr uint32_t SMEM_BYTES = 232448;
static_assert(SO_OFF + 1536 <= SMEM_BYTES, "smem");

__device__ __forceinline__ void trap_if(bool c) { asm volatile("{\n.reg .pred p;\nsetp.ne.u32 p, %0, 0;\n@p trap;\n}\n" ::"r"((uint32_t)c)); }
__device__ __forceinline__ uint32_t smem_u32(const void* p) { return (uint32_t)__cvta_generic_to_shared(p); }
__device__ __forceinline__ void mbar_init(uint32_t bar, int cnt) { asm volatile("mbarrier.init.shared::cta.b64 [%0], %1;" ::"r"(bar), "r"(cnt) : "memory"); }
__device__ __forceinline__ void mbar_expect_tx(uint32_t bar, int bytes) { asm volatile("mbarrier.arrive.expect_tx.shared::cta.b64 _, [%0], %1;" ::"r"(bar), "r"(bytes) : "memory"); }
__device__ __forceinline__ void mbar_arrive(uint32_t bar) { asm volatile("mbarrier.arrive.shared::cta.b64 _, [%0];" ::"r"(bar) : "memory"); }
__device__ __forceinline__ void mbar_wait(uint32_t bar) {
  asm volatile(
      "{\n.reg .pred p;\n.reg .u32 c;\nmov.u32 c, 0;\n"
      "W_%=:\nmbarrier.try_wait.parity.shared::cta.b64 p, [%0], 0;\n@p bra D_%=;\n"
      "add.u32 c, c, 1;\nsetp.lt.u32 p, c, %1;\n@p bra W_%=;\ntrap;\nD_%=:\n}\n" ::"r"(bar), "n"(SPIN_LIMIT) : "memory");
}
__device__ __forceinline__ uint32_t mbar_test(uint32_t bar) {
  uint32_t ok;
  asm volatile("{\n.reg .pred p;\nmbarrier.test_wait.parity.shared::cta.b64 p, [%1], 0;\nselp.u32 %0, 1, 0, p;\n}\n" : "=r"(ok) : "r"(bar) : "memory");
  return ok;
}
__device__ __forceinline__ void tma3(uint32_t dst, const CUtensorMap* m, int c0, int c1, int c2, uint32_t bar) {
  asm volatile("cp.async.bulk.tensor.3d.shared::cluster.global.mbarrier::complete_tx::bytes [%0], [%1, {%3,%4,%5}], [%2];"
               ::"r"(dst), "l"(m), "r"(bar), "r"(c0), "r"(c1), "r"(c2) : "memory");
}
__device__ __forceinline__ void tma4(uint32_t dst, const CUtensorMap* m, int c0, int c1, int c2, int c3, uint32_t bar) {
  asm volatile("cp.async.bulk.tensor.4d.shared::cluster.global.mbarrier::complete_tx::bytes [%0], [%1, {%3,%4,%5,%6}], [%2];"
               ::"r"(dst), "l"(m), "r"(bar), "r"(c0), "r"(c1), "r"(c2), "r"(c3) : "memory");
}
__device__ __forceinline__ void tma5(uint32_t dst, const CUtensorMap* m, int c0, int c1, int c2, int c3, int c4, uint32_t bar) {
  asm volatile("cp.async.bulk.tensor.5d.shared::cluster.global.mbarrier::complete_tx::bytes [%0], [%1, {%3,%4,%5,%6,%7}], [%2];"
               ::"r"(dst), "l"(m), "r"(bar), "r"(c0), "r"(c1), "r"(c2), "r"(c3), "r"(c4) : "memory");
}
__device__ __forceinline__ void bulk_g2s(uint32_t dst, const void* src, int bytes, uint32_t bar) {
  asm volatile("cp.async.bulk.shared::cluster.global.mbarrier::complete_tx::bytes [%0], [%1], %2, [%3];"
               ::"r"(dst), "l"(src), "r"(bytes), "r"(bar) : "memory");
}
__device__ __forceinline__ void bulk_s2g(void* dst, uint32_t src, int bytes) {
  asm volatile("cp.async.bulk.global.shared::cta.bulk_group [%0], [%1], %2;" ::"l"(dst), "r"(src), "r"(bytes) : "memory");
}
__device__ __forceinline__ void l2_prefetch(const void* src, int bytes) {
  asm volatile("cp.async.bulk.prefetch.L2.global [%0], %1;" ::"l"(src), "r"(bytes) : "memory");
}
__device__ __forceinline__ void wgmma_fence() { asm volatile("wgmma.fence.sync.aligned;" ::: "memory"); }
__device__ __forceinline__ void wgmma_commit() { asm volatile("wgmma.commit_group.sync.aligned;" ::: "memory"); }
template <int N> __device__ __forceinline__ void wgmma_wait() { asm volatile("wgmma.wait_group.sync.aligned %0;" ::"n"(N) : "memory"); }
__host__ __device__ constexpr uint32_t desc_lo(uint32_t addr, uint32_t lbo) { return ((addr & 0x3FFFF) >> 4) | ((lbo >> 4) << 16); }
__host__ __device__ constexpr uint32_t desc_hi(uint32_t sbo, uint32_t swz) { return (sbo >> 4) | (swz << 30); }
__device__ __forceinline__ void bar_sync(int id, int n) { asm volatile("bar.sync %0, %1;" ::"r"(id), "r"(n) : "memory"); }
__device__ __forceinline__ uint32_t lds32(uint32_t a) { uint32_t v; asm volatile("ld.shared.u32 %0, [%1];" : "=r"(v) : "r"(a) : "memory"); return v; }
__device__ __forceinline__ float2 lds64f(uint32_t a) { float2 v; asm volatile("ld.shared.v2.f32 {%0,%1}, [%2];" : "=f"(v.x), "=f"(v.y) : "r"(a) : "memory"); return v; }
__device__ __forceinline__ float4 lds128f(uint32_t a) { float4 v; asm volatile("ld.shared.v4.f32 {%0,%1,%2,%3}, [%4];" : "=f"(v.x), "=f"(v.y), "=f"(v.z), "=f"(v.w) : "r"(a) : "memory"); return v; }
__device__ __forceinline__ void ldsm4t(uint32_t (&r)[4], uint32_t a) {
  asm volatile("ldmatrix.sync.aligned.m8n8.x4.trans.shared.b16 {%0,%1,%2,%3}, [%4];" : "=r"(r[0]), "=r"(r[1]), "=r"(r[2]), "=r"(r[3]) : "r"(a) : "memory");
}
__device__ __forceinline__ uint4 ldv128(const void* a) { uint4 v; asm volatile("ld.global.nc.v4.u32 {%0,%1,%2,%3}, [%4];" : "=r"(v.x), "=r"(v.y), "=r"(v.z), "=r"(v.w) : "l"(a) : "memory"); return v; }
__device__ __forceinline__ uint2 ldv64(const void* a) { uint2 v; asm volatile("ld.global.nc.v2.u32 {%0,%1}, [%2];" : "=r"(v.x), "=r"(v.y) : "l"(a) : "memory"); return v; }
__device__ __forceinline__ uint32_t ldv16(const void* a) { uint32_t v; asm volatile("ld.global.nc.u16 %0, [%1];" : "=r"(v) : "l"(a) : "memory"); return v; }
__device__ __forceinline__ void sts128(uint32_t a, uint4 v) { asm volatile("st.shared.v4.u32 [%0], {%1,%2,%3,%4};" ::"r"(a), "r"(v.x), "r"(v.y), "r"(v.z), "r"(v.w) : "memory"); }
__device__ __forceinline__ void sts32(uint32_t a, uint32_t v) { asm volatile("st.shared.u32 [%0], %1;" ::"r"(a), "r"(v) : "memory"); }
__device__ __forceinline__ void sts64f(uint32_t a, float x, float y) { asm volatile("st.shared.v2.f32 [%0], {%1,%2};" ::"r"(a), "f"(x), "f"(y) : "memory"); }
__device__ __forceinline__ void red_rlx(unsigned* p) { asm volatile("red.relaxed.gpu.global.add.u32 [%0], 1;" ::"l"(p) : "memory"); }
__device__ __forceinline__ void red_rel(unsigned* p) { asm volatile("red.release.gpu.global.add.u32 [%0], 1;" ::"l"(p) : "memory"); }
__device__ __forceinline__ void fence_async_global() { asm volatile("fence.proxy.async.global;" ::: "memory"); }
__device__ __forceinline__ void fence_async_smem() { asm volatile("fence.proxy.async.shared::cta;" ::: "memory"); }
__device__ __forceinline__ void rec_st(uint4* p, float a, float b, unsigned tag) {
  asm volatile("{\n.reg .b128 t;\n.reg .b64 lo, hi;\nmov.b64 lo, {%1,%2};\nmov.b64 hi, {%3,%3};\nmov.b128 t, {lo,hi};\n"
               "st.relaxed.gpu.global.b128 [%0], t;\n}\n" ::"l"(p), "r"(__float_as_uint(a)), "r"(__float_as_uint(b)), "r"(tag) : "memory");
}
__device__ __forceinline__ unsigned rec_ld(const uint4* p, float& a, float& b) {
  unsigned x, y, t;
  asm volatile("{\n.reg .b128 t;\n.reg .b64 lo, hi;\n.reg .b32 u;\nld.relaxed.gpu.global.b128 t, [%3];\nmov.b128 {lo,hi}, t;\n"
               "mov.b64 {%0,%1}, lo;\nmov.b64 {%2,u}, hi;\n}\n" : "=r"(x), "=r"(y), "=r"(t) : "l"(p) : "memory");
  a = __uint_as_float(x); b = __uint_as_float(y);
  return t;
}
__device__ __forceinline__ unsigned ld_rlx(const unsigned* p) { unsigned v; asm volatile("ld.relaxed.gpu.global.u32 %0, [%1];" : "=r"(v) : "l"(p) : "memory"); return v; }
__device__ __forceinline__ void flag_poll(const unsigned* p, unsigned target) {
  uint32_t it = 0;
  while (!__all_sync(0xffffffffu, (int)(ld_rlx(p) - target) >= 0)) { trap_if(++it > SPIN_LIMIT); }
  asm volatile("fence.acquire.gpu;" ::: "memory");
}
__device__ __forceinline__ void cnt_poll(const unsigned* p, unsigned target) {
  unsigned a = ld_rlx(p); __nanosleep(100);
  unsigned b = ld_rlx(p); __nanosleep(100);
  unsigned c = ld_rlx(p);
  uint32_t it = 0;
  while (true) {
    if (__all_sync(0xffffffffu, (int)(a - target) >= 0)) break;
    a = ld_rlx(p);
    if (__all_sync(0xffffffffu, (int)(b - target) >= 0)) break;
    b = ld_rlx(p);
    if (__all_sync(0xffffffffu, (int)(c - target) >= 0)) break;
    c = ld_rlx(p);
    trap_if(++it > SPIN_LIMIT);
  }
  asm volatile("fence.acquire.gpu;" ::: "memory");
}
__device__ __forceinline__ void h_release(int idx, int T, int i) {
  const int Q = (i & 2) ? (T + 2) / 3 - 1 : T / 3;
  if (Q >= 0 && Q < 4 && ((i & 2) == 0 || T % 3 == 0)) red_rel(&g_hcnt[(idx * 8 + 2 * Q + (i & 1)) * 32]);
}
__device__ __forceinline__ uint32_t pack_bf16(float lo, float hi) {
  uint32_t r; asm("cvt.rn.bf16x2.f32 %0, %1, %2;" : "=r"(r) : "f"(hi), "f"(lo)); return r;
}
__device__ __forceinline__ float bf_lo(uint32_t w) { return __uint_as_float(w << 16); }
__device__ __forceinline__ float bf_hi(uint32_t w) { return __uint_as_float(w & 0xffff0000u); }
__device__ __forceinline__ uint32_t hmul2(uint32_t a, uint32_t b) {
  __nv_bfloat162 r = __hmul2_rn(*(__nv_bfloat162*)&a, *(__nv_bfloat162*)&b); return *(uint32_t*)&r;
}
__device__ __forceinline__ uint32_t hadd2(uint32_t a, uint32_t b) {
  __nv_bfloat162 r = __hadd2_rn(*(__nv_bfloat162*)&a, *(__nv_bfloat162*)&b); return *(uint32_t*)&r;
}
__device__ __forceinline__ float2 cmul(float2 a, float2 b) { return make_float2(a.x * b.x - a.y * b.y, a.x * b.y + a.y * b.x); }
__device__ __forceinline__ float2 cfma(float2 a, float2 b, float2 c) {
  return make_float2(fmaf(a.x, b.x, fmaf(-a.y, b.y, c.x)), fmaf(a.x, b.y, fmaf(a.y, b.x, c.y)));
}
template <int N> __device__ __forceinline__ void fence_regs(float (&a)[N]) {
#pragma unroll
  for (int i = 0; i < N; i++) asm volatile("" : "+f"(a[i])::"memory");
}
__device__ __forceinline__ bool elect_one() {
  uint32_t e; asm volatile("{\n.reg .pred P;\nelect.sync _|P, 0xffffffff;\nselp.u32 %0, 1, 0, P;\n}\n" : "=r"(e)); return e != 0;
}
__device__ __forceinline__ int tid_opaque() { int t; asm volatile("mov.u32 %0, %%tid.x;" : "=r"(t)); return t; }
struct Role { int T1, GP, side, m2, dg, cch0; bool last, has2; };
__device__ __forceinline__ Role unpack_role(int x) {
  Role r; r.T1 = x & 15; r.GP = (x >> 4) & 7; r.side = (x >> 7) & 1; r.m2 = (x >> 8) & 63; r.dg = (x >> 14) & 3;
  r.has2 = (x >> 16) & 1; r.last = r.T1 == NT1 - 1; r.cch0 = 160 * r.dg + r.m2; return r;
}
__device__ __forceinline__ Role fresh_role(int x) { asm volatile("" : "+r"(x)); return unpack_role(__shfl_sync(0xffffffffu, x, 0)); }
#define ROLE(x) const Role R_ = fresh_role(x); const int T1 = R_.T1, GP = R_.GP, side = R_.side, m2 = R_.m2, dg = R_.dg, cch0 = R_.cch0; \
  const bool last = R_.last, has2 = R_.has2; (void)T1; (void)GP; (void)side; (void)m2; (void)dg; (void)cch0; (void)last; (void)has2;
__device__ __forceinline__ int n_to_t(int n) {
  int T = n / 160, nl = n - T * 160;
  int L = (T == NT1 - 1) ? 32 : 40;
  return T * 160 + L * ((nl & 7) >> 1) + 2 * (nl >> 3) + (nl & 1);
}

template<int TA> __device__ __forceinline__ void wgmma_n160(float (&d)[80], uint32_t alo, uint32_t ahi, uint32_t blo, uint32_t bhi){
  asm volatile("{\n.reg .b64 da, db;\nmov.b64 da, {%80,%81};\nmov.b64 db, {%82,%83};\n"
    "wgmma.mma_async.sync.aligned.m64n160k16.f32.bf16.bf16 {%0, %1, %2, %3, %4, %5, %6, %7, %8, %9, %10, %11, %12, %13, %14, %15, %16, %17, %18, %19, %20, %21, %22, %23, %24, %25, %26, %27, %28, %29, %30, %31, %32, %33, %34, %35, %36, %37, %38, %39, %40, %41, %42, %43, %44, %45, %46, %47, %48, %49, %50, %51, %52, %53, %54, %55, %56, %57, %58, %59, %60, %61, %62, %63, %64, %65, %66, %67, %68, %69, %70, %71, %72, %73, %74, %75, %76, %77, %78, %79}, da, db, 1, 1, 1, %84, 0;\n}\n"
    : "+f"(d[0]), "+f"(d[1]), "+f"(d[2]), "+f"(d[3]), "+f"(d[4]), "+f"(d[5]), "+f"(d[6]), "+f"(d[7]), "+f"(d[8]), "+f"(d[9]), "+f"(d[10]), "+f"(d[11]), "+f"(d[12]), "+f"(d[13]), "+f"(d[14]), "+f"(d[15]), "+f"(d[16]), "+f"(d[17]), "+f"(d[18]), "+f"(d[19]), "+f"(d[20]), "+f"(d[21]), "+f"(d[22]), "+f"(d[23]), "+f"(d[24]), "+f"(d[25]), "+f"(d[26]), "+f"(d[27]), "+f"(d[28]), "+f"(d[29]), "+f"(d[30]), "+f"(d[31]), "+f"(d[32]), "+f"(d[33]), "+f"(d[34]), "+f"(d[35]), "+f"(d[36]), "+f"(d[37]), "+f"(d[38]), "+f"(d[39]), "+f"(d[40]), "+f"(d[41]), "+f"(d[42]), "+f"(d[43]), "+f"(d[44]), "+f"(d[45]), "+f"(d[46]), "+f"(d[47]), "+f"(d[48]), "+f"(d[49]), "+f"(d[50]), "+f"(d[51]), "+f"(d[52]), "+f"(d[53]), "+f"(d[54]), "+f"(d[55]), "+f"(d[56]), "+f"(d[57]), "+f"(d[58]), "+f"(d[59]), "+f"(d[60]), "+f"(d[61]), "+f"(d[62]), "+f"(d[63]), "+f"(d[64]), "+f"(d[65]), "+f"(d[66]), "+f"(d[67]), "+f"(d[68]), "+f"(d[69]), "+f"(d[70]), "+f"(d[71]), "+f"(d[72]), "+f"(d[73]), "+f"(d[74]), "+f"(d[75]), "+f"(d[76]), "+f"(d[77]), "+f"(d[78]), "+f"(d[79])
    : "r"(alo), "r"(ahi), "r"(blo), "r"(bhi), "n"(TA));
}
template<int N> __device__ __forceinline__ void wgmma_rs_hi(float (&d)[64], uint32_t a0, uint32_t a1, uint32_t a2, uint32_t a3, uint32_t blo);
template<> __device__ __forceinline__ void wgmma_rs_hi<16>(float (&d)[64], uint32_t a0, uint32_t a1, uint32_t a2, uint32_t a3, uint32_t blo){
  asm volatile("{\n.reg .b64 db;\nmov.b64 db, {%12,8};\nwgmma.mma_async.sync.aligned.m64n16k16.f32.bf16.bf16 {%0, %1, %2, %3, %4, %5, %6, %7}, {%8,%9,%10,%11}, db, 1, 1, 1, 0;\n}\n"
    : "+f"(d[56]), "+f"(d[57]), "+f"(d[58]), "+f"(d[59]), "+f"(d[60]), "+f"(d[61]), "+f"(d[62]), "+f"(d[63])
    : "r"(a0), "r"(a1), "r"(a2), "r"(a3), "r"(blo));
}
template<> __device__ __forceinline__ void wgmma_rs_hi<32>(float (&d)[64], uint32_t a0, uint32_t a1, uint32_t a2, uint32_t a3, uint32_t blo){
  asm volatile("{\n.reg .b64 db;\nmov.b64 db, {%20,8};\nwgmma.mma_async.sync.aligned.m64n32k16.f32.bf16.bf16 {%0, %1, %2, %3, %4, %5, %6, %7, %8, %9, %10, %11, %12, %13, %14, %15}, {%16,%17,%18,%19}, db, 1, 1, 1, 0;\n}\n"
    : "+f"(d[48]), "+f"(d[49]), "+f"(d[50]), "+f"(d[51]), "+f"(d[52]), "+f"(d[53]), "+f"(d[54]), "+f"(d[55]), "+f"(d[56]), "+f"(d[57]), "+f"(d[58]), "+f"(d[59]), "+f"(d[60]), "+f"(d[61]), "+f"(d[62]), "+f"(d[63])
    : "r"(a0), "r"(a1), "r"(a2), "r"(a3), "r"(blo));
}
template<> __device__ __forceinline__ void wgmma_rs_hi<48>(float (&d)[64], uint32_t a0, uint32_t a1, uint32_t a2, uint32_t a3, uint32_t blo){
  asm volatile("{\n.reg .b64 db;\nmov.b64 db, {%28,8};\nwgmma.mma_async.sync.aligned.m64n48k16.f32.bf16.bf16 {%0, %1, %2, %3, %4, %5, %6, %7, %8, %9, %10, %11, %12, %13, %14, %15, %16, %17, %18, %19, %20, %21, %22, %23}, {%24,%25,%26,%27}, db, 1, 1, 1, 0;\n}\n"
    : "+f"(d[40]), "+f"(d[41]), "+f"(d[42]), "+f"(d[43]), "+f"(d[44]), "+f"(d[45]), "+f"(d[46]), "+f"(d[47]), "+f"(d[48]), "+f"(d[49]), "+f"(d[50]), "+f"(d[51]), "+f"(d[52]), "+f"(d[53]), "+f"(d[54]), "+f"(d[55]), "+f"(d[56]), "+f"(d[57]), "+f"(d[58]), "+f"(d[59]), "+f"(d[60]), "+f"(d[61]), "+f"(d[62]), "+f"(d[63])
    : "r"(a0), "r"(a1), "r"(a2), "r"(a3), "r"(blo));
}
template<> __device__ __forceinline__ void wgmma_rs_hi<64>(float (&d)[64], uint32_t a0, uint32_t a1, uint32_t a2, uint32_t a3, uint32_t blo){
  asm volatile("{\n.reg .b64 db;\nmov.b64 db, {%36,8};\nwgmma.mma_async.sync.aligned.m64n64k16.f32.bf16.bf16 {%0, %1, %2, %3, %4, %5, %6, %7, %8, %9, %10, %11, %12, %13, %14, %15, %16, %17, %18, %19, %20, %21, %22, %23, %24, %25, %26, %27, %28, %29, %30, %31}, {%32,%33,%34,%35}, db, 1, 1, 1, 0;\n}\n"
    : "+f"(d[32]), "+f"(d[33]), "+f"(d[34]), "+f"(d[35]), "+f"(d[36]), "+f"(d[37]), "+f"(d[38]), "+f"(d[39]), "+f"(d[40]), "+f"(d[41]), "+f"(d[42]), "+f"(d[43]), "+f"(d[44]), "+f"(d[45]), "+f"(d[46]), "+f"(d[47]), "+f"(d[48]), "+f"(d[49]), "+f"(d[50]), "+f"(d[51]), "+f"(d[52]), "+f"(d[53]), "+f"(d[54]), "+f"(d[55]), "+f"(d[56]), "+f"(d[57]), "+f"(d[58]), "+f"(d[59]), "+f"(d[60]), "+f"(d[61]), "+f"(d[62]), "+f"(d[63])
    : "r"(a0), "r"(a1), "r"(a2), "r"(a3), "r"(blo));
}
template<> __device__ __forceinline__ void wgmma_rs_hi<80>(float (&d)[64], uint32_t a0, uint32_t a1, uint32_t a2, uint32_t a3, uint32_t blo){
  asm volatile("{\n.reg .b64 db;\nmov.b64 db, {%44,8};\nwgmma.mma_async.sync.aligned.m64n80k16.f32.bf16.bf16 {%0, %1, %2, %3, %4, %5, %6, %7, %8, %9, %10, %11, %12, %13, %14, %15, %16, %17, %18, %19, %20, %21, %22, %23, %24, %25, %26, %27, %28, %29, %30, %31, %32, %33, %34, %35, %36, %37, %38, %39}, {%40,%41,%42,%43}, db, 1, 1, 1, 0;\n}\n"
    : "+f"(d[24]), "+f"(d[25]), "+f"(d[26]), "+f"(d[27]), "+f"(d[28]), "+f"(d[29]), "+f"(d[30]), "+f"(d[31]), "+f"(d[32]), "+f"(d[33]), "+f"(d[34]), "+f"(d[35]), "+f"(d[36]), "+f"(d[37]), "+f"(d[38]), "+f"(d[39]), "+f"(d[40]), "+f"(d[41]), "+f"(d[42]), "+f"(d[43]), "+f"(d[44]), "+f"(d[45]), "+f"(d[46]), "+f"(d[47]), "+f"(d[48]), "+f"(d[49]), "+f"(d[50]), "+f"(d[51]), "+f"(d[52]), "+f"(d[53]), "+f"(d[54]), "+f"(d[55]), "+f"(d[56]), "+f"(d[57]), "+f"(d[58]), "+f"(d[59]), "+f"(d[60]), "+f"(d[61]), "+f"(d[62]), "+f"(d[63])
    : "r"(a0), "r"(a1), "r"(a2), "r"(a3), "r"(blo));
}
template<> __device__ __forceinline__ void wgmma_rs_hi<96>(float (&d)[64], uint32_t a0, uint32_t a1, uint32_t a2, uint32_t a3, uint32_t blo){
  asm volatile("{\n.reg .b64 db;\nmov.b64 db, {%52,8};\nwgmma.mma_async.sync.aligned.m64n96k16.f32.bf16.bf16 {%0, %1, %2, %3, %4, %5, %6, %7, %8, %9, %10, %11, %12, %13, %14, %15, %16, %17, %18, %19, %20, %21, %22, %23, %24, %25, %26, %27, %28, %29, %30, %31, %32, %33, %34, %35, %36, %37, %38, %39, %40, %41, %42, %43, %44, %45, %46, %47}, {%48,%49,%50,%51}, db, 1, 1, 1, 0;\n}\n"
    : "+f"(d[16]), "+f"(d[17]), "+f"(d[18]), "+f"(d[19]), "+f"(d[20]), "+f"(d[21]), "+f"(d[22]), "+f"(d[23]), "+f"(d[24]), "+f"(d[25]), "+f"(d[26]), "+f"(d[27]), "+f"(d[28]), "+f"(d[29]), "+f"(d[30]), "+f"(d[31]), "+f"(d[32]), "+f"(d[33]), "+f"(d[34]), "+f"(d[35]), "+f"(d[36]), "+f"(d[37]), "+f"(d[38]), "+f"(d[39]), "+f"(d[40]), "+f"(d[41]), "+f"(d[42]), "+f"(d[43]), "+f"(d[44]), "+f"(d[45]), "+f"(d[46]), "+f"(d[47]), "+f"(d[48]), "+f"(d[49]), "+f"(d[50]), "+f"(d[51]), "+f"(d[52]), "+f"(d[53]), "+f"(d[54]), "+f"(d[55]), "+f"(d[56]), "+f"(d[57]), "+f"(d[58]), "+f"(d[59]), "+f"(d[60]), "+f"(d[61]), "+f"(d[62]), "+f"(d[63])
    : "r"(a0), "r"(a1), "r"(a2), "r"(a3), "r"(blo));
}
template<> __device__ __forceinline__ void wgmma_rs_hi<112>(float (&d)[64], uint32_t a0, uint32_t a1, uint32_t a2, uint32_t a3, uint32_t blo){
  asm volatile("{\n.reg .b64 db;\nmov.b64 db, {%60,8};\nwgmma.mma_async.sync.aligned.m64n112k16.f32.bf16.bf16 {%0, %1, %2, %3, %4, %5, %6, %7, %8, %9, %10, %11, %12, %13, %14, %15, %16, %17, %18, %19, %20, %21, %22, %23, %24, %25, %26, %27, %28, %29, %30, %31, %32, %33, %34, %35, %36, %37, %38, %39, %40, %41, %42, %43, %44, %45, %46, %47, %48, %49, %50, %51, %52, %53, %54, %55}, {%56,%57,%58,%59}, db, 1, 1, 1, 0;\n}\n"
    : "+f"(d[8]), "+f"(d[9]), "+f"(d[10]), "+f"(d[11]), "+f"(d[12]), "+f"(d[13]), "+f"(d[14]), "+f"(d[15]), "+f"(d[16]), "+f"(d[17]), "+f"(d[18]), "+f"(d[19]), "+f"(d[20]), "+f"(d[21]), "+f"(d[22]), "+f"(d[23]), "+f"(d[24]), "+f"(d[25]), "+f"(d[26]), "+f"(d[27]), "+f"(d[28]), "+f"(d[29]), "+f"(d[30]), "+f"(d[31]), "+f"(d[32]), "+f"(d[33]), "+f"(d[34]), "+f"(d[35]), "+f"(d[36]), "+f"(d[37]), "+f"(d[38]), "+f"(d[39]), "+f"(d[40]), "+f"(d[41]), "+f"(d[42]), "+f"(d[43]), "+f"(d[44]), "+f"(d[45]), "+f"(d[46]), "+f"(d[47]), "+f"(d[48]), "+f"(d[49]), "+f"(d[50]), "+f"(d[51]), "+f"(d[52]), "+f"(d[53]), "+f"(d[54]), "+f"(d[55]), "+f"(d[56]), "+f"(d[57]), "+f"(d[58]), "+f"(d[59]), "+f"(d[60]), "+f"(d[61]), "+f"(d[62]), "+f"(d[63])
    : "r"(a0), "r"(a1), "r"(a2), "r"(a3), "r"(blo));
}
template<> __device__ __forceinline__ void wgmma_rs_hi<128>(float (&d)[64], uint32_t a0, uint32_t a1, uint32_t a2, uint32_t a3, uint32_t blo){
  asm volatile("{\n.reg .b64 db;\nmov.b64 db, {%68,8};\nwgmma.mma_async.sync.aligned.m64n128k16.f32.bf16.bf16 {%0, %1, %2, %3, %4, %5, %6, %7, %8, %9, %10, %11, %12, %13, %14, %15, %16, %17, %18, %19, %20, %21, %22, %23, %24, %25, %26, %27, %28, %29, %30, %31, %32, %33, %34, %35, %36, %37, %38, %39, %40, %41, %42, %43, %44, %45, %46, %47, %48, %49, %50, %51, %52, %53, %54, %55, %56, %57, %58, %59, %60, %61, %62, %63}, {%64,%65,%66,%67}, db, 1, 1, 1, 0;\n}\n"
    : "+f"(d[0]), "+f"(d[1]), "+f"(d[2]), "+f"(d[3]), "+f"(d[4]), "+f"(d[5]), "+f"(d[6]), "+f"(d[7]), "+f"(d[8]), "+f"(d[9]), "+f"(d[10]), "+f"(d[11]), "+f"(d[12]), "+f"(d[13]), "+f"(d[14]), "+f"(d[15]), "+f"(d[16]), "+f"(d[17]), "+f"(d[18]), "+f"(d[19]), "+f"(d[20]), "+f"(d[21]), "+f"(d[22]), "+f"(d[23]), "+f"(d[24]), "+f"(d[25]), "+f"(d[26]), "+f"(d[27]), "+f"(d[28]), "+f"(d[29]), "+f"(d[30]), "+f"(d[31]), "+f"(d[32]), "+f"(d[33]), "+f"(d[34]), "+f"(d[35]), "+f"(d[36]), "+f"(d[37]), "+f"(d[38]), "+f"(d[39]), "+f"(d[40]), "+f"(d[41]), "+f"(d[42]), "+f"(d[43]), "+f"(d[44]), "+f"(d[45]), "+f"(d[46]), "+f"(d[47]), "+f"(d[48]), "+f"(d[49]), "+f"(d[50]), "+f"(d[51]), "+f"(d[52]), "+f"(d[53]), "+f"(d[54]), "+f"(d[55]), "+f"(d[56]), "+f"(d[57]), "+f"(d[58]), "+f"(d[59]), "+f"(d[60]), "+f"(d[61]), "+f"(d[62]), "+f"(d[63])
    : "r"(a0), "r"(a1), "r"(a2), "r"(a3), "r"(blo));
}

struct CvCtx {
  uint32_t koff, zero, so[3];
  int srcA, srcB;
  bool wrapA, s3, kodd;
};
struct CvPipe { uint32_t Ap, Ep, keep, send; };
template <int LO> __device__ __forceinline__ void cv_copy(float (&acc)[64]) {
#pragma unroll
  for (int i = LO; i < 64; i++) { float t; asm volatile("mov.b32 %0, %1;" : "=f"(t) : "f"(acc[i]) : "memory"); acc[i] = t; }
}
template <int G> __device__ __forceinline__ void cv_raw(uint32_t (&A)[4][4], uint32_t kaddr) {
#pragma unroll
  for (int i = 0; i < 4; i++) {
    const uint32_t a = kaddr + (4 * G + i) * 128;
    A[i][0] = lds32(a); A[i][1] = lds32(a + 4); A[i][3] = lds32(a + 8);
  }
}
__device__ __forceinline__ void cv_form(uint32_t (&A)[4][4], uint32_t sel) {
#pragma unroll
  for (int i = 0; i < 4; i++) {
    asm volatile("prmt.b32 %0, %0, %1, %2;" : "+r"(A[i][0]) : "r"(A[i][1]), "r"(sel));
    asm volatile("prmt.b32 %0, %1, %2, %3;" : "=r"(A[i][2]) : "r"(A[i][1]), "r"(A[i][3]), "r"(sel));
  }
}
#define CVV 2
template <int G> __device__ __forceinline__ void cv_step(float (&acc)[64], uint32_t (&A)[4][4], CvPipe& s, const CvCtx& c, uint32_t cb, uint32_t stg) {
  constexpr int JA = G - 1, JB = G - 2, NH = CVV == 1 ? 4 : (CVV == 3 ? 2 : 1);
  const uint32_t db0 = desc_lo(cb + CV_U + 192, CV_PL);
  uint32_t B[4][4];
  uint32_t ra[2], rb;
  if constexpr (G < 8) {
    wgmma_fence();
#pragma unroll
    for (int i = 0; i < NH; i++) wgmma_rs_hi<128 - 16 * (G & 7)>(acc, A[i][0], A[i][1], A[i][2], A[i][3], db0 - 4 * i);
    wgmma_commit();
    __syncwarp();
  }
  if constexpr (JA >= 0 && JA < 8) {
    const uint32_t p0 = pack_bf16(acc[8 * JA + 1], acc[8 * JA + 3]), p1 = pack_bf16(acc[8 * JA + 5], acc[8 * JA + 7]);
    ra[0] = __shfl_sync(0xffffffffu, c.wrapA ? s.Ap : p0, c.srcA);
    ra[1] = __shfl_sync(0xffffffffu, c.wrapA ? p0 : p1, c.srcA);
    s.Ap = p1;
  }
  if constexpr (JB >= 0) rb = __shfl_sync(0xffffffffu, s.send, c.srcB);
  if constexpr (G < 7) cv_raw<G + 1>(B, cb + c.koff);
  uint32_t z = 0;
  if constexpr (G < 8 && NH < 4) {
    __syncwarp();
    wgmma_fence();
#pragma unroll
    for (int i = NH; i < 4; i++) wgmma_rs_hi<128 - 16 * (G & 7)>(acc, A[i][0], A[i][1], A[i][2], A[i][3], db0 - 4 * i);
    wgmma_commit();
    asm volatile("mov.u32 %0, %%clock;" : "=r"(z)::"memory");
    z &= c.zero;
  }
  if constexpr (G < 7) cv_form(B, 0x5432u | z);
  if constexpr (JB >= 0) sts32(stg + ((c.so[JB / 3] >> (10 * (JB % 3))) & 0xffc), hadd2(rb | z, s.keep));
  if constexpr (JA >= 0 && JA < 8) {
    const uint32_t sh = 16 | z, mk = 0xffff0000u | z;
    const uint32_t ev = pack_bf16(acc[8 * JA] + __uint_as_float(ra[0] << sh), acc[8 * JA + 2] + __uint_as_float(ra[0] & mk));
    const uint32_t od = pack_bf16(acc[8 * JA + 4] + __uint_as_float(ra[1] << sh), acc[8 * JA + 6] + __uint_as_float(ra[1] & mk));
    s.send = c.kodd ? ev : (c.s3 ? s.Ep : od);
    s.keep = c.kodd ? od : ev;
    s.Ep = od;
  }
  if constexpr (G < 8) { __syncwarp(); wgmma_wait<0>(); cv_copy<8 * (G & 7)>(acc); }
  if constexpr (G < 9) cv_step<G + 1>(acc, B, s, c, cb, stg);
}
__device__ __forceinline__ uint32_t cv_stage(int slot) { return sb + (slot < 4 ? 40960 + slot * 4096 : CV_OFF + CV_K); }
__device__ __forceinline__ void cv_setup(CvCtx& c) {
  const int tid = tid_opaque() & 127, w = tid >> 5, lane = tid & 31, r = lane >> 2, q = lane & 3;
  const int i0 = (r >> 1) & 1, i1 = r >> 2;
  c.koff = CV_K - 32 + 4 * (8 * (r >> 1) + 2 * w + (r & 1) + 2 * q);
  c.srcA = i0 ? lane - 8 : lane + 8 - q + ((q + 3) & 3);
  c.wrapA = i0 && q == 3;
  c.srcB = i1 == 0 ? (lane - q + 16 + ((q + 3) & 3)) : (lane - q - 16 + ((q + 1) & 3));
  c.s3 = (i1 == 1 && q == 3); c.kodd = (i1 == 1 && q < 3);
  c.zero = lds32(sb + EP_OFF + 24);
#pragma unroll
  for (int i = 0; i < 3; i++) c.so[i] = lds32(sb + SO_OFF + 512 * i + 4 * tid);
}
__device__ __forceinline__ void cv_table() {
  const int tid = tid_opaque() & 127, r = (tid & 31) >> 2, q = tid & 3;
  int t = 16 * (2 * (r < 4 ? q : 4 + ((q + 1) & 3)) + ((r >> 1) & 1)) + 4 * (tid >> 5) + 2 * (r & 1);
#pragma unroll 1
  for (int i = 0; i < 3; i++) {
    uint32_t v = 0;
#pragma unroll 1
    for (int x = 0; x < 3; x++, t += 256) {
      const int T = t / 160, tl = t - T * 160;
      const int qq = (T >= NT1 - 1) ? (tl >> 5) : (tl / 40);
      int ck = 20 * T + ((tl - qq * ((T >= NT1 - 1) ? 32 : 40)) >> 1);
      ck ^= (ck >> 2) & 6;
      v |= (uint32_t)((ck * 4 + qq) & 1023) << (10 * x + 2);
    }
    sts32(sb + SO_OFF + 512 * i + 4 * tid, v);
  }
}
__device__ __forceinline__ void conv_channel(int slot, const CvCtx& c) {
  const uint32_t cb = sb + CV_OFF + slot * CV_B;
  float acc[64];
  CvPipe s;
  s.Ap = s.Ep = 0u;
  uint32_t A[4][4];
#pragma unroll
  for (int i = 0; i < 64; i++) acc[i] = 0.f;
  if (slot == 4) mbar_wait(bars + 8 * B_CVDONE);
  mbar_wait(bars + 8 * (B_CVFULL + slot));
  cv_raw<0>(A, cb + c.koff);
  {
    const uint32_t w0 = lds32(cb + CV_K);
    const uint32_t wp = __byte_perm(pack_bf16(bf_lo(w0) + __uint_as_float(lds32(sb + EP_OFF + 4 * slot)), 0.f), w0, 0x7610);
    if (c.koff == CV_K) A[0][0] = wp;
    if (c.koff == CV_K - 4) A[0][1] = wp;
    if (c.koff == CV_K - 8) A[0][3] = wp;
  }
  cv_form(A, 0x5432u);
  cv_copy<0>(acc);
  cv_step<0>(acc, A, s, c, cb, cv_stage(slot));
  fence_async_smem();
  mbar_arrive(bars + 8 * (B_CVDONE + slot));
}

__device__ __forceinline__ void kv_issue(const Params& p, int c, int m2, int dg) {
  const uint32_t fb = bars + 8 * (B_KV + c);
  mbar_expect_tx(fb, KV_PIECE);
  tma3(sb + KS_OFF + c * KV_PIECE, &p.mK, 160 * dg + 32 * c, 64 * m2 - 3, 0, fb);
  tma3(sb + KS_OFF + c * KV_PIECE + 4864, &p.mV, 160 * dg + 32 * c, 64 * m2 - 1, 0, fb);
}
__device__ __forceinline__ void kv_tile(int m, int c, int y, uint32_t (&o)[4][4]) {
  const int lane = tid_opaque() & 31, tg = lane & 3, pr = 8 * (y ^ (tg >> 1)) + (lane >> 2);
  const uint32_t pb = sb + KS_OFF + c * KV_PIECE + 4 * pr;
  const uint32_t ka = pb + tg * 1216, va = pb + 4864 + tg * 1088 + 64;
  const uint32_t kh = (m == 0 && tg > 0) ? ka - 192 : ka;
  uint32_t kk[19], u[16];
  const float4 t = lds128f(sb + TAP_OFF + 256 * c + 16 * pr);
#pragma unroll
  for (int i = 0; i < 19; i++) { kk[i] = lds32((i < 3 ? kh : ka) + i * 64); if (i >= 3) u[i - 3] = lds32(va + (i - 3) * 64); }
  const uint32_t dst = sb + KS_OFF + c * KV_PIECE + pr * 64 + tg * 16;
  if (y) {
    __syncwarp();
#pragma unroll
    for (int x = 0; x < 4; x++) sts128((dst ^ 512) + x * 1024, make_uint4(o[x][0], o[x][1], o[x][2], o[x][3]));
  }
  const uint32_t w0 = __byte_perm(__float_as_uint(t.x), __float_as_uint(t.z), 0x5410), w1 = __byte_perm(__float_as_uint(t.x), __float_as_uint(t.z), 0x7632);
  const uint32_t w2 = __byte_perm(__float_as_uint(t.y), __float_as_uint(t.w), 0x5410), w3 = __byte_perm(__float_as_uint(t.y), __float_as_uint(t.w), 0x7632);
#pragma unroll
  for (int i = 0; i < 16; i++) {
    uint32_t a = hmul2(kk[i], w3);
    a = hadd2(a, hmul2(kk[i + 1], w2)); a = hadd2(a, hmul2(kk[i + 2], w1)); a = hadd2(a, hmul2(kk[i + 3], w0));
    u[i] = hmul2(a, u[i]);
  }
#pragma unroll
  for (int x = 0; x < 4; x++) {
#pragma unroll
    for (int qq = 0; qq < 4; qq++) o[x][qq] = __byte_perm(u[15 - 4 * qq - (x & 2)], u[14 - 4 * qq - (x & 2)], (x & 1) ? 0x7632 : 0x5410);
    if (y) sts128(dst + x * 1024, make_uint4(o[x][0], o[x][1], o[x][2], o[x][3]));
  }
}
__device__ __forceinline__ void ln_finish(float s1, float s2, float& mean, float& rstd) {
  mean = s1 * (1.f / 640.f);
  const float v = fmaxf(fmaf(-mean, mean, s2 * (1.f / 640.f)), 0.f) + 1e-5f;
  asm("rsqrt.approx.ftz.f32 %0, %1;" : "=f"(rstd) : "f"(v));
}
__device__ __forceinline__ void stat_table(int T1, unsigned want, int l, int g, const uint4* x0, const uint4* x1, float (&xa)[2], float (&xb)[2]) {
  const int n = 32 * g + (tid_opaque() & 31);
  const uint4* rp = &g_stats[8 * l * SEQ + min(160 * T1 + n, SEQ - 1)];
  float a[4], b[4];
  uint32_t it = 0;
  while (true) {
    bool ok = true;
#pragma unroll
    for (int i = 0; i < 4; i++) ok &= (rec_ld(rp + SEQ * i, a[i], b[i]) == want);
    ok &= rec_ld(x0, xa[0], xb[0]) == want;
    ok &= rec_ld(x1, xa[1], xb[1]) == want;
    if (__all_sync(0xffffffffu, ok)) break;
    trap_if(++it > SPIN_LIMIT);
  }
  float m, rs;
  ln_finish((a[0] + a[1]) + (a[2] + a[3]), (b[0] + b[1]) + (b[2] + b[3]), m, rs);
  sts64f(sb + STAB_OFF + n * 8, rs, -m * rs);
}
__device__ __forceinline__ void stats_reduce(float (&a)[2], float (&b)[2], float (&mean)[2], float (&rstd)[2]) {
#pragma unroll
  for (int o = 1; o < 4; o <<= 1)
#pragma unroll
    for (int h = 0; h < 2; h++) { a[h] += __shfl_xor_sync(0xffffffffu, a[h], o); b[h] += __shfl_xor_sync(0xffffffffu, b[h], o); }
#pragma unroll
  for (int h = 0; h < 2; h++) ln_finish(a[h], b[h], mean[h], rstd[h]);
}

template <bool FIRST>
__device__ __forceinline__ void stats_publish(int which, int n0, int dg, unsigned tag, const float (&acc)[80]) {
  const int q = tid_opaque() & 3, h = q & 1;
  float s1[2] = {0.f, 0.f}, s2[2] = {0.f, 0.f}, t1[2] = {0.f, 0.f}, t2[2] = {0.f, 0.f};
#pragma unroll
  for (int j = 0; j < 20; j++)
#pragma unroll
    for (int y = 0; y < 2; y++) {
      const float a = acc[4 * j + 2 * y], b = acc[4 * j + 2 * y + 1];
      s1[y] += a; t1[y] += b; s2[y] = fmaf(a, a, s2[y]); t2[y] = fmaf(b, b, t2[y]);
    }
#pragma unroll
  for (int y = 0; y < 2; y++) { s1[y] += t1[y]; s2[y] += t2[y]; }
  float a = (h ? s1[1] : s1[0]) + __shfl_xor_sync(0xffffffffu, h ? s1[0] : s1[1], 1);
  float b = (h ? s2[1] : s2[0]) + __shfl_xor_sync(0xffffffffu, h ? s2[0] : s2[1], 1);
  a += __shfl_xor_sync(0xffffffffu, a, 2);
  b += __shfl_xor_sync(0xffffffffu, b, 2);
  if (FIRST) {
    rec_st(&g_stats[((q >> 1) * 4 + dg) * SEQ + n0 + 8 * h], a, b, q < 2 ? tag : tag - 1);
    rec_st(&g_stats[((q >> 1) * 4 + 8 + dg) * SEQ + n0 + 8 * h], a, b, tag - 1);
  } else if (q < 2) rec_st(&g_stats[(which * 4 + dg) * SEQ + n0 + 8 * h], a, b, tag);
}
__device__ __forceinline__ void stats_get(int which, int n0, unsigned tag, float (&mean)[2], float (&rstd)[2]) {
  const uint4* p0 = &g_stats[(which * 4 + (tid_opaque() & 3)) * SEQ + n0];
  float a[2], b[2];
  uint32_t it = 0;
  while (true) {
    const unsigned t0 = rec_ld(p0, a[0], b[0]), t1 = rec_ld(p0 + 8, a[1], b[1]);
    if (__all_sync(0xffffffffu, t0 == tag && t1 == tag)) break;
    trap_if(++it > SPIN_LIMIT);
  }
  stats_reduce(a, b, mean, rstd);
}
__device__ __forceinline__ void x0_load(float (&acc)[80]) {
  const int t = tid_opaque() & 127;
  const uint32_t xa = sb + XT_OFF + (16 * (t >> 5) + ((t & 31) >> 2)) * 320 + 8 * (t & 3);
  mbar_wait(bars + 8 * B_XT);
#pragma unroll
  for (int h = 0; h < 2; h++)
#pragma unroll
    for (int J = 0; J < 10; J++) {
      const float2 v = lds64f(xa + h * 2560 + 32 * J);
      const uint32_t x = __float_as_uint(v.x), y = __float_as_uint(v.y);
      acc[8 * J + 2 * h] = bf_lo(x); acc[8 * J + 2 * h + 1] = bf_hi(x);
      acc[8 * J + 4 + 2 * h] = bf_lo(y); acc[8 * J + 4 + 2 * h + 1] = bf_hi(y);
    }
}

template <bool FROM_X0>
__device__ __forceinline__ void dskip_init(float (&acc)[80], const float (&mean)[2], const float (&rstd)[2]) {
  const int t = tid_opaque() & 127;
  const uint32_t xa = sb + XT_OFF + (16 * (t >> 5) + ((t & 31) >> 2)) * 320 + 8 * (t & 3), da = sb + DTAB_OFF + 8 * (t & 3);
  float2 dw[10], xv[10][2];
#pragma unroll
  for (int J = 0; J < 2; J++) { dw[J] = lds64f(da + 32 * J); if (FROM_X0) { xv[J][0] = lds64f(xa + 32 * J); xv[J][1] = lds64f(xa + 2560 + 32 * J); } }
#pragma unroll
  for (int J = 0; J < 10; J++) {
    if (J + 2 < 10) { dw[J + 2] = lds64f(da + 32 * (J + 2)); if (FROM_X0) { xv[J + 2][0] = lds64f(xa + 32 * (J + 2)); xv[J + 2][1] = lds64f(xa + 2560 + 32 * (J + 2)); } }
#pragma unroll
    for (int x = 0; x < 8; x++) {
      const int h = (x >> 1) & 1;
      const uint32_t dwd = __float_as_uint(x < 4 ? dw[J].x : dw[J].y);
      const float tt = fmaf(rstd[h], (x & 1) ? bf_hi(dwd) : bf_lo(dwd), 1.f);
      float a = acc[8 * J + x];
      if (FROM_X0) { const uint32_t xw = __float_as_uint(x < 4 ? xv[J][h].x : xv[J][h].y); a = (x & 1) ? bf_hi(xw) : bf_lo(xw); }
      acc[8 * J + x] = FROM_X0 ? (a - mean[h]) * tt : fmaf(a, tt, -mean[h] * tt);
    }
  }
}

__global__ void __launch_bounds__(512, 1) fused_kernel(const __grid_constant__ Params p) {
  extern __shared__ __align__(1024) uint8_t smem_raw[];
  const int tid = threadIdx.x, lane = tid & 31;
  const int wid = __shfl_sync(0xffffffffu, tid >> 5, 0), wg = wid >> 2;
  unsigned smid; asm volatile("mov.u32 %0, %%smid;" : "=r"(smid));
  const int role = p.role[min(smid, 131u)];
  if (wid == 12) {
    const bool el = elect_one();
    if (el) {
      asm volatile("prefetch.tensormap [%0];" ::"l"(&p.mB) : "memory");
      asm volatile("prefetch.tensormap [%0];" ::"l"((role & 15) == NT1 - 1 ? &p.mXl : &p.mX) : "memory");
#pragma unroll
      for (int k = 0; k < S1; k++) mbar_init(bars + 8 * (B_G1FULL + k), 1);
#pragma unroll
      for (int k = 0; k < 6; k++) mbar_init(bars + 8 * (B_XT + k), 1);
      asm volatile("fence.mbarrier_init.release.cluster;" ::: "memory");
    }
    if (role >= 0) {
      __syncwarp();
      asm volatile("bar.arrive 5, 288;" ::: "memory");
      const Role R = unpack_role(role);
      if (elect_one()) {
        TS(45);
#pragma unroll 1
        for (int k = 0; k < S1; k++) {
          const uint32_t fb = bars + 8 * (B_G1FULL + k);
          mbar_expect_tx(fb, G1_STAGE);
          tma4(sb + k * G1_STAGE + G1_XOFF, R.last ? &p.mXl : &p.mX, 64 * k, 0, 0, R.last ? 0 : 80 * R.T1, fb);
          tma5(sb + k * G1_STAGE, &p.mB, 64 * k, 0, 0, 4 * R.side, 2 * R.GP, fb);
          if (PFD) asm volatile("prefetch.tensormap [%0];" ::"l"(&p.mK + k) : "memory");
        }
        if (R.has2) {
          mbar_expect_tx(bars + 8 * B_XT, 20480);
#pragma unroll 1
          for (int h = 0; h < 2; h++) {
            const int ng = 8 * R.m2 + 4 * h, T = ng / 20;
            tma4(sb + XT_OFF + h * 10240, T == NT1 - 1 ? &p.mXtl : &p.mXt, 160 * R.dg, 0, 0, T == NT1 - 1 ? ng - 240 : ng + 60 * T, bars + 8 * B_XT);
          }
#pragma unroll 1
          for (int c = 0; c < KV0; c++) kv_issue(p, c, R.m2, R.dg);
        }
        TS(44);
      }
      __syncwarp();
      bar_sync(6, 64);
    }
  }
  trap_if(smid >= 132 || smem_u32(smem_raw) != sb);
  if (role < 0) {
    if (wid == 0) {
      const unsigned tag = ld_rlx(g_epoch);
      uint32_t it = 0;
      while (!__all_sync(0xffffffffu, (int)(ld_rlx(&g_hcnt[(lane & 7) * 32]) - 40 * tag) >= 0)) { __nanosleep(500); trap_if(++it > SPIN_LIMIT); }
    }
    return;
  }
  float mean0[2] = {0.f, 0.f}, rstd0[2] = {0.f, 0.f};
  if (wg == 2 || wid == 14) {
    ROLE(role)
    const int c = wid == 14 ? 4 : wid - 8;
    const unsigned tag = ld_rlx(g_epoch);
    if (has2) {
      uint2 bv[2][5];
#pragma unroll
      for (int x = 0; x < 2; x++)
#pragma unroll
        for (int i = 0; i < 5; i++) bv[x][i] = ldv64((const uint2*)((x ? p.bim : p.bre) + (cch0 + 32 * c) * DM) + lane + 32 * i);
      float sv[2];
#pragma unroll
      for (int x = 0; x < 2; x++) {
        float a = 0.f;
#pragma unroll
        for (int i = 0; i < 5; i++) a += (bf_lo(bv[x][i].x) + bf_hi(bv[x][i].x)) + (bf_lo(bv[x][i].y) + bf_hi(bv[x][i].y));
        sv[x] = a;
      }
#pragma unroll
      for (int o = 16; o > 0; o >>= 1) { sv[0] += __shfl_xor_sync(0xffffffffu, sv[0], o); sv[1] += __shfl_xor_sync(0xffffffffu, sv[1], o); }
      if (lane < 2) rec_st(&g_sB[(cch0 + 32 * c) * 2 + lane], sv[0], sv[1], tag);
      if (tid == 256) TS(47);
      __syncwarp();
      bar_sync(8, 192);
      if (wg == 2) {
        float xs[80];
        x0_load(xs);
        stats_publish<true>(0, 64 * m2 + 16 * c + (lane >> 2), dg, tag, xs);
        if (tid == 256) TS(31);
      }
      mbar_wait(bars + 8 * B_EP);
      mbar_wait(bars + 8 * (B_KV + c));
      mbar_wait(bars + 8 * (B_G1DONE + PAUSE_K - 1));
      if (tid == 448) TS(52);
      uint32_t o[4][4] = {};
#pragma unroll 1
      for (int y = 0; y < 2; y++) kv_tile(m2, c, y, o);
      fence_async_smem();
      __syncwarp();
      if (lane == 0) {
        mbar_arrive(bars + 8 * B_PREP);
        bulk_s2g(g_kv + (dg * 32 + m2) * 20480 + c * 4096, sb + KS_OFF + c * KV_PIECE, 4096);
        asm volatile("cp.async.bulk.commit_group;" ::: "memory");
      }
      __syncwarp();
      if (tid == 448) TS(51);
    } else bar_sync(8, 192);
    {
      const uint4* x0 = wg == 2 ? &g_stats[(lane & 3) * SEQ + (has2 ? 64 * m2 : 0) + 16 * c + (lane >> 2)] : &g_sB[(128 * GP + 32 * side + lane) * 2];
      float xa[2], xb[2];
      stat_table(T1, tag, 0, c, x0, x0 + (wg == 2 ? 8 : 128), xa, xb);
      if (wg == 2) stats_reduce(xa, xb, mean0, rstd0);
      else {
#pragma unroll
        for (int i = 0; i < 2; i++) sts64f(sb + CTAB_OFF + (32 * i + lane) * 24 + 16, p.swap ? xb[i] : xa[i], p.swap ? xa[i] : xb[i]);
      }
      mbar_arrive(bars + 8 * B_STAB);
      if (tid == 448) TS(26);
    }
    if (has2) {
      if (lane == 0) {
        asm volatile("cp.async.bulk.wait_group 0;" ::: "memory");
        fence_async_global();
        mbar_arrive(bars + 8 * B_PREP2);
      }
      __syncwarp();
    }
  } else if (wid == 15) {
    ROLE(role)
    const int ch = 128 * GP + 32 * side + lane;
    uint32_t r0 = ldv16(p.lre + ch), r1 = ldv16(p.lim + ch), r2 = ldv16(p.logdt + ch);
    const uint32_t r3 = ldv16(p.lre + ch + 64), r4 = ldv16(p.lim + ch + 64), r5 = ldv16(p.logdt + ch + 64);
#pragma unroll 1
    for (int i = 0; i < 2; i++) {
      const float lr = bf_lo(r0), li = bf_lo(r1);
      const float dt = __bfloat162float(__float2bfloat16_rn(expf(bf_lo(r2))));
      const float mag = expf(dt * lr);
      float sn, cs; sincospif(dt * li * 0.31830988618379067f, &sn, &cs);
      const float ar = mag * cs, ai = mag * sn;
      const float inv = 2.f / (lr * lr + li * li);
      const uint32_t ad = sb + CTAB_OFF + (32 * i + lane) * 24;
      sts64f(ad, ar, ai);
      sts64f(ad + 8, ((ar - 1.f) * lr + ai * li) * inv, (ai * lr - (ar - 1.f) * li) * inv);
      r0 = r3; r1 = r4; r2 = r5;
    }
    if (lane == 0) TS(46);
    __syncwarp();
    bar_sync(7, 64);
    mbar_arrive(bars + 8 * B_CTAB);
  } else if (wid == 13) {
    ROLE(role)
    uint4 tv[3];
    const uint32_t e0 = ld_rlx(g_epoch);
    const uint32_t e1 = ldv16(p.ssmD + min(cch0 + 32 * lane, 639));
    const uint4 dv = ldv128((const uint4*)(p.dskip + 160 * dg) + min(lane, 19));
#pragma unroll
    for (int i = 0; i < 3; i++) tv[i] = ldv128((const uint4*)(p.shiftk + 640 * dg) + min(lane + 32 * i, 79));
    sts128(sb + DTAB_OFF + 16 * min(lane, 19), dv);
#pragma unroll
    for (int i = 0; i < 3; i++) sts128(sb + TAP_OFF + 16 * min(lane + 32 * i, 79), tv[i]);
    if (lane < 7) sts32(sb + EP_OFF + 4 * lane, lane < 5 ? e1 << 16 : (lane == 5 ? e0 : 0u));
    __syncwarp();
    bar_sync(9, 64);
    mbar_arrive(bars + 8 * B_CTAB);
    if (lane == 0) { mbar_arrive(bars + 8 * B_EP); TS(53); }
    if (has2) {
      mbar_wait(bars + 8 * B_PREP2);
      if (lane < 4) red_rel(&g_kvcnt[(dg * 4 + lane) * 32]);
      __syncwarp();
      if (lane == 0) { mbar_arrive(bars + 8 * B_PUB); TS(30); }
    }
  } else if (wid != 12) {
    if (elect_one()) {
      if (wid < 7) {
        const int b0 = wid < 4 ? 4 + 19 * wid : 85 + 21 * (wid - 4), cnt = wid < 4 ? 2 : 1;
#pragma unroll
        for (int i = 0; i < 21; i++) mbar_init(bars + 8 * (b0 + i), cnt);
      } else {
#pragma unroll
        for (int i = 0; i < 12; i++) mbar_init(bars + 8 * (B_CVDONE + i), (i == 5 || i == 6) ? 160 : 128);
        mbar_init(bars + 8 * B_CTAB, 192); mbar_init(bars + 8 * B_PREP, 5); mbar_init(bars + 8 * B_PREP2, 5);
      }
      asm volatile("fence.mbarrier_init.release.cluster;" ::: "memory");
    }
    __syncwarp();
    bar_sync(5, 288);
    if (wid == 2) asm volatile("bar.arrive 8, 192;\nbar.arrive 6, 64;\nbar.arrive 9, 64;\nbar.arrive 7, 64;" ::: "memory");
    if (tid == 128) TS(0);
    if (wg == 1) { cv_table(); mbar_arrive(bars + 8 * B_CTAB); }
  }

  if (wid == 12) {
    ROLE(role)
    uint32_t dst = sb;
#pragma unroll 1
    for (int k = S1; k < 10; k++) {
      const uint32_t fb = bars + 8 * (B_G1FULL + k);
      mbar_wait(bars + 8 * (B_G1DONE + k - S1));
      if (elect_one()) {
        mbar_expect_tx(fb, 20480);
        tma4(dst + G1_XOFF, last ? &p.mXl : &p.mX, 64 * k, 0, 0, last ? 0 : 80 * T1, fb);
        mbar_expect_tx(fb, 16384);
        tma5(dst, &p.mB, 64 * k, 0, 0, 4 * side, 2 * GP, fb);
        if (has2 && k - S1 + KV0 < 5) kv_issue(p, k - S1 + KV0, m2, dg);
      }
      dst += G1_STAGE; if (k == 2 * S1 - 1) dst = sb;
    }
  } else if (wid == 15 && (role >> 16)) {
    ROLE(role)
    if (TPF >= 0) {
      mbar_wait(bars + 8 * (B_KV + TPF));
      if (elect_one()) {
#pragma unroll
        for (int c = 0; c < 5; c++) l2_prefetch(p.ssmk + (cch0 + 32 * c) * SEQ, 4096);
        if (CPF) { l2_prefetch(p.cre + (160 * dg + 5 * m2) * DM, 6400); l2_prefetch(p.cim + (160 * dg + 5 * m2) * DM, 6400); }
      }
    }
    mbar_wait(bars + 8 * B_PREP2);
    if (lane < 10) sts128(sb + CV_OFF + (lane >> 1) * CV_B + CV_K - 32 + 16 * (lane & 1), make_uint4(0, 0, 0, 0));
    fence_async_smem();
    __syncwarp();
    const unsigned tag = lds32(sb + EP_OFF + 20);
    if (TAPW) mbar_wait(bars + 8 * B_PUB);
    if (elect_one()) {
#pragma unroll 1
      for (int c = 0; c < 5; c++) {
        if (c == 0) asm volatile("prefetch.tensormap [%0];" ::"l"(&p.mU) : "memory");
        mbar_expect_tx(bars + 8 * (B_CVFULL + c), 4096 + 2 * CV_PL);
        bulk_g2s(sb + CV_OFF + c * CV_B + CV_K, p.ssmk + (cch0 + 32 * c) * SEQ, 4096, bars + 8 * (B_CVFULL + c));
      }
    }
    mbar_wait(bars + 8 * B_PUB);
    cnt_poll(&g_kvcnt[(dg * 4 + (m2 >> 3)) * 32], 32 * tag);
    fence_async_global();
    if (elect_one()) {
      TS(28);
#pragma unroll
      for (int c = 0; c < 5; c++)
        tma5(sb + CV_OFF + c * CV_B + CV_U, &p.mU, 0, -3, 2 * c, 16 * (m2 & 1) + (m2 >> 1), dg, bars + 8 * (B_CVFULL + c));
#pragma unroll
      for (int i = 0; i < 3; i++) asm volatile("prefetch.tensormap [%0];" ::"l"(&p.mCre + i) : "memory");
      TS(54);
    }
    __syncwarp();
  }
  {
    const int w = wid & 3;
    if (wg == 2 && !(role >> 16)) {
      float xa[2], xb[2];
      mbar_wait(bars + 8 * (B_G1FULL + 11));
      stat_table(role & 15, lds32(sb + EP_OFF + 20), 1, w, g_stats, g_stats, xa, xb);
      mbar_arrive(bars + 8 * (B_STAB + 1));
    }
#pragma unroll 1
    for (int l = 0; l < 2; l++) {
      if (wg < 2) {
        float acc[80];
#pragma unroll
        for (int i = 0; i < 80; i++) acc[i] = 0.f;
        ROLE(role)
        const int tid = tid_opaque(), r = (tid & 31) >> 2, q = tid & 3;
        const int ch = 128 * GP + 64 * wg + 32 * side + 8 * w + r;
        const uint32_t ca = sb + CTAB_OFF + (32 * wg + 8 * w + r) * 24;
        float2 lam = make_float2(0.f, 0.f), p8 = lam, p16 = lam, pL = lam, p2L = lam;
        fence_regs(acc);
        {
          const uint32_t alo0 = (l == 0 ? desc_lo(sb, 16) : desc_lo(sb + G2_WOFF, 16)) + wg * 512;
          const uint32_t blo0 = l == 0 ? desc_lo(sb + G1_XOFF, 16) : desc_lo(sb + X1_OFF, 128);
          const uint32_t bhi = l == 0 ? desc_hi(1024, 1) : desc_hi(1024, 0), xstep = l == 0 ? 2 : 16;
          const uint32_t astep = l == 0 ? G1_STAGE >> 4 : 1024, bstep = l == 0 ? G1_STAGE >> 4 : 1280, aend = alo0 + (S1 + l) * astep;
          uint32_t alo = alo0, blo = blo0;
          uint32_t fb = bars + 8 * (B_G1FULL + 10 * l);
          mbar_wait(fb);
          if (tid == 0) TS(1 + 8 * l);
#pragma unroll 1
          for (int k = 0; k < 10; k++) {
            uint32_t ok; const uint32_t nb = k < 9 ? fb + 8 : fb;
            wgmma_fence();
#pragma unroll
            for (int kk = 0; kk < 4; kk++) {
              wgmma_n160<0>(acc, alo + kk * 2, desc_hi(1024, 1), blo + kk * xstep, bhi);
              if (kk == 0) ok = mbar_test(nb);
              if (kk == STG_KK && k == 9 && tid == 0) mbar_arrive(bars + 8 * (B_STG + l));
            }
            wgmma_commit();
            alo += astep; blo += bstep;
            if (blo == desc_lo(sb + G_OFF, 128)) blo = desc_lo(sb, 128);
            if (alo == aend) { alo = alo0; blo = blo0; }
            wgmma_wait<1>();
            if (k > 0 && (tid & 127) == 0) mbar_arrive(fb + 8 * (B_G1DONE - B_G1FULL - 1));
            if (!ok) mbar_wait(nb);
            if (wg == 1 && k == (l ? 8 - STG_D : 9 - STG0)) mbar_wait(bars + 8 * (B_STG + l));
            if (k == 3) {
              mbar_wait(bars + 8 * B_CTAB);
              lam = lds64f(ca);
              if (l == 0 && q < 2) rec_st(&g_E[(q * NT1 + T1) * DM + ch], 0.f, 0.f, lds32(sb + EP_OFF + 20) - 1);
              if (p.swap) lam.y = -lam.y;
              const float2 p2 = cmul(lam, lam), p4 = cmul(p2, p2);
              p8 = cmul(p4, p4); p16 = cmul(p8, p8);
              pL = cmul(p16, p16);
              if (!last) pL = cmul(pL, p8);
              p2L = cmul(pL, pL);
            }
            if (k == PAUSE_K && has2) mbar_wait(bars + 8 * B_PREP);
            fb += 8;
          }
        }
        mbar_wait(bars + 8 * (B_STAB + l));
        const float2 sB = lds64f(ca + 16);
        const unsigned tag = lds32(sb + EP_OFF + 20);
        wgmma_wait<0>();
        fence_regs(acc);
        if ((tid & 127) == 0) { mbar_arrive(bars + 8 * (B_G1DONE + 10 * l + 9)); TS(wg ? 17 + l : 2 + 8 * l); }
        float2 ec[3];
#pragma unroll
        for (int jj = 0; jj < 8; jj++)
#pragma unroll
          for (int y = 0; y < 3; y++) {
            if (y == 2 && (jj & 1)) continue;
            const int j = y == 2 ? 16 + (jj >> 1) : 8 * y + jj;
            const float4 st = lds128f(sb + STAB_OFF + (8 * j + 2 * q) * 8);
            acc[4 * j + 0] = fmaf(acc[4 * j + 0], st.x, st.y * sB.x);
            acc[4 * j + 2] = fmaf(acc[4 * j + 2], st.x, st.y * sB.y);
            acc[4 * j + 1] = fmaf(acc[4 * j + 1], st.z, st.w * sB.x);
            acc[4 * j + 3] = fmaf(acc[4 * j + 3], st.z, st.w * sB.y);
            ec[y] = jj == 0 ? make_float2(acc[4 * j + 0], acc[4 * j + 2]) : cfma(lam, ec[y], make_float2(acc[4 * j + 0], acc[4 * j + 2]));
            ec[y] = cfma(lam, ec[y], make_float2(acc[4 * j + 1], acc[4 * j + 3]));
          }
        float2 e = cfma(p16, ec[0], ec[1]);
        if (!last) e = cfma(p8, e, ec[2]);
        {
          float2 v = make_float2(__shfl_up_sync(0xffffffffu, e.x, 1, 4), __shfl_up_sync(0xffffffffu, e.y, 1, 4));
          if (q >= 1) e = cfma(pL, v, e);
          v = make_float2(__shfl_up_sync(0xffffffffu, e.x, 2, 4), __shfl_up_sync(0xffffffffu, e.y, 2, 4));
          if (q >= 2) e = cfma(p2L, v, e);
        }
        if (!last && q == 3) rec_st(&g_E[(l * NT1 + T1) * DM + ch], e.x, e.y, tag);
        if (tid == 0) TS(3 + 8 * l);
        float2 ex = make_float2(__shfl_up_sync(0xffffffffu, e.x, 1, 4), __shfl_up_sync(0xffffffffu, e.y, 1, 4));
        if (q == 0) ex = make_float2(0.f, 0.f);
        const float2 coef = lds64f(ca + 8), lamc = make_float2(lam.x, p.swap ? lam.y : -lam.y);
        float m00 = coef.x, m01 = -coef.y, m10 = -coef.y, m11 = -coef.x;
        if (p.swap) { m00 = -coef.y; m01 = coef.x; m10 = -coef.x; m11 = -coef.y; }
        float2 pLq, p160q, p640;
        {
          const float2 p80 = last ? cmul(p2L, p16) : p2L, p160 = cmul(p80, p80), p320 = cmul(p160, p160), one = make_float2(1.f, 0.f);
          p640 = cmul(p320, p320);
          pLq = cmul((q & 1) ? pL : one, (q & 2) ? p2L : one);
          p160q = cmul((q & 1) ? p160 : one, (q & 2) ? p320 : one);
        }
        float2 c, ev[3];
        unsigned tg[3];
        const uint4* ep = &g_E[(l * NT1 + T1 - 1 - q) * DM + ch];
#pragma unroll
        for (int j = 0; j < 20; j++) {
          if (j == CPOLL) {
#pragma unroll
            for (int i = 0; i < 3; i++) {
              ev[i] = make_float2(0.f, 0.f); tg[i] = tag;
              if (T1 - 1 - q - 4 * i >= 0) tg[i] = rec_ld(ep - 4 * i * DM, ev[i].x, ev[i].y);
            }
          }
#pragma unroll
          for (int x = 0; x < 2; x++) {
            const float b0 = acc[4 * j + x], b1 = acc[4 * j + 2 + x];
            acc[4 * j + x] = fmaf(b0, m00, b1 * m01);
            acc[4 * j + 2 + x] = fmaf(b0, m10, b1 * m11);
          }
          if (j == CPOLL - 1 || j == 19) asm volatile("" : "+f"(acc[4 * j]), "+f"(acc[4 * j + 1]), "+f"(acc[4 * j + 2]), "+f"(acc[4 * j + 3])::"memory");
        }
        {
          uint32_t it = 0;
          while (__any_sync(0xffffffffu, tg[0] != tag || tg[1] != tag || tg[2] != tag)) {
#pragma unroll
            for (int i = 0; i < 3; i++)
              if (tg[i] != tag) tg[i] = rec_ld(ep - 4 * i * DM, ev[i].x, ev[i].y);
            trap_if(++it > SPIN_LIMIT);
          }
          c = cfma(p640, cfma(p640, ev[2], ev[1]), ev[0]);
          c = cmul(c, p160q);
          c.x += __shfl_xor_sync(0xffffffffu, c.x, 1); c.y += __shfl_xor_sync(0xffffffffu, c.y, 1);
          c.x += __shfl_xor_sync(0xffffffffu, c.x, 2); c.y += __shfl_xor_sync(0xffffffffu, c.y, 2);
        }
        if (tid == 0) TS(4 + 8 * l);
        if (wg == 1 && l >= HOLD0) mbar_wait(bars + 8 * (B_REL + l));
        c = cfma(pLq, c, ex);
        float2 hh = make_float2(fmaf(c.x, m00, c.y * m01), fmaf(c.x, m10, c.y * m11));
        uint8_t* hb = g_h + (size_t)l * (32 * 20 * 8192) + (10 * wg + 2 * GP) * 8192 + (4 * side + w) * 1024 + (tid_opaque() & 31) * 4;
#pragma unroll
        for (int j4 = 0; j4 < 5; j4++) {
          const int ng = 20 * T1 + 4 * j4;
          uint8_t* hp = hb + (size_t)(ng >> 3) * 163840 + (ng & 7) * 128;
#pragma unroll
          for (int jj = 0; jj < 4; jj++) {
            const int j = 4 * j4 + jj;
            const float2 h0 = cfma(lamc, hh, make_float2(acc[4 * j + 0], acc[4 * j + 2]));
            hh = cfma(lamc, h0, make_float2(acc[4 * j + 1], acc[4 * j + 3]));
            if (j4 < 4 || !last) {
              *(uint32_t*)(hp + jj * 128) = pack_bf16(h0.x, hh.x);
              *(uint32_t*)(hp + jj * 128 + 8192) = pack_bf16(h0.y, hh.y);
            }
          }
        }
        mbar_arrive(bars + 8 * (B_HST + 2 * l + wg));
        if (tid == 0) TS(5 + 8 * l);
        if (tid == 128) TS(l ? 25 : 19);
        if (l == 0 && wid == 4) {
          mbar_wait(bars + 8 * B_HST);
          mbar_wait(bars + 8 * (B_HST + 1));
          if ((tid & 31) < 8) h_release((tid >> 2) & 1, T1, tid & 3);
          __syncwarp();
          if (tid == 128) { mbar_arrive(bars + 8 * B_REL); TS(6); }
        }
      }
      if (l == 0) {
        ROLE(role)
        if (has2) {
          CvCtx cc;
          mbar_wait(bars + 8 * B_CTAB);
          cv_setup(cc);
          mbar_wait(bars + 8 * (B_G1DONE + 9));
#pragma unroll 1
          for (int c = (wg + 2) & 3; c < 5; c += 4) conv_channel(c, cc);
          if ((tid & 127) == 0) TS(wg == 2 ? 32 : (wg == 3 ? 50 : 7 + wg));
        }
      }
      if (wg >= 2) break;
    }
    if (wg == 3) {
    ROLE(role)
    const int pw = wid & 3, gpc = 2 * min(m2 >> 3, 3) + (dg >> 1);
    mbar_wait(bars + 8 * B_EP);
    const unsigned tag = lds32(sb + EP_OFF + 20);
    if (pw == 0) {
      if (elect_one()) {
#pragma unroll 1
        for (int l = 0; l < 2; l++) {
          uint32_t dst = sb;
          if (l == 1) {
            dst = sb + G2_WOFF;
#pragma unroll 1
            for (int k = 0; k < 10; k++) {
              mbar_wait(k > 4 ? bars + 8 * (B_G1DONE + 5 + k) : (has2 ? bars + 8 * (B_G2DONE + 14 + min(k, 3)) : bars + 8 * (B_G1DONE + 9)));
              mbar_expect_tx(bars + 8 * (B_G1FULL + 10 + k), 16384);
              tma5(dst, &p.mB, 64 * k, 0, 0, 4 * side, 2 * GP, bars + 8 * (B_G1FULL + 10 + k));
              dst += 16384; if (k == 4) dst = sb + G2_WOFF;
            }
          }
          if (has2) {
            const uint32_t fb2 = bars + 8 * (B_G2FULL + 20 * l), wb2 = bars + 8 * (B_G2DONE + 20 * l - S2);
            dst = sb + G2_WOFF + (WTAIL ? 4 * l * G2_WB : 0);
            int kc = 0;
#pragma unroll 1
            for (int k = 0; k < 20; k++) {
              mbar_wait(k >= S2 ? wb2 + 8 * k : bars + 8 * (l ? B_G1DONE + (WTAIL ? (k < 3 ? 15 + k : 13 + k) : 19) : (k == 5 ? B_XFREE : (k == 6 ? B_SFREE : B_REL))));
              mbar_expect_tx(fb2 + 8 * k, G2_WB);
              tma5(dst, &p.mCre + (k & 1), kc, 0, 0, 0, 10 * dg, fb2 + 8 * k);
              kc += (k & 1) << 7; if (k == 9) kc = 64;
              dst += G2_WB; if (dst == sb + G2_WOFF + S2 * G2_WB) dst = sb + G2_WOFF;
            }
          }
        }
      }
    } else if (pw == 1) {
#pragma unroll 1
      for (int l = 0; l < 2; l++) {
        if (l == 1) {
          mbar_wait(bars + 8 * (has2 ? B_G2DONE + 19 : B_G1DONE + 9));
          if (has2) mbar_wait(bars + 8 * B_UST);
          cnt_poll(&g_ucnt[gpc * 32], 128 * tag);
          fence_async_global();
          if (elect_one()) {
            TS(20);
            const int bytes = last ? 16384 : 20480;
            const uint8_t* src = g_u + T1 * 204800;
            uint32_t dst = sb + X1_OFF;
#pragma unroll 1
            for (int k = 0; k < 10; k++) {
              if (k > 4) mbar_wait(bars + 8 * (B_G1DONE + 5 + k));
              mbar_expect_tx(bars + 8 * (B_G1FULL + 10 + k), bytes);
              bulk_g2s(dst, src, bytes, bars + 8 * (B_G1FULL + 10 + k));
              src += 20480; dst += 20480; if (dst == sb + G_OFF) dst = sb; if (k == 4) dst = sb + X1_OFF;
            }
          }
          __syncwarp();
        }
        if (has2) {
          mbar_wait(bars + 8 * (B_HST + 2 * l));
          mbar_wait(bars + 8 * (B_G1DONE + 10 * l + 9));
          cnt_poll(&g_hcnt[(l * 16 + gpc) * 32], 40 * tag);
          fence_async_global();
          if (elect_one()) {
            TS(21 + 2 * l);
            const uint32_t fb2 = bars + 8 * (B_G2FULL + 20 * l), wb2 = bars + 8 * (B_G2DONE + 20 * l - S2);
            const uint8_t* src = g_h + (l * 32 + m2) * 163840;
            uint32_t dst = sb;
#pragma unroll 1
            for (int k = 0; k < 20; k++) {
              if (k >= 5) mbar_wait(k >= S2 ? wb2 + 8 * k : bars + 8 * B_SFREE);
              if (k == 10) { mbar_wait(bars + 8 * (B_H1 + l)); fence_async_global(); }
              mbar_expect_tx(fb2 + 8 * k, G2_XB);
              bulk_g2s(dst, src, G2_XB, fb2 + 8 * k);
              src += 8192; dst += G2_XB; if (dst == sb + S2 * G2_XB) dst = sb;
            }
          }
          __syncwarp();
        }
      }
    } else if (pw == 2) {
#pragma unroll 1
      for (int l = 0; l < 2; l++) {
        if (l == 1) {
          float xa[2], xb[2];
          mbar_wait(bars + 8 * (B_G1FULL + 11));
          stat_table(T1, tag, 1, 4, g_stats, g_stats, xa, xb);
          mbar_arrive(bars + 8 * (B_STAB + 1));
        }
#pragma unroll 1
        for (int w = 0; w < 2 * l; w++) {
          mbar_wait(bars + 8 * (B_HST + 2 + w));
          if (lane < 4) h_release(2 + w, T1, lane);
          __syncwarp();
          if (lane == 0) { if (w == 0) mbar_arrive(bars + 8 * (B_REL + 1)); TS(w ? 16 : 14); }
        }
        if (l == 0 && has2 && elect_one()) {
#pragma unroll 1
          for (int i = 0; i < 5; i++) {
            const int c = i < 3 ? i : 7 - i;
            mbar_wait(bars + 8 * (B_CVDONE + c));
            bulk_s2g(g_G + (cch0 + 32 * c) * 4096, cv_stage(c), 4096);
          }
          asm volatile("cp.async.bulk.commit_group;" ::: "memory");
          asm volatile("cp.async.bulk.wait_group.read 0;" ::: "memory");
          mbar_arrive(bars + 8 * B_SFREE);
          asm volatile("cp.async.bulk.wait_group 0;" ::: "memory");
          TS(48);
          fence_async_global();
          asm volatile("fence.acq_rel.gpu;" ::: "memory");
#pragma unroll
          for (int i = 0; i < 4; i++) red_rlx(&g_gcnt[(dg * 4 + i) * 32]);
          TS(49);
          mbar_arrive(bars + 8 * (B_GO + 1));
        }
        __syncwarp();
      }
    } else if (has2) {
      mbar_wait(bars + 8 * B_REL);
      if (!CPF && elect_one()) {
        l2_prefetch(p.cre + (160 * dg + 5 * m2) * DM, 6400); l2_prefetch(p.cim + (160 * dg + 5 * m2) * DM, 6400);
      }
      mbar_wait(bars + 8 * (B_HST + 1));
      flag_poll(&g_hcnt[(8 + gpc) * 32], 40 * tag);
      if (lane == 0) { mbar_arrive(bars + 8 * B_H1); TS(22); }
      mbar_wait(bars + 8 * (B_GO + 1));
      flag_poll(&g_gcnt[(dg * 4 + (m2 >> 3)) * 32], 32 * tag);
      fence_async_global();
      if (elect_one()) {
        TS(29);
        mbar_expect_tx(bars + 8 * B_GFULL, 20480);
        tma5(sb + G_OFF, &p.mG, 64 * m2, 0, 0, 0, 10 * dg, bars + 8 * B_GFULL);
      }
      mbar_wait(bars + 8 * (B_HST + 3));
      cnt_poll(&g_hcnt[(24 + gpc) * 32], 40 * tag);
      if (lane == 0) { mbar_arrive(bars + 8 * (B_H1 + 1)); TS(24); }
    }
    } else if (wg == 2 && (role >> 16)) {
      float acc[80];
      float off[2] = {mean0[0], mean0[1]};
      const unsigned tag = lds32(sb + EP_OFF + 20);
      dskip_init<true>(acc, mean0, rstd0);
      mbar_arrive(bars + 8 * B_XFREE);
#pragma unroll 1
      for (int l = 0; l < 2; l++) {
        float mean[2], rstd[2];
        {
          uint32_t alo = desc_lo(sb, 1024), blo = desc_lo(sb + G2_WOFF, 16) + (WTAIL ? l * (G2_WB >> 2) : 0);
          uint32_t fb = bars + 8 * (B_G2FULL + 20 * l);
          fence_regs(acc);
          mbar_wait(bars + 8 * (B_CVDONE + 2));
          mbar_wait(bars + 8 * (B_CVDONE + 3));
          mbar_wait(fb);
          if (tid == 256) TS(33 + 6 * l);
#pragma unroll 1
          for (int k = 0; k < 20; k++) {
            if (l == TSL && (k & 3) == 3 && tid == 256) TS(56 + (k >> 2));
            uint32_t ok; const uint32_t nb = k < 19 ? fb + 8 : fb;
            wgmma_fence();
#pragma unroll
            for (int kk = 0; kk < 4; kk++) {
              wgmma_n160<1>(acc, alo + kk * 128, desc_hi(128, 0), blo + kk * 2, desc_hi(1024, 1));
              if (kk == 0) ok = mbar_test(nb);
            }
            wgmma_commit();
            alo += G2_XB >> 4; blo += G2_WB >> 4;
            if (alo == desc_lo(sb + S2 * G2_XB, 1024)) alo = desc_lo(sb, 1024);
            if (blo == desc_lo(sb + G_OFF, 16)) blo = desc_lo(sb + G2_WOFF, 16);
            wgmma_wait<1>();
            if (k > 0 && tid == 256) mbar_arrive(fb + 8 * (B_G2DONE - B_G2FULL - 1));
            if (!ok) mbar_wait(nb);
            fb += 8;
          }
          wgmma_wait<0>();
          fence_regs(acc);
          if (tid == 256) TS(34 + 6 * l);
          if (tid == 256) mbar_arrive(bars + 8 * (B_G2DONE + 20 * l + 19));
        }
        ROLE(role)
        const int tq = tid_opaque() & 31, n0 = 64 * m2 + 16 * w + (tq >> 2);
        stats_publish<false>(2 * l + 1, n0, dg, tag, acc);
        uint32_t gf[10][4];
        mbar_wait(bars + 8 * B_GFULL);
        const uint32_t ga = sb + G_OFF + (8 * (tq >> 4) + (tq & 7)) * 128 + (((2 * w + ((tq >> 3) & 1)) ^ ((2 * m2) & 6) ^ (tq & 7)) << 4);
#pragma unroll
        for (int J = 0; J < 2; J++) ldsm4t(gf[J], ga + J * 2048);
        if (tid == 256) TS(35 + 6 * l);
        uint8_t* dst[2][2];
#pragma unroll
        for (int h = 0; h < 2; h++) {
          if (l == 0) {
            const int ng = 8 * m2 + 2 * w + h, T = ng / 20;
            uint8_t* ub = g_u + (T * 204800 + (ng - 20 * T) * 1024 + (tq & 2) * 64 + (tq & 28) * 4 + (tq & 1) * 8 + (5 * dg >> 1) * 20480);
            dst[h][1] = ub + ((dg & 1) ? 20480 - 512 : 0);
            dst[h][0] = ub + (dg & 1) * 512;
          } else {
            dst[h][0] = dst[h][1] = (uint8_t*)(p.out + (n_to_t(n0 + 8 * h) * DM + 160 * dg + 4 * (tq & 3)));
          }
        }
        stats_get(2 * l + 1, n0, tag, mean, rstd);
        if (tid == 256) TS(36 + 6 * l);
        off[0] += mean[0]; off[1] += mean[1];
        const float ov[2] = {l ? off[0] : 0.f, l ? off[1] : 0.f};
#pragma unroll
        for (int J = 0; J < 10; J++) {
          if (J + 2 < 10) ldsm4t(gf[J + 2 < 10 ? J + 2 : 0], ga + (J + 2) * 2048);
#pragma unroll
          for (int x = 0; x < 8; x++) {
            const int h = (x >> 1) & 1;
            const uint32_t gwd = gf[J][x >> 1];
            const float t = fmaf(rstd[h], (x & 1) ? bf_hi(gwd) : bf_lo(gwd), 1.f);
            acc[8 * J + x] = fmaf(acc[8 * J + x], t, fmaf(-mean[h], t, ov[h]));
          }
#pragma unroll
          for (int h = 0; h < 2; h++) {
            if (l == 0)
              *(uint2*)(dst[h][(J >> 1) & 1] + (J >> 2) * 20480 + (J & 3) * 256) =
                  make_uint2(pack_bf16(acc[8 * J + 2 * h], acc[8 * J + 2 * h + 1]), pack_bf16(acc[8 * J + 4 + 2 * h], acc[8 * J + 5 + 2 * h]));
            else
              *(float4*)(dst[h][0] + 64 * J) = make_float4(acc[8 * J + 2 * h], acc[8 * J + 2 * h + 1], acc[8 * J + 4 + 2 * h], acc[8 * J + 5 + 2 * h]);
          }
          __syncwarp();
        }
        if (l == 0) {
          bar_sync(3, 128);
          if (tid == 288) { TS(37); mbar_arrive(bars + 8 * B_UST); }
          if (tid < 264) red_rel(&g_ucnt[(tid & 7) * 32]);
          __syncwarp();
          if (tid == 256) TS(38);
          stats_publish<false>(2, n0, dg, tag, acc);
          mbar_wait(bars + 8 * (B_G1FULL + 11));
          float xa[2], xb[2];
          const uint4* x0 = &g_stats[(8 + (tq & 3)) * SEQ + n0];
          stat_table(T1, tag, 1, w, x0, x0 + 8, xa, xb);
          mbar_arrive(bars + 8 * (B_STAB + 1));
          if (tid == 256) TS(27);
          stats_reduce(xa, xb, mean, rstd);
          off[0] += mean[0]; off[1] += mean[1];
          mbar_wait(bars + 8 * (B_HST + 2));
          dskip_init<false>(acc, mean, rstd);
        } else {
          if (tid == 256) {
            TS(43);
            if (m2 == 31 && dg == 3) asm volatile("st.relaxed.gpu.global.u32 [%0], %1;" ::"l"(g_epoch), "r"(tag + 1) : "memory");
          }
        }
      }
    }
  }
}

typedef CUresult (*EncFn)(CUtensorMap*, CUtensorMapDataType, cuuint32_t, void*, const cuuint64_t*, const cuuint64_t*,
                          const cuuint32_t*, const cuuint32_t*, CUtensorMapInterleave, CUtensorMapSwizzle,
                          CUtensorMapL2promotion, CUtensorMapFloatOOBfill);

void encode(EncFn fn, CUtensorMap* m, const void* ptr, int rank, const cuuint64_t* dims, const cuuint64_t* strides, const cuuint32_t* box,
            CUtensorMapSwizzle swz = CU_TENSOR_MAP_SWIZZLE_128B, int prom = 2) {
  cuuint32_t es[5] = {1, 1, 1, 1, 1};
  fn(m, CU_TENSOR_MAP_DATA_TYPE_BFLOAT16, rank, (void*)ptr, dims, strides, box, es, CU_TENSOR_MAP_INTERLEAVE_NONE,
     swz, (CUtensorMapL2promotion)prom, CU_TENSOR_MAP_FLOAT_OOB_FILL_NONE);
}

}

extern "C" void kernel_launch(void* const* d_in, const int* in_sizes, int n_in, void* d_out, int out_size) {
  (void)in_sizes; (void)n_in; (void)out_size;
  Params p;
  typedef const __nv_bfloat16* BP;
  p.x = (BP)d_in[0]; p.lre = (BP)d_in[1]; p.lim = (BP)d_in[2]; p.bre = (BP)d_in[3]; p.bim = (BP)d_in[4];
  p.cre = (BP)d_in[5]; p.cim = (BP)d_in[6]; p.logdt = (BP)d_in[7]; p.dskip = (BP)d_in[8];
  p.k = (BP)d_in[10]; p.v = (BP)d_in[11]; p.shiftk = (BP)d_in[12]; p.ssmk = (BP)d_in[13]; p.ssmD = (BP)d_in[14];
  p.out = (float*)d_out;
  for (int sm = 0; sm < 132; sm++) {
    const int tpc = sm >> 1, side = sm & 1;
    int gpc, gi;
    if (tpc < 32) { gpc = tpc & 7; gi = tpc >> 3; }
    else if (tpc < 60) { gpc = 1 + (tpc - 32) % 7; gi = 4 + (tpc - 32) / 7; }
    else if (tpc < 62) { gpc = tpc - 54; gi = 8; }
    else { gpc = 0; gi = tpc - 58; }
    const int pos = 8 * gpc + gi + (gpc == 7 ? 1 : 0);
    int T1, GP;
    if (pos < 52) { const int hh = pos / 26, x = pos - 26 * hh; T1 = x >> 1; GP = 2 * hh + (x & 1); }
    else { T1 = pos - 52; GP = 4; }
    const int m2 = 8 * (gpc >> 1) + gi, dg = 2 * (gpc & 1) + side;
    p.role[sm] = pos == 65 ? -1 : (T1 | (GP << 4) | (side << 7) | (m2 << 8) | (dg << 14) | ((gi < 8) << 16));
  }
  void* fnp = nullptr;
  cudaDriverEntryPointQueryResult qr;
  cudaGetDriverEntryPoint("cuTensorMapEncodeTiled", &fnp, cudaEnableDefault, &qr);
  EncFn fn = (EncFn)fnp;
  void* gG = nullptr;
  cudaGetSymbolAddress(&gG, g_G);
  void* gKV = nullptr;
  cudaGetSymbolAddress(&gKV, g_kv);
  {
    cuuint64_t dims[5] = {32, 32, 10, 32, 4}, st[4] = {20480, 2048, 64, 655360}; cuuint32_t box[5] = {32, 35, 2, 1, 1};
    encode(fn, &p.mU, gKV, 5, dims, st, box, CU_TENSOR_MAP_SWIZZLE_NONE, 1);
  }
  const cuuint64_t RB = DM * 2;
  {
    p.swap = p.bim < p.bre;
    const char* lo = (const char*)(p.swap ? p.bim : p.bre); const char* hi = (const char*)(p.swap ? p.bre : p.bim);
    cuuint64_t dims[5] = {640, 8, 2, 8, 10}, st[4] = {RB, (cuuint64_t)(hi - lo), 8 * RB, 64 * RB}; cuuint32_t box[5] = {64, 8, 2, 4, 2};
    encode(fn, &p.mB, lo, 5, dims, st, box);
  }
  {
    cuuint64_t dims[5] = {640, 2, 4, 2, 40}, st[4] = {RB, 4 * RB, 2 * RB, 16 * RB}; cuuint32_t box[5] = {64, 2, 4, 2, 10};
    encode(fn, &p.mCre, p.cre, 5, dims, st, box); encode(fn, &p.mCim, p.cim, 5, dims, st, box);
    cuuint64_t dimg[5] = {2048, 2, 4, 2, 40}, stg[4] = {4096, 4 * 4096, 2 * 4096, 16 * 4096};
    encode(fn, &p.mG, gG, 5, dimg, stg, box);
  }
  {
    cuuint64_t dims[4] = {640, 2, 4, 900}, st[3] = {RB, 40 * RB, 2 * RB}; cuuint32_t box[4] = {64, 2, 4, 20};
    encode(fn, &p.mX, p.x, 4, dims, st, box);
    cuuint64_t diml[4] = {640, 2, 4, 16}, stl[3] = {RB, 32 * RB, 2 * RB};
    encode(fn, &p.mXl, p.x + (size_t)1920 * DM, 4, diml, stl, box);
    cuuint32_t boxt[4] = {160, 2, 4, 4};
    encode(fn, &p.mXt, p.x, 4, dims, st, boxt, CU_TENSOR_MAP_SWIZZLE_NONE);
    encode(fn, &p.mXtl, p.x + (size_t)1920 * DM, 4, diml, stl, boxt, CU_TENSOR_MAP_SWIZZLE_NONE);
    cuuint64_t dk[3] = {640, 2000, 4}, sk[2] = {RB, 16 * RB}; cuuint32_t bk[3] = {32, 19, 4}, bv[3] = {32, 17, 4};
    encode(fn, &p.mK, p.k, 3, dk, sk, bk, CU_TENSOR_MAP_SWIZZLE_NONE);
    encode(fn, &p.mV, p.v, 3, dk, sk, bv, CU_TENSOR_MAP_SWIZZLE_NONE);
  }
  cudaFuncSetAttribute(fused_kernel, cudaFuncAttributeMaxDynamicSharedMemorySize, SMEM_BYTES);
  cudaLaunchConfig_t cfg = {};
  cfg.gridDim = dim3(132); cfg.blockDim = dim3(512); cfg.dynamicSmemBytes = SMEM_BYTES; cfg.stream = cudaStreamPerThread;
  cudaLaunchKernelEx(&cfg, fused_kernel, p);
}
```

```cpp
#include <cuda_runtime.h>
#include <cuda.h>
#include <cuda_bf16.h>
#include <stdint.h>

namespace {

constexpr int SEQ = 2048, DM = 640;
constexpr int NT1 = 13;
#define EXP 0
#define WPF1 3
#define WPF2 7
#define CPOLL 10
#define KV0 1
#define TAPLATE 1
#define STG_D 3
#define STG_KK 1
#define HOLD0 1
#define WREL 0
#define UREL 1
#define TSL 1
#define STG0 2
#define WTAIL 1
#define PFD 1
#define TAPW 1
#define TPF 4
#define CPF 0
#define MK0 7
#define MK1 4
#define PACE 180
#define XB0 3
#define PAUSE_K 5
constexpr uint32_t SPIN_LIMIT = 1u << 22;

__device__ __align__(1024) uint8_t g_h[2 * 32 * 20 * 8192];
__device__ __align__(1024) uint8_t g_u[NT1 * 10 * 20480];
__device__ __align__(1024) uint8_t g_kv[DM * 4096];
__device__ __align__(1024) uint8_t g_G[DM * 4096];
__device__ __align__(128) uint4 g_E[2 * NT1 * DM];
__device__ __align__(128) uint4 g_stats[4 * 4 * SEQ];
__device__ __align__(128) uint4 g_sB[DM * 2];
__device__ __align__(128) unsigned g_hcnt[2 * 2 * 8 * 32];
__device__ __align__(128) unsigned g_ucnt[8 * 32];
__device__ __align__(128) unsigned g_kvcnt[16 * 32];
__device__ __align__(128) unsigned g_gcnt[16 * 32];
__device__ __align__(128) unsigned g_epoch[32] = {1};
#define TS(i) do {} while (0)

struct Params {
  CUtensorMap mX, mB, mXl, mK, mV, mXt, mXtl, mCre, mCim, mG, mU;
  const __nv_bfloat16 *x, *lre, *lim, *bre, *bim, *cre, *cim, *logdt, *dskip, *k, *v, *shiftk, *ssmk, *ssmD;
  float* out;
  int swap;
  int role[132];
};

constexpr uint32_t sb = 1024;
constexpr uint32_t G1_STAGE = 36864, G1_XOFF = 16384;
constexpr int S1 = 4;
constexpr uint32_t XT_OFF = 159744, KS_OFF = 180224, KV_PIECE = 9216;
constexpr uint32_t G2_XB = 8192, G2_WB = 20480, G2_WOFF = 57344, G_OFF = 200704;
constexpr uint32_t X1_OFF = 139264;
constexpr int S2 = 7;
constexpr uint32_t CV_OFF = KS_OFF, CV_K = 128, CV_PL = 2240, CV_U = CV_K + 4096, CV_B = KV_PIECE;
constexpr uint32_t MISC = 226304;
constexpr uint32_t BAR_OFF = MISC;
constexpr int B_G1FULL = 0, B_G1DONE = 20, B_G2FULL = 40,
              B_G2DONE = 85, B_GFULL = 125, B_EP = 126, B_H1 = 127  , B_CVFULL = 129  , B_STG = 134  , B_REL = 136  , B_SFREE = 138, B_UST = 142,
              B_GO = 139  , B_PUB = 147,
              B_CVDONE = 148  , B_STAB = 153  , B_XFREE = 155, B_HST = 156  ,
              B_CTAB = 160, B_PREP = 161, B_XT = 162, B_KV = 163  , B_PREP2 = 84;
constexpr uint32_t bars = sb + BAR_OFF;
constexpr uint32_t STAB_OFF = MISC + 1344;
constexpr uint32_t CTAB_OFF = STAB_OFF + 1280;
constexpr uint32_t DTAB_OFF = CTAB_OFF + 1536;
constexpr uint32_t EP_OFF = DTAB_OFF + 320;
constexpr uint32_t SO_OFF = EP_OFF + 32;
constexpr uint32_t TAP_OFF = 147456;
constexpr uint32_t MX0_OFF = TAP_OFF + 1280, MX1_OFF = G_OFF + 20480;
constexpr uint32_t SMEM_BYTES = 232448;
static_assert(SO_OFF + 1536 <= SMEM_BYTES, "smem");

__device__ __forceinline__ void trap_if(bool c) { asm volatile("{\n.reg .pred p;\nsetp.ne.u32 p, %0, 0;\n@p trap;\n}\n" ::"r"((uint32_t)c)); }
__device__ __forceinline__ uint32_t smem_u32(const void* p) { return (uint32_t)__cvta_generic_to_shared(p); }
__device__ __forceinline__ void mbar_init(uint32_t bar, int cnt) { asm volatile("mbarrier.init.shared::cta.b64 [%0], %1;" ::"r"(bar), "r"(cnt) : "memory"); }
__device__ __forceinline__ void mbar_expect_tx(uint32_t bar, int bytes) { asm volatile("mbarrier.arrive.expect_tx.shared::cta.b64 _, [%0], %1;" ::"r"(bar), "r"(bytes) : "memory"); }
__device__ __forceinline__ void mbar_arrive(uint32_t bar) { asm volatile("mbarrier.arrive.shared::cta.b64 _, [%0];" ::"r"(bar) : "memory"); }
__device__ __forceinline__ void mbar_wait(uint32_t bar) {
  asm volatile(
      "{\n.reg .pred p;\n.reg .u32 c;\nmov.u32 c, 0;\n"
      "W_%=:\nmbarrier.try_wait.parity.shared::cta.b64 p, [%0], 0;\n@p bra D_%=;\n"
      "add.u32 c, c, 1;\nsetp.lt.u32 p, c, %1;\n@p bra W_%=;\ntrap;\nD_%=:\n}\n" ::"r"(bar), "n"(SPIN_LIMIT) : "memory");
}
__device__ __forceinline__ uint32_t mbar_test(uint32_t bar) {
  uint32_t ok;
  asm volatile("{\n.reg .pred p;\nmbarrier.test_wait.parity.shared::cta.b64 p, [%1], 0;\nselp.u32 %0, 1, 0, p;\n}\n" : "=r"(ok) : "r"(bar) : "memory");
  return ok;
}
__device__ __forceinline__ void tma3(uint32_t dst, const CUtensorMap* m, int c0, int c1, int c2, uint32_t bar) {
  asm volatile("cp.async.bulk.tensor.3d.shared::cluster.global.mbarrier::complete_tx::bytes [%0], [%1, {%3,%4,%5}], [%2];"
               ::"r"(dst), "l"(m), "r"(bar), "r"(c0), "r"(c1), "r"(c2) : "memory");
}
__device__ __forceinline__ void tma4(uint32_t dst, const CUtensorMap* m, int c0, int c1, int c2, int c3, uint32_t bar) {
  asm volatile("cp.async.bulk.tensor.4d.shared::cluster.global.mbarrier::complete_tx::bytes [%0], [%1, {%3,%4,%5,%6}], [%2];"
               ::"r"(dst), "l"(m), "r"(bar), "r"(c0), "r"(c1), "r"(c2), "r"(c3) : "memory");
}
__device__ __forceinline__ void tma5(uint32_t dst, const CUtensorMap* m, int c0, int c1, int c2, int c3, int c4, uint32_t bar) {
  asm volatile("cp.async.bulk.tensor.5d.shared::cluster.global.mbarrier::complete_tx::bytes [%0], [%1, {%3,%4,%5,%6,%7}], [%2];"
               ::"r"(dst), "l"(m), "r"(bar), "r"(c0), "r"(c1), "r"(c2), "r"(c3), "r"(c4) : "memory");
}
__device__ __forceinline__ void bulk_g2s(uint32_t dst, const void* src, int bytes, uint32_t bar) {
  asm volatile("cp.async.bulk.shared::cluster.global.mbarrier::complete_tx::bytes [%0], [%1], %2, [%3];"
               ::"r"(dst), "l"(src), "r"(bytes), "r"(bar) : "memory");
}
__device__ __forceinline__ void bulk_s2g(void* dst, uint32_t src, int bytes) {
  asm volatile("cp.async.bulk.global.shared::cta.bulk_group [%0], [%1], %2;" ::"l"(dst), "r"(src), "r"(bytes) : "memory");
}
__device__ __forceinline__ void l2_prefetch(const void* src, int bytes) {
  asm volatile("cp.async.bulk.prefetch.L2.global [%0], %1;" ::"l"(src), "r"(bytes) : "memory");
}
__device__ __forceinline__ void wgmma_fence() { asm volatile("wgmma.fence.sync.aligned;" ::: "memory"); }
__device__ __forceinline__ void wgmma_commit() { asm volatile("wgmma.commit_group.sync.aligned;" ::: "memory"); }
template <int N> __device__ __forceinline__ void wgmma_wait() { asm volatile("wgmma.wait_group.sync.aligned %0;" ::"n"(N) : "memory"); }
__host__ __device__ constexpr uint32_t desc_lo(uint32_t addr, uint32_t lbo) { return ((addr & 0x3FFFF) >> 4) | ((lbo >> 4) << 16); }
__host__ __device__ constexpr uint32_t desc_hi(uint32_t sbo, uint32_t swz) { return (sbo >> 4) | (swz << 30); }
__device__ __forceinline__ void bar_sync(int id, int n) { asm volatile("bar.sync %0, %1;" ::"r"(id), "r"(n) : "memory"); }
__device__ __forceinline__ uint32_t lds32(uint32_t a) { uint32_t v; asm volatile("ld.shared.u32 %0, [%1];" : "=r"(v) : "r"(a) : "memory"); return v; }
__device__ __forceinline__ float2 lds64f(uint32_t a) { float2 v; asm volatile("ld.shared.v2.f32 {%0,%1}, [%2];" : "=f"(v.x), "=f"(v.y) : "r"(a) : "memory"); return v; }
__device__ __forceinline__ float4 lds128f(uint32_t a) { float4 v; asm volatile("ld.shared.v4.f32 {%0,%1,%2,%3}, [%4];" : "=f"(v.x), "=f"(v.y), "=f"(v.z), "=f"(v.w) : "r"(a) : "memory"); return v; }
__device__ __forceinline__ void ldsm4t(uint32_t (&r)[4], uint32_t a) {
  asm volatile("ldmatrix.sync.aligned.m8n8.x4.trans.shared.b16 {%0,%1,%2,%3}, [%4];" : "=r"(r[0]), "=r"(r[1]), "=r"(r[2]), "=r"(r[3]) : "r"(a) : "memory");
}
__device__ __forceinline__ uint4 ldv128(const void* a) { uint4 v; asm volatile("ld.global.nc.v4.u32 {%0,%1,%2,%3}, [%4];" : "=r"(v.x), "=r"(v.y), "=r"(v.z), "=r"(v.w) : "l"(a) : "memory"); return v; }
__device__ __forceinline__ uint2 ldv64(const void* a) { uint2 v; asm volatile("ld.global.nc.v2.u32 {%0,%1}, [%2];" : "=r"(v.x), "=r"(v.y) : "l"(a) : "memory"); return v; }
__device__ __forceinline__ uint32_t ldv16(const void* a) { uint32_t v; asm volatile("ld.global.nc.u16 %0, [%1];" : "=r"(v) : "l"(a) : "memory"); return v; }
__device__ __forceinline__ void sts128(uint32_t a, uint4 v) { asm volatile("st.shared.v4.u32 [%0], {%1,%2,%3,%4};" ::"r"(a), "r"(v.x), "r"(v.y), "r"(v.z), "r"(v.w) : "memory"); }
__device__ __forceinline__ void sts32(uint32_t a, uint32_t v) { asm volatile("st.shared.u32 [%0], %1;" ::"r"(a), "r"(v) : "memory"); }
__device__ __forceinline__ void sts64f(uint32_t a, float x, float y) { asm volatile("st.shared.v2.f32 [%0], {%1,%2};" ::"r"(a), "f"(x), "f"(y) : "memory"); }
__device__ __forceinline__ void red_rlx(unsigned* p) { asm volatile("red.relaxed.gpu.global.add.u32 [%0], 1;" ::"l"(p) : "memory"); }
__device__ __forceinline__ void red_rel(unsigned* p) { asm volatile("red.release.gpu.global.add.u32 [%0], 1;" ::"l"(p) : "memory"); }
__device__ __forceinline__ void fence_async_global() { asm volatile("fence.proxy.async.global;" ::: "memory"); }
__device__ __forceinline__ void fence_async_smem() { asm volatile("fence.proxy.async.shared::cta;" ::: "memory"); }
__device__ __forceinline__ void rec_st(uint4* p, float a, float b, unsigned tag) {
  asm volatile("{\n.reg .b128 t;\n.reg .b64 lo, hi;\nmov.b64 lo, {%1,%2};\nmov.b64 hi, {%3,%3};\nmov.b128 t, {lo,hi};\n"
               "st.relaxed.gpu.global.b128 [%0], t;\n}\n" ::"l"(p), "r"(__float_as_uint(a)), "r"(__float_as_uint(b)), "r"(tag) : "memory");
}
__device__ __forceinline__ unsigned rec_ld(const uint4* p, float& a, float& b) {
  unsigned x, y, t;
  asm volatile("{\n.reg .b128 t;\n.reg .b64 lo, hi;\n.reg .b32 u;\nld.relaxed.gpu.global.b128 t, [%3];\nmov.b128 {lo,hi}, t;\n"
               "mov.b64 {%0,%1}, lo;\nmov.b64 {%2,u}, hi;\n}\n" : "=r"(x), "=r"(y), "=r"(t) : "l"(p) : "memory");
  a = __uint_as_float(x); b = __uint_as_float(y);
  return t;
}
__device__ __forceinline__ unsigned ld_rlx(const unsigned* p) { unsigned v; asm volatile("ld.relaxed.gpu.global.u32 %0, [%1];" : "=r"(v) : "l"(p) : "memory"); return v; }
__device__ __forceinline__ void flag_poll(const unsigned* p, unsigned target) {
  uint32_t it = 0;
  while (!__all_sync(0xffffffffu, (int)(ld_rlx(p) - target) >= 0)) { trap_if(++it > SPIN_LIMIT); }
  asm volatile("fence.acquire.gpu;" ::: "memory");
}
__device__ __forceinline__ void cnt_poll(const unsigned* p, unsigned target) {
  unsigned a = ld_rlx(p); __nanosleep(100);
  unsigned b = ld_rlx(p); __nanosleep(100);
  unsigned c = ld_rlx(p);
  uint32_t it = 0;
  while (true) {
    if (__all_sync(0xffffffffu, (int)(a - target) >= 0)) break;
    a = ld_rlx(p);
    if (__all_sync(0xffffffffu, (int)(b - target) >= 0)) break;
    b = ld_rlx(p);
    if (__all_sync(0xffffffffu, (int)(c - target) >= 0)) break;
    c = ld_rlx(p);
    trap_if(++it > SPIN_LIMIT);
  }
  asm volatile("fence.acquire.gpu;" ::: "memory");
}
__device__ __forceinline__ void h_release(int idx, int T, int i) {
  const int Q = (i & 2) ? (T + 2) / 3 - 1 : T / 3;
  if (Q >= 0 && Q < 4 && ((i & 2) == 0 || T % 3 == 0)) red_rel(&g_hcnt[(idx * 8 + 2 * Q + (i & 1)) * 32]);
}
__device__ __forceinline__ uint32_t pack_bf16(float lo, float hi) {
  uint32_t r; asm("cvt.rn.bf16x2.f32 %0, %1, %2;" : "=r"(r) : "f"(hi), "f"(lo)); return r;
}
__device__ __forceinline__ float bf_lo(uint32_t w) { return __uint_as_float(w << 16); }
__device__ __forceinline__ float bf_hi(uint32_t w) { return __uint_as_float(w & 0xffff0000u); }
__device__ __forceinline__ uint32_t hmul2(uint32_t a, uint32_t b) {
  __nv_bfloat162 r = __hmul2_rn(*(__nv_bfloat162*)&a, *(__nv_bfloat162*)&b); return *(uint32_t*)&r;
}
__device__ __forceinline__ uint32_t hadd2(uint32_t a, uint32_t b) {
  __nv_bfloat162 r = __hadd2_rn(*(__nv_bfloat162*)&a, *(__nv_bfloat162*)&b); return *(uint32_t*)&r;
}
__device__ __forceinline__ float2 cmul(float2 a, float2 b) { return make_float2(a.x * b.x - a.y * b.y, a.x * b.y + a.y * b.x); }
__device__ __forceinline__ float2 cfma(float2 a, float2 b, float2 c) {
  return make_float2(fmaf(a.x, b.x, fmaf(-a.y, b.y, c.x)), fmaf(a.x, b.y, fmaf(a.y, b.x, c.y)));
}
template <int N> __device__ __forceinline__ void fence_regs(float (&a)[N]) {
#pragma unroll
  for (int i = 0; i < N; i++) asm volatile("" : "+f"(a[i])::"memory");
}
__device__ __forceinline__ bool elect_one() {
  uint32_t e; asm volatile("{\n.reg .pred P;\nelect.sync _|P, 0xffffffff;\nselp.u32 %0, 1, 0, P;\n}\n" : "=r"(e)); return e != 0;
}
__device__ __forceinline__ int tid_opaque() { int t; asm volatile("mov.u32 %0, %%tid.x;" : "=r"(t)); return t; }
struct Role { int T1, GP, side, m2, dg, cch0; bool last, has2; };
__device__ __forceinline__ Role unpack_role(int x) {
  Role r; r.T1 = x & 15; r.GP = (x >> 4) & 7; r.side = (x >> 7) & 1; r.m2 = (x >> 8) & 63; r.dg = (x >> 14) & 3;
  r.has2 = (x >> 16) & 1; r.last = r.T1 == NT1 - 1; r.cch0 = 160 * r.dg + r.m2; return r;
}
__device__ __forceinline__ Role fresh_role(int x) { asm volatile("" : "+r"(x)); return unpack_role(__shfl_sync(0xffffffffu, x, 0)); }
#define ROLE(x) const Role R_ = fresh_role(x); const int T1 = R_.T1, GP = R_.GP, side = R_.side, m2 = R_.m2, dg = R_.dg, cch0 = R_.cch0; \
  const bool last = R_.last, has2 = R_.has2; (void)T1; (void)GP; (void)side; (void)m2; (void)dg; (void)cch0; (void)last; (void)has2;
__device__ __forceinline__ int n_to_t(int n) {
  int T = n / 160, nl = n - T * 160;
  int L = (T == NT1 - 1) ? 32 : 40;
  return T * 160 + L * ((nl & 7) >> 1) + 2 * (nl >> 3) + (nl & 1);
}

template<int TA> __device__ __forceinline__ void wgmma_n160(float (&d)[80], uint32_t alo, uint32_t ahi, uint32_t blo, uint32_t bhi){
  asm volatile("{\n.reg .b64 da, db;\nmov.b64 da, {%80,%81};\nmov.b64 db, {%82,%83};\n"
    "wgmma.mma_async.sync.aligned.m64n160k16.f32.bf16.bf16 {%0, %1, %2, %3, %4, %5, %6, %7, %8, %9, %10, %11, %12, %13, %14, %15, %16, %17, %18, %19, %20, %21, %22, %23, %24, %25, %26, %27, %28, %29, %30, %31, %32, %33, %34, %35, %36, %37, %38, %39, %40, %41, %42, %43, %44, %45, %46, %47, %48, %49, %50, %51, %52, %53, %54, %55, %56, %57, %58, %59, %60, %61, %62, %63, %64, %65, %66, %67, %68, %69, %70, %71, %72, %73, %74, %75, %76, %77, %78, %79}, da, db, 1, 1, 1, %84, 0;\n}\n"
    : "+f"(d[0]), "+f"(d[1]), "+f"(d[2]), "+f"(d[3]), "+f"(d[4]), "+f"(d[5]), "+f"(d[6]), "+f"(d[7]), "+f"(d[8]), "+f"(d[9]), "+f"(d[10]), "+f"(d[11]), "+f"(d[12]), "+f"(d[13]), "+f"(d[14]), "+f"(d[15]), "+f"(d[16]), "+f"(d[17]), "+f"(d[18]), "+f"(d[19]), "+f"(d[20]), "+f"(d[21]), "+f"(d[22]), "+f"(d[23]), "+f"(d[24]), "+f"(d[25]), "+f"(d[26]), "+f"(d[27]), "+f"(d[28]), "+f"(d[29]), "+f"(d[30]), "+f"(d[31]), "+f"(d[32]), "+f"(d[33]), "+f"(d[34]), "+f"(d[35]), "+f"(d[36]), "+f"(d[37]), "+f"(d[38]), "+f"(d[39]), "+f"(d[40]), "+f"(d[41]), "+f"(d[42]), "+f"(d[43]), "+f"(d[44]), "+f"(d[45]), "+f"(d[46]), "+f"(d[47]), "+f"(d[48]), "+f"(d[49]), "+f"(d[50]), "+f"(d[51]), "+f"(d[52]), "+f"(d[53]), "+f"(d[54]), "+f"(d[55]), "+f"(d[56]), "+f"(d[57]), "+f"(d[58]), "+f"(d[59]), "+f"(d[60]), "+f"(d[61]), "+f"(d[62]), "+f"(d[63]), "+f"(d[64]), "+f"(d[65]), "+f"(d[66]), "+f"(d[67]), "+f"(d[68]), "+f"(d[69]), "+f"(d[70]), "+f"(d[71]), "+f"(d[72]), "+f"(d[73]), "+f"(d[74]), "+f"(d[75]), "+f"(d[76]), "+f"(d[77]), "+f"(d[78]), "+f"(d[79])
    : "r"(alo), "r"(ahi), "r"(blo), "r"(bhi), "n"(TA));
}
__device__ __forceinline__ void wgmma_rs_n160(float (&d)[80], uint32_t a0, uint32_t a1, uint32_t a2, uint32_t a3, uint32_t blo){
  asm volatile("{\n.reg .b64 db;\nmov.b64 db, {%84,8};\nwgmma.mma_async.sync.aligned.m64n160k16.f32.bf16.bf16 {%0, %1, %2, %3, %4, %5, %6, %7, %8, %9, %10, %11, %12, %13, %14, %15, %16, %17, %18, %19, %20, %21, %22, %23, %24, %25, %26, %27, %28, %29, %30, %31, %32, %33, %34, %35, %36, %37, %38, %39, %40, %41, %42, %43, %44, %45, %46, %47, %48, %49, %50, %51, %52, %53, %54, %55, %56, %57, %58, %59, %60, %61, %62, %63, %64, %65, %66, %67, %68, %69, %70, %71, %72, %73, %74, %75, %76, %77, %78, %79}, {%80,%81,%82,%83}, db, 1, 1, 1, 0;\n}\n"
    : "+f"(d[0]), "+f"(d[1]), "+f"(d[2]), "+f"(d[3]), "+f"(d[4]), "+f"(d[5]), "+f"(d[6]), "+f"(d[7]), "+f"(d[8]), "+f"(d[9]), "+f"(d[10]), "+f"(d[11]), "+f"(d[12]), "+f"(d[13]), "+f"(d[14]), "+f"(d[15]), "+f"(d[16]), "+f"(d[17]), "+f"(d[18]), "+f"(d[19]), "+f"(d[20]), "+f"(d[21]), "+f"(d[22]), "+f"(d[23]), "+f"(d[24]), "+f"(d[25]), "+f"(d[26]), "+f"(d[27]), "+f"(d[28]), "+f"(d[29]), "+f"(d[30]), "+f"(d[31]), "+f"(d[32]), "+f"(d[33]), "+f"(d[34]), "+f"(d[35]), "+f"(d[36]), "+f"(d[37]), "+f"(d[38]), "+f"(d[39]), "+f"(d[40]), "+f"(d[41]), "+f"(d[42]), "+f"(d[43]), "+f"(d[44]), "+f"(d[45]), "+f"(d[46]), "+f"(d[47]), "+f"(d[48]), "+f"(d[49]), "+f"(d[50]), "+f"(d[51]), "+f"(d[52]), "+f"(d[53]), "+f"(d[54]), "+f"(d[55]), "+f"(d[56]), "+f"(d[57]), "+f"(d[58]), "+f"(d[59]), "+f"(d[60]), "+f"(d[61]), "+f"(d[62]), "+f"(d[63]), "+f"(d[64]), "+f"(d[65]), "+f"(d[66]), "+f"(d[67]), "+f"(d[68]), "+f"(d[69]), "+f"(d[70]), "+f"(d[71]), "+f"(d[72]), "+f"(d[73]), "+f"(d[74]), "+f"(d[75]), "+f"(d[76]), "+f"(d[77]), "+f"(d[78]), "+f"(d[79])
    : "r"(a0), "r"(a1), "r"(a2), "r"(a3), "r"(blo));
}
template<int N> __device__ __forceinline__ void wgmma_rs_hi(float (&d)[64], uint32_t a0, uint32_t a1, uint32_t a2, uint32_t a3, uint32_t blo);
template<> __device__ __forceinline__ void wgmma_rs_hi<16>(float (&d)[64], uint32_t a0, uint32_t a1, uint32_t a2, uint32_t a3, uint32_t blo){
  asm volatile("{\n.reg .b64 db;\nmov.b64 db, {%12,8};\nwgmma.mma_async.sync.aligned.m64n16k16.f32.bf16.bf16 {%0, %1, %2, %3, %4, %5, %6, %7}, {%8,%9,%10,%11}, db, 1, 1, 1, 0;\n}\n"
    : "+f"(d[56]), "+f"(d[57]), "+f"(d[58]), "+f"(d[59]), "+f"(d[60]), "+f"(d[61]), "+f"(d[62]), "+f"(d[63])
    : "r"(a0), "r"(a1), "r"(a2), "r"(a3), "r"(blo));
}
template<> __device__ __forceinline__ void wgmma_rs_hi<32>(float (&d)[64], uint32_t a0, uint32_t a1, uint32_t a2, uint32_t a3, uint32_t blo){
  asm volatile("{\n.reg .b64 db;\nmov.b64 db, {%20,8};\nwgmma.mma_async.sync.aligned.m64n32k16.f32.bf16.bf16 {%0, %1, %2, %3, %4, %5, %6, %7, %8, %9, %10, %11, %12, %13, %14, %15}, {%16,%17,%18,%19}, db, 1, 1, 1, 0;\n}\n"
    : "+f"(d[48]), "+f"(d[49]), "+f"(d[50]), "+f"(d[51]), "+f"(d[52]), "+f"(d[53]), "+f"(d[54]), "+f"(d[55]), "+f"(d[56]), "+f"(d[57]), "+f"(d[58]), "+f"(d[59]), "+f"(d[60]), "+f"(d[61]), "+f"(d[62]), "+f"(d[63])
    : "r"(a0), "r"(a1), "r"(a2), "r"(a3), "r"(blo));
}
template<> __device__ __forceinline__ void wgmma_rs_hi<48>(float (&d)[64], uint32_t a0, uint32_t a1, uint32_t a2, uint32_t a3, uint32_t blo){
  asm volatile("{\n.reg .b64 db;\nmov.b64 db, {%28,8};\nwgmma.mma_async.sync.aligned.m64n48k16.f32.bf16.bf16 {%0, %1, %2, %3, %4, %5, %6, %7, %8, %9, %10, %11, %12, %13, %14, %15, %16, %17, %18, %19, %20, %21, %22, %23}, {%24,%25,%26,%27}, db, 1, 1, 1, 0;\n}\n"
    : "+f"(d[40]), "+f"(d[41]), "+f"(d[42]), "+f"(d[43]), "+f"(d[44]), "+f"(d[45]), "+f"(d[46]), "+f"(d[47]), "+f"(d[48]), "+f"(d[49]), "+f"(d[50]), "+f"(d[51]), "+f"(d[52]), "+f"(d[53]), "+f"(d[54]), "+f"(d[55]), "+f"(d[56]), "+f"(d[57]), "+f"(d[58]), "+f"(d[59]), "+f"(d[60]), "+f"(d[61]), "+f"(d[62]), "+f"(d[63])
    : "r"(a0), "r"(a1), "r"(a2), "r"(a3), "r"(blo));
}
template<> __device__ __forceinline__ void wgmma_rs_hi<64>(float (&d)[64], uint32_t a0, uint32_t a1, uint32_t a2, uint32_t a3, uint32_t blo){
  asm volatile("{\n.reg .b64 db;\nmov.b64 db, {%36,8};\nwgmma.mma_async.sync.aligned.m64n64k16.f32.bf16.bf16 {%0, %1, %2, %3, %4, %5, %6, %7, %8, %9, %10, %11, %12, %13, %14, %15, %16, %17, %18, %19, %20, %21, %22, %23, %24, %25, %26, %27, %28, %29, %30, %31}, {%32,%33,%34,%35}, db, 1, 1, 1, 0;\n}\n"
    : "+f"(d[32]), "+f"(d[33]), "+f"(d[34]), "+f"(d[35]), "+f"(d[36]), "+f"(d[37]), "+f"(d[38]), "+f"(d[39]), "+f"(d[40]), "+f"(d[41]), "+f"(d[42]), "+f"(d[43]), "+f"(d[44]), "+f"(d[45]), "+f"(d[46]), "+f"(d[47]), "+f"(d[48]), "+f"(d[49]), "+f"(d[50]), "+f"(d[51]), "+f"(d[52]), "+f"(d[53]), "+f"(d[54]), "+f"(d[55]), "+f"(d[56]), "+f"(d[57]), "+f"(d[58]), "+f"(d[59]), "+f"(d[60]), "+f"(d[61]), "+f"(d[62]), "+f"(d[63])
    : "r"(a0), "r"(a1), "r"(a2), "r"(a3), "r"(blo));
}
template<> __device__ __forceinline__ void wgmma_rs_hi<80>(float (&d)[64], uint32_t a0, uint32_t a1, uint32_t a2, uint32_t a3, uint32_t blo){
  asm volatile("{\n.reg .b64 db;\nmov.b64 db, {%44,8};\nwgmma.mma_async.sync.aligned.m64n80k16.f32.bf16.bf16 {%0, %1, %2, %3, %4, %5, %6, %7, %8, %9, %10, %11, %12, %13, %14, %15, %16, %17, %18, %19, %20, %21, %22, %23, %24, %25, %26, %27, %28, %29, %30, %31, %32, %33, %34, %35, %36, %37, %38, %39}, {%40,%41,%42,%43}, db, 1, 1, 1, 0;\n}\n"
    : "+f"(d[24]), "+f"(d[25]), "+f"(d[26]), "+f"(d[27]), "+f"(d[28]), "+f"(d[29]), "+f"(d[30]), "+f"(d[31]), "+f"(d[32]), "+f"(d[33]), "+f"(d[34]), "+f"(d[35]), "+f"(d[36]), "+f"(d[37]), "+f"(d[38]), "+f"(d[39]), "+f"(d[40]), "+f"(d[41]), "+f"(d[42]), "+f"(d[43]), "+f"(d[44]), "+f"(d[45]), "+f"(d[46]), "+f"(d[47]), "+f"(d[48]), "+f"(d[49]), "+f"(d[50]), "+f"(d[51]), "+f"(d[52]), "+f"(d[53]), "+f"(d[54]), "+f"(d[55]), "+f"(d[56]), "+f"(d[57]), "+f"(d[58]), "+f"(d[59]), "+f"(d[60]), "+f"(d[61]), "+f"(d[62]), "+f"(d[63])
    : "r"(a0), "r"(a1), "r"(a2), "r"(a3), "r"(blo));
}
template<> __device__ __forceinline__ void wgmma_rs_hi<96>(float (&d)[64], uint32_t a0, uint32_t a1, uint32_t a2, uint32_t a3, uint32_t blo){
  asm volatile("{\n.reg .b64 db;\nmov.b64 db, {%52,8};\nwgmma.mma_async.sync.aligned.m64n96k16.f32.bf16.bf16 {%0, %1, %2, %3, %4, %5, %6, %7, %8, %9, %10, %11, %12, %13, %14, %15, %16, %17, %18, %19, %20, %21, %22, %23, %24, %25, %26, %27, %28, %29, %30, %31, %32, %33, %34, %35, %36, %37, %38, %39, %40, %41, %42, %43, %44, %45, %46, %47}, {%48,%49,%50,%51}, db, 1, 1, 1, 0;\n}\n"
    : "+f"(d[16]), "+f"(d[17]), "+f"(d[18]), "+f"(d[19]), "+f"(d[20]), "+f"(d[21]), "+f"(d[22]), "+f"(d[23]), "+f"(d[24]), "+f"(d[25]), "+f"(d[26]), "+f"(d[27]), "+f"(d[28]), "+f"(d[29]), "+f"(d[30]), "+f"(d[31]), "+f"(d[32]), "+f"(d[33]), "+f"(d[34]), "+f"(d[35]), "+f"(d[36]), "+f"(d[37]), "+f"(d[38]), "+f"(d[39]), "+f"(d[40]), "+f"(d[41]), "+f"(d[42]), "+f"(d[43]), "+f"(d[44]), "+f"(d[45]), "+f"(d[46]), "+f"(d[47]), "+f"(d[48]), "+f"(d[49]), "+f"(d[50]), "+f"(d[51]), "+f"(d[52]), "+f"(d[53]), "+f"(d[54]), "+f"(d[55]), "+f"(d[56]), "+f"(d[57]), "+f"(d[58]), "+f"(d[59]), "+f"(d[60]), "+f"(d[61]), "+f"(d[62]), "+f"(d[63])
    : "r"(a0), "r"(a1), "r"(a2), "r"(a3), "r"(blo));
}
template<> __device__ __forceinline__ void wgmma_rs_hi<112>(float (&d)[64], uint32_t a0, uint32_t a1, uint32_t a2, uint32_t a3, uint32_t blo){
  asm volatile("{\n.reg .b64 db;\nmov.b64 db, {%60,8};\nwgmma.mma_async.sync.aligned.m64n112k16.f32.bf16.bf16 {%0, %1, %2, %3, %4, %5, %6, %7, %8, %9, %10, %11, %12, %13, %14, %15, %16, %17, %18, %19, %20, %21, %22, %23, %24, %25, %26, %27, %28, %29, %30, %31, %32, %33, %34, %35, %36, %37, %38, %39, %40, %41, %42, %43, %44, %45, %46, %47, %48, %49, %50, %51, %52, %53, %54, %55}, {%56,%57,%58,%59}, db, 1, 1, 1, 0;\n}\n"
    : "+f"(d[8]), "+f"(d[9]), "+f"(d[10]), "+f"(d[11]), "+f"(d[12]), "+f"(d[13]), "+f"(d[14]), "+f"(d[15]), "+f"(d[16]), "+f"(d[17]), "+f"(d[18]), "+f"(d[19]), "+f"(d[20]), "+f"(d[21]), "+f"(d[22]), "+f"(d[23]), "+f"(d[24]), "+f"(d[25]), "+f"(d[26]), "+f"(d[27]), "+f"(d[28]), "+f"(d[29]), "+f"(d[30]), "+f"(d[31]), "+f"(d[32]), "+f"(d[33]), "+f"(d[34]), "+f"(d[35]), "+f"(d[36]), "+f"(d[37]), "+f"(d[38]), "+f"(d[39]), "+f"(d[40]), "+f"(d[41]), "+f"(d[42]), "+f"(d[43]), "+f"(d[44]), "+f"(d[45]), "+f"(d[46]), "+f"(d[47]), "+f"(d[48]), "+f"(d[49]), "+f"(d[50]), "+f"(d[51]), "+f"(d[52]), "+f"(d[53]), "+f"(d[54]), "+f"(d[55]), "+f"(d[56]), "+f"(d[57]), "+f"(d[58]), "+f"(d[59]), "+f"(d[60]), "+f"(d[61]), "+f"(d[62]), "+f"(d[63])
    : "r"(a0), "r"(a1), "r"(a2), "r"(a3), "r"(blo));
}
template<> __device__ __forceinline__ void wgmma_rs_hi<128>(float (&d)[64], uint32_t a0, uint32_t a1, uint32_t a2, uint32_t a3, uint32_t blo){
  asm volatile("{\n.reg .b64 db;\nmov.b64 db, {%68,8};\nwgmma.mma_async.sync.aligned.m64n128k16.f32.bf16.bf16 {%0, %1, %2, %3, %4, %5, %6, %7, %8, %9, %10, %11, %12, %13, %14, %15, %16, %17, %18, %19, %20, %21, %22, %23, %24, %25, %26, %27, %28, %29, %30, %31, %32, %33, %34, %35, %36, %37, %38, %39, %40, %41, %42, %43, %44, %45, %46, %47, %48, %49, %50, %51, %52, %53, %54, %55, %56, %57, %58, %59, %60, %61, %62, %63}, {%64,%65,%66,%67}, db, 1, 1, 1, 0;\n}\n"
    : "+f"(d[0]), "+f"(d[1]), "+f"(d[2]), "+f"(d[3]), "+f"(d[4]), "+f"(d[5]), "+f"(d[6]), "+f"(d[7]), "+f"(d[8]), "+f"(d[9]), "+f"(d[10]), "+f"(d[11]), "+f"(d[12]), "+f"(d[13]), "+f"(d[14]), "+f"(d[15]), "+f"(d[16]), "+f"(d[17]), "+f"(d[18]), "+f"(d[19]), "+f"(d[20]), "+f"(d[21]), "+f"(d[22]), "+f"(d[23]), "+f"(d[24]), "+f"(d[25]), "+f"(d[26]), "+f"(d[27]), "+f"(d[28]), "+f"(d[29]), "+f"(d[30]), "+f"(d[31]), "+f"(d[32]), "+f"(d[33]), "+f"(d[34]), "+f"(d[35]), "+f"(d[36]), "+f"(d[37]), "+f"(d[38]), "+f"(d[39]), "+f"(d[40]), "+f"(d[41]), "+f"(d[42]), "+f"(d[43]), "+f"(d[44]), "+f"(d[45]), "+f"(d[46]), "+f"(d[47]), "+f"(d[48]), "+f"(d[49]), "+f"(d[50]), "+f"(d[51]), "+f"(d[52]), "+f"(d[53]), "+f"(d[54]), "+f"(d[55]), "+f"(d[56]), "+f"(d[57]), "+f"(d[58]), "+f"(d[59]), "+f"(d[60]), "+f"(d[61]), "+f"(d[62]), "+f"(d[63])
    : "r"(a0), "r"(a1), "r"(a2), "r"(a3), "r"(blo));
}

struct CvCtx {
  uint32_t koff, zero, so[3];
  int srcA, srcB;
  bool wrapA, s3, kodd;
};
struct CvPipe { uint32_t Ap, Ep, keep, send; };
template <int LO> __device__ __forceinline__ void cv_copy(float (&acc)[64]) {
#pragma unroll
  for (int i = LO; i < 64; i++) { float t; asm volatile("mov.b32 %0, %1;" : "=f"(t) : "f"(acc[i]) : "memory"); acc[i] = t; }
}
template <int G> __device__ __forceinline__ void cv_raw(uint32_t (&A)[4][4], uint32_t kaddr) {
#pragma unroll
  for (int i = 0; i < 4; i++) {
    const uint32_t a = kaddr + (4 * G + i) * 128;
    A[i][0] = lds32(a); A[i][1] = lds32(a + 4); A[i][3] = lds32(a + 8);
  }
}
__device__ __forceinline__ void cv_form(uint32_t (&A)[4][4], uint32_t sel) {
#pragma unroll
  for (int i = 0; i < 4; i++) {
    asm volatile("prmt.b32 %0, %0, %1, %2;" : "+r"(A[i][0]) : "r"(A[i][1]), "r"(sel));
    asm volatile("prmt.b32 %0, %1, %2, %3;" : "=r"(A[i][2]) : "r"(A[i][1]), "r"(A[i][3]), "r"(sel));
  }
}
#define CVV 2
template <int G> __device__ __forceinline__ void cv_step(float (&acc)[64], uint32_t (&A)[4][4], CvPipe& s, const CvCtx& c, uint32_t cb, uint32_t stg) {
  constexpr int JA = G - 1, JB = G - 2, NH = CVV == 1 ? 4 : (CVV == 3 ? 2 : 1);
  const uint32_t db0 = desc_lo(cb + CV_U + 192, CV_PL);
  uint32_t B[4][4];
  uint32_t ra[2], rb;
  if constexpr (G < 8) {
    wgmma_fence();
#pragma unroll
    for (int i = 0; i < NH; i++) wgmma_rs_hi<128 - 16 * (G & 7)>(acc, A[i][0], A[i][1], A[i][2], A[i][3], db0 - 4 * i);
    wgmma_commit();
    __syncwarp();
  }
  if constexpr (JA >= 0 && JA < 8) {
    const uint32_t p0 = pack_bf16(acc[8 * JA + 1], acc[8 * JA + 3]), p1 = pack_bf16(acc[8 * JA + 5], acc[8 * JA + 7]);
    ra[0] = __shfl_sync(0xffffffffu, c.wrapA ? s.Ap : p0, c.srcA);
    ra[1] = __shfl_sync(0xffffffffu, c.wrapA ? p0 : p1, c.srcA);
    s.Ap = p1;
  }
  if constexpr (JB >= 0) rb = __shfl_sync(0xffffffffu, s.send, c.srcB);
  if constexpr (G < 7) cv_raw<G + 1>(B, cb + c.koff);
  uint32_t z = 0;
  if constexpr (G < 8 && NH < 4) {
    __syncwarp();
    wgmma_fence();
#pragma unroll
    for (int i = NH; i < 4; i++) wgmma_rs_hi<128 - 16 * (G & 7)>(acc, A[i][0], A[i][1], A[i][2], A[i][3], db0 - 4 * i);
    wgmma_commit();
    asm volatile("mov.u32 %0, %%clock;" : "=r"(z)::"memory");
    z &= c.zero;
  }
  if constexpr (G < 7) cv_form(B, 0x5432u | z);
  if constexpr (JB >= 0) sts32(stg + ((c.so[JB / 3] >> (10 * (JB % 3))) & 0xffc), hadd2(rb | z, s.keep));
  if constexpr (JA >= 0 && JA < 8) {
    const uint32_t sh = 16 | z, mk = 0xffff0000u | z;
    const uint32_t ev = pack_bf16(acc[8 * JA] + __uint_as_float(ra[0] << sh), acc[8 * JA + 2] + __uint_as_float(ra[0] & mk));
    const uint32_t od = pack_bf16(acc[8 * JA + 4] + __uint_as_float(ra[1] << sh), acc[8 * JA + 6] + __uint_as_float(ra[1] & mk));
    s.send = c.kodd ? ev : (c.s3 ? s.Ep : od);
    s.keep = c.kodd ? od : ev;
    s.Ep = od;
  }
  if constexpr (G < 8) { __syncwarp(); wgmma_wait<0>(); cv_copy<8 * (G & 7)>(acc); }
  if constexpr (G < 9) cv_step<G + 1>(acc, B, s, c, cb, stg);
}
__device__ __forceinline__ uint32_t cv_stage(int slot) { return sb + (slot < 4 ? 40960 + slot * 4096 : CV_OFF + CV_K); }
__device__ __forceinline__ void cv_setup(CvCtx& c) {
  const int tid = tid_opaque() & 127, w = tid >> 5, lane = tid & 31, r = lane >> 2, q = lane & 3;
  const int i0 = (r >> 1) & 1, i1 = r >> 2;
  c.koff = CV_K - 32 + 4 * (8 * (r >> 1) + 2 * w + (r & 1) + 2 * q);
  c.srcA = i0 ? lane - 8 : lane + 8 - q + ((q + 3) & 3);
  c.wrapA = i0 && q == 3;
  c.srcB = i1 == 0 ? (lane - q + 16 + ((q + 3) & 3)) : (lane - q - 16 + ((q + 1) & 3));
  c.s3 = (i1 == 1 && q == 3); c.kodd = (i1 == 1 && q < 3);
  c.zero = lds32(sb + EP_OFF + 24);
#pragma unroll
  for (int i = 0; i < 3; i++) c.so[i] = lds32(sb + SO_OFF + 512 * i + 4 * tid);
}
__device__ __forceinline__ void cv_table() {
  const int tid = tid_opaque() & 127, r = (tid & 31) >> 2, q = tid & 3;
  int t = 16 * (2 * (r < 4 ? q : 4 + ((q + 1) & 3)) + ((r >> 1) & 1)) + 4 * (tid >> 5) + 2 * (r & 1);
#pragma unroll 1
  for (int i = 0; i < 3; i++) {
    uint32_t v = 0;
#pragma unroll 1
    for (int x = 0; x < 3; x++, t += 256) {
      const int T = t / 160, tl = t - T * 160;
      const int qq = (T >= NT1 - 1) ? (tl >> 5) : (tl / 40);
      int ck = 20 * T + ((tl - qq * ((T >= NT1 - 1) ? 32 : 40)) >> 1);
      ck ^= (ck >> 2) & 6;
      v |= (uint32_t)((ck * 4 + qq) & 1023) << (10 * x + 2);
    }
    sts32(sb + SO_OFF + 512 * i + 4 * tid, v);
  }
}
__device__ __forceinline__ void conv_channel(int slot, const CvCtx& c) {
  const uint32_t cb = sb + CV_OFF + slot * CV_B;
  float acc[64];
  CvPipe s;
  s.Ap = s.Ep = 0u;
  uint32_t A[4][4];
#pragma unroll
  for (int i = 0; i < 64; i++) acc[i] = 0.f;
  if (slot == 4) mbar_wait(bars + 8 * B_CVDONE);
  mbar_wait(bars + 8 * (B_CVFULL + slot));
  cv_raw<0>(A, cb + c.koff);
  {
    const uint32_t w0 = lds32(cb + CV_K);
    const uint32_t wp = __byte_perm(pack_bf16(bf_lo(w0) + __uint_as_float(lds32(sb + EP_OFF + 4 * slot)), 0.f), w0, 0x7610);
    if (c.koff == CV_K) A[0][0] = wp;
    if (c.koff == CV_K - 4) A[0][1] = wp;
    if (c.koff == CV_K - 8) A[0][3] = wp;
  }
  cv_form(A, 0x5432u);
  cv_copy<0>(acc);
  cv_step<0>(acc, A, s, c, cb, cv_stage(slot));
  fence_async_smem();
  mbar_arrive(bars + 8 * (B_CVDONE + slot));
}

__device__ __forceinline__ void kv_issue(const Params& p, int c, int m2, int dg) {
  const uint32_t fb = bars + 8 * (B_KV + c);
  mbar_expect_tx(fb, KV_PIECE);
  tma3(sb + KS_OFF + c * KV_PIECE, &p.mK, 160 * dg + 32 * c, 64 * m2 - 3, 0, fb);
  tma3(sb + KS_OFF + c * KV_PIECE + 4864, &p.mV, 160 * dg + 32 * c, 64 * m2 - 1, 0, fb);
}
__device__ __forceinline__ void kv_tile(int m, int c, int y, uint32_t (&o)[4][4]) {
  const int lane = tid_opaque() & 31, tg = lane & 3, pr = 8 * (y ^ (tg >> 1)) + (lane >> 2);
  const uint32_t pb = sb + KS_OFF + c * KV_PIECE + 4 * pr;
  const uint32_t ka = pb + tg * 1216, va = pb + 4864 + tg * 1088 + 64;
  const uint32_t kh = (m == 0 && tg > 0) ? ka - 192 : ka;
  uint32_t kk[19], u[16];
  const float4 t = lds128f(sb + TAP_OFF + 256 * c + 16 * pr);
#pragma unroll
  for (int i = 0; i < 19; i++) { kk[i] = lds32((i < 3 ? kh : ka) + i * 64); if (i >= 3) u[i - 3] = lds32(va + (i - 3) * 64); }
  const uint32_t dst = sb + KS_OFF + c * KV_PIECE + pr * 64 + tg * 16;
  if (y) {
    __syncwarp();
#pragma unroll
    for (int x = 0; x < 4; x++) sts128((dst ^ 512) + x * 1024, make_uint4(o[x][0], o[x][1], o[x][2], o[x][3]));
  }
  const uint32_t w0 = __byte_perm(__float_as_uint(t.x), __float_as_uint(t.z), 0x5410), w1 = __byte_perm(__float_as_uint(t.x), __float_as_uint(t.z), 0x7632);
  const uint32_t w2 = __byte_perm(__float_as_uint(t.y), __float_as_uint(t.w), 0x5410), w3 = __byte_perm(__float_as_uint(t.y), __float_as_uint(t.w), 0x7632);
#pragma unroll
  for (int i = 0; i < 16; i++) {
    uint32_t a = hmul2(kk[i], w3);
    a = hadd2(a, hmul2(kk[i + 1], w2)); a = hadd2(a, hmul2(kk[i + 2], w1)); a = hadd2(a, hmul2(kk[i + 3], w0));
    u[i] = hmul2(a, u[i]);
  }
#pragma unroll
  for (int x = 0; x < 4; x++) {
#pragma unroll
    for (int qq = 0; qq < 4; qq++) o[x][qq] = __byte_perm(u[15 - 4 * qq - (x & 2)], u[14 - 4 * qq - (x & 2)], (x & 1) ? 0x7632 : 0x5410);
    if (y) sts128(dst + x * 1024, make_uint4(o[x][0], o[x][1], o[x][2], o[x][3]));
  }
}
__device__ __forceinline__ void ln_finish(float s1, float s2, float& mean, float& rstd) {
  mean = s1 * (1.f / 640.f);
  const float v = fmaxf(fmaf(-mean, mean, s2 * (1.f / 640.f)), 0.f) + 1e-5f;
  asm("rsqrt.approx.ftz.f32 %0, %1;" : "=f"(rstd) : "f"(v));
}
__device__ __forceinline__ void stat_table(int T1, unsigned want, int l, int g, const uint4* x0, const uint4* x1, float (&xa)[2], float (&xb)[2]) {
  const int n = 32 * g + (tid_opaque() & 31);
  const uint4* rp = &g_stats[8 * l * SEQ + min(160 * T1 + n, SEQ - 1)];
  float a[4], b[4];
  uint32_t it = 0;
  while (true) {
    bool ok = true;
#pragma unroll
    for (int i = 0; i < 4; i++) ok &= (rec_ld(rp + SEQ * i, a[i], b[i]) == want);
    ok &= rec_ld(x0, xa[0], xb[0]) == want;
    ok &= rec_ld(x1, xa[1], xb[1]) == want;
    if (__all_sync(0xffffffffu, ok)) break;
    trap_if(++it > SPIN_LIMIT);
  }
  float m, rs;
  ln_finish((a[0] + a[1]) + (a[2] + a[3]), (b[0] + b[1]) + (b[2] + b[3]), m, rs);
  sts32(sb + STAB_OFF + ((n >> 1) & 3) * 160 + (n >> 3) * 8 + (n & 1) * 4, __float_as_uint(rs));
  const uint32_t hi = pack_bf16(-m, -m);
  const float lo = -m - bf_lo(hi);
  sts128(sb + (l ? MX1_OFF : MX0_OFF) + n * 16, make_uint4(hi, pack_bf16(lo, lo), 0u, 0u));
  fence_async_smem();
}
__device__ __forceinline__ void stats_reduce(float (&a)[2], float (&b)[2], float (&mean)[2], float (&rstd)[2]) {
#pragma unroll
  for (int o = 1; o < 4; o <<= 1)
#pragma unroll
    for (int h = 0; h < 2; h++) { a[h] += __shfl_xor_sync(0xffffffffu, a[h], o); b[h] += __shfl_xor_sync(0xffffffffu, b[h], o); }
#pragma unroll
  for (int h = 0; h < 2; h++) ln_finish(a[h], b[h], mean[h], rstd[h]);
}

template <bool FIRST>
__device__ __forceinline__ void stats_publish(int which, int n0, int dg, unsigned tag, const float (&acc)[80]) {
  const int q = tid_opaque() & 3, h = q & 1;
  float s1[2] = {0.f, 0.f}, s2[2] = {0.f, 0.f}, t1[2] = {0.f, 0.f}, t2[2] = {0.f, 0.f};
#pragma unroll
  for (int j = 0; j < 20; j++)
#pragma unroll
    for (int y = 0; y < 2; y++) {
      const float a = acc[4 * j + 2 * y], b = acc[4 * j + 2 * y + 1];
      s1[y] += a; t1[y] += b; s2[y] = fmaf(a, a, s2[y]); t2[y] = fmaf(b, b, t2[y]);
    }
#pragma unroll
  for (int y = 0; y < 2; y++) { s1[y] += t1[y]; s2[y] += t2[y]; }
  float a = (h ? s1[1] : s1[0]) + __shfl_xor_sync(0xffffffffu, h ? s1[0] : s1[1], 1);
  float b = (h ? s2[1] : s2[0]) + __shfl_xor_sync(0xffffffffu, h ? s2[0] : s2[1], 1);
  a += __shfl_xor_sync(0xffffffffu, a, 2);
  b += __shfl_xor_sync(0xffffffffu, b, 2);
  if (FIRST) {
    rec_st(&g_stats[((q >> 1) * 4 + dg) * SEQ + n0 + 8 * h], a, b, q < 2 ? tag : tag - 1);
    rec_st(&g_stats[((q >> 1) * 4 + 8 + dg) * SEQ + n0 + 8 * h], a, b, tag - 1);
  } else if (q < 2) rec_st(&g_stats[(which * 4 + dg) * SEQ + n0 + 8 * h], a, b, tag);
}
__device__ __forceinline__ void stats_get(int which, int n0, unsigned tag, float (&mean)[2], float (&rstd)[2]) {
  const uint4* p0 = &g_stats[(which * 4 + (tid_opaque() & 3)) * SEQ + n0];
  float a[2], b[2];
  uint32_t it = 0;
  while (true) {
    const unsigned t0 = rec_ld(p0, a[0], b[0]), t1 = rec_ld(p0 + 8, a[1], b[1]);
    if (__all_sync(0xffffffffu, t0 == tag && t1 == tag)) break;
    trap_if(++it > SPIN_LIMIT);
  }
  stats_reduce(a, b, mean, rstd);
}
__device__ __forceinline__ void x0_load(float (&acc)[80]) {
  const int t = tid_opaque() & 127;
  const uint32_t xa = sb + XT_OFF + (16 * (t >> 5) + ((t & 31) >> 2)) * 320 + 8 * (t & 3);
  mbar_wait(bars + 8 * B_XT);
#pragma unroll
  for (int h = 0; h < 2; h++)
#pragma unroll
    for (int J = 0; J < 10; J++) {
      const float2 v = lds64f(xa + h * 2560 + 32 * J);
      const uint32_t x = __float_as_uint(v.x), y = __float_as_uint(v.y);
      acc[8 * J + 2 * h] = bf_lo(x); acc[8 * J + 2 * h + 1] = bf_hi(x);
      acc[8 * J + 4 + 2 * h] = bf_lo(y); acc[8 * J + 4 + 2 * h + 1] = bf_hi(y);
    }
}

template <bool FROM_X0>
__device__ __forceinline__ void dskip_init(float (&acc)[80], const float (&mean)[2], const float (&rstd)[2]) {
  const int t = tid_opaque() & 127;
  const uint32_t xa = sb + XT_OFF + (16 * (t >> 5) + ((t & 31) >> 2)) * 320 + 8 * (t & 3), da = sb + DTAB_OFF + 8 * (t & 3);
  float2 dw[10], xv[10][2];
#pragma unroll
  for (int J = 0; J < 2; J++) { dw[J] = lds64f(da + 32 * J); if (FROM_X0) { xv[J][0] = lds64f(xa + 32 * J); xv[J][1] = lds64f(xa + 2560 + 32 * J); } }
#pragma unroll
  for (int J = 0; J < 10; J++) {
    if (J + 2 < 10) { dw[J + 2] = lds64f(da + 32 * (J + 2)); if (FROM_X0) { xv[J + 2][0] = lds64f(xa + 32 * (J + 2)); xv[J + 2][1] = lds64f(xa + 2560 + 32 * (J + 2)); } }
#pragma unroll
    for (int x = 0; x < 8; x++) {
      const int h = (x >> 1) & 1;
      const uint32_t dwd = __float_as_uint(x < 4 ? dw[J].x : dw[J].y);
      const float tt = fmaf(rstd[h], (x & 1) ? bf_hi(dwd) : bf_lo(dwd), 1.f);
      float a = acc[8 * J + x];
      if (FROM_X0) { const uint32_t xw = __float_as_uint(x < 4 ? xv[J][h].x : xv[J][h].y); a = (x & 1) ? bf_hi(xw) : bf_lo(xw); }
      acc[8 * J + x] = FROM_X0 ? (a - mean[h]) * tt : fmaf(a, tt, -mean[h] * tt);
    }
  }
}

__global__ void __launch_bounds__(512, 1) fused_kernel(const __grid_constant__ Params p) {
  extern __shared__ __align__(1024) uint8_t smem_raw[];
  const int tid = threadIdx.x, lane = tid & 31;
  const int wid = __shfl_sync(0xffffffffu, tid >> 5, 0), wg = wid >> 2;
  unsigned smid; asm volatile("mov.u32 %0, %%smid;" : "=r"(smid));
  const int role = p.role[min(smid, 131u)];
  if (wid == 12) {
    const bool el = elect_one();
    if (el) {
      asm volatile("prefetch.tensormap [%0];" ::"l"(&p.mB) : "memory");
      asm volatile("prefetch.tensormap [%0];" ::"l"((role & 15) == NT1 - 1 ? &p.mXl : &p.mX) : "memory");
#pragma unroll
      for (int k = 0; k < S1; k++) mbar_init(bars + 8 * (B_G1FULL + k), 1);
#pragma unroll
      for (int k = 0; k < 6; k++) mbar_init(bars + 8 * (B_XT + k), 1);
      asm volatile("fence.mbarrier_init.release.cluster;" ::: "memory");
    }
    if (role >= 0) {
      __syncwarp();
      asm volatile("bar.arrive 5, 288;" ::: "memory");
      const Role R = unpack_role(role);
      if (elect_one()) {
        TS(45);
#pragma unroll 1
        for (int k = 0; k < S1; k++) {
          const uint32_t fb = bars + 8 * (B_G1FULL + k);
          mbar_expect_tx(fb, G1_STAGE);
          tma4(sb + k * G1_STAGE + G1_XOFF, R.last ? &p.mXl : &p.mX, 64 * k, 0, 0, R.last ? 0 : 80 * R.T1, fb);
          tma5(sb + k * G1_STAGE, &p.mB, 64 * k, 0, 0, 4 * R.side, 2 * R.GP, fb);
          if (PFD) asm volatile("prefetch.tensormap [%0];" ::"l"(&p.mK + k) : "memory");
        }
        if (R.has2) {
          mbar_expect_tx(bars + 8 * B_XT, 20480);
#pragma unroll 1
          for (int h = 0; h < 2; h++) {
            const int ng = 8 * R.m2 + 4 * h, T = ng / 20;
            tma4(sb + XT_OFF + h * 10240, T == NT1 - 1 ? &p.mXtl : &p.mXt, 160 * R.dg, 0, 0, T == NT1 - 1 ? ng - 240 : ng + 60 * T, bars + 8 * B_XT);
          }
#pragma unroll 1
          for (int c = 0; c < KV0; c++) kv_issue(p, c, R.m2, R.dg);
        }
        TS(44);
      }
      __syncwarp();
      bar_sync(6, 64);
    }
  }
  trap_if(smid >= 132 || smem_u32(smem_raw) != sb);
  if (role < 0) {
    if (wid == 0) {
      const unsigned tag = ld_rlx(g_epoch);
      uint32_t it = 0;
      while (!__all_sync(0xffffffffu, (int)(ld_rlx(&g_hcnt[(lane & 7) * 32]) - 40 * tag) >= 0)) { __nanosleep(500); trap_if(++it > SPIN_LIMIT); }
    }
    return;
  }
  float mean0[2] = {0.f, 0.f}, rstd0[2] = {0.f, 0.f};
  if (wg == 2 || wid == 14) {
    ROLE(role)
    const int c = wid == 14 ? 4 : wid - 8;
    const unsigned tag = ld_rlx(g_epoch);
    if (has2) {
      uint2 bv[2][5];
#pragma unroll
      for (int x = 0; x < 2; x++)
#pragma unroll
        for (int i = 0; i < 5; i++) bv[x][i] = ldv64((const uint2*)((x ? p.bim : p.bre) + (cch0 + 32 * c) * DM) + lane + 32 * i);
      float sv[2];
#pragma unroll
      for (int x = 0; x < 2; x++) {
        float a = 0.f;
#pragma unroll
        for (int i = 0; i < 5; i++) a += (bf_lo(bv[x][i].x) + bf_hi(bv[x][i].x)) + (bf_lo(bv[x][i].y) + bf_hi(bv[x][i].y));
        sv[x] = a;
      }
#pragma unroll
      for (int o = 16; o > 0; o >>= 1) { sv[0] += __shfl_xor_sync(0xffffffffu, sv[0], o); sv[1] += __shfl_xor_sync(0xffffffffu, sv[1], o); }
      if (lane < 2) rec_st(&g_sB[(cch0 + 32 * c) * 2 + lane], sv[0], sv[1], tag);
      if (tid == 256) TS(47);
      __syncwarp();
      bar_sync(8, 192);
      if (wg == 2) {
        float xs[80];
        x0_load(xs);
        stats_publish<true>(0, 64 * m2 + 16 * c + (lane >> 2), dg, tag, xs);
        if (tid == 256) TS(31);
      }
      mbar_wait(bars + 8 * B_EP);
      mbar_wait(bars + 8 * (B_KV + c));
      mbar_wait(bars + 8 * (B_G1DONE + PAUSE_K - 1));
      if (tid == 448) TS(52);
      uint32_t o[4][4] = {};
#pragma unroll 1
      for (int y = 0; y < 2; y++) kv_tile(m2, c, y, o);
      fence_async_smem();
      __syncwarp();
      if (lane == 0) {
        mbar_arrive(bars + 8 * B_PREP);
        bulk_s2g(g_kv + (dg * 32 + m2) * 20480 + c * 4096, sb + KS_OFF + c * KV_PIECE, 4096);
        asm volatile("cp.async.bulk.commit_group;" ::: "memory");
      }
      __syncwarp();
      if (tid == 448) TS(51);
    } else bar_sync(8, 192);
    {
      const uint4* x0 = wg == 2 ? &g_stats[(lane & 3) * SEQ + (has2 ? 64 * m2 : 0) + 16 * c + (lane >> 2)] : &g_sB[(128 * GP + 32 * side + lane) * 2];
      float xa[2], xb[2];
      stat_table(T1, tag, 0, c, x0, x0 + (wg == 2 ? 8 : 128), xa, xb);
      if (wg == 2) stats_reduce(xa, xb, mean0, rstd0);
      else {
#pragma unroll
        for (int i = 0; i < 2; i++) {
          const float ha = bf_lo(pack_bf16(xa[i], 0.f)), hb = bf_lo(pack_bf16(xb[i], 0.f));
          const float pa = __uint_as_float(pack_bf16(ha, xa[i] - ha)), pb = __uint_as_float(pack_bf16(hb, xb[i] - hb));
          sts64f(sb + CTAB_OFF + (32 * i + lane) * 24 + 16, p.swap ? pb : pa, p.swap ? pa : pb);
        }
      }
      mbar_arrive(bars + 8 * B_STAB);
      if (tid == 448) TS(26);
    }
    if (has2) {
      if (lane == 0) {
        asm volatile("cp.async.bulk.wait_group 0;" ::: "memory");
        fence_async_global();
        mbar_arrive(bars + 8 * B_PREP2);
      }
      __syncwarp();
    }
  } else if (wid == 15) {
    ROLE(role)
    const int ch = 128 * GP + 32 * side + lane;
    uint32_t r0 = ldv16(p.lre + ch), r1 = ldv16(p.lim + ch), r2 = ldv16(p.logdt + ch);
    const uint32_t r3 = ldv16(p.lre + ch + 64), r4 = ldv16(p.lim + ch + 64), r5 = ldv16(p.logdt + ch + 64);
#pragma unroll 1
    for (int i = 0; i < 2; i++) {
      const float lr = bf_lo(r0), li = bf_lo(r1);
      const float dt = __bfloat162float(__float2bfloat16_rn(expf(bf_lo(r2))));
      const float mag = expf(dt * lr);
      float sn, cs; sincospif(dt * li * 0.31830988618379067f, &sn, &cs);
      const float ar = mag * cs, ai = mag * sn;
      const float inv = 2.f / (lr * lr + li * li);
      const uint32_t ad = sb + CTAB_OFF + (32 * i + lane) * 24;
      sts64f(ad, ar, ai);
      sts64f(ad + 8, ((ar - 1.f) * lr + ai * li) * inv, (ai * lr - (ar - 1.f) * li) * inv);
      r0 = r3; r1 = r4; r2 = r5;
    }
    if (lane == 0) TS(46);
    __syncwarp();
    bar_sync(7, 64);
    mbar_arrive(bars + 8 * B_CTAB);
  } else if (wid == 13) {
    ROLE(role)
    uint4 tv[3];
    const uint32_t e0 = ld_rlx(g_epoch);
    const uint32_t e1 = ldv16(p.ssmD + min(cch0 + 32 * lane, 639));
    const uint4 dv = ldv128((const uint4*)(p.dskip + 160 * dg) + min(lane, 19));
#pragma unroll
    for (int i = 0; i < 3; i++) tv[i] = ldv128((const uint4*)(p.shiftk + 640 * dg) + min(lane + 32 * i, 79));
    sts128(sb + DTAB_OFF + 16 * min(lane, 19), dv);
#pragma unroll
    for (int i = 0; i < 3; i++) sts128(sb + TAP_OFF + 16 * min(lane + 32 * i, 79), tv[i]);
    if (lane < 7) sts32(sb + EP_OFF + 4 * lane, lane < 5 ? e1 << 16 : (lane == 5 ? e0 : 0u));
    __syncwarp();
    bar_sync(9, 64);
    mbar_arrive(bars + 8 * B_CTAB);
    if (lane == 0) { mbar_arrive(bars + 8 * B_EP); TS(53); }
    if (has2) {
      mbar_wait(bars + 8 * B_PREP2);
      if (lane < 4) red_rel(&g_kvcnt[(dg * 4 + lane) * 32]);
      __syncwarp();
      if (lane == 0) { mbar_arrive(bars + 8 * B_PUB); TS(30); }
    }
  } else if (wid != 12) {
    if (elect_one()) {
      if (wid < 7) {
        const int b0 = wid < 4 ? 4 + 19 * wid : 85 + 21 * (wid - 4), cnt = wid < 4 ? 2 : 1;
#pragma unroll
        for (int i = 0; i < 21; i++) mbar_init(bars + 8 * (b0 + i), cnt);
      } else {
#pragma unroll
        for (int i = 0; i < 12; i++) mbar_init(bars + 8 * (B_CVDONE + i), (i == 5 || i == 6) ? 160 : 128);
        mbar_init(bars + 8 * B_CTAB, 192); mbar_init(bars + 8 * B_PREP, 5); mbar_init(bars + 8 * B_PREP2, 5);
      }
      asm volatile("fence.mbarrier_init.release.cluster;" ::: "memory");
    }
    __syncwarp();
    bar_sync(5, 288);
    if (wid == 2) asm volatile("bar.arrive 8, 192;\nbar.arrive 6, 64;\nbar.arrive 9, 64;\nbar.arrive 7, 64;" ::: "memory");
    if (tid == 128) TS(0);
    if (wg == 1) { cv_table(); mbar_arrive(bars + 8 * B_CTAB); }
  }

  if (wid == 12) {
    ROLE(role)
    uint32_t dst = sb;
#pragma unroll 1
    for (int k = S1; k < 10; k++) {
      const uint32_t fb = bars + 8 * (B_G1FULL + k);
      mbar_wait(bars + 8 * (B_G1DONE + k - S1));
      if (elect_one()) {
        mbar_expect_tx(fb, 20480);
        tma4(dst + G1_XOFF, last ? &p.mXl : &p.mX, 64 * k, 0, 0, last ? 0 : 80 * T1, fb);
        mbar_expect_tx(fb, 16384);
        tma5(dst, &p.mB, 64 * k, 0, 0, 4 * side, 2 * GP, fb);
        if (has2 && k - S1 + KV0 < 5) kv_issue(p, k - S1 + KV0, m2, dg);
      }
      dst += G1_STAGE; if (k == 2 * S1 - 1) dst = sb;
    }
  } else if (wid == 15 && (role >> 16)) {
    ROLE(role)
    if (TPF >= 0) {
      mbar_wait(bars + 8 * (B_KV + TPF));
      if (elect_one()) {
#pragma unroll
        for (int c = 0; c < 5; c++) l2_prefetch(p.ssmk + (cch0 + 32 * c) * SEQ, 4096);
        if (CPF) { l2_prefetch(p.cre + (160 * dg + 5 * m2) * DM, 6400); l2_prefetch(p.cim + (160 * dg + 5 * m2) * DM, 6400); }
      }
    }
    mbar_wait(bars + 8 * B_PREP2);
    if (lane < 10) sts128(sb + CV_OFF + (lane >> 1) * CV_B + CV_K - 32 + 16 * (lane & 1), make_uint4(0, 0, 0, 0));
    fence_async_smem();
    __syncwarp();
    const unsigned tag = lds32(sb + EP_OFF + 20);
    if (TAPW) mbar_wait(bars + 8 * B_PUB);
    if (elect_one()) {
#pragma unroll 1
      for (int c = 0; c < 5; c++) {
        if (c == 0) asm volatile("prefetch.tensormap [%0];" ::"l"(&p.mU) : "memory");
        mbar_expect_tx(bars + 8 * (B_CVFULL + c), 4096 + 2 * CV_PL);
        bulk_g2s(sb + CV_OFF + c * CV_B + CV_K, p.ssmk + (cch0 + 32 * c) * SEQ, 4096, bars + 8 * (B_CVFULL + c));
      }
    }
    mbar_wait(bars + 8 * B_PUB);
    cnt_poll(&g_kvcnt[(dg * 4 + (m2 >> 3)) * 32], 32 * tag);
    fence_async_global();
    if (elect_one()) {
      TS(28);
#pragma unroll
      for (int c = 0; c < 5; c++)
        tma5(sb + CV_OFF + c * CV_B + CV_U, &p.mU, 0, -3, 2 * c, 16 * (m2 & 1) + (m2 >> 1), dg, bars + 8 * (B_CVFULL + c));
#pragma unroll
      for (int i = 0; i < 3; i++) asm volatile("prefetch.tensormap [%0];" ::"l"(&p.mCre + i) : "memory");
      TS(54);
    }
    __syncwarp();
  }
  {
    const int w = wid & 3;
    if (wg == 2 && !(role >> 16)) {
      float xa[2], xb[2];
      mbar_wait(bars + 8 * (B_G1FULL + 11));
      stat_table(role & 15, lds32(sb + EP_OFF + 20), 1, w, g_stats, g_stats, xa, xb);
      mbar_arrive(bars + 8 * (B_STAB + 1));
    }
#pragma unroll 1
    for (int l = 0; l < 2; l++) {
      if (wg < 2) {
        float acc[80];
#pragma unroll
        for (int i = 0; i < 80; i++) acc[i] = 0.f;
        ROLE(role)
        const int tid = tid_opaque(), r = (tid & 31) >> 2, q = tid & 3;
        const int ch = 128 * GP + 64 * wg + 32 * side + 8 * w + r;
        const uint32_t ca = sb + CTAB_OFF + (32 * wg + 8 * w + r) * 24;
        float2 lam = make_float2(0.f, 0.f), p8 = lam, p16 = lam, pL = lam, p2L = lam;
        fence_regs(acc);
        {
          const uint32_t alo0 = (l == 0 ? desc_lo(sb, 16) : desc_lo(sb + G2_WOFF, 16)) + wg * 512;
          const uint32_t blo0 = l == 0 ? desc_lo(sb + G1_XOFF, 16) : desc_lo(sb + X1_OFF, 128);
          const uint32_t bhi = l == 0 ? desc_hi(1024, 1) : desc_hi(1024, 0), xstep = l == 0 ? 2 : 16;
          const uint32_t astep = l == 0 ? G1_STAGE >> 4 : 1024, bstep = l == 0 ? G1_STAGE >> 4 : 1280, aend = alo0 + (S1 + l) * astep;
          uint32_t alo = alo0, blo = blo0;
          uint32_t fb = bars + 8 * (B_G1FULL + 10 * l);
          mbar_wait(fb);
          if (tid == 0) TS(1 + 8 * l);
#pragma unroll 1
          for (int k = 0; k < 10; k++) {
            uint32_t ok; const uint32_t nb = k < 9 ? fb + 8 : fb;
            wgmma_fence();
#pragma unroll
            for (int kk = 0; kk < 4; kk++) {
              wgmma_n160<0>(acc, alo + kk * 2, desc_hi(1024, 1), blo + kk * xstep, bhi);
              if (kk == 0) ok = mbar_test(nb);
              if (kk == STG_KK && k == 9 && tid == 0) mbar_arrive(bars + 8 * (B_STG + l));
            }
            wgmma_commit();
            alo += astep; blo += bstep;
            if (blo == desc_lo(sb + G_OFF, 128)) blo = desc_lo(sb, 128);
            if (alo == aend) { alo = alo0; blo = blo0; }
            wgmma_wait<1>();
            if (k > 0 && (tid & 127) == 0) mbar_arrive(fb + 8 * (B_G1DONE - B_G1FULL - 1));
            if (!ok) mbar_wait(nb);
            if (k == (l ? MK1 : MK0)) {
              mbar_wait(bars + 8 * (B_STAB + l));
              const float2 sB = lds64f(ca + 16);
              uint32_t a0 = q < 2 ? __float_as_uint(sB.x) : 0u, a1 = q < 2 ? __float_as_uint(sB.y) : 0u, a2 = 0u, a3 = 0u;
              asm volatile("" : "+r"(a0), "+r"(a1), "+r"(a2), "+r"(a3)::"memory");
              wgmma_fence();
              wgmma_rs_n160(acc, a0, a1, a2, a3, l ? desc_lo(sb + MX1_OFF, 0) : desc_lo(sb + MX0_OFF, 0));
              wgmma_commit();
            }
            if (wg == 1 && k == (l ? 8 - STG_D : 9 - STG0)) mbar_wait(bars + 8 * (B_STG + l));
            if (k == 3) {
              mbar_wait(bars + 8 * B_CTAB);
              lam = lds64f(ca);
              if (l == 0 && q < 2) rec_st(&g_E[(q * NT1 + T1) * DM + ch], 0.f, 0.f, lds32(sb + EP_OFF + 20) - 1);
              if (p.swap) lam.y = -lam.y;
              const float2 p2 = cmul(lam, lam), p4 = cmul(p2, p2);
              p8 = cmul(p4, p4); p16 = cmul(p8, p8);
              pL = cmul(p16, p16);
              if (!last) pL = cmul(pL, p8);
              p2L = cmul(pL, pL);
            }
            if (k == PAUSE_K && l == 0 && has2) mbar_wait(bars + 8 * B_PREP);
            fb += 8;
          }
        }
        const unsigned tag = lds32(sb + EP_OFF + 20);
        wgmma_wait<0>();
        fence_regs(acc);
        if ((tid & 127) == 0) { mbar_arrive(bars + 8 * (B_G1DONE + 10 * l + 9)); TS(wg ? 17 + l : 2 + 8 * l); }
        float2 ec[3];
#pragma unroll
        for (int jj = 0; jj < 4; jj++)
#pragma unroll
          for (int y = 0; y < 3; y++) {
            if (y == 2 && (jj & 1)) continue;
            const int j = y == 2 ? 16 + jj : 8 * y + 2 * jj;
            const float4 st = lds128f(sb + STAB_OFF + q * 160 + j * 8);
            const float rs[4] = {st.x, st.y, st.z, st.w};
#pragma unroll
            for (int x = 0; x < 4; x++) {
              const int i = 4 * j + 4 * (x >> 1) + (x & 1);
              acc[i] *= rs[x]; acc[i + 2] *= rs[x];
              ec[y] = (jj == 0 && x == 0) ? make_float2(acc[i], acc[i + 2]) : cfma(lam, ec[y], make_float2(acc[i], acc[i + 2]));
            }
          }
        float2 e = cfma(p16, ec[0], ec[1]);
        if (!last) e = cfma(p8, e, ec[2]);
        {
          float2 v = make_float2(__shfl_up_sync(0xffffffffu, e.x, 1, 4), __shfl_up_sync(0xffffffffu, e.y, 1, 4));
          if (q >= 1) e = cfma(pL, v, e);
          v = make_float2(__shfl_up_sync(0xffffffffu, e.x, 2, 4), __shfl_up_sync(0xffffffffu, e.y, 2, 4));
          if (q >= 2) e = cfma(p2L, v, e);
        }
        if (!last && q == 3) rec_st(&g_E[(l * NT1 + T1) * DM + ch], e.x, e.y, tag);
        if (tid == 0) TS(3 + 8 * l);
        float2 ex = make_float2(__shfl_up_sync(0xffffffffu, e.x, 1, 4), __shfl_up_sync(0xffffffffu, e.y, 1, 4));
        if (q == 0) ex = make_float2(0.f, 0.f);
        const float2 coef = lds64f(ca + 8), lamc = make_float2(lam.x, p.swap ? lam.y : -lam.y);
        float m00 = coef.x, m01 = -coef.y, m10 = -coef.y, m11 = -coef.x;
        if (p.swap) { m00 = -coef.y; m01 = coef.x; m10 = -coef.x; m11 = -coef.y; }
        float2 pLq, p160q, p640;
        {
          const float2 p80 = last ? cmul(p2L, p16) : p2L, p160 = cmul(p80, p80), p320 = cmul(p160, p160), one = make_float2(1.f, 0.f);
          p640 = cmul(p320, p320);
          pLq = cmul((q & 1) ? pL : one, (q & 2) ? p2L : one);
          p160q = cmul((q & 1) ? p160 : one, (q & 2) ? p320 : one);
        }
        float2 c, ev[3];
        unsigned tg[3];
        const uint4* ep = &g_E[(l * NT1 + T1 - 1 - q) * DM + ch];
#pragma unroll
        for (int j = 0; j < 20; j++) {
          if (j == CPOLL) {
#pragma unroll
            for (int i = 0; i < 3; i++) {
              ev[i] = make_float2(0.f, 0.f); tg[i] = tag;
              if (T1 - 1 - q - 4 * i >= 0) tg[i] = rec_ld(ep - 4 * i * DM, ev[i].x, ev[i].y);
            }
          }
#pragma unroll
          for (int x = 0; x < 2; x++) {
            const float b0 = acc[4 * j + x], b1 = acc[4 * j + 2 + x];
            acc[4 * j + x] = fmaf(b0, m00, b1 * m01);
            acc[4 * j + 2 + x] = fmaf(b0, m10, b1 * m11);
          }
          if (j == CPOLL - 1 || j == 19) asm volatile("" : "+f"(acc[4 * j]), "+f"(acc[4 * j + 1]), "+f"(acc[4 * j + 2]), "+f"(acc[4 * j + 3])::"memory");
        }
        {
          uint32_t it = 0;
          while (__any_sync(0xffffffffu, tg[0] != tag || tg[1] != tag || tg[2] != tag)) {
#pragma unroll
            for (int i = 0; i < 3; i++)
              if (tg[i] != tag) tg[i] = rec_ld(ep - 4 * i * DM, ev[i].x, ev[i].y);
            trap_if(++it > SPIN_LIMIT);
          }
          c = cfma(p640, cfma(p640, ev[2], ev[1]), ev[0]);
          c = cmul(c, p160q);
          c.x += __shfl_xor_sync(0xffffffffu, c.x, 1); c.y += __shfl_xor_sync(0xffffffffu, c.y, 1);
          c.x += __shfl_xor_sync(0xffffffffu, c.x, 2); c.y += __shfl_xor_sync(0xffffffffu, c.y, 2);
        }
        if (tid == 0) TS(4 + 8 * l);
        if (wg == 1 && l >= HOLD0) mbar_wait(bars + 8 * (B_REL + l));
        const uint32_t c0 = (uint32_t)clock();
        c = cfma(pLq, c, ex);
        float2 hh = make_float2(fmaf(c.x, m00, c.y * m01), fmaf(c.x, m10, c.y * m11));
        uint8_t* hb = g_h + (size_t)l * (32 * 20 * 8192) + (10 * wg + 2 * GP) * 8192 + (4 * side + w) * 1024 + (tid_opaque() & 31) * 4;
#pragma unroll
        for (int j4 = 0; j4 < 5; j4++) {
          if (PACE && j4 > 0 && wg == 1 && l == 1) { while (__any_sync(0xffffffffu, (uint32_t)clock() - c0 < PACE * j4)) {} }
          const int ng = 20 * T1 + 4 * j4;
          uint8_t* hp = hb + (size_t)(ng >> 3) * 163840 + (ng & 7) * 128;
#pragma unroll
          for (int jj = 0; jj < 4; jj++) {
            const int j = 4 * j4 + jj;
            const float2 h0 = cfma(lamc, hh, make_float2(acc[4 * j + 0], acc[4 * j + 2]));
            hh = cfma(lamc, h0, make_float2(acc[4 * j + 1], acc[4 * j + 3]));
            if (j4 < 4 || !last) {
              *(uint32_t*)(hp + jj * 128) = pack_bf16(h0.x, hh.x);
              *(uint32_t*)(hp + jj * 128 + 8192) = pack_bf16(h0.y, hh.y);
            }
          }
        }
        mbar_arrive(bars + 8 * (B_HST + 2 * l + wg));
        if (tid == 0) TS(5 + 8 * l);
        if (tid == 128) TS(l ? 25 : 19);
        if (l == 0 && wid == 4) {
          mbar_wait(bars + 8 * B_HST);
          mbar_wait(bars + 8 * (B_HST + 1));
          if ((tid & 31) < 8) h_release((tid >> 2) & 1, T1, tid & 3);
          __syncwarp();
          if (tid == 128) { mbar_arrive(bars + 8 * B_REL); TS(6); }
        }
      }
      if (l == 0) {
        ROLE(role)
        if (has2) {
          CvCtx cc;
          mbar_wait(bars + 8 * B_CTAB);
          cv_setup(cc);
          mbar_wait(bars + 8 * (B_G1DONE + 9));
#pragma unroll 1
          for (int c = (wg + 2) & 3; c < 5; c += 4) conv_channel(c, cc);
          if ((tid & 127) == 0) TS(wg == 2 ? 32 : (wg == 3 ? 50 : 7 + wg));
        }
      }
      if (wg >= 2) break;
    }
    if (wg == 3) {
    ROLE(role)
    const int pw = wid & 3, gpc = 2 * min(m2 >> 3, 3) + (dg >> 1);
    mbar_wait(bars + 8 * B_EP);
    const unsigned tag = lds32(sb + EP_OFF + 20);
    if (pw == 0) {
      if (elect_one()) {
#pragma unroll 1
        for (int l = 0; l < 2; l++) {
          uint32_t dst = sb;
          if (l == 1) {
            dst = sb + G2_WOFF;
#pragma unroll 1
            for (int k = 0; k < 10; k++) {
              mbar_wait(k > 4 ? bars + 8 * (B_G1DONE + 5 + k) : (has2 ? bars + 8 * (B_G2DONE + 14 + min(k, 3)) : bars + 8 * (B_G1DONE + 9)));
              mbar_expect_tx(bars + 8 * (B_G1FULL + 10 + k), 16384);
              tma5(dst, &p.mB, 64 * k, 0, 0, 4 * side, 2 * GP, bars + 8 * (B_G1FULL + 10 + k));
              dst += 16384; if (k == 4) dst = sb + G2_WOFF;
            }
          }
          if (has2) {
            const uint32_t fb2 = bars + 8 * (B_G2FULL + 20 * l), wb2 = bars + 8 * (B_G2DONE + 20 * l - S2);
            dst = sb + G2_WOFF + (WTAIL ? 4 * l * G2_WB : 0);
            int kc = 0;
#pragma unroll 1
            for (int k = 0; k < 20; k++) {
              mbar_wait(k >= S2 ? wb2 + 8 * k : bars + 8 * (l ? B_G1DONE + (WTAIL ? (k < 3 ? 15 + k : 13 + k) : 19) : (k == 5 ? B_XFREE : (k == 6 ? B_SFREE : B_REL))));
              mbar_expect_tx(fb2 + 8 * k, G2_WB);
              tma5(dst, &p.mCre + (k & 1), kc, 0, 0, 0, 10 * dg, fb2 + 8 * k);
              kc += (k & 1) << 7; if (k == 9) kc = 64;
              dst += G2_WB; if (dst == sb + G2_WOFF + S2 * G2_WB) dst = sb + G2_WOFF;
            }
          }
        }
      }
    } else if (pw == 1) {
#pragma unroll 1
      for (int l = 0; l < 2; l++) {
        if (l == 1) {
          mbar_wait(bars + 8 * (has2 ? B_G2DONE + 19 : B_G1DONE + 9));
          if (has2) mbar_wait(bars + 8 * B_UST);
          cnt_poll(&g_ucnt[gpc * 32], 128 * tag);
          fence_async_global();
          if (elect_one()) {
            TS(20);
            const int bytes = last ? 16384 : 20480;
            const uint8_t* src = g_u + T1 * 204800;
            uint32_t dst = sb + X1_OFF;
#pragma unroll 1
            for (int k = 0; k < 10; k++) {
              if (k > 4) mbar_wait(bars + 8 * (B_G1DONE + 5 + k));
              mbar_expect_tx(bars + 8 * (B_G1FULL + 10 + k), bytes);
              bulk_g2s(dst, src, bytes, bars + 8 * (B_G1FULL + 10 + k));
              src += 20480; dst += 20480; if (dst == sb + G_OFF) dst = sb; if (k == 4) dst = sb + X1_OFF;
            }
          }
          __syncwarp();
        }
        if (has2) {
          mbar_wait(bars + 8 * (B_HST + 2 * l));
          mbar_wait(bars + 8 * (B_G1DONE + 10 * l + 9));
          cnt_poll(&g_hcnt[(l * 16 + gpc) * 32], 40 * tag);
          fence_async_global();
          if (elect_one()) {
            TS(21 + 2 * l);
            const uint32_t fb2 = bars + 8 * (B_G2FULL + 20 * l), wb2 = bars + 8 * (B_G2DONE + 20 * l - S2);
            const uint8_t* src = g_h + (l * 32 + m2) * 163840;
            uint32_t dst = sb;
#pragma unroll 1
            for (int k = 0; k < 20; k++) {
              if (k >= (l ? XB0 : 5)) mbar_wait(k >= S2 ? wb2 + 8 * k : (l ? fb2 + 8 * (k - XB0) : bars + 8 * B_SFREE));
              if (k == 10) { mbar_wait(bars + 8 * (B_H1 + l)); fence_async_global(); }
              mbar_expect_tx(fb2 + 8 * k, G2_XB);
              bulk_g2s(dst, src, G2_XB, fb2 + 8 * k);
              src += 8192; dst += G2_XB; if (dst == sb + S2 * G2_XB) dst = sb;
            }
          }
          __syncwarp();
        }
      }
    } else if (pw == 2) {
#pragma unroll 1
      for (int l = 0; l < 2; l++) {
        if (l == 1) {
          float xa[2], xb[2];
          mbar_wait(bars + 8 * (B_G1FULL + 11));
          stat_table(T1, tag, 1, 4, g_stats, g_stats, xa, xb);
          mbar_arrive(bars + 8 * (B_STAB + 1));
        }
#pragma unroll 1
        for (int w = 0; w < 2 * l; w++) {
          mbar_wait(bars + 8 * (B_HST + 2 + w));
          if (lane < 4) h_release(2 + w, T1, lane);
          __syncwarp();
          if (lane == 0) { if (w == 0) mbar_arrive(bars + 8 * (B_REL + 1)); TS(w ? 16 : 14); }
        }
        if (l == 0 && has2 && elect_one()) {
#pragma unroll 1
          for (int i = 0; i < 5; i++) {
            const int c = i < 3 ? i : 7 - i;
            mbar_wait(bars + 8 * (B_CVDONE + c));
            bulk_s2g(g_G + (cch0 + 32 * c) * 4096, cv_stage(c), 4096);
          }
          asm volatile("cp.async.bulk.commit_group;" ::: "memory");
          asm volatile("cp.async.bulk.wait_group.read 0;" ::: "memory");
          mbar_arrive(bars + 8 * B_SFREE);
          asm volatile("cp.async.bulk.wait_group 0;" ::: "memory");
          TS(48);
          fence_async_global();
          asm volatile("fence.acq_rel.gpu;" ::: "memory");
#pragma unroll
          for (int i = 0; i < 4; i++) red_rlx(&g_gcnt[(dg * 4 + i) * 32]);
          TS(49);
          mbar_arrive(bars + 8 * (B_GO + 1));
        }
        __syncwarp();
      }
    } else if (has2) {
      mbar_wait(bars + 8 * B_REL);
      if (!CPF && elect_one()) {
        l2_prefetch(p.cre + (160 * dg + 5 * m2) * DM, 6400); l2_prefetch(p.cim + (160 * dg + 5 * m2) * DM, 6400);
      }
      mbar_wait(bars + 8 * (B_HST + 1));
      flag_poll(&g_hcnt[(8 + gpc) * 32], 40 * tag);
      if (lane == 0) { mbar_arrive(bars + 8 * B_H1); TS(22); }
      mbar_wait(bars + 8 * (B_GO + 1));
      flag_poll(&g_gcnt[(dg * 4 + (m2 >> 3)) * 32], 32 * tag);
      fence_async_global();
      if (elect_one()) {
        TS(29);
        mbar_expect_tx(bars + 8 * B_GFULL, 20480);
        tma5(sb + G_OFF, &p.mG, 64 * m2, 0, 0, 0, 10 * dg, bars + 8 * B_GFULL);
      }
      mbar_wait(bars + 8 * (B_HST + 3));
      cnt_poll(&g_hcnt[(24 + gpc) * 32], 40 * tag);
      if (lane == 0) { mbar_arrive(bars + 8 * (B_H1 + 1)); TS(24); }
    }
    } else if (wg == 2 && (role >> 16)) {
      float acc[80];
      float off[2] = {mean0[0], mean0[1]};
      const unsigned tag = lds32(sb + EP_OFF + 20);
      dskip_init<true>(acc, mean0, rstd0);
      mbar_arrive(bars + 8 * B_XFREE);
#pragma unroll 1
      for (int l = 0; l < 2; l++) {
        float mean[2], rstd[2];
        {
          uint32_t alo = desc_lo(sb, 1024), blo = desc_lo(sb + G2_WOFF, 16) + (WTAIL ? l * (G2_WB >> 2) : 0);
          uint32_t fb = bars + 8 * (B_G2FULL + 20 * l);
          fence_regs(acc);
          mbar_wait(bars + 8 * (B_CVDONE + 2));
          mbar_wait(bars + 8 * (B_CVDONE + 3));
          mbar_wait(fb);
          if (tid == 256) TS(33 + 6 * l);
#pragma unroll 1
          for (int k = 0; k < 20; k++) {
            if (l == TSL && (k & 3) == 3 && tid == 256) TS(56 + (k >> 2));
            uint32_t ok; const uint32_t nb = k < 19 ? fb + 8 : fb;
            wgmma_fence();
#pragma unroll
            for (int kk = 0; kk < 4; kk++) {
              wgmma_n160<1>(acc, alo + kk * 128, desc_hi(128, 0), blo + kk * 2, desc_hi(1024, 1));
              if (kk == 0) ok = mbar_test(nb);
            }
            wgmma_commit();
            alo += G2_XB >> 4; blo += G2_WB >> 4;
            if (alo == desc_lo(sb + S2 * G2_XB, 1024)) alo = desc_lo(sb, 1024);
            if (blo == desc_lo(sb + G_OFF, 16)) blo = desc_lo(sb + G2_WOFF, 16);
            wgmma_wait<1>();
            if (k > 0 && tid == 256) mbar_arrive(fb + 8 * (B_G2DONE - B_G2FULL - 1));
            if (!ok) mbar_wait(nb);
            fb += 8;
          }
          wgmma_wait<0>();
          fence_regs(acc);
          if (tid == 256) TS(34 + 6 * l);
          if (tid == 256) mbar_arrive(bars + 8 * (B_G2DONE + 20 * l + 19));
        }
        ROLE(role)
        const int tq = tid_opaque() & 31, n0 = 64 * m2 + 16 * w + (tq >> 2);
        stats_publish<false>(2 * l + 1, n0, dg, tag, acc);
        uint32_t gf[10][4];
        mbar_wait(bars + 8 * B_GFULL);
        const uint32_t ga = sb + G_OFF + (8 * (tq >> 4) + (tq & 7)) * 128 + (((2 * w + ((tq >> 3) & 1)) ^ ((2 * m2) & 6) ^ (tq & 7)) << 4);
#pragma unroll
        for (int J = 0; J < 2; J++) ldsm4t(gf[J], ga + J * 2048);
        if (tid == 256) TS(35 + 6 * l);
        uint8_t* dst[2][2];
#pragma unroll
        for (int h = 0; h < 2; h++) {
          if (l == 0) {
            const int ng = 8 * m2 + 2 * w + h, T = ng / 20;
            uint8_t* ub = g_u + (T * 204800 + (ng - 20 * T) * 1024 + (tq & 2) * 64 + (tq & 28) * 4 + (tq & 1) * 8 + (5 * dg >> 1) * 20480);
            dst[h][1] = ub + ((dg & 1) ? 20480 - 512 : 0);
            dst[h][0] = ub + (dg & 1) * 512;
          } else {
            dst[h][0] = dst[h][1] = (uint8_t*)(p.out + (n_to_t(n0 + 8 * h) * DM + 160 * dg + 4 * (tq & 3)));
          }
        }
        stats_get(2 * l + 1, n0, tag, mean, rstd);
        if (tid == 256) TS(36 + 6 * l);
        off[0] += mean[0]; off[1] += mean[1];
        const float ov[2] = {l ? off[0] : 0.f, l ? off[1] : 0.f};
#pragma unroll
        for (int J = 0; J < 10; J++) {
          if (J + 2 < 10) ldsm4t(gf[J + 2 < 10 ? J + 2 : 0], ga + (J + 2) * 2048);
#pragma unroll
          for (int x = 0; x < 8; x++) {
            const int h = (x >> 1) & 1;
            const uint32_t gwd = gf[J][x >> 1];
            const float t = fmaf(rstd[h], (x & 1) ? bf_hi(gwd) : bf_lo(gwd), 1.f);
            acc[8 * J + x] = fmaf(acc[8 * J + x], t, fmaf(-mean[h], t, ov[h]));
          }
#pragma unroll
          for (int h = 0; h < 2; h++) {
            if (l == 0)
              *(uint2*)(dst[h][(J >> 1) & 1] + (J >> 2) * 20480 + (J & 3) * 256) =
                  make_uint2(pack_bf16(acc[8 * J + 2 * h], acc[8 * J + 2 * h + 1]), pack_bf16(acc[8 * J + 4 + 2 * h], acc[8 * J + 5 + 2 * h]));
            else
              *(float4*)(dst[h][0] + 64 * J) = make_float4(acc[8 * J + 2 * h], acc[8 * J + 2 * h + 1], acc[8 * J + 4 + 2 * h], acc[8 * J + 5 + 2 * h]);
          }
          __syncwarp();
        }
        if (l == 0) {
          bar_sync(3, 128);
          if (tid == 288) { TS(37); mbar_arrive(bars + 8 * B_UST); }
          if (tid < 264) red_rel(&g_ucnt[(tid & 7) * 32]);
          __syncwarp();
          if (tid == 256) TS(38);
          stats_publish<false>(2, n0, dg, tag, acc);
          mbar_wait(bars + 8 * (B_G1FULL + 11));
          float xa[2], xb[2];
          const uint4* x0 = &g_stats[(8 + (tq & 3)) * SEQ + n0];
          stat_table(T1, tag, 1, w, x0, x0 + 8, xa, xb);
          mbar_arrive(bars + 8 * (B_STAB + 1));
          if (tid == 256) TS(27);
          stats_reduce(xa, xb, mean, rstd);
          off[0] += mean[0]; off[1] += mean[1];
          mbar_wait(bars + 8 * (B_HST + 2));
          dskip_init<false>(acc, mean, rstd);
        } else {
          if (tid == 256) {
            TS(43);
            if (m2 == 31 && dg == 3) asm volatile("st.relaxed.gpu.global.u32 [%0], %1;" ::"l"(g_epoch), "r"(tag + 1) : "memory");
          }
        }
      }
    }
  }
}

typedef CUresult (*EncFn)(CUtensorMap*, CUtensorMapDataType, cuuint32_t, void*, const cuuint64_t*, const cuuint64_t*,
                          const cuuint32_t*, const cuuint32_t*, CUtensorMapInterleave, CUtensorMapSwizzle,
                          CUtensorMapL2promotion, CUtensorMapFloatOOBfill);

void encode(EncFn fn, CUtensorMap* m, const void* ptr, int rank, const cuuint64_t* dims, const cuuint64_t* strides, const cuuint32_t* box,
            CUtensorMapSwizzle swz = CU_TENSOR_MAP_SWIZZLE_128B, int prom = 2) {
  cuuint32_t es[5] = {1, 1, 1, 1, 1};
  fn(m, CU_TENSOR_MAP_DATA_TYPE_BFLOAT16, rank, (void*)ptr, dims, strides, box, es, CU_TENSOR_MAP_INTERLEAVE_NONE,
     swz, (CUtensorMapL2promotion)prom, CU_TENSOR_MAP_FLOAT_OOB_FILL_NONE);
}

}

extern "C" void kernel_launch(void* const* d_in, const int* in_sizes, int n_in, void* d_out, int out_size) {
  (void)in_sizes; (void)n_in; (void)out_size;
  Params p;
  typedef const __nv_bfloat16* BP;
  p.x = (BP)d_in[0]; p.lre = (BP)d_in[1]; p.lim = (BP)d_in[2]; p.bre = (BP)d_in[3]; p.bim = (BP)d_in[4];
  p.cre = (BP)d_in[5]; p.cim = (BP)d_in[6]; p.logdt = (BP)d_in[7]; p.dskip = (BP)d_in[8];
  p.k = (BP)d_in[10]; p.v = (BP)d_in[11]; p.shiftk = (BP)d_in[12]; p.ssmk = (BP)d_in[13]; p.ssmD = (BP)d_in[14];
  p.out = (float*)d_out;
  for (int sm = 0; sm < 132; sm++) {
    const int tpc = sm >> 1, side = sm & 1;
    int gpc, gi;
    if (tpc < 32) { gpc = tpc & 7; gi = tpc >> 3; }
    else if (tpc < 60) { gpc = 1 + (tpc - 32) % 7; gi = 4 + (tpc - 32) / 7; }
    else if (tpc < 62) { gpc = tpc - 54; gi = 8; }
    else { gpc = 0; gi = tpc - 58; }
    const int pos = 8 * gpc + gi + (gpc == 7 ? 1 : 0);
    int T1, GP;
    if (pos < 52) { const int hh = pos / 26, x = pos - 26 * hh; T1 = x >> 1; GP = 2 * hh + (x & 1); }
    else { T1 = pos - 52; GP = 4; }
    const int m2 = 8 * (gpc >> 1) + gi, dg = 2 * (gpc & 1) + side;
    p.role[sm] = pos == 65 ? -1 : (T1 | (GP << 4) | (side << 7) | (m2 << 8) | (dg << 14) | ((gi < 8) << 16));
  }
  void* fnp = nullptr;
  cudaDriverEntryPointQueryResult qr;
  cudaGetDriverEntryPoint("cuTensorMapEncodeTiled", &fnp, cudaEnableDefault, &qr);
  EncFn fn = (EncFn)fnp;
  void* gG = nullptr;
  cudaGetSymbolAddress(&gG, g_G);
  void* gKV = nullptr;
  cudaGetSymbolAddress(&gKV, g_kv);
  {
    cuuint64_t dims[5] = {32, 32, 10, 32, 4}, st[4] = {20480, 2048, 64, 655360}; cuuint32_t box[5] = {32, 35, 2, 1, 1};
    encode(fn, &p.mU, gKV, 5, dims, st, box, CU_TENSOR_MAP_SWIZZLE_NONE, 1);
  }
  const cuuint64_t RB = DM * 2;
  {
    p.swap = p.bim < p.bre;
    const char* lo = (const char*)(p.swap ? p.bim : p.bre); const char* hi = (const char*)(p.swap ? p.bre : p.bim);
    cuuint64_t dims[5] = {640, 8, 2, 8, 10}, st[4] = {RB, (cuuint64_t)(hi - lo), 8 * RB, 64 * RB}; cuuint32_t box[5] = {64, 8, 2, 4, 2};
    encode(fn, &p.mB, lo, 5, dims, st, box);
  }
  {
    cuuint64_t dims[5] = {640, 2, 4, 2, 40}, st[4] = {RB, 4 * RB, 2 * RB, 16 * RB}; cuuint32_t box[5] = {64, 2, 4, 2, 10};
    encode(fn, &p.mCre, p.cre, 5, dims, st, box); encode(fn, &p.mCim, p.cim, 5, dims, st, box);
    cuuint64_t dimg[5] = {2048, 2, 4, 2, 40}, stg[4] = {4096, 4 * 4096, 2 * 4096, 16 * 4096};
    encode(fn, &p.mG, gG, 5, dimg, stg, box);
  }
  {
    cuuint64_t dims[4] = {640, 2, 4, 900}, st[3] = {RB, 40 * RB, 2 * RB}; cuuint32_t box[4] = {64, 2, 4, 20};
    encode(fn, &p.mX, p.x, 4, dims, st, box);
    cuuint64_t diml[4] = {640, 2, 4, 16}, stl[3] = {RB, 32 * RB, 2 * RB};
    encode(fn, &p.mXl, p.x + (size_t)1920 * DM, 4, diml, stl, box);
    cuuint32_t boxt[4] = {160, 2, 4, 4};
    encode(fn, &p.mXt, p.x, 4, dims, st, boxt, CU_TENSOR_MAP_SWIZZLE_NONE);
    encode(fn, &p.mXtl, p.x + (size_t)1920 * DM, 4, diml, stl, boxt, CU_TENSOR_MAP_SWIZZLE_NONE);
    cuuint64_t dk[3] = {640, 2000, 4}, sk[2] = {RB, 16 * RB}; cuuint32_t bk[3] = {32, 19, 4}, bv[3] = {32, 17, 4};
    encode(fn, &p.mK, p.k, 3, dk, sk, bk, CU_TENSOR_MAP_SWIZZLE_NONE);
    encode(fn, &p.mV, p.v, 3, dk, sk, bv, CU_TENSOR_MAP_SWIZZLE_NONE);
  }
  cudaFuncSetAttribute(fused_kernel, cudaFuncAttributeMaxDynamicSharedMemorySize, SMEM_BYTES);
  cudaLaunchConfig_t cfg = {};
  cfg.gridDim = dim3(132); cfg.blockDim = dim3(512); cfg.dynamicSmemBytes = SMEM_BYTES; cfg.stream = cudaStreamPerThread;
  cudaLaunchKernelEx(&cfg, fused_kernel, p);
}
```

```cpp
#include <cuda_runtime.h>
#include <cuda.h>
#include <cuda_bf16.h>
#include <stdint.h>

namespace {

constexpr int SEQ = 2048, DM = 640;
constexpr int NT1 = 13;
#define EXP 0
#define WPF1 3
#define WPF2 7
#define CPOLL 10
#define KV0 1
#define TAPLATE 1
#define STG_D 3
#define STG_KK 1
#define HOLD0 1
#define WREL 0
#define UREL 1
#define TSL 1
#define STG0 2
#define WTAIL 1
#define PFD 1
#define TAPW 1
#define TPF 4
#define CPF 0
#define MK0 7
#define MK1 4
#define PACE 180
#define XB0 3
#define TAPN 2
#define PAUSE_K 5
constexpr uint32_t SPIN_LIMIT = 1u << 22;

__device__ __align__(1024) uint8_t g_h[2 * 32 * 20 * 8192];
__device__ __align__(1024) uint8_t g_u[NT1 * 10 * 20480];
__device__ __align__(1024) uint8_t g_kv[DM * 4096];
__device__ __align__(1024) uint8_t g_G[DM * 4096];
__device__ __align__(128) uint4 g_E[2 * NT1 * DM];
__device__ __align__(128) uint4 g_stats[4 * 4 * SEQ];
__device__ __align__(128) uint4 g_sB[DM * 2];
__device__ __align__(128) unsigned g_hcnt[2 * 2 * 8 * 32];
__device__ __align__(128) unsigned g_ucnt[8 * 32];
__device__ __align__(128) unsigned g_kvcnt[16 * 32];
__device__ __align__(128) unsigned g_gcnt[16 * 32];
__device__ __align__(128) unsigned g_epoch[32] = {1};
#define TS(i) do {} while (0)

struct Params {
  CUtensorMap mX, mB, mXl, mK, mV, mXt, mXtl, mCre, mCim, mG, mU;
  const __nv_bfloat16 *x, *lre, *lim, *bre, *bim, *cre, *cim, *logdt, *dskip, *k, *v, *shiftk, *ssmk, *ssmD;
  float* out;
  int swap;
  int role[132];
};

constexpr uint32_t sb = 1024;
constexpr uint32_t G1_STAGE = 36864, G1_XOFF = 16384;
constexpr int S1 = 4;
constexpr uint32_t XT_OFF = 159744, KS_OFF = 180224, KV_PIECE = 9216;
constexpr uint32_t G2_XB = 8192, G2_WB = 20480, G2_WOFF = 57344, G_OFF = 200704;
constexpr uint32_t X1_OFF = 139264;
constexpr int S2 = 7;
constexpr uint32_t CV_OFF = KS_OFF, CV_K = 128, CV_PL = 2240, CV_U = CV_K + 4096, CV_B = KV_PIECE;
constexpr uint32_t MISC = 226304;
constexpr uint32_t BAR_OFF = MISC;
constexpr int B_G1FULL = 0, B_G1DONE = 20, B_G2FULL = 40,
              B_G2DONE = 85, B_GFULL = 125, B_EP = 126, B_H1 = 127  , B_CVFULL = 129  , B_STG = 134  , B_REL = 136  , B_SFREE = 138, B_UST = 142,
              B_GO = 139  , B_PUB = 147,
              B_CVDONE = 148  , B_STAB = 153  , B_XFREE = 155, B_HST = 156  ,
              B_CTAB = 160, B_PREP = 161, B_XT = 162, B_KV = 163  , B_PREP2 = 84, B_PD = 168  ;
constexpr uint32_t bars = sb + BAR_OFF;
constexpr uint32_t STAB_OFF = MISC + 1392;
constexpr uint32_t CTAB_OFF = STAB_OFF + 640;
constexpr uint32_t DTAB_OFF = CTAB_OFF + 1536;
constexpr uint32_t EP_OFF = DTAB_OFF + 320;
constexpr uint32_t SO_OFF = EP_OFF + 32;
constexpr uint32_t TAP_OFF = 147456;
constexpr uint32_t MX0_OFF = TAP_OFF + 1280, MX1_OFF = G_OFF + 20480;
constexpr uint32_t SMEM_BYTES = 232448;
static_assert(SO_OFF + 1536 <= SMEM_BYTES, "smem");

__device__ __forceinline__ void trap_if(bool c) { asm volatile("{\n.reg .pred p;\nsetp.ne.u32 p, %0, 0;\n@p trap;\n}\n" ::"r"((uint32_t)c)); }
__device__ __forceinline__ uint32_t smem_u32(const void* p) { return (uint32_t)__cvta_generic_to_shared(p); }
__device__ __forceinline__ void mbar_init(uint32_t bar, int cnt) { asm volatile("mbarrier.init.shared::cta.b64 [%0], %1;" ::"r"(bar), "r"(cnt) : "memory"); }
__device__ __forceinline__ void mbar_expect_tx(uint32_t bar, int bytes) { asm volatile("mbarrier.arrive.expect_tx.shared::cta.b64 _, [%0], %1;" ::"r"(bar), "r"(bytes) : "memory"); }
__device__ __forceinline__ void mbar_arrive(uint32_t bar) { asm volatile("mbarrier.arrive.shared::cta.b64 _, [%0];" ::"r"(bar) : "memory"); }
__device__ __forceinline__ void mbar_wait(uint32_t bar) {
  asm volatile(
      "{\n.reg .pred p;\n.reg .u32 c;\nmov.u32 c, 0;\n"
      "W_%=:\nmbarrier.try_wait.parity.shared::cta.b64 p, [%0], 0;\n@p bra D_%=;\n"
      "add.u32 c, c, 1;\nsetp.lt.u32 p, c, %1;\n@p bra W_%=;\ntrap;\nD_%=:\n}\n" ::"r"(bar), "n"(SPIN_LIMIT) : "memory");
}
__device__ __forceinline__ uint32_t mbar_test(uint32_t bar) {
  uint32_t ok;
  asm volatile("{\n.reg .pred p;\nmbarrier.test_wait.parity.shared::cta.b64 p, [%1], 0;\nselp.u32 %0, 1, 0, p;\n}\n" : "=r"(ok) : "r"(bar) : "memory");
  return ok;
}
__device__ __forceinline__ void tma3(uint32_t dst, const CUtensorMap* m, int c0, int c1, int c2, uint32_t bar) {
  asm volatile("cp.async.bulk.tensor.3d.shared::cluster.global.mbarrier::complete_tx::bytes [%0], [%1, {%3,%4,%5}], [%2];"
               ::"r"(dst), "l"(m), "r"(bar), "r"(c0), "r"(c1), "r"(c2) : "memory");
}
__device__ __forceinline__ void tma4(uint32_t dst, const CUtensorMap* m, int c0, int c1, int c2, int c3, uint32_t bar) {
  asm volatile("cp.async.bulk.tensor.4d.shared::cluster.global.mbarrier::complete_tx::bytes [%0], [%1, {%3,%4,%5,%6}], [%2];"
               ::"r"(dst), "l"(m), "r"(bar), "r"(c0), "r"(c1), "r"(c2), "r"(c3) : "memory");
}
__device__ __forceinline__ void tma5(uint32_t dst, const CUtensorMap* m, int c0, int c1, int c2, int c3, int c4, uint32_t bar) {
  asm volatile("cp.async.bulk.tensor.5d.shared::cluster.global.mbarrier::complete_tx::bytes [%0], [%1, {%3,%4,%5,%6,%7}], [%2];"
               ::"r"(dst), "l"(m), "r"(bar), "r"(c0), "r"(c1), "r"(c2), "r"(c3), "r"(c4) : "memory");
}
__device__ __forceinline__ void bulk_g2s(uint32_t dst, const void* src, int bytes, uint32_t bar) {
  asm volatile("cp.async.bulk.shared::cluster.global.mbarrier::complete_tx::bytes [%0], [%1], %2, [%3];"
               ::"r"(dst), "l"(src), "r"(bytes), "r"(bar) : "memory");
}
__device__ __forceinline__ void bulk_s2g(void* dst, uint32_t src, int bytes) {
  asm volatile("cp.async.bulk.global.shared::cta.bulk_group [%0], [%1], %2;" ::"l"(dst), "r"(src), "r"(bytes) : "memory");
}
__device__ __forceinline__ void l2_prefetch(const void* src, int bytes) {
  asm volatile("cp.async.bulk.prefetch.L2.global [%0], %1;" ::"l"(src), "r"(bytes) : "memory");
}
__device__ __forceinline__ void wgmma_fence() { asm volatile("wgmma.fence.sync.aligned;" ::: "memory"); }
__device__ __forceinline__ void wgmma_commit() { asm volatile("wgmma.commit_group.sync.aligned;" ::: "memory"); }
template <int N> __device__ __forceinline__ void wgmma_wait() { asm volatile("wgmma.wait_group.sync.aligned %0;" ::"n"(N) : "memory"); }
__host__ __device__ constexpr uint32_t desc_lo(uint32_t addr, uint32_t lbo) { return ((addr & 0x3FFFF) >> 4) | ((lbo >> 4) << 16); }
__host__ __device__ constexpr uint32_t desc_hi(uint32_t sbo, uint32_t swz) { return (sbo >> 4) | (swz << 30); }
__device__ __forceinline__ void bar_sync(int id, int n) { asm volatile("bar.sync %0, %1;" ::"r"(id), "r"(n) : "memory"); }
__device__ __forceinline__ uint32_t lds32(uint32_t a) { uint32_t v; asm volatile("ld.shared.u32 %0, [%1];" : "=r"(v) : "r"(a) : "memory"); return v; }
__device__ __forceinline__ float2 lds64f(uint32_t a) { float2 v; asm volatile("ld.shared.v2.f32 {%0,%1}, [%2];" : "=f"(v.x), "=f"(v.y) : "r"(a) : "memory"); return v; }
__device__ __forceinline__ float4 lds128f(uint32_t a) { float4 v; asm volatile("ld.shared.v4.f32 {%0,%1,%2,%3}, [%4];" : "=f"(v.x), "=f"(v.y), "=f"(v.z), "=f"(v.w) : "r"(a) : "memory"); return v; }
__device__ __forceinline__ void ldsm4t(uint32_t (&r)[4], uint32_t a) {
  asm volatile("ldmatrix.sync.aligned.m8n8.x4.trans.shared.b16 {%0,%1,%2,%3}, [%4];" : "=r"(r[0]), "=r"(r[1]), "=r"(r[2]), "=r"(r[3]) : "r"(a) : "memory");
}
__device__ __forceinline__ uint4 ldv128(const void* a) { uint4 v; asm volatile("ld.global.nc.v4.u32 {%0,%1,%2,%3}, [%4];" : "=r"(v.x), "=r"(v.y), "=r"(v.z), "=r"(v.w) : "l"(a) : "memory"); return v; }
__device__ __forceinline__ uint2 ldv64(const void* a) { uint2 v; asm volatile("ld.global.nc.v2.u32 {%0,%1}, [%2];" : "=r"(v.x), "=r"(v.y) : "l"(a) : "memory"); return v; }
__device__ __forceinline__ uint32_t ldv16(const void* a) { uint32_t v; asm volatile("ld.global.nc.u16 %0, [%1];" : "=r"(v) : "l"(a) : "memory"); return v; }
__device__ __forceinline__ void sts128(uint32_t a, uint4 v) { asm volatile("st.shared.v4.u32 [%0], {%1,%2,%3,%4};" ::"r"(a), "r"(v.x), "r"(v.y), "r"(v.z), "r"(v.w) : "memory"); }
__device__ __forceinline__ void sts32(uint32_t a, uint32_t v) { asm volatile("st.shared.u32 [%0], %1;" ::"r"(a), "r"(v) : "memory"); }
__device__ __forceinline__ void sts64f(uint32_t a, float x, float y) { asm volatile("st.shared.v2.f32 [%0], {%1,%2};" ::"r"(a), "f"(x), "f"(y) : "memory"); }
__device__ __forceinline__ void red_rlx(unsigned* p) { asm volatile("red.relaxed.gpu.global.add.u32 [%0], 1;" ::"l"(p) : "memory"); }
__device__ __forceinline__ void red_rel(unsigned* p) { asm volatile("red.release.gpu.global.add.u32 [%0], 1;" ::"l"(p) : "memory"); }
__device__ __forceinline__ void fence_async_global() { asm volatile("fence.proxy.async.global;" ::: "memory"); }
__device__ __forceinline__ void fence_async_smem() { asm volatile("fence.proxy.async.shared::cta;" ::: "memory"); }
__device__ __forceinline__ void rec_st(uint4* p, float a, float b, unsigned tag) {
  asm volatile("{\n.reg .b128 t;\n.reg .b64 lo, hi;\nmov.b64 lo, {%1,%2};\nmov.b64 hi, {%3,%3};\nmov.b128 t, {lo,hi};\n"
               "st.relaxed.gpu.global.b128 [%0], t;\n}\n" ::"l"(p), "r"(__float_as_uint(a)), "r"(__float_as_uint(b)), "r"(tag) : "memory");
}
__device__ __forceinline__ unsigned rec_ld(const uint4* p, float& a, float& b) {
  unsigned x, y, t;
  asm volatile("{\n.reg .b128 t;\n.reg .b64 lo, hi;\n.reg .b32 u;\nld.relaxed.gpu.global.b128 t, [%3];\nmov.b128 {lo,hi}, t;\n"
               "mov.b64 {%0,%1}, lo;\nmov.b64 {%2,u}, hi;\n}\n" : "=r"(x), "=r"(y), "=r"(t) : "l"(p) : "memory");
  a = __uint_as_float(x); b = __uint_as_float(y);
  return t;
}
__device__ __forceinline__ unsigned ld_rlx(const unsigned* p) { unsigned v; asm volatile("ld.relaxed.gpu.global.u32 %0, [%1];" : "=r"(v) : "l"(p) : "memory"); return v; }
__device__ __forceinline__ void flag_poll(const unsigned* p, unsigned target) {
  uint32_t it = 0;
  while (!__all_sync(0xffffffffu, (int)(ld_rlx(p) - target) >= 0)) { trap_if(++it > SPIN_LIMIT); }
  asm volatile("fence.acquire.gpu;" ::: "memory");
}
__device__ __forceinline__ void cnt_poll(const unsigned* p, unsigned target) {
  unsigned a = ld_rlx(p); __nanosleep(100);
  unsigned b = ld_rlx(p); __nanosleep(100);
  unsigned c = ld_rlx(p);
  uint32_t it = 0;
  while (true) {
    if (__all_sync(0xffffffffu, (int)(a - target) >= 0)) break;
    a = ld_rlx(p);
    if (__all_sync(0xffffffffu, (int)(b - target) >= 0)) break;
    b = ld_rlx(p);
    if (__all_sync(0xffffffffu, (int)(c - target) >= 0)) break;
    c = ld_rlx(p);
    trap_if(++it > SPIN_LIMIT);
  }
  asm volatile("fence.acquire.gpu;" ::: "memory");
}
__device__ __forceinline__ void h_release(int idx, int T, int i) {
  const int Q = (i & 2) ? (T + 2) / 3 - 1 : T / 3;
  if (Q >= 0 && Q < 4 && ((i & 2) == 0 || T % 3 == 0)) red_rel(&g_hcnt[(idx * 8 + 2 * Q + (i & 1)) * 32]);
}
__device__ __forceinline__ uint32_t pack_bf16(float lo, float hi) {
  uint32_t r; asm("cvt.rn.bf16x2.f32 %0, %1, %2;" : "=r"(r) : "f"(hi), "f"(lo)); return r;
}
__device__ __forceinline__ float bf_lo(uint32_t w) { return __uint_as_float(w << 16); }
__device__ __forceinline__ float bf_hi(uint32_t w) { return __uint_as_float(w & 0xffff0000u); }
__device__ __forceinline__ uint32_t hmul2(uint32_t a, uint32_t b) {
  __nv_bfloat162 r = __hmul2_rn(*(__nv_bfloat162*)&a, *(__nv_bfloat162*)&b); return *(uint32_t*)&r;
}
__device__ __forceinline__ uint32_t hadd2(uint32_t a, uint32_t b) {
  __nv_bfloat162 r = __hadd2_rn(*(__nv_bfloat162*)&a, *(__nv_bfloat162*)&b); return *(uint32_t*)&r;
}
__device__ __forceinline__ float2 cmul(float2 a, float2 b) { return make_float2(a.x * b.x - a.y * b.y, a.x * b.y + a.y * b.x); }
__device__ __forceinline__ float2 cfma(float2 a, float2 b, float2 c) {
  return make_float2(fmaf(a.x, b.x, fmaf(-a.y, b.y, c.x)), fmaf(a.x, b.y, fmaf(a.y, b.x, c.y)));
}
template <int N> __device__ __forceinline__ void fence_regs(float (&a)[N]) {
#pragma unroll
  for (int i = 0; i < N; i++) asm volatile("" : "+f"(a[i])::"memory");
}
__device__ __forceinline__ bool elect_one() {
  uint32_t e; asm volatile("{\n.reg .pred P;\nelect.sync _|P, 0xffffffff;\nselp.u32 %0, 1, 0, P;\n}\n" : "=r"(e)); return e != 0;
}
__device__ __forceinline__ int tid_opaque() { int t; asm volatile("mov.u32 %0, %%tid.x;" : "=r"(t)); return t; }
struct Role { int T1, GP, side, m2, dg, cch0; bool last, has2; };
__device__ __forceinline__ Role unpack_role(int x) {
  Role r; r.T1 = x & 15; r.GP = (x >> 4) & 7; r.side = (x >> 7) & 1; r.m2 = (x >> 8) & 63; r.dg = (x >> 14) & 3;
  r.has2 = (x >> 16) & 1; r.last = r.T1 == NT1 - 1; r.cch0 = 160 * r.dg + r.m2; return r;
}
__device__ __forceinline__ Role fresh_role(int x) { asm volatile("" : "+r"(x)); return unpack_role(__shfl_sync(0xffffffffu, x, 0)); }
#define ROLE(x) const Role R_ = fresh_role(x); const int T1 = R_.T1, GP = R_.GP, side = R_.side, m2 = R_.m2, dg = R_.dg, cch0 = R_.cch0; \
  const bool last = R_.last, has2 = R_.has2; (void)T1; (void)GP; (void)side; (void)m2; (void)dg; (void)cch0; (void)last; (void)has2;
__device__ __forceinline__ int n_to_t(int n) {
  int T = n / 160, nl = n - T * 160;
  int L = (T == NT1 - 1) ? 32 : 40;
  return T * 160 + L * ((nl & 7) >> 1) + 2 * (nl >> 3) + (nl & 1);
}

template<int TA> __device__ __forceinline__ void wgmma_n160(float (&d)[80], uint32_t alo, uint32_t ahi, uint32_t blo, uint32_t bhi){
  asm volatile("{\n.reg .b64 da, db;\nmov.b64 da, {%80,%81};\nmov.b64 db, {%82,%83};\n"
    "wgmma.mma_async.sync.aligned.m64n160k16.f32.bf16.bf16 {%0, %1, %2, %3, %4, %5, %6, %7, %8, %9, %10, %11, %12, %13, %14, %15, %16, %17, %18, %19, %20, %21, %22, %23, %24, %25, %26, %27, %28, %29, %30, %31, %32, %33, %34, %35, %36, %37, %38, %39, %40, %41, %42, %43, %44, %45, %46, %47, %48, %49, %50, %51, %52, %53, %54, %55, %56, %57, %58, %59, %60, %61, %62, %63, %64, %65, %66, %67, %68, %69, %70, %71, %72, %73, %74, %75, %76, %77, %78, %79}, da, db, 1, 1, 1, %84, 0;\n}\n"
    : "+f"(d[0]), "+f"(d[1]), "+f"(d[2]), "+f"(d[3]), "+f"(d[4]), "+f"(d[5]), "+f"(d[6]), "+f"(d[7]), "+f"(d[8]), "+f"(d[9]), "+f"(d[10]), "+f"(d[11]), "+f"(d[12]), "+f"(d[13]), "+f"(d[14]), "+f"(d[15]), "+f"(d[16]), "+f"(d[17]), "+f"(d[18]), "+f"(d[19]), "+f"(d[20]), "+f"(d[21]), "+f"(d[22]), "+f"(d[23]), "+f"(d[24]), "+f"(d[25]), "+f"(d[26]), "+f"(d[27]), "+f"(d[28]), "+f"(d[29]), "+f"(d[30]), "+f"(d[31]), "+f"(d[32]), "+f"(d[33]), "+f"(d[34]), "+f"(d[35]), "+f"(d[36]), "+f"(d[37]), "+f"(d[38]), "+f"(d[39]), "+f"(d[40]), "+f"(d[41]), "+f"(d[42]), "+f"(d[43]), "+f"(d[44]), "+f"(d[45]), "+f"(d[46]), "+f"(d[47]), "+f"(d[48]), "+f"(d[49]), "+f"(d[50]), "+f"(d[51]), "+f"(d[52]), "+f"(d[53]), "+f"(d[54]), "+f"(d[55]), "+f"(d[56]), "+f"(d[57]), "+f"(d[58]), "+f"(d[59]), "+f"(d[60]), "+f"(d[61]), "+f"(d[62]), "+f"(d[63]), "+f"(d[64]), "+f"(d[65]), "+f"(d[66]), "+f"(d[67]), "+f"(d[68]), "+f"(d[69]), "+f"(d[70]), "+f"(d[71]), "+f"(d[72]), "+f"(d[73]), "+f"(d[74]), "+f"(d[75]), "+f"(d[76]), "+f"(d[77]), "+f"(d[78]), "+f"(d[79])
    : "r"(alo), "r"(ahi), "r"(blo), "r"(bhi), "n"(TA));
}
__device__ __forceinline__ void wgmma_rs_n160(float (&d)[80], uint32_t a0, uint32_t a1, uint32_t a2, uint32_t a3, uint32_t blo){
  asm volatile("{\n.reg .b64 db;\nmov.b64 db, {%84,8};\nwgmma.mma_async.sync.aligned.m64n160k16.f32.bf16.bf16 {%0, %1, %2, %3, %4, %5, %6, %7, %8, %9, %10, %11, %12, %13, %14, %15, %16, %17, %18, %19, %20, %21, %22, %23, %24, %25, %26, %27, %28, %29, %30, %31, %32, %33, %34, %35, %36, %37, %38, %39, %40, %41, %42, %43, %44, %45, %46, %47, %48, %49, %50, %51, %52, %53, %54, %55, %56, %57, %58, %59, %60, %61, %62, %63, %64, %65, %66, %67, %68, %69, %70, %71, %72, %73, %74, %75, %76, %77, %78, %79}, {%80,%81,%82,%83}, db, 1, 1, 1, 0;\n}\n"
    : "+f"(d[0]), "+f"(d[1]), "+f"(d[2]), "+f"(d[3]), "+f"(d[4]), "+f"(d[5]), "+f"(d[6]), "+f"(d[7]), "+f"(d[8]), "+f"(d[9]), "+f"(d[10]), "+f"(d[11]), "+f"(d[12]), "+f"(d[13]), "+f"(d[14]), "+f"(d[15]), "+f"(d[16]), "+f"(d[17]), "+f"(d[18]), "+f"(d[19]), "+f"(d[20]), "+f"(d[21]), "+f"(d[22]), "+f"(d[23]), "+f"(d[24]), "+f"(d[25]), "+f"(d[26]), "+f"(d[27]), "+f"(d[28]), "+f"(d[29]), "+f"(d[30]), "+f"(d[31]), "+f"(d[32]), "+f"(d[33]), "+f"(d[34]), "+f"(d[35]), "+f"(d[36]), "+f"(d[37]), "+f"(d[38]), "+f"(d[39]), "+f"(d[40]), "+f"(d[41]), "+f"(d[42]), "+f"(d[43]), "+f"(d[44]), "+f"(d[45]), "+f"(d[46]), "+f"(d[47]), "+f"(d[48]), "+f"(d[49]), "+f"(d[50]), "+f"(d[51]), "+f"(d[52]), "+f"(d[53]), "+f"(d[54]), "+f"(d[55]), "+f"(d[56]), "+f"(d[57]), "+f"(d[58]), "+f"(d[59]), "+f"(d[60]), "+f"(d[61]), "+f"(d[62]), "+f"(d[63]), "+f"(d[64]), "+f"(d[65]), "+f"(d[66]), "+f"(d[67]), "+f"(d[68]), "+f"(d[69]), "+f"(d[70]), "+f"(d[71]), "+f"(d[72]), "+f"(d[73]), "+f"(d[74]), "+f"(d[75]), "+f"(d[76]), "+f"(d[77]), "+f"(d[78]), "+f"(d[79])
    : "r"(a0), "r"(a1), "r"(a2), "r"(a3), "r"(blo));
}
template<int N> __device__ __forceinline__ void wgmma_rs_hi(float (&d)[64], uint32_t a0, uint32_t a1, uint32_t a2, uint32_t a3, uint32_t blo);
template<> __device__ __forceinline__ void wgmma_rs_hi<16>(float (&d)[64], uint32_t a0, uint32_t a1, uint32_t a2, uint32_t a3, uint32_t blo){
  asm volatile("{\n.reg .b64 db;\nmov.b64 db, {%12,8};\nwgmma.mma_async.sync.aligned.m64n16k16.f32.bf16.bf16 {%0, %1, %2, %3, %4, %5, %6, %7}, {%8,%9,%10,%11}, db, 1, 1, 1, 0;\n}\n"
    : "+f"(d[56]), "+f"(d[57]), "+f"(d[58]), "+f"(d[59]), "+f"(d[60]), "+f"(d[61]), "+f"(d[62]), "+f"(d[63])
    : "r"(a0), "r"(a1), "r"(a2), "r"(a3), "r"(blo));
}
template<> __device__ __forceinline__ void wgmma_rs_hi<32>(float (&d)[64], uint32_t a0, uint32_t a1, uint32_t a2, uint32_t a3, uint32_t blo){
  asm volatile("{\n.reg .b64 db;\nmov.b64 db, {%20,8};\nwgmma.mma_async.sync.aligned.m64n32k16.f32.bf16.bf16 {%0, %1, %2, %3, %4, %5, %6, %7, %8, %9, %10, %11, %12, %13, %14, %15}, {%16,%17,%18,%19}, db, 1, 1, 1, 0;\n}\n"
    : "+f"(d[48]), "+f"(d[49]), "+f"(d[50]), "+f"(d[51]), "+f"(d[52]), "+f"(d[53]), "+f"(d[54]), "+f"(d[55]), "+f"(d[56]), "+f"(d[57]), "+f"(d[58]), "+f"(d[59]), "+f"(d[60]), "+f"(d[61]), "+f"(d[62]), "+f"(d[63])
    : "r"(a0), "r"(a1), "r"(a2), "r"(a3), "r"(blo));
}
template<> __device__ __forceinline__ void wgmma_rs_hi<48>(float (&d)[64], uint32_t a0, uint32_t a1, uint32_t a2, uint32_t a3, uint32_t blo){
  asm volatile("{\n.reg .b64 db;\nmov.b64 db, {%28,8};\nwgmma.mma_async.sync.aligned.m64n48k16.f32.bf16.bf16 {%0, %1, %2, %3, %4, %5, %6, %7, %8, %9, %10, %11, %12, %13, %14, %15, %16, %17, %18, %19, %20, %21, %22, %23}, {%24,%25,%26,%27}, db, 1, 1, 1, 0;\n}\n"
    : "+f"(d[40]), "+f"(d[41]), "+f"(d[42]), "+f"(d[43]), "+f"(d[44]), "+f"(d[45]), "+f"(d[46]), "+f"(d[47]), "+f"(d[48]), "+f"(d[49]), "+f"(d[50]), "+f"(d[51]), "+f"(d[52]), "+f"(d[53]), "+f"(d[54]), "+f"(d[55]), "+f"(d[56]), "+f"(d[57]), "+f"(d[58]), "+f"(d[59]), "+f"(d[60]), "+f"(d[61]), "+f"(d[62]), "+f"(d[63])
    : "r"(a0), "r"(a1), "r"(a2), "r"(a3), "r"(blo));
}
template<> __device__ __forceinline__ void wgmma_rs_hi<64>(float (&d)[64], uint32_t a0, uint32_t a1, uint32_t a2, uint32_t a3, uint32_t blo){
  asm volatile("{\n.reg .b64 db;\nmov.b64 db, {%36,8};\nwgmma.mma_async.sync.aligned.m64n64k16.f32.bf16.bf16 {%0, %1, %2, %3, %4, %5, %6, %7, %8, %9, %10, %11, %12, %13, %14, %15, %16, %17, %18, %19, %20, %21, %22, %23, %24, %25, %26, %27, %28, %29, %30, %31}, {%32,%33,%34,%35}, db, 1, 1, 1, 0;\n}\n"
    : "+f"(d[32]), "+f"(d[33]), "+f"(d[34]), "+f"(d[35]), "+f"(d[36]), "+f"(d[37]), "+f"(d[38]), "+f"(d[39]), "+f"(d[40]), "+f"(d[41]), "+f"(d[42]), "+f"(d[43]), "+f"(d[44]), "+f"(d[45]), "+f"(d[46]), "+f"(d[47]), "+f"(d[48]), "+f"(d[49]), "+f"(d[50]), "+f"(d[51]), "+f"(d[52]), "+f"(d[53]), "+f"(d[54]), "+f"(d[55]), "+f"(d[56]), "+f"(d[57]), "+f"(d[58]), "+f"(d[59]), "+f"(d[60]), "+f"(d[61]), "+f"(d[62]), "+f"(d[63])
    : "r"(a0), "r"(a1), "r"(a2), "r"(a3), "r"(blo));
}
template<> __device__ __forceinline__ void wgmma_rs_hi<80>(float (&d)[64], uint32_t a0, uint32_t a1, uint32_t a2, uint32_t a3, uint32_t blo){
  asm volatile("{\n.reg .b64 db;\nmov.b64 db, {%44,8};\nwgmma.mma_async.sync.aligned.m64n80k16.f32.bf16.bf16 {%0, %1, %2, %3, %4, %5, %6, %7, %8, %9, %10, %11, %12, %13, %14, %15, %16, %17, %18, %19, %20, %21, %22, %23, %24, %25, %26, %27, %28, %29, %30, %31, %32, %33, %34, %35, %36, %37, %38, %39}, {%40,%41,%42,%43}, db, 1, 1, 1, 0;\n}\n"
    : "+f"(d[24]), "+f"(d[25]), "+f"(d[26]), "+f"(d[27]), "+f"(d[28]), "+f"(d[29]), "+f"(d[30]), "+f"(d[31]), "+f"(d[32]), "+f"(d[33]), "+f"(d[34]), "+f"(d[35]), "+f"(d[36]), "+f"(d[37]), "+f"(d[38]), "+f"(d[39]), "+f"(d[40]), "+f"(d[41]), "+f"(d[42]), "+f"(d[43]), "+f"(d[44]), "+f"(d[45]), "+f"(d[46]), "+f"(d[47]), "+f"(d[48]), "+f"(d[49]), "+f"(d[50]), "+f"(d[51]), "+f"(d[52]), "+f"(d[53]), "+f"(d[54]), "+f"(d[55]), "+f"(d[56]), "+f"(d[57]), "+f"(d[58]), "+f"(d[59]), "+f"(d[60]), "+f"(d[61]), "+f"(d[62]), "+f"(d[63])
    : "r"(a0), "r"(a1), "r"(a2), "r"(a3), "r"(blo));
}
template<> __device__ __forceinline__ void wgmma_rs_hi<96>(float (&d)[64], uint32_t a0, uint32_t a1, uint32_t a2, uint32_t a3, uint32_t blo){
  asm volatile("{\n.reg .b64 db;\nmov.b64 db, {%52,8};\nwgmma.mma_async.sync.aligned.m64n96k16.f32.bf16.bf16 {%0, %1, %2, %3, %4, %5, %6, %7, %8, %9, %10, %11, %12, %13, %14, %15, %16, %17, %18, %19, %20, %21, %22, %23, %24, %25, %26, %27, %28, %29, %30, %31, %32, %33, %34, %35, %36, %37, %38, %39, %40, %41, %42, %43, %44, %45, %46, %47}, {%48,%49,%50,%51}, db, 1, 1, 1, 0;\n}\n"
    : "+f"(d[16]), "+f"(d[17]), "+f"(d[18]), "+f"(d[19]), "+f"(d[20]), "+f"(d[21]), "+f"(d[22]), "+f"(d[23]), "+f"(d[24]), "+f"(d[25]), "+f"(d[26]), "+f"(d[27]), "+f"(d[28]), "+f"(d[29]), "+f"(d[30]), "+f"(d[31]), "+f"(d[32]), "+f"(d[33]), "+f"(d[34]), "+f"(d[35]), "+f"(d[36]), "+f"(d[37]), "+f"(d[38]), "+f"(d[39]), "+f"(d[40]), "+f"(d[41]), "+f"(d[42]), "+f"(d[43]), "+f"(d[44]), "+f"(d[45]), "+f"(d[46]), "+f"(d[47]), "+f"(d[48]), "+f"(d[49]), "+f"(d[50]), "+f"(d[51]), "+f"(d[52]), "+f"(d[53]), "+f"(d[54]), "+f"(d[55]), "+f"(d[56]), "+f"(d[57]), "+f"(d[58]), "+f"(d[59]), "+f"(d[60]), "+f"(d[61]), "+f"(d[62]), "+f"(d[63])
    : "r"(a0), "r"(a1), "r"(a2), "r"(a3), "r"(blo));
}
template<> __device__ __forceinline__ void wgmma_rs_hi<112>(float (&d)[64], uint32_t a0, uint32_t a1, uint32_t a2, uint32_t a3, uint32_t blo){
  asm volatile("{\n.reg .b64 db;\nmov.b64 db, {%60,8};\nwgmma.mma_async.sync.aligned.m64n112k16.f32.bf16.bf16 {%0, %1, %2, %3, %4, %5, %6, %7, %8, %9, %10, %11, %12, %13, %14, %15, %16, %17, %18, %19, %20, %21, %22, %23, %24, %25, %26, %27, %28, %29, %30, %31, %32, %33, %34, %35, %36, %37, %38, %39, %40, %41, %42, %43, %44, %45, %46, %47, %48, %49, %50, %51, %52, %53, %54, %55}, {%56,%57,%58,%59}, db, 1, 1, 1, 0;\n}\n"
    : "+f"(d[8]), "+f"(d[9]), "+f"(d[10]), "+f"(d[11]), "+f"(d[12]), "+f"(d[13]), "+f"(d[14]), "+f"(d[15]), "+f"(d[16]), "+f"(d[17]), "+f"(d[18]), "+f"(d[19]), "+f"(d[20]), "+f"(d[21]), "+f"(d[22]), "+f"(d[23]), "+f"(d[24]), "+f"(d[25]), "+f"(d[26]), "+f"(d[27]), "+f"(d[28]), "+f"(d[29]), "+f"(d[30]), "+f"(d[31]), "+f"(d[32]), "+f"(d[33]), "+f"(d[34]), "+f"(d[35]), "+f"(d[36]), "+f"(d[37]), "+f"(d[38]), "+f"(d[39]), "+f"(d[40]), "+f"(d[41]), "+f"(d[42]), "+f"(d[43]), "+f"(d[44]), "+f"(d[45]), "+f"(d[46]), "+f"(d[47]), "+f"(d[48]), "+f"(d[49]), "+f"(d[50]), "+f"(d[51]), "+f"(d[52]), "+f"(d[53]), "+f"(d[54]), "+f"(d[55]), "+f"(d[56]), "+f"(d[57]), "+f"(d[58]), "+f"(d[59]), "+f"(d[60]), "+f"(d[61]), "+f"(d[62]), "+f"(d[63])
    : "r"(a0), "r"(a1), "r"(a2), "r"(a3), "r"(blo));
}
template<> __device__ __forceinline__ void wgmma_rs_hi<128>(float (&d)[64], uint32_t a0, uint32_t a1, uint32_t a2, uint32_t a3, uint32_t blo){
  asm volatile("{\n.reg .b64 db;\nmov.b64 db, {%68,8};\nwgmma.mma_async.sync.aligned.m64n128k16.f32.bf16.bf16 {%0, %1, %2, %3, %4, %5, %6, %7, %8, %9, %10, %11, %12, %13, %14, %15, %16, %17, %18, %19, %20, %21, %22, %23, %24, %25, %26, %27, %28, %29, %30, %31, %32, %33, %34, %35, %36, %37, %38, %39, %40, %41, %42, %43, %44, %45, %46, %47, %48, %49, %50, %51, %52, %53, %54, %55, %56, %57, %58, %59, %60, %61, %62, %63}, {%64,%65,%66,%67}, db, 1, 1, 1, 0;\n}\n"
    : "+f"(d[0]), "+f"(d[1]), "+f"(d[2]), "+f"(d[3]), "+f"(d[4]), "+f"(d[5]), "+f"(d[6]), "+f"(d[7]), "+f"(d[8]), "+f"(d[9]), "+f"(d[10]), "+f"(d[11]), "+f"(d[12]), "+f"(d[13]), "+f"(d[14]), "+f"(d[15]), "+f"(d[16]), "+f"(d[17]), "+f"(d[18]), "+f"(d[19]), "+f"(d[20]), "+f"(d[21]), "+f"(d[22]), "+f"(d[23]), "+f"(d[24]), "+f"(d[25]), "+f"(d[26]), "+f"(d[27]), "+f"(d[28]), "+f"(d[29]), "+f"(d[30]), "+f"(d[31]), "+f"(d[32]), "+f"(d[33]), "+f"(d[34]), "+f"(d[35]), "+f"(d[36]), "+f"(d[37]), "+f"(d[38]), "+f"(d[39]), "+f"(d[40]), "+f"(d[41]), "+f"(d[42]), "+f"(d[43]), "+f"(d[44]), "+f"(d[45]), "+f"(d[46]), "+f"(d[47]), "+f"(d[48]), "+f"(d[49]), "+f"(d[50]), "+f"(d[51]), "+f"(d[52]), "+f"(d[53]), "+f"(d[54]), "+f"(d[55]), "+f"(d[56]), "+f"(d[57]), "+f"(d[58]), "+f"(d[59]), "+f"(d[60]), "+f"(d[61]), "+f"(d[62]), "+f"(d[63])
    : "r"(a0), "r"(a1), "r"(a2), "r"(a3), "r"(blo));
}

struct CvCtx {
  uint32_t koff, zero, so[3];
  int srcA, srcB;
  bool wrapA, s3, kodd;
};
struct CvPipe { uint32_t Ap, Ep, keep, send; };
template <int LO> __device__ __forceinline__ void cv_copy(float (&acc)[64]) {
#pragma unroll
  for (int i = LO; i < 64; i++) { float t; asm volatile("mov.b32 %0, %1;" : "=f"(t) : "f"(acc[i]) : "memory"); acc[i] = t; }
}
template <int G> __device__ __forceinline__ void cv_raw(uint32_t (&A)[4][4], uint32_t kaddr) {
#pragma unroll
  for (int i = 0; i < 4; i++) {
    const uint32_t a = kaddr + (4 * G + i) * 128;
    A[i][0] = lds32(a); A[i][1] = lds32(a + 4); A[i][3] = lds32(a + 8);
  }
}
__device__ __forceinline__ void cv_form(uint32_t (&A)[4][4], uint32_t sel) {
#pragma unroll
  for (int i = 0; i < 4; i++) {
    asm volatile("prmt.b32 %0, %0, %1, %2;" : "+r"(A[i][0]) : "r"(A[i][1]), "r"(sel));
    asm volatile("prmt.b32 %0, %1, %2, %3;" : "=r"(A[i][2]) : "r"(A[i][1]), "r"(A[i][3]), "r"(sel));
  }
}
#define CVV 2
template <int G> __device__ __forceinline__ void cv_step(float (&acc)[64], uint32_t (&A)[4][4], CvPipe& s, const CvCtx& c, uint32_t cb, uint32_t stg) {
  constexpr int JA = G - 1, JB = G - 2, NH = CVV == 1 ? 4 : (CVV == 3 ? 2 : 1);
  const uint32_t db0 = desc_lo(cb + CV_U + 192, CV_PL);
  uint32_t B[4][4];
  uint32_t ra[2], rb;
  if constexpr (G < 8) {
    wgmma_fence();
#pragma unroll
    for (int i = 0; i < NH; i++) wgmma_rs_hi<128 - 16 * (G & 7)>(acc, A[i][0], A[i][1], A[i][2], A[i][3], db0 - 4 * i);
    wgmma_commit();
    __syncwarp();
  }
  if constexpr (JA >= 0 && JA < 8) {
    const uint32_t p0 = pack_bf16(acc[8 * JA + 1], acc[8 * JA + 3]), p1 = pack_bf16(acc[8 * JA + 5], acc[8 * JA + 7]);
    ra[0] = __shfl_sync(0xffffffffu, c.wrapA ? s.Ap : p0, c.srcA);
    ra[1] = __shfl_sync(0xffffffffu, c.wrapA ? p0 : p1, c.srcA);
    s.Ap = p1;
  }
  if constexpr (JB >= 0) rb = __shfl_sync(0xffffffffu, s.send, c.srcB);
  if constexpr (G < 7) cv_raw<G + 1>(B, cb + c.koff);
  uint32_t z = 0;
  if constexpr (G < 8 && NH < 4) {
    __syncwarp();
    wgmma_fence();
#pragma unroll
    for (int i = NH; i < 4; i++) wgmma_rs_hi<128 - 16 * (G & 7)>(acc, A[i][0], A[i][1], A[i][2], A[i][3], db0 - 4 * i);
    wgmma_commit();
    asm volatile("mov.u32 %0, %%clock;" : "=r"(z)::"memory");
    z &= c.zero;
  }
  if constexpr (G < 7) cv_form(B, 0x5432u | z);
  if constexpr (JB >= 0) sts32(stg + ((c.so[JB / 3] >> (10 * (JB % 3))) & 0xffc), hadd2(rb | z, s.keep));
  if constexpr (JA >= 0 && JA < 8) {
    const uint32_t sh = 16 | z, mk = 0xffff0000u | z;
    const uint32_t ev = pack_bf16(acc[8 * JA] + __uint_as_float(ra[0] << sh), acc[8 * JA + 2] + __uint_as_float(ra[0] & mk));
    const uint32_t od = pack_bf16(acc[8 * JA + 4] + __uint_as_float(ra[1] << sh), acc[8 * JA + 6] + __uint_as_float(ra[1] & mk));
    s.send = c.kodd ? ev : (c.s3 ? s.Ep : od);
    s.keep = c.kodd ? od : ev;
    s.Ep = od;
  }
  if constexpr (G < 8) { __syncwarp(); wgmma_wait<0>(); cv_copy<8 * (G & 7)>(acc); }
  if constexpr (G < 9) cv_step<G + 1>(acc, B, s, c, cb, stg);
}
__device__ __forceinline__ uint32_t cv_stage(int slot) { return sb + (slot < 4 ? 40960 + slot * 4096 : CV_OFF + CV_K); }
__device__ __forceinline__ void cv_setup(CvCtx& c) {
  const int tid = tid_opaque() & 127, w = tid >> 5, lane = tid & 31, r = lane >> 2, q = lane & 3;
  const int i0 = (r >> 1) & 1, i1 = r >> 2;
  c.koff = CV_K - 32 + 4 * (8 * (r >> 1) + 2 * w + (r & 1) + 2 * q);
  c.srcA = i0 ? lane - 8 : lane + 8 - q + ((q + 3) & 3);
  c.wrapA = i0 && q == 3;
  c.srcB = i1 == 0 ? (lane - q + 16 + ((q + 3) & 3)) : (lane - q - 16 + ((q + 1) & 3));
  c.s3 = (i1 == 1 && q == 3); c.kodd = (i1 == 1 && q < 3);
  c.zero = lds32(sb + EP_OFF + 24);
#pragma unroll
  for (int i = 0; i < 3; i++) c.so[i] = lds32(sb + SO_OFF + 512 * i + 4 * tid);
}
__device__ __forceinline__ void cv_table() {
  const int tid = tid_opaque() & 127, r = (tid & 31) >> 2, q = tid & 3;
  int t = 16 * (2 * (r < 4 ? q : 4 + ((q + 1) & 3)) + ((r >> 1) & 1)) + 4 * (tid >> 5) + 2 * (r & 1);
#pragma unroll 1
  for (int i = 0; i < 3; i++) {
    uint32_t v = 0;
#pragma unroll 1
    for (int x = 0; x < 3; x++, t += 256) {
      const int T = t / 160, tl = t - T * 160;
      const int qq = (T >= NT1 - 1) ? (tl >> 5) : (tl / 40);
      int ck = 20 * T + ((tl - qq * ((T >= NT1 - 1) ? 32 : 40)) >> 1);
      ck ^= (ck >> 2) & 6;
      v |= (uint32_t)((ck * 4 + qq) & 1023) << (10 * x + 2);
    }
    sts32(sb + SO_OFF + 512 * i + 4 * tid, v);
  }
}
__device__ __forceinline__ void conv_channel(int slot, const CvCtx& c) {
  const uint32_t cb = sb + CV_OFF + slot * CV_B;
  float acc[64];
  CvPipe s;
  s.Ap = s.Ep = 0u;
  uint32_t A[4][4];
#pragma unroll
  for (int i = 0; i < 64; i++) acc[i] = 0.f;
  if (slot == 4) mbar_wait(bars + 8 * B_CVDONE);
  mbar_wait(bars + 8 * (B_CVFULL + slot));
  cv_raw<0>(A, cb + c.koff);
  {
    const uint32_t w0 = lds32(cb + CV_K);
    const uint32_t wp = __byte_perm(pack_bf16(bf_lo(w0) + __uint_as_float(lds32(sb + EP_OFF + 4 * slot)), 0.f), w0, 0x7610);
    if (c.koff == CV_K) A[0][0] = wp;
    if (c.koff == CV_K - 4) A[0][1] = wp;
    if (c.koff == CV_K - 8) A[0][3] = wp;
  }
  cv_form(A, 0x5432u);
  cv_copy<0>(acc);
  cv_step<0>(acc, A, s, c, cb, cv_stage(slot));
  fence_async_smem();
  mbar_arrive(bars + 8 * (B_CVDONE + slot));
}

__device__ __forceinline__ void kv_issue(const Params& p, int c, int m2, int dg) {
  const uint32_t fb = bars + 8 * (B_KV + c);
  mbar_expect_tx(fb, KV_PIECE);
  tma3(sb + KS_OFF + c * KV_PIECE, &p.mK, 160 * dg + 32 * c, 64 * m2 - 3, 0, fb);
  tma3(sb + KS_OFF + c * KV_PIECE + 4864, &p.mV, 160 * dg + 32 * c, 64 * m2 - 1, 0, fb);
}
__device__ __forceinline__ void kv_tile(int m, int c, int y, uint32_t (&o)[4][4]) {
  const int lane = tid_opaque() & 31, tg = lane & 3, pr = 8 * (y ^ (tg >> 1)) + (lane >> 2);
  const uint32_t pb = sb + KS_OFF + c * KV_PIECE + 4 * pr;
  const uint32_t ka = pb + tg * 1216, va = pb + 4864 + tg * 1088 + 64;
  const uint32_t kh = (m == 0 && tg > 0) ? ka - 192 : ka;
  uint32_t kk[19], u[16];
  const float4 t = lds128f(sb + TAP_OFF + 256 * c + 16 * pr);
#pragma unroll
  for (int i = 0; i < 19; i++) { kk[i] = lds32((i < 3 ? kh : ka) + i * 64); if (i >= 3) u[i - 3] = lds32(va + (i - 3) * 64); }
  const uint32_t dst = sb + KS_OFF + c * KV_PIECE + pr * 64 + tg * 16;
  if (y) {
    __syncwarp();
#pragma unroll
    for (int x = 0; x < 4; x++) sts128((dst ^ 512) + x * 1024, make_uint4(o[x][0], o[x][1], o[x][2], o[x][3]));
  }
  const uint32_t w0 = __byte_perm(__float_as_uint(t.x), __float_as_uint(t.z), 0x5410), w1 = __byte_perm(__float_as_uint(t.x), __float_as_uint(t.z), 0x7632);
  const uint32_t w2 = __byte_perm(__float_as_uint(t.y), __float_as_uint(t.w), 0x5410), w3 = __byte_perm(__float_as_uint(t.y), __float_as_uint(t.w), 0x7632);
#pragma unroll
  for (int i = 0; i < 16; i++) {
    uint32_t a = hmul2(kk[i], w3);
    a = hadd2(a, hmul2(kk[i + 1], w2)); a = hadd2(a, hmul2(kk[i + 2], w1)); a = hadd2(a, hmul2(kk[i + 3], w0));
    u[i] = hmul2(a, u[i]);
  }
#pragma unroll
  for (int x = 0; x < 4; x++) {
#pragma unroll
    for (int qq = 0; qq < 4; qq++) o[x][qq] = __byte_perm(u[15 - 4 * qq - (x & 2)], u[14 - 4 * qq - (x & 2)], (x & 1) ? 0x7632 : 0x5410);
    if (y) sts128(dst + x * 1024, make_uint4(o[x][0], o[x][1], o[x][2], o[x][3]));
  }
}
__device__ __forceinline__ void ln_finish(float s1, float s2, float& mean, float& rstd) {
  mean = s1 * (1.f / 640.f);
  const float v = fmaxf(fmaf(-mean, mean, s2 * (1.f / 640.f)), 0.f) + 1e-5f;
  asm("rsqrt.approx.ftz.f32 %0, %1;" : "=f"(rstd) : "f"(v));
}
__device__ __forceinline__ void stat_table(int T1, unsigned want, int l, int g, const uint4* x0, const uint4* x1, float (&xa)[2], float (&xb)[2]) {
  const int n = 32 * g + (tid_opaque() & 31);
  const uint4* rp = &g_stats[8 * l * SEQ + min(160 * T1 + n, SEQ - 1)];
  float a[4], b[4];
  uint32_t it = 0;
  while (true) {
    bool ok = true;
#pragma unroll
    for (int i = 0; i < 4; i++) ok &= (rec_ld(rp + SEQ * i, a[i], b[i]) == want);
    ok &= rec_ld(x0, xa[0], xb[0]) == want;
    ok &= rec_ld(x1, xa[1], xb[1]) == want;
    if (__all_sync(0xffffffffu, ok)) break;
    trap_if(++it > SPIN_LIMIT);
  }
  float m, rs;
  ln_finish((a[0] + a[1]) + (a[2] + a[3]), (b[0] + b[1]) + (b[2] + b[3]), m, rs);
  sts32(sb + STAB_OFF + ((n >> 1) & 3) * 160 + (n >> 3) * 8 + (n & 1) * 4, __float_as_uint(rs));
  const uint32_t hi = pack_bf16(-m, -m);
  const float lo = -m - bf_lo(hi);
  sts128(sb + (l ? MX1_OFF : MX0_OFF) + n * 16, make_uint4(hi, pack_bf16(lo, lo), 0u, 0u));
  fence_async_smem();
}
__device__ __forceinline__ void stats_reduce(float (&a)[2], float (&b)[2], float (&mean)[2], float (&rstd)[2]) {
#pragma unroll
  for (int o = 1; o < 4; o <<= 1)
#pragma unroll
    for (int h = 0; h < 2; h++) { a[h] += __shfl_xor_sync(0xffffffffu, a[h], o); b[h] += __shfl_xor_sync(0xffffffffu, b[h], o); }
#pragma unroll
  for (int h = 0; h < 2; h++) ln_finish(a[h], b[h], mean[h], rstd[h]);
}

template <bool FIRST>
__device__ __forceinline__ void stats_publish(int which, int n0, int dg, unsigned tag, const float (&acc)[80]) {
  const int q = tid_opaque() & 3, h = q & 1;
  float s1[2] = {0.f, 0.f}, s2[2] = {0.f, 0.f}, t1[2] = {0.f, 0.f}, t2[2] = {0.f, 0.f};
#pragma unroll
  for (int j = 0; j < 20; j++)
#pragma unroll
    for (int y = 0; y < 2; y++) {
      const float a = acc[4 * j + 2 * y], b = acc[4 * j + 2 * y + 1];
      s1[y] += a; t1[y] += b; s2[y] = fmaf(a, a, s2[y]); t2[y] = fmaf(b, b, t2[y]);
    }
#pragma unroll
  for (int y = 0; y < 2; y++) { s1[y] += t1[y]; s2[y] += t2[y]; }
  float a = (h ? s1[1] : s1[0]) + __shfl_xor_sync(0xffffffffu, h ? s1[0] : s1[1], 1);
  float b = (h ? s2[1] : s2[0]) + __shfl_xor_sync(0xffffffffu, h ? s2[0] : s2[1], 1);
  a += __shfl_xor_sync(0xffffffffu, a, 2);
  b += __shfl_xor_sync(0xffffffffu, b, 2);
  if (FIRST) {
    rec_st(&g_stats[((q >> 1) * 4 + dg) * SEQ + n0 + 8 * h], a, b, q < 2 ? tag : tag - 1);
    rec_st(&g_stats[((q >> 1) * 4 + 8 + dg) * SEQ + n0 + 8 * h], a, b, tag - 1);
  } else if (q < 2) rec_st(&g_stats[(which * 4 + dg) * SEQ + n0 + 8 * h], a, b, tag);
}
__device__ __forceinline__ void stats_get(int which, int n0, unsigned tag, float (&mean)[2], float (&rstd)[2]) {
  const uint4* p0 = &g_stats[(which * 4 + (tid_opaque() & 3)) * SEQ + n0];
  float a[2], b[2];
  uint32_t it = 0;
  while (true) {
    const unsigned t0 = rec_ld(p0, a[0], b[0]), t1 = rec_ld(p0 + 8, a[1], b[1]);
    if (__all_sync(0xffffffffu, t0 == tag && t1 == tag)) break;
    trap_if(++it > SPIN_LIMIT);
  }
  stats_reduce(a, b, mean, rstd);
}
__device__ __forceinline__ void x0_load(float (&acc)[80]) {
  const int t = tid_opaque() & 127;
  const uint32_t xa = sb + XT_OFF + (16 * (t >> 5) + ((t & 31) >> 2)) * 320 + 8 * (t & 3);
  mbar_wait(bars + 8 * B_XT);
#pragma unroll
  for (int h = 0; h < 2; h++)
#pragma unroll
    for (int J = 0; J < 10; J++) {
      const float2 v = lds64f(xa + h * 2560 + 32 * J);
      const uint32_t x = __float_as_uint(v.x), y = __float_as_uint(v.y);
      acc[8 * J + 2 * h] = bf_lo(x); acc[8 * J + 2 * h + 1] = bf_hi(x);
      acc[8 * J + 4 + 2 * h] = bf_lo(y); acc[8 * J + 4 + 2 * h + 1] = bf_hi(y);
    }
}

template <bool FROM_X0>
__device__ __forceinline__ void dskip_init(float (&acc)[80], const float (&mean)[2], const float (&rstd)[2]) {
  const int t = tid_opaque() & 127;
  const uint32_t xa = sb + XT_OFF + (16 * (t >> 5) + ((t & 31) >> 2)) * 320 + 8 * (t & 3), da = sb + DTAB_OFF + 8 * (t & 3);
  float2 dw[10], xv[10][2];
#pragma unroll
  for (int J = 0; J < 2; J++) { dw[J] = lds64f(da + 32 * J); if (FROM_X0) { xv[J][0] = lds64f(xa + 32 * J); xv[J][1] = lds64f(xa + 2560 + 32 * J); } }
#pragma unroll
  for (int J = 0; J < 10; J++) {
    if (J + 2 < 10) { dw[J + 2] = lds64f(da + 32 * (J + 2)); if (FROM_X0) { xv[J + 2][0] = lds64f(xa + 32 * (J + 2)); xv[J + 2][1] = lds64f(xa + 2560 + 32 * (J + 2)); } }
#pragma unroll
    for (int x = 0; x < 8; x++) {
      const int h = (x >> 1) & 1;
      const uint32_t dwd = __float_as_uint(x < 4 ? dw[J].x : dw[J].y);
      const float tt = fmaf(rstd[h], (x & 1) ? bf_hi(dwd) : bf_lo(dwd), 1.f);
      float a = acc[8 * J + x];
      if (FROM_X0) { const uint32_t xw = __float_as_uint(x < 4 ? xv[J][h].x : xv[J][h].y); a = (x & 1) ? bf_hi(xw) : bf_lo(xw); }
      acc[8 * J + x] = FROM_X0 ? (a - mean[h]) * tt : fmaf(a, tt, -mean[h] * tt);
    }
  }
}

__global__ void __launch_bounds__(512, 1) fused_kernel(const __grid_constant__ Params p) {
  extern __shared__ __align__(1024) uint8_t smem_raw[];
  const int tid = threadIdx.x, lane = tid & 31;
  const int wid = __shfl_sync(0xffffffffu, tid >> 5, 0), wg = wid >> 2;
  unsigned smid; asm volatile("mov.u32 %0, %%smid;" : "=r"(smid));
  const int role = p.role[min(smid, 131u)];
  if (wid == 12) {
    const bool el = elect_one();
    if (el) {
      asm volatile("prefetch.tensormap [%0];" ::"l"(&p.mB) : "memory");
      asm volatile("prefetch.tensormap [%0];" ::"l"((role & 15) == NT1 - 1 ? &p.mXl : &p.mX) : "memory");
#pragma unroll
      for (int k = 0; k < S1; k++) mbar_init(bars + 8 * (B_G1FULL + k), 1);
#pragma unroll
      for (int k = 0; k < 6; k++) mbar_init(bars + 8 * (B_XT + k), 1);
      asm volatile("fence.mbarrier_init.release.cluster;" ::: "memory");
    }
    if (role >= 0) {
      __syncwarp();
      asm volatile("bar.arrive 5, 288;" ::: "memory");
      const Role R = unpack_role(role);
      if (elect_one()) {
        TS(45);
#pragma unroll 1
        for (int k = 0; k < S1; k++) {
          const uint32_t fb = bars + 8 * (B_G1FULL + k);
          mbar_expect_tx(fb, G1_STAGE);
          tma4(sb + k * G1_STAGE + G1_XOFF, R.last ? &p.mXl : &p.mX, 64 * k, 0, 0, R.last ? 0 : 80 * R.T1, fb);
          tma5(sb + k * G1_STAGE, &p.mB, 64 * k, 0, 0, 4 * R.side, 2 * R.GP, fb);
          if (PFD) asm volatile("prefetch.tensormap [%0];" ::"l"(&p.mK + k) : "memory");
        }
        if (R.has2) {
          mbar_expect_tx(bars + 8 * B_XT, 20480);
#pragma unroll 1
          for (int h = 0; h < 2; h++) {
            const int ng = 8 * R.m2 + 4 * h, T = ng / 20;
            tma4(sb + XT_OFF + h * 10240, T == NT1 - 1 ? &p.mXtl : &p.mXt, 160 * R.dg, 0, 0, T == NT1 - 1 ? ng - 240 : ng + 60 * T, bars + 8 * B_XT);
          }
#pragma unroll 1
          for (int c = 0; c < KV0; c++) kv_issue(p, c, R.m2, R.dg);
        }
        TS(44);
      }
      __syncwarp();
      bar_sync(6, 64);
    }
  }
  trap_if(smid >= 132 || smem_u32(smem_raw) != sb);
  if (role < 0) {
    if (wid == 0) {
      const unsigned tag = ld_rlx(g_epoch);
      uint32_t it = 0;
      while (!__all_sync(0xffffffffu, (int)(ld_rlx(&g_hcnt[(lane & 7) * 32]) - 40 * tag) >= 0)) { __nanosleep(500); trap_if(++it > SPIN_LIMIT); }
    }
    return;
  }
  float mean0[2] = {0.f, 0.f}, rstd0[2] = {0.f, 0.f};
  if (wg == 2 || wid == 14) {
    ROLE(role)
    const int c = wid == 14 ? 4 : wid - 8;
    const unsigned tag = ld_rlx(g_epoch);
    if (has2) {
      uint2 bv[2][5];
#pragma unroll
      for (int x = 0; x < 2; x++)
#pragma unroll
        for (int i = 0; i < 5; i++) bv[x][i] = ldv64((const uint2*)((x ? p.bim : p.bre) + (cch0 + 32 * c) * DM) + lane + 32 * i);
      float sv[2];
#pragma unroll
      for (int x = 0; x < 2; x++) {
        float a = 0.f;
#pragma unroll
        for (int i = 0; i < 5; i++) a += (bf_lo(bv[x][i].x) + bf_hi(bv[x][i].x)) + (bf_lo(bv[x][i].y) + bf_hi(bv[x][i].y));
        sv[x] = a;
      }
#pragma unroll
      for (int o = 16; o > 0; o >>= 1) { sv[0] += __shfl_xor_sync(0xffffffffu, sv[0], o); sv[1] += __shfl_xor_sync(0xffffffffu, sv[1], o); }
      if (lane < 2) rec_st(&g_sB[(cch0 + 32 * c) * 2 + lane], sv[0], sv[1], tag);
      if (tid == 256) TS(47);
      __syncwarp();
      bar_sync(8, 192);
      if (wg == 2) {
        float xs[80];
        x0_load(xs);
        stats_publish<true>(0, 64 * m2 + 16 * c + (lane >> 2), dg, tag, xs);
        if (tid == 256) TS(31);
      }
      mbar_wait(bars + 8 * B_EP);
      mbar_wait(bars + 8 * (B_KV + c));
      mbar_wait(bars + 8 * (B_G1DONE + PAUSE_K - 1));
      if (tid == 448) TS(52);
      uint32_t o[4][4] = {};
#pragma unroll 1
      for (int y = 0; y < 2; y++) kv_tile(m2, c, y, o);
      fence_async_smem();
      __syncwarp();
      if (lane == 0) { mbar_arrive(bars + 8 * B_PREP); mbar_arrive(bars + 8 * (B_PD + c)); }
      if (tid == 448) TS(51);
    } else bar_sync(8, 192);
    {
      const uint4* x0 = wg == 2 ? &g_stats[(lane & 3) * SEQ + (has2 ? 64 * m2 : 0) + 16 * c + (lane >> 2)] : &g_sB[(128 * GP + 32 * side + lane) * 2];
      float xa[2], xb[2];
      stat_table(T1, tag, 0, c, x0, x0 + (wg == 2 ? 8 : 128), xa, xb);
      if (wg == 2) stats_reduce(xa, xb, mean0, rstd0);
      else {
#pragma unroll
        for (int i = 0; i < 2; i++) {
          const float ha = bf_lo(pack_bf16(xa[i], 0.f)), hb = bf_lo(pack_bf16(xb[i], 0.f));
          const float pa = __uint_as_float(pack_bf16(ha, xa[i] - ha)), pb = __uint_as_float(pack_bf16(hb, xb[i] - hb));
          sts64f(sb + CTAB_OFF + (32 * i + lane) * 24 + 16, p.swap ? pb : pa, p.swap ? pa : pb);
        }
      }
      mbar_arrive(bars + 8 * B_STAB);
      if (tid == 448) TS(26);
    }
  } else if (wid == 15) {
    ROLE(role)
    const int ch = 128 * GP + 32 * side + lane;
    uint32_t r0 = ldv16(p.lre + ch), r1 = ldv16(p.lim + ch), r2 = ldv16(p.logdt + ch);
    const uint32_t r3 = ldv16(p.lre + ch + 64), r4 = ldv16(p.lim + ch + 64), r5 = ldv16(p.logdt + ch + 64);
#pragma unroll 1
    for (int i = 0; i < 2; i++) {
      const float lr = bf_lo(r0), li = bf_lo(r1);
      const float dt = __bfloat162float(__float2bfloat16_rn(expf(bf_lo(r2))));
      const float mag = expf(dt * lr);
      float sn, cs; sincospif(dt * li * 0.31830988618379067f, &sn, &cs);
      const float ar = mag * cs, ai = mag * sn;
      const float inv = 2.f / (lr * lr + li * li);
      const uint32_t ad = sb + CTAB_OFF + (32 * i + lane) * 24;
      sts64f(ad, ar, ai);
      sts64f(ad + 8, ((ar - 1.f) * lr + ai * li) * inv, (ai * lr - (ar - 1.f) * li) * inv);
      r0 = r3; r1 = r4; r2 = r5;
    }
    if (lane == 0) TS(46);
    __syncwarp();
    bar_sync(7, 64);
    mbar_arrive(bars + 8 * B_CTAB);
  } else if (wid == 13) {
    ROLE(role)
    uint4 tv[3];
    const uint32_t e0 = ld_rlx(g_epoch);
    const uint32_t e1 = ldv16(p.ssmD + min(cch0 + 32 * lane, 639));
    const uint4 dv = ldv128((const uint4*)(p.dskip + 160 * dg) + min(lane, 19));
#pragma unroll
    for (int i = 0; i < 3; i++) tv[i] = ldv128((const uint4*)(p.shiftk + 640 * dg) + min(lane + 32 * i, 79));
    sts128(sb + DTAB_OFF + 16 * min(lane, 19), dv);
#pragma unroll
    for (int i = 0; i < 3; i++) sts128(sb + TAP_OFF + 16 * min(lane + 32 * i, 79), tv[i]);
    if (lane < 7) sts32(sb + EP_OFF + 4 * lane, lane < 5 ? e1 << 16 : (lane == 5 ? e0 : 0u));
    __syncwarp();
    bar_sync(9, 64);
    mbar_arrive(bars + 8 * B_CTAB);
    if (lane == 0) { mbar_arrive(bars + 8 * B_EP); TS(53); }
    if (has2) {
#pragma unroll 1
      for (int i = 0; i < 5; i++) {
        const int c = i == 2 ? 3 : (i == 3 ? 2 : i);
        mbar_wait(bars + 8 * (B_PD + c));
        if (lane == 0) bulk_s2g(g_kv + (dg * 32 + m2) * 20480 + c * 4096, sb + KS_OFF + c * KV_PIECE, 4096);
      }
      if (lane == 0) {
        asm volatile("cp.async.bulk.commit_group;" ::: "memory");
        asm volatile("cp.async.bulk.wait_group 0;" ::: "memory");
        mbar_arrive(bars + 8 * B_PREP2);
        fence_async_global();
      }
      __syncwarp();
      if (lane < 4) red_rel(&g_kvcnt[(dg * 4 + lane) * 32]);
      __syncwarp();
      if (lane == 0) { mbar_arrive(bars + 8 * B_PUB); TS(30); }
    }
  } else if (wid != 12) {
    if (elect_one()) {
      if (wid < 7) {
        const int b0 = wid < 4 ? 4 + 19 * wid : 85 + 21 * (wid - 4), cnt = wid < 4 ? 2 : 1;
#pragma unroll
        for (int i = 0; i < 21; i++) mbar_init(bars + 8 * (b0 + i), cnt);
      } else {
#pragma unroll
        for (int i = 0; i < 12; i++) mbar_init(bars + 8 * (B_CVDONE + i), (i == 5 || i == 6) ? 160 : 128);
        mbar_init(bars + 8 * B_CTAB, 192); mbar_init(bars + 8 * B_PREP, 5); mbar_init(bars + 8 * B_PREP2, 1);
#pragma unroll
        for (int i = 0; i < 5; i++) mbar_init(bars + 8 * (B_PD + i), 1);
      }
      asm volatile("fence.mbarrier_init.release.cluster;" ::: "memory");
    }
    __syncwarp();
    bar_sync(5, 288);
    if (wid == 2) asm volatile("bar.arrive 8, 192;\nbar.arrive 6, 64;\nbar.arrive 9, 64;\nbar.arrive 7, 64;" ::: "memory");
    if (tid == 128) TS(0);
    if (wg == 1) { cv_table(); mbar_arrive(bars + 8 * B_CTAB); }
  }

  if (wid == 12) {
    ROLE(role)
    uint32_t dst = sb;
#pragma unroll 1
    for (int k = S1; k < 10; k++) {
      const uint32_t fb = bars + 8 * (B_G1FULL + k);
      mbar_wait(bars + 8 * (B_G1DONE + k - S1));
      if (elect_one()) {
        mbar_expect_tx(fb, 20480);
        tma4(dst + G1_XOFF, last ? &p.mXl : &p.mX, 64 * k, 0, 0, last ? 0 : 80 * T1, fb);
        mbar_expect_tx(fb, 16384);
        tma5(dst, &p.mB, 64 * k, 0, 0, 4 * side, 2 * GP, fb);
        if (has2 && k - S1 + KV0 < 5) kv_issue(p, k - S1 + KV0, m2, dg);
      }
      dst += G1_STAGE; if (k == 2 * S1 - 1) dst = sb;
    }
  } else if (wid == 15 && (role >> 16)) {
    ROLE(role)
    if (TPF >= 0) {
      mbar_wait(bars + 8 * (B_KV + TPF));
      if (elect_one()) {
#pragma unroll
        for (int c = 0; c < 5; c++) l2_prefetch(p.ssmk + (cch0 + 32 * c) * SEQ, 4096);
        if (CPF) { l2_prefetch(p.cre + (160 * dg + 5 * m2) * DM, 6400); l2_prefetch(p.cim + (160 * dg + 5 * m2) * DM, 6400); }
      }
    }
    mbar_wait(bars + 8 * B_PREP2);
    if (lane < 10) sts128(sb + CV_OFF + (lane >> 1) * CV_B + CV_K - 32 + 16 * (lane & 1), make_uint4(0, 0, 0, 0));
    fence_async_smem();
    __syncwarp();
    const unsigned tag = lds32(sb + EP_OFF + 20);
    if (TAPW) mbar_wait(bars + 8 * B_PUB);
    if (elect_one()) {
#pragma unroll 1
      for (int c = 0; c < 5; c++) {
        if (c == 0) asm volatile("prefetch.tensormap [%0];" ::"l"(&p.mU) : "memory");
        mbar_expect_tx(bars + 8 * (B_CVFULL + c), 4096 + 2 * CV_PL);
        if (c < TAPN) bulk_g2s(sb + CV_OFF + c * CV_B + CV_K, p.ssmk + (cch0 + 32 * c) * SEQ, 4096, bars + 8 * (B_CVFULL + c));
      }
    }
    mbar_wait(bars + 8 * B_PUB);
    cnt_poll(&g_kvcnt[(dg * 4 + (m2 >> 3)) * 32], 32 * tag);
    fence_async_global();
    if (elect_one()) {
      TS(28);
#pragma unroll
      for (int c = 0; c < 5; c++) {
        tma5(sb + CV_OFF + c * CV_B + CV_U, &p.mU, 0, -3, 2 * c, 16 * (m2 & 1) + (m2 >> 1), dg, bars + 8 * (B_CVFULL + c));
        if (c >= TAPN) bulk_g2s(sb + CV_OFF + c * CV_B + CV_K, p.ssmk + (cch0 + 32 * c) * SEQ, 4096, bars + 8 * (B_CVFULL + c));
      }
#pragma unroll
      for (int i = 0; i < 3; i++) asm volatile("prefetch.tensormap [%0];" ::"l"(&p.mCre + i) : "memory");
      TS(54);
    }
    __syncwarp();
  }
  {
    const int w = wid & 3;
    if (wg == 2 && !(role >> 16)) {
      float xa[2], xb[2];
      mbar_wait(bars + 8 * (B_G1FULL + 11));
      stat_table(role & 15, lds32(sb + EP_OFF + 20), 1, w, g_stats, g_stats, xa, xb);
      mbar_arrive(bars + 8 * (B_STAB + 1));
    }
#pragma unroll 1
    for (int l = 0; l < 2; l++) {
      if (wg < 2) {
        float acc[80];
#pragma unroll
        for (int i = 0; i < 80; i++) acc[i] = 0.f;
        ROLE(role)
        const int tid = tid_opaque(), r = (tid & 31) >> 2, q = tid & 3;
        const int ch = 128 * GP + 64 * wg + 32 * side + 8 * w + r;
        const uint32_t ca = sb + CTAB_OFF + (32 * wg + 8 * w + r) * 24;
        float2 lam = make_float2(0.f, 0.f), p8 = lam, p16 = lam, pL = lam, p2L = lam;
        fence_regs(acc);
        {
          const uint32_t alo0 = (l == 0 ? desc_lo(sb, 16) : desc_lo(sb + G2_WOFF, 16)) + wg * 512;
          const uint32_t blo0 = l == 0 ? desc_lo(sb + G1_XOFF, 16) : desc_lo(sb + X1_OFF, 128);
          const uint32_t bhi = l == 0 ? desc_hi(1024, 1) : desc_hi(1024, 0), xstep = l == 0 ? 2 : 16;
          const uint32_t astep = l == 0 ? G1_STAGE >> 4 : 1024, bstep = l == 0 ? G1_STAGE >> 4 : 1280, aend = alo0 + (S1 + l) * astep;
          uint32_t alo = alo0, blo = blo0;
          uint32_t fb = bars + 8 * (B_G1FULL + 10 * l);
          mbar_wait(fb);
          if (tid == 0) TS(1 + 8 * l);
#pragma unroll 1
          for (int k = 0; k < 10; k++) {
            uint32_t ok; const uint32_t nb = k < 9 ? fb + 8 : fb;
            wgmma_fence();
#pragma unroll
            for (int kk = 0; kk < 4; kk++) {
              wgmma_n160<0>(acc, alo + kk * 2, desc_hi(1024, 1), blo + kk * xstep, bhi);
              if (kk == 0) ok = mbar_test(nb);
              if (kk == STG_KK && k == 9 && tid == 0) mbar_arrive(bars + 8 * (B_STG + l));
            }
            wgmma_commit();
            alo += astep; blo += bstep;
            if (blo == desc_lo(sb + G_OFF, 128)) blo = desc_lo(sb, 128);
            if (alo == aend) { alo = alo0; blo = blo0; }
            wgmma_wait<1>();
            if (k > 0 && (tid & 127) == 0) mbar_arrive(fb + 8 * (B_G1DONE - B_G1FULL - 1));
            if (!ok) mbar_wait(nb);
            if (k == (l ? MK1 : MK0)) {
              mbar_wait(bars + 8 * (B_STAB + l));
              const float2 sB = lds64f(ca + 16);
              uint32_t a0 = q < 2 ? __float_as_uint(sB.x) : 0u, a1 = q < 2 ? __float_as_uint(sB.y) : 0u, a2 = 0u, a3 = 0u;
              asm volatile("" : "+r"(a0), "+r"(a1), "+r"(a2), "+r"(a3)::"memory");
              wgmma_fence();
              wgmma_rs_n160(acc, a0, a1, a2, a3, l ? desc_lo(sb + MX1_OFF, 0) : desc_lo(sb + MX0_OFF, 0));
              wgmma_commit();
            }
            if (wg == 1 && k == (l ? 8 - STG_D : 9 - STG0)) mbar_wait(bars + 8 * (B_STG + l));
            if (k == 3) {
              mbar_wait(bars + 8 * B_CTAB);
              lam = lds64f(ca);
              if (l == 0 && q < 2) rec_st(&g_E[(q * NT1 + T1) * DM + ch], 0.f, 0.f, lds32(sb + EP_OFF + 20) - 1);
              if (p.swap) lam.y = -lam.y;
              const float2 p2 = cmul(lam, lam), p4 = cmul(p2, p2);
              p8 = cmul(p4, p4); p16 = cmul(p8, p8);
              pL = cmul(p16, p16);
              if (!last) pL = cmul(pL, p8);
              p2L = cmul(pL, pL);
            }
            if (k == PAUSE_K && l == 0 && has2) mbar_wait(bars + 8 * B_PREP);
            fb += 8;
          }
        }
        const unsigned tag = lds32(sb + EP_OFF + 20);
        wgmma_wait<0>();
        fence_regs(acc);
        if ((tid & 127) == 0) { mbar_arrive(bars + 8 * (B_G1DONE + 10 * l + 9)); TS(wg ? 17 + l : 2 + 8 * l); }
        float2 ec[3];
#pragma unroll
        for (int jj = 0; jj < 4; jj++)
#pragma unroll
          for (int y = 0; y < 3; y++) {
            if (y == 2 && (jj & 1)) continue;
            const int j = y == 2 ? 16 + jj : 8 * y + 2 * jj;
            const float4 st = lds128f(sb + STAB_OFF + q * 160 + j * 8);
            const float rs[4] = {st.x, st.y, st.z, st.w};
#pragma unroll
            for (int x = 0; x < 4; x++) {
              const int i = 4 * j + 4 * (x >> 1) + (x & 1);
              acc[i] *= rs[x]; acc[i + 2] *= rs[x];
              ec[y] = (jj == 0 && x == 0) ? make_float2(acc[i], acc[i + 2]) : cfma(lam, ec[y], make_float2(acc[i], acc[i + 2]));
            }
          }
        float2 e = cfma(p16, ec[0], ec[1]);
        if (!last) e = cfma(p8, e, ec[2]);
        {
          float2 v = make_float2(__shfl_up_sync(0xffffffffu, e.x, 1, 4), __shfl_up_sync(0xffffffffu, e.y, 1, 4));
          if (q >= 1) e = cfma(pL, v, e);
          v = make_float2(__shfl_up_sync(0xffffffffu, e.x, 2, 4), __shfl_up_sync(0xffffffffu, e.y, 2, 4));
          if (q >= 2) e = cfma(p2L, v, e);
        }
        if (!last && q == 3) rec_st(&g_E[(l * NT1 + T1) * DM + ch], e.x, e.y, tag);
        if (tid == 0) TS(3 + 8 * l);
        float2 ex = make_float2(__shfl_up_sync(0xffffffffu, e.x, 1, 4), __shfl_up_sync(0xffffffffu, e.y, 1, 4));
        if (q == 0) ex = make_float2(0.f, 0.f);
        const float2 coef = lds64f(ca + 8), lamc = make_float2(lam.x, p.swap ? lam.y : -lam.y);
        float m00 = coef.x, m01 = -coef.y, m10 = -coef.y, m11 = -coef.x;
        if (p.swap) { m00 = -coef.y; m01 = coef.x; m10 = -coef.x; m11 = -coef.y; }
        float2 pLq, p160q, p640;
        {
          const float2 p80 = last ? cmul(p2L, p16) : p2L, p160 = cmul(p80, p80), p320 = cmul(p160, p160), one = make_float2(1.f, 0.f);
          p640 = cmul(p320, p320);
          pLq = cmul((q & 1) ? pL : one, (q & 2) ? p2L : one);
          p160q = cmul((q & 1) ? p160 : one, (q & 2) ? p320 : one);
        }
        float2 c, ev[3];
        unsigned tg[3];
        const uint4* ep = &g_E[(l * NT1 + T1 - 1 - q) * DM + ch];
#pragma unroll
        for (int j = 0; j < 20; j++) {
          if (j == CPOLL) {
#pragma unroll
            for (int i = 0; i < 3; i++) {
              ev[i] = make_float2(0.f, 0.f); tg[i] = tag;
              if (T1 - 1 - q - 4 * i >= 0) tg[i] = rec_ld(ep - 4 * i * DM, ev[i].x, ev[i].y);
            }
          }
#pragma unroll
          for (int x = 0; x < 2; x++) {
            const float b0 = acc[4 * j + x], b1 = acc[4 * j + 2 + x];
            acc[4 * j + x] = fmaf(b0, m00, b1 * m01);
            acc[4 * j + 2 + x] = fmaf(b0, m10, b1 * m11);
          }
          if (j == CPOLL - 1 || j == 19) asm volatile("" : "+f"(acc[4 * j]), "+f"(acc[4 * j + 1]), "+f"(acc[4 * j + 2]), "+f"(acc[4 * j + 3])::"memory");
        }
        {
          uint32_t it = 0;
          while (__any_sync(0xffffffffu, tg[0] != tag || tg[1] != tag || tg[2] != tag)) {
#pragma unroll
            for (int i = 0; i < 3; i++)
              if (tg[i] != tag) tg[i] = rec_ld(ep - 4 * i * DM, ev[i].x, ev[i].y);
            trap_if(++it > SPIN_LIMIT);
          }
          c = cfma(p640, cfma(p640, ev[2], ev[1]), ev[0]);
          c = cmul(c, p160q);
          c.x += __shfl_xor_sync(0xffffffffu, c.x, 1); c.y += __shfl_xor_sync(0xffffffffu, c.y, 1);
          c.x += __shfl_xor_sync(0xffffffffu, c.x, 2); c.y += __shfl_xor_sync(0xffffffffu, c.y, 2);
        }
        if (tid == 0) TS(4 + 8 * l);
        if (wg == 1 && l >= HOLD0) mbar_wait(bars + 8 * (B_REL + l));
        const uint32_t c0 = (uint32_t)clock();
        c = cfma(pLq, c, ex);
        float2 hh = make_float2(fmaf(c.x, m00, c.y * m01), fmaf(c.x, m10, c.y * m11));
        uint8_t* hb = g_h + (size_t)l * (32 * 20 * 8192) + (10 * wg + 2 * GP) * 8192 + (4 * side + w) * 1024 + (tid_opaque() & 31) * 4;
#pragma unroll
        for (int j4 = 0; j4 < 5; j4++) {
          if (PACE && j4 > 0 && wg == 1 && l == 1) { while (__any_sync(0xffffffffu, (uint32_t)clock() - c0 < PACE * j4)) {} }
          const int ng = 20 * T1 + 4 * j4;
          uint8_t* hp = hb + (size_t)(ng >> 3) * 163840 + (ng & 7) * 128;
#pragma unroll
          for (int jj = 0; jj < 4; jj++) {
            const int j = 4 * j4 + jj;
            const float2 h0 = cfma(lamc, hh, make_float2(acc[4 * j + 0], acc[4 * j + 2]));
            hh = cfma(lamc, h0, make_float2(acc[4 * j + 1], acc[4 * j + 3]));
            if (j4 < 4 || !last) {
              *(uint32_t*)(hp + jj * 128) = pack_bf16(h0.x, hh.x);
              *(uint32_t*)(hp + jj * 128 + 8192) = pack_bf16(h0.y, hh.y);
            }
          }
        }
        mbar_arrive(bars + 8 * (B_HST + 2 * l + wg));
        if (tid == 0) TS(5 + 8 * l);
        if (tid == 128) TS(l ? 25 : 19);
        if (l == 0 && wid == 4) {
          mbar_wait(bars + 8 * B_HST);
          mbar_wait(bars + 8 * (B_HST + 1));
          if ((tid & 31) < 8) h_release((tid >> 2) & 1, T1, tid & 3);
          __syncwarp();
          if (tid == 128) { mbar_arrive(bars + 8 * B_REL); TS(6); }
        }
      }
      if (l == 0) {
        ROLE(role)
        if (has2) {
          CvCtx cc;
          mbar_wait(bars + 8 * B_CTAB);
          cv_setup(cc);
          mbar_wait(bars + 8 * (B_G1DONE + 9));
#pragma unroll 1
          for (int c = (wg + 2) & 3; c < 5; c += 4) conv_channel(c, cc);
          if ((tid & 127) == 0) TS(wg == 2 ? 32 : (wg == 3 ? 50 : 7 + wg));
        }
      }
      if (wg >= 2) break;
    }
    if (wg == 3) {
    ROLE(role)
    const int pw = wid & 3, gpc = 2 * min(m2 >> 3, 3) + (dg >> 1);
    mbar_wait(bars + 8 * B_EP);
    const unsigned tag = lds32(sb + EP_OFF + 20);
    if (pw == 0) {
      if (elect_one()) {
#pragma unroll 1
        for (int l = 0; l < 2; l++) {
          uint32_t dst = sb;
          if (l == 1) {
            dst = sb + G2_WOFF;
#pragma unroll 1
            for (int k = 0; k < 10; k++) {
              mbar_wait(k > 4 ? bars + 8 * (B_G1DONE + 5 + k) : (has2 ? bars + 8 * (B_G2DONE + 14 + min(k, 3)) : bars + 8 * (B_G1DONE + 9)));
              mbar_expect_tx(bars + 8 * (B_G1FULL + 10 + k), 16384);
              tma5(dst, &p.mB, 64 * k, 0, 0, 4 * side, 2 * GP, bars + 8 * (B_G1FULL + 10 + k));
              dst += 16384; if (k == 4) dst = sb + G2_WOFF;
            }
          }
          if (has2) {
            const uint32_t fb2 = bars + 8 * (B_G2FULL + 20 * l), wb2 = bars + 8 * (B_G2DONE + 20 * l - S2);
            dst = sb + G2_WOFF + (WTAIL ? 4 * l * G2_WB : 0);
            int kc = 0;
#pragma unroll 1
            for (int k = 0; k < 20; k++) {
              mbar_wait(k >= S2 ? wb2 + 8 * k : bars + 8 * (l ? B_G1DONE + (WTAIL ? (k < 3 ? 15 + k : 13 + k) : 19) : (k == 5 ? B_XFREE : (k == 6 ? B_SFREE : B_REL))));
              mbar_expect_tx(fb2 + 8 * k, G2_WB);
              tma5(dst, &p.mCre + (k & 1), kc, 0, 0, 0, 10 * dg, fb2 + 8 * k);
              kc += (k & 1) << 7; if (k == 9) kc = 64;
              dst += G2_WB; if (dst == sb + G2_WOFF + S2 * G2_WB) dst = sb + G2_WOFF;
            }
          }
        }
      }
    } else if (pw == 1) {
#pragma unroll 1
      for (int l = 0; l < 2; l++) {
        if (l == 1) {
          mbar_wait(bars + 8 * (has2 ? B_G2DONE + 19 : B_G1DONE + 9));
          if (has2) mbar_wait(bars + 8 * B_UST);
          cnt_poll(&g_ucnt[gpc * 32], 128 * tag);
          fence_async_global();
          if (elect_one()) {
            TS(20);
            const int bytes = last ? 16384 : 20480;
            const uint8_t* src = g_u + T1 * 204800;
            uint32_t dst = sb + X1_OFF;
#pragma unroll 1
            for (int k = 0; k < 10; k++) {
              if (k > 4) mbar_wait(bars + 8 * (B_G1DONE + 5 + k));
              mbar_expect_tx(bars + 8 * (B_G1FULL + 10 + k), bytes);
              bulk_g2s(dst, src, bytes, bars + 8 * (B_G1FULL + 10 + k));
              src += 20480; dst += 20480; if (dst == sb + G_OFF) dst = sb; if (k == 4) dst = sb + X1_OFF;
            }
          }
          __syncwarp();
        }
        if (has2) {
          mbar_wait(bars + 8 * (B_HST + 2 * l));
          mbar_wait(bars + 8 * (B_G1DONE + 10 * l + 9));
          cnt_poll(&g_hcnt[(l * 16 + gpc) * 32], 40 * tag);
          fence_async_global();
          if (elect_one()) {
            TS(21 + 2 * l);
            const uint32_t fb2 = bars + 8 * (B_G2FULL + 20 * l), wb2 = bars + 8 * (B_G2DONE + 20 * l - S2);
            const uint8_t* src = g_h + (l * 32 + m2) * 163840;
            uint32_t dst = sb;
#pragma unroll 1
            for (int k = 0; k < 20; k++) {
              if (k >= (l ? XB0 : 5)) mbar_wait(k >= S2 ? wb2 + 8 * k : (l ? fb2 + 8 * (k - XB0) : bars + 8 * B_SFREE));
              if (k == 10) { mbar_wait(bars + 8 * (B_H1 + l)); fence_async_global(); }
              mbar_expect_tx(fb2 + 8 * k, G2_XB);
              bulk_g2s(dst, src, G2_XB, fb2 + 8 * k);
              src += 8192; dst += G2_XB; if (dst == sb + S2 * G2_XB) dst = sb;
            }
          }
          __syncwarp();
        }
      }
    } else if (pw == 2) {
#pragma unroll 1
      for (int l = 0; l < 2; l++) {
        if (l == 1) {
          float xa[2], xb[2];
          mbar_wait(bars + 8 * (B_G1FULL + 11));
          stat_table(T1, tag, 1, 4, g_stats, g_stats, xa, xb);
          mbar_arrive(bars + 8 * (B_STAB + 1));
        }
#pragma unroll 1
        for (int w = 0; w < 2 * l; w++) {
          mbar_wait(bars + 8 * (B_HST + 2 + w));
          if (lane < 4) h_release(2 + w, T1, lane);
          __syncwarp();
          if (lane == 0) { if (w == 0) mbar_arrive(bars + 8 * (B_REL + 1)); TS(w ? 16 : 14); }
        }
        if (l == 0 && has2 && elect_one()) {
#pragma unroll 1
          for (int i = 0; i < 5; i++) {
            const int c = i < 3 ? i : 7 - i;
            mbar_wait(bars + 8 * (B_CVDONE + c));
            bulk_s2g(g_G + (cch0 + 32 * c) * 4096, cv_stage(c), 4096);
          }
          asm volatile("cp.async.bulk.commit_group;" ::: "memory");
          asm volatile("cp.async.bulk.wait_group.read 0;" ::: "memory");
          mbar_arrive(bars + 8 * B_SFREE);
          asm volatile("cp.async.bulk.wait_group 0;" ::: "memory");
          TS(48);
          fence_async_global();
          asm volatile("fence.acq_rel.gpu;" ::: "memory");
#pragma unroll
          for (int i = 0; i < 4; i++) red_rlx(&g_gcnt[(dg * 4 + i) * 32]);
          TS(49);
          mbar_arrive(bars + 8 * (B_GO + 1));
        }
        __syncwarp();
      }
    } else if (has2) {
      mbar_wait(bars + 8 * B_REL);
      if (!CPF && elect_one()) {
        l2_prefetch(p.cre + (160 * dg + 5 * m2) * DM, 6400); l2_prefetch(p.cim + (160 * dg + 5 * m2) * DM, 6400);
      }
      mbar_wait(bars + 8 * (B_HST + 1));
      flag_poll(&g_hcnt[(8 + gpc) * 32], 40 * tag);
      if (lane == 0) { mbar_arrive(bars + 8 * B_H1); TS(22); }
      mbar_wait(bars + 8 * (B_GO + 1));
      flag_poll(&g_gcnt[(dg * 4 + (m2 >> 3)) * 32], 32 * tag);
      fence_async_global();
      if (elect_one()) {
        TS(29);
        mbar_expect_tx(bars + 8 * B_GFULL, 20480);
        tma5(sb + G_OFF, &p.mG, 64 * m2, 0, 0, 0, 10 * dg, bars + 8 * B_GFULL);
      }
      mbar_wait(bars + 8 * (B_HST + 3));
      cnt_poll(&g_hcnt[(24 + gpc) * 32], 40 * tag);
      if (lane == 0) { mbar_arrive(bars + 8 * (B_H1 + 1)); TS(24); }
    }
    } else if (wg == 2 && (role >> 16)) {
      float acc[80];
      float off[2] = {mean0[0], mean0[1]};
      const unsigned tag = lds32(sb + EP_OFF + 20);
      dskip_init<true>(acc, mean0, rstd0);
      mbar_arrive(bars + 8 * B_XFREE);
#pragma unroll 1
      for (int l = 0; l < 2; l++) {
        float mean[2], rstd[2];
        {
          uint32_t alo = desc_lo(sb, 1024), blo = desc_lo(sb + G2_WOFF, 16) + (WTAIL ? l * (G2_WB >> 2) : 0);
          uint32_t fb = bars + 8 * (B_G2FULL + 20 * l);
          fence_regs(acc);
          mbar_wait(bars + 8 * (B_CVDONE + 2));
          mbar_wait(bars + 8 * (B_CVDONE + 3));
          mbar_wait(fb);
          if (tid == 256) TS(33 + 6 * l);
#pragma unroll 1
          for (int k = 0; k < 20; k++) {
            if (l == TSL && (k & 3) == 3 && tid == 256) TS(56 + (k >> 2));
            uint32_t ok; const uint32_t nb = k < 19 ? fb + 8 : fb;
            wgmma_fence();
#pragma unroll
            for (int kk = 0; kk < 4; kk++) {
              wgmma_n160<1>(acc, alo + kk * 128, desc_hi(128, 0), blo + kk * 2, desc_hi(1024, 1));
              if (kk == 0) ok = mbar_test(nb);
            }
            wgmma_commit();
            alo += G2_XB >> 4; blo += G2_WB >> 4;
            if (alo == desc_lo(sb + S2 * G2_XB, 1024)) alo = desc_lo(sb, 1024);
            if (blo == desc_lo(sb + G_OFF, 16)) blo = desc_lo(sb + G2_WOFF, 16);
            wgmma_wait<1>();
            if (k > 0 && tid == 256) mbar_arrive(fb + 8 * (B_G2DONE - B_G2FULL - 1));
            if (!ok) mbar_wait(nb);
            fb += 8;
          }
          wgmma_wait<0>();
          fence_regs(acc);
          if (tid == 256) TS(34 + 6 * l);
          if (tid == 256) mbar_arrive(bars + 8 * (B_G2DONE + 20 * l + 19));
        }
        ROLE(role)
        const int tq = tid_opaque() & 31, n0 = 64 * m2 + 16 * w + (tq >> 2);
        stats_publish<false>(2 * l + 1, n0, dg, tag, acc);
        uint32_t gf[10][4];
        mbar_wait(bars + 8 * B_GFULL);
        const uint32_t ga = sb + G_OFF + (8 * (tq >> 4) + (tq & 7)) * 128 + (((2 * w + ((tq >> 3) & 1)) ^ ((2 * m2) & 6) ^ (tq & 7)) << 4);
#pragma unroll
        for (int J = 0; J < 2; J++) ldsm4t(gf[J], ga + J * 2048);
        if (tid == 256) TS(35 + 6 * l);
        uint8_t* dst[2][2];
#pragma unroll
        for (int h = 0; h < 2; h++) {
          if (l == 0) {
            const int ng = 8 * m2 + 2 * w + h, T = ng / 20;
            uint8_t* ub = g_u + (T * 204800 + (ng - 20 * T) * 1024 + (tq & 2) * 64 + (tq & 28) * 4 + (tq & 1) * 8 + (5 * dg >> 1) * 20480);
            dst[h][1] = ub + ((dg & 1) ? 20480 - 512 : 0);
            dst[h][0] = ub + (dg & 1) * 512;
          } else {
            dst[h][0] = dst[h][1] = (uint8_t*)(p.out + (n_to_t(n0 + 8 * h) * DM + 160 * dg + 4 * (tq & 3)));
          }
        }
        stats_get(2 * l + 1, n0, tag, mean, rstd);
        if (tid == 256) TS(36 + 6 * l);
        off[0] += mean[0]; off[1] += mean[1];
        const float ov[2] = {l ? off[0] : 0.f, l ? off[1] : 0.f};
#pragma unroll
        for (int J = 0; J < 10; J++) {
          if (J + 2 < 10) ldsm4t(gf[J + 2 < 10 ? J + 2 : 0], ga + (J + 2) * 2048);
#pragma unroll
          for (int x = 0; x < 8; x++) {
            const int h = (x >> 1) & 1;
            const uint32_t gwd = gf[J][x >> 1];
            const float t = fmaf(rstd[h], (x & 1) ? bf_hi(gwd) : bf_lo(gwd), 1.f);
            acc[8 * J + x] = fmaf(acc[8 * J + x], t, fmaf(-mean[h], t, ov[h]));
          }
#pragma unroll
          for (int h = 0; h < 2; h++) {
            if (l == 0)
              *(uint2*)(dst[h][(J >> 1) & 1] + (J >> 2) * 20480 + (J & 3) * 256) =
                  make_uint2(pack_bf16(acc[8 * J + 2 * h], acc[8 * J + 2 * h + 1]), pack_bf16(acc[8 * J + 4 + 2 * h], acc[8 * J + 5 + 2 * h]));
            else
              *(float4*)(dst[h][0] + 64 * J) = make_float4(acc[8 * J + 2 * h], acc[8 * J + 2 * h + 1], acc[8 * J + 4 + 2 * h], acc[8 * J + 5 + 2 * h]);
          }
          __syncwarp();
        }
        if (l == 0) {
          bar_sync(3, 128);
          if (tid == 288) { TS(37); mbar_arrive(bars + 8 * B_UST); }
          if (tid < 264) red_rel(&g_ucnt[(tid & 7) * 32]);
          __syncwarp();
          if (tid == 256) TS(38);
          stats_publish<false>(2, n0, dg, tag, acc);
          mbar_wait(bars + 8 * (B_G1FULL + 11));
          float xa[2], xb[2];
          const uint4* x0 = &g_stats[(8 + (tq & 3)) * SEQ + n0];
          stat_table(T1, tag, 1, w, x0, x0 + 8, xa, xb);
          mbar_arrive(bars + 8 * (B_STAB + 1));
          if (tid == 256) TS(27);
          stats_reduce(xa, xb, mean, rstd);
          off[0] += mean[0]; off[1] += mean[1];
          mbar_wait(bars + 8 * (B_HST + 2));
          dskip_init<false>(acc, mean, rstd);
        } else {
          if (tid == 256) {
            TS(43);
            if (m2 == 31 && dg == 3) asm volatile("st.relaxed.gpu.global.u32 [%0], %1;" ::"l"(g_epoch), "r"(tag + 1) : "memory");
          }
        }
      }
    }
  }
}

typedef CUresult (*EncFn)(CUtensorMap*, CUtensorMapDataType, cuuint32_t, void*, const cuuint64_t*, const cuuint64_t*,
                          const cuuint32_t*, const cuuint32_t*, CUtensorMapInterleave, CUtensorMapSwizzle,
                          CUtensorMapL2promotion, CUtensorMapFloatOOBfill);

void encode(EncFn fn, CUtensorMap* m, const void* ptr, int rank, const cuuint64_t* dims, const cuuint64_t* strides, const cuuint32_t* box,
            CUtensorMapSwizzle swz = CU_TENSOR_MAP_SWIZZLE_128B, int prom = 2) {
  cuuint32_t es[5] = {1, 1, 1, 1, 1};
  fn(m, CU_TENSOR_MAP_DATA_TYPE_BFLOAT16, rank, (void*)ptr, dims, strides, box, es, CU_TENSOR_MAP_INTERLEAVE_NONE,
     swz, (CUtensorMapL2promotion)prom, CU_TENSOR_MAP_FLOAT_OOB_FILL_NONE);
}

}

extern "C" void kernel_launch(void* const* d_in, const int* in_sizes, int n_in, void* d_out, int out_size) {
  (void)in_sizes; (void)n_in; (void)out_size;
  Params p;
  typedef const __nv_bfloat16* BP;
  p.x = (BP)d_in[0]; p.lre = (BP)d_in[1]; p.lim = (BP)d_in[2]; p.bre = (BP)d_in[3]; p.bim = (BP)d_in[4];
  p.cre = (BP)d_in[5]; p.cim = (BP)d_in[6]; p.logdt = (BP)d_in[7]; p.dskip = (BP)d_in[8];
  p.k = (BP)d_in[10]; p.v = (BP)d_in[11]; p.shiftk = (BP)d_in[12]; p.ssmk = (BP)d_in[13]; p.ssmD = (BP)d_in[14];
  p.out = (float*)d_out;
  for (int sm = 0; sm < 132; sm++) {
    const int tpc = sm >> 1, side = sm & 1;
    int gpc, gi;
    if (tpc < 32) { gpc = tpc & 7; gi = tpc >> 3; }
    else if (tpc < 60) { gpc = 1 + (tpc - 32) % 7; gi = 4 + (tpc - 32) / 7; }
    else if (tpc < 62) { gpc = tpc - 54; gi = 8; }
    else { gpc = 0; gi = tpc - 58; }
    const int pos = 8 * gpc + gi + (gpc == 7 ? 1 : 0);
    int T1, GP;
    if (pos < 52) { const int hh = pos / 26, x = pos - 26 * hh; T1 = x >> 1; GP = 2 * hh + (x & 1); }
    else { T1 = pos - 52; GP = 4; }
    const int m2 = 8 * (gpc >> 1) + gi, dg = 2 * (gpc & 1) + side;
    p.role[sm] = pos == 65 ? -1 : (T1 | (GP << 4) | (side << 7) | (m2 << 8) | (dg << 14) | ((gi < 8) << 16));
  }
  void* fnp = nullptr;
  cudaDriverEntryPointQueryResult qr;
  cudaGetDriverEntryPoint("cuTensorMapEncodeTiled", &fnp, cudaEnableDefault, &qr);
  EncFn fn = (EncFn)fnp;
  void* gG = nullptr;
  cudaGetSymbolAddress(&gG, g_G);
  void* gKV = nullptr;
  cudaGetSymbolAddress(&gKV, g_kv);
  {
    cuuint64_t dims[5] = {32, 32, 10, 32, 4}, st[4] = {20480, 2048, 64, 655360}; cuuint32_t box[5] = {32, 35, 2, 1, 1};
    encode(fn, &p.mU, gKV, 5, dims, st, box, CU_TENSOR_MAP_SWIZZLE_NONE, 1);
  }
  const cuuint64_t RB = DM * 2;
  {
    p.swap = p.bim < p.bre;
    const char* lo = (const char*)(p.swap ? p.bim : p.bre); const char* hi = (const char*)(p.swap ? p.bre : p.bim);
    cuuint64_t dims[5] = {640, 8, 2, 8, 10}, st[4] = {RB, (cuuint64_t)(hi - lo), 8 * RB, 64 * RB}; cuuint32_t box[5] = {64, 8, 2, 4, 2};
    encode(fn, &p.mB, lo, 5, dims, st, box);
  }
  {
    cuuint64_t dims[5] = {640, 2, 4, 2, 40}, st[4] = {RB, 4 * RB, 2 * RB, 16 * RB}; cuuint32_t box[5] = {64, 2, 4, 2, 10};
    encode(fn, &p.mCre, p.cre, 5, dims, st, box); encode(fn, &p.mCim, p.cim, 5, dims, st, box);
    cuuint64_t dimg[5] = {2048, 2, 4, 2, 40}, stg[4] = {4096, 4 * 4096, 2 * 4096, 16 * 4096};
    encode(fn, &p.mG, gG, 5, dimg, stg, box);
  }
  {
    cuuint64_t dims[4] = {640, 2, 4, 900}, st[3] = {RB, 40 * RB, 2 * RB}; cuuint32_t box[4] = {64, 2, 4, 20};
    encode(fn, &p.mX, p.x, 4, dims, st, box);
    cuuint64_t diml[4] = {640, 2, 4, 16}, stl[3] = {RB, 32 * RB, 2 * RB};
    encode(fn, &p.mXl, p.x + (size_t)1920 * DM, 4, diml, stl, box);
    cuuint32_t boxt[4] = {160, 2, 4, 4};
    encode(fn, &p.mXt, p.x, 4, dims, st, boxt, CU_TENSOR_MAP_SWIZZLE_NONE);
    encode(fn, &p.mXtl, p.x + (size_t)1920 * DM, 4, diml, stl, boxt, CU_TENSOR_MAP_SWIZZLE_NONE);
    cuuint64_t dk[3] = {640, 2000, 4}, sk[2] = {RB, 16 * RB}; cuuint32_t bk[3] = {32, 19, 4}, bv[3] = {32, 17, 4};
    encode(fn, &p.mK, p.k, 3, dk, sk, bk, CU_TENSOR_MAP_SWIZZLE_NONE);
    encode(fn, &p.mV, p.v, 3, dk, sk, bv, CU_TENSOR_MAP_SWIZZLE_NONE);
  }
  cudaFuncSetAttribute(fused_kernel, cudaFuncAttributeMaxDynamicSharedMemorySize, SMEM_BYTES);
  cudaLaunchConfig_t cfg = {};
  cfg.gridDim = dim3(132); cfg.blockDim = dim3(512); cfg.dynamicSmemBytes = SMEM_BYTES; cfg.stream = cudaStreamPerThread;
  cudaLaunchKernelEx(&cfg, fused_kernel, p);
}
```

```cpp
#include <cuda_runtime.h>
#include <cuda.h>
#include <cuda_bf16.h>
#include <stdint.h>

namespace {

constexpr int SEQ = 2048, DM = 640;
constexpr int NT1 = 13;
#define EXP 0
#define WPF1 3
#define WPF2 7
#define CPOLL 10
#define KV0 1
#define TAPLATE 1
#define STG_D 3
#define STG_KK 1
#define HOLD0 1
#define WREL 0
#define UREL 1
#define TSL 1
#define STG0 2
#define WTAIL 1
#define PFD 1
#define TAPW 0
#define TPF 4
#define CPF 0
#define MK0 7
#define MK1 4
#define PACE 180
#define XB0 3
#define TAPN 2
#define REL3 0
#define PAUSE_K 5
constexpr uint32_t SPIN_LIMIT = 1u << 22;

__device__ __align__(1024) uint8_t g_h[2 * 32 * 20 * 8192];
__device__ __align__(1024) uint8_t g_u[NT1 * 10 * 20480];
__device__ __align__(1024) uint8_t g_kv[DM * 4096];
__device__ __align__(1024) uint8_t g_G[DM * 4096];
__device__ __align__(128) uint4 g_E[2 * NT1 * DM];
__device__ __align__(128) uint4 g_stats[4 * 4 * SEQ];
__device__ __align__(128) uint4 g_sB[DM * 2];
__device__ __align__(128) unsigned g_hcnt[2 * 2 * 8 * 32];
__device__ __align__(128) unsigned g_ucnt[8 * 32];
__device__ __align__(128) unsigned g_kvcnt[16 * 32];
__device__ __align__(128) unsigned g_gcnt[16 * 32];
__device__ __align__(128) unsigned g_epoch[32] = {1};
#define TS(i) do {} while (0)

struct Params {
  CUtensorMap mX, mB, mXl, mK, mV, mXt, mXtl, mCre, mCim, mG, mU;
  const __nv_bfloat16 *x, *lre, *lim, *bre, *bim, *cre, *cim, *logdt, *dskip, *k, *v, *shiftk, *ssmk, *ssmD;
  float* out;
  int swap;
  int role[132];
};

constexpr uint32_t sb = 1024;
constexpr uint32_t G1_STAGE = 36864, G1_XOFF = 16384;
constexpr int S1 = 4;
constexpr uint32_t XT_OFF = 159744, KS_OFF = 180224, KV_PIECE = 9216;
constexpr uint32_t G2_XB = 8192, G2_WB = 20480, G2_WOFF = 57344, G_OFF = 200704;
constexpr uint32_t X1_OFF = 139264;
constexpr int S2 = 7;
constexpr uint32_t CV_OFF = KS_OFF, CV_K = 128, CV_PL = 2240, CV_U = CV_K + 4096, CV_B = KV_PIECE;
constexpr uint32_t MISC = 226304;
constexpr uint32_t BAR_OFF = MISC;
constexpr int B_G1FULL = 0, B_G1DONE = 20, B_G2FULL = 40,
              B_G2DONE = 85, B_GFULL = 125, B_EP = 126, B_H1 = 127  , B_CVFULL = 129  , B_STG = 134  , B_REL = 136  , B_SFREE = 138, B_UST = 142,
              B_GO = 139  , B_PUB = 147,
              B_CVDONE = 148  , B_STAB = 153  , B_XFREE = 155, B_HST = 156  ,
              B_CTAB = 160, B_PREP = 161, B_XT = 162, B_KV = 163  , B_PREP2 = 84, B_PD = 168  ;
constexpr uint32_t bars = sb + BAR_OFF;
constexpr uint32_t STAB_OFF = MISC + 1392;
constexpr uint32_t CTAB_OFF = STAB_OFF + 640;
constexpr uint32_t DTAB_OFF = CTAB_OFF + 1536;
constexpr uint32_t EP_OFF = DTAB_OFF + 320;
constexpr uint32_t SO_OFF = EP_OFF + 32;
constexpr uint32_t TAP_OFF = 147456;
constexpr uint32_t MX0_OFF = TAP_OFF + 1280, MX1_OFF = G_OFF + 20480;
constexpr uint32_t SMEM_BYTES = 232448;
static_assert(SO_OFF + 1536 <= SMEM_BYTES, "smem");

__device__ __forceinline__ void trap_if(bool c) { asm volatile("{\n.reg .pred p;\nsetp.ne.u32 p, %0, 0;\n@p trap;\n}\n" ::"r"((uint32_t)c)); }
__device__ __forceinline__ uint32_t smem_u32(const void* p) { return (uint32_t)__cvta_generic_to_shared(p); }
__device__ __forceinline__ void mbar_init(uint32_t bar, int cnt) { asm volatile("mbarrier.init.shared::cta.b64 [%0], %1;" ::"r"(bar), "r"(cnt) : "memory"); }
__device__ __forceinline__ void mbar_expect_tx(uint32_t bar, int bytes) { asm volatile("mbarrier.arrive.expect_tx.shared::cta.b64 _, [%0], %1;" ::"r"(bar), "r"(bytes) : "memory"); }
__device__ __forceinline__ void mbar_arrive(uint32_t bar) { asm volatile("mbarrier.arrive.shared::cta.b64 _, [%0];" ::"r"(bar) : "memory"); }
__device__ __forceinline__ void mbar_wait(uint32_t bar) {
  asm volatile(
      "{\n.reg .pred p;\n.reg .u32 c;\nmov.u32 c, 0;\n"
      "W_%=:\nmbarrier.try_wait.parity.shared::cta.b64 p, [%0], 0;\n@p bra D_%=;\n"
      "add.u32 c, c, 1;\nsetp.lt.u32 p, c, %1;\n@p bra W_%=;\ntrap;\nD_%=:\n}\n" ::"r"(bar), "n"(SPIN_LIMIT) : "memory");
}
__device__ __forceinline__ uint32_t mbar_test(uint32_t bar) {
  uint32_t ok;
  asm volatile("{\n.reg .pred p;\nmbarrier.test_wait.parity.shared::cta.b64 p, [%1], 0;\nselp.u32 %0, 1, 0, p;\n}\n" : "=r"(ok) : "r"(bar) : "memory");
  return ok;
}
__device__ __forceinline__ void tma3(uint32_t dst, const CUtensorMap* m, int c0, int c1, int c2, uint32_t bar) {
  asm volatile("cp.async.bulk.tensor.3d.shared::cluster.global.mbarrier::complete_tx::bytes [%0], [%1, {%3,%4,%5}], [%2];"
               ::"r"(dst), "l"(m), "r"(bar), "r"(c0), "r"(c1), "r"(c2) : "memory");
}
__device__ __forceinline__ void tma4(uint32_t dst, const CUtensorMap* m, int c0, int c1, int c2, int c3, uint32_t bar) {
  asm volatile("cp.async.bulk.tensor.4d.shared::cluster.global.mbarrier::complete_tx::bytes [%0], [%1, {%3,%4,%5,%6}], [%2];"
               ::"r"(dst), "l"(m), "r"(bar), "r"(c0), "r"(c1), "r"(c2), "r"(c3) : "memory");
}
__device__ __forceinline__ void tma5(uint32_t dst, const CUtensorMap* m, int c0, int c1, int c2, int c3, int c4, uint32_t bar) {
  asm volatile("cp.async.bulk.tensor.5d.shared::cluster.global.mbarrier::complete_tx::bytes [%0], [%1, {%3,%4,%5,%6,%7}], [%2];"
               ::"r"(dst), "l"(m), "r"(bar), "r"(c0), "r"(c1), "r"(c2), "r"(c3), "r"(c4) : "memory");
}
__device__ __forceinline__ void bulk_g2s(uint32_t dst, const void* src, int bytes, uint32_t bar) {
  asm volatile("cp.async.bulk.shared::cluster.global.mbarrier::complete_tx::bytes [%0], [%1], %2, [%3];"
               ::"r"(dst), "l"(src), "r"(bytes), "r"(bar) : "memory");
}
__device__ __forceinline__ void bulk_s2g(void* dst, uint32_t src, int bytes) {
  asm volatile("cp.async.bulk.global.shared::cta.bulk_group [%0], [%1], %2;" ::"l"(dst), "r"(src), "r"(bytes) : "memory");
}
__device__ __forceinline__ void l2_prefetch(const void* src, int bytes) {
  asm volatile("cp.async.bulk.prefetch.L2.global [%0], %1;" ::"l"(src), "r"(bytes) : "memory");
}
__device__ __forceinline__ void wgmma_fence() { asm volatile("wgmma.fence.sync.aligned;" ::: "memory"); }
__device__ __forceinline__ void wgmma_commit() { asm volatile("wgmma.commit_group.sync.aligned;" ::: "memory"); }
template <int N> __device__ __forceinline__ void wgmma_wait() { asm volatile("wgmma.wait_group.sync.aligned %0;" ::"n"(N) : "memory"); }
__host__ __device__ constexpr uint32_t desc_lo(uint32_t addr, uint32_t lbo) { return ((addr & 0x3FFFF) >> 4) | ((lbo >> 4) << 16); }
__host__ __device__ constexpr uint32_t desc_hi(uint32_t sbo, uint32_t swz) { return (sbo >> 4) | (swz << 30); }
__device__ __forceinline__ void bar_sync(int id, int n) { asm volatile("bar.sync %0, %1;" ::"r"(id), "r"(n) : "memory"); }
__device__ __forceinline__ uint32_t lds32(uint32_t a) { uint32_t v; asm volatile("ld.shared.u32 %0, [%1];" : "=r"(v) : "r"(a) : "memory"); return v; }
__device__ __forceinline__ float2 lds64f(uint32_t a) { float2 v; asm volatile("ld.shared.v2.f32 {%0,%1}, [%2];" : "=f"(v.x), "=f"(v.y) : "r"(a) : "memory"); return v; }
__device__ __forceinline__ float4 lds128f(uint32_t a) { float4 v; asm volatile("ld.shared.v4.f32 {%0,%1,%2,%3}, [%4];" : "=f"(v.x), "=f"(v.y), "=f"(v.z), "=f"(v.w) : "r"(a) : "memory"); return v; }
__device__ __forceinline__ void ldsm4t(uint32_t (&r)[4], uint32_t a) {
  asm volatile("ldmatrix.sync.aligned.m8n8.x4.trans.shared.b16 {%0,%1,%2,%3}, [%4];" : "=r"(r[0]), "=r"(r[1]), "=r"(r[2]), "=r"(r[3]) : "r"(a) : "memory");
}
__device__ __forceinline__ uint4 ldv128(const void* a) { uint4 v; asm volatile("ld.global.nc.v4.u32 {%0,%1,%2,%3}, [%4];" : "=r"(v.x), "=r"(v.y), "=r"(v.z), "=r"(v.w) : "l"(a) : "memory"); return v; }
__device__ __forceinline__ uint2 ldv64(const void* a) { uint2 v; asm volatile("ld.global.nc.v2.u32 {%0,%1}, [%2];" : "=r"(v.x), "=r"(v.y) : "l"(a) : "memory"); return v; }
__device__ __forceinline__ uint32_t ldv16(const void* a) { uint32_t v; asm volatile("ld.global.nc.u16 %0, [%1];" : "=r"(v) : "l"(a) : "memory"); return v; }
__device__ __forceinline__ void sts128(uint32_t a, uint4 v) { asm volatile("st.shared.v4.u32 [%0], {%1,%2,%3,%4};" ::"r"(a), "r"(v.x), "r"(v.y), "r"(v.z), "r"(v.w) : "memory"); }
__device__ __forceinline__ void sts32(uint32_t a, uint32_t v) { asm volatile("st.shared.u32 [%0], %1;" ::"r"(a), "r"(v) : "memory"); }
__device__ __forceinline__ void sts64f(uint32_t a, float x, float y) { asm volatile("st.shared.v2.f32 [%0], {%1,%2};" ::"r"(a), "f"(x), "f"(y) : "memory"); }
__device__ __forceinline__ void red_rlx(unsigned* p) { asm volatile("red.relaxed.gpu.global.add.u32 [%0], 1;" ::"l"(p) : "memory"); }
__device__ __forceinline__ void red_rel(unsigned* p) { asm volatile("red.release.gpu.global.add.u32 [%0], 1;" ::"l"(p) : "memory"); }
__device__ __forceinline__ void fence_async_global() { asm volatile("fence.proxy.async.global;" ::: "memory"); }
__device__ __forceinline__ void fence_async_smem() { asm volatile("fence.proxy.async.shared::cta;" ::: "memory"); }
__device__ __forceinline__ void rec_st(uint4* p, float a, float b, unsigned tag) {
  asm volatile("{\n.reg .b128 t;\n.reg .b64 lo, hi;\nmov.b64 lo, {%1,%2};\nmov.b64 hi, {%3,%3};\nmov.b128 t, {lo,hi};\n"
               "st.relaxed.gpu.global.b128 [%0], t;\n}\n" ::"l"(p), "r"(__float_as_uint(a)), "r"(__float_as_uint(b)), "r"(tag) : "memory");
}
__device__ __forceinline__ unsigned rec_ld(const uint4* p, float& a, float& b) {
  unsigned x, y, t;
  asm volatile("{\n.reg .b128 t;\n.reg .b64 lo, hi;\n.reg .b32 u;\nld.relaxed.gpu.global.b128 t, [%3];\nmov.b128 {lo,hi}, t;\n"
               "mov.b64 {%0,%1}, lo;\nmov.b64 {%2,u}, hi;\n}\n" : "=r"(x), "=r"(y), "=r"(t) : "l"(p) : "memory");
  a = __uint_as_float(x); b = __uint_as_float(y);
  return t;
}
__device__ __forceinline__ unsigned ld_rlx(const unsigned* p) { unsigned v; asm volatile("ld.relaxed.gpu.global.u32 %0, [%1];" : "=r"(v) : "l"(p) : "memory"); return v; }
__device__ __forceinline__ void flag_poll(const unsigned* p, unsigned target) {
  uint32_t it = 0;
  while (!__all_sync(0xffffffffu, (int)(ld_rlx(p) - target) >= 0)) { trap_if(++it > SPIN_LIMIT); }
  asm volatile("fence.acquire.gpu;" ::: "memory");
}
__device__ __forceinline__ void cnt_poll(const unsigned* p, unsigned target) {
  unsigned a = ld_rlx(p); __nanosleep(100);
  unsigned b = ld_rlx(p); __nanosleep(100);
  unsigned c = ld_rlx(p);
  uint32_t it = 0;
  while (true) {
    if (__all_sync(0xffffffffu, (int)(a - target) >= 0)) break;
    a = ld_rlx(p);
    if (__all_sync(0xffffffffu, (int)(b - target) >= 0)) break;
    b = ld_rlx(p);
    if (__all_sync(0xffffffffu, (int)(c - target) >= 0)) break;
    c = ld_rlx(p);
    trap_if(++it > SPIN_LIMIT);
  }
  asm volatile("fence.acquire.gpu;" ::: "memory");
}
__device__ __forceinline__ void h_release(int idx, int T, int i) {
  const int Q = (i & 2) ? (T + 2) / 3 - 1 : T / 3;
  if (Q >= 0 && Q < 4 && ((i & 2) == 0 || T % 3 == 0)) red_rel(&g_hcnt[(idx * 8 + 2 * Q + (i & 1)) * 32]);
}
__device__ __forceinline__ uint32_t pack_bf16(float lo, float hi) {
  uint32_t r; asm("cvt.rn.bf16x2.f32 %0, %1, %2;" : "=r"(r) : "f"(hi), "f"(lo)); return r;
}
__device__ __forceinline__ float bf_lo(uint32_t w) { return __uint_as_float(w << 16); }
__device__ __forceinline__ float bf_hi(uint32_t w) { return __uint_as_float(w & 0xffff0000u); }
__device__ __forceinline__ uint32_t hmul2(uint32_t a, uint32_t b) {
  __nv_bfloat162 r = __hmul2_rn(*(__nv_bfloat162*)&a, *(__nv_bfloat162*)&b); return *(uint32_t*)&r;
}
__device__ __forceinline__ uint32_t hadd2(uint32_t a, uint32_t b) {
  __nv_bfloat162 r = __hadd2_rn(*(__nv_bfloat162*)&a, *(__nv_bfloat162*)&b); return *(uint32_t*)&r;
}
__device__ __forceinline__ float2 cmul(float2 a, float2 b) { return make_float2(a.x * b.x - a.y * b.y, a.x * b.y + a.y * b.x); }
__device__ __forceinline__ float2 cfma(float2 a, float2 b, float2 c) {
  return make_float2(fmaf(a.x, b.x, fmaf(-a.y, b.y, c.x)), fmaf(a.x, b.y, fmaf(a.y, b.x, c.y)));
}
template <int N> __device__ __forceinline__ void fence_regs(float (&a)[N]) {
#pragma unroll
  for (int i = 0; i < N; i++) asm volatile("" : "+f"(a[i])::"memory");
}
__device__ __forceinline__ bool elect_one() {
  uint32_t e; asm volatile("{\n.reg .pred P;\nelect.sync _|P, 0xffffffff;\nselp.u32 %0, 1, 0, P;\n}\n" : "=r"(e)); return e != 0;
}
__device__ __forceinline__ int tid_opaque() { int t; asm volatile("mov.u32 %0, %%tid.x;" : "=r"(t)); return t; }
struct Role { int T1, GP, side, m2, dg, cch0; bool last, has2; };
__device__ __forceinline__ Role unpack_role(int x) {
  Role r; r.T1 = x & 15; r.GP = (x >> 4) & 7; r.side = (x >> 7) & 1; r.m2 = (x >> 8) & 63; r.dg = (x >> 14) & 3;
  r.has2 = (x >> 16) & 1; r.last = r.T1 == NT1 - 1; r.cch0 = 160 * r.dg + r.m2; return r;
}
__device__ __forceinline__ Role fresh_role(int x) { asm volatile("" : "+r"(x)); return unpack_role(__shfl_sync(0xffffffffu, x, 0)); }
#define ROLE(x) const Role R_ = fresh_role(x); const int T1 = R_.T1, GP = R_.GP, side = R_.side, m2 = R_.m2, dg = R_.dg, cch0 = R_.cch0; \
  const bool last = R_.last, has2 = R_.has2; (void)T1; (void)GP; (void)side; (void)m2; (void)dg; (void)cch0; (void)last; (void)has2;
__device__ __forceinline__ int n_to_t(int n) {
  int T = n / 160, nl = n - T * 160;
  int L = (T == NT1 - 1) ? 32 : 40;
  return T * 160 + L * ((nl & 7) >> 1) + 2 * (nl >> 3) + (nl & 1);
}

template<int TA> __device__ __forceinline__ void wgmma_n160(float (&d)[80], uint32_t alo, uint32_t ahi, uint32_t blo, uint32_t bhi){
  asm volatile("{\n.reg .b64 da, db;\nmov.b64 da, {%80,%81};\nmov.b64 db, {%82,%83};\n"
    "wgmma.mma_async.sync.aligned.m64n160k16.f32.bf16.bf16 {%0, %1, %2, %3, %4, %5, %6, %7, %8, %9, %10, %11, %12, %13, %14, %15, %16, %17, %18, %19, %20, %21, %22, %23, %24, %25, %26, %27, %28, %29, %30, %31, %32, %33, %34, %35, %36, %37, %38, %39, %40, %41, %42, %43, %44, %45, %46, %47, %48, %49, %50, %51, %52, %53, %54, %55, %56, %57, %58, %59, %60, %61, %62, %63, %64, %65, %66, %67, %68, %69, %70, %71, %72, %73, %74, %75, %76, %77, %78, %79}, da, db, 1, 1, 1, %84, 0;\n}\n"
    : "+f"(d[0]), "+f"(d[1]), "+f"(d[2]), "+f"(d[3]), "+f"(d[4]), "+f"(d[5]), "+f"(d[6]), "+f"(d[7]), "+f"(d[8]), "+f"(d[9]), "+f"(d[10]), "+f"(d[11]), "+f"(d[12]), "+f"(d[13]), "+f"(d[14]), "+f"(d[15]), "+f"(d[16]), "+f"(d[17]), "+f"(d[18]), "+f"(d[19]), "+f"(d[20]), "+f"(d[21]), "+f"(d[22]), "+f"(d[23]), "+f"(d[24]), "+f"(d[25]), "+f"(d[26]), "+f"(d[27]), "+f"(d[28]), "+f"(d[29]), "+f"(d[30]), "+f"(d[31]), "+f"(d[32]), "+f"(d[33]), "+f"(d[34]), "+f"(d[35]), "+f"(d[36]), "+f"(d[37]), "+f"(d[38]), "+f"(d[39]), "+f"(d[40]), "+f"(d[41]), "+f"(d[42]), "+f"(d[43]), "+f"(d[44]), "+f"(d[45]), "+f"(d[46]), "+f"(d[47]), "+f"(d[48]), "+f"(d[49]), "+f"(d[50]), "+f"(d[51]), "+f"(d[52]), "+f"(d[53]), "+f"(d[54]), "+f"(d[55]), "+f"(d[56]), "+f"(d[57]), "+f"(d[58]), "+f"(d[59]), "+f"(d[60]), "+f"(d[61]), "+f"(d[62]), "+f"(d[63]), "+f"(d[64]), "+f"(d[65]), "+f"(d[66]), "+f"(d[67]), "+f"(d[68]), "+f"(d[69]), "+f"(d[70]), "+f"(d[71]), "+f"(d[72]), "+f"(d[73]), "+f"(d[74]), "+f"(d[75]), "+f"(d[76]), "+f"(d[77]), "+f"(d[78]), "+f"(d[79])
    : "r"(alo), "r"(ahi), "r"(blo), "r"(bhi), "n"(TA));
}
__device__ __forceinline__ void wgmma_rs_n160(float (&d)[80], uint32_t a0, uint32_t a1, uint32_t a2, uint32_t a3, uint32_t blo){
  asm volatile("{\n.reg .b64 db;\nmov.b64 db, {%84,8};\nwgmma.mma_async.sync.aligned.m64n160k16.f32.bf16.bf16 {%0, %1, %2, %3, %4, %5, %6, %7, %8, %9, %10, %11, %12, %13, %14, %15, %16, %17, %18, %19, %20, %21, %22, %23, %24, %25, %26, %27, %28, %29, %30, %31, %32, %33, %34, %35, %36, %37, %38, %39, %40, %41, %42, %43, %44, %45, %46, %47, %48, %49, %50, %51, %52, %53, %54, %55, %56, %57, %58, %59, %60, %61, %62, %63, %64, %65, %66, %67, %68, %69, %70, %71, %72, %73, %74, %75, %76, %77, %78, %79}, {%80,%81,%82,%83}, db, 1, 1, 1, 0;\n}\n"
    : "+f"(d[0]), "+f"(d[1]), "+f"(d[2]), "+f"(d[3]), "+f"(d[4]), "+f"(d[5]), "+f"(d[6]), "+f"(d[7]), "+f"(d[8]), "+f"(d[9]), "+f"(d[10]), "+f"(d[11]), "+f"(d[12]), "+f"(d[13]), "+f"(d[14]), "+f"(d[15]), "+f"(d[16]), "+f"(d[17]), "+f"(d[18]), "+f"(d[19]), "+f"(d[20]), "+f"(d[21]), "+f"(d[22]), "+f"(d[23]), "+f"(d[24]), "+f"(d[25]), "+f"(d[26]), "+f"(d[27]), "+f"(d[28]), "+f"(d[29]), "+f"(d[30]), "+f"(d[31]), "+f"(d[32]), "+f"(d[33]), "+f"(d[34]), "+f"(d[35]), "+f"(d[36]), "+f"(d[37]), "+f"(d[38]), "+f"(d[39]), "+f"(d[40]), "+f"(d[41]), "+f"(d[42]), "+f"(d[43]), "+f"(d[44]), "+f"(d[45]), "+f"(d[46]), "+f"(d[47]), "+f"(d[48]), "+f"(d[49]), "+f"(d[50]), "+f"(d[51]), "+f"(d[52]), "+f"(d[53]), "+f"(d[54]), "+f"(d[55]), "+f"(d[56]), "+f"(d[57]), "+f"(d[58]), "+f"(d[59]), "+f"(d[60]), "+f"(d[61]), "+f"(d[62]), "+f"(d[63]), "+f"(d[64]), "+f"(d[65]), "+f"(d[66]), "+f"(d[67]), "+f"(d[68]), "+f"(d[69]), "+f"(d[70]), "+f"(d[71]), "+f"(d[72]), "+f"(d[73]), "+f"(d[74]), "+f"(d[75]), "+f"(d[76]), "+f"(d[77]), "+f"(d[78]), "+f"(d[79])
    : "r"(a0), "r"(a1), "r"(a2), "r"(a3), "r"(blo));
}
template<int N> __device__ __forceinline__ void wgmma_rs_hi(float (&d)[64], uint32_t a0, uint32_t a1, uint32_t a2, uint32_t a3, uint32_t blo);
template<> __device__ __forceinline__ void wgmma_rs_hi<16>(float (&d)[64], uint32_t a0, uint32_t a1, uint32_t a2, uint32_t a3, uint32_t blo){
  asm volatile("{\n.reg .b64 db;\nmov.b64 db, {%12,8};\nwgmma.mma_async.sync.aligned.m64n16k16.f32.bf16.bf16 {%0, %1, %2, %3, %4, %5, %6, %7}, {%8,%9,%10,%11}, db, 1, 1, 1, 0;\n}\n"
    : "+f"(d[56]), "+f"(d[57]), "+f"(d[58]), "+f"(d[59]), "+f"(d[60]), "+f"(d[61]), "+f"(d[62]), "+f"(d[63])
    : "r"(a0), "r"(a1), "r"(a2), "r"(a3), "r"(blo));
}
template<> __device__ __forceinline__ void wgmma_rs_hi<32>(float (&d)[64], uint32_t a0, uint32_t a1, uint32_t a2, uint32_t a3, uint32_t blo){
  asm volatile("{\n.reg .b64 db;\nmov.b64 db, {%20,8};\nwgmma.mma_async.sync.aligned.m64n32k16.f32.bf16.bf16 {%0, %1, %2, %3, %4, %5, %6, %7, %8, %9, %10, %11, %12, %13, %14, %15}, {%16,%17,%18,%19}, db, 1, 1, 1, 0;\n}\n"
    : "+f"(d[48]), "+f"(d[49]), "+f"(d[50]), "+f"(d[51]), "+f"(d[52]), "+f"(d[53]), "+f"(d[54]), "+f"(d[55]), "+f"(d[56]), "+f"(d[57]), "+f"(d[58]), "+f"(d[59]), "+f"(d[60]), "+f"(d[61]), "+f"(d[62]), "+f"(d[63])
    : "r"(a0), "r"(a1), "r"(a2), "r"(a3), "r"(blo));
}
template<> __device__ __forceinline__ void wgmma_rs_hi<48>(float (&d)[64], uint32_t a0, uint32_t a1, uint32_t a2, uint32_t a3, uint32_t blo){
  asm volatile("{\n.reg .b64 db;\nmov.b64 db, {%28,8};\nwgmma.mma_async.sync.aligned.m64n48k16.f32.bf16.bf16 {%0, %1, %2, %3, %4, %5, %6, %7, %8, %9, %10, %11, %12, %13, %14, %15, %16, %17, %18, %19, %20, %21, %22, %23}, {%24,%25,%26,%27}, db, 1, 1, 1, 0;\n}\n"
    : "+f"(d[40]), "+f"(d[41]), "+f"(d[42]), "+f"(d[43]), "+f"(d[44]), "+f"(d[45]), "+f"(d[46]), "+f"(d[47]), "+f"(d[48]), "+f"(d[49]), "+f"(d[50]), "+f"(d[51]), "+f"(d[52]), "+f"(d[53]), "+f"(d[54]), "+f"(d[55]), "+f"(d[56]), "+f"(d[57]), "+f"(d[58]), "+f"(d[59]), "+f"(d[60]), "+f"(d[61]), "+f"(d[62]), "+f"(d[63])
    : "r"(a0), "r"(a1), "r"(a2), "r"(a3), "r"(blo));
}
template<> __device__ __forceinline__ void wgmma_rs_hi<64>(float (&d)[64], uint32_t a0, uint32_t a1, uint32_t a2, uint32_t a3, uint32_t blo){
  asm volatile("{\n.reg .b64 db;\nmov.b64 db, {%36,8};\nwgmma.mma_async.sync.aligned.m64n64k16.f32.bf16.bf16 {%0, %1, %2, %3, %4, %5, %6, %7, %8, %9, %10, %11, %12, %13, %14, %15, %16, %17, %18, %19, %20, %21, %22, %23, %24, %25, %26, %27, %28, %29, %30, %31}, {%32,%33,%34,%35}, db, 1, 1, 1, 0;\n}\n"
    : "+f"(d[32]), "+f"(d[33]), "+f"(d[34]), "+f"(d[35]), "+f"(d[36]), "+f"(d[37]), "+f"(d[38]), "+f"(d[39]), "+f"(d[40]), "+f"(d[41]), "+f"(d[42]), "+f"(d[43]), "+f"(d[44]), "+f"(d[45]), "+f"(d[46]), "+f"(d[47]), "+f"(d[48]), "+f"(d[49]), "+f"(d[50]), "+f"(d[51]), "+f"(d[52]), "+f"(d[53]), "+f"(d[54]), "+f"(d[55]), "+f"(d[56]), "+f"(d[57]), "+f"(d[58]), "+f"(d[59]), "+f"(d[60]), "+f"(d[61]), "+f"(d[62]), "+f"(d[63])
    : "r"(a0), "r"(a1), "r"(a2), "r"(a3), "r"(blo));
}
template<> __device__ __forceinline__ void wgmma_rs_hi<80>(float (&d)[64], uint32_t a0, uint32_t a1, uint32_t a2, uint32_t a3, uint32_t blo){
  asm volatile("{\n.reg .b64 db;\nmov.b64 db, {%44,8};\nwgmma.mma_async.sync.aligned.m64n80k16.f32.bf16.bf16 {%0, %1, %2, %3, %4, %5, %6, %7, %8, %9, %10, %11, %12, %13, %14, %15, %16, %17, %18, %19, %20, %21, %22, %23, %24, %25, %26, %27, %28, %29, %30, %31, %32, %33, %34, %35, %36, %37, %38, %39}, {%40,%41,%42,%43}, db, 1, 1, 1, 0;\n}\n"
    : "+f"(d[24]), "+f"(d[25]), "+f"(d[26]), "+f"(d[27]), "+f"(d[28]), "+f"(d[29]), "+f"(d[30]), "+f"(d[31]), "+f"(d[32]), "+f"(d[33]), "+f"(d[34]), "+f"(d[35]), "+f"(d[36]), "+f"(d[37]), "+f"(d[38]), "+f"(d[39]), "+f"(d[40]), "+f"(d[41]), "+f"(d[42]), "+f"(d[43]), "+f"(d[44]), "+f"(d[45]), "+f"(d[46]), "+f"(d[47]), "+f"(d[48]), "+f"(d[49]), "+f"(d[50]), "+f"(d[51]), "+f"(d[52]), "+f"(d[53]), "+f"(d[54]), "+f"(d[55]), "+f"(d[56]), "+f"(d[57]), "+f"(d[58]), "+f"(d[59]), "+f"(d[60]), "+f"(d[61]), "+f"(d[62]), "+f"(d[63])
    : "r"(a0), "r"(a1), "r"(a2), "r"(a3), "r"(blo));
}
template<> __device__ __forceinline__ void wgmma_rs_hi<96>(float (&d)[64], uint32_t a0, uint32_t a1, uint32_t a2, uint32_t a3, uint32_t blo){
  asm volatile("{\n.reg .b64 db;\nmov.b64 db, {%52,8};\nwgmma.mma_async.sync.aligned.m64n96k16.f32.bf16.bf16 {%0, %1, %2, %3, %4, %5, %6, %7, %8, %9, %10, %11, %12, %13, %14, %15, %16, %17, %18, %19, %20, %21, %22, %23, %24, %25, %26, %27, %28, %29, %30, %31, %32, %33, %34, %35, %36, %37, %38, %39, %40, %41, %42, %43, %44, %45, %46, %47}, {%48,%49,%50,%51}, db, 1, 1, 1, 0;\n}\n"
    : "+f"(d[16]), "+f"(d[17]), "+f"(d[18]), "+f"(d[19]), "+f"(d[20]), "+f"(d[21]), "+f"(d[22]), "+f"(d[23]), "+f"(d[24]), "+f"(d[25]), "+f"(d[26]), "+f"(d[27]), "+f"(d[28]), "+f"(d[29]), "+f"(d[30]), "+f"(d[31]), "+f"(d[32]), "+f"(d[33]), "+f"(d[34]), "+f"(d[35]), "+f"(d[36]), "+f"(d[37]), "+f"(d[38]), "+f"(d[39]), "+f"(d[40]), "+f"(d[41]), "+f"(d[42]), "+f"(d[43]), "+f"(d[44]), "+f"(d[45]), "+f"(d[46]), "+f"(d[47]), "+f"(d[48]), "+f"(d[49]), "+f"(d[50]), "+f"(d[51]), "+f"(d[52]), "+f"(d[53]), "+f"(d[54]), "+f"(d[55]), "+f"(d[56]), "+f"(d[57]), "+f"(d[58]), "+f"(d[59]), "+f"(d[60]), "+f"(d[61]), "+f"(d[62]), "+f"(d[63])
    : "r"(a0), "r"(a1), "r"(a2), "r"(a3), "r"(blo));
}
template<> __device__ __forceinline__ void wgmma_rs_hi<112>(float (&d)[64], uint32_t a0, uint32_t a1, uint32_t a2, uint32_t a3, uint32_t blo){
  asm volatile("{\n.reg .b64 db;\nmov.b64 db, {%60,8};\nwgmma.mma_async.sync.aligned.m64n112k16.f32.bf16.bf16 {%0, %1, %2, %3, %4, %5, %6, %7, %8, %9, %10, %11, %12, %13, %14, %15, %16, %17, %18, %19, %20, %21, %22, %23, %24, %25, %26, %27, %28, %29, %30, %31, %32, %33, %34, %35, %36, %37, %38, %39, %40, %41, %42, %43, %44, %45, %46, %47, %48, %49, %50, %51, %52, %53, %54, %55}, {%56,%57,%58,%59}, db, 1, 1, 1, 0;\n}\n"
    : "+f"(d[8]), "+f"(d[9]), "+f"(d[10]), "+f"(d[11]), "+f"(d[12]), "+f"(d[13]), "+f"(d[14]), "+f"(d[15]), "+f"(d[16]), "+f"(d[17]), "+f"(d[18]), "+f"(d[19]), "+f"(d[20]), "+f"(d[21]), "+f"(d[22]), "+f"(d[23]), "+f"(d[24]), "+f"(d[25]), "+f"(d[26]), "+f"(d[27]), "+f"(d[28]), "+f"(d[29]), "+f"(d[30]), "+f"(d[31]), "+f"(d[32]), "+f"(d[33]), "+f"(d[34]), "+f"(d[35]), "+f"(d[36]), "+f"(d[37]), "+f"(d[38]), "+f"(d[39]), "+f"(d[40]), "+f"(d[41]), "+f"(d[42]), "+f"(d[43]), "+f"(d[44]), "+f"(d[45]), "+f"(d[46]), "+f"(d[47]), "+f"(d[48]), "+f"(d[49]), "+f"(d[50]), "+f"(d[51]), "+f"(d[52]), "+f"(d[53]), "+f"(d[54]), "+f"(d[55]), "+f"(d[56]), "+f"(d[57]), "+f"(d[58]), "+f"(d[59]), "+f"(d[60]), "+f"(d[61]), "+f"(d[62]), "+f"(d[63])
    : "r"(a0), "r"(a1), "r"(a2), "r"(a3), "r"(blo));
}
template<> __device__ __forceinline__ void wgmma_rs_hi<128>(float (&d)[64], uint32_t a0, uint32_t a1, uint32_t a2, uint32_t a3, uint32_t blo){
  asm volatile("{\n.reg .b64 db;\nmov.b64 db, {%68,8};\nwgmma.mma_async.sync.aligned.m64n128k16.f32.bf16.bf16 {%0, %1, %2, %3, %4, %5, %6, %7, %8, %9, %10, %11, %12, %13, %14, %15, %16, %17, %18, %19, %20, %21, %22, %23, %24, %25, %26, %27, %28, %29, %30, %31, %32, %33, %34, %35, %36, %37, %38, %39, %40, %41, %42, %43, %44, %45, %46, %47, %48, %49, %50, %51, %52, %53, %54, %55, %56, %57, %58, %59, %60, %61, %62, %63}, {%64,%65,%66,%67}, db, 1, 1, 1, 0;\n}\n"
    : "+f"(d[0]), "+f"(d[1]), "+f"(d[2]), "+f"(d[3]), "+f"(d[4]), "+f"(d[5]), "+f"(d[6]), "+f"(d[7]), "+f"(d[8]), "+f"(d[9]), "+f"(d[10]), "+f"(d[11]), "+f"(d[12]), "+f"(d[13]), "+f"(d[14]), "+f"(d[15]), "+f"(d[16]), "+f"(d[17]), "+f"(d[18]), "+f"(d[19]), "+f"(d[20]), "+f"(d[21]), "+f"(d[22]), "+f"(d[23]), "+f"(d[24]), "+f"(d[25]), "+f"(d[26]), "+f"(d[27]), "+f"(d[28]), "+f"(d[29]), "+f"(d[30]), "+f"(d[31]), "+f"(d[32]), "+f"(d[33]), "+f"(d[34]), "+f"(d[35]), "+f"(d[36]), "+f"(d[37]), "+f"(d[38]), "+f"(d[39]), "+f"(d[40]), "+f"(d[41]), "+f"(d[42]), "+f"(d[43]), "+f"(d[44]), "+f"(d[45]), "+f"(d[46]), "+f"(d[47]), "+f"(d[48]), "+f"(d[49]), "+f"(d[50]), "+f"(d[51]), "+f"(d[52]), "+f"(d[53]), "+f"(d[54]), "+f"(d[55]), "+f"(d[56]), "+f"(d[57]), "+f"(d[58]), "+f"(d[59]), "+f"(d[60]), "+f"(d[61]), "+f"(d[62]), "+f"(d[63])
    : "r"(a0), "r"(a1), "r"(a2), "r"(a3), "r"(blo));
}

struct CvCtx {
  uint32_t koff, zero, so[3];
  int srcA, srcB;
  bool wrapA, s3, kodd;
};
struct CvPipe { uint32_t Ap, Ep, keep, send; };
template <int LO> __device__ __forceinline__ void cv_copy(float (&acc)[64]) {
#pragma unroll
  for (int i = LO; i < 64; i++) { float t; asm volatile("mov.b32 %0, %1;" : "=f"(t) : "f"(acc[i]) : "memory"); acc[i] = t; }
}
template <int G> __device__ __forceinline__ void cv_raw(uint32_t (&A)[4][4], uint32_t kaddr) {
#pragma unroll
  for (int i = 0; i < 4; i++) {
    const uint32_t a = kaddr + (4 * G + i) * 128;
    A[i][0] = lds32(a); A[i][1] = lds32(a + 4); A[i][3] = lds32(a + 8);
  }
}
__device__ __forceinline__ void cv_form(uint32_t (&A)[4][4], uint32_t sel) {
#pragma unroll
  for (int i = 0; i < 4; i++) {
    asm volatile("prmt.b32 %0, %0, %1, %2;" : "+r"(A[i][0]) : "r"(A[i][1]), "r"(sel));
    asm volatile("prmt.b32 %0, %1, %2, %3;" : "=r"(A[i][2]) : "r"(A[i][1]), "r"(A[i][3]), "r"(sel));
  }
}
#define CVV 2
template <int G> __device__ __forceinline__ void cv_step(float (&acc)[64], uint32_t (&A)[4][4], CvPipe& s, const CvCtx& c, uint32_t cb, uint32_t stg) {
  constexpr int JA = G - 1, JB = G - 2, NH = CVV == 1 ? 4 : (CVV == 3 ? 2 : 1);
  const uint32_t db0 = desc_lo(cb + CV_U + 192, CV_PL);
  uint32_t B[4][4];
  uint32_t ra[2], rb;
  if constexpr (G < 8) {
    wgmma_fence();
#pragma unroll
    for (int i = 0; i < NH; i++) wgmma_rs_hi<128 - 16 * (G & 7)>(acc, A[i][0], A[i][1], A[i][2], A[i][3], db0 - 4 * i);
    wgmma_commit();
    __syncwarp();
  }
  if constexpr (JA >= 0 && JA < 8) {
    const uint32_t p0 = pack_bf16(acc[8 * JA + 1], acc[8 * JA + 3]), p1 = pack_bf16(acc[8 * JA + 5], acc[8 * JA + 7]);
    ra[0] = __shfl_sync(0xffffffffu, c.wrapA ? s.Ap : p0, c.srcA);
    ra[1] = __shfl_sync(0xffffffffu, c.wrapA ? p0 : p1, c.srcA);
    s.Ap = p1;
  }
  if constexpr (JB >= 0) rb = __shfl_sync(0xffffffffu, s.send, c.srcB);
  if constexpr (G < 7) cv_raw<G + 1>(B, cb + c.koff);
  uint32_t z = 0;
  if constexpr (G < 8 && NH < 4) {
    __syncwarp();
    wgmma_fence();
#pragma unroll
    for (int i = NH; i < 4; i++) wgmma_rs_hi<128 - 16 * (G & 7)>(acc, A[i][0], A[i][1], A[i][2], A[i][3], db0 - 4 * i);
    wgmma_commit();
    asm volatile("mov.u32 %0, %%clock;" : "=r"(z)::"memory");
    z &= c.zero;
  }
  if constexpr (G < 7) cv_form(B, 0x5432u | z);
  if constexpr (JB >= 0) sts32(stg + ((c.so[JB / 3] >> (10 * (JB % 3))) & 0xffc), hadd2(rb | z, s.keep));
  if constexpr (JA >= 0 && JA < 8) {
    const uint32_t sh = 16 | z, mk = 0xffff0000u | z;
    const uint32_t ev = pack_bf16(acc[8 * JA] + __uint_as_float(ra[0] << sh), acc[8 * JA + 2] + __uint_as_float(ra[0] & mk));
    const uint32_t od = pack_bf16(acc[8 * JA + 4] + __uint_as_float(ra[1] << sh), acc[8 * JA + 6] + __uint_as_float(ra[1] & mk));
    s.send = c.kodd ? ev : (c.s3 ? s.Ep : od);
    s.keep = c.kodd ? od : ev;
    s.Ep = od;
  }
  if constexpr (G < 8) { __syncwarp(); wgmma_wait<0>(); cv_copy<8 * (G & 7)>(acc); }
  if constexpr (G < 9) cv_step<G + 1>(acc, B, s, c, cb, stg);
}
__device__ __forceinline__ uint32_t cv_stage(int slot) { return sb + (slot < 4 ? 40960 + slot * 4096 : CV_OFF + CV_K); }
__device__ __forceinline__ void cv_setup(CvCtx& c) {
  const int tid = tid_opaque() & 127, w = tid >> 5, lane = tid & 31, r = lane >> 2, q = lane & 3;
  const int i0 = (r >> 1) & 1, i1 = r >> 2;
  c.koff = CV_K - 32 + 4 * (8 * (r >> 1) + 2 * w + (r & 1) + 2 * q);
  c.srcA = i0 ? lane - 8 : lane + 8 - q + ((q + 3) & 3);
  c.wrapA = i0 && q == 3;
  c.srcB = i1 == 0 ? (lane - q + 16 + ((q + 3) & 3)) : (lane - q - 16 + ((q + 1) & 3));
  c.s3 = (i1 == 1 && q == 3); c.kodd = (i1 == 1 && q < 3);
  c.zero = lds32(sb + EP_OFF + 24);
#pragma unroll
  for (int i = 0; i < 3; i++) c.so[i] = lds32(sb + SO_OFF + 512 * i + 4 * tid);
}
__device__ __forceinline__ void cv_table() {
  const int tid = tid_opaque() & 127, r = (tid & 31) >> 2, q = tid & 3;
  int t = 16 * (2 * (r < 4 ? q : 4 + ((q + 1) & 3)) + ((r >> 1) & 1)) + 4 * (tid >> 5) + 2 * (r & 1);
#pragma unroll 1
  for (int i = 0; i < 3; i++) {
    uint32_t v = 0;
#pragma unroll 1
    for (int x = 0; x < 3; x++, t += 256) {
      const int T = t / 160, tl = t - T * 160;
      const int qq = (T >= NT1 - 1) ? (tl >> 5) : (tl / 40);
      int ck = 20 * T + ((tl - qq * ((T >= NT1 - 1) ? 32 : 40)) >> 1);
      ck ^= (ck >> 2) & 6;
      v |= (uint32_t)((ck * 4 + qq) & 1023) << (10 * x + 2);
    }
    sts32(sb + SO_OFF + 512 * i + 4 * tid, v);
  }
}
__device__ __forceinline__ void conv_channel(int slot, const CvCtx& c) {
  const uint32_t cb = sb + CV_OFF + slot * CV_B;
  float acc[64];
  CvPipe s;
  s.Ap = s.Ep = 0u;
  uint32_t A[4][4];
#pragma unroll
  for (int i = 0; i < 64; i++) acc[i] = 0.f;
  if (slot == 4) mbar_wait(bars + 8 * B_CVDONE);
  mbar_wait(bars + 8 * (B_CVFULL + slot));
  cv_raw<0>(A, cb + c.koff);
  {
    const uint32_t w0 = lds32(cb + CV_K);
    const uint32_t wp = __byte_perm(pack_bf16(bf_lo(w0) + __uint_as_float(lds32(sb + EP_OFF + 4 * slot)), 0.f), w0, 0x7610);
    if (c.koff == CV_K) A[0][0] = wp;
    if (c.koff == CV_K - 4) A[0][1] = wp;
    if (c.koff == CV_K - 8) A[0][3] = wp;
  }
  cv_form(A, 0x5432u);
  cv_copy<0>(acc);
  cv_step<0>(acc, A, s, c, cb, cv_stage(slot));
  fence_async_smem();
  mbar_arrive(bars + 8 * (B_CVDONE + slot));
}

__device__ __forceinline__ void kv_issue(const Params& p, int c, int m2, int dg) {
  const uint32_t fb = bars + 8 * (B_KV + c);
  mbar_expect_tx(fb, KV_PIECE);
  tma3(sb + KS_OFF + c * KV_PIECE, &p.mK, 160 * dg + 32 * c, 64 * m2 - 3, 0, fb);
  tma3(sb + KS_OFF + c * KV_PIECE + 4864, &p.mV, 160 * dg + 32 * c, 64 * m2 - 1, 0, fb);
}
__device__ __forceinline__ void kv_tile(int m, int c, int y, uint32_t (&o)[4][4]) {
  const int lane = tid_opaque() & 31, tg = lane & 3, pr = 8 * (y ^ (tg >> 1)) + (lane >> 2);
  const uint32_t pb = sb + KS_OFF + c * KV_PIECE + 4 * pr;
  const uint32_t ka = pb + tg * 1216, va = pb + 4864 + tg * 1088 + 64;
  const uint32_t kh = (m == 0 && tg > 0) ? ka - 192 : ka;
  uint32_t kk[19], u[16];
  const float4 t = lds128f(sb + TAP_OFF + 256 * c + 16 * pr);
#pragma unroll
  for (int i = 0; i < 19; i++) { kk[i] = lds32((i < 3 ? kh : ka) + i * 64); if (i >= 3) u[i - 3] = lds32(va + (i - 3) * 64); }
  const uint32_t dst = sb + KS_OFF + c * KV_PIECE + pr * 64 + tg * 16;
  if (y) {
    __syncwarp();
#pragma unroll
    for (int x = 0; x < 4; x++) sts128((dst ^ 512) + x * 1024, make_uint4(o[x][0], o[x][1], o[x][2], o[x][3]));
  }
  const uint32_t w0 = __byte_perm(__float_as_uint(t.x), __float_as_uint(t.z), 0x5410), w1 = __byte_perm(__float_as_uint(t.x), __float_as_uint(t.z), 0x7632);
  const uint32_t w2 = __byte_perm(__float_as_uint(t.y), __float_as_uint(t.w), 0x5410), w3 = __byte_perm(__float_as_uint(t.y), __float_as_uint(t.w), 0x7632);
#pragma unroll
  for (int i = 0; i < 16; i++) {
    uint32_t a = hmul2(kk[i], w3);
    a = hadd2(a, hmul2(kk[i + 1], w2)); a = hadd2(a, hmul2(kk[i + 2], w1)); a = hadd2(a, hmul2(kk[i + 3], w0));
    u[i] = hmul2(a, u[i]);
  }
#pragma unroll
  for (int x = 0; x < 4; x++) {
#pragma unroll
    for (int qq = 0; qq < 4; qq++) o[x][qq] = __byte_perm(u[15 - 4 * qq - (x & 2)], u[14 - 4 * qq - (x & 2)], (x & 1) ? 0x7632 : 0x5410);
    if (y) sts128(dst + x * 1024, make_uint4(o[x][0], o[x][1], o[x][2], o[x][3]));
  }
}
__device__ __forceinline__ void ln_finish(float s1, float s2, float& mean, float& rstd) {
  mean = s1 * (1.f / 640.f);
  const float v = fmaxf(fmaf(-mean, mean, s2 * (1.f / 640.f)), 0.f) + 1e-5f;
  asm("rsqrt.approx.ftz.f32 %0, %1;" : "=f"(rstd) : "f"(v));
}
__device__ __forceinline__ void stat_table(int T1, unsigned want, int l, int g, const uint4* x0, const uint4* x1, float (&xa)[2], float (&xb)[2]) {
  const int n = 32 * g + (tid_opaque() & 31);
  const uint4* rp = &g_stats[8 * l * SEQ + min(160 * T1 + n, SEQ - 1)];
  float a[4], b[4];
  uint32_t it = 0;
  while (true) {
    bool ok = true;
#pragma unroll
    for (int i = 0; i < 4; i++) ok &= (rec_ld(rp + SEQ * i, a[i], b[i]) == want);
    ok &= rec_ld(x0, xa[0], xb[0]) == want;
    ok &= rec_ld(x1, xa[1], xb[1]) == want;
    if (__all_sync(0xffffffffu, ok)) break;
    trap_if(++it > SPIN_LIMIT);
  }
  float m, rs;
  ln_finish((a[0] + a[1]) + (a[2] + a[3]), (b[0] + b[1]) + (b[2] + b[3]), m, rs);
  sts32(sb + STAB_OFF + ((n >> 1) & 3) * 160 + (n >> 3) * 8 + (n & 1) * 4, __float_as_uint(rs));
  const uint32_t hi = pack_bf16(-m, -m);
  const float lo = -m - bf_lo(hi);
  sts128(sb + (l ? MX1_OFF : MX0_OFF) + n * 16, make_uint4(hi, pack_bf16(lo, lo), 0u, 0u));
  fence_async_smem();
}
__device__ __forceinline__ void stats_reduce(float (&a)[2], float (&b)[2], float (&mean)[2], float (&rstd)[2]) {
#pragma unroll
  for (int o = 1; o < 4; o <<= 1)
#pragma unroll
    for (int h = 0; h < 2; h++) { a[h] += __shfl_xor_sync(0xffffffffu, a[h], o); b[h] += __shfl_xor_sync(0xffffffffu, b[h], o); }
#pragma unroll
  for (int h = 0; h < 2; h++) ln_finish(a[h], b[h], mean[h], rstd[h]);
}

template <bool FIRST>
__device__ __forceinline__ void stats_publish(int which, int n0, int dg, unsigned tag, const float (&acc)[80]) {
  const int q = tid_opaque() & 3, h = q & 1;
  float s1[2] = {0.f, 0.f}, s2[2] = {0.f, 0.f}, t1[2] = {0.f, 0.f}, t2[2] = {0.f, 0.f};
#pragma unroll
  for (int j = 0; j < 20; j++)
#pragma unroll
    for (int y = 0; y < 2; y++) {
      const float a = acc[4 * j + 2 * y], b = acc[4 * j + 2 * y + 1];
      s1[y] += a; t1[y] += b; s2[y] = fmaf(a, a, s2[y]); t2[y] = fmaf(b, b, t2[y]);
    }
#pragma unroll
  for (int y = 0; y < 2; y++) { s1[y] += t1[y]; s2[y] += t2[y]; }
  float a = (h ? s1[1] : s1[0]) + __shfl_xor_sync(0xffffffffu, h ? s1[0] : s1[1], 1);
  float b = (h ? s2[1] : s2[0]) + __shfl_xor_sync(0xffffffffu, h ? s2[0] : s2[1], 1);
  a += __shfl_xor_sync(0xffffffffu, a, 2);
  b += __shfl_xor_sync(0xffffffffu, b, 2);
  if (FIRST) {
    rec_st(&g_stats[((q >> 1) * 4 + dg) * SEQ + n0 + 8 * h], a, b, q < 2 ? tag : tag - 1);
    rec_st(&g_stats[((q >> 1) * 4 + 8 + dg) * SEQ + n0 + 8 * h], a, b, tag - 1);
  } else if (q < 2) rec_st(&g_stats[(which * 4 + dg) * SEQ + n0 + 8 * h], a, b, tag);
}
__device__ __forceinline__ void stats_get(int which, int n0, unsigned tag, float (&mean)[2], float (&rstd)[2]) {
  const uint4* p0 = &g_stats[(which * 4 + (tid_opaque() & 3)) * SEQ + n0];
  float a[2], b[2];
  uint32_t it = 0;
  while (true) {
    const unsigned t0 = rec_ld(p0, a[0], b[0]), t1 = rec_ld(p0 + 8, a[1], b[1]);
    if (__all_sync(0xffffffffu, t0 == tag && t1 == tag)) break;
    trap_if(++it > SPIN_LIMIT);
  }
  stats_reduce(a, b, mean, rstd);
}
__device__ __forceinline__ void x0_load(float (&acc)[80]) {
  const int t = tid_opaque() & 127;
  const uint32_t xa = sb + XT_OFF + (16 * (t >> 5) + ((t & 31) >> 2)) * 320 + 8 * (t & 3);
  mbar_wait(bars + 8 * B_XT);
#pragma unroll
  for (int h = 0; h < 2; h++)
#pragma unroll
    for (int J = 0; J < 10; J++) {
      const float2 v = lds64f(xa + h * 2560 + 32 * J);
      const uint32_t x = __float_as_uint(v.x), y = __float_as_uint(v.y);
      acc[8 * J + 2 * h] = bf_lo(x); acc[8 * J + 2 * h + 1] = bf_hi(x);
      acc[8 * J + 4 + 2 * h] = bf_lo(y); acc[8 * J + 4 + 2 * h + 1] = bf_hi(y);
    }
}

template <bool FROM_X0>
__device__ __forceinline__ void dskip_init(float (&acc)[80], const float (&mean)[2], const float (&rstd)[2]) {
  const int t = tid_opaque() & 127;
  const uint32_t xa = sb + XT_OFF + (16 * (t >> 5) + ((t & 31) >> 2)) * 320 + 8 * (t & 3), da = sb + DTAB_OFF + 8 * (t & 3);
  float2 dw[10], xv[10][2];
#pragma unroll
  for (int J = 0; J < 2; J++) { dw[J] = lds64f(da + 32 * J); if (FROM_X0) { xv[J][0] = lds64f(xa + 32 * J); xv[J][1] = lds64f(xa + 2560 + 32 * J); } }
#pragma unroll
  for (int J = 0; J < 10; J++) {
    if (J + 2 < 10) { dw[J + 2] = lds64f(da + 32 * (J + 2)); if (FROM_X0) { xv[J + 2][0] = lds64f(xa + 32 * (J + 2)); xv[J + 2][1] = lds64f(xa + 2560 + 32 * (J + 2)); } }
#pragma unroll
    for (int x = 0; x < 8; x++) {
      const int h = (x >> 1) & 1;
      const uint32_t dwd = __float_as_uint(x < 4 ? dw[J].x : dw[J].y);
      const float tt = fmaf(rstd[h], (x & 1) ? bf_hi(dwd) : bf_lo(dwd), 1.f);
      float a = acc[8 * J + x];
      if (FROM_X0) { const uint32_t xw = __float_as_uint(x < 4 ? xv[J][h].x : xv[J][h].y); a = (x & 1) ? bf_hi(xw) : bf_lo(xw); }
      acc[8 * J + x] = FROM_X0 ? (a - mean[h]) * tt : fmaf(a, tt, -mean[h] * tt);
    }
  }
}

__global__ void __launch_bounds__(512, 1) fused_kernel(const __grid_constant__ Params p) {
  extern __shared__ __align__(1024) uint8_t smem_raw[];
  const int tid = threadIdx.x, lane = tid & 31;
  const int wid = __shfl_sync(0xffffffffu, tid >> 5, 0), wg = wid >> 2;
  unsigned smid; asm volatile("mov.u32 %0, %%smid;" : "=r"(smid));
  const int role = p.role[min(smid, 131u)];
  if (wid == 12) {
    const bool el = elect_one();
    if (el) {
      asm volatile("prefetch.tensormap [%0];" ::"l"(&p.mB) : "memory");
      asm volatile("prefetch.tensormap [%0];" ::"l"((role & 15) == NT1 - 1 ? &p.mXl : &p.mX) : "memory");
#pragma unroll
      for (int k = 0; k < S1; k++) mbar_init(bars + 8 * (B_G1FULL + k), 1);
#pragma unroll
      for (int k = 0; k < 6; k++) mbar_init(bars + 8 * (B_XT + k), 1);
      asm volatile("fence.mbarrier_init.release.cluster;" ::: "memory");
    }
    if (role >= 0) {
      __syncwarp();
      asm volatile("bar.arrive 5, 288;" ::: "memory");
      const Role R = unpack_role(role);
      if (elect_one()) {
        TS(45);
#pragma unroll 1
        for (int k = 0; k < S1; k++) {
          const uint32_t fb = bars + 8 * (B_G1FULL + k);
          mbar_expect_tx(fb, G1_STAGE);
          tma4(sb + k * G1_STAGE + G1_XOFF, R.last ? &p.mXl : &p.mX, 64 * k, 0, 0, R.last ? 0 : 80 * R.T1, fb);
          tma5(sb + k * G1_STAGE, &p.mB, 64 * k, 0, 0, 4 * R.side, 2 * R.GP, fb);
          if (PFD) asm volatile("prefetch.tensormap [%0];" ::"l"(&p.mK + k) : "memory");
        }
        if (R.has2) {
          mbar_expect_tx(bars + 8 * B_XT, 20480);
#pragma unroll 1
          for (int h = 0; h < 2; h++) {
            const int ng = 8 * R.m2 + 4 * h, T = ng / 20;
            tma4(sb + XT_OFF + h * 10240, T == NT1 - 1 ? &p.mXtl : &p.mXt, 160 * R.dg, 0, 0, T == NT1 - 1 ? ng - 240 : ng + 60 * T, bars + 8 * B_XT);
          }
#pragma unroll 1
          for (int c = 0; c < KV0; c++) kv_issue(p, c, R.m2, R.dg);
        }
        TS(44);
      }
      __syncwarp();
      bar_sync(6, 64);
    }
  }
  trap_if(smid >= 132 || smem_u32(smem_raw) != sb);
  if (role < 0) {
    if (wid == 0) {
      const unsigned tag = ld_rlx(g_epoch);
      uint32_t it = 0;
      while (!__all_sync(0xffffffffu, (int)(ld_rlx(&g_hcnt[(lane & 7) * 32]) - 40 * tag) >= 0)) { __nanosleep(500); trap_if(++it > SPIN_LIMIT); }
    }
    return;
  }
  float mean0[2] = {0.f, 0.f}, rstd0[2] = {0.f, 0.f};
  if (wg == 2 || wid == 14) {
    ROLE(role)
    const int c = wid == 14 ? 4 : wid - 8;
    const unsigned tag = ld_rlx(g_epoch);
    if (has2) {
      uint2 bv[2][5];
#pragma unroll
      for (int x = 0; x < 2; x++)
#pragma unroll
        for (int i = 0; i < 5; i++) bv[x][i] = ldv64((const uint2*)((x ? p.bim : p.bre) + (cch0 + 32 * c) * DM) + lane + 32 * i);
      float sv[2];
#pragma unroll
      for (int x = 0; x < 2; x++) {
        float a = 0.f;
#pragma unroll
        for (int i = 0; i < 5; i++) a += (bf_lo(bv[x][i].x) + bf_hi(bv[x][i].x)) + (bf_lo(bv[x][i].y) + bf_hi(bv[x][i].y));
        sv[x] = a;
      }
#pragma unroll
      for (int o = 16; o > 0; o >>= 1) { sv[0] += __shfl_xor_sync(0xffffffffu, sv[0], o); sv[1] += __shfl_xor_sync(0xffffffffu, sv[1], o); }
      if (lane < 2) rec_st(&g_sB[(cch0 + 32 * c) * 2 + lane], sv[0], sv[1], tag);
      if (tid == 256) TS(47);
      __syncwarp();
      bar_sync(8, 192);
      if (wg == 2) {
        float xs[80];
        x0_load(xs);
        stats_publish<true>(0, 64 * m2 + 16 * c + (lane >> 2), dg, tag, xs);
        if (tid == 256) TS(31);
      }
      mbar_wait(bars + 8 * B_EP);
      mbar_wait(bars + 8 * (B_KV + c));
      mbar_wait(bars + 8 * (B_G1DONE + PAUSE_K - 1));
      if (tid == 448) TS(52);
      uint32_t o[4][4] = {};
#pragma unroll 1
      for (int y = 0; y < 2; y++) kv_tile(m2, c, y, o);
      fence_async_smem();
      __syncwarp();
      if (lane == 0) { mbar_arrive(bars + 8 * B_PREP); mbar_arrive(bars + 8 * (B_PD + c)); }
      if (tid == 448) TS(51);
    } else bar_sync(8, 192);
    {
      const uint4* x0 = wg == 2 ? &g_stats[(lane & 3) * SEQ + (has2 ? 64 * m2 : 0) + 16 * c + (lane >> 2)] : &g_sB[(128 * GP + 32 * side + lane) * 2];
      float xa[2], xb[2];
      stat_table(T1, tag, 0, c, x0, x0 + (wg == 2 ? 8 : 128), xa, xb);
      if (wg == 2) stats_reduce(xa, xb, mean0, rstd0);
      else {
#pragma unroll
        for (int i = 0; i < 2; i++) {
          const float ha = bf_lo(pack_bf16(xa[i], 0.f)), hb = bf_lo(pack_bf16(xb[i], 0.f));
          const float pa = __uint_as_float(pack_bf16(ha, xa[i] - ha)), pb = __uint_as_float(pack_bf16(hb, xb[i] - hb));
          sts64f(sb + CTAB_OFF + (32 * i + lane) * 24 + 16, p.swap ? pb : pa, p.swap ? pa : pb);
        }
      }
      mbar_arrive(bars + 8 * B_STAB);
      if (tid == 448) TS(26);
    }
  } else if (wid == 15) {
    ROLE(role)
    const int ch = 128 * GP + 32 * side + lane;
    uint32_t r0 = ldv16(p.lre + ch), r1 = ldv16(p.lim + ch), r2 = ldv16(p.logdt + ch);
    const uint32_t r3 = ldv16(p.lre + ch + 64), r4 = ldv16(p.lim + ch + 64), r5 = ldv16(p.logdt + ch + 64);
#pragma unroll 1
    for (int i = 0; i < 2; i++) {
      const float lr = bf_lo(r0), li = bf_lo(r1);
      const float dt = __bfloat162float(__float2bfloat16_rn(expf(bf_lo(r2))));
      const float mag = expf(dt * lr);
      float sn, cs; sincospif(dt * li * 0.31830988618379067f, &sn, &cs);
      const float ar = mag * cs, ai = mag * sn;
      const float inv = 2.f / (lr * lr + li * li);
      const uint32_t ad = sb + CTAB_OFF + (32 * i + lane) * 24;
      sts64f(ad, ar, ai);
      sts64f(ad + 8, ((ar - 1.f) * lr + ai * li) * inv, (ai * lr - (ar - 1.f) * li) * inv);
      r0 = r3; r1 = r4; r2 = r5;
    }
    if (lane == 0) TS(46);
    __syncwarp();
    bar_sync(7, 64);
    mbar_arrive(bars + 8 * B_CTAB);
  } else if (wid == 13) {
    ROLE(role)
    uint4 tv[3];
    const uint32_t e0 = ld_rlx(g_epoch);
    const uint32_t e1 = ldv16(p.ssmD + min(cch0 + 32 * lane, 639));
    const uint4 dv = ldv128((const uint4*)(p.dskip + 160 * dg) + min(lane, 19));
#pragma unroll
    for (int i = 0; i < 3; i++) tv[i] = ldv128((const uint4*)(p.shiftk + 640 * dg) + min(lane + 32 * i, 79));
    sts128(sb + DTAB_OFF + 16 * min(lane, 19), dv);
#pragma unroll
    for (int i = 0; i < 3; i++) sts128(sb + TAP_OFF + 16 * min(lane + 32 * i, 79), tv[i]);
    if (lane < 7) sts32(sb + EP_OFF + 4 * lane, lane < 5 ? e1 << 16 : (lane == 5 ? e0 : 0u));
    __syncwarp();
    bar_sync(9, 64);
    mbar_arrive(bars + 8 * B_CTAB);
    if (lane == 0) { mbar_arrive(bars + 8 * B_EP); TS(53); }
    if (has2) {
#pragma unroll 1
      for (int i = 0; i < 5; i++) {
        const int c = i == 2 ? 3 : (i == 3 ? 2 : i);
        mbar_wait(bars + 8 * (B_PD + c));
        if (lane == 0) bulk_s2g(g_kv + (dg * 32 + m2) * 20480 + c * 4096, sb + KS_OFF + c * KV_PIECE, 4096);
      }
      if (lane == 0) {
        asm volatile("cp.async.bulk.commit_group;" ::: "memory");
        asm volatile("cp.async.bulk.wait_group 0;" ::: "memory");
        mbar_arrive(bars + 8 * B_PREP2);
        fence_async_global();
      }
      __syncwarp();
      if (lane < 4) red_rel(&g_kvcnt[(dg * 4 + lane) * 32]);
      __syncwarp();
      if (lane == 0) { mbar_arrive(bars + 8 * B_PUB); TS(30); }
    }
  } else if (wid != 12) {
    if (elect_one()) {
      if (wid < 7) {
        const int b0 = wid < 4 ? 4 + 19 * wid : 85 + 21 * (wid - 4), cnt = wid < 4 ? 2 : 1;
#pragma unroll
        for (int i = 0; i < 21; i++) mbar_init(bars + 8 * (b0 + i), cnt);
      } else {
#pragma unroll
        for (int i = 0; i < 12; i++) mbar_init(bars + 8 * (B_CVDONE + i), (i == 5 || i == 6) ? 160 : 128);
        mbar_init(bars + 8 * B_CTAB, 192); mbar_init(bars + 8 * B_PREP, 5); mbar_init(bars + 8 * B_PREP2, 1);
#pragma unroll
        for (int i = 0; i < 5; i++) mbar_init(bars + 8 * (B_PD + i), 1);
      }
      asm volatile("fence.mbarrier_init.release.cluster;" ::: "memory");
    }
    __syncwarp();
    bar_sync(5, 288);
    if (wid == 2) asm volatile("bar.arrive 8, 192;\nbar.arrive 6, 64;\nbar.arrive 9, 64;\nbar.arrive 7, 64;" ::: "memory");
    if (tid == 128) TS(0);
    if (wg == 1) { cv_table(); mbar_arrive(bars + 8 * B_CTAB); }
  }

  if (wid == 12) {
    ROLE(role)
    uint32_t dst = sb;
#pragma unroll 1
    for (int k = S1; k < 10; k++) {
      const uint32_t fb = bars + 8 * (B_G1FULL + k);
      mbar_wait(bars + 8 * (B_G1DONE + k - S1));
      if (elect_one()) {
        mbar_expect_tx(fb, 20480);
        tma4(dst + G1_XOFF, last ? &p.mXl : &p.mX, 64 * k, 0, 0, last ? 0 : 80 * T1, fb);
        mbar_expect_tx(fb, 16384);
        tma5(dst, &p.mB, 64 * k, 0, 0, 4 * side, 2 * GP, fb);
        if (has2 && k - S1 + KV0 < 5) kv_issue(p, k - S1 + KV0, m2, dg);
      }
      dst += G1_STAGE; if (k == 2 * S1 - 1) dst = sb;
    }
  } else if (wid == 15 && (role >> 16)) {
    ROLE(role)
    if (TPF >= 0) {
      mbar_wait(bars + 8 * (B_KV + TPF));
      if (elect_one()) {
#pragma unroll
        for (int c = 0; c < 5; c++) l2_prefetch(p.ssmk + (cch0 + 32 * c) * SEQ, 4096);
        if (CPF) { l2_prefetch(p.cre + (160 * dg + 5 * m2) * DM, 6400); l2_prefetch(p.cim + (160 * dg + 5 * m2) * DM, 6400); }
      }
    }
    mbar_wait(bars + 8 * B_PREP2);
    if (lane < 10) sts128(sb + CV_OFF + (lane >> 1) * CV_B + CV_K - 32 + 16 * (lane & 1), make_uint4(0, 0, 0, 0));
    fence_async_smem();
    __syncwarp();
    const unsigned tag = lds32(sb + EP_OFF + 20);
    if (TAPW) mbar_wait(bars + 8 * B_PUB);
    if (elect_one()) {
#pragma unroll 1
      for (int c = 0; c < 5; c++) {
        if (c == 0) asm volatile("prefetch.tensormap [%0];" ::"l"(&p.mU) : "memory");
        mbar_expect_tx(bars + 8 * (B_CVFULL + c), 4096 + 2 * CV_PL);
        if (c < TAPN) bulk_g2s(sb + CV_OFF + c * CV_B + CV_K, p.ssmk + (cch0 + 32 * c) * SEQ, 4096, bars + 8 * (B_CVFULL + c));
      }
    }
    mbar_wait(bars + 8 * B_PUB);
    cnt_poll(&g_kvcnt[(dg * 4 + (m2 >> 3)) * 32], 32 * tag);
    fence_async_global();
    if (elect_one()) {
      TS(28);
#pragma unroll
      for (int c = 0; c < 5; c++) {
        tma5(sb + CV_OFF + c * CV_B + CV_U, &p.mU, 0, -3, 2 * c, 16 * (m2 & 1) + (m2 >> 1), dg, bars + 8 * (B_CVFULL + c));
        if (c >= TAPN) bulk_g2s(sb + CV_OFF + c * CV_B + CV_K, p.ssmk + (cch0 + 32 * c) * SEQ, 4096, bars + 8 * (B_CVFULL + c));
      }
#pragma unroll
      for (int i = 0; i < 3; i++) asm volatile("prefetch.tensormap [%0];" ::"l"(&p.mCre + i) : "memory");
      TS(54);
    }
    __syncwarp();
  }
  {
    const int w = wid & 3;
    if (wg == 2 && !(role >> 16)) {
      float xa[2], xb[2];
      mbar_wait(bars + 8 * (B_G1FULL + 11));
      stat_table(role & 15, lds32(sb + EP_OFF + 20), 1, w, g_stats, g_stats, xa, xb);
      mbar_arrive(bars + 8 * (B_STAB + 1));
    }
#pragma unroll 1
    for (int l = 0; l < 2; l++) {
      if (wg < 2) {
        float acc[80];
#pragma unroll
        for (int i = 0; i < 80; i++) acc[i] = 0.f;
        ROLE(role)
        const int tid = tid_opaque(), r = (tid & 31) >> 2, q = tid & 3;
        const int ch = 128 * GP + 64 * wg + 32 * side + 8 * w + r;
        const uint32_t ca = sb + CTAB_OFF + (32 * wg + 8 * w + r) * 24;
        float2 lam = make_float2(0.f, 0.f), p8 = lam, p16 = lam, pL = lam, p2L = lam;
        fence_regs(acc);
        {
          const uint32_t alo0 = (l == 0 ? desc_lo(sb, 16) : desc_lo(sb + G2_WOFF, 16)) + wg * 512;
          const uint32_t blo0 = l == 0 ? desc_lo(sb + G1_XOFF, 16) : desc_lo(sb + X1_OFF, 128);
          const uint32_t bhi = l == 0 ? desc_hi(1024, 1) : desc_hi(1024, 0), xstep = l == 0 ? 2 : 16;
          const uint32_t astep = l == 0 ? G1_STAGE >> 4 : 1024, bstep = l == 0 ? G1_STAGE >> 4 : 1280, aend = alo0 + (S1 + l) * astep;
          uint32_t alo = alo0, blo = blo0;
          uint32_t fb = bars + 8 * (B_G1FULL + 10 * l);
          mbar_wait(fb);
          if (tid == 0) TS(1 + 8 * l);
#pragma unroll 1
          for (int k = 0; k < 10; k++) {
            uint32_t ok; const uint32_t nb = k < 9 ? fb + 8 : fb;
            wgmma_fence();
#pragma unroll
            for (int kk = 0; kk < 4; kk++) {
              wgmma_n160<0>(acc, alo + kk * 2, desc_hi(1024, 1), blo + kk * xstep, bhi);
              if (kk == 0) ok = mbar_test(nb);
              if (kk == STG_KK && k == 9 && tid == 0) mbar_arrive(bars + 8 * (B_STG + l));
            }
            wgmma_commit();
            alo += astep; blo += bstep;
            if (blo == desc_lo(sb + G_OFF, 128)) blo = desc_lo(sb, 128);
            if (alo == aend) { alo = alo0; blo = blo0; }
            wgmma_wait<1>();
            if (k > 0 && (tid & 127) == 0) mbar_arrive(fb + 8 * (B_G1DONE - B_G1FULL - 1));
            if (!ok) mbar_wait(nb);
            if (k == (l ? MK1 : MK0)) {
              mbar_wait(bars + 8 * (B_STAB + l));
              const float2 sB = lds64f(ca + 16);
              uint32_t a0 = q < 2 ? __float_as_uint(sB.x) : 0u, a1 = q < 2 ? __float_as_uint(sB.y) : 0u, a2 = 0u, a3 = 0u;
              asm volatile("" : "+r"(a0), "+r"(a1), "+r"(a2), "+r"(a3)::"memory");
              wgmma_fence();
              wgmma_rs_n160(acc, a0, a1, a2, a3, l ? desc_lo(sb + MX1_OFF, 0) : desc_lo(sb + MX0_OFF, 0));
              wgmma_commit();
            }
            if (wg == 1 && k == (l ? 8 - STG_D : 9 - STG0)) mbar_wait(bars + 8 * (B_STG + l));
            if (k == 3) {
              mbar_wait(bars + 8 * B_CTAB);
              lam = lds64f(ca);
              if (l == 0 && q < 2) rec_st(&g_E[(q * NT1 + T1) * DM + ch], 0.f, 0.f, lds32(sb + EP_OFF + 20) - 1);
              if (p.swap) lam.y = -lam.y;
              const float2 p2 = cmul(lam, lam), p4 = cmul(p2, p2);
              p8 = cmul(p4, p4); p16 = cmul(p8, p8);
              pL = cmul(p16, p16);
              if (!last) pL = cmul(pL, p8);
              p2L = cmul(pL, pL);
            }
            if (k == PAUSE_K && l == 0 && has2) mbar_wait(bars + 8 * B_PREP);
            fb += 8;
          }
        }
        const unsigned tag = lds32(sb + EP_OFF + 20);
        wgmma_wait<0>();
        fence_regs(acc);
        if ((tid & 127) == 0) { mbar_arrive(bars + 8 * (B_G1DONE + 10 * l + 9)); TS(wg ? 17 + l : 2 + 8 * l); }
        float2 ec[3];
#pragma unroll
        for (int jj = 0; jj < 4; jj++)
#pragma unroll
          for (int y = 0; y < 3; y++) {
            if (y == 2 && (jj & 1)) continue;
            const int j = y == 2 ? 16 + jj : 8 * y + 2 * jj;
            const float4 st = lds128f(sb + STAB_OFF + q * 160 + j * 8);
            const float rs[4] = {st.x, st.y, st.z, st.w};
#pragma unroll
            for (int x = 0; x < 4; x++) {
              const int i = 4 * j + 4 * (x >> 1) + (x & 1);
              acc[i] *= rs[x]; acc[i + 2] *= rs[x];
              ec[y] = (jj == 0 && x == 0) ? make_float2(acc[i], acc[i + 2]) : cfma(lam, ec[y], make_float2(acc[i], acc[i + 2]));
            }
          }
        float2 e = cfma(p16, ec[0], ec[1]);
        if (!last) e = cfma(p8, e, ec[2]);
        {
          float2 v = make_float2(__shfl_up_sync(0xffffffffu, e.x, 1, 4), __shfl_up_sync(0xffffffffu, e.y, 1, 4));
          if (q >= 1) e = cfma(pL, v, e);
          v = make_float2(__shfl_up_sync(0xffffffffu, e.x, 2, 4), __shfl_up_sync(0xffffffffu, e.y, 2, 4));
          if (q >= 2) e = cfma(p2L, v, e);
        }
        if (!last && q == 3) rec_st(&g_E[(l * NT1 + T1) * DM + ch], e.x, e.y, tag);
        if (tid == 0) TS(3 + 8 * l);
        float2 ex = make_float2(__shfl_up_sync(0xffffffffu, e.x, 1, 4), __shfl_up_sync(0xffffffffu, e.y, 1, 4));
        if (q == 0) ex = make_float2(0.f, 0.f);
        const float2 coef = lds64f(ca + 8), lamc = make_float2(lam.x, p.swap ? lam.y : -lam.y);
        float m00 = coef.x, m01 = -coef.y, m10 = -coef.y, m11 = -coef.x;
        if (p.swap) { m00 = -coef.y; m01 = coef.x; m10 = -coef.x; m11 = -coef.y; }
        float2 pLq, p160q, p640;
        {
          const float2 p80 = last ? cmul(p2L, p16) : p2L, p160 = cmul(p80, p80), p320 = cmul(p160, p160), one = make_float2(1.f, 0.f);
          p640 = cmul(p320, p320);
          pLq = cmul((q & 1) ? pL : one, (q & 2) ? p2L : one);
          p160q = cmul((q & 1) ? p160 : one, (q & 2) ? p320 : one);
        }
        float2 c, ev[3];
        unsigned tg[3];
        const uint4* ep = &g_E[(l * NT1 + T1 - 1 - q) * DM + ch];
#pragma unroll
        for (int j = 0; j < 20; j++) {
          if (j == CPOLL) {
#pragma unroll
            for (int i = 0; i < 3; i++) {
              ev[i] = make_float2(0.f, 0.f); tg[i] = tag;
              if (T1 - 1 - q - 4 * i >= 0) tg[i] = rec_ld(ep - 4 * i * DM, ev[i].x, ev[i].y);
            }
          }
#pragma unroll
          for (int x = 0; x < 2; x++) {
            const float b0 = acc[4 * j + x], b1 = acc[4 * j + 2 + x];
            acc[4 * j + x] = fmaf(b0, m00, b1 * m01);
            acc[4 * j + 2 + x] = fmaf(b0, m10, b1 * m11);
          }
          if (j == CPOLL - 1 || j == 19) asm volatile("" : "+f"(acc[4 * j]), "+f"(acc[4 * j + 1]), "+f"(acc[4 * j + 2]), "+f"(acc[4 * j + 3])::"memory");
        }
        {
          uint32_t it = 0;
          while (__any_sync(0xffffffffu, tg[0] != tag || tg[1] != tag || tg[2] != tag)) {
#pragma unroll
            for (int i = 0; i < 3; i++)
              if (tg[i] != tag) tg[i] = rec_ld(ep - 4 * i * DM, ev[i].x, ev[i].y);
            trap_if(++it > SPIN_LIMIT);
          }
          c = cfma(p640, cfma(p640, ev[2], ev[1]), ev[0]);
          c = cmul(c, p160q);
          c.x += __shfl_xor_sync(0xffffffffu, c.x, 1); c.y += __shfl_xor_sync(0xffffffffu, c.y, 1);
          c.x += __shfl_xor_sync(0xffffffffu, c.x, 2); c.y += __shfl_xor_sync(0xffffffffu, c.y, 2);
        }
        if (tid == 0) TS(4 + 8 * l);
        if (wg == 1 && l >= HOLD0) mbar_wait(bars + 8 * (B_REL + l));
        const uint32_t c0 = (uint32_t)clock();
        c = cfma(pLq, c, ex);
        float2 hh = make_float2(fmaf(c.x, m00, c.y * m01), fmaf(c.x, m10, c.y * m11));
        uint8_t* hb = g_h + (size_t)l * (32 * 20 * 8192) + (10 * wg + 2 * GP) * 8192 + (4 * side + w) * 1024 + (tid_opaque() & 31) * 4;
#pragma unroll
        for (int j4 = 0; j4 < 5; j4++) {
          if (PACE && j4 > 0 && wg == 1 && l == 1) { while (__any_sync(0xffffffffu, (uint32_t)clock() - c0 < PACE * j4)) {} }
          const int ng = 20 * T1 + 4 * j4;
          uint8_t* hp = hb + (size_t)(ng >> 3) * 163840 + (ng & 7) * 128;
#pragma unroll
          for (int jj = 0; jj < 4; jj++) {
            const int j = 4 * j4 + jj;
            const float2 h0 = cfma(lamc, hh, make_float2(acc[4 * j + 0], acc[4 * j + 2]));
            hh = cfma(lamc, h0, make_float2(acc[4 * j + 1], acc[4 * j + 3]));
            if (j4 < 4 || !last) {
              *(uint32_t*)(hp + jj * 128) = pack_bf16(h0.x, hh.x);
              *(uint32_t*)(hp + jj * 128 + 8192) = pack_bf16(h0.y, hh.y);
            }
          }
        }
        mbar_arrive(bars + 8 * (B_HST + 2 * l + wg));
        if (tid == 0) TS(5 + 8 * l);
        if (tid == 128) TS(l ? 25 : 19);
        if (!REL3 && l == 0 && wid == 4) {
          mbar_wait(bars + 8 * B_HST);
          mbar_wait(bars + 8 * (B_HST + 1));
          if ((tid & 31) < 8) h_release((tid >> 2) & 1, T1, tid & 3);
          __syncwarp();
          if (tid == 128) { mbar_arrive(bars + 8 * B_REL); TS(6); }
        }
      }
      if (l == 0) {
        ROLE(role)
        if (has2) {
          CvCtx cc;
          mbar_wait(bars + 8 * B_CTAB);
          cv_setup(cc);
          mbar_wait(bars + 8 * (B_G1DONE + 9));
#pragma unroll 1
          for (int c = (wg + 2) & 3; c < 5; c += 4) conv_channel(c, cc);
          if ((tid & 127) == 0) TS(wg == 2 ? 32 : (wg == 3 ? 50 : 7 + wg));
        }
      }
      if (wg >= 2) break;
    }
    if (wg == 3) {
    ROLE(role)
    const int pw = wid & 3, gpc = 2 * min(m2 >> 3, 3) + (dg >> 1);
    mbar_wait(bars + 8 * B_EP);
    const unsigned tag = lds32(sb + EP_OFF + 20);
    if (pw == 0) {
      if (elect_one()) {
#pragma unroll 1
        for (int l = 0; l < 2; l++) {
          uint32_t dst = sb;
          if (l == 1) {
            dst = sb + G2_WOFF;
#pragma unroll 1
            for (int k = 0; k < 10; k++) {
              mbar_wait(k > 4 ? bars + 8 * (B_G1DONE + 5 + k) : (has2 ? bars + 8 * (B_G2DONE + 14 + min(k, 3)) : bars + 8 * (B_G1DONE + 9)));
              mbar_expect_tx(bars + 8 * (B_G1FULL + 10 + k), 16384);
              tma5(dst, &p.mB, 64 * k, 0, 0, 4 * side, 2 * GP, bars + 8 * (B_G1FULL + 10 + k));
              dst += 16384; if (k == 4) dst = sb + G2_WOFF;
            }
          }
          if (has2) {
            const uint32_t fb2 = bars + 8 * (B_G2FULL + 20 * l), wb2 = bars + 8 * (B_G2DONE + 20 * l - S2);
            dst = sb + G2_WOFF + (WTAIL ? 4 * l * G2_WB : 0);
            int kc = 0;
#pragma unroll 1
            for (int k = 0; k < 20; k++) {
              mbar_wait(k >= S2 ? wb2 + 8 * k : bars + 8 * (l ? B_G1DONE + (WTAIL ? (k < 3 ? 15 + k : 13 + k) : 19) : (k == 5 ? B_XFREE : (k == 6 ? B_SFREE : B_REL))));
              mbar_expect_tx(fb2 + 8 * k, G2_WB);
              tma5(dst, &p.mCre + (k & 1), kc, 0, 0, 0, 10 * dg, fb2 + 8 * k);
              kc += (k & 1) << 7; if (k == 9) kc = 64;
              dst += G2_WB; if (dst == sb + G2_WOFF + S2 * G2_WB) dst = sb + G2_WOFF;
            }
          }
        }
      }
    } else if (pw == 1) {
#pragma unroll 1
      for (int l = 0; l < 2; l++) {
        if (l == 1) {
          mbar_wait(bars + 8 * (has2 ? B_G2DONE + 19 : B_G1DONE + 9));
          if (has2) mbar_wait(bars + 8 * B_UST);
          cnt_poll(&g_ucnt[gpc * 32], 128 * tag);
          fence_async_global();
          if (elect_one()) {
            TS(20);
            const int bytes = last ? 16384 : 20480;
            const uint8_t* src = g_u + T1 * 204800;
            uint32_t dst = sb + X1_OFF;
#pragma unroll 1
            for (int k = 0; k < 10; k++) {
              if (k > 4) mbar_wait(bars + 8 * (B_G1DONE + 5 + k));
              mbar_expect_tx(bars + 8 * (B_G1FULL + 10 + k), bytes);
              bulk_g2s(dst, src, bytes, bars + 8 * (B_G1FULL + 10 + k));
              src += 20480; dst += 20480; if (dst == sb + G_OFF) dst = sb; if (k == 4) dst = sb + X1_OFF;
            }
          }
          __syncwarp();
        }
        if (has2) {
          mbar_wait(bars + 8 * (B_HST + 2 * l));
          mbar_wait(bars + 8 * (B_G1DONE + 10 * l + 9));
          cnt_poll(&g_hcnt[(l * 16 + gpc) * 32], 40 * tag);
          fence_async_global();
          if (elect_one()) {
            TS(21 + 2 * l);
            const uint32_t fb2 = bars + 8 * (B_G2FULL + 20 * l), wb2 = bars + 8 * (B_G2DONE + 20 * l - S2);
            const uint8_t* src = g_h + (l * 32 + m2) * 163840;
            uint32_t dst = sb;
#pragma unroll 1
            for (int k = 0; k < 20; k++) {
              if (k >= (l ? XB0 : 5)) mbar_wait(k >= S2 ? wb2 + 8 * k : (l ? fb2 + 8 * (k - XB0) : bars + 8 * B_SFREE));
              if (k == 10) { mbar_wait(bars + 8 * (B_H1 + l)); fence_async_global(); }
              mbar_expect_tx(fb2 + 8 * k, G2_XB);
              bulk_g2s(dst, src, G2_XB, fb2 + 8 * k);
              src += 8192; dst += G2_XB; if (dst == sb + S2 * G2_XB) dst = sb;
            }
          }
          __syncwarp();
        }
      }
    } else if (pw == 2) {
#pragma unroll 1
      for (int l = 0; l < 2; l++) {
        if (l == 1) {
          float xa[2], xb[2];
          mbar_wait(bars + 8 * (B_G1FULL + 11));
          stat_table(T1, tag, 1, 4, g_stats, g_stats, xa, xb);
          mbar_arrive(bars + 8 * (B_STAB + 1));
        }
        if (REL3 && l == 0) {
          mbar_wait(bars + 8 * B_HST);
          mbar_wait(bars + 8 * (B_HST + 1));
          if (lane < 8) h_release(lane >> 2, T1, lane & 3);
          __syncwarp();
          if (lane == 0) { mbar_arrive(bars + 8 * B_REL); TS(6); }
        }
#pragma unroll 1
        for (int w = 0; w < 2 * l; w++) {
          mbar_wait(bars + 8 * (B_HST + 2 + w));
          if (lane < 4) h_release(2 + w, T1, lane);
          __syncwarp();
          if (lane == 0) { if (w == 0) mbar_arrive(bars + 8 * (B_REL + 1)); TS(w ? 16 : 14); }
        }
        if (l == 0 && has2 && elect_one()) {
#pragma unroll 1
          for (int i = 0; i < 5; i++) {
            const int c = i < 3 ? i : 7 - i;
            mbar_wait(bars + 8 * (B_CVDONE + c));
            bulk_s2g(g_G + (cch0 + 32 * c) * 4096, cv_stage(c), 4096);
          }
          asm volatile("cp.async.bulk.commit_group;" ::: "memory");
          asm volatile("cp.async.bulk.wait_group.read 0;" ::: "memory");
          mbar_arrive(bars + 8 * B_SFREE);
          asm volatile("cp.async.bulk.wait_group 0;" ::: "memory");
          TS(48);
          fence_async_global();
          asm volatile("fence.acq_rel.gpu;" ::: "memory");
#pragma unroll
          for (int i = 0; i < 4; i++) red_rlx(&g_gcnt[(dg * 4 + i) * 32]);
          TS(49);
          mbar_arrive(bars + 8 * (B_GO + 1));
        }
        __syncwarp();
      }
    } else if (has2) {
      mbar_wait(bars + 8 * B_REL);
      if (!CPF && elect_one()) {
        l2_prefetch(p.cre + (160 * dg + 5 * m2) * DM, 6400); l2_prefetch(p.cim + (160 * dg + 5 * m2) * DM, 6400);
      }
      mbar_wait(bars + 8 * (B_HST + 1));
      flag_poll(&g_hcnt[(8 + gpc) * 32], 40 * tag);
      if (lane == 0) { mbar_arrive(bars + 8 * B_H1); TS(22); }
      mbar_wait(bars + 8 * (B_GO + 1));
      flag_poll(&g_gcnt[(dg * 4 + (m2 >> 3)) * 32], 32 * tag);
      fence_async_global();
      if (elect_one()) {
        TS(29);
        mbar_expect_tx(bars + 8 * B_GFULL, 20480);
        tma5(sb + G_OFF, &p.mG, 64 * m2, 0, 0, 0, 10 * dg, bars + 8 * B_GFULL);
      }
      mbar_wait(bars + 8 * (B_HST + 3));
      cnt_poll(&g_hcnt[(24 + gpc) * 32], 40 * tag);
      if (lane == 0) { mbar_arrive(bars + 8 * (B_H1 + 1)); TS(24); }
    }
    } else if (wg == 2 && (role >> 16)) {
      float acc[80];
      float off[2] = {mean0[0], mean0[1]};
      const unsigned tag = lds32(sb + EP_OFF + 20);
      dskip_init<true>(acc, mean0, rstd0);
      mbar_arrive(bars + 8 * B_XFREE);
#pragma unroll 1
      for (int l = 0; l < 2; l++) {
        float mean[2], rstd[2];
        {
          uint32_t alo = desc_lo(sb, 1024), blo = desc_lo(sb + G2_WOFF, 16) + (WTAIL ? l * (G2_WB >> 2) : 0);
          uint32_t fb = bars + 8 * (B_G2FULL + 20 * l);
          fence_regs(acc);
          mbar_wait(bars + 8 * (B_CVDONE + 2));
          mbar_wait(bars + 8 * (B_CVDONE + 3));
          mbar_wait(fb);
          if (tid == 256) TS(33 + 6 * l);
#pragma unroll 1
          for (int k = 0; k < 20; k++) {
            if (l == TSL && (k & 3) == 3 && tid == 256) TS(56 + (k >> 2));
            uint32_t ok; const uint32_t nb = k < 19 ? fb + 8 : fb;
            wgmma_fence();
#pragma unroll
            for (int kk = 0; kk < 4; kk++) {
              wgmma_n160<1>(acc, alo + kk * 128, desc_hi(128, 0), blo + kk * 2, desc_hi(1024, 1));
              if (kk == 0) ok = mbar_test(nb);
            }
            wgmma_commit();
            alo += G2_XB >> 4; blo += G2_WB >> 4;
            if (alo == desc_lo(sb + S2 * G2_XB, 1024)) alo = desc_lo(sb, 1024);
            if (blo == desc_lo(sb + G_OFF, 16)) blo = desc_lo(sb + G2_WOFF, 16);
            wgmma_wait<1>();
            if (k > 0 && tid == 256) mbar_arrive(fb + 8 * (B_G2DONE - B_G2FULL - 1));
            if (!ok) mbar_wait(nb);
            fb += 8;
          }
          wgmma_wait<0>();
          fence_regs(acc);
          if (tid == 256) TS(34 + 6 * l);
          if (tid == 256) mbar_arrive(bars + 8 * (B_G2DONE + 20 * l + 19));
        }
        ROLE(role)
        const int tq = tid_opaque() & 31, n0 = 64 * m2 + 16 * w + (tq >> 2);
        stats_publish<false>(2 * l + 1, n0, dg, tag, acc);
        uint32_t gf[10][4];
        mbar_wait(bars + 8 * B_GFULL);
        const uint32_t ga = sb + G_OFF + (8 * (tq >> 4) + (tq & 7)) * 128 + (((2 * w + ((tq >> 3) & 1)) ^ ((2 * m2) & 6) ^ (tq & 7)) << 4);
#pragma unroll
        for (int J = 0; J < 2; J++) ldsm4t(gf[J], ga + J * 2048);
        if (tid == 256) TS(35 + 6 * l);
        uint8_t* dst[2][2];
#pragma unroll
        for (int h = 0; h < 2; h++) {
          if (l == 0) {
            const int ng = 8 * m2 + 2 * w + h, T = ng / 20;
            uint8_t* ub = g_u + (T * 204800 + (ng - 20 * T) * 1024 + (tq & 2) * 64 + (tq & 28) * 4 + (tq & 1) * 8 + (5 * dg >> 1) * 20480);
            dst[h][1] = ub + ((dg & 1) ? 20480 - 512 : 0);
            dst[h][0] = ub + (dg & 1) * 512;
          } else {
            dst[h][0] = dst[h][1] = (uint8_t*)(p.out + (n_to_t(n0 + 8 * h) * DM + 160 * dg + 4 * (tq & 3)));
          }
        }
        stats_get(2 * l + 1, n0, tag, mean, rstd);
        if (tid == 256) TS(36 + 6 * l);
        off[0] += mean[0]; off[1] += mean[1];
        const float ov[2] = {l ? off[0] : 0.f, l ? off[1] : 0.f};
#pragma unroll
        for (int J = 0; J < 10; J++) {
          if (J + 2 < 10) ldsm4t(gf[J + 2 < 10 ? J + 2 : 0], ga + (J + 2) * 2048);
#pragma unroll
          for (int x = 0; x < 8; x++) {
            const int h = (x >> 1) & 1;
            const uint32_t gwd = gf[J][x >> 1];
            const float t = fmaf(rstd[h], (x & 1) ? bf_hi(gwd) : bf_lo(gwd), 1.f);
            acc[8 * J + x] = fmaf(acc[8 * J + x], t, fmaf(-mean[h], t, ov[h]));
          }
#pragma unroll
          for (int h = 0; h < 2; h++) {
            if (l == 0)
              *(uint2*)(dst[h][(J >> 1) & 1] + (J >> 2) * 20480 + (J & 3) * 256) =
                  make_uint2(pack_bf16(acc[8 * J + 2 * h], acc[8 * J + 2 * h + 1]), pack_bf16(acc[8 * J + 4 + 2 * h], acc[8 * J + 5 + 2 * h]));
            else
              *(float4*)(dst[h][0] + 64 * J) = make_float4(acc[8 * J + 2 * h], acc[8 * J + 2 * h + 1], acc[8 * J + 4 + 2 * h], acc[8 * J + 5 + 2 * h]);
          }
          __syncwarp();
        }
        if (l == 0) {
          bar_sync(3, 128);
          if (tid == 288) { TS(37); mbar_arrive(bars + 8 * B_UST); }
          if (tid < 264) red_rel(&g_ucnt[(tid & 7) * 32]);
          __syncwarp();
          if (tid == 256) TS(38);
          stats_publish<false>(2, n0, dg, tag, acc);
          mbar_wait(bars + 8 * (B_G1FULL + 11));
          float xa[2], xb[2];
          const uint4* x0 = &g_stats[(8 + (tq & 3)) * SEQ + n0];
          stat_table(T1, tag, 1, w, x0, x0 + 8, xa, xb);
          mbar_arrive(bars + 8 * (B_STAB + 1));
          if (tid == 256) TS(27);
          stats_reduce(xa, xb, mean, rstd);
          off[0] += mean[0]; off[1] += mean[1];
          mbar_wait(bars + 8 * (B_HST + 2));
          dskip_init<false>(acc, mean, rstd);
        } else {
          if (tid == 256) {
            TS(43);
            if (m2 == 31 && dg == 3) asm volatile("st.relaxed.gpu.global.u32 [%0], %1;" ::"l"(g_epoch), "r"(tag + 1) : "memory");
          }
        }
      }
    }
  }
}

typedef CUresult (*EncFn)(CUtensorMap*, CUtensorMapDataType, cuuint32_t, void*, const cuuint64_t*, const cuuint64_t*,
                          const cuuint32_t*, const cuuint32_t*, CUtensorMapInterleave, CUtensorMapSwizzle,
                          CUtensorMapL2promotion, CUtensorMapFloatOOBfill);

void encode(EncFn fn, CUtensorMap* m, const void* ptr, int rank, const cuuint64_t* dims, const cuuint64_t* strides, const cuuint32_t* box,
            CUtensorMapSwizzle swz = CU_TENSOR_MAP_SWIZZLE_128B, int prom = 2) {
  cuuint32_t es[5] = {1, 1, 1, 1, 1};
  fn(m, CU_TENSOR_MAP_DATA_TYPE_BFLOAT16, rank, (void*)ptr, dims, strides, box, es, CU_TENSOR_MAP_INTERLEAVE_NONE,
     swz, (CUtensorMapL2promotion)prom, CU_TENSOR_MAP_FLOAT_OOB_FILL_NONE);
}

}

extern "C" void kernel_launch(void* const* d_in, const int* in_sizes, int n_in, void* d_out, int out_size) {
  (void)in_sizes; (void)n_in; (void)out_size;
  Params p;
  typedef const __nv_bfloat16* BP;
  p.x = (BP)d_in[0]; p.lre = (BP)d_in[1]; p.lim = (BP)d_in[2]; p.bre = (BP)d_in[3]; p.bim = (BP)d_in[4];
  p.cre = (BP)d_in[5]; p.cim = (BP)d_in[6]; p.logdt = (BP)d_in[7]; p.dskip = (BP)d_in[8];
  p.k = (BP)d_in[10]; p.v = (BP)d_in[11]; p.shiftk = (BP)d_in[12]; p.ssmk = (BP)d_in[13]; p.ssmD = (BP)d_in[14];
  p.out = (float*)d_out;
  for (int sm = 0; sm < 132; sm++) {
    const int tpc = sm >> 1, side = sm & 1;
    int gpc, gi;
    if (tpc < 32) { gpc = tpc & 7; gi = tpc >> 3; }
    else if (tpc < 60) { gpc = 1 + (tpc - 32) % 7; gi = 4 + (tpc - 32) / 7; }
    else if (tpc < 62) { gpc = tpc - 54; gi = 8; }
    else { gpc = 0; gi = tpc - 58; }
    const int pos = 8 * gpc + gi + (gpc == 7 ? 1 : 0);
    int T1, GP;
    if (pos < 52) { const int hh = pos / 26, x = pos - 26 * hh; T1 = x >> 1; GP = 2 * hh + (x & 1); }
    else { T1 = pos - 52; GP = 4; }
    const int m2 = 8 * (gpc >> 1) + gi, dg = 2 * (gpc & 1) + side;
    p.role[sm] = pos == 65 ? -1 : (T1 | (GP << 4) | (side << 7) | (m2 << 8) | (dg << 14) | ((gi < 8) << 16));
  }
  void* fnp = nullptr;
  cudaDriverEntryPointQueryResult qr;
  cudaGetDriverEntryPoint("cuTensorMapEncodeTiled", &fnp, cudaEnableDefault, &qr);
  EncFn fn = (EncFn)fnp;
  void* gG = nullptr;
  cudaGetSymbolAddress(&gG, g_G);
  void* gKV = nullptr;
  cudaGetSymbolAddress(&gKV, g_kv);
  {
    cuuint64_t dims[5] = {32, 32, 10, 32, 4}, st[4] = {20480, 2048, 64, 655360}; cuuint32_t box[5] = {32, 35, 2, 1, 1};
    encode(fn, &p.mU, gKV, 5, dims, st, box, CU_TENSOR_MAP_SWIZZLE_NONE, 1);
  }
  const cuuint64_t RB = DM * 2;
  {
    p.swap = p.bim < p.bre;
    const char* lo = (const char*)(p.swap ? p.bim : p.bre); const char* hi = (const char*)(p.swap ? p.bre : p.bim);
    cuuint64_t dims[5] = {640, 8, 2, 8, 10}, st[4] = {RB, (cuuint64_t)(hi - lo), 8 * RB, 64 * RB}; cuuint32_t box[5] = {64, 8, 2, 4, 2};
    encode(fn, &p.mB, lo, 5, dims, st, box);
  }
  {
    cuuint64_t dims[5] = {640, 2, 4, 2, 40}, st[4] = {RB, 4 * RB, 2 * RB, 16 * RB}; cuuint32_t box[5] = {64, 2, 4, 2, 10};
    encode(fn, &p.mCre, p.cre, 5, dims, st, box); encode(fn, &p.mCim, p.cim, 5, dims, st, box);
    cuuint64_t dimg[5] = {2048, 2, 4, 2, 40}, stg[4] = {4096, 4 * 4096, 2 * 4096, 16 * 4096};
    encode(fn, &p.mG, gG, 5, dimg, stg, box);
  }
  {
    cuuint64_t dims[4] = {640, 2, 4, 900}, st[3] = {RB, 40 * RB, 2 * RB}; cuuint32_t box[4] = {64, 2, 4, 20};
    encode(fn, &p.mX, p.x, 4, dims, st, box);
    cuuint64_t diml[4] = {640, 2, 4, 16}, stl[3] = {RB, 32 * RB, 2 * RB};
    encode(fn, &p.mXl, p.x + (size_t)1920 * DM, 4, diml, stl, box);
    cuuint32_t boxt[4] = {160, 2, 4, 4};
    encode(fn, &p.mXt, p.x, 4, dims, st, boxt, CU_TENSOR_MAP_SWIZZLE_NONE);
    encode(fn, &p.mXtl, p.x + (size_t)1920 * DM, 4, diml, stl, boxt, CU_TENSOR_MAP_SWIZZLE_NONE);
    cuuint64_t dk[3] = {640, 2000, 4}, sk[2] = {RB, 16 * RB}; cuuint32_t bk[3] = {32, 19, 4}, bv[3] = {32, 17, 4};
    encode(fn, &p.mK, p.k, 3, dk, sk, bk, CU_TENSOR_MAP_SWIZZLE_NONE);
    encode(fn, &p.mV, p.v, 3, dk, sk, bv, CU_TENSOR_MAP_SWIZZLE_NONE);
  }
  cudaFuncSetAttribute(fused_kernel, cudaFuncAttributeMaxDynamicSharedMemorySize, SMEM_BYTES);
  cudaLaunchConfig_t cfg = {};
  cfg.gridDim = dim3(132); cfg.blockDim = dim3(512); cfg.dynamicSmemBytes = SMEM_BYTES; cfg.stream = cudaStreamPerThread;
  cudaLaunchKernelEx(&cfg, fused_kernel, p);
}
```

```cpp
#include <cuda_runtime.h>
#include <cuda.h>
#include <cuda_bf16.h>
#include <stdint.h>

namespace {

constexpr int SEQ = 2048, DM = 640;
constexpr int NT1 = 13;
#define EXP 0
#define WPF1 3
#define WPF2 7
#define CPOLL 10
#define KV0 1
#define TAPLATE 1
#define STG_D 3
#define STG_KK 1
#define HOLD0 1
#define WREL 0
#define UREL 1
#define TSL 1
#define STG0 2
#define WTAIL 1
#define PFD 1
#define TAPW 0
#define TPF 4
#define CPF 0
#define MK0 7
#define MK1 4
#define PACE 180
#define XB0 3
#define TAPN 2
#define REL3 0
#define REP2 0
#define PAUSE_K 5
constexpr uint32_t SPIN_LIMIT = 1u << 22;

__device__ __align__(1024) uint8_t g_h[2 * 32 * 20 * 8192];
__device__ __align__(1024) uint8_t g_u[NT1 * 10 * 20480];
__device__ __align__(1024) uint8_t g_kv[DM * 4096];
__device__ __align__(1024) uint8_t g_G[DM * 4096];
__device__ __align__(128) uint4 g_E[2 * NT1 * DM];
__device__ __align__(128) uint4 g_stats[4 * 4 * SEQ];
__device__ __align__(128) uint4 g_sB[DM * 2];
__device__ __align__(128) unsigned g_hcnt[2 * 2 * 8 * 32];
__device__ __align__(128) unsigned g_ucnt[8 * 32];
__device__ __align__(128) unsigned g_kvcnt[16 * 32];
__device__ __align__(128) unsigned g_gcnt[16 * 32];
__device__ __align__(128) unsigned g_epoch[32] = {1};
#define TS(i) do {} while (0)

struct Params {
  CUtensorMap mX, mB, mXl, mK, mV, mXt, mXtl, mCre, mCim, mG, mU;
  const __nv_bfloat16 *x, *lre, *lim, *bre, *bim, *cre, *cim, *logdt, *dskip, *k, *v, *shiftk, *ssmk, *ssmD;
  float* out;
  int swap;
  int role[132];
};

constexpr uint32_t sb = 1024;
constexpr uint32_t G1_STAGE = 36864, G1_XOFF = 16384;
constexpr int S1 = 4;
constexpr uint32_t XT_OFF = 159744, KS_OFF = 180224, KV_PIECE = 9216;
constexpr uint32_t G2_XB = 8192, G2_WB = 20480, G2_WOFF = 57344, G_OFF = 200704;
constexpr uint32_t X1_OFF = 139264;
constexpr int S2 = 7;
constexpr uint32_t CV_OFF = KS_OFF, CV_K = 128, CV_PL = 2240, CV_U = CV_K + 4096, CV_B = KV_PIECE;
constexpr uint32_t MISC = 226304;
constexpr uint32_t BAR_OFF = MISC;
constexpr int B_G1FULL = 0, B_G1DONE = 20, B_G2FULL = 40,
              B_G2DONE = 85, B_GFULL = 125, B_EP = 126, B_H1 = 127  , B_CVFULL = 129  , B_STG = 134  , B_REL = 136  , B_SFREE = 138, B_UST = 142,
              B_GO = 139  , B_PUB = 147,
              B_CVDONE = 148  , B_STAB = 153  , B_XFREE = 155, B_HST = 156  ,
              B_CTAB = 160, B_PREP = 161, B_XT = 162, B_KV = 163  , B_PREP2 = 84, B_PD = 168  ;
constexpr uint32_t bars = sb + BAR_OFF;
constexpr uint32_t STAB_OFF = MISC + 1392;
constexpr uint32_t CTAB_OFF = STAB_OFF + 640;
constexpr uint32_t DTAB_OFF = CTAB_OFF + 1536;
constexpr uint32_t EP_OFF = DTAB_OFF + 320;
constexpr uint32_t SO_OFF = EP_OFF + 32;
constexpr uint32_t TAP_OFF = 147456;
constexpr uint32_t MX0_OFF = TAP_OFF + 1280, MX1_OFF = G_OFF + 20480;
constexpr uint32_t DX_OFF = MX1_OFF + 2560;
constexpr uint32_t SMEM_BYTES = 232448;
static_assert(SO_OFF + 1536 <= SMEM_BYTES, "smem");

__device__ __forceinline__ void trap_if(bool c) { asm volatile("{\n.reg .pred p;\nsetp.ne.u32 p, %0, 0;\n@p trap;\n}\n" ::"r"((uint32_t)c)); }
__device__ __forceinline__ uint32_t smem_u32(const void* p) { return (uint32_t)__cvta_generic_to_shared(p); }
__device__ __forceinline__ void mbar_init(uint32_t bar, int cnt) { asm volatile("mbarrier.init.shared::cta.b64 [%0], %1;" ::"r"(bar), "r"(cnt) : "memory"); }
__device__ __forceinline__ void mbar_expect_tx(uint32_t bar, int bytes) { asm volatile("mbarrier.arrive.expect_tx.shared::cta.b64 _, [%0], %1;" ::"r"(bar), "r"(bytes) : "memory"); }
__device__ __forceinline__ void mbar_arrive(uint32_t bar) { asm volatile("mbarrier.arrive.shared::cta.b64 _, [%0];" ::"r"(bar) : "memory"); }
__device__ __forceinline__ void mbar_wait(uint32_t bar) {
  asm volatile(
      "{\n.reg .pred p;\n.reg .u32 c;\nmov.u32 c, 0;\n"
      "W_%=:\nmbarrier.try_wait.parity.shared::cta.b64 p, [%0], 0;\n@p bra D_%=;\n"
      "add.u32 c, c, 1;\nsetp.lt.u32 p, c, %1;\n@p bra W_%=;\ntrap;\nD_%=:\n}\n" ::"r"(bar), "n"(SPIN_LIMIT) : "memory");
}
__device__ __forceinline__ uint32_t mbar_test(uint32_t bar) {
  uint32_t ok;
  asm volatile("{\n.reg .pred p;\nmbarrier.test_wait.parity.shared::cta.b64 p, [%1], 0;\nselp.u32 %0, 1, 0, p;\n}\n" : "=r"(ok) : "r"(bar) : "memory");
  return ok;
}
__device__ __forceinline__ void tma3(uint32_t dst, const CUtensorMap* m, int c0, int c1, int c2, uint32_t bar) {
  asm volatile("cp.async.bulk.tensor.3d.shared::cluster.global.mbarrier::complete_tx::bytes [%0], [%1, {%3,%4,%5}], [%2];"
               ::"r"(dst), "l"(m), "r"(bar), "r"(c0), "r"(c1), "r"(c2) : "memory");
}
__device__ __forceinline__ void tma4(uint32_t dst, const CUtensorMap* m, int c0, int c1, int c2, int c3, uint32_t bar) {
  asm volatile("cp.async.bulk.tensor.4d.shared::cluster.global.mbarrier::complete_tx::bytes [%0], [%1, {%3,%4,%5,%6}], [%2];"
               ::"r"(dst), "l"(m), "r"(bar), "r"(c0), "r"(c1), "r"(c2), "r"(c3) : "memory");
}
__device__ __forceinline__ void tma5(uint32_t dst, const CUtensorMap* m, int c0, int c1, int c2, int c3, int c4, uint32_t bar) {
  asm volatile("cp.async.bulk.tensor.5d.shared::cluster.global.mbarrier::complete_tx::bytes [%0], [%1, {%3,%4,%5,%6,%7}], [%2];"
               ::"r"(dst), "l"(m), "r"(bar), "r"(c0), "r"(c1), "r"(c2), "r"(c3), "r"(c4) : "memory");
}
__device__ __forceinline__ void bulk_g2s(uint32_t dst, const void* src, int bytes, uint32_t bar) {
  asm volatile("cp.async.bulk.shared::cluster.global.mbarrier::complete_tx::bytes [%0], [%1], %2, [%3];"
               ::"r"(dst), "l"(src), "r"(bytes), "r"(bar) : "memory");
}
__device__ __forceinline__ void bulk_s2g(void* dst, uint32_t src, int bytes) {
  asm volatile("cp.async.bulk.global.shared::cta.bulk_group [%0], [%1], %2;" ::"l"(dst), "r"(src), "r"(bytes) : "memory");
}
__device__ __forceinline__ void l2_prefetch(const void* src, int bytes) {
  asm volatile("cp.async.bulk.prefetch.L2.global [%0], %1;" ::"l"(src), "r"(bytes) : "memory");
}
__device__ __forceinline__ void wgmma_fence() { asm volatile("wgmma.fence.sync.aligned;" ::: "memory"); }
__device__ __forceinline__ void wgmma_commit() { asm volatile("wgmma.commit_group.sync.aligned;" ::: "memory"); }
template <int N> __device__ __forceinline__ void wgmma_wait() { asm volatile("wgmma.wait_group.sync.aligned %0;" ::"n"(N) : "memory"); }
__host__ __device__ constexpr uint32_t desc_lo(uint32_t addr, uint32_t lbo) { return ((addr & 0x3FFFF) >> 4) | ((lbo >> 4) << 16); }
__host__ __device__ constexpr uint32_t desc_hi(uint32_t sbo, uint32_t swz) { return (sbo >> 4) | (swz << 30); }
__device__ __forceinline__ void bar_sync(int id, int n) { asm volatile("bar.sync %0, %1;" ::"r"(id), "r"(n) : "memory"); }
__device__ __forceinline__ uint32_t lds32(uint32_t a) { uint32_t v; asm volatile("ld.shared.u32 %0, [%1];" : "=r"(v) : "r"(a) : "memory"); return v; }
__device__ __forceinline__ float2 lds64f(uint32_t a) { float2 v; asm volatile("ld.shared.v2.f32 {%0,%1}, [%2];" : "=f"(v.x), "=f"(v.y) : "r"(a) : "memory"); return v; }
__device__ __forceinline__ float4 lds128f(uint32_t a) { float4 v; asm volatile("ld.shared.v4.f32 {%0,%1,%2,%3}, [%4];" : "=f"(v.x), "=f"(v.y), "=f"(v.z), "=f"(v.w) : "r"(a) : "memory"); return v; }
__device__ __forceinline__ void ldsm4t(uint32_t (&r)[4], uint32_t a) {
  asm volatile("ldmatrix.sync.aligned.m8n8.x4.trans.shared.b16 {%0,%1,%2,%3}, [%4];" : "=r"(r[0]), "=r"(r[1]), "=r"(r[2]), "=r"(r[3]) : "r"(a) : "memory");
}
__device__ __forceinline__ uint4 ldv128(const void* a) { uint4 v; asm volatile("ld.global.nc.v4.u32 {%0,%1,%2,%3}, [%4];" : "=r"(v.x), "=r"(v.y), "=r"(v.z), "=r"(v.w) : "l"(a) : "memory"); return v; }
__device__ __forceinline__ uint2 ldv64(const void* a) { uint2 v; asm volatile("ld.global.nc.v2.u32 {%0,%1}, [%2];" : "=r"(v.x), "=r"(v.y) : "l"(a) : "memory"); return v; }
__device__ __forceinline__ uint32_t ldv16(const void* a) { uint32_t v; asm volatile("ld.global.nc.u16 %0, [%1];" : "=r"(v) : "l"(a) : "memory"); return v; }
__device__ __forceinline__ void sts128(uint32_t a, uint4 v) { asm volatile("st.shared.v4.u32 [%0], {%1,%2,%3,%4};" ::"r"(a), "r"(v.x), "r"(v.y), "r"(v.z), "r"(v.w) : "memory"); }
__device__ __forceinline__ void sts32(uint32_t a, uint32_t v) { asm volatile("st.shared.u32 [%0], %1;" ::"r"(a), "r"(v) : "memory"); }
__device__ __forceinline__ void sts64f(uint32_t a, float x, float y) { asm volatile("st.shared.v2.f32 [%0], {%1,%2};" ::"r"(a), "f"(x), "f"(y) : "memory"); }
__device__ __forceinline__ void red_rlx(unsigned* p) { asm volatile("red.relaxed.gpu.global.add.u32 [%0], 1;" ::"l"(p) : "memory"); }
__device__ __forceinline__ void red_rel(unsigned* p) { asm volatile("red.release.gpu.global.add.u32 [%0], 1;" ::"l"(p) : "memory"); }
__device__ __forceinline__ void fence_async_global() { asm volatile("fence.proxy.async.global;" ::: "memory"); }
__device__ __forceinline__ void fence_async_smem() { asm volatile("fence.proxy.async.shared::cta;" ::: "memory"); }
__device__ __forceinline__ void rec_st(uint4* p, float a, float b, unsigned tag) {
  asm volatile("{\n.reg .b128 t;\n.reg .b64 lo, hi;\nmov.b64 lo, {%1,%2};\nmov.b64 hi, {%3,%3};\nmov.b128 t, {lo,hi};\n"
               "st.relaxed.gpu.global.b128 [%0], t;\n}\n" ::"l"(p), "r"(__float_as_uint(a)), "r"(__float_as_uint(b)), "r"(tag) : "memory");
}
__device__ __forceinline__ unsigned rec_ld(const uint4* p, float& a, float& b) {
  unsigned x, y, t;
  asm volatile("{\n.reg .b128 t;\n.reg .b64 lo, hi;\n.reg .b32 u;\nld.relaxed.gpu.global.b128 t, [%3];\nmov.b128 {lo,hi}, t;\n"
               "mov.b64 {%0,%1}, lo;\nmov.b64 {%2,u}, hi;\n}\n" : "=r"(x), "=r"(y), "=r"(t) : "l"(p) : "memory");
  a = __uint_as_float(x); b = __uint_as_float(y);
  return t;
}
__device__ __forceinline__ unsigned ld_rlx(const unsigned* p) { unsigned v; asm volatile("ld.relaxed.gpu.global.u32 %0, [%1];" : "=r"(v) : "l"(p) : "memory"); return v; }
__device__ __forceinline__ void flag_poll(const unsigned* p, unsigned target) {
  uint32_t it = 0;
  while (!__all_sync(0xffffffffu, (int)(ld_rlx(p) - target) >= 0)) { trap_if(++it > SPIN_LIMIT); }
  asm volatile("fence.acquire.gpu;" ::: "memory");
}
__device__ __forceinline__ void cnt_poll(const unsigned* p, unsigned target) {
  unsigned a = ld_rlx(p); __nanosleep(100);
  unsigned b = ld_rlx(p); __nanosleep(100);
  unsigned c = ld_rlx(p);
  uint32_t it = 0;
  while (true) {
    if (__all_sync(0xffffffffu, (int)(a - target) >= 0)) break;
    a = ld_rlx(p);
    if (__all_sync(0xffffffffu, (int)(b - target) >= 0)) break;
    b = ld_rlx(p);
    if (__all_sync(0xffffffffu, (int)(c - target) >= 0)) break;
    c = ld_rlx(p);
    trap_if(++it > SPIN_LIMIT);
  }
  asm volatile("fence.acquire.gpu;" ::: "memory");
}
__device__ __forceinline__ void h_release(int idx, int T, int i) {
  const int Q = (i & 2) ? (T + 2) / 3 - 1 : T / 3;
  if (Q >= 0 && Q < 4 && ((i & 2) == 0 || T % 3 == 0)) red_rel(&g_hcnt[(idx * 8 + 2 * Q + (i & 1)) * 32]);
}
__device__ __forceinline__ uint32_t pack_bf16(float lo, float hi) {
  uint32_t r; asm("cvt.rn.bf16x2.f32 %0, %1, %2;" : "=r"(r) : "f"(hi), "f"(lo)); return r;
}
__device__ __forceinline__ float bf_lo(uint32_t w) { return __uint_as_float(w << 16); }
__device__ __forceinline__ float bf_hi(uint32_t w) { return __uint_as_float(w & 0xffff0000u); }
__device__ __forceinline__ uint32_t hmul2(uint32_t a, uint32_t b) {
  __nv_bfloat162 r = __hmul2_rn(*(__nv_bfloat162*)&a, *(__nv_bfloat162*)&b); return *(uint32_t*)&r;
}
__device__ __forceinline__ uint32_t hadd2(uint32_t a, uint32_t b) {
  __nv_bfloat162 r = __hadd2_rn(*(__nv_bfloat162*)&a, *(__nv_bfloat162*)&b); return *(uint32_t*)&r;
}
__device__ __forceinline__ float2 cmul(float2 a, float2 b) { return make_float2(a.x * b.x - a.y * b.y, a.x * b.y + a.y * b.x); }
__device__ __forceinline__ float2 cfma(float2 a, float2 b, float2 c) {
  return make_float2(fmaf(a.x, b.x, fmaf(-a.y, b.y, c.x)), fmaf(a.x, b.y, fmaf(a.y, b.x, c.y)));
}
template <int N> __device__ __forceinline__ void fence_regs(float (&a)[N]) {
#pragma unroll
  for (int i = 0; i < N; i++) asm volatile("" : "+f"(a[i])::"memory");
}
__device__ __forceinline__ bool elect_one() {
  uint32_t e; asm volatile("{\n.reg .pred P;\nelect.sync _|P, 0xffffffff;\nselp.u32 %0, 1, 0, P;\n}\n" : "=r"(e)); return e != 0;
}
__device__ __forceinline__ int tid_opaque() { int t; asm volatile("mov.u32 %0, %%tid.x;" : "=r"(t)); return t; }
struct Role { int T1, GP, side, m2, dg, cch0; bool last, has2; };
__device__ __forceinline__ Role unpack_role(int x) {
  Role r; r.T1 = x & 15; r.GP = (x >> 4) & 7; r.side = (x >> 7) & 1; r.m2 = (x >> 8) & 63; r.dg = (x >> 14) & 3;
  r.has2 = (x >> 16) & 1; r.last = r.T1 == NT1 - 1; r.cch0 = 160 * r.dg + r.m2; return r;
}
__device__ __forceinline__ Role fresh_role(int x) { asm volatile("" : "+r"(x)); return unpack_role(__shfl_sync(0xffffffffu, x, 0)); }
#define ROLE(x) const Role R_ = fresh_role(x); const int T1 = R_.T1, GP = R_.GP, side = R_.side, m2 = R_.m2, dg = R_.dg, cch0 = R_.cch0; \
  const bool last = R_.last, has2 = R_.has2; (void)T1; (void)GP; (void)side; (void)m2; (void)dg; (void)cch0; (void)last; (void)has2;
__device__ __forceinline__ int n_to_t(int n) {
  int T = n / 160, nl = n - T * 160;
  int L = (T == NT1 - 1) ? 32 : 40;
  return T * 160 + L * ((nl & 7) >> 1) + 2 * (nl >> 3) + (nl & 1);
}

template<int TA> __device__ __forceinline__ void wgmma_n160(float (&d)[80], uint32_t alo, uint32_t ahi, uint32_t blo, uint32_t bhi){
  asm volatile("{\n.reg .b64 da, db;\nmov.b64 da, {%80,%81};\nmov.b64 db, {%82,%83};\n"
    "wgmma.mma_async.sync.aligned.m64n160k16.f32.bf16.bf16 {%0, %1, %2, %3, %4, %5, %6, %7, %8, %9, %10, %11, %12, %13, %14, %15, %16, %17, %18, %19, %20, %21, %22, %23, %24, %25, %26, %27, %28, %29, %30, %31, %32, %33, %34, %35, %36, %37, %38, %39, %40, %41, %42, %43, %44, %45, %46, %47, %48, %49, %50, %51, %52, %53, %54, %55, %56, %57, %58, %59, %60, %61, %62, %63, %64, %65, %66, %67, %68, %69, %70, %71, %72, %73, %74, %75, %76, %77, %78, %79}, da, db, 1, 1, 1, %84, 0;\n}\n"
    : "+f"(d[0]), "+f"(d[1]), "+f"(d[2]), "+f"(d[3]), "+f"(d[4]), "+f"(d[5]), "+f"(d[6]), "+f"(d[7]), "+f"(d[8]), "+f"(d[9]), "+f"(d[10]), "+f"(d[11]), "+f"(d[12]), "+f"(d[13]), "+f"(d[14]), "+f"(d[15]), "+f"(d[16]), "+f"(d[17]), "+f"(d[18]), "+f"(d[19]), "+f"(d[20]), "+f"(d[21]), "+f"(d[22]), "+f"(d[23]), "+f"(d[24]), "+f"(d[25]), "+f"(d[26]), "+f"(d[27]), "+f"(d[28]), "+f"(d[29]), "+f"(d[30]), "+f"(d[31]), "+f"(d[32]), "+f"(d[33]), "+f"(d[34]), "+f"(d[35]), "+f"(d[36]), "+f"(d[37]), "+f"(d[38]), "+f"(d[39]), "+f"(d[40]), "+f"(d[41]), "+f"(d[42]), "+f"(d[43]), "+f"(d[44]), "+f"(d[45]), "+f"(d[46]), "+f"(d[47]), "+f"(d[48]), "+f"(d[49]), "+f"(d[50]), "+f"(d[51]), "+f"(d[52]), "+f"(d[53]), "+f"(d[54]), "+f"(d[55]), "+f"(d[56]), "+f"(d[57]), "+f"(d[58]), "+f"(d[59]), "+f"(d[60]), "+f"(d[61]), "+f"(d[62]), "+f"(d[63]), "+f"(d[64]), "+f"(d[65]), "+f"(d[66]), "+f"(d[67]), "+f"(d[68]), "+f"(d[69]), "+f"(d[70]), "+f"(d[71]), "+f"(d[72]), "+f"(d[73]), "+f"(d[74]), "+f"(d[75]), "+f"(d[76]), "+f"(d[77]), "+f"(d[78]), "+f"(d[79])
    : "r"(alo), "r"(ahi), "r"(blo), "r"(bhi), "n"(TA));
}
__device__ __forceinline__ void wgmma_rs_n160(float (&d)[80], uint32_t a0, uint32_t a1, uint32_t a2, uint32_t a3, uint32_t blo){
  asm volatile("{\n.reg .b64 db;\nmov.b64 db, {%84,8};\nwgmma.mma_async.sync.aligned.m64n160k16.f32.bf16.bf16 {%0, %1, %2, %3, %4, %5, %6, %7, %8, %9, %10, %11, %12, %13, %14, %15, %16, %17, %18, %19, %20, %21, %22, %23, %24, %25, %26, %27, %28, %29, %30, %31, %32, %33, %34, %35, %36, %37, %38, %39, %40, %41, %42, %43, %44, %45, %46, %47, %48, %49, %50, %51, %52, %53, %54, %55, %56, %57, %58, %59, %60, %61, %62, %63, %64, %65, %66, %67, %68, %69, %70, %71, %72, %73, %74, %75, %76, %77, %78, %79}, {%80,%81,%82,%83}, db, 1, 1, 1, 0;\n}\n"
    : "+f"(d[0]), "+f"(d[1]), "+f"(d[2]), "+f"(d[3]), "+f"(d[4]), "+f"(d[5]), "+f"(d[6]), "+f"(d[7]), "+f"(d[8]), "+f"(d[9]), "+f"(d[10]), "+f"(d[11]), "+f"(d[12]), "+f"(d[13]), "+f"(d[14]), "+f"(d[15]), "+f"(d[16]), "+f"(d[17]), "+f"(d[18]), "+f"(d[19]), "+f"(d[20]), "+f"(d[21]), "+f"(d[22]), "+f"(d[23]), "+f"(d[24]), "+f"(d[25]), "+f"(d[26]), "+f"(d[27]), "+f"(d[28]), "+f"(d[29]), "+f"(d[30]), "+f"(d[31]), "+f"(d[32]), "+f"(d[33]), "+f"(d[34]), "+f"(d[35]), "+f"(d[36]), "+f"(d[37]), "+f"(d[38]), "+f"(d[39]), "+f"(d[40]), "+f"(d[41]), "+f"(d[42]), "+f"(d[43]), "+f"(d[44]), "+f"(d[45]), "+f"(d[46]), "+f"(d[47]), "+f"(d[48]), "+f"(d[49]), "+f"(d[50]), "+f"(d[51]), "+f"(d[52]), "+f"(d[53]), "+f"(d[54]), "+f"(d[55]), "+f"(d[56]), "+f"(d[57]), "+f"(d[58]), "+f"(d[59]), "+f"(d[60]), "+f"(d[61]), "+f"(d[62]), "+f"(d[63]), "+f"(d[64]), "+f"(d[65]), "+f"(d[66]), "+f"(d[67]), "+f"(d[68]), "+f"(d[69]), "+f"(d[70]), "+f"(d[71]), "+f"(d[72]), "+f"(d[73]), "+f"(d[74]), "+f"(d[75]), "+f"(d[76]), "+f"(d[77]), "+f"(d[78]), "+f"(d[79])
    : "r"(a0), "r"(a1), "r"(a2), "r"(a3), "r"(blo));
}
template<int N> __device__ __forceinline__ void wgmma_rs_hi(float (&d)[64], uint32_t a0, uint32_t a1, uint32_t a2, uint32_t a3, uint32_t blo);
template<> __device__ __forceinline__ void wgmma_rs_hi<16>(float (&d)[64], uint32_t a0, uint32_t a1, uint32_t a2, uint32_t a3, uint32_t blo){
  asm volatile("{\n.reg .b64 db;\nmov.b64 db, {%12,8};\nwgmma.mma_async.sync.aligned.m64n16k16.f32.bf16.bf16 {%0, %1, %2, %3, %4, %5, %6, %7}, {%8,%9,%10,%11}, db, 1, 1, 1, 0;\n}\n"
    : "+f"(d[56]), "+f"(d[57]), "+f"(d[58]), "+f"(d[59]), "+f"(d[60]), "+f"(d[61]), "+f"(d[62]), "+f"(d[63])
    : "r"(a0), "r"(a1), "r"(a2), "r"(a3), "r"(blo));
}
template<> __device__ __forceinline__ void wgmma_rs_hi<32>(float (&d)[64], uint32_t a0, uint32_t a1, uint32_t a2, uint32_t a3, uint32_t blo){
  asm volatile("{\n.reg .b64 db;\nmov.b64 db, {%20,8};\nwgmma.mma_async.sync.aligned.m64n32k16.f32.bf16.bf16 {%0, %1, %2, %3, %4, %5, %6, %7, %8, %9, %10, %11, %12, %13, %14, %15}, {%16,%17,%18,%19}, db, 1, 1, 1, 0;\n}\n"
    : "+f"(d[48]), "+f"(d[49]), "+f"(d[50]), "+f"(d[51]), "+f"(d[52]), "+f"(d[53]), "+f"(d[54]), "+f"(d[55]), "+f"(d[56]), "+f"(d[57]), "+f"(d[58]), "+f"(d[59]), "+f"(d[60]), "+f"(d[61]), "+f"(d[62]), "+f"(d[63])
    : "r"(a0), "r"(a1), "r"(a2), "r"(a3), "r"(blo));
}
template<> __device__ __forceinline__ void wgmma_rs_hi<48>(float (&d)[64], uint32_t a0, uint32_t a1, uint32_t a2, uint32_t a3, uint32_t blo){
  asm volatile("{\n.reg .b64 db;\nmov.b64 db, {%28,8};\nwgmma.mma_async.sync.aligned.m64n48k16.f32.bf16.bf16 {%0, %1, %2, %3, %4, %5, %6, %7, %8, %9, %10, %11, %12, %13, %14, %15, %16, %17, %18, %19, %20, %21, %22, %23}, {%24,%25,%26,%27}, db, 1, 1, 1, 0;\n}\n"
    : "+f"(d[40]), "+f"(d[41]), "+f"(d[42]), "+f"(d[43]), "+f"(d[44]), "+f"(d[45]), "+f"(d[46]), "+f"(d[47]), "+f"(d[48]), "+f"(d[49]), "+f"(d[50]), "+f"(d[51]), "+f"(d[52]), "+f"(d[53]), "+f"(d[54]), "+f"(d[55]), "+f"(d[56]), "+f"(d[57]), "+f"(d[58]), "+f"(d[59]), "+f"(d[60]), "+f"(d[61]), "+f"(d[62]), "+f"(d[63])
    : "r"(a0), "r"(a1), "r"(a2), "r"(a3), "r"(blo));
}
template<> __device__ __forceinline__ void wgmma_rs_hi<64>(float (&d)[64], uint32_t a0, uint32_t a1, uint32_t a2, uint32_t a3, uint32_t blo){
  asm volatile("{\n.reg .b64 db;\nmov.b64 db, {%36,8};\nwgmma.mma_async.sync.aligned.m64n64k16.f32.bf16.bf16 {%0, %1, %2, %3, %4, %5, %6, %7, %8, %9, %10, %11, %12, %13, %14, %15, %16, %17, %18, %19, %20, %21, %22, %23, %24, %25, %26, %27, %28, %29, %30, %31}, {%32,%33,%34,%35}, db, 1, 1, 1, 0;\n}\n"
    : "+f"(d[32]), "+f"(d[33]), "+f"(d[34]), "+f"(d[35]), "+f"(d[36]), "+f"(d[37]), "+f"(d[38]), "+f"(d[39]), "+f"(d[40]), "+f"(d[41]), "+f"(d[42]), "+f"(d[43]), "+f"(d[44]), "+f"(d[45]), "+f"(d[46]), "+f"(d[47]), "+f"(d[48]), "+f"(d[49]), "+f"(d[50]), "+f"(d[51]), "+f"(d[52]), "+f"(d[53]), "+f"(d[54]), "+f"(d[55]), "+f"(d[56]), "+f"(d[57]), "+f"(d[58]), "+f"(d[59]), "+f"(d[60]), "+f"(d[61]), "+f"(d[62]), "+f"(d[63])
    : "r"(a0), "r"(a1), "r"(a2), "r"(a3), "r"(blo));
}
template<> __device__ __forceinline__ void wgmma_rs_hi<80>(float (&d)[64], uint32_t a0, uint32_t a1, uint32_t a2, uint32_t a3, uint32_t blo){
  asm volatile("{\n.reg .b64 db;\nmov.b64 db, {%44,8};\nwgmma.mma_async.sync.aligned.m64n80k16.f32.bf16.bf16 {%0, %1, %2, %3, %4, %5, %6, %7, %8, %9, %10, %11, %12, %13, %14, %15, %16, %17, %18, %19, %20, %21, %22, %23, %24, %25, %26, %27, %28, %29, %30, %31, %32, %33, %34, %35, %36, %37, %38, %39}, {%40,%41,%42,%43}, db, 1, 1, 1, 0;\n}\n"
    : "+f"(d[24]), "+f"(d[25]), "+f"(d[26]), "+f"(d[27]), "+f"(d[28]), "+f"(d[29]), "+f"(d[30]), "+f"(d[31]), "+f"(d[32]), "+f"(d[33]), "+f"(d[34]), "+f"(d[35]), "+f"(d[36]), "+f"(d[37]), "+f"(d[38]), "+f"(d[39]), "+f"(d[40]), "+f"(d[41]), "+f"(d[42]), "+f"(d[43]), "+f"(d[44]), "+f"(d[45]), "+f"(d[46]), "+f"(d[47]), "+f"(d[48]), "+f"(d[49]), "+f"(d[50]), "+f"(d[51]), "+f"(d[52]), "+f"(d[53]), "+f"(d[54]), "+f"(d[55]), "+f"(d[56]), "+f"(d[57]), "+f"(d[58]), "+f"(d[59]), "+f"(d[60]), "+f"(d[61]), "+f"(d[62]), "+f"(d[63])
    : "r"(a0), "r"(a1), "r"(a2), "r"(a3), "r"(blo));
}
template<> __device__ __forceinline__ void wgmma_rs_hi<96>(float (&d)[64], uint32_t a0, uint32_t a1, uint32_t a2, uint32_t a3, uint32_t blo){
  asm volatile("{\n.reg .b64 db;\nmov.b64 db, {%52,8};\nwgmma.mma_async.sync.aligned.m64n96k16.f32.bf16.bf16 {%0, %1, %2, %3, %4, %5, %6, %7, %8, %9, %10, %11, %12, %13, %14, %15, %16, %17, %18, %19, %20, %21, %22, %23, %24, %25, %26, %27, %28, %29, %30, %31, %32, %33, %34, %35, %36, %37, %38, %39, %40, %41, %42, %43, %44, %45, %46, %47}, {%48,%49,%50,%51}, db, 1, 1, 1, 0;\n}\n"
    : "+f"(d[16]), "+f"(d[17]), "+f"(d[18]), "+f"(d[19]), "+f"(d[20]), "+f"(d[21]), "+f"(d[22]), "+f"(d[23]), "+f"(d[24]), "+f"(d[25]), "+f"(d[26]), "+f"(d[27]), "+f"(d[28]), "+f"(d[29]), "+f"(d[30]), "+f"(d[31]), "+f"(d[32]), "+f"(d[33]), "+f"(d[34]), "+f"(d[35]), "+f"(d[36]), "+f"(d[37]), "+f"(d[38]), "+f"(d[39]), "+f"(d[40]), "+f"(d[41]), "+f"(d[42]), "+f"(d[43]), "+f"(d[44]), "+f"(d[45]), "+f"(d[46]), "+f"(d[47]), "+f"(d[48]), "+f"(d[49]), "+f"(d[50]), "+f"(d[51]), "+f"(d[52]), "+f"(d[53]), "+f"(d[54]), "+f"(d[55]), "+f"(d[56]), "+f"(d[57]), "+f"(d[58]), "+f"(d[59]), "+f"(d[60]), "+f"(d[61]), "+f"(d[62]), "+f"(d[63])
    : "r"(a0), "r"(a1), "r"(a2), "r"(a3), "r"(blo));
}
template<> __device__ __forceinline__ void wgmma_rs_hi<112>(float (&d)[64], uint32_t a0, uint32_t a1, uint32_t a2, uint32_t a3, uint32_t blo){
  asm volatile("{\n.reg .b64 db;\nmov.b64 db, {%60,8};\nwgmma.mma_async.sync.aligned.m64n112k16.f32.bf16.bf16 {%0, %1, %2, %3, %4, %5, %6, %7, %8, %9, %10, %11, %12, %13, %14, %15, %16, %17, %18, %19, %20, %21, %22, %23, %24, %25, %26, %27, %28, %29, %30, %31, %32, %33, %34, %35, %36, %37, %38, %39, %40, %41, %42, %43, %44, %45, %46, %47, %48, %49, %50, %51, %52, %53, %54, %55}, {%56,%57,%58,%59}, db, 1, 1, 1, 0;\n}\n"
    : "+f"(d[8]), "+f"(d[9]), "+f"(d[10]), "+f"(d[11]), "+f"(d[12]), "+f"(d[13]), "+f"(d[14]), "+f"(d[15]), "+f"(d[16]), "+f"(d[17]), "+f"(d[18]), "+f"(d[19]), "+f"(d[20]), "+f"(d[21]), "+f"(d[22]), "+f"(d[23]), "+f"(d[24]), "+f"(d[25]), "+f"(d[26]), "+f"(d[27]), "+f"(d[28]), "+f"(d[29]), "+f"(d[30]), "+f"(d[31]), "+f"(d[32]), "+f"(d[33]), "+f"(d[34]), "+f"(d[35]), "+f"(d[36]), "+f"(d[37]), "+f"(d[38]), "+f"(d[39]), "+f"(d[40]), "+f"(d[41]), "+f"(d[42]), "+f"(d[43]), "+f"(d[44]), "+f"(d[45]), "+f"(d[46]), "+f"(d[47]), "+f"(d[48]), "+f"(d[49]), "+f"(d[50]), "+f"(d[51]), "+f"(d[52]), "+f"(d[53]), "+f"(d[54]), "+f"(d[55]), "+f"(d[56]), "+f"(d[57]), "+f"(d[58]), "+f"(d[59]), "+f"(d[60]), "+f"(d[61]), "+f"(d[62]), "+f"(d[63])
    : "r"(a0), "r"(a1), "r"(a2), "r"(a3), "r"(blo));
}
template<> __device__ __forceinline__ void wgmma_rs_hi<128>(float (&d)[64], uint32_t a0, uint32_t a1, uint32_t a2, uint32_t a3, uint32_t blo){
  asm volatile("{\n.reg .b64 db;\nmov.b64 db, {%68,8};\nwgmma.mma_async.sync.aligned.m64n128k16.f32.bf16.bf16 {%0, %1, %2, %3, %4, %5, %6, %7, %8, %9, %10, %11, %12, %13, %14, %15, %16, %17, %18, %19, %20, %21, %22, %23, %24, %25, %26, %27, %28, %29, %30, %31, %32, %33, %34, %35, %36, %37, %38, %39, %40, %41, %42, %43, %44, %45, %46, %47, %48, %49, %50, %51, %52, %53, %54, %55, %56, %57, %58, %59, %60, %61, %62, %63}, {%64,%65,%66,%67}, db, 1, 1, 1, 0;\n}\n"
    : "+f"(d[0]), "+f"(d[1]), "+f"(d[2]), "+f"(d[3]), "+f"(d[4]), "+f"(d[5]), "+f"(d[6]), "+f"(d[7]), "+f"(d[8]), "+f"(d[9]), "+f"(d[10]), "+f"(d[11]), "+f"(d[12]), "+f"(d[13]), "+f"(d[14]), "+f"(d[15]), "+f"(d[16]), "+f"(d[17]), "+f"(d[18]), "+f"(d[19]), "+f"(d[20]), "+f"(d[21]), "+f"(d[22]), "+f"(d[23]), "+f"(d[24]), "+f"(d[25]), "+f"(d[26]), "+f"(d[27]), "+f"(d[28]), "+f"(d[29]), "+f"(d[30]), "+f"(d[31]), "+f"(d[32]), "+f"(d[33]), "+f"(d[34]), "+f"(d[35]), "+f"(d[36]), "+f"(d[37]), "+f"(d[38]), "+f"(d[39]), "+f"(d[40]), "+f"(d[41]), "+f"(d[42]), "+f"(d[43]), "+f"(d[44]), "+f"(d[45]), "+f"(d[46]), "+f"(d[47]), "+f"(d[48]), "+f"(d[49]), "+f"(d[50]), "+f"(d[51]), "+f"(d[52]), "+f"(d[53]), "+f"(d[54]), "+f"(d[55]), "+f"(d[56]), "+f"(d[57]), "+f"(d[58]), "+f"(d[59]), "+f"(d[60]), "+f"(d[61]), "+f"(d[62]), "+f"(d[63])
    : "r"(a0), "r"(a1), "r"(a2), "r"(a3), "r"(blo));
}

struct CvCtx {
  uint32_t koff, zero, so[3];
  int srcA, srcB;
  bool wrapA, s3, kodd;
};
struct CvPipe { uint32_t Ap, Ep, keep, send; };
template <int LO> __device__ __forceinline__ void cv_copy(float (&acc)[64]) {
#pragma unroll
  for (int i = LO; i < 64; i++) { float t; asm volatile("mov.b32 %0, %1;" : "=f"(t) : "f"(acc[i]) : "memory"); acc[i] = t; }
}
template <int G> __device__ __forceinline__ void cv_raw(uint32_t (&A)[4][4], uint32_t kaddr) {
#pragma unroll
  for (int i = 0; i < 4; i++) {
    const uint32_t a = kaddr + (4 * G + i) * 128;
    A[i][0] = lds32(a); A[i][1] = lds32(a + 4); A[i][3] = lds32(a + 8);
  }
}
__device__ __forceinline__ void cv_form(uint32_t (&A)[4][4], uint32_t sel) {
#pragma unroll
  for (int i = 0; i < 4; i++) {
    asm volatile("prmt.b32 %0, %0, %1, %2;" : "+r"(A[i][0]) : "r"(A[i][1]), "r"(sel));
    asm volatile("prmt.b32 %0, %1, %2, %3;" : "=r"(A[i][2]) : "r"(A[i][1]), "r"(A[i][3]), "r"(sel));
  }
}
#define CVV 2
template <int G> __device__ __forceinline__ void cv_step(float (&acc)[64], uint32_t (&A)[4][4], CvPipe& s, const CvCtx& c, uint32_t cb, uint32_t stg) {
  constexpr int JA = G - 1, JB = G - 2, NH = CVV == 1 ? 4 : (CVV == 3 ? 2 : 1);
  const uint32_t db0 = desc_lo(cb + CV_U + 192, CV_PL);
  uint32_t B[4][4];
  uint32_t ra[2], rb;
  if constexpr (G < 8) {
    wgmma_fence();
#pragma unroll
    for (int i = 0; i < NH; i++) wgmma_rs_hi<128 - 16 * (G & 7)>(acc, A[i][0], A[i][1], A[i][2], A[i][3], db0 - 4 * i);
    wgmma_commit();
    __syncwarp();
  }
  if constexpr (JA >= 0 && JA < 8) {
    const uint32_t p0 = pack_bf16(acc[8 * JA + 1], acc[8 * JA + 3]), p1 = pack_bf16(acc[8 * JA + 5], acc[8 * JA + 7]);
    ra[0] = __shfl_sync(0xffffffffu, c.wrapA ? s.Ap : p0, c.srcA);
    ra[1] = __shfl_sync(0xffffffffu, c.wrapA ? p0 : p1, c.srcA);
    s.Ap = p1;
  }
  if constexpr (JB >= 0) rb = __shfl_sync(0xffffffffu, s.send, c.srcB);
  if constexpr (G < 7) cv_raw<G + 1>(B, cb + c.koff);
  uint32_t z = 0;
  if constexpr (G < 8 && NH < 4) {
    __syncwarp();
    wgmma_fence();
#pragma unroll
    for (int i = NH; i < 4; i++) wgmma_rs_hi<128 - 16 * (G & 7)>(acc, A[i][0], A[i][1], A[i][2], A[i][3], db0 - 4 * i);
    wgmma_commit();
    asm volatile("mov.u32 %0, %%clock;" : "=r"(z)::"memory");
    z &= c.zero;
  }
  if constexpr (G < 7) cv_form(B, 0x5432u | z);
  if constexpr (JB >= 0) sts32(stg + ((c.so[JB / 3] >> (10 * (JB % 3))) & 0xffc), hadd2(rb | z, s.keep));
  if constexpr (JA >= 0 && JA < 8) {
    const uint32_t sh = 16 | z, mk = 0xffff0000u | z;
    const uint32_t ev = pack_bf16(acc[8 * JA] + __uint_as_float(ra[0] << sh), acc[8 * JA + 2] + __uint_as_float(ra[0] & mk));
    const uint32_t od = pack_bf16(acc[8 * JA + 4] + __uint_as_float(ra[1] << sh), acc[8 * JA + 6] + __uint_as_float(ra[1] & mk));
    s.send = c.kodd ? ev : (c.s3 ? s.Ep : od);
    s.keep = c.kodd ? od : ev;
    s.Ep = od;
  }
  if constexpr (G < 8) { __syncwarp(); wgmma_wait<0>(); cv_copy<8 * (G & 7)>(acc); }
  if constexpr (G < 9) cv_step<G + 1>(acc, B, s, c, cb, stg);
}
__device__ __forceinline__ uint32_t cv_stage(int slot) { return sb + (slot < 4 ? 40960 + slot * 4096 : CV_OFF + CV_K); }
__device__ __forceinline__ void cv_setup(CvCtx& c) {
  const int tid = tid_opaque() & 127, w = tid >> 5, lane = tid & 31, r = lane >> 2, q = lane & 3;
  const int i0 = (r >> 1) & 1, i1 = r >> 2;
  c.koff = CV_K - 32 + 4 * (8 * (r >> 1) + 2 * w + (r & 1) + 2 * q);
  c.srcA = i0 ? lane - 8 : lane + 8 - q + ((q + 3) & 3);
  c.wrapA = i0 && q == 3;
  c.srcB = i1 == 0 ? (lane - q + 16 + ((q + 3) & 3)) : (lane - q - 16 + ((q + 1) & 3));
  c.s3 = (i1 == 1 && q == 3); c.kodd = (i1 == 1 && q < 3);
  c.zero = lds32(sb + EP_OFF + 24);
#pragma unroll
  for (int i = 0; i < 3; i++) c.so[i] = lds32(sb + SO_OFF + 512 * i + 4 * tid);
}
__device__ __forceinline__ void cv_table() {
  const int tid = tid_opaque() & 127, r = (tid & 31) >> 2, q = tid & 3;
  int t = 16 * (2 * (r < 4 ? q : 4 + ((q + 1) & 3)) + ((r >> 1) & 1)) + 4 * (tid >> 5) + 2 * (r & 1);
#pragma unroll 1
  for (int i = 0; i < 3; i++) {
    uint32_t v = 0;
#pragma unroll 1
    for (int x = 0; x < 3; x++, t += 256) {
      const int T = t / 160, tl = t - T * 160;
      const int qq = (T >= NT1 - 1) ? (tl >> 5) : (tl / 40);
      int ck = 20 * T + ((tl - qq * ((T >= NT1 - 1) ? 32 : 40)) >> 1);
      ck ^= (ck >> 2) & 6;
      v |= (uint32_t)((ck * 4 + qq) & 1023) << (10 * x + 2);
    }
    sts32(sb + SO_OFF + 512 * i + 4 * tid, v);
  }
}
__device__ __forceinline__ void conv_channel(int slot, const CvCtx& c) {
  const uint32_t cb = sb + CV_OFF + slot * CV_B;
  float acc[64];
  CvPipe s;
  s.Ap = s.Ep = 0u;
  uint32_t A[4][4];
#pragma unroll
  for (int i = 0; i < 64; i++) acc[i] = 0.f;
  if (slot == 4) mbar_wait(bars + 8 * B_CVDONE);
  mbar_wait(bars + 8 * (B_CVFULL + slot));
  cv_raw<0>(A, cb + c.koff);
  {
    const uint32_t w0 = lds32(cb + CV_K);
    const uint32_t wp = __byte_perm(pack_bf16(bf_lo(w0) + __uint_as_float(lds32(sb + EP_OFF + 4 * slot)), 0.f), w0, 0x7610);
    if (c.koff == CV_K) A[0][0] = wp;
    if (c.koff == CV_K - 4) A[0][1] = wp;
    if (c.koff == CV_K - 8) A[0][3] = wp;
  }
  cv_form(A, 0x5432u);
  cv_copy<0>(acc);
  cv_step<0>(acc, A, s, c, cb, cv_stage(slot));
  fence_async_smem();
  mbar_arrive(bars + 8 * (B_CVDONE + slot));
}

__device__ __forceinline__ void kv_issue(const Params& p, int c, int m2, int dg) {
  const uint32_t fb = bars + 8 * (B_KV + c);
  mbar_expect_tx(fb, KV_PIECE);
  tma3(sb + KS_OFF + c * KV_PIECE, &p.mK, 160 * dg + 32 * c, 64 * m2 - 3, 0, fb);
  tma3(sb + KS_OFF + c * KV_PIECE + 4864, &p.mV, 160 * dg + 32 * c, 64 * m2 - 1, 0, fb);
}
__device__ __forceinline__ void kv_tile(int m, int c, int y, uint32_t (&o)[4][4]) {
  const int lane = tid_opaque() & 31, tg = lane & 3, pr = 8 * (y ^ (tg >> 1)) + (lane >> 2);
  const uint32_t pb = sb + KS_OFF + c * KV_PIECE + 4 * pr;
  const uint32_t ka = pb + tg * 1216, va = pb + 4864 + tg * 1088 + 64;
  const uint32_t kh = (m == 0 && tg > 0) ? ka - 192 : ka;
  uint32_t kk[19], u[16];
  const float4 t = lds128f(sb + TAP_OFF + 256 * c + 16 * pr);
#pragma unroll
  for (int i = 0; i < 19; i++) { kk[i] = lds32((i < 3 ? kh : ka) + i * 64); if (i >= 3) u[i - 3] = lds32(va + (i - 3) * 64); }
  const uint32_t dst = sb + KS_OFF + c * KV_PIECE + pr * 64 + tg * 16;
  if (y) {
    __syncwarp();
#pragma unroll
    for (int x = 0; x < 4; x++) sts128((dst ^ 512) + x * 1024, make_uint4(o[x][0], o[x][1], o[x][2], o[x][3]));
  }
  const uint32_t w0 = __byte_perm(__float_as_uint(t.x), __float_as_uint(t.z), 0x5410), w1 = __byte_perm(__float_as_uint(t.x), __float_as_uint(t.z), 0x7632);
  const uint32_t w2 = __byte_perm(__float_as_uint(t.y), __float_as_uint(t.w), 0x5410), w3 = __byte_perm(__float_as_uint(t.y), __float_as_uint(t.w), 0x7632);
#pragma unroll
  for (int i = 0; i < 16; i++) {
    uint32_t a = hmul2(kk[i], w3);
    a = hadd2(a, hmul2(kk[i + 1], w2)); a = hadd2(a, hmul2(kk[i + 2], w1)); a = hadd2(a, hmul2(kk[i + 3], w0));
    u[i] = hmul2(a, u[i]);
  }
#pragma unroll
  for (int x = 0; x < 4; x++) {
#pragma unroll
    for (int qq = 0; qq < 4; qq++) o[x][qq] = __byte_perm(u[15 - 4 * qq - (x & 2)], u[14 - 4 * qq - (x & 2)], (x & 1) ? 0x7632 : 0x5410);
    if (y) sts128(dst + x * 1024, make_uint4(o[x][0], o[x][1], o[x][2], o[x][3]));
  }
}
__device__ __forceinline__ void ln_finish(float s1, float s2, float& mean, float& rstd) {
  mean = s1 * (1.f / 640.f);
  const float v = fmaxf(fmaf(-mean, mean, s2 * (1.f / 640.f)), 0.f) + 1e-5f;
  asm("rsqrt.approx.ftz.f32 %0, %1;" : "=f"(rstd) : "f"(v));
}
__device__ __forceinline__ void stat_table(int T1, unsigned want, int l, int g, const uint4* x0, const uint4* x1, float (&xa)[2], float (&xb)[2]) {
  const int n = 32 * g + (tid_opaque() & 31);
  const uint4* rp = &g_stats[8 * l * SEQ + min(160 * T1 + n, SEQ - 1)];
  float a[4], b[4];
  uint32_t it = 0;
  while (true) {
    bool ok = true;
#pragma unroll
    for (int i = 0; i < 4; i++) ok &= (rec_ld(rp + SEQ * i, a[i], b[i]) == want);
    ok &= rec_ld(x0, xa[0], xb[0]) == want;
    ok &= rec_ld(x1, xa[1], xb[1]) == want;
    if (__all_sync(0xffffffffu, ok)) break;
    trap_if(++it > SPIN_LIMIT);
  }
  float m, rs;
  ln_finish((a[0] + a[1]) + (a[2] + a[3]), (b[0] + b[1]) + (b[2] + b[3]), m, rs);
  sts32(sb + STAB_OFF + ((n >> 1) & 3) * 160 + (n >> 3) * 8 + (n & 1) * 4, __float_as_uint(rs));
  const uint32_t hi = pack_bf16(-m, -m);
  const float lo = -m - bf_lo(hi);
  sts128(sb + (l ? MX1_OFF : MX0_OFF) + n * 16, make_uint4(hi, pack_bf16(lo, lo), 0u, 0u));
  fence_async_smem();
}
__device__ __forceinline__ void stats_reduce(float (&a)[2], float (&b)[2], float (&mean)[2], float (&rstd)[2]) {
#pragma unroll
  for (int o = 1; o < 4; o <<= 1)
#pragma unroll
    for (int h = 0; h < 2; h++) { a[h] += __shfl_xor_sync(0xffffffffu, a[h], o); b[h] += __shfl_xor_sync(0xffffffffu, b[h], o); }
#pragma unroll
  for (int h = 0; h < 2; h++) ln_finish(a[h], b[h], mean[h], rstd[h]);
}

template <bool FIRST>
__device__ __forceinline__ void stats_publish(int which, int n0, int dg, unsigned tag, const float (&acc)[80]) {
  const int q = tid_opaque() & 3, h = q & 1;
  float s1[2] = {0.f, 0.f}, s2[2] = {0.f, 0.f}, t1[2] = {0.f, 0.f}, t2[2] = {0.f, 0.f};
#pragma unroll
  for (int j = 0; j < 20; j++)
#pragma unroll
    for (int y = 0; y < 2; y++) {
      const float a = acc[4 * j + 2 * y], b = acc[4 * j + 2 * y + 1];
      s1[y] += a; t1[y] += b; s2[y] = fmaf(a, a, s2[y]); t2[y] = fmaf(b, b, t2[y]);
    }
#pragma unroll
  for (int y = 0; y < 2; y++) { s1[y] += t1[y]; s2[y] += t2[y]; }
  float a = (h ? s1[1] : s1[0]) + __shfl_xor_sync(0xffffffffu, h ? s1[0] : s1[1], 1);
  float b = (h ? s2[1] : s2[0]) + __shfl_xor_sync(0xffffffffu, h ? s2[0] : s2[1], 1);
  a += __shfl_xor_sync(0xffffffffu, a, 2);
  b += __shfl_xor_sync(0xffffffffu, b, 2);
  if (FIRST) {
    rec_st(&g_stats[((q >> 1) * 4 + dg) * SEQ + n0 + 8 * h], a, b, q < 2 ? tag : tag - 1);
    rec_st(&g_stats[((q >> 1) * 4 + 8 + dg) * SEQ + n0 + 8 * h], a, b, tag - 1);
  } else if (q < 2) rec_st(&g_stats[(which * 4 + dg) * SEQ + n0 + 8 * h], a, b, tag);
}
__device__ __forceinline__ void stats_get(int which, int n0, unsigned tag, float (&mean)[2], float (&rstd)[2]) {
  const uint4* p0 = &g_stats[(which * 4 + (tid_opaque() & 3)) * SEQ + n0];
  float a[2], b[2];
  uint32_t it = 0;
  while (true) {
    const unsigned t0 = rec_ld(p0, a[0], b[0]), t1 = rec_ld(p0 + 8, a[1], b[1]);
    if (__all_sync(0xffffffffu, t0 == tag && t1 == tag)) break;
    trap_if(++it > SPIN_LIMIT);
  }
  stats_reduce(a, b, mean, rstd);
}
__device__ __forceinline__ void x0_load(float (&acc)[80]) {
  const int t = tid_opaque() & 127;
  const uint32_t xa = sb + XT_OFF + (16 * (t >> 5) + ((t & 31) >> 2)) * 320 + 8 * (t & 3);
  mbar_wait(bars + 8 * B_XT);
#pragma unroll
  for (int h = 0; h < 2; h++)
#pragma unroll
    for (int J = 0; J < 10; J++) {
      const float2 v = lds64f(xa + h * 2560 + 32 * J);
      const uint32_t x = __float_as_uint(v.x), y = __float_as_uint(v.y);
      acc[8 * J + 2 * h] = bf_lo(x); acc[8 * J + 2 * h + 1] = bf_hi(x);
      acc[8 * J + 4 + 2 * h] = bf_lo(y); acc[8 * J + 4 + 2 * h + 1] = bf_hi(y);
    }
}

template <bool FROM_X0>
__device__ __forceinline__ void dskip_init(float (&acc)[80], const float (&mean)[2], const float (&rstd)[2]) {
  const int t = tid_opaque() & 127;
  const uint32_t xa = sb + XT_OFF + (16 * (t >> 5) + ((t & 31) >> 2)) * 320 + 8 * (t & 3), da = sb + DTAB_OFF + 8 * (t & 3);
  float2 dw[10], xv[10][2];
#pragma unroll
  for (int J = 0; J < 2; J++) { dw[J] = lds64f(da + 32 * J); if (FROM_X0) { xv[J][0] = lds64f(xa + 32 * J); xv[J][1] = lds64f(xa + 2560 + 32 * J); } }
#pragma unroll
  for (int J = 0; J < 10; J++) {
    if (J + 2 < 10) { dw[J + 2] = lds64f(da + 32 * (J + 2)); if (FROM_X0) { xv[J + 2][0] = lds64f(xa + 32 * (J + 2)); xv[J + 2][1] = lds64f(xa + 2560 + 32 * (J + 2)); } }
#pragma unroll
    for (int x = 0; x < 8; x++) {
      const int h = (x >> 1) & 1;
      const uint32_t dwd = __float_as_uint(x < 4 ? dw[J].x : dw[J].y);
      const float tt = fmaf(rstd[h], (x & 1) ? bf_hi(dwd) : bf_lo(dwd), 1.f);
      float a = acc[8 * J + x];
      if (FROM_X0) { const uint32_t xw = __float_as_uint(x < 4 ? xv[J][h].x : xv[J][h].y); a = (x & 1) ? bf_hi(xw) : bf_lo(xw); }
      acc[8 * J + x] = FROM_X0 ? (a - mean[h]) * tt : fmaf(a, tt, -mean[h] * tt);
    }
  }
}

__global__ void __launch_bounds__(512, 1) fused_kernel(const __grid_constant__ Params p) {
  extern __shared__ __align__(1024) uint8_t smem_raw[];
  const int tid = threadIdx.x, lane = tid & 31;
  const int wid = __shfl_sync(0xffffffffu, tid >> 5, 0), wg = wid >> 2;
  unsigned smid; asm volatile("mov.u32 %0, %%smid;" : "=r"(smid));
  const int role = p.role[min(smid, 131u)];
  if (wid == 12) {
    const bool el = elect_one();
    if (el) {
      asm volatile("prefetch.tensormap [%0];" ::"l"(&p.mB) : "memory");
      asm volatile("prefetch.tensormap [%0];" ::"l"((role & 15) == NT1 - 1 ? &p.mXl : &p.mX) : "memory");
#pragma unroll
      for (int k = 0; k < S1; k++) mbar_init(bars + 8 * (B_G1FULL + k), 1);
#pragma unroll
      for (int k = 0; k < 6; k++) mbar_init(bars + 8 * (B_XT + k), 1);
      asm volatile("fence.mbarrier_init.release.cluster;" ::: "memory");
    }
    if (role >= 0) {
      __syncwarp();
      asm volatile("bar.arrive 5, 288;" ::: "memory");
      const Role R = unpack_role(role);
      if (elect_one()) {
        TS(45);
#pragma unroll 1
        for (int k = 0; k < S1; k++) {
          const uint32_t fb = bars + 8 * (B_G1FULL + k);
          mbar_expect_tx(fb, G1_STAGE);
          tma4(sb + k * G1_STAGE + G1_XOFF, R.last ? &p.mXl : &p.mX, 64 * k, 0, 0, R.last ? 0 : 80 * R.T1, fb);
          tma5(sb + k * G1_STAGE, &p.mB, 64 * k, 0, 0, 4 * R.side, 2 * R.GP, fb);
          if (PFD) asm volatile("prefetch.tensormap [%0];" ::"l"(&p.mK + k) : "memory");
        }
        if (R.has2) {
          mbar_expect_tx(bars + 8 * B_XT, 20480);
#pragma unroll 1
          for (int h = 0; h < 2; h++) {
            const int ng = 8 * R.m2 + 4 * h, T = ng / 20;
            tma4(sb + XT_OFF + h * 10240, T == NT1 - 1 ? &p.mXtl : &p.mXt, 160 * R.dg, 0, 0, T == NT1 - 1 ? ng - 240 : ng + 60 * T, bars + 8 * B_XT);
          }
#pragma unroll 1
          for (int c = 0; c < KV0; c++) kv_issue(p, c, R.m2, R.dg);
        }
        TS(44);
      }
      __syncwarp();
      bar_sync(6, 64);
    }
  }
  trap_if(smid >= 132 || smem_u32(smem_raw) != sb);
  if (role < 0) {
    if (wid == 0) {
      const unsigned tag = ld_rlx(g_epoch);
      uint32_t it = 0;
      while (!__all_sync(0xffffffffu, (int)(ld_rlx(&g_hcnt[(lane & 7) * 32]) - 40 * tag) >= 0)) { __nanosleep(500); trap_if(++it > SPIN_LIMIT); }
    }
    return;
  }
  float mean0[2] = {0.f, 0.f}, rstd0[2] = {0.f, 0.f};
  if (wg == 2 || wid == 14) {
    ROLE(role)
    const int c = wid == 14 ? 4 : wid - 8;
    const unsigned tag = ld_rlx(g_epoch);
    if (has2) {
      uint2 bv[2][5];
#pragma unroll
      for (int x = 0; x < 2; x++)
#pragma unroll
        for (int i = 0; i < 5; i++) bv[x][i] = ldv64((const uint2*)((x ? p.bim : p.bre) + (cch0 + 32 * c) * DM) + lane + 32 * i);
      float sv[2];
#pragma unroll
      for (int x = 0; x < 2; x++) {
        float a = 0.f;
#pragma unroll
        for (int i = 0; i < 5; i++) a += (bf_lo(bv[x][i].x) + bf_hi(bv[x][i].x)) + (bf_lo(bv[x][i].y) + bf_hi(bv[x][i].y));
        sv[x] = a;
      }
#pragma unroll
      for (int o = 16; o > 0; o >>= 1) { sv[0] += __shfl_xor_sync(0xffffffffu, sv[0], o); sv[1] += __shfl_xor_sync(0xffffffffu, sv[1], o); }
      if (lane < 2) rec_st(&g_sB[(cch0 + 32 * c) * 2 + lane], sv[0], sv[1], tag);
      if (tid == 256) TS(47);
      __syncwarp();
      bar_sync(8, 192);
      if (wg == 2) {
        float xs[80];
        x0_load(xs);
        stats_publish<true>(0, 64 * m2 + 16 * c + (lane >> 2), dg, tag, xs);
        if (tid == 256) TS(31);
      }
      mbar_wait(bars + 8 * B_EP);
      mbar_wait(bars + 8 * (B_KV + c));
      mbar_wait(bars + 8 * (B_G1DONE + PAUSE_K - 1));
      if (tid == 448) TS(52);
      uint32_t o[4][4] = {};
#pragma unroll 1
      for (int y = 0; y < 2; y++) kv_tile(m2, c, y, o);
      fence_async_smem();
      __syncwarp();
      if (lane == 0) { mbar_arrive(bars + 8 * B_PREP); mbar_arrive(bars + 8 * (B_PD + c)); }
      if (tid == 448) TS(51);
    } else bar_sync(8, 192);
    {
      const uint4* x0 = wg == 2 ? &g_stats[(lane & 3) * SEQ + (has2 ? 64 * m2 : 0) + 16 * c + (lane >> 2)] : &g_sB[(128 * GP + 32 * side + lane) * 2];
      float xa[2], xb[2];
      stat_table(T1, tag, 0, c, x0, x0 + (wg == 2 ? 8 : 128), xa, xb);
      if (wg == 2) stats_reduce(xa, xb, mean0, rstd0);
      else {
#pragma unroll
        for (int i = 0; i < 2; i++) {
          const float ha = bf_lo(pack_bf16(xa[i], 0.f)), hb = bf_lo(pack_bf16(xb[i], 0.f));
          const float pa = __uint_as_float(pack_bf16(ha, xa[i] - ha)), pb = __uint_as_float(pack_bf16(hb, xb[i] - hb));
          sts64f(sb + CTAB_OFF + (32 * i + lane) * 24 + 16, p.swap ? pb : pa, p.swap ? pa : pb);
        }
      }
      mbar_arrive(bars + 8 * B_STAB);
      if (tid == 448) TS(26);
    }
  } else if (wid == 15) {
    ROLE(role)
    const int ch = 128 * GP + 32 * side + lane;
    uint32_t r0 = ldv16(p.lre + ch), r1 = ldv16(p.lim + ch), r2 = ldv16(p.logdt + ch);
    const uint32_t r3 = ldv16(p.lre + ch + 64), r4 = ldv16(p.lim + ch + 64), r5 = ldv16(p.logdt + ch + 64);
#pragma unroll 1
    for (int i = 0; i < 2; i++) {
      const float lr = bf_lo(r0), li = bf_lo(r1);
      const float dt = __bfloat162float(__float2bfloat16_rn(expf(bf_lo(r2))));
      const float mag = expf(dt * lr);
      float sn, cs; sincospif(dt * li * 0.31830988618379067f, &sn, &cs);
      const float ar = mag * cs, ai = mag * sn;
      const float inv = 2.f / (lr * lr + li * li);
      const uint32_t ad = sb + CTAB_OFF + (32 * i + lane) * 24;
      sts64f(ad, ar, ai);
      sts64f(ad + 8, ((ar - 1.f) * lr + ai * li) * inv, (ai * lr - (ar - 1.f) * li) * inv);
      r0 = r3; r1 = r4; r2 = r5;
    }
    if (lane == 0) TS(46);
    __syncwarp();
    bar_sync(7, 64);
    mbar_arrive(bars + 8 * B_CTAB);
  } else if (wid == 13) {
    ROLE(role)
    uint4 tv[3];
    const uint32_t e0 = ld_rlx(g_epoch);
    const uint32_t e1 = ldv16(p.ssmD + min(cch0 + 32 * lane, 639));
    const uint4 dv = ldv128((const uint4*)(p.dskip + 160 * dg) + min(lane, 19));
#pragma unroll
    for (int i = 0; i < 3; i++) tv[i] = ldv128((const uint4*)(p.shiftk + 640 * dg) + min(lane + 32 * i, 79));
    sts128(sb + DTAB_OFF + 16 * min(lane, 19), dv);
#pragma unroll
    for (int i = 0; i < 3; i++) sts128(sb + TAP_OFF + 16 * min(lane + 32 * i, 79), tv[i]);
    if (lane < 7) sts32(sb + EP_OFF + 4 * lane, lane < 5 ? e1 << 16 : (lane == 5 ? e0 : 0u));
    __syncwarp();
    bar_sync(9, 64);
    mbar_arrive(bars + 8 * B_CTAB);
    if (lane == 0) { mbar_arrive(bars + 8 * B_EP); TS(53); }
    if (has2) {
#pragma unroll 1
      for (int i = 0; i < 5; i++) {
        const int c = i == 2 ? 3 : (i == 3 ? 2 : i);
        mbar_wait(bars + 8 * (B_PD + c));
        if (lane == 0) bulk_s2g(g_kv + (dg * 32 + m2) * 20480 + c * 4096, sb + KS_OFF + c * KV_PIECE, 4096);
      }
      if (lane == 0) {
        asm volatile("cp.async.bulk.commit_group;" ::: "memory");
        asm volatile("cp.async.bulk.wait_group 0;" ::: "memory");
        mbar_arrive(bars + 8 * B_PREP2);
        fence_async_global();
      }
      __syncwarp();
      if (lane < 4) red_rel(&g_kvcnt[(dg * 4 + lane) * 32]);
      __syncwarp();
      if (lane == 0) { mbar_arrive(bars + 8 * B_PUB); TS(30); }
    }
  } else if (wid != 12) {
    if (elect_one()) {
      if (wid < 7) {
        const int b0 = wid < 4 ? 4 + 19 * wid : 85 + 21 * (wid - 4), cnt = wid < 4 ? 2 : 1;
#pragma unroll
        for (int i = 0; i < 21; i++) mbar_init(bars + 8 * (b0 + i), cnt);
      } else {
#pragma unroll
        for (int i = 0; i < 12; i++) mbar_init(bars + 8 * (B_CVDONE + i), (i == 5 || i == 6) ? 160 : 128);
        mbar_init(bars + 8 * B_CTAB, 192); mbar_init(bars + 8 * B_PREP, 5); mbar_init(bars + 8 * B_PREP2, 1);
#pragma unroll
        for (int i = 0; i < 5; i++) mbar_init(bars + 8 * (B_PD + i), 1);
      }
      asm volatile("fence.mbarrier_init.release.cluster;" ::: "memory");
    }
    __syncwarp();
    bar_sync(5, 288);
    if (wid == 2) asm volatile("bar.arrive 8, 192;\nbar.arrive 6, 64;\nbar.arrive 9, 64;\nbar.arrive 7, 64;" ::: "memory");
    if (tid == 128) TS(0);
    if (wg == 1) { cv_table(); mbar_arrive(bars + 8 * B_CTAB); }
  }

  if (wid == 12) {
    ROLE(role)
    uint32_t dst = sb;
#pragma unroll 1
    for (int k = S1; k < 10; k++) {
      const uint32_t fb = bars + 8 * (B_G1FULL + k);
      mbar_wait(bars + 8 * (B_G1DONE + k - S1));
      if (elect_one()) {
        mbar_expect_tx(fb, 20480);
        tma4(dst + G1_XOFF, last ? &p.mXl : &p.mX, 64 * k, 0, 0, last ? 0 : 80 * T1, fb);
        mbar_expect_tx(fb, 16384);
        tma5(dst, &p.mB, 64 * k, 0, 0, 4 * side, 2 * GP, fb);
        if (has2 && k - S1 + KV0 < 5) kv_issue(p, k - S1 + KV0, m2, dg);
      }
      dst += G1_STAGE; if (k == 2 * S1 - 1) dst = sb;
    }
  } else if (wid == 15 && (role >> 16)) {
    ROLE(role)
    if (TPF >= 0) {
      mbar_wait(bars + 8 * (B_KV + TPF));
      if (elect_one()) {
#pragma unroll
        for (int c = 0; c < 5; c++) l2_prefetch(p.ssmk + (cch0 + 32 * c) * SEQ, 4096);
        if (CPF) { l2_prefetch(p.cre + (160 * dg + 5 * m2) * DM, 6400); l2_prefetch(p.cim + (160 * dg + 5 * m2) * DM, 6400); }
      }
    }
    mbar_wait(bars + 8 * B_PREP2);
    if (lane < 10) sts128(sb + CV_OFF + (lane >> 1) * CV_B + CV_K - 32 + 16 * (lane & 1), make_uint4(0, 0, 0, 0));
    fence_async_smem();
    __syncwarp();
    const unsigned tag = lds32(sb + EP_OFF + 20);
    if (TAPW) mbar_wait(bars + 8 * B_PUB);
    if (elect_one()) {
#pragma unroll 1
      for (int c = 0; c < 5; c++) {
        if (c == 0) asm volatile("prefetch.tensormap [%0];" ::"l"(&p.mU) : "memory");
        mbar_expect_tx(bars + 8 * (B_CVFULL + c), 4096 + 2 * CV_PL);
        if (c < TAPN) bulk_g2s(sb + CV_OFF + c * CV_B + CV_K, p.ssmk + (cch0 + 32 * c) * SEQ, 4096, bars + 8 * (B_CVFULL + c));
      }
    }
    mbar_wait(bars + 8 * B_PUB);
    cnt_poll(&g_kvcnt[(dg * 4 + (m2 >> 3)) * 32], 32 * tag);
    fence_async_global();
    if (elect_one()) {
      TS(28);
#pragma unroll
      for (int c = 0; c < 5; c++) {
        tma5(sb + CV_OFF + c * CV_B + CV_U, &p.mU, 0, -3, 2 * c, 16 * (m2 & 1) + (m2 >> 1), dg, bars + 8 * (B_CVFULL + c));
        if (c >= TAPN) bulk_g2s(sb + CV_OFF + c * CV_B + CV_K, p.ssmk + (cch0 + 32 * c) * SEQ, 4096, bars + 8 * (B_CVFULL + c));
      }
#pragma unroll
      for (int i = 0; i < 3; i++) asm volatile("prefetch.tensormap [%0];" ::"l"(&p.mCre + i) : "memory");
      TS(54);
    }
    __syncwarp();
  }
  {
    const int w = wid & 3;
    if (wg == 2 && !(role >> 16)) {
      float xa[2], xb[2];
      mbar_wait(bars + 8 * (B_G1FULL + 11));
      stat_table(role & 15, lds32(sb + EP_OFF + 20), 1, w, g_stats, g_stats, xa, xb);
      mbar_arrive(bars + 8 * (B_STAB + 1));
    }
#pragma unroll 1
    for (int l = 0; l < 2; l++) {
      if (wg < 2) {
        float acc[80];
#pragma unroll
        for (int i = 0; i < 80; i++) acc[i] = 0.f;
        ROLE(role)
        const int tid = tid_opaque(), r = (tid & 31) >> 2, q = tid & 3;
        const int ch = 128 * GP + 64 * wg + 32 * side + 8 * w + r;
        const uint32_t ca = sb + CTAB_OFF + (32 * wg + 8 * w + r) * 24;
        float2 lam = make_float2(0.f, 0.f), p8 = lam, p16 = lam, pL = lam, p2L = lam;
        fence_regs(acc);
        {
          const uint32_t alo0 = (l == 0 ? desc_lo(sb, 16) : desc_lo(sb + G2_WOFF, 16)) + wg * 512;
          const uint32_t blo0 = l == 0 ? desc_lo(sb + G1_XOFF, 16) : desc_lo(sb + X1_OFF, 128);
          const uint32_t bhi = l == 0 ? desc_hi(1024, 1) : desc_hi(1024, 0), xstep = l == 0 ? 2 : 16;
          const uint32_t astep = l == 0 ? G1_STAGE >> 4 : 1024, bstep = l == 0 ? G1_STAGE >> 4 : 1280, aend = alo0 + (S1 + l) * astep;
          uint32_t alo = alo0, blo = blo0;
          uint32_t fb = bars + 8 * (B_G1FULL + 10 * l);
          mbar_wait(fb);
          if (tid == 0) TS(1 + 8 * l);
#pragma unroll 1
          for (int k = 0; k < 10; k++) {
            uint32_t ok; const uint32_t nb = k < 9 ? fb + 8 : fb;
            wgmma_fence();
#pragma unroll
            for (int kk = 0; kk < 4; kk++) {
              wgmma_n160<0>(acc, alo + kk * 2, desc_hi(1024, 1), blo + kk * xstep, bhi);
              if (kk == 0) ok = mbar_test(nb);
              if (kk == STG_KK && k == 9 && tid == 0) mbar_arrive(bars + 8 * (B_STG + l));
            }
            wgmma_commit();
            alo += astep; blo += bstep;
            if (blo == desc_lo(sb + G_OFF, 128)) blo = desc_lo(sb, 128);
            if (alo == aend) { alo = alo0; blo = blo0; }
            wgmma_wait<1>();
            if (k > 0 && (tid & 127) == 0) mbar_arrive(fb + 8 * (B_G1DONE - B_G1FULL - 1));
            if (!ok) mbar_wait(nb);
            if (k == (l ? MK1 : MK0)) {
              mbar_wait(bars + 8 * (B_STAB + l));
              const float2 sB = lds64f(ca + 16);
              uint32_t a0 = q < 2 ? __float_as_uint(sB.x) : 0u, a1 = q < 2 ? __float_as_uint(sB.y) : 0u, a2 = 0u, a3 = 0u;
              asm volatile("" : "+r"(a0), "+r"(a1), "+r"(a2), "+r"(a3)::"memory");
              wgmma_fence();
              wgmma_rs_n160(acc, a0, a1, a2, a3, l ? desc_lo(sb + MX1_OFF, 0) : desc_lo(sb + MX0_OFF, 0));
              wgmma_commit();
            }
            if (wg == 1 && k == (l ? 8 - STG_D : 9 - STG0)) mbar_wait(bars + 8 * (B_STG + l));
            if (k == 3) {
              mbar_wait(bars + 8 * B_CTAB);
              lam = lds64f(ca);
              if (l == 0 && q < 2) rec_st(&g_E[(q * NT1 + T1) * DM + ch], 0.f, 0.f, lds32(sb + EP_OFF + 20) - 1);
              if (p.swap) lam.y = -lam.y;
              const float2 p2 = cmul(lam, lam), p4 = cmul(p2, p2);
              p8 = cmul(p4, p4); p16 = cmul(p8, p8);
              pL = cmul(p16, p16);
              if (!last) pL = cmul(pL, p8);
              p2L = cmul(pL, pL);
            }
            if (k == PAUSE_K && l == 0 && has2) mbar_wait(bars + 8 * B_PREP);
            fb += 8;
          }
        }
        const unsigned tag = lds32(sb + EP_OFF + 20);
        wgmma_wait<0>();
        fence_regs(acc);
        if ((tid & 127) == 0) { mbar_arrive(bars + 8 * (B_G1DONE + 10 * l + 9)); TS(wg ? 17 + l : 2 + 8 * l); }
        float2 ec[3];
#pragma unroll
        for (int jj = 0; jj < 4; jj++)
#pragma unroll
          for (int y = 0; y < 3; y++) {
            if (y == 2 && (jj & 1)) continue;
            const int j = y == 2 ? 16 + jj : 8 * y + 2 * jj;
            const float4 st = lds128f(sb + STAB_OFF + q * 160 + j * 8);
            const float rs[4] = {st.x, st.y, st.z, st.w};
#pragma unroll
            for (int x = 0; x < 4; x++) {
              const int i = 4 * j + 4 * (x >> 1) + (x & 1);
              acc[i] *= rs[x]; acc[i + 2] *= rs[x];
              ec[y] = (jj == 0 && x == 0) ? make_float2(acc[i], acc[i + 2]) : cfma(lam, ec[y], make_float2(acc[i], acc[i + 2]));
            }
          }
        float2 e = cfma(p16, ec[0], ec[1]);
        if (!last) e = cfma(p8, e, ec[2]);
        {
          float2 v = make_float2(__shfl_up_sync(0xffffffffu, e.x, 1, 4), __shfl_up_sync(0xffffffffu, e.y, 1, 4));
          if (q >= 1) e = cfma(pL, v, e);
          v = make_float2(__shfl_up_sync(0xffffffffu, e.x, 2, 4), __shfl_up_sync(0xffffffffu, e.y, 2, 4));
          if (q >= 2) e = cfma(p2L, v, e);
        }
        if (!last && q == 3) rec_st(&g_E[(l * NT1 + T1) * DM + ch], e.x, e.y, tag);
        if (tid == 0) TS(3 + 8 * l);
        float2 ex = make_float2(__shfl_up_sync(0xffffffffu, e.x, 1, 4), __shfl_up_sync(0xffffffffu, e.y, 1, 4));
        if (q == 0) ex = make_float2(0.f, 0.f);
        const float2 coef = lds64f(ca + 8), lamc = make_float2(lam.x, p.swap ? lam.y : -lam.y);
        float m00 = coef.x, m01 = -coef.y, m10 = -coef.y, m11 = -coef.x;
        if (p.swap) { m00 = -coef.y; m01 = coef.x; m10 = -coef.x; m11 = -coef.y; }
        float2 pLq, p160q, p640;
        {
          const float2 p80 = last ? cmul(p2L, p16) : p2L, p160 = cmul(p80, p80), p320 = cmul(p160, p160), one = make_float2(1.f, 0.f);
          p640 = cmul(p320, p320);
          pLq = cmul((q & 1) ? pL : one, (q & 2) ? p2L : one);
          p160q = cmul((q & 1) ? p160 : one, (q & 2) ? p320 : one);
        }
        float2 c, ev[3];
        unsigned tg[3];
        const uint4* ep = &g_E[(l * NT1 + T1 - 1 - q) * DM + ch];
#pragma unroll
        for (int j = 0; j < 20; j++) {
          if (j == CPOLL) {
#pragma unroll
            for (int i = 0; i < 3; i++) {
              ev[i] = make_float2(0.f, 0.f); tg[i] = tag;
              if (T1 - 1 - q - 4 * i >= 0) tg[i] = rec_ld(ep - 4 * i * DM, ev[i].x, ev[i].y);
            }
          }
#pragma unroll
          for (int x = 0; x < 2; x++) {
            const float b0 = acc[4 * j + x], b1 = acc[4 * j + 2 + x];
            acc[4 * j + x] = fmaf(b0, m00, b1 * m01);
            acc[4 * j + 2 + x] = fmaf(b0, m10, b1 * m11);
          }
          if (j == CPOLL - 1 || j == 19) asm volatile("" : "+f"(acc[4 * j]), "+f"(acc[4 * j + 1]), "+f"(acc[4 * j + 2]), "+f"(acc[4 * j + 3])::"memory");
        }
        {
          uint32_t it = 0;
          while (__any_sync(0xffffffffu, tg[0] != tag || tg[1] != tag || tg[2] != tag)) {
#pragma unroll
            for (int i = 0; i < 3; i++)
              if (tg[i] != tag) tg[i] = rec_ld(ep - 4 * i * DM, ev[i].x, ev[i].y);
            trap_if(++it > SPIN_LIMIT);
          }
          c = cfma(p640, cfma(p640, ev[2], ev[1]), ev[0]);
          c = cmul(c, p160q);
          c.x += __shfl_xor_sync(0xffffffffu, c.x, 1); c.y += __shfl_xor_sync(0xffffffffu, c.y, 1);
          c.x += __shfl_xor_sync(0xffffffffu, c.x, 2); c.y += __shfl_xor_sync(0xffffffffu, c.y, 2);
        }
        if (tid == 0) TS(4 + 8 * l);
        if (wg == 1 && l >= HOLD0) mbar_wait(bars + 8 * (B_REL + l));
        const uint32_t c0 = (uint32_t)clock();
        c = cfma(pLq, c, ex);
        float2 hh = make_float2(fmaf(c.x, m00, c.y * m01), fmaf(c.x, m10, c.y * m11));
        uint8_t* hb = g_h + (size_t)l * (32 * 20 * 8192) + (10 * wg + 2 * GP) * 8192 + (4 * side + w) * 1024 + (tid_opaque() & 31) * 4;
#pragma unroll
        for (int j4 = 0; j4 < 5; j4++) {
          if (PACE && j4 > 0 && wg == 1 && l == 1) { while (__any_sync(0xffffffffu, (uint32_t)clock() - c0 < PACE * j4)) {} }
          const int ng = 20 * T1 + 4 * j4;
          uint8_t* hp = hb + (size_t)(ng >> 3) * 163840 + (ng & 7) * 128;
#pragma unroll
          for (int jj = 0; jj < 4; jj++) {
            const int j = 4 * j4 + jj;
            const float2 h0 = cfma(lamc, hh, make_float2(acc[4 * j + 0], acc[4 * j + 2]));
            hh = cfma(lamc, h0, make_float2(acc[4 * j + 1], acc[4 * j + 3]));
            if (j4 < 4 || !last) {
              *(uint32_t*)(hp + jj * 128) = pack_bf16(h0.x, hh.x);
              *(uint32_t*)(hp + jj * 128 + 8192) = pack_bf16(h0.y, hh.y);
            }
          }
        }
        mbar_arrive(bars + 8 * (B_HST + 2 * l + wg));
        if (tid == 0) TS(5 + 8 * l);
        if (tid == 128) TS(l ? 25 : 19);
        if (!REL3 && l == 0 && wid == 4) {
          mbar_wait(bars + 8 * B_HST);
          mbar_wait(bars + 8 * (B_HST + 1));
          if ((tid & 31) < 8) h_release((tid >> 2) & 1, T1, tid & 3);
          __syncwarp();
          if (tid == 128) { mbar_arrive(bars + 8 * B_REL); TS(6); }
        }
      }
      if (l == 0) {
        ROLE(role)
        if (has2) {
          CvCtx cc;
          mbar_wait(bars + 8 * B_CTAB);
          cv_setup(cc);
          mbar_wait(bars + 8 * (B_G1DONE + 9));
#pragma unroll 1
          for (int c = (wg + 2) & 3; c < 5; c += 4) conv_channel(c, cc);
          if ((tid & 127) == 0) TS(wg == 2 ? 32 : (wg == 3 ? 50 : 7 + wg));
        }
      }
      if (wg >= 2) break;
    }
    if (wg == 3) {
    ROLE(role)
    const int pw = wid & 3, gpc = 2 * min(m2 >> 3, 3) + (dg >> 1);
    mbar_wait(bars + 8 * B_EP);
    const unsigned tag = lds32(sb + EP_OFF + 20);
    if (pw == 0) {
      if (elect_one()) {
#pragma unroll 1
        for (int l = 0; l < 2; l++) {
          uint32_t dst = sb;
          if (l == 1) {
            dst = sb + G2_WOFF;
#pragma unroll 1
            for (int k = 0; k < 10; k++) {
              mbar_wait(k > 4 ? bars + 8 * (B_G1DONE + 5 + k) : (has2 ? bars + 8 * (B_G2DONE + 14 + min(k, 3)) : bars + 8 * (B_G1DONE + 9)));
              mbar_expect_tx(bars + 8 * (B_G1FULL + 10 + k), 16384);
              tma5(dst, &p.mB, 64 * k, 0, 0, 4 * side, 2 * GP, bars + 8 * (B_G1FULL + 10 + k));
              dst += 16384; if (k == 4) dst = sb + G2_WOFF;
            }
          }
          if (has2) {
            const uint32_t fb2 = bars + 8 * (B_G2FULL + 20 * l), wb2 = bars + 8 * (B_G2DONE + 20 * l - S2);
            dst = sb + G2_WOFF + (WTAIL ? 4 * l * G2_WB : 0);
            int kc = 0;
#pragma unroll 1
            for (int k = 0; k < 20; k++) {
              mbar_wait(k >= S2 ? wb2 + 8 * k : bars + 8 * (l ? B_G1DONE + (WTAIL ? (k < 3 ? 15 + k : 13 + k) : 19) : (k == 5 ? B_XFREE : (k == 6 ? B_SFREE : B_REL))));
              mbar_expect_tx(fb2 + 8 * k, G2_WB);
              tma5(dst, &p.mCre + (k & 1), kc, 0, 0, 0, 10 * dg, fb2 + 8 * k);
              kc += (k & 1) << 7; if (k == 9) kc = 64;
              dst += G2_WB; if (dst == sb + G2_WOFF + S2 * G2_WB) dst = sb + G2_WOFF;
            }
          }
        }
      }
    } else if (pw == 1) {
#pragma unroll 1
      for (int l = 0; l < 2; l++) {
        if (l == 1) {
          mbar_wait(bars + 8 * (has2 ? B_G2DONE + 19 : B_G1DONE + 9));
          if (has2) mbar_wait(bars + 8 * B_UST);
          cnt_poll(&g_ucnt[gpc * 32], 128 * tag);
          fence_async_global();
          if (elect_one()) {
            TS(20);
            const int bytes = last ? 16384 : 20480;
            const uint8_t* src = g_u + T1 * 204800;
            uint32_t dst = sb + X1_OFF;
#pragma unroll 1
            for (int k = 0; k < 10; k++) {
              if (k > 4) mbar_wait(bars + 8 * (B_G1DONE + 5 + k));
              mbar_expect_tx(bars + 8 * (B_G1FULL + 10 + k), bytes);
              bulk_g2s(dst, src, bytes, bars + 8 * (B_G1FULL + 10 + k));
              src += 20480; dst += 20480; if (dst == sb + G_OFF) dst = sb; if (k == 4) dst = sb + X1_OFF;
            }
          }
          __syncwarp();
        }
        if (has2) {
          mbar_wait(bars + 8 * (B_HST + 2 * l));
          mbar_wait(bars + 8 * (B_G1DONE + 10 * l + 9));
          cnt_poll(&g_hcnt[(l * 16 + gpc) * 32], 40 * tag);
          fence_async_global();
          if (elect_one()) {
            TS(21 + 2 * l);
            const uint32_t fb2 = bars + 8 * (B_G2FULL + 20 * l), wb2 = bars + 8 * (B_G2DONE + 20 * l - S2);
            const uint8_t* src = g_h + (l * 32 + m2) * 163840;
            uint32_t dst = sb;
#pragma unroll 1
            for (int k = 0; k < 20; k++) {
              if (k >= (l ? XB0 : 5)) mbar_wait(k >= S2 ? wb2 + 8 * k : (l ? fb2 + 8 * (k - XB0) : bars + 8 * B_SFREE));
              if (k == 10) { mbar_wait(bars + 8 * (B_H1 + l)); fence_async_global(); }
              mbar_expect_tx(fb2 + 8 * k, G2_XB);
              bulk_g2s(dst, src, G2_XB, fb2 + 8 * k);
              src += 8192; dst += G2_XB; if (dst == sb + S2 * G2_XB) dst = sb;
            }
          }
          __syncwarp();
        }
      }
    } else if (pw == 2) {
#pragma unroll 1
      for (int l = 0; l < 2; l++) {
        if (l == 1) {
          float xa[2], xb[2];
          mbar_wait(bars + 8 * (B_G1FULL + 11));
          stat_table(T1, tag, 1, 4, g_stats, g_stats, xa, xb);
          mbar_arrive(bars + 8 * (B_STAB + 1));
        }
        if (REL3 && l == 0) {
          mbar_wait(bars + 8 * B_HST);
          mbar_wait(bars + 8 * (B_HST + 1));
          if (lane < 8) h_release(lane >> 2, T1, lane & 3);
          __syncwarp();
          if (lane == 0) { mbar_arrive(bars + 8 * B_REL); TS(6); }
        }
#pragma unroll 1
        for (int w = 0; w < 2 * l; w++) {
          mbar_wait(bars + 8 * (B_HST + 2 + w));
          if (lane < 4) h_release(2 + w, T1, lane);
          __syncwarp();
          if (lane == 0) { if (w == 0) mbar_arrive(bars + 8 * (B_REL + 1)); TS(w ? 16 : 14); }
        }
        if (l == 0 && has2 && elect_one()) {
#pragma unroll 1
          for (int i = 0; i < 5; i++) {
            const int c = i < 3 ? i : 7 - i;
            mbar_wait(bars + 8 * (B_CVDONE + c));
            bulk_s2g(g_G + (cch0 + 32 * c) * 4096, cv_stage(c), 4096);
          }
          asm volatile("cp.async.bulk.commit_group;" ::: "memory");
          asm volatile("cp.async.bulk.wait_group.read 0;" ::: "memory");
          mbar_arrive(bars + 8 * B_SFREE);
          asm volatile("cp.async.bulk.wait_group 0;" ::: "memory");
          TS(48);
          fence_async_global();
          asm volatile("fence.acq_rel.gpu;" ::: "memory");
#pragma unroll
          for (int i = 0; i < 4; i++) red_rlx(&g_gcnt[(dg * 4 + i) * 32]);
          TS(49);
          mbar_arrive(bars + 8 * (B_GO + 1));
        }
        __syncwarp();
      }
    } else if (has2) {
      mbar_wait(bars + 8 * B_REL);
      if (!CPF && elect_one()) {
        l2_prefetch(p.cre + (160 * dg + 5 * m2) * DM, 6400); l2_prefetch(p.cim + (160 * dg + 5 * m2) * DM, 6400);
      }
      mbar_wait(bars + 8 * (B_HST + 1));
      flag_poll(&g_hcnt[(8 + gpc) * 32], 40 * tag);
      if (lane == 0) { mbar_arrive(bars + 8 * B_H1); TS(22); }
      mbar_wait(bars + 8 * (B_GO + 1));
      flag_poll(&g_gcnt[(dg * 4 + (m2 >> 3)) * 32], 32 * tag);
      fence_async_global();
      if (elect_one()) {
        TS(29);
        mbar_expect_tx(bars + 8 * B_GFULL, 20480);
        tma5(sb + G_OFF, &p.mG, 64 * m2, 0, 0, 0, 10 * dg, bars + 8 * B_GFULL);
      }
      mbar_wait(bars + 8 * (B_HST + 3));
      cnt_poll(&g_hcnt[(24 + gpc) * 32], 40 * tag);
      if (lane == 0) { mbar_arrive(bars + 8 * (B_H1 + 1)); TS(24); }
    }
    } else if (wg == 2 && (role >> 16)) {
      float acc[80];
      float off[2] = {mean0[0], mean0[1]};
      const unsigned tag = lds32(sb + EP_OFF + 20);
      dskip_init<true>(acc, mean0, rstd0);
      mbar_arrive(bars + 8 * B_XFREE);
#pragma unroll 1
      for (int step = 1; step < 4; step++) {
        const int l = step >> 1;
        if (step != 2) {
          uint32_t alo = desc_lo(sb, 1024), blo = desc_lo(sb + G2_WOFF, 16) + (WTAIL ? l * (G2_WB >> 2) : 0);
          uint32_t fb = bars + 8 * (B_G2FULL + 20 * l);
          fence_regs(acc);
          mbar_wait(bars + 8 * (B_CVDONE + 2));
          mbar_wait(bars + 8 * (B_CVDONE + 3));
          mbar_wait(fb);
          if (tid == 256) TS(33 + 6 * l);
#pragma unroll 1
          for (int k = 0; k < 20; k++) {
            if (l == TSL && (k & 3) == 3 && tid == 256) TS(56 + (k >> 2));
            uint32_t ok; const uint32_t nb = k < 19 ? fb + 8 : fb;
            wgmma_fence();
#pragma unroll
            for (int kk = 0; kk < 4; kk++) {
              wgmma_n160<1>(acc, alo + kk * 128, desc_hi(128, 0), blo + kk * 2, desc_hi(1024, 1));
              if (kk == 0) ok = mbar_test(nb);
            }
            wgmma_commit();
            alo += G2_XB >> 4; blo += G2_WB >> 4;
            if (alo == desc_lo(sb + S2 * G2_XB, 1024)) alo = desc_lo(sb, 1024);
            if (blo == desc_lo(sb + G_OFF, 16)) blo = desc_lo(sb + G2_WOFF, 16);
            wgmma_wait<1>();
            if (k > 0 && tid == 256) mbar_arrive(fb + 8 * (B_G2DONE - B_G2FULL - 1));
            if (!ok) mbar_wait(nb);
            fb += 8;
          }
          wgmma_wait<0>();
          fence_regs(acc);
          if (tid == 256) TS(34 + 6 * l);
          if (tid == 256) mbar_arrive(bars + 8 * (B_G2DONE + 20 * l + 19));
        }
        ROLE(role)
        const int tq = tid_opaque() & 31, n0 = 64 * m2 + 16 * w + (tq >> 2);
#pragma unroll 1
        for (int rep = 0;; rep++) {
          stats_publish<false>(step, n0, dg, tag, acc);
          if (step != 2 || rep == 1) break;
          for (int n = tid & 127; n < 160; n += 128) {
            const int d = 16 * (n >> 4) + 4 * ((n >> 1) & 3) + 2 * ((n >> 3) & 1) + (n & 1);
            const uint32_t dw = lds32(sb + DTAB_OFF + 2 * (d & ~1)), dd = __byte_perm(dw, dw, (d & 1) ? 0x3232 : 0x1010);
            sts128(sb + DX_OFF + 16 * n, make_uint4(dd, dd, dd, dd));
          }
          mbar_wait(bars + 8 * (B_G1FULL + 11));
          float xa[2], xb[2];
          stat_table(T1, tag, 1, w, g_stats, g_stats, xa, xb);
          mbar_arrive(bars + 8 * (B_STAB + 1));
          if (tid == 256) TS(27);
          mbar_wait(bars + 8 * (B_HST + 2));
          if (!REP2) break;
        }
        uint32_t gf[10][4];
        mbar_wait(bars + 8 * B_GFULL);
        uint32_t ga = sb + G_OFF + (8 * (tq >> 4) + (tq & 7)) * 128 + (((2 * w + ((tq >> 3) & 1)) ^ ((2 * m2) & 6) ^ (tq & 7)) << 4), gstep = 2048;
        if (step == 2) { ga = sb + DX_OFF + (8 * (tq >> 4) + (tq & 7)) * 16; gstep = 256; }
#pragma unroll
        for (int J = 0; J < 2; J++) ldsm4t(gf[J], ga + J * gstep);
        if (tid == 256) TS(35 + 6 * l);
        uint8_t* dst[2][2];
#pragma unroll
        for (int h = 0; h < 2; h++) {
          if (l == 0) {
            const int ng = 8 * m2 + 2 * w + h, T = ng / 20;
            uint8_t* ub = g_u + (T * 204800 + (ng - 20 * T) * 1024 + (tq & 2) * 64 + (tq & 28) * 4 + (tq & 1) * 8 + (5 * dg >> 1) * 20480);
            dst[h][1] = ub + ((dg & 1) ? 20480 - 512 : 0);
            dst[h][0] = ub + (dg & 1) * 512;
          } else {
            dst[h][0] = dst[h][1] = (uint8_t*)(p.out + (n_to_t(n0 + 8 * h) * DM + 160 * dg + 4 * (tq & 3)));
          }
        }
        float mean[2], rstd[2];
        stats_get(step, n0, tag, mean, rstd);
        if (tid == 256) TS(36 + 6 * l);
        off[0] += mean[0]; off[1] += mean[1];
        const float ov[2] = {step == 3 ? off[0] : 0.f, step == 3 ? off[1] : 0.f};
#pragma unroll
        for (int J = 0; J < 10; J++) {
          if (J + 2 < 10) ldsm4t(gf[J + 2 < 10 ? J + 2 : 0], ga + (J + 2) * gstep);
#pragma unroll
          for (int x = 0; x < 8; x++) {
            const int h = (x >> 1) & 1;
            const uint32_t gwd = gf[J][x >> 1];
            const float t = fmaf(rstd[h], (x & 1) ? bf_hi(gwd) : bf_lo(gwd), 1.f);
            acc[8 * J + x] = fmaf(acc[8 * J + x], t, fmaf(-mean[h], t, ov[h]));
          }
#pragma unroll
          for (int h = 0; h < 2; h++) {
            if (step == 1)
              *(uint2*)(dst[h][(J >> 1) & 1] + (J >> 2) * 20480 + (J & 3) * 256) =
                  make_uint2(pack_bf16(acc[8 * J + 2 * h], acc[8 * J + 2 * h + 1]), pack_bf16(acc[8 * J + 4 + 2 * h], acc[8 * J + 5 + 2 * h]));
            if (step == 3)
              *(float4*)(dst[h][0] + 64 * J) = make_float4(acc[8 * J + 2 * h], acc[8 * J + 2 * h + 1], acc[8 * J + 4 + 2 * h], acc[8 * J + 5 + 2 * h]);
          }
          __syncwarp();
        }
        if (step == 1) {
          bar_sync(3, 128);
          if (tid == 288) { TS(37); mbar_arrive(bars + 8 * B_UST); }
          if (tid < 264) red_rel(&g_ucnt[(tid & 7) * 32]);
          __syncwarp();
          if (tid == 256) TS(38);
        } else if (step == 3) {
          if (tid == 256) {
            TS(43);
            if (m2 == 31 && dg == 3) asm volatile("st.relaxed.gpu.global.u32 [%0], %1;" ::"l"(g_epoch), "r"(tag + 1) : "memory");
          }
        }
      }
    }
  }
}

typedef CUresult (*EncFn)(CUtensorMap*, CUtensorMapDataType, cuuint32_t, void*, const cuuint64_t*, const cuuint64_t*,
                          const cuuint32_t*, const cuuint32_t*, CUtensorMapInterleave, CUtensorMapSwizzle,
                          CUtensorMapL2promotion, CUtensorMapFloatOOBfill);

void encode(EncFn fn, CUtensorMap* m, const void* ptr, int rank, const cuuint64_t* dims, const cuuint64_t* strides, const cuuint32_t* box,
            CUtensorMapSwizzle swz = CU_TENSOR_MAP_SWIZZLE_128B, int prom = 2) {
  cuuint32_t es[5] = {1, 1, 1, 1, 1};
  fn(m, CU_TENSOR_MAP_DATA_TYPE_BFLOAT16, rank, (void*)ptr, dims, strides, box, es, CU_TENSOR_MAP_INTERLEAVE_NONE,
     swz, (CUtensorMapL2promotion)prom, CU_TENSOR_MAP_FLOAT_OOB_FILL_NONE);
}

}

extern "C" void kernel_launch(void* const* d_in, const int* in_sizes, int n_in, void* d_out, int out_size) {
  (void)in_sizes; (void)n_in; (void)out_size;
  Params p;
  typedef const __nv_bfloat16* BP;
  p.x = (BP)d_in[0]; p.lre = (BP)d_in[1]; p.lim = (BP)d_in[2]; p.bre = (BP)d_in[3]; p.bim = (BP)d_in[4];
  p.cre = (BP)d_in[5]; p.cim = (BP)d_in[6]; p.logdt = (BP)d_in[7]; p.dskip = (BP)d_in[8];
  p.k = (BP)d_in[10]; p.v = (BP)d_in[11]; p.shiftk = (BP)d_in[12]; p.ssmk = (BP)d_in[13]; p.ssmD = (BP)d_in[14];
  p.out = (float*)d_out;
  for (int sm = 0; sm < 132; sm++) {
    const int tpc = sm >> 1, side = sm & 1;
    int gpc, gi;
    if (tpc < 32) { gpc = tpc & 7; gi = tpc >> 3; }
    else if (tpc < 60) { gpc = 1 + (tpc - 32) % 7; gi = 4 + (tpc - 32) / 7; }
    else if (tpc < 62) { gpc = tpc - 54; gi = 8; }
    else { gpc = 0; gi = tpc - 58; }
    const int pos = 8 * gpc + gi + (gpc == 7 ? 1 : 0);
    int T1, GP;
    if (pos < 52) { const int hh = pos / 26, x = pos - 26 * hh; T1 = x >> 1; GP = 2 * hh + (x & 1); }
    else { T1 = pos - 52; GP = 4; }
    const int m2 = 8 * (gpc >> 1) + gi, dg = 2 * (gpc & 1) + side;
    p.role[sm] = pos == 65 ? -1 : (T1 | (GP << 4) | (side << 7) | (m2 << 8) | (dg << 14) | ((gi < 8) << 16));
  }
  void* fnp = nullptr;
  cudaDriverEntryPointQueryResult qr;
  cudaGetDriverEntryPoint("cuTensorMapEncodeTiled", &fnp, cudaEnableDefault, &qr);
  EncFn fn = (EncFn)fnp;
  void* gG = nullptr;
  cudaGetSymbolAddress(&gG, g_G);
  void* gKV = nullptr;
  cudaGetSymbolAddress(&gKV, g_kv);
  {
    cuuint64_t dims[5] = {32, 32, 10, 32, 4}, st[4] = {20480, 2048, 64, 655360}; cuuint32_t box[5] = {32, 35, 2, 1, 1};
    encode(fn, &p.mU, gKV, 5, dims, st, box, CU_TENSOR_MAP_SWIZZLE_NONE, 1);
  }
  const cuuint64_t RB = DM * 2;
  {
    p.swap = p.bim < p.bre;
    const char* lo = (const char*)(p.swap ? p.bim : p.bre); const char* hi = (const char*)(p.swap ? p.bre : p.bim);
    cuuint64_t dims[5] = {640, 8, 2, 8, 10}, st[4] = {RB, (cuuint64_t)(hi - lo), 8 * RB, 64 * RB}; cuuint32_t box[5] = {64, 8, 2, 4, 2};
    encode(fn, &p.mB, lo, 5, dims, st, box);
  }
  {
    cuuint64_t dims[5] = {640, 2, 4, 2, 40}, st[4] = {RB, 4 * RB, 2 * RB, 16 * RB}; cuuint32_t box[5] = {64, 2, 4, 2, 10};
    encode(fn, &p.mCre, p.cre, 5, dims, st, box); encode(fn, &p.mCim, p.cim, 5, dims, st, box);
    cuuint64_t dimg[5] = {2048, 2, 4, 2, 40}, stg[4] = {4096, 4 * 4096, 2 * 4096, 16 * 4096};
    encode(fn, &p.mG, gG, 5, dimg, stg, box);
  }
  {
    cuuint64_t dims[4] = {640, 2, 4, 900}, st[3] = {RB, 40 * RB, 2 * RB}; cuuint32_t box[4] = {64, 2, 4, 20};
    encode(fn, &p.mX, p.x, 4, dims, st, box);
    cuuint64_t diml[4] = {640, 2, 4, 16}, stl[3] = {RB, 32 * RB, 2 * RB};
    encode(fn, &p.mXl, p.x + (size_t)1920 * DM, 4, diml, stl, box);
    cuuint32_t boxt[4] = {160, 2, 4, 4};
    encode(fn, &p.mXt, p.x, 4, dims, st, boxt, CU_TENSOR_MAP_SWIZZLE_NONE);
    encode(fn, &p.mXtl, p.x + (size_t)1920 * DM, 4, diml, stl, boxt, CU_TENSOR_MAP_SWIZZLE_NONE);
    cuuint64_t dk[3] = {640, 2000, 4}, sk[2] = {RB, 16 * RB}; cuuint32_t bk[3] = {32, 19, 4}, bv[3] = {32, 17, 4};
    encode(fn, &p.mK, p.k, 3, dk, sk, bk, CU_TENSOR_MAP_SWIZZLE_NONE);
    encode(fn, &p.mV, p.v, 3, dk, sk, bv, CU_TENSOR_MAP_SWIZZLE_NONE);
  }
  cudaFuncSetAttribute(fused_kernel, cudaFuncAttributeMaxDynamicSharedMemorySize, SMEM_BYTES);
  cudaLaunchConfig_t cfg = {};
  cfg.gridDim = dim3(132); cfg.blockDim = dim3(512); cfg.dynamicSmemBytes = SMEM_BYTES; cfg.stream = cudaStreamPerThread;
  cudaLaunchKernelEx(&cfg, fused_kernel, p);
}
```

```cpp
#include <cuda_runtime.h>
#include <cuda.h>
#include <cuda_bf16.h>
#include <stdint.h>

namespace {

constexpr int SEQ = 2048, DM = 640;
constexpr int NT1 = 13;
#define EXP 0
#define WPF1 3
#define WPF2 7
#define CPOLL 10
#define KV0 1
#define TAPLATE 1
#define STG_D 3
#define STG_KK 1
#define HOLD0 1
#define WREL 0
#define UREL 1
#define TSL 1
#define STG0 2
#define WTAIL 1
#define PFD 1
#define TAPW 0
#define TPF 4
#define CPF 0
#define MK0 7
#define MK1 4
#define PACE 180
#define XB0 3
#define TAPN 2
#define REL3 0
#define REP2 0
#define XLATE 0
#define PAUSE_K 5
constexpr uint32_t SPIN_LIMIT = 1u << 22;

__device__ __align__(1024) uint8_t g_h[2 * 32 * 20 * 8192];
__device__ __align__(1024) uint8_t g_u[NT1 * 10 * 20480];
__device__ __align__(1024) uint8_t g_kv[DM * 4096];
__device__ __align__(1024) uint8_t g_G[DM * 4096];
__device__ __align__(128) uint4 g_E[2 * NT1 * DM];
__device__ __align__(128) uint4 g_stats[4 * 4 * SEQ];
__device__ __align__(128) uint4 g_sB[DM * 2];
__device__ __align__(128) unsigned g_hcnt[2 * 2 * 8 * 32];
__device__ __align__(128) unsigned g_ucnt[8 * 32];
__device__ __align__(128) unsigned g_kvcnt[16 * 32];
__device__ __align__(128) unsigned g_gcnt[16 * 32];
__device__ __align__(128) unsigned g_epoch[32] = {1};
#define TS(i) do {} while (0)

struct Params {
  CUtensorMap mX, mB, mXl, mK, mV, mXt, mXtl, mCre, mCim, mG, mU;
  const __nv_bfloat16 *x, *lre, *lim, *bre, *bim, *cre, *cim, *logdt, *dskip, *k, *v, *shiftk, *ssmk, *ssmD;
  float* out;
  int swap;
  int role[132];
};

constexpr uint32_t sb = 1024;
constexpr uint32_t G1_STAGE = 36864, G1_XOFF = 16384;
constexpr int S1 = 4;
constexpr uint32_t XT_OFF = 159744, KS_OFF = 180224, KV_PIECE = 9216;
constexpr uint32_t G2_XB = 8192, G2_WB = 20480, G2_WOFF = 57344, G_OFF = 200704;
constexpr uint32_t X1_OFF = 139264;
constexpr int S2 = 7;
constexpr uint32_t CV_OFF = KS_OFF, CV_K = 128, CV_PL = 2240, CV_U = CV_K + 4096, CV_B = KV_PIECE;
constexpr uint32_t MISC = 226304;
constexpr uint32_t BAR_OFF = MISC;
constexpr int B_G1FULL = 0, B_G1DONE = 20, B_G2FULL = 40,
              B_G2DONE = 85, B_GFULL = 125, B_EP = 126, B_H1 = 127  , B_CVFULL = 129  , B_STG = 134  , B_REL = 136  , B_SFREE = 138, B_UST = 142,
              B_GO = 139  , B_PUB = 147,
              B_CVDONE = 148  , B_STAB = 153  , B_XFREE = 155, B_HST = 156  ,
              B_CTAB = 160, B_PREP = 161, B_XT = 162, B_KV = 163  , B_PREP2 = 84, B_PD = 168  ;
constexpr uint32_t bars = sb + BAR_OFF;
constexpr uint32_t STAB_OFF = MISC + 1392;
constexpr uint32_t CTAB_OFF = STAB_OFF + 640;
constexpr uint32_t DTAB_OFF = CTAB_OFF + 1536;
constexpr uint32_t EP_OFF = DTAB_OFF + 320;
constexpr uint32_t SO_OFF = EP_OFF + 32;
constexpr uint32_t TAP_OFF = 147456;
constexpr uint32_t MX0_OFF = TAP_OFF + 1280, MX1_OFF = G_OFF + 20480;
constexpr uint32_t DX_OFF = MX1_OFF + 2560;
constexpr uint32_t SMEM_BYTES = 232448;
static_assert(SO_OFF + 1536 <= SMEM_BYTES, "smem");

__device__ __forceinline__ void trap_if(bool c) { asm volatile("{\n.reg .pred p;\nsetp.ne.u32 p, %0, 0;\n@p trap;\n}\n" ::"r"((uint32_t)c)); }
__device__ __forceinline__ uint32_t smem_u32(const void* p) { return (uint32_t)__cvta_generic_to_shared(p); }
__device__ __forceinline__ void mbar_init(uint32_t bar, int cnt) { asm volatile("mbarrier.init.shared::cta.b64 [%0], %1;" ::"r"(bar), "r"(cnt) : "memory"); }
__device__ __forceinline__ void mbar_expect_tx(uint32_t bar, int bytes) { asm volatile("mbarrier.arrive.expect_tx.shared::cta.b64 _, [%0], %1;" ::"r"(bar), "r"(bytes) : "memory"); }
__device__ __forceinline__ void mbar_arrive(uint32_t bar) { asm volatile("mbarrier.arrive.shared::cta.b64 _, [%0];" ::"r"(bar) : "memory"); }
__device__ __forceinline__ void mbar_wait(uint32_t bar) {
  asm volatile(
      "{\n.reg .pred p;\n.reg .u32 c;\nmov.u32 c, 0;\n"
      "W_%=:\nmbarrier.try_wait.parity.shared::cta.b64 p, [%0], 0;\n@p bra D_%=;\n"
      "add.u32 c, c, 1;\nsetp.lt.u32 p, c, %1;\n@p bra W_%=;\ntrap;\nD_%=:\n}\n" ::"r"(bar), "n"(SPIN_LIMIT) : "memory");
}
__device__ __forceinline__ uint32_t mbar_test(uint32_t bar) {
  uint32_t ok;
  asm volatile("{\n.reg .pred p;\nmbarrier.test_wait.parity.shared::cta.b64 p, [%1], 0;\nselp.u32 %0, 1, 0, p;\n}\n" : "=r"(ok) : "r"(bar) : "memory");
  return ok;
}
__device__ __forceinline__ void tma3(uint32_t dst, const CUtensorMap* m, int c0, int c1, int c2, uint32_t bar) {
  asm volatile("cp.async.bulk.tensor.3d.shared::cluster.global.mbarrier::complete_tx::bytes [%0], [%1, {%3,%4,%5}], [%2];"
               ::"r"(dst), "l"(m), "r"(bar), "r"(c0), "r"(c1), "r"(c2) : "memory");
}
__device__ __forceinline__ void tma4(uint32_t dst, const CUtensorMap* m, int c0, int c1, int c2, int c3, uint32_t bar) {
  asm volatile("cp.async.bulk.tensor.4d.shared::cluster.global.mbarrier::complete_tx::bytes [%0], [%1, {%3,%4,%5,%6}], [%2];"
               ::"r"(dst), "l"(m), "r"(bar), "r"(c0), "r"(c1), "r"(c2), "r"(c3) : "memory");
}
__device__ __forceinline__ void tma5(uint32_t dst, const CUtensorMap* m, int c0, int c1, int c2, int c3, int c4, uint32_t bar) {
  asm volatile("cp.async.bulk.tensor.5d.shared::cluster.global.mbarrier::complete_tx::bytes [%0], [%1, {%3,%4,%5,%6,%7}], [%2];"
               ::"r"(dst), "l"(m), "r"(bar), "r"(c0), "r"(c1), "r"(c2), "r"(c3), "r"(c4) : "memory");
}
__device__ __forceinline__ void bulk_g2s(uint32_t dst, const void* src, int bytes, uint32_t bar) {
  asm volatile("cp.async.bulk.shared::cluster.global.mbarrier::complete_tx::bytes [%0], [%1], %2, [%3];"
               ::"r"(dst), "l"(src), "r"(bytes), "r"(bar) : "memory");
}
__device__ __forceinline__ void bulk_s2g(void* dst, uint32_t src, int bytes) {
  asm volatile("cp.async.bulk.global.shared::cta.bulk_group [%0], [%1], %2;" ::"l"(dst), "r"(src), "r"(bytes) : "memory");
}
__device__ __forceinline__ void l2_prefetch(const void* src, int bytes) {
  asm volatile("cp.async.bulk.prefetch.L2.global [%0], %1;" ::"l"(src), "r"(bytes) : "memory");
}
__device__ __forceinline__ void wgmma_fence() { asm volatile("wgmma.fence.sync.aligned;" ::: "memory"); }
__device__ __forceinline__ void wgmma_commit() { asm volatile("wgmma.commit_group.sync.aligned;" ::: "memory"); }
template <int N> __device__ __forceinline__ void wgmma_wait() { asm volatile("wgmma.wait_group.sync.aligned %0;" ::"n"(N) : "memory"); }
__host__ __device__ constexpr uint32_t desc_lo(uint32_t addr, uint32_t lbo) { return ((addr & 0x3FFFF) >> 4) | ((lbo >> 4) << 16); }
__host__ __device__ constexpr uint32_t desc_hi(uint32_t sbo, uint32_t swz) { return (sbo >> 4) | (swz << 30); }
__device__ __forceinline__ void bar_sync(int id, int n) { asm volatile("bar.sync %0, %1;" ::"r"(id), "r"(n) : "memory"); }
__device__ __forceinline__ uint32_t lds32(uint32_t a) { uint32_t v; asm volatile("ld.shared.u32 %0, [%1];" : "=r"(v) : "r"(a) : "memory"); return v; }
__device__ __forceinline__ float2 lds64f(uint32_t a) { float2 v; asm volatile("ld.shared.v2.f32 {%0,%1}, [%2];" : "=f"(v.x), "=f"(v.y) : "r"(a) : "memory"); return v; }
__device__ __forceinline__ float4 lds128f(uint32_t a) { float4 v; asm volatile("ld.shared.v4.f32 {%0,%1,%2,%3}, [%4];" : "=f"(v.x), "=f"(v.y), "=f"(v.z), "=f"(v.w) : "r"(a) : "memory"); return v; }
__device__ __forceinline__ void ldsm4t(uint32_t (&r)[4], uint32_t a) {
  asm volatile("ldmatrix.sync.aligned.m8n8.x4.trans.shared.b16 {%0,%1,%2,%3}, [%4];" : "=r"(r[0]), "=r"(r[1]), "=r"(r[2]), "=r"(r[3]) : "r"(a) : "memory");
}
__device__ __forceinline__ uint4 ldv128(const void* a) { uint4 v; asm volatile("ld.global.nc.v4.u32 {%0,%1,%2,%3}, [%4];" : "=r"(v.x), "=r"(v.y), "=r"(v.z), "=r"(v.w) : "l"(a) : "memory"); return v; }
__device__ __forceinline__ uint2 ldv64(const void* a) { uint2 v; asm volatile("ld.global.nc.v2.u32 {%0,%1}, [%2];" : "=r"(v.x), "=r"(v.y) : "l"(a) : "memory"); return v; }
__device__ __forceinline__ uint32_t ldv16(const void* a) { uint32_t v; asm volatile("ld.global.nc.u16 %0, [%1];" : "=r"(v) : "l"(a) : "memory"); return v; }
__device__ __forceinline__ void sts128(uint32_t a, uint4 v) { asm volatile("st.shared.v4.u32 [%0], {%1,%2,%3,%4};" ::"r"(a), "r"(v.x), "r"(v.y), "r"(v.z), "r"(v.w) : "memory"); }
__device__ __forceinline__ void sts32(uint32_t a, uint32_t v) { asm volatile("st.shared.u32 [%0], %1;" ::"r"(a), "r"(v) : "memory"); }
__device__ __forceinline__ void sts64f(uint32_t a, float x, float y) { asm volatile("st.shared.v2.f32 [%0], {%1,%2};" ::"r"(a), "f"(x), "f"(y) : "memory"); }
__device__ __forceinline__ void red_rlx(unsigned* p) { asm volatile("red.relaxed.gpu.global.add.u32 [%0], 1;" ::"l"(p) : "memory"); }
__device__ __forceinline__ void red_rel(unsigned* p) { asm volatile("red.release.gpu.global.add.u32 [%0], 1;" ::"l"(p) : "memory"); }
__device__ __forceinline__ void fence_async_global() { asm volatile("fence.proxy.async.global;" ::: "memory"); }
__device__ __forceinline__ void fence_async_smem() { asm volatile("fence.proxy.async.shared::cta;" ::: "memory"); }
__device__ __forceinline__ void rec_st(uint4* p, float a, float b, unsigned tag) {
  asm volatile("{\n.reg .b128 t;\n.reg .b64 lo, hi;\nmov.b64 lo, {%1,%2};\nmov.b64 hi, {%3,%3};\nmov.b128 t, {lo,hi};\n"
               "st.relaxed.gpu.global.b128 [%0], t;\n}\n" ::"l"(p), "r"(__float_as_uint(a)), "r"(__float_as_uint(b)), "r"(tag) : "memory");
}
__device__ __forceinline__ unsigned rec_ld(const uint4* p, float& a, float& b) {
  unsigned x, y, t;
  asm volatile("{\n.reg .b128 t;\n.reg .b64 lo, hi;\n.reg .b32 u;\nld.relaxed.gpu.global.b128 t, [%3];\nmov.b128 {lo,hi}, t;\n"
               "mov.b64 {%0,%1}, lo;\nmov.b64 {%2,u}, hi;\n}\n" : "=r"(x), "=r"(y), "=r"(t) : "l"(p) : "memory");
  a = __uint_as_float(x); b = __uint_as_float(y);
  return t;
}
__device__ __forceinline__ unsigned ld_rlx(const unsigned* p) { unsigned v; asm volatile("ld.relaxed.gpu.global.u32 %0, [%1];" : "=r"(v) : "l"(p) : "memory"); return v; }
__device__ __forceinline__ void flag_poll(const unsigned* p, unsigned target) {
  uint32_t it = 0;
  while (!__all_sync(0xffffffffu, (int)(ld_rlx(p) - target) >= 0)) { trap_if(++it > SPIN_LIMIT); }
  asm volatile("fence.acquire.gpu;" ::: "memory");
}
__device__ __forceinline__ void cnt_poll(const unsigned* p, unsigned target) {
  unsigned a = ld_rlx(p); __nanosleep(100);
  unsigned b = ld_rlx(p); __nanosleep(100);
  unsigned c = ld_rlx(p);
  uint32_t it = 0;
  while (true) {
    if (__all_sync(0xffffffffu, (int)(a - target) >= 0)) break;
    a = ld_rlx(p);
    if (__all_sync(0xffffffffu, (int)(b - target) >= 0)) break;
    b = ld_rlx(p);
    if (__all_sync(0xffffffffu, (int)(c - target) >= 0)) break;
    c = ld_rlx(p);
    trap_if(++it > SPIN_LIMIT);
  }
  asm volatile("fence.acquire.gpu;" ::: "memory");
}
__device__ __forceinline__ void h_release(int idx, int T, int i) {
  const int Q = (i & 2) ? (T + 2) / 3 - 1 : T / 3;
  if (Q >= 0 && Q < 4 && ((i & 2) == 0 || T % 3 == 0)) red_rel(&g_hcnt[(idx * 8 + 2 * Q + (i & 1)) * 32]);
}
__device__ __forceinline__ uint32_t pack_bf16(float lo, float hi) {
  uint32_t r; asm("cvt.rn.bf16x2.f32 %0, %1, %2;" : "=r"(r) : "f"(hi), "f"(lo)); return r;
}
__device__ __forceinline__ float bf_lo(uint32_t w) { return __uint_as_float(w << 16); }
__device__ __forceinline__ float bf_hi(uint32_t w) { return __uint_as_float(w & 0xffff0000u); }
__device__ __forceinline__ uint32_t hmul2(uint32_t a, uint32_t b) {
  __nv_bfloat162 r = __hmul2_rn(*(__nv_bfloat162*)&a, *(__nv_bfloat162*)&b); return *(uint32_t*)&r;
}
__device__ __forceinline__ uint32_t hadd2(uint32_t a, uint32_t b) {
  __nv_bfloat162 r = __hadd2_rn(*(__nv_bfloat162*)&a, *(__nv_bfloat162*)&b); return *(uint32_t*)&r;
}
__device__ __forceinline__ float2 cmul(float2 a, float2 b) { return make_float2(a.x * b.x - a.y * b.y, a.x * b.y + a.y * b.x); }
__device__ __forceinline__ float2 cfma(float2 a, float2 b, float2 c) {
  return make_float2(fmaf(a.x, b.x, fmaf(-a.y, b.y, c.x)), fmaf(a.x, b.y, fmaf(a.y, b.x, c.y)));
}
template <int N> __device__ __forceinline__ void fence_regs(float (&a)[N]) {
#pragma unroll
  for (int i = 0; i < N; i++) asm volatile("" : "+f"(a[i])::"memory");
}
__device__ __forceinline__ bool elect_one() {
  uint32_t e; asm volatile("{\n.reg .pred P;\nelect.sync _|P, 0xffffffff;\nselp.u32 %0, 1, 0, P;\n}\n" : "=r"(e)); return e != 0;
}
__device__ __forceinline__ int tid_opaque() { int t; asm volatile("mov.u32 %0, %%tid.x;" : "=r"(t)); return t; }
struct Role { int T1, GP, side, m2, dg, cch0; bool last, has2; };
__device__ __forceinline__ Role unpack_role(int x) {
  Role r; r.T1 = x & 15; r.GP = (x >> 4) & 7; r.side = (x >> 7) & 1; r.m2 = (x >> 8) & 63; r.dg = (x >> 14) & 3;
  r.has2 = (x >> 16) & 1; r.last = r.T1 == NT1 - 1; r.cch0 = 160 * r.dg + r.m2; return r;
}
__device__ __forceinline__ Role fresh_role(int x) { asm volatile("" : "+r"(x)); return unpack_role(__shfl_sync(0xffffffffu, x, 0)); }
#define ROLE(x) const Role R_ = fresh_role(x); const int T1 = R_.T1, GP = R_.GP, side = R_.side, m2 = R_.m2, dg = R_.dg, cch0 = R_.cch0; \
  const bool last = R_.last, has2 = R_.has2; (void)T1; (void)GP; (void)side; (void)m2; (void)dg; (void)cch0; (void)last; (void)has2;
__device__ __forceinline__ int n_to_t(int n) {
  int T = n / 160, nl = n - T * 160;
  int L = (T == NT1 - 1) ? 32 : 40;
  return T * 160 + L * ((nl & 7) >> 1) + 2 * (nl >> 3) + (nl & 1);
}

template<int TA> __device__ __forceinline__ void wgmma_n160(float (&d)[80], uint32_t alo, uint32_t ahi, uint32_t blo, uint32_t bhi){
  asm volatile("{\n.reg .b64 da, db;\nmov.b64 da, {%80,%81};\nmov.b64 db, {%82,%83};\n"
    "wgmma.mma_async.sync.aligned.m64n160k16.f32.bf16.bf16 {%0, %1, %2, %3, %4, %5, %6, %7, %8, %9, %10, %11, %12, %13, %14, %15, %16, %17, %18, %19, %20, %21, %22, %23, %24, %25, %26, %27, %28, %29, %30, %31, %32, %33, %34, %35, %36, %37, %38, %39, %40, %41, %42, %43, %44, %45, %46, %47, %48, %49, %50, %51, %52, %53, %54, %55, %56, %57, %58, %59, %60, %61, %62, %63, %64, %65, %66, %67, %68, %69, %70, %71, %72, %73, %74, %75, %76, %77, %78, %79}, da, db, 1, 1, 1, %84, 0;\n}\n"
    : "+f"(d[0]), "+f"(d[1]), "+f"(d[2]), "+f"(d[3]), "+f"(d[4]), "+f"(d[5]), "+f"(d[6]), "+f"(d[7]), "+f"(d[8]), "+f"(d[9]), "+f"(d[10]), "+f"(d[11]), "+f"(d[12]), "+f"(d[13]), "+f"(d[14]), "+f"(d[15]), "+f"(d[16]), "+f"(d[17]), "+f"(d[18]), "+f"(d[19]), "+f"(d[20]), "+f"(d[21]), "+f"(d[22]), "+f"(d[23]), "+f"(d[24]), "+f"(d[25]), "+f"(d[26]), "+f"(d[27]), "+f"(d[28]), "+f"(d[29]), "+f"(d[30]), "+f"(d[31]), "+f"(d[32]), "+f"(d[33]), "+f"(d[34]), "+f"(d[35]), "+f"(d[36]), "+f"(d[37]), "+f"(d[38]), "+f"(d[39]), "+f"(d[40]), "+f"(d[41]), "+f"(d[42]), "+f"(d[43]), "+f"(d[44]), "+f"(d[45]), "+f"(d[46]), "+f"(d[47]), "+f"(d[48]), "+f"(d[49]), "+f"(d[50]), "+f"(d[51]), "+f"(d[52]), "+f"(d[53]), "+f"(d[54]), "+f"(d[55]), "+f"(d[56]), "+f"(d[57]), "+f"(d[58]), "+f"(d[59]), "+f"(d[60]), "+f"(d[61]), "+f"(d[62]), "+f"(d[63]), "+f"(d[64]), "+f"(d[65]), "+f"(d[66]), "+f"(d[67]), "+f"(d[68]), "+f"(d[69]), "+f"(d[70]), "+f"(d[71]), "+f"(d[72]), "+f"(d[73]), "+f"(d[74]), "+f"(d[75]), "+f"(d[76]), "+f"(d[77]), "+f"(d[78]), "+f"(d[79])
    : "r"(alo), "r"(ahi), "r"(blo), "r"(bhi), "n"(TA));
}
__device__ __forceinline__ void wgmma_rs_n160(float (&d)[80], uint32_t a0, uint32_t a1, uint32_t a2, uint32_t a3, uint32_t blo){
  asm volatile("{\n.reg .b64 db;\nmov.b64 db, {%84,8};\nwgmma.mma_async.sync.aligned.m64n160k16.f32.bf16.bf16 {%0, %1, %2, %3, %4, %5, %6, %7, %8, %9, %10, %11, %12, %13, %14, %15, %16, %17, %18, %19, %20, %21, %22, %23, %24, %25, %26, %27, %28, %29, %30, %31, %32, %33, %34, %35, %36, %37, %38, %39, %40, %41, %42, %43, %44, %45, %46, %47, %48, %49, %50, %51, %52, %53, %54, %55, %56, %57, %58, %59, %60, %61, %62, %63, %64, %65, %66, %67, %68, %69, %70, %71, %72, %73, %74, %75, %76, %77, %78, %79}, {%80,%81,%82,%83}, db, 1, 1, 1, 0;\n}\n"
    : "+f"(d[0]), "+f"(d[1]), "+f"(d[2]), "+f"(d[3]), "+f"(d[4]), "+f"(d[5]), "+f"(d[6]), "+f"(d[7]), "+f"(d[8]), "+f"(d[9]), "+f"(d[10]), "+f"(d[11]), "+f"(d[12]), "+f"(d[13]), "+f"(d[14]), "+f"(d[15]), "+f"(d[16]), "+f"(d[17]), "+f"(d[18]), "+f"(d[19]), "+f"(d[20]), "+f"(d[21]), "+f"(d[22]), "+f"(d[23]), "+f"(d[24]), "+f"(d[25]), "+f"(d[26]), "+f"(d[27]), "+f"(d[28]), "+f"(d[29]), "+f"(d[30]), "+f"(d[31]), "+f"(d[32]), "+f"(d[33]), "+f"(d[34]), "+f"(d[35]), "+f"(d[36]), "+f"(d[37]), "+f"(d[38]), "+f"(d[39]), "+f"(d[40]), "+f"(d[41]), "+f"(d[42]), "+f"(d[43]), "+f"(d[44]), "+f"(d[45]), "+f"(d[46]), "+f"(d[47]), "+f"(d[48]), "+f"(d[49]), "+f"(d[50]), "+f"(d[51]), "+f"(d[52]), "+f"(d[53]), "+f"(d[54]), "+f"(d[55]), "+f"(d[56]), "+f"(d[57]), "+f"(d[58]), "+f"(d[59]), "+f"(d[60]), "+f"(d[61]), "+f"(d[62]), "+f"(d[63]), "+f"(d[64]), "+f"(d[65]), "+f"(d[66]), "+f"(d[67]), "+f"(d[68]), "+f"(d[69]), "+f"(d[70]), "+f"(d[71]), "+f"(d[72]), "+f"(d[73]), "+f"(d[74]), "+f"(d[75]), "+f"(d[76]), "+f"(d[77]), "+f"(d[78]), "+f"(d[79])
    : "r"(a0), "r"(a1), "r"(a2), "r"(a3), "r"(blo));
}
template<int N> __device__ __forceinline__ void wgmma_rs_hi(float (&d)[64], uint32_t a0, uint32_t a1, uint32_t a2, uint32_t a3, uint32_t blo);
template<> __device__ __forceinline__ void wgmma_rs_hi<16>(float (&d)[64], uint32_t a0, uint32_t a1, uint32_t a2, uint32_t a3, uint32_t blo){
  asm volatile("{\n.reg .b64 db;\nmov.b64 db, {%12,8};\nwgmma.mma_async.sync.aligned.m64n16k16.f32.bf16.bf16 {%0, %1, %2, %3, %4, %5, %6, %7}, {%8,%9,%10,%11}, db, 1, 1, 1, 0;\n}\n"
    : "+f"(d[56]), "+f"(d[57]), "+f"(d[58]), "+f"(d[59]), "+f"(d[60]), "+f"(d[61]), "+f"(d[62]), "+f"(d[63])
    : "r"(a0), "r"(a1), "r"(a2), "r"(a3), "r"(blo));
}
template<> __device__ __forceinline__ void wgmma_rs_hi<32>(float (&d)[64], uint32_t a0, uint32_t a1, uint32_t a2, uint32_t a3, uint32_t blo){
  asm volatile("{\n.reg .b64 db;\nmov.b64 db, {%20,8};\nwgmma.mma_async.sync.aligned.m64n32k16.f32.bf16.bf16 {%0, %1, %2, %3, %4, %5, %6, %7, %8, %9, %10, %11, %12, %13, %14, %15}, {%16,%17,%18,%19}, db, 1, 1, 1, 0;\n}\n"
    : "+f"(d[48]), "+f"(d[49]), "+f"(d[50]), "+f"(d[51]), "+f"(d[52]), "+f"(d[53]), "+f"(d[54]), "+f"(d[55]), "+f"(d[56]), "+f"(d[57]), "+f"(d[58]), "+f"(d[59]), "+f"(d[60]), "+f"(d[61]), "+f"(d[62]), "+f"(d[63])
    : "r"(a0), "r"(a1), "r"(a2), "r"(a3), "r"(blo));
}
template<> __device__ __forceinline__ void wgmma_rs_hi<48>(float (&d)[64], uint32_t a0, uint32_t a1, uint32_t a2, uint32_t a3, uint32_t blo){
  asm volatile("{\n.reg .b64 db;\nmov.b64 db, {%28,8};\nwgmma.mma_async.sync.aligned.m64n48k16.f32.bf16.bf16 {%0, %1, %2, %3, %4, %5, %6, %7, %8, %9, %10, %11, %12, %13, %14, %15, %16, %17, %18, %19, %20, %21, %22, %23}, {%24,%25,%26,%27}, db, 1, 1, 1, 0;\n}\n"
    : "+f"(d[40]), "+f"(d[41]), "+f"(d[42]), "+f"(d[43]), "+f"(d[44]), "+f"(d[45]), "+f"(d[46]), "+f"(d[47]), "+f"(d[48]), "+f"(d[49]), "+f"(d[50]), "+f"(d[51]), "+f"(d[52]), "+f"(d[53]), "+f"(d[54]), "+f"(d[55]), "+f"(d[56]), "+f"(d[57]), "+f"(d[58]), "+f"(d[59]), "+f"(d[60]), "+f"(d[61]), "+f"(d[62]), "+f"(d[63])
    : "r"(a0), "r"(a1), "r"(a2), "r"(a3), "r"(blo));
}
template<> __device__ __forceinline__ void wgmma_rs_hi<64>(float (&d)[64], uint32_t a0, uint32_t a1, uint32_t a2, uint32_t a3, uint32_t blo){
  asm volatile("{\n.reg .b64 db;\nmov.b64 db, {%36,8};\nwgmma.mma_async.sync.aligned.m64n64k16.f32.bf16.bf16 {%0, %1, %2, %3, %4, %5, %6, %7, %8, %9, %10, %11, %12, %13, %14, %15, %16, %17, %18, %19, %20, %21, %22, %23, %24, %25, %26, %27, %28, %29, %30, %31}, {%32,%33,%34,%35}, db, 1, 1, 1, 0;\n}\n"
    : "+f"(d[32]), "+f"(d[33]), "+f"(d[34]), "+f"(d[35]), "+f"(d[36]), "+f"(d[37]), "+f"(d[38]), "+f"(d[39]), "+f"(d[40]), "+f"(d[41]), "+f"(d[42]), "+f"(d[43]), "+f"(d[44]), "+f"(d[45]), "+f"(d[46]), "+f"(d[47]), "+f"(d[48]), "+f"(d[49]), "+f"(d[50]), "+f"(d[51]), "+f"(d[52]), "+f"(d[53]), "+f"(d[54]), "+f"(d[55]), "+f"(d[56]), "+f"(d[57]), "+f"(d[58]), "+f"(d[59]), "+f"(d[60]), "+f"(d[61]), "+f"(d[62]), "+f"(d[63])
    : "r"(a0), "r"(a1), "r"(a2), "r"(a3), "r"(blo));
}
template<> __device__ __forceinline__ void wgmma_rs_hi<80>(float (&d)[64], uint32_t a0, uint32_t a1, uint32_t a2, uint32_t a3, uint32_t blo){
  asm volatile("{\n.reg .b64 db;\nmov.b64 db, {%44,8};\nwgmma.mma_async.sync.aligned.m64n80k16.f32.bf16.bf16 {%0, %1, %2, %3, %4, %5, %6, %7, %8, %9, %10, %11, %12, %13, %14, %15, %16, %17, %18, %19, %20, %21, %22, %23, %24, %25, %26, %27, %28, %29, %30, %31, %32, %33, %34, %35, %36, %37, %38, %39}, {%40,%41,%42,%43}, db, 1, 1, 1, 0;\n}\n"
    : "+f"(d[24]), "+f"(d[25]), "+f"(d[26]), "+f"(d[27]), "+f"(d[28]), "+f"(d[29]), "+f"(d[30]), "+f"(d[31]), "+f"(d[32]), "+f"(d[33]), "+f"(d[34]), "+f"(d[35]), "+f"(d[36]), "+f"(d[37]), "+f"(d[38]), "+f"(d[39]), "+f"(d[40]), "+f"(d[41]), "+f"(d[42]), "+f"(d[43]), "+f"(d[44]), "+f"(d[45]), "+f"(d[46]), "+f"(d[47]), "+f"(d[48]), "+f"(d[49]), "+f"(d[50]), "+f"(d[51]), "+f"(d[52]), "+f"(d[53]), "+f"(d[54]), "+f"(d[55]), "+f"(d[56]), "+f"(d[57]), "+f"(d[58]), "+f"(d[59]), "+f"(d[60]), "+f"(d[61]), "+f"(d[62]), "+f"(d[63])
    : "r"(a0), "r"(a1), "r"(a2), "r"(a3), "r"(blo));
}
template<> __device__ __forceinline__ void wgmma_rs_hi<96>(float (&d)[64], uint32_t a0, uint32_t a1, uint32_t a2, uint32_t a3, uint32_t blo){
  asm volatile("{\n.reg .b64 db;\nmov.b64 db, {%52,8};\nwgmma.mma_async.sync.aligned.m64n96k16.f32.bf16.bf16 {%0, %1, %2, %3, %4, %5, %6, %7, %8, %9, %10, %11, %12, %13, %14, %15, %16, %17, %18, %19, %20, %21, %22, %23, %24, %25, %26, %27, %28, %29, %30, %31, %32, %33, %34, %35, %36, %37, %38, %39, %40, %41, %42, %43, %44, %45, %46, %47}, {%48,%49,%50,%51}, db, 1, 1, 1, 0;\n}\n"
    : "+f"(d[16]), "+f"(d[17]), "+f"(d[18]), "+f"(d[19]), "+f"(d[20]), "+f"(d[21]), "+f"(d[22]), "+f"(d[23]), "+f"(d[24]), "+f"(d[25]), "+f"(d[26]), "+f"(d[27]), "+f"(d[28]), "+f"(d[29]), "+f"(d[30]), "+f"(d[31]), "+f"(d[32]), "+f"(d[33]), "+f"(d[34]), "+f"(d[35]), "+f"(d[36]), "+f"(d[37]), "+f"(d[38]), "+f"(d[39]), "+f"(d[40]), "+f"(d[41]), "+f"(d[42]), "+f"(d[43]), "+f"(d[44]), "+f"(d[45]), "+f"(d[46]), "+f"(d[47]), "+f"(d[48]), "+f"(d[49]), "+f"(d[50]), "+f"(d[51]), "+f"(d[52]), "+f"(d[53]), "+f"(d[54]), "+f"(d[55]), "+f"(d[56]), "+f"(d[57]), "+f"(d[58]), "+f"(d[59]), "+f"(d[60]), "+f"(d[61]), "+f"(d[62]), "+f"(d[63])
    : "r"(a0), "r"(a1), "r"(a2), "r"(a3), "r"(blo));
}
template<> __device__ __forceinline__ void wgmma_rs_hi<112>(float (&d)[64], uint32_t a0, uint32_t a1, uint32_t a2, uint32_t a3, uint32_t blo){
  asm volatile("{\n.reg .b64 db;\nmov.b64 db, {%60,8};\nwgmma.mma_async.sync.aligned.m64n112k16.f32.bf16.bf16 {%0, %1, %2, %3, %4, %5, %6, %7, %8, %9, %10, %11, %12, %13, %14, %15, %16, %17, %18, %19, %20, %21, %22, %23, %24, %25, %26, %27, %28, %29, %30, %31, %32, %33, %34, %35, %36, %37, %38, %39, %40, %41, %42, %43, %44, %45, %46, %47, %48, %49, %50, %51, %52, %53, %54, %55}, {%56,%57,%58,%59}, db, 1, 1, 1, 0;\n}\n"
    : "+f"(d[8]), "+f"(d[9]), "+f"(d[10]), "+f"(d[11]), "+f"(d[12]), "+f"(d[13]), "+f"(d[14]), "+f"(d[15]), "+f"(d[16]), "+f"(d[17]), "+f"(d[18]), "+f"(d[19]), "+f"(d[20]), "+f"(d[21]), "+f"(d[22]), "+f"(d[23]), "+f"(d[24]), "+f"(d[25]), "+f"(d[26]), "+f"(d[27]), "+f"(d[28]), "+f"(d[29]), "+f"(d[30]), "+f"(d[31]), "+f"(d[32]), "+f"(d[33]), "+f"(d[34]), "+f"(d[35]), "+f"(d[36]), "+f"(d[37]), "+f"(d[38]), "+f"(d[39]), "+f"(d[40]), "+f"(d[41]), "+f"(d[42]), "+f"(d[43]), "+f"(d[44]), "+f"(d[45]), "+f"(d[46]), "+f"(d[47]), "+f"(d[48]), "+f"(d[49]), "+f"(d[50]), "+f"(d[51]), "+f"(d[52]), "+f"(d[53]), "+f"(d[54]), "+f"(d[55]), "+f"(d[56]), "+f"(d[57]), "+f"(d[58]), "+f"(d[59]), "+f"(d[60]), "+f"(d[61]), "+f"(d[62]), "+f"(d[63])
    : "r"(a0), "r"(a1), "r"(a2), "r"(a3), "r"(blo));
}
template<> __device__ __forceinline__ void wgmma_rs_hi<128>(float (&d)[64], uint32_t a0, uint32_t a1, uint32_t a2, uint32_t a3, uint32_t blo){
  asm volatile("{\n.reg .b64 db;\nmov.b64 db, {%68,8};\nwgmma.mma_async.sync.aligned.m64n128k16.f32.bf16.bf16 {%0, %1, %2, %3, %4, %5, %6, %7, %8, %9, %10, %11, %12, %13, %14, %15, %16, %17, %18, %19, %20, %21, %22, %23, %24, %25, %26, %27, %28, %29, %30, %31, %32, %33, %34, %35, %36, %37, %38, %39, %40, %41, %42, %43, %44, %45, %46, %47, %48, %49, %50, %51, %52, %53, %54, %55, %56, %57, %58, %59, %60, %61, %62, %63}, {%64,%65,%66,%67}, db, 1, 1, 1, 0;\n}\n"
    : "+f"(d[0]), "+f"(d[1]), "+f"(d[2]), "+f"(d[3]), "+f"(d[4]), "+f"(d[5]), "+f"(d[6]), "+f"(d[7]), "+f"(d[8]), "+f"(d[9]), "+f"(d[10]), "+f"(d[11]), "+f"(d[12]), "+f"(d[13]), "+f"(d[14]), "+f"(d[15]), "+f"(d[16]), "+f"(d[17]), "+f"(d[18]), "+f"(d[19]), "+f"(d[20]), "+f"(d[21]), "+f"(d[22]), "+f"(d[23]), "+f"(d[24]), "+f"(d[25]), "+f"(d[26]), "+f"(d[27]), "+f"(d[28]), "+f"(d[29]), "+f"(d[30]), "+f"(d[31]), "+f"(d[32]), "+f"(d[33]), "+f"(d[34]), "+f"(d[35]), "+f"(d[36]), "+f"(d[37]), "+f"(d[38]), "+f"(d[39]), "+f"(d[40]), "+f"(d[41]), "+f"(d[42]), "+f"(d[43]), "+f"(d[44]), "+f"(d[45]), "+f"(d[46]), "+f"(d[47]), "+f"(d[48]), "+f"(d[49]), "+f"(d[50]), "+f"(d[51]), "+f"(d[52]), "+f"(d[53]), "+f"(d[54]), "+f"(d[55]), "+f"(d[56]), "+f"(d[57]), "+f"(d[58]), "+f"(d[59]), "+f"(d[60]), "+f"(d[61]), "+f"(d[62]), "+f"(d[63])
    : "r"(a0), "r"(a1), "r"(a2), "r"(a3), "r"(blo));
}

struct CvCtx {
  uint32_t koff, zero, so[3];
  int srcA, srcB;
  bool wrapA, s3, kodd;
};
struct CvPipe { uint32_t Ap, Ep, keep, send; };
template <int LO> __device__ __forceinline__ void cv_copy(float (&acc)[64]) {
#pragma unroll
  for (int i = LO; i < 64; i++) { float t; asm volatile("mov.b32 %0, %1;" : "=f"(t) : "f"(acc[i]) : "memory"); acc[i] = t; }
}
template <int G> __device__ __forceinline__ void cv_raw(uint32_t (&A)[4][4], uint32_t kaddr) {
#pragma unroll
  for (int i = 0; i < 4; i++) {
    const uint32_t a = kaddr + (4 * G + i) * 128;
    A[i][0] = lds32(a); A[i][1] = lds32(a + 4); A[i][3] = lds32(a + 8);
  }
}
__device__ __forceinline__ void cv_form(uint32_t (&A)[4][4], uint32_t sel) {
#pragma unroll
  for (int i = 0; i < 4; i++) {
    asm volatile("prmt.b32 %0, %0, %1, %2;" : "+r"(A[i][0]) : "r"(A[i][1]), "r"(sel));
    asm volatile("prmt.b32 %0, %1, %2, %3;" : "=r"(A[i][2]) : "r"(A[i][1]), "r"(A[i][3]), "r"(sel));
  }
}
#define CVV 2
template <int G> __device__ __forceinline__ void cv_step(float (&acc)[64], uint32_t (&A)[4][4], CvPipe& s, const CvCtx& c, uint32_t cb, uint32_t stg) {
  constexpr int JA = G - 1, JB = G - 2, NH = CVV == 1 ? 4 : (CVV == 3 ? 2 : 1);
  const uint32_t db0 = desc_lo(cb + CV_U + 192, CV_PL);
  uint32_t B[4][4];
  uint32_t ra[2], rb;
  if constexpr (G < 8) {
    wgmma_fence();
#pragma unroll
    for (int i = 0; i < NH; i++) wgmma_rs_hi<128 - 16 * (G & 7)>(acc, A[i][0], A[i][1], A[i][2], A[i][3], db0 - 4 * i);
    wgmma_commit();
    __syncwarp();
  }
  if constexpr (JA >= 0 && JA < 8) {
    const uint32_t p0 = pack_bf16(acc[8 * JA + 1], acc[8 * JA + 3]), p1 = pack_bf16(acc[8 * JA + 5], acc[8 * JA + 7]);
    ra[0] = __shfl_sync(0xffffffffu, c.wrapA ? s.Ap : p0, c.srcA);
    ra[1] = __shfl_sync(0xffffffffu, c.wrapA ? p0 : p1, c.srcA);
    s.Ap = p1;
  }
  if constexpr (JB >= 0) rb = __shfl_sync(0xffffffffu, s.send, c.srcB);
  if constexpr (G < 7) cv_raw<G + 1>(B, cb + c.koff);
  uint32_t z = 0;
  if constexpr (G < 8 && NH < 4) {
    __syncwarp();
    wgmma_fence();
#pragma unroll
    for (int i = NH; i < 4; i++) wgmma_rs_hi<128 - 16 * (G & 7)>(acc, A[i][0], A[i][1], A[i][2], A[i][3], db0 - 4 * i);
    wgmma_commit();
    asm volatile("mov.u32 %0, %%clock;" : "=r"(z)::"memory");
    z &= c.zero;
  }
  if constexpr (G < 7) cv_form(B, 0x5432u | z);
  if constexpr (JB >= 0) sts32(stg + ((c.so[JB / 3] >> (10 * (JB % 3))) & 0xffc), hadd2(rb | z, s.keep));
  if constexpr (JA >= 0 && JA < 8) {
    const uint32_t sh = 16 | z, mk = 0xffff0000u | z;
    const uint32_t ev = pack_bf16(acc[8 * JA] + __uint_as_float(ra[0] << sh), acc[8 * JA + 2] + __uint_as_float(ra[0] & mk));
    const uint32_t od = pack_bf16(acc[8 * JA + 4] + __uint_as_float(ra[1] << sh), acc[8 * JA + 6] + __uint_as_float(ra[1] & mk));
    s.send = c.kodd ? ev : (c.s3 ? s.Ep : od);
    s.keep = c.kodd ? od : ev;
    s.Ep = od;
  }
  if constexpr (G < 8) { __syncwarp(); wgmma_wait<0>(); cv_copy<8 * (G & 7)>(acc); }
  if constexpr (G < 9) cv_step<G + 1>(acc, B, s, c, cb, stg);
}
__device__ __forceinline__ uint32_t cv_stage(int slot) { return sb + (slot < 4 ? 40960 + slot * 4096 : CV_OFF + CV_K); }
__device__ __forceinline__ void cv_setup(CvCtx& c) {
  const int tid = tid_opaque() & 127, w = tid >> 5, lane = tid & 31, r = lane >> 2, q = lane & 3;
  const int i0 = (r >> 1) & 1, i1 = r >> 2;
  c.koff = CV_K - 32 + 4 * (8 * (r >> 1) + 2 * w + (r & 1) + 2 * q);
  c.srcA = i0 ? lane - 8 : lane + 8 - q + ((q + 3) & 3);
  c.wrapA = i0 && q == 3;
  c.srcB = i1 == 0 ? (lane - q + 16 + ((q + 3) & 3)) : (lane - q - 16 + ((q + 1) & 3));
  c.s3 = (i1 == 1 && q == 3); c.kodd = (i1 == 1 && q < 3);
  c.zero = lds32(sb + EP_OFF + 24);
#pragma unroll
  for (int i = 0; i < 3; i++) c.so[i] = lds32(sb + SO_OFF + 512 * i + 4 * tid);
}
__device__ __forceinline__ void cv_table() {
  const int tid = tid_opaque() & 127, r = (tid & 31) >> 2, q = tid & 3;
  int t = 16 * (2 * (r < 4 ? q : 4 + ((q + 1) & 3)) + ((r >> 1) & 1)) + 4 * (tid >> 5) + 2 * (r & 1);
#pragma unroll 1
  for (int i = 0; i < 3; i++) {
    uint32_t v = 0;
#pragma unroll 1
    for (int x = 0; x < 3; x++, t += 256) {
      const int T = t / 160, tl = t - T * 160;
      const int qq = (T >= NT1 - 1) ? (tl >> 5) : (tl / 40);
      int ck = 20 * T + ((tl - qq * ((T >= NT1 - 1) ? 32 : 40)) >> 1);
      ck ^= (ck >> 2) & 6;
      v |= (uint32_t)((ck * 4 + qq) & 1023) << (10 * x + 2);
    }
    sts32(sb + SO_OFF + 512 * i + 4 * tid, v);
  }
}
__device__ __forceinline__ void conv_channel(int slot, const CvCtx& c) {
  const uint32_t cb = sb + CV_OFF + slot * CV_B;
  float acc[64];
  CvPipe s;
  s.Ap = s.Ep = 0u;
  uint32_t A[4][4];
#pragma unroll
  for (int i = 0; i < 64; i++) acc[i] = 0.f;
  if (slot == 4) mbar_wait(bars + 8 * B_CVDONE);
  mbar_wait(bars + 8 * (B_CVFULL + slot));
  cv_raw<0>(A, cb + c.koff);
  {
    const uint32_t w0 = lds32(cb + CV_K);
    const uint32_t wp = __byte_perm(pack_bf16(bf_lo(w0) + __uint_as_float(lds32(sb + EP_OFF + 4 * slot)), 0.f), w0, 0x7610);
    if (c.koff == CV_K) A[0][0] = wp;
    if (c.koff == CV_K - 4) A[0][1] = wp;
    if (c.koff == CV_K - 8) A[0][3] = wp;
  }
  cv_form(A, 0x5432u);
  cv_copy<0>(acc);
  cv_step<0>(acc, A, s, c, cb, cv_stage(slot));
  fence_async_smem();
  mbar_arrive(bars + 8 * (B_CVDONE + slot));
}

__device__ __forceinline__ void xt_issue(const Params& p, int m2, int dg) {
  mbar_expect_tx(bars + 8 * B_XT, 20480);
#pragma unroll 1
  for (int h = 0; h < 2; h++) {
    const int ng = 8 * m2 + 4 * h, T = ng / 20;
    tma4(sb + XT_OFF + h * 10240, T == NT1 - 1 ? &p.mXtl : &p.mXt, 160 * dg, 0, 0, T == NT1 - 1 ? ng - 240 : ng + 60 * T, bars + 8 * B_XT);
  }
}
__device__ __forceinline__ void kv_issue(const Params& p, int c, int m2, int dg) {
  const uint32_t fb = bars + 8 * (B_KV + c);
  mbar_expect_tx(fb, KV_PIECE);
  tma3(sb + KS_OFF + c * KV_PIECE, &p.mK, 160 * dg + 32 * c, 64 * m2 - 3, 0, fb);
  tma3(sb + KS_OFF + c * KV_PIECE + 4864, &p.mV, 160 * dg + 32 * c, 64 * m2 - 1, 0, fb);
}
__device__ __forceinline__ void kv_tile(int m, int c, int y, uint32_t (&o)[4][4]) {
  const int lane = tid_opaque() & 31, tg = lane & 3, pr = 8 * (y ^ (tg >> 1)) + (lane >> 2);
  const uint32_t pb = sb + KS_OFF + c * KV_PIECE + 4 * pr;
  const uint32_t ka = pb + tg * 1216, va = pb + 4864 + tg * 1088 + 64;
  const uint32_t kh = (m == 0 && tg > 0) ? ka - 192 : ka;
  uint32_t kk[19], u[16];
  const float4 t = lds128f(sb + TAP_OFF + 256 * c + 16 * pr);
#pragma unroll
  for (int i = 0; i < 19; i++) { kk[i] = lds32((i < 3 ? kh : ka) + i * 64); if (i >= 3) u[i - 3] = lds32(va + (i - 3) * 64); }
  const uint32_t dst = sb + KS_OFF + c * KV_PIECE + pr * 64 + tg * 16;
  if (y) {
    __syncwarp();
#pragma unroll
    for (int x = 0; x < 4; x++) sts128((dst ^ 512) + x * 1024, make_uint4(o[x][0], o[x][1], o[x][2], o[x][3]));
  }
  const uint32_t w0 = __byte_perm(__float_as_uint(t.x), __float_as_uint(t.z), 0x5410), w1 = __byte_perm(__float_as_uint(t.x), __float_as_uint(t.z), 0x7632);
  const uint32_t w2 = __byte_perm(__float_as_uint(t.y), __float_as_uint(t.w), 0x5410), w3 = __byte_perm(__float_as_uint(t.y), __float_as_uint(t.w), 0x7632);
#pragma unroll
  for (int i = 0; i < 16; i++) {
    uint32_t a = hmul2(kk[i], w3);
    a = hadd2(a, hmul2(kk[i + 1], w2)); a = hadd2(a, hmul2(kk[i + 2], w1)); a = hadd2(a, hmul2(kk[i + 3], w0));
    u[i] = hmul2(a, u[i]);
  }
#pragma unroll
  for (int x = 0; x < 4; x++) {
#pragma unroll
    for (int qq = 0; qq < 4; qq++) o[x][qq] = __byte_perm(u[15 - 4 * qq - (x & 2)], u[14 - 4 * qq - (x & 2)], (x & 1) ? 0x7632 : 0x5410);
    if (y) sts128(dst + x * 1024, make_uint4(o[x][0], o[x][1], o[x][2], o[x][3]));
  }
}
__device__ __forceinline__ void ln_finish(float s1, float s2, float& mean, float& rstd) {
  mean = s1 * (1.f / 640.f);
  const float v = fmaxf(fmaf(-mean, mean, s2 * (1.f / 640.f)), 0.f) + 1e-5f;
  asm("rsqrt.approx.ftz.f32 %0, %1;" : "=f"(rstd) : "f"(v));
}
__device__ __forceinline__ void stat_table(int T1, unsigned want, int l, int g, const uint4* x0, const uint4* x1, float (&xa)[2], float (&xb)[2]) {
  const int n = 32 * g + (tid_opaque() & 31);
  const uint4* rp = &g_stats[8 * l * SEQ + min(160 * T1 + n, SEQ - 1)];
  float a[4], b[4];
  uint32_t it = 0;
  while (true) {
    bool ok = true;
#pragma unroll
    for (int i = 0; i < 4; i++) ok &= (rec_ld(rp + SEQ * i, a[i], b[i]) == want);
    ok &= rec_ld(x0, xa[0], xb[0]) == want;
    ok &= rec_ld(x1, xa[1], xb[1]) == want;
    if (__all_sync(0xffffffffu, ok)) break;
    trap_if(++it > SPIN_LIMIT);
  }
  float m, rs;
  ln_finish((a[0] + a[1]) + (a[2] + a[3]), (b[0] + b[1]) + (b[2] + b[3]), m, rs);
  sts32(sb + STAB_OFF + ((n >> 1) & 3) * 160 + (n >> 3) * 8 + (n & 1) * 4, __float_as_uint(rs));
  const uint32_t hi = pack_bf16(-m, -m);
  const float lo = -m - bf_lo(hi);
  sts128(sb + (l ? MX1_OFF : MX0_OFF) + n * 16, make_uint4(hi, pack_bf16(lo, lo), 0u, 0u));
  fence_async_smem();
}
__device__ __forceinline__ void stats_reduce(float (&a)[2], float (&b)[2], float (&mean)[2], float (&rstd)[2]) {
#pragma unroll
  for (int o = 1; o < 4; o <<= 1)
#pragma unroll
    for (int h = 0; h < 2; h++) { a[h] += __shfl_xor_sync(0xffffffffu, a[h], o); b[h] += __shfl_xor_sync(0xffffffffu, b[h], o); }
#pragma unroll
  for (int h = 0; h < 2; h++) ln_finish(a[h], b[h], mean[h], rstd[h]);
}

template <bool FIRST>
__device__ __forceinline__ void stats_publish(int which, int n0, int dg, unsigned tag, const float (&acc)[80]) {
  const int q = tid_opaque() & 3, h = q & 1;
  float s1[2] = {0.f, 0.f}, s2[2] = {0.f, 0.f}, t1[2] = {0.f, 0.f}, t2[2] = {0.f, 0.f};
#pragma unroll
  for (int j = 0; j < 20; j++)
#pragma unroll
    for (int y = 0; y < 2; y++) {
      const float a = acc[4 * j + 2 * y], b = acc[4 * j + 2 * y + 1];
      s1[y] += a; t1[y] += b; s2[y] = fmaf(a, a, s2[y]); t2[y] = fmaf(b, b, t2[y]);
    }
#pragma unroll
  for (int y = 0; y < 2; y++) { s1[y] += t1[y]; s2[y] += t2[y]; }
  float a = (h ? s1[1] : s1[0]) + __shfl_xor_sync(0xffffffffu, h ? s1[0] : s1[1], 1);
  float b = (h ? s2[1] : s2[0]) + __shfl_xor_sync(0xffffffffu, h ? s2[0] : s2[1], 1);
  a += __shfl_xor_sync(0xffffffffu, a, 2);
  b += __shfl_xor_sync(0xffffffffu, b, 2);
  if (FIRST) {
    rec_st(&g_stats[((q >> 1) * 4 + dg) * SEQ + n0 + 8 * h], a, b, q < 2 ? tag : tag - 1);
    rec_st(&g_stats[((q >> 1) * 4 + 8 + dg) * SEQ + n0 + 8 * h], a, b, tag - 1);
  } else if (q < 2) rec_st(&g_stats[(which * 4 + dg) * SEQ + n0 + 8 * h], a, b, tag);
}
__device__ __forceinline__ void stats_get(int which, int n0, unsigned tag, float (&mean)[2], float (&rstd)[2]) {
  const uint4* p0 = &g_stats[(which * 4 + (tid_opaque() & 3)) * SEQ + n0];
  float a[2], b[2];
  uint32_t it = 0;
  while (true) {
    const unsigned t0 = rec_ld(p0, a[0], b[0]), t1 = rec_ld(p0 + 8, a[1], b[1]);
    if (__all_sync(0xffffffffu, t0 == tag && t1 == tag)) break;
    trap_if(++it > SPIN_LIMIT);
  }
  stats_reduce(a, b, mean, rstd);
}
__device__ __forceinline__ void x0_load(float (&acc)[80]) {
  const int t = tid_opaque() & 127;
  const uint32_t xa = sb + XT_OFF + (16 * (t >> 5) + ((t & 31) >> 2)) * 320 + 8 * (t & 3);
  mbar_wait(bars + 8 * B_XT);
#pragma unroll
  for (int h = 0; h < 2; h++)
#pragma unroll
    for (int J = 0; J < 10; J++) {
      const float2 v = lds64f(xa + h * 2560 + 32 * J);
      const uint32_t x = __float_as_uint(v.x), y = __float_as_uint(v.y);
      acc[8 * J + 2 * h] = bf_lo(x); acc[8 * J + 2 * h + 1] = bf_hi(x);
      acc[8 * J + 4 + 2 * h] = bf_lo(y); acc[8 * J + 4 + 2 * h + 1] = bf_hi(y);
    }
}

template <bool FROM_X0>
__device__ __forceinline__ void dskip_init(float (&acc)[80], const float (&mean)[2], const float (&rstd)[2]) {
  const int t = tid_opaque() & 127;
  const uint32_t xa = sb + XT_OFF + (16 * (t >> 5) + ((t & 31) >> 2)) * 320 + 8 * (t & 3), da = sb + DTAB_OFF + 8 * (t & 3);
  float2 dw[10], xv[10][2];
#pragma unroll
  for (int J = 0; J < 2; J++) { dw[J] = lds64f(da + 32 * J); if (FROM_X0) { xv[J][0] = lds64f(xa + 32 * J); xv[J][1] = lds64f(xa + 2560 + 32 * J); } }
#pragma unroll
  for (int J = 0; J < 10; J++) {
    if (J + 2 < 10) { dw[J + 2] = lds64f(da + 32 * (J + 2)); if (FROM_X0) { xv[J + 2][0] = lds64f(xa + 32 * (J + 2)); xv[J + 2][1] = lds64f(xa + 2560 + 32 * (J + 2)); } }
#pragma unroll
    for (int x = 0; x < 8; x++) {
      const int h = (x >> 1) & 1;
      const uint32_t dwd = __float_as_uint(x < 4 ? dw[J].x : dw[J].y);
      const float tt = fmaf(rstd[h], (x & 1) ? bf_hi(dwd) : bf_lo(dwd), 1.f);
      float a = acc[8 * J + x];
      if (FROM_X0) { const uint32_t xw = __float_as_uint(x < 4 ? xv[J][h].x : xv[J][h].y); a = (x & 1) ? bf_hi(xw) : bf_lo(xw); }
      acc[8 * J + x] = FROM_X0 ? (a - mean[h]) * tt : fmaf(a, tt, -mean[h] * tt);
    }
  }
}

__global__ void __launch_bounds__(512, 1) fused_kernel(const __grid_constant__ Params p) {
  extern __shared__ __align__(1024) uint8_t smem_raw[];
  const int tid = threadIdx.x, lane = tid & 31;
  const int wid = __shfl_sync(0xffffffffu, tid >> 5, 0), wg = wid >> 2;
  unsigned smid; asm volatile("mov.u32 %0, %%smid;" : "=r"(smid));
  const int role = p.role[min(smid, 131u)];
  if (wid == 12) {
    const bool el = elect_one();
    if (el) {
      asm volatile("prefetch.tensormap [%0];" ::"l"(&p.mB) : "memory");
      asm volatile("prefetch.tensormap [%0];" ::"l"((role & 15) == NT1 - 1 ? &p.mXl : &p.mX) : "memory");
#pragma unroll
      for (int k = 0; k < S1; k++) mbar_init(bars + 8 * (B_G1FULL + k), 1);
#pragma unroll
      for (int k = 0; k < 6; k++) mbar_init(bars + 8 * (B_XT + k), 1);
      asm volatile("fence.mbarrier_init.release.cluster;" ::: "memory");
    }
    if (role >= 0) {
      __syncwarp();
      asm volatile("bar.arrive 5, 288;" ::: "memory");
      const Role R = unpack_role(role);
      if (elect_one()) {
        TS(45);
#pragma unroll 1
        for (int k = 0; k < S1; k++) {
          const uint32_t fb = bars + 8 * (B_G1FULL + k);
          mbar_expect_tx(fb, G1_STAGE);
          tma4(sb + k * G1_STAGE + G1_XOFF, R.last ? &p.mXl : &p.mX, 64 * k, 0, 0, R.last ? 0 : 80 * R.T1, fb);
          tma5(sb + k * G1_STAGE, &p.mB, 64 * k, 0, 0, 4 * R.side, 2 * R.GP, fb);
          if (PFD) asm volatile("prefetch.tensormap [%0];" ::"l"(&p.mK + k) : "memory");
        }
        if (R.has2) {
          if (!XLATE) xt_issue(p, R.m2, R.dg);
#pragma unroll 1
          for (int c = 0; c < KV0; c++) kv_issue(p, c, R.m2, R.dg);
        }
        TS(44);
      }
      __syncwarp();
      bar_sync(6, 64);
    }
  }
  trap_if(smid >= 132 || smem_u32(smem_raw) != sb);
  if (role < 0) {
    if (wid == 0) {
      const unsigned tag = ld_rlx(g_epoch);
      uint32_t it = 0;
      while (!__all_sync(0xffffffffu, (int)(ld_rlx(&g_hcnt[(lane & 7) * 32]) - 40 * tag) >= 0)) { __nanosleep(500); trap_if(++it > SPIN_LIMIT); }
    }
    return;
  }
  float mean0[2] = {0.f, 0.f}, rstd0[2] = {0.f, 0.f};
  if (wg == 2 || wid == 14) {
    ROLE(role)
    const int c = wid == 14 ? 4 : wid - 8;
    const unsigned tag = ld_rlx(g_epoch);
    if (has2) {
      uint2 bv[2][5];
#pragma unroll
      for (int x = 0; x < 2; x++)
#pragma unroll
        for (int i = 0; i < 5; i++) bv[x][i] = ldv64((const uint2*)((x ? p.bim : p.bre) + (cch0 + 32 * c) * DM) + lane + 32 * i);
      float sv[2];
#pragma unroll
      for (int x = 0; x < 2; x++) {
        float a = 0.f;
#pragma unroll
        for (int i = 0; i < 5; i++) a += (bf_lo(bv[x][i].x) + bf_hi(bv[x][i].x)) + (bf_lo(bv[x][i].y) + bf_hi(bv[x][i].y));
        sv[x] = a;
      }
#pragma unroll
      for (int o = 16; o > 0; o >>= 1) { sv[0] += __shfl_xor_sync(0xffffffffu, sv[0], o); sv[1] += __shfl_xor_sync(0xffffffffu, sv[1], o); }
      if (lane < 2) rec_st(&g_sB[(cch0 + 32 * c) * 2 + lane], sv[0], sv[1], tag);
      if (tid == 256) TS(47);
      __syncwarp();
      bar_sync(8, 192);
      if (wg == 2) {
        float xs[80];
        x0_load(xs);
        stats_publish<true>(0, 64 * m2 + 16 * c + (lane >> 2), dg, tag, xs);
        if (tid == 256) TS(31);
      }
      mbar_wait(bars + 8 * B_EP);
      mbar_wait(bars + 8 * (B_KV + c));
      mbar_wait(bars + 8 * (B_G1DONE + PAUSE_K - 1));
      if (tid == 448) TS(52);
      uint32_t o[4][4] = {};
#pragma unroll 1
      for (int y = 0; y < 2; y++) kv_tile(m2, c, y, o);
      fence_async_smem();
      __syncwarp();
      if (lane == 0) { mbar_arrive(bars + 8 * B_PREP); mbar_arrive(bars + 8 * (B_PD + c)); }
      if (tid == 448) TS(51);
    } else bar_sync(8, 192);
    {
      const uint4* x0 = wg == 2 ? &g_stats[(lane & 3) * SEQ + (has2 ? 64 * m2 : 0) + 16 * c + (lane >> 2)] : &g_sB[(128 * GP + 32 * side + lane) * 2];
      float xa[2], xb[2];
      stat_table(T1, tag, 0, c, x0, x0 + (wg == 2 ? 8 : 128), xa, xb);
      if (wg == 2) stats_reduce(xa, xb, mean0, rstd0);
      else {
#pragma unroll
        for (int i = 0; i < 2; i++) {
          const float ha = bf_lo(pack_bf16(xa[i], 0.f)), hb = bf_lo(pack_bf16(xb[i], 0.f));
          const float pa = __uint_as_float(pack_bf16(ha, xa[i] - ha)), pb = __uint_as_float(pack_bf16(hb, xb[i] - hb));
          sts64f(sb + CTAB_OFF + (32 * i + lane) * 24 + 16, p.swap ? pb : pa, p.swap ? pa : pb);
        }
      }
      mbar_arrive(bars + 8 * B_STAB);
      if (tid == 448) TS(26);
    }
  } else if (wid == 15) {
    ROLE(role)
    const int ch = 128 * GP + 32 * side + lane;
    uint32_t r0 = ldv16(p.lre + ch), r1 = ldv16(p.lim + ch), r2 = ldv16(p.logdt + ch);
    const uint32_t r3 = ldv16(p.lre + ch + 64), r4 = ldv16(p.lim + ch + 64), r5 = ldv16(p.logdt + ch + 64);
#pragma unroll 1
    for (int i = 0; i < 2; i++) {
      const float lr = bf_lo(r0), li = bf_lo(r1);
      const float dt = __bfloat162float(__float2bfloat16_rn(expf(bf_lo(r2))));
      const float mag = expf(dt * lr);
      float sn, cs; sincospif(dt * li * 0.31830988618379067f, &sn, &cs);
      const float ar = mag * cs, ai = mag * sn;
      const float inv = 2.f / (lr * lr + li * li);
      const uint32_t ad = sb + CTAB_OFF + (32 * i + lane) * 24;
      sts64f(ad, ar, ai);
      sts64f(ad + 8, ((ar - 1.f) * lr + ai * li) * inv, (ai * lr - (ar - 1.f) * li) * inv);
      r0 = r3; r1 = r4; r2 = r5;
    }
    if (lane == 0) TS(46);
    __syncwarp();
    bar_sync(7, 64);
    mbar_arrive(bars + 8 * B_CTAB);
  } else if (wid == 13) {
    ROLE(role)
    uint4 tv[3];
    const uint32_t e0 = ld_rlx(g_epoch);
    const uint32_t e1 = ldv16(p.ssmD + min(cch0 + 32 * lane, 639));
    const uint4 dv = ldv128((const uint4*)(p.dskip + 160 * dg) + min(lane, 19));
#pragma unroll
    for (int i = 0; i < 3; i++) tv[i] = ldv128((const uint4*)(p.shiftk + 640 * dg) + min(lane + 32 * i, 79));
    sts128(sb + DTAB_OFF + 16 * min(lane, 19), dv);
#pragma unroll
    for (int i = 0; i < 3; i++) sts128(sb + TAP_OFF + 16 * min(lane + 32 * i, 79), tv[i]);
    if (lane < 7) sts32(sb + EP_OFF + 4 * lane, lane < 5 ? e1 << 16 : (lane == 5 ? e0 : 0u));
    __syncwarp();
    bar_sync(9, 64);
    mbar_arrive(bars + 8 * B_CTAB);
    if (lane == 0) { mbar_arrive(bars + 8 * B_EP); TS(53); }
    if (has2) {
#pragma unroll 1
      for (int i = 0; i < 5; i++) {
        const int c = i == 2 ? 3 : (i == 3 ? 2 : i);
        mbar_wait(bars + 8 * (B_PD + c));
        if (lane == 0) bulk_s2g(g_kv + (dg * 32 + m2) * 20480 + c * 4096, sb + KS_OFF + c * KV_PIECE, 4096);
      }
      if (lane == 0) {
        asm volatile("cp.async.bulk.commit_group;" ::: "memory");
        asm volatile("cp.async.bulk.wait_group 0;" ::: "memory");
        mbar_arrive(bars + 8 * B_PREP2);
        fence_async_global();
      }
      __syncwarp();
      if (lane < 4) red_rel(&g_kvcnt[(dg * 4 + lane) * 32]);
      __syncwarp();
      if (lane == 0) { mbar_arrive(bars + 8 * B_PUB); TS(30); }
    }
  } else if (wid != 12) {
    if (elect_one()) {
      if (wid < 7) {
        const int b0 = wid < 4 ? 4 + 19 * wid : 85 + 21 * (wid - 4), cnt = wid < 4 ? 2 : 1;
#pragma unroll
        for (int i = 0; i < 21; i++) mbar_init(bars + 8 * (b0 + i), cnt);
      } else {
#pragma unroll
        for (int i = 0; i < 12; i++) mbar_init(bars + 8 * (B_CVDONE + i), (i == 5 || i == 6) ? 160 : 128);
        mbar_init(bars + 8 * B_CTAB, 192); mbar_init(bars + 8 * B_PREP, 5); mbar_init(bars + 8 * B_PREP2, 1);
#pragma unroll
        for (int i = 0; i < 5; i++) mbar_init(bars + 8 * (B_PD + i), 1);
      }
      asm volatile("fence.mbarrier_init.release.cluster;" ::: "memory");
    }
    __syncwarp();
    bar_sync(5, 288);
    if (wid == 2) asm volatile("bar.arrive 8, 192;\nbar.arrive 6, 64;\nbar.arrive 9, 64;\nbar.arrive 7, 64;" ::: "memory");
    if (tid == 128) TS(0);
    if (wg == 1) { cv_table(); mbar_arrive(bars + 8 * B_CTAB); }
  }

  if (wid == 12) {
    ROLE(role)
    uint32_t dst = sb;
#pragma unroll 1
    for (int k = S1; k < 10; k++) {
      const uint32_t fb = bars + 8 * (B_G1FULL + k);
      mbar_wait(bars + 8 * (B_G1DONE + k - S1));
      if (elect_one()) {
        mbar_expect_tx(fb, 20480);
        tma4(dst + G1_XOFF, last ? &p.mXl : &p.mX, 64 * k, 0, 0, last ? 0 : 80 * T1, fb);
        mbar_expect_tx(fb, 16384);
        tma5(dst, &p.mB, 64 * k, 0, 0, 4 * side, 2 * GP, fb);
        if (has2 && k - S1 + KV0 < 5) kv_issue(p, k - S1 + KV0, m2, dg);
        if (has2 && k == XLATE) xt_issue(p, m2, dg);
      }
      dst += G1_STAGE; if (k == 2 * S1 - 1) dst = sb;
    }
  } else if (wid == 15 && (role >> 16)) {
    ROLE(role)
    if (TPF >= 0) {
      mbar_wait(bars + 8 * (B_KV + TPF));
      if (elect_one()) {
#pragma unroll
        for (int c = 0; c < 5; c++) l2_prefetch(p.ssmk + (cch0 + 32 * c) * SEQ, 4096);
        if (CPF) { l2_prefetch(p.cre + (160 * dg + 5 * m2) * DM, 6400); l2_prefetch(p.cim + (160 * dg + 5 * m2) * DM, 6400); }
      }
    }
    mbar_wait(bars + 8 * B_PREP2);
    if (lane < 10) sts128(sb + CV_OFF + (lane >> 1) * CV_B + CV_K - 32 + 16 * (lane & 1), make_uint4(0, 0, 0, 0));
    fence_async_smem();
    __syncwarp();
    const unsigned tag = lds32(sb + EP_OFF + 20);
    if (TAPW) mbar_wait(bars + 8 * B_PUB);
    if (elect_one()) {
#pragma unroll 1
      for (int c = 0; c < 5; c++) {
        if (c == 0) asm volatile("prefetch.tensormap [%0];" ::"l"(&p.mU) : "memory");
        mbar_expect_tx(bars + 8 * (B_CVFULL + c), 4096 + 2 * CV_PL);
        if (c < TAPN) bulk_g2s(sb + CV_OFF + c * CV_B + CV_K, p.ssmk + (cch0 + 32 * c) * SEQ, 4096, bars + 8 * (B_CVFULL + c));
      }
    }
    mbar_wait(bars + 8 * B_PUB);
    cnt_poll(&g_kvcnt[(dg * 4 + (m2 >> 3)) * 32], 32 * tag);
    fence_async_global();
    if (elect_one()) {
      TS(28);
#pragma unroll
      for (int c = 0; c < 5; c++) {
        tma5(sb + CV_OFF + c * CV_B + CV_U, &p.mU, 0, -3, 2 * c, 16 * (m2 & 1) + (m2 >> 1), dg, bars + 8 * (B_CVFULL + c));
        if (c >= TAPN) bulk_g2s(sb + CV_OFF + c * CV_B + CV_K, p.ssmk + (cch0 + 32 * c) * SEQ, 4096, bars + 8 * (B_CVFULL + c));
      }
#pragma unroll
      for (int i = 0; i < 3; i++) asm volatile("prefetch.tensormap [%0];" ::"l"(&p.mCre + i) : "memory");
      TS(54);
    }
    __syncwarp();
  }
  {
    const int w = wid & 3;
    if (wg == 2 && !(role >> 16)) {
      float xa[2], xb[2];
      mbar_wait(bars + 8 * (B_G1FULL + 11));
      stat_table(role & 15, lds32(sb + EP_OFF + 20), 1, w, g_stats, g_stats, xa, xb);
      mbar_arrive(bars + 8 * (B_STAB + 1));
    }
#pragma unroll 1
    for (int l = 0; l < 2; l++) {
      if (wg < 2) {
        float acc[80];
#pragma unroll
        for (int i = 0; i < 80; i++) acc[i] = 0.f;
        ROLE(role)
        const int tid = tid_opaque(), r = (tid & 31) >> 2, q = tid & 3;
        const int ch = 128 * GP + 64 * wg + 32 * side + 8 * w + r;
        const uint32_t ca = sb + CTAB_OFF + (32 * wg + 8 * w + r) * 24;
        float2 lam = make_float2(0.f, 0.f), p8 = lam, p16 = lam, pL = lam, p2L = lam;
        fence_regs(acc);
        {
          const uint32_t alo0 = (l == 0 ? desc_lo(sb, 16) : desc_lo(sb + G2_WOFF, 16)) + wg * 512;
          const uint32_t blo0 = l == 0 ? desc_lo(sb + G1_XOFF, 16) : desc_lo(sb + X1_OFF, 128);
          const uint32_t bhi = l == 0 ? desc_hi(1024, 1) : desc_hi(1024, 0), xstep = l == 0 ? 2 : 16;
          const uint32_t astep = l == 0 ? G1_STAGE >> 4 : 1024, bstep = l == 0 ? G1_STAGE >> 4 : 1280, aend = alo0 + (S1 + l) * astep;
          uint32_t alo = alo0, blo = blo0;
          uint32_t fb = bars + 8 * (B_G1FULL + 10 * l);
          mbar_wait(fb);
          if (tid == 0) TS(1 + 8 * l);
#pragma unroll 1
          for (int k = 0; k < 10; k++) {
            uint32_t ok; const uint32_t nb = k < 9 ? fb + 8 : fb;
            wgmma_fence();
#pragma unroll
            for (int kk = 0; kk < 4; kk++) {
              wgmma_n160<0>(acc, alo + kk * 2, desc_hi(1024, 1), blo + kk * xstep, bhi);
              if (kk == 0) ok = mbar_test(nb);
              if (kk == STG_KK && k == 9 && tid == 0) mbar_arrive(bars + 8 * (B_STG + l));
            }
            wgmma_commit();
            alo += astep; blo += bstep;
            if (blo == desc_lo(sb + G_OFF, 128)) blo = desc_lo(sb, 128);
            if (alo == aend) { alo = alo0; blo = blo0; }
            wgmma_wait<1>();
            if (k > 0 && (tid & 127) == 0) mbar_arrive(fb + 8 * (B_G1DONE - B_G1FULL - 1));
            if (!ok) mbar_wait(nb);
            if (k == (l ? MK1 : MK0)) {
              mbar_wait(bars + 8 * (B_STAB + l));
              const float2 sB = lds64f(ca + 16);
              uint32_t a0 = q < 2 ? __float_as_uint(sB.x) : 0u, a1 = q < 2 ? __float_as_uint(sB.y) : 0u, a2 = 0u, a3 = 0u;
              asm volatile("" : "+r"(a0), "+r"(a1), "+r"(a2), "+r"(a3)::"memory");
              wgmma_fence();
              wgmma_rs_n160(acc, a0, a1, a2, a3, l ? desc_lo(sb + MX1_OFF, 0) : desc_lo(sb + MX0_OFF, 0));
              wgmma_commit();
            }
            if (wg == 1 && k == (l ? 8 - STG_D : 9 - STG0)) mbar_wait(bars + 8 * (B_STG + l));
            if (k == 3) {
              mbar_wait(bars + 8 * B_CTAB);
              lam = lds64f(ca);
              if (l == 0 && q < 2) rec_st(&g_E[(q * NT1 + T1) * DM + ch], 0.f, 0.f, lds32(sb + EP_OFF + 20) - 1);
              if (p.swap) lam.y = -lam.y;
              const float2 p2 = cmul(lam, lam), p4 = cmul(p2, p2);
              p8 = cmul(p4, p4); p16 = cmul(p8, p8);
              pL = cmul(p16, p16);
              if (!last) pL = cmul(pL, p8);
              p2L = cmul(pL, pL);
            }
            if (k == PAUSE_K && l == 0 && has2) mbar_wait(bars + 8 * B_PREP);
            fb += 8;
          }
        }
        const unsigned tag = lds32(sb + EP_OFF + 20);
        wgmma_wait<0>();
        fence_regs(acc);
        if ((tid & 127) == 0) { mbar_arrive(bars + 8 * (B_G1DONE + 10 * l + 9)); TS(wg ? 17 + l : 2 + 8 * l); }
        float2 ec[3];
#pragma unroll
        for (int jj = 0; jj < 4; jj++)
#pragma unroll
          for (int y = 0; y < 3; y++) {
            if (y == 2 && (jj & 1)) continue;
            const int j = y == 2 ? 16 + jj : 8 * y + 2 * jj;
            const float4 st = lds128f(sb + STAB_OFF + q * 160 + j * 8);
            const float rs[4] = {st.x, st.y, st.z, st.w};
#pragma unroll
            for (int x = 0; x < 4; x++) {
              const int i = 4 * j + 4 * (x >> 1) + (x & 1);
              acc[i] *= rs[x]; acc[i + 2] *= rs[x];
              ec[y] = (jj == 0 && x == 0) ? make_float2(acc[i], acc[i + 2]) : cfma(lam, ec[y], make_float2(acc[i], acc[i + 2]));
            }
          }
        float2 e = cfma(p16, ec[0], ec[1]);
        if (!last) e = cfma(p8, e, ec[2]);
        {
          float2 v = make_float2(__shfl_up_sync(0xffffffffu, e.x, 1, 4), __shfl_up_sync(0xffffffffu, e.y, 1, 4));
          if (q >= 1) e = cfma(pL, v, e);
          v = make_float2(__shfl_up_sync(0xffffffffu, e.x, 2, 4), __shfl_up_sync(0xffffffffu, e.y, 2, 4));
          if (q >= 2) e = cfma(p2L, v, e);
        }
        if (!last && q == 3) rec_st(&g_E[(l * NT1 + T1) * DM + ch], e.x, e.y, tag);
        if (tid == 0) TS(3 + 8 * l);
        float2 ex = make_float2(__shfl_up_sync(0xffffffffu, e.x, 1, 4), __shfl_up_sync(0xffffffffu, e.y, 1, 4));
        if (q == 0) ex = make_float2(0.f, 0.f);
        const float2 coef = lds64f(ca + 8), lamc = make_float2(lam.x, p.swap ? lam.y : -lam.y);
        float m00 = coef.x, m01 = -coef.y, m10 = -coef.y, m11 = -coef.x;
        if (p.swap) { m00 = -coef.y; m01 = coef.x; m10 = -coef.x; m11 = -coef.y; }
        float2 pLq, p160q, p640;
        {
          const float2 p80 = last ? cmul(p2L, p16) : p2L, p160 = cmul(p80, p80), p320 = cmul(p160, p160), one = make_float2(1.f, 0.f);
          p640 = cmul(p320, p320);
          pLq = cmul((q & 1) ? pL : one, (q & 2) ? p2L : one);
          p160q = cmul((q & 1) ? p160 : one, (q & 2) ? p320 : one);
        }
        float2 c, ev[3];
        unsigned tg[3];
        const uint4* ep = &g_E[(l * NT1 + T1 - 1 - q) * DM + ch];
#pragma unroll
        for (int j = 0; j < 20; j++) {
          if (j == CPOLL) {
#pragma unroll
            for (int i = 0; i < 3; i++) {
              ev[i] = make_float2(0.f, 0.f); tg[i] = tag;
              if (T1 - 1 - q - 4 * i >= 0) tg[i] = rec_ld(ep - 4 * i * DM, ev[i].x, ev[i].y);
            }
          }
#pragma unroll
          for (int x = 0; x < 2; x++) {
            const float b0 = acc[4 * j + x], b1 = acc[4 * j + 2 + x];
            acc[4 * j + x] = fmaf(b0, m00, b1 * m01);
            acc[4 * j + 2 + x] = fmaf(b0, m10, b1 * m11);
          }
          if (j == CPOLL - 1 || j == 19) asm volatile("" : "+f"(acc[4 * j]), "+f"(acc[4 * j + 1]), "+f"(acc[4 * j + 2]), "+f"(acc[4 * j + 3])::"memory");
        }
        {
          uint32_t it = 0;
          while (__any_sync(0xffffffffu, tg[0] != tag || tg[1] != tag || tg[2] != tag)) {
#pragma unroll
            for (int i = 0; i < 3; i++)
              if (tg[i] != tag) tg[i] = rec_ld(ep - 4 * i * DM, ev[i].x, ev[i].y);
            trap_if(++it > SPIN_LIMIT);
          }
          c = cfma(p640, cfma(p640, ev[2], ev[1]), ev[0]);
          c = cmul(c, p160q);
          c.x += __shfl_xor_sync(0xffffffffu, c.x, 1); c.y += __shfl_xor_sync(0xffffffffu, c.y, 1);
          c.x += __shfl_xor_sync(0xffffffffu, c.x, 2); c.y += __shfl_xor_sync(0xffffffffu, c.y, 2);
        }
        if (tid == 0) TS(4 + 8 * l);
        if (wg == 1 && l >= HOLD0) mbar_wait(bars + 8 * (B_REL + l));
        const uint32_t c0 = (uint32_t)clock();
        c = cfma(pLq, c, ex);
        float2 hh = make_float2(fmaf(c.x, m00, c.y * m01), fmaf(c.x, m10, c.y * m11));
        uint8_t* hb = g_h + (size_t)l * (32 * 20 * 8192) + (10 * wg + 2 * GP) * 8192 + (4 * side + w) * 1024 + (tid_opaque() & 31) * 4;
#pragma unroll
        for (int j4 = 0; j4 < 5; j4++) {
          if (PACE && j4 > 0 && wg == 1 && l == 1) { while (__any_sync(0xffffffffu, (uint32_t)clock() - c0 < PACE * j4)) {} }
          const int ng = 20 * T1 + 4 * j4;
          uint8_t* hp = hb + (size_t)(ng >> 3) * 163840 + (ng & 7) * 128;
#pragma unroll
          for (int jj = 0; jj < 4; jj++) {
            const int j = 4 * j4 + jj;
            const float2 h0 = cfma(lamc, hh, make_float2(acc[4 * j + 0], acc[4 * j + 2]));
            hh = cfma(lamc, h0, make_float2(acc[4 * j + 1], acc[4 * j + 3]));
            if (j4 < 4 || !last) {
              *(uint32_t*)(hp + jj * 128) = pack_bf16(h0.x, hh.x);
              *(uint32_t*)(hp + jj * 128 + 8192) = pack_bf16(h0.y, hh.y);
            }
          }
        }
        mbar_arrive(bars + 8 * (B_HST + 2 * l + wg));
        if (tid == 0) TS(5 + 8 * l);
        if (tid == 128) TS(l ? 25 : 19);
        if (!REL3 && l == 0 && wid == 4) {
          mbar_wait(bars + 8 * B_HST);
          mbar_wait(bars + 8 * (B_HST + 1));
          if ((tid & 31) < 8) h_release((tid >> 2) & 1, T1, tid & 3);
          __syncwarp();
          if (tid == 128) { mbar_arrive(bars + 8 * B_REL); TS(6); }
        }
      }
      if (l == 0) {
        ROLE(role)
        if (has2) {
          CvCtx cc;
          mbar_wait(bars + 8 * B_CTAB);
          cv_setup(cc);
          mbar_wait(bars + 8 * (B_G1DONE + 9));
#pragma unroll 1
          for (int c = (wg + 2) & 3; c < 5; c += 4) conv_channel(c, cc);
          if ((tid & 127) == 0) TS(wg == 2 ? 32 : (wg == 3 ? 50 : 7 + wg));
        }
      }
      if (wg >= 2) break;
    }
    if (wg == 3) {
    ROLE(role)
    const int pw = wid & 3, gpc = 2 * min(m2 >> 3, 3) + (dg >> 1);
    mbar_wait(bars + 8 * B_EP);
    const unsigned tag = lds32(sb + EP_OFF + 20);
    if (pw == 0) {
      if (elect_one()) {
#pragma unroll 1
        for (int l = 0; l < 2; l++) {
          uint32_t dst = sb;
          if (l == 1) {
            dst = sb + G2_WOFF;
#pragma unroll 1
            for (int k = 0; k < 10; k++) {
              mbar_wait(k > 4 ? bars + 8 * (B_G1DONE + 5 + k) : (has2 ? bars + 8 * (B_G2DONE + 14 + min(k, 3)) : bars + 8 * (B_G1DONE + 9)));
              mbar_expect_tx(bars + 8 * (B_G1FULL + 10 + k), 16384);
              tma5(dst, &p.mB, 64 * k, 0, 0, 4 * side, 2 * GP, bars + 8 * (B_G1FULL + 10 + k));
              dst += 16384; if (k == 4) dst = sb + G2_WOFF;
            }
          }
          if (has2) {
            const uint32_t fb2 = bars + 8 * (B_G2FULL + 20 * l), wb2 = bars + 8 * (B_G2DONE + 20 * l - S2);
            dst = sb + G2_WOFF + (WTAIL ? 4 * l * G2_WB : 0);
            int kc = 0;
#pragma unroll 1
            for (int k = 0; k < 20; k++) {
              mbar_wait(k >= S2 ? wb2 + 8 * k : bars + 8 * (l ? B_G1DONE + (WTAIL ? (k < 3 ? 15 + k : 13 + k) : 19) : (k == 5 ? B_XFREE : (k == 6 ? B_SFREE : B_REL))));
              mbar_expect_tx(fb2 + 8 * k, G2_WB);
              tma5(dst, &p.mCre + (k & 1), kc, 0, 0, 0, 10 * dg, fb2 + 8 * k);
              kc += (k & 1) << 7; if (k == 9) kc = 64;
              dst += G2_WB; if (dst == sb + G2_WOFF + S2 * G2_WB) dst = sb + G2_WOFF;
            }
          }
        }
      }
    } else if (pw == 1) {
#pragma unroll 1
      for (int l = 0; l < 2; l++) {
        if (l == 1) {
          mbar_wait(bars + 8 * (has2 ? B_G2DONE + 19 : B_G1DONE + 9));
          if (has2) mbar_wait(bars + 8 * B_UST);
          cnt_poll(&g_ucnt[gpc * 32], 128 * tag);
          fence_async_global();
          if (elect_one()) {
            TS(20);
            const int bytes = last ? 16384 : 20480;
            const uint8_t* src = g_u + T1 * 204800;
            uint32_t dst = sb + X1_OFF;
#pragma unroll 1
            for (int k = 0; k < 10; k++) {
              if (k > 4) mbar_wait(bars + 8 * (B_G1DONE + 5 + k));
              mbar_expect_tx(bars + 8 * (B_G1FULL + 10 + k), bytes);
              bulk_g2s(dst, src, bytes, bars + 8 * (B_G1FULL + 10 + k));
              src += 20480; dst += 20480; if (dst == sb + G_OFF) dst = sb; if (k == 4) dst = sb + X1_OFF;
            }
          }
          __syncwarp();
        }
        if (has2) {
          mbar_wait(bars + 8 * (B_HST + 2 * l));
          mbar_wait(bars + 8 * (B_G1DONE + 10 * l + 9));
          cnt_poll(&g_hcnt[(l * 16 + gpc) * 32], 40 * tag);
          fence_async_global();
          if (elect_one()) {
            TS(21 + 2 * l);
            const uint32_t fb2 = bars + 8 * (B_G2FULL + 20 * l), wb2 = bars + 8 * (B_G2DONE + 20 * l - S2);
            const uint8_t* src = g_h + (l * 32 + m2) * 163840;
            uint32_t dst = sb;
#pragma unroll 1
            for (int k = 0; k < 20; k++) {
              if (k >= (l ? XB0 : 5)) mbar_wait(k >= S2 ? wb2 + 8 * k : (l ? fb2 + 8 * (k - XB0) : bars + 8 * B_SFREE));
              if (k == 10) { mbar_wait(bars + 8 * (B_H1 + l)); fence_async_global(); }
              mbar_expect_tx(fb2 + 8 * k, G2_XB);
              bulk_g2s(dst, src, G2_XB, fb2 + 8 * k);
              src += 8192; dst += G2_XB; if (dst == sb + S2 * G2_XB) dst = sb;
            }
          }
          __syncwarp();
        }
      }
    } else if (pw == 2) {
#pragma unroll 1
      for (int l = 0; l < 2; l++) {
        if (l == 1) {
          float xa[2], xb[2];
          mbar_wait(bars + 8 * (B_G1FULL + 11));
          stat_table(T1, tag, 1, 4, g_stats, g_stats, xa, xb);
          mbar_arrive(bars + 8 * (B_STAB + 1));
        }
        if (REL3 && l == 0) {
          mbar_wait(bars + 8 * B_HST);
          mbar_wait(bars + 8 * (B_HST + 1));
          if (lane < 8) h_release(lane >> 2, T1, lane & 3);
          __syncwarp();
          if (lane == 0) { mbar_arrive(bars + 8 * B_REL); TS(6); }
        }
#pragma unroll 1
        for (int w = 0; w < 2 * l; w++) {
          mbar_wait(bars + 8 * (B_HST + 2 + w));
          if (lane < 4) h_release(2 + w, T1, lane);
          __syncwarp();
          if (lane == 0) { if (w == 0) mbar_arrive(bars + 8 * (B_REL + 1)); TS(w ? 16 : 14); }
        }
        if (l == 0 && has2 && elect_one()) {
#pragma unroll 1
          for (int i = 0; i < 5; i++) {
            const int c = i < 3 ? i : 7 - i;
            mbar_wait(bars + 8 * (B_CVDONE + c));
            bulk_s2g(g_G + (cch0 + 32 * c) * 4096, cv_stage(c), 4096);
          }
          asm volatile("cp.async.bulk.commit_group;" ::: "memory");
          asm volatile("cp.async.bulk.wait_group.read 0;" ::: "memory");
          mbar_arrive(bars + 8 * B_SFREE);
          asm volatile("cp.async.bulk.wait_group 0;" ::: "memory");
          TS(48);
          fence_async_global();
          asm volatile("fence.acq_rel.gpu;" ::: "memory");
#pragma unroll
          for (int i = 0; i < 4; i++) red_rlx(&g_gcnt[(dg * 4 + i) * 32]);
          TS(49);
          mbar_arrive(bars + 8 * (B_GO + 1));
        }
        __syncwarp();
      }
    } else if (has2) {
      mbar_wait(bars + 8 * B_REL);
      if (!CPF && elect_one()) {
        l2_prefetch(p.cre + (160 * dg + 5 * m2) * DM, 6400); l2_prefetch(p.cim + (160 * dg + 5 * m2) * DM, 6400);
      }
      mbar_wait(bars + 8 * (B_HST + 1));
      flag_poll(&g_hcnt[(8 + gpc) * 32], 40 * tag);
      if (lane == 0) { mbar_arrive(bars + 8 * B_H1); TS(22); }
      mbar_wait(bars + 8 * (B_GO + 1));
      flag_poll(&g_gcnt[(dg * 4 + (m2 >> 3)) * 32], 32 * tag);
      fence_async_global();
      if (elect_one()) {
        TS(29);
        mbar_expect_tx(bars + 8 * B_GFULL, 20480);
        tma5(sb + G_OFF, &p.mG, 64 * m2, 0, 0, 0, 10 * dg, bars + 8 * B_GFULL);
      }
      mbar_wait(bars + 8 * (B_HST + 3));
      cnt_poll(&g_hcnt[(24 + gpc) * 32], 40 * tag);
      if (lane == 0) { mbar_arrive(bars + 8 * (B_H1 + 1)); TS(24); }
    }
    } else if (wg == 2 && (role >> 16)) {
      float acc[80];
      float off[2] = {mean0[0], mean0[1]};
      const unsigned tag = lds32(sb + EP_OFF + 20);
      dskip_init<true>(acc, mean0, rstd0);
      mbar_arrive(bars + 8 * B_XFREE);
#pragma unroll 1
      for (int step = 1; step < 4; step++) {
        const int l = step >> 1;
        if (step != 2) {
          uint32_t alo = desc_lo(sb, 1024), blo = desc_lo(sb + G2_WOFF, 16) + (WTAIL ? l * (G2_WB >> 2) : 0);
          uint32_t fb = bars + 8 * (B_G2FULL + 20 * l);
          fence_regs(acc);
          mbar_wait(bars + 8 * (B_CVDONE + 2));
          mbar_wait(bars + 8 * (B_CVDONE + 3));
          mbar_wait(fb);
          if (tid == 256) TS(33 + 6 * l);
#pragma unroll 1
          for (int k = 0; k < 20; k++) {
            if (l == TSL && (k & 3) == 3 && tid == 256) TS(56 + (k >> 2));
            uint32_t ok; const uint32_t nb = k < 19 ? fb + 8 : fb;
            wgmma_fence();
#pragma unroll
            for (int kk = 0; kk < 4; kk++) {
              wgmma_n160<1>(acc, alo + kk * 128, desc_hi(128, 0), blo + kk * 2, desc_hi(1024, 1));
              if (kk == 0) ok = mbar_test(nb);
            }
            wgmma_commit();
            alo += G2_XB >> 4; blo += G2_WB >> 4;
            if (alo == desc_lo(sb + S2 * G2_XB, 1024)) alo = desc_lo(sb, 1024);
            if (blo == desc_lo(sb + G_OFF, 16)) blo = desc_lo(sb + G2_WOFF, 16);
            wgmma_wait<1>();
            if (k > 0 && tid == 256) mbar_arrive(fb + 8 * (B_G2DONE - B_G2FULL - 1));
            if (!ok) mbar_wait(nb);
            fb += 8;
          }
          wgmma_wait<0>();
          fence_regs(acc);
          if (tid == 256) TS(34 + 6 * l);
          if (tid == 256) mbar_arrive(bars + 8 * (B_G2DONE + 20 * l + 19));
        }
        ROLE(role)
        const int tq = tid_opaque() & 31, n0 = 64 * m2 + 16 * w + (tq >> 2);
#pragma unroll 1
        for (int rep = 0;; rep++) {
          stats_publish<false>(step, n0, dg, tag, acc);
          if (step != 2 || rep == 1) break;
          for (int n = tid & 127; n < 160; n += 128) {
            const int d = 16 * (n >> 4) + 4 * ((n >> 1) & 3) + 2 * ((n >> 3) & 1) + (n & 1);
            const uint32_t dw = lds32(sb + DTAB_OFF + 2 * (d & ~1)), dd = __byte_perm(dw, dw, (d & 1) ? 0x3232 : 0x1010);
            sts128(sb + DX_OFF + 16 * n, make_uint4(dd, dd, dd, dd));
          }
          mbar_wait(bars + 8 * (B_G1FULL + 11));
          float xa[2], xb[2];
          stat_table(T1, tag, 1, w, g_stats, g_stats, xa, xb);
          mbar_arrive(bars + 8 * (B_STAB + 1));
          if (tid == 256) TS(27);
          mbar_wait(bars + 8 * (B_HST + 2));
          if (!REP2) break;
        }
        uint32_t gf[10][4];
        mbar_wait(bars + 8 * B_GFULL);
        uint32_t ga = sb + G_OFF + (8 * (tq >> 4) + (tq & 7)) * 128 + (((2 * w + ((tq >> 3) & 1)) ^ ((2 * m2) & 6) ^ (tq & 7)) << 4), gstep = 2048;
        if (step == 2) { ga = sb + DX_OFF + (8 * (tq >> 4) + (tq & 7)) * 16; gstep = 256; }
#pragma unroll
        for (int J = 0; J < 2; J++) ldsm4t(gf[J], ga + J * gstep);
        if (tid == 256) TS(35 + 6 * l);
        uint8_t* dst[2][2];
#pragma unroll
        for (int h = 0; h < 2; h++) {
          if (l == 0) {
            const int ng = 8 * m2 + 2 * w + h, T = ng / 20;
            uint8_t* ub = g_u + (T * 204800 + (ng - 20 * T) * 1024 + (tq & 2) * 64 + (tq & 28) * 4 + (tq & 1) * 8 + (5 * dg >> 1) * 20480);
            dst[h][1] = ub + ((dg & 1) ? 20480 - 512 : 0);
            dst[h][0] = ub + (dg & 1) * 512;
          } else {
            dst[h][0] = dst[h][1] = (uint8_t*)(p.out + (n_to_t(n0 + 8 * h) * DM + 160 * dg + 4 * (tq & 3)));
          }
        }
        float mean[2], rstd[2];
        stats_get(step, n0, tag, mean, rstd);
        if (tid == 256) TS(36 + 6 * l);
        off[0] += mean[0]; off[1] += mean[1];
        const float ov[2] = {step == 3 ? off[0] : 0.f, step == 3 ? off[1] : 0.f};
#pragma unroll
        for (int J = 0; J < 10; J++) {
          if (J + 2 < 10) ldsm4t(gf[J + 2 < 10 ? J + 2 : 0], ga + (J + 2) * gstep);
#pragma unroll
          for (int x = 0; x < 8; x++) {
            const int h = (x >> 1) & 1;
            const uint32_t gwd = gf[J][x >> 1];
            const float t = fmaf(rstd[h], (x & 1) ? bf_hi(gwd) : bf_lo(gwd), 1.f);
            acc[8 * J + x] = fmaf(acc[8 * J + x], t, fmaf(-mean[h], t, ov[h]));
          }
#pragma unroll
          for (int h = 0; h < 2; h++) {
            if (step == 1)
              *(uint2*)(dst[h][(J >> 1) & 1] + (J >> 2) * 20480 + (J & 3) * 256) =
                  make_uint2(pack_bf16(acc[8 * J + 2 * h], acc[8 * J + 2 * h + 1]), pack_bf16(acc[8 * J + 4 + 2 * h], acc[8 * J + 5 + 2 * h]));
            if (step == 3)
              *(float4*)(dst[h][0] + 64 * J) = make_float4(acc[8 * J + 2 * h], acc[8 * J + 2 * h + 1], acc[8 * J + 4 + 2 * h], acc[8 * J + 5 + 2 * h]);
          }
          __syncwarp();
        }
        if (step == 1) {
          bar_sync(3, 128);
          if (tid == 288) { TS(37); mbar_arrive(bars + 8 * B_UST); }
          if (tid < 264) red_rel(&g_ucnt[(tid & 7) * 32]);
          __syncwarp();
          if (tid == 256) TS(38);
        } else if (step == 3) {
          if (tid == 256) {
            TS(43);
            if (m2 == 31 && dg == 3) asm volatile("st.relaxed.gpu.global.u32 [%0], %1;" ::"l"(g_epoch), "r"(tag + 1) : "memory");
          }
        }
      }
    }
  }
}

typedef CUresult (*EncFn)(CUtensorMap*, CUtensorMapDataType, cuuint32_t, void*, const cuuint64_t*, const cuuint64_t*,
                          const cuuint32_t*, const cuuint32_t*, CUtensorMapInterleave, CUtensorMapSwizzle,
                          CUtensorMapL2promotion, CUtensorMapFloatOOBfill);

void encode(EncFn fn, CUtensorMap* m, const void* ptr, int rank, const cuuint64_t* dims, const cuuint64_t* strides, const cuuint32_t* box,
            CUtensorMapSwizzle swz = CU_TENSOR_MAP_SWIZZLE_128B, int prom = 2) {
  cuuint32_t es[5] = {1, 1, 1, 1, 1};
  fn(m, CU_TENSOR_MAP_DATA_TYPE_BFLOAT16, rank, (void*)ptr, dims, strides, box, es, CU_TENSOR_MAP_INTERLEAVE_NONE,
     swz, (CUtensorMapL2promotion)prom, CU_TENSOR_MAP_FLOAT_OOB_FILL_NONE);
}

}

extern "C" void kernel_launch(void* const* d_in, const int* in_sizes, int n_in, void* d_out, int out_size) {
  (void)in_sizes; (void)n_in; (void)out_size;
  Params p;
  typedef const __nv_bfloat16* BP;
  p.x = (BP)d_in[0]; p.lre = (BP)d_in[1]; p.lim = (BP)d_in[2]; p.bre = (BP)d_in[3]; p.bim = (BP)d_in[4];
  p.cre = (BP)d_in[5]; p.cim = (BP)d_in[6]; p.logdt = (BP)d_in[7]; p.dskip = (BP)d_in[8];
  p.k = (BP)d_in[10]; p.v = (BP)d_in[11]; p.shiftk = (BP)d_in[12]; p.ssmk = (BP)d_in[13]; p.ssmD = (BP)d_in[14];
  p.out = (float*)d_out;
  for (int sm = 0; sm < 132; sm++) {
    const int tpc = sm >> 1, side = sm & 1;
    int gpc, gi;
    if (tpc < 32) { gpc = tpc & 7; gi = tpc >> 3; }
    else if (tpc < 60) { gpc = 1 + (tpc - 32) % 7; gi = 4 + (tpc - 32) / 7; }
    else if (tpc < 62) { gpc = tpc - 54; gi = 8; }
    else { gpc = 0; gi = tpc - 58; }
    const int pos = 8 * gpc + gi + (gpc == 7 ? 1 : 0);
    int T1, GP;
    if (pos < 52) { const int hh = pos / 26, x = pos - 26 * hh; T1 = x >> 1; GP = 2 * hh + (x & 1); }
    else { T1 = pos - 52; GP = 4; }
    const int m2 = 8 * (gpc >> 1) + gi, dg = 2 * (gpc & 1) + side;
    p.role[sm] = pos == 65 ? -1 : (T1 | (GP << 4) | (side << 7) | (m2 << 8) | (dg << 14) | ((gi < 8) << 16));
  }
  void* fnp = nullptr;
  cudaDriverEntryPointQueryResult qr;
  cudaGetDriverEntryPoint("cuTensorMapEncodeTiled", &fnp, cudaEnableDefault, &qr);
  EncFn fn = (EncFn)fnp;
  void* gG = nullptr;
  cudaGetSymbolAddress(&gG, g_G);
  void* gKV = nullptr;
  cudaGetSymbolAddress(&gKV, g_kv);
  {
    cuuint64_t dims[5] = {32, 32, 10, 32, 4}, st[4] = {20480, 2048, 64, 655360}; cuuint32_t box[5] = {32, 35, 2, 1, 1};
    encode(fn, &p.mU, gKV, 5, dims, st, box, CU_TENSOR_MAP_SWIZZLE_NONE, 1);
  }
  const cuuint64_t RB = DM * 2;
  {
    p.swap = p.bim < p.bre;
    const char* lo = (const char*)(p.swap ? p.bim : p.bre); const char* hi = (const char*)(p.swap ? p.bre : p.bim);
    cuuint64_t dims[5] = {640, 8, 2, 8, 10}, st[4] = {RB, (cuuint64_t)(hi - lo), 8 * RB, 64 * RB}; cuuint32_t box[5] = {64, 8, 2, 4, 2};
    encode(fn, &p.mB, lo, 5, dims, st, box);
  }
  {
    cuuint64_t dims[5] = {640, 2, 4, 2, 40}, st[4] = {RB, 4 * RB, 2 * RB, 16 * RB}; cuuint32_t box[5] = {64, 2, 4, 2, 10};
    encode(fn, &p.mCre, p.cre, 5, dims, st, box); encode(fn, &p.mCim, p.cim, 5, dims, st, box);
    cuuint64_t dimg[5] = {2048, 2, 4, 2, 40}, stg[4] = {4096, 4 * 4096, 2 * 4096, 16 * 4096};
    encode(fn, &p.mG, gG, 5, dimg, stg, box);
  }
  {
    cuuint64_t dims[4] = {640, 2, 4, 900}, st[3] = {RB, 40 * RB, 2 * RB}; cuuint32_t box[4] = {64, 2, 4, 20};
    encode(fn, &p.mX, p.x, 4, dims, st, box);
    cuuint64_t diml[4] = {640, 2, 4, 16}, stl[3] = {RB, 32 * RB, 2 * RB};
    encode(fn, &p.mXl, p.x + (size_t)1920 * DM, 4, diml, stl, box);
    cuuint32_t boxt[4] = {160, 2, 4, 4};
    encode(fn, &p.mXt, p.x, 4, dims, st, boxt, CU_TENSOR_MAP_SWIZZLE_NONE);
    encode(fn, &p.mXtl, p.x + (size_t)1920 * DM, 4, diml, stl, boxt, CU_TENSOR_MAP_SWIZZLE_NONE);
    cuuint64_t dk[3] = {640, 2000, 4}, sk[2] = {RB, 16 * RB}; cuuint32_t bk[3] = {32, 19, 4}, bv[3] = {32, 17, 4};
    encode(fn, &p.mK, p.k, 3, dk, sk, bk, CU_TENSOR_MAP_SWIZZLE_NONE);
    encode(fn, &p.mV, p.v, 3, dk, sk, bv, CU_TENSOR_MAP_SWIZZLE_NONE);
  }
  cudaFuncSetAttribute(fused_kernel, cudaFuncAttributeMaxDynamicSharedMemorySize, SMEM_BYTES);
  cudaLaunchConfig_t cfg = {};
  cfg.gridDim = dim3(132); cfg.blockDim = dim3(512); cfg.dynamicSmemBytes = SMEM_BYTES; cfg.stream = cudaStreamPerThread;
  cudaLaunchKernelEx(&cfg, fused_kernel, p);
}
```

```cpp
#include <cuda_runtime.h>
#include <cuda.h>
#include <cuda_bf16.h>
#include <stdint.h>

namespace {

constexpr int SEQ = 2048, DM = 640;
constexpr int NT1 = 13;
#define EXP 0
#define WPF1 3
#define WPF2 7
#define CPOLL 10
#define KV0 1
#define TAPLATE 1
#define STG_D 3
#define STG_KK 1
#define HOLD0 1
#define WREL 0
#define UREL 1
#define TSL 1
#define STG0 2
#define WTAIL 1
#define PFD 1
#define TAPW 0
#define TPF 4
#define CPF 0
#define MK0 7
#define MK1 4
#define PACE 300
#define XB0 7
#define TAPN 2
#define REP2 0
#define UNSAFE 0
#define PAUSE_K 5
constexpr uint32_t SPIN_LIMIT = 1u << 22;

__device__ __align__(1024) uint8_t g_h[2 * 32 * 20 * 8192];
__device__ __align__(1024) uint8_t g_u[NT1 * 10 * 20480];
__device__ __align__(1024) uint8_t g_kv[DM * 4096];
__device__ __align__(1024) uint8_t g_G[DM * 4096];
__device__ __align__(128) uint4 g_E[2 * NT1 * DM];
__device__ __align__(128) uint4 g_stats[4 * 4 * SEQ];
__device__ __align__(128) uint4 g_sB[DM * 2];
__device__ __align__(128) unsigned g_hcnt[2 * 2 * 8 * 32];
__device__ __align__(128) unsigned g_ucnt[8 * 32];
__device__ __align__(128) unsigned g_kvcnt[16 * 32];
__device__ __align__(128) unsigned g_gcnt[16 * 32];
__device__ __align__(128) unsigned g_epoch[32] = {1};
#define TS(i) do {} while (0)

struct Params {
  CUtensorMap mX, mB, mXl, mK, mV, mXt, mXtl, mCre, mCim, mG, mU;
  const __nv_bfloat16 *x, *lre, *lim, *bre, *bim, *cre, *cim, *logdt, *dskip, *k, *v, *shiftk, *ssmk, *ssmD;
  float* out;
  int swap;
  int role[132];
};

constexpr uint32_t sb = 1024;
constexpr uint32_t G1_STAGE = 36864, G1_XOFF = 16384;
constexpr int S1 = 4;
constexpr uint32_t XT_OFF = 159744, KS_OFF = 180224, KV_PIECE = 9216;
constexpr uint32_t G2_XB = 8192, G2_WB = 20480, G2_WOFF = 57344, G_OFF = 200704;
constexpr uint32_t X1_OFF = 139264;
constexpr int S2 = 7;
constexpr uint32_t CV_OFF = KS_OFF, CV_K = 128, CV_PL = 2240, CV_U = CV_K + 4096, CV_B = KV_PIECE;
constexpr uint32_t MISC = 226304;
constexpr uint32_t BAR_OFF = MISC;
constexpr int B_G1FULL = 0, B_G1DONE = 20, B_G2FULL = 40,
              B_G2DONE = 85, B_GFULL = 125, B_EP = 126, B_H1 = 127  , B_CVFULL = 129  , B_STG = 134  , B_REL = 136  , B_SFREE = 138, B_UST = 142,
              B_GO = 139  , B_PUB = 147,
              B_CVDONE = 148  , B_STAB = 153  , B_XFREE = 155, B_HST = 156  ,
              B_CTAB = 160, B_PREP = 161, B_XT = 162, B_KV = 163  , B_PREP2 = 84, B_PD = 168  ,
              B_XV1 = 173  , B_XV2 = 183  , B_RETRY = 223;
constexpr uint32_t bars = sb + BAR_OFF;
constexpr uint32_t STAB_OFF = MISC + 1792;
constexpr uint32_t CTAB_OFF = STAB_OFF + 640;
constexpr uint32_t DTAB_OFF = CTAB_OFF + 1536;
constexpr uint32_t EP_OFF = DTAB_OFF + 320;
constexpr uint32_t SO_OFF = EP_OFF + 32;
constexpr uint32_t TAP_OFF = 147456;
constexpr uint32_t MX0_OFF = TAP_OFF + 1280, MX1_OFF = G_OFF + 20480;
constexpr uint32_t DX_OFF = MX1_OFF + 2560;
constexpr uint32_t SMEM_BYTES = 232448;
static_assert(SO_OFF + 1536 <= SMEM_BYTES, "smem");

__device__ __forceinline__ void trap_if(bool c) { asm volatile("{\n.reg .pred p;\nsetp.ne.u32 p, %0, 0;\n@p trap;\n}\n" ::"r"((uint32_t)c)); }
__device__ __forceinline__ uint32_t smem_u32(const void* p) { return (uint32_t)__cvta_generic_to_shared(p); }
__device__ __forceinline__ void mbar_init(uint32_t bar, int cnt) { asm volatile("mbarrier.init.shared::cta.b64 [%0], %1;" ::"r"(bar), "r"(cnt) : "memory"); }
__device__ __forceinline__ void mbar_expect_tx(uint32_t bar, int bytes) { asm volatile("mbarrier.arrive.expect_tx.shared::cta.b64 _, [%0], %1;" ::"r"(bar), "r"(bytes) : "memory"); }
__device__ __forceinline__ void mbar_arrive(uint32_t bar) { asm volatile("mbarrier.arrive.shared::cta.b64 _, [%0];" ::"r"(bar) : "memory"); }
__device__ __forceinline__ bool elect_one() {
  uint32_t e; asm volatile("{\n.reg .pred P;\nelect.sync _|P, 0xffffffff;\nselp.u32 %0, 1, 0, P;\n}\n" : "=r"(e)); return e != 0;
}
__device__ __forceinline__ void mbar_wait(uint32_t bar) {
  asm volatile(
      "{\n.reg .pred p;\n.reg .u32 c;\nmov.u32 c, 0;\n"
      "W_%=:\nmbarrier.try_wait.parity.shared::cta.b64 p, [%0], 0;\n@p bra D_%=;\n"
      "add.u32 c, c, 1;\nsetp.lt.u32 p, c, %1;\n@p bra W_%=;\ntrap;\nD_%=:\n}\n" ::"r"(bar), "n"(SPIN_LIMIT) : "memory");
}
__device__ __forceinline__ uint32_t mbar_test(uint32_t bar) {
  uint32_t ok;
  asm volatile("{\n.reg .pred p;\nmbarrier.test_wait.parity.shared::cta.b64 p, [%1], 0;\nselp.u32 %0, 1, 0, p;\n}\n" : "=r"(ok) : "r"(bar) : "memory");
  return ok;
}
__device__ __forceinline__ void tma3(uint32_t dst, const CUtensorMap* m, int c0, int c1, int c2, uint32_t bar) {
  asm volatile("cp.async.bulk.tensor.3d.shared::cluster.global.mbarrier::complete_tx::bytes [%0], [%1, {%3,%4,%5}], [%2];"
               ::"r"(dst), "l"(m), "r"(bar), "r"(c0), "r"(c1), "r"(c2) : "memory");
}
__device__ __forceinline__ void tma4(uint32_t dst, const CUtensorMap* m, int c0, int c1, int c2, int c3, uint32_t bar) {
  asm volatile("cp.async.bulk.tensor.4d.shared::cluster.global.mbarrier::complete_tx::bytes [%0], [%1, {%3,%4,%5,%6}], [%2];"
               ::"r"(dst), "l"(m), "r"(bar), "r"(c0), "r"(c1), "r"(c2), "r"(c3) : "memory");
}
__device__ __forceinline__ void tma5(uint32_t dst, const CUtensorMap* m, int c0, int c1, int c2, int c3, int c4, uint32_t bar) {
  asm volatile("cp.async.bulk.tensor.5d.shared::cluster.global.mbarrier::complete_tx::bytes [%0], [%1, {%3,%4,%5,%6,%7}], [%2];"
               ::"r"(dst), "l"(m), "r"(bar), "r"(c0), "r"(c1), "r"(c2), "r"(c3), "r"(c4) : "memory");
}
__device__ __forceinline__ void bulk_g2s(uint32_t dst, const void* src, int bytes, uint32_t bar) {
  asm volatile("cp.async.bulk.shared::cluster.global.mbarrier::complete_tx::bytes [%0], [%1], %2, [%3];"
               ::"r"(dst), "l"(src), "r"(bytes), "r"(bar) : "memory");
}
__device__ __forceinline__ void bulk_s2g(void* dst, uint32_t src, int bytes) {
  asm volatile("cp.async.bulk.global.shared::cta.bulk_group [%0], [%1], %2;" ::"l"(dst), "r"(src), "r"(bytes) : "memory");
}
__device__ __forceinline__ void l2_prefetch(const void* src, int bytes) {
  asm volatile("cp.async.bulk.prefetch.L2.global [%0], %1;" ::"l"(src), "r"(bytes) : "memory");
}
__device__ __forceinline__ void wgmma_fence() { asm volatile("wgmma.fence.sync.aligned;" ::: "memory"); }
__device__ __forceinline__ void wgmma_commit() { asm volatile("wgmma.commit_group.sync.aligned;" ::: "memory"); }
template <int N> __device__ __forceinline__ void wgmma_wait() { asm volatile("wgmma.wait_group.sync.aligned %0;" ::"n"(N) : "memory"); }
__host__ __device__ constexpr uint32_t desc_lo(uint32_t addr, uint32_t lbo) { return ((addr & 0x3FFFF) >> 4) | ((lbo >> 4) << 16); }
__host__ __device__ constexpr uint32_t desc_hi(uint32_t sbo, uint32_t swz) { return (sbo >> 4) | (swz << 30); }
__device__ __forceinline__ void bar_sync(int id, int n) { asm volatile("bar.sync %0, %1;" ::"r"(id), "r"(n) : "memory"); }
__device__ __forceinline__ uint32_t lds32(uint32_t a) { uint32_t v; asm volatile("ld.shared.u32 %0, [%1];" : "=r"(v) : "r"(a) : "memory"); return v; }
__device__ __forceinline__ float2 lds64f(uint32_t a) { float2 v; asm volatile("ld.shared.v2.f32 {%0,%1}, [%2];" : "=f"(v.x), "=f"(v.y) : "r"(a) : "memory"); return v; }
__device__ __forceinline__ float4 lds128f(uint32_t a) { float4 v; asm volatile("ld.shared.v4.f32 {%0,%1,%2,%3}, [%4];" : "=f"(v.x), "=f"(v.y), "=f"(v.z), "=f"(v.w) : "r"(a) : "memory"); return v; }
__device__ __forceinline__ void ldsm4t(uint32_t (&r)[4], uint32_t a) {
  asm volatile("ldmatrix.sync.aligned.m8n8.x4.trans.shared.b16 {%0,%1,%2,%3}, [%4];" : "=r"(r[0]), "=r"(r[1]), "=r"(r[2]), "=r"(r[3]) : "r"(a) : "memory");
}
__device__ __forceinline__ uint4 ldv128(const void* a) { uint4 v; asm volatile("ld.global.nc.v4.u32 {%0,%1,%2,%3}, [%4];" : "=r"(v.x), "=r"(v.y), "=r"(v.z), "=r"(v.w) : "l"(a) : "memory"); return v; }
__device__ __forceinline__ uint2 ldv64(const void* a) { uint2 v; asm volatile("ld.global.nc.v2.u32 {%0,%1}, [%2];" : "=r"(v.x), "=r"(v.y) : "l"(a) : "memory"); return v; }
__device__ __forceinline__ uint32_t ldv16(const void* a) { uint32_t v; asm volatile("ld.global.nc.u16 %0, [%1];" : "=r"(v) : "l"(a) : "memory"); return v; }
__device__ __forceinline__ void sts128(uint32_t a, uint4 v) { asm volatile("st.shared.v4.u32 [%0], {%1,%2,%3,%4};" ::"r"(a), "r"(v.x), "r"(v.y), "r"(v.z), "r"(v.w) : "memory"); }
__device__ __forceinline__ void sts32(uint32_t a, uint32_t v) { asm volatile("st.shared.u32 [%0], %1;" ::"r"(a), "r"(v) : "memory"); }
__device__ __forceinline__ void sts64f(uint32_t a, float x, float y) { asm volatile("st.shared.v2.f32 [%0], {%1,%2};" ::"r"(a), "f"(x), "f"(y) : "memory"); }
__device__ __forceinline__ void red_rlx(unsigned* p) { asm volatile("red.relaxed.gpu.global.add.u32 [%0], 1;" ::"l"(p) : "memory"); }
__device__ __forceinline__ void red_rel(unsigned* p) { asm volatile("red.release.gpu.global.add.u32 [%0], 1;" ::"l"(p) : "memory"); }
__device__ __forceinline__ void fence_async_global() { asm volatile("fence.proxy.async.global;" ::: "memory"); }
__device__ __forceinline__ void fence_async_smem() { asm volatile("fence.proxy.async.shared::cta;" ::: "memory"); }
__device__ __forceinline__ void rec_st(uint4* p, float a, float b, unsigned tag) {
  asm volatile("{\n.reg .b128 t;\n.reg .b64 lo, hi;\nmov.b64 lo, {%1,%2};\nmov.b64 hi, {%3,%3};\nmov.b128 t, {lo,hi};\n"
               "st.relaxed.gpu.global.b128 [%0], t;\n}\n" ::"l"(p), "r"(__float_as_uint(a)), "r"(__float_as_uint(b)), "r"(tag) : "memory");
}
__device__ __forceinline__ unsigned rec_ld(const uint4* p, float& a, float& b) {
  unsigned x, y, t;
  asm volatile("{\n.reg .b128 t;\n.reg .b64 lo, hi;\n.reg .b32 u;\nld.relaxed.gpu.global.b128 t, [%3];\nmov.b128 {lo,hi}, t;\n"
               "mov.b64 {%0,%1}, lo;\nmov.b64 {%2,u}, hi;\n}\n" : "=r"(x), "=r"(y), "=r"(t) : "l"(p) : "memory");
  a = __uint_as_float(x); b = __uint_as_float(y);
  return t;
}
__device__ __forceinline__ unsigned ld_rlx(const unsigned* p) { unsigned v; asm volatile("ld.relaxed.gpu.global.u32 %0, [%1];" : "=r"(v) : "l"(p) : "memory"); return v; }
__device__ __forceinline__ void flag_poll(const unsigned* p, unsigned target) {
  uint32_t it = 0;
  while (!__all_sync(0xffffffffu, (int)(ld_rlx(p) - target) >= 0)) { trap_if(++it > SPIN_LIMIT); }
  asm volatile("fence.acquire.gpu;" ::: "memory");
}
__device__ __forceinline__ void cnt_poll(const unsigned* p, unsigned target) {
  unsigned a = ld_rlx(p); __nanosleep(100);
  unsigned b = ld_rlx(p); __nanosleep(100);
  unsigned c = ld_rlx(p);
  uint32_t it = 0;
  while (true) {
    if (__all_sync(0xffffffffu, (int)(a - target) >= 0)) break;
    a = ld_rlx(p);
    if (__all_sync(0xffffffffu, (int)(b - target) >= 0)) break;
    b = ld_rlx(p);
    if (__all_sync(0xffffffffu, (int)(c - target) >= 0)) break;
    c = ld_rlx(p);
    trap_if(++it > SPIN_LIMIT);
  }
  asm volatile("fence.acquire.gpu;" ::: "memory");
}
template <int N>
__device__ __forceinline__ void validate_block(uint32_t landed, uint32_t full, uint32_t dst, const uint8_t* src, int n, uint32_t woff, uint32_t par, uint32_t& ph) {
  mbar_wait(landed);
  uint32_t it = 0;
  while (true) {
    uint32_t bad = 0;
#pragma unroll
    for (int i = 0; i < N; i++) bad |= lds32(dst + woff + 1024 * (i < N - 4 ? i : min(i, n - 1))) ^ par;
    if (!__any_sync(0xffffffffu, bad & 1)) break;
    fence_async_smem();
    __syncwarp();
    if (elect_one()) { mbar_expect_tx(bars + 8 * B_RETRY, n * 1024); bulk_g2s(dst, src, n * 1024, bars + 8 * B_RETRY); }
    uint32_t ok, spins = 0;
    do {
      asm volatile("{\n.reg .pred p;\nmbarrier.try_wait.parity.shared::cta.b64 p, [%1], %2;\nselp.u32 %0, 1, 0, p;\n}\n" : "=r"(ok) : "r"(bars + 8 * B_RETRY), "r"(ph) : "memory");
      trap_if(++spins > SPIN_LIMIT);
    } while (!__all_sync(0xffffffffu, ok));
    ph ^= 1;
    trap_if(++it > 100000);
  }
  if ((threadIdx.x & 31) == 0) mbar_arrive(full);
}
__device__ __forceinline__ uint32_t tag_word(uint32_t v, bool c, uint32_t par) { return c ? (v & ~1u) | par : v; }
__device__ __forceinline__ void h_release(int idx, int T, int i) {
  const int Q = (i & 2) ? (T + 2) / 3 - 1 : T / 3;
  if (Q >= 0 && Q < 4 && ((i & 2) == 0 || T % 3 == 0)) { if ((UNSAFE & 2) && idx >= 2) red_rlx(&g_hcnt[(idx * 8 + 2 * Q + (i & 1)) * 32]); else red_rlx(&g_hcnt[(idx * 8 + 2 * Q + (i & 1)) * 32]); }
}
__device__ __forceinline__ uint32_t pack_bf16(float lo, float hi) {
  uint32_t r; asm("cvt.rn.bf16x2.f32 %0, %1, %2;" : "=r"(r) : "f"(hi), "f"(lo)); return r;
}
__device__ __forceinline__ float bf_lo(uint32_t w) { return __uint_as_float(w << 16); }
__device__ __forceinline__ float bf_hi(uint32_t w) { return __uint_as_float(w & 0xffff0000u); }
__device__ __forceinline__ uint32_t hmul2(uint32_t a, uint32_t b) {
  __nv_bfloat162 r = __hmul2_rn(*(__nv_bfloat162*)&a, *(__nv_bfloat162*)&b); return *(uint32_t*)&r;
}
__device__ __forceinline__ uint32_t hadd2(uint32_t a, uint32_t b) {
  __nv_bfloat162 r = __hadd2_rn(*(__nv_bfloat162*)&a, *(__nv_bfloat162*)&b); return *(uint32_t*)&r;
}
__device__ __forceinline__ float2 cmul(float2 a, float2 b) { return make_float2(a.x * b.x - a.y * b.y, a.x * b.y + a.y * b.x); }
__device__ __forceinline__ float2 cfma(float2 a, float2 b, float2 c) {
  return make_float2(fmaf(a.x, b.x, fmaf(-a.y, b.y, c.x)), fmaf(a.x, b.y, fmaf(a.y, b.x, c.y)));
}
template <int N> __device__ __forceinline__ void fence_regs(float (&a)[N]) {
#pragma unroll
  for (int i = 0; i < N; i++) asm volatile("" : "+f"(a[i])::"memory");
}
__device__ __forceinline__ int tid_opaque() { int t; asm volatile("mov.u32 %0, %%tid.x;" : "=r"(t)); return t; }
struct Role { int T1, GP, side, m2, dg, cch0; bool last, has2; };
__device__ __forceinline__ Role unpack_role(int x) {
  Role r; r.T1 = x & 15; r.GP = (x >> 4) & 7; r.side = (x >> 7) & 1; r.m2 = (x >> 8) & 63; r.dg = (x >> 14) & 3;
  r.has2 = (x >> 16) & 1; r.last = r.T1 == NT1 - 1; r.cch0 = 160 * r.dg + r.m2; return r;
}
__device__ __forceinline__ Role fresh_role(int x) { asm volatile("" : "+r"(x)); return unpack_role(__shfl_sync(0xffffffffu, x, 0)); }
#define ROLE(x) const Role R_ = fresh_role(x); const int T1 = R_.T1, GP = R_.GP, side = R_.side, m2 = R_.m2, dg = R_.dg, cch0 = R_.cch0; \
  const bool last = R_.last, has2 = R_.has2; (void)T1; (void)GP; (void)side; (void)m2; (void)dg; (void)cch0; (void)last; (void)has2;
__device__ __forceinline__ int n_to_t(int n) {
  int T = n / 160, nl = n - T * 160;
  int L = (T == NT1 - 1) ? 32 : 40;
  return T * 160 + L * ((nl & 7) >> 1) + 2 * (nl >> 3) + (nl & 1);
}

template<int TA> __device__ __forceinline__ void wgmma_n160(float (&d)[80], uint32_t alo, uint32_t ahi, uint32_t blo, uint32_t bhi){
  asm volatile("{\n.reg .b64 da, db;\nmov.b64 da, {%80,%81};\nmov.b64 db, {%82,%83};\n"
    "wgmma.mma_async.sync.aligned.m64n160k16.f32.bf16.bf16 {%0, %1, %2, %3, %4, %5, %6, %7, %8, %9, %10, %11, %12, %13, %14, %15, %16, %17, %18, %19, %20, %21, %22, %23, %24, %25, %26, %27, %28, %29, %30, %31, %32, %33, %34, %35, %36, %37, %38, %39, %40, %41, %42, %43, %44, %45, %46, %47, %48, %49, %50, %51, %52, %53, %54, %55, %56, %57, %58, %59, %60, %61, %62, %63, %64, %65, %66, %67, %68, %69, %70, %71, %72, %73, %74, %75, %76, %77, %78, %79}, da, db, 1, 1, 1, %84, 0;\n}\n"
    : "+f"(d[0]), "+f"(d[1]), "+f"(d[2]), "+f"(d[3]), "+f"(d[4]), "+f"(d[5]), "+f"(d[6]), "+f"(d[7]), "+f"(d[8]), "+f"(d[9]), "+f"(d[10]), "+f"(d[11]), "+f"(d[12]), "+f"(d[13]), "+f"(d[14]), "+f"(d[15]), "+f"(d[16]), "+f"(d[17]), "+f"(d[18]), "+f"(d[19]), "+f"(d[20]), "+f"(d[21]), "+f"(d[22]), "+f"(d[23]), "+f"(d[24]), "+f"(d[25]), "+f"(d[26]), "+f"(d[27]), "+f"(d[28]), "+f"(d[29]), "+f"(d[30]), "+f"(d[31]), "+f"(d[32]), "+f"(d[33]), "+f"(d[34]), "+f"(d[35]), "+f"(d[36]), "+f"(d[37]), "+f"(d[38]), "+f"(d[39]), "+f"(d[40]), "+f"(d[41]), "+f"(d[42]), "+f"(d[43]), "+f"(d[44]), "+f"(d[45]), "+f"(d[46]), "+f"(d[47]), "+f"(d[48]), "+f"(d[49]), "+f"(d[50]), "+f"(d[51]), "+f"(d[52]), "+f"(d[53]), "+f"(d[54]), "+f"(d[55]), "+f"(d[56]), "+f"(d[57]), "+f"(d[58]), "+f"(d[59]), "+f"(d[60]), "+f"(d[61]), "+f"(d[62]), "+f"(d[63]), "+f"(d[64]), "+f"(d[65]), "+f"(d[66]), "+f"(d[67]), "+f"(d[68]), "+f"(d[69]), "+f"(d[70]), "+f"(d[71]), "+f"(d[72]), "+f"(d[73]), "+f"(d[74]), "+f"(d[75]), "+f"(d[76]), "+f"(d[77]), "+f"(d[78]), "+f"(d[79])
    : "r"(alo), "r"(ahi), "r"(blo), "r"(bhi), "n"(TA));
}
__device__ __forceinline__ void wgmma_rs_n160(float (&d)[80], uint32_t a0, uint32_t a1, uint32_t a2, uint32_t a3, uint32_t blo){
  asm volatile("{\n.reg .b64 db;\nmov.b64 db, {%84,8};\nwgmma.mma_async.sync.aligned.m64n160k16.f32.bf16.bf16 {%0, %1, %2, %3, %4, %5, %6, %7, %8, %9, %10, %11, %12, %13, %14, %15, %16, %17, %18, %19, %20, %21, %22, %23, %24, %25, %26, %27, %28, %29, %30, %31, %32, %33, %34, %35, %36, %37, %38, %39, %40, %41, %42, %43, %44, %45, %46, %47, %48, %49, %50, %51, %52, %53, %54, %55, %56, %57, %58, %59, %60, %61, %62, %63, %64, %65, %66, %67, %68, %69, %70, %71, %72, %73, %74, %75, %76, %77, %78, %79}, {%80,%81,%82,%83}, db, 1, 1, 1, 0;\n}\n"
    : "+f"(d[0]), "+f"(d[1]), "+f"(d[2]), "+f"(d[3]), "+f"(d[4]), "+f"(d[5]), "+f"(d[6]), "+f"(d[7]), "+f"(d[8]), "+f"(d[9]), "+f"(d[10]), "+f"(d[11]), "+f"(d[12]), "+f"(d[13]), "+f"(d[14]), "+f"(d[15]), "+f"(d[16]), "+f"(d[17]), "+f"(d[18]), "+f"(d[19]), "+f"(d[20]), "+f"(d[21]), "+f"(d[22]), "+f"(d[23]), "+f"(d[24]), "+f"(d[25]), "+f"(d[26]), "+f"(d[27]), "+f"(d[28]), "+f"(d[29]), "+f"(d[30]), "+f"(d[31]), "+f"(d[32]), "+f"(d[33]), "+f"(d[34]), "+f"(d[35]), "+f"(d[36]), "+f"(d[37]), "+f"(d[38]), "+f"(d[39]), "+f"(d[40]), "+f"(d[41]), "+f"(d[42]), "+f"(d[43]), "+f"(d[44]), "+f"(d[45]), "+f"(d[46]), "+f"(d[47]), "+f"(d[48]), "+f"(d[49]), "+f"(d[50]), "+f"(d[51]), "+f"(d[52]), "+f"(d[53]), "+f"(d[54]), "+f"(d[55]), "+f"(d[56]), "+f"(d[57]), "+f"(d[58]), "+f"(d[59]), "+f"(d[60]), "+f"(d[61]), "+f"(d[62]), "+f"(d[63]), "+f"(d[64]), "+f"(d[65]), "+f"(d[66]), "+f"(d[67]), "+f"(d[68]), "+f"(d[69]), "+f"(d[70]), "+f"(d[71]), "+f"(d[72]), "+f"(d[73]), "+f"(d[74]), "+f"(d[75]), "+f"(d[76]), "+f"(d[77]), "+f"(d[78]), "+f"(d[79])
    : "r"(a0), "r"(a1), "r"(a2), "r"(a3), "r"(blo));
}
template<int N> __device__ __forceinline__ void wgmma_rs_hi(float (&d)[64], uint32_t a0, uint32_t a1, uint32_t a2, uint32_t a3, uint32_t blo);
template<> __device__ __forceinline__ void wgmma_rs_hi<16>(float (&d)[64], uint32_t a0, uint32_t a1, uint32_t a2, uint32_t a3, uint32_t blo){
  asm volatile("{\n.reg .b64 db;\nmov.b64 db, {%12,8};\nwgmma.mma_async.sync.aligned.m64n16k16.f32.bf16.bf16 {%0, %1, %2, %3, %4, %5, %6, %7}, {%8,%9,%10,%11}, db, 1, 1, 1, 0;\n}\n"
    : "+f"(d[56]), "+f"(d[57]), "+f"(d[58]), "+f"(d[59]), "+f"(d[60]), "+f"(d[61]), "+f"(d[62]), "+f"(d[63])
    : "r"(a0), "r"(a1), "r"(a2), "r"(a3), "r"(blo));
}
template<> __device__ __forceinline__ void wgmma_rs_hi<32>(float (&d)[64], uint32_t a0, uint32_t a1, uint32_t a2, uint32_t a3, uint32_t blo){
  asm volatile("{\n.reg .b64 db;\nmov.b64 db, {%20,8};\nwgmma.mma_async.sync.aligned.m64n32k16.f32.bf16.bf16 {%0, %1, %2, %3, %4, %5, %6, %7, %8, %9, %10, %11, %12, %13, %14, %15}, {%16,%17,%18,%19}, db, 1, 1, 1, 0;\n}\n"
    : "+f"(d[48]), "+f"(d[49]), "+f"(d[50]), "+f"(d[51]), "+f"(d[52]), "+f"(d[53]), "+f"(d[54]), "+f"(d[55]), "+f"(d[56]), "+f"(d[57]), "+f"(d[58]), "+f"(d[59]), "+f"(d[60]), "+f"(d[61]), "+f"(d[62]), "+f"(d[63])
    : "r"(a0), "r"(a1), "r"(a2), "r"(a3), "r"(blo));
}
template<> __device__ __forceinline__ void wgmma_rs_hi<48>(float (&d)[64], uint32_t a0, uint32_t a1, uint32_t a2, uint32_t a3, uint32_t blo){
  asm volatile("{\n.reg .b64 db;\nmov.b64 db, {%28,8};\nwgmma.mma_async.sync.aligned.m64n48k16.f32.bf16.bf16 {%0, %1, %2, %3, %4, %5, %6, %7, %8, %9, %10, %11, %12, %13, %14, %15, %16, %17, %18, %19, %20, %21, %22, %23}, {%24,%25,%26,%27}, db, 1, 1, 1, 0;\n}\n"
    : "+f"(d[40]), "+f"(d[41]), "+f"(d[42]), "+f"(d[43]), "+f"(d[44]), "+f"(d[45]), "+f"(d[46]), "+f"(d[47]), "+f"(d[48]), "+f"(d[49]), "+f"(d[50]), "+f"(d[51]), "+f"(d[52]), "+f"(d[53]), "+f"(d[54]), "+f"(d[55]), "+f"(d[56]), "+f"(d[57]), "+f"(d[58]), "+f"(d[59]), "+f"(d[60]), "+f"(d[61]), "+f"(d[62]), "+f"(d[63])
    : "r"(a0), "r"(a1), "r"(a2), "r"(a3), "r"(blo));
}
template<> __device__ __forceinline__ void wgmma_rs_hi<64>(float (&d)[64], uint32_t a0, uint32_t a1, uint32_t a2, uint32_t a3, uint32_t blo){
  asm volatile("{\n.reg .b64 db;\nmov.b64 db, {%36,8};\nwgmma.mma_async.sync.aligned.m64n64k16.f32.bf16.bf16 {%0, %1, %2, %3, %4, %5, %6, %7, %8, %9, %10, %11, %12, %13, %14, %15, %16, %17, %18, %19, %20, %21, %22, %23, %24, %25, %26, %27, %28, %29, %30, %31}, {%32,%33,%34,%35}, db, 1, 1, 1, 0;\n}\n"
    : "+f"(d[32]), "+f"(d[33]), "+f"(d[34]), "+f"(d[35]), "+f"(d[36]), "+f"(d[37]), "+f"(d[38]), "+f"(d[39]), "+f"(d[40]), "+f"(d[41]), "+f"(d[42]), "+f"(d[43]), "+f"(d[44]), "+f"(d[45]), "+f"(d[46]), "+f"(d[47]), "+f"(d[48]), "+f"(d[49]), "+f"(d[50]), "+f"(d[51]), "+f"(d[52]), "+f"(d[53]), "+f"(d[54]), "+f"(d[55]), "+f"(d[56]), "+f"(d[57]), "+f"(d[58]), "+f"(d[59]), "+f"(d[60]), "+f"(d[61]), "+f"(d[62]), "+f"(d[63])
    : "r"(a0), "r"(a1), "r"(a2), "r"(a3), "r"(blo));
}
template<> __device__ __forceinline__ void wgmma_rs_hi<80>(float (&d)[64], uint32_t a0, uint32_t a1, uint32_t a2, uint32_t a3, uint32_t blo){
  asm volatile("{\n.reg .b64 db;\nmov.b64 db, {%44,8};\nwgmma.mma_async.sync.aligned.m64n80k16.f32.bf16.bf16 {%0, %1, %2, %3, %4, %5, %6, %7, %8, %9, %10, %11, %12, %13, %14, %15, %16, %17, %18, %19, %20, %21, %22, %23, %24, %25, %26, %27, %28, %29, %30, %31, %32, %33, %34, %35, %36, %37, %38, %39}, {%40,%41,%42,%43}, db, 1, 1, 1, 0;\n}\n"
    : "+f"(d[24]), "+f"(d[25]), "+f"(d[26]), "+f"(d[27]), "+f"(d[28]), "+f"(d[29]), "+f"(d[30]), "+f"(d[31]), "+f"(d[32]), "+f"(d[33]), "+f"(d[34]), "+f"(d[35]), "+f"(d[36]), "+f"(d[37]), "+f"(d[38]), "+f"(d[39]), "+f"(d[40]), "+f"(d[41]), "+f"(d[42]), "+f"(d[43]), "+f"(d[44]), "+f"(d[45]), "+f"(d[46]), "+f"(d[47]), "+f"(d[48]), "+f"(d[49]), "+f"(d[50]), "+f"(d[51]), "+f"(d[52]), "+f"(d[53]), "+f"(d[54]), "+f"(d[55]), "+f"(d[56]), "+f"(d[57]), "+f"(d[58]), "+f"(d[59]), "+f"(d[60]), "+f"(d[61]), "+f"(d[62]), "+f"(d[63])
    : "r"(a0), "r"(a1), "r"(a2), "r"(a3), "r"(blo));
}
template<> __device__ __forceinline__ void wgmma_rs_hi<96>(float (&d)[64], uint32_t a0, uint32_t a1, uint32_t a2, uint32_t a3, uint32_t blo){
  asm volatile("{\n.reg .b64 db;\nmov.b64 db, {%52,8};\nwgmma.mma_async.sync.aligned.m64n96k16.f32.bf16.bf16 {%0, %1, %2, %3, %4, %5, %6, %7, %8, %9, %10, %11, %12, %13, %14, %15, %16, %17, %18, %19, %20, %21, %22, %23, %24, %25, %26, %27, %28, %29, %30, %31, %32, %33, %34, %35, %36, %37, %38, %39, %40, %41, %42, %43, %44, %45, %46, %47}, {%48,%49,%50,%51}, db, 1, 1, 1, 0;\n}\n"
    : "+f"(d[16]), "+f"(d[17]), "+f"(d[18]), "+f"(d[19]), "+f"(d[20]), "+f"(d[21]), "+f"(d[22]), "+f"(d[23]), "+f"(d[24]), "+f"(d[25]), "+f"(d[26]), "+f"(d[27]), "+f"(d[28]), "+f"(d[29]), "+f"(d[30]), "+f"(d[31]), "+f"(d[32]), "+f"(d[33]), "+f"(d[34]), "+f"(d[35]), "+f"(d[36]), "+f"(d[37]), "+f"(d[38]), "+f"(d[39]), "+f"(d[40]), "+f"(d[41]), "+f"(d[42]), "+f"(d[43]), "+f"(d[44]), "+f"(d[45]), "+f"(d[46]), "+f"(d[47]), "+f"(d[48]), "+f"(d[49]), "+f"(d[50]), "+f"(d[51]), "+f"(d[52]), "+f"(d[53]), "+f"(d[54]), "+f"(d[55]), "+f"(d[56]), "+f"(d[57]), "+f"(d[58]), "+f"(d[59]), "+f"(d[60]), "+f"(d[61]), "+f"(d[62]), "+f"(d[63])
    : "r"(a0), "r"(a1), "r"(a2), "r"(a3), "r"(blo));
}
template<> __device__ __forceinline__ void wgmma_rs_hi<112>(float (&d)[64], uint32_t a0, uint32_t a1, uint32_t a2, uint32_t a3, uint32_t blo){
  asm volatile("{\n.reg .b64 db;\nmov.b64 db, {%60,8};\nwgmma.mma_async.sync.aligned.m64n112k16.f32.bf16.bf16 {%0, %1, %2, %3, %4, %5, %6, %7, %8, %9, %10, %11, %12, %13, %14, %15, %16, %17, %18, %19, %20, %21, %22, %23, %24, %25, %26, %27, %28, %29, %30, %31, %32, %33, %34, %35, %36, %37, %38, %39, %40, %41, %42, %43, %44, %45, %46, %47, %48, %49, %50, %51, %52, %53, %54, %55}, {%56,%57,%58,%59}, db, 1, 1, 1, 0;\n}\n"
    : "+f"(d[8]), "+f"(d[9]), "+f"(d[10]), "+f"(d[11]), "+f"(d[12]), "+f"(d[13]), "+f"(d[14]), "+f"(d[15]), "+f"(d[16]), "+f"(d[17]), "+f"(d[18]), "+f"(d[19]), "+f"(d[20]), "+f"(d[21]), "+f"(d[22]), "+f"(d[23]), "+f"(d[24]), "+f"(d[25]), "+f"(d[26]), "+f"(d[27]), "+f"(d[28]), "+f"(d[29]), "+f"(d[30]), "+f"(d[31]), "+f"(d[32]), "+f"(d[33]), "+f"(d[34]), "+f"(d[35]), "+f"(d[36]), "+f"(d[37]), "+f"(d[38]), "+f"(d[39]), "+f"(d[40]), "+f"(d[41]), "+f"(d[42]), "+f"(d[43]), "+f"(d[44]), "+f"(d[45]), "+f"(d[46]), "+f"(d[47]), "+f"(d[48]), "+f"(d[49]), "+f"(d[50]), "+f"(d[51]), "+f"(d[52]), "+f"(d[53]), "+f"(d[54]), "+f"(d[55]), "+f"(d[56]), "+f"(d[57]), "+f"(d[58]), "+f"(d[59]), "+f"(d[60]), "+f"(d[61]), "+f"(d[62]), "+f"(d[63])
    : "r"(a0), "r"(a1), "r"(a2), "r"(a3), "r"(blo));
}
template<> __device__ __forceinline__ void wgmma_rs_hi<128>(float (&d)[64], uint32_t a0, uint32_t a1, uint32_t a2, uint32_t a3, uint32_t blo){
  asm volatile("{\n.reg .b64 db;\nmov.b64 db, {%68,8};\nwgmma.mma_async.sync.aligned.m64n128k16.f32.bf16.bf16 {%0, %1, %2, %3, %4, %5, %6, %7, %8, %9, %10, %11, %12, %13, %14, %15, %16, %17, %18, %19, %20, %21, %22, %23, %24, %25, %26, %27, %28, %29, %30, %31, %32, %33, %34, %35, %36, %37, %38, %39, %40, %41, %42, %43, %44, %45, %46, %47, %48, %49, %50, %51, %52, %53, %54, %55, %56, %57, %58, %59, %60, %61, %62, %63}, {%64,%65,%66,%67}, db, 1, 1, 1, 0;\n}\n"
    : "+f"(d[0]), "+f"(d[1]), "+f"(d[2]), "+f"(d[3]), "+f"(d[4]), "+f"(d[5]), "+f"(d[6]), "+f"(d[7]), "+f"(d[8]), "+f"(d[9]), "+f"(d[10]), "+f"(d[11]), "+f"(d[12]), "+f"(d[13]), "+f"(d[14]), "+f"(d[15]), "+f"(d[16]), "+f"(d[17]), "+f"(d[18]), "+f"(d[19]), "+f"(d[20]), "+f"(d[21]), "+f"(d[22]), "+f"(d[23]), "+f"(d[24]), "+f"(d[25]), "+f"(d[26]), "+f"(d[27]), "+f"(d[28]), "+f"(d[29]), "+f"(d[30]), "+f"(d[31]), "+f"(d[32]), "+f"(d[33]), "+f"(d[34]), "+f"(d[35]), "+f"(d[36]), "+f"(d[37]), "+f"(d[38]), "+f"(d[39]), "+f"(d[40]), "+f"(d[41]), "+f"(d[42]), "+f"(d[43]), "+f"(d[44]), "+f"(d[45]), "+f"(d[46]), "+f"(d[47]), "+f"(d[48]), "+f"(d[49]), "+f"(d[50]), "+f"(d[51]), "+f"(d[52]), "+f"(d[53]), "+f"(d[54]), "+f"(d[55]), "+f"(d[56]), "+f"(d[57]), "+f"(d[58]), "+f"(d[59]), "+f"(d[60]), "+f"(d[61]), "+f"(d[62]), "+f"(d[63])
    : "r"(a0), "r"(a1), "r"(a2), "r"(a3), "r"(blo));
}

struct CvCtx {
  uint32_t koff, zero, so[3];
  int srcA, srcB;
  bool wrapA, s3, kodd;
};
struct CvPipe { uint32_t Ap, Ep, keep, send; };
template <int LO> __device__ __forceinline__ void cv_copy(float (&acc)[64]) {
#pragma unroll
  for (int i = LO; i < 64; i++) { float t; asm volatile("mov.b32 %0, %1;" : "=f"(t) : "f"(acc[i]) : "memory"); acc[i] = t; }
}
template <int G> __device__ __forceinline__ void cv_raw(uint32_t (&A)[4][4], uint32_t kaddr) {
#pragma unroll
  for (int i = 0; i < 4; i++) {
    const uint32_t a = kaddr + (4 * G + i) * 128;
    A[i][0] = lds32(a); A[i][1] = lds32(a + 4); A[i][3] = lds32(a + 8);
  }
}
__device__ __forceinline__ void cv_form(uint32_t (&A)[4][4], uint32_t sel) {
#pragma unroll
  for (int i = 0; i < 4; i++) {
    asm volatile("prmt.b32 %0, %0, %1, %2;" : "+r"(A[i][0]) : "r"(A[i][1]), "r"(sel));
    asm volatile("prmt.b32 %0, %1, %2, %3;" : "=r"(A[i][2]) : "r"(A[i][1]), "r"(A[i][3]), "r"(sel));
  }
}
#define CVV 2
template <int G> __device__ __forceinline__ void cv_step(float (&acc)[64], uint32_t (&A)[4][4], CvPipe& s, const CvCtx& c, uint32_t cb, uint32_t stg) {
  constexpr int JA = G - 1, JB = G - 2, NH = CVV == 1 ? 4 : (CVV == 3 ? 2 : 1);
  const uint32_t db0 = desc_lo(cb + CV_U + 192, CV_PL);
  uint32_t B[4][4];
  uint32_t ra[2], rb;
  if constexpr (G < 8) {
    wgmma_fence();
#pragma unroll
    for (int i = 0; i < NH; i++) wgmma_rs_hi<128 - 16 * (G & 7)>(acc, A[i][0], A[i][1], A[i][2], A[i][3], db0 - 4 * i);
    wgmma_commit();
    __syncwarp();
  }
  if constexpr (JA >= 0 && JA < 8) {
    const uint32_t p0 = pack_bf16(acc[8 * JA + 1], acc[8 * JA + 3]), p1 = pack_bf16(acc[8 * JA + 5], acc[8 * JA + 7]);
    ra[0] = __shfl_sync(0xffffffffu, c.wrapA ? s.Ap : p0, c.srcA);
    ra[1] = __shfl_sync(0xffffffffu, c.wrapA ? p0 : p1, c.srcA);
    s.Ap = p1;
  }
  if constexpr (JB >= 0) rb = __shfl_sync(0xffffffffu, s.send, c.srcB);
  if constexpr (G < 7) cv_raw<G + 1>(B, cb + c.koff);
  uint32_t z = 0;
  if constexpr (G < 8 && NH < 4) {
    __syncwarp();
    wgmma_fence();
#pragma unroll
    for (int i = NH; i < 4; i++) wgmma_rs_hi<128 - 16 * (G & 7)>(acc, A[i][0], A[i][1], A[i][2], A[i][3], db0 - 4 * i);
    wgmma_commit();
    asm volatile("mov.u32 %0, %%clock;" : "=r"(z)::"memory");
    z &= c.zero;
  }
  if constexpr (G < 7) cv_form(B, 0x5432u | z);
  if constexpr (JB >= 0) sts32(stg + ((c.so[JB / 3] >> (10 * (JB % 3))) & 0xffc), hadd2(rb | z, s.keep));
  if constexpr (JA >= 0 && JA < 8) {
    const uint32_t sh = 16 | z, mk = 0xffff0000u | z;
    const uint32_t ev = pack_bf16(acc[8 * JA] + __uint_as_float(ra[0] << sh), acc[8 * JA + 2] + __uint_as_float(ra[0] & mk));
    const uint32_t od = pack_bf16(acc[8 * JA + 4] + __uint_as_float(ra[1] << sh), acc[8 * JA + 6] + __uint_as_float(ra[1] & mk));
    s.send = c.kodd ? ev : (c.s3 ? s.Ep : od);
    s.keep = c.kodd ? od : ev;
    s.Ep = od;
  }
  if constexpr (G < 8) { __syncwarp(); wgmma_wait<0>(); cv_copy<8 * (G & 7)>(acc); }
  if constexpr (G < 9) cv_step<G + 1>(acc, B, s, c, cb, stg);
}
__device__ __forceinline__ uint32_t cv_stage(int slot) { return sb + (slot < 4 ? 40960 + slot * 4096 : CV_OFF + CV_K); }
__device__ __forceinline__ void cv_setup(CvCtx& c) {
  const int tid = tid_opaque() & 127, w = tid >> 5, lane = tid & 31, r = lane >> 2, q = lane & 3;
  const int i0 = (r >> 1) & 1, i1 = r >> 2;
  c.koff = CV_K - 32 + 4 * (8 * (r >> 1) + 2 * w + (r & 1) + 2 * q);
  c.srcA = i0 ? lane - 8 : lane + 8 - q + ((q + 3) & 3);
  c.wrapA = i0 && q == 3;
  c.srcB = i1 == 0 ? (lane - q + 16 + ((q + 3) & 3)) : (lane - q - 16 + ((q + 1) & 3));
  c.s3 = (i1 == 1 && q == 3); c.kodd = (i1 == 1 && q < 3);
  c.zero = lds32(sb + EP_OFF + 24);
#pragma unroll
  for (int i = 0; i < 3; i++) c.so[i] = lds32(sb + SO_OFF + 512 * i + 4 * tid);
}
__device__ __forceinline__ void cv_table() {
  const int tid = tid_opaque() & 127, r = (tid & 31) >> 2, q = tid & 3;
  int t = 16 * (2 * (r < 4 ? q : 4 + ((q + 1) & 3)) + ((r >> 1) & 1)) + 4 * (tid >> 5) + 2 * (r & 1);
#pragma unroll 1
  for (int i = 0; i < 3; i++) {
    uint32_t v = 0;
#pragma unroll 1
    for (int x = 0; x < 3; x++, t += 256) {
      const int T = t / 160, tl = t - T * 160;
      const int qq = (T >= NT1 - 1) ? (tl >> 5) : (tl / 40);
      int ck = 20 * T + ((tl - qq * ((T >= NT1 - 1) ? 32 : 40)) >> 1);
      ck ^= (ck >> 2) & 6;
      v |= (uint32_t)((ck * 4 + qq) & 1023) << (10 * x + 2);
    }
    sts32(sb + SO_OFF + 512 * i + 4 * tid, v);
  }
}
__device__ __forceinline__ void conv_channel(int slot, const CvCtx& c) {
  const uint32_t cb = sb + CV_OFF + slot * CV_B;
  float acc[64];
  CvPipe s;
  s.Ap = s.Ep = 0u;
  uint32_t A[4][4];
#pragma unroll
  for (int i = 0; i < 64; i++) acc[i] = 0.f;
  if (slot == 4) mbar_wait(bars + 8 * B_CVDONE);
  mbar_wait(bars + 8 * (B_CVFULL + slot));
  cv_raw<0>(A, cb + c.koff);
  {
    const uint32_t w0 = lds32(cb + CV_K);
    const uint32_t wp = __byte_perm(pack_bf16(bf_lo(w0) + __uint_as_float(lds32(sb + EP_OFF + 4 * slot)), 0.f), w0, 0x7610);
    if (c.koff == CV_K) A[0][0] = wp;
    if (c.koff == CV_K - 4) A[0][1] = wp;
    if (c.koff == CV_K - 8) A[0][3] = wp;
  }
  cv_form(A, 0x5432u);
  cv_copy<0>(acc);
  cv_step<0>(acc, A, s, c, cb, cv_stage(slot));
  fence_async_smem();
  mbar_arrive(bars + 8 * (B_CVDONE + slot));
}

__device__ __forceinline__ void kv_issue(const Params& p, int c, int m2, int dg) {
  const uint32_t fb = bars + 8 * (B_KV + c);
  mbar_expect_tx(fb, KV_PIECE);
  tma3(sb + KS_OFF + c * KV_PIECE, &p.mK, 160 * dg + 32 * c, 64 * m2 - 3, 0, fb);
  tma3(sb + KS_OFF + c * KV_PIECE + 4864, &p.mV, 160 * dg + 32 * c, 64 * m2 - 1, 0, fb);
}
__device__ __forceinline__ void kv_tile(int m, int c, int y, uint32_t (&o)[4][4]) {
  const int lane = tid_opaque() & 31, tg = lane & 3, pr = 8 * (y ^ (tg >> 1)) + (lane >> 2);
  const uint32_t pb = sb + KS_OFF + c * KV_PIECE + 4 * pr;
  const uint32_t ka = pb + tg * 1216, va = pb + 4864 + tg * 1088 + 64;
  const uint32_t kh = (m == 0 && tg > 0) ? ka - 192 : ka;
  uint32_t kk[19], u[16];
  const float4 t = lds128f(sb + TAP_OFF + 256 * c + 16 * pr);
#pragma unroll
  for (int i = 0; i < 19; i++) { kk[i] = lds32((i < 3 ? kh : ka) + i * 64); if (i >= 3) u[i - 3] = lds32(va + (i - 3) * 64); }
  const uint32_t dst = sb + KS_OFF + c * KV_PIECE + pr * 64 + tg * 16;
  if (y) {
    __syncwarp();
#pragma unroll
    for (int x = 0; x < 4; x++) sts128((dst ^ 512) + x * 1024, make_uint4(o[x][0], o[x][1], o[x][2], o[x][3]));
  }
  const uint32_t w0 = __byte_perm(__float_as_uint(t.x), __float_as_uint(t.z), 0x5410), w1 = __byte_perm(__float_as_uint(t.x), __float_as_uint(t.z), 0x7632);
  const uint32_t w2 = __byte_perm(__float_as_uint(t.y), __float_as_uint(t.w), 0x5410), w3 = __byte_perm(__float_as_uint(t.y), __float_as_uint(t.w), 0x7632);
#pragma unroll
  for (int i = 0; i < 16; i++) {
    uint32_t a = hmul2(kk[i], w3);
    a = hadd2(a, hmul2(kk[i + 1], w2)); a = hadd2(a, hmul2(kk[i + 2], w1)); a = hadd2(a, hmul2(kk[i + 3], w0));
    u[i] = hmul2(a, u[i]);
  }
#pragma unroll
  for (int x = 0; x < 4; x++) {
#pragma unroll
    for (int qq = 0; qq < 4; qq++) o[x][qq] = __byte_perm(u[15 - 4 * qq - (x & 2)], u[14 - 4 * qq - (x & 2)], (x & 1) ? 0x7632 : 0x5410);
    if (y) sts128(dst + x * 1024, make_uint4(o[x][0], o[x][1], o[x][2], o[x][3]));
  }
}
__device__ __forceinline__ void ln_finish(float s1, float s2, float& mean, float& rstd) {
  mean = s1 * (1.f / 640.f);
  const float v = fmaxf(fmaf(-mean, mean, s2 * (1.f / 640.f)), 0.f) + 1e-5f;
  asm("rsqrt.approx.ftz.f32 %0, %1;" : "=f"(rstd) : "f"(v));
}
__device__ __forceinline__ void stat_table(int T1, unsigned want, int l, int g, const uint4* x0, const uint4* x1, float (&xa)[2], float (&xb)[2]) {
  const int n = 32 * g + (tid_opaque() & 31);
  const uint4* rp = &g_stats[8 * l * SEQ + min(160 * T1 + n, SEQ - 1)];
  float a[4], b[4];
  uint32_t it = 0;
  while (true) {
    bool ok = true;
#pragma unroll
    for (int i = 0; i < 4; i++) ok &= (rec_ld(rp + SEQ * i, a[i], b[i]) == want);
    ok &= rec_ld(x0, xa[0], xb[0]) == want;
    ok &= rec_ld(x1, xa[1], xb[1]) == want;
    if (__all_sync(0xffffffffu, ok)) break;
    trap_if(++it > SPIN_LIMIT);
  }
  float m, rs;
  ln_finish((a[0] + a[1]) + (a[2] + a[3]), (b[0] + b[1]) + (b[2] + b[3]), m, rs);
  sts32(sb + STAB_OFF + ((n >> 1) & 3) * 160 + (n >> 3) * 8 + (n & 1) * 4, __float_as_uint(rs));
  const uint32_t hi = pack_bf16(-m, -m);
  const float lo = -m - bf_lo(hi);
  sts128(sb + (l ? MX1_OFF : MX0_OFF) + n * 16, make_uint4(hi, pack_bf16(lo, lo), 0u, 0u));
  fence_async_smem();
}
__device__ __forceinline__ void stats_reduce(float (&a)[2], float (&b)[2], float (&mean)[2], float (&rstd)[2]) {
#pragma unroll
  for (int o = 1; o < 4; o <<= 1)
#pragma unroll
    for (int h = 0; h < 2; h++) { a[h] += __shfl_xor_sync(0xffffffffu, a[h], o); b[h] += __shfl_xor_sync(0xffffffffu, b[h], o); }
#pragma unroll
  for (int h = 0; h < 2; h++) ln_finish(a[h], b[h], mean[h], rstd[h]);
}

template <bool FIRST>
__device__ __forceinline__ void stats_publish(int which, int n0, int dg, unsigned tag, const float (&acc)[80]) {
  const int q = tid_opaque() & 3, h = q & 1;
  float s1[2] = {0.f, 0.f}, s2[2] = {0.f, 0.f}, t1[2] = {0.f, 0.f}, t2[2] = {0.f, 0.f};
#pragma unroll
  for (int j = 0; j < 20; j++)
#pragma unroll
    for (int y = 0; y < 2; y++) {
      const float a = acc[4 * j + 2 * y], b = acc[4 * j + 2 * y + 1];
      s1[y] += a; t1[y] += b; s2[y] = fmaf(a, a, s2[y]); t2[y] = fmaf(b, b, t2[y]);
    }
#pragma unroll
  for (int y = 0; y < 2; y++) { s1[y] += t1[y]; s2[y] += t2[y]; }
  float a = (h ? s1[1] : s1[0]) + __shfl_xor_sync(0xffffffffu, h ? s1[0] : s1[1], 1);
  float b = (h ? s2[1] : s2[0]) + __shfl_xor_sync(0xffffffffu, h ? s2[0] : s2[1], 1);
  a += __shfl_xor_sync(0xffffffffu, a, 2);
  b += __shfl_xor_sync(0xffffffffu, b, 2);
  if (FIRST) {
    rec_st(&g_stats[((q >> 1) * 4 + dg) * SEQ + n0 + 8 * h], a, b, q < 2 ? tag : tag - 1);
    rec_st(&g_stats[((q >> 1) * 4 + 8 + dg) * SEQ + n0 + 8 * h], a, b, tag - 1);
  } else if (q < 2) rec_st(&g_stats[(which * 4 + dg) * SEQ + n0 + 8 * h], a, b, tag);
}
__device__ __forceinline__ void stats_get(int which, int n0, unsigned tag, float (&mean)[2], float (&rstd)[2]) {
  const uint4* p0 = &g_stats[(which * 4 + (tid_opaque() & 3)) * SEQ + n0];
  float a[2], b[2];
  uint32_t it = 0;
  while (true) {
    const unsigned t0 = rec_ld(p0, a[0], b[0]), t1 = rec_ld(p0 + 8, a[1], b[1]);
    if (__all_sync(0xffffffffu, t0 == tag && t1 == tag)) break;
    trap_if(++it > SPIN_LIMIT);
  }
  stats_reduce(a, b, mean, rstd);
}
__device__ __forceinline__ void x0_load(float (&acc)[80]) {
  const int t = tid_opaque() & 127;
  const uint32_t xa = sb + XT_OFF + (16 * (t >> 5) + ((t & 31) >> 2)) * 320 + 8 * (t & 3);
  mbar_wait(bars + 8 * B_XT);
#pragma unroll
  for (int h = 0; h < 2; h++)
#pragma unroll
    for (int J = 0; J < 10; J++) {
      const float2 v = lds64f(xa + h * 2560 + 32 * J);
      const uint32_t x = __float_as_uint(v.x), y = __float_as_uint(v.y);
      acc[8 * J + 2 * h] = bf_lo(x); acc[8 * J + 2 * h + 1] = bf_hi(x);
      acc[8 * J + 4 + 2 * h] = bf_lo(y); acc[8 * J + 4 + 2 * h + 1] = bf_hi(y);
    }
}

template <bool FROM_X0>
__device__ __forceinline__ void dskip_init(float (&acc)[80], const float (&mean)[2], const float (&rstd)[2]) {
  const int t = tid_opaque() & 127;
  const uint32_t xa = sb + XT_OFF + (16 * (t >> 5) + ((t & 31) >> 2)) * 320 + 8 * (t & 3), da = sb + DTAB_OFF + 8 * (t & 3);
  float2 dw[10], xv[10][2];
#pragma unroll
  for (int J = 0; J < 2; J++) { dw[J] = lds64f(da + 32 * J); if (FROM_X0) { xv[J][0] = lds64f(xa + 32 * J); xv[J][1] = lds64f(xa + 2560 + 32 * J); } }
#pragma unroll
  for (int J = 0; J < 10; J++) {
    if (J + 2 < 10) { dw[J + 2] = lds64f(da + 32 * (J + 2)); if (FROM_X0) { xv[J + 2][0] = lds64f(xa + 32 * (J + 2)); xv[J + 2][1] = lds64f(xa + 2560 + 32 * (J + 2)); } }
#pragma unroll
    for (int x = 0; x < 8; x++) {
      const int h = (x >> 1) & 1;
      const uint32_t dwd = __float_as_uint(x < 4 ? dw[J].x : dw[J].y);
      const float tt = fmaf(rstd[h], (x & 1) ? bf_hi(dwd) : bf_lo(dwd), 1.f);
      float a = acc[8 * J + x];
      if (FROM_X0) { const uint32_t xw = __float_as_uint(x < 4 ? xv[J][h].x : xv[J][h].y); a = (x & 1) ? bf_hi(xw) : bf_lo(xw); }
      acc[8 * J + x] = FROM_X0 ? (a - mean[h]) * tt : fmaf(a, tt, -mean[h] * tt);
    }
  }
}

__global__ void __launch_bounds__(512, 1) fused_kernel(const __grid_constant__ Params p) {
  extern __shared__ __align__(1024) uint8_t smem_raw[];
  const int tid = threadIdx.x, lane = tid & 31;
  const int wid = __shfl_sync(0xffffffffu, tid >> 5, 0), wg = wid >> 2;
  unsigned smid; asm volatile("mov.u32 %0, %%smid;" : "=r"(smid));
  const int role = p.role[min(smid, 131u)];
  if (wid == 12) {
    const bool el = elect_one();
    if (el) {
      asm volatile("prefetch.tensormap [%0];" ::"l"(&p.mB) : "memory");
      asm volatile("prefetch.tensormap [%0];" ::"l"((role & 15) == NT1 - 1 ? &p.mXl : &p.mX) : "memory");
#pragma unroll
      for (int k = 0; k < S1; k++) mbar_init(bars + 8 * (B_G1FULL + k), 1);
#pragma unroll
      for (int k = 0; k < 6; k++) mbar_init(bars + 8 * (B_XT + k), 1);
      asm volatile("fence.mbarrier_init.release.cluster;" ::: "memory");
    }
    if (role >= 0) {
      __syncwarp();
      asm volatile("bar.arrive 5, 288;" ::: "memory");
      const Role R = unpack_role(role);
      if (elect_one()) {
        TS(45);
#pragma unroll 1
        for (int k = 0; k < S1; k++) {
          const uint32_t fb = bars + 8 * (B_G1FULL + k);
          mbar_expect_tx(fb, G1_STAGE);
          tma4(sb + k * G1_STAGE + G1_XOFF, R.last ? &p.mXl : &p.mX, 64 * k, 0, 0, R.last ? 0 : 80 * R.T1, fb);
          tma5(sb + k * G1_STAGE, &p.mB, 64 * k, 0, 0, 4 * R.side, 2 * R.GP, fb);
          if (PFD) asm volatile("prefetch.tensormap [%0];" ::"l"(&p.mK + k) : "memory");
        }
        if (R.has2) {
          mbar_expect_tx(bars + 8 * B_XT, 20480);
#pragma unroll 1
          for (int h = 0; h < 2; h++) {
            const int ng = 8 * R.m2 + 4 * h, T = ng / 20;
            tma4(sb + XT_OFF + h * 10240, T == NT1 - 1 ? &p.mXtl : &p.mXt, 160 * R.dg, 0, 0, T == NT1 - 1 ? ng - 240 : ng + 60 * T, bars + 8 * B_XT);
          }
#pragma unroll 1
          for (int c = 0; c < KV0; c++) kv_issue(p, c, R.m2, R.dg);
        }
        TS(44);
      }
      __syncwarp();
      bar_sync(6, 64);
    }
  }
  trap_if(smid >= 132 || smem_u32(smem_raw) != sb);
  if (role < 0) {
    if (wid == 0) {
      const unsigned tag = ld_rlx(g_epoch);
      uint32_t it = 0;
      while (!__all_sync(0xffffffffu, (int)(ld_rlx(&g_hcnt[(lane & 7) * 32]) - 40 * tag) >= 0)) { __nanosleep(500); trap_if(++it > SPIN_LIMIT); }
    }
    return;
  }
  float mean0[2] = {0.f, 0.f}, rstd0[2] = {0.f, 0.f};
  if (wg == 2 || wid == 14) {
    ROLE(role)
    const int c = wid == 14 ? 4 : wid - 8;
    const unsigned tag = ld_rlx(g_epoch);
    if (has2) {
      uint2 bv[2][5];
#pragma unroll
      for (int x = 0; x < 2; x++)
#pragma unroll
        for (int i = 0; i < 5; i++) bv[x][i] = ldv64((const uint2*)((x ? p.bim : p.bre) + (cch0 + 32 * c) * DM) + lane + 32 * i);
      float sv[2];
#pragma unroll
      for (int x = 0; x < 2; x++) {
        float a = 0.f;
#pragma unroll
        for (int i = 0; i < 5; i++) a += (bf_lo(bv[x][i].x) + bf_hi(bv[x][i].x)) + (bf_lo(bv[x][i].y) + bf_hi(bv[x][i].y));
        sv[x] = a;
      }
#pragma unroll
      for (int o = 16; o > 0; o >>= 1) { sv[0] += __shfl_xor_sync(0xffffffffu, sv[0], o); sv[1] += __shfl_xor_sync(0xffffffffu, sv[1], o); }
      if (lane < 2) rec_st(&g_sB[(cch0 + 32 * c) * 2 + lane], sv[0], sv[1], tag);
      if (tid == 256) TS(47);
      __syncwarp();
      bar_sync(8, 192);
      if (wg == 2) {
        float xs[80];
        x0_load(xs);
        stats_publish<true>(0, 64 * m2 + 16 * c + (lane >> 2), dg, tag, xs);
        if (tid == 256) TS(31);
      }
      mbar_wait(bars + 8 * B_EP);
      mbar_wait(bars + 8 * (B_KV + c));
      mbar_wait(bars + 8 * (B_G1DONE + PAUSE_K - 1));
      if (tid == 448) TS(52);
      uint32_t o[4][4] = {};
#pragma unroll 1
      for (int y = 0; y < 2; y++) kv_tile(m2, c, y, o);
      fence_async_smem();
      __syncwarp();
      if (lane == 0) { mbar_arrive(bars + 8 * B_PREP); mbar_arrive(bars + 8 * (B_PD + c)); }
      if (tid == 448) TS(51);
    } else bar_sync(8, 192);
    {
      const uint4* x0 = wg == 2 ? &g_stats[(lane & 3) * SEQ + (has2 ? 64 * m2 : 0) + 16 * c + (lane >> 2)] : &g_sB[(128 * GP + 32 * side + lane) * 2];
      float xa[2], xb[2];
      stat_table(T1, tag, 0, c, x0, x0 + (wg == 2 ? 8 : 128), xa, xb);
      if (wg == 2) stats_reduce(xa, xb, mean0, rstd0);
      else {
#pragma unroll
        for (int i = 0; i < 2; i++) {
          const float ha = bf_lo(pack_bf16(xa[i], 0.f)), hb = bf_lo(pack_bf16(xb[i], 0.f));
          const float pa = __uint_as_float(pack_bf16(ha, xa[i] - ha)), pb = __uint_as_float(pack_bf16(hb, xb[i] - hb));
          sts64f(sb + CTAB_OFF + (32 * i + lane) * 24 + 16, p.swap ? pb : pa, p.swap ? pa : pb);
        }
      }
      mbar_arrive(bars + 8 * B_STAB);
      if (tid == 448) TS(26);
    }
  } else if (wid == 15) {
    ROLE(role)
    const int ch = 128 * GP + 32 * side + lane;
    uint32_t r0 = ldv16(p.lre + ch), r1 = ldv16(p.lim + ch), r2 = ldv16(p.logdt + ch);
    const uint32_t r3 = ldv16(p.lre + ch + 64), r4 = ldv16(p.lim + ch + 64), r5 = ldv16(p.logdt + ch + 64);
#pragma unroll 1
    for (int i = 0; i < 2; i++) {
      const float lr = bf_lo(r0), li = bf_lo(r1);
      const float dt = __bfloat162float(__float2bfloat16_rn(expf(bf_lo(r2))));
      const float mag = expf(dt * lr);
      float sn, cs; sincospif(dt * li * 0.31830988618379067f, &sn, &cs);
      const float ar = mag * cs, ai = mag * sn;
      const float inv = 2.f / (lr * lr + li * li);
      const uint32_t ad = sb + CTAB_OFF + (32 * i + lane) * 24;
      sts64f(ad, ar, ai);
      sts64f(ad + 8, ((ar - 1.f) * lr + ai * li) * inv, (ai * lr - (ar - 1.f) * li) * inv);
      r0 = r3; r1 = r4; r2 = r5;
    }
    if (lane == 0) TS(46);
    __syncwarp();
    bar_sync(7, 64);
    mbar_arrive(bars + 8 * B_CTAB);
  } else if (wid == 13) {
    ROLE(role)
    uint4 tv[3];
    const uint32_t e0 = ld_rlx(g_epoch);
    const uint32_t e1 = ldv16(p.ssmD + min(cch0 + 32 * lane, 639));
    const uint4 dv = ldv128((const uint4*)(p.dskip + 160 * dg) + min(lane, 19));
#pragma unroll
    for (int i = 0; i < 3; i++) tv[i] = ldv128((const uint4*)(p.shiftk + 640 * dg) + min(lane + 32 * i, 79));
    sts128(sb + DTAB_OFF + 16 * min(lane, 19), dv);
#pragma unroll
    for (int i = 0; i < 3; i++) sts128(sb + TAP_OFF + 16 * min(lane + 32 * i, 79), tv[i]);
    if (lane < 7) sts32(sb + EP_OFF + 4 * lane, lane < 5 ? e1 << 16 : (lane == 5 ? e0 : 0u));
    __syncwarp();
    bar_sync(9, 64);
    mbar_arrive(bars + 8 * B_CTAB);
    if (lane == 0) { mbar_arrive(bars + 8 * B_EP); TS(53); }
    if (has2) {
#pragma unroll 1
      for (int i = 0; i < 5; i++) {
        const int c = i == 2 ? 3 : (i == 3 ? 2 : i);
        mbar_wait(bars + 8 * (B_PD + c));
        if (lane == 0) bulk_s2g(g_kv + (dg * 32 + m2) * 20480 + c * 4096, sb + KS_OFF + c * KV_PIECE, 4096);
      }
      if (lane == 0) {
        asm volatile("cp.async.bulk.commit_group;" ::: "memory");
        asm volatile("cp.async.bulk.wait_group 0;" ::: "memory");
        mbar_arrive(bars + 8 * B_PREP2);
        fence_async_global();
      }
      __syncwarp();
      if (lane < 4) red_rel(&g_kvcnt[(dg * 4 + lane) * 32]);
      __syncwarp();
      if (lane == 0) { mbar_arrive(bars + 8 * B_PUB); TS(30); }
    }
  } else if (wid != 12) {
    if (elect_one()) {
      if (wid < 7) {
        const int b0 = wid < 4 ? 4 + 19 * wid : 85 + 21 * (wid - 4), cnt = wid < 4 ? 2 : 1;
#pragma unroll
        for (int i = 0; i < 21; i++) mbar_init(bars + 8 * (b0 + i), cnt);
#pragma unroll
        for (int i = 0; i < 8; i++) mbar_init(bars + 8 * (B_PD + 8 * wid + i), 1);
      } else {
#pragma unroll
        for (int i = 0; i < 12; i++) mbar_init(bars + 8 * (B_CVDONE + i), (i == 5 || i == 6) ? 160 : 128);
        mbar_init(bars + 8 * B_CTAB, 192); mbar_init(bars + 8 * B_PREP, 5); mbar_init(bars + 8 * B_PREP2, 1);
      }
      asm volatile("fence.mbarrier_init.release.cluster;" ::: "memory");
    }
    __syncwarp();
    bar_sync(5, 288);
    if (wid == 2) asm volatile("bar.arrive 8, 192;\nbar.arrive 6, 64;\nbar.arrive 9, 64;\nbar.arrive 7, 64;" ::: "memory");
    if (tid == 128) TS(0);
    if (wg == 1) { cv_table(); mbar_arrive(bars + 8 * B_CTAB); }
  }

  if (wid == 12) {
    ROLE(role)
    uint32_t dst = sb;
#pragma unroll 1
    for (int k = S1; k < 10; k++) {
      const uint32_t fb = bars + 8 * (B_G1FULL + k);
      mbar_wait(bars + 8 * (B_G1DONE + k - S1));
      if (elect_one()) {
        mbar_expect_tx(fb, 20480);
        tma4(dst + G1_XOFF, last ? &p.mXl : &p.mX, 64 * k, 0, 0, last ? 0 : 80 * T1, fb);
        mbar_expect_tx(fb, 16384);
        tma5(dst, &p.mB, 64 * k, 0, 0, 4 * side, 2 * GP, fb);
        if (has2 && k - S1 + KV0 < 5) kv_issue(p, k - S1 + KV0, m2, dg);
      }
      dst += G1_STAGE; if (k == 2 * S1 - 1) dst = sb;
    }
  } else if (wid == 15 && (role >> 16)) {
    ROLE(role)
    if (TPF >= 0) {
      mbar_wait(bars + 8 * (B_KV + TPF));
      if (elect_one()) {
#pragma unroll
        for (int c = 0; c < 5; c++) l2_prefetch(p.ssmk + (cch0 + 32 * c) * SEQ, 4096);
        if (CPF) { l2_prefetch(p.cre + (160 * dg + 5 * m2) * DM, 6400); l2_prefetch(p.cim + (160 * dg + 5 * m2) * DM, 6400); }
      }
    }
    mbar_wait(bars + 8 * B_PREP2);
    if (lane < 10) sts128(sb + CV_OFF + (lane >> 1) * CV_B + CV_K - 32 + 16 * (lane & 1), make_uint4(0, 0, 0, 0));
    fence_async_smem();
    __syncwarp();
    const unsigned tag = lds32(sb + EP_OFF + 20);
    if (TAPW) mbar_wait(bars + 8 * B_PUB);
    if (elect_one()) {
#pragma unroll 1
      for (int c = 0; c < 5; c++) {
        if (c == 0) asm volatile("prefetch.tensormap [%0];" ::"l"(&p.mU) : "memory");
        mbar_expect_tx(bars + 8 * (B_CVFULL + c), 4096 + 2 * CV_PL);
        if (c < TAPN) bulk_g2s(sb + CV_OFF + c * CV_B + CV_K, p.ssmk + (cch0 + 32 * c) * SEQ, 4096, bars + 8 * (B_CVFULL + c));
      }
    }
    mbar_wait(bars + 8 * B_PUB);
    cnt_poll(&g_kvcnt[(dg * 4 + (m2 >> 3)) * 32], 32 * tag);
    fence_async_global();
    if (elect_one()) {
      TS(28);
#pragma unroll
      for (int c = 0; c < 5; c++) {
        tma5(sb + CV_OFF + c * CV_B + CV_U, &p.mU, 0, -3, 2 * c, 16 * (m2 & 1) + (m2 >> 1), dg, bars + 8 * (B_CVFULL + c));
        if (c >= TAPN) bulk_g2s(sb + CV_OFF + c * CV_B + CV_K, p.ssmk + (cch0 + 32 * c) * SEQ, 4096, bars + 8 * (B_CVFULL + c));
      }
#pragma unroll
      for (int i = 0; i < 3; i++) asm volatile("prefetch.tensormap [%0];" ::"l"(&p.mCre + i) : "memory");
      TS(54);
    }
    __syncwarp();
  }
  {
    const int w = wid & 3;
    if (wg == 2 && !(role >> 16)) {
      float xa[2], xb[2];
      mbar_wait(bars + 8 * (B_G1FULL + 11));
      stat_table(role & 15, lds32(sb + EP_OFF + 20), 1, w, g_stats, g_stats, xa, xb);
      mbar_arrive(bars + 8 * (B_STAB + 1));
    }
#pragma unroll 1
    for (int l = 0; l < 2; l++) {
      if (wg < 2) {
        float acc[80];
#pragma unroll
        for (int i = 0; i < 80; i++) acc[i] = 0.f;
        ROLE(role)
        const int tid = tid_opaque(), r = (tid & 31) >> 2, q = tid & 3;
        const int ch = 128 * GP + 64 * wg + 32 * side + 8 * w + r;
        const uint32_t ca = sb + CTAB_OFF + (32 * wg + 8 * w + r) * 24;
        float2 lam = make_float2(0.f, 0.f), p8 = lam, p16 = lam, pL = lam, p2L = lam;
        fence_regs(acc);
        {
          const uint32_t alo0 = (l == 0 ? desc_lo(sb, 16) : desc_lo(sb + G2_WOFF, 16)) + wg * 512;
          const uint32_t blo0 = l == 0 ? desc_lo(sb + G1_XOFF, 16) : desc_lo(sb + X1_OFF, 128);
          const uint32_t bhi = l == 0 ? desc_hi(1024, 1) : desc_hi(1024, 0), xstep = l == 0 ? 2 : 16;
          const uint32_t astep = l == 0 ? G1_STAGE >> 4 : 1024, bstep = l == 0 ? G1_STAGE >> 4 : 1280, aend = alo0 + (S1 + l) * astep;
          uint32_t alo = alo0, blo = blo0;
          uint32_t fb = bars + 8 * (B_G1FULL + 10 * l);
          mbar_wait(fb);
          if (tid == 0) TS(1 + 8 * l);
#pragma unroll 1
          for (int k = 0; k < 10; k++) {
            uint32_t ok; const uint32_t nb = k < 9 ? fb + 8 : fb;
            wgmma_fence();
#pragma unroll
            for (int kk = 0; kk < 4; kk++) {
              wgmma_n160<0>(acc, alo + kk * 2, desc_hi(1024, 1), blo + kk * xstep, bhi);
              if (kk == 0) ok = mbar_test(nb);
              if (kk == STG_KK && k == 9 && tid == 0) mbar_arrive(bars + 8 * (B_STG + l));
            }
            wgmma_commit();
            alo += astep; blo += bstep;
            if (blo == desc_lo(sb + G_OFF, 128)) blo = desc_lo(sb, 128);
            if (alo == aend) { alo = alo0; blo = blo0; }
            wgmma_wait<1>();
            if (k > 0 && (tid & 127) == 0) mbar_arrive(fb + 8 * (B_G1DONE - B_G1FULL - 1));
            if (!ok) mbar_wait(nb);
            if (k == (l ? MK1 : MK0)) {
              mbar_wait(bars + 8 * (B_STAB + l));
              const float2 sB = lds64f(ca + 16);
              uint32_t a0 = q < 2 ? __float_as_uint(sB.x) : 0u, a1 = q < 2 ? __float_as_uint(sB.y) : 0u, a2 = 0u, a3 = 0u;
              asm volatile("" : "+r"(a0), "+r"(a1), "+r"(a2), "+r"(a3)::"memory");
              wgmma_fence();
              wgmma_rs_n160(acc, a0, a1, a2, a3, l ? desc_lo(sb + MX1_OFF, 0) : desc_lo(sb + MX0_OFF, 0));
              wgmma_commit();
            }
            if (wg == 1 && k == (l ? 8 - STG_D : 9 - STG0)) mbar_wait(bars + 8 * (B_STG + l));
            if (k == 3) {
              mbar_wait(bars + 8 * B_CTAB);
              lam = lds64f(ca);
              if (l == 0 && q < 2) rec_st(&g_E[(q * NT1 + T1) * DM + ch], 0.f, 0.f, lds32(sb + EP_OFF + 20) - 1);
              if (p.swap) lam.y = -lam.y;
              const float2 p2 = cmul(lam, lam), p4 = cmul(p2, p2);
              p8 = cmul(p4, p4); p16 = cmul(p8, p8);
              pL = cmul(p16, p16);
              if (!last) pL = cmul(pL, p8);
              p2L = cmul(pL, pL);
            }
            if (k == PAUSE_K && l == 0 && has2) mbar_wait(bars + 8 * B_PREP);
            fb += 8;
          }
        }
        const unsigned tag = lds32(sb + EP_OFF + 20);
        wgmma_wait<0>();
        fence_regs(acc);
        if ((tid & 127) == 0) { mbar_arrive(bars + 8 * (B_G1DONE + 10 * l + 9)); TS(wg ? 17 + l : 2 + 8 * l); }
        float2 ec[3];
#pragma unroll
        for (int jj = 0; jj < 4; jj++)
#pragma unroll
          for (int y = 0; y < 3; y++) {
            if (y == 2 && (jj & 1)) continue;
            const int j = y == 2 ? 16 + jj : 8 * y + 2 * jj;
            const float4 st = lds128f(sb + STAB_OFF + q * 160 + j * 8);
            const float rs[4] = {st.x, st.y, st.z, st.w};
#pragma unroll
            for (int x = 0; x < 4; x++) {
              const int i = 4 * j + 4 * (x >> 1) + (x & 1);
              acc[i] *= rs[x]; acc[i + 2] *= rs[x];
              ec[y] = (jj == 0 && x == 0) ? make_float2(acc[i], acc[i + 2]) : cfma(lam, ec[y], make_float2(acc[i], acc[i + 2]));
            }
          }
        float2 e = cfma(p16, ec[0], ec[1]);
        if (!last) e = cfma(p8, e, ec[2]);
        {
          float2 v = make_float2(__shfl_up_sync(0xffffffffu, e.x, 1, 4), __shfl_up_sync(0xffffffffu, e.y, 1, 4));
          if (q >= 1) e = cfma(pL, v, e);
          v = make_float2(__shfl_up_sync(0xffffffffu, e.x, 2, 4), __shfl_up_sync(0xffffffffu, e.y, 2, 4));
          if (q >= 2) e = cfma(p2L, v, e);
        }
        if (!last && q == 3) rec_st(&g_E[(l * NT1 + T1) * DM + ch], e.x, e.y, tag);
        if (tid == 0) TS(3 + 8 * l);
        float2 ex = make_float2(__shfl_up_sync(0xffffffffu, e.x, 1, 4), __shfl_up_sync(0xffffffffu, e.y, 1, 4));
        if (q == 0) ex = make_float2(0.f, 0.f);
        const float2 coef = lds64f(ca + 8), lamc = make_float2(lam.x, p.swap ? lam.y : -lam.y);
        float m00 = coef.x, m01 = -coef.y, m10 = -coef.y, m11 = -coef.x;
        if (p.swap) { m00 = -coef.y; m01 = coef.x; m10 = -coef.x; m11 = -coef.y; }
        float2 pLq, p160q, p640;
        {
          const float2 p80 = last ? cmul(p2L, p16) : p2L, p160 = cmul(p80, p80), p320 = cmul(p160, p160), one = make_float2(1.f, 0.f);
          p640 = cmul(p320, p320);
          pLq = cmul((q & 1) ? pL : one, (q & 2) ? p2L : one);
          p160q = cmul((q & 1) ? p160 : one, (q & 2) ? p320 : one);
        }
        float2 c, ev[3];
        unsigned tg[3];
        const uint4* ep = &g_E[(l * NT1 + T1 - 1 - q) * DM + ch];
#pragma unroll
        for (int j = 0; j < 20; j++) {
          if (j == CPOLL) {
#pragma unroll
            for (int i = 0; i < 3; i++) {
              ev[i] = make_float2(0.f, 0.f); tg[i] = tag;
              if (T1 - 1 - q - 4 * i >= 0) tg[i] = rec_ld(ep - 4 * i * DM, ev[i].x, ev[i].y);
            }
          }
#pragma unroll
          for (int x = 0; x < 2; x++) {
            const float b0 = acc[4 * j + x], b1 = acc[4 * j + 2 + x];
            acc[4 * j + x] = fmaf(b0, m00, b1 * m01);
            acc[4 * j + 2 + x] = fmaf(b0, m10, b1 * m11);
          }
          if (j == CPOLL - 1 || j == 19) asm volatile("" : "+f"(acc[4 * j]), "+f"(acc[4 * j + 1]), "+f"(acc[4 * j + 2]), "+f"(acc[4 * j + 3])::"memory");
        }
        {
          uint32_t it = 0;
          while (__any_sync(0xffffffffu, tg[0] != tag || tg[1] != tag || tg[2] != tag)) {
#pragma unroll
            for (int i = 0; i < 3; i++)
              if (tg[i] != tag) tg[i] = rec_ld(ep - 4 * i * DM, ev[i].x, ev[i].y);
            trap_if(++it > SPIN_LIMIT);
          }
          c = cfma(p640, cfma(p640, ev[2], ev[1]), ev[0]);
          c = cmul(c, p160q);
          c.x += __shfl_xor_sync(0xffffffffu, c.x, 1); c.y += __shfl_xor_sync(0xffffffffu, c.y, 1);
          c.x += __shfl_xor_sync(0xffffffffu, c.x, 2); c.y += __shfl_xor_sync(0xffffffffu, c.y, 2);
        }
        if (tid == 0) TS(4 + 8 * l);
        if (wg == 1 && l >= HOLD0) mbar_wait(bars + 8 * (B_REL + l));
        const uint32_t c0 = (uint32_t)clock();
        c = cfma(pLq, c, ex);
        float2 hh = make_float2(fmaf(c.x, m00, c.y * m01), fmaf(c.x, m10, c.y * m11));
        uint8_t* hb = g_h + (size_t)l * (32 * 20 * 8192) + (10 * wg + 2 * GP) * 8192 + (4 * side + w) * 1024 + (tid_opaque() & 31) * 4;
#pragma unroll
        for (int j4 = 0; j4 < 5; j4++) {
          if (PACE && j4 > 0 && wg == 1 && l == 1) { while (__any_sync(0xffffffffu, (uint32_t)clock() - c0 < PACE * j4)) {} }
          const int ng = 20 * T1 + 4 * j4;
          uint8_t* hp = hb + (size_t)(ng >> 3) * 163840 + (ng & 7) * 128;
#pragma unroll
          for (int jj = 0; jj < 4; jj++) {
            const int j = 4 * j4 + jj;
            const float2 h0 = cfma(lamc, hh, make_float2(acc[4 * j + 0], acc[4 * j + 2]));
            hh = cfma(lamc, h0, make_float2(acc[4 * j + 1], acc[4 * j + 3]));
            if (j4 < 4 || !last) {
              *(uint32_t*)(hp + jj * 128) = tag_word(pack_bf16(h0.x, hh.x), (tid & 7) == jj, tag & 1);
              *(uint32_t*)(hp + jj * 128 + 8192) = tag_word(pack_bf16(h0.y, hh.y), (tid & 7) == jj, tag & 1);
            }
          }
        }
        mbar_arrive(bars + 8 * (B_HST + 2 * l + wg));
        if (tid == 0) TS(5 + 8 * l);
        if (tid == 128) TS(l ? 25 : 19);
        if (l == 0 && wid == 4) {
          mbar_wait(bars + 8 * B_HST);
          mbar_wait(bars + 8 * (B_HST + 1));
          if ((tid & 31) < 4) h_release(0, T1, tid & 3);
          __syncwarp();
          if (tid == 128) { mbar_arrive(bars + 8 * B_REL); TS(6); }
        }
      }
      if (l == 0) {
        ROLE(role)
        if (has2) {
          CvCtx cc;
          mbar_wait(bars + 8 * B_CTAB);
          cv_setup(cc);
          mbar_wait(bars + 8 * (B_G1DONE + 9));
#pragma unroll 1
          for (int c = (wg + 2) & 3; c < 5; c += 4) conv_channel(c, cc);
          if ((tid & 127) == 0) TS(wg == 2 ? 32 : (wg == 3 ? 50 : 7 + wg));
        }
      }
      if (wg >= 2) break;
    }
    if (wg == 3) {
    ROLE(role)
    const int pw = wid & 3, gpc = 2 * min(m2 >> 3, 3) + (dg >> 1);
    mbar_wait(bars + 8 * B_EP);
    const unsigned tag = lds32(sb + EP_OFF + 20);
    if (pw == 0) {
      if (elect_one()) {
#pragma unroll 1
        for (int l = 0; l < 2; l++) {
          uint32_t dst = sb;
          if (l == 1) {
            dst = sb + G2_WOFF;
#pragma unroll 1
            for (int k = 0; k < 10; k++) {
              mbar_wait(k > 4 ? bars + 8 * (B_G1DONE + 5 + k) : (has2 ? bars + 8 * (B_G2DONE + 14 + min(k, 3)) : bars + 8 * (B_G1DONE + 9)));
              mbar_expect_tx(bars + 8 * (B_G1FULL + 10 + k), 16384);
              tma5(dst, &p.mB, 64 * k, 0, 0, 4 * side, 2 * GP, bars + 8 * (B_G1FULL + 10 + k));
              dst += 16384; if (k == 4) dst = sb + G2_WOFF;
            }
          }
          if (has2) {
            const uint32_t fb2 = bars + 8 * (B_G2FULL + 20 * l), wb2 = bars + 8 * (B_G2DONE + 20 * l - S2);
            dst = sb + G2_WOFF + (WTAIL ? 4 * l * G2_WB : 0);
            int kc = 0;
#pragma unroll 1
            for (int k = 0; k < 20; k++) {
              mbar_wait(k >= S2 ? wb2 + 8 * k : bars + 8 * (l ? B_G1DONE + (WTAIL ? (k < 3 ? 15 + k : 13 + k) : 19) : (k == 5 ? B_XFREE : (k == 6 ? B_SFREE : B_REL))));
              mbar_expect_tx(fb2 + 8 * k, G2_WB);
              tma5(dst, &p.mCre + (k & 1), kc, 0, 0, 0, 10 * dg, fb2 + 8 * k);
              kc += (k & 1) << 7; if (k == 9) kc = 64;
              dst += G2_WB; if (dst == sb + G2_WOFF + S2 * G2_WB) dst = sb + G2_WOFF;
            }
          }
        }
      }
    } else if (pw == 1) {
#pragma unroll 1
      for (int l = 0; l < 2; l++) {
        if (l == 1) {
          mbar_wait(bars + 8 * (has2 ? B_G2DONE + 19 : B_G1DONE + 9));
          if (has2) mbar_wait(bars + 8 * B_UST);
          cnt_poll(&g_ucnt[gpc * 32], 128 * tag);
          fence_async_global();
          if (elect_one()) {
            TS(20);
            const int bytes = last ? 16384 : 20480;
            const uint8_t* src = g_u + T1 * 204800;
            uint32_t dst = sb + X1_OFF;
#pragma unroll 1
            for (int k = 0; k < 10; k++) {
              if (k > 4) mbar_wait(bars + 8 * (B_G1DONE + 5 + k));
              mbar_expect_tx(bars + 8 * (B_XV1 + k), bytes);
              bulk_g2s(dst, src, bytes, bars + 8 * (B_XV1 + k));
              src += 20480; dst += 20480; if (dst == sb + G_OFF) dst = sb; if (k == 4) dst = sb + X1_OFF;
            }
          }
          __syncwarp();
        }
        if (has2) {
          mbar_wait(bars + 8 * (B_HST + 2 * l));
          mbar_wait(bars + 8 * (B_G1DONE + 10 * l + 9));
          cnt_poll(&g_hcnt[(l * 16 + gpc) * 32], 40 * tag);
          fence_async_global();
          if (elect_one()) {
            TS(21 + 2 * l);
            const uint32_t fb2 = bars + 8 * (B_XV2 + 20 * l), wb2 = bars + 8 * (B_G2DONE + 20 * l - S2);
            const uint8_t* src = g_h + (l * 32 + m2) * 163840;
            uint32_t dst = sb;
#pragma unroll 1
            for (int k = 0; k < 20; k++) {
              if (k >= (l ? XB0 : 5)) mbar_wait(k >= S2 ? wb2 + 8 * k : (l ? fb2 + 8 * (k - XB0) : bars + 8 * B_SFREE));
              if (k == 10 && l == 1) mbar_wait(bars + 8 * B_H1);
              mbar_expect_tx(fb2 + 8 * k, G2_XB);
              bulk_g2s(dst, src, G2_XB, fb2 + 8 * k);
              src += 8192; dst += G2_XB; if (dst == sb + S2 * G2_XB) dst = sb;
            }
          }
          __syncwarp();
        }
      }
    } else if (pw == 2) {
#pragma unroll 1
      for (int l = 0; l < 2; l++) {
        if (l == 1) {
          float xa[2], xb[2];
          mbar_wait(bars + 8 * (B_G1FULL + 11));
          stat_table(T1, tag, 1, 4, g_stats, g_stats, xa, xb);
          mbar_arrive(bars + 8 * (B_STAB + 1));
        }
#pragma unroll 1
        for (int w = 0; w < 2 * l; w++) {
          mbar_wait(bars + 8 * (B_HST + 2 + w));
          if (lane < 4) h_release(2 + w, T1, lane);
          __syncwarp();
          if (lane == 0) { if (w == 0) mbar_arrive(bars + 8 * (B_REL + 1)); TS(w ? 16 : 14); }
        }
        if (l == 0 && has2 && elect_one()) {
#pragma unroll 1
          for (int i = 0; i < 5; i++) {
            const int c = i < 3 ? i : 7 - i;
            mbar_wait(bars + 8 * (B_CVDONE + c));
            bulk_s2g(g_G + (cch0 + 32 * c) * 4096, cv_stage(c), 4096);
          }
          asm volatile("cp.async.bulk.commit_group;" ::: "memory");
          asm volatile("cp.async.bulk.wait_group.read 0;" ::: "memory");
          mbar_arrive(bars + 8 * B_SFREE);
          asm volatile("cp.async.bulk.wait_group 0;" ::: "memory");
          TS(48);
          fence_async_global();
          asm volatile("fence.acq_rel.gpu;" ::: "memory");
#pragma unroll
          for (int i = 0; i < 4; i++) red_rlx(&g_gcnt[(dg * 4 + i) * 32]);
          TS(49);
        }
        __syncwarp();
        if (has2) {
          if (l == 0) {
            flag_poll(&g_gcnt[(dg * 4 + (m2 >> 3)) * 32], 32 * tag);
            fence_async_global();
            if (elect_one()) {
              TS(29);
              mbar_expect_tx(bars + 8 * B_GFULL, 20480);
              tma5(sb + G_OFF, &p.mG, 64 * m2, 0, 0, 0, 10 * dg, bars + 8 * B_GFULL);
            }
          } else {
            cnt_poll(&g_hcnt[(24 + gpc) * 32], 40 * tag);
            if (lane == 0) { mbar_arrive(bars + 8 * B_H1); TS(24); }
          }
        }
      }
    } else {
      if (!CPF && has2) {
        mbar_wait(bars + 8 * B_REL);
        if (elect_one()) { l2_prefetch(p.cre + (160 * dg + 5 * m2) * DM, 6400); l2_prefetch(p.cim + (160 * dg + 5 * m2) * DM, 6400); }
      }
      uint32_t ph = 0;
#pragma unroll 1
      for (int l = 0; l < 2; l++) {
        if (l == 1) {
          uint32_t dst = sb + X1_OFF;
#pragma unroll 1
          for (int k = 0; k < 10; k++) {
            validate_block<20>(bars + 8 * (B_XV1 + k), bars + 8 * (B_G1FULL + 10 + k), dst, g_u + (T1 * 10 + k) * 20480, last ? 16 : 20,
                               (lane & 7) * 128 + (lane >> 3) * 32 + (lane & 6) * 4, tag & 1, ph);
            dst += 20480; if (dst == sb + G_OFF) dst = sb; if (k == 4) dst = sb + X1_OFF;
          }
        }
        if (has2) {
          uint32_t dst = sb;
#pragma unroll 1
          for (int k = 0; k < 20; k++) {
            validate_block<8>(bars + 8 * (B_XV2 + 20 * l + k), bars + 8 * (B_G2FULL + 20 * l + k), dst, g_h + ((l * 32 + m2) * 20 + k) * 8192, 8,
                              (lane & 7) * 128 + (lane >> 3) * 32 + (lane & 3) * 4, tag & 1, ph);
            dst += G2_XB; if (dst == sb + S2 * G2_XB) dst = sb;
          }
        }
      }
    }
    } else if (wg == 2 && (role >> 16)) {
      float acc[80];
      float off[2] = {mean0[0], mean0[1]};
      const unsigned tag = lds32(sb + EP_OFF + 20);
      dskip_init<true>(acc, mean0, rstd0);
      mbar_arrive(bars + 8 * B_XFREE);
#pragma unroll 1
      for (int step = 1; step < 4; step++) {
        const int l = step >> 1;
        if (step != 2) {
          uint32_t alo = desc_lo(sb, 1024), blo = desc_lo(sb + G2_WOFF, 16) + (WTAIL ? l * (G2_WB >> 2) : 0);
          uint32_t fb = bars + 8 * (B_G2FULL + 20 * l);
          fence_regs(acc);
          mbar_wait(bars + 8 * (B_CVDONE + 2));
          mbar_wait(bars + 8 * (B_CVDONE + 3));
          mbar_wait(fb);
          if (tid == 256) TS(33 + 6 * l);
#pragma unroll 1
          for (int k = 0; k < 20; k++) {
            if (l == TSL && (k & 3) == 3 && tid == 256) TS(56 + (k >> 2));
            uint32_t ok; const uint32_t nb = k < 19 ? fb + 8 : fb;
            wgmma_fence();
#pragma unroll
            for (int kk = 0; kk < 4; kk++) {
              wgmma_n160<1>(acc, alo + kk * 128, desc_hi(128, 0), blo + kk * 2, desc_hi(1024, 1));
              if (kk == 0) ok = mbar_test(nb);
            }
            wgmma_commit();
            alo += G2_XB >> 4; blo += G2_WB >> 4;
            if (alo == desc_lo(sb + S2 * G2_XB, 1024)) alo = desc_lo(sb, 1024);
            if (blo == desc_lo(sb + G_OFF, 16)) blo = desc_lo(sb + G2_WOFF, 16);
            wgmma_wait<1>();
            if (k > 0 && tid == 256) mbar_arrive(fb + 8 * (B_G2DONE - B_G2FULL - 1));
            if (!ok) mbar_wait(nb);
            fb += 8;
          }
          wgmma_wait<0>();
          fence_regs(acc);
          if (tid == 256) TS(34 + 6 * l);
          if (tid == 256) mbar_arrive(bars + 8 * (B_G2DONE + 20 * l + 19));
        }
        ROLE(role)
        const int tq = tid_opaque() & 31, n0 = 64 * m2 + 16 * w + (tq >> 2);
#pragma unroll 1
        for (int rep = 0;; rep++) {
          stats_publish<false>(step, n0, dg, tag, acc);
          if (step != 2 || rep == 1) break;
          for (int n = tid & 127; n < 160; n += 128) {
            const int d = 16 * (n >> 4) + 4 * ((n >> 1) & 3) + 2 * ((n >> 3) & 1) + (n & 1);
            const uint32_t dw = lds32(sb + DTAB_OFF + 2 * (d & ~1)), dd = __byte_perm(dw, dw, (d & 1) ? 0x3232 : 0x1010);
            sts128(sb + DX_OFF + 16 * n, make_uint4(dd, dd, dd, dd));
          }
          mbar_wait(bars + 8 * (B_G1FULL + 11));
          float xa[2], xb[2];
          stat_table(T1, tag, 1, w, g_stats, g_stats, xa, xb);
          mbar_arrive(bars + 8 * (B_STAB + 1));
          if (tid == 256) TS(27);
          mbar_wait(bars + 8 * (B_HST + 2));
          if (!REP2) break;
        }
        uint32_t gf[10][4];
        mbar_wait(bars + 8 * B_GFULL);
        uint32_t ga = sb + G_OFF + (8 * (tq >> 4) + (tq & 7)) * 128 + (((2 * w + ((tq >> 3) & 1)) ^ ((2 * m2) & 6) ^ (tq & 7)) << 4), gstep = 2048;
        if (step == 2) { ga = sb + DX_OFF + (8 * (tq >> 4) + (tq & 7)) * 16; gstep = 256; }
#pragma unroll
        for (int J = 0; J < 2; J++) ldsm4t(gf[J], ga + J * gstep);
        if (tid == 256) TS(35 + 6 * l);
        uint8_t* dst[2][2];
#pragma unroll
        for (int h = 0; h < 2; h++) {
          if (l == 0) {
            const int ng = 8 * m2 + 2 * w + h, T = ng / 20;
            uint8_t* ub = g_u + (T * 204800 + (ng - 20 * T) * 1024 + (tq & 2) * 64 + (tq & 28) * 4 + (tq & 1) * 8 + (5 * dg >> 1) * 20480);
            dst[h][1] = ub + ((dg & 1) ? 20480 - 512 : 0);
            dst[h][0] = ub + (dg & 1) * 512;
          } else {
            dst[h][0] = dst[h][1] = (uint8_t*)(p.out + (n_to_t(n0 + 8 * h) * DM + 160 * dg + 4 * (tq & 3)));
          }
        }
        const int tix = (((tq >> 1) & 2) + (tq & 1) + 2 * dg) & 3;
        float mean[2], rstd[2];
        stats_get(step, n0, tag, mean, rstd);
        if (tid == 256) TS(36 + 6 * l);
        off[0] += mean[0]; off[1] += mean[1];
        const float ov[2] = {step == 3 ? off[0] : 0.f, step == 3 ? off[1] : 0.f};
#pragma unroll
        for (int J = 0; J < 10; J++) {
          if (J + 2 < 10) ldsm4t(gf[J + 2 < 10 ? J + 2 : 0], ga + (J + 2) * gstep);
#pragma unroll
          for (int x = 0; x < 8; x++) {
            const int h = (x >> 1) & 1;
            const uint32_t gwd = gf[J][x >> 1];
            const float t = fmaf(rstd[h], (x & 1) ? bf_hi(gwd) : bf_lo(gwd), 1.f);
            acc[8 * J + x] = fmaf(acc[8 * J + x], t, fmaf(-mean[h], t, ov[h]));
          }
#pragma unroll
          for (int h = 0; h < 2; h++) {
            if (step == 1)
              *(uint2*)(dst[h][(J >> 1) & 1] + (J >> 2) * 20480 + (J & 3) * 256) =
                  make_uint2(tag_word(pack_bf16(acc[8 * J + 2 * h], acc[8 * J + 2 * h + 1]), tix == (J & 3), tag & 1), pack_bf16(acc[8 * J + 4 + 2 * h], acc[8 * J + 5 + 2 * h]));
            if (step == 3)
              *(float4*)(dst[h][0] + 64 * J) = make_float4(acc[8 * J + 2 * h], acc[8 * J + 2 * h + 1], acc[8 * J + 4 + 2 * h], acc[8 * J + 5 + 2 * h]);
          }
          __syncwarp();
        }
        if (step == 1) {
          bar_sync(3, 128);
          if (tid == 288) { TS(37); mbar_arrive(bars + 8 * B_UST); }
          if (tid < 264) { if (UNSAFE & 1) red_rlx(&g_ucnt[(tid & 7) * 32]); else red_rel(&g_ucnt[(tid & 7) * 32]); }
          __syncwarp();
          if (tid == 256) TS(38);
        } else if (step == 3) {
          if (tid == 256) {
            TS(43);
            if (m2 == 31 && dg == 3) asm volatile("st.relaxed.gpu.global.u32 [%0], %1;" ::"l"(g_epoch), "r"(tag + 1) : "memory");
          }
        }
      }
    }
  }
}

typedef CUresult (*EncFn)(CUtensorMap*, CUtensorMapDataType, cuuint32_t, void*, const cuuint64_t*, const cuuint64_t*,
                          const cuuint32_t*, const cuuint32_t*, CUtensorMapInterleave, CUtensorMapSwizzle,
                          CUtensorMapL2promotion, CUtensorMapFloatOOBfill);

void encode(EncFn fn, CUtensorMap* m, const void* ptr, int rank, const cuuint64_t* dims, const cuuint64_t* strides, const cuuint32_t* box,
            CUtensorMapSwizzle swz = CU_TENSOR_MAP_SWIZZLE_128B, int prom = 2) {
  cuuint32_t es[5] = {1, 1, 1, 1, 1};
  fn(m, CU_TENSOR_MAP_DATA_TYPE_BFLOAT16, rank, (void*)ptr, dims, strides, box, es, CU_TENSOR_MAP_INTERLEAVE_NONE,
     swz, (CUtensorMapL2promotion)prom, CU_TENSOR_MAP_FLOAT_OOB_FILL_NONE);
}

}

extern "C" void kernel_launch(void* const* d_in, const int* in_sizes, int n_in, void* d_out, int out_size) {
  (void)in_sizes; (void)n_in; (void)out_size;
  Params p;
  typedef const __nv_bfloat16* BP;
  p.x = (BP)d_in[0]; p.lre = (BP)d_in[1]; p.lim = (BP)d_in[2]; p.bre = (BP)d_in[3]; p.bim = (BP)d_in[4];
  p.cre = (BP)d_in[5]; p.cim = (BP)d_in[6]; p.logdt = (BP)d_in[7]; p.dskip = (BP)d_in[8];
  p.k = (BP)d_in[10]; p.v = (BP)d_in[11]; p.shiftk = (BP)d_in[12]; p.ssmk = (BP)d_in[13]; p.ssmD = (BP)d_in[14];
  p.out = (float*)d_out;
  for (int sm = 0; sm < 132; sm++) {
    const int tpc = sm >> 1, side = sm & 1;
    int gpc, gi;
    if (tpc < 32) { gpc = tpc & 7; gi = tpc >> 3; }
    else if (tpc < 60) { gpc = 1 + (tpc - 32) % 7; gi = 4 + (tpc - 32) / 7; }
    else if (tpc < 62) { gpc = tpc - 54; gi = 8; }
    else { gpc = 0; gi = tpc - 58; }
    const int pos = 8 * gpc + gi + (gpc == 7 ? 1 : 0);
    int T1, GP;
    if (pos < 52) { const int hh = pos / 26, x = pos - 26 * hh; T1 = x >> 1; GP = 2 * hh + (x & 1); }
    else { T1 = pos - 52; GP = 4; }
    const int m2 = 8 * (gpc >> 1) + gi, dg = 2 * (gpc & 1) + side;
    p.role[sm] = pos == 65 ? -1 : (T1 | (GP << 4) | (side << 7) | (m2 << 8) | (dg << 14) | ((gi < 8) << 16));
  }
  void* fnp = nullptr;
  cudaDriverEntryPointQueryResult qr;
  cudaGetDriverEntryPoint("cuTensorMapEncodeTiled", &fnp, cudaEnableDefault, &qr);
  EncFn fn = (EncFn)fnp;
  void* gG = nullptr;
  cudaGetSymbolAddress(&gG, g_G);
  void* gKV = nullptr;
  cudaGetSymbolAddress(&gKV, g_kv);
  {
    cuuint64_t dims[5] = {32, 32, 10, 32, 4}, st[4] = {20480, 2048, 64, 655360}; cuuint32_t box[5] = {32, 35, 2, 1, 1};
    encode(fn, &p.mU, gKV, 5, dims, st, box, CU_TENSOR_MAP_SWIZZLE_NONE, 1);
  }
  const cuuint64_t RB = DM * 2;
  {
    p.swap = p.bim < p.bre;
    const char* lo = (const char*)(p.swap ? p.bim : p.bre); const char* hi = (const char*)(p.swap ? p.bre : p.bim);
    cuuint64_t dims[5] = {640, 8, 2, 8, 10}, st[4] = {RB, (cuuint64_t)(hi - lo), 8 * RB, 64 * RB}; cuuint32_t box[5] = {64, 8, 2, 4, 2};
    encode(fn, &p.mB, lo, 5, dims, st, box);
  }
  {
    cuuint64_t dims[5] = {640, 2, 4, 2, 40}, st[4] = {RB, 4 * RB, 2 * RB, 16 * RB}; cuuint32_t box[5] = {64, 2, 4, 2, 10};
    encode(fn, &p.mCre, p.cre, 5, dims, st, box); encode(fn, &p.mCim, p.cim, 5, dims, st, box);
    cuuint64_t dimg[5] = {2048, 2, 4, 2, 40}, stg[4] = {4096, 4 * 4096, 2 * 4096, 16 * 4096};
    encode(fn, &p.mG, gG, 5, dimg, stg, box);
  }
  {
    cuuint64_t dims[4] = {640, 2, 4, 900}, st[3] = {RB, 40 * RB, 2 * RB}; cuuint32_t box[4] = {64, 2, 4, 20};
    encode(fn, &p.mX, p.x, 4, dims, st, box);
    cuuint64_t diml[4] = {640, 2, 4, 16}, stl[3] = {RB, 32 * RB, 2 * RB};
    encode(fn, &p.mXl, p.x + (size_t)1920 * DM, 4, diml, stl, box);
    cuuint32_t boxt[4] = {160, 2, 4, 4};
    encode(fn, &p.mXt, p.x, 4, dims, st, boxt, CU_TENSOR_MAP_SWIZZLE_NONE);
    encode(fn, &p.mXtl, p.x + (size_t)1920 * DM, 4, diml, stl, boxt, CU_TENSOR_MAP_SWIZZLE_NONE);
    cuuint64_t dk[3] = {640, 2000, 4}, sk[2] = {RB, 16 * RB}; cuuint32_t bk[3] = {32, 19, 4}, bv[3] = {32, 17, 4};
    encode(fn, &p.mK, p.k, 3, dk, sk, bk, CU_TENSOR_MAP_SWIZZLE_NONE);
    encode(fn, &p.mV, p.v, 3, dk, sk, bv, CU_TENSOR_MAP_SWIZZLE_NONE);
  }
  cudaFuncSetAttribute(fused_kernel, cudaFuncAttributeMaxDynamicSharedMemorySize, SMEM_BYTES);
  cudaLaunchConfig_t cfg = {};
  cfg.gridDim = dim3(132); cfg.blockDim = dim3(512); cfg.dynamicSmemBytes = SMEM_BYTES; cfg.stream = cudaStreamPerThread;
  cudaLaunchKernelEx(&cfg, fused_kernel, p);
}
```

```cpp
#include <cuda_runtime.h>
#include <cuda.h>
#include <cuda_bf16.h>
#include <stdint.h>

namespace {

constexpr int SEQ = 2048, DM = 640;
constexpr int NT1 = 13;
#define EXP 0
#define WPF1 3
#define WPF2 7
#define CPOLL 10
#define KV0 1
#define TAPLATE 1
#define STG_D 3
#define STG_KK 1
#define HOLD0 1
#define WREL 0
#define UREL 1
#define TSL 1
#define STG0 2
#define WTAIL 1
#define PFD 1
#define TAPW 0
#define TPF 4
#define CPF 0
#define MK0 7
#define MK1 4
#define PACE 180
#define XB0 3
#define TAPN 2
#define REL3 0
#define REP2 0
#define PAUSE_K 5
constexpr uint32_t SPIN_LIMIT = 1u << 22;

__device__ __align__(1024) uint8_t g_h[2 * 32 * 20 * 8192];
__device__ __align__(1024) uint8_t g_u[NT1 * 10 * 20480];
__device__ __align__(1024) uint8_t g_kv[DM * 4096];
__device__ __align__(1024) uint8_t g_G[DM * 4096];
__device__ __align__(128) uint4 g_E[2 * NT1 * DM];
__device__ __align__(128) uint4 g_stats[4 * 4 * SEQ];
__device__ __align__(128) uint4 g_sB[DM * 2];
__device__ __align__(128) unsigned g_hcnt[2 * 2 * 8 * 32];
__device__ __align__(128) unsigned g_ucnt[8 * 32];
__device__ __align__(128) unsigned g_kvcnt[16 * 32];
__device__ __align__(128) unsigned g_gcnt[16 * 32];
__device__ __align__(128) unsigned g_epoch[32] = {1};
#define TS(i) do {} while (0)

struct Params {
  CUtensorMap mX, mB, mXl, mK, mV, mXt, mXtl, mCre, mCim, mG, mU;
  const __nv_bfloat16 *x, *lre, *lim, *bre, *bim, *cre, *cim, *logdt, *dskip, *k, *v, *shiftk, *ssmk, *ssmD;
  float* out;
  int swap;
  int role[132];
};

constexpr uint32_t sb = 1024;
constexpr uint32_t G1_STAGE = 36864, G1_XOFF = 16384;
constexpr int S1 = 4;
constexpr uint32_t XT_OFF = 159744, KS_OFF = 180224, KV_PIECE = 9216;
constexpr uint32_t G2_XB = 8192, G2_WB = 20480, G2_WOFF = 57344, G_OFF = 200704;
constexpr uint32_t X1_OFF = 139264;
constexpr int S2 = 7;
constexpr uint32_t CV_OFF = KS_OFF, CV_K = 128, CV_PL = 2240, CV_U = CV_K + 4096, CV_B = KV_PIECE;
constexpr uint32_t MISC = 226304;
constexpr uint32_t BAR_OFF = MISC;
constexpr int B_G1FULL = 0, B_G1DONE = 20, B_G2FULL = 40,
              B_G2DONE = 85, B_GFULL = 125, B_EP = 126, B_H1 = 127  , B_CVFULL = 129  , B_STG = 134  , B_REL = 136  , B_SFREE = 138, B_UST = 142,
              B_GO = 139  , B_PUB = 147,
              B_CVDONE = 148  , B_STAB = 153  , B_XFREE = 155, B_HST = 156  ,
              B_CTAB = 160, B_PREP = 161, B_XT = 162, B_KV = 163  , B_PREP2 = 84, B_PD = 168  ;
constexpr uint32_t bars = sb + BAR_OFF;
constexpr uint32_t STAB_OFF = MISC + 1392;
constexpr uint32_t CTAB_OFF = STAB_OFF + 640;
constexpr uint32_t DTAB_OFF = CTAB_OFF + 1536;
constexpr uint32_t EP_OFF = DTAB_OFF + 320;
constexpr uint32_t SO_OFF = EP_OFF + 32;
constexpr uint32_t TAP_OFF = 147456;
constexpr uint32_t MX0_OFF = TAP_OFF + 1280, MX1_OFF = G_OFF + 20480;
constexpr uint32_t DX_OFF = MX1_OFF + 2560;
constexpr uint32_t SMEM_BYTES = 232448;
static_assert(SO_OFF + 1536 <= SMEM_BYTES, "smem");

__device__ __forceinline__ void trap_if(bool c) { asm volatile("{\n.reg .pred p;\nsetp.ne.u32 p, %0, 0;\n@p trap;\n}\n" ::"r"((uint32_t)c)); }
__device__ __forceinline__ uint32_t smem_u32(const void* p) { return (uint32_t)__cvta_generic_to_shared(p); }
__device__ __forceinline__ void mbar_init(uint32_t bar, int cnt) { asm volatile("mbarrier.init.shared::cta.b64 [%0], %1;" ::"r"(bar), "r"(cnt) : "memory"); }
__device__ __forceinline__ void mbar_expect_tx(uint32_t bar, int bytes) { asm volatile("mbarrier.arrive.expect_tx.shared::cta.b64 _, [%0], %1;" ::"r"(bar), "r"(bytes) : "memory"); }
__device__ __forceinline__ void mbar_arrive(uint32_t bar) { asm volatile("mbarrier.arrive.shared::cta.b64 _, [%0];" ::"r"(bar) : "memory"); }
__device__ __forceinline__ void mbar_wait(uint32_t bar) {
  asm volatile(
      "{\n.reg .pred p;\n.reg .u32 c;\nmov.u32 c, 0;\n"
      "W_%=:\nmbarrier.try_wait.parity.shared::cta.b64 p, [%0], 0;\n@p bra D_%=;\n"
      "add.u32 c, c, 1;\nsetp.lt.u32 p, c, %1;\n@p bra W_%=;\ntrap;\nD_%=:\n}\n" ::"r"(bar), "n"(SPIN_LIMIT) : "memory");
}
__device__ __forceinline__ uint32_t mbar_test(uint32_t bar) {
  uint32_t ok;
  asm volatile("{\n.reg .pred p;\nmbarrier.test_wait.parity.shared::cta.b64 p, [%1], 0;\nselp.u32 %0, 1, 0, p;\n}\n" : "=r"(ok) : "r"(bar) : "memory");
  return ok;
}
__device__ __forceinline__ void tma3(uint32_t dst, const CUtensorMap* m, int c0, int c1, int c2, uint32_t bar) {
  asm volatile("cp.async.bulk.tensor.3d.shared::cluster.global.mbarrier::complete_tx::bytes [%0], [%1, {%3,%4,%5}], [%2];"
               ::"r"(dst), "l"(m), "r"(bar), "r"(c0), "r"(c1), "r"(c2) : "memory");
}
__device__ __forceinline__ void tma4(uint32_t dst, const CUtensorMap* m, int c0, int c1, int c2, int c3, uint32_t bar) {
  asm volatile("cp.async.bulk.tensor.4d.shared::cluster.global.mbarrier::complete_tx::bytes [%0], [%1, {%3,%4,%5,%6}], [%2];"
               ::"r"(dst), "l"(m), "r"(bar), "r"(c0), "r"(c1), "r"(c2), "r"(c3) : "memory");
}
__device__ __forceinline__ void tma5(uint32_t dst, const CUtensorMap* m, int c0, int c1, int c2, int c3, int c4, uint32_t bar) {
  asm volatile("cp.async.bulk.tensor.5d.shared::cluster.global.mbarrier::complete_tx::bytes [%0], [%1, {%3,%4,%5,%6,%7}], [%2];"
               ::"r"(dst), "l"(m), "r"(bar), "r"(c0), "r"(c1), "r"(c2), "r"(c3), "r"(c4) : "memory");
}
__device__ __forceinline__ void bulk_g2s(uint32_t dst, const void* src, int bytes, uint32_t bar) {
  asm volatile("cp.async.bulk.shared::cluster.global.mbarrier::complete_tx::bytes [%0], [%1], %2, [%3];"
               ::"r"(dst), "l"(src), "r"(bytes), "r"(bar) : "memory");
}
__device__ __forceinline__ void bulk_s2g(void* dst, uint32_t src, int bytes) {
  asm volatile("cp.async.bulk.global.shared::cta.bulk_group [%0], [%1], %2;" ::"l"(dst), "r"(src), "r"(bytes) : "memory");
}
__device__ __forceinline__ void l2_prefetch(const void* src, int bytes) {
  asm volatile("cp.async.bulk.prefetch.L2.global [%0], %1;" ::"l"(src), "r"(bytes) : "memory");
}
__device__ __forceinline__ void wgmma_fence() { asm volatile("wgmma.fence.sync.aligned;" ::: "memory"); }
__device__ __forceinline__ void wgmma_commit() { asm volatile("wgmma.commit_group.sync.aligned;" ::: "memory"); }
template <int N> __device__ __forceinline__ void wgmma_wait() { asm volatile("wgmma.wait_group.sync.aligned %0;" ::"n"(N) : "memory"); }
__host__ __device__ constexpr uint32_t desc_lo(uint32_t addr, uint32_t lbo) { return ((addr & 0x3FFFF) >> 4) | ((lbo >> 4) << 16); }
__host__ __device__ constexpr uint32_t desc_hi(uint32_t sbo, uint32_t swz) { return (sbo >> 4) | (swz << 30); }
__device__ __forceinline__ void bar_sync(int id, int n) { asm volatile("bar.sync %0, %1;" ::"r"(id), "r"(n) : "memory"); }
__device__ __forceinline__ uint32_t lds32(uint32_t a) { uint32_t v; asm volatile("ld.shared.u32 %0, [%1];" : "=r"(v) : "r"(a) : "memory"); return v; }
__device__ __forceinline__ float2 lds64f(uint32_t a) { float2 v; asm volatile("ld.shared.v2.f32 {%0,%1}, [%2];" : "=f"(v.x), "=f"(v.y) : "r"(a) : "memory"); return v; }
__device__ __forceinline__ float4 lds128f(uint32_t a) { float4 v; asm volatile("ld.shared.v4.f32 {%0,%1,%2,%3}, [%4];" : "=f"(v.x), "=f"(v.y), "=f"(v.z), "=f"(v.w) : "r"(a) : "memory"); return v; }
__device__ __forceinline__ void ldsm4t(uint32_t (&r)[4], uint32_t a) {
  asm volatile("ldmatrix.sync.aligned.m8n8.x4.trans.shared.b16 {%0,%1,%2,%3}, [%4];" : "=r"(r[0]), "=r"(r[1]), "=r"(r[2]), "=r"(r[3]) : "r"(a) : "memory");
}
__device__ __forceinline__ uint4 ldv128(const void* a) { uint4 v; asm volatile("ld.global.nc.v4.u32 {%0,%1,%2,%3}, [%4];" : "=r"(v.x), "=r"(v.y), "=r"(v.z), "=r"(v.w) : "l"(a) : "memory"); return v; }
__device__ __forceinline__ uint2 ldv64(const void* a) { uint2 v; asm volatile("ld.global.nc.v2.u32 {%0,%1}, [%2];" : "=r"(v.x), "=r"(v.y) : "l"(a) : "memory"); return v; }
__device__ __forceinline__ uint32_t ldv16(const void* a) { uint32_t v; asm volatile("ld.global.nc.u16 %0, [%1];" : "=r"(v) : "l"(a) : "memory"); return v; }
__device__ __forceinline__ void sts128(uint32_t a, uint4 v) { asm volatile("st.shared.v4.u32 [%0], {%1,%2,%3,%4};" ::"r"(a), "r"(v.x), "r"(v.y), "r"(v.z), "r"(v.w) : "memory"); }
__device__ __forceinline__ void sts32(uint32_t a, uint32_t v) { asm volatile("st.shared.u32 [%0], %1;" ::"r"(a), "r"(v) : "memory"); }
__device__ __forceinline__ void sts64f(uint32_t a, float x, float y) { asm volatile("st.shared.v2.f32 [%0], {%1,%2};" ::"r"(a), "f"(x), "f"(y) : "memory"); }
__device__ __forceinline__ void red_rlx(unsigned* p) { asm volatile("red.relaxed.gpu.global.add.u32 [%0], 1;" ::"l"(p) : "memory"); }
__device__ __forceinline__ void red_rel(unsigned* p) { asm volatile("red.release.gpu.global.add.u32 [%0], 1;" ::"l"(p) : "memory"); }
__device__ __forceinline__ void fence_async_global() { asm volatile("fence.proxy.async.global;" ::: "memory"); }
__device__ __forceinline__ void fence_async_smem() { asm volatile("fence.proxy.async.shared::cta;" ::: "memory"); }
__device__ __forceinline__ void rec_st(uint4* p, float a, float b, unsigned tag) {
  asm volatile("{\n.reg .b128 t;\n.reg .b64 lo, hi;\nmov.b64 lo, {%1,%2};\nmov.b64 hi, {%3,%3};\nmov.b128 t, {lo,hi};\n"
               "st.relaxed.gpu.global.b128 [%0], t;\n}\n" ::"l"(p), "r"(__float_as_uint(a)), "r"(__float_as_uint(b)), "r"(tag) : "memory");
}
__device__ __forceinline__ unsigned rec_ld(const uint4* p, float& a, float& b) {
  unsigned x, y, t;
  asm volatile("{\n.reg .b128 t;\n.reg .b64 lo, hi;\n.reg .b32 u;\nld.relaxed.gpu.global.b128 t, [%3];\nmov.b128 {lo,hi}, t;\n"
               "mov.b64 {%0,%1}, lo;\nmov.b64 {%2,u}, hi;\n}\n" : "=r"(x), "=r"(y), "=r"(t) : "l"(p) : "memory");
  a = __uint_as_float(x); b = __uint_as_float(y);
  return t;
}
__device__ __forceinline__ unsigned ld_rlx(const unsigned* p) { unsigned v; asm volatile("ld.relaxed.gpu.global.u32 %0, [%1];" : "=r"(v) : "l"(p) : "memory"); return v; }
__device__ __forceinline__ void flag_poll(const unsigned* p, unsigned target) {
  uint32_t it = 0;
  while (!__all_sync(0xffffffffu, (int)(ld_rlx(p) - target) >= 0)) { trap_if(++it > SPIN_LIMIT); }
  asm volatile("fence.acquire.gpu;" ::: "memory");
}
__device__ __forceinline__ void cnt_poll(const unsigned* p, unsigned target) {
  unsigned a = ld_rlx(p); __nanosleep(100);
  unsigned b = ld_rlx(p); __nanosleep(100);
  unsigned c = ld_rlx(p);
  uint32_t it = 0;
  while (true) {
    if (__all_sync(0xffffffffu, (int)(a - target) >= 0)) break;
    a = ld_rlx(p);
    if (__all_sync(0xffffffffu, (int)(b - target) >= 0)) break;
    b = ld_rlx(p);
    if (__all_sync(0xffffffffu, (int)(c - target) >= 0)) break;
    c = ld_rlx(p);
    trap_if(++it > SPIN_LIMIT);
  }
  asm volatile("fence.acquire.gpu;" ::: "memory");
}
__device__ __forceinline__ void h_release(int idx, int T, int i) {
  const int Q = (i & 2) ? (T + 2) / 3 - 1 : T / 3;
  if (Q >= 0 && Q < 4 && ((i & 2) == 0 || T % 3 == 0)) red_rel(&g_hcnt[(idx * 8 + 2 * Q + (i & 1)) * 32]);
}
__device__ __forceinline__ uint32_t pack_bf16(float lo, float hi) {
  uint32_t r; asm("cvt.rn.bf16x2.f32 %0, %1, %2;" : "=r"(r) : "f"(hi), "f"(lo)); return r;
}
__device__ __forceinline__ float bf_lo(uint32_t w) { return __uint_as_float(w << 16); }
__device__ __forceinline__ float bf_hi(uint32_t w) { return __uint_as_float(w & 0xffff0000u); }
__device__ __forceinline__ uint32_t hmul2(uint32_t a, uint32_t b) {
  __nv_bfloat162 r = __hmul2_rn(*(__nv_bfloat162*)&a, *(__nv_bfloat162*)&b); return *(uint32_t*)&r;
}
__device__ __forceinline__ uint32_t hadd2(uint32_t a, uint32_t b) {
  __nv_bfloat162 r = __hadd2_rn(*(__nv_bfloat162*)&a, *(__nv_bfloat162*)&b); return *(uint32_t*)&r;
}
__device__ __forceinline__ float2 cmul(float2 a, float2 b) { return make_float2(a.x * b.x - a.y * b.y, a.x * b.y + a.y * b.x); }
__device__ __forceinline__ float2 cfma(float2 a, float2 b, float2 c) {
  return make_float2(fmaf(a.x, b.x, fmaf(-a.y, b.y, c.x)), fmaf(a.x, b.y, fmaf(a.y, b.x, c.y)));
}
template <int N> __device__ __forceinline__ void fence_regs(float (&a)[N]) {
#pragma unroll
  for (int i = 0; i < N; i++) asm volatile("" : "+f"(a[i])::"memory");
}
__device__ __forceinline__ bool elect_one() {
  uint32_t e; asm volatile("{\n.reg .pred P;\nelect.sync _|P, 0xffffffff;\nselp.u32 %0, 1, 0, P;\n}\n" : "=r"(e)); return e != 0;
}
__device__ __forceinline__ int tid_opaque() { int t; asm volatile("mov.u32 %0, %%tid.x;" : "=r"(t)); return t; }
struct Role { int T1, GP, side, m2, dg, cch0; bool last, has2; };
__device__ __forceinline__ Role unpack_role(int x) {
  Role r; r.T1 = x & 15; r.GP = (x >> 4) & 7; r.side = (x >> 7) & 1; r.m2 = (x >> 8) & 63; r.dg = (x >> 14) & 3;
  r.has2 = (x >> 16) & 1; r.last = r.T1 == NT1 - 1; r.cch0 = 160 * r.dg + r.m2; return r;
}
__device__ __forceinline__ Role fresh_role(int x) { asm volatile("" : "+r"(x)); return unpack_role(__shfl_sync(0xffffffffu, x, 0)); }
#define ROLE(x) const Role R_ = fresh_role(x); const int T1 = R_.T1, GP = R_.GP, side = R_.side, m2 = R_.m2, dg = R_.dg, cch0 = R_.cch0; \
  const bool last = R_.last, has2 = R_.has2; (void)T1; (void)GP; (void)side; (void)m2; (void)dg; (void)cch0; (void)last; (void)has2;
__device__ __forceinline__ int n_to_t(int n) {
  int T = n / 160, nl = n - T * 160;
  int L = (T == NT1 - 1) ? 32 : 40;
  return T * 160 + L * ((nl & 7) >> 1) + 2 * (nl >> 3) + (nl & 1);
}

template<int TA> __device__ __forceinline__ void wgmma_n160(float (&d)[80], uint32_t alo, uint32_t ahi, uint32_t blo, uint32_t bhi){
  asm volatile("{\n.reg .b64 da, db;\nmov.b64 da, {%80,%81};\nmov.b64 db, {%82,%83};\n"
    "wgmma.mma_async.sync.aligned.m64n160k16.f32.bf16.bf16 {%0, %1, %2, %3, %4, %5, %6, %7, %8, %9, %10, %11, %12, %13, %14, %15, %16, %17, %18, %19, %20, %21, %22, %23, %24, %25, %26, %27, %28, %29, %30, %31, %32, %33, %34, %35, %36, %37, %38, %39, %40, %41, %42, %43, %44, %45, %46, %47, %48, %49, %50, %51, %52, %53, %54, %55, %56, %57, %58, %59, %60, %61, %62, %63, %64, %65, %66, %67, %68, %69, %70, %71, %72, %73, %74, %75, %76, %77, %78, %79}, da, db, 1, 1, 1, %84, 0;\n}\n"
    : "+f"(d[0]), "+f"(d[1]), "+f"(d[2]), "+f"(d[3]), "+f"(d[4]), "+f"(d[5]), "+f"(d[6]), "+f"(d[7]), "+f"(d[8]), "+f"(d[9]), "+f"(d[10]), "+f"(d[11]), "+f"(d[12]), "+f"(d[13]), "+f"(d[14]), "+f"(d[15]), "+f"(d[16]), "+f"(d[17]), "+f"(d[18]), "+f"(d[19]), "+f"(d[20]), "+f"(d[21]), "+f"(d[22]), "+f"(d[23]), "+f"(d[24]), "+f"(d[25]), "+f"(d[26]), "+f"(d[27]), "+f"(d[28]), "+f"(d[29]), "+f"(d[30]), "+f"(d[31]), "+f"(d[32]), "+f"(d[33]), "+f"(d[34]), "+f"(d[35]), "+f"(d[36]), "+f"(d[37]), "+f"(d[38]), "+f"(d[39]), "+f"(d[40]), "+f"(d[41]), "+f"(d[42]), "+f"(d[43]), "+f"(d[44]), "+f"(d[45]), "+f"(d[46]), "+f"(d[47]), "+f"(d[48]), "+f"(d[49]), "+f"(d[50]), "+f"(d[51]), "+f"(d[52]), "+f"(d[53]), "+f"(d[54]), "+f"(d[55]), "+f"(d[56]), "+f"(d[57]), "+f"(d[58]), "+f"(d[59]), "+f"(d[60]), "+f"(d[61]), "+f"(d[62]), "+f"(d[63]), "+f"(d[64]), "+f"(d[65]), "+f"(d[66]), "+f"(d[67]), "+f"(d[68]), "+f"(d[69]), "+f"(d[70]), "+f"(d[71]), "+f"(d[72]), "+f"(d[73]), "+f"(d[74]), "+f"(d[75]), "+f"(d[76]), "+f"(d[77]), "+f"(d[78]), "+f"(d[79])
    : "r"(alo), "r"(ahi), "r"(blo), "r"(bhi), "n"(TA));
}
__device__ __forceinline__ void wgmma_rs_n160(float (&d)[80], uint32_t a0, uint32_t a1, uint32_t a2, uint32_t a3, uint32_t blo){
  asm volatile("{\n.reg .b64 db;\nmov.b64 db, {%84,8};\nwgmma.mma_async.sync.aligned.m64n160k16.f32.bf16.bf16 {%0, %1, %2, %3, %4, %5, %6, %7, %8, %9, %10, %11, %12, %13, %14, %15, %16, %17, %18, %19, %20, %21, %22, %23, %24, %25, %26, %27, %28, %29, %30, %31, %32, %33, %34, %35, %36, %37, %38, %39, %40, %41, %42, %43, %44, %45, %46, %47, %48, %49, %50, %51, %52, %53, %54, %55, %56, %57, %58, %59, %60, %61, %62, %63, %64, %65, %66, %67, %68, %69, %70, %71, %72, %73, %74, %75, %76, %77, %78, %79}, {%80,%81,%82,%83}, db, 1, 1, 1, 0;\n}\n"
    : "+f"(d[0]), "+f"(d[1]), "+f"(d[2]), "+f"(d[3]), "+f"(d[4]), "+f"(d[5]), "+f"(d[6]), "+f"(d[7]), "+f"(d[8]), "+f"(d[9]), "+f"(d[10]), "+f"(d[11]), "+f"(d[12]), "+f"(d[13]), "+f"(d[14]), "+f"(d[15]), "+f"(d[16]), "+f"(d[17]), "+f"(d[18]), "+f"(d[19]), "+f"(d[20]), "+f"(d[21]), "+f"(d[22]), "+f"(d[23]), "+f"(d[24]), "+f"(d[25]), "+f"(d[26]), "+f"(d[27]), "+f"(d[28]), "+f"(d[29]), "+f"(d[30]), "+f"(d[31]), "+f"(d[32]), "+f"(d[33]), "+f"(d[34]), "+f"(d[35]), "+f"(d[36]), "+f"(d[37]), "+f"(d[38]), "+f"(d[39]), "+f"(d[40]), "+f"(d[41]), "+f"(d[42]), "+f"(d[43]), "+f"(d[44]), "+f"(d[45]), "+f"(d[46]), "+f"(d[47]), "+f"(d[48]), "+f"(d[49]), "+f"(d[50]), "+f"(d[51]), "+f"(d[52]), "+f"(d[53]), "+f"(d[54]), "+f"(d[55]), "+f"(d[56]), "+f"(d[57]), "+f"(d[58]), "+f"(d[59]), "+f"(d[60]), "+f"(d[61]), "+f"(d[62]), "+f"(d[63]), "+f"(d[64]), "+f"(d[65]), "+f"(d[66]), "+f"(d[67]), "+f"(d[68]), "+f"(d[69]), "+f"(d[70]), "+f"(d[71]), "+f"(d[72]), "+f"(d[73]), "+f"(d[74]), "+f"(d[75]), "+f"(d[76]), "+f"(d[77]), "+f"(d[78]), "+f"(d[79])
    : "r"(a0), "r"(a1), "r"(a2), "r"(a3), "r"(blo));
}
template<int N> __device__ __forceinline__ void wgmma_rs_hi(float (&d)[64], uint32_t a0, uint32_t a1, uint32_t a2, uint32_t a3, uint32_t blo);
template<> __device__ __forceinline__ void wgmma_rs_hi<16>(float (&d)[64], uint32_t a0, uint32_t a1, uint32_t a2, uint32_t a3, uint32_t blo){
  asm volatile("{\n.reg .b64 db;\nmov.b64 db, {%12,8};\nwgmma.mma_async.sync.aligned.m64n16k16.f32.bf16.bf16 {%0, %1, %2, %3, %4, %5, %6, %7}, {%8,%9,%10,%11}, db, 1, 1, 1, 0;\n}\n"
    : "+f"(d[56]), "+f"(d[57]), "+f"(d[58]), "+f"(d[59]), "+f"(d[60]), "+f"(d[61]), "+f"(d[62]), "+f"(d[63])
    : "r"(a0), "r"(a1), "r"(a2), "r"(a3), "r"(blo));
}
template<> __device__ __forceinline__ void wgmma_rs_hi<32>(float (&d)[64], uint32_t a0, uint32_t a1, uint32_t a2, uint32_t a3, uint32_t blo){
  asm volatile("{\n.reg .b64 db;\nmov.b64 db, {%20,8};\nwgmma.mma_async.sync.aligned.m64n32k16.f32.bf16.bf16 {%0, %1, %2, %3, %4, %5, %6, %7, %8, %9, %10, %11, %12, %13, %14, %15}, {%16,%17,%18,%19}, db, 1, 1, 1, 0;\n}\n"
    : "+f"(d[48]), "+f"(d[49]), "+f"(d[50]), "+f"(d[51]), "+f"(d[52]), "+f"(d[53]), "+f"(d[54]), "+f"(d[55]), "+f"(d[56]), "+f"(d[57]), "+f"(d[58]), "+f"(d[59]), "+f"(d[60]), "+f"(d[61]), "+f"(d[62]), "+f"(d[63])
    : "r"(a0), "r"(a1), "r"(a2), "r"(a3), "r"(blo));
}
template<> __device__ __forceinline__ void wgmma_rs_hi<48>(float (&d)[64], uint32_t a0, uint32_t a1, uint32_t a2, uint32_t a3, uint32_t blo){
  asm volatile("{\n.reg .b64 db;\nmov.b64 db, {%28,8};\nwgmma.mma_async.sync.aligned.m64n48k16.f32.bf16.bf16 {%0, %1, %2, %3, %4, %5, %6, %7, %8, %9, %10, %11, %12, %13, %14, %15, %16, %17, %18, %19, %20, %21, %22, %23}, {%24,%25,%26,%27}, db, 1, 1, 1, 0;\n}\n"
    : "+f"(d[40]), "+f"(d[41]), "+f"(d[42]), "+f"(d[43]), "+f"(d[44]), "+f"(d[45]), "+f"(d[46]), "+f"(d[47]), "+f"(d[48]), "+f"(d[49]), "+f"(d[50]), "+f"(d[51]), "+f"(d[52]), "+f"(d[53]), "+f"(d[54]), "+f"(d[55]), "+f"(d[56]), "+f"(d[57]), "+f"(d[58]), "+f"(d[59]), "+f"(d[60]), "+f"(d[61]), "+f"(d[62]), "+f"(d[63])
    : "r"(a0), "r"(a1), "r"(a2), "r"(a3), "r"(blo));
}
template<> __device__ __forceinline__ void wgmma_rs_hi<64>(float (&d)[64], uint32_t a0, uint32_t a1, uint32_t a2, uint32_t a3, uint32_t blo){
  asm volatile("{\n.reg .b64 db;\nmov.b64 db, {%36,8};\nwgmma.mma_async.sync.aligned.m64n64k16.f32.bf16.bf16 {%0, %1, %2, %3, %4, %5, %6, %7, %8, %9, %10, %11, %12, %13, %14, %15, %16, %17, %18, %19, %20, %21, %22, %23, %24, %25, %26, %27, %28, %29, %30, %31}, {%32,%33,%34,%35}, db, 1, 1, 1, 0;\n}\n"
    : "+f"(d[32]), "+f"(d[33]), "+f"(d[34]), "+f"(d[35]), "+f"(d[36]), "+f"(d[37]), "+f"(d[38]), "+f"(d[39]), "+f"(d[40]), "+f"(d[41]), "+f"(d[42]), "+f"(d[43]), "+f"(d[44]), "+f"(d[45]), "+f"(d[46]), "+f"(d[47]), "+f"(d[48]), "+f"(d[49]), "+f"(d[50]), "+f"(d[51]), "+f"(d[52]), "+f"(d[53]), "+f"(d[54]), "+f"(d[55]), "+f"(d[56]), "+f"(d[57]), "+f"(d[58]), "+f"(d[59]), "+f"(d[60]), "+f"(d[61]), "+f"(d[62]), "+f"(d[63])
    : "r"(a0), "r"(a1), "r"(a2), "r"(a3), "r"(blo));
}
template<> __device__ __forceinline__ void wgmma_rs_hi<80>(float (&d)[64], uint32_t a0, uint32_t a1, uint32_t a2, uint32_t a3, uint32_t blo){
  asm volatile("{\n.reg .b64 db;\nmov.b64 db, {%44,8};\nwgmma.mma_async.sync.aligned.m64n80k16.f32.bf16.bf16 {%0, %1, %2, %3, %4, %5, %6, %7, %8, %9, %10, %11, %12, %13, %14, %15, %16, %17, %18, %19, %20, %21, %22, %23, %24, %25, %26, %27, %28, %29, %30, %31, %32, %33, %34, %35, %36, %37, %38, %39}, {%40,%41,%42,%43}, db, 1, 1, 1, 0;\n}\n"
    : "+f"(d[24]), "+f"(d[25]), "+f"(d[26]), "+f"(d[27]), "+f"(d[28]), "+f"(d[29]), "+f"(d[30]), "+f"(d[31]), "+f"(d[32]), "+f"(d[33]), "+f"(d[34]), "+f"(d[35]), "+f"(d[36]), "+f"(d[37]), "+f"(d[38]), "+f"(d[39]), "+f"(d[40]), "+f"(d[41]), "+f"(d[42]), "+f"(d[43]), "+f"(d[44]), "+f"(d[45]), "+f"(d[46]), "+f"(d[47]), "+f"(d[48]), "+f"(d[49]), "+f"(d[50]), "+f"(d[51]), "+f"(d[52]), "+f"(d[53]), "+f"(d[54]), "+f"(d[55]), "+f"(d[56]), "+f"(d[57]), "+f"(d[58]), "+f"(d[59]), "+f"(d[60]), "+f"(d[61]), "+f"(d[62]), "+f"(d[63])
    : "r"(a0), "r"(a1), "r"(a2), "r"(a3), "r"(blo));
}
template<> __device__ __forceinline__ void wgmma_rs_hi<96>(float (&d)[64], uint32_t a0, uint32_t a1, uint32_t a2, uint32_t a3, uint32_t blo){
  asm volatile("{\n.reg .b64 db;\nmov.b64 db, {%52,8};\nwgmma.mma_async.sync.aligned.m64n96k16.f32.bf16.bf16 {%0, %1, %2, %3, %4, %5, %6, %7, %8, %9, %10, %11, %12, %13, %14, %15, %16, %17, %18, %19, %20, %21, %22, %23, %24, %25, %26, %27, %28, %29, %30, %31, %32, %33, %34, %35, %36, %37, %38, %39, %40, %41, %42, %43, %44, %45, %46, %47}, {%48,%49,%50,%51}, db, 1, 1, 1, 0;\n}\n"
    : "+f"(d[16]), "+f"(d[17]), "+f"(d[18]), "+f"(d[19]), "+f"(d[20]), "+f"(d[21]), "+f"(d[22]), "+f"(d[23]), "+f"(d[24]), "+f"(d[25]), "+f"(d[26]), "+f"(d[27]), "+f"(d[28]), "+f"(d[29]), "+f"(d[30]), "+f"(d[31]), "+f"(d[32]), "+f"(d[33]), "+f"(d[34]), "+f"(d[35]), "+f"(d[36]), "+f"(d[37]), "+f"(d[38]), "+f"(d[39]), "+f"(d[40]), "+f"(d[41]), "+f"(d[42]), "+f"(d[43]), "+f"(d[44]), "+f"(d[45]), "+f"(d[46]), "+f"(d[47]), "+f"(d[48]), "+f"(d[49]), "+f"(d[50]), "+f"(d[51]), "+f"(d[52]), "+f"(d[53]), "+f"(d[54]), "+f"(d[55]), "+f"(d[56]), "+f"(d[57]), "+f"(d[58]), "+f"(d[59]), "+f"(d[60]), "+f"(d[61]), "+f"(d[62]), "+f"(d[63])
    : "r"(a0), "r"(a1), "r"(a2), "r"(a3), "r"(blo));
}
template<> __device__ __forceinline__ void wgmma_rs_hi<112>(float (&d)[64], uint32_t a0, uint32_t a1, uint32_t a2, uint32_t a3, uint32_t blo){
  asm volatile("{\n.reg .b64 db;\nmov.b64 db, {%60,8};\nwgmma.mma_async.sync.aligned.m64n112k16.f32.bf16.bf16 {%0, %1, %2, %3, %4, %5, %6, %7, %8, %9, %10, %11, %12, %13, %14, %15, %16, %17, %18, %19, %20, %21, %22, %23, %24, %25, %26, %27, %28, %29, %30, %31, %32, %33, %34, %35, %36, %37, %38, %39, %40, %41, %42, %43, %44, %45, %46, %47, %48, %49, %50, %51, %52, %53, %54, %55}, {%56,%57,%58,%59}, db, 1, 1, 1, 0;\n}\n"
    : "+f"(d[8]), "+f"(d[9]), "+f"(d[10]), "+f"(d[11]), "+f"(d[12]), "+f"(d[13]), "+f"(d[14]), "+f"(d[15]), "+f"(d[16]), "+f"(d[17]), "+f"(d[18]), "+f"(d[19]), "+f"(d[20]), "+f"(d[21]), "+f"(d[22]), "+f"(d[23]), "+f"(d[24]), "+f"(d[25]), "+f"(d[26]), "+f"(d[27]), "+f"(d[28]), "+f"(d[29]), "+f"(d[30]), "+f"(d[31]), "+f"(d[32]), "+f"(d[33]), "+f"(d[34]), "+f"(d[35]), "+f"(d[36]), "+f"(d[37]), "+f"(d[38]), "+f"(d[39]), "+f"(d[40]), "+f"(d[41]), "+f"(d[42]), "+f"(d[43]), "+f"(d[44]), "+f"(d[45]), "+f"(d[46]), "+f"(d[47]), "+f"(d[48]), "+f"(d[49]), "+f"(d[50]), "+f"(d[51]), "+f"(d[52]), "+f"(d[53]), "+f"(d[54]), "+f"(d[55]), "+f"(d[56]), "+f"(d[57]), "+f"(d[58]), "+f"(d[59]), "+f"(d[60]), "+f"(d[61]), "+f"(d[62]), "+f"(d[63])
    : "r"(a0), "r"(a1), "r"(a2), "r"(a3), "r"(blo));
}
template<> __device__ __forceinline__ void wgmma_rs_hi<128>(float (&d)[64], uint32_t a0, uint32_t a1, uint32_t a2, uint32_t a3, uint32_t blo){
  asm volatile("{\n.reg .b64 db;\nmov.b64 db, {%68,8};\nwgmma.mma_async.sync.aligned.m64n128k16.f32.bf16.bf16 {%0, %1, %2, %3, %4, %5, %6, %7, %8, %9, %10, %11, %12, %13, %14, %15, %16, %17, %18, %19, %20, %21, %22, %23, %24, %25, %26, %27, %28, %29, %30, %31, %32, %33, %34, %35, %36, %37, %38, %39, %40, %41, %42, %43, %44, %45, %46, %47, %48, %49, %50, %51, %52, %53, %54, %55, %56, %57, %58, %59, %60, %61, %62, %63}, {%64,%65,%66,%67}, db, 1, 1, 1, 0;\n}\n"
    : "+f"(d[0]), "+f"(d[1]), "+f"(d[2]), "+f"(d[3]), "+f"(d[4]), "+f"(d[5]), "+f"(d[6]), "+f"(d[7]), "+f"(d[8]), "+f"(d[9]), "+f"(d[10]), "+f"(d[11]), "+f"(d[12]), "+f"(d[13]), "+f"(d[14]), "+f"(d[15]), "+f"(d[16]), "+f"(d[17]), "+f"(d[18]), "+f"(d[19]), "+f"(d[20]), "+f"(d[21]), "+f"(d[22]), "+f"(d[23]), "+f"(d[24]), "+f"(d[25]), "+f"(d[26]), "+f"(d[27]), "+f"(d[28]), "+f"(d[29]), "+f"(d[30]), "+f"(d[31]), "+f"(d[32]), "+f"(d[33]), "+f"(d[34]), "+f"(d[35]), "+f"(d[36]), "+f"(d[37]), "+f"(d[38]), "+f"(d[39]), "+f"(d[40]), "+f"(d[41]), "+f"(d[42]), "+f"(d[43]), "+f"(d[44]), "+f"(d[45]), "+f"(d[46]), "+f"(d[47]), "+f"(d[48]), "+f"(d[49]), "+f"(d[50]), "+f"(d[51]), "+f"(d[52]), "+f"(d[53]), "+f"(d[54]), "+f"(d[55]), "+f"(d[56]), "+f"(d[57]), "+f"(d[58]), "+f"(d[59]), "+f"(d[60]), "+f"(d[61]), "+f"(d[62]), "+f"(d[63])
    : "r"(a0), "r"(a1), "r"(a2), "r"(a3), "r"(blo));
}

struct CvCtx {
  uint32_t koff, zero, so[3];
  int srcA, srcB;
  bool wrapA, s3, kodd;
};
struct CvPipe { uint32_t Ap, Ep, keep, send; };
template <int LO> __device__ __forceinline__ void cv_copy(float (&acc)[64]) {
#pragma unroll
  for (int i = LO; i < 64; i++) { float t; asm volatile("mov.b32 %0, %1;" : "=f"(t) : "f"(acc[i]) : "memory"); acc[i] = t; }
}
template <int G> __device__ __forceinline__ void cv_raw(uint32_t (&A)[4][4], uint32_t kaddr) {
#pragma unroll
  for (int i = 0; i < 4; i++) {
    const uint32_t a = kaddr + (4 * G + i) * 128;
    A[i][0] = lds32(a); A[i][1] = lds32(a + 4); A[i][3] = lds32(a + 8);
  }
}
__device__ __forceinline__ void cv_form(uint32_t (&A)[4][4], uint32_t sel) {
#pragma unroll
  for (int i = 0; i < 4; i++) {
    asm volatile("prmt.b32 %0, %0, %1, %2;" : "+r"(A[i][0]) : "r"(A[i][1]), "r"(sel));
    asm volatile("prmt.b32 %0, %1, %2, %3;" : "=r"(A[i][2]) : "r"(A[i][1]), "r"(A[i][3]), "r"(sel));
  }
}
#define CVV 2
template <int G> __device__ __forceinline__ void cv_step(float (&acc)[64], uint32_t (&A)[4][4], CvPipe& s, const CvCtx& c, uint32_t cb, uint32_t stg) {
  constexpr int JA = G - 1, JB = G - 2, NH = CVV == 1 ? 4 : (CVV == 3 ? 2 : 1);
  const uint32_t db0 = desc_lo(cb + CV_U + 192, CV_PL);
  uint32_t B[4][4];
  uint32_t ra[2], rb;
  if constexpr (G < 8) {
    wgmma_fence();
#pragma unroll
    for (int i = 0; i < NH; i++) wgmma_rs_hi<128 - 16 * (G & 7)>(acc, A[i][0], A[i][1], A[i][2], A[i][3], db0 - 4 * i);
    wgmma_commit();
    __syncwarp();
  }
  if constexpr (JA >= 0 && JA < 8) {
    const uint32_t p0 = pack_bf16(acc[8 * JA + 1], acc[8 * JA + 3]), p1 = pack_bf16(acc[8 * JA + 5], acc[8 * JA + 7]);
    ra[0] = __shfl_sync(0xffffffffu, c.wrapA ? s.Ap : p0, c.srcA);
    ra[1] = __shfl_sync(0xffffffffu, c.wrapA ? p0 : p1, c.srcA);
    s.Ap = p1;
  }
  if constexpr (JB >= 0) rb = __shfl_sync(0xffffffffu, s.send, c.srcB);
  if constexpr (G < 7) cv_raw<G + 1>(B, cb + c.koff);
  uint32_t z = 0;
  if constexpr (G < 8 && NH < 4) {
    __syncwarp();
    wgmma_fence();
#pragma unroll
    for (int i = NH; i < 4; i++) wgmma_rs_hi<128 - 16 * (G & 7)>(acc, A[i][0], A[i][1], A[i][2], A[i][3], db0 - 4 * i);
    wgmma_commit();
    asm volatile("mov.u32 %0, %%clock;" : "=r"(z)::"memory");
    z &= c.zero;
  }
  if constexpr (G < 7) cv_form(B, 0x5432u | z);
  if constexpr (JB >= 0) sts32(stg + ((c.so[JB / 3] >> (10 * (JB % 3))) & 0xffc), hadd2(rb | z, s.keep));
  if constexpr (JA >= 0 && JA < 8) {
    const uint32_t sh = 16 | z, mk = 0xffff0000u | z;
    const uint32_t ev = pack_bf16(acc[8 * JA] + __uint_as_float(ra[0] << sh), acc[8 * JA + 2] + __uint_as_float(ra[0] & mk));
    const uint32_t od = pack_bf16(acc[8 * JA + 4] + __uint_as_float(ra[1] << sh), acc[8 * JA + 6] + __uint_as_float(ra[1] & mk));
    s.send = c.kodd ? ev : (c.s3 ? s.Ep : od);
    s.keep = c.kodd ? od : ev;
    s.Ep = od;
  }
  if constexpr (G < 8) { __syncwarp(); wgmma_wait<0>(); cv_copy<8 * (G & 7)>(acc); }
  if constexpr (G < 9) cv_step<G + 1>(acc, B, s, c, cb, stg);
}
__device__ __forceinline__ uint32_t cv_stage(int slot) { return sb + (slot < 4 ? 40960 + slot * 4096 : CV_OFF + CV_K); }
__device__ __forceinline__ void cv_setup(CvCtx& c) {
  const int tid = tid_opaque() & 127, w = tid >> 5, lane = tid & 31, r = lane >> 2, q = lane & 3;
  const int i0 = (r >> 1) & 1, i1 = r >> 2;
  c.koff = CV_K - 32 + 4 * (8 * (r >> 1) + 2 * w + (r & 1) + 2 * q);
  c.srcA = i0 ? lane - 8 : lane + 8 - q + ((q + 3) & 3);
  c.wrapA = i0 && q == 3;
  c.srcB = i1 == 0 ? (lane - q + 16 + ((q + 3) & 3)) : (lane - q - 16 + ((q + 1) & 3));
  c.s3 = (i1 == 1 && q == 3); c.kodd = (i1 == 1 && q < 3);
  c.zero = lds32(sb + EP_OFF + 24);
#pragma unroll
  for (int i = 0; i < 3; i++) c.so[i] = lds32(sb + SO_OFF + 512 * i + 4 * tid);
}
__device__ __forceinline__ void cv_table() {
  const int tid = tid_opaque() & 127, r = (tid & 31) >> 2, q = tid & 3;
  int t = 16 * (2 * (r < 4 ? q : 4 + ((q + 1) & 3)) + ((r >> 1) & 1)) + 4 * (tid >> 5) + 2 * (r & 1);
#pragma unroll 1
  for (int i = 0; i < 3; i++) {
    uint32_t v = 0;
#pragma unroll 1
    for (int x = 0; x < 3; x++, t += 256) {
      const int T = t / 160, tl = t - T * 160;
      const int qq = (T >= NT1 - 1) ? (tl >> 5) : (tl / 40);
      int ck = 20 * T + ((tl - qq * ((T >= NT1 - 1) ? 32 : 40)) >> 1);
      ck ^= (ck >> 2) & 6;
      v |= (uint32_t)((ck * 4 + qq) & 1023) << (10 * x + 2);
    }
    sts32(sb + SO_OFF + 512 * i + 4 * tid, v);
  }
}
__device__ __forceinline__ void conv_channel(int slot, const CvCtx& c) {
  const uint32_t cb = sb + CV_OFF + slot * CV_B;
  float acc[64];
  CvPipe s;
  s.Ap = s.Ep = 0u;
  uint32_t A[4][4];
#pragma unroll
  for (int i = 0; i < 64; i++) acc[i] = 0.f;
  if (slot == 4) mbar_wait(bars + 8 * B_CVDONE);
  mbar_wait(bars + 8 * (B_CVFULL + slot));
  cv_raw<0>(A, cb + c.koff);
  {
    const uint32_t w0 = lds32(cb + CV_K);
    const uint32_t wp = __byte_perm(pack_bf16(bf_lo(w0) + __uint_as_float(lds32(sb + EP_OFF + 4 * slot)), 0.f), w0, 0x7610);
    if (c.koff == CV_K) A[0][0] = wp;
    if (c.koff == CV_K - 4) A[0][1] = wp;
    if (c.koff == CV_K - 8) A[0][3] = wp;
  }
  cv_form(A, 0x5432u);
  cv_copy<0>(acc);
  cv_step<0>(acc, A, s, c, cb, cv_stage(slot));
  fence_async_smem();
  mbar_arrive(bars + 8 * (B_CVDONE + slot));
}

__device__ __forceinline__ void kv_issue(const Params& p, int c, int m2, int dg) {
  const uint32_t fb = bars + 8 * (B_KV + c);
  mbar_expect_tx(fb, KV_PIECE);
  tma3(sb + KS_OFF + c * KV_PIECE, &p.mK, 160 * dg + 32 * c, 64 * m2 - 3, 0, fb);
  tma3(sb + KS_OFF + c * KV_PIECE + 4864, &p.mV, 160 * dg + 32 * c, 64 * m2 - 1, 0, fb);
}
__device__ __forceinline__ void kv_tile(int m, int c, int y, uint32_t (&o)[4][4]) {
  const int lane = tid_opaque() & 31, tg = lane & 3, pr = 8 * (y ^ (tg >> 1)) + (lane >> 2);
  const uint32_t pb = sb + KS_OFF + c * KV_PIECE + 4 * pr;
  const uint32_t ka = pb + tg * 1216, va = pb + 4864 + tg * 1088 + 64;
  const uint32_t kh = (m == 0 && tg > 0) ? ka - 192 : ka;
  uint32_t kk[19], u[16];
  const float4 t = lds128f(sb + TAP_OFF + 256 * c + 16 * pr);
#pragma unroll
  for (int i = 0; i < 19; i++) { kk[i] = lds32((i < 3 ? kh : ka) + i * 64); if (i >= 3) u[i - 3] = lds32(va + (i - 3) * 64); }
  const uint32_t dst = sb + KS_OFF + c * KV_PIECE + pr * 64 + tg * 16;
  if (y) {
    __syncwarp();
#pragma unroll
    for (int x = 0; x < 4; x++) sts128((dst ^ 512) + x * 1024, make_uint4(o[x][0], o[x][1], o[x][2], o[x][3]));
  }
  const uint32_t w0 = __byte_perm(__float_as_uint(t.x), __float_as_uint(t.z), 0x5410), w1 = __byte_perm(__float_as_uint(t.x), __float_as_uint(t.z), 0x7632);
  const uint32_t w2 = __byte_perm(__float_as_uint(t.y), __float_as_uint(t.w), 0x5410), w3 = __byte_perm(__float_as_uint(t.y), __float_as_uint(t.w), 0x7632);
#pragma unroll
  for (int i = 0; i < 16; i++) {
    uint32_t a = hmul2(kk[i], w3);
    a = hadd2(a, hmul2(kk[i + 1], w2)); a = hadd2(a, hmul2(kk[i + 2], w1)); a = hadd2(a, hmul2(kk[i + 3], w0));
    u[i] = hmul2(a, u[i]);
  }
#pragma unroll
  for (int x = 0; x < 4; x++) {
#pragma unroll
    for (int qq = 0; qq < 4; qq++) o[x][qq] = __byte_perm(u[15 - 4 * qq - (x & 2)], u[14 - 4 * qq - (x & 2)], (x & 1) ? 0x7632 : 0x5410);
    if (y) sts128(dst + x * 1024, make_uint4(o[x][0], o[x][1], o[x][2], o[x][3]));
  }
}
__device__ __forceinline__ void ln_finish(float s1, float s2, float& mean, float& rstd) {
  mean = s1 * (1.f / 640.f);
  const float v = fmaxf(fmaf(-mean, mean, s2 * (1.f / 640.f)), 0.f) + 1e-5f;
  asm("rsqrt.approx.ftz.f32 %0, %1;" : "=f"(rstd) : "f"(v));
}
__device__ __forceinline__ void stat_table(int T1, unsigned want, int l, int g, const uint4* x0, const uint4* x1, float (&xa)[2], float (&xb)[2]) {
  const int n = 32 * g + (tid_opaque() & 31);
  const uint4* rp = &g_stats[8 * l * SEQ + min(160 * T1 + n, SEQ - 1)];
  float a[4], b[4];
  uint32_t it = 0;
  while (true) {
    bool ok = true;
#pragma unroll
    for (int i = 0; i < 4; i++) ok &= (rec_ld(rp + SEQ * i, a[i], b[i]) == want);
    ok &= rec_ld(x0, xa[0], xb[0]) == want;
    ok &= rec_ld(x1, xa[1], xb[1]) == want;
    if (__all_sync(0xffffffffu, ok)) break;
    trap_if(++it > SPIN_LIMIT);
  }
  float m, rs;
  ln_finish((a[0] + a[1]) + (a[2] + a[3]), (b[0] + b[1]) + (b[2] + b[3]), m, rs);
  sts32(sb + STAB_OFF + ((n >> 1) & 3) * 160 + (n >> 3) * 8 + (n & 1) * 4, __float_as_uint(rs));
  const uint32_t hi = pack_bf16(-m, -m);
  const float lo = -m - bf_lo(hi);
  sts128(sb + (l ? MX1_OFF : MX0_OFF) + n * 16, make_uint4(hi, pack_bf16(lo, lo), 0u, 0u));
  fence_async_smem();
}
__device__ __forceinline__ void stats_reduce(float (&a)[2], float (&b)[2], float (&mean)[2], float (&rstd)[2]) {
#pragma unroll
  for (int o = 1; o < 4; o <<= 1)
#pragma unroll
    for (int h = 0; h < 2; h++) { a[h] += __shfl_xor_sync(0xffffffffu, a[h], o); b[h] += __shfl_xor_sync(0xffffffffu, b[h], o); }
#pragma unroll
  for (int h = 0; h < 2; h++) ln_finish(a[h], b[h], mean[h], rstd[h]);
}

template <bool FIRST>
__device__ __forceinline__ void stats_publish(int which, int n0, int dg, unsigned tag, const float (&acc)[80]) {
  const int q = tid_opaque() & 3, h = q & 1;
  float s1[2] = {0.f, 0.f}, s2[2] = {0.f, 0.f}, t1[2] = {0.f, 0.f}, t2[2] = {0.f, 0.f};
#pragma unroll
  for (int j = 0; j < 20; j++)
#pragma unroll
    for (int y = 0; y < 2; y++) {
      const float a = acc[4 * j + 2 * y], b = acc[4 * j + 2 * y + 1];
      s1[y] += a; t1[y] += b; s2[y] = fmaf(a, a, s2[y]); t2[y] = fmaf(b, b, t2[y]);
    }
#pragma unroll
  for (int y = 0; y < 2; y++) { s1[y] += t1[y]; s2[y] += t2[y]; }
  float a = (h ? s1[1] : s1[0]) + __shfl_xor_sync(0xffffffffu, h ? s1[0] : s1[1], 1);
  float b = (h ? s2[1] : s2[0]) + __shfl_xor_sync(0xffffffffu, h ? s2[0] : s2[1], 1);
  a += __shfl_xor_sync(0xffffffffu, a, 2);
  b += __shfl_xor_sync(0xffffffffu, b, 2);
  if (FIRST) {
    rec_st(&g_stats[((q >> 1) * 4 + dg) * SEQ + n0 + 8 * h], a, b, q < 2 ? tag : tag - 1);
    rec_st(&g_stats[((q >> 1) * 4 + 8 + dg) * SEQ + n0 + 8 * h], a, b, tag - 1);
  } else if (q < 2) rec_st(&g_stats[(which * 4 + dg) * SEQ + n0 + 8 * h], a, b, tag);
}
__device__ __forceinline__ void stats_get(int which, int n0, unsigned tag, float (&mean)[2], float (&rstd)[2]) {
  const uint4* p0 = &g_stats[(which * 4 + (tid_opaque() & 3)) * SEQ + n0];
  float a[2], b[2];
  uint32_t it = 0;
  while (true) {
    const unsigned t0 = rec_ld(p0, a[0], b[0]), t1 = rec_ld(p0 + 8, a[1], b[1]);
    if (__all_sync(0xffffffffu, t0 == tag && t1 == tag)) break;
    trap_if(++it > SPIN_LIMIT);
  }
  stats_reduce(a, b, mean, rstd);
}
__device__ __forceinline__ void x0_load(float (&acc)[80]) {
  const int t = tid_opaque() & 127;
  const uint32_t xa = sb + XT_OFF + (16 * (t >> 5) + ((t & 31) >> 2)) * 320 + 8 * (t & 3);
  mbar_wait(bars + 8 * B_XT);
#pragma unroll
  for (int h = 0; h < 2; h++)
#pragma unroll
    for (int J = 0; J < 10; J++) {
      const float2 v = lds64f(xa + h * 2560 + 32 * J);
      const uint32_t x = __float_as_uint(v.x), y = __float_as_uint(v.y);
      acc[8 * J + 2 * h] = bf_lo(x); acc[8 * J + 2 * h + 1] = bf_hi(x);
      acc[8 * J + 4 + 2 * h] = bf_lo(y); acc[8 * J + 4 + 2 * h + 1] = bf_hi(y);
    }
}

template <bool FROM_X0>
__device__ __forceinline__ void dskip_init(float (&acc)[80], const float (&mean)[2], const float (&rstd)[2]) {
  const int t = tid_opaque() & 127;
  const uint32_t xa = sb + XT_OFF + (16 * (t >> 5) + ((t & 31) >> 2)) * 320 + 8 * (t & 3), da = sb + DTAB_OFF + 8 * (t & 3);
  float2 dw[10], xv[10][2];
#pragma unroll
  for (int J = 0; J < 2; J++) { dw[J] = lds64f(da + 32 * J); if (FROM_X0) { xv[J][0] = lds64f(xa + 32 * J); xv[J][1] = lds64f(xa + 2560 + 32 * J); } }
#pragma unroll
  for (int J = 0; J < 10; J++) {
    if (J + 2 < 10) { dw[J + 2] = lds64f(da + 32 * (J + 2)); if (FROM_X0) { xv[J + 2][0] = lds64f(xa + 32 * (J + 2)); xv[J + 2][1] = lds64f(xa + 2560 + 32 * (J + 2)); } }
#pragma unroll
    for (int x = 0; x < 8; x++) {
      const int h = (x >> 1) & 1;
      const uint32_t dwd = __float_as_uint(x < 4 ? dw[J].x : dw[J].y);
      const float tt = fmaf(rstd[h], (x & 1) ? bf_hi(dwd) : bf_lo(dwd), 1.f);
      float a = acc[8 * J + x];
      if (FROM_X0) { const uint32_t xw = __float_as_uint(x < 4 ? xv[J][h].x : xv[J][h].y); a = (x & 1) ? bf_hi(xw) : bf_lo(xw); }
      acc[8 * J + x] = FROM_X0 ? (a - mean[h]) * tt : fmaf(a, tt, -mean[h] * tt);
    }
  }
}

__global__ void __launch_bounds__(512, 1) fused_kernel(const __grid_constant__ Params p) {
  extern __shared__ __align__(1024) uint8_t smem_raw[];
  const int tid = threadIdx.x, lane = tid & 31;
  const int wid = __shfl_sync(0xffffffffu, tid >> 5, 0), wg = wid >> 2;
  unsigned smid; asm volatile("mov.u32 %0, %%smid;" : "=r"(smid));
  const int role = p.role[min(smid, 131u)];
  if (wid == 12) {
    const bool el = elect_one();
    if (el) {
      asm volatile("prefetch.tensormap [%0];" ::"l"(&p.mB) : "memory");
      asm volatile("prefetch.tensormap [%0];" ::"l"((role & 15) == NT1 - 1 ? &p.mXl : &p.mX) : "memory");
#pragma unroll
      for (int k = 0; k < S1; k++) mbar_init(bars + 8 * (B_G1FULL + k), 1);
#pragma unroll
      for (int k = 0; k < 6; k++) mbar_init(bars + 8 * (B_XT + k), 1);
      asm volatile("fence.mbarrier_init.release.cluster;" ::: "memory");
    }
    if (role >= 0) {
      __syncwarp();
      asm volatile("bar.arrive 5, 288;" ::: "memory");
      const Role R = unpack_role(role);
      if (elect_one()) {
        TS(45);
#pragma unroll 1
        for (int k = 0; k < S1; k++) {
          const uint32_t fb = bars + 8 * (B_G1FULL + k);
          mbar_expect_tx(fb, G1_STAGE);
          tma4(sb + k * G1_STAGE + G1_XOFF, R.last ? &p.mXl : &p.mX, 64 * k, 0, 0, R.last ? 0 : 80 * R.T1, fb);
          tma5(sb + k * G1_STAGE, &p.mB, 64 * k, 0, 0, 4 * R.side, 2 * R.GP, fb);
          if (PFD) asm volatile("prefetch.tensormap [%0];" ::"l"(&p.mK + k) : "memory");
        }
        if (R.has2) {
          mbar_expect_tx(bars + 8 * B_XT, 20480);
#pragma unroll 1
          for (int h = 0; h < 2; h++) {
            const int ng = 8 * R.m2 + 4 * h, T = ng / 20;
            tma4(sb + XT_OFF + h * 10240, T == NT1 - 1 ? &p.mXtl : &p.mXt, 160 * R.dg, 0, 0, T == NT1 - 1 ? ng - 240 : ng + 60 * T, bars + 8 * B_XT);
          }
#pragma unroll 1
          for (int c = 0; c < KV0; c++) kv_issue(p, c, R.m2, R.dg);
        }
        TS(44);
      }
      __syncwarp();
      bar_sync(6, 64);
    }
  }
  trap_if(smid >= 132 || smem_u32(smem_raw) != sb);
  if (role < 0) {
    if (wid == 0) {
      const unsigned tag = ld_rlx(g_epoch);
      uint32_t it = 0;
      while (!__all_sync(0xffffffffu, (int)(ld_rlx(&g_hcnt[(lane & 7) * 32]) - 40 * tag) >= 0)) { __nanosleep(500); trap_if(++it > SPIN_LIMIT); }
    }
    return;
  }
  float mean0[2] = {0.f, 0.f}, rstd0[2] = {0.f, 0.f};
  if (wg == 2 || wid == 14) {
    ROLE(role)
    const int c = wid == 14 ? 4 : wid - 8;
    const unsigned tag = ld_rlx(g_epoch);
    if (has2) {
      uint2 bv[2][5];
#pragma unroll
      for (int x = 0; x < 2; x++)
#pragma unroll
        for (int i = 0; i < 5; i++) bv[x][i] = ldv64((const uint2*)((x ? p.bim : p.bre) + (cch0 + 32 * c) * DM) + lane + 32 * i);
      float sv[2];
#pragma unroll
      for (int x = 0; x < 2; x++) {
        float a = 0.f;
#pragma unroll
        for (int i = 0; i < 5; i++) a += (bf_lo(bv[x][i].x) + bf_hi(bv[x][i].x)) + (bf_lo(bv[x][i].y) + bf_hi(bv[x][i].y));
        sv[x] = a;
      }
#pragma unroll
      for (int o = 16; o > 0; o >>= 1) { sv[0] += __shfl_xor_sync(0xffffffffu, sv[0], o); sv[1] += __shfl_xor_sync(0xffffffffu, sv[1], o); }
      if (lane < 2) rec_st(&g_sB[(cch0 + 32 * c) * 2 + lane], sv[0], sv[1], tag);
      if (tid == 256) TS(47);
      __syncwarp();
      bar_sync(8, 192);
      if (wg == 2) {
        float xs[80];
        x0_load(xs);
        stats_publish<true>(0, 64 * m2 + 16 * c + (lane >> 2), dg, tag, xs);
        if (tid == 256) TS(31);
      }
      mbar_wait(bars + 8 * B_EP);
      mbar_wait(bars + 8 * (B_KV + c));
      mbar_wait(bars + 8 * (B_G1DONE + PAUSE_K - 1));
      if (tid == 448) TS(52);
      uint32_t o[4][4] = {};
#pragma unroll 1
      for (int y = 0; y < 2; y++) kv_tile(m2, c, y, o);
      fence_async_smem();
      __syncwarp();
      if (lane == 0) { mbar_arrive(bars + 8 * B_PREP); mbar_arrive(bars + 8 * (B_PD + c)); }
      if (tid == 448) TS(51);
    } else bar_sync(8, 192);
    {
      const uint4* x0 = wg == 2 ? &g_stats[(lane & 3) * SEQ + (has2 ? 64 * m2 : 0) + 16 * c + (lane >> 2)] : &g_sB[(128 * GP + 32 * side + lane) * 2];
      float xa[2], xb[2];
      stat_table(T1, tag, 0, c, x0, x0 + (wg == 2 ? 8 : 128), xa, xb);
      if (wg == 2) stats_reduce(xa, xb, mean0, rstd0);
      else {
#pragma unroll
        for (int i = 0; i < 2; i++) {
          const float ha = bf_lo(pack_bf16(xa[i], 0.f)), hb = bf_lo(pack_bf16(xb[i], 0.f));
          const float pa = __uint_as_float(pack_bf16(ha, xa[i] - ha)), pb = __uint_as_float(pack_bf16(hb, xb[i] - hb));
          sts64f(sb + CTAB_OFF + (32 * i + lane) * 24 + 16, p.swap ? pb : pa, p.swap ? pa : pb);
        }
      }
      mbar_arrive(bars + 8 * B_STAB);
      if (tid == 448) TS(26);
    }
  } else if (wid == 15) {
    ROLE(role)
    const int ch = 128 * GP + 32 * side + lane;
    uint32_t r0 = ldv16(p.lre + ch), r1 = ldv16(p.lim + ch), r2 = ldv16(p.logdt + ch);
    const uint32_t r3 = ldv16(p.lre + ch + 64), r4 = ldv16(p.lim + ch + 64), r5 = ldv16(p.logdt + ch + 64);
#pragma unroll 1
    for (int i = 0; i < 2; i++) {
      const float lr = bf_lo(r0), li = bf_lo(r1);
      const float dt = __bfloat162float(__float2bfloat16_rn(expf(bf_lo(r2))));
      const float mag = expf(dt * lr);
      float sn, cs; sincospif(dt * li * 0.31830988618379067f, &sn, &cs);
      const float ar = mag * cs, ai = mag * sn;
      const float inv = 2.f / (lr * lr + li * li);
      const uint32_t ad = sb + CTAB_OFF + (32 * i + lane) * 24;
      sts64f(ad, ar, ai);
      sts64f(ad + 8, ((ar - 1.f) * lr + ai * li) * inv, (ai * lr - (ar - 1.f) * li) * inv);
      r0 = r3; r1 = r4; r2 = r5;
    }
    if (lane == 0) TS(46);
    __syncwarp();
    bar_sync(7, 64);
    mbar_arrive(bars + 8 * B_CTAB);
  } else if (wid == 13) {
    ROLE(role)
    uint4 tv[3];
    const uint32_t e0 = ld_rlx(g_epoch);
    const uint32_t e1 = ldv16(p.ssmD + min(cch0 + 32 * lane, 639));
    const uint4 dv = ldv128((const uint4*)(p.dskip + 160 * dg) + min(lane, 19));
#pragma unroll
    for (int i = 0; i < 3; i++) tv[i] = ldv128((const uint4*)(p.shiftk + 640 * dg) + min(lane + 32 * i, 79));
    sts128(sb + DTAB_OFF + 16 * min(lane, 19), dv);
#pragma unroll
    for (int i = 0; i < 3; i++) sts128(sb + TAP_OFF + 16 * min(lane + 32 * i, 79), tv[i]);
    if (lane < 7) sts32(sb + EP_OFF + 4 * lane, lane < 5 ? e1 << 16 : (lane == 5 ? e0 : 0u));
    __syncwarp();
    bar_sync(9, 64);
    mbar_arrive(bars + 8 * B_CTAB);
    if (lane == 0) { mbar_arrive(bars + 8 * B_EP); TS(53); }
    if (has2) {
#pragma unroll 1
      for (int i = 0; i < 5; i++) {
        const int c = i == 2 ? 3 : (i == 3 ? 2 : i);
        mbar_wait(bars + 8 * (B_PD + c));
        if (lane == 0) bulk_s2g(g_kv + (dg * 32 + m2) * 20480 + c * 4096, sb + KS_OFF + c * KV_PIECE, 4096);
      }
      if (lane == 0) {
        asm volatile("cp.async.bulk.commit_group;" ::: "memory");
        asm volatile("cp.async.bulk.wait_group 0;" ::: "memory");
        mbar_arrive(bars + 8 * B_PREP2);
        fence_async_global();
      }
      __syncwarp();
      if (lane < 4) red_rel(&g_kvcnt[(dg * 4 + lane) * 32]);
      __syncwarp();
      if (lane == 0) { mbar_arrive(bars + 8 * B_PUB); TS(30); }
    }
  } else if (wid != 12) {
    if (elect_one()) {
      if (wid < 7) {
        const int b0 = wid < 4 ? 4 + 19 * wid : 85 + 21 * (wid - 4), cnt = wid < 4 ? 2 : 1;
#pragma unroll
        for (int i = 0; i < 21; i++) mbar_init(bars + 8 * (b0 + i), cnt);
      } else {
#pragma unroll
        for (int i = 0; i < 12; i++) mbar_init(bars + 8 * (B_CVDONE + i), (i == 5 || i == 6) ? 160 : 128);
        mbar_init(bars + 8 * B_CTAB, 192); mbar_init(bars + 8 * B_PREP, 5); mbar_init(bars + 8 * B_PREP2, 1);
#pragma unroll
        for (int i = 0; i < 5; i++) mbar_init(bars + 8 * (B_PD + i), 1);
      }
      asm volatile("fence.mbarrier_init.release.cluster;" ::: "memory");
    }
    __syncwarp();
    bar_sync(5, 288);
    if (wid == 2) asm volatile("bar.arrive 8, 192;\nbar.arrive 6, 64;\nbar.arrive 9, 64;\nbar.arrive 7, 64;" ::: "memory");
    if (tid == 128) TS(0);
    if (wg == 1) { cv_table(); mbar_arrive(bars + 8 * B_CTAB); }
  }

  if (wid == 12) {
    ROLE(role)
    uint32_t dst = sb;
#pragma unroll 1
    for (int k = S1; k < 10; k++) {
      const uint32_t fb = bars + 8 * (B_G1FULL + k);
      mbar_wait(bars + 8 * (B_G1DONE + k - S1));
      if (elect_one()) {
        mbar_expect_tx(fb, 20480);
        tma4(dst + G1_XOFF, last ? &p.mXl : &p.mX, 64 * k, 0, 0, last ? 0 : 80 * T1, fb);
        mbar_expect_tx(fb, 16384);
        tma5(dst, &p.mB, 64 * k, 0, 0, 4 * side, 2 * GP, fb);
        if (has2 && k - S1 + KV0 < 5) kv_issue(p, k - S1 + KV0, m2, dg);
      }
      dst += G1_STAGE; if (k == 2 * S1 - 1) dst = sb;
    }
  } else if (wid == 15 && (role >> 16)) {
    ROLE(role)
    if (TPF >= 0) {
      mbar_wait(bars + 8 * (B_KV + TPF));
      if (elect_one()) {
#pragma unroll
        for (int c = 0; c < 5; c++) l2_prefetch(p.ssmk + (cch0 + 32 * c) * SEQ, 4096);
        if (CPF) { l2_prefetch(p.cre + (160 * dg + 5 * m2) * DM, 6400); l2_prefetch(p.cim + (160 * dg + 5 * m2) * DM, 6400); }
      }
    }
    mbar_wait(bars + 8 * B_PREP2);
    if (lane < 10) sts128(sb + CV_OFF + (lane >> 1) * CV_B + CV_K - 32 + 16 * (lane & 1), make_uint4(0, 0, 0, 0));
    fence_async_smem();
    __syncwarp();
    const unsigned tag = lds32(sb + EP_OFF + 20);
    if (TAPW) mbar_wait(bars + 8 * B_PUB);
    if (elect_one()) {
#pragma unroll 1
      for (int c = 0; c < 5; c++) {
        if (c == 0) asm volatile("prefetch.tensormap [%0];" ::"l"(&p.mU) : "memory");
        mbar_expect_tx(bars + 8 * (B_CVFULL + c), 4096 + 2 * CV_PL);
        if (c < TAPN) bulk_g2s(sb + CV_OFF + c * CV_B + CV_K, p.ssmk + (cch0 + 32 * c) * SEQ, 4096, bars + 8 * (B_CVFULL + c));
      }
    }
    mbar_wait(bars + 8 * B_PUB);
    cnt_poll(&g_kvcnt[(dg * 4 + (m2 >> 3)) * 32], 32 * tag);
    fence_async_global();
    if (elect_one()) {
      TS(28);
#pragma unroll
      for (int c = 0; c < 5; c++) {
        tma5(sb + CV_OFF + c * CV_B + CV_U, &p.mU, 0, -3, 2 * c, 16 * (m2 & 1) + (m2 >> 1), dg, bars + 8 * (B_CVFULL + c));
        if (c >= TAPN) bulk_g2s(sb + CV_OFF + c * CV_B + CV_K, p.ssmk + (cch0 + 32 * c) * SEQ, 4096, bars + 8 * (B_CVFULL + c));
      }
#pragma unroll
      for (int i = 0; i < 3; i++) asm volatile("prefetch.tensormap [%0];" ::"l"(&p.mCre + i) : "memory");
      TS(54);
    }
    __syncwarp();
  }
  {
    const int w = wid & 3;
    if (wg == 2 && !(role >> 16)) {
      float xa[2], xb[2];
      mbar_wait(bars + 8 * (B_G1FULL + 11));
      stat_table(role & 15, lds32(sb + EP_OFF + 20), 1, w, g_stats, g_stats, xa, xb);
      mbar_arrive(bars + 8 * (B_STAB + 1));
    }
#pragma unroll 1
    for (int l = 0; l < 2; l++) {
      if (wg < 2) {
        float acc[80];
#pragma unroll
        for (int i = 0; i < 80; i++) acc[i] = 0.f;
        ROLE(role)
        const int tid = tid_opaque(), r = (tid & 31) >> 2, q = tid & 3;
        const int ch = 128 * GP + 64 * wg + 32 * side + 8 * w + r;
        const uint32_t ca = sb + CTAB_OFF + (32 * wg + 8 * w + r) * 24;
        float2 lam = make_float2(0.f, 0.f), p8 = lam, p16 = lam, pL = lam, p2L = lam;
        fence_regs(acc);
        {
          const uint32_t alo0 = (l == 0 ? desc_lo(sb, 16) : desc_lo(sb + G2_WOFF, 16)) + wg * 512;
          const uint32_t blo0 = l == 0 ? desc_lo(sb + G1_XOFF, 16) : desc_lo(sb + X1_OFF, 128);
          const uint32_t bhi = l == 0 ? desc_hi(1024, 1) : desc_hi(1024, 0), xstep = l == 0 ? 2 : 16;
          const uint32_t astep = l == 0 ? G1_STAGE >> 4 : 1024, bstep = l == 0 ? G1_STAGE >> 4 : 1280, aend = alo0 + (S1 + l) * astep;
          uint32_t alo = alo0, blo = blo0;
          const uint32_t special = 8u | (l ? (1u << MK1) | (wg << (8 - STG_D)) : (1u << MK0) | (1u << PAUSE_K) | (wg << (9 - STG0)));
          uint32_t fb = bars + 8 * (B_G1FULL + 10 * l), nb = fb + 8;
          mbar_wait(fb);
          if (tid == 0) TS(1 + 8 * l);
#pragma unroll 1
          for (int k = 0; k < 10; k++) {
            uint32_t ok;
            wgmma_fence();
#pragma unroll
            for (int kk = 0; kk < 4; kk++) {
              wgmma_n160<0>(acc, alo + kk * 2, desc_hi(1024, 1), blo + kk * xstep, bhi);
              if (kk == 0) { ok = mbar_test(nb); asm volatile("add.u32 %0, %0, %1;" : "+r"(nb) : "r"(k < 8 ? 8 : 0)); }
              if (kk == STG_KK && k == 9 && tid == 0) mbar_arrive(bars + 8 * (B_STG + l));
            }
            wgmma_commit();
            alo += astep; blo += bstep;
            if (blo == desc_lo(sb + G_OFF, 128)) blo = desc_lo(sb, 128);
            if (alo == aend) { alo = alo0; blo = blo0; }
            wgmma_wait<1>();
            if (k > 0 && (tid & 127) == 0) mbar_arrive(fb + 8 * (B_G1DONE - B_G1FULL - 1));
            if (!ok) mbar_wait(fb + 8);
            if ((special >> k) & 1) {
            if (k == (l ? MK1 : MK0)) {
              mbar_wait(bars + 8 * (B_STAB + l));
              const float2 sB = lds64f(ca + 16);
              uint32_t a0 = q < 2 ? __float_as_uint(sB.x) : 0u, a1 = q < 2 ? __float_as_uint(sB.y) : 0u, a2 = 0u, a3 = 0u;
              asm volatile("" : "+r"(a0), "+r"(a1), "+r"(a2), "+r"(a3)::"memory");
              wgmma_fence();
              wgmma_rs_n160(acc, a0, a1, a2, a3, l ? desc_lo(sb + MX1_OFF, 0) : desc_lo(sb + MX0_OFF, 0));
              wgmma_commit();
            }
            if (wg == 1 && k == (l ? 8 - STG_D : 9 - STG0)) mbar_wait(bars + 8 * (B_STG + l));
            if (k == 3) {
              mbar_wait(bars + 8 * B_CTAB);
              lam = lds64f(ca);
              if (l == 0 && q < 2) rec_st(&g_E[(q * NT1 + T1) * DM + ch], 0.f, 0.f, lds32(sb + EP_OFF + 20) - 1);
              if (p.swap) lam.y = -lam.y;
              const float2 p2 = cmul(lam, lam), p4 = cmul(p2, p2);
              p8 = cmul(p4, p4); p16 = cmul(p8, p8);
              pL = cmul(p16, p16);
              if (!last) pL = cmul(pL, p8);
              p2L = cmul(pL, pL);
            }
            if (k == PAUSE_K && l == 0 && has2) mbar_wait(bars + 8 * B_PREP);
            }
            fb += 8;
          }
        }
        const unsigned tag = lds32(sb + EP_OFF + 20);
        wgmma_wait<0>();
        fence_regs(acc);
        if ((tid & 127) == 0) { mbar_arrive(bars + 8 * (B_G1DONE + 10 * l + 9)); TS(wg ? 17 + l : 2 + 8 * l); }
        float2 ec[3];
#pragma unroll
        for (int jj = 0; jj < 4; jj++)
#pragma unroll
          for (int y = 0; y < 3; y++) {
            if (y == 2 && (jj & 1)) continue;
            const int j = y == 2 ? 16 + jj : 8 * y + 2 * jj;
            const float4 st = lds128f(sb + STAB_OFF + q * 160 + j * 8);
            const float rs[4] = {st.x, st.y, st.z, st.w};
#pragma unroll
            for (int x = 0; x < 4; x++) {
              const int i = 4 * j + 4 * (x >> 1) + (x & 1);
              acc[i] *= rs[x]; acc[i + 2] *= rs[x];
              ec[y] = (jj == 0 && x == 0) ? make_float2(acc[i], acc[i + 2]) : cfma(lam, ec[y], make_float2(acc[i], acc[i + 2]));
            }
          }
        float2 e = cfma(p16, ec[0], ec[1]);
        if (!last) e = cfma(p8, e, ec[2]);
        {
          float2 v = make_float2(__shfl_up_sync(0xffffffffu, e.x, 1, 4), __shfl_up_sync(0xffffffffu, e.y, 1, 4));
          if (q >= 1) e = cfma(pL, v, e);
          v = make_float2(__shfl_up_sync(0xffffffffu, e.x, 2, 4), __shfl_up_sync(0xffffffffu, e.y, 2, 4));
          if (q >= 2) e = cfma(p2L, v, e);
        }
        if (!last && q == 3) rec_st(&g_E[(l * NT1 + T1) * DM + ch], e.x, e.y, tag);
        if (tid == 0) TS(3 + 8 * l);
        float2 ex = make_float2(__shfl_up_sync(0xffffffffu, e.x, 1, 4), __shfl_up_sync(0xffffffffu, e.y, 1, 4));
        if (q == 0) ex = make_float2(0.f, 0.f);
        const float2 coef = lds64f(ca + 8), lamc = make_float2(lam.x, p.swap ? lam.y : -lam.y);
        float m00 = coef.x, m01 = -coef.y, m10 = -coef.y, m11 = -coef.x;
        if (p.swap) { m00 = -coef.y; m01 = coef.x; m10 = -coef.x; m11 = -coef.y; }
        float2 pLq, p160q, p640;
        {
          const float2 p80 = last ? cmul(p2L, p16) : p2L, p160 = cmul(p80, p80), p320 = cmul(p160, p160), one = make_float2(1.f, 0.f);
          p640 = cmul(p320, p320);
          pLq = cmul((q & 1) ? pL : one, (q & 2) ? p2L : one);
          p160q = cmul((q & 1) ? p160 : one, (q & 2) ? p320 : one);
        }
        float2 c, ev[3];
        unsigned tg[3];
        const uint4* ep = &g_E[(l * NT1 + T1 - 1 - q) * DM + ch];
#pragma unroll
        for (int j = 0; j < 20; j++) {
          if (j == CPOLL) {
#pragma unroll
            for (int i = 0; i < 3; i++) {
              ev[i] = make_float2(0.f, 0.f); tg[i] = tag;
              if (T1 - 1 - q - 4 * i >= 0) tg[i] = rec_ld(ep - 4 * i * DM, ev[i].x, ev[i].y);
            }
          }
#pragma unroll
          for (int x = 0; x < 2; x++) {
            const float b0 = acc[4 * j + x], b1 = acc[4 * j + 2 + x];
            acc[4 * j + x] = fmaf(b0, m00, b1 * m01);
            acc[4 * j + 2 + x] = fmaf(b0, m10, b1 * m11);
          }
          if (j == CPOLL - 1 || j == 19) asm volatile("" : "+f"(acc[4 * j]), "+f"(acc[4 * j + 1]), "+f"(acc[4 * j + 2]), "+f"(acc[4 * j + 3])::"memory");
        }
        {
          uint32_t it = 0;
          while (__any_sync(0xffffffffu, tg[0] != tag || tg[1] != tag || tg[2] != tag)) {
#pragma unroll
            for (int i = 0; i < 3; i++)
              if (tg[i] != tag) tg[i] = rec_ld(ep - 4 * i * DM, ev[i].x, ev[i].y);
            trap_if(++it > SPIN_LIMIT);
          }
          c = cfma(p640, cfma(p640, ev[2], ev[1]), ev[0]);
          c = cmul(c, p160q);
          c.x += __shfl_xor_sync(0xffffffffu, c.x, 1); c.y += __shfl_xor_sync(0xffffffffu, c.y, 1);
          c.x += __shfl_xor_sync(0xffffffffu, c.x, 2); c.y += __shfl_xor_sync(0xffffffffu, c.y, 2);
        }
        if (tid == 0) TS(4 + 8 * l);
        if (wg == 1 && l >= HOLD0) mbar_wait(bars + 8 * (B_REL + l));
        const uint32_t c0 = (uint32_t)clock();
        c = cfma(pLq, c, ex);
        float2 hh = make_float2(fmaf(c.x, m00, c.y * m01), fmaf(c.x, m10, c.y * m11));
        uint8_t* hb = g_h + (size_t)l * (32 * 20 * 8192) + (10 * wg + 2 * GP) * 8192 + (4 * side + w) * 1024 + (tid_opaque() & 31) * 4;
#pragma unroll
        for (int j4 = 0; j4 < 5; j4++) {
          if (PACE && j4 > 0 && wg == 1 && l == 1) { while (__any_sync(0xffffffffu, (uint32_t)clock() - c0 < PACE * j4)) {} }
          const int ng = 20 * T1 + 4 * j4;
          uint8_t* hp = hb + (size_t)(ng >> 3) * 163840 + (ng & 7) * 128;
#pragma unroll
          for (int jj = 0; jj < 4; jj++) {
            const int j = 4 * j4 + jj;
            const float2 h0 = cfma(lamc, hh, make_float2(acc[4 * j + 0], acc[4 * j + 2]));
            hh = cfma(lamc, h0, make_float2(acc[4 * j + 1], acc[4 * j + 3]));
            if (j4 < 4 || !last) {
              *(uint32_t*)(hp + jj * 128) = pack_bf16(h0.x, hh.x);
              *(uint32_t*)(hp + jj * 128 + 8192) = pack_bf16(h0.y, hh.y);
            }
          }
        }
        mbar_arrive(bars + 8 * (B_HST + 2 * l + wg));
        if (tid == 0) TS(5 + 8 * l);
        if (tid == 128) TS(l ? 25 : 19);
        if (!REL3 && l == 0 && wid == 4) {
          mbar_wait(bars + 8 * B_HST);
          mbar_wait(bars + 8 * (B_HST + 1));
          if ((tid & 31) < 8) h_release((tid >> 2) & 1, T1, tid & 3);
          __syncwarp();
          if (tid == 128) { mbar_arrive(bars + 8 * B_REL); TS(6); }
        }
      }
      if (l == 0) {
        ROLE(role)
        if (has2) {
          CvCtx cc;
          mbar_wait(bars + 8 * B_CTAB);
          cv_setup(cc);
          mbar_wait(bars + 8 * (B_G1DONE + 9));
#pragma unroll 1
          for (int c = (wg + 2) & 3; c < 5; c += 4) conv_channel(c, cc);
          if ((tid & 127) == 0) TS(wg == 2 ? 32 : (wg == 3 ? 50 : 7 + wg));
        }
      }
      if (wg >= 2) break;
    }
    if (wg == 3) {
    ROLE(role)
    const int pw = wid & 3, gpc = 2 * min(m2 >> 3, 3) + (dg >> 1);
    mbar_wait(bars + 8 * B_EP);
    const unsigned tag = lds32(sb + EP_OFF + 20);
    if (pw == 0) {
      if (elect_one()) {
#pragma unroll 1
        for (int l = 0; l < 2; l++) {
          uint32_t dst = sb;
          if (l == 1) {
            dst = sb + G2_WOFF;
#pragma unroll 1
            for (int k = 0; k < 10; k++) {
              mbar_wait(k > 4 ? bars + 8 * (B_G1DONE + 5 + k) : (has2 ? bars + 8 * (B_G2DONE + 14 + min(k, 3)) : bars + 8 * (B_G1DONE + 9)));
              mbar_expect_tx(bars + 8 * (B_G1FULL + 10 + k), 16384);
              tma5(dst, &p.mB, 64 * k, 0, 0, 4 * side, 2 * GP, bars + 8 * (B_G1FULL + 10 + k));
              dst += 16384; if (k == 4) dst = sb + G2_WOFF;
            }
          }
          if (has2) {
            const uint32_t fb2 = bars + 8 * (B_G2FULL + 20 * l), wb2 = bars + 8 * (B_G2DONE + 20 * l - S2);
            dst = sb + G2_WOFF + (WTAIL ? 4 * l * G2_WB : 0);
            int kc = 0;
#pragma unroll 1
            for (int k = 0; k < 20; k++) {
              mbar_wait(k >= S2 ? wb2 + 8 * k : bars + 8 * (l ? B_G1DONE + (WTAIL ? (k < 3 ? 15 + k : 13 + k) : 19) : (k == 5 ? B_XFREE : (k == 6 ? B_SFREE : B_REL))));
              mbar_expect_tx(fb2 + 8 * k, G2_WB);
              tma5(dst, &p.mCre + (k & 1), kc, 0, 0, 0, 10 * dg, fb2 + 8 * k);
              kc += (k & 1) << 7; if (k == 9) kc = 64;
              dst += G2_WB; if (dst == sb + G2_WOFF + S2 * G2_WB) dst = sb + G2_WOFF;
            }
          }
        }
      }
    } else if (pw == 1) {
#pragma unroll 1
      for (int l = 0; l < 2; l++) {
        if (l == 1) {
          mbar_wait(bars + 8 * (has2 ? B_G2DONE + 19 : B_G1DONE + 9));
          if (has2) mbar_wait(bars + 8 * B_UST);
          cnt_poll(&g_ucnt[gpc * 32], 128 * tag);
          fence_async_global();
          if (elect_one()) {
            TS(20);
            const int bytes = last ? 16384 : 20480;
            const uint8_t* src = g_u + T1 * 204800;
            uint32_t dst = sb + X1_OFF;
#pragma unroll 1
            for (int k = 0; k < 10; k++) {
              if (k > 4) mbar_wait(bars + 8 * (B_G1DONE + 5 + k));
              mbar_expect_tx(bars + 8 * (B_G1FULL + 10 + k), bytes);
              bulk_g2s(dst, src, bytes, bars + 8 * (B_G1FULL + 10 + k));
              src += 20480; dst += 20480; if (dst == sb + G_OFF) dst = sb; if (k == 4) dst = sb + X1_OFF;
            }
          }
          __syncwarp();
        }
        if (has2) {
          mbar_wait(bars + 8 * (B_HST + 2 * l));
          mbar_wait(bars + 8 * (B_G1DONE + 10 * l + 9));
          cnt_poll(&g_hcnt[(l * 16 + gpc) * 32], 40 * tag);
          fence_async_global();
          if (elect_one()) {
            TS(21 + 2 * l);
            const uint32_t fb2 = bars + 8 * (B_G2FULL + 20 * l), wb2 = bars + 8 * (B_G2DONE + 20 * l - S2);
            const uint8_t* src = g_h + (l * 32 + m2) * 163840;
            uint32_t dst = sb;
#pragma unroll 1
            for (int k = 0; k < 20; k++) {
              if (k >= (l ? XB0 : 5)) mbar_wait(k >= S2 ? wb2 + 8 * k : (l ? fb2 + 8 * (k - XB0) : bars + 8 * B_SFREE));
              if (k == 10) { mbar_wait(bars + 8 * (B_H1 + l)); fence_async_global(); }
              mbar_expect_tx(fb2 + 8 * k, G2_XB);
              bulk_g2s(dst, src, G2_XB, fb2 + 8 * k);
              src += 8192; dst += G2_XB; if (dst == sb + S2 * G2_XB) dst = sb;
            }
          }
          __syncwarp();
        }
      }
    } else if (pw == 2) {
#pragma unroll 1
      for (int l = 0; l < 2; l++) {
        if (l == 1) {
          float xa[2], xb[2];
          mbar_wait(bars + 8 * (B_G1FULL + 11));
          stat_table(T1, tag, 1, 4, g_stats, g_stats, xa, xb);
          mbar_arrive(bars + 8 * (B_STAB + 1));
        }
        if (REL3 && l == 0) {
          mbar_wait(bars + 8 * B_HST);
          mbar_wait(bars + 8 * (B_HST + 1));
          if (lane < 8) h_release(lane >> 2, T1, lane & 3);
          __syncwarp();
          if (lane == 0) { mbar_arrive(bars + 8 * B_REL); TS(6); }
        }
#pragma unroll 1
        for (int w = 0; w < 2 * l; w++) {
          mbar_wait(bars + 8 * (B_HST + 2 + w));
          if (lane < 4) h_release(2 + w, T1, lane);
          __syncwarp();
          if (lane == 0) { if (w == 0) mbar_arrive(bars + 8 * (B_REL + 1)); TS(w ? 16 : 14); }
        }
        if (l == 0 && has2 && elect_one()) {
#pragma unroll 1
          for (int i = 0; i < 5; i++) {
            const int c = i < 3 ? i : 7 - i;
            mbar_wait(bars + 8 * (B_CVDONE + c));
            bulk_s2g(g_G + (cch0 + 32 * c) * 4096, cv_stage(c), 4096);
          }
          asm volatile("cp.async.bulk.commit_group;" ::: "memory");
          asm volatile("cp.async.bulk.wait_group.read 0;" ::: "memory");
          mbar_arrive(bars + 8 * B_SFREE);
          asm volatile("cp.async.bulk.wait_group 0;" ::: "memory");
          TS(48);
          fence_async_global();
          asm volatile("fence.acq_rel.gpu;" ::: "memory");
#pragma unroll
          for (int i = 0; i < 4; i++) red_rlx(&g_gcnt[(dg * 4 + i) * 32]);
          TS(49);
          mbar_arrive(bars + 8 * (B_GO + 1));
        }
        __syncwarp();
      }
    } else if (has2) {
      mbar_wait(bars + 8 * B_REL);
      if (!CPF && elect_one()) {
        l2_prefetch(p.cre + (160 * dg + 5 * m2) * DM, 6400); l2_prefetch(p.cim + (160 * dg + 5 * m2) * DM, 6400);
      }
      mbar_wait(bars + 8 * (B_HST + 1));
      flag_poll(&g_hcnt[(8 + gpc) * 32], 40 * tag);
      if (lane == 0) { mbar_arrive(bars + 8 * B_H1); TS(22); }
      mbar_wait(bars + 8 * (B_GO + 1));
      flag_poll(&g_gcnt[(dg * 4 + (m2 >> 3)) * 32], 32 * tag);
      fence_async_global();
      if (elect_one()) {
        TS(29);
        mbar_expect_tx(bars + 8 * B_GFULL, 20480);
        tma5(sb + G_OFF, &p.mG, 64 * m2, 0, 0, 0, 10 * dg, bars + 8 * B_GFULL);
      }
      mbar_wait(bars + 8 * (B_HST + 3));
      cnt_poll(&g_hcnt[(24 + gpc) * 32], 40 * tag);
      if (lane == 0) { mbar_arrive(bars + 8 * (B_H1 + 1)); TS(24); }
    }
    } else if (wg == 2 && (role >> 16)) {
      float acc[80];
      float off[2] = {mean0[0], mean0[1]};
      const unsigned tag = lds32(sb + EP_OFF + 20);
      dskip_init<true>(acc, mean0, rstd0);
      mbar_arrive(bars + 8 * B_XFREE);
#pragma unroll 1
      for (int step = 1; step < 4; step++) {
        const int l = step >> 1;
        if (step != 2) {
          uint32_t alo = desc_lo(sb, 1024), blo = desc_lo(sb + G2_WOFF, 16) + (WTAIL ? l * (G2_WB >> 2) : 0);
          uint32_t fb = bars + 8 * (B_G2FULL + 20 * l);
          fence_regs(acc);
          mbar_wait(bars + 8 * (B_CVDONE + 2));
          mbar_wait(bars + 8 * (B_CVDONE + 3));
          mbar_wait(fb);
          if (tid == 256) TS(33 + 6 * l);
#pragma unroll 1
          for (int k = 0; k < 20; k++) {
            if (l == TSL && (k & 3) == 3 && tid == 256) TS(56 + (k >> 2));
            uint32_t ok; const uint32_t nb = k < 19 ? fb + 8 : fb;
            wgmma_fence();
#pragma unroll
            for (int kk = 0; kk < 4; kk++) {
              wgmma_n160<1>(acc, alo + kk * 128, desc_hi(128, 0), blo + kk * 2, desc_hi(1024, 1));
              if (kk == 0) ok = mbar_test(nb);
            }
            wgmma_commit();
            alo += G2_XB >> 4; blo += G2_WB >> 4;
            if (alo == desc_lo(sb + S2 * G2_XB, 1024)) alo = desc_lo(sb, 1024);
            if (blo == desc_lo(sb + G_OFF, 16)) blo = desc_lo(sb + G2_WOFF, 16);
            wgmma_wait<1>();
            if (k > 0 && tid == 256) mbar_arrive(fb + 8 * (B_G2DONE - B_G2FULL - 1));
            if (!ok) mbar_wait(nb);
            fb += 8;
          }
          wgmma_wait<0>();
          fence_regs(acc);
          if (tid == 256) TS(34 + 6 * l);
          if (tid == 256) mbar_arrive(bars + 8 * (B_G2DONE + 20 * l + 19));
        }
        ROLE(role)
        const int tq = tid_opaque() & 31, n0 = 64 * m2 + 16 * w + (tq >> 2);
#pragma unroll 1
        for (int rep = 0;; rep++) {
          stats_publish<false>(step, n0, dg, tag, acc);
          if (step != 2 || rep == 1) break;
          for (int n = tid & 127; n < 160; n += 128) {
            const int d = 16 * (n >> 4) + 4 * ((n >> 1) & 3) + 2 * ((n >> 3) & 1) + (n & 1);
            const uint32_t dw = lds32(sb + DTAB_OFF + 2 * (d & ~1)), dd = __byte_perm(dw, dw, (d & 1) ? 0x3232 : 0x1010);
            sts128(sb + DX_OFF + 16 * n, make_uint4(dd, dd, dd, dd));
          }
          mbar_wait(bars + 8 * (B_G1FULL + 11));
          float xa[2], xb[2];
          stat_table(T1, tag, 1, w, g_stats, g_stats, xa, xb);
          mbar_arrive(bars + 8 * (B_STAB + 1));
          if (tid == 256) TS(27);
          mbar_wait(bars + 8 * (B_HST + 2));
          if (!REP2) break;
        }
        uint32_t gf[10][4];
        mbar_wait(bars + 8 * B_GFULL);
        uint32_t ga = sb + G_OFF + (8 * (tq >> 4) + (tq & 7)) * 128 + (((2 * w + ((tq >> 3) & 1)) ^ ((2 * m2) & 6) ^ (tq & 7)) << 4), gstep = 2048;
        if (step == 2) { ga = sb + DX_OFF + (8 * (tq >> 4) + (tq & 7)) * 16; gstep = 256; }
#pragma unroll
        for (int J = 0; J < 2; J++) ldsm4t(gf[J], ga + J * gstep);
        if (tid == 256) TS(35 + 6 * l);
        uint8_t* dst[2][2];
#pragma unroll
        for (int h = 0; h < 2; h++) {
          if (l == 0) {
            const int ng = 8 * m2 + 2 * w + h, T = ng / 20;
            uint8_t* ub = g_u + (T * 204800 + (ng - 20 * T) * 1024 + (tq & 2) * 64 + (tq & 28) * 4 + (tq & 1) * 8 + (5 * dg >> 1) * 20480);
            dst[h][1] = ub + ((dg & 1) ? 20480 - 512 : 0);
            dst[h][0] = ub + (dg & 1) * 512;
          } else {
            dst[h][0] = dst[h][1] = (uint8_t*)(p.out + (n_to_t(n0 + 8 * h) * DM + 160 * dg + 4 * (tq & 3)));
          }
        }
        float mean[2], rstd[2];
        stats_get(step, n0, tag, mean, rstd);
        if (tid == 256) TS(36 + 6 * l);
        off[0] += mean[0]; off[1] += mean[1];
        const float ov[2] = {step == 3 ? off[0] : 0.f, step == 3 ? off[1] : 0.f};
#pragma unroll
        for (int J = 0; J < 10; J++) {
          if (J + 2 < 10) ldsm4t(gf[J + 2 < 10 ? J + 2 : 0], ga + (J + 2) * gstep);
#pragma unroll
          for (int x = 0; x < 8; x++) {
            const int h = (x >> 1) & 1;
            const uint32_t gwd = gf[J][x >> 1];
            const float t = fmaf(rstd[h], (x & 1) ? bf_hi(gwd) : bf_lo(gwd), 1.f);
            acc[8 * J + x] = fmaf(acc[8 * J + x], t, fmaf(-mean[h], t, ov[h]));
          }
#pragma unroll
          for (int h = 0; h < 2; h++) {
            if (step == 1)
              *(uint2*)(dst[h][(J >> 1) & 1] + (J >> 2) * 20480 + (J & 3) * 256) =
                  make_uint2(pack_bf16(acc[8 * J + 2 * h], acc[8 * J + 2 * h + 1]), pack_bf16(acc[8 * J + 4 + 2 * h], acc[8 * J + 5 + 2 * h]));
            if (step == 3)
              *(float4*)(dst[h][0] + 64 * J) = make_float4(acc[8 * J + 2 * h], acc[8 * J + 2 * h + 1], acc[8 * J + 4 + 2 * h], acc[8 * J + 5 + 2 * h]);
          }
          __syncwarp();
        }
        if (step == 1) {
          bar_sync(3, 128);
          if (tid == 288) { TS(37); mbar_arrive(bars + 8 * B_UST); }
          if (tid < 264) red_rel(&g_ucnt[(tid & 7) * 32]);
          __syncwarp();
          if (tid == 256) TS(38);
        } else if (step == 3) {
          if (tid == 256) {
            TS(43);
            if (m2 == 31 && dg == 3) asm volatile("st.relaxed.gpu.global.u32 [%0], %1;" ::"l"(g_epoch), "r"(tag + 1) : "memory");
          }
        }
      }
    }
  }
}

typedef CUresult (*EncFn)(CUtensorMap*, CUtensorMapDataType, cuuint32_t, void*, const cuuint64_t*, const cuuint64_t*,
                          const cuuint32_t*, const cuuint32_t*, CUtensorMapInterleave, CUtensorMapSwizzle,
                          CUtensorMapL2promotion, CUtensorMapFloatOOBfill);

void encode(EncFn fn, CUtensorMap* m, const void* ptr, int rank, const cuuint64_t* dims, const cuuint64_t* strides, const cuuint32_t* box,
            CUtensorMapSwizzle swz = CU_TENSOR_MAP_SWIZZLE_128B, int prom = 2) {
  cuuint32_t es[5] = {1, 1, 1, 1, 1};
  fn(m, CU_TENSOR_MAP_DATA_TYPE_BFLOAT16, rank, (void*)ptr, dims, strides, box, es, CU_TENSOR_MAP_INTERLEAVE_NONE,
     swz, (CUtensorMapL2promotion)prom, CU_TENSOR_MAP_FLOAT_OOB_FILL_NONE);
}

}

extern "C" void kernel_launch(void* const* d_in, const int* in_sizes, int n_in, void* d_out, int out_size) {
  (void)in_sizes; (void)n_in; (void)out_size;
  Params p;
  typedef const __nv_bfloat16* BP;
  p.x = (BP)d_in[0]; p.lre = (BP)d_in[1]; p.lim = (BP)d_in[2]; p.bre = (BP)d_in[3]; p.bim = (BP)d_in[4];
  p.cre = (BP)d_in[5]; p.cim = (BP)d_in[6]; p.logdt = (BP)d_in[7]; p.dskip = (BP)d_in[8];
  p.k = (BP)d_in[10]; p.v = (BP)d_in[11]; p.shiftk = (BP)d_in[12]; p.ssmk = (BP)d_in[13]; p.ssmD = (BP)d_in[14];
  p.out = (float*)d_out;
  for (int sm = 0; sm < 132; sm++) {
    const int tpc = sm >> 1, side = sm & 1;
    int gpc, gi;
    if (tpc < 32) { gpc = tpc & 7; gi = tpc >> 3; }
    else if (tpc < 60) { gpc = 1 + (tpc - 32) % 7; gi = 4 + (tpc - 32) / 7; }
    else if (tpc < 62) { gpc = tpc - 54; gi = 8; }
    else { gpc = 0; gi = tpc - 58; }
    const int pos = 8 * gpc + gi + (gpc == 7 ? 1 : 0);
    int T1, GP;
    if (pos < 52) { const int hh = pos / 26, x = pos - 26 * hh; T1 = x >> 1; GP = 2 * hh + (x & 1); }
    else { T1 = pos - 52; GP = 4; }
    const int m2 = 8 * (gpc >> 1) + gi, dg = 2 * (gpc & 1) + side;
    p.role[sm] = pos == 65 ? -1 : (T1 | (GP << 4) | (side << 7) | (m2 << 8) | (dg << 14) | ((gi < 8) << 16));
  }
  void* fnp = nullptr;
  cudaDriverEntryPointQueryResult qr;
  cudaGetDriverEntryPoint("cuTensorMapEncodeTiled", &fnp, cudaEnableDefault, &qr);
  EncFn fn = (EncFn)fnp;
  void* gG = nullptr;
  cudaGetSymbolAddress(&gG, g_G);
  void* gKV = nullptr;
  cudaGetSymbolAddress(&gKV, g_kv);
  {
    cuuint64_t dims[5] = {32, 32, 10, 32, 4}, st[4] = {20480, 2048, 64, 655360}; cuuint32_t box[5] = {32, 35, 2, 1, 1};
    encode(fn, &p.mU, gKV, 5, dims, st, box, CU_TENSOR_MAP_SWIZZLE_NONE, 1);
  }
  const cuuint64_t RB = DM * 2;
  {
    p.swap = p.bim < p.bre;
    const char* lo = (const char*)(p.swap ? p.bim : p.bre); const char* hi = (const char*)(p.swap ? p.bre : p.bim);
    cuuint64_t dims[5] = {640, 8, 2, 8, 10}, st[4] = {RB, (cuuint64_t)(hi - lo), 8 * RB, 64 * RB}; cuuint32_t box[5] = {64, 8, 2, 4, 2};
    encode(fn, &p.mB, lo, 5, dims, st, box);
  }
  {
    cuuint64_t dims[5] = {640, 2, 4, 2, 40}, st[4] = {RB, 4 * RB, 2 * RB, 16 * RB}; cuuint32_t box[5] = {64, 2, 4, 2, 10};
    encode(fn, &p.mCre, p.cre, 5, dims, st, box); encode(fn, &p.mCim, p.cim, 5, dims, st, box);
    cuuint64_t dimg[5] = {2048, 2, 4, 2, 40}, stg[4] = {4096, 4 * 4096, 2 * 4096, 16 * 4096};
    encode(fn, &p.mG, gG, 5, dimg, stg, box);
  }
  {
    cuuint64_t dims[4] = {640, 2, 4, 900}, st[3] = {RB, 40 * RB, 2 * RB}; cuuint32_t box[4] = {64, 2, 4, 20};
    encode(fn, &p.mX, p.x, 4, dims, st, box);
    cuuint64_t diml[4] = {640, 2, 4, 16}, stl[3] = {RB, 32 * RB, 2 * RB};
    encode(fn, &p.mXl, p.x + (size_t)1920 * DM, 4, diml, stl, box);
    cuuint32_t boxt[4] = {160, 2, 4, 4};
    encode(fn, &p.mXt, p.x, 4, dims, st, boxt, CU_TENSOR_MAP_SWIZZLE_NONE);
    encode(fn, &p.mXtl, p.x + (size_t)1920 * DM, 4, diml, stl, boxt, CU_TENSOR_MAP_SWIZZLE_NONE);
    cuuint64_t dk[3] = {640, 2000, 4}, sk[2] = {RB, 16 * RB}; cuuint32_t bk[3] = {32, 19, 4}, bv[3] = {32, 17, 4};
    encode(fn, &p.mK, p.k, 3, dk, sk, bk, CU_TENSOR_MAP_SWIZZLE_NONE);
    encode(fn, &p.mV, p.v, 3, dk, sk, bv, CU_TENSOR_MAP_SWIZZLE_NONE);
  }
  cudaFuncSetAttribute(fused_kernel, cudaFuncAttributeMaxDynamicSharedMemorySize, SMEM_BYTES);
  cudaLaunchConfig_t cfg = {};
  cfg.gridDim = dim3(132); cfg.blockDim = dim3(512); cfg.dynamicSmemBytes = SMEM_BYTES; cfg.stream = cudaStreamPerThread;
  cudaLaunchKernelEx(&cfg, fused_kernel, p);
}
```

```cpp
#include <cuda_runtime.h>
#include <cuda.h>
#include <cuda_bf16.h>
#include <stdint.h>

namespace {

constexpr int SEQ = 2048, DM = 640;
constexpr int NT1 = 13;
#define EXP 0
#define WPF1 3
#define WPF2 7
#define CPOLL 10
#define KV0 1
#define TAPLATE 1
#define STG_D 3
#define STG_KK 1
#define HOLD1 0
#define SPEC0 300
#define NGATE (B_HST + 2)
#define WREL 0
#define UREL 1
#define TSL 1
#define STG0 2
#define WTAIL 1
#define PFD 1
#define TAPW 0
#define TPF 4
#define CPF 0
#define MK0 7
#define MK1 4
#define PACE 180
#define TAPN 2
#define PAUSE_K 5
constexpr uint32_t SPIN_LIMIT = 1u << 22;

__device__ __align__(1024) uint8_t g_h[32 * 20 * 8192];
__device__ __align__(1024) uint8_t g_u[NT1 * 10 * 20480];
__device__ __align__(1024) uint8_t g_kv[DM * 4096];
__device__ __align__(1024) uint8_t g_G[DM * 4096];
__device__ __align__(128) uint4 g_E[2 * NT1 * DM];
__device__ __align__(128) uint4 g_stats[4 * 4 * SEQ];
__device__ __align__(128) uint4 g_sB[DM * 2];
__device__ __align__(128) unsigned g_hcnt[8 * 32];
__device__ __align__(128) unsigned g_ucnt[8 * 32];
__device__ __align__(128) unsigned g_kvcnt[16 * 32];
__device__ __align__(128) unsigned g_gcnt[16 * 32];
__device__ __align__(128) unsigned g_epoch[32] = {1};
#define TS(i) do {} while (0)

struct Params {
  CUtensorMap mX, mB, mXl, mK, mV, mXt, mXtl, mCre, mCim, mG, mU;
  const __nv_bfloat16 *x, *lre, *lim, *bre, *bim, *cre, *cim, *logdt, *dskip, *k, *v, *shiftk, *ssmk, *ssmD;
  float* out;
  int swap;
  int role[132];
};

constexpr uint32_t sb = 1024;
constexpr uint32_t G1_STAGE = 36864, G1_XOFF = 16384;
constexpr int S1 = 4;
constexpr uint32_t XT_OFF = 159744, KS_OFF = 180224, KV_PIECE = 9216;
constexpr uint32_t G2_XB = 8192, G2_WB = 20480, G2_WOFF = 57344, G_OFF = 200704;
constexpr uint32_t X1_OFF = 139264;
constexpr int S2 = 7;
constexpr uint32_t CV_OFF = KS_OFF, CV_K = 128, CV_PL = 2240, CV_U = CV_K + 4096, CV_B = KV_PIECE;
constexpr uint32_t MISC = 226304;
constexpr uint32_t BAR_OFF = MISC;
constexpr int B_G1FULL = 0, B_G1DONE = 20, B_G2FULL = 40,
              B_G2DONE = 85, B_GFULL = 125, B_EP = 126, B_CVFULL = 129  , B_STG = 134  , B_REL = 136  , B_SFREE = 138, B_UST = 142,
              B_GO = 139  , B_PUB = 147,
              B_CVDONE = 148  , B_STAB = 153  , B_XFREE = 155, B_HST = 156  ,
              B_CTAB = 160, B_PREP = 161, B_XT = 162, B_KV = 163  , B_PREP2 = 84, B_PD = 168  ,
              B_XV = 173  , B_RETRY = 193  ;
constexpr uint32_t bars = sb + BAR_OFF;
constexpr uint32_t STAB_OFF = MISC + 1648;
constexpr uint32_t CTAB_OFF = STAB_OFF + 640;
constexpr uint32_t DTAB_OFF = CTAB_OFF + 1536;
constexpr uint32_t EP_OFF = DTAB_OFF + 320;
constexpr uint32_t SO_OFF = EP_OFF + 32;
constexpr uint32_t TAP_OFF = 147456;
constexpr uint32_t MX0_OFF = TAP_OFF + 1280, MX1_OFF = G_OFF + 20480;
constexpr uint32_t DX_OFF = MX1_OFF + 2560;
constexpr uint32_t SMEM_BYTES = 232448;
static_assert(SO_OFF + 1536 <= SMEM_BYTES, "smem");

__device__ __forceinline__ void trap_if(bool c) { asm volatile("{\n.reg .pred p;\nsetp.ne.u32 p, %0, 0;\n@p trap;\n}\n" ::"r"((uint32_t)c)); }
__device__ __forceinline__ uint32_t smem_u32(const void* p) { return (uint32_t)__cvta_generic_to_shared(p); }
__device__ __forceinline__ void mbar_init(uint32_t bar, int cnt) { asm volatile("mbarrier.init.shared::cta.b64 [%0], %1;" ::"r"(bar), "r"(cnt) : "memory"); }
__device__ __forceinline__ void mbar_expect_tx(uint32_t bar, int bytes) { asm volatile("mbarrier.arrive.expect_tx.shared::cta.b64 _, [%0], %1;" ::"r"(bar), "r"(bytes) : "memory"); }
__device__ __forceinline__ void mbar_arrive(uint32_t bar) { asm volatile("mbarrier.arrive.shared::cta.b64 _, [%0];" ::"r"(bar) : "memory"); }
__device__ __forceinline__ bool elect_one() {
  uint32_t e; asm volatile("{\n.reg .pred P;\nelect.sync _|P, 0xffffffff;\nselp.u32 %0, 1, 0, P;\n}\n" : "=r"(e)); return e != 0;
}
__device__ __forceinline__ void mbar_wait(uint32_t bar) {
  asm volatile(
      "{\n.reg .pred p;\n.reg .u32 c;\nmov.u32 c, 0;\n"
      "W_%=:\nmbarrier.try_wait.parity.shared::cta.b64 p, [%0], 0;\n@p bra D_%=;\n"
      "add.u32 c, c, 1;\nsetp.lt.u32 p, c, %1;\n@p bra W_%=;\ntrap;\nD_%=:\n}\n" ::"r"(bar), "n"(SPIN_LIMIT) : "memory");
}
__device__ __forceinline__ uint32_t mbar_test(uint32_t bar) {
  uint32_t ok;
  asm volatile("{\n.reg .pred p;\nmbarrier.test_wait.parity.shared::cta.b64 p, [%1], 0;\nselp.u32 %0, 1, 0, p;\n}\n" : "=r"(ok) : "r"(bar) : "memory");
  return ok;
}
__device__ __forceinline__ void tma3(uint32_t dst, const CUtensorMap* m, int c0, int c1, int c2, uint32_t bar) {
  asm volatile("cp.async.bulk.tensor.3d.shared::cluster.global.mbarrier::complete_tx::bytes [%0], [%1, {%3,%4,%5}], [%2];"
               ::"r"(dst), "l"(m), "r"(bar), "r"(c0), "r"(c1), "r"(c2) : "memory");
}
__device__ __forceinline__ void tma4(uint32_t dst, const CUtensorMap* m, int c0, int c1, int c2, int c3, uint32_t bar) {
  asm volatile("cp.async.bulk.tensor.4d.shared::cluster.global.mbarrier::complete_tx::bytes [%0], [%1, {%3,%4,%5,%6}], [%2];"
               ::"r"(dst), "l"(m), "r"(bar), "r"(c0), "r"(c1), "r"(c2), "r"(c3) : "memory");
}
__device__ __forceinline__ void tma5(uint32_t dst, const CUtensorMap* m, int c0, int c1, int c2, int c3, int c4, uint32_t bar) {
  asm volatile("cp.async.bulk.tensor.5d.shared::cluster.global.mbarrier::complete_tx::bytes [%0], [%1, {%3,%4,%5,%6,%7}], [%2];"
               ::"r"(dst), "l"(m), "r"(bar), "r"(c0), "r"(c1), "r"(c2), "r"(c3), "r"(c4) : "memory");
}
__device__ __forceinline__ void bulk_g2s(uint32_t dst, const void* src, int bytes, uint32_t bar) {
  asm volatile("cp.async.bulk.shared::cluster.global.mbarrier::complete_tx::bytes [%0], [%1], %2, [%3];"
               ::"r"(dst), "l"(src), "r"(bytes), "r"(bar) : "memory");
}
__device__ __forceinline__ void bulk_s2g(void* dst, uint32_t src, int bytes) {
  asm volatile("cp.async.bulk.global.shared::cta.bulk_group [%0], [%1], %2;" ::"l"(dst), "r"(src), "r"(bytes) : "memory");
}
__device__ __forceinline__ void l2_prefetch(const void* src, int bytes) {
  asm volatile("cp.async.bulk.prefetch.L2.global [%0], %1;" ::"l"(src), "r"(bytes) : "memory");
}
__device__ __forceinline__ void wgmma_fence() { asm volatile("wgmma.fence.sync.aligned;" ::: "memory"); }
__device__ __forceinline__ void wgmma_commit() { asm volatile("wgmma.commit_group.sync.aligned;" ::: "memory"); }
template <int N> __device__ __forceinline__ void wgmma_wait() { asm volatile("wgmma.wait_group.sync.aligned %0;" ::"n"(N) : "memory"); }
__host__ __device__ constexpr uint32_t desc_lo(uint32_t addr, uint32_t lbo) { return ((addr & 0x3FFFF) >> 4) | ((lbo >> 4) << 16); }
__host__ __device__ constexpr uint32_t desc_hi(uint32_t sbo, uint32_t swz) { return (sbo >> 4) | (swz << 30); }
__device__ __forceinline__ void bar_sync(int id, int n) { asm volatile("bar.sync %0, %1;" ::"r"(id), "r"(n) : "memory"); }
__device__ __forceinline__ uint32_t lds32(uint32_t a) { uint32_t v; asm volatile("ld.shared.u32 %0, [%1];" : "=r"(v) : "r"(a) : "memory"); return v; }
__device__ __forceinline__ float2 lds64f(uint32_t a) { float2 v; asm volatile("ld.shared.v2.f32 {%0,%1}, [%2];" : "=f"(v.x), "=f"(v.y) : "r"(a) : "memory"); return v; }
__device__ __forceinline__ float4 lds128f(uint32_t a) { float4 v; asm volatile("ld.shared.v4.f32 {%0,%1,%2,%3}, [%4];" : "=f"(v.x), "=f"(v.y), "=f"(v.z), "=f"(v.w) : "r"(a) : "memory"); return v; }
__device__ __forceinline__ void ldsm4t(uint32_t (&r)[4], uint32_t a) {
  asm volatile("ldmatrix.sync.aligned.m8n8.x4.trans.shared.b16 {%0,%1,%2,%3}, [%4];" : "=r"(r[0]), "=r"(r[1]), "=r"(r[2]), "=r"(r[3]) : "r"(a) : "memory");
}
__device__ __forceinline__ uint4 ldv128(const void* a) { uint4 v; asm volatile("ld.global.nc.v4.u32 {%0,%1,%2,%3}, [%4];" : "=r"(v.x), "=r"(v.y), "=r"(v.z), "=r"(v.w) : "l"(a) : "memory"); return v; }
__device__ __forceinline__ uint2 ldv64(const void* a) { uint2 v; asm volatile("ld.global.nc.v2.u32 {%0,%1}, [%2];" : "=r"(v.x), "=r"(v.y) : "l"(a) : "memory"); return v; }
__device__ __forceinline__ uint32_t ldv16(const void* a) { uint32_t v; asm volatile("ld.global.nc.u16 %0, [%1];" : "=r"(v) : "l"(a) : "memory"); return v; }
__device__ __forceinline__ void sts128(uint32_t a, uint4 v) { asm volatile("st.shared.v4.u32 [%0], {%1,%2,%3,%4};" ::"r"(a), "r"(v.x), "r"(v.y), "r"(v.z), "r"(v.w) : "memory"); }
__device__ __forceinline__ void sts32(uint32_t a, uint32_t v) { asm volatile("st.shared.u32 [%0], %1;" ::"r"(a), "r"(v) : "memory"); }
__device__ __forceinline__ void sts64f(uint32_t a, float x, float y) { asm volatile("st.shared.v2.f32 [%0], {%1,%2};" ::"r"(a), "f"(x), "f"(y) : "memory"); }
__device__ __forceinline__ void red_rlx(unsigned* p) { asm volatile("red.relaxed.gpu.global.add.u32 [%0], 1;" ::"l"(p) : "memory"); }
__device__ __forceinline__ void red_rel(unsigned* p) { asm volatile("red.release.gpu.global.add.u32 [%0], 1;" ::"l"(p) : "memory"); }
__device__ __forceinline__ void fence_async_global() { asm volatile("fence.proxy.async.global;" ::: "memory"); }
__device__ __forceinline__ void fence_async_smem() { asm volatile("fence.proxy.async.shared::cta;" ::: "memory"); }
__device__ __forceinline__ void rec_st(uint4* p, float a, float b, unsigned tag) {
  asm volatile("{\n.reg .b128 t;\n.reg .b64 lo, hi;\nmov.b64 lo, {%1,%2};\nmov.b64 hi, {%3,%3};\nmov.b128 t, {lo,hi};\n"
               "st.relaxed.gpu.global.b128 [%0], t;\n}\n" ::"l"(p), "r"(__float_as_uint(a)), "r"(__float_as_uint(b)), "r"(tag) : "memory");
}
__device__ __forceinline__ unsigned rec_ld(const uint4* p, float& a, float& b) {
  unsigned x, y, t;
  asm volatile("{\n.reg .b128 t;\n.reg .b64 lo, hi;\n.reg .b32 u;\nld.relaxed.gpu.global.b128 t, [%3];\nmov.b128 {lo,hi}, t;\n"
               "mov.b64 {%0,%1}, lo;\nmov.b64 {%2,u}, hi;\n}\n" : "=r"(x), "=r"(y), "=r"(t) : "l"(p) : "memory");
  a = __uint_as_float(x); b = __uint_as_float(y);
  return t;
}
__device__ __forceinline__ unsigned ld_rlx(const unsigned* p) { unsigned v; asm volatile("ld.relaxed.gpu.global.u32 %0, [%1];" : "=r"(v) : "l"(p) : "memory"); return v; }
__device__ __forceinline__ void flag_poll(const unsigned* p, unsigned target) {
  uint32_t it = 0;
  while (!__all_sync(0xffffffffu, (int)(ld_rlx(p) - target) >= 0)) { trap_if(++it > SPIN_LIMIT); }
  asm volatile("fence.acquire.gpu;" ::: "memory");
}
__device__ __forceinline__ void cnt_poll(const unsigned* p, unsigned target) {
  unsigned a = ld_rlx(p); __nanosleep(100);
  unsigned b = ld_rlx(p); __nanosleep(100);
  unsigned c = ld_rlx(p);
  uint32_t it = 0;
  while (true) {
    if (__all_sync(0xffffffffu, (int)(a - target) >= 0)) break;
    a = ld_rlx(p);
    if (__all_sync(0xffffffffu, (int)(b - target) >= 0)) break;
    b = ld_rlx(p);
    if (__all_sync(0xffffffffu, (int)(c - target) >= 0)) break;
    c = ld_rlx(p);
    trap_if(++it > SPIN_LIMIT);
  }
  asm volatile("fence.acquire.gpu;" ::: "memory");
}
__device__ __forceinline__ void validate_block(uint32_t bar, uint32_t full, uint32_t dst, const uint8_t* src, uint32_t woff, uint32_t rb, uint32_t& ph) {
  uint32_t it = 0, par = 0;
  while (true) {
    uint32_t ok, spins = 0;
    do {
      asm volatile("{\n.reg .pred p;\nmbarrier.try_wait.parity.shared::cta.b64 p, [%1], %2;\nselp.u32 %0, 1, 0, p;\n}\n" : "=r"(ok) : "r"(bar), "r"(par) : "memory");
      trap_if(++spins > SPIN_LIMIT);
    } while (!__all_sync(0xffffffffu, ok));
    uint32_t bad = 0;
#pragma unroll
    for (int i = 0; i < 8; i++) bad |= lds32(dst + woff + 128 * i);
    if (!__any_sync(0xffffffffu, bad & 1)) break;
    if (elect_one()) { mbar_expect_tx(rb, 8192); bulk_g2s(dst, src, 8192, rb); }
    bar = rb; par = ph; ph ^= 1;
    trap_if(++it > 100000);
  }
  if ((threadIdx.x & 31) == 0) mbar_arrive(full);
}
__device__ __forceinline__ uint32_t tag_word(uint32_t v, uint32_t m, uint32_t par) {
  uint32_t r; asm("lop3.b32 %0, %1, %2, %3, 0xb8;" : "=r"(r) : "r"(v), "r"(m), "r"(par)); return r;
}
__device__ __forceinline__ void h_release(int idx, int T, int i) {
  const int Q = (i & 2) ? (T + 2) / 3 - 1 : T / 3;
  if (Q >= 0 && Q < 4 && ((i & 2) == 0 || T % 3 == 0)) red_rel(&g_hcnt[(idx * 8 + 2 * Q + (i & 1)) * 32]);
}
__device__ __forceinline__ uint32_t pack_bf16(float lo, float hi) {
  uint32_t r; asm("cvt.rn.bf16x2.f32 %0, %1, %2;" : "=r"(r) : "f"(hi), "f"(lo)); return r;
}
__device__ __forceinline__ float bf_lo(uint32_t w) { return __uint_as_float(w << 16); }
__device__ __forceinline__ float bf_hi(uint32_t w) { return __uint_as_float(w & 0xffff0000u); }
__device__ __forceinline__ uint32_t hmul2(uint32_t a, uint32_t b) {
  __nv_bfloat162 r = __hmul2_rn(*(__nv_bfloat162*)&a, *(__nv_bfloat162*)&b); return *(uint32_t*)&r;
}
__device__ __forceinline__ uint32_t hadd2(uint32_t a, uint32_t b) {
  __nv_bfloat162 r = __hadd2_rn(*(__nv_bfloat162*)&a, *(__nv_bfloat162*)&b); return *(uint32_t*)&r;
}
__device__ __forceinline__ float2 cmul(float2 a, float2 b) { return make_float2(a.x * b.x - a.y * b.y, a.x * b.y + a.y * b.x); }
__device__ __forceinline__ float2 cfma(float2 a, float2 b, float2 c) {
  return make_float2(fmaf(a.x, b.x, fmaf(-a.y, b.y, c.x)), fmaf(a.x, b.y, fmaf(a.y, b.x, c.y)));
}
template <int N> __device__ __forceinline__ void fence_regs(float (&a)[N]) {
#pragma unroll
  for (int i = 0; i < N; i++) asm volatile("" : "+f"(a[i])::"memory");
}
__device__ __forceinline__ int tid_opaque() { int t; asm volatile("mov.u32 %0, %%tid.x;" : "=r"(t)); return t; }
struct Role { int T1, GP, side, m2, dg, cch0; bool last, has2; };
__device__ __forceinline__ Role unpack_role(int x) {
  Role r; r.T1 = x & 15; r.GP = (x >> 4) & 7; r.side = (x >> 7) & 1; r.m2 = (x >> 8) & 63; r.dg = (x >> 14) & 3;
  r.has2 = (x >> 16) & 1; r.last = r.T1 == NT1 - 1; r.cch0 = 160 * r.dg + r.m2; return r;
}
__device__ __forceinline__ Role fresh_role(int x) { asm volatile("" : "+r"(x)); return unpack_role(__shfl_sync(0xffffffffu, x, 0)); }
#define ROLE(x) const Role R_ = fresh_role(x); const int T1 = R_.T1, GP = R_.GP, side = R_.side, m2 = R_.m2, dg = R_.dg, cch0 = R_.cch0; \
  const bool last = R_.last, has2 = R_.has2; (void)T1; (void)GP; (void)side; (void)m2; (void)dg; (void)cch0; (void)last; (void)has2;
__device__ __forceinline__ int n_to_t(int n) {
  int T = n / 160, nl = n - T * 160;
  int L = (T == NT1 - 1) ? 32 : 40;
  return T * 160 + L * ((nl & 7) >> 1) + 2 * (nl >> 3) + (nl & 1);
}

template<int TA> __device__ __forceinline__ void wgmma_n160(float (&d)[80], uint32_t alo, uint32_t ahi, uint32_t blo, uint32_t bhi){
  asm volatile("{\n.reg .b64 da, db;\nmov.b64 da, {%80,%81};\nmov.b64 db, {%82,%83};\n"
    "wgmma.mma_async.sync.aligned.m64n160k16.f32.bf16.bf16 {%0, %1, %2, %3, %4, %5, %6, %7, %8, %9, %10, %11, %12, %13, %14, %15, %16, %17, %18, %19, %20, %21, %22, %23, %24, %25, %26, %27, %28, %29, %30, %31, %32, %33, %34, %35, %36, %37, %38, %39, %40, %41, %42, %43, %44, %45, %46, %47, %48, %49, %50, %51, %52, %53, %54, %55, %56, %57, %58, %59, %60, %61, %62, %63, %64, %65, %66, %67, %68, %69, %70, %71, %72, %73, %74, %75, %76, %77, %78, %79}, da, db, 1, 1, 1, %84, 0;\n}\n"
    : "+f"(d[0]), "+f"(d[1]), "+f"(d[2]), "+f"(d[3]), "+f"(d[4]), "+f"(d[5]), "+f"(d[6]), "+f"(d[7]), "+f"(d[8]), "+f"(d[9]), "+f"(d[10]), "+f"(d[11]), "+f"(d[12]), "+f"(d[13]), "+f"(d[14]), "+f"(d[15]), "+f"(d[16]), "+f"(d[17]), "+f"(d[18]), "+f"(d[19]), "+f"(d[20]), "+f"(d[21]), "+f"(d[22]), "+f"(d[23]), "+f"(d[24]), "+f"(d[25]), "+f"(d[26]), "+f"(d[27]), "+f"(d[28]), "+f"(d[29]), "+f"(d[30]), "+f"(d[31]), "+f"(d[32]), "+f"(d[33]), "+f"(d[34]), "+f"(d[35]), "+f"(d[36]), "+f"(d[37]), "+f"(d[38]), "+f"(d[39]), "+f"(d[40]), "+f"(d[41]), "+f"(d[42]), "+f"(d[43]), "+f"(d[44]), "+f"(d[45]), "+f"(d[46]), "+f"(d[47]), "+f"(d[48]), "+f"(d[49]), "+f"(d[50]), "+f"(d[51]), "+f"(d[52]), "+f"(d[53]), "+f"(d[54]), "+f"(d[55]), "+f"(d[56]), "+f"(d[57]), "+f"(d[58]), "+f"(d[59]), "+f"(d[60]), "+f"(d[61]), "+f"(d[62]), "+f"(d[63]), "+f"(d[64]), "+f"(d[65]), "+f"(d[66]), "+f"(d[67]), "+f"(d[68]), "+f"(d[69]), "+f"(d[70]), "+f"(d[71]), "+f"(d[72]), "+f"(d[73]), "+f"(d[74]), "+f"(d[75]), "+f"(d[76]), "+f"(d[77]), "+f"(d[78]), "+f"(d[79])
    : "r"(alo), "r"(ahi), "r"(blo), "r"(bhi), "n"(TA));
}
__device__ __forceinline__ void wgmma_rs_n160(float (&d)[80], uint32_t a0, uint32_t a1, uint32_t a2, uint32_t a3, uint32_t blo){
  asm volatile("{\n.reg .b64 db;\nmov.b64 db, {%84,8};\nwgmma.mma_async.sync.aligned.m64n160k16.f32.bf16.bf16 {%0, %1, %2, %3, %4, %5, %6, %7, %8, %9, %10, %11, %12, %13, %14, %15, %16, %17, %18, %19, %20, %21, %22, %23, %24, %25, %26, %27, %28, %29, %30, %31, %32, %33, %34, %35, %36, %37, %38, %39, %40, %41, %42, %43, %44, %45, %46, %47, %48, %49, %50, %51, %52, %53, %54, %55, %56, %57, %58, %59, %60, %61, %62, %63, %64, %65, %66, %67, %68, %69, %70, %71, %72, %73, %74, %75, %76, %77, %78, %79}, {%80,%81,%82,%83}, db, 1, 1, 1, 0;\n}\n"
    : "+f"(d[0]), "+f"(d[1]), "+f"(d[2]), "+f"(d[3]), "+f"(d[4]), "+f"(d[5]), "+f"(d[6]), "+f"(d[7]), "+f"(d[8]), "+f"(d[9]), "+f"(d[10]), "+f"(d[11]), "+f"(d[12]), "+f"(d[13]), "+f"(d[14]), "+f"(d[15]), "+f"(d[16]), "+f"(d[17]), "+f"(d[18]), "+f"(d[19]), "+f"(d[20]), "+f"(d[21]), "+f"(d[22]), "+f"(d[23]), "+f"(d[24]), "+f"(d[25]), "+f"(d[26]), "+f"(d[27]), "+f"(d[28]), "+f"(d[29]), "+f"(d[30]), "+f"(d[31]), "+f"(d[32]), "+f"(d[33]), "+f"(d[34]), "+f"(d[35]), "+f"(d[36]), "+f"(d[37]), "+f"(d[38]), "+f"(d[39]), "+f"(d[40]), "+f"(d[41]), "+f"(d[42]), "+f"(d[43]), "+f"(d[44]), "+f"(d[45]), "+f"(d[46]), "+f"(d[47]), "+f"(d[48]), "+f"(d[49]), "+f"(d[50]), "+f"(d[51]), "+f"(d[52]), "+f"(d[53]), "+f"(d[54]), "+f"(d[55]), "+f"(d[56]), "+f"(d[57]), "+f"(d[58]), "+f"(d[59]), "+f"(d[60]), "+f"(d[61]), "+f"(d[62]), "+f"(d[63]), "+f"(d[64]), "+f"(d[65]), "+f"(d[66]), "+f"(d[67]), "+f"(d[68]), "+f"(d[69]), "+f"(d[70]), "+f"(d[71]), "+f"(d[72]), "+f"(d[73]), "+f"(d[74]), "+f"(d[75]), "+f"(d[76]), "+f"(d[77]), "+f"(d[78]), "+f"(d[79])
    : "r"(a0), "r"(a1), "r"(a2), "r"(a3), "r"(blo));
}
template<int N> __device__ __forceinline__ void wgmma_rs_hi(float (&d)[64], uint32_t a0, uint32_t a1, uint32_t a2, uint32_t a3, uint32_t blo);
template<> __device__ __forceinline__ void wgmma_rs_hi<16>(float (&d)[64], uint32_t a0, uint32_t a1, uint32_t a2, uint32_t a3, uint32_t blo){
  asm volatile("{\n.reg .b64 db;\nmov.b64 db, {%12,8};\nwgmma.mma_async.sync.aligned.m64n16k16.f32.bf16.bf16 {%0, %1, %2, %3, %4, %5, %6, %7}, {%8,%9,%10,%11}, db, 1, 1, 1, 0;\n}\n"
    : "+f"(d[56]), "+f"(d[57]), "+f"(d[58]), "+f"(d[59]), "+f"(d[60]), "+f"(d[61]), "+f"(d[62]), "+f"(d[63])
    : "r"(a0), "r"(a1), "r"(a2), "r"(a3), "r"(blo));
}
template<> __device__ __forceinline__ void wgmma_rs_hi<32>(float (&d)[64], uint32_t a0, uint32_t a1, uint32_t a2, uint32_t a3, uint32_t blo){
  asm volatile("{\n.reg .b64 db;\nmov.b64 db, {%20,8};\nwgmma.mma_async.sync.aligned.m64n32k16.f32.bf16.bf16 {%0, %1, %2, %3, %4, %5, %6, %7, %8, %9, %10, %11, %12, %13, %14, %15}, {%16,%17,%18,%19}, db, 1, 1, 1, 0;\n}\n"
    : "+f"(d[48]), "+f"(d[49]), "+f"(d[50]), "+f"(d[51]), "+f"(d[52]), "+f"(d[53]), "+f"(d[54]), "+f"(d[55]), "+f"(d[56]), "+f"(d[57]), "+f"(d[58]), "+f"(d[59]), "+f"(d[60]), "+f"(d[61]), "+f"(d[62]), "+f"(d[63])
    : "r"(a0), "r"(a1), "r"(a2), "r"(a3), "r"(blo));
}
template<> __device__ __forceinline__ void wgmma_rs_hi<48>(float (&d)[64], uint32_t a0, uint32_t a1, uint32_t a2, uint32_t a3, uint32_t blo){
  asm volatile("{\n.reg .b64 db;\nmov.b64 db, {%28,8};\nwgmma.mma_async.sync.aligned.m64n48k16.f32.bf16.bf16 {%0, %1, %2, %3, %4, %5, %6, %7, %8, %9, %10, %11, %12, %13, %14, %15, %16, %17, %18, %19, %20, %21, %22, %23}, {%24,%25,%26,%27}, db, 1, 1, 1, 0;\n}\n"
    : "+f"(d[40]), "+f"(d[41]), "+f"(d[42]), "+f"(d[43]), "+f"(d[44]), "+f"(d[45]), "+f"(d[46]), "+f"(d[47]), "+f"(d[48]), "+f"(d[49]), "+f"(d[50]), "+f"(d[51]), "+f"(d[52]), "+f"(d[53]), "+f"(d[54]), "+f"(d[55]), "+f"(d[56]), "+f"(d[57]), "+f"(d[58]), "+f"(d[59]), "+f"(d[60]), "+f"(d[61]), "+f"(d[62]), "+f"(d[63])
    : "r"(a0), "r"(a1), "r"(a2), "r"(a3), "r"(blo));
}
template<> __device__ __forceinline__ void wgmma_rs_hi<64>(float (&d)[64], uint32_t a0, uint32_t a1, uint32_t a2, uint32_t a3, uint32_t blo){
  asm volatile("{\n.reg .b64 db;\nmov.b64 db, {%36,8};\nwgmma.mma_async.sync.aligned.m64n64k16.f32.bf16.bf16 {%0, %1, %2, %3, %4, %5, %6, %7, %8, %9, %10, %11, %12, %13, %14, %15, %16, %17, %18, %19, %20, %21, %22, %23, %24, %25, %26, %27, %28, %29, %30, %31}, {%32,%33,%34,%35}, db, 1, 1, 1, 0;\n}\n"
    : "+f"(d[32]), "+f"(d[33]), "+f"(d[34]), "+f"(d[35]), "+f"(d[36]), "+f"(d[37]), "+f"(d[38]), "+f"(d[39]), "+f"(d[40]), "+f"(d[41]), "+f"(d[42]), "+f"(d[43]), "+f"(d[44]), "+f"(d[45]), "+f"(d[46]), "+f"(d[47]), "+f"(d[48]), "+f"(d[49]), "+f"(d[50]), "+f"(d[51]), "+f"(d[52]), "+f"(d[53]), "+f"(d[54]), "+f"(d[55]), "+f"(d[56]), "+f"(d[57]), "+f"(d[58]), "+f"(d[59]), "+f"(d[60]), "+f"(d[61]), "+f"(d[62]), "+f"(d[63])
    : "r"(a0), "r"(a1), "r"(a2), "r"(a3), "r"(blo));
}
template<> __device__ __forceinline__ void wgmma_rs_hi<80>(float (&d)[64], uint32_t a0, uint32_t a1, uint32_t a2, uint32_t a3, uint32_t blo){
  asm volatile("{\n.reg .b64 db;\nmov.b64 db, {%44,8};\nwgmma.mma_async.sync.aligned.m64n80k16.f32.bf16.bf16 {%0, %1, %2, %3, %4, %5, %6, %7, %8, %9, %10, %11, %12, %13, %14, %15, %16, %17, %18, %19, %20, %21, %22, %23, %24, %25, %26, %27, %28, %29, %30, %31, %32, %33, %34, %35, %36, %37, %38, %39}, {%40,%41,%42,%43}, db, 1, 1, 1, 0;\n}\n"
    : "+f"(d[24]), "+f"(d[25]), "+f"(d[26]), "+f"(d[27]), "+f"(d[28]), "+f"(d[29]), "+f"(d[30]), "+f"(d[31]), "+f"(d[32]), "+f"(d[33]), "+f"(d[34]), "+f"(d[35]), "+f"(d[36]), "+f"(d[37]), "+f"(d[38]), "+f"(d[39]), "+f"(d[40]), "+f"(d[41]), "+f"(d[42]), "+f"(d[43]), "+f"(d[44]), "+f"(d[45]), "+f"(d[46]), "+f"(d[47]), "+f"(d[48]), "+f"(d[49]), "+f"(d[50]), "+f"(d[51]), "+f"(d[52]), "+f"(d[53]), "+f"(d[54]), "+f"(d[55]), "+f"(d[56]), "+f"(d[57]), "+f"(d[58]), "+f"(d[59]), "+f"(d[60]), "+f"(d[61]), "+f"(d[62]), "+f"(d[63])
    : "r"(a0), "r"(a1), "r"(a2), "r"(a3), "r"(blo));
}
template<> __device__ __forceinline__ void wgmma_rs_hi<96>(float (&d)[64], uint32_t a0, uint32_t a1, uint32_t a2, uint32_t a3, uint32_t blo){
  asm volatile("{\n.reg .b64 db;\nmov.b64 db, {%52,8};\nwgmma.mma_async.sync.aligned.m64n96k16.f32.bf16.bf16 {%0, %1, %2, %3, %4, %5, %6, %7, %8, %9, %10, %11, %12, %13, %14, %15, %16, %17, %18, %19, %20, %21, %22, %23, %24, %25, %26, %27, %28, %29, %30, %31, %32, %33, %34, %35, %36, %37, %38, %39, %40, %41, %42, %43, %44, %45, %46, %47}, {%48,%49,%50,%51}, db, 1, 1, 1, 0;\n}\n"
    : "+f"(d[16]), "+f"(d[17]), "+f"(d[18]), "+f"(d[19]), "+f"(d[20]), "+f"(d[21]), "+f"(d[22]), "+f"(d[23]), "+f"(d[24]), "+f"(d[25]), "+f"(d[26]), "+f"(d[27]), "+f"(d[28]), "+f"(d[29]), "+f"(d[30]), "+f"(d[31]), "+f"(d[32]), "+f"(d[33]), "+f"(d[34]), "+f"(d[35]), "+f"(d[36]), "+f"(d[37]), "+f"(d[38]), "+f"(d[39]), "+f"(d[40]), "+f"(d[41]), "+f"(d[42]), "+f"(d[43]), "+f"(d[44]), "+f"(d[45]), "+f"(d[46]), "+f"(d[47]), "+f"(d[48]), "+f"(d[49]), "+f"(d[50]), "+f"(d[51]), "+f"(d[52]), "+f"(d[53]), "+f"(d[54]), "+f"(d[55]), "+f"(d[56]), "+f"(d[57]), "+f"(d[58]), "+f"(d[59]), "+f"(d[60]), "+f"(d[61]), "+f"(d[62]), "+f"(d[63])
    : "r"(a0), "r"(a1), "r"(a2), "r"(a3), "r"(blo));
}
template<> __device__ __forceinline__ void wgmma_rs_hi<112>(float (&d)[64], uint32_t a0, uint32_t a1, uint32_t a2, uint32_t a3, uint32_t blo){
  asm volatile("{\n.reg .b64 db;\nmov.b64 db, {%60,8};\nwgmma.mma_async.sync.aligned.m64n112k16.f32.bf16.bf16 {%0, %1, %2, %3, %4, %5, %6, %7, %8, %9, %10, %11, %12, %13, %14, %15, %16, %17, %18, %19, %20, %21, %22, %23, %24, %25, %26, %27, %28, %29, %30, %31, %32, %33, %34, %35, %36, %37, %38, %39, %40, %41, %42, %43, %44, %45, %46, %47, %48, %49, %50, %51, %52, %53, %54, %55}, {%56,%57,%58,%59}, db, 1, 1, 1, 0;\n}\n"
    : "+f"(d[8]), "+f"(d[9]), "+f"(d[10]), "+f"(d[11]), "+f"(d[12]), "+f"(d[13]), "+f"(d[14]), "+f"(d[15]), "+f"(d[16]), "+f"(d[17]), "+f"(d[18]), "+f"(d[19]), "+f"(d[20]), "+f"(d[21]), "+f"(d[22]), "+f"(d[23]), "+f"(d[24]), "+f"(d[25]), "+f"(d[26]), "+f"(d[27]), "+f"(d[28]), "+f"(d[29]), "+f"(d[30]), "+f"(d[31]), "+f"(d[32]), "+f"(d[33]), "+f"(d[34]), "+f"(d[35]), "+f"(d[36]), "+f"(d[37]), "+f"(d[38]), "+f"(d[39]), "+f"(d[40]), "+f"(d[41]), "+f"(d[42]), "+f"(d[43]), "+f"(d[44]), "+f"(d[45]), "+f"(d[46]), "+f"(d[47]), "+f"(d[48]), "+f"(d[49]), "+f"(d[50]), "+f"(d[51]), "+f"(d[52]), "+f"(d[53]), "+f"(d[54]), "+f"(d[55]), "+f"(d[56]), "+f"(d[57]), "+f"(d[58]), "+f"(d[59]), "+f"(d[60]), "+f"(d[61]), "+f"(d[62]), "+f"(d[63])
    : "r"(a0), "r"(a1), "r"(a2), "r"(a3), "r"(blo));
}
template<> __device__ __forceinline__ void wgmma_rs_hi<128>(float (&d)[64], uint32_t a0, uint32_t a1, uint32_t a2, uint32_t a3, uint32_t blo){
  asm volatile("{\n.reg .b64 db;\nmov.b64 db, {%68,8};\nwgmma.mma_async.sync.aligned.m64n128k16.f32.bf16.bf16 {%0, %1, %2, %3, %4, %5, %6, %7, %8, %9, %10, %11, %12, %13, %14, %15, %16, %17, %18, %19, %20, %21, %22, %23, %24, %25, %26, %27, %28, %29, %30, %31, %32, %33, %34, %35, %36, %37, %38, %39, %40, %41, %42, %43, %44, %45, %46, %47, %48, %49, %50, %51, %52, %53, %54, %55, %56, %57, %58, %59, %60, %61, %62, %63}, {%64,%65,%66,%67}, db, 1, 1, 1, 0;\n}\n"
    : "+f"(d[0]), "+f"(d[1]), "+f"(d[2]), "+f"(d[3]), "+f"(d[4]), "+f"(d[5]), "+f"(d[6]), "+f"(d[7]), "+f"(d[8]), "+f"(d[9]), "+f"(d[10]), "+f"(d[11]), "+f"(d[12]), "+f"(d[13]), "+f"(d[14]), "+f"(d[15]), "+f"(d[16]), "+f"(d[17]), "+f"(d[18]), "+f"(d[19]), "+f"(d[20]), "+f"(d[21]), "+f"(d[22]), "+f"(d[23]), "+f"(d[24]), "+f"(d[25]), "+f"(d[26]), "+f"(d[27]), "+f"(d[28]), "+f"(d[29]), "+f"(d[30]), "+f"(d[31]), "+f"(d[32]), "+f"(d[33]), "+f"(d[34]), "+f"(d[35]), "+f"(d[36]), "+f"(d[37]), "+f"(d[38]), "+f"(d[39]), "+f"(d[40]), "+f"(d[41]), "+f"(d[42]), "+f"(d[43]), "+f"(d[44]), "+f"(d[45]), "+f"(d[46]), "+f"(d[47]), "+f"(d[48]), "+f"(d[49]), "+f"(d[50]), "+f"(d[51]), "+f"(d[52]), "+f"(d[53]), "+f"(d[54]), "+f"(d[55]), "+f"(d[56]), "+f"(d[57]), "+f"(d[58]), "+f"(d[59]), "+f"(d[60]), "+f"(d[61]), "+f"(d[62]), "+f"(d[63])
    : "r"(a0), "r"(a1), "r"(a2), "r"(a3), "r"(blo));
}

struct CvCtx {
  uint32_t koff, zero, so[3];
  int srcA, srcB;
  bool wrapA, s3, kodd;
};
struct CvPipe { uint32_t Ap, Ep, keep, send; };
template <int LO> __device__ __forceinline__ void cv_copy(float (&acc)[64]) {
#pragma unroll
  for (int i = LO; i < 64; i++) { float t; asm volatile("mov.b32 %0, %1;" : "=f"(t) : "f"(acc[i]) : "memory"); acc[i] = t; }
}
template <int G> __device__ __forceinline__ void cv_raw(uint32_t (&A)[4][4], uint32_t kaddr) {
#pragma unroll
  for (int i = 0; i < 4; i++) {
    const uint32_t a = kaddr + (4 * G + i) * 128;
    A[i][0] = lds32(a); A[i][1] = lds32(a + 4); A[i][3] = lds32(a + 8);
  }
}
__device__ __forceinline__ void cv_form(uint32_t (&A)[4][4], uint32_t sel) {
#pragma unroll
  for (int i = 0; i < 4; i++) {
    asm volatile("prmt.b32 %0, %0, %1, %2;" : "+r"(A[i][0]) : "r"(A[i][1]), "r"(sel));
    asm volatile("prmt.b32 %0, %1, %2, %3;" : "=r"(A[i][2]) : "r"(A[i][1]), "r"(A[i][3]), "r"(sel));
  }
}
#define CVV 2
template <int G> __device__ __forceinline__ void cv_step(float (&acc)[64], uint32_t (&A)[4][4], CvPipe& s, const CvCtx& c, uint32_t cb, uint32_t stg) {
  constexpr int JA = G - 1, JB = G - 2, NH = CVV == 1 ? 4 : (CVV == 3 ? 2 : 1);
  const uint32_t db0 = desc_lo(cb + CV_U + 192, CV_PL);
  uint32_t B[4][4];
  uint32_t ra[2], rb;
  if constexpr (G < 8) {
    wgmma_fence();
#pragma unroll
    for (int i = 0; i < NH; i++) wgmma_rs_hi<128 - 16 * (G & 7)>(acc, A[i][0], A[i][1], A[i][2], A[i][3], db0 - 4 * i);
    wgmma_commit();
    __syncwarp();
  }
  if constexpr (JA >= 0 && JA < 8) {
    const uint32_t p0 = pack_bf16(acc[8 * JA + 1], acc[8 * JA + 3]), p1 = pack_bf16(acc[8 * JA + 5], acc[8 * JA + 7]);
    ra[0] = __shfl_sync(0xffffffffu, c.wrapA ? s.Ap : p0, c.srcA);
    ra[1] = __shfl_sync(0xffffffffu, c.wrapA ? p0 : p1, c.srcA);
    s.Ap = p1;
  }
  if constexpr (JB >= 0) rb = __shfl_sync(0xffffffffu, s.send, c.srcB);
  if constexpr (G < 7) cv_raw<G + 1>(B, cb + c.koff);
  uint32_t z = 0;
  if constexpr (G < 8 && NH < 4) {
    __syncwarp();
    wgmma_fence();
#pragma unroll
    for (int i = NH; i < 4; i++) wgmma_rs_hi<128 - 16 * (G & 7)>(acc, A[i][0], A[i][1], A[i][2], A[i][3], db0 - 4 * i);
    wgmma_commit();
    asm volatile("mov.u32 %0, %%clock;" : "=r"(z)::"memory");
    z &= c.zero;
  }
  if constexpr (G < 7) cv_form(B, 0x5432u | z);
  if constexpr (JB >= 0) sts32(stg + ((c.so[JB / 3] >> (10 * (JB % 3))) & 0xffc), hadd2(rb | z, s.keep));
  if constexpr (JA >= 0 && JA < 8) {
    const uint32_t sh = 16 | z, mk = 0xffff0000u | z;
    const uint32_t ev = pack_bf16(acc[8 * JA] + __uint_as_float(ra[0] << sh), acc[8 * JA + 2] + __uint_as_float(ra[0] & mk));
    const uint32_t od = pack_bf16(acc[8 * JA + 4] + __uint_as_float(ra[1] << sh), acc[8 * JA + 6] + __uint_as_float(ra[1] & mk));
    s.send = c.kodd ? ev : (c.s3 ? s.Ep : od);
    s.keep = c.kodd ? od : ev;
    s.Ep = od;
  }
  if constexpr (G < 8) { __syncwarp(); wgmma_wait<0>(); cv_copy<8 * (G & 7)>(acc); }
  if constexpr (G < 9) cv_step<G + 1>(acc, B, s, c, cb, stg);
}
__device__ __forceinline__ uint32_t cv_stage(int slot) { return sb + (slot < 4 ? 40960 + slot * 4096 : CV_OFF + CV_K); }
__device__ __forceinline__ void cv_setup(CvCtx& c) {
  const int tid = tid_opaque() & 127, w = tid >> 5, lane = tid & 31, r = lane >> 2, q = lane & 3;
  const int i0 = (r >> 1) & 1, i1 = r >> 2;
  c.koff = CV_K - 32 + 4 * (8 * (r >> 1) + 2 * w + (r & 1) + 2 * q);
  c.srcA = i0 ? lane - 8 : lane + 8 - q + ((q + 3) & 3);
  c.wrapA = i0 && q == 3;
  c.srcB = i1 == 0 ? (lane - q + 16 + ((q + 3) & 3)) : (lane - q - 16 + ((q + 1) & 3));
  c.s3 = (i1 == 1 && q == 3); c.kodd = (i1 == 1 && q < 3);
  c.zero = lds32(sb + EP_OFF + 24);
#pragma unroll
  for (int i = 0; i < 3; i++) c.so[i] = lds32(sb + SO_OFF + 512 * i + 4 * tid);
}
__device__ __forceinline__ void cv_table() {
  const int tid = tid_opaque() & 127, r = (tid & 31) >> 2, q = tid & 3;
  int t = 16 * (2 * (r < 4 ? q : 4 + ((q + 1) & 3)) + ((r >> 1) & 1)) + 4 * (tid >> 5) + 2 * (r & 1);
#pragma unroll 1
  for (int i = 0; i < 3; i++) {
    uint32_t v = 0;
#pragma unroll 1
    for (int x = 0; x < 3; x++, t += 256) {
      const int T = t / 160, tl = t - T * 160;
      const int qq = (T >= NT1 - 1) ? (tl >> 5) : (tl / 40);
      int ck = 20 * T + ((tl - qq * ((T >= NT1 - 1) ? 32 : 40)) >> 1);
      ck ^= (ck >> 2) & 6;
      v |= (uint32_t)((ck * 4 + qq) & 1023) << (10 * x + 2);
    }
    sts32(sb + SO_OFF + 512 * i + 4 * tid, v);
  }
}
__device__ __forceinline__ void conv_channel(int slot, const CvCtx& c) {
  const uint32_t cb = sb + CV_OFF + slot * CV_B;
  float acc[64];
  CvPipe s;
  s.Ap = s.Ep = 0u;
  uint32_t A[4][4];
#pragma unroll
  for (int i = 0; i < 64; i++) acc[i] = 0.f;
  if (slot == 4) mbar_wait(bars + 8 * B_CVDONE);
  mbar_wait(bars + 8 * (B_CVFULL + slot));
  cv_raw<0>(A, cb + c.koff);
  {
    const uint32_t w0 = lds32(cb + CV_K);
    const uint32_t wp = __byte_perm(pack_bf16(bf_lo(w0) + __uint_as_float(lds32(sb + EP_OFF + 4 * slot)), 0.f), w0, 0x7610);
    if (c.koff == CV_K) A[0][0] = wp;
    if (c.koff == CV_K - 4) A[0][1] = wp;
    if (c.koff == CV_K - 8) A[0][3] = wp;
  }
  cv_form(A, 0x5432u);
  cv_copy<0>(acc);
  cv_step<0>(acc, A, s, c, cb, cv_stage(slot));
  fence_async_smem();
  mbar_arrive(bars + 8 * (B_CVDONE + slot));
}

__device__ __forceinline__ void kv_issue(const Params& p, int c, int m2, int dg) {
  const uint32_t fb = bars + 8 * (B_KV + c);
  mbar_expect_tx(fb, KV_PIECE);
  tma3(sb + KS_OFF + c * KV_PIECE, &p.mK, 160 * dg + 32 * c, 64 * m2 - 3, 0, fb);
  tma3(sb + KS_OFF + c * KV_PIECE + 4864, &p.mV, 160 * dg + 32 * c, 64 * m2 - 1, 0, fb);
}
__device__ __forceinline__ void kv_tile(int m, int c, int y, uint32_t (&o)[4][4]) {
  const int lane = tid_opaque() & 31, tg = lane & 3, pr = 8 * (y ^ (tg >> 1)) + (lane >> 2);
  const uint32_t pb = sb + KS_OFF + c * KV_PIECE + 4 * pr;
  const uint32_t ka = pb + tg * 1216, va = pb + 4864 + tg * 1088 + 64;
  const uint32_t kh = (m == 0 && tg > 0) ? ka - 192 : ka;
  uint32_t kk[19], u[16];
  const float4 t = lds128f(sb + TAP_OFF + 256 * c + 16 * pr);
#pragma unroll
  for (int i = 0; i < 19; i++) { kk[i] = lds32((i < 3 ? kh : ka) + i * 64); if (i >= 3) u[i - 3] = lds32(va + (i - 3) * 64); }
  const uint32_t dst = sb + KS_OFF + c * KV_PIECE + pr * 64 + tg * 16;
  if (y) {
    __syncwarp();
#pragma unroll
    for (int x = 0; x < 4; x++) sts128((dst ^ 512) + x * 1024, make_uint4(o[x][0], o[x][1], o[x][2], o[x][3]));
  }
  const uint32_t w0 = __byte_perm(__float_as_uint(t.x), __float_as_uint(t.z), 0x5410), w1 = __byte_perm(__float_as_uint(t.x), __float_as_uint(t.z), 0x7632);
  const uint32_t w2 = __byte_perm(__float_as_uint(t.y), __float_as_uint(t.w), 0x5410), w3 = __byte_perm(__float_as_uint(t.y), __float_as_uint(t.w), 0x7632);
#pragma unroll
  for (int i = 0; i < 16; i++) {
    uint32_t a = hmul2(kk[i], w3);
    a = hadd2(a, hmul2(kk[i + 1], w2)); a = hadd2(a, hmul2(kk[i + 2], w1)); a = hadd2(a, hmul2(kk[i + 3], w0));
    u[i] = hmul2(a, u[i]);
  }
#pragma unroll
  for (int x = 0; x < 4; x++) {
#pragma unroll
    for (int qq = 0; qq < 4; qq++) o[x][qq] = __byte_perm(u[15 - 4 * qq - (x & 2)], u[14 - 4 * qq - (x & 2)], (x & 1) ? 0x7632 : 0x5410);
    if (y) sts128(dst + x * 1024, make_uint4(o[x][0], o[x][1], o[x][2], o[x][3]));
  }
}
__device__ __forceinline__ void ln_finish(float s1, float s2, float& mean, float& rstd) {
  mean = s1 * (1.f / 640.f);
  const float v = fmaxf(fmaf(-mean, mean, s2 * (1.f / 640.f)), 0.f) + 1e-5f;
  asm("rsqrt.approx.ftz.f32 %0, %1;" : "=f"(rstd) : "f"(v));
}
__device__ __forceinline__ void stat_table(int T1, unsigned want, int l, int g, const uint4* x0, const uint4* x1, float (&xa)[2], float (&xb)[2]) {
  const int n = 32 * g + (tid_opaque() & 31);
  const uint4* rp = &g_stats[8 * l * SEQ + min(160 * T1 + n, SEQ - 1)];
  float a[4], b[4];
  uint32_t it = 0;
  while (true) {
    bool ok = true;
#pragma unroll
    for (int i = 0; i < 4; i++) ok &= (rec_ld(rp + SEQ * i, a[i], b[i]) == want);
    ok &= rec_ld(x0, xa[0], xb[0]) == want;
    ok &= rec_ld(x1, xa[1], xb[1]) == want;
    if (__all_sync(0xffffffffu, ok)) break;
    trap_if(++it > SPIN_LIMIT);
  }
  float m, rs;
  ln_finish((a[0] + a[1]) + (a[2] + a[3]), (b[0] + b[1]) + (b[2] + b[3]), m, rs);
  sts32(sb + STAB_OFF + ((n >> 1) & 3) * 160 + (n >> 3) * 8 + (n & 1) * 4, __float_as_uint(rs));
  const uint32_t hi = pack_bf16(-m, -m);
  const float lo = -m - bf_lo(hi);
  sts128(sb + (l ? MX1_OFF : MX0_OFF) + n * 16, make_uint4(hi, pack_bf16(lo, lo), 0u, 0u));
  fence_async_smem();
}
__device__ __forceinline__ void stats_reduce(float (&a)[2], float (&b)[2], float (&mean)[2], float (&rstd)[2]) {
#pragma unroll
  for (int o = 1; o < 4; o <<= 1)
#pragma unroll
    for (int h = 0; h < 2; h++) { a[h] += __shfl_xor_sync(0xffffffffu, a[h], o); b[h] += __shfl_xor_sync(0xffffffffu, b[h], o); }
#pragma unroll
  for (int h = 0; h < 2; h++) ln_finish(a[h], b[h], mean[h], rstd[h]);
}

template <bool FIRST>
__device__ __forceinline__ void stats_publish(int which, int n0, int dg, unsigned tag, const float (&acc)[80]) {
  const int q = tid_opaque() & 3, h = q & 1;
  float s1[2] = {0.f, 0.f}, s2[2] = {0.f, 0.f}, t1[2] = {0.f, 0.f}, t2[2] = {0.f, 0.f};
#pragma unroll
  for (int j = 0; j < 20; j++)
#pragma unroll
    for (int y = 0; y < 2; y++) {
      const float a = acc[4 * j + 2 * y], b = acc[4 * j + 2 * y + 1];
      s1[y] += a; t1[y] += b; s2[y] = fmaf(a, a, s2[y]); t2[y] = fmaf(b, b, t2[y]);
    }
#pragma unroll
  for (int y = 0; y < 2; y++) { s1[y] += t1[y]; s2[y] += t2[y]; }
  float a = (h ? s1[1] : s1[0]) + __shfl_xor_sync(0xffffffffu, h ? s1[0] : s1[1], 1);
  float b = (h ? s2[1] : s2[0]) + __shfl_xor_sync(0xffffffffu, h ? s2[0] : s2[1], 1);
  a += __shfl_xor_sync(0xffffffffu, a, 2);
  b += __shfl_xor_sync(0xffffffffu, b, 2);
  if (FIRST) {
    rec_st(&g_stats[((q >> 1) * 4 + dg) * SEQ + n0 + 8 * h], a, b, q < 2 ? tag : tag - 1);
    rec_st(&g_stats[((q >> 1) * 4 + 8 + dg) * SEQ + n0 + 8 * h], a, b, tag - 1);
  } else if (q < 2) rec_st(&g_stats[(which * 4 + dg) * SEQ + n0 + 8 * h], a, b, tag);
}
__device__ __forceinline__ void stats_get(int which, int n0, unsigned tag, float (&mean)[2], float (&rstd)[2]) {
  const uint4* p0 = &g_stats[(which * 4 + (tid_opaque() & 3)) * SEQ + n0];
  float a[2], b[2];
  uint32_t it = 0;
  while (true) {
    const unsigned t0 = rec_ld(p0, a[0], b[0]), t1 = rec_ld(p0 + 8, a[1], b[1]);
    if (__all_sync(0xffffffffu, t0 == tag && t1 == tag)) break;
    trap_if(++it > SPIN_LIMIT);
  }
  stats_reduce(a, b, mean, rstd);
}
__device__ __forceinline__ void x0_load(float (&acc)[80]) {
  const int t = tid_opaque() & 127;
  const uint32_t xa = sb + XT_OFF + (16 * (t >> 5) + ((t & 31) >> 2)) * 320 + 8 * (t & 3);
  mbar_wait(bars + 8 * B_XT);
#pragma unroll
  for (int h = 0; h < 2; h++)
#pragma unroll
    for (int J = 0; J < 10; J++) {
      const float2 v = lds64f(xa + h * 2560 + 32 * J);
      const uint32_t x = __float_as_uint(v.x), y = __float_as_uint(v.y);
      acc[8 * J + 2 * h] = bf_lo(x); acc[8 * J + 2 * h + 1] = bf_hi(x);
      acc[8 * J + 4 + 2 * h] = bf_lo(y); acc[8 * J + 4 + 2 * h + 1] = bf_hi(y);
    }
}

template <bool FROM_X0>
__device__ __forceinline__ void dskip_init(float (&acc)[80], const float (&mean)[2], const float (&rstd)[2]) {
  const int t = tid_opaque() & 127;
  const uint32_t xa = sb + XT_OFF + (16 * (t >> 5) + ((t & 31) >> 2)) * 320 + 8 * (t & 3), da = sb + DTAB_OFF + 8 * (t & 3);
  float2 dw[10], xv[10][2];
#pragma unroll
  for (int J = 0; J < 2; J++) { dw[J] = lds64f(da + 32 * J); if (FROM_X0) { xv[J][0] = lds64f(xa + 32 * J); xv[J][1] = lds64f(xa + 2560 + 32 * J); } }
#pragma unroll
  for (int J = 0; J < 10; J++) {
    if (J + 2 < 10) { dw[J + 2] = lds64f(da + 32 * (J + 2)); if (FROM_X0) { xv[J + 2][0] = lds64f(xa + 32 * (J + 2)); xv[J + 2][1] = lds64f(xa + 2560 + 32 * (J + 2)); } }
#pragma unroll
    for (int x = 0; x < 8; x++) {
      const int h = (x >> 1) & 1;
      const uint32_t dwd = __float_as_uint(x < 4 ? dw[J].x : dw[J].y);
      const float tt = fmaf(rstd[h], (x & 1) ? bf_hi(dwd) : bf_lo(dwd), 1.f);
      float a = acc[8 * J + x];
      if (FROM_X0) { const uint32_t xw = __float_as_uint(x < 4 ? xv[J][h].x : xv[J][h].y); a = (x & 1) ? bf_hi(xw) : bf_lo(xw); }
      acc[8 * J + x] = FROM_X0 ? (a - mean[h]) * tt : fmaf(a, tt, -mean[h] * tt);
    }
  }
}

__global__ void __launch_bounds__(512, 1) fused_kernel(const __grid_constant__ Params p) {
  extern __shared__ __align__(1024) uint8_t smem_raw[];
  const int tid = threadIdx.x, lane = tid & 31;
  const int wid = __shfl_sync(0xffffffffu, tid >> 5, 0), wg = wid >> 2;
  unsigned smid; asm volatile("mov.u32 %0, %%smid;" : "=r"(smid));
  const int role = p.role[min(smid, 131u)];
  if (wid == 12) {
    const bool el = elect_one();
    if (el) {
      asm volatile("prefetch.tensormap [%0];" ::"l"(&p.mB) : "memory");
      asm volatile("prefetch.tensormap [%0];" ::"l"((role & 15) == NT1 - 1 ? &p.mXl : &p.mX) : "memory");
#pragma unroll
      for (int k = 0; k < S1; k++) mbar_init(bars + 8 * (B_G1FULL + k), 1);
#pragma unroll
      for (int k = 0; k < 6; k++) mbar_init(bars + 8 * (B_XT + k), 1);
      asm volatile("fence.mbarrier_init.release.cluster;" ::: "memory");
    }
    if (role >= 0) {
      __syncwarp();
      asm volatile("bar.arrive 5, 288;" ::: "memory");
      const Role R = unpack_role(role);
      if (elect_one()) {
        TS(45);
#pragma unroll 1
        for (int k = 0; k < S1; k++) {
          const uint32_t fb = bars + 8 * (B_G1FULL + k);
          mbar_expect_tx(fb, G1_STAGE);
          tma4(sb + k * G1_STAGE + G1_XOFF, R.last ? &p.mXl : &p.mX, 64 * k, 0, 0, R.last ? 0 : 80 * R.T1, fb);
          tma5(sb + k * G1_STAGE, &p.mB, 64 * k, 0, 0, 4 * R.side, 2 * R.GP, fb);
          if (PFD) asm volatile("prefetch.tensormap [%0];" ::"l"(&p.mK + k) : "memory");
        }
        if (R.has2) {
          mbar_expect_tx(bars + 8 * B_XT, 20480);
#pragma unroll 1
          for (int h = 0; h < 2; h++) {
            const int ng = 8 * R.m2 + 4 * h, T = ng / 20;
            tma4(sb + XT_OFF + h * 10240, T == NT1 - 1 ? &p.mXtl : &p.mXt, 160 * R.dg, 0, 0, T == NT1 - 1 ? ng - 240 : ng + 60 * T, bars + 8 * B_XT);
          }
#pragma unroll 1
          for (int c = 0; c < KV0; c++) kv_issue(p, c, R.m2, R.dg);
        }
        TS(44);
      }
      __syncwarp();
      bar_sync(6, 64);
    }
  }
  trap_if(smid >= 132 || smem_u32(smem_raw) != sb);
  if (role < 0) {
    if (wid == 0) {
      const unsigned tag = ld_rlx(g_epoch);
      uint32_t it = 0;
      while (!__all_sync(0xffffffffu, (int)(ld_rlx(&g_hcnt[(lane & 7) * 32]) - 40 * tag) >= 0)) { __nanosleep(500); trap_if(++it > SPIN_LIMIT); }
    }
    return;
  }
  float mean0[2] = {0.f, 0.f}, rstd0[2] = {0.f, 0.f};
  if (wg == 2 || wid == 14) {
    ROLE(role)
    const int c = wid == 14 ? 4 : wid - 8;
    const unsigned tag = ld_rlx(g_epoch);
    if (has2) {
      uint2 bv[2][5];
#pragma unroll
      for (int x = 0; x < 2; x++)
#pragma unroll
        for (int i = 0; i < 5; i++) bv[x][i] = ldv64((const uint2*)((x ? p.bim : p.bre) + (cch0 + 32 * c) * DM) + lane + 32 * i);
      float sv[2];
#pragma unroll
      for (int x = 0; x < 2; x++) {
        float a = 0.f;
#pragma unroll
        for (int i = 0; i < 5; i++) a += (bf_lo(bv[x][i].x) + bf_hi(bv[x][i].x)) + (bf_lo(bv[x][i].y) + bf_hi(bv[x][i].y));
        sv[x] = a;
      }
#pragma unroll
      for (int o = 16; o > 0; o >>= 1) { sv[0] += __shfl_xor_sync(0xffffffffu, sv[0], o); sv[1] += __shfl_xor_sync(0xffffffffu, sv[1], o); }
      if (lane < 2) rec_st(&g_sB[(cch0 + 32 * c) * 2 + lane], sv[0], sv[1], tag);
      if (tid == 256) TS(47);
      __syncwarp();
      bar_sync(8, 192);
      if (wg == 2) {
        float xs[80];
        x0_load(xs);
        stats_publish<true>(0, 64 * m2 + 16 * c + (lane >> 2), dg, tag, xs);
        if (tid == 256) TS(31);
      }
      mbar_wait(bars + 8 * B_EP);
      mbar_wait(bars + 8 * (B_KV + c));
      mbar_wait(bars + 8 * (B_G1DONE + PAUSE_K - 1));
      if (tid == 448) TS(52);
      uint32_t o[4][4] = {};
#pragma unroll 1
      for (int y = 0; y < 2; y++) kv_tile(m2, c, y, o);
      fence_async_smem();
      __syncwarp();
      if (lane == 0) { mbar_arrive(bars + 8 * B_PREP); mbar_arrive(bars + 8 * (B_PD + c)); }
      if (tid == 448) TS(51);
    } else bar_sync(8, 192);
    {
      const uint4* x0 = wg == 2 ? &g_stats[(lane & 3) * SEQ + (has2 ? 64 * m2 : 0) + 16 * c + (lane >> 2)] : &g_sB[(128 * GP + 32 * side + lane) * 2];
      float xa[2], xb[2];
      stat_table(T1, tag, 0, c, x0, x0 + (wg == 2 ? 8 : 128), xa, xb);
      if (wg == 2) stats_reduce(xa, xb, mean0, rstd0);
      else {
#pragma unroll
        for (int i = 0; i < 2; i++) {
          const float ha = bf_lo(pack_bf16(xa[i], 0.f)), hb = bf_lo(pack_bf16(xb[i], 0.f));
          const float pa = __uint_as_float(pack_bf16(ha, xa[i] - ha)), pb = __uint_as_float(pack_bf16(hb, xb[i] - hb));
          sts64f(sb + CTAB_OFF + (32 * i + lane) * 24 + 16, p.swap ? pb : pa, p.swap ? pa : pb);
        }
      }
      mbar_arrive(bars + 8 * B_STAB);
      if (tid == 448) TS(26);
    }
  } else if (wid == 15) {
    ROLE(role)
    const int ch = 128 * GP + 32 * side + lane;
    uint32_t r0 = ldv16(p.lre + ch), r1 = ldv16(p.lim + ch), r2 = ldv16(p.logdt + ch);
    const uint32_t r3 = ldv16(p.lre + ch + 64), r4 = ldv16(p.lim + ch + 64), r5 = ldv16(p.logdt + ch + 64);
#pragma unroll 1
    for (int i = 0; i < 2; i++) {
      const float lr = bf_lo(r0), li = bf_lo(r1);
      const float dt = __bfloat162float(__float2bfloat16_rn(expf(bf_lo(r2))));
      const float mag = expf(dt * lr);
      float sn, cs; sincospif(dt * li * 0.31830988618379067f, &sn, &cs);
      const float ar = mag * cs, ai = mag * sn;
      const float inv = 2.f / (lr * lr + li * li);
      const uint32_t ad = sb + CTAB_OFF + (32 * i + lane) * 24;
      sts64f(ad, ar, ai);
      sts64f(ad + 8, ((ar - 1.f) * lr + ai * li) * inv, (ai * lr - (ar - 1.f) * li) * inv);
      r0 = r3; r1 = r4; r2 = r5;
    }
    if (lane == 0) TS(46);
    __syncwarp();
    bar_sync(7, 64);
    mbar_arrive(bars + 8 * B_CTAB);
  } else if (wid == 13) {
    ROLE(role)
    uint4 tv[3];
    const uint32_t e0 = ld_rlx(g_epoch);
    const uint32_t e1 = ldv16(p.ssmD + min(cch0 + 32 * lane, 639));
    const uint4 dv = ldv128((const uint4*)(p.dskip + 160 * dg) + min(lane, 19));
#pragma unroll
    for (int i = 0; i < 3; i++) tv[i] = ldv128((const uint4*)(p.shiftk + 640 * dg) + min(lane + 32 * i, 79));
    sts128(sb + DTAB_OFF + 16 * min(lane, 19), dv);
#pragma unroll
    for (int i = 0; i < 3; i++) sts128(sb + TAP_OFF + 16 * min(lane + 32 * i, 79), tv[i]);
    if (lane < 7) sts32(sb + EP_OFF + 4 * lane, lane < 5 ? e1 << 16 : (lane == 5 ? e0 : 0u));
    __syncwarp();
    bar_sync(9, 64);
    mbar_arrive(bars + 8 * B_CTAB);
    if (lane == 0) { mbar_arrive(bars + 8 * B_EP); TS(53); }
    if (has2) {
#pragma unroll 1
      for (int i = 0; i < 5; i++) {
        const int c = i == 2 ? 3 : (i == 3 ? 2 : i);
        mbar_wait(bars + 8 * (B_PD + c));
        if (lane == 0) bulk_s2g(g_kv + (dg * 32 + m2) * 20480 + c * 4096, sb + KS_OFF + c * KV_PIECE, 4096);
      }
      if (lane == 0) {
        asm volatile("cp.async.bulk.commit_group;" ::: "memory");
        asm volatile("cp.async.bulk.wait_group 0;" ::: "memory");
        mbar_arrive(bars + 8 * B_PREP2);
        fence_async_global();
      }
      __syncwarp();
      if (lane < 4) red_rel(&g_kvcnt[(dg * 4 + lane) * 32]);
      __syncwarp();
      if (lane == 0) { mbar_arrive(bars + 8 * B_PUB); TS(30); }
    }
  } else if (wid != 12) {
    if (elect_one()) {
      if (wid < 7) {
        const int b0 = wid < 4 ? 4 + 19 * wid : 85 + 21 * (wid - 4), cnt = wid < 4 ? 2 : 1;
#pragma unroll
        for (int i = 0; i < 21; i++) mbar_init(bars + 8 * (b0 + i), cnt);
#pragma unroll
        for (int i = 0; i < 5; i++) mbar_init(bars + 8 * (B_PD + 5 * wid + i), 1);
      } else {
#pragma unroll
        for (int i = 0; i < 12; i++) mbar_init(bars + 8 * (B_CVDONE + i), (i == 5 || i == 6) ? 160 : 128);
        mbar_init(bars + 8 * B_CTAB, 192); mbar_init(bars + 8 * B_PREP, 5); mbar_init(bars + 8 * B_PREP2, 1);
      }
      asm volatile("fence.mbarrier_init.release.cluster;" ::: "memory");
    }
    __syncwarp();
    bar_sync(5, 288);
    if (wid == 2) asm volatile("bar.arrive 8, 192;\nbar.arrive 6, 64;\nbar.arrive 9, 64;\nbar.arrive 7, 64;" ::: "memory");
    if (tid == 128) TS(0);
    if (wg == 1) { cv_table(); mbar_arrive(bars + 8 * B_CTAB); }
  }

  if (wid == 12) {
    ROLE(role)
    uint32_t dst = sb;
#pragma unroll 1
    for (int k = S1; k < 10; k++) {
      const uint32_t fb = bars + 8 * (B_G1FULL + k);
      mbar_wait(bars + 8 * (B_G1DONE + k - S1));
      if (elect_one()) {
        mbar_expect_tx(fb, 20480);
        tma4(dst + G1_XOFF, last ? &p.mXl : &p.mX, 64 * k, 0, 0, last ? 0 : 80 * T1, fb);
        mbar_expect_tx(fb, 16384);
        tma5(dst, &p.mB, 64 * k, 0, 0, 4 * side, 2 * GP, fb);
        if (has2 && k - S1 + KV0 < 5) kv_issue(p, k - S1 + KV0, m2, dg);
      }
      dst += G1_STAGE; if (k == 2 * S1 - 1) dst = sb;
    }
  } else if (wid == 15 && (role >> 16)) {
    ROLE(role)
    if (TPF >= 0) {
      mbar_wait(bars + 8 * (B_KV + TPF));
      if (elect_one()) {
#pragma unroll
        for (int c = 0; c < 5; c++) l2_prefetch(p.ssmk + (cch0 + 32 * c) * SEQ, 4096);
        if (CPF) { l2_prefetch(p.cre + (160 * dg + 5 * m2) * DM, 6400); l2_prefetch(p.cim + (160 * dg + 5 * m2) * DM, 6400); }
      }
    }
    mbar_wait(bars + 8 * B_PREP2);
    if (lane < 10) sts128(sb + CV_OFF + (lane >> 1) * CV_B + CV_K - 32 + 16 * (lane & 1), make_uint4(0, 0, 0, 0));
    fence_async_smem();
    __syncwarp();
    const unsigned tag = lds32(sb + EP_OFF + 20);
    if (TAPW) mbar_wait(bars + 8 * B_PUB);
    if (elect_one()) {
#pragma unroll 1
      for (int c = 0; c < 5; c++) {
        if (c == 0) asm volatile("prefetch.tensormap [%0];" ::"l"(&p.mU) : "memory");
        mbar_expect_tx(bars + 8 * (B_CVFULL + c), 4096 + 2 * CV_PL);
        if (c < TAPN) bulk_g2s(sb + CV_OFF + c * CV_B + CV_K, p.ssmk + (cch0 + 32 * c) * SEQ, 4096, bars + 8 * (B_CVFULL + c));
      }
    }
    mbar_wait(bars + 8 * B_PUB);
    cnt_poll(&g_kvcnt[(dg * 4 + (m2 >> 3)) * 32], 32 * tag);
    fence_async_global();
    if (elect_one()) {
      TS(28);
#pragma unroll
      for (int c = 0; c < 5; c++) {
        tma5(sb + CV_OFF + c * CV_B + CV_U, &p.mU, 0, -3, 2 * c, 16 * (m2 & 1) + (m2 >> 1), dg, bars + 8 * (B_CVFULL + c));
        if (c >= TAPN) bulk_g2s(sb + CV_OFF + c * CV_B + CV_K, p.ssmk + (cch0 + 32 * c) * SEQ, 4096, bars + 8 * (B_CVFULL + c));
      }
#pragma unroll
      for (int i = 0; i < 3; i++) asm volatile("prefetch.tensormap [%0];" ::"l"(&p.mCre + i) : "memory");
      TS(54);
    }
    __syncwarp();
  }
  {
    const int w = wid & 3;
    if (wg == 2 && !(role >> 16)) {
      float xa[2], xb[2];
      mbar_wait(bars + 8 * (B_G1FULL + 11));
      stat_table(role & 15, lds32(sb + EP_OFF + 20), 1, w, g_stats, g_stats, xa, xb);
      mbar_arrive(bars + 8 * (B_STAB + 1));
    }
#pragma unroll 1
    for (int l = 0; l < 2; l++) {
      if (wg < 2) {
        float acc[80];
#pragma unroll
        for (int i = 0; i < 80; i++) acc[i] = 0.f;
        ROLE(role)
        const int tid = tid_opaque(), r = (tid & 31) >> 2, q = tid & 3;
        const int ch = 128 * GP + 64 * wg + 32 * side + 8 * w + r;
        const uint32_t ca = sb + CTAB_OFF + (32 * wg + 8 * w + r) * 24;
        float2 lam = make_float2(0.f, 0.f), p8 = lam, p16 = lam, pL = lam, p2L = lam;
        fence_regs(acc);
        {
          const uint32_t alo0 = (l == 0 ? desc_lo(sb, 16) : desc_lo(sb + G2_WOFF, 16)) + wg * 512;
          const uint32_t blo0 = l == 0 ? desc_lo(sb + G1_XOFF, 16) : desc_lo(sb + X1_OFF, 128);
          const uint32_t bhi = l == 0 ? desc_hi(1024, 1) : desc_hi(1024, 0), xstep = l == 0 ? 2 : 16;
          const uint32_t astep = l == 0 ? G1_STAGE >> 4 : 1024, bstep = l == 0 ? G1_STAGE >> 4 : 1280, aend = alo0 + (S1 + l) * astep;
          uint32_t alo = alo0, blo = blo0;
          const uint32_t special = 8u | (l ? (1u << MK1) | (wg << (8 - STG_D)) : (1u << MK0) | (1u << PAUSE_K) | (wg << (9 - STG0)));
          uint32_t fb = bars + 8 * (B_G1FULL + 10 * l), nb = fb + 8;
          mbar_wait(fb);
          if (tid == 0) TS(1 + 8 * l);
#pragma unroll 1
          for (int k = 0; k < 10; k++) {
            uint32_t ok;
            wgmma_fence();
#pragma unroll
            for (int kk = 0; kk < 4; kk++) {
              wgmma_n160<0>(acc, alo + kk * 2, desc_hi(1024, 1), blo + kk * xstep, bhi);
              if (kk == 0) { ok = mbar_test(nb); asm volatile("add.u32 %0, %0, %1;" : "+r"(nb) : "r"(k < 8 ? 8 : 0)); }
              if (kk == STG_KK && k == 9 && tid == 0) mbar_arrive(bars + 8 * (B_STG + l));
            }
            wgmma_commit();
            alo += astep; blo += bstep;
            if (blo == desc_lo(sb + G_OFF, 128)) blo = desc_lo(sb, 128);
            if (alo == aend) { alo = alo0; blo = blo0; }
            wgmma_wait<1>();
            if (k > 0 && (tid & 127) == 0) mbar_arrive(fb + 8 * (B_G1DONE - B_G1FULL - 1));
            if (!ok) mbar_wait(fb + 8);
            if ((special >> k) & 1) {
            if (k == (l ? MK1 : MK0)) {
              mbar_wait(bars + 8 * (B_STAB + l));
              const float2 sB = lds64f(ca + 16);
              uint32_t a0 = q < 2 ? __float_as_uint(sB.x) : 0u, a1 = q < 2 ? __float_as_uint(sB.y) : 0u, a2 = 0u, a3 = 0u;
              asm volatile("" : "+r"(a0), "+r"(a1), "+r"(a2), "+r"(a3)::"memory");
              wgmma_fence();
              wgmma_rs_n160(acc, a0, a1, a2, a3, l ? desc_lo(sb + MX1_OFF, 0) : desc_lo(sb + MX0_OFF, 0));
              wgmma_commit();
            }
            if (wg == 1 && k == (l ? 8 - STG_D : 9 - STG0)) mbar_wait(bars + 8 * (B_STG + l));
            if (k == 3) {
              mbar_wait(bars + 8 * B_CTAB);
              lam = lds64f(ca);
              if (l == 0 && q < 2) rec_st(&g_E[(q * NT1 + T1) * DM + ch], 0.f, 0.f, lds32(sb + EP_OFF + 20) - 1);
              if (p.swap) lam.y = -lam.y;
              const float2 p2 = cmul(lam, lam), p4 = cmul(p2, p2);
              p8 = cmul(p4, p4); p16 = cmul(p8, p8);
              pL = cmul(p16, p16);
              if (!last) pL = cmul(pL, p8);
              p2L = cmul(pL, pL);
            }
            if (k == PAUSE_K && l == 0 && has2) mbar_wait(bars + 8 * B_PREP);
            }
            fb += 8;
          }
        }
        const unsigned tag = lds32(sb + EP_OFF + 20);
        wgmma_wait<0>();
        fence_regs(acc);
        if ((tid & 127) == 0) { mbar_arrive(bars + 8 * (B_G1DONE + 10 * l + 9)); TS(wg ? 17 + l : 2 + 8 * l); }
        float2 ec[3];
#pragma unroll
        for (int jj = 0; jj < 4; jj++)
#pragma unroll
          for (int y = 0; y < 3; y++) {
            if (y == 2 && (jj & 1)) continue;
            const int j = y == 2 ? 16 + jj : 8 * y + 2 * jj;
            const float4 st = lds128f(sb + STAB_OFF + q * 160 + j * 8);
            const float rs[4] = {st.x, st.y, st.z, st.w};
#pragma unroll
            for (int x = 0; x < 4; x++) {
              const int i = 4 * j + 4 * (x >> 1) + (x & 1);
              acc[i] *= rs[x]; acc[i + 2] *= rs[x];
              ec[y] = (jj == 0 && x == 0) ? make_float2(acc[i], acc[i + 2]) : cfma(lam, ec[y], make_float2(acc[i], acc[i + 2]));
            }
          }
        float2 e = cfma(p16, ec[0], ec[1]);
        if (!last) e = cfma(p8, e, ec[2]);
        {
          float2 v = make_float2(__shfl_up_sync(0xffffffffu, e.x, 1, 4), __shfl_up_sync(0xffffffffu, e.y, 1, 4));
          if (q >= 1) e = cfma(pL, v, e);
          v = make_float2(__shfl_up_sync(0xffffffffu, e.x, 2, 4), __shfl_up_sync(0xffffffffu, e.y, 2, 4));
          if (q >= 2) e = cfma(p2L, v, e);
        }
        if (!last && q == 3) rec_st(&g_E[(l * NT1 + T1) * DM + ch], e.x, e.y, tag);
        if (tid == 0) TS(3 + 8 * l);
        float2 ex = make_float2(__shfl_up_sync(0xffffffffu, e.x, 1, 4), __shfl_up_sync(0xffffffffu, e.y, 1, 4));
        if (q == 0) ex = make_float2(0.f, 0.f);
        const float2 coef = lds64f(ca + 8), lamc = make_float2(lam.x, p.swap ? lam.y : -lam.y);
        float m00 = coef.x, m01 = -coef.y, m10 = -coef.y, m11 = -coef.x;
        if (p.swap) { m00 = -coef.y; m01 = coef.x; m10 = -coef.x; m11 = -coef.y; }
        float2 pLq, p160q, p640;
        {
          const float2 p80 = last ? cmul(p2L, p16) : p2L, p160 = cmul(p80, p80), p320 = cmul(p160, p160), one = make_float2(1.f, 0.f);
          p640 = cmul(p320, p320);
          pLq = cmul((q & 1) ? pL : one, (q & 2) ? p2L : one);
          p160q = cmul((q & 1) ? p160 : one, (q & 2) ? p320 : one);
        }
        float2 c, ev[3];
        unsigned tg[3];
        const uint4* ep = &g_E[(l * NT1 + T1 - 1 - q) * DM + ch];
#pragma unroll
        for (int j = 0; j < 20; j++) {
          if (j == CPOLL) {
#pragma unroll
            for (int i = 0; i < 3; i++) {
              ev[i] = make_float2(0.f, 0.f); tg[i] = tag;
              if (T1 - 1 - q - 4 * i >= 0) tg[i] = rec_ld(ep - 4 * i * DM, ev[i].x, ev[i].y);
            }
          }
#pragma unroll
          for (int x = 0; x < 2; x++) {
            const float b0 = acc[4 * j + x], b1 = acc[4 * j + 2 + x];
            acc[4 * j + x] = fmaf(b0, m00, b1 * m01);
            acc[4 * j + 2 + x] = fmaf(b0, m10, b1 * m11);
          }
          if (j == CPOLL - 1 || j == 19) asm volatile("" : "+f"(acc[4 * j]), "+f"(acc[4 * j + 1]), "+f"(acc[4 * j + 2]), "+f"(acc[4 * j + 3])::"memory");
        }
        {
          uint32_t it = 0;
          while (__any_sync(0xffffffffu, tg[0] != tag || tg[1] != tag || tg[2] != tag)) {
#pragma unroll
            for (int i = 0; i < 3; i++)
              if (tg[i] != tag) tg[i] = rec_ld(ep - 4 * i * DM, ev[i].x, ev[i].y);
            trap_if(++it > SPIN_LIMIT);
          }
          c = cfma(p640, cfma(p640, ev[2], ev[1]), ev[0]);
          c = cmul(c, p160q);
          c.x += __shfl_xor_sync(0xffffffffu, c.x, 1); c.y += __shfl_xor_sync(0xffffffffu, c.y, 1);
          c.x += __shfl_xor_sync(0xffffffffu, c.x, 2); c.y += __shfl_xor_sync(0xffffffffu, c.y, 2);
        }
        if (tid == 0) TS(4 + 8 * l);
        if (HOLD1 && wg == 1 && l == 1 && has2) mbar_wait(bars + 8 * HOLD1);
        const uint32_t c0 = (uint32_t)clock(), tm = (tid & 7) == 4 * side + w;
        c = cfma(pLq, c, ex);
        float2 hh = make_float2(fmaf(c.x, m00, c.y * m01), fmaf(c.x, m10, c.y * m11));
        uint8_t* hb = g_h + (10 * wg + 2 * GP) * 8192 + (4 * side + w) * 1024 + (tid_opaque() & 31) * 4;
#pragma unroll
        for (int j4 = 0; j4 < 5; j4++) {
          if (PACE && j4 > 0 && wg == 1 && l == 1) { while (__any_sync(0xffffffffu, (uint32_t)clock() - c0 < PACE * j4)) {} }
          const int ng = 20 * T1 + 4 * j4;
          uint8_t* hp = hb + (size_t)(ng >> 3) * 163840 + (ng & 7) * 128;
#pragma unroll
          for (int jj = 0; jj < 4; jj++) {
            const int j = 4 * j4 + jj;
            const float2 h0 = cfma(lamc, hh, make_float2(acc[4 * j + 0], acc[4 * j + 2]));
            hh = cfma(lamc, h0, make_float2(acc[4 * j + 1], acc[4 * j + 3]));
            if (j4 < 4 || !last) {
              *(uint32_t*)(hp + jj * 128) = tag_word(pack_bf16(h0.x, hh.x), tm, 1 - l);
              *(uint32_t*)(hp + jj * 128 + 8192) = tag_word(pack_bf16(h0.y, hh.y), tm, 1 - l);
            }
          }
        }
        mbar_arrive(bars + 8 * (B_HST + 2 * l + wg));
        if (tid == 0) TS(5 + 8 * l);
        if (tid == 128) TS(l ? 25 : 19);
        if (l == 0 && wid == 4) {
          mbar_wait(bars + 8 * B_HST);
          mbar_wait(bars + 8 * (B_HST + 1));
          if ((tid & 31) < 4) h_release(0, T1, tid & 3);
          __syncwarp();
          if (tid == 128) { mbar_arrive(bars + 8 * B_REL); TS(6); }
        }
      }
      if (l == 0) {
        ROLE(role)
        if (has2) {
          CvCtx cc;
          mbar_wait(bars + 8 * B_CTAB);
          cv_setup(cc);
          mbar_wait(bars + 8 * (B_G1DONE + 9));
#pragma unroll 1
          for (int c = (wg + 2) & 3; c < 5; c += 4) conv_channel(c, cc);
          if ((tid & 127) == 0) TS(wg == 2 ? 32 : (wg == 3 ? 50 : 7 + wg));
        }
      }
      if (wg >= 2) break;
    }
    if (wg < 2 && (role >> 16)) {
      const int ln = tid_opaque() & 31;
      const uint8_t* src = g_h + ((role >> 8) & 63) * 163840;
      uint32_t ph = 0;
      if (wg == 0) {
        mbar_wait(bars + 8 * (B_G1DONE + 19));
        __nanosleep(SPEC0);
        if (elect_one()) {
          if (w == 0) TS(23);
#pragma unroll 1
          for (int k = w; k < S2; k += 4) { mbar_expect_tx(bars + 8 * (B_XV + k), G2_XB); bulk_g2s(sb + k * G2_XB, src + k * 8192, G2_XB, bars + 8 * (B_XV + k)); }
        }
        __syncwarp();
      }
#pragma unroll 1
      for (int k = 10 * wg + w; k < 10 * wg + 10; k += 4)
        validate_block(bars + 8 * (B_XV + k), bars + 8 * (B_G2FULL + 20 + k), sb + (k % S2) * G2_XB, src + k * 8192,
                       (ln & 7) * 1028 + (ln >> 3) * 32, bars + 8 * (B_RETRY + wid), ph);
    }
    if (wg == 3) {
    ROLE(role)
    const int pw = wid & 3, gpc = 2 * min(m2 >> 3, 3) + (dg >> 1);
    mbar_wait(bars + 8 * B_EP);
    const unsigned tag = lds32(sb + EP_OFF + 20);
    if (pw == 0) {
      if (elect_one()) {
#pragma unroll 1
        for (int l = 0; l < 2; l++) {
          uint32_t dst = sb;
          if (l == 1) {
            dst = sb + G2_WOFF;
#pragma unroll 1
            for (int k = 0; k < 10; k++) {
              mbar_wait(k > 4 ? bars + 8 * (B_G1DONE + 5 + k) : (has2 ? bars + 8 * (B_G2DONE + 14 + min(k, 3)) : bars + 8 * (B_G1DONE + 9)));
              mbar_expect_tx(bars + 8 * (B_G1FULL + 10 + k), 16384);
              tma5(dst, &p.mB, 64 * k, 0, 0, 4 * side, 2 * GP, bars + 8 * (B_G1FULL + 10 + k));
              dst += 16384; if (k == 4) dst = sb + G2_WOFF;
            }
          }
          if (has2) {
            const uint32_t fb2 = bars + 8 * (B_G2FULL + 20 * l), wb2 = bars + 8 * (B_G2DONE + 20 * l - S2);
            dst = sb + G2_WOFF + (WTAIL ? 4 * l * G2_WB : 0);
            int kc = 0;
#pragma unroll 1
            for (int k = 0; k < 20; k++) {
              mbar_wait(k >= S2 ? wb2 + 8 * k : bars + 8 * (l ? B_G1DONE + (WTAIL ? (k < 3 ? 15 + k : 13 + k) : 19) : (k == 5 ? B_XFREE : (k == 6 ? B_SFREE : B_REL))));
              mbar_expect_tx(fb2 + 8 * k, G2_WB);
              tma5(dst, &p.mCre + (k & 1), kc, 0, 0, 0, 10 * dg, fb2 + 8 * k);
              kc += (k & 1) << 7; if (k == 9) kc = 64;
              dst += G2_WB; if (dst == sb + G2_WOFF + S2 * G2_WB) dst = sb + G2_WOFF;
            }
          }
        }
      }
    } else if (pw == 1) {
#pragma unroll 1
      for (int l = 0; l < 2; l++) {
        if (l == 1) {
          mbar_wait(bars + 8 * (has2 ? B_G2DONE + 19 : B_G1DONE + 9));
          if (has2) mbar_wait(bars + 8 * B_UST);
          cnt_poll(&g_ucnt[gpc * 32], 128 * tag);
          fence_async_global();
          if (elect_one()) {
            TS(20);
            const int bytes = last ? 16384 : 20480;
            const uint8_t* src = g_u + T1 * 204800;
            uint32_t dst = sb + X1_OFF;
#pragma unroll 1
            for (int k = 0; k < 10; k++) {
              if (k > 4) mbar_wait(bars + 8 * (B_G1DONE + 5 + k));
              mbar_expect_tx(bars + 8 * (B_G1FULL + 10 + k), bytes);
              bulk_g2s(dst, src, bytes, bars + 8 * (B_G1FULL + 10 + k));
              src += 20480; dst += 20480; if (dst == sb + G_OFF) dst = sb; if (k == 4) dst = sb + X1_OFF;
            }
          }
          __syncwarp();
        }
        if (has2) {
          if (l == 0) {
            mbar_wait(bars + 8 * B_REL);
            cnt_poll(&g_hcnt[gpc * 32], 40 * tag);
            fence_async_global();
          }
          if (elect_one()) {
            if (l == 0) TS(21);
            const uint32_t fb2 = bars + 8 * (l ? B_XV : B_G2FULL), wb2 = bars + 8 * (B_G2DONE + 20 * l - S2);
            const uint8_t* src = g_h + m2 * 163840 + l * S2 * 8192;
            uint32_t dst = sb;
#pragma unroll 1
            for (int k = l * S2; k < 20; k++) {
              if (k >= 5) mbar_wait(k >= S2 ? wb2 + 8 * k : bars + 8 * B_SFREE);
              mbar_expect_tx(fb2 + 8 * k, G2_XB);
              bulk_g2s(dst, src, G2_XB, fb2 + 8 * k);
              src += 8192; dst += G2_XB; if (dst == sb + S2 * G2_XB) dst = sb;
            }
          }
          __syncwarp();
        }
      }
    } else if (pw == 2) {
#pragma unroll 1
      for (int l = 0; l < 2; l++) {
        if (l == 1) {
          float xa[2], xb[2];
          mbar_wait(bars + 8 * (B_G1FULL + 11));
          stat_table(T1, tag, 1, 4, g_stats, g_stats, xa, xb);
          mbar_arrive(bars + 8 * (B_STAB + 1));
        }
        if (l == 0 && has2 && elect_one()) {
#pragma unroll 1
          for (int i = 0; i < 5; i++) {
            const int c = i < 3 ? i : 7 - i;
            mbar_wait(bars + 8 * (B_CVDONE + c));
            bulk_s2g(g_G + (cch0 + 32 * c) * 4096, cv_stage(c), 4096);
          }
          asm volatile("cp.async.bulk.commit_group;" ::: "memory");
          asm volatile("cp.async.bulk.wait_group.read 0;" ::: "memory");
          mbar_arrive(bars + 8 * B_SFREE);
          asm volatile("cp.async.bulk.wait_group 0;" ::: "memory");
          TS(48);
          fence_async_global();
          asm volatile("fence.acq_rel.gpu;" ::: "memory");
#pragma unroll
          for (int i = 0; i < 4; i++) red_rlx(&g_gcnt[(dg * 4 + i) * 32]);
          TS(49);
          mbar_arrive(bars + 8 * (B_GO + 1));
        }
        __syncwarp();
      }
    } else if (has2) {
      mbar_wait(bars + 8 * B_REL);
      if (!CPF && elect_one()) {
        l2_prefetch(p.cre + (160 * dg + 5 * m2) * DM, 6400); l2_prefetch(p.cim + (160 * dg + 5 * m2) * DM, 6400);
      }
      mbar_wait(bars + 8 * (B_GO + 1));
      flag_poll(&g_gcnt[(dg * 4 + (m2 >> 3)) * 32], 32 * tag);
      fence_async_global();
      if (elect_one()) {
        TS(29);
        mbar_expect_tx(bars + 8 * B_GFULL, 20480);
        tma5(sb + G_OFF, &p.mG, 64 * m2, 0, 0, 0, 10 * dg, bars + 8 * B_GFULL);
      }
    }
    } else if (wg == 2 && (role >> 16)) {
      float acc[80];
      float off[2] = {mean0[0], mean0[1]};
      const unsigned tag = lds32(sb + EP_OFF + 20);
      dskip_init<true>(acc, mean0, rstd0);
      mbar_arrive(bars + 8 * B_XFREE);
#pragma unroll 1
      for (int step = 1; step < 4; step++) {
        const int l = step >> 1;
        if (step != 2) {
          uint32_t alo = desc_lo(sb, 1024), blo = desc_lo(sb + G2_WOFF, 16) + (WTAIL ? l * (G2_WB >> 2) : 0);
          uint32_t fb = bars + 8 * (B_G2FULL + 20 * l);
          fence_regs(acc);
          mbar_wait(bars + 8 * (B_CVDONE + 2));
          mbar_wait(bars + 8 * (B_CVDONE + 3));
          mbar_wait(fb);
          if (tid == 256) TS(33 + 6 * l);
#pragma unroll 1
          for (int k = 0; k < 20; k++) {
            if (l == TSL && (k & 3) == 3 && tid == 256) TS(56 + (k >> 2));
            uint32_t ok; const uint32_t nb = k < 19 ? fb + 8 : fb;
            wgmma_fence();
#pragma unroll
            for (int kk = 0; kk < 4; kk++) {
              wgmma_n160<1>(acc, alo + kk * 128, desc_hi(128, 0), blo + kk * 2, desc_hi(1024, 1));
              if (kk == 0) ok = mbar_test(nb);
            }
            wgmma_commit();
            alo += G2_XB >> 4; blo += G2_WB >> 4;
            if (alo == desc_lo(sb + S2 * G2_XB, 1024)) alo = desc_lo(sb, 1024);
            if (blo == desc_lo(sb + G_OFF, 16)) blo = desc_lo(sb + G2_WOFF, 16);
            wgmma_wait<1>();
            if (k > 0 && tid == 256) mbar_arrive(fb + 8 * (B_G2DONE - B_G2FULL - 1));
            if (!ok) mbar_wait(nb);
            fb += 8;
          }
          wgmma_wait<0>();
          fence_regs(acc);
          if (tid == 256) TS(34 + 6 * l);
          if (tid == 256) mbar_arrive(bars + 8 * (B_G2DONE + 20 * l + 19));
        }
        ROLE(role)
        const int tq = tid_opaque() & 31, n0 = 64 * m2 + 16 * w + (tq >> 2);
#pragma unroll 1
        for (int rep = 0;; rep++) {
          stats_publish<false>(step, n0, dg, tag, acc);
          if (step != 2 || rep == 1) break;
          for (int n = tid & 127; n < 160; n += 128) {
            const int d = 16 * (n >> 4) + 4 * ((n >> 1) & 3) + 2 * ((n >> 3) & 1) + (n & 1);
            const uint32_t dw = lds32(sb + DTAB_OFF + 2 * (d & ~1)), dd = __byte_perm(dw, dw, (d & 1) ? 0x3232 : 0x1010);
            sts128(sb + DX_OFF + 16 * n, make_uint4(dd, dd, dd, dd));
          }
          mbar_wait(bars + 8 * (B_G1FULL + 11));
          float xa[2], xb[2];
          stat_table(T1, tag, 1, w, g_stats, g_stats, xa, xb);
          mbar_arrive(bars + 8 * (B_STAB + 1));
          if (tid == 256) TS(27);
          bar_sync(3, 128);
          break;
        }
        uint32_t gf[10][4];
        mbar_wait(bars + 8 * B_GFULL);
        uint32_t ga = sb + G_OFF + (8 * (tq >> 4) + (tq & 7)) * 128 + (((2 * w + ((tq >> 3) & 1)) ^ ((2 * m2) & 6) ^ (tq & 7)) << 4), gstep = 2048;
        if (step == 2) { ga = sb + DX_OFF + (8 * (tq >> 4) + (tq & 7)) * 16; gstep = 256; }
#pragma unroll
        for (int J = 0; J < 2; J++) ldsm4t(gf[J], ga + J * gstep);
        if (tid == 256) TS(35 + 6 * l);
        uint8_t* dst[2][2];
#pragma unroll
        for (int h = 0; h < 2; h++) {
          if (l == 0) {
            const int ng = 8 * m2 + 2 * w + h, T = ng / 20;
            uint8_t* ub = g_u + (T * 204800 + (ng - 20 * T) * 1024 + (tq & 2) * 64 + (tq & 28) * 4 + (tq & 1) * 8 + (5 * dg >> 1) * 20480);
            dst[h][1] = ub + ((dg & 1) ? 20480 - 512 : 0);
            dst[h][0] = ub + (dg & 1) * 512;
          } else {
            dst[h][0] = dst[h][1] = (uint8_t*)(p.out + (n_to_t(n0 + 8 * h) * DM + 160 * dg + 4 * (tq & 3)));
          }
        }
        float mean[2], rstd[2];
        stats_get(step, n0, tag, mean, rstd);
        if (tid == 256) TS(36 + 6 * l);
        if (step == 2) mbar_wait(bars + 8 * NGATE);
        off[0] += mean[0]; off[1] += mean[1];
        const float ov[2] = {step == 3 ? off[0] : 0.f, step == 3 ? off[1] : 0.f};
#pragma unroll
        for (int J = 0; J < 10; J++) {
          if (J + 2 < 10) ldsm4t(gf[J + 2 < 10 ? J + 2 : 0], ga + (J + 2) * gstep);
#pragma unroll
          for (int x = 0; x < 8; x++) {
            const int h = (x >> 1) & 1;
            const uint32_t gwd = gf[J][x >> 1];
            const float t = fmaf(rstd[h], (x & 1) ? bf_hi(gwd) : bf_lo(gwd), 1.f);
            acc[8 * J + x] = fmaf(acc[8 * J + x], t, fmaf(-mean[h], t, ov[h]));
          }
#pragma unroll
          for (int h = 0; h < 2; h++) {
            if (step == 1)
              *(uint2*)(dst[h][(J >> 1) & 1] + (J >> 2) * 20480 + (J & 3) * 256) =
                  make_uint2(pack_bf16(acc[8 * J + 2 * h], acc[8 * J + 2 * h + 1]), pack_bf16(acc[8 * J + 4 + 2 * h], acc[8 * J + 5 + 2 * h]));
            if (step == 3)
              *(float4*)(dst[h][0] + 64 * J) = make_float4(acc[8 * J + 2 * h], acc[8 * J + 2 * h + 1], acc[8 * J + 4 + 2 * h], acc[8 * J + 5 + 2 * h]);
          }
          __syncwarp();
        }
        if (step == 1) {
          bar_sync(3, 128);
          if (tid == 288) { TS(37); mbar_arrive(bars + 8 * B_UST); }
          if (tid < 264) red_rel(&g_ucnt[(tid & 7) * 32]);
          __syncwarp();
          if (tid == 256) TS(38);
        } else if (step == 2) {
          if (tid == 256) TS(22);
        } else {
          if (tid == 256) {
            TS(43);
            if (m2 == 31 && dg == 3) asm volatile("st.relaxed.gpu.global.u32 [%0], %1;" ::"l"(g_epoch), "r"(tag + 1) : "memory");
          }
        }
      }
    }
  }
}

typedef CUresult (*EncFn)(CUtensorMap*, CUtensorMapDataType, cuuint32_t, void*, const cuuint64_t*, const cuuint64_t*,
                          const cuuint32_t*, const cuuint32_t*, CUtensorMapInterleave, CUtensorMapSwizzle,
                          CUtensorMapL2promotion, CUtensorMapFloatOOBfill);

void encode(EncFn fn, CUtensorMap* m, const void* ptr, int rank, const cuuint64_t* dims, const cuuint64_t* strides, const cuuint32_t* box,
            CUtensorMapSwizzle swz = CU_TENSOR_MAP_SWIZZLE_128B, int prom = 2) {
  cuuint32_t es[5] = {1, 1, 1, 1, 1};
  fn(m, CU_TENSOR_MAP_DATA_TYPE_BFLOAT16, rank, (void*)ptr, dims, strides, box, es, CU_TENSOR_MAP_INTERLEAVE_NONE,
     swz, (CUtensorMapL2promotion)prom, CU_TENSOR_MAP_FLOAT_OOB_FILL_NONE);
}

}

extern "C" void kernel_launch(void* const* d_in, const int* in_sizes, int n_in, void* d_out, int out_size) {
  (void)in_sizes; (void)n_in; (void)out_size;
  Params p;
  typedef const __nv_bfloat16* BP;
  p.x = (BP)d_in[0]; p.lre = (BP)d_in[1]; p.lim = (BP)d_in[2]; p.bre = (BP)d_in[3]; p.bim = (BP)d_in[4];
  p.cre = (BP)d_in[5]; p.cim = (BP)d_in[6]; p.logdt = (BP)d_in[7]; p.dskip = (BP)d_in[8];
  p.k = (BP)d_in[10]; p.v = (BP)d_in[11]; p.shiftk = (BP)d_in[12]; p.ssmk = (BP)d_in[13]; p.ssmD = (BP)d_in[14];
  p.out = (float*)d_out;
  for (int sm = 0; sm < 132; sm++) {
    const int tpc = sm >> 1, side = sm & 1;
    int gpc, gi;
    if (tpc < 32) { gpc = tpc & 7; gi = tpc >> 3; }
    else if (tpc < 60) { gpc = 1 + (tpc - 32) % 7; gi = 4 + (tpc - 32) / 7; }
    else if (tpc < 62) { gpc = tpc - 54; gi = 8; }
    else { gpc = 0; gi = tpc - 58; }
    const int pos = 8 * gpc + gi + (gpc == 7 ? 1 : 0);
    int T1, GP;
    if (pos < 52) { const int hh = pos / 26, x = pos - 26 * hh; T1 = x >> 1; GP = 2 * hh + (x & 1); }
    else { T1 = pos - 52; GP = 4; }
    const int m2 = 8 * (gpc >> 1) + gi, dg = 2 * (gpc & 1) + side;
    p.role[sm] = pos == 65 ? -1 : (T1 | (GP << 4) | (side << 7) | (m2 << 8) | (dg << 14) | ((gi < 8) << 16));
  }
  void* fnp = nullptr;
  cudaDriverEntryPointQueryResult qr;
  cudaGetDriverEntryPoint("cuTensorMapEncodeTiled", &fnp, cudaEnableDefault, &qr);
  EncFn fn = (EncFn)fnp;
  void* gG = nullptr;
  cudaGetSymbolAddress(&gG, g_G);
  void* gKV = nullptr;
  cudaGetSymbolAddress(&gKV, g_kv);
  {
    cuuint64_t dims[5] = {32, 32, 10, 32, 4}, st[4] = {20480, 2048, 64, 655360}; cuuint32_t box[5] = {32, 35, 2, 1, 1};
    encode(fn, &p.mU, gKV, 5, dims, st, box, CU_TENSOR_MAP_SWIZZLE_NONE, 1);
  }
  const cuuint64_t RB = DM * 2;
  {
    p.swap = p.bim < p.bre;
    const char* lo = (const char*)(p.swap ? p.bim : p.bre); const char* hi = (const char*)(p.swap ? p.bre : p.bim);
    cuuint64_t dims[5] = {640, 8, 2, 8, 10}, st[4] = {RB, (cuuint64_t)(hi - lo), 8 * RB, 64 * RB}; cuuint32_t box[5] = {64, 8, 2, 4, 2};
    encode(fn, &p.mB, lo, 5, dims, st, box);
  }
  {
    cuuint64_t dims[5] = {640, 2, 4, 2, 40}, st[4] = {RB, 4 * RB, 2 * RB, 16 * RB}; cuuint32_t box[5] = {64, 2, 4, 2, 10};
    encode(fn, &p.mCre, p.cre, 5, dims, st, box); encode(fn, &p.mCim, p.cim, 5, dims, st, box);
    cuuint64_t dimg[5] = {2048, 2, 4, 2, 40}, stg[4] = {4096, 4 * 4096, 2 * 4096, 16 * 4096};
    encode(fn, &p.mG, gG, 5, dimg, stg, box);
  }
  {
    cuuint64_t dims[4] = {640, 2, 4, 900}, st[3] = {RB, 40 * RB, 2 * RB}; cuuint32_t box[4] = {64, 2, 4, 20};
    encode(fn, &p.mX, p.x, 4, dims, st, box);
    cuuint64_t diml[4] = {640, 2, 4, 16}, stl[3] = {RB, 32 * RB, 2 * RB};
    encode(fn, &p.mXl, p.x + (size_t)1920 * DM, 4, diml, stl, box);
    cuuint32_t boxt[4] = {160, 2, 4, 4};
    encode(fn, &p.mXt, p.x, 4, dims, st, boxt, CU_TENSOR_MAP_SWIZZLE_NONE);
    encode(fn, &p.mXtl, p.x + (size_t)1920 * DM, 4, diml, stl, boxt, CU_TENSOR_MAP_SWIZZLE_NONE);
    cuuint64_t dk[3] = {640, 2000, 4}, sk[2] = {RB, 16 * RB}; cuuint32_t bk[3] = {32, 19, 4}, bv[3] = {32, 17, 4};
    encode(fn, &p.mK, p.k, 3, dk, sk, bk, CU_TENSOR_MAP_SWIZZLE_NONE);
    encode(fn, &p.mV, p.v, 3, dk, sk, bv, CU_TENSOR_MAP_SWIZZLE_NONE);
  }
  cudaFuncSetAttribute(fused_kernel, cudaFuncAttributeMaxDynamicSharedMemorySize, SMEM_BYTES);
  cudaLaunchConfig_t cfg = {};
  cfg.gridDim = dim3(132); cfg.blockDim = dim3(512); cfg.dynamicSmemBytes = SMEM_BYTES; cfg.stream = cudaStreamPerThread;
  cudaLaunchKernelEx(&cfg, fused_kernel, p);
}
```

```cpp
#include <cuda_runtime.h>
#include <cuda.h>
#include <cuda_bf16.h>
#include <stdint.h>

namespace {

constexpr int SEQ = 2048, DM = 640;
constexpr int NT1 = 13;
#define EXP 0
#define WPF1 3
#define WPF2 7
#define CPOLL 10
#define KV0 1
#define TAPLATE 1
#define STG_D 3
#define STG_KK 1
#define HOLD1 0
#define SPEC0 300
#define NGATE (B_HST + 2)
#define WREL 0
#define UREL 1
#define TSL 1
#define STG0 2
#define WTAIL 1
#define PFD 1
#define TAPW 0
#define TPF 4
#define CPF 0
#define MK0 7
#define MK1 4
#define PACE 180
#define TAPN 2
#define SPLITI 1
#define SPECW 0
#define PAUSE_K 5
constexpr uint32_t SPIN_LIMIT = 1u << 22;

__device__ __align__(1024) uint8_t g_h[32 * 20 * 8192];
__device__ __align__(1024) uint8_t g_u[NT1 * 10 * 20480];
__device__ __align__(1024) uint8_t g_kv[DM * 4096];
__device__ __align__(1024) uint8_t g_G[DM * 4096];
__device__ __align__(128) uint4 g_E[2 * NT1 * DM];
__device__ __align__(128) uint4 g_stats[4 * 4 * SEQ];
__device__ __align__(128) uint4 g_sB[DM * 2];
__device__ __align__(128) unsigned g_hcnt[8 * 32];
__device__ __align__(128) unsigned g_ucnt[8 * 32];
__device__ __align__(128) unsigned g_kvcnt[16 * 32];
__device__ __align__(128) unsigned g_gcnt[16 * 32];
__device__ __align__(128) unsigned g_epoch[32] = {1};
#define TS(i) do {} while (0)

struct Params {
  CUtensorMap mX, mB, mXl, mK, mV, mXt, mXtl, mCre, mCim, mG, mU;
  const __nv_bfloat16 *x, *lre, *lim, *bre, *bim, *cre, *cim, *logdt, *dskip, *k, *v, *shiftk, *ssmk, *ssmD;
  float* out;
  int swap;
  int role[132];
};

constexpr uint32_t sb = 1024;
constexpr uint32_t G1_STAGE = 36864, G1_XOFF = 16384;
constexpr int S1 = 4;
constexpr uint32_t XT_OFF = 159744, KS_OFF = 180224, KV_PIECE = 9216;
constexpr uint32_t G2_XB = 8192, G2_WB = 20480, G2_WOFF = 57344, G_OFF = 200704;
constexpr uint32_t X1_OFF = 139264;
constexpr int S2 = 7;
constexpr uint32_t CV_OFF = KS_OFF, CV_K = 128, CV_PL = 2240, CV_U = CV_K + 4096, CV_B = KV_PIECE;
constexpr uint32_t MISC = 226304;
constexpr uint32_t BAR_OFF = MISC;
constexpr int B_G1FULL = 0, B_G1DONE = 20, B_G2FULL = 40,
              B_G2DONE = 85, B_GFULL = 125, B_EP = 126, B_CVFULL = 129  , B_STG = 134  , B_REL = 136  , B_SFREE = 138, B_UST = 142,
              B_GO = 139  , B_PUB = 147,
              B_CVDONE = 148  , B_STAB = 153  , B_XFREE = 155, B_HST = 156  ,
              B_CTAB = 160, B_PREP = 161, B_XT = 162, B_KV = 163  , B_PREP2 = 84, B_PD = 168  ,
              B_XV = 173  , B_RETRY = 193  ;
constexpr uint32_t bars = sb + BAR_OFF;
constexpr uint32_t STAB_OFF = MISC + 1648;
constexpr uint32_t CTAB_OFF = STAB_OFF + 640;
constexpr uint32_t DTAB_OFF = CTAB_OFF + 1536;
constexpr uint32_t EP_OFF = DTAB_OFF + 320;
constexpr uint32_t SO_OFF = EP_OFF + 32;
constexpr uint32_t TAP_OFF = 147456;
constexpr uint32_t MX0_OFF = TAP_OFF + 1280, MX1_OFF = G_OFF + 20480;
constexpr uint32_t DX_OFF = MX1_OFF + 2560;
constexpr uint32_t SMEM_BYTES = 232448;
static_assert(SO_OFF + 1536 <= SMEM_BYTES, "smem");

__device__ __forceinline__ void trap_if(bool c) { asm volatile("{\n.reg .pred p;\nsetp.ne.u32 p, %0, 0;\n@p trap;\n}\n" ::"r"((uint32_t)c)); }
__device__ __forceinline__ uint32_t smem_u32(const void* p) { return (uint32_t)__cvta_generic_to_shared(p); }
__device__ __forceinline__ void mbar_init(uint32_t bar, int cnt) { asm volatile("mbarrier.init.shared::cta.b64 [%0], %1;" ::"r"(bar), "r"(cnt) : "memory"); }
__device__ __forceinline__ void mbar_expect_tx(uint32_t bar, int bytes) { asm volatile("mbarrier.arrive.expect_tx.shared::cta.b64 _, [%0], %1;" ::"r"(bar), "r"(bytes) : "memory"); }
__device__ __forceinline__ void mbar_arrive(uint32_t bar) { asm volatile("mbarrier.arrive.shared::cta.b64 _, [%0];" ::"r"(bar) : "memory"); }
__device__ __forceinline__ bool elect_one() {
  uint32_t e; asm volatile("{\n.reg .pred P;\nelect.sync _|P, 0xffffffff;\nselp.u32 %0, 1, 0, P;\n}\n" : "=r"(e)); return e != 0;
}
__device__ __forceinline__ void mbar_wait(uint32_t bar) {
  asm volatile(
      "{\n.reg .pred p;\n.reg .u32 c;\nmov.u32 c, 0;\n"
      "W_%=:\nmbarrier.try_wait.parity.shared::cta.b64 p, [%0], 0;\n@p bra D_%=;\n"
      "add.u32 c, c, 1;\nsetp.lt.u32 p, c, %1;\n@p bra W_%=;\ntrap;\nD_%=:\n}\n" ::"r"(bar), "n"(SPIN_LIMIT) : "memory");
}
__device__ __forceinline__ uint32_t mbar_test(uint32_t bar) {
  uint32_t ok;
  asm volatile("{\n.reg .pred p;\nmbarrier.test_wait.parity.shared::cta.b64 p, [%1], 0;\nselp.u32 %0, 1, 0, p;\n}\n" : "=r"(ok) : "r"(bar) : "memory");
  return ok;
}
__device__ __forceinline__ void tma3(uint32_t dst, const CUtensorMap* m, int c0, int c1, int c2, uint32_t bar) {
  asm volatile("cp.async.bulk.tensor.3d.shared::cluster.global.mbarrier::complete_tx::bytes [%0], [%1, {%3,%4,%5}], [%2];"
               ::"r"(dst), "l"(m), "r"(bar), "r"(c0), "r"(c1), "r"(c2) : "memory");
}
__device__ __forceinline__ void tma4(uint32_t dst, const CUtensorMap* m, int c0, int c1, int c2, int c3, uint32_t bar) {
  asm volatile("cp.async.bulk.tensor.4d.shared::cluster.global.mbarrier::complete_tx::bytes [%0], [%1, {%3,%4,%5,%6}], [%2];"
               ::"r"(dst), "l"(m), "r"(bar), "r"(c0), "r"(c1), "r"(c2), "r"(c3) : "memory");
}
__device__ __forceinline__ void tma5(uint32_t dst, const CUtensorMap* m, int c0, int c1, int c2, int c3, int c4, uint32_t bar) {
  asm volatile("cp.async.bulk.tensor.5d.shared::cluster.global.mbarrier::complete_tx::bytes [%0], [%1, {%3,%4,%5,%6,%7}], [%2];"
               ::"r"(dst), "l"(m), "r"(bar), "r"(c0), "r"(c1), "r"(c2), "r"(c3), "r"(c4) : "memory");
}
__device__ __forceinline__ void bulk_g2s(uint32_t dst, const void* src, int bytes, uint32_t bar) {
  asm volatile("cp.async.bulk.shared::cluster.global.mbarrier::complete_tx::bytes [%0], [%1], %2, [%3];"
               ::"r"(dst), "l"(src), "r"(bytes), "r"(bar) : "memory");
}
__device__ __forceinline__ void bulk_s2g(void* dst, uint32_t src, int bytes) {
  asm volatile("cp.async.bulk.global.shared::cta.bulk_group [%0], [%1], %2;" ::"l"(dst), "r"(src), "r"(bytes) : "memory");
}
__device__ __forceinline__ void l2_prefetch(const void* src, int bytes) {
  asm volatile("cp.async.bulk.prefetch.L2.global [%0], %1;" ::"l"(src), "r"(bytes) : "memory");
}
__device__ __forceinline__ void wgmma_fence() { asm volatile("wgmma.fence.sync.aligned;" ::: "memory"); }
__device__ __forceinline__ void wgmma_commit() { asm volatile("wgmma.commit_group.sync.aligned;" ::: "memory"); }
template <int N> __device__ __forceinline__ void wgmma_wait() { asm volatile("wgmma.wait_group.sync.aligned %0;" ::"n"(N) : "memory"); }
__host__ __device__ constexpr uint32_t desc_lo(uint32_t addr, uint32_t lbo) { return ((addr & 0x3FFFF) >> 4) | ((lbo >> 4) << 16); }
__host__ __device__ constexpr uint32_t desc_hi(uint32_t sbo, uint32_t swz) { return (sbo >> 4) | (swz << 30); }
__device__ __forceinline__ void bar_sync(int id, int n) { asm volatile("bar.sync %0, %1;" ::"r"(id), "r"(n) : "memory"); }
__device__ __forceinline__ uint32_t lds32(uint32_t a) { uint32_t v; asm volatile("ld.shared.u32 %0, [%1];" : "=r"(v) : "r"(a) : "memory"); return v; }
__device__ __forceinline__ float2 lds64f(uint32_t a) { float2 v; asm volatile("ld.shared.v2.f32 {%0,%1}, [%2];" : "=f"(v.x), "=f"(v.y) : "r"(a) : "memory"); return v; }
__device__ __forceinline__ float4 lds128f(uint32_t a) { float4 v; asm volatile("ld.shared.v4.f32 {%0,%1,%2,%3}, [%4];" : "=f"(v.x), "=f"(v.y), "=f"(v.z), "=f"(v.w) : "r"(a) : "memory"); return v; }
__device__ __forceinline__ void ldsm4t(uint32_t (&r)[4], uint32_t a) {
  asm volatile("ldmatrix.sync.aligned.m8n8.x4.trans.shared.b16 {%0,%1,%2,%3}, [%4];" : "=r"(r[0]), "=r"(r[1]), "=r"(r[2]), "=r"(r[3]) : "r"(a) : "memory");
}
__device__ __forceinline__ uint4 ldv128(const void* a) { uint4 v; asm volatile("ld.global.nc.v4.u32 {%0,%1,%2,%3}, [%4];" : "=r"(v.x), "=r"(v.y), "=r"(v.z), "=r"(v.w) : "l"(a) : "memory"); return v; }
__device__ __forceinline__ uint2 ldv64(const void* a) { uint2 v; asm volatile("ld.global.nc.v2.u32 {%0,%1}, [%2];" : "=r"(v.x), "=r"(v.y) : "l"(a) : "memory"); return v; }
__device__ __forceinline__ uint32_t ldv16(const void* a) { uint32_t v; asm volatile("ld.global.nc.u16 %0, [%1];" : "=r"(v) : "l"(a) : "memory"); return v; }
__device__ __forceinline__ void sts128(uint32_t a, uint4 v) { asm volatile("st.shared.v4.u32 [%0], {%1,%2,%3,%4};" ::"r"(a), "r"(v.x), "r"(v.y), "r"(v.z), "r"(v.w) : "memory"); }
__device__ __forceinline__ void sts32(uint32_t a, uint32_t v) { asm volatile("st.shared.u32 [%0], %1;" ::"r"(a), "r"(v) : "memory"); }
__device__ __forceinline__ void sts64f(uint32_t a, float x, float y) { asm volatile("st.shared.v2.f32 [%0], {%1,%2};" ::"r"(a), "f"(x), "f"(y) : "memory"); }
__device__ __forceinline__ void red_rlx(unsigned* p) { asm volatile("red.relaxed.gpu.global.add.u32 [%0], 1;" ::"l"(p) : "memory"); }
__device__ __forceinline__ void red_rel(unsigned* p) { asm volatile("red.release.gpu.global.add.u32 [%0], 1;" ::"l"(p) : "memory"); }
__device__ __forceinline__ void fence_async_global() { asm volatile("fence.proxy.async.global;" ::: "memory"); }
__device__ __forceinline__ void fence_async_smem() { asm volatile("fence.proxy.async.shared::cta;" ::: "memory"); }
__device__ __forceinline__ void rec_st(uint4* p, float a, float b, unsigned tag) {
  asm volatile("{\n.reg .b128 t;\n.reg .b64 lo, hi;\nmov.b64 lo, {%1,%2};\nmov.b64 hi, {%3,%3};\nmov.b128 t, {lo,hi};\n"
               "st.relaxed.gpu.global.b128 [%0], t;\n}\n" ::"l"(p), "r"(__float_as_uint(a)), "r"(__float_as_uint(b)), "r"(tag) : "memory");
}
__device__ __forceinline__ unsigned rec_ld(const uint4* p, float& a, float& b) {
  unsigned x, y, t;
  asm volatile("{\n.reg .b128 t;\n.reg .b64 lo, hi;\n.reg .b32 u;\nld.relaxed.gpu.global.b128 t, [%3];\nmov.b128 {lo,hi}, t;\n"
               "mov.b64 {%0,%1}, lo;\nmov.b64 {%2,u}, hi;\n}\n" : "=r"(x), "=r"(y), "=r"(t) : "l"(p) : "memory");
  a = __uint_as_float(x); b = __uint_as_float(y);
  return t;
}
__device__ __forceinline__ unsigned ld_rlx(const unsigned* p) { unsigned v; asm volatile("ld.relaxed.gpu.global.u32 %0, [%1];" : "=r"(v) : "l"(p) : "memory"); return v; }
__device__ __forceinline__ void flag_poll(const unsigned* p, unsigned target) {
  uint32_t it = 0;
  while (!__all_sync(0xffffffffu, (int)(ld_rlx(p) - target) >= 0)) { trap_if(++it > SPIN_LIMIT); }
  asm volatile("fence.acquire.gpu;" ::: "memory");
}
__device__ __forceinline__ void cnt_poll(const unsigned* p, unsigned target) {
  unsigned a = ld_rlx(p); __nanosleep(100);
  unsigned b = ld_rlx(p); __nanosleep(100);
  unsigned c = ld_rlx(p);
  uint32_t it = 0;
  while (true) {
    if (__all_sync(0xffffffffu, (int)(a - target) >= 0)) break;
    a = ld_rlx(p);
    if (__all_sync(0xffffffffu, (int)(b - target) >= 0)) break;
    b = ld_rlx(p);
    if (__all_sync(0xffffffffu, (int)(c - target) >= 0)) break;
    c = ld_rlx(p);
    trap_if(++it > SPIN_LIMIT);
  }
  asm volatile("fence.acquire.gpu;" ::: "memory");
}
__device__ __forceinline__ void validate_block(uint32_t bar, uint32_t full, uint32_t dst, const uint8_t* src, uint32_t woff, uint32_t rb, uint32_t& ph) {
  uint32_t it = 0, par = 0;
  while (true) {
    uint32_t ok, spins = 0;
    do {
      asm volatile("{\n.reg .pred p;\nmbarrier.try_wait.parity.shared::cta.b64 p, [%1], %2;\nselp.u32 %0, 1, 0, p;\n}\n" : "=r"(ok) : "r"(bar), "r"(par) : "memory");
      trap_if(++spins > SPIN_LIMIT);
    } while (!__all_sync(0xffffffffu, ok));
    uint32_t bad = 0;
#pragma unroll
    for (int i = 0; i < 8; i++) bad |= lds32(dst + woff + 128 * i);
    if (!__any_sync(0xffffffffu, bad & 1)) break;
    if (elect_one()) { mbar_expect_tx(rb, 8192); bulk_g2s(dst, src, 8192, rb); }
    bar = rb; par = ph; ph ^= 1;
    trap_if(++it > 100000);
  }
  if ((threadIdx.x & 31) == 0) mbar_arrive(full);
}
__device__ __forceinline__ uint32_t tag_word(uint32_t v, uint32_t m, uint32_t par) {
  uint32_t r; asm("lop3.b32 %0, %1, %2, %3, 0xb8;" : "=r"(r) : "r"(v), "r"(m), "r"(par)); return r;
}
__device__ __forceinline__ void h_release(int idx, int T, int i) {
  const int Q = (i & 2) ? (T + 2) / 3 - 1 : T / 3;
  if (Q >= 0 && Q < 4 && ((i & 2) == 0 || T % 3 == 0)) red_rel(&g_hcnt[(idx * 8 + 2 * Q + (i & 1)) * 32]);
}
__device__ __forceinline__ uint32_t pack_bf16(float lo, float hi) {
  uint32_t r; asm("cvt.rn.bf16x2.f32 %0, %1, %2;" : "=r"(r) : "f"(hi), "f"(lo)); return r;
}
__device__ __forceinline__ float bf_lo(uint32_t w) { return __uint_as_float(w << 16); }
__device__ __forceinline__ float bf_hi(uint32_t w) { return __uint_as_float(w & 0xffff0000u); }
__device__ __forceinline__ uint32_t hmul2(uint32_t a, uint32_t b) {
  __nv_bfloat162 r = __hmul2_rn(*(__nv_bfloat162*)&a, *(__nv_bfloat162*)&b); return *(uint32_t*)&r;
}
__device__ __forceinline__ uint32_t hadd2(uint32_t a, uint32_t b) {
  __nv_bfloat162 r = __hadd2_rn(*(__nv_bfloat162*)&a, *(__nv_bfloat162*)&b); return *(uint32_t*)&r;
}
__device__ __forceinline__ float2 cmul(float2 a, float2 b) { return make_float2(a.x * b.x - a.y * b.y, a.x * b.y + a.y * b.x); }
__device__ __forceinline__ float2 cfma(float2 a, float2 b, float2 c) {
  return make_float2(fmaf(a.x, b.x, fmaf(-a.y, b.y, c.x)), fmaf(a.x, b.y, fmaf(a.y, b.x, c.y)));
}
template <int N> __device__ __forceinline__ void fence_regs(float (&a)[N]) {
#pragma unroll
  for (int i = 0; i < N; i++) asm volatile("" : "+f"(a[i])::"memory");
}
__device__ __forceinline__ int tid_opaque() { int t; asm volatile("mov.u32 %0, %%tid.x;" : "=r"(t)); return t; }
struct Role { int T1, GP, side, m2, dg, cch0; bool last, has2; };
__device__ __forceinline__ Role unpack_role(int x) {
  Role r; r.T1 = x & 15; r.GP = (x >> 4) & 7; r.side = (x >> 7) & 1; r.m2 = (x >> 8) & 63; r.dg = (x >> 14) & 3;
  r.has2 = (x >> 16) & 1; r.last = r.T1 == NT1 - 1; r.cch0 = 160 * r.dg + r.m2; return r;
}
__device__ __forceinline__ Role fresh_role(int x) { asm volatile("" : "+r"(x)); return unpack_role(__shfl_sync(0xffffffffu, x, 0)); }
#define ROLE(x) const Role R_ = fresh_role(x); const int T1 = R_.T1, GP = R_.GP, side = R_.side, m2 = R_.m2, dg = R_.dg, cch0 = R_.cch0; \
  const bool last = R_.last, has2 = R_.has2; (void)T1; (void)GP; (void)side; (void)m2; (void)dg; (void)cch0; (void)last; (void)has2;
__device__ __forceinline__ int n_to_t(int n) {
  int T = n / 160, nl = n - T * 160;
  int L = (T == NT1 - 1) ? 32 : 40;
  return T * 160 + L * ((nl & 7) >> 1) + 2 * (nl >> 3) + (nl & 1);
}

template<int TA> __device__ __forceinline__ void wgmma_n160(float (&d)[80], uint32_t alo, uint32_t ahi, uint32_t blo, uint32_t bhi){
  asm volatile("{\n.reg .b64 da, db;\nmov.b64 da, {%80,%81};\nmov.b64 db, {%82,%83};\n"
    "wgmma.mma_async.sync.aligned.m64n160k16.f32.bf16.bf16 {%0, %1, %2, %3, %4, %5, %6, %7, %8, %9, %10, %11, %12, %13, %14, %15, %16, %17, %18, %19, %20, %21, %22, %23, %24, %25, %26, %27, %28, %29, %30, %31, %32, %33, %34, %35, %36, %37, %38, %39, %40, %41, %42, %43, %44, %45, %46, %47, %48, %49, %50, %51, %52, %53, %54, %55, %56, %57, %58, %59, %60, %61, %62, %63, %64, %65, %66, %67, %68, %69, %70, %71, %72, %73, %74, %75, %76, %77, %78, %79}, da, db, 1, 1, 1, %84, 0;\n}\n"
    : "+f"(d[0]), "+f"(d[1]), "+f"(d[2]), "+f"(d[3]), "+f"(d[4]), "+f"(d[5]), "+f"(d[6]), "+f"(d[7]), "+f"(d[8]), "+f"(d[9]), "+f"(d[10]), "+f"(d[11]), "+f"(d[12]), "+f"(d[13]), "+f"(d[14]), "+f"(d[15]), "+f"(d[16]), "+f"(d[17]), "+f"(d[18]), "+f"(d[19]), "+f"(d[20]), "+f"(d[21]), "+f"(d[22]), "+f"(d[23]), "+f"(d[24]), "+f"(d[25]), "+f"(d[26]), "+f"(d[27]), "+f"(d[28]), "+f"(d[29]), "+f"(d[30]), "+f"(d[31]), "+f"(d[32]), "+f"(d[33]), "+f"(d[34]), "+f"(d[35]), "+f"(d[36]), "+f"(d[37]), "+f"(d[38]), "+f"(d[39]), "+f"(d[40]), "+f"(d[41]), "+f"(d[42]), "+f"(d[43]), "+f"(d[44]), "+f"(d[45]), "+f"(d[46]), "+f"(d[47]), "+f"(d[48]), "+f"(d[49]), "+f"(d[50]), "+f"(d[51]), "+f"(d[52]), "+f"(d[53]), "+f"(d[54]), "+f"(d[55]), "+f"(d[56]), "+f"(d[57]), "+f"(d[58]), "+f"(d[59]), "+f"(d[60]), "+f"(d[61]), "+f"(d[62]), "+f"(d[63]), "+f"(d[64]), "+f"(d[65]), "+f"(d[66]), "+f"(d[67]), "+f"(d[68]), "+f"(d[69]), "+f"(d[70]), "+f"(d[71]), "+f"(d[72]), "+f"(d[73]), "+f"(d[74]), "+f"(d[75]), "+f"(d[76]), "+f"(d[77]), "+f"(d[78]), "+f"(d[79])
    : "r"(alo), "r"(ahi), "r"(blo), "r"(bhi), "n"(TA));
}
__device__ __forceinline__ void wgmma_rs_n160(float (&d)[80], uint32_t a0, uint32_t a1, uint32_t a2, uint32_t a3, uint32_t blo){
  asm volatile("{\n.reg .b64 db;\nmov.b64 db, {%84,8};\nwgmma.mma_async.sync.aligned.m64n160k16.f32.bf16.bf16 {%0, %1, %2, %3, %4, %5, %6, %7, %8, %9, %10, %11, %12, %13, %14, %15, %16, %17, %18, %19, %20, %21, %22, %23, %24, %25, %26, %27, %28, %29, %30, %31, %32, %33, %34, %35, %36, %37, %38, %39, %40, %41, %42, %43, %44, %45, %46, %47, %48, %49, %50, %51, %52, %53, %54, %55, %56, %57, %58, %59, %60, %61, %62, %63, %64, %65, %66, %67, %68, %69, %70, %71, %72, %73, %74, %75, %76, %77, %78, %79}, {%80,%81,%82,%83}, db, 1, 1, 1, 0;\n}\n"
    : "+f"(d[0]), "+f"(d[1]), "+f"(d[2]), "+f"(d[3]), "+f"(d[4]), "+f"(d[5]), "+f"(d[6]), "+f"(d[7]), "+f"(d[8]), "+f"(d[9]), "+f"(d[10]), "+f"(d[11]), "+f"(d[12]), "+f"(d[13]), "+f"(d[14]), "+f"(d[15]), "+f"(d[16]), "+f"(d[17]), "+f"(d[18]), "+f"(d[19]), "+f"(d[20]), "+f"(d[21]), "+f"(d[22]), "+f"(d[23]), "+f"(d[24]), "+f"(d[25]), "+f"(d[26]), "+f"(d[27]), "+f"(d[28]), "+f"(d[29]), "+f"(d[30]), "+f"(d[31]), "+f"(d[32]), "+f"(d[33]), "+f"(d[34]), "+f"(d[35]), "+f"(d[36]), "+f"(d[37]), "+f"(d[38]), "+f"(d[39]), "+f"(d[40]), "+f"(d[41]), "+f"(d[42]), "+f"(d[43]), "+f"(d[44]), "+f"(d[45]), "+f"(d[46]), "+f"(d[47]), "+f"(d[48]), "+f"(d[49]), "+f"(d[50]), "+f"(d[51]), "+f"(d[52]), "+f"(d[53]), "+f"(d[54]), "+f"(d[55]), "+f"(d[56]), "+f"(d[57]), "+f"(d[58]), "+f"(d[59]), "+f"(d[60]), "+f"(d[61]), "+f"(d[62]), "+f"(d[63]), "+f"(d[64]), "+f"(d[65]), "+f"(d[66]), "+f"(d[67]), "+f"(d[68]), "+f"(d[69]), "+f"(d[70]), "+f"(d[71]), "+f"(d[72]), "+f"(d[73]), "+f"(d[74]), "+f"(d[75]), "+f"(d[76]), "+f"(d[77]), "+f"(d[78]), "+f"(d[79])
    : "r"(a0), "r"(a1), "r"(a2), "r"(a3), "r"(blo));
}
template<int N> __device__ __forceinline__ void wgmma_rs_hi(float (&d)[64], uint32_t a0, uint32_t a1, uint32_t a2, uint32_t a3, uint32_t blo);
template<> __device__ __forceinline__ void wgmma_rs_hi<16>(float (&d)[64], uint32_t a0, uint32_t a1, uint32_t a2, uint32_t a3, uint32_t blo){
  asm volatile("{\n.reg .b64 db;\nmov.b64 db, {%12,8};\nwgmma.mma_async.sync.aligned.m64n16k16.f32.bf16.bf16 {%0, %1, %2, %3, %4, %5, %6, %7}, {%8,%9,%10,%11}, db, 1, 1, 1, 0;\n}\n"
    : "+f"(d[56]), "+f"(d[57]), "+f"(d[58]), "+f"(d[59]), "+f"(d[60]), "+f"(d[61]), "+f"(d[62]), "+f"(d[63])
    : "r"(a0), "r"(a1), "r"(a2), "r"(a3), "r"(blo));
}
template<> __device__ __forceinline__ void wgmma_rs_hi<32>(float (&d)[64], uint32_t a0, uint32_t a1, uint32_t a2, uint32_t a3, uint32_t blo){
  asm volatile("{\n.reg .b64 db;\nmov.b64 db, {%20,8};\nwgmma.mma_async.sync.aligned.m64n32k16.f32.bf16.bf16 {%0, %1, %2, %3, %4, %5, %6, %7, %8, %9, %10, %11, %12, %13, %14, %15}, {%16,%17,%18,%19}, db, 1, 1, 1, 0;\n}\n"
    : "+f"(d[48]), "+f"(d[49]), "+f"(d[50]), "+f"(d[51]), "+f"(d[52]), "+f"(d[53]), "+f"(d[54]), "+f"(d[55]), "+f"(d[56]), "+f"(d[57]), "+f"(d[58]), "+f"(d[59]), "+f"(d[60]), "+f"(d[61]), "+f"(d[62]), "+f"(d[63])
    : "r"(a0), "r"(a1), "r"(a2), "r"(a3), "r"(blo));
}
template<> __device__ __forceinline__ void wgmma_rs_hi<48>(float (&d)[64], uint32_t a0, uint32_t a1, uint32_t a2, uint32_t a3, uint32_t blo){
  asm volatile("{\n.reg .b64 db;\nmov.b64 db, {%28,8};\nwgmma.mma_async.sync.aligned.m64n48k16.f32.bf16.bf16 {%0, %1, %2, %3, %4, %5, %6, %7, %8, %9, %10, %11, %12, %13, %14, %15, %16, %17, %18, %19, %20, %21, %22, %23}, {%24,%25,%26,%27}, db, 1, 1, 1, 0;\n}\n"
    : "+f"(d[40]), "+f"(d[41]), "+f"(d[42]), "+f"(d[43]), "+f"(d[44]), "+f"(d[45]), "+f"(d[46]), "+f"(d[47]), "+f"(d[48]), "+f"(d[49]), "+f"(d[50]), "+f"(d[51]), "+f"(d[52]), "+f"(d[53]), "+f"(d[54]), "+f"(d[55]), "+f"(d[56]), "+f"(d[57]), "+f"(d[58]), "+f"(d[59]), "+f"(d[60]), "+f"(d[61]), "+f"(d[62]), "+f"(d[63])
    : "r"(a0), "r"(a1), "r"(a2), "r"(a3), "r"(blo));
}
template<> __device__ __forceinline__ void wgmma_rs_hi<64>(float (&d)[64], uint32_t a0, uint32_t a1, uint32_t a2, uint32_t a3, uint32_t blo){
  asm volatile("{\n.reg .b64 db;\nmov.b64 db, {%36,8};\nwgmma.mma_async.sync.aligned.m64n64k16.f32.bf16.bf16 {%0, %1, %2, %3, %4, %5, %6, %7, %8, %9, %10, %11, %12, %13, %14, %15, %16, %17, %18, %19, %20, %21, %22, %23, %24, %25, %26, %27, %28, %29, %30, %31}, {%32,%33,%34,%35}, db, 1, 1, 1, 0;\n}\n"
    : "+f"(d[32]), "+f"(d[33]), "+f"(d[34]), "+f"(d[35]), "+f"(d[36]), "+f"(d[37]), "+f"(d[38]), "+f"(d[39]), "+f"(d[40]), "+f"(d[41]), "+f"(d[42]), "+f"(d[43]), "+f"(d[44]), "+f"(d[45]), "+f"(d[46]), "+f"(d[47]), "+f"(d[48]), "+f"(d[49]), "+f"(d[50]), "+f"(d[51]), "+f"(d[52]), "+f"(d[53]), "+f"(d[54]), "+f"(d[55]), "+f"(d[56]), "+f"(d[57]), "+f"(d[58]), "+f"(d[59]), "+f"(d[60]), "+f"(d[61]), "+f"(d[62]), "+f"(d[63])
    : "r"(a0), "r"(a1), "r"(a2), "r"(a3), "r"(blo));
}
template<> __device__ __forceinline__ void wgmma_rs_hi<80>(float (&d)[64], uint32_t a0, uint32_t a1, uint32_t a2, uint32_t a3, uint32_t blo){
  asm volatile("{\n.reg .b64 db;\nmov.b64 db, {%44,8};\nwgmma.mma_async.sync.aligned.m64n80k16.f32.bf16.bf16 {%0, %1, %2, %3, %4, %5, %6, %7, %8, %9, %10, %11, %12, %13, %14, %15, %16, %17, %18, %19, %20, %21, %22, %23, %24, %25, %26, %27, %28, %29, %30, %31, %32, %33, %34, %35, %36, %37, %38, %39}, {%40,%41,%42,%43}, db, 1, 1, 1, 0;\n}\n"
    : "+f"(d[24]), "+f"(d[25]), "+f"(d[26]), "+f"(d[27]), "+f"(d[28]), "+f"(d[29]), "+f"(d[30]), "+f"(d[31]), "+f"(d[32]), "+f"(d[33]), "+f"(d[34]), "+f"(d[35]), "+f"(d[36]), "+f"(d[37]), "+f"(d[38]), "+f"(d[39]), "+f"(d[40]), "+f"(d[41]), "+f"(d[42]), "+f"(d[43]), "+f"(d[44]), "+f"(d[45]), "+f"(d[46]), "+f"(d[47]), "+f"(d[48]), "+f"(d[49]), "+f"(d[50]), "+f"(d[51]), "+f"(d[52]), "+f"(d[53]), "+f"(d[54]), "+f"(d[55]), "+f"(d[56]), "+f"(d[57]), "+f"(d[58]), "+f"(d[59]), "+f"(d[60]), "+f"(d[61]), "+f"(d[62]), "+f"(d[63])
    : "r"(a0), "r"(a1), "r"(a2), "r"(a3), "r"(blo));
}
template<> __device__ __forceinline__ void wgmma_rs_hi<96>(float (&d)[64], uint32_t a0, uint32_t a1, uint32_t a2, uint32_t a3, uint32_t blo){
  asm volatile("{\n.reg .b64 db;\nmov.b64 db, {%52,8};\nwgmma.mma_async.sync.aligned.m64n96k16.f32.bf16.bf16 {%0, %1, %2, %3, %4, %5, %6, %7, %8, %9, %10, %11, %12, %13, %14, %15, %16, %17, %18, %19, %20, %21, %22, %23, %24, %25, %26, %27, %28, %29, %30, %31, %32, %33, %34, %35, %36, %37, %38, %39, %40, %41, %42, %43, %44, %45, %46, %47}, {%48,%49,%50,%51}, db, 1, 1, 1, 0;\n}\n"
    : "+f"(d[16]), "+f"(d[17]), "+f"(d[18]), "+f"(d[19]), "+f"(d[20]), "+f"(d[21]), "+f"(d[22]), "+f"(d[23]), "+f"(d[24]), "+f"(d[25]), "+f"(d[26]), "+f"(d[27]), "+f"(d[28]), "+f"(d[29]), "+f"(d[30]), "+f"(d[31]), "+f"(d[32]), "+f"(d[33]), "+f"(d[34]), "+f"(d[35]), "+f"(d[36]), "+f"(d[37]), "+f"(d[38]), "+f"(d[39]), "+f"(d[40]), "+f"(d[41]), "+f"(d[42]), "+f"(d[43]), "+f"(d[44]), "+f"(d[45]), "+f"(d[46]), "+f"(d[47]), "+f"(d[48]), "+f"(d[49]), "+f"(d[50]), "+f"(d[51]), "+f"(d[52]), "+f"(d[53]), "+f"(d[54]), "+f"(d[55]), "+f"(d[56]), "+f"(d[57]), "+f"(d[58]), "+f"(d[59]), "+f"(d[60]), "+f"(d[61]), "+f"(d[62]), "+f"(d[63])
    : "r"(a0), "r"(a1), "r"(a2), "r"(a3), "r"(blo));
}
template<> __device__ __forceinline__ void wgmma_rs_hi<112>(float (&d)[64], uint32_t a0, uint32_t a1, uint32_t a2, uint32_t a3, uint32_t blo){
  asm volatile("{\n.reg .b64 db;\nmov.b64 db, {%60,8};\nwgmma.mma_async.sync.aligned.m64n112k16.f32.bf16.bf16 {%0, %1, %2, %3, %4, %5, %6, %7, %8, %9, %10, %11, %12, %13, %14, %15, %16, %17, %18, %19, %20, %21, %22, %23, %24, %25, %26, %27, %28, %29, %30, %31, %32, %33, %34, %35, %36, %37, %38, %39, %40, %41, %42, %43, %44, %45, %46, %47, %48, %49, %50, %51, %52, %53, %54, %55}, {%56,%57,%58,%59}, db, 1, 1, 1, 0;\n}\n"
    : "+f"(d[8]), "+f"(d[9]), "+f"(d[10]), "+f"(d[11]), "+f"(d[12]), "+f"(d[13]), "+f"(d[14]), "+f"(d[15]), "+f"(d[16]), "+f"(d[17]), "+f"(d[18]), "+f"(d[19]), "+f"(d[20]), "+f"(d[21]), "+f"(d[22]), "+f"(d[23]), "+f"(d[24]), "+f"(d[25]), "+f"(d[26]), "+f"(d[27]), "+f"(d[28]), "+f"(d[29]), "+f"(d[30]), "+f"(d[31]), "+f"(d[32]), "+f"(d[33]), "+f"(d[34]), "+f"(d[35]), "+f"(d[36]), "+f"(d[37]), "+f"(d[38]), "+f"(d[39]), "+f"(d[40]), "+f"(d[41]), "+f"(d[42]), "+f"(d[43]), "+f"(d[44]), "+f"(d[45]), "+f"(d[46]), "+f"(d[47]), "+f"(d[48]), "+f"(d[49]), "+f"(d[50]), "+f"(d[51]), "+f"(d[52]), "+f"(d[53]), "+f"(d[54]), "+f"(d[55]), "+f"(d[56]), "+f"(d[57]), "+f"(d[58]), "+f"(d[59]), "+f"(d[60]), "+f"(d[61]), "+f"(d[62]), "+f"(d[63])
    : "r"(a0), "r"(a1), "r"(a2), "r"(a3), "r"(blo));
}
template<> __device__ __forceinline__ void wgmma_rs_hi<128>(float (&d)[64], uint32_t a0, uint32_t a1, uint32_t a2, uint32_t a3, uint32_t blo){
  asm volatile("{\n.reg .b64 db;\nmov.b64 db, {%68,8};\nwgmma.mma_async.sync.aligned.m64n128k16.f32.bf16.bf16 {%0, %1, %2, %3, %4, %5, %6, %7, %8, %9, %10, %11, %12, %13, %14, %15, %16, %17, %18, %19, %20, %21, %22, %23, %24, %25, %26, %27, %28, %29, %30, %31, %32, %33, %34, %35, %36, %37, %38, %39, %40, %41, %42, %43, %44, %45, %46, %47, %48, %49, %50, %51, %52, %53, %54, %55, %56, %57, %58, %59, %60, %61, %62, %63}, {%64,%65,%66,%67}, db, 1, 1, 1, 0;\n}\n"
    : "+f"(d[0]), "+f"(d[1]), "+f"(d[2]), "+f"(d[3]), "+f"(d[4]), "+f"(d[5]), "+f"(d[6]), "+f"(d[7]), "+f"(d[8]), "+f"(d[9]), "+f"(d[10]), "+f"(d[11]), "+f"(d[12]), "+f"(d[13]), "+f"(d[14]), "+f"(d[15]), "+f"(d[16]), "+f"(d[17]), "+f"(d[18]), "+f"(d[19]), "+f"(d[20]), "+f"(d[21]), "+f"(d[22]), "+f"(d[23]), "+f"(d[24]), "+f"(d[25]), "+f"(d[26]), "+f"(d[27]), "+f"(d[28]), "+f"(d[29]), "+f"(d[30]), "+f"(d[31]), "+f"(d[32]), "+f"(d[33]), "+f"(d[34]), "+f"(d[35]), "+f"(d[36]), "+f"(d[37]), "+f"(d[38]), "+f"(d[39]), "+f"(d[40]), "+f"(d[41]), "+f"(d[42]), "+f"(d[43]), "+f"(d[44]), "+f"(d[45]), "+f"(d[46]), "+f"(d[47]), "+f"(d[48]), "+f"(d[49]), "+f"(d[50]), "+f"(d[51]), "+f"(d[52]), "+f"(d[53]), "+f"(d[54]), "+f"(d[55]), "+f"(d[56]), "+f"(d[57]), "+f"(d[58]), "+f"(d[59]), "+f"(d[60]), "+f"(d[61]), "+f"(d[62]), "+f"(d[63])
    : "r"(a0), "r"(a1), "r"(a2), "r"(a3), "r"(blo));
}

struct CvCtx {
  uint32_t koff, zero, so[3];
  int srcA, srcB;
  bool wrapA, s3, kodd;
};
struct CvPipe { uint32_t Ap, Ep, keep, send; };
template <int LO> __device__ __forceinline__ void cv_copy(float (&acc)[64]) {
#pragma unroll
  for (int i = LO; i < 64; i++) { float t; asm volatile("mov.b32 %0, %1;" : "=f"(t) : "f"(acc[i]) : "memory"); acc[i] = t; }
}
template <int G> __device__ __forceinline__ void cv_raw(uint32_t (&A)[4][4], uint32_t kaddr) {
#pragma unroll
  for (int i = 0; i < 4; i++) {
    const uint32_t a = kaddr + (4 * G + i) * 128;
    A[i][0] = lds32(a); A[i][1] = lds32(a + 4); A[i][3] = lds32(a + 8);
  }
}
__device__ __forceinline__ void cv_form(uint32_t (&A)[4][4], uint32_t sel) {
#pragma unroll
  for (int i = 0; i < 4; i++) {
    asm volatile("prmt.b32 %0, %0, %1, %2;" : "+r"(A[i][0]) : "r"(A[i][1]), "r"(sel));
    asm volatile("prmt.b32 %0, %1, %2, %3;" : "=r"(A[i][2]) : "r"(A[i][1]), "r"(A[i][3]), "r"(sel));
  }
}
#define CVV 2
template <int G> __device__ __forceinline__ void cv_step(float (&acc)[64], uint32_t (&A)[4][4], CvPipe& s, const CvCtx& c, uint32_t cb, uint32_t stg) {
  constexpr int JA = G - 1, JB = G - 2, NH = CVV == 1 ? 4 : (CVV == 3 ? 2 : 1);
  const uint32_t db0 = desc_lo(cb + CV_U + 192, CV_PL);
  uint32_t B[4][4];
  uint32_t ra[2], rb;
  if constexpr (G < 8) {
    wgmma_fence();
#pragma unroll
    for (int i = 0; i < NH; i++) wgmma_rs_hi<128 - 16 * (G & 7)>(acc, A[i][0], A[i][1], A[i][2], A[i][3], db0 - 4 * i);
    wgmma_commit();
    __syncwarp();
  }
  if constexpr (JA >= 0 && JA < 8) {
    const uint32_t p0 = pack_bf16(acc[8 * JA + 1], acc[8 * JA + 3]), p1 = pack_bf16(acc[8 * JA + 5], acc[8 * JA + 7]);
    ra[0] = __shfl_sync(0xffffffffu, c.wrapA ? s.Ap : p0, c.srcA);
    ra[1] = __shfl_sync(0xffffffffu, c.wrapA ? p0 : p1, c.srcA);
    s.Ap = p1;
  }
  if constexpr (JB >= 0) rb = __shfl_sync(0xffffffffu, s.send, c.srcB);
  if constexpr (G < 7) cv_raw<G + 1>(B, cb + c.koff);
  uint32_t z = 0;
  if constexpr (G < 8 && NH < 4) {
    __syncwarp();
    wgmma_fence();
#pragma unroll
    for (int i = NH; i < 4; i++) wgmma_rs_hi<128 - 16 * (G & 7)>(acc, A[i][0], A[i][1], A[i][2], A[i][3], db0 - 4 * i);
    wgmma_commit();
    asm volatile("mov.u32 %0, %%clock;" : "=r"(z)::"memory");
    z &= c.zero;
  }
  if constexpr (G < 7) cv_form(B, 0x5432u | z);
  if constexpr (JB >= 0) sts32(stg + ((c.so[JB / 3] >> (10 * (JB % 3))) & 0xffc), hadd2(rb | z, s.keep));
  if constexpr (JA >= 0 && JA < 8) {
    const uint32_t sh = 16 | z, mk = 0xffff0000u | z;
    const uint32_t ev = pack_bf16(acc[8 * JA] + __uint_as_float(ra[0] << sh), acc[8 * JA + 2] + __uint_as_float(ra[0] & mk));
    const uint32_t od = pack_bf16(acc[8 * JA + 4] + __uint_as_float(ra[1] << sh), acc[8 * JA + 6] + __uint_as_float(ra[1] & mk));
    s.send = c.kodd ? ev : (c.s3 ? s.Ep : od);
    s.keep = c.kodd ? od : ev;
    s.Ep = od;
  }
  if constexpr (G < 8) { __syncwarp(); wgmma_wait<0>(); cv_copy<8 * (G & 7)>(acc); }
  if constexpr (G < 9) cv_step<G + 1>(acc, B, s, c, cb, stg);
}
__device__ __forceinline__ uint32_t cv_stage(int slot) { return sb + (slot < 4 ? 40960 + slot * 4096 : CV_OFF + CV_K); }
__device__ __forceinline__ void cv_setup(CvCtx& c) {
  const int tid = tid_opaque() & 127, w = tid >> 5, lane = tid & 31, r = lane >> 2, q = lane & 3;
  const int i0 = (r >> 1) & 1, i1 = r >> 2;
  c.koff = CV_K - 32 + 4 * (8 * (r >> 1) + 2 * w + (r & 1) + 2 * q);
  c.srcA = i0 ? lane - 8 : lane + 8 - q + ((q + 3) & 3);
  c.wrapA = i0 && q == 3;
  c.srcB = i1 == 0 ? (lane - q + 16 + ((q + 3) & 3)) : (lane - q - 16 + ((q + 1) & 3));
  c.s3 = (i1 == 1 && q == 3); c.kodd = (i1 == 1 && q < 3);
  c.zero = lds32(sb + EP_OFF + 24);
#pragma unroll
  for (int i = 0; i < 3; i++) c.so[i] = lds32(sb + SO_OFF + 512 * i + 4 * tid);
}
__device__ __forceinline__ void cv_table() {
  const int tid = tid_opaque() & 127, r = (tid & 31) >> 2, q = tid & 3;
  int t = 16 * (2 * (r < 4 ? q : 4 + ((q + 1) & 3)) + ((r >> 1) & 1)) + 4 * (tid >> 5) + 2 * (r & 1);
#pragma unroll 1
  for (int i = 0; i < 3; i++) {
    uint32_t v = 0;
#pragma unroll 1
    for (int x = 0; x < 3; x++, t += 256) {
      const int T = t / 160, tl = t - T * 160;
      const int qq = (T >= NT1 - 1) ? (tl >> 5) : (tl / 40);
      int ck = 20 * T + ((tl - qq * ((T >= NT1 - 1) ? 32 : 40)) >> 1);
      ck ^= (ck >> 2) & 6;
      v |= (uint32_t)((ck * 4 + qq) & 1023) << (10 * x + 2);
    }
    sts32(sb + SO_OFF + 512 * i + 4 * tid, v);
  }
}
__device__ __forceinline__ void conv_channel(int slot, const CvCtx& c) {
  const uint32_t cb = sb + CV_OFF + slot * CV_B;
  float acc[64];
  CvPipe s;
  s.Ap = s.Ep = 0u;
  uint32_t A[4][4];
#pragma unroll
  for (int i = 0; i < 64; i++) acc[i] = 0.f;
  if (slot == 4) mbar_wait(bars + 8 * B_CVDONE);
  mbar_wait(bars + 8 * (B_CVFULL + slot));
  cv_raw<0>(A, cb + c.koff);
  {
    const uint32_t w0 = lds32(cb + CV_K);
    const uint32_t wp = __byte_perm(pack_bf16(bf_lo(w0) + __uint_as_float(lds32(sb + EP_OFF + 4 * slot)), 0.f), w0, 0x7610);
    if (c.koff == CV_K) A[0][0] = wp;
    if (c.koff == CV_K - 4) A[0][1] = wp;
    if (c.koff == CV_K - 8) A[0][3] = wp;
  }
  cv_form(A, 0x5432u);
  cv_copy<0>(acc);
  cv_step<0>(acc, A, s, c, cb, cv_stage(slot));
  fence_async_smem();
  mbar_arrive(bars + 8 * (B_CVDONE + slot));
}

__device__ __forceinline__ void kv_issue(const Params& p, int c, int m2, int dg) {
  const uint32_t fb = bars + 8 * (B_KV + c);
  mbar_expect_tx(fb, KV_PIECE);
  tma3(sb + KS_OFF + c * KV_PIECE, &p.mK, 160 * dg + 32 * c, 64 * m2 - 3, 0, fb);
  tma3(sb + KS_OFF + c * KV_PIECE + 4864, &p.mV, 160 * dg + 32 * c, 64 * m2 - 1, 0, fb);
}
__device__ __forceinline__ void kv_tile(int m, int c, int y, uint32_t (&o)[4][4]) {
  const int lane = tid_opaque() & 31, tg = lane & 3, pr = 8 * (y ^ (tg >> 1)) + (lane >> 2);
  const uint32_t pb = sb + KS_OFF + c * KV_PIECE + 4 * pr;
  const uint32_t ka = pb + tg * 1216, va = pb + 4864 + tg * 1088 + 64;
  const uint32_t kh = (m == 0 && tg > 0) ? ka - 192 : ka;
  uint32_t kk[19], u[16];
  const float4 t = lds128f(sb + TAP_OFF + 256 * c + 16 * pr);
#pragma unroll
  for (int i = 0; i < 19; i++) { kk[i] = lds32((i < 3 ? kh : ka) + i * 64); if (i >= 3) u[i - 3] = lds32(va + (i - 3) * 64); }
  const uint32_t dst = sb + KS_OFF + c * KV_PIECE + pr * 64 + tg * 16;
  if (y) {
    __syncwarp();
#pragma unroll
    for (int x = 0; x < 4; x++) sts128((dst ^ 512) + x * 1024, make_uint4(o[x][0], o[x][1], o[x][2], o[x][3]));
  }
  const uint32_t w0 = __byte_perm(__float_as_uint(t.x), __float_as_uint(t.z), 0x5410), w1 = __byte_perm(__float_as_uint(t.x), __float_as_uint(t.z), 0x7632);
  const uint32_t w2 = __byte_perm(__float_as_uint(t.y), __float_as_uint(t.w), 0x5410), w3 = __byte_perm(__float_as_uint(t.y), __float_as_uint(t.w), 0x7632);
#pragma unroll
  for (int i = 0; i < 16; i++) {
    uint32_t a = hmul2(kk[i], w3);
    a = hadd2(a, hmul2(kk[i + 1], w2)); a = hadd2(a, hmul2(kk[i + 2], w1)); a = hadd2(a, hmul2(kk[i + 3], w0));
    u[i] = hmul2(a, u[i]);
  }
#pragma unroll
  for (int x = 0; x < 4; x++) {
#pragma unroll
    for (int qq = 0; qq < 4; qq++) o[x][qq] = __byte_perm(u[15 - 4 * qq - (x & 2)], u[14 - 4 * qq - (x & 2)], (x & 1) ? 0x7632 : 0x5410);
    if (y) sts128(dst + x * 1024, make_uint4(o[x][0], o[x][1], o[x][2], o[x][3]));
  }
}
__device__ __forceinline__ void ln_finish(float s1, float s2, float& mean, float& rstd) {
  mean = s1 * (1.f / 640.f);
  const float v = fmaxf(fmaf(-mean, mean, s2 * (1.f / 640.f)), 0.f) + 1e-5f;
  asm("rsqrt.approx.ftz.f32 %0, %1;" : "=f"(rstd) : "f"(v));
}
__device__ __forceinline__ void stat_table(int T1, unsigned want, int l, int g, const uint4* x0, const uint4* x1, float (&xa)[2], float (&xb)[2]) {
  const int n = 32 * g + (tid_opaque() & 31);
  const uint4* rp = &g_stats[8 * l * SEQ + min(160 * T1 + n, SEQ - 1)];
  float a[4], b[4];
  uint32_t it = 0;
  while (true) {
    bool ok = true;
#pragma unroll
    for (int i = 0; i < 4; i++) ok &= (rec_ld(rp + SEQ * i, a[i], b[i]) == want);
    ok &= rec_ld(x0, xa[0], xb[0]) == want;
    ok &= rec_ld(x1, xa[1], xb[1]) == want;
    if (__all_sync(0xffffffffu, ok)) break;
    trap_if(++it > SPIN_LIMIT);
  }
  float m, rs;
  ln_finish((a[0] + a[1]) + (a[2] + a[3]), (b[0] + b[1]) + (b[2] + b[3]), m, rs);
  sts32(sb + STAB_OFF + ((n >> 1) & 3) * 160 + (n >> 3) * 8 + (n & 1) * 4, __float_as_uint(rs));
  const uint32_t hi = pack_bf16(-m, -m);
  const float lo = -m - bf_lo(hi);
  sts128(sb + (l ? MX1_OFF : MX0_OFF) + n * 16, make_uint4(hi, pack_bf16(lo, lo), 0u, 0u));
  fence_async_smem();
}
__device__ __forceinline__ void stats_reduce(float (&a)[2], float (&b)[2], float (&mean)[2], float (&rstd)[2]) {
#pragma unroll
  for (int o = 1; o < 4; o <<= 1)
#pragma unroll
    for (int h = 0; h < 2; h++) { a[h] += __shfl_xor_sync(0xffffffffu, a[h], o); b[h] += __shfl_xor_sync(0xffffffffu, b[h], o); }
#pragma unroll
  for (int h = 0; h < 2; h++) ln_finish(a[h], b[h], mean[h], rstd[h]);
}

template <bool FIRST>
__device__ __forceinline__ void stats_publish(int which, int n0, int dg, unsigned tag, const float (&acc)[80]) {
  const int q = tid_opaque() & 3, h = q & 1;
  float s1[2] = {0.f, 0.f}, s2[2] = {0.f, 0.f}, t1[2] = {0.f, 0.f}, t2[2] = {0.f, 0.f};
#pragma unroll
  for (int j = 0; j < 20; j++)
#pragma unroll
    for (int y = 0; y < 2; y++) {
      const float a = acc[4 * j + 2 * y], b = acc[4 * j + 2 * y + 1];
      s1[y] += a; t1[y] += b; s2[y] = fmaf(a, a, s2[y]); t2[y] = fmaf(b, b, t2[y]);
    }
#pragma unroll
  for (int y = 0; y < 2; y++) { s1[y] += t1[y]; s2[y] += t2[y]; }
  float a = (h ? s1[1] : s1[0]) + __shfl_xor_sync(0xffffffffu, h ? s1[0] : s1[1], 1);
  float b = (h ? s2[1] : s2[0]) + __shfl_xor_sync(0xffffffffu, h ? s2[0] : s2[1], 1);
  a += __shfl_xor_sync(0xffffffffu, a, 2);
  b += __shfl_xor_sync(0xffffffffu, b, 2);
  if (FIRST) {
    rec_st(&g_stats[((q >> 1) * 4 + dg) * SEQ + n0 + 8 * h], a, b, q < 2 ? tag : tag - 1);
    rec_st(&g_stats[((q >> 1) * 4 + 8 + dg) * SEQ + n0 + 8 * h], a, b, tag - 1);
  } else if (q < 2) rec_st(&g_stats[(which * 4 + dg) * SEQ + n0 + 8 * h], a, b, tag);
}
__device__ __forceinline__ void stats_get(int which, int n0, unsigned tag, float (&mean)[2], float (&rstd)[2]) {
  const uint4* p0 = &g_stats[(which * 4 + (tid_opaque() & 3)) * SEQ + n0];
  float a[2], b[2];
  uint32_t it = 0;
  while (true) {
    const unsigned t0 = rec_ld(p0, a[0], b[0]), t1 = rec_ld(p0 + 8, a[1], b[1]);
    if (__all_sync(0xffffffffu, t0 == tag && t1 == tag)) break;
    trap_if(++it > SPIN_LIMIT);
  }
  stats_reduce(a, b, mean, rstd);
}
__device__ __forceinline__ void x0_load(float (&acc)[80]) {
  const int t = tid_opaque() & 127;
  const uint32_t xa = sb + XT_OFF + (16 * (t >> 5) + ((t & 31) >> 2)) * 320 + 8 * (t & 3);
  mbar_wait(bars + 8 * B_XT);
#pragma unroll
  for (int h = 0; h < 2; h++)
#pragma unroll
    for (int J = 0; J < 10; J++) {
      const float2 v = lds64f(xa + h * 2560 + 32 * J);
      const uint32_t x = __float_as_uint(v.x), y = __float_as_uint(v.y);
      acc[8 * J + 2 * h] = bf_lo(x); acc[8 * J + 2 * h + 1] = bf_hi(x);
      acc[8 * J + 4 + 2 * h] = bf_lo(y); acc[8 * J + 4 + 2 * h + 1] = bf_hi(y);
    }
}

template <bool FROM_X0>
__device__ __forceinline__ void dskip_init(float (&acc)[80], const float (&mean)[2], const float (&rstd)[2]) {
  const int t = tid_opaque() & 127;
  const uint32_t xa = sb + XT_OFF + (16 * (t >> 5) + ((t & 31) >> 2)) * 320 + 8 * (t & 3), da = sb + DTAB_OFF + 8 * (t & 3);
  float2 dw[10], xv[10][2];
#pragma unroll
  for (int J = 0; J < 2; J++) { dw[J] = lds64f(da + 32 * J); if (FROM_X0) { xv[J][0] = lds64f(xa + 32 * J); xv[J][1] = lds64f(xa + 2560 + 32 * J); } }
#pragma unroll
  for (int J = 0; J < 10; J++) {
    if (J + 2 < 10) { dw[J + 2] = lds64f(da + 32 * (J + 2)); if (FROM_X0) { xv[J + 2][0] = lds64f(xa + 32 * (J + 2)); xv[J + 2][1] = lds64f(xa + 2560 + 32 * (J + 2)); } }
#pragma unroll
    for (int x = 0; x < 8; x++) {
      const int h = (x >> 1) & 1;
      const uint32_t dwd = __float_as_uint(x < 4 ? dw[J].x : dw[J].y);
      const float tt = fmaf(rstd[h], (x & 1) ? bf_hi(dwd) : bf_lo(dwd), 1.f);
      float a = acc[8 * J + x];
      if (FROM_X0) { const uint32_t xw = __float_as_uint(x < 4 ? xv[J][h].x : xv[J][h].y); a = (x & 1) ? bf_hi(xw) : bf_lo(xw); }
      acc[8 * J + x] = FROM_X0 ? (a - mean[h]) * tt : fmaf(a, tt, -mean[h] * tt);
    }
  }
}

__global__ void __launch_bounds__(512, 1) fused_kernel(const __grid_constant__ Params p) {
  extern __shared__ __align__(1024) uint8_t smem_raw[];
  const int tid = threadIdx.x, lane = tid & 31;
  const int wid = __shfl_sync(0xffffffffu, tid >> 5, 0), wg = wid >> 2;
  unsigned smid; asm volatile("mov.u32 %0, %%smid;" : "=r"(smid));
  const int role = p.role[min(smid, 131u)];
  if (wid == 12) {
    const bool el = elect_one();
    if (el) {
      asm volatile("prefetch.tensormap [%0];" ::"l"(&p.mB) : "memory");
      asm volatile("prefetch.tensormap [%0];" ::"l"((role & 15) == NT1 - 1 ? &p.mXl : &p.mX) : "memory");
#pragma unroll
      for (int k = 0; k < S1; k++) mbar_init(bars + 8 * (B_G1FULL + k), 1);
#pragma unroll
      for (int k = 0; k < 6; k++) mbar_init(bars + 8 * (B_XT + k), 1);
      asm volatile("fence.mbarrier_init.release.cluster;" ::: "memory");
    }
    if (role >= 0) {
      __syncwarp();
      asm volatile("bar.arrive 5, 288;" ::: "memory");
      const Role R = unpack_role(role);
      if (elect_one()) {
        TS(45);
#pragma unroll 1
        for (int k = 0; k < S1; k++) {
          const uint32_t fb = bars + 8 * (B_G1FULL + k);
          mbar_expect_tx(fb, G1_STAGE);
          tma4(sb + k * G1_STAGE + G1_XOFF, R.last ? &p.mXl : &p.mX, 64 * k, 0, 0, R.last ? 0 : 80 * R.T1, fb);
          tma5(sb + k * G1_STAGE, &p.mB, 64 * k, 0, 0, 4 * R.side, 2 * R.GP, fb);
          if (PFD) asm volatile("prefetch.tensormap [%0];" ::"l"(&p.mK + k) : "memory");
        }
        if (R.has2) {
          mbar_expect_tx(bars + 8 * B_XT, 20480);
#pragma unroll 1
          for (int h = 0; h < 2; h++) {
            const int ng = 8 * R.m2 + 4 * h, T = ng / 20;
            tma4(sb + XT_OFF + h * 10240, T == NT1 - 1 ? &p.mXtl : &p.mXt, 160 * R.dg, 0, 0, T == NT1 - 1 ? ng - 240 : ng + 60 * T, bars + 8 * B_XT);
          }
#pragma unroll 1
          for (int c = 0; c < KV0; c++) kv_issue(p, c, R.m2, R.dg);
        }
        TS(44);
      }
      __syncwarp();
      bar_sync(6, 64);
    }
  }
  trap_if(smid >= 132 || smem_u32(smem_raw) != sb);
  if (role < 0) {
    if (wid == 0) {
      const unsigned tag = ld_rlx(g_epoch);
      uint32_t it = 0;
      while (!__all_sync(0xffffffffu, (int)(ld_rlx(&g_hcnt[(lane & 7) * 32]) - 40 * tag) >= 0)) { __nanosleep(500); trap_if(++it > SPIN_LIMIT); }
    }
    return;
  }
  float mean0[2] = {0.f, 0.f}, rstd0[2] = {0.f, 0.f};
  if (wg == 2 || wid == 14) {
    ROLE(role)
    const int c = wid == 14 ? 4 : wid - 8;
    const unsigned tag = ld_rlx(g_epoch);
    if (has2) {
      uint2 bv[2][5];
#pragma unroll
      for (int x = 0; x < 2; x++)
#pragma unroll
        for (int i = 0; i < 5; i++) bv[x][i] = ldv64((const uint2*)((x ? p.bim : p.bre) + (cch0 + 32 * c) * DM) + lane + 32 * i);
      float sv[2];
#pragma unroll
      for (int x = 0; x < 2; x++) {
        float a = 0.f;
#pragma unroll
        for (int i = 0; i < 5; i++) a += (bf_lo(bv[x][i].x) + bf_hi(bv[x][i].x)) + (bf_lo(bv[x][i].y) + bf_hi(bv[x][i].y));
        sv[x] = a;
      }
#pragma unroll
      for (int o = 16; o > 0; o >>= 1) { sv[0] += __shfl_xor_sync(0xffffffffu, sv[0], o); sv[1] += __shfl_xor_sync(0xffffffffu, sv[1], o); }
      if (lane < 2) rec_st(&g_sB[(cch0 + 32 * c) * 2 + lane], sv[0], sv[1], tag);
      if (tid == 256) TS(47);
      __syncwarp();
      bar_sync(8, 192);
      if (wg == 2) {
        float xs[80];
        x0_load(xs);
        stats_publish<true>(0, 64 * m2 + 16 * c + (lane >> 2), dg, tag, xs);
        if (tid == 256) TS(31);
      }
      mbar_wait(bars + 8 * B_EP);
      mbar_wait(bars + 8 * (B_KV + c));
      mbar_wait(bars + 8 * (B_G1DONE + PAUSE_K - 1));
      if (tid == 448) TS(52);
      uint32_t o[4][4] = {};
#pragma unroll 1
      for (int y = 0; y < 2; y++) kv_tile(m2, c, y, o);
      fence_async_smem();
      __syncwarp();
      if (lane == 0) { mbar_arrive(bars + 8 * B_PREP); mbar_arrive(bars + 8 * (B_PD + c)); }
      if (tid == 448) TS(51);
    } else bar_sync(8, 192);
    {
      const uint4* x0 = wg == 2 ? &g_stats[(lane & 3) * SEQ + (has2 ? 64 * m2 : 0) + 16 * c + (lane >> 2)] : &g_sB[(128 * GP + 32 * side + lane) * 2];
      float xa[2], xb[2];
      stat_table(T1, tag, 0, c, x0, x0 + (wg == 2 ? 8 : 128), xa, xb);
      if (wg == 2) stats_reduce(xa, xb, mean0, rstd0);
      else {
#pragma unroll
        for (int i = 0; i < 2; i++) {
          const float ha = bf_lo(pack_bf16(xa[i], 0.f)), hb = bf_lo(pack_bf16(xb[i], 0.f));
          const float pa = __uint_as_float(pack_bf16(ha, xa[i] - ha)), pb = __uint_as_float(pack_bf16(hb, xb[i] - hb));
          sts64f(sb + CTAB_OFF + (32 * i + lane) * 24 + 16, p.swap ? pb : pa, p.swap ? pa : pb);
        }
      }
      mbar_arrive(bars + 8 * B_STAB);
      if (tid == 448) TS(26);
    }
  } else if (wid == 15) {
    ROLE(role)
    const int ch = 128 * GP + 32 * side + lane;
    uint32_t r0 = ldv16(p.lre + ch), r1 = ldv16(p.lim + ch), r2 = ldv16(p.logdt + ch);
    const uint32_t r3 = ldv16(p.lre + ch + 64), r4 = ldv16(p.lim + ch + 64), r5 = ldv16(p.logdt + ch + 64);
#pragma unroll 1
    for (int i = 0; i < 2; i++) {
      const float lr = bf_lo(r0), li = bf_lo(r1);
      const float dt = __bfloat162float(__float2bfloat16_rn(expf(bf_lo(r2))));
      const float mag = expf(dt * lr);
      float sn, cs; sincospif(dt * li * 0.31830988618379067f, &sn, &cs);
      const float ar = mag * cs, ai = mag * sn;
      const float inv = 2.f / (lr * lr + li * li);
      const uint32_t ad = sb + CTAB_OFF + (32 * i + lane) * 24;
      sts64f(ad, ar, ai);
      sts64f(ad + 8, ((ar - 1.f) * lr + ai * li) * inv, (ai * lr - (ar - 1.f) * li) * inv);
      r0 = r3; r1 = r4; r2 = r5;
    }
    if (lane == 0) TS(46);
    __syncwarp();
    bar_sync(7, 64);
    mbar_arrive(bars + 8 * B_CTAB);
  } else if (wid == 13) {
    ROLE(role)
    uint4 tv[3];
    const uint32_t e0 = ld_rlx(g_epoch);
    const uint32_t e1 = ldv16(p.ssmD + min(cch0 + 32 * lane, 639));
    const uint4 dv = ldv128((const uint4*)(p.dskip + 160 * dg) + min(lane, 19));
#pragma unroll
    for (int i = 0; i < 3; i++) tv[i] = ldv128((const uint4*)(p.shiftk + 640 * dg) + min(lane + 32 * i, 79));
    sts128(sb + DTAB_OFF + 16 * min(lane, 19), dv);
#pragma unroll
    for (int i = 0; i < 3; i++) sts128(sb + TAP_OFF + 16 * min(lane + 32 * i, 79), tv[i]);
    if (lane < 7) sts32(sb + EP_OFF + 4 * lane, lane < 5 ? e1 << 16 : (lane == 5 ? e0 : 0u));
    __syncwarp();
    bar_sync(9, 64);
    mbar_arrive(bars + 8 * B_CTAB);
    if (lane == 0) { mbar_arrive(bars + 8 * B_EP); TS(53); }
    if (has2) {
#pragma unroll 1
      for (int i = 0; i < 5; i++) {
        const int c = i == 2 ? 3 : (i == 3 ? 2 : i);
        mbar_wait(bars + 8 * (B_PD + c));
        if (lane == 0) bulk_s2g(g_kv + (dg * 32 + m2) * 20480 + c * 4096, sb + KS_OFF + c * KV_PIECE, 4096);
      }
      if (lane == 0) {
        asm volatile("cp.async.bulk.commit_group;" ::: "memory");
        asm volatile("cp.async.bulk.wait_group 0;" ::: "memory");
        mbar_arrive(bars + 8 * B_PREP2);
        fence_async_global();
      }
      __syncwarp();
      if (lane < 4) red_rel(&g_kvcnt[(dg * 4 + lane) * 32]);
      __syncwarp();
      if (lane == 0) { mbar_arrive(bars + 8 * B_PUB); TS(30); }
    }
  } else if (wid != 12) {
    if (elect_one()) {
      if (wid < 7) {
        const int b0 = wid < 4 ? 4 + 19 * wid : 85 + 21 * (wid - 4), cnt = wid < 4 ? 2 : 1;
#pragma unroll
        for (int i = 0; i < 21; i++) mbar_init(bars + 8 * (b0 + i), cnt);
#pragma unroll
        for (int i = 0; i < 5; i++) mbar_init(bars + 8 * (B_PD + 5 * wid + i), 1);
      } else {
#pragma unroll
        for (int i = 0; i < 12; i++) mbar_init(bars + 8 * (B_CVDONE + i), (i == 5 || i == 6) ? 160 : 128);
        mbar_init(bars + 8 * B_CTAB, 192); mbar_init(bars + 8 * B_PREP, 5); mbar_init(bars + 8 * B_PREP2, 1);
      }
      asm volatile("fence.mbarrier_init.release.cluster;" ::: "memory");
    }
    __syncwarp();
    bar_sync(5, 288);
    if (wid == 2) asm volatile("bar.arrive 8, 192;\nbar.arrive 6, 64;\nbar.arrive 9, 64;\nbar.arrive 7, 64;" ::: "memory");
    if (tid == 128) TS(0);
    if (wg == 1) { cv_table(); mbar_arrive(bars + 8 * B_CTAB); }
  }

  if (wid == 12) {
    ROLE(role)
    uint32_t dst = sb;
#pragma unroll 1
    for (int k = S1; k < 10; k++) {
      const uint32_t fb = bars + 8 * (B_G1FULL + k);
      mbar_wait(bars + 8 * (B_G1DONE + k - S1));
      if (elect_one()) {
        mbar_expect_tx(fb, 20480);
        tma4(dst + G1_XOFF, last ? &p.mXl : &p.mX, 64 * k, 0, 0, last ? 0 : 80 * T1, fb);
        mbar_expect_tx(fb, 16384);
        tma5(dst, &p.mB, 64 * k, 0, 0, 4 * side, 2 * GP, fb);
        if (has2 && k - S1 + KV0 < 5) kv_issue(p, k - S1 + KV0, m2, dg);
      }
      dst += G1_STAGE; if (k == 2 * S1 - 1) dst = sb;
    }
  } else if (wid == 15 && (role >> 16)) {
    ROLE(role)
    if (TPF >= 0) {
      mbar_wait(bars + 8 * (B_KV + TPF));
      if (elect_one()) {
#pragma unroll
        for (int c = 0; c < 5; c++) l2_prefetch(p.ssmk + (cch0 + 32 * c) * SEQ, 4096);
        if (CPF) { l2_prefetch(p.cre + (160 * dg + 5 * m2) * DM, 6400); l2_prefetch(p.cim + (160 * dg + 5 * m2) * DM, 6400); }
      }
    }
    mbar_wait(bars + 8 * B_PREP2);
    if (lane < 10) sts128(sb + CV_OFF + (lane >> 1) * CV_B + CV_K - 32 + 16 * (lane & 1), make_uint4(0, 0, 0, 0));
    fence_async_smem();
    __syncwarp();
    const unsigned tag = lds32(sb + EP_OFF + 20);
    if (TAPW) mbar_wait(bars + 8 * B_PUB);
    if (elect_one()) {
#pragma unroll 1
      for (int c = 0; c < 5; c++) {
        if (c == 0) asm volatile("prefetch.tensormap [%0];" ::"l"(&p.mU) : "memory");
        mbar_expect_tx(bars + 8 * (B_CVFULL + c), 4096 + 2 * CV_PL);
        if (c < TAPN) bulk_g2s(sb + CV_OFF + c * CV_B + CV_K, p.ssmk + (cch0 + 32 * c) * SEQ, 4096, bars + 8 * (B_CVFULL + c));
      }
    }
    mbar_wait(bars + 8 * B_PUB);
    cnt_poll(&g_kvcnt[(dg * 4 + (m2 >> 3)) * 32], 32 * tag);
    fence_async_global();
    if (elect_one()) {
      TS(28);
#pragma unroll
      for (int c = 0; c < 5; c++) {
        tma5(sb + CV_OFF + c * CV_B + CV_U, &p.mU, 0, -3, 2 * c, 16 * (m2 & 1) + (m2 >> 1), dg, bars + 8 * (B_CVFULL + c));
        if (c >= TAPN) bulk_g2s(sb + CV_OFF + c * CV_B + CV_K, p.ssmk + (cch0 + 32 * c) * SEQ, 4096, bars + 8 * (B_CVFULL + c));
      }
#pragma unroll
      for (int i = 0; i < 3; i++) asm volatile("prefetch.tensormap [%0];" ::"l"(&p.mCre + i) : "memory");
      TS(54);
    }
    __syncwarp();
  }
  {
    const int w = wid & 3;
    if (wg == 2 && !(role >> 16)) {
      float xa[2], xb[2];
      mbar_wait(bars + 8 * (B_G1FULL + 11));
      stat_table(role & 15, lds32(sb + EP_OFF + 20), 1, w, g_stats, g_stats, xa, xb);
      mbar_arrive(bars + 8 * (B_STAB + 1));
    }
#pragma unroll 1
    for (int l = 0; l < 2; l++) {
      if (wg < 2) {
        float acc[80];
#pragma unroll
        for (int i = 0; i < 80; i++) acc[i] = 0.f;
        ROLE(role)
        const int tid = tid_opaque(), r = (tid & 31) >> 2, q = tid & 3;
        const int ch = 128 * GP + 64 * wg + 32 * side + 8 * w + r;
        const uint32_t ca = sb + CTAB_OFF + (32 * wg + 8 * w + r) * 24;
        float2 lam = make_float2(0.f, 0.f), p8 = lam, p16 = lam, pL = lam, p2L = lam;
        fence_regs(acc);
        {
          const uint32_t alo0 = (l == 0 ? desc_lo(sb, 16) : desc_lo(sb + G2_WOFF, 16)) + wg * 512;
          const uint32_t blo0 = l == 0 ? desc_lo(sb + G1_XOFF, 16) : desc_lo(sb + X1_OFF, 128);
          const uint32_t bhi = l == 0 ? desc_hi(1024, 1) : desc_hi(1024, 0), xstep = l == 0 ? 2 : 16;
          const uint32_t astep = l == 0 ? G1_STAGE >> 4 : 1024, bstep = l == 0 ? G1_STAGE >> 4 : 1280, aend = alo0 + (S1 + l) * astep;
          uint32_t alo = alo0, blo = blo0;
          const uint32_t special = 8u | (l ? (1u << MK1) | (wg << (8 - STG_D)) : (1u << MK0) | (1u << PAUSE_K) | (wg << (9 - STG0)));
          uint32_t fb = bars + 8 * (B_G1FULL + 10 * l), nb = fb + 8;
          mbar_wait(fb);
          if (tid == 0) TS(1 + 8 * l);
#pragma unroll 1
          for (int k = 0; k < 10; k++) {
            uint32_t ok;
            wgmma_fence();
#pragma unroll
            for (int kk = 0; kk < 4; kk++) {
              wgmma_n160<0>(acc, alo + kk * 2, desc_hi(1024, 1), blo + kk * xstep, bhi);
              if (kk == 0) { ok = mbar_test(nb); asm volatile("add.u32 %0, %0, %1;" : "+r"(nb) : "r"(k < 8 ? 8 : 0)); }
              if (kk == STG_KK && k == 9 && tid == 0) mbar_arrive(bars + 8 * (B_STG + l));
            }
            wgmma_commit();
            alo += astep; blo += bstep;
            if (blo == desc_lo(sb + G_OFF, 128)) blo = desc_lo(sb, 128);
            if (alo == aend) { alo = alo0; blo = blo0; }
            wgmma_wait<1>();
            if (k > 0 && (tid & 127) == 0) mbar_arrive(fb + 8 * (B_G1DONE - B_G1FULL - 1));
            if (!ok) mbar_wait(fb + 8);
            if ((special >> k) & 1) {
            if (k == (l ? MK1 : MK0)) {
              mbar_wait(bars + 8 * (B_STAB + l));
              const float2 sB = lds64f(ca + 16);
              uint32_t a0 = q < 2 ? __float_as_uint(sB.x) : 0u, a1 = q < 2 ? __float_as_uint(sB.y) : 0u, a2 = 0u, a3 = 0u;
              asm volatile("" : "+r"(a0), "+r"(a1), "+r"(a2), "+r"(a3)::"memory");
              wgmma_fence();
              wgmma_rs_n160(acc, a0, a1, a2, a3, l ? desc_lo(sb + MX1_OFF, 0) : desc_lo(sb + MX0_OFF, 0));
              wgmma_commit();
            }
            if (wg == 1 && k == (l ? 8 - STG_D : 9 - STG0)) mbar_wait(bars + 8 * (B_STG + l));
            if (k == 3) {
              mbar_wait(bars + 8 * B_CTAB);
              lam = lds64f(ca);
              if (l == 0 && q < 2) rec_st(&g_E[(q * NT1 + T1) * DM + ch], 0.f, 0.f, lds32(sb + EP_OFF + 20) - 1);
              if (p.swap) lam.y = -lam.y;
              const float2 p2 = cmul(lam, lam), p4 = cmul(p2, p2);
              p8 = cmul(p4, p4); p16 = cmul(p8, p8);
              pL = cmul(p16, p16);
              if (!last) pL = cmul(pL, p8);
              p2L = cmul(pL, pL);
            }
            if (k == PAUSE_K && l == 0 && has2) mbar_wait(bars + 8 * B_PREP);
            }
            fb += 8;
          }
        }
        const unsigned tag = lds32(sb + EP_OFF + 20);
        wgmma_wait<0>();
        fence_regs(acc);
        if ((tid & 127) == 0) { mbar_arrive(bars + 8 * (B_G1DONE + 10 * l + 9)); TS(wg ? 17 + l : 2 + 8 * l); }
        float2 ec[3];
#pragma unroll
        for (int jj = 0; jj < 4; jj++)
#pragma unroll
          for (int y = 0; y < 3; y++) {
            if (y == 2 && (jj & 1)) continue;
            const int j = y == 2 ? 16 + jj : 8 * y + 2 * jj;
            const float4 st = lds128f(sb + STAB_OFF + q * 160 + j * 8);
            const float rs[4] = {st.x, st.y, st.z, st.w};
#pragma unroll
            for (int x = 0; x < 4; x++) {
              const int i = 4 * j + 4 * (x >> 1) + (x & 1);
              acc[i] *= rs[x]; acc[i + 2] *= rs[x];
              ec[y] = (jj == 0 && x == 0) ? make_float2(acc[i], acc[i + 2]) : cfma(lam, ec[y], make_float2(acc[i], acc[i + 2]));
            }
          }
        float2 e = cfma(p16, ec[0], ec[1]);
        if (!last) e = cfma(p8, e, ec[2]);
        {
          float2 v = make_float2(__shfl_up_sync(0xffffffffu, e.x, 1, 4), __shfl_up_sync(0xffffffffu, e.y, 1, 4));
          if (q >= 1) e = cfma(pL, v, e);
          v = make_float2(__shfl_up_sync(0xffffffffu, e.x, 2, 4), __shfl_up_sync(0xffffffffu, e.y, 2, 4));
          if (q >= 2) e = cfma(p2L, v, e);
        }
        if (!last && q == 3) rec_st(&g_E[(l * NT1 + T1) * DM + ch], e.x, e.y, tag);
        if (tid == 0) TS(3 + 8 * l);
        float2 ex = make_float2(__shfl_up_sync(0xffffffffu, e.x, 1, 4), __shfl_up_sync(0xffffffffu, e.y, 1, 4));
        if (q == 0) ex = make_float2(0.f, 0.f);
        const float2 coef = lds64f(ca + 8), lamc = make_float2(lam.x, p.swap ? lam.y : -lam.y);
        float m00 = coef.x, m01 = -coef.y, m10 = -coef.y, m11 = -coef.x;
        if (p.swap) { m00 = -coef.y; m01 = coef.x; m10 = -coef.x; m11 = -coef.y; }
        float2 pLq, p160q, p640;
        {
          const float2 p80 = last ? cmul(p2L, p16) : p2L, p160 = cmul(p80, p80), p320 = cmul(p160, p160), one = make_float2(1.f, 0.f);
          p640 = cmul(p320, p320);
          pLq = cmul((q & 1) ? pL : one, (q & 2) ? p2L : one);
          p160q = cmul((q & 1) ? p160 : one, (q & 2) ? p320 : one);
        }
        float2 c, ev[3];
        unsigned tg[3];
        const uint4* ep = &g_E[(l * NT1 + T1 - 1 - q) * DM + ch];
#pragma unroll
        for (int j = 0; j < 20; j++) {
          if (j == CPOLL) {
#pragma unroll
            for (int i = 0; i < 3; i++) {
              ev[i] = make_float2(0.f, 0.f); tg[i] = tag;
              if (T1 - 1 - q - 4 * i >= 0) tg[i] = rec_ld(ep - 4 * i * DM, ev[i].x, ev[i].y);
            }
          }
#pragma unroll
          for (int x = 0; x < 2; x++) {
            const float b0 = acc[4 * j + x], b1 = acc[4 * j + 2 + x];
            acc[4 * j + x] = fmaf(b0, m00, b1 * m01);
            acc[4 * j + 2 + x] = fmaf(b0, m10, b1 * m11);
          }
          if (j == CPOLL - 1 || j == 19) asm volatile("" : "+f"(acc[4 * j]), "+f"(acc[4 * j + 1]), "+f"(acc[4 * j + 2]), "+f"(acc[4 * j + 3])::"memory");
        }
        {
          uint32_t it = 0;
          while (__any_sync(0xffffffffu, tg[0] != tag || tg[1] != tag || tg[2] != tag)) {
#pragma unroll
            for (int i = 0; i < 3; i++)
              if (tg[i] != tag) tg[i] = rec_ld(ep - 4 * i * DM, ev[i].x, ev[i].y);
            trap_if(++it > SPIN_LIMIT);
          }
          c = cfma(p640, cfma(p640, ev[2], ev[1]), ev[0]);
          c = cmul(c, p160q);
          c.x += __shfl_xor_sync(0xffffffffu, c.x, 1); c.y += __shfl_xor_sync(0xffffffffu, c.y, 1);
          c.x += __shfl_xor_sync(0xffffffffu, c.x, 2); c.y += __shfl_xor_sync(0xffffffffu, c.y, 2);
        }
        if (tid == 0) TS(4 + 8 * l);
        if (HOLD1 && wg == 1 && l == 1 && has2) mbar_wait(bars + 8 * HOLD1);
        const uint32_t c0 = (uint32_t)clock(), tm = (tid & 7) == 4 * side + w;
        c = cfma(pLq, c, ex);
        float2 hh = make_float2(fmaf(c.x, m00, c.y * m01), fmaf(c.x, m10, c.y * m11));
        uint8_t* hb = g_h + (10 * wg + 2 * GP) * 8192 + (4 * side + w) * 1024 + (tid_opaque() & 31) * 4;
#pragma unroll
        for (int j4 = 0; j4 < 5; j4++) {
          if (PACE && j4 > 0 && wg == 1 && l == 1) { while (__any_sync(0xffffffffu, (uint32_t)clock() - c0 < PACE * j4)) {} }
          const int ng = 20 * T1 + 4 * j4;
          uint8_t* hp = hb + (size_t)(ng >> 3) * 163840 + (ng & 7) * 128;
#pragma unroll
          for (int jj = 0; jj < 4; jj++) {
            const int j = 4 * j4 + jj;
            const float2 h0 = cfma(lamc, hh, make_float2(acc[4 * j + 0], acc[4 * j + 2]));
            hh = cfma(lamc, h0, make_float2(acc[4 * j + 1], acc[4 * j + 3]));
            if (j4 < 4 || !last) {
              *(uint32_t*)(hp + jj * 128) = tag_word(pack_bf16(h0.x, hh.x), tm, 1 - l);
              *(uint32_t*)(hp + jj * 128 + 8192) = tag_word(pack_bf16(h0.y, hh.y), tm, 1 - l);
            }
          }
        }
        mbar_arrive(bars + 8 * (B_HST + 2 * l + wg));
        if (tid == 0) TS(5 + 8 * l);
        if (tid == 128) TS(l ? 25 : 19);
        if (l == 0 && wid == 4) {
          mbar_wait(bars + 8 * B_HST);
          mbar_wait(bars + 8 * (B_HST + 1));
          if ((tid & 31) < 4) h_release(0, T1, tid & 3);
          __syncwarp();
          if (tid == 128) { mbar_arrive(bars + 8 * B_REL); TS(6); }
        }
      }
      if (l == 0) {
        ROLE(role)
        if (has2) {
          CvCtx cc;
          mbar_wait(bars + 8 * B_CTAB);
          cv_setup(cc);
          mbar_wait(bars + 8 * (B_G1DONE + 9));
#pragma unroll 1
          for (int c = (wg + 2) & 3; c < 5; c += 4) conv_channel(c, cc);
          if ((tid & 127) == 0) TS(wg == 2 ? 32 : (wg == 3 ? 50 : 7 + wg));
        }
      }
      if (wg >= 2) break;
    }
    if (wg < 2 && (role >> 16)) {
      const int ln = tid_opaque() & 31;
      const uint8_t* src = g_h + ((role >> 8) & 63) * 163840;
      uint32_t ph = 0;
      if (wg == 0) {
        mbar_wait(bars + 8 * (B_G1DONE + 19));
        if (SPEC0 + SPECW) __nanosleep(SPEC0 + SPECW * w);
        if (tid == 0) TS(23);
        if (!SPLITI && w < 3 && elect_one()) { mbar_expect_tx(bars + 8 * (B_XV + w + 4), G2_XB); }
      }
#pragma unroll 1
      for (int k = 10 * wg + w; k < 10 * wg + 10; k += 4) {
        if (k < (SPLITI ? S2 : 4) && elect_one()) {
          mbar_expect_tx(bars + 8 * (B_XV + k), G2_XB);
          bulk_g2s(sb + k * G2_XB, src + k * 8192, G2_XB, bars + 8 * (B_XV + k));
          if (!SPLITI && k < 3) bulk_g2s(sb + (k + 4) * G2_XB, src + (k + 4) * 8192, G2_XB, bars + 8 * (B_XV + k + 4));
        }
        validate_block(bars + 8 * (B_XV + k), bars + 8 * (B_G2FULL + 20 + k), sb + (k % S2) * G2_XB, src + k * 8192,
                       (ln & 7) * 1028 + (ln >> 3) * 32, bars + 8 * (B_RETRY + wid), ph);
      }
    }
    if (wg == 3) {
    ROLE(role)
    const int pw = wid & 3, gpc = 2 * min(m2 >> 3, 3) + (dg >> 1);
    mbar_wait(bars + 8 * B_EP);
    const unsigned tag = lds32(sb + EP_OFF + 20);
    if (pw == 0) {
      if (elect_one()) {
#pragma unroll 1
        for (int l = 0; l < 2; l++) {
          uint32_t dst = sb;
          if (l == 1) {
            dst = sb + G2_WOFF;
#pragma unroll 1
            for (int k = 0; k < 10; k++) {
              mbar_wait(k > 4 ? bars + 8 * (B_G1DONE + 5 + k) : (has2 ? bars + 8 * (B_G2DONE + 14 + min(k, 3)) : bars + 8 * (B_G1DONE + 9)));
              mbar_expect_tx(bars + 8 * (B_G1FULL + 10 + k), 16384);
              tma5(dst, &p.mB, 64 * k, 0, 0, 4 * side, 2 * GP, bars + 8 * (B_G1FULL + 10 + k));
              dst += 16384; if (k == 4) dst = sb + G2_WOFF;
            }
          }
          if (has2) {
            const uint32_t fb2 = bars + 8 * (B_G2FULL + 20 * l), wb2 = bars + 8 * (B_G2DONE + 20 * l - S2);
            dst = sb + G2_WOFF + (WTAIL ? 4 * l * G2_WB : 0);
            int kc = 0;
#pragma unroll 1
            for (int k = 0; k < 20; k++) {
              mbar_wait(k >= S2 ? wb2 + 8 * k : bars + 8 * (l ? B_G1DONE + (WTAIL ? (k < 3 ? 15 + k : 13 + k) : 19) : (k == 5 ? B_XFREE : (k == 6 ? B_SFREE : B_REL))));
              mbar_expect_tx(fb2 + 8 * k, G2_WB);
              tma5(dst, &p.mCre + (k & 1), kc, 0, 0, 0, 10 * dg, fb2 + 8 * k);
              kc += (k & 1) << 7; if (k == 9) kc = 64;
              dst += G2_WB; if (dst == sb + G2_WOFF + S2 * G2_WB) dst = sb + G2_WOFF;
            }
          }
        }
      }
    } else if (pw == 1) {
#pragma unroll 1
      for (int l = 0; l < 2; l++) {
        if (l == 1) {
          mbar_wait(bars + 8 * (has2 ? B_G2DONE + 19 : B_G1DONE + 9));
          if (has2) mbar_wait(bars + 8 * B_UST);
          cnt_poll(&g_ucnt[gpc * 32], 128 * tag);
          fence_async_global();
          if (elect_one()) {
            TS(20);
            const int bytes = last ? 16384 : 20480;
            const uint8_t* src = g_u + T1 * 204800;
            uint32_t dst = sb + X1_OFF;
#pragma unroll 1
            for (int k = 0; k < 10; k++) {
              if (k > 4) mbar_wait(bars + 8 * (B_G1DONE + 5 + k));
              mbar_expect_tx(bars + 8 * (B_G1FULL + 10 + k), bytes);
              bulk_g2s(dst, src, bytes, bars + 8 * (B_G1FULL + 10 + k));
              src += 20480; dst += 20480; if (dst == sb + G_OFF) dst = sb; if (k == 4) dst = sb + X1_OFF;
            }
          }
          __syncwarp();
        }
        if (has2) {
          if (l == 0) {
            mbar_wait(bars + 8 * B_REL);
            cnt_poll(&g_hcnt[gpc * 32], 40 * tag);
            fence_async_global();
          }
          if (elect_one()) {
            if (l == 0) TS(21);
            const uint32_t fb2 = bars + 8 * (l ? B_XV : B_G2FULL), wb2 = bars + 8 * (B_G2DONE + 20 * l - S2);
            const uint8_t* src = g_h + m2 * 163840 + l * S2 * 8192;
            uint32_t dst = sb;
#pragma unroll 1
            for (int k = l * S2; k < 20; k++) {
              if (k >= 5) mbar_wait(k >= S2 ? wb2 + 8 * k : bars + 8 * B_SFREE);
              mbar_expect_tx(fb2 + 8 * k, G2_XB);
              bulk_g2s(dst, src, G2_XB, fb2 + 8 * k);
              src += 8192; dst += G2_XB; if (dst == sb + S2 * G2_XB) dst = sb;
            }
          }
          __syncwarp();
        }
      }
    } else if (pw == 2) {
#pragma unroll 1
      for (int l = 0; l < 2; l++) {
        if (l == 1) {
          float xa[2], xb[2];
          mbar_wait(bars + 8 * (B_G1FULL + 11));
          stat_table(T1, tag, 1, 4, g_stats, g_stats, xa, xb);
          mbar_arrive(bars + 8 * (B_STAB + 1));
        }
        if (l == 0 && has2 && elect_one()) {
#pragma unroll 1
          for (int i = 0; i < 5; i++) {
            const int c = i < 3 ? i : 7 - i;
            mbar_wait(bars + 8 * (B_CVDONE + c));
            bulk_s2g(g_G + (cch0 + 32 * c) * 4096, cv_stage(c), 4096);
          }
          asm volatile("cp.async.bulk.commit_group;" ::: "memory");
          asm volatile("cp.async.bulk.wait_group.read 0;" ::: "memory");
          mbar_arrive(bars + 8 * B_SFREE);
          asm volatile("cp.async.bulk.wait_group 0;" ::: "memory");
          TS(48);
          fence_async_global();
          asm volatile("fence.acq_rel.gpu;" ::: "memory");
#pragma unroll
          for (int i = 0; i < 4; i++) red_rlx(&g_gcnt[(dg * 4 + i) * 32]);
          TS(49);
          mbar_arrive(bars + 8 * (B_GO + 1));
        }
        __syncwarp();
      }
    } else if (has2) {
      mbar_wait(bars + 8 * B_REL);
      if (!CPF && elect_one()) {
        l2_prefetch(p.cre + (160 * dg + 5 * m2) * DM, 6400); l2_prefetch(p.cim + (160 * dg + 5 * m2) * DM, 6400);
      }
      mbar_wait(bars + 8 * (B_GO + 1));
      flag_poll(&g_gcnt[(dg * 4 + (m2 >> 3)) * 32], 32 * tag);
      fence_async_global();
      if (elect_one()) {
        TS(29);
        mbar_expect_tx(bars + 8 * B_GFULL, 20480);
        tma5(sb + G_OFF, &p.mG, 64 * m2, 0, 0, 0, 10 * dg, bars + 8 * B_GFULL);
      }
    }
    } else if (wg == 2 && (role >> 16)) {
      float acc[80];
      float off[2] = {mean0[0], mean0[1]};
      const unsigned tag = lds32(sb + EP_OFF + 20);
      dskip_init<true>(acc, mean0, rstd0);
      mbar_arrive(bars + 8 * B_XFREE);
#pragma unroll 1
      for (int step = 1; step < 4; step++) {
        const int l = step >> 1;
        if (step != 2) {
          uint32_t alo = desc_lo(sb, 1024), blo = desc_lo(sb + G2_WOFF, 16) + (WTAIL ? l * (G2_WB >> 2) : 0);
          uint32_t fb = bars + 8 * (B_G2FULL + 20 * l);
          fence_regs(acc);
          mbar_wait(bars + 8 * (B_CVDONE + 2));
          mbar_wait(bars + 8 * (B_CVDONE + 3));
          mbar_wait(fb);
          if (tid == 256) TS(33 + 6 * l);
#pragma unroll 1
          for (int k = 0; k < 20; k++) {
            if (l == TSL && (k & 3) == 3 && tid == 256) TS(56 + (k >> 2));
            uint32_t ok; const uint32_t nb = k < 19 ? fb + 8 : fb;
            wgmma_fence();
#pragma unroll
            for (int kk = 0; kk < 4; kk++) {
              wgmma_n160<1>(acc, alo + kk * 128, desc_hi(128, 0), blo + kk * 2, desc_hi(1024, 1));
              if (kk == 0) ok = mbar_test(nb);
            }
            wgmma_commit();
            alo += G2_XB >> 4; blo += G2_WB >> 4;
            if (alo == desc_lo(sb + S2 * G2_XB, 1024)) alo = desc_lo(sb, 1024);
            if (blo == desc_lo(sb + G_OFF, 16)) blo = desc_lo(sb + G2_WOFF, 16);
            wgmma_wait<1>();
            if (k > 0 && tid == 256) mbar_arrive(fb + 8 * (B_G2DONE - B_G2FULL - 1));
            if (!ok) mbar_wait(nb);
            fb += 8;
          }
          wgmma_wait<0>();
          fence_regs(acc);
          if (tid == 256) TS(34 + 6 * l);
          if (tid == 256) mbar_arrive(bars + 8 * (B_G2DONE + 20 * l + 19));
        }
        ROLE(role)
        const int tq = tid_opaque() & 31, n0 = 64 * m2 + 16 * w + (tq >> 2);
#pragma unroll 1
        for (int rep = 0;; rep++) {
          stats_publish<false>(step, n0, dg, tag, acc);
          if (step != 2 || rep == 1) break;
          for (int n = tid & 127; n < 160; n += 128) {
            const int d = 16 * (n >> 4) + 4 * ((n >> 1) & 3) + 2 * ((n >> 3) & 1) + (n & 1);
            const uint32_t dw = lds32(sb + DTAB_OFF + 2 * (d & ~1)), dd = __byte_perm(dw, dw, (d & 1) ? 0x3232 : 0x1010);
            sts128(sb + DX_OFF + 16 * n, make_uint4(dd, dd, dd, dd));
          }
          mbar_wait(bars + 8 * (B_G1FULL + 11));
          float xa[2], xb[2];
          stat_table(T1, tag, 1, w, g_stats, g_stats, xa, xb);
          mbar_arrive(bars + 8 * (B_STAB + 1));
          if (tid == 256) TS(27);
          bar_sync(3, 128);
          break;
        }
        uint32_t gf[10][4];
        mbar_wait(bars + 8 * B_GFULL);
        uint32_t ga = sb + G_OFF + (8 * (tq >> 4) + (tq & 7)) * 128 + (((2 * w + ((tq >> 3) & 1)) ^ ((2 * m2) & 6) ^ (tq & 7)) << 4), gstep = 2048;
        if (step == 2) { ga = sb + DX_OFF + (8 * (tq >> 4) + (tq & 7)) * 16; gstep = 256; }
#pragma unroll
        for (int J = 0; J < 2; J++) ldsm4t(gf[J], ga + J * gstep);
        if (tid == 256) TS(35 + 6 * l);
        uint8_t* dst[2][2];
#pragma unroll
        for (int h = 0; h < 2; h++) {
          if (l == 0) {
            const int ng = 8 * m2 + 2 * w + h, T = ng / 20;
            uint8_t* ub = g_u + (T * 204800 + (ng - 20 * T) * 1024 + (tq & 2) * 64 + (tq & 28) * 4 + (tq & 1) * 8 + (5 * dg >> 1) * 20480);
            dst[h][1] = ub + ((dg & 1) ? 20480 - 512 : 0);
            dst[h][0] = ub + (dg & 1) * 512;
          } else {
            dst[h][0] = dst[h][1] = (uint8_t*)(p.out + (n_to_t(n0 + 8 * h) * DM + 160 * dg + 4 * (tq & 3)));
          }
        }
        float mean[2], rstd[2];
        stats_get(step, n0, tag, mean, rstd);
        if (tid == 256) TS(36 + 6 * l);
        if (step == 2) mbar_wait(bars + 8 * NGATE);
        off[0] += mean[0]; off[1] += mean[1];
        const float ov[2] = {step == 3 ? off[0] : 0.f, step == 3 ? off[1] : 0.f};
#pragma unroll
        for (int J = 0; J < 10; J++) {
          if (J + 2 < 10) ldsm4t(gf[J + 2 < 10 ? J + 2 : 0], ga + (J + 2) * gstep);
#pragma unroll
          for (int x = 0; x < 8; x++) {
            const int h = (x >> 1) & 1;
            const uint32_t gwd = gf[J][x >> 1];
            const float t = fmaf(rstd[h], (x & 1) ? bf_hi(gwd) : bf_lo(gwd), 1.f);
            acc[8 * J + x] = fmaf(acc[8 * J + x], t, fmaf(-mean[h], t, ov[h]));
          }
#pragma unroll
          for (int h = 0; h < 2; h++) {
            if (step == 1)
              *(uint2*)(dst[h][(J >> 1) & 1] + (J >> 2) * 20480 + (J & 3) * 256) =
                  make_uint2(pack_bf16(acc[8 * J + 2 * h], acc[8 * J + 2 * h + 1]), pack_bf16(acc[8 * J + 4 + 2 * h], acc[8 * J + 5 + 2 * h]));
            if (step == 3)
              *(float4*)(dst[h][0] + 64 * J) = make_float4(acc[8 * J + 2 * h], acc[8 * J + 2 * h + 1], acc[8 * J + 4 + 2 * h], acc[8 * J + 5 + 2 * h]);
          }
          __syncwarp();
        }
        if (step == 1) {
          bar_sync(3, 128);
          if (tid == 288) { TS(37); mbar_arrive(bars + 8 * B_UST); }
          if (tid < 264) red_rel(&g_ucnt[(tid & 7) * 32]);
          __syncwarp();
          if (tid == 256) TS(38);
        } else if (step == 2) {
          if (tid == 256) TS(22);
        } else {
          if (tid == 256) {
            TS(43);
            if (m2 == 31 && dg == 3) asm volatile("st.relaxed.gpu.global.u32 [%0], %1;" ::"l"(g_epoch), "r"(tag + 1) : "memory");
          }
        }
      }
    }
  }
}

typedef CUresult (*EncFn)(CUtensorMap*, CUtensorMapDataType, cuuint32_t, void*, const cuuint64_t*, const cuuint64_t*,
                          const cuuint32_t*, const cuuint32_t*, CUtensorMapInterleave, CUtensorMapSwizzle,
                          CUtensorMapL2promotion, CUtensorMapFloatOOBfill);

void encode(EncFn fn, CUtensorMap* m, const void* ptr, int rank, const cuuint64_t* dims, const cuuint64_t* strides, const cuuint32_t* box,
            CUtensorMapSwizzle swz = CU_TENSOR_MAP_SWIZZLE_128B, int prom = 2) {
  cuuint32_t es[5] = {1, 1, 1, 1, 1};
  fn(m, CU_TENSOR_MAP_DATA_TYPE_BFLOAT16, rank, (void*)ptr, dims, strides, box, es, CU_TENSOR_MAP_INTERLEAVE_NONE,
     swz, (CUtensorMapL2promotion)prom, CU_TENSOR_MAP_FLOAT_OOB_FILL_NONE);
}

}

extern "C" void kernel_launch(void* const* d_in, const int* in_sizes, int n_in, void* d_out, int out_size) {
  (void)in_sizes; (void)n_in; (void)out_size;
  Params p;
  typedef const __nv_bfloat16* BP;
  p.x = (BP)d_in[0]; p.lre = (BP)d_in[1]; p.lim = (BP)d_in[2]; p.bre = (BP)d_in[3]; p.bim = (BP)d_in[4];
  p.cre = (BP)d_in[5]; p.cim = (BP)d_in[6]; p.logdt = (BP)d_in[7]; p.dskip = (BP)d_in[8];
  p.k = (BP)d_in[10]; p.v = (BP)d_in[11]; p.shiftk = (BP)d_in[12]; p.ssmk = (BP)d_in[13]; p.ssmD = (BP)d_in[14];
  p.out = (float*)d_out;
  for (int sm = 0; sm < 132; sm++) {
    const int tpc = sm >> 1, side = sm & 1;
    int gpc, gi;
    if (tpc < 32) { gpc = tpc & 7; gi = tpc >> 3; }
    else if (tpc < 60) { gpc = 1 + (tpc - 32) % 7; gi = 4 + (tpc - 32) / 7; }
    else if (tpc < 62) { gpc = tpc - 54; gi = 8; }
    else { gpc = 0; gi = tpc - 58; }
    const int pos = 8 * gpc + gi + (gpc == 7 ? 1 : 0);
    int T1, GP;
    if (pos < 52) { const int hh = pos / 26, x = pos - 26 * hh; T1 = x >> 1; GP = 2 * hh + (x & 1); }
    else { T1 = pos - 52; GP = 4; }
    const int m2 = 8 * (gpc >> 1) + gi, dg = 2 * (gpc & 1) + side;
    p.role[sm] = pos == 65 ? -1 : (T1 | (GP << 4) | (side << 7) | (m2 << 8) | (dg << 14) | ((gi < 8) << 16));
  }
  void* fnp = nullptr;
  cudaDriverEntryPointQueryResult qr;
  cudaGetDriverEntryPoint("cuTensorMapEncodeTiled", &fnp, cudaEnableDefault, &qr);
  EncFn fn = (EncFn)fnp;
  void* gG = nullptr;
  cudaGetSymbolAddress(&gG, g_G);
  void* gKV = nullptr;
  cudaGetSymbolAddress(&gKV, g_kv);
  {
    cuuint64_t dims[5] = {32, 32, 10, 32, 4}, st[4] = {20480, 2048, 64, 655360}; cuuint32_t box[5] = {32, 35, 2, 1, 1};
    encode(fn, &p.mU, gKV, 5, dims, st, box, CU_TENSOR_MAP_SWIZZLE_NONE, 1);
  }
  const cuuint64_t RB = DM * 2;
  {
    p.swap = p.bim < p.bre;
    const char* lo = (const char*)(p.swap ? p.bim : p.bre); const char* hi = (const char*)(p.swap ? p.bre : p.bim);
    cuuint64_t dims[5] = {640, 8, 2, 8, 10}, st[4] = {RB, (cuuint64_t)(hi - lo), 8 * RB, 64 * RB}; cuuint32_t box[5] = {64, 8, 2, 4, 2};
    encode(fn, &p.mB, lo, 5, dims, st, box);
  }
  {
    cuuint64_t dims[5] = {640, 2, 4, 2, 40}, st[4] = {RB, 4 * RB, 2 * RB, 16 * RB}; cuuint32_t box[5] = {64, 2, 4, 2, 10};
    encode(fn, &p.mCre, p.cre, 5, dims, st, box); encode(fn, &p.mCim, p.cim, 5, dims, st, box);
    cuuint64_t dimg[5] = {2048, 2, 4, 2, 40}, stg[4] = {4096, 4 * 4096, 2 * 4096, 16 * 4096};
    encode(fn, &p.mG, gG, 5, dimg, stg, box);
  }
  {
    cuuint64_t dims[4] = {640, 2, 4, 900}, st[3] = {RB, 40 * RB, 2 * RB}; cuuint32_t box[4] = {64, 2, 4, 20};
    encode(fn, &p.mX, p.x, 4, dims, st, box);
    cuuint64_t diml[4] = {640, 2, 4, 16}, stl[3] = {RB, 32 * RB, 2 * RB};
    encode(fn, &p.mXl, p.x + (size_t)1920 * DM, 4, diml, stl, box);
    cuuint32_t boxt[4] = {160, 2, 4, 4};
    encode(fn, &p.mXt, p.x, 4, dims, st, boxt, CU_TENSOR_MAP_SWIZZLE_NONE);
    encode(fn, &p.mXtl, p.x + (size_t)1920 * DM, 4, diml, stl, boxt, CU_TENSOR_MAP_SWIZZLE_NONE);
    cuuint64_t dk[3] = {640, 2000, 4}, sk[2] = {RB, 16 * RB}; cuuint32_t bk[3] = {32, 19, 4}, bv[3] = {32, 17, 4};
    encode(fn, &p.mK, p.k, 3, dk, sk, bk, CU_TENSOR_MAP_SWIZZLE_NONE);
    encode(fn, &p.mV, p.v, 3, dk, sk, bv, CU_TENSOR_MAP_SWIZZLE_NONE);
  }
  cudaFuncSetAttribute(fused_kernel, cudaFuncAttributeMaxDynamicSharedMemorySize, SMEM_BYTES);
  cudaLaunchConfig_t cfg = {};
  cfg.gridDim = dim3(132); cfg.blockDim = dim3(512); cfg.dynamicSmemBytes = SMEM_BYTES; cfg.stream = cudaStreamPerThread;
  cudaLaunchKernelEx(&cfg, fused_kernel, p);
}
```

```cpp
#include <cuda_runtime.h>
#include <cuda.h>
#include <cuda_bf16.h>
#include <stdint.h>

namespace {

constexpr int SEQ = 2048, DM = 640;
constexpr int NT1 = 13;
#define EXP 0
#define WPF1 3
#define WPF2 7
#define CPOLL 10
#define KV0 1
#define TAPLATE 1
#define STG_D 3
#define STG_KK 1
#define HOLD1 0
#define SPEC0 100
#define WREL 0
#define UREL 1
#define TSL 1
#define STG0 2
#define WTAIL 1
#define PFD 1
#define TAPW 0
#define TPF 4
#define CPF 0
#define MK0 7
#define MK1 4
#define PACE 350
#define TAPN 2
#define SPLITI 1
#define SPECW 60
#define PAUSE_K 5
constexpr uint32_t SPIN_LIMIT = 1u << 22;

__device__ __align__(1024) uint8_t g_h[32 * 20 * 8192];
__device__ __align__(1024) uint8_t g_u[NT1 * 10 * 20480];
__device__ __align__(1024) uint8_t g_kv[DM * 4096];
__device__ __align__(1024) uint8_t g_G[DM * 4096];
__device__ __align__(128) uint4 g_E[2 * NT1 * DM];
__device__ __align__(128) uint4 g_stats[4 * 4 * SEQ];
__device__ __align__(128) uint4 g_sB[DM * 2];
__device__ __align__(128) unsigned g_hcnt[8 * 32];
__device__ __align__(128) unsigned g_ucnt[8 * 32];
__device__ __align__(128) unsigned g_kvcnt[16 * 32];
__device__ __align__(128) unsigned g_gcnt[16 * 32];
__device__ __align__(128) unsigned g_epoch[32] = {1};
#define TS(i) do {} while (0)

struct Params {
  CUtensorMap mX, mB, mXl, mK, mV, mXt, mXtl, mCre, mCim, mG, mU;
  const __nv_bfloat16 *x, *lre, *lim, *bre, *bim, *cre, *cim, *logdt, *dskip, *k, *v, *shiftk, *ssmk, *ssmD;
  float* out;
  int swap;
  int role[132];
};

constexpr uint32_t sb = 1024;
constexpr uint32_t G1_STAGE = 36864, G1_XOFF = 16384;
constexpr int S1 = 4;
constexpr uint32_t XT_OFF = 159744, KS_OFF = 180224, KV_PIECE = 9216;
constexpr uint32_t G2_XB = 8192, G2_WB = 20480, G2_WOFF = 57344, G_OFF = 200704;
constexpr uint32_t X1_OFF = 139264;
constexpr int S2 = 7;
constexpr uint32_t CV_OFF = KS_OFF, CV_K = 128, CV_PL = 2240, CV_U = CV_K + 4096, CV_B = KV_PIECE;
constexpr uint32_t MISC = 226304;
constexpr uint32_t BAR_OFF = MISC;
constexpr int B_G1FULL = 0, B_G1DONE = 20, B_G2FULL = 40,
              B_G2DONE = 85, B_GFULL = 125, B_EP = 126, B_CVFULL = 129  , B_STG = 134  , B_REL = 136  , B_SFREE = 138,
              B_GO = 139  , B_PUB = 147,
              B_CVDONE = 148  , B_STAB = 153  , B_XFREE = 155, B_HST = 156  , B_UST = 158,
              B_CTAB = 160, B_PREP = 161, B_XT = 162, B_KV = 163  , B_PREP2 = 84, B_PD = 168  ,
              B_XV = 173  , B_RETRY = 193  ;
constexpr uint32_t bars = sb + BAR_OFF;
constexpr uint32_t STAB_OFF = MISC + 1648;
constexpr uint32_t CTAB_OFF = STAB_OFF + 640;
constexpr uint32_t DTAB_OFF = CTAB_OFF + 1536;
constexpr uint32_t EP_OFF = DTAB_OFF + 320;
constexpr uint32_t SO_OFF = EP_OFF + 32;
constexpr uint32_t TAP_OFF = 147456;
constexpr uint32_t MX0_OFF = TAP_OFF + 1280, MX1_OFF = G_OFF + 20480;
constexpr uint32_t DX_OFF = MX1_OFF + 2560;
constexpr uint32_t SMEM_BYTES = 232448;
static_assert(SO_OFF + 1536 <= SMEM_BYTES, "smem");

__device__ __forceinline__ void trap_if(bool c) { asm volatile("{\n.reg .pred p;\nsetp.ne.u32 p, %0, 0;\n@p trap;\n}\n" ::"r"((uint32_t)c)); }
__device__ __forceinline__ uint32_t smem_u32(const void* p) { return (uint32_t)__cvta_generic_to_shared(p); }
__device__ __forceinline__ void mbar_init(uint32_t bar, int cnt) { asm volatile("mbarrier.init.shared::cta.b64 [%0], %1;" ::"r"(bar), "r"(cnt) : "memory"); }
__device__ __forceinline__ void mbar_expect_tx(uint32_t bar, int bytes) { asm volatile("mbarrier.arrive.expect_tx.shared::cta.b64 _, [%0], %1;" ::"r"(bar), "r"(bytes) : "memory"); }
__device__ __forceinline__ void mbar_arrive(uint32_t bar) { asm volatile("mbarrier.arrive.shared::cta.b64 _, [%0];" ::"r"(bar) : "memory"); }
__device__ __forceinline__ bool elect_one() {
  uint32_t e; asm volatile("{\n.reg .pred P;\nelect.sync _|P, 0xffffffff;\nselp.u32 %0, 1, 0, P;\n}\n" : "=r"(e)); return e != 0;
}
__device__ __forceinline__ void mbar_wait(uint32_t bar) {
  asm volatile(
      "{\n.reg .pred p;\n.reg .u32 c;\nmov.u32 c, 0;\n"
      "W_%=:\nmbarrier.try_wait.parity.shared::cta.b64 p, [%0], 0;\n@p bra D_%=;\n"
      "add.u32 c, c, 1;\nsetp.lt.u32 p, c, %1;\n@p bra W_%=;\ntrap;\nD_%=:\n}\n" ::"r"(bar), "n"(SPIN_LIMIT) : "memory");
}
__device__ __forceinline__ uint32_t mbar_test(uint32_t bar) {
  uint32_t ok;
  asm volatile("{\n.reg .pred p;\nmbarrier.test_wait.parity.shared::cta.b64 p, [%1], 0;\nselp.u32 %0, 1, 0, p;\n}\n" : "=r"(ok) : "r"(bar) : "memory");
  return ok;
}
__device__ __forceinline__ void tma3(uint32_t dst, const CUtensorMap* m, int c0, int c1, int c2, uint32_t bar) {
  asm volatile("cp.async.bulk.tensor.3d.shared::cluster.global.mbarrier::complete_tx::bytes [%0], [%1, {%3,%4,%5}], [%2];"
               ::"r"(dst), "l"(m), "r"(bar), "r"(c0), "r"(c1), "r"(c2) : "memory");
}
__device__ __forceinline__ void tma4(uint32_t dst, const CUtensorMap* m, int c0, int c1, int c2, int c3, uint32_t bar) {
  asm volatile("cp.async.bulk.tensor.4d.shared::cluster.global.mbarrier::complete_tx::bytes [%0], [%1, {%3,%4,%5,%6}], [%2];"
               ::"r"(dst), "l"(m), "r"(bar), "r"(c0), "r"(c1), "r"(c2), "r"(c3) : "memory");
}
__device__ __forceinline__ void tma5(uint32_t dst, const CUtensorMap* m, int c0, int c1, int c2, int c3, int c4, uint32_t bar) {
  asm volatile("cp.async.bulk.tensor.5d.shared::cluster.global.mbarrier::complete_tx::bytes [%0], [%1, {%3,%4,%5,%6,%7}], [%2];"
               ::"r"(dst), "l"(m), "r"(bar), "r"(c0), "r"(c1), "r"(c2), "r"(c3), "r"(c4) : "memory");
}
__device__ __forceinline__ void bulk_g2s(uint32_t dst, const void* src, int bytes, uint32_t bar) {
  asm volatile("cp.async.bulk.shared::cluster.global.mbarrier::complete_tx::bytes [%0], [%1], %2, [%3];"
               ::"r"(dst), "l"(src), "r"(bytes), "r"(bar) : "memory");
}
__device__ __forceinline__ void bulk_s2g(void* dst, uint32_t src, int bytes) {
  asm volatile("cp.async.bulk.global.shared::cta.bulk_group [%0], [%1], %2;" ::"l"(dst), "r"(src), "r"(bytes) : "memory");
}
__device__ __forceinline__ void l2_prefetch(const void* src, int bytes) {
  asm volatile("cp.async.bulk.prefetch.L2.global [%0], %1;" ::"l"(src), "r"(bytes) : "memory");
}
__device__ __forceinline__ void wgmma_fence() { asm volatile("wgmma.fence.sync.aligned;" ::: "memory"); }
__device__ __forceinline__ void wgmma_commit() { asm volatile("wgmma.commit_group.sync.aligned;" ::: "memory"); }
template <int N> __device__ __forceinline__ void wgmma_wait() { asm volatile("wgmma.wait_group.sync.aligned %0;" ::"n"(N) : "memory"); }
__host__ __device__ constexpr uint32_t desc_lo(uint32_t addr, uint32_t lbo) { return ((addr & 0x3FFFF) >> 4) | ((lbo >> 4) << 16); }
__host__ __device__ constexpr uint32_t desc_hi(uint32_t sbo, uint32_t swz) { return (sbo >> 4) | (swz << 30); }
__device__ __forceinline__ void bar_sync(int id, int n) { asm volatile("bar.sync %0, %1;" ::"r"(id), "r"(n) : "memory"); }
__device__ __forceinline__ uint32_t lds32(uint32_t a) { uint32_t v; asm volatile("ld.shared.u32 %0, [%1];" : "=r"(v) : "r"(a) : "memory"); return v; }
__device__ __forceinline__ float2 lds64f(uint32_t a) { float2 v; asm volatile("ld.shared.v2.f32 {%0,%1}, [%2];" : "=f"(v.x), "=f"(v.y) : "r"(a) : "memory"); return v; }
__device__ __forceinline__ float4 lds128f(uint32_t a) { float4 v; asm volatile("ld.shared.v4.f32 {%0,%1,%2,%3}, [%4];" : "=f"(v.x), "=f"(v.y), "=f"(v.z), "=f"(v.w) : "r"(a) : "memory"); return v; }
__device__ __forceinline__ void ldsm4t(uint32_t (&r)[4], uint32_t a) {
  asm volatile("ldmatrix.sync.aligned.m8n8.x4.trans.shared.b16 {%0,%1,%2,%3}, [%4];" : "=r"(r[0]), "=r"(r[1]), "=r"(r[2]), "=r"(r[3]) : "r"(a) : "memory");
}
__device__ __forceinline__ uint4 ldv128(const void* a) { uint4 v; asm volatile("ld.global.nc.v4.u32 {%0,%1,%2,%3}, [%4];" : "=r"(v.x), "=r"(v.y), "=r"(v.z), "=r"(v.w) : "l"(a) : "memory"); return v; }
__device__ __forceinline__ uint2 ldv64(const void* a) { uint2 v; asm volatile("ld.global.nc.v2.u32 {%0,%1}, [%2];" : "=r"(v.x), "=r"(v.y) : "l"(a) : "memory"); return v; }
__device__ __forceinline__ uint32_t ldv16(const void* a) { uint32_t v; asm volatile("ld.global.nc.u16 %0, [%1];" : "=r"(v) : "l"(a) : "memory"); return v; }
__device__ __forceinline__ void sts128(uint32_t a, uint4 v) { asm volatile("st.shared.v4.u32 [%0], {%1,%2,%3,%4};" ::"r"(a), "r"(v.x), "r"(v.y), "r"(v.z), "r"(v.w) : "memory"); }
__device__ __forceinline__ void sts32(uint32_t a, uint32_t v) { asm volatile("st.shared.u32 [%0], %1;" ::"r"(a), "r"(v) : "memory"); }
__device__ __forceinline__ void sts64f(uint32_t a, float x, float y) { asm volatile("st.shared.v2.f32 [%0], {%1,%2};" ::"r"(a), "f"(x), "f"(y) : "memory"); }
__device__ __forceinline__ void red_rlx(unsigned* p) { asm volatile("red.relaxed.gpu.global.add.u32 [%0], 1;" ::"l"(p) : "memory"); }
__device__ __forceinline__ void red_rel(unsigned* p) { asm volatile("red.release.gpu.global.add.u32 [%0], 1;" ::"l"(p) : "memory"); }
__device__ __forceinline__ void fence_async_global() { asm volatile("fence.proxy.async.global;" ::: "memory"); }
__device__ __forceinline__ void fence_async_smem() { asm volatile("fence.proxy.async.shared::cta;" ::: "memory"); }
__device__ __forceinline__ void rec_st(uint4* p, float a, float b, unsigned tag) {
  asm volatile("{\n.reg .b128 t;\n.reg .b64 lo, hi;\nmov.b64 lo, {%1,%2};\nmov.b64 hi, {%3,%3};\nmov.b128 t, {lo,hi};\n"
               "st.relaxed.gpu.global.b128 [%0], t;\n}\n" ::"l"(p), "r"(__float_as_uint(a)), "r"(__float_as_uint(b)), "r"(tag) : "memory");
}
__device__ __forceinline__ unsigned rec_ld(const uint4* p, float& a, float& b) {
  unsigned x, y, t;
  asm volatile("{\n.reg .b128 t;\n.reg .b64 lo, hi;\n.reg .b32 u;\nld.relaxed.gpu.global.b128 t, [%3];\nmov.b128 {lo,hi}, t;\n"
               "mov.b64 {%0,%1}, lo;\nmov.b64 {%2,u}, hi;\n}\n" : "=r"(x), "=r"(y), "=r"(t) : "l"(p) : "memory");
  a = __uint_as_float(x); b = __uint_as_float(y);
  return t;
}
__device__ __forceinline__ unsigned ld_rlx(const unsigned* p) { unsigned v; asm volatile("ld.relaxed.gpu.global.u32 %0, [%1];" : "=r"(v) : "l"(p) : "memory"); return v; }
__device__ __forceinline__ void flag_poll(const unsigned* p, unsigned target) {
  uint32_t it = 0;
  while (!__all_sync(0xffffffffu, (int)(ld_rlx(p) - target) >= 0)) { trap_if(++it > SPIN_LIMIT); }
  asm volatile("fence.acquire.gpu;" ::: "memory");
}
__device__ __forceinline__ void cnt_poll(const unsigned* p, unsigned target) {
  unsigned a = ld_rlx(p); __nanosleep(100);
  unsigned b = ld_rlx(p); __nanosleep(100);
  unsigned c = ld_rlx(p);
  uint32_t it = 0;
  while (true) {
    if (__all_sync(0xffffffffu, (int)(a - target) >= 0)) break;
    a = ld_rlx(p);
    if (__all_sync(0xffffffffu, (int)(b - target) >= 0)) break;
    b = ld_rlx(p);
    if (__all_sync(0xffffffffu, (int)(c - target) >= 0)) break;
    c = ld_rlx(p);
    trap_if(++it > SPIN_LIMIT);
  }
  asm volatile("fence.acquire.gpu;" ::: "memory");
}
__device__ __forceinline__ void validate_block(uint32_t bar, uint32_t full, uint32_t dst, const uint8_t* src, uint32_t woff, uint32_t rb, uint32_t& ph) {
  uint32_t it = 0, par = 0;
  while (true) {
    uint32_t ok, spins = 0;
    do {
      asm volatile("{\n.reg .pred p;\nmbarrier.try_wait.parity.shared::cta.b64 p, [%1], %2;\nselp.u32 %0, 1, 0, p;\n}\n" : "=r"(ok) : "r"(bar), "r"(par) : "memory");
      trap_if(++spins > SPIN_LIMIT);
    } while (!__all_sync(0xffffffffu, ok));
    uint32_t bad = 0;
#pragma unroll
    for (int i = 0; i < 8; i++) bad |= lds32(dst + woff + 128 * i);
    if (!__any_sync(0xffffffffu, bad & 1)) break;
    if (elect_one()) { mbar_expect_tx(rb, 8192); bulk_g2s(dst, src, 8192, rb); }
    bar = rb; par = ph; ph ^= 1;
    trap_if(++it > 100000);
  }
  if ((threadIdx.x & 31) == 0) mbar_arrive(full);
}
__device__ __forceinline__ uint32_t tag_word(uint32_t v, uint32_t m, uint32_t par) {
  uint32_t r; asm("lop3.b32 %0, %1, %2, %3, 0xb8;" : "=r"(r) : "r"(v), "r"(m), "r"(par)); return r;
}
__device__ __forceinline__ void h_release(int idx, int T, int i) {
  const int Q = (i & 2) ? (T + 2) / 3 - 1 : T / 3;
  if (Q >= 0 && Q < 4 && ((i & 2) == 0 || T % 3 == 0)) red_rel(&g_hcnt[(idx * 8 + 2 * Q + (i & 1)) * 32]);
}
__device__ __forceinline__ uint32_t pack_bf16(float lo, float hi) {
  uint32_t r; asm("cvt.rn.bf16x2.f32 %0, %1, %2;" : "=r"(r) : "f"(hi), "f"(lo)); return r;
}
__device__ __forceinline__ float bf_lo(uint32_t w) { return __uint_as_float(w << 16); }
__device__ __forceinline__ float bf_hi(uint32_t w) { return __uint_as_float(w & 0xffff0000u); }
__device__ __forceinline__ uint32_t hmul2(uint32_t a, uint32_t b) {
  __nv_bfloat162 r = __hmul2_rn(*(__nv_bfloat162*)&a, *(__nv_bfloat162*)&b); return *(uint32_t*)&r;
}
__device__ __forceinline__ uint32_t hadd2(uint32_t a, uint32_t b) {
  __nv_bfloat162 r = __hadd2_rn(*(__nv_bfloat162*)&a, *(__nv_bfloat162*)&b); return *(uint32_t*)&r;
}
__device__ __forceinline__ float2 cmul(float2 a, float2 b) { return make_float2(a.x * b.x - a.y * b.y, a.x * b.y + a.y * b.x); }
__device__ __forceinline__ float2 cfma(float2 a, float2 b, float2 c) {
  return make_float2(fmaf(a.x, b.x, fmaf(-a.y, b.y, c.x)), fmaf(a.x, b.y, fmaf(a.y, b.x, c.y)));
}
template <int N> __device__ __forceinline__ void fence_regs(float (&a)[N]) {
#pragma unroll
  for (int i = 0; i < N; i++) asm volatile("" : "+f"(a[i])::"memory");
}
__device__ __forceinline__ int tid_opaque() { int t; asm volatile("mov.u32 %0, %%tid.x;" : "=r"(t)); return t; }
struct Role { int T1, GP, side, m2, dg, cch0; bool last, has2; };
__device__ __forceinline__ Role unpack_role(int x) {
  Role r; r.T1 = x & 15; r.GP = (x >> 4) & 7; r.side = (x >> 7) & 1; r.m2 = (x >> 8) & 63; r.dg = (x >> 14) & 3;
  r.has2 = (x >> 16) & 1; r.last = r.T1 == NT1 - 1; r.cch0 = 160 * r.dg + r.m2; return r;
}
__device__ __forceinline__ Role fresh_role(int x) { asm volatile("" : "+r"(x)); return unpack_role(__shfl_sync(0xffffffffu, x, 0)); }
#define ROLE(x) const Role R_ = fresh_role(x); const int T1 = R_.T1, GP = R_.GP, side = R_.side, m2 = R_.m2, dg = R_.dg, cch0 = R_.cch0; \
  const bool last = R_.last, has2 = R_.has2; (void)T1; (void)GP; (void)side; (void)m2; (void)dg; (void)cch0; (void)last; (void)has2;
__device__ __forceinline__ int n_to_t(int n) {
  int T = n / 160, nl = n - T * 160;
  int L = (T == NT1 - 1) ? 32 : 40;
  return T * 160 + L * ((nl & 7) >> 1) + 2 * (nl >> 3) + (nl & 1);
}

template<int TA> __device__ __forceinline__ void wgmma_n160(float (&d)[80], uint32_t alo, uint32_t ahi, uint32_t blo, uint32_t bhi){
  asm volatile("{\n.reg .b64 da, db;\nmov.b64 da, {%80,%81};\nmov.b64 db, {%82,%83};\n"
    "wgmma.mma_async.sync.aligned.m64n160k16.f32.bf16.bf16 {%0, %1, %2, %3, %4, %5, %6, %7, %8, %9, %10, %11, %12, %13, %14, %15, %16, %17, %18, %19, %20, %21, %22, %23, %24, %25, %26, %27, %28, %29, %30, %31, %32, %33, %34, %35, %36, %37, %38, %39, %40, %41, %42, %43, %44, %45, %46, %47, %48, %49, %50, %51, %52, %53, %54, %55, %56, %57, %58, %59, %60, %61, %62, %63, %64, %65, %66, %67, %68, %69, %70, %71, %72, %73, %74, %75, %76, %77, %78, %79}, da, db, 1, 1, 1, %84, 0;\n}\n"
    : "+f"(d[0]), "+f"(d[1]), "+f"(d[2]), "+f"(d[3]), "+f"(d[4]), "+f"(d[5]), "+f"(d[6]), "+f"(d[7]), "+f"(d[8]), "+f"(d[9]), "+f"(d[10]), "+f"(d[11]), "+f"(d[12]), "+f"(d[13]), "+f"(d[14]), "+f"(d[15]), "+f"(d[16]), "+f"(d[17]), "+f"(d[18]), "+f"(d[19]), "+f"(d[20]), "+f"(d[21]), "+f"(d[22]), "+f"(d[23]), "+f"(d[24]), "+f"(d[25]), "+f"(d[26]), "+f"(d[27]), "+f"(d[28]), "+f"(d[29]), "+f"(d[30]), "+f"(d[31]), "+f"(d[32]), "+f"(d[33]), "+f"(d[34]), "+f"(d[35]), "+f"(d[36]), "+f"(d[37]), "+f"(d[38]), "+f"(d[39]), "+f"(d[40]), "+f"(d[41]), "+f"(d[42]), "+f"(d[43]), "+f"(d[44]), "+f"(d[45]), "+f"(d[46]), "+f"(d[47]), "+f"(d[48]), "+f"(d[49]), "+f"(d[50]), "+f"(d[51]), "+f"(d[52]), "+f"(d[53]), "+f"(d[54]), "+f"(d[55]), "+f"(d[56]), "+f"(d[57]), "+f"(d[58]), "+f"(d[59]), "+f"(d[60]), "+f"(d[61]), "+f"(d[62]), "+f"(d[63]), "+f"(d[64]), "+f"(d[65]), "+f"(d[66]), "+f"(d[67]), "+f"(d[68]), "+f"(d[69]), "+f"(d[70]), "+f"(d[71]), "+f"(d[72]), "+f"(d[73]), "+f"(d[74]), "+f"(d[75]), "+f"(d[76]), "+f"(d[77]), "+f"(d[78]), "+f"(d[79])
    : "r"(alo), "r"(ahi), "r"(blo), "r"(bhi), "n"(TA));
}
__device__ __forceinline__ void wgmma_rs_n160(float (&d)[80], uint32_t a0, uint32_t a1, uint32_t a2, uint32_t a3, uint32_t blo){
  asm volatile("{\n.reg .b64 db;\nmov.b64 db, {%84,8};\nwgmma.mma_async.sync.aligned.m64n160k16.f32.bf16.bf16 {%0, %1, %2, %3, %4, %5, %6, %7, %8, %9, %10, %11, %12, %13, %14, %15, %16, %17, %18, %19, %20, %21, %22, %23, %24, %25, %26, %27, %28, %29, %30, %31, %32, %33, %34, %35, %36, %37, %38, %39, %40, %41, %42, %43, %44, %45, %46, %47, %48, %49, %50, %51, %52, %53, %54, %55, %56, %57, %58, %59, %60, %61, %62, %63, %64, %65, %66, %67, %68, %69, %70, %71, %72, %73, %74, %75, %76, %77, %78, %79}, {%80,%81,%82,%83}, db, 1, 1, 1, 0;\n}\n"
    : "+f"(d[0]), "+f"(d[1]), "+f"(d[2]), "+f"(d[3]), "+f"(d[4]), "+f"(d[5]), "+f"(d[6]), "+f"(d[7]), "+f"(d[8]), "+f"(d[9]), "+f"(d[10]), "+f"(d[11]), "+f"(d[12]), "+f"(d[13]), "+f"(d[14]), "+f"(d[15]), "+f"(d[16]), "+f"(d[17]), "+f"(d[18]), "+f"(d[19]), "+f"(d[20]), "+f"(d[21]), "+f"(d[22]), "+f"(d[23]), "+f"(d[24]), "+f"(d[25]), "+f"(d[26]), "+f"(d[27]), "+f"(d[28]), "+f"(d[29]), "+f"(d[30]), "+f"(d[31]), "+f"(d[32]), "+f"(d[33]), "+f"(d[34]), "+f"(d[35]), "+f"(d[36]), "+f"(d[37]), "+f"(d[38]), "+f"(d[39]), "+f"(d[40]), "+f"(d[41]), "+f"(d[42]), "+f"(d[43]), "+f"(d[44]), "+f"(d[45]), "+f"(d[46]), "+f"(d[47]), "+f"(d[48]), "+f"(d[49]), "+f"(d[50]), "+f"(d[51]), "+f"(d[52]), "+f"(d[53]), "+f"(d[54]), "+f"(d[55]), "+f"(d[56]), "+f"(d[57]), "+f"(d[58]), "+f"(d[59]), "+f"(d[60]), "+f"(d[61]), "+f"(d[62]), "+f"(d[63]), "+f"(d[64]), "+f"(d[65]), "+f"(d[66]), "+f"(d[67]), "+f"(d[68]), "+f"(d[69]), "+f"(d[70]), "+f"(d[71]), "+f"(d[72]), "+f"(d[73]), "+f"(d[74]), "+f"(d[75]), "+f"(d[76]), "+f"(d[77]), "+f"(d[78]), "+f"(d[79])
    : "r"(a0), "r"(a1), "r"(a2), "r"(a3), "r"(blo));
}
template<int N> __device__ __forceinline__ void wgmma_rs_hi(float (&d)[64], uint32_t a0, uint32_t a1, uint32_t a2, uint32_t a3, uint32_t blo);
template<> __device__ __forceinline__ void wgmma_rs_hi<16>(float (&d)[64], uint32_t a0, uint32_t a1, uint32_t a2, uint32_t a3, uint32_t blo){
  asm volatile("{\n.reg .b64 db;\nmov.b64 db, {%12,8};\nwgmma.mma_async.sync.aligned.m64n16k16.f32.bf16.bf16 {%0, %1, %2, %3, %4, %5, %6, %7}, {%8,%9,%10,%11}, db, 1, 1, 1, 0;\n}\n"
    : "+f"(d[56]), "+f"(d[57]), "+f"(d[58]), "+f"(d[59]), "+f"(d[60]), "+f"(d[61]), "+f"(d[62]), "+f"(d[63])
    : "r"(a0), "r"(a1), "r"(a2), "r"(a3), "r"(blo));
}
template<> __device__ __forceinline__ void wgmma_rs_hi<32>(float (&d)[64], uint32_t a0, uint32_t a1, uint32_t a2, uint32_t a3, uint32_t blo){
  asm volatile("{\n.reg .b64 db;\nmov.b64 db, {%20,8};\nwgmma.mma_async.sync.aligned.m64n32k16.f32.bf16.bf16 {%0, %1, %2, %3, %4, %5, %6, %7, %8, %9, %10, %11, %12, %13, %14, %15}, {%16,%17,%18,%19}, db, 1, 1, 1, 0;\n}\n"
    : "+f"(d[48]), "+f"(d[49]), "+f"(d[50]), "+f"(d[51]), "+f"(d[52]), "+f"(d[53]), "+f"(d[54]), "+f"(d[55]), "+f"(d[56]), "+f"(d[57]), "+f"(d[58]), "+f"(d[59]), "+f"(d[60]), "+f"(d[61]), "+f"(d[62]), "+f"(d[63])
    : "r"(a0), "r"(a1), "r"(a2), "r"(a3), "r"(blo));
}
template<> __device__ __forceinline__ void wgmma_rs_hi<48>(float (&d)[64], uint32_t a0, uint32_t a1, uint32_t a2, uint32_t a3, uint32_t blo){
  asm volatile("{\n.reg .b64 db;\nmov.b64 db, {%28,8};\nwgmma.mma_async.sync.aligned.m64n48k16.f32.bf16.bf16 {%0, %1, %2, %3, %4, %5, %6, %7, %8, %9, %10, %11, %12, %13, %14, %15, %16, %17, %18, %19, %20, %21, %22, %23}, {%24,%25,%26,%27}, db, 1, 1, 1, 0;\n}\n"
    : "+f"(d[40]), "+f"(d[41]), "+f"(d[42]), "+f"(d[43]), "+f"(d[44]), "+f"(d[45]), "+f"(d[46]), "+f"(d[47]), "+f"(d[48]), "+f"(d[49]), "+f"(d[50]), "+f"(d[51]), "+f"(d[52]), "+f"(d[53]), "+f"(d[54]), "+f"(d[55]), "+f"(d[56]), "+f"(d[57]), "+f"(d[58]), "+f"(d[59]), "+f"(d[60]), "+f"(d[61]), "+f"(d[62]), "+f"(d[63])
    : "r"(a0), "r"(a1), "r"(a2), "r"(a3), "r"(blo));
}
template<> __device__ __forceinline__ void wgmma_rs_hi<64>(float (&d)[64], uint32_t a0, uint32_t a1, uint32_t a2, uint32_t a3, uint32_t blo){
  asm volatile("{\n.reg .b64 db;\nmov.b64 db, {%36,8};\nwgmma.mma_async.sync.aligned.m64n64k16.f32.bf16.bf16 {%0, %1, %2, %3, %4, %5, %6, %7, %8, %9, %10, %11, %12, %13, %14, %15, %16, %17, %18, %19, %20, %21, %22, %23, %24, %25, %26, %27, %28, %29, %30, %31}, {%32,%33,%34,%35}, db, 1, 1, 1, 0;\n}\n"
    : "+f"(d[32]), "+f"(d[33]), "+f"(d[34]), "+f"(d[35]), "+f"(d[36]), "+f"(d[37]), "+f"(d[38]), "+f"(d[39]), "+f"(d[40]), "+f"(d[41]), "+f"(d[42]), "+f"(d[43]), "+f"(d[44]), "+f"(d[45]), "+f"(d[46]), "+f"(d[47]), "+f"(d[48]), "+f"(d[49]), "+f"(d[50]), "+f"(d[51]), "+f"(d[52]), "+f"(d[53]), "+f"(d[54]), "+f"(d[55]), "+f"(d[56]), "+f"(d[57]), "+f"(d[58]), "+f"(d[59]), "+f"(d[60]), "+f"(d[61]), "+f"(d[62]), "+f"(d[63])
    : "r"(a0), "r"(a1), "r"(a2), "r"(a3), "r"(blo));
}
template<> __device__ __forceinline__ void wgmma_rs_hi<80>(float (&d)[64], uint32_t a0, uint32_t a1, uint32_t a2, uint32_t a3, uint32_t blo){
  asm volatile("{\n.reg .b64 db;\nmov.b64 db, {%44,8};\nwgmma.mma_async.sync.aligned.m64n80k16.f32.bf16.bf16 {%0, %1, %2, %3, %4, %5, %6, %7, %8, %9, %10, %11, %12, %13, %14, %15, %16, %17, %18, %19, %20, %21, %22, %23, %24, %25, %26, %27, %28, %29, %30, %31, %32, %33, %34, %35, %36, %37, %38, %39}, {%40,%41,%42,%43}, db, 1, 1, 1, 0;\n}\n"
    : "+f"(d[24]), "+f"(d[25]), "+f"(d[26]), "+f"(d[27]), "+f"(d[28]), "+f"(d[29]), "+f"(d[30]), "+f"(d[31]), "+f"(d[32]), "+f"(d[33]), "+f"(d[34]), "+f"(d[35]), "+f"(d[36]), "+f"(d[37]), "+f"(d[38]), "+f"(d[39]), "+f"(d[40]), "+f"(d[41]), "+f"(d[42]), "+f"(d[43]), "+f"(d[44]), "+f"(d[45]), "+f"(d[46]), "+f"(d[47]), "+f"(d[48]), "+f"(d[49]), "+f"(d[50]), "+f"(d[51]), "+f"(d[52]), "+f"(d[53]), "+f"(d[54]), "+f"(d[55]), "+f"(d[56]), "+f"(d[57]), "+f"(d[58]), "+f"(d[59]), "+f"(d[60]), "+f"(d[61]), "+f"(d[62]), "+f"(d[63])
    : "r"(a0), "r"(a1), "r"(a2), "r"(a3), "r"(blo));
}
template<> __device__ __forceinline__ void wgmma_rs_hi<96>(float (&d)[64], uint32_t a0, uint32_t a1, uint32_t a2, uint32_t a3, uint32_t blo){
  asm volatile("{\n.reg .b64 db;\nmov.b64 db, {%52,8};\nwgmma.mma_async.sync.aligned.m64n96k16.f32.bf16.bf16 {%0, %1, %2, %3, %4, %5, %6, %7, %8, %9, %10, %11, %12, %13, %14, %15, %16, %17, %18, %19, %20, %21, %22, %23, %24, %25, %26, %27, %28, %29, %30, %31, %32, %33, %34, %35, %36, %37, %38, %39, %40, %41, %42, %43, %44, %45, %46, %47}, {%48,%49,%50,%51}, db, 1, 1, 1, 0;\n}\n"
    : "+f"(d[16]), "+f"(d[17]), "+f"(d[18]), "+f"(d[19]), "+f"(d[20]), "+f"(d[21]), "+f"(d[22]), "+f"(d[23]), "+f"(d[24]), "+f"(d[25]), "+f"(d[26]), "+f"(d[27]), "+f"(d[28]), "+f"(d[29]), "+f"(d[30]), "+f"(d[31]), "+f"(d[32]), "+f"(d[33]), "+f"(d[34]), "+f"(d[35]), "+f"(d[36]), "+f"(d[37]), "+f"(d[38]), "+f"(d[39]), "+f"(d[40]), "+f"(d[41]), "+f"(d[42]), "+f"(d[43]), "+f"(d[44]), "+f"(d[45]), "+f"(d[46]), "+f"(d[47]), "+f"(d[48]), "+f"(d[49]), "+f"(d[50]), "+f"(d[51]), "+f"(d[52]), "+f"(d[53]), "+f"(d[54]), "+f"(d[55]), "+f"(d[56]), "+f"(d[57]), "+f"(d[58]), "+f"(d[59]), "+f"(d[60]), "+f"(d[61]), "+f"(d[62]), "+f"(d[63])
    : "r"(a0), "r"(a1), "r"(a2), "r"(a3), "r"(blo));
}
template<> __device__ __forceinline__ void wgmma_rs_hi<112>(float (&d)[64], uint32_t a0, uint32_t a1, uint32_t a2, uint32_t a3, uint32_t blo){
  asm volatile("{\n.reg .b64 db;\nmov.b64 db, {%60,8};\nwgmma.mma_async.sync.aligned.m64n112k16.f32.bf16.bf16 {%0, %1, %2, %3, %4, %5, %6, %7, %8, %9, %10, %11, %12, %13, %14, %15, %16, %17, %18, %19, %20, %21, %22, %23, %24, %25, %26, %27, %28, %29, %30, %31, %32, %33, %34, %35, %36, %37, %38, %39, %40, %41, %42, %43, %44, %45, %46, %47, %48, %49, %50, %51, %52, %53, %54, %55}, {%56,%57,%58,%59}, db, 1, 1, 1, 0;\n}\n"
    : "+f"(d[8]), "+f"(d[9]), "+f"(d[10]), "+f"(d[11]), "+f"(d[12]), "+f"(d[13]), "+f"(d[14]), "+f"(d[15]), "+f"(d[16]), "+f"(d[17]), "+f"(d[18]), "+f"(d[19]), "+f"(d[20]), "+f"(d[21]), "+f"(d[22]), "+f"(d[23]), "+f"(d[24]), "+f"(d[25]), "+f"(d[26]), "+f"(d[27]), "+f"(d[28]), "+f"(d[29]), "+f"(d[30]), "+f"(d[31]), "+f"(d[32]), "+f"(d[33]), "+f"(d[34]), "+f"(d[35]), "+f"(d[36]), "+f"(d[37]), "+f"(d[38]), "+f"(d[39]), "+f"(d[40]), "+f"(d[41]), "+f"(d[42]), "+f"(d[43]), "+f"(d[44]), "+f"(d[45]), "+f"(d[46]), "+f"(d[47]), "+f"(d[48]), "+f"(d[49]), "+f"(d[50]), "+f"(d[51]), "+f"(d[52]), "+f"(d[53]), "+f"(d[54]), "+f"(d[55]), "+f"(d[56]), "+f"(d[57]), "+f"(d[58]), "+f"(d[59]), "+f"(d[60]), "+f"(d[61]), "+f"(d[62]), "+f"(d[63])
    : "r"(a0), "r"(a1), "r"(a2), "r"(a3), "r"(blo));
}
template<> __device__ __forceinline__ void wgmma_rs_hi<128>(float (&d)[64], uint32_t a0, uint32_t a1, uint32_t a2, uint32_t a3, uint32_t blo){
  asm volatile("{\n.reg .b64 db;\nmov.b64 db, {%68,8};\nwgmma.mma_async.sync.aligned.m64n128k16.f32.bf16.bf16 {%0, %1, %2, %3, %4, %5, %6, %7, %8, %9, %10, %11, %12, %13, %14, %15, %16, %17, %18, %19, %20, %21, %22, %23, %24, %25, %26, %27, %28, %29, %30, %31, %32, %33, %34, %35, %36, %37, %38, %39, %40, %41, %42, %43, %44, %45, %46, %47, %48, %49, %50, %51, %52, %53, %54, %55, %56, %57, %58, %59, %60, %61, %62, %63}, {%64,%65,%66,%67}, db, 1, 1, 1, 0;\n}\n"
    : "+f"(d[0]), "+f"(d[1]), "+f"(d[2]), "+f"(d[3]), "+f"(d[4]), "+f"(d[5]), "+f"(d[6]), "+f"(d[7]), "+f"(d[8]), "+f"(d[9]), "+f"(d[10]), "+f"(d[11]), "+f"(d[12]), "+f"(d[13]), "+f"(d[14]), "+f"(d[15]), "+f"(d[16]), "+f"(d[17]), "+f"(d[18]), "+f"(d[19]), "+f"(d[20]), "+f"(d[21]), "+f"(d[22]), "+f"(d[23]), "+f"(d[24]), "+f"(d[25]), "+f"(d[26]), "+f"(d[27]), "+f"(d[28]), "+f"(d[29]), "+f"(d[30]), "+f"(d[31]), "+f"(d[32]), "+f"(d[33]), "+f"(d[34]), "+f"(d[35]), "+f"(d[36]), "+f"(d[37]), "+f"(d[38]), "+f"(d[39]), "+f"(d[40]), "+f"(d[41]), "+f"(d[42]), "+f"(d[43]), "+f"(d[44]), "+f"(d[45]), "+f"(d[46]), "+f"(d[47]), "+f"(d[48]), "+f"(d[49]), "+f"(d[50]), "+f"(d[51]), "+f"(d[52]), "+f"(d[53]), "+f"(d[54]), "+f"(d[55]), "+f"(d[56]), "+f"(d[57]), "+f"(d[58]), "+f"(d[59]), "+f"(d[60]), "+f"(d[61]), "+f"(d[62]), "+f"(d[63])
    : "r"(a0), "r"(a1), "r"(a2), "r"(a3), "r"(blo));
}

struct CvCtx {
  uint32_t koff, zero, so[3];
  int srcA, srcB;
  bool wrapA, s3, kodd;
};
struct CvPipe { uint32_t Ap, Ep, keep, send; };
template <int LO> __device__ __forceinline__ void cv_copy(float (&acc)[64]) {
#pragma unroll
  for (int i = LO; i < 64; i++) { float t; asm volatile("mov.b32 %0, %1;" : "=f"(t) : "f"(acc[i]) : "memory"); acc[i] = t; }
}
template <int G> __device__ __forceinline__ void cv_raw(uint32_t (&A)[4][4], uint32_t kaddr) {
#pragma unroll
  for (int i = 0; i < 4; i++) {
    const uint32_t a = kaddr + (4 * G + i) * 128;
    A[i][0] = lds32(a); A[i][1] = lds32(a + 4); A[i][3] = lds32(a + 8);
  }
}
__device__ __forceinline__ void cv_form(uint32_t (&A)[4][4], uint32_t sel) {
#pragma unroll
  for (int i = 0; i < 4; i++) {
    asm volatile("prmt.b32 %0, %0, %1, %2;" : "+r"(A[i][0]) : "r"(A[i][1]), "r"(sel));
    asm volatile("prmt.b32 %0, %1, %2, %3;" : "=r"(A[i][2]) : "r"(A[i][1]), "r"(A[i][3]), "r"(sel));
  }
}
#define CVV 2
template <int G> __device__ __forceinline__ void cv_step(float (&acc)[64], uint32_t (&A)[4][4], CvPipe& s, const CvCtx& c, uint32_t cb, uint32_t stg) {
  constexpr int JA = G - 1, JB = G - 2, NH = CVV == 1 ? 4 : (CVV == 3 ? 2 : 1);
  const uint32_t db0 = desc_lo(cb + CV_U + 192, CV_PL);
  uint32_t B[4][4];
  uint32_t ra[2], rb;
  if constexpr (G < 8) {
    wgmma_fence();
#pragma unroll
    for (int i = 0; i < NH; i++) wgmma_rs_hi<128 - 16 * (G & 7)>(acc, A[i][0], A[i][1], A[i][2], A[i][3], db0 - 4 * i);
    wgmma_commit();
    __syncwarp();
  }
  if constexpr (JA >= 0 && JA < 8) {
    const uint32_t p0 = pack_bf16(acc[8 * JA + 1], acc[8 * JA + 3]), p1 = pack_bf16(acc[8 * JA + 5], acc[8 * JA + 7]);
    ra[0] = __shfl_sync(0xffffffffu, c.wrapA ? s.Ap : p0, c.srcA);
    ra[1] = __shfl_sync(0xffffffffu, c.wrapA ? p0 : p1, c.srcA);
    s.Ap = p1;
  }
  if constexpr (JB >= 0) rb = __shfl_sync(0xffffffffu, s.send, c.srcB);
  if constexpr (G < 7) cv_raw<G + 1>(B, cb + c.koff);
  uint32_t z = 0;
  if constexpr (G < 8 && NH < 4) {
    __syncwarp();
    wgmma_fence();
#pragma unroll
    for (int i = NH; i < 4; i++) wgmma_rs_hi<128 - 16 * (G & 7)>(acc, A[i][0], A[i][1], A[i][2], A[i][3], db0 - 4 * i);
    wgmma_commit();
    asm volatile("mov.u32 %0, %%clock;" : "=r"(z)::"memory");
    z &= c.zero;
  }
  if constexpr (G < 7) cv_form(B, 0x5432u | z);
  if constexpr (JB >= 0) sts32(stg + ((c.so[JB / 3] >> (10 * (JB % 3))) & 0xffc), hadd2(rb | z, s.keep));
  if constexpr (JA >= 0 && JA < 8) {
    const uint32_t sh = 16 | z, mk = 0xffff0000u | z;
    const uint32_t ev = pack_bf16(acc[8 * JA] + __uint_as_float(ra[0] << sh), acc[8 * JA + 2] + __uint_as_float(ra[0] & mk));
    const uint32_t od = pack_bf16(acc[8 * JA + 4] + __uint_as_float(ra[1] << sh), acc[8 * JA + 6] + __uint_as_float(ra[1] & mk));
    s.send = c.kodd ? ev : (c.s3 ? s.Ep : od);
    s.keep = c.kodd ? od : ev;
    s.Ep = od;
  }
  if constexpr (G < 8) { __syncwarp(); wgmma_wait<0>(); cv_copy<8 * (G & 7)>(acc); }
  if constexpr (G < 9) cv_step<G + 1>(acc, B, s, c, cb, stg);
}
__device__ __forceinline__ uint32_t cv_stage(int slot) { return sb + (slot < 4 ? 40960 + slot * 4096 : CV_OFF + CV_K); }
__device__ __forceinline__ void cv_setup(CvCtx& c) {
  const int tid = tid_opaque() & 127, w = tid >> 5, lane = tid & 31, r = lane >> 2, q = lane & 3;
  const int i0 = (r >> 1) & 1, i1 = r >> 2;
  c.koff = CV_K - 32 + 4 * (8 * (r >> 1) + 2 * w + (r & 1) + 2 * q);
  c.srcA = i0 ? lane - 8 : lane + 8 - q + ((q + 3) & 3);
  c.wrapA = i0 && q == 3;
  c.srcB = i1 == 0 ? (lane - q + 16 + ((q + 3) & 3)) : (lane - q - 16 + ((q + 1) & 3));
  c.s3 = (i1 == 1 && q == 3); c.kodd = (i1 == 1 && q < 3);
  c.zero = lds32(sb + EP_OFF + 24);
#pragma unroll
  for (int i = 0; i < 3; i++) c.so[i] = lds32(sb + SO_OFF + 512 * i + 4 * tid);
}
__device__ __forceinline__ void cv_table() {
  const int tid = tid_opaque() & 127, r = (tid & 31) >> 2, q = tid & 3;
  int t = 16 * (2 * (r < 4 ? q : 4 + ((q + 1) & 3)) + ((r >> 1) & 1)) + 4 * (tid >> 5) + 2 * (r & 1);
#pragma unroll 1
  for (int i = 0; i < 3; i++) {
    uint32_t v = 0;
#pragma unroll 1
    for (int x = 0; x < 3; x++, t += 256) {
      const int T = t / 160, tl = t - T * 160;
      const int qq = (T >= NT1 - 1) ? (tl >> 5) : (tl / 40);
      int ck = 20 * T + ((tl - qq * ((T >= NT1 - 1) ? 32 : 40)) >> 1);
      ck ^= (ck >> 2) & 6;
      v |= (uint32_t)((ck * 4 + qq) & 1023) << (10 * x + 2);
    }
    sts32(sb + SO_OFF + 512 * i + 4 * tid, v);
  }
}
__device__ __forceinline__ void conv_channel(int slot, const CvCtx& c) {
  const uint32_t cb = sb + CV_OFF + slot * CV_B;
  float acc[64];
  CvPipe s;
  s.Ap = s.Ep = 0u;
  uint32_t A[4][4];
#pragma unroll
  for (int i = 0; i < 64; i++) acc[i] = 0.f;
  if (slot == 4) mbar_wait(bars + 8 * B_CVDONE);
  mbar_wait(bars + 8 * (B_CVFULL + slot));
  cv_raw<0>(A, cb + c.koff);
  {
    const uint32_t w0 = lds32(cb + CV_K);
    const uint32_t wp = __byte_perm(pack_bf16(bf_lo(w0) + __uint_as_float(lds32(sb + EP_OFF + 4 * slot)), 0.f), w0, 0x7610);
    if (c.koff == CV_K) A[0][0] = wp;
    if (c.koff == CV_K - 4) A[0][1] = wp;
    if (c.koff == CV_K - 8) A[0][3] = wp;
  }
  cv_form(A, 0x5432u);
  cv_copy<0>(acc);
  cv_step<0>(acc, A, s, c, cb, cv_stage(slot));
  fence_async_smem();
  mbar_arrive(bars + 8 * (B_CVDONE + slot));
}

__device__ __forceinline__ void kv_issue(const Params& p, int c, int m2, int dg) {
  const uint32_t fb = bars + 8 * (B_KV + c);
  mbar_expect_tx(fb, KV_PIECE);
  tma3(sb + KS_OFF + c * KV_PIECE, &p.mK, 160 * dg + 32 * c, 64 * m2 - 3, 0, fb);
  tma3(sb + KS_OFF + c * KV_PIECE + 4864, &p.mV, 160 * dg + 32 * c, 64 * m2 - 1, 0, fb);
}
__device__ __forceinline__ void kv_tile(int m, int c, int y, uint32_t (&o)[4][4]) {
  const int lane = tid_opaque() & 31, tg = lane & 3, pr = 8 * (y ^ (tg >> 1)) + (lane >> 2);
  const uint32_t pb = sb + KS_OFF + c * KV_PIECE + 4 * pr;
  const uint32_t ka = pb + tg * 1216, va = pb + 4864 + tg * 1088 + 64;
  const uint32_t kh = (m == 0 && tg > 0) ? ka - 192 : ka;
  uint32_t kk[19], u[16];
  const float4 t = lds128f(sb + TAP_OFF + 256 * c + 16 * pr);
#pragma unroll
  for (int i = 0; i < 19; i++) { kk[i] = lds32((i < 3 ? kh : ka) + i * 64); if (i >= 3) u[i - 3] = lds32(va + (i - 3) * 64); }
  const uint32_t dst = sb + KS_OFF + c * KV_PIECE + pr * 64 + tg * 16;
  if (y) {
    __syncwarp();
#pragma unroll
    for (int x = 0; x < 4; x++) sts128((dst ^ 512) + x * 1024, make_uint4(o[x][0], o[x][1], o[x][2], o[x][3]));
  }
  const uint32_t w0 = __byte_perm(__float_as_uint(t.x), __float_as_uint(t.z), 0x5410), w1 = __byte_perm(__float_as_uint(t.x), __float_as_uint(t.z), 0x7632);
  const uint32_t w2 = __byte_perm(__float_as_uint(t.y), __float_as_uint(t.w), 0x5410), w3 = __byte_perm(__float_as_uint(t.y), __float_as_uint(t.w), 0x7632);
#pragma unroll
  for (int i = 0; i < 16; i++) {
    uint32_t a = hmul2(kk[i], w3);
    a = hadd2(a, hmul2(kk[i + 1], w2)); a = hadd2(a, hmul2(kk[i + 2], w1)); a = hadd2(a, hmul2(kk[i + 3], w0));
    u[i] = hmul2(a, u[i]);
  }
#pragma unroll
  for (int x = 0; x < 4; x++) {
#pragma unroll
    for (int qq = 0; qq < 4; qq++) o[x][qq] = __byte_perm(u[15 - 4 * qq - (x & 2)], u[14 - 4 * qq - (x & 2)], (x & 1) ? 0x7632 : 0x5410);
    if (y) sts128(dst + x * 1024, make_uint4(o[x][0], o[x][1], o[x][2], o[x][3]));
  }
}
__device__ __forceinline__ void ln_finish(float s1, float s2, float& mean, float& rstd) {
  mean = s1 * (1.f / 640.f);
  const float v = fmaxf(fmaf(-mean, mean, s2 * (1.f / 640.f)), 0.f) + 1e-5f;
  asm("rsqrt.approx.ftz.f32 %0, %1;" : "=f"(rstd) : "f"(v));
}
__device__ __forceinline__ void stat_table(int T1, unsigned want, int l, int g, const uint4* x0, const uint4* x1, float (&xa)[2], float (&xb)[2]) {
  const int n = 32 * g + (tid_opaque() & 31);
  const uint4* rp = &g_stats[8 * l * SEQ + min(160 * T1 + n, SEQ - 1)];
  float a[4], b[4];
  uint32_t it = 0;
  while (true) {
    bool ok = true;
#pragma unroll
    for (int i = 0; i < 4; i++) ok &= (rec_ld(rp + SEQ * i, a[i], b[i]) == want);
    ok &= rec_ld(x0, xa[0], xb[0]) == want;
    ok &= rec_ld(x1, xa[1], xb[1]) == want;
    if (__all_sync(0xffffffffu, ok)) break;
    trap_if(++it > SPIN_LIMIT);
  }
  float m, rs;
  ln_finish((a[0] + a[1]) + (a[2] + a[3]), (b[0] + b[1]) + (b[2] + b[3]), m, rs);
  sts32(sb + STAB_OFF + ((n >> 1) & 3) * 160 + (n >> 3) * 8 + (n & 1) * 4, __float_as_uint(rs));
  const uint32_t hi = pack_bf16(-m, -m);
  const float lo = -m - bf_lo(hi);
  sts128(sb + (l ? MX1_OFF : MX0_OFF) + n * 16, make_uint4(hi, pack_bf16(lo, lo), 0u, 0u));
  fence_async_smem();
}
__device__ __forceinline__ void stats_reduce(float (&a)[2], float (&b)[2], float (&mean)[2], float (&rstd)[2]) {
#pragma unroll
  for (int o = 1; o < 4; o <<= 1)
#pragma unroll
    for (int h = 0; h < 2; h++) { a[h] += __shfl_xor_sync(0xffffffffu, a[h], o); b[h] += __shfl_xor_sync(0xffffffffu, b[h], o); }
#pragma unroll
  for (int h = 0; h < 2; h++) ln_finish(a[h], b[h], mean[h], rstd[h]);
}

template <bool FIRST>
__device__ __forceinline__ void stats_publish(int which, int n0, int dg, unsigned tag, const float (&acc)[80]) {
  const int q = tid_opaque() & 3, h = q & 1;
  float s1[2] = {0.f, 0.f}, s2[2] = {0.f, 0.f}, t1[2] = {0.f, 0.f}, t2[2] = {0.f, 0.f};
#pragma unroll
  for (int j = 0; j < 20; j++)
#pragma unroll
    for (int y = 0; y < 2; y++) {
      const float a = acc[4 * j + 2 * y], b = acc[4 * j + 2 * y + 1];
      s1[y] += a; t1[y] += b; s2[y] = fmaf(a, a, s2[y]); t2[y] = fmaf(b, b, t2[y]);
    }
#pragma unroll
  for (int y = 0; y < 2; y++) { s1[y] += t1[y]; s2[y] += t2[y]; }
  float a = (h ? s1[1] : s1[0]) + __shfl_xor_sync(0xffffffffu, h ? s1[0] : s1[1], 1);
  float b = (h ? s2[1] : s2[0]) + __shfl_xor_sync(0xffffffffu, h ? s2[0] : s2[1], 1);
  a += __shfl_xor_sync(0xffffffffu, a, 2);
  b += __shfl_xor_sync(0xffffffffu, b, 2);
  if (FIRST) {
    rec_st(&g_stats[((q >> 1) * 4 + dg) * SEQ + n0 + 8 * h], a, b, q < 2 ? tag : tag - 1);
    rec_st(&g_stats[((q >> 1) * 4 + 8 + dg) * SEQ + n0 + 8 * h], a, b, tag - 1);
  } else if (q < 2) rec_st(&g_stats[(which * 4 + dg) * SEQ + n0 + 8 * h], a, b, tag);
}
__device__ __forceinline__ void stats_get(int which, int n0, unsigned tag, float (&mean)[2], float (&rstd)[2]) {
  const uint4* p0 = &g_stats[(which * 4 + (tid_opaque() & 3)) * SEQ + n0];
  float a[2], b[2];
  uint32_t it = 0;
  while (true) {
    const unsigned t0 = rec_ld(p0, a[0], b[0]), t1 = rec_ld(p0 + 8, a[1], b[1]);
    if (__all_sync(0xffffffffu, t0 == tag && t1 == tag)) break;
    trap_if(++it > SPIN_LIMIT);
  }
  stats_reduce(a, b, mean, rstd);
}
__device__ __forceinline__ void x0_load(float (&acc)[80]) {
  const int t = tid_opaque() & 127;
  const uint32_t xa = sb + XT_OFF + (16 * (t >> 5) + ((t & 31) >> 2)) * 320 + 8 * (t & 3);
  mbar_wait(bars + 8 * B_XT);
#pragma unroll
  for (int h = 0; h < 2; h++)
#pragma unroll
    for (int J = 0; J < 10; J++) {
      const float2 v = lds64f(xa + h * 2560 + 32 * J);
      const uint32_t x = __float_as_uint(v.x), y = __float_as_uint(v.y);
      acc[8 * J + 2 * h] = bf_lo(x); acc[8 * J + 2 * h + 1] = bf_hi(x);
      acc[8 * J + 4 + 2 * h] = bf_lo(y); acc[8 * J + 4 + 2 * h + 1] = bf_hi(y);
    }
}

template <bool FROM_X0>
__device__ __forceinline__ void dskip_init(float (&acc)[80], const float (&mean)[2], const float (&rstd)[2]) {
  const int t = tid_opaque() & 127;
  const uint32_t xa = sb + XT_OFF + (16 * (t >> 5) + ((t & 31) >> 2)) * 320 + 8 * (t & 3), da = sb + DTAB_OFF + 8 * (t & 3);
  float2 dw[10], xv[10][2];
#pragma unroll
  for (int J = 0; J < 2; J++) { dw[J] = lds64f(da + 32 * J); if (FROM_X0) { xv[J][0] = lds64f(xa + 32 * J); xv[J][1] = lds64f(xa + 2560 + 32 * J); } }
#pragma unroll
  for (int J = 0; J < 10; J++) {
    if (J + 2 < 10) { dw[J + 2] = lds64f(da + 32 * (J + 2)); if (FROM_X0) { xv[J + 2][0] = lds64f(xa + 32 * (J + 2)); xv[J + 2][1] = lds64f(xa + 2560 + 32 * (J + 2)); } }
#pragma unroll
    for (int x = 0; x < 8; x++) {
      const int h = (x >> 1) & 1;
      const uint32_t dwd = __float_as_uint(x < 4 ? dw[J].x : dw[J].y);
      const float tt = fmaf(rstd[h], (x & 1) ? bf_hi(dwd) : bf_lo(dwd), 1.f);
      float a = acc[8 * J + x];
      if (FROM_X0) { const uint32_t xw = __float_as_uint(x < 4 ? xv[J][h].x : xv[J][h].y); a = (x & 1) ? bf_hi(xw) : bf_lo(xw); }
      acc[8 * J + x] = FROM_X0 ? (a - mean[h]) * tt : fmaf(a, tt, -mean[h] * tt);
    }
  }
}

__global__ void __launch_bounds__(512, 1) fused_kernel(const __grid_constant__ Params p) {
  extern __shared__ __align__(1024) uint8_t smem_raw[];
  const int tid = threadIdx.x, lane = tid & 31;
  const int wid = __shfl_sync(0xffffffffu, tid >> 5, 0), wg = wid >> 2;
  unsigned smid; asm volatile("mov.u32 %0, %%smid;" : "=r"(smid));
  const int role = p.role[min(smid, 131u)];
  if (wid == 12) {
    const bool el = elect_one();
    if (el) {
      asm volatile("prefetch.tensormap [%0];" ::"l"(&p.mB) : "memory");
      asm volatile("prefetch.tensormap [%0];" ::"l"((role & 15) == NT1 - 1 ? &p.mXl : &p.mX) : "memory");
#pragma unroll
      for (int k = 0; k < S1; k++) mbar_init(bars + 8 * (B_G1FULL + k), 1);
#pragma unroll
      for (int k = 0; k < 6; k++) mbar_init(bars + 8 * (B_XT + k), 1);
      asm volatile("fence.mbarrier_init.release.cluster;" ::: "memory");
    }
    if (role >= 0) {
      __syncwarp();
      asm volatile("bar.arrive 5, 288;" ::: "memory");
      const Role R = unpack_role(role);
      if (elect_one()) {
        TS(45);
#pragma unroll 1
        for (int k = 0; k < S1; k++) {
          const uint32_t fb = bars + 8 * (B_G1FULL + k);
          mbar_expect_tx(fb, G1_STAGE);
          tma4(sb + k * G1_STAGE + G1_XOFF, R.last ? &p.mXl : &p.mX, 64 * k, 0, 0, R.last ? 0 : 80 * R.T1, fb);
          tma5(sb + k * G1_STAGE, &p.mB, 64 * k, 0, 0, 4 * R.side, 2 * R.GP, fb);
          if (PFD) asm volatile("prefetch.tensormap [%0];" ::"l"(&p.mK + k) : "memory");
        }
        if (R.has2) {
          mbar_expect_tx(bars + 8 * B_XT, 20480);
#pragma unroll 1
          for (int h = 0; h < 2; h++) {
            const int ng = 8 * R.m2 + 4 * h, T = ng / 20;
            tma4(sb + XT_OFF + h * 10240, T == NT1 - 1 ? &p.mXtl : &p.mXt, 160 * R.dg, 0, 0, T == NT1 - 1 ? ng - 240 : ng + 60 * T, bars + 8 * B_XT);
          }
#pragma unroll 1
          for (int c = 0; c < KV0; c++) kv_issue(p, c, R.m2, R.dg);
        }
        TS(44);
      }
      __syncwarp();
      bar_sync(6, 64);
    }
  }
  trap_if(smid >= 132 || smem_u32(smem_raw) != sb);
  if (role < 0) {
    if (wid == 0) {
      const unsigned tag = ld_rlx(g_epoch);
      uint32_t it = 0;
      while (!__all_sync(0xffffffffu, (int)(ld_rlx(&g_hcnt[(lane & 7) * 32]) - 40 * tag) >= 0)) { __nanosleep(500); trap_if(++it > SPIN_LIMIT); }
    }
    return;
  }
  float mean0[2] = {0.f, 0.f}, rstd0[2] = {0.f, 0.f};
  if (wg == 2 || wid == 14) {
    ROLE(role)
    const int c = wid == 14 ? 4 : wid - 8;
    const unsigned tag = ld_rlx(g_epoch);
    if (has2) {
      uint2 bv[2][5];
#pragma unroll
      for (int x = 0; x < 2; x++)
#pragma unroll
        for (int i = 0; i < 5; i++) bv[x][i] = ldv64((const uint2*)((x ? p.bim : p.bre) + (cch0 + 32 * c) * DM) + lane + 32 * i);
      float sv[2];
#pragma unroll
      for (int x = 0; x < 2; x++) {
        float a = 0.f;
#pragma unroll
        for (int i = 0; i < 5; i++) a += (bf_lo(bv[x][i].x) + bf_hi(bv[x][i].x)) + (bf_lo(bv[x][i].y) + bf_hi(bv[x][i].y));
        sv[x] = a;
      }
#pragma unroll
      for (int o = 16; o > 0; o >>= 1) { sv[0] += __shfl_xor_sync(0xffffffffu, sv[0], o); sv[1] += __shfl_xor_sync(0xffffffffu, sv[1], o); }
      if (lane < 2) rec_st(&g_sB[(cch0 + 32 * c) * 2 + lane], sv[0], sv[1], tag);
      if (tid == 256) TS(47);
      __syncwarp();
      bar_sync(8, 192);
      if (wg == 2) {
        float xs[80];
        x0_load(xs);
        stats_publish<true>(0, 64 * m2 + 16 * c + (lane >> 2), dg, tag, xs);
        if (tid == 256) TS(31);
      }
      mbar_wait(bars + 8 * B_EP);
      mbar_wait(bars + 8 * (B_KV + c));
      mbar_wait(bars + 8 * (B_G1DONE + PAUSE_K - 1));
      if (tid == 448) TS(52);
      uint32_t o[4][4] = {};
#pragma unroll 1
      for (int y = 0; y < 2; y++) kv_tile(m2, c, y, o);
      fence_async_smem();
      __syncwarp();
      if (lane == 0) { mbar_arrive(bars + 8 * B_PREP); mbar_arrive(bars + 8 * (B_PD + c)); }
      if (tid == 448) TS(51);
    } else bar_sync(8, 192);
    {
      const uint4* x0 = wg == 2 ? &g_stats[(lane & 3) * SEQ + (has2 ? 64 * m2 : 0) + 16 * c + (lane >> 2)] : &g_sB[(128 * GP + 32 * side + lane) * 2];
      float xa[2], xb[2];
      stat_table(T1, tag, 0, c, x0, x0 + (wg == 2 ? 8 : 128), xa, xb);
      if (wg == 2) stats_reduce(xa, xb, mean0, rstd0);
      else {
#pragma unroll
        for (int i = 0; i < 2; i++) {
          const float ha = bf_lo(pack_bf16(xa[i], 0.f)), hb = bf_lo(pack_bf16(xb[i], 0.f));
          const float pa = __uint_as_float(pack_bf16(ha, xa[i] - ha)), pb = __uint_as_float(pack_bf16(hb, xb[i] - hb));
          sts64f(sb + CTAB_OFF + (32 * i + lane) * 24 + 16, p.swap ? pb : pa, p.swap ? pa : pb);
        }
      }
      mbar_arrive(bars + 8 * B_STAB);
      if (tid == 448) TS(26);
    }
  } else if (wid == 15) {
    ROLE(role)
    const int ch = 128 * GP + 32 * side + lane;
    uint32_t r0 = ldv16(p.lre + ch), r1 = ldv16(p.lim + ch), r2 = ldv16(p.logdt + ch);
    const uint32_t r3 = ldv16(p.lre + ch + 64), r4 = ldv16(p.lim + ch + 64), r5 = ldv16(p.logdt + ch + 64);
#pragma unroll 1
    for (int i = 0; i < 2; i++) {
      const float lr = bf_lo(r0), li = bf_lo(r1);
      const float dt = __bfloat162float(__float2bfloat16_rn(expf(bf_lo(r2))));
      const float mag = expf(dt * lr);
      float sn, cs; sincospif(dt * li * 0.31830988618379067f, &sn, &cs);
      const float ar = mag * cs, ai = mag * sn;
      const float inv = 2.f / (lr * lr + li * li);
      const uint32_t ad = sb + CTAB_OFF + (32 * i + lane) * 24;
      sts64f(ad, ar, ai);
      sts64f(ad + 8, ((ar - 1.f) * lr + ai * li) * inv, (ai * lr - (ar - 1.f) * li) * inv);
      r0 = r3; r1 = r4; r2 = r5;
    }
    if (lane == 0) TS(46);
    __syncwarp();
    bar_sync(7, 64);
    mbar_arrive(bars + 8 * B_CTAB);
  } else if (wid == 13) {
    ROLE(role)
    uint4 tv[3];
    const uint32_t e0 = ld_rlx(g_epoch);
    const uint32_t e1 = ldv16(p.ssmD + min(cch0 + 32 * lane, 639));
    const uint4 dv = ldv128((const uint4*)(p.dskip + 160 * dg) + min(lane, 19));
#pragma unroll
    for (int i = 0; i < 3; i++) tv[i] = ldv128((const uint4*)(p.shiftk + 640 * dg) + min(lane + 32 * i, 79));
    sts128(sb + DTAB_OFF + 16 * min(lane, 19), dv);
#pragma unroll
    for (int i = 0; i < 3; i++) sts128(sb + TAP_OFF + 16 * min(lane + 32 * i, 79), tv[i]);
    if (lane < 7) sts32(sb + EP_OFF + 4 * lane, lane < 5 ? e1 << 16 : (lane == 5 ? e0 : 0u));
    __syncwarp();
    bar_sync(9, 64);
    mbar_arrive(bars + 8 * B_CTAB);
    if (lane == 0) { mbar_arrive(bars + 8 * B_EP); TS(53); }
    if (has2) {
#pragma unroll 1
      for (int i = 0; i < 5; i++) {
        const int c = i == 2 ? 3 : (i == 3 ? 2 : i);
        mbar_wait(bars + 8 * (B_PD + c));
        if (lane == 0) bulk_s2g(g_kv + (dg * 32 + m2) * 20480 + c * 4096, sb + KS_OFF + c * KV_PIECE, 4096);
      }
      if (lane == 0) {
        asm volatile("cp.async.bulk.commit_group;" ::: "memory");
        asm volatile("cp.async.bulk.wait_group 0;" ::: "memory");
        mbar_arrive(bars + 8 * B_PREP2);
        fence_async_global();
      }
      __syncwarp();
      if (lane < 4) red_rel(&g_kvcnt[(dg * 4 + lane) * 32]);
      __syncwarp();
      if (lane == 0) { mbar_arrive(bars + 8 * B_PUB); TS(30); }
    }
  } else if (wid != 12) {
    if (elect_one()) {
      if (wid < 7) {
        const int b0 = wid < 4 ? 4 + 19 * wid : 85 + 21 * (wid - 4), cnt = wid < 4 ? 2 : 1;
#pragma unroll
        for (int i = 0; i < 21; i++) mbar_init(bars + 8 * (b0 + i), cnt);
#pragma unroll
        for (int i = 0; i < 5; i++) mbar_init(bars + 8 * (B_PD + 5 * wid + i), 1);
      } else {
#pragma unroll
        for (int i = 0; i < 12; i++) mbar_init(bars + 8 * (B_CVDONE + i), (i == 5 || i == 6) ? 160 : 128);
        mbar_init(bars + 8 * B_CTAB, 192); mbar_init(bars + 8 * B_PREP, 5); mbar_init(bars + 8 * B_PREP2, 1);
      }
      asm volatile("fence.mbarrier_init.release.cluster;" ::: "memory");
    }
    __syncwarp();
    bar_sync(5, 288);
    if (wid == 2) asm volatile("bar.arrive 8, 192;\nbar.arrive 6, 64;\nbar.arrive 9, 64;\nbar.arrive 7, 64;" ::: "memory");
    if (tid == 128) TS(0);
    if (wg == 1) { cv_table(); mbar_arrive(bars + 8 * B_CTAB); }
  }

  if (wid == 12) {
    ROLE(role)
    uint32_t dst = sb;
#pragma unroll 1
    for (int k = S1; k < 10; k++) {
      const uint32_t fb = bars + 8 * (B_G1FULL + k);
      mbar_wait(bars + 8 * (B_G1DONE + k - S1));
      if (elect_one()) {
        mbar_expect_tx(fb, 20480);
        tma4(dst + G1_XOFF, last ? &p.mXl : &p.mX, 64 * k, 0, 0, last ? 0 : 80 * T1, fb);
        mbar_expect_tx(fb, 16384);
        tma5(dst, &p.mB, 64 * k, 0, 0, 4 * side, 2 * GP, fb);
        if (has2 && k - S1 + KV0 < 5) kv_issue(p, k - S1 + KV0, m2, dg);
      }
      dst += G1_STAGE; if (k == 2 * S1 - 1) dst = sb;
    }
  } else if (wid == 15 && (role >> 16)) {
    ROLE(role)
    if (TPF >= 0) {
      mbar_wait(bars + 8 * (B_KV + TPF));
      if (elect_one()) {
#pragma unroll
        for (int c = 0; c < 5; c++) l2_prefetch(p.ssmk + (cch0 + 32 * c) * SEQ, 4096);
        if (CPF) { l2_prefetch(p.cre + (160 * dg + 5 * m2) * DM, 6400); l2_prefetch(p.cim + (160 * dg + 5 * m2) * DM, 6400); }
      }
    }
    mbar_wait(bars + 8 * B_PREP2);
    if (lane < 10) sts128(sb + CV_OFF + (lane >> 1) * CV_B + CV_K - 32 + 16 * (lane & 1), make_uint4(0, 0, 0, 0));
    fence_async_smem();
    __syncwarp();
    const unsigned tag = lds32(sb + EP_OFF + 20);
    if (TAPW) mbar_wait(bars + 8 * B_PUB);
    if (elect_one()) {
#pragma unroll 1
      for (int c = 0; c < 5; c++) {
        if (c == 0) asm volatile("prefetch.tensormap [%0];" ::"l"(&p.mU) : "memory");
        mbar_expect_tx(bars + 8 * (B_CVFULL + c), 4096 + 2 * CV_PL);
        if (c < TAPN) bulk_g2s(sb + CV_OFF + c * CV_B + CV_K, p.ssmk + (cch0 + 32 * c) * SEQ, 4096, bars + 8 * (B_CVFULL + c));
      }
    }
    mbar_wait(bars + 8 * B_PUB);
    cnt_poll(&g_kvcnt[(dg * 4 + (m2 >> 3)) * 32], 32 * tag);
    fence_async_global();
    if (elect_one()) {
      TS(28);
#pragma unroll
      for (int c = 0; c < 5; c++) {
        tma5(sb + CV_OFF + c * CV_B + CV_U, &p.mU, 0, -3, 2 * c, 16 * (m2 & 1) + (m2 >> 1), dg, bars + 8 * (B_CVFULL + c));
        if (c >= TAPN) bulk_g2s(sb + CV_OFF + c * CV_B + CV_K, p.ssmk + (cch0 + 32 * c) * SEQ, 4096, bars + 8 * (B_CVFULL + c));
      }
#pragma unroll
      for (int i = 0; i < 3; i++) asm volatile("prefetch.tensormap [%0];" ::"l"(&p.mCre + i) : "memory");
      TS(54);
    }
    __syncwarp();
  }
  {
    const int w = wid & 3;
    if (wg == 2 && !(role >> 16)) {
      float xa[2], xb[2];
      mbar_wait(bars + 8 * (B_G1FULL + 11));
      stat_table(role & 15, lds32(sb + EP_OFF + 20), 1, w, g_stats, g_stats, xa, xb);
      mbar_arrive(bars + 8 * (B_STAB + 1));
    }
#pragma unroll 1
    for (int l = 0; l < 2; l++) {
      if (wg < 2) {
        float acc[80];
#pragma unroll
        for (int i = 0; i < 80; i++) acc[i] = 0.f;
        ROLE(role)
        const int tid = tid_opaque(), r = (tid & 31) >> 2, q = tid & 3;
        const int ch = 128 * GP + 64 * wg + 32 * side + 8 * w + r;
        const uint32_t ca = sb + CTAB_OFF + (32 * wg + 8 * w + r) * 24;
        float2 lam = make_float2(0.f, 0.f), p8 = lam, p16 = lam, pL = lam, p2L = lam;
        fence_regs(acc);
        {
          const uint32_t alo0 = (l == 0 ? desc_lo(sb, 16) : desc_lo(sb + G2_WOFF, 16)) + wg * 512;
          const uint32_t blo0 = l == 0 ? desc_lo(sb + G1_XOFF, 16) : desc_lo(sb + X1_OFF, 128);
          const uint32_t bhi = l == 0 ? desc_hi(1024, 1) : desc_hi(1024, 0), xstep = l == 0 ? 2 : 16;
          const uint32_t astep = l == 0 ? G1_STAGE >> 4 : 1024, bstep = l == 0 ? G1_STAGE >> 4 : 1280, aend = alo0 + (S1 + l) * astep;
          uint32_t alo = alo0, blo = blo0;
          const uint32_t special = 8u | (l ? (1u << MK1) | (wg << (8 - STG_D)) : (1u << MK0) | (1u << PAUSE_K) | (wg << (9 - STG0)));
          uint32_t fb = bars + 8 * (B_G1FULL + 10 * l), nb = fb + 8;
          mbar_wait(fb);
          if (tid == 0) TS(1 + 8 * l);
#pragma unroll 1
          for (int k = 0; k < 10; k++) {
            uint32_t ok;
            wgmma_fence();
#pragma unroll
            for (int kk = 0; kk < 4; kk++) {
              wgmma_n160<0>(acc, alo + kk * 2, desc_hi(1024, 1), blo + kk * xstep, bhi);
              if (kk == 0) { ok = mbar_test(nb); asm volatile("add.u32 %0, %0, %1;" : "+r"(nb) : "r"(k < 8 ? 8 : 0)); }
              if (kk == STG_KK && k == 9 && tid == 0) mbar_arrive(bars + 8 * (B_STG + l));
            }
            wgmma_commit();
            alo += astep; blo += bstep;
            if (blo == desc_lo(sb + G_OFF, 128)) blo = desc_lo(sb, 128);
            if (alo == aend) { alo = alo0; blo = blo0; }
            wgmma_wait<1>();
            if (k > 0 && (tid & 127) == 0) mbar_arrive(fb + 8 * (B_G1DONE - B_G1FULL - 1));
            if (!ok) mbar_wait(fb + 8);
            if ((special >> k) & 1) {
            if (k == (l ? MK1 : MK0)) {
              mbar_wait(bars + 8 * (B_STAB + l));
              const float2 sB = lds64f(ca + 16);
              uint32_t a0 = q < 2 ? __float_as_uint(sB.x) : 0u, a1 = q < 2 ? __float_as_uint(sB.y) : 0u, a2 = 0u, a3 = 0u;
              asm volatile("" : "+r"(a0), "+r"(a1), "+r"(a2), "+r"(a3)::"memory");
              wgmma_fence();
              wgmma_rs_n160(acc, a0, a1, a2, a3, l ? desc_lo(sb + MX1_OFF, 0) : desc_lo(sb + MX0_OFF, 0));
              wgmma_commit();
            }
            if (wg == 1 && k == (l ? 8 - STG_D : 9 - STG0)) mbar_wait(bars + 8 * (B_STG + l));
            if (k == 3) {
              mbar_wait(bars + 8 * B_CTAB);
              lam = lds64f(ca);
              if (l == 0 && q < 2) rec_st(&g_E[(q * NT1 + T1) * DM + ch], 0.f, 0.f, lds32(sb + EP_OFF + 20) - 1);
              if (p.swap) lam.y = -lam.y;
              const float2 p2 = cmul(lam, lam), p4 = cmul(p2, p2);
              p8 = cmul(p4, p4); p16 = cmul(p8, p8);
              pL = cmul(p16, p16);
              if (!last) pL = cmul(pL, p8);
              p2L = cmul(pL, pL);
            }
            if (k == PAUSE_K && l == 0 && has2) mbar_wait(bars + 8 * B_PREP);
            }
            fb += 8;
          }
        }
        const unsigned tag = lds32(sb + EP_OFF + 20);
        wgmma_wait<0>();
        fence_regs(acc);
        if ((tid & 127) == 0) { mbar_arrive(bars + 8 * (B_G1DONE + 10 * l + 9)); TS(wg ? 17 + l : 2 + 8 * l); }
        float2 ec[3];
#pragma unroll
        for (int jj = 0; jj < 4; jj++)
#pragma unroll
          for (int y = 0; y < 3; y++) {
            if (y == 2 && (jj & 1)) continue;
            const int j = y == 2 ? 16 + jj : 8 * y + 2 * jj;
            const float4 st = lds128f(sb + STAB_OFF + q * 160 + j * 8);
            const float rs[4] = {st.x, st.y, st.z, st.w};
#pragma unroll
            for (int x = 0; x < 4; x++) {
              const int i = 4 * j + 4 * (x >> 1) + (x & 1);
              acc[i] *= rs[x]; acc[i + 2] *= rs[x];
              ec[y] = (jj == 0 && x == 0) ? make_float2(acc[i], acc[i + 2]) : cfma(lam, ec[y], make_float2(acc[i], acc[i + 2]));
            }
          }
        float2 e = cfma(p16, ec[0], ec[1]);
        if (!last) e = cfma(p8, e, ec[2]);
        {
          float2 v = make_float2(__shfl_up_sync(0xffffffffu, e.x, 1, 4), __shfl_up_sync(0xffffffffu, e.y, 1, 4));
          if (q >= 1) e = cfma(pL, v, e);
          v = make_float2(__shfl_up_sync(0xffffffffu, e.x, 2, 4), __shfl_up_sync(0xffffffffu, e.y, 2, 4));
          if (q >= 2) e = cfma(p2L, v, e);
        }
        if (!last && q == 3) rec_st(&g_E[(l * NT1 + T1) * DM + ch], e.x, e.y, tag);
        if (tid == 0) TS(3 + 8 * l);
        float2 ex = make_float2(__shfl_up_sync(0xffffffffu, e.x, 1, 4), __shfl_up_sync(0xffffffffu, e.y, 1, 4));
        if (q == 0) ex = make_float2(0.f, 0.f);
        const float2 coef = lds64f(ca + 8), lamc = make_float2(lam.x, p.swap ? lam.y : -lam.y);
        float m00 = coef.x, m01 = -coef.y, m10 = -coef.y, m11 = -coef.x;
        if (p.swap) { m00 = -coef.y; m01 = coef.x; m10 = -coef.x; m11 = -coef.y; }
        float2 pLq, p160q, p640;
        {
          const float2 p80 = last ? cmul(p2L, p16) : p2L, p160 = cmul(p80, p80), p320 = cmul(p160, p160), one = make_float2(1.f, 0.f);
          p640 = cmul(p320, p320);
          pLq = cmul((q & 1) ? pL : one, (q & 2) ? p2L : one);
          p160q = cmul((q & 1) ? p160 : one, (q & 2) ? p320 : one);
        }
        float2 c, ev[3];
        unsigned tg[3];
        const uint4* ep = &g_E[(l * NT1 + T1 - 1 - q) * DM + ch];
#pragma unroll
        for (int j = 0; j < 20; j++) {
          if (j == CPOLL) {
#pragma unroll
            for (int i = 0; i < 3; i++) {
              ev[i] = make_float2(0.f, 0.f); tg[i] = tag;
              if (T1 - 1 - q - 4 * i >= 0) tg[i] = rec_ld(ep - 4 * i * DM, ev[i].x, ev[i].y);
            }
          }
#pragma unroll
          for (int x = 0; x < 2; x++) {
            const float b0 = acc[4 * j + x], b1 = acc[4 * j + 2 + x];
            acc[4 * j + x] = fmaf(b0, m00, b1 * m01);
            acc[4 * j + 2 + x] = fmaf(b0, m10, b1 * m11);
          }
          if (j == CPOLL - 1 || j == 19) asm volatile("" : "+f"(acc[4 * j]), "+f"(acc[4 * j + 1]), "+f"(acc[4 * j + 2]), "+f"(acc[4 * j + 3])::"memory");
        }
        {
          uint32_t it = 0;
          while (__any_sync(0xffffffffu, tg[0] != tag || tg[1] != tag || tg[2] != tag)) {
#pragma unroll
            for (int i = 0; i < 3; i++)
              if (tg[i] != tag) tg[i] = rec_ld(ep - 4 * i * DM, ev[i].x, ev[i].y);
            trap_if(++it > SPIN_LIMIT);
          }
          c = cfma(p640, cfma(p640, ev[2], ev[1]), ev[0]);
          c = cmul(c, p160q);
          c.x += __shfl_xor_sync(0xffffffffu, c.x, 1); c.y += __shfl_xor_sync(0xffffffffu, c.y, 1);
          c.x += __shfl_xor_sync(0xffffffffu, c.x, 2); c.y += __shfl_xor_sync(0xffffffffu, c.y, 2);
        }
        if (tid == 0) TS(4 + 8 * l);
        if (HOLD1 && wg == 1 && l == 1 && has2) mbar_wait(bars + 8 * HOLD1);
        const uint32_t c0 = (uint32_t)clock(), tm = (tid & 7) == 4 * side + w;
        c = cfma(pLq, c, ex);
        float2 hh = make_float2(fmaf(c.x, m00, c.y * m01), fmaf(c.x, m10, c.y * m11));
        uint8_t* hb = g_h + (10 * wg + 2 * GP) * 8192 + (4 * side + w) * 1024 + (tid_opaque() & 31) * 4;
#pragma unroll
        for (int j4 = 0; j4 < 5; j4++) {
          if (PACE && j4 > 0 && wg == 1 && l == 1) { while (__any_sync(0xffffffffu, (uint32_t)clock() - c0 < PACE * j4)) {} }
          const int ng = 20 * T1 + 4 * j4;
          uint8_t* hp = hb + (size_t)(ng >> 3) * 163840 + (ng & 7) * 128;
#pragma unroll
          for (int jj = 0; jj < 4; jj++) {
            const int j = 4 * j4 + jj;
            const float2 h0 = cfma(lamc, hh, make_float2(acc[4 * j + 0], acc[4 * j + 2]));
            hh = cfma(lamc, h0, make_float2(acc[4 * j + 1], acc[4 * j + 3]));
            if (j4 < 4 || !last) {
              *(uint32_t*)(hp + jj * 128) = tag_word(pack_bf16(h0.x, hh.x), tm, 1 - l);
              *(uint32_t*)(hp + jj * 128 + 8192) = tag_word(pack_bf16(h0.y, hh.y), tm, 1 - l);
            }
          }
        }
        if (l == 0) mbar_arrive(bars + 8 * (B_HST + wg));
        if (tid == 0) TS(5 + 8 * l);
        if (tid == 128) TS(l ? 25 : 19);
        if (l == 0 && wid == 4) {
          mbar_wait(bars + 8 * B_HST);
          mbar_wait(bars + 8 * (B_HST + 1));
          if ((tid & 31) < 4) h_release(0, T1, tid & 3);
          __syncwarp();
          if (tid == 128) { mbar_arrive(bars + 8 * B_REL); TS(6); }
        }
      }
      if (l == 0) {
        ROLE(role)
        if (has2) {
          CvCtx cc;
          mbar_wait(bars + 8 * B_CTAB);
          cv_setup(cc);
          mbar_wait(bars + 8 * (B_G1DONE + 9));
#pragma unroll 1
          for (int c = (wg + 2) & 3; c < 5; c += 4) conv_channel(c, cc);
          if ((tid & 127) == 0) TS(wg == 2 ? 32 : (wg == 3 ? 50 : 7 + wg));
        }
      }
      if (wg >= 2) break;
    }
    if (wg < 2 && (role >> 16)) {
      const int ln = tid_opaque() & 31;
      const uint8_t* src = g_h + ((role >> 8) & 63) * 163840;
      uint32_t ph = 0;
      if (wg == 0) {
        mbar_wait(bars + 8 * (B_G1DONE + 19));
        if (SPEC0 + SPECW) __nanosleep(SPEC0 + SPECW * w);
        if (tid == 0) TS(23);
        if (!SPLITI && w < 3 && elect_one()) { mbar_expect_tx(bars + 8 * (B_XV + w + 4), G2_XB); }
      }
#pragma unroll 1
      for (int k = 10 * wg + w; k < 10 * wg + 10; k += 4) {
        if (k < (SPLITI ? S2 : 4) && elect_one()) {
          mbar_expect_tx(bars + 8 * (B_XV + k), G2_XB);
          bulk_g2s(sb + k * G2_XB, src + k * 8192, G2_XB, bars + 8 * (B_XV + k));
          if (!SPLITI && k < 3) bulk_g2s(sb + (k + 4) * G2_XB, src + (k + 4) * 8192, G2_XB, bars + 8 * (B_XV + k + 4));
        }
        validate_block(bars + 8 * (B_XV + k), bars + 8 * (B_G2FULL + 20 + k), sb + (k % S2) * G2_XB, src + k * 8192,
                       (ln & 7) * 1028 + (ln >> 3) * 32, bars + 8 * (B_RETRY + wid), ph);
      }
    }
    if (wg == 3) {
    ROLE(role)
    const int pw = wid & 3, gpc = 2 * min(m2 >> 3, 3) + (dg >> 1);
    mbar_wait(bars + 8 * B_EP);
    const unsigned tag = lds32(sb + EP_OFF + 20);
    if (pw == 0) {
      if (elect_one()) {
#pragma unroll 1
        for (int l = 0; l < 2; l++) {
          uint32_t dst = sb;
          if (l == 1) {
            dst = sb + G2_WOFF;
#pragma unroll 1
            for (int k = 0; k < 10; k++) {
              mbar_wait(k > 4 ? bars + 8 * (B_G1DONE + 5 + k) : (has2 ? bars + 8 * (B_G2DONE + 14 + min(k, 3)) : bars + 8 * (B_G1DONE + 9)));
              mbar_expect_tx(bars + 8 * (B_G1FULL + 10 + k), 16384);
              tma5(dst, &p.mB, 64 * k, 0, 0, 4 * side, 2 * GP, bars + 8 * (B_G1FULL + 10 + k));
              dst += 16384; if (k == 4) dst = sb + G2_WOFF;
            }
          }
          if (has2) {
            const uint32_t fb2 = bars + 8 * (B_G2FULL + 20 * l), wb2 = bars + 8 * (B_G2DONE + 20 * l - S2);
            dst = sb + G2_WOFF + (WTAIL ? 4 * l * G2_WB : 0);
            int kc = 0;
#pragma unroll 1
            for (int k = 0; k < 20; k++) {
              mbar_wait(k >= S2 ? wb2 + 8 * k : bars + 8 * (l ? B_G1DONE + (WTAIL ? (k < 3 ? 15 + k : 13 + k) : 19) : (k == 5 ? B_XFREE : (k == 6 ? B_SFREE : B_REL))));
              mbar_expect_tx(fb2 + 8 * k, G2_WB);
              tma5(dst, &p.mCre + (k & 1), kc, 0, 0, 0, 10 * dg, fb2 + 8 * k);
              kc += (k & 1) << 7; if (k == 9) kc = 64;
              dst += G2_WB; if (dst == sb + G2_WOFF + S2 * G2_WB) dst = sb + G2_WOFF;
            }
          }
        }
      }
    } else if (pw == 1) {
#pragma unroll 1
      for (int l = 0; l < 2; l++) {
        if (l == 1) {
          mbar_wait(bars + 8 * (has2 ? B_G2DONE + 19 : B_G1DONE + 9));
          if (has2) mbar_wait(bars + 8 * B_UST);
          cnt_poll(&g_ucnt[gpc * 32], 128 * tag);
          fence_async_global();
          if (elect_one()) {
            TS(20);
            const int bytes = last ? 16384 : 20480;
            const uint8_t* src = g_u + T1 * 204800;
            uint32_t dst = sb + X1_OFF;
#pragma unroll 1
            for (int k = 0; k < 10; k++) {
              if (k > 4) mbar_wait(bars + 8 * (B_G1DONE + 5 + k));
              mbar_expect_tx(bars + 8 * (B_G1FULL + 10 + k), bytes);
              bulk_g2s(dst, src, bytes, bars + 8 * (B_G1FULL + 10 + k));
              src += 20480; dst += 20480; if (dst == sb + G_OFF) dst = sb; if (k == 4) dst = sb + X1_OFF;
            }
          }
          __syncwarp();
        }
        if (has2) {
          if (l == 0) {
            mbar_wait(bars + 8 * B_REL);
            cnt_poll(&g_hcnt[gpc * 32], 40 * tag);
            fence_async_global();
          }
          if (elect_one()) {
            if (l == 0) TS(21);
            const uint32_t fb2 = bars + 8 * (l ? B_XV : B_G2FULL), wb2 = bars + 8 * (B_G2DONE + 20 * l - S2);
            const uint8_t* src = g_h + m2 * 163840 + l * S2 * 8192;
            uint32_t dst = sb;
#pragma unroll 1
            for (int k = l * S2; k < 20; k++) {
              if (k >= 5) mbar_wait(k >= S2 ? wb2 + 8 * k : bars + 8 * B_SFREE);
              mbar_expect_tx(fb2 + 8 * k, G2_XB);
              bulk_g2s(dst, src, G2_XB, fb2 + 8 * k);
              src += 8192; dst += G2_XB; if (dst == sb + S2 * G2_XB) dst = sb;
            }
          }
          __syncwarp();
        }
      }
    } else if (pw == 2) {
#pragma unroll 1
      for (int l = 0; l < 2; l++) {
        if (l == 1) {
          if (has2) {
            mbar_wait(bars + 8 * B_UST);
            if (lane < 8) red_rel(&g_ucnt[lane * 32]);
            __syncwarp();
            if (lane == 0) TS(38);
          }
          float xa[2], xb[2];
          mbar_wait(bars + 8 * (B_G1FULL + 11));
          stat_table(T1, tag, 1, 4, g_stats, g_stats, xa, xb);
          mbar_arrive(bars + 8 * (B_STAB + 1));
        }
        if (l == 0 && has2 && elect_one()) {
#pragma unroll 1
          for (int i = 0; i < 5; i++) {
            const int c = i < 3 ? i : 7 - i;
            mbar_wait(bars + 8 * (B_CVDONE + c));
            bulk_s2g(g_G + (cch0 + 32 * c) * 4096, cv_stage(c), 4096);
          }
          asm volatile("cp.async.bulk.commit_group;" ::: "memory");
          asm volatile("cp.async.bulk.wait_group.read 0;" ::: "memory");
          mbar_arrive(bars + 8 * B_SFREE);
          asm volatile("cp.async.bulk.wait_group 0;" ::: "memory");
          TS(48);
          fence_async_global();
          asm volatile("fence.acq_rel.gpu;" ::: "memory");
#pragma unroll
          for (int i = 0; i < 4; i++) red_rlx(&g_gcnt[(dg * 4 + i) * 32]);
          TS(49);
          mbar_arrive(bars + 8 * (B_GO + 1));
        }
        __syncwarp();
      }
    } else if (has2) {
      mbar_wait(bars + 8 * B_REL);
      if (!CPF && elect_one()) {
        l2_prefetch(p.cre + (160 * dg + 5 * m2) * DM, 6400); l2_prefetch(p.cim + (160 * dg + 5 * m2) * DM, 6400);
      }
      mbar_wait(bars + 8 * (B_GO + 1));
      flag_poll(&g_gcnt[(dg * 4 + (m2 >> 3)) * 32], 32 * tag);
      fence_async_global();
      if (elect_one()) {
        TS(29);
        mbar_expect_tx(bars + 8 * B_GFULL, 20480);
        tma5(sb + G_OFF, &p.mG, 64 * m2, 0, 0, 0, 10 * dg, bars + 8 * B_GFULL);
      }
    }
    } else if (wg == 2 && (role >> 16)) {
      float acc[80];
      float off[2] = {mean0[0], mean0[1]};
      const unsigned tag = lds32(sb + EP_OFF + 20);
      dskip_init<true>(acc, mean0, rstd0);
      mbar_arrive(bars + 8 * B_XFREE);
      mbar_wait(bars + 8 * (B_CVDONE + 2));
      mbar_wait(bars + 8 * (B_CVDONE + 3));
#pragma unroll 1
      for (int step = 1; step < 4; step++) {
        const int l = step >> 1;
        if (step != 2) {
          uint32_t alo = desc_lo(sb, 1024), blo = desc_lo(sb + G2_WOFF, 16) + (WTAIL ? l * (G2_WB >> 2) : 0);
          uint32_t fb = bars + 8 * (B_G2FULL + 20 * l);
          fence_regs(acc);
          mbar_wait(fb);
          if (tid == 256) TS(33 + 6 * l);
#pragma unroll 1
          for (int k = 0; k < 20; k++) {
            if (l == TSL && (k & 3) == 3 && tid == 256) TS(56 + (k >> 2));
            uint32_t ok; const uint32_t nb = k < 19 ? fb + 8 : fb;
            wgmma_fence();
#pragma unroll
            for (int kk = 0; kk < 4; kk++) {
              wgmma_n160<1>(acc, alo + kk * 128, desc_hi(128, 0), blo + kk * 2, desc_hi(1024, 1));
              if (kk == 0) ok = mbar_test(nb);
            }
            wgmma_commit();
            alo += G2_XB >> 4; blo += G2_WB >> 4;
            if (alo == desc_lo(sb + S2 * G2_XB, 1024)) alo = desc_lo(sb, 1024);
            if (blo == desc_lo(sb + G_OFF, 16)) blo = desc_lo(sb + G2_WOFF, 16);
            wgmma_wait<1>();
            if (k > 0 && tid == 256) mbar_arrive(fb + 8 * (B_G2DONE - B_G2FULL - 1));
            if (!ok) mbar_wait(nb);
            fb += 8;
          }
          wgmma_wait<0>();
          fence_regs(acc);
          if (tid == 256) TS(34 + 6 * l);
          if (tid == 256) mbar_arrive(bars + 8 * (B_G2DONE + 20 * l + 19));
        }
        ROLE(role)
        const int tq = tid_opaque() & 31, n0 = 64 * m2 + 16 * w + (tq >> 2);
        stats_publish<false>(step, n0, dg, tag, acc);
        uint32_t gf[10][4];
        mbar_wait(bars + 8 * B_GFULL);
        uint32_t ga = sb + G_OFF + (8 * (tq >> 4) + (tq & 7)) * 128 + (((2 * w + ((tq >> 3) & 1)) ^ ((2 * m2) & 6) ^ (tq & 7)) << 4), gstep = 2048;
        if (step == 2) { ga = sb + DX_OFF + (8 * (tq >> 4) + (tq & 7)) * 16; gstep = 256; }
#pragma unroll
        for (int J = 0; J < 2; J++) ldsm4t(gf[J], ga + J * gstep);
        if (tid == 256) TS(35 + 6 * l);
        uint8_t* dst[2][2];
#pragma unroll
        for (int h = 0; h < 2; h++) {
          if (l == 0) {
            const int ng = 8 * m2 + 2 * w + h, T = ng / 20;
            uint8_t* ub = g_u + (T * 204800 + (ng - 20 * T) * 1024 + (tq & 2) * 64 + (tq & 28) * 4 + (tq & 1) * 8 + (5 * dg >> 1) * 20480);
            dst[h][1] = ub + ((dg & 1) ? 20480 - 512 : 0);
            dst[h][0] = ub + (dg & 1) * 512;
          } else {
            dst[h][0] = dst[h][1] = (uint8_t*)(p.out + (n_to_t(n0 + 8 * h) * DM + 160 * dg + 4 * (tq & 3)));
          }
        }
        float mean[2], rstd[2];
        stats_get(step, n0, tag, mean, rstd);
        if (tid == 256) TS(36 + 6 * l);
        off[0] += mean[0]; off[1] += mean[1];
        const float ov[2] = {step == 3 ? off[0] : 0.f, step == 3 ? off[1] : 0.f};
#pragma unroll
        for (int J = 0; J < 10; J++) {
          if (J + 2 < 10) ldsm4t(gf[J + 2 < 10 ? J + 2 : 0], ga + (J + 2) * gstep);
#pragma unroll
          for (int x = 0; x < 8; x++) {
            const int h = (x >> 1) & 1;
            const uint32_t gwd = gf[J][x >> 1];
            const float t = fmaf(rstd[h], (x & 1) ? bf_hi(gwd) : bf_lo(gwd), 1.f);
            acc[8 * J + x] = fmaf(acc[8 * J + x], t, fmaf(-mean[h], t, ov[h]));
          }
#pragma unroll
          for (int h = 0; h < 2; h++) {
            if (step == 1)
              *(uint2*)(dst[h][(J >> 1) & 1] + (J >> 2) * 20480 + (J & 3) * 256) =
                  make_uint2(pack_bf16(acc[8 * J + 2 * h], acc[8 * J + 2 * h + 1]), pack_bf16(acc[8 * J + 4 + 2 * h], acc[8 * J + 5 + 2 * h]));
            if (step == 3)
              *(float4*)(dst[h][0] + 64 * J) = make_float4(acc[8 * J + 2 * h], acc[8 * J + 2 * h + 1], acc[8 * J + 4 + 2 * h], acc[8 * J + 5 + 2 * h]);
          }
          __syncwarp();
        }
        if (step == 1) {
          mbar_arrive(bars + 8 * B_UST);
          if (tid == 256) TS(37);
          for (int n = tid & 127; n < 160; n += 128) {
            const int d = 16 * (n >> 4) + 4 * ((n >> 1) & 3) + 2 * ((n >> 3) & 1) + (n & 1);
            const uint32_t dw = lds32(sb + DTAB_OFF + 2 * (d & ~1)), dd = __byte_perm(dw, dw, (d & 1) ? 0x3232 : 0x1010);
            sts128(sb + DX_OFF + 16 * n, make_uint4(dd, dd, dd, dd));
          }
          bar_sync(3, 128);
        } else if (step == 2) {
          if (tid == 256) TS(22);
          mbar_wait(bars + 8 * (B_G1FULL + 11));
          float xa[2], xb[2];
          stat_table(T1, tag, 1, w, g_stats, g_stats, xa, xb);
          mbar_arrive(bars + 8 * (B_STAB + 1));
          if (tid == 256) TS(27);
        } else {
          if (tid == 256) {
            TS(43);
            if (m2 == 31 && dg == 3) asm volatile("st.relaxed.gpu.global.u32 [%0], %1;" ::"l"(g_epoch), "r"(tag + 1) : "memory");
          }
        }
      }
    }
  }
}

typedef CUresult (*EncFn)(CUtensorMap*, CUtensorMapDataType, cuuint32_t, void*, const cuuint64_t*, const cuuint64_t*,
                          const cuuint32_t*, const cuuint32_t*, CUtensorMapInterleave, CUtensorMapSwizzle,
                          CUtensorMapL2promotion, CUtensorMapFloatOOBfill);

void encode(EncFn fn, CUtensorMap* m, const void* ptr, int rank, const cuuint64_t* dims, const cuuint64_t* strides, const cuuint32_t* box,
            CUtensorMapSwizzle swz = CU_TENSOR_MAP_SWIZZLE_128B, int prom = 2) {
  cuuint32_t es[5] = {1, 1, 1, 1, 1};
  fn(m, CU_TENSOR_MAP_DATA_TYPE_BFLOAT16, rank, (void*)ptr, dims, strides, box, es, CU_TENSOR_MAP_INTERLEAVE_NONE,
     swz, (CUtensorMapL2promotion)prom, CU_TENSOR_MAP_FLOAT_OOB_FILL_NONE);
}

}

extern "C" void kernel_launch(void* const* d_in, const int* in_sizes, int n_in, void* d_out, int out_size) {
  (void)in_sizes; (void)n_in; (void)out_size;
  Params p;
  typedef const __nv_bfloat16* BP;
  p.x = (BP)d_in[0]; p.lre = (BP)d_in[1]; p.lim = (BP)d_in[2]; p.bre = (BP)d_in[3]; p.bim = (BP)d_in[4];
  p.cre = (BP)d_in[5]; p.cim = (BP)d_in[6]; p.logdt = (BP)d_in[7]; p.dskip = (BP)d_in[8];
  p.k = (BP)d_in[10]; p.v = (BP)d_in[11]; p.shiftk = (BP)d_in[12]; p.ssmk = (BP)d_in[13]; p.ssmD = (BP)d_in[14];
  p.out = (float*)d_out;
  for (int sm = 0; sm < 132; sm++) {
    const int tpc = sm >> 1, side = sm & 1;
    int gpc, gi;
    if (tpc < 32) { gpc = tpc & 7; gi = tpc >> 3; }
    else if (tpc < 60) { gpc = 1 + (tpc - 32) % 7; gi = 4 + (tpc - 32) / 7; }
    else if (tpc < 62) { gpc = tpc - 54; gi = 8; }
    else { gpc = 0; gi = tpc - 58; }
    const int pos = 8 * gpc + gi + (gpc == 7 ? 1 : 0);
    int T1, GP;
    if (pos < 52) { const int hh = pos / 26, x = pos - 26 * hh; T1 = x >> 1; GP = 2 * hh + (x & 1); }
    else { T1 = pos - 52; GP = 4; }
    const int m2 = 8 * (gpc >> 1) + gi, dg = 2 * (gpc & 1) + side;
    p.role[sm] = pos == 65 ? -1 : (T1 | (GP << 4) | (side << 7) | (m2 << 8) | (dg << 14) | ((gi < 8) << 16));
  }
  void* fnp = nullptr;
  cudaDriverEntryPointQueryResult qr;
  cudaGetDriverEntryPoint("cuTensorMapEncodeTiled", &fnp, cudaEnableDefault, &qr);
  EncFn fn = (EncFn)fnp;
  void* gG = nullptr;
  cudaGetSymbolAddress(&gG, g_G);
  void* gKV = nullptr;
  cudaGetSymbolAddress(&gKV, g_kv);
  {
    cuuint64_t dims[5] = {32, 32, 10, 32, 4}, st[4] = {20480, 2048, 64, 655360}; cuuint32_t box[5] = {32, 35, 2, 1, 1};
    encode(fn, &p.mU, gKV, 5, dims, st, box, CU_TENSOR_MAP_SWIZZLE_NONE, 1);
  }
  const cuuint64_t RB = DM * 2;
  {
    p.swap = p.bim < p.bre;
    const char* lo = (const char*)(p.swap ? p.bim : p.bre); const char* hi = (const char*)(p.swap ? p.bre : p.bim);
    cuuint64_t dims[5] = {640, 8, 2, 8, 10}, st[4] = {RB, (cuuint64_t)(hi - lo), 8 * RB, 64 * RB}; cuuint32_t box[5] = {64, 8, 2, 4, 2};
    encode(fn, &p.mB, lo, 5, dims, st, box);
  }
  {
    cuuint64_t dims[5] = {640, 2, 4, 2, 40}, st[4] = {RB, 4 * RB, 2 * RB, 16 * RB}; cuuint32_t box[5] = {64, 2, 4, 2, 10};
    encode(fn, &p.mCre, p.cre, 5, dims, st, box); encode(fn, &p.mCim, p.cim, 5, dims, st, box);
    cuuint64_t dimg[5] = {2048, 2, 4, 2, 40}, stg[4] = {4096, 4 * 4096, 2 * 4096, 16 * 4096};
    encode(fn, &p.mG, gG, 5, dimg, stg, box);
  }
  {
    cuuint64_t dims[4] = {640, 2, 4, 900}, st[3] = {RB, 40 * RB, 2 * RB}; cuuint32_t box[4] = {64, 2, 4, 20};
    encode(fn, &p.mX, p.x, 4, dims, st, box);
    cuuint64_t diml[4] = {640, 2, 4, 16}, stl[3] = {RB, 32 * RB, 2 * RB};
    encode(fn, &p.mXl, p.x + (size_t)1920 * DM, 4, diml, stl, box);
    cuuint32_t boxt[4] = {160, 2, 4, 4};
    encode(fn, &p.mXt, p.x, 4, dims, st, boxt, CU_TENSOR_MAP_SWIZZLE_NONE);
    encode(fn, &p.mXtl, p.x + (size_t)1920 * DM, 4, diml, stl, boxt, CU_TENSOR_MAP_SWIZZLE_NONE);
    cuuint64_t dk[3] = {640, 2000, 4}, sk[2] = {RB, 16 * RB}; cuuint32_t bk[3] = {32, 19, 4}, bv[3] = {32, 17, 4};
    encode(fn, &p.mK, p.k, 3, dk, sk, bk, CU_TENSOR_MAP_SWIZZLE_NONE);
    encode(fn, &p.mV, p.v, 3, dk, sk, bv, CU_TENSOR_MAP_SWIZZLE_NONE);
  }
  cudaFuncSetAttribute(fused_kernel, cudaFuncAttributeMaxDynamicSharedMemorySize, SMEM_BYTES);
  cudaLaunchConfig_t cfg = {};
  cfg.gridDim = dim3(132); cfg.blockDim = dim3(512); cfg.dynamicSmemBytes = SMEM_BYTES; cfg.stream = cudaStreamPerThread;
  cudaLaunchKernelEx(&cfg, fused_kernel, p);
}
```

```cpp
#include <cuda_runtime.h>
#include <cuda.h>
#include <cuda_bf16.h>
#include <stdint.h>

namespace {

constexpr int SEQ = 2048, DM = 640;
constexpr int NT1 = 13;
#define EXP 0
#define WPF1 3
#define WPF2 7
#define CPOLL 10
#define KV0 1
#define TAPLATE 1
#define STG_D 3
#define STG_KK 1
#define HOLD1 0
#define SPEC0 100
#define WREL 0
#define UREL 1
#define TSL 1
#define STG0 2
#define WTAIL 1
#define PFD 1
#define TAPW 0
#define TPF 4
#define CPF 0
#define MK0 7
#define MK1 4
#define PACE 350
#define TAPN 2
#define SPLITI 1
#define SPECW 60
#define SPECU 200
#define PAUSE_K 5
constexpr uint32_t SPIN_LIMIT = 1u << 22;

__device__ __align__(1024) uint8_t g_h[32 * 20 * 8192];
__device__ __align__(1024) uint8_t g_u[NT1 * 10 * 20480];
__device__ __align__(1024) uint8_t g_kv[DM * 4096];
__device__ __align__(1024) uint8_t g_G[DM * 4096];
__device__ __align__(128) uint4 g_E[2 * NT1 * DM];
__device__ __align__(128) uint4 g_stats[4 * 4 * SEQ];
__device__ __align__(128) uint4 g_sB[DM * 2];
__device__ __align__(128) unsigned g_hcnt[8 * 32];
__device__ __align__(128) unsigned g_ucnt[8 * 32];
__device__ __align__(128) unsigned g_kvcnt[16 * 32];
__device__ __align__(128) unsigned g_gcnt[16 * 32];
__device__ __align__(128) unsigned g_epoch[32] = {1};
#define TS(i) do {} while (0)

struct Params {
  CUtensorMap mX, mB, mXl, mK, mV, mXt, mXtl, mCre, mCim, mG, mU;
  const __nv_bfloat16 *x, *lre, *lim, *bre, *bim, *cre, *cim, *logdt, *dskip, *k, *v, *shiftk, *ssmk, *ssmD;
  float* out;
  int swap;
  int role[132];
};

constexpr uint32_t sb = 1024;
constexpr uint32_t G1_STAGE = 36864, G1_XOFF = 16384;
constexpr int S1 = 4;
constexpr uint32_t XT_OFF = 159744, KS_OFF = 180224, KV_PIECE = 9216;
constexpr uint32_t G2_XB = 8192, G2_WB = 20480, G2_WOFF = 57344, G_OFF = 200704;
constexpr uint32_t X1_OFF = 139264;
constexpr int S2 = 7;
constexpr uint32_t CV_OFF = KS_OFF, CV_K = 128, CV_PL = 2240, CV_U = CV_K + 4096, CV_B = KV_PIECE;
constexpr uint32_t MISC = 226304;
constexpr uint32_t BAR_OFF = MISC;
constexpr int B_G1FULL = 0, B_G1DONE = 20, B_G2FULL = 40,
              B_G2DONE = 85, B_GFULL = 125, B_EP = 126, B_CVFULL = 129  , B_STG = 134  , B_REL = 136  , B_SFREE = 138,
              B_GO = 139  , B_PUB = 147,
              B_CVDONE = 148  , B_STAB = 153  , B_XFREE = 155, B_HST = 156  , B_UST = 158,
              B_CTAB = 160, B_PREP = 161, B_XT = 162, B_KV = 163  , B_PREP2 = 84, B_PD = 168  ,
              B_XV = 173  , B_RETRY = 193  , B_USEEN = 209;
constexpr uint32_t bars = sb + BAR_OFF;
constexpr uint32_t STAB_OFF = MISC + 1680;
constexpr uint32_t CTAB_OFF = STAB_OFF + 640;
constexpr uint32_t DTAB_OFF = CTAB_OFF + 1536;
constexpr uint32_t EP_OFF = DTAB_OFF + 320;
constexpr uint32_t SO_OFF = EP_OFF + 32;
constexpr uint32_t TAP_OFF = 147456;
constexpr uint32_t MX0_OFF = TAP_OFF + 1280, MX1_OFF = G_OFF + 20480;
constexpr uint32_t DX_OFF = MX1_OFF + 2560;
constexpr uint32_t SMEM_BYTES = 232448;
static_assert(SO_OFF + 1536 <= SMEM_BYTES, "smem");

__device__ __forceinline__ void trap_if(bool c) { asm volatile("{\n.reg .pred p;\nsetp.ne.u32 p, %0, 0;\n@p trap;\n}\n" ::"r"((uint32_t)c)); }
__device__ __forceinline__ uint32_t smem_u32(const void* p) { return (uint32_t)__cvta_generic_to_shared(p); }
__device__ __forceinline__ void mbar_init(uint32_t bar, int cnt) { asm volatile("mbarrier.init.shared::cta.b64 [%0], %1;" ::"r"(bar), "r"(cnt) : "memory"); }
__device__ __forceinline__ void mbar_expect_tx(uint32_t bar, int bytes) { asm volatile("mbarrier.arrive.expect_tx.shared::cta.b64 _, [%0], %1;" ::"r"(bar), "r"(bytes) : "memory"); }
__device__ __forceinline__ void mbar_arrive(uint32_t bar) { asm volatile("mbarrier.arrive.shared::cta.b64 _, [%0];" ::"r"(bar) : "memory"); }
__device__ __forceinline__ bool elect_one() {
  uint32_t e; asm volatile("{\n.reg .pred P;\nelect.sync _|P, 0xffffffff;\nselp.u32 %0, 1, 0, P;\n}\n" : "=r"(e)); return e != 0;
}
__device__ __forceinline__ void mbar_wait(uint32_t bar) {
  asm volatile(
      "{\n.reg .pred p;\n.reg .u32 c;\nmov.u32 c, 0;\n"
      "W_%=:\nmbarrier.try_wait.parity.shared::cta.b64 p, [%0], 0;\n@p bra D_%=;\n"
      "add.u32 c, c, 1;\nsetp.lt.u32 p, c, %1;\n@p bra W_%=;\ntrap;\nD_%=:\n}\n" ::"r"(bar), "n"(SPIN_LIMIT) : "memory");
}
__device__ __forceinline__ uint32_t mbar_test(uint32_t bar) {
  uint32_t ok;
  asm volatile("{\n.reg .pred p;\nmbarrier.test_wait.parity.shared::cta.b64 p, [%1], 0;\nselp.u32 %0, 1, 0, p;\n}\n" : "=r"(ok) : "r"(bar) : "memory");
  return ok;
}
__device__ __forceinline__ void tma3(uint32_t dst, const CUtensorMap* m, int c0, int c1, int c2, uint32_t bar) {
  asm volatile("cp.async.bulk.tensor.3d.shared::cluster.global.mbarrier::complete_tx::bytes [%0], [%1, {%3,%4,%5}], [%2];"
               ::"r"(dst), "l"(m), "r"(bar), "r"(c0), "r"(c1), "r"(c2) : "memory");
}
__device__ __forceinline__ void tma4(uint32_t dst, const CUtensorMap* m, int c0, int c1, int c2, int c3, uint32_t bar) {
  asm volatile("cp.async.bulk.tensor.4d.shared::cluster.global.mbarrier::complete_tx::bytes [%0], [%1, {%3,%4,%5,%6}], [%2];"
               ::"r"(dst), "l"(m), "r"(bar), "r"(c0), "r"(c1), "r"(c2), "r"(c3) : "memory");
}
__device__ __forceinline__ void tma5(uint32_t dst, const CUtensorMap* m, int c0, int c1, int c2, int c3, int c4, uint32_t bar) {
  asm volatile("cp.async.bulk.tensor.5d.shared::cluster.global.mbarrier::complete_tx::bytes [%0], [%1, {%3,%4,%5,%6,%7}], [%2];"
               ::"r"(dst), "l"(m), "r"(bar), "r"(c0), "r"(c1), "r"(c2), "r"(c3), "r"(c4) : "memory");
}
__device__ __forceinline__ void bulk_g2s(uint32_t dst, const void* src, int bytes, uint32_t bar) {
  asm volatile("cp.async.bulk.shared::cluster.global.mbarrier::complete_tx::bytes [%0], [%1], %2, [%3];"
               ::"r"(dst), "l"(src), "r"(bytes), "r"(bar) : "memory");
}
__device__ __forceinline__ void bulk_s2g(void* dst, uint32_t src, int bytes) {
  asm volatile("cp.async.bulk.global.shared::cta.bulk_group [%0], [%1], %2;" ::"l"(dst), "r"(src), "r"(bytes) : "memory");
}
__device__ __forceinline__ void l2_prefetch(const void* src, int bytes) {
  asm volatile("cp.async.bulk.prefetch.L2.global [%0], %1;" ::"l"(src), "r"(bytes) : "memory");
}
__device__ __forceinline__ void wgmma_fence() { asm volatile("wgmma.fence.sync.aligned;" ::: "memory"); }
__device__ __forceinline__ void wgmma_commit() { asm volatile("wgmma.commit_group.sync.aligned;" ::: "memory"); }
template <int N> __device__ __forceinline__ void wgmma_wait() { asm volatile("wgmma.wait_group.sync.aligned %0;" ::"n"(N) : "memory"); }
__host__ __device__ constexpr uint32_t desc_lo(uint32_t addr, uint32_t lbo) { return ((addr & 0x3FFFF) >> 4) | ((lbo >> 4) << 16); }
__host__ __device__ constexpr uint32_t desc_hi(uint32_t sbo, uint32_t swz) { return (sbo >> 4) | (swz << 30); }
__device__ __forceinline__ void bar_sync(int id, int n) { asm volatile("bar.sync %0, %1;" ::"r"(id), "r"(n) : "memory"); }
__device__ __forceinline__ uint32_t lds32(uint32_t a) { uint32_t v; asm volatile("ld.shared.u32 %0, [%1];" : "=r"(v) : "r"(a) : "memory"); return v; }
__device__ __forceinline__ float2 lds64f(uint32_t a) { float2 v; asm volatile("ld.shared.v2.f32 {%0,%1}, [%2];" : "=f"(v.x), "=f"(v.y) : "r"(a) : "memory"); return v; }
__device__ __forceinline__ float4 lds128f(uint32_t a) { float4 v; asm volatile("ld.shared.v4.f32 {%0,%1,%2,%3}, [%4];" : "=f"(v.x), "=f"(v.y), "=f"(v.z), "=f"(v.w) : "r"(a) : "memory"); return v; }
__device__ __forceinline__ void ldsm4t(uint32_t (&r)[4], uint32_t a) {
  asm volatile("ldmatrix.sync.aligned.m8n8.x4.trans.shared.b16 {%0,%1,%2,%3}, [%4];" : "=r"(r[0]), "=r"(r[1]), "=r"(r[2]), "=r"(r[3]) : "r"(a) : "memory");
}
__device__ __forceinline__ uint4 ldv128(const void* a) { uint4 v; asm volatile("ld.global.nc.v4.u32 {%0,%1,%2,%3}, [%4];" : "=r"(v.x), "=r"(v.y), "=r"(v.z), "=r"(v.w) : "l"(a) : "memory"); return v; }
__device__ __forceinline__ uint2 ldv64(const void* a) { uint2 v; asm volatile("ld.global.nc.v2.u32 {%0,%1}, [%2];" : "=r"(v.x), "=r"(v.y) : "l"(a) : "memory"); return v; }
__device__ __forceinline__ uint32_t ldv16(const void* a) { uint32_t v; asm volatile("ld.global.nc.u16 %0, [%1];" : "=r"(v) : "l"(a) : "memory"); return v; }
__device__ __forceinline__ void sts128(uint32_t a, uint4 v) { asm volatile("st.shared.v4.u32 [%0], {%1,%2,%3,%4};" ::"r"(a), "r"(v.x), "r"(v.y), "r"(v.z), "r"(v.w) : "memory"); }
__device__ __forceinline__ void sts32(uint32_t a, uint32_t v) { asm volatile("st.shared.u32 [%0], %1;" ::"r"(a), "r"(v) : "memory"); }
__device__ __forceinline__ void sts64f(uint32_t a, float x, float y) { asm volatile("st.shared.v2.f32 [%0], {%1,%2};" ::"r"(a), "f"(x), "f"(y) : "memory"); }
__device__ __forceinline__ void red_rlx(unsigned* p) { asm volatile("red.relaxed.gpu.global.add.u32 [%0], 1;" ::"l"(p) : "memory"); }
__device__ __forceinline__ void red_rel(unsigned* p) { asm volatile("red.release.gpu.global.add.u32 [%0], 1;" ::"l"(p) : "memory"); }
__device__ __forceinline__ void fence_async_global() { asm volatile("fence.proxy.async.global;" ::: "memory"); }
__device__ __forceinline__ void fence_async_smem() { asm volatile("fence.proxy.async.shared::cta;" ::: "memory"); }
__device__ __forceinline__ void rec_st(uint4* p, float a, float b, unsigned tag) {
  asm volatile("{\n.reg .b128 t;\n.reg .b64 lo, hi;\nmov.b64 lo, {%1,%2};\nmov.b64 hi, {%3,%3};\nmov.b128 t, {lo,hi};\n"
               "st.relaxed.gpu.global.b128 [%0], t;\n}\n" ::"l"(p), "r"(__float_as_uint(a)), "r"(__float_as_uint(b)), "r"(tag) : "memory");
}
__device__ __forceinline__ unsigned rec_ld(const uint4* p, float& a, float& b) {
  unsigned x, y, t;
  asm volatile("{\n.reg .b128 t;\n.reg .b64 lo, hi;\n.reg .b32 u;\nld.relaxed.gpu.global.b128 t, [%3];\nmov.b128 {lo,hi}, t;\n"
               "mov.b64 {%0,%1}, lo;\nmov.b64 {%2,u}, hi;\n}\n" : "=r"(x), "=r"(y), "=r"(t) : "l"(p) : "memory");
  a = __uint_as_float(x); b = __uint_as_float(y);
  return t;
}
__device__ __forceinline__ unsigned ld_rlx(const unsigned* p) { unsigned v; asm volatile("ld.relaxed.gpu.global.u32 %0, [%1];" : "=r"(v) : "l"(p) : "memory"); return v; }
__device__ __forceinline__ void flag_poll(const unsigned* p, unsigned target) {
  uint32_t it = 0;
  while (!__all_sync(0xffffffffu, (int)(ld_rlx(p) - target) >= 0)) { trap_if(++it > SPIN_LIMIT); }
  asm volatile("fence.acquire.gpu;" ::: "memory");
}
__device__ __forceinline__ void cnt_poll(const unsigned* p, unsigned target) {
  unsigned a = ld_rlx(p); __nanosleep(100);
  unsigned b = ld_rlx(p); __nanosleep(100);
  unsigned c = ld_rlx(p);
  uint32_t it = 0;
  while (true) {
    if (__all_sync(0xffffffffu, (int)(a - target) >= 0)) break;
    a = ld_rlx(p);
    if (__all_sync(0xffffffffu, (int)(b - target) >= 0)) break;
    b = ld_rlx(p);
    if (__all_sync(0xffffffffu, (int)(c - target) >= 0)) break;
    c = ld_rlx(p);
    trap_if(++it > SPIN_LIMIT);
  }
  asm volatile("fence.acquire.gpu;" ::: "memory");
}
template <bool U>
__device__ __forceinline__ void validate_block(uint32_t bar, uint32_t full, uint32_t dst, const uint8_t* src, int n, int g0, uint32_t woff, uint32_t rb, uint32_t& ph) {
  uint32_t it = 0, par = 0;
  while (true) {
    if (U || it) {
      if (elect_one()) { mbar_expect_tx(rb, n * 1024); bulk_g2s(dst, src, n * 1024, rb); }
      bar = rb; par = ph; ph ^= 1;
    }
    uint32_t ok, spins = 0;
    do {
      asm volatile("{\n.reg .pred p;\nmbarrier.try_wait.parity.shared::cta.b64 p, [%1], %2;\nselp.u32 %0, 1, 0, p;\n}\n" : "=r"(ok) : "r"(bar), "r"(par) : "memory");
      trap_if(++spins > SPIN_LIMIT);
    } while (!__all_sync(0xffffffffu, ok));
    uint32_t bad = 0;
#pragma unroll
    for (int i = 0; i < (U ? 5 : 8); i++) {
      const int g = min(i, n - 1);
      bad |= U ? ~lds32(dst + woff + 1024 * g + ((g0 + g) & 6) * 4) : lds32(dst + woff + 128 * i);
    }
    if (!__any_sync(0xffffffffu, bad & 1)) break;
    trap_if(++it > 100000);
  }
  if ((threadIdx.x & 31) == 0) mbar_arrive(full);
}
__device__ __forceinline__ uint32_t tag_word(uint32_t v, uint32_t m, uint32_t par) {
  uint32_t r; asm("lop3.b32 %0, %1, %2, %3, 0xb8;" : "=r"(r) : "r"(v), "r"(m), "r"(par)); return r;
}
__device__ __forceinline__ void h_release(int idx, int T, int i) {
  const int Q = (i & 2) ? (T + 2) / 3 - 1 : T / 3;
  if (Q >= 0 && Q < 4 && ((i & 2) == 0 || T % 3 == 0)) red_rel(&g_hcnt[(idx * 8 + 2 * Q + (i & 1)) * 32]);
}
__device__ __forceinline__ uint32_t pack_bf16(float lo, float hi) {
  uint32_t r; asm("cvt.rn.bf16x2.f32 %0, %1, %2;" : "=r"(r) : "f"(hi), "f"(lo)); return r;
}
__device__ __forceinline__ float bf_lo(uint32_t w) { return __uint_as_float(w << 16); }
__device__ __forceinline__ float bf_hi(uint32_t w) { return __uint_as_float(w & 0xffff0000u); }
__device__ __forceinline__ uint32_t hmul2(uint32_t a, uint32_t b) {
  __nv_bfloat162 r = __hmul2_rn(*(__nv_bfloat162*)&a, *(__nv_bfloat162*)&b); return *(uint32_t*)&r;
}
__device__ __forceinline__ uint32_t hadd2(uint32_t a, uint32_t b) {
  __nv_bfloat162 r = __hadd2_rn(*(__nv_bfloat162*)&a, *(__nv_bfloat162*)&b); return *(uint32_t*)&r;
}
__device__ __forceinline__ float2 cmul(float2 a, float2 b) { return make_float2(a.x * b.x - a.y * b.y, a.x * b.y + a.y * b.x); }
__device__ __forceinline__ float2 cfma(float2 a, float2 b, float2 c) {
  return make_float2(fmaf(a.x, b.x, fmaf(-a.y, b.y, c.x)), fmaf(a.x, b.y, fmaf(a.y, b.x, c.y)));
}
template <int N> __device__ __forceinline__ void fence_regs(float (&a)[N]) {
#pragma unroll
  for (int i = 0; i < N; i++) asm volatile("" : "+f"(a[i])::"memory");
}
__device__ __forceinline__ int tid_opaque() { int t; asm volatile("mov.u32 %0, %%tid.x;" : "=r"(t)); return t; }
struct Role { int T1, GP, side, m2, dg, cch0; bool last, has2; };
__device__ __forceinline__ Role unpack_role(int x) {
  Role r; r.T1 = x & 15; r.GP = (x >> 4) & 7; r.side = (x >> 7) & 1; r.m2 = (x >> 8) & 63; r.dg = (x >> 14) & 3;
  r.has2 = (x >> 16) & 1; r.last = r.T1 == NT1 - 1; r.cch0 = 160 * r.dg + r.m2; return r;
}
__device__ __forceinline__ Role fresh_role(int x) { asm volatile("" : "+r"(x)); return unpack_role(__shfl_sync(0xffffffffu, x, 0)); }
#define ROLE(x) const Role R_ = fresh_role(x); const int T1 = R_.T1, GP = R_.GP, side = R_.side, m2 = R_.m2, dg = R_.dg, cch0 = R_.cch0; \
  const bool last = R_.last, has2 = R_.has2; (void)T1; (void)GP; (void)side; (void)m2; (void)dg; (void)cch0; (void)last; (void)has2;
__device__ __forceinline__ int n_to_t(int n) {
  int T = n / 160, nl = n - T * 160;
  int L = (T == NT1 - 1) ? 32 : 40;
  return T * 160 + L * ((nl & 7) >> 1) + 2 * (nl >> 3) + (nl & 1);
}

template<int TA> __device__ __forceinline__ void wgmma_n160(float (&d)[80], uint32_t alo, uint32_t ahi, uint32_t blo, uint32_t bhi){
  asm volatile("{\n.reg .b64 da, db;\nmov.b64 da, {%80,%81};\nmov.b64 db, {%82,%83};\n"
    "wgmma.mma_async.sync.aligned.m64n160k16.f32.bf16.bf16 {%0, %1, %2, %3, %4, %5, %6, %7, %8, %9, %10, %11, %12, %13, %14, %15, %16, %17, %18, %19, %20, %21, %22, %23, %24, %25, %26, %27, %28, %29, %30, %31, %32, %33, %34, %35, %36, %37, %38, %39, %40, %41, %42, %43, %44, %45, %46, %47, %48, %49, %50, %51, %52, %53, %54, %55, %56, %57, %58, %59, %60, %61, %62, %63, %64, %65, %66, %67, %68, %69, %70, %71, %72, %73, %74, %75, %76, %77, %78, %79}, da, db, 1, 1, 1, %84, 0;\n}\n"
    : "+f"(d[0]), "+f"(d[1]), "+f"(d[2]), "+f"(d[3]), "+f"(d[4]), "+f"(d[5]), "+f"(d[6]), "+f"(d[7]), "+f"(d[8]), "+f"(d[9]), "+f"(d[10]), "+f"(d[11]), "+f"(d[12]), "+f"(d[13]), "+f"(d[14]), "+f"(d[15]), "+f"(d[16]), "+f"(d[17]), "+f"(d[18]), "+f"(d[19]), "+f"(d[20]), "+f"(d[21]), "+f"(d[22]), "+f"(d[23]), "+f"(d[24]), "+f"(d[25]), "+f"(d[26]), "+f"(d[27]), "+f"(d[28]), "+f"(d[29]), "+f"(d[30]), "+f"(d[31]), "+f"(d[32]), "+f"(d[33]), "+f"(d[34]), "+f"(d[35]), "+f"(d[36]), "+f"(d[37]), "+f"(d[38]), "+f"(d[39]), "+f"(d[40]), "+f"(d[41]), "+f"(d[42]), "+f"(d[43]), "+f"(d[44]), "+f"(d[45]), "+f"(d[46]), "+f"(d[47]), "+f"(d[48]), "+f"(d[49]), "+f"(d[50]), "+f"(d[51]), "+f"(d[52]), "+f"(d[53]), "+f"(d[54]), "+f"(d[55]), "+f"(d[56]), "+f"(d[57]), "+f"(d[58]), "+f"(d[59]), "+f"(d[60]), "+f"(d[61]), "+f"(d[62]), "+f"(d[63]), "+f"(d[64]), "+f"(d[65]), "+f"(d[66]), "+f"(d[67]), "+f"(d[68]), "+f"(d[69]), "+f"(d[70]), "+f"(d[71]), "+f"(d[72]), "+f"(d[73]), "+f"(d[74]), "+f"(d[75]), "+f"(d[76]), "+f"(d[77]), "+f"(d[78]), "+f"(d[79])
    : "r"(alo), "r"(ahi), "r"(blo), "r"(bhi), "n"(TA));
}
__device__ __forceinline__ void wgmma_rs_n160(float (&d)[80], uint32_t a0, uint32_t a1, uint32_t a2, uint32_t a3, uint32_t blo){
  asm volatile("{\n.reg .b64 db;\nmov.b64 db, {%84,8};\nwgmma.mma_async.sync.aligned.m64n160k16.f32.bf16.bf16 {%0, %1, %2, %3, %4, %5, %6, %7, %8, %9, %10, %11, %12, %13, %14, %15, %16, %17, %18, %19, %20, %21, %22, %23, %24, %25, %26, %27, %28, %29, %30, %31, %32, %33, %34, %35, %36, %37, %38, %39, %40, %41, %42, %43, %44, %45, %46, %47, %48, %49, %50, %51, %52, %53, %54, %55, %56, %57, %58, %59, %60, %61, %62, %63, %64, %65, %66, %67, %68, %69, %70, %71, %72, %73, %74, %75, %76, %77, %78, %79}, {%80,%81,%82,%83}, db, 1, 1, 1, 0;\n}\n"
    : "+f"(d[0]), "+f"(d[1]), "+f"(d[2]), "+f"(d[3]), "+f"(d[4]), "+f"(d[5]), "+f"(d[6]), "+f"(d[7]), "+f"(d[8]), "+f"(d[9]), "+f"(d[10]), "+f"(d[11]), "+f"(d[12]), "+f"(d[13]), "+f"(d[14]), "+f"(d[15]), "+f"(d[16]), "+f"(d[17]), "+f"(d[18]), "+f"(d[19]), "+f"(d[20]), "+f"(d[21]), "+f"(d[22]), "+f"(d[23]), "+f"(d[24]), "+f"(d[25]), "+f"(d[26]), "+f"(d[27]), "+f"(d[28]), "+f"(d[29]), "+f"(d[30]), "+f"(d[31]), "+f"(d[32]), "+f"(d[33]), "+f"(d[34]), "+f"(d[35]), "+f"(d[36]), "+f"(d[37]), "+f"(d[38]), "+f"(d[39]), "+f"(d[40]), "+f"(d[41]), "+f"(d[42]), "+f"(d[43]), "+f"(d[44]), "+f"(d[45]), "+f"(d[46]), "+f"(d[47]), "+f"(d[48]), "+f"(d[49]), "+f"(d[50]), "+f"(d[51]), "+f"(d[52]), "+f"(d[53]), "+f"(d[54]), "+f"(d[55]), "+f"(d[56]), "+f"(d[57]), "+f"(d[58]), "+f"(d[59]), "+f"(d[60]), "+f"(d[61]), "+f"(d[62]), "+f"(d[63]), "+f"(d[64]), "+f"(d[65]), "+f"(d[66]), "+f"(d[67]), "+f"(d[68]), "+f"(d[69]), "+f"(d[70]), "+f"(d[71]), "+f"(d[72]), "+f"(d[73]), "+f"(d[74]), "+f"(d[75]), "+f"(d[76]), "+f"(d[77]), "+f"(d[78]), "+f"(d[79])
    : "r"(a0), "r"(a1), "r"(a2), "r"(a3), "r"(blo));
}
template<int N> __device__ __forceinline__ void wgmma_rs_hi(float (&d)[64], uint32_t a0, uint32_t a1, uint32_t a2, uint32_t a3, uint32_t blo);
template<> __device__ __forceinline__ void wgmma_rs_hi<16>(float (&d)[64], uint32_t a0, uint32_t a1, uint32_t a2, uint32_t a3, uint32_t blo){
  asm volatile("{\n.reg .b64 db;\nmov.b64 db, {%12,8};\nwgmma.mma_async.sync.aligned.m64n16k16.f32.bf16.bf16 {%0, %1, %2, %3, %4, %5, %6, %7}, {%8,%9,%10,%11}, db, 1, 1, 1, 0;\n}\n"
    : "+f"(d[56]), "+f"(d[57]), "+f"(d[58]), "+f"(d[59]), "+f"(d[60]), "+f"(d[61]), "+f"(d[62]), "+f"(d[63])
    : "r"(a0), "r"(a1), "r"(a2), "r"(a3), "r"(blo));
}
template<> __device__ __forceinline__ void wgmma_rs_hi<32>(float (&d)[64], uint32_t a0, uint32_t a1, uint32_t a2, uint32_t a3, uint32_t blo){
  asm volatile("{\n.reg .b64 db;\nmov.b64 db, {%20,8};\nwgmma.mma_async.sync.aligned.m64n32k16.f32.bf16.bf16 {%0, %1, %2, %3, %4, %5, %6, %7, %8, %9, %10, %11, %12, %13, %14, %15}, {%16,%17,%18,%19}, db, 1, 1, 1, 0;\n}\n"
    : "+f"(d[48]), "+f"(d[49]), "+f"(d[50]), "+f"(d[51]), "+f"(d[52]), "+f"(d[53]), "+f"(d[54]), "+f"(d[55]), "+f"(d[56]), "+f"(d[57]), "+f"(d[58]), "+f"(d[59]), "+f"(d[60]), "+f"(d[61]), "+f"(d[62]), "+f"(d[63])
    : "r"(a0), "r"(a1), "r"(a2), "r"(a3), "r"(blo));
}
template<> __device__ __forceinline__ void wgmma_rs_hi<48>(float (&d)[64], uint32_t a0, uint32_t a1, uint32_t a2, uint32_t a3, uint32_t blo){
  asm volatile("{\n.reg .b64 db;\nmov.b64 db, {%28,8};\nwgmma.mma_async.sync.aligned.m64n48k16.f32.bf16.bf16 {%0, %1, %2, %3, %4, %5, %6, %7, %8, %9, %10, %11, %12, %13, %14, %15, %16, %17, %18, %19, %20, %21, %22, %23}, {%24,%25,%26,%27}, db, 1, 1, 1, 0;\n}\n"
    : "+f"(d[40]), "+f"(d[41]), "+f"(d[42]), "+f"(d[43]), "+f"(d[44]), "+f"(d[45]), "+f"(d[46]), "+f"(d[47]), "+f"(d[48]), "+f"(d[49]), "+f"(d[50]), "+f"(d[51]), "+f"(d[52]), "+f"(d[53]), "+f"(d[54]), "+f"(d[55]), "+f"(d[56]), "+f"(d[57]), "+f"(d[58]), "+f"(d[59]), "+f"(d[60]), "+f"(d[61]), "+f"(d[62]), "+f"(d[63])
    : "r"(a0), "r"(a1), "r"(a2), "r"(a3), "r"(blo));
}
template<> __device__ __forceinline__ void wgmma_rs_hi<64>(float (&d)[64], uint32_t a0, uint32_t a1, uint32_t a2, uint32_t a3, uint32_t blo){
  asm volatile("{\n.reg .b64 db;\nmov.b64 db, {%36,8};\nwgmma.mma_async.sync.aligned.m64n64k16.f32.bf16.bf16 {%0, %1, %2, %3, %4, %5, %6, %7, %8, %9, %10, %11, %12, %13, %14, %15, %16, %17, %18, %19, %20, %21, %22, %23, %24, %25, %26, %27, %28, %29, %30, %31}, {%32,%33,%34,%35}, db, 1, 1, 1, 0;\n}\n"
    : "+f"(d[32]), "+f"(d[33]), "+f"(d[34]), "+f"(d[35]), "+f"(d[36]), "+f"(d[37]), "+f"(d[38]), "+f"(d[39]), "+f"(d[40]), "+f"(d[41]), "+f"(d[42]), "+f"(d[43]), "+f"(d[44]), "+f"(d[45]), "+f"(d[46]), "+f"(d[47]), "+f"(d[48]), "+f"(d[49]), "+f"(d[50]), "+f"(d[51]), "+f"(d[52]), "+f"(d[53]), "+f"(d[54]), "+f"(d[55]), "+f"(d[56]), "+f"(d[57]), "+f"(d[58]), "+f"(d[59]), "+f"(d[60]), "+f"(d[61]), "+f"(d[62]), "+f"(d[63])
    : "r"(a0), "r"(a1), "r"(a2), "r"(a3), "r"(blo));
}
template<> __device__ __forceinline__ void wgmma_rs_hi<80>(float (&d)[64], uint32_t a0, uint32_t a1, uint32_t a2, uint32_t a3, uint32_t blo){
  asm volatile("{\n.reg .b64 db;\nmov.b64 db, {%44,8};\nwgmma.mma_async.sync.aligned.m64n80k16.f32.bf16.bf16 {%0, %1, %2, %3, %4, %5, %6, %7, %8, %9, %10, %11, %12, %13, %14, %15, %16, %17, %18, %19, %20, %21, %22, %23, %24, %25, %26, %27, %28, %29, %30, %31, %32, %33, %34, %35, %36, %37, %38, %39}, {%40,%41,%42,%43}, db, 1, 1, 1, 0;\n}\n"
    : "+f"(d[24]), "+f"(d[25]), "+f"(d[26]), "+f"(d[27]), "+f"(d[28]), "+f"(d[29]), "+f"(d[30]), "+f"(d[31]), "+f"(d[32]), "+f"(d[33]), "+f"(d[34]), "+f"(d[35]), "+f"(d[36]), "+f"(d[37]), "+f"(d[38]), "+f"(d[39]), "+f"(d[40]), "+f"(d[41]), "+f"(d[42]), "+f"(d[43]), "+f"(d[44]), "+f"(d[45]), "+f"(d[46]), "+f"(d[47]), "+f"(d[48]), "+f"(d[49]), "+f"(d[50]), "+f"(d[51]), "+f"(d[52]), "+f"(d[53]), "+f"(d[54]), "+f"(d[55]), "+f"(d[56]), "+f"(d[57]), "+f"(d[58]), "+f"(d[59]), "+f"(d[60]), "+f"(d[61]), "+f"(d[62]), "+f"(d[63])
    : "r"(a0), "r"(a1), "r"(a2), "r"(a3), "r"(blo));
}
template<> __device__ __forceinline__ void wgmma_rs_hi<96>(float (&d)[64], uint32_t a0, uint32_t a1, uint32_t a2, uint32_t a3, uint32_t blo){
  asm volatile("{\n.reg .b64 db;\nmov.b64 db, {%52,8};\nwgmma.mma_async.sync.aligned.m64n96k16.f32.bf16.bf16 {%0, %1, %2, %3, %4, %5, %6, %7, %8, %9, %10, %11, %12, %13, %14, %15, %16, %17, %18, %19, %20, %21, %22, %23, %24, %25, %26, %27, %28, %29, %30, %31, %32, %33, %34, %35, %36, %37, %38, %39, %40, %41, %42, %43, %44, %45, %46, %47}, {%48,%49,%50,%51}, db, 1, 1, 1, 0;\n}\n"
    : "+f"(d[16]), "+f"(d[17]), "+f"(d[18]), "+f"(d[19]), "+f"(d[20]), "+f"(d[21]), "+f"(d[22]), "+f"(d[23]), "+f"(d[24]), "+f"(d[25]), "+f"(d[26]), "+f"(d[27]), "+f"(d[28]), "+f"(d[29]), "+f"(d[30]), "+f"(d[31]), "+f"(d[32]), "+f"(d[33]), "+f"(d[34]), "+f"(d[35]), "+f"(d[36]), "+f"(d[37]), "+f"(d[38]), "+f"(d[39]), "+f"(d[40]), "+f"(d[41]), "+f"(d[42]), "+f"(d[43]), "+f"(d[44]), "+f"(d[45]), "+f"(d[46]), "+f"(d[47]), "+f"(d[48]), "+f"(d[49]), "+f"(d[50]), "+f"(d[51]), "+f"(d[52]), "+f"(d[53]), "+f"(d[54]), "+f"(d[55]), "+f"(d[56]), "+f"(d[57]), "+f"(d[58]), "+f"(d[59]), "+f"(d[60]), "+f"(d[61]), "+f"(d[62]), "+f"(d[63])
    : "r"(a0), "r"(a1), "r"(a2), "r"(a3), "r"(blo));
}
template<> __device__ __forceinline__ void wgmma_rs_hi<112>(float (&d)[64], uint32_t a0, uint32_t a1, uint32_t a2, uint32_t a3, uint32_t blo){
  asm volatile("{\n.reg .b64 db;\nmov.b64 db, {%60,8};\nwgmma.mma_async.sync.aligned.m64n112k16.f32.bf16.bf16 {%0, %1, %2, %3, %4, %5, %6, %7, %8, %9, %10, %11, %12, %13, %14, %15, %16, %17, %18, %19, %20, %21, %22, %23, %24, %25, %26, %27, %28, %29, %30, %31, %32, %33, %34, %35, %36, %37, %38, %39, %40, %41, %42, %43, %44, %45, %46, %47, %48, %49, %50, %51, %52, %53, %54, %55}, {%56,%57,%58,%59}, db, 1, 1, 1, 0;\n}\n"
    : "+f"(d[8]), "+f"(d[9]), "+f"(d[10]), "+f"(d[11]), "+f"(d[12]), "+f"(d[13]), "+f"(d[14]), "+f"(d[15]), "+f"(d[16]), "+f"(d[17]), "+f"(d[18]), "+f"(d[19]), "+f"(d[20]), "+f"(d[21]), "+f"(d[22]), "+f"(d[23]), "+f"(d[24]), "+f"(d[25]), "+f"(d[26]), "+f"(d[27]), "+f"(d[28]), "+f"(d[29]), "+f"(d[30]), "+f"(d[31]), "+f"(d[32]), "+f"(d[33]), "+f"(d[34]), "+f"(d[35]), "+f"(d[36]), "+f"(d[37]), "+f"(d[38]), "+f"(d[39]), "+f"(d[40]), "+f"(d[41]), "+f"(d[42]), "+f"(d[43]), "+f"(d[44]), "+f"(d[45]), "+f"(d[46]), "+f"(d[47]), "+f"(d[48]), "+f"(d[49]), "+f"(d[50]), "+f"(d[51]), "+f"(d[52]), "+f"(d[53]), "+f"(d[54]), "+f"(d[55]), "+f"(d[56]), "+f"(d[57]), "+f"(d[58]), "+f"(d[59]), "+f"(d[60]), "+f"(d[61]), "+f"(d[62]), "+f"(d[63])
    : "r"(a0), "r"(a1), "r"(a2), "r"(a3), "r"(blo));
}
template<> __device__ __forceinline__ void wgmma_rs_hi<128>(float (&d)[64], uint32_t a0, uint32_t a1, uint32_t a2, uint32_t a3, uint32_t blo){
  asm volatile("{\n.reg .b64 db;\nmov.b64 db, {%68,8};\nwgmma.mma_async.sync.aligned.m64n128k16.f32.bf16.bf16 {%0, %1, %2, %3, %4, %5, %6, %7, %8, %9, %10, %11, %12, %13, %14, %15, %16, %17, %18, %19, %20, %21, %22, %23, %24, %25, %26, %27, %28, %29, %30, %31, %32, %33, %34, %35, %36, %37, %38, %39, %40, %41, %42, %43, %44, %45, %46, %47, %48, %49, %50, %51, %52, %53, %54, %55, %56, %57, %58, %59, %60, %61, %62, %63}, {%64,%65,%66,%67}, db, 1, 1, 1, 0;\n}\n"
    : "+f"(d[0]), "+f"(d[1]), "+f"(d[2]), "+f"(d[3]), "+f"(d[4]), "+f"(d[5]), "+f"(d[6]), "+f"(d[7]), "+f"(d[8]), "+f"(d[9]), "+f"(d[10]), "+f"(d[11]), "+f"(d[12]), "+f"(d[13]), "+f"(d[14]), "+f"(d[15]), "+f"(d[16]), "+f"(d[17]), "+f"(d[18]), "+f"(d[19]), "+f"(d[20]), "+f"(d[21]), "+f"(d[22]), "+f"(d[23]), "+f"(d[24]), "+f"(d[25]), "+f"(d[26]), "+f"(d[27]), "+f"(d[28]), "+f"(d[29]), "+f"(d[30]), "+f"(d[31]), "+f"(d[32]), "+f"(d[33]), "+f"(d[34]), "+f"(d[35]), "+f"(d[36]), "+f"(d[37]), "+f"(d[38]), "+f"(d[39]), "+f"(d[40]), "+f"(d[41]), "+f"(d[42]), "+f"(d[43]), "+f"(d[44]), "+f"(d[45]), "+f"(d[46]), "+f"(d[47]), "+f"(d[48]), "+f"(d[49]), "+f"(d[50]), "+f"(d[51]), "+f"(d[52]), "+f"(d[53]), "+f"(d[54]), "+f"(d[55]), "+f"(d[56]), "+f"(d[57]), "+f"(d[58]), "+f"(d[59]), "+f"(d[60]), "+f"(d[61]), "+f"(d[62]), "+f"(d[63])
    : "r"(a0), "r"(a1), "r"(a2), "r"(a3), "r"(blo));
}

struct CvCtx {
  uint32_t koff, zero, so[3];
  int srcA, srcB;
  bool wrapA, s3, kodd;
};
struct CvPipe { uint32_t Ap, Ep, keep, send; };
template <int LO> __device__ __forceinline__ void cv_copy(float (&acc)[64]) {
#pragma unroll
  for (int i = LO; i < 64; i++) { float t; asm volatile("mov.b32 %0, %1;" : "=f"(t) : "f"(acc[i]) : "memory"); acc[i] = t; }
}
template <int G> __device__ __forceinline__ void cv_raw(uint32_t (&A)[4][4], uint32_t kaddr) {
#pragma unroll
  for (int i = 0; i < 4; i++) {
    const uint32_t a = kaddr + (4 * G + i) * 128;
    A[i][0] = lds32(a); A[i][1] = lds32(a + 4); A[i][3] = lds32(a + 8);
  }
}
__device__ __forceinline__ void cv_form(uint32_t (&A)[4][4], uint32_t sel) {
#pragma unroll
  for (int i = 0; i < 4; i++) {
    asm volatile("prmt.b32 %0, %0, %1, %2;" : "+r"(A[i][0]) : "r"(A[i][1]), "r"(sel));
    asm volatile("prmt.b32 %0, %1, %2, %3;" : "=r"(A[i][2]) : "r"(A[i][1]), "r"(A[i][3]), "r"(sel));
  }
}
#define CVV 2
template <int G> __device__ __forceinline__ void cv_step(float (&acc)[64], uint32_t (&A)[4][4], CvPipe& s, const CvCtx& c, uint32_t cb, uint32_t stg) {
  constexpr int JA = G - 1, JB = G - 2, NH = CVV == 1 ? 4 : (CVV == 3 ? 2 : 1);
  const uint32_t db0 = desc_lo(cb + CV_U + 192, CV_PL);
  uint32_t B[4][4];
  uint32_t ra[2], rb;
  if constexpr (G < 8) {
    wgmma_fence();
#pragma unroll
    for (int i = 0; i < NH; i++) wgmma_rs_hi<128 - 16 * (G & 7)>(acc, A[i][0], A[i][1], A[i][2], A[i][3], db0 - 4 * i);
    wgmma_commit();
    __syncwarp();
  }
  if constexpr (JA >= 0 && JA < 8) {
    const uint32_t p0 = pack_bf16(acc[8 * JA + 1], acc[8 * JA + 3]), p1 = pack_bf16(acc[8 * JA + 5], acc[8 * JA + 7]);
    ra[0] = __shfl_sync(0xffffffffu, c.wrapA ? s.Ap : p0, c.srcA);
    ra[1] = __shfl_sync(0xffffffffu, c.wrapA ? p0 : p1, c.srcA);
    s.Ap = p1;
  }
  if constexpr (JB >= 0) rb = __shfl_sync(0xffffffffu, s.send, c.srcB);
  if constexpr (G < 7) cv_raw<G + 1>(B, cb + c.koff);
  uint32_t z = 0;
  if constexpr (G < 8 && NH < 4) {
    __syncwarp();
    wgmma_fence();
#pragma unroll
    for (int i = NH; i < 4; i++) wgmma_rs_hi<128 - 16 * (G & 7)>(acc, A[i][0], A[i][1], A[i][2], A[i][3], db0 - 4 * i);
    wgmma_commit();
    asm volatile("mov.u32 %0, %%clock;" : "=r"(z)::"memory");
    z &= c.zero;
  }
  if constexpr (G < 7) cv_form(B, 0x5432u | z);
  if constexpr (JB >= 0) sts32(stg + ((c.so[JB / 3] >> (10 * (JB % 3))) & 0xffc), hadd2(rb | z, s.keep));
  if constexpr (JA >= 0 && JA < 8) {
    const uint32_t sh = 16 | z, mk = 0xffff0000u | z;
    const uint32_t ev = pack_bf16(acc[8 * JA] + __uint_as_float(ra[0] << sh), acc[8 * JA + 2] + __uint_as_float(ra[0] & mk));
    const uint32_t od = pack_bf16(acc[8 * JA + 4] + __uint_as_float(ra[1] << sh), acc[8 * JA + 6] + __uint_as_float(ra[1] & mk));
    s.send = c.kodd ? ev : (c.s3 ? s.Ep : od);
    s.keep = c.kodd ? od : ev;
    s.Ep = od;
  }
  if constexpr (G < 8) { __syncwarp(); wgmma_wait<0>(); cv_copy<8 * (G & 7)>(acc); }
  if constexpr (G < 9) cv_step<G + 1>(acc, B, s, c, cb, stg);
}
__device__ __forceinline__ uint32_t cv_stage(int slot) { return sb + (slot < 4 ? 40960 + slot * 4096 : CV_OFF + CV_K); }
__device__ __forceinline__ void cv_setup(CvCtx& c) {
  const int tid = tid_opaque() & 127, w = tid >> 5, lane = tid & 31, r = lane >> 2, q = lane & 3;
  const int i0 = (r >> 1) & 1, i1 = r >> 2;
  c.koff = CV_K - 32 + 4 * (8 * (r >> 1) + 2 * w + (r & 1) + 2 * q);
  c.srcA = i0 ? lane - 8 : lane + 8 - q + ((q + 3) & 3);
  c.wrapA = i0 && q == 3;
  c.srcB = i1 == 0 ? (lane - q + 16 + ((q + 3) & 3)) : (lane - q - 16 + ((q + 1) & 3));
  c.s3 = (i1 == 1 && q == 3); c.kodd = (i1 == 1 && q < 3);
  c.zero = lds32(sb + EP_OFF + 24);
#pragma unroll
  for (int i = 0; i < 3; i++) c.so[i] = lds32(sb + SO_OFF + 512 * i + 4 * tid);
}
__device__ __forceinline__ void cv_table() {
  const int tid = tid_opaque() & 127, r = (tid & 31) >> 2, q = tid & 3;
  int t = 16 * (2 * (r < 4 ? q : 4 + ((q + 1) & 3)) + ((r >> 1) & 1)) + 4 * (tid >> 5) + 2 * (r & 1);
#pragma unroll 1
  for (int i = 0; i < 3; i++) {
    uint32_t v = 0;
#pragma unroll 1
    for (int x = 0; x < 3; x++, t += 256) {
      const int T = t / 160, tl = t - T * 160;
      const int qq = (T >= NT1 - 1) ? (tl >> 5) : (tl / 40);
      int ck = 20 * T + ((tl - qq * ((T >= NT1 - 1) ? 32 : 40)) >> 1);
      ck ^= (ck >> 2) & 6;
      v |= (uint32_t)((ck * 4 + qq) & 1023) << (10 * x + 2);
    }
    sts32(sb + SO_OFF + 512 * i + 4 * tid, v);
  }
}
__device__ __forceinline__ void conv_channel(int slot, const CvCtx& c) {
  const uint32_t cb = sb + CV_OFF + slot * CV_B;
  float acc[64];
  CvPipe s;
  s.Ap = s.Ep = 0u;
  uint32_t A[4][4];
#pragma unroll
  for (int i = 0; i < 64; i++) acc[i] = 0.f;
  if (slot == 4) mbar_wait(bars + 8 * B_CVDONE);
  mbar_wait(bars + 8 * (B_CVFULL + slot));
  cv_raw<0>(A, cb + c.koff);
  {
    const uint32_t w0 = lds32(cb + CV_K);
    const uint32_t wp = __byte_perm(pack_bf16(bf_lo(w0) + __uint_as_float(lds32(sb + EP_OFF + 4 * slot)), 0.f), w0, 0x7610);
    if (c.koff == CV_K) A[0][0] = wp;
    if (c.koff == CV_K - 4) A[0][1] = wp;
    if (c.koff == CV_K - 8) A[0][3] = wp;
  }
  cv_form(A, 0x5432u);
  cv_copy<0>(acc);
  cv_step<0>(acc, A, s, c, cb, cv_stage(slot));
  fence_async_smem();
  mbar_arrive(bars + 8 * (B_CVDONE + slot));
}

__device__ __forceinline__ void kv_issue(const Params& p, int c, int m2, int dg) {
  const uint32_t fb = bars + 8 * (B_KV + c);
  mbar_expect_tx(fb, KV_PIECE);
  tma3(sb + KS_OFF + c * KV_PIECE, &p.mK, 160 * dg + 32 * c, 64 * m2 - 3, 0, fb);
  tma3(sb + KS_OFF + c * KV_PIECE + 4864, &p.mV, 160 * dg + 32 * c, 64 * m2 - 1, 0, fb);
}
__device__ __forceinline__ void kv_tile(int m, int c, int y, uint32_t (&o)[4][4]) {
  const int lane = tid_opaque() & 31, tg = lane & 3, pr = 8 * (y ^ (tg >> 1)) + (lane >> 2);
  const uint32_t pb = sb + KS_OFF + c * KV_PIECE + 4 * pr;
  const uint32_t ka = pb + tg * 1216, va = pb + 4864 + tg * 1088 + 64;
  const uint32_t kh = (m == 0 && tg > 0) ? ka - 192 : ka;
  uint32_t kk[19], u[16];
  const float4 t = lds128f(sb + TAP_OFF + 256 * c + 16 * pr);
#pragma unroll
  for (int i = 0; i < 19; i++) { kk[i] = lds32((i < 3 ? kh : ka) + i * 64); if (i >= 3) u[i - 3] = lds32(va + (i - 3) * 64); }
  const uint32_t dst = sb + KS_OFF + c * KV_PIECE + pr * 64 + tg * 16;
  if (y) {
    __syncwarp();
#pragma unroll
    for (int x = 0; x < 4; x++) sts128((dst ^ 512) + x * 1024, make_uint4(o[x][0], o[x][1], o[x][2], o[x][3]));
  }
  const uint32_t w0 = __byte_perm(__float_as_uint(t.x), __float_as_uint(t.z), 0x5410), w1 = __byte_perm(__float_as_uint(t.x), __float_as_uint(t.z), 0x7632);
  const uint32_t w2 = __byte_perm(__float_as_uint(t.y), __float_as_uint(t.w), 0x5410), w3 = __byte_perm(__float_as_uint(t.y), __float_as_uint(t.w), 0x7632);
#pragma unroll
  for (int i = 0; i < 16; i++) {
    uint32_t a = hmul2(kk[i], w3);
    a = hadd2(a, hmul2(kk[i + 1], w2)); a = hadd2(a, hmul2(kk[i + 2], w1)); a = hadd2(a, hmul2(kk[i + 3], w0));
    u[i] = hmul2(a, u[i]);
  }
#pragma unroll
  for (int x = 0; x < 4; x++) {
#pragma unroll
    for (int qq = 0; qq < 4; qq++) o[x][qq] = __byte_perm(u[15 - 4 * qq - (x & 2)], u[14 - 4 * qq - (x & 2)], (x & 1) ? 0x7632 : 0x5410);
    if (y) sts128(dst + x * 1024, make_uint4(o[x][0], o[x][1], o[x][2], o[x][3]));
  }
}
__device__ __forceinline__ void ln_finish(float s1, float s2, float& mean, float& rstd) {
  mean = s1 * (1.f / 640.f);
  const float v = fmaxf(fmaf(-mean, mean, s2 * (1.f / 640.f)), 0.f) + 1e-5f;
  asm("rsqrt.approx.ftz.f32 %0, %1;" : "=f"(rstd) : "f"(v));
}
__device__ __forceinline__ void stat_table(int T1, unsigned want, int l, int g, const uint4* x0, const uint4* x1, float (&xa)[2], float (&xb)[2]) {
  const int n = 32 * g + (tid_opaque() & 31);
  const uint4* rp = &g_stats[8 * l * SEQ + min(160 * T1 + n, SEQ - 1)];
  float a[4], b[4];
  uint32_t it = 0;
  while (true) {
    bool ok = true;
#pragma unroll
    for (int i = 0; i < 4; i++) ok &= (rec_ld(rp + SEQ * i, a[i], b[i]) == want);
    ok &= rec_ld(x0, xa[0], xb[0]) == want;
    ok &= rec_ld(x1, xa[1], xb[1]) == want;
    if (__all_sync(0xffffffffu, ok)) break;
    trap_if(++it > SPIN_LIMIT);
  }
  float m, rs;
  ln_finish((a[0] + a[1]) + (a[2] + a[3]), (b[0] + b[1]) + (b[2] + b[3]), m, rs);
  sts32(sb + STAB_OFF + ((n >> 1) & 3) * 160 + (n >> 3) * 8 + (n & 1) * 4, __float_as_uint(rs));
  const uint32_t hi = pack_bf16(-m, -m);
  const float lo = -m - bf_lo(hi);
  sts128(sb + (l ? MX1_OFF : MX0_OFF) + n * 16, make_uint4(hi, pack_bf16(lo, lo), 0u, 0u));
  fence_async_smem();
}
__device__ __forceinline__ void stats_reduce(float (&a)[2], float (&b)[2], float (&mean)[2], float (&rstd)[2]) {
#pragma unroll
  for (int o = 1; o < 4; o <<= 1)
#pragma unroll
    for (int h = 0; h < 2; h++) { a[h] += __shfl_xor_sync(0xffffffffu, a[h], o); b[h] += __shfl_xor_sync(0xffffffffu, b[h], o); }
#pragma unroll
  for (int h = 0; h < 2; h++) ln_finish(a[h], b[h], mean[h], rstd[h]);
}

template <bool FIRST>
__device__ __forceinline__ void stats_publish(int which, int n0, int dg, unsigned tag, const float (&acc)[80]) {
  const int q = tid_opaque() & 3, h = q & 1;
  float s1[2] = {0.f, 0.f}, s2[2] = {0.f, 0.f}, t1[2] = {0.f, 0.f}, t2[2] = {0.f, 0.f};
#pragma unroll
  for (int j = 0; j < 20; j++)
#pragma unroll
    for (int y = 0; y < 2; y++) {
      const float a = acc[4 * j + 2 * y], b = acc[4 * j + 2 * y + 1];
      s1[y] += a; t1[y] += b; s2[y] = fmaf(a, a, s2[y]); t2[y] = fmaf(b, b, t2[y]);
    }
#pragma unroll
  for (int y = 0; y < 2; y++) { s1[y] += t1[y]; s2[y] += t2[y]; }
  float a = (h ? s1[1] : s1[0]) + __shfl_xor_sync(0xffffffffu, h ? s1[0] : s1[1], 1);
  float b = (h ? s2[1] : s2[0]) + __shfl_xor_sync(0xffffffffu, h ? s2[0] : s2[1], 1);
  a += __shfl_xor_sync(0xffffffffu, a, 2);
  b += __shfl_xor_sync(0xffffffffu, b, 2);
  if (FIRST) {
    rec_st(&g_stats[((q >> 1) * 4 + dg) * SEQ + n0 + 8 * h], a, b, q < 2 ? tag : tag - 1);
    rec_st(&g_stats[((q >> 1) * 4 + 8 + dg) * SEQ + n0 + 8 * h], a, b, tag - 1);
  } else if (q < 2) rec_st(&g_stats[(which * 4 + dg) * SEQ + n0 + 8 * h], a, b, tag);
}
__device__ __forceinline__ void stats_get(int which, int n0, unsigned tag, float (&mean)[2], float (&rstd)[2]) {
  const uint4* p0 = &g_stats[(which * 4 + (tid_opaque() & 3)) * SEQ + n0];
  float a[2], b[2];
  uint32_t it = 0;
  while (true) {
    const unsigned t0 = rec_ld(p0, a[0], b[0]), t1 = rec_ld(p0 + 8, a[1], b[1]);
    if (__all_sync(0xffffffffu, t0 == tag && t1 == tag)) break;
    trap_if(++it > SPIN_LIMIT);
  }
  stats_reduce(a, b, mean, rstd);
}
__device__ __forceinline__ void x0_load(float (&acc)[80]) {
  const int t = tid_opaque() & 127;
  const uint32_t xa = sb + XT_OFF + (16 * (t >> 5) + ((t & 31) >> 2)) * 320 + 8 * (t & 3);
  mbar_wait(bars + 8 * B_XT);
#pragma unroll
  for (int h = 0; h < 2; h++)
#pragma unroll
    for (int J = 0; J < 10; J++) {
      const float2 v = lds64f(xa + h * 2560 + 32 * J);
      const uint32_t x = __float_as_uint(v.x), y = __float_as_uint(v.y);
      acc[8 * J + 2 * h] = bf_lo(x); acc[8 * J + 2 * h + 1] = bf_hi(x);
      acc[8 * J + 4 + 2 * h] = bf_lo(y); acc[8 * J + 4 + 2 * h + 1] = bf_hi(y);
    }
}

template <bool FROM_X0>
__device__ __forceinline__ void dskip_init(float (&acc)[80], const float (&mean)[2], const float (&rstd)[2]) {
  const int t = tid_opaque() & 127;
  const uint32_t xa = sb + XT_OFF + (16 * (t >> 5) + ((t & 31) >> 2)) * 320 + 8 * (t & 3), da = sb + DTAB_OFF + 8 * (t & 3);
  float2 dw[10], xv[10][2];
#pragma unroll
  for (int J = 0; J < 2; J++) { dw[J] = lds64f(da + 32 * J); if (FROM_X0) { xv[J][0] = lds64f(xa + 32 * J); xv[J][1] = lds64f(xa + 2560 + 32 * J); } }
#pragma unroll
  for (int J = 0; J < 10; J++) {
    if (J + 2 < 10) { dw[J + 2] = lds64f(da + 32 * (J + 2)); if (FROM_X0) { xv[J + 2][0] = lds64f(xa + 32 * (J + 2)); xv[J + 2][1] = lds64f(xa + 2560 + 32 * (J + 2)); } }
#pragma unroll
    for (int x = 0; x < 8; x++) {
      const int h = (x >> 1) & 1;
      const uint32_t dwd = __float_as_uint(x < 4 ? dw[J].x : dw[J].y);
      const float tt = fmaf(rstd[h], (x & 1) ? bf_hi(dwd) : bf_lo(dwd), 1.f);
      float a = acc[8 * J + x];
      if (FROM_X0) { const uint32_t xw = __float_as_uint(x < 4 ? xv[J][h].x : xv[J][h].y); a = (x & 1) ? bf_hi(xw) : bf_lo(xw); }
      acc[8 * J + x] = FROM_X0 ? (a - mean[h]) * tt : fmaf(a, tt, -mean[h] * tt);
    }
  }
}

__global__ void __launch_bounds__(512, 1) fused_kernel(const __grid_constant__ Params p) {
  extern __shared__ __align__(1024) uint8_t smem_raw[];
  const int tid = threadIdx.x, lane = tid & 31;
  const int wid = __shfl_sync(0xffffffffu, tid >> 5, 0), wg = wid >> 2;
  unsigned smid; asm volatile("mov.u32 %0, %%smid;" : "=r"(smid));
  const int role = p.role[min(smid, 131u)];
  if (wid == 12) {
    const bool el = elect_one();
    if (el) {
      asm volatile("prefetch.tensormap [%0];" ::"l"(&p.mB) : "memory");
      asm volatile("prefetch.tensormap [%0];" ::"l"((role & 15) == NT1 - 1 ? &p.mXl : &p.mX) : "memory");
#pragma unroll
      for (int k = 0; k < S1; k++) mbar_init(bars + 8 * (B_G1FULL + k), 1);
#pragma unroll
      for (int k = 0; k < 6; k++) mbar_init(bars + 8 * (B_XT + k), 1);
      asm volatile("fence.mbarrier_init.release.cluster;" ::: "memory");
    }
    if (role >= 0) {
      __syncwarp();
      asm volatile("bar.arrive 5, 288;" ::: "memory");
      const Role R = unpack_role(role);
      if (elect_one()) {
        TS(45);
#pragma unroll 1
        for (int k = 0; k < S1; k++) {
          const uint32_t fb = bars + 8 * (B_G1FULL + k);
          mbar_expect_tx(fb, G1_STAGE);
          tma4(sb + k * G1_STAGE + G1_XOFF, R.last ? &p.mXl : &p.mX, 64 * k, 0, 0, R.last ? 0 : 80 * R.T1, fb);
          tma5(sb + k * G1_STAGE, &p.mB, 64 * k, 0, 0, 4 * R.side, 2 * R.GP, fb);
          if (PFD) asm volatile("prefetch.tensormap [%0];" ::"l"(&p.mK + k) : "memory");
        }
        if (R.has2) {
          mbar_expect_tx(bars + 8 * B_XT, 20480);
#pragma unroll 1
          for (int h = 0; h < 2; h++) {
            const int ng = 8 * R.m2 + 4 * h, T = ng / 20;
            tma4(sb + XT_OFF + h * 10240, T == NT1 - 1 ? &p.mXtl : &p.mXt, 160 * R.dg, 0, 0, T == NT1 - 1 ? ng - 240 : ng + 60 * T, bars + 8 * B_XT);
          }
#pragma unroll 1
          for (int c = 0; c < KV0; c++) kv_issue(p, c, R.m2, R.dg);
        }
        TS(44);
      }
      __syncwarp();
      bar_sync(6, 64);
    }
  }
  trap_if(smid >= 132 || smem_u32(smem_raw) != sb);
  if (role < 0) {
    if (wid == 0) {
      const unsigned tag = ld_rlx(g_epoch);
      uint32_t it = 0;
      while (!__all_sync(0xffffffffu, (int)(ld_rlx(&g_hcnt[(lane & 7) * 32]) - 40 * tag) >= 0)) { __nanosleep(500); trap_if(++it > SPIN_LIMIT); }
    }
    return;
  }
  float mean0[2] = {0.f, 0.f}, rstd0[2] = {0.f, 0.f};
  if (wg == 2 || wid == 14) {
    ROLE(role)
    const int c = wid == 14 ? 4 : wid - 8;
    const unsigned tag = ld_rlx(g_epoch);
    if (has2) {
      uint2 bv[2][5];
#pragma unroll
      for (int x = 0; x < 2; x++)
#pragma unroll
        for (int i = 0; i < 5; i++) bv[x][i] = ldv64((const uint2*)((x ? p.bim : p.bre) + (cch0 + 32 * c) * DM) + lane + 32 * i);
      float sv[2];
#pragma unroll
      for (int x = 0; x < 2; x++) {
        float a = 0.f;
#pragma unroll
        for (int i = 0; i < 5; i++) a += (bf_lo(bv[x][i].x) + bf_hi(bv[x][i].x)) + (bf_lo(bv[x][i].y) + bf_hi(bv[x][i].y));
        sv[x] = a;
      }
#pragma unroll
      for (int o = 16; o > 0; o >>= 1) { sv[0] += __shfl_xor_sync(0xffffffffu, sv[0], o); sv[1] += __shfl_xor_sync(0xffffffffu, sv[1], o); }
      if (lane < 2) rec_st(&g_sB[(cch0 + 32 * c) * 2 + lane], sv[0], sv[1], tag);
      if (tid == 256) TS(47);
      __syncwarp();
      bar_sync(8, 192);
      if (wg == 2) {
        float xs[80];
        x0_load(xs);
        stats_publish<true>(0, 64 * m2 + 16 * c + (lane >> 2), dg, tag, xs);
        if (tid == 256) TS(31);
      }
      mbar_wait(bars + 8 * B_EP);
      mbar_wait(bars + 8 * (B_KV + c));
      mbar_wait(bars + 8 * (B_G1DONE + PAUSE_K - 1));
      if (tid == 448) TS(52);
      uint32_t o[4][4] = {};
#pragma unroll 1
      for (int y = 0; y < 2; y++) kv_tile(m2, c, y, o);
      fence_async_smem();
      __syncwarp();
      if (lane == 0) { mbar_arrive(bars + 8 * B_PREP); mbar_arrive(bars + 8 * (B_PD + c)); }
      if (tid == 448) TS(51);
    } else bar_sync(8, 192);
    {
      const uint4* x0 = wg == 2 ? &g_stats[(lane & 3) * SEQ + (has2 ? 64 * m2 : 0) + 16 * c + (lane >> 2)] : &g_sB[(128 * GP + 32 * side + lane) * 2];
      float xa[2], xb[2];
      stat_table(T1, tag, 0, c, x0, x0 + (wg == 2 ? 8 : 128), xa, xb);
      if (wg == 2) stats_reduce(xa, xb, mean0, rstd0);
      else {
#pragma unroll
        for (int i = 0; i < 2; i++) {
          const float ha = bf_lo(pack_bf16(xa[i], 0.f)), hb = bf_lo(pack_bf16(xb[i], 0.f));
          const float pa = __uint_as_float(pack_bf16(ha, xa[i] - ha)), pb = __uint_as_float(pack_bf16(hb, xb[i] - hb));
          sts64f(sb + CTAB_OFF + (32 * i + lane) * 24 + 16, p.swap ? pb : pa, p.swap ? pa : pb);
        }
      }
      mbar_arrive(bars + 8 * B_STAB);
      if (tid == 448) TS(26);
    }
  } else if (wid == 15) {
    ROLE(role)
    const int ch = 128 * GP + 32 * side + lane;
    uint32_t r0 = ldv16(p.lre + ch), r1 = ldv16(p.lim + ch), r2 = ldv16(p.logdt + ch);
    const uint32_t r3 = ldv16(p.lre + ch + 64), r4 = ldv16(p.lim + ch + 64), r5 = ldv16(p.logdt + ch + 64);
#pragma unroll 1
    for (int i = 0; i < 2; i++) {
      const float lr = bf_lo(r0), li = bf_lo(r1);
      const float dt = __bfloat162float(__float2bfloat16_rn(expf(bf_lo(r2))));
      const float mag = expf(dt * lr);
      float sn, cs; sincospif(dt * li * 0.31830988618379067f, &sn, &cs);
      const float ar = mag * cs, ai = mag * sn;
      const float inv = 2.f / (lr * lr + li * li);
      const uint32_t ad = sb + CTAB_OFF + (32 * i + lane) * 24;
      sts64f(ad, ar, ai);
      sts64f(ad + 8, ((ar - 1.f) * lr + ai * li) * inv, (ai * lr - (ar - 1.f) * li) * inv);
      r0 = r3; r1 = r4; r2 = r5;
    }
    if (lane == 0) TS(46);
    __syncwarp();
    bar_sync(7, 64);
    mbar_arrive(bars + 8 * B_CTAB);
  } else if (wid == 13) {
    ROLE(role)
    uint4 tv[3];
    const uint32_t e0 = ld_rlx(g_epoch);
    const uint32_t e1 = ldv16(p.ssmD + min(cch0 + 32 * lane, 639));
    const uint4 dv = ldv128((const uint4*)(p.dskip + 160 * dg) + min(lane, 19));
#pragma unroll
    for (int i = 0; i < 3; i++) tv[i] = ldv128((const uint4*)(p.shiftk + 640 * dg) + min(lane + 32 * i, 79));
    sts128(sb + DTAB_OFF + 16 * min(lane, 19), dv);
#pragma unroll
    for (int i = 0; i < 3; i++) sts128(sb + TAP_OFF + 16 * min(lane + 32 * i, 79), tv[i]);
    if (lane < 7) sts32(sb + EP_OFF + 4 * lane, lane < 5 ? e1 << 16 : (lane == 5 ? e0 : 0u));
    __syncwarp();
    bar_sync(9, 64);
    mbar_arrive(bars + 8 * B_CTAB);
    if (lane == 0) { mbar_arrive(bars + 8 * B_EP); TS(53); }
    if (has2) {
#pragma unroll 1
      for (int i = 0; i < 5; i++) {
        const int c = i == 2 ? 3 : (i == 3 ? 2 : i);
        mbar_wait(bars + 8 * (B_PD + c));
        if (lane == 0) bulk_s2g(g_kv + (dg * 32 + m2) * 20480 + c * 4096, sb + KS_OFF + c * KV_PIECE, 4096);
      }
      if (lane == 0) {
        asm volatile("cp.async.bulk.commit_group;" ::: "memory");
        asm volatile("cp.async.bulk.wait_group 0;" ::: "memory");
        mbar_arrive(bars + 8 * B_PREP2);
        fence_async_global();
      }
      __syncwarp();
      if (lane < 4) red_rel(&g_kvcnt[(dg * 4 + lane) * 32]);
      __syncwarp();
      if (lane == 0) { mbar_arrive(bars + 8 * B_PUB); TS(30); }
    }
  } else if (wid != 12) {
    if (elect_one()) {
      if (wid < 7) {
        const int b0 = wid < 4 ? 4 + 19 * wid : 85 + 21 * (wid - 4), cnt = wid < 4 ? 2 : 1;
#pragma unroll
        for (int i = 0; i < 21; i++) mbar_init(bars + 8 * (b0 + i), cnt);
#pragma unroll
        for (int i = 0; i < 6; i++) mbar_init(bars + 8 * (B_PD + 6 * wid + i), 1);
        if (wid == 0) { mbar_init(bars + 8 * (B_G1FULL + 10), 5); mbar_init(bars + 8 * (B_G1FULL + 11), 5); }
      } else {
#pragma unroll
        for (int i = 0; i < 12; i++) mbar_init(bars + 8 * (B_CVDONE + i), (i == 5 || i == 6) ? 160 : 128);
        mbar_init(bars + 8 * B_CTAB, 192); mbar_init(bars + 8 * B_PREP, 5); mbar_init(bars + 8 * B_PREP2, 1);
      }
      asm volatile("fence.mbarrier_init.release.cluster;" ::: "memory");
    }
    __syncwarp();
    bar_sync(5, 288);
    if (wid == 2) asm volatile("bar.arrive 8, 192;\nbar.arrive 6, 64;\nbar.arrive 9, 64;\nbar.arrive 7, 64;" ::: "memory");
    if (tid == 128) TS(0);
    if (wg == 1) { cv_table(); mbar_arrive(bars + 8 * B_CTAB); }
  }

  if (wid == 12) {
    ROLE(role)
    uint32_t dst = sb;
#pragma unroll 1
    for (int k = S1; k < 10; k++) {
      const uint32_t fb = bars + 8 * (B_G1FULL + k);
      mbar_wait(bars + 8 * (B_G1DONE + k - S1));
      if (elect_one()) {
        mbar_expect_tx(fb, 20480);
        tma4(dst + G1_XOFF, last ? &p.mXl : &p.mX, 64 * k, 0, 0, last ? 0 : 80 * T1, fb);
        mbar_expect_tx(fb, 16384);
        tma5(dst, &p.mB, 64 * k, 0, 0, 4 * side, 2 * GP, fb);
        if (has2 && k - S1 + KV0 < 5) kv_issue(p, k - S1 + KV0, m2, dg);
      }
      dst += G1_STAGE; if (k == 2 * S1 - 1) dst = sb;
    }
  } else if (wid == 15 && (role >> 16)) {
    ROLE(role)
    if (TPF >= 0) {
      mbar_wait(bars + 8 * (B_KV + TPF));
      if (elect_one()) {
#pragma unroll
        for (int c = 0; c < 5; c++) l2_prefetch(p.ssmk + (cch0 + 32 * c) * SEQ, 4096);
        if (CPF) { l2_prefetch(p.cre + (160 * dg + 5 * m2) * DM, 6400); l2_prefetch(p.cim + (160 * dg + 5 * m2) * DM, 6400); }
      }
    }
    mbar_wait(bars + 8 * B_PREP2);
    if (lane < 10) sts128(sb + CV_OFF + (lane >> 1) * CV_B + CV_K - 32 + 16 * (lane & 1), make_uint4(0, 0, 0, 0));
    fence_async_smem();
    __syncwarp();
    const unsigned tag = lds32(sb + EP_OFF + 20);
    if (TAPW) mbar_wait(bars + 8 * B_PUB);
    if (elect_one()) {
#pragma unroll 1
      for (int c = 0; c < 5; c++) {
        if (c == 0) asm volatile("prefetch.tensormap [%0];" ::"l"(&p.mU) : "memory");
        mbar_expect_tx(bars + 8 * (B_CVFULL + c), 4096 + 2 * CV_PL);
        if (c < TAPN) bulk_g2s(sb + CV_OFF + c * CV_B + CV_K, p.ssmk + (cch0 + 32 * c) * SEQ, 4096, bars + 8 * (B_CVFULL + c));
      }
    }
    mbar_wait(bars + 8 * B_PUB);
    cnt_poll(&g_kvcnt[(dg * 4 + (m2 >> 3)) * 32], 32 * tag);
    fence_async_global();
    if (elect_one()) {
      TS(28);
#pragma unroll
      for (int c = 0; c < 5; c++) {
        tma5(sb + CV_OFF + c * CV_B + CV_U, &p.mU, 0, -3, 2 * c, 16 * (m2 & 1) + (m2 >> 1), dg, bars + 8 * (B_CVFULL + c));
        if (c >= TAPN) bulk_g2s(sb + CV_OFF + c * CV_B + CV_K, p.ssmk + (cch0 + 32 * c) * SEQ, 4096, bars + 8 * (B_CVFULL + c));
      }
#pragma unroll
      for (int i = 0; i < 3; i++) asm volatile("prefetch.tensormap [%0];" ::"l"(&p.mCre + i) : "memory");
      TS(54);
    }
    __syncwarp();
  }
  {
    const int w = wid & 3;
    if (wg == 2 && !(role >> 16)) {
      float xa[2], xb[2];
      mbar_wait(bars + 8 * (B_G1FULL + 12));
      stat_table(role & 15, lds32(sb + EP_OFF + 20), 1, w, g_stats, g_stats, xa, xb);
      mbar_arrive(bars + 8 * (B_STAB + 1));
    }
#pragma unroll 1
    for (int l = 0; l < 2; l++) {
      if (wg < 2) {
        float acc[80];
#pragma unroll
        for (int i = 0; i < 80; i++) acc[i] = 0.f;
        ROLE(role)
        const int tid = tid_opaque(), r = (tid & 31) >> 2, q = tid & 3;
        const int ch = 128 * GP + 64 * wg + 32 * side + 8 * w + r;
        const uint32_t ca = sb + CTAB_OFF + (32 * wg + 8 * w + r) * 24;
        float2 lam = make_float2(0.f, 0.f), p8 = lam, p16 = lam, pL = lam, p2L = lam;
        fence_regs(acc);
        {
          const uint32_t alo0 = (l == 0 ? desc_lo(sb, 16) : desc_lo(sb + G2_WOFF, 16)) + wg * 512;
          const uint32_t blo0 = l == 0 ? desc_lo(sb + G1_XOFF, 16) : desc_lo(sb + X1_OFF, 128);
          const uint32_t bhi = l == 0 ? desc_hi(1024, 1) : desc_hi(1024, 0), xstep = l == 0 ? 2 : 16;
          const uint32_t astep = l == 0 ? G1_STAGE >> 4 : 1024, bstep = l == 0 ? G1_STAGE >> 4 : 1280, aend = alo0 + (S1 + l) * astep;
          uint32_t alo = alo0, blo = blo0;
          const uint32_t special = 8u | (l ? (1u << MK1) | (wg << (8 - STG_D)) : (1u << MK0) | (1u << PAUSE_K) | (wg << (9 - STG0)));
          uint32_t fb = bars + 8 * (B_G1FULL + 10 * l), nb = fb + 8;
          mbar_wait(fb);
          if (tid == 0) TS(1 + 8 * l);
#pragma unroll 1
          for (int k = 0; k < 10; k++) {
            uint32_t ok;
            wgmma_fence();
#pragma unroll
            for (int kk = 0; kk < 4; kk++) {
              wgmma_n160<0>(acc, alo + kk * 2, desc_hi(1024, 1), blo + kk * xstep, bhi);
              if (kk == 0) { ok = mbar_test(nb); asm volatile("add.u32 %0, %0, %1;" : "+r"(nb) : "r"(k < 8 ? 8 : 0)); }
              if (kk == STG_KK && k == 9 && tid == 0) mbar_arrive(bars + 8 * (B_STG + l));
            }
            wgmma_commit();
            alo += astep; blo += bstep;
            if (blo == desc_lo(sb + G_OFF, 128)) blo = desc_lo(sb, 128);
            if (alo == aend) { alo = alo0; blo = blo0; }
            wgmma_wait<1>();
            if (k > 0 && (tid & 127) == 0) mbar_arrive(fb + 8 * (B_G1DONE - B_G1FULL - 1));
            if (!ok) mbar_wait(fb + 8);
            if ((special >> k) & 1) {
            if (k == (l ? MK1 : MK0)) {
              mbar_wait(bars + 8 * (B_STAB + l));
              const float2 sB = lds64f(ca + 16);
              uint32_t a0 = q < 2 ? __float_as_uint(sB.x) : 0u, a1 = q < 2 ? __float_as_uint(sB.y) : 0u, a2 = 0u, a3 = 0u;
              asm volatile("" : "+r"(a0), "+r"(a1), "+r"(a2), "+r"(a3)::"memory");
              wgmma_fence();
              wgmma_rs_n160(acc, a0, a1, a2, a3, l ? desc_lo(sb + MX1_OFF, 0) : desc_lo(sb + MX0_OFF, 0));
              wgmma_commit();
            }
            if (wg == 1 && k == (l ? 8 - STG_D : 9 - STG0)) mbar_wait(bars + 8 * (B_STG + l));
            if (k == 3) {
              mbar_wait(bars + 8 * B_CTAB);
              lam = lds64f(ca);
              if (l == 0 && q < 2) rec_st(&g_E[(q * NT1 + T1) * DM + ch], 0.f, 0.f, lds32(sb + EP_OFF + 20) - 1);
              if (p.swap) lam.y = -lam.y;
              const float2 p2 = cmul(lam, lam), p4 = cmul(p2, p2);
              p8 = cmul(p4, p4); p16 = cmul(p8, p8);
              pL = cmul(p16, p16);
              if (!last) pL = cmul(pL, p8);
              p2L = cmul(pL, pL);
            }
            if (k == PAUSE_K && l == 0 && has2) mbar_wait(bars + 8 * B_PREP);
            }
            fb += 8;
          }
        }
        const unsigned tag = lds32(sb + EP_OFF + 20);
        wgmma_wait<0>();
        fence_regs(acc);
        if ((tid & 127) == 0) { mbar_arrive(bars + 8 * (B_G1DONE + 10 * l + 9)); TS(wg ? 17 + l : 2 + 8 * l); }
        float2 ec[3];
#pragma unroll
        for (int jj = 0; jj < 4; jj++)
#pragma unroll
          for (int y = 0; y < 3; y++) {
            if (y == 2 && (jj & 1)) continue;
            const int j = y == 2 ? 16 + jj : 8 * y + 2 * jj;
            const float4 st = lds128f(sb + STAB_OFF + q * 160 + j * 8);
            const float rs[4] = {st.x, st.y, st.z, st.w};
#pragma unroll
            for (int x = 0; x < 4; x++) {
              const int i = 4 * j + 4 * (x >> 1) + (x & 1);
              acc[i] *= rs[x]; acc[i + 2] *= rs[x];
              ec[y] = (jj == 0 && x == 0) ? make_float2(acc[i], acc[i + 2]) : cfma(lam, ec[y], make_float2(acc[i], acc[i + 2]));
            }
          }
        float2 e = cfma(p16, ec[0], ec[1]);
        if (!last) e = cfma(p8, e, ec[2]);
        {
          float2 v = make_float2(__shfl_up_sync(0xffffffffu, e.x, 1, 4), __shfl_up_sync(0xffffffffu, e.y, 1, 4));
          if (q >= 1) e = cfma(pL, v, e);
          v = make_float2(__shfl_up_sync(0xffffffffu, e.x, 2, 4), __shfl_up_sync(0xffffffffu, e.y, 2, 4));
          if (q >= 2) e = cfma(p2L, v, e);
        }
        if (!last && q == 3) rec_st(&g_E[(l * NT1 + T1) * DM + ch], e.x, e.y, tag);
        if (tid == 0) TS(3 + 8 * l);
        float2 ex = make_float2(__shfl_up_sync(0xffffffffu, e.x, 1, 4), __shfl_up_sync(0xffffffffu, e.y, 1, 4));
        if (q == 0) ex = make_float2(0.f, 0.f);
        const float2 coef = lds64f(ca + 8), lamc = make_float2(lam.x, p.swap ? lam.y : -lam.y);
        float m00 = coef.x, m01 = -coef.y, m10 = -coef.y, m11 = -coef.x;
        if (p.swap) { m00 = -coef.y; m01 = coef.x; m10 = -coef.x; m11 = -coef.y; }
        float2 pLq, p160q, p640;
        {
          const float2 p80 = last ? cmul(p2L, p16) : p2L, p160 = cmul(p80, p80), p320 = cmul(p160, p160), one = make_float2(1.f, 0.f);
          p640 = cmul(p320, p320);
          pLq = cmul((q & 1) ? pL : one, (q & 2) ? p2L : one);
          p160q = cmul((q & 1) ? p160 : one, (q & 2) ? p320 : one);
        }
        float2 c, ev[3];
        unsigned tg[3];
        const uint4* ep = &g_E[(l * NT1 + T1 - 1 - q) * DM + ch];
#pragma unroll
        for (int j = 0; j < 20; j++) {
          if (j == CPOLL) {
#pragma unroll
            for (int i = 0; i < 3; i++) {
              ev[i] = make_float2(0.f, 0.f); tg[i] = tag;
              if (T1 - 1 - q - 4 * i >= 0) tg[i] = rec_ld(ep - 4 * i * DM, ev[i].x, ev[i].y);
            }
          }
#pragma unroll
          for (int x = 0; x < 2; x++) {
            const float b0 = acc[4 * j + x], b1 = acc[4 * j + 2 + x];
            acc[4 * j + x] = fmaf(b0, m00, b1 * m01);
            acc[4 * j + 2 + x] = fmaf(b0, m10, b1 * m11);
          }
          if (j == CPOLL - 1 || j == 19) asm volatile("" : "+f"(acc[4 * j]), "+f"(acc[4 * j + 1]), "+f"(acc[4 * j + 2]), "+f"(acc[4 * j + 3])::"memory");
        }
        {
          uint32_t it = 0;
          while (__any_sync(0xffffffffu, tg[0] != tag || tg[1] != tag || tg[2] != tag)) {
#pragma unroll
            for (int i = 0; i < 3; i++)
              if (tg[i] != tag) tg[i] = rec_ld(ep - 4 * i * DM, ev[i].x, ev[i].y);
            trap_if(++it > SPIN_LIMIT);
          }
          c = cfma(p640, cfma(p640, ev[2], ev[1]), ev[0]);
          c = cmul(c, p160q);
          c.x += __shfl_xor_sync(0xffffffffu, c.x, 1); c.y += __shfl_xor_sync(0xffffffffu, c.y, 1);
          c.x += __shfl_xor_sync(0xffffffffu, c.x, 2); c.y += __shfl_xor_sync(0xffffffffu, c.y, 2);
        }
        if (tid == 0) TS(4 + 8 * l);
        if (HOLD1 && wg == 1 && l == 1 && has2) mbar_wait(bars + 8 * HOLD1);
        const uint32_t c0 = (uint32_t)clock(), tm = (tid & 7) == 4 * side + w;
        c = cfma(pLq, c, ex);
        float2 hh = make_float2(fmaf(c.x, m00, c.y * m01), fmaf(c.x, m10, c.y * m11));
        uint8_t* hb = g_h + (10 * wg + 2 * GP) * 8192 + (4 * side + w) * 1024 + (tid_opaque() & 31) * 4;
#pragma unroll
        for (int j4 = 0; j4 < 5; j4++) {
          if (PACE && j4 > 0 && wg == 1 && l == 1) { while (__any_sync(0xffffffffu, (uint32_t)clock() - c0 < PACE * j4)) {} }
          const int ng = 20 * T1 + 4 * j4;
          uint8_t* hp = hb + (size_t)(ng >> 3) * 163840 + (ng & 7) * 128;
#pragma unroll
          for (int jj = 0; jj < 4; jj++) {
            const int j = 4 * j4 + jj;
            const float2 h0 = cfma(lamc, hh, make_float2(acc[4 * j + 0], acc[4 * j + 2]));
            hh = cfma(lamc, h0, make_float2(acc[4 * j + 1], acc[4 * j + 3]));
            if (j4 < 4 || !last) {
              *(uint32_t*)(hp + jj * 128) = tag_word(pack_bf16(h0.x, hh.x), tm, 1 - l);
              *(uint32_t*)(hp + jj * 128 + 8192) = tag_word(pack_bf16(h0.y, hh.y), tm, 1 - l);
            }
          }
        }
        if (l == 0) mbar_arrive(bars + 8 * (B_HST + wg));
        if (tid == 0) TS(5 + 8 * l);
        if (tid == 128) TS(l ? 25 : 19);
        if (l == 0 && wid == 4) {
          mbar_wait(bars + 8 * B_HST);
          mbar_wait(bars + 8 * (B_HST + 1));
          if ((tid & 31) < 4) h_release(0, T1, tid & 3);
          __syncwarp();
          if (tid == 128) { mbar_arrive(bars + 8 * B_REL); TS(6); }
        }
      }
      if (l == 0) {
        ROLE(role)
        if (has2) {
          CvCtx cc;
          mbar_wait(bars + 8 * B_CTAB);
          cv_setup(cc);
          mbar_wait(bars + 8 * (B_G1DONE + 9));
#pragma unroll 1
          for (int c = (wg + 2) & 3; c < 5; c += 4) conv_channel(c, cc);
          if ((tid & 127) == 0) TS(wg == 2 ? 32 : (wg == 3 ? 50 : 7 + wg));
        }
      }
      if (wg >= 2) break;
      if (l == 0) {
        const int ln = tid_opaque() & 31, T1 = role & 15, n = T1 == NT1 - 1 ? 4 : 5;
        uint32_t ph = 0;
        mbar_wait(bars + 8 * ((role >> 16) ? B_UST : B_USEEN));
        __nanosleep(SPECU);
        if (tid == 0) TS(15);
        validate_block<true>(0, bars + 8 * (B_G1FULL + 10 + wg), sb + X1_OFF + wg * 20480 + w * n * 1024, g_u + (T1 * 10 + wg) * 20480 + w * n * 1024, n, w * n,
                             (ln & 7) * 128 + (ln >> 3) * 32, bars + 8 * (B_RETRY + 8 + wid), ph);
      }
    }
    if (wg < 2 && (role >> 16)) {
      const int ln = tid_opaque() & 31;
      const uint8_t* src = g_h + ((role >> 8) & 63) * 163840;
      uint32_t ph = 0;
      if (wg == 0) {
        mbar_wait(bars + 8 * (B_G1DONE + 19));
        if (SPEC0 + SPECW) __nanosleep(SPEC0 + SPECW * w);
        if (tid == 0) TS(23);
        if (!SPLITI && w < 3 && elect_one()) { mbar_expect_tx(bars + 8 * (B_XV + w + 4), G2_XB); }
      }
#pragma unroll 1
      for (int k = 10 * wg + w; k < 10 * wg + 10; k += 4) {
        if (k < (SPLITI ? S2 : 4) && elect_one()) {
          mbar_expect_tx(bars + 8 * (B_XV + k), G2_XB);
          bulk_g2s(sb + k * G2_XB, src + k * 8192, G2_XB, bars + 8 * (B_XV + k));
          if (!SPLITI && k < 3) bulk_g2s(sb + (k + 4) * G2_XB, src + (k + 4) * 8192, G2_XB, bars + 8 * (B_XV + k + 4));
        }
        validate_block<false>(bars + 8 * (B_XV + k), bars + 8 * (B_G2FULL + 20 + k), sb + (k % S2) * G2_XB, src + k * 8192, 8, 0,
                       (ln & 7) * 1028 + (ln >> 3) * 32, bars + 8 * (B_RETRY + wid), ph);
      }
    }
    if (wg == 3) {
    ROLE(role)
    const int pw = wid & 3, gpc = 2 * min(m2 >> 3, 3) + (dg >> 1);
    mbar_wait(bars + 8 * B_EP);
    const unsigned tag = lds32(sb + EP_OFF + 20);
    if (pw == 0) {
      if (elect_one()) {
#pragma unroll 1
        for (int l = 0; l < 2; l++) {
          uint32_t dst = sb;
          if (l == 1) {
            dst = sb + G2_WOFF;
#pragma unroll 1
            for (int k = 0; k < 10; k++) {
              mbar_wait(k > 4 ? bars + 8 * (B_G1DONE + 5 + k) : (has2 ? bars + 8 * (B_G2DONE + 14 + min(k, 3)) : bars + 8 * (B_G1DONE + 9)));
              mbar_expect_tx(bars + 8 * (B_G1FULL + 10 + k), 16384);
              tma5(dst, &p.mB, 64 * k, 0, 0, 4 * side, 2 * GP, bars + 8 * (B_G1FULL + 10 + k));
              dst += 16384; if (k == 4) dst = sb + G2_WOFF;
            }
          }
          if (has2) {
            const uint32_t fb2 = bars + 8 * (B_G2FULL + 20 * l), wb2 = bars + 8 * (B_G2DONE + 20 * l - S2);
            dst = sb + G2_WOFF + (WTAIL ? 4 * l * G2_WB : 0);
            int kc = 0;
#pragma unroll 1
            for (int k = 0; k < 20; k++) {
              mbar_wait(k >= S2 ? wb2 + 8 * k : bars + 8 * (l ? B_G1DONE + (WTAIL ? (k < 3 ? 15 + k : 13 + k) : 19) : (k == 5 ? B_XFREE : (k == 6 ? B_SFREE : B_REL))));
              mbar_expect_tx(fb2 + 8 * k, G2_WB);
              tma5(dst, &p.mCre + (k & 1), kc, 0, 0, 0, 10 * dg, fb2 + 8 * k);
              kc += (k & 1) << 7; if (k == 9) kc = 64;
              dst += G2_WB; if (dst == sb + G2_WOFF + S2 * G2_WB) dst = sb + G2_WOFF;
            }
          }
        }
      }
    } else if (pw == 1) {
#pragma unroll 1
      for (int l = 0; l < 2; l++) {
        if (l == 1) {
          mbar_wait(bars + 8 * (has2 ? B_G2DONE + 19 : B_G1DONE + 9));
          if (has2) mbar_wait(bars + 8 * B_UST);
          cnt_poll(&g_ucnt[gpc * 32], 128 * tag);
          fence_async_global();
          if (elect_one()) {
            TS(20);
            const int bytes = last ? 16384 : 20480;
            const uint8_t* src = g_u + T1 * 204800 + 40960;
            uint32_t dst = sb + X1_OFF + 40960;
            mbar_arrive(bars + 8 * B_USEEN);
#pragma unroll 1
            for (int k = 2; k < 10; k++) {
              if (k > 4) mbar_wait(bars + 8 * (B_G1DONE + 5 + k));
              mbar_expect_tx(bars + 8 * (B_G1FULL + 10 + k), bytes);
              bulk_g2s(dst, src, bytes, bars + 8 * (B_G1FULL + 10 + k));
              src += 20480; dst += 20480; if (dst == sb + G_OFF) dst = sb; if (k == 4) dst = sb + X1_OFF;
            }
          }
          __syncwarp();
        }
        if (has2) {
          if (l == 0) {
            mbar_wait(bars + 8 * B_REL);
            cnt_poll(&g_hcnt[gpc * 32], 40 * tag);
            fence_async_global();
          }
          if (elect_one()) {
            if (l == 0) TS(21);
            const uint32_t fb2 = bars + 8 * (l ? B_XV : B_G2FULL), wb2 = bars + 8 * (B_G2DONE + 20 * l - S2);
            const uint8_t* src = g_h + m2 * 163840 + l * S2 * 8192;
            uint32_t dst = sb;
#pragma unroll 1
            for (int k = l * S2; k < 20; k++) {
              if (k >= 5) mbar_wait(k >= S2 ? wb2 + 8 * k : bars + 8 * B_SFREE);
              mbar_expect_tx(fb2 + 8 * k, G2_XB);
              bulk_g2s(dst, src, G2_XB, fb2 + 8 * k);
              src += 8192; dst += G2_XB; if (dst == sb + S2 * G2_XB) dst = sb;
            }
          }
          __syncwarp();
        }
      }
    } else if (pw == 2) {
#pragma unroll 1
      for (int l = 0; l < 2; l++) {
        if (l == 1) {
          if (has2) {
            mbar_wait(bars + 8 * B_UST);
            if (lane < 8) red_rel(&g_ucnt[lane * 32]);
            __syncwarp();
            if (lane == 0) TS(38);
          }
          float xa[2], xb[2];
          mbar_wait(bars + 8 * (B_G1FULL + 12));
          stat_table(T1, tag, 1, 4, g_stats, g_stats, xa, xb);
          mbar_arrive(bars + 8 * (B_STAB + 1));
        }
        if (l == 0 && has2) {
          const int x = 4 * m2 + dg, T = x / 10;
          uint4* z = (uint4*)(g_u + T * 204800 + (x - 10 * T) * 4096 + (x >= 124 ? 4096 : 0)) + lane;
#pragma unroll
          for (int i = 0; i < 8; i++) z[32 * i] = make_uint4(0u, 0u, 0u, 0u);
          __syncwarp();
        }
        if (l == 0 && has2 && elect_one()) {
#pragma unroll 1
          for (int i = 0; i < 5; i++) {
            const int c = i < 3 ? i : 7 - i;
            mbar_wait(bars + 8 * (B_CVDONE + c));
            bulk_s2g(g_G + (cch0 + 32 * c) * 4096, cv_stage(c), 4096);
          }
          asm volatile("cp.async.bulk.commit_group;" ::: "memory");
          asm volatile("cp.async.bulk.wait_group.read 0;" ::: "memory");
          mbar_arrive(bars + 8 * B_SFREE);
          asm volatile("cp.async.bulk.wait_group 0;" ::: "memory");
          TS(48);
          fence_async_global();
          asm volatile("fence.acq_rel.gpu;" ::: "memory");
#pragma unroll
          for (int i = 0; i < 4; i++) red_rlx(&g_gcnt[(dg * 4 + i) * 32]);
          TS(49);
          mbar_arrive(bars + 8 * (B_GO + 1));
        }
        __syncwarp();
      }
    } else if (has2) {
      mbar_wait(bars + 8 * B_REL);
      if (!CPF && elect_one()) {
        l2_prefetch(p.cre + (160 * dg + 5 * m2) * DM, 6400); l2_prefetch(p.cim + (160 * dg + 5 * m2) * DM, 6400);
      }
      mbar_wait(bars + 8 * (B_GO + 1));
      flag_poll(&g_gcnt[(dg * 4 + (m2 >> 3)) * 32], 32 * tag);
      fence_async_global();
      if (elect_one()) {
        TS(29);
        mbar_expect_tx(bars + 8 * B_GFULL, 20480);
        tma5(sb + G_OFF, &p.mG, 64 * m2, 0, 0, 0, 10 * dg, bars + 8 * B_GFULL);
      }
    }
    } else if (wg == 2 && (role >> 16)) {
      float acc[80];
      float off[2] = {mean0[0], mean0[1]};
      const unsigned tag = lds32(sb + EP_OFF + 20);
      dskip_init<true>(acc, mean0, rstd0);
      mbar_arrive(bars + 8 * B_XFREE);
      mbar_wait(bars + 8 * (B_CVDONE + 2));
      mbar_wait(bars + 8 * (B_CVDONE + 3));
#pragma unroll 1
      for (int step = 1; step < 4; step++) {
        const int l = step >> 1;
        if (step != 2) {
          uint32_t alo = desc_lo(sb, 1024), blo = desc_lo(sb + G2_WOFF, 16) + (WTAIL ? l * (G2_WB >> 2) : 0);
          uint32_t fb = bars + 8 * (B_G2FULL + 20 * l);
          fence_regs(acc);
          mbar_wait(fb);
          if (tid == 256) TS(33 + 6 * l);
#pragma unroll 1
          for (int k = 0; k < 20; k++) {
            if (l == TSL && (k & 3) == 3 && tid == 256) TS(56 + (k >> 2));
            uint32_t ok; const uint32_t nb = k < 19 ? fb + 8 : fb;
            wgmma_fence();
#pragma unroll
            for (int kk = 0; kk < 4; kk++) {
              wgmma_n160<1>(acc, alo + kk * 128, desc_hi(128, 0), blo + kk * 2, desc_hi(1024, 1));
              if (kk == 0) ok = mbar_test(nb);
            }
            wgmma_commit();
            alo += G2_XB >> 4; blo += G2_WB >> 4;
            if (alo == desc_lo(sb + S2 * G2_XB, 1024)) alo = desc_lo(sb, 1024);
            if (blo == desc_lo(sb + G_OFF, 16)) blo = desc_lo(sb + G2_WOFF, 16);
            wgmma_wait<1>();
            if (k > 0 && tid == 256) mbar_arrive(fb + 8 * (B_G2DONE - B_G2FULL - 1));
            if (!ok) mbar_wait(nb);
            fb += 8;
          }
          mbar_wait(bars + 8 * B_GFULL);
          wgmma_wait<0>();
          fence_regs(acc);
          if (tid == 256) TS(34 + 6 * l);
          if (tid == 256) mbar_arrive(bars + 8 * (B_G2DONE + 20 * l + 19));
        }
        ROLE(role)
        const int tq = tid_opaque() & 31, n0 = 64 * m2 + 16 * w + (tq >> 2);
        stats_publish<false>(step, n0, dg, tag, acc);
        uint32_t gf[10][4];
        uint32_t ga = sb + G_OFF + (8 * (tq >> 4) + (tq & 7)) * 128 + (((2 * w + ((tq >> 3) & 1)) ^ ((2 * m2) & 6) ^ (tq & 7)) << 4), gstep = 2048;
        if (step == 2) { ga = sb + DX_OFF + (8 * (tq >> 4) + (tq & 7)) * 16; gstep = 256; }
#pragma unroll
        for (int J = 0; J < 2; J++) ldsm4t(gf[J], ga + J * gstep);
        if (tid == 256) TS(35 + 6 * l);
        uint8_t* dst[2][2];
#pragma unroll
        for (int h = 0; h < 2; h++) {
          if (l == 0) {
            const int ng = 8 * m2 + 2 * w + h, T = ng / 20;
            uint8_t* ub = g_u + (T * 204800 + (ng - 20 * T) * 1024 + (tq & 2) * 64 + (tq & 28) * 4 + (tq & 1) * 8 + (5 * dg >> 1) * 20480);
            dst[h][1] = ub + ((dg & 1) ? 20480 - 512 : 0);
            dst[h][0] = ub + (dg & 1) * 512;
          } else {
            dst[h][0] = dst[h][1] = (uint8_t*)(p.out + (n_to_t(n0 + 8 * h) * DM + 160 * dg + 4 * (tq & 3)));
          }
        }
        const uint32_t tm = dg == 0 && ((tq >> 1) & 2) + (tq & 1) == ((w + 2 * ((8 * m2 + 2 * w) / 20)) & 3);
        float mean[2], rstd[2];
        stats_get(step, n0, tag, mean, rstd);
        if (tid == 256) TS(36 + 6 * l);
        off[0] += mean[0]; off[1] += mean[1];
        const float ov[2] = {step == 3 ? off[0] : 0.f, step == 3 ? off[1] : 0.f};
#pragma unroll
        for (int J = 0; J < 10; J++) {
          if (J + 2 < 10) ldsm4t(gf[J + 2 < 10 ? J + 2 : 0], ga + (J + 2) * gstep);
#pragma unroll
          for (int x = 0; x < 8; x++) {
            const int h = (x >> 1) & 1;
            const uint32_t gwd = gf[J][x >> 1];
            const float t = fmaf(rstd[h], (x & 1) ? bf_hi(gwd) : bf_lo(gwd), 1.f);
            acc[8 * J + x] = fmaf(acc[8 * J + x], t, fmaf(-mean[h], t, ov[h]));
          }
#pragma unroll
          for (int h = 0; h < 2; h++) {
            if (step == 1)
              *(uint2*)(dst[h][(J >> 1) & 1] + (J >> 2) * 20480 + (J & 3) * 256) =
                  make_uint2(pack_bf16(acc[8 * J + 2 * h], acc[8 * J + 2 * h + 1]) | (J < 8 ? tm : 0u), pack_bf16(acc[8 * J + 4 + 2 * h], acc[8 * J + 5 + 2 * h]));
            if (step == 3)
              *(float4*)(dst[h][0] + 64 * J) = make_float4(acc[8 * J + 2 * h], acc[8 * J + 2 * h + 1], acc[8 * J + 4 + 2 * h], acc[8 * J + 5 + 2 * h]);
          }
          __syncwarp();
        }
        if (step == 1) {
          mbar_arrive(bars + 8 * B_UST);
          if (tid == 256) TS(37);
          for (int n = tid & 127; n < 160; n += 128) {
            const int d = 16 * (n >> 4) + 4 * ((n >> 1) & 3) + 2 * ((n >> 3) & 1) + (n & 1);
            const uint32_t dw = lds32(sb + DTAB_OFF + 2 * (d & ~1)), dd = __byte_perm(dw, dw, (d & 1) ? 0x3232 : 0x1010);
            sts128(sb + DX_OFF + 16 * n, make_uint4(dd, dd, dd, dd));
          }
          bar_sync(3, 128);
        } else if (step == 2) {
          if (tid == 256) TS(22);
          mbar_wait(bars + 8 * (B_G1FULL + 12));
          float xa[2], xb[2];
          stat_table(T1, tag, 1, w, g_stats, g_stats, xa, xb);
          mbar_arrive(bars + 8 * (B_STAB + 1));
          if (tid == 256) TS(27);
        } else {
          if (tid == 256) {
            TS(43);
            if (m2 == 31 && dg == 3) asm volatile("st.relaxed.gpu.global.u32 [%0], %1;" ::"l"(g_epoch), "r"(tag + 1) : "memory");
          }
        }
      }
    }
  }
}

typedef CUresult (*EncFn)(CUtensorMap*, CUtensorMapDataType, cuuint32_t, void*, const cuuint64_t*, const cuuint64_t*,
                          const cuuint32_t*, const cuuint32_t*, CUtensorMapInterleave, CUtensorMapSwizzle,
                          CUtensorMapL2promotion, CUtensorMapFloatOOBfill);

void encode(EncFn fn, CUtensorMap* m, const void* ptr, int rank, const cuuint64_t* dims, const cuuint64_t* strides, const cuuint32_t* box,
            CUtensorMapSwizzle swz = CU_TENSOR_MAP_SWIZZLE_128B, int prom = 2) {
  cuuint32_t es[5] = {1, 1, 1, 1, 1};
  fn(m, CU_TENSOR_MAP_DATA_TYPE_BFLOAT16, rank, (void*)ptr, dims, strides, box, es, CU_TENSOR_MAP_INTERLEAVE_NONE,
     swz, (CUtensorMapL2promotion)prom, CU_TENSOR_MAP_FLOAT_OOB_FILL_NONE);
}

}

extern "C" void kernel_launch(void* const* d_in, const int* in_sizes, int n_in, void* d_out, int out_size) {
  (void)in_sizes; (void)n_in; (void)out_size;
  Params p;
  typedef const __nv_bfloat16* BP;
  p.x = (BP)d_in[0]; p.lre = (BP)d_in[1]; p.lim = (BP)d_in[2]; p.bre = (BP)d_in[3]; p.bim = (BP)d_in[4];
  p.cre = (BP)d_in[5]; p.cim = (BP)d_in[6]; p.logdt = (BP)d_in[7]; p.dskip = (BP)d_in[8];
  p.k = (BP)d_in[10]; p.v = (BP)d_in[11]; p.shiftk = (BP)d_in[12]; p.ssmk = (BP)d_in[13]; p.ssmD = (BP)d_in[14];
  p.out = (float*)d_out;
  for (int sm = 0; sm < 132; sm++) {
    const int tpc = sm >> 1, side = sm & 1;
    int gpc, gi;
    if (tpc < 32) { gpc = tpc & 7; gi = tpc >> 3; }
    else if (tpc < 60) { gpc = 1 + (tpc - 32) % 7; gi = 4 + (tpc - 32) / 7; }
    else if (tpc < 62) { gpc = tpc - 54; gi = 8; }
    else { gpc = 0; gi = tpc - 58; }
    const int pos = 8 * gpc + gi + (gpc == 7 ? 1 : 0);
    int T1, GP;
    if (pos < 52) { const int hh = pos / 26, x = pos - 26 * hh; T1 = x >> 1; GP = 2 * hh + (x & 1); }
    else { T1 = pos - 52; GP = 4; }
    const int m2 = 8 * (gpc >> 1) + gi, dg = 2 * (gpc & 1) + side;
    p.role[sm] = pos == 65 ? -1 : (T1 | (GP << 4) | (side << 7) | (m2 << 8) | (dg << 14) | ((gi < 8) << 16));
  }
  void* fnp = nullptr;
  cudaDriverEntryPointQueryResult qr;
  cudaGetDriverEntryPoint("cuTensorMapEncodeTiled", &fnp, cudaEnableDefault, &qr);
  EncFn fn = (EncFn)fnp;
  void* gG = nullptr;
  cudaGetSymbolAddress(&gG, g_G);
  void* gKV = nullptr;
  cudaGetSymbolAddress(&gKV, g_kv);
  {
    cuuint64_t dims[5] = {32, 32, 10, 32, 4}, st[4] = {20480, 2048, 64, 655360}; cuuint32_t box[5] = {32, 35, 2, 1, 1};
    encode(fn, &p.mU, gKV, 5, dims, st, box, CU_TENSOR_MAP_SWIZZLE_NONE, 1);
  }
  const cuuint64_t RB = DM * 2;
  {
    p.swap = p.bim < p.bre;
    const char* lo = (const char*)(p.swap ? p.bim : p.bre); const char* hi = (const char*)(p.swap ? p.bre : p.bim);
    cuuint64_t dims[5] = {640, 8, 2, 8, 10}, st[4] = {RB, (cuuint64_t)(hi - lo), 8 * RB, 64 * RB}; cuuint32_t box[5] = {64, 8, 2, 4, 2};
    encode(fn, &p.mB, lo, 5, dims, st, box);
  }
  {
    cuuint64_t dims[5] = {640, 2, 4, 2, 40}, st[4] = {RB, 4 * RB, 2 * RB, 16 * RB}; cuuint32_t box[5] = {64, 2, 4, 2, 10};
    encode(fn, &p.mCre, p.cre, 5, dims, st, box); encode(fn, &p.mCim, p.cim, 5, dims, st, box);
    cuuint64_t dimg[5] = {2048, 2, 4, 2, 40}, stg[4] = {4096, 4 * 4096, 2 * 4096, 16 * 4096};
    encode(fn, &p.mG, gG, 5, dimg, stg, box);
  }
  {
    cuuint64_t dims[4] = {640, 2, 4, 900}, st[3] = {RB, 40 * RB, 2 * RB}; cuuint32_t box[4] = {64, 2, 4, 20};
    encode(fn, &p.mX, p.x, 4, dims, st, box);
    cuuint64_t diml[4] = {640, 2, 4, 16}, stl[3] = {RB, 32 * RB, 2 * RB};
    encode(fn, &p.mXl, p.x + (size_t)1920 * DM, 4, diml, stl, box);
    cuuint32_t boxt[4] = {160, 2, 4, 4};
    encode(fn, &p.mXt, p.x, 4, dims, st, boxt, CU_TENSOR_MAP_SWIZZLE_NONE);
    encode(fn, &p.mXtl, p.x + (size_t)1920 * DM, 4, diml, stl, boxt, CU_TENSOR_MAP_SWIZZLE_NONE);
    cuuint64_t dk[3] = {640, 2000, 4}, sk[2] = {RB, 16 * RB}; cuuint32_t bk[3] = {32, 19, 4}, bv[3] = {32, 17, 4};
    encode(fn, &p.mK, p.k, 3, dk, sk, bk, CU_TENSOR_MAP_SWIZZLE_NONE);
    encode(fn, &p.mV, p.v, 3, dk, sk, bv, CU_TENSOR_MAP_SWIZZLE_NONE);
  }
  cudaFuncSetAttribute(fused_kernel, cudaFuncAttributeMaxDynamicSharedMemorySize, SMEM_BYTES);
  cudaLaunchConfig_t cfg = {};
  cfg.gridDim = dim3(132); cfg.blockDim = dim3(512); cfg.dynamicSmemBytes = SMEM_BYTES; cfg.stream = cudaStreamPerThread;
  cudaLaunchKernelEx(&cfg, fused_kernel, p);
}
```

```cpp
#include <cuda_runtime.h>
#include <cuda.h>
#include <cuda_bf16.h>
#include <stdint.h>

namespace {

constexpr int SEQ = 2048, DM = 640;
constexpr int NT1 = 13;
#define EXP 0
#define WPF1 3
#define WPF2 7
#define CPOLL 10
#define KV0 1
#define TAPLATE 1
#define STG_D 3
#define STG_KK 1
#define HOLD1 0
#define SPEC0 100
#define WREL 0
#define UREL 1
#define TSL 1
#define STG0 2
#define WTAIL 1
#define PFD 1
#define TAPW 0
#define TPF 4
#define CPF 0
#define MK0 7
#define MK1 4
#define PACE 350
#define TAPN 2
#define SPLITI 1
#define SPECW 60
#define PAUSE_K 5
constexpr uint32_t SPIN_LIMIT = 1u << 22;

__device__ __align__(1024) uint8_t g_h[32 * 20 * 8192];
__device__ __align__(1024) uint8_t g_u[NT1 * 10 * 20480];
__device__ __align__(1024) uint8_t g_kv[DM * 4096];
__device__ __align__(1024) uint8_t g_G[DM * 4096];
__device__ __align__(128) uint4 g_E[2 * NT1 * DM];
__device__ __align__(128) uint4 g_stats[4 * 4 * SEQ];
__device__ __align__(128) uint4 g_sB[DM * 2];
__device__ __align__(128) unsigned g_hcnt[8 * 32];
__device__ __align__(128) unsigned g_ucnt[8 * 32];
__device__ __align__(128) unsigned g_kvcnt[16 * 32];
__device__ __align__(128) unsigned g_gcnt[16 * 32];
__device__ __align__(128) unsigned g_epoch[32] = {1};
#define TS(i) do {} while (0)

struct Params {
  CUtensorMap mX, mB, mXl, mK, mV, mXt, mXtl, mCre, mCim, mG, mU;
  const __nv_bfloat16 *x, *lre, *lim, *bre, *bim, *cre, *cim, *logdt, *dskip, *k, *v, *shiftk, *ssmk, *ssmD;
  float* out;
  int swap;
  int role[132];
};

constexpr uint32_t sb = 1024;
constexpr uint32_t G1_STAGE = 36864, G1_XOFF = 16384;
constexpr int S1 = 4;
constexpr uint32_t XT_OFF = 159744, KS_OFF = 180224, KV_PIECE = 9216;
constexpr uint32_t G2_XB = 8192, G2_WB = 20480, G2_WOFF = 57344, G_OFF = 200704;
constexpr uint32_t X1_OFF = 139264;
constexpr int S2 = 7;
constexpr uint32_t CV_OFF = KS_OFF, CV_K = 128, CV_PL = 2240, CV_U = CV_K + 4096, CV_B = KV_PIECE;
constexpr uint32_t MISC = 226304;
constexpr uint32_t BAR_OFF = MISC;
constexpr int B_G1FULL = 0, B_G1DONE = 20, B_G2FULL = 40,
              B_G2DONE = 85, B_GFULL = 125, B_EP = 126, B_CVFULL = 129  , B_STG = 134  , B_REL = 136  , B_SFREE = 138,
              B_GO = 139  , B_PUB = 147,
              B_CVDONE = 148  , B_STAB = 153  , B_XFREE = 155, B_HST = 156  , B_UST = 158,
              B_CTAB = 160, B_PREP = 161, B_XT = 162, B_KV = 163  , B_PREP2 = 84, B_PD = 168  ,
              B_XV = 173  , B_RETRY = 193  ;
constexpr uint32_t bars = sb + BAR_OFF;
constexpr uint32_t STAB_OFF = MISC + 1648;
constexpr uint32_t CTAB_OFF = STAB_OFF + 640;
constexpr uint32_t DTAB_OFF = CTAB_OFF + 1536;
constexpr uint32_t EP_OFF = DTAB_OFF + 320;
constexpr uint32_t SO_OFF = EP_OFF + 32;
constexpr uint32_t TAP_OFF = 147456;
constexpr uint32_t MX0_OFF = TAP_OFF + 1280, MX1_OFF = G_OFF + 20480;
constexpr uint32_t DX_OFF = MX1_OFF + 2560;
constexpr uint32_t SMEM_BYTES = 232448;
static_assert(SO_OFF + 1536 <= SMEM_BYTES, "smem");

__device__ __forceinline__ void trap_if(bool c) { asm volatile("{\n.reg .pred p;\nsetp.ne.u32 p, %0, 0;\n@p trap;\n}\n" ::"r"((uint32_t)c)); }
__device__ __forceinline__ uint32_t smem_u32(const void* p) { return (uint32_t)__cvta_generic_to_shared(p); }
__device__ __forceinline__ void mbar_init(uint32_t bar, int cnt) { asm volatile("mbarrier.init.shared::cta.b64 [%0], %1;" ::"r"(bar), "r"(cnt) : "memory"); }
__device__ __forceinline__ void mbar_expect_tx(uint32_t bar, int bytes) { asm volatile("mbarrier.arrive.expect_tx.shared::cta.b64 _, [%0], %1;" ::"r"(bar), "r"(bytes) : "memory"); }
__device__ __forceinline__ void mbar_arrive(uint32_t bar) { asm volatile("mbarrier.arrive.shared::cta.b64 _, [%0];" ::"r"(bar) : "memory"); }
__device__ __forceinline__ bool elect_one() {
  uint32_t e; asm volatile("{\n.reg .pred P;\nelect.sync _|P, 0xffffffff;\nselp.u32 %0, 1, 0, P;\n}\n" : "=r"(e)); return e != 0;
}
__device__ __forceinline__ void mbar_wait(uint32_t bar) {
  asm volatile(
      "{\n.reg .pred p;\n.reg .u32 c;\nmov.u32 c, 0;\n"
      "W_%=:\nmbarrier.try_wait.parity.shared::cta.b64 p, [%0], 0;\n@p bra D_%=;\n"
      "add.u32 c, c, 1;\nsetp.lt.u32 p, c, %1;\n@p bra W_%=;\ntrap;\nD_%=:\n}\n" ::"r"(bar), "n"(SPIN_LIMIT) : "memory");
}
__device__ __forceinline__ uint32_t mbar_test(uint32_t bar) {
  uint32_t ok;
  asm volatile("{\n.reg .pred p;\nmbarrier.test_wait.parity.shared::cta.b64 p, [%1], 0;\nselp.u32 %0, 1, 0, p;\n}\n" : "=r"(ok) : "r"(bar) : "memory");
  return ok;
}
__device__ __forceinline__ void tma3(uint32_t dst, const CUtensorMap* m, int c0, int c1, int c2, uint32_t bar) {
  asm volatile("cp.async.bulk.tensor.3d.shared::cluster.global.mbarrier::complete_tx::bytes [%0], [%1, {%3,%4,%5}], [%2];"
               ::"r"(dst), "l"(m), "r"(bar), "r"(c0), "r"(c1), "r"(c2) : "memory");
}
__device__ __forceinline__ void tma4(uint32_t dst, const CUtensorMap* m, int c0, int c1, int c2, int c3, uint32_t bar) {
  asm volatile("cp.async.bulk.tensor.4d.shared::cluster.global.mbarrier::complete_tx::bytes [%0], [%1, {%3,%4,%5,%6}], [%2];"
               ::"r"(dst), "l"(m), "r"(bar), "r"(c0), "r"(c1), "r"(c2), "r"(c3) : "memory");
}
__device__ __forceinline__ void tma5(uint32_t dst, const CUtensorMap* m, int c0, int c1, int c2, int c3, int c4, uint32_t bar) {
  asm volatile("cp.async.bulk.tensor.5d.shared::cluster.global.mbarrier::complete_tx::bytes [%0], [%1, {%3,%4,%5,%6,%7}], [%2];"
               ::"r"(dst), "l"(m), "r"(bar), "r"(c0), "r"(c1), "r"(c2), "r"(c3), "r"(c4) : "memory");
}
__device__ __forceinline__ void bulk_g2s(uint32_t dst, const void* src, int bytes, uint32_t bar) {
  asm volatile("cp.async.bulk.shared::cluster.global.mbarrier::complete_tx::bytes [%0], [%1], %2, [%3];"
               ::"r"(dst), "l"(src), "r"(bytes), "r"(bar) : "memory");
}
__device__ __forceinline__ void bulk_s2g(void* dst, uint32_t src, int bytes) {
  asm volatile("cp.async.bulk.global.shared::cta.bulk_group [%0], [%1], %2;" ::"l"(dst), "r"(src), "r"(bytes) : "memory");
}
__device__ __forceinline__ void l2_prefetch(const void* src, int bytes) {
  asm volatile("cp.async.bulk.prefetch.L2.global [%0], %1;" ::"l"(src), "r"(bytes) : "memory");
}
__device__ __forceinline__ void wgmma_fence() { asm volatile("wgmma.fence.sync.aligned;" ::: "memory"); }
__device__ __forceinline__ void wgmma_commit() { asm volatile("wgmma.commit_group.sync.aligned;" ::: "memory"); }
template <int N> __device__ __forceinline__ void wgmma_wait() { asm volatile("wgmma.wait_group.sync.aligned %0;" ::"n"(N) : "memory"); }
__host__ __device__ constexpr uint32_t desc_lo(uint32_t addr, uint32_t lbo) { return ((addr & 0x3FFFF) >> 4) | ((lbo >> 4) << 16); }
__host__ __device__ constexpr uint32_t desc_hi(uint32_t sbo, uint32_t swz) { return (sbo >> 4) | (swz << 30); }
__device__ __forceinline__ void bar_sync(int id, int n) { asm volatile("bar.sync %0, %1;" ::"r"(id), "r"(n) : "memory"); }
__device__ __forceinline__ uint32_t lds32(uint32_t a) { uint32_t v; asm volatile("ld.shared.u32 %0, [%1];" : "=r"(v) : "r"(a) : "memory"); return v; }
__device__ __forceinline__ float2 lds64f(uint32_t a) { float2 v; asm volatile("ld.shared.v2.f32 {%0,%1}, [%2];" : "=f"(v.x), "=f"(v.y) : "r"(a) : "memory"); return v; }
__device__ __forceinline__ float4 lds128f(uint32_t a) { float4 v; asm volatile("ld.shared.v4.f32 {%0,%1,%2,%3}, [%4];" : "=f"(v.x), "=f"(v.y), "=f"(v.z), "=f"(v.w) : "r"(a) : "memory"); return v; }
__device__ __forceinline__ void ldsm4t(uint32_t (&r)[4], uint32_t a) {
  asm volatile("ldmatrix.sync.aligned.m8n8.x4.trans.shared.b16 {%0,%1,%2,%3}, [%4];" : "=r"(r[0]), "=r"(r[1]), "=r"(r[2]), "=r"(r[3]) : "r"(a) : "memory");
}
__device__ __forceinline__ uint4 ldv128(const void* a) { uint4 v; asm volatile("ld.global.nc.v4.u32 {%0,%1,%2,%3}, [%4];" : "=r"(v.x), "=r"(v.y), "=r"(v.z), "=r"(v.w) : "l"(a) : "memory"); return v; }
__device__ __forceinline__ uint2 ldv64(const void* a) { uint2 v; asm volatile("ld.global.nc.v2.u32 {%0,%1}, [%2];" : "=r"(v.x), "=r"(v.y) : "l"(a) : "memory"); return v; }
__device__ __forceinline__ uint32_t ldv16(const void* a) { uint32_t v; asm volatile("ld.global.nc.u16 %0, [%1];" : "=r"(v) : "l"(a) : "memory"); return v; }
__device__ __forceinline__ void sts128(uint32_t a, uint4 v) { asm volatile("st.shared.v4.u32 [%0], {%1,%2,%3,%4};" ::"r"(a), "r"(v.x), "r"(v.y), "r"(v.z), "r"(v.w) : "memory"); }
__device__ __forceinline__ void sts32(uint32_t a, uint32_t v) { asm volatile("st.shared.u32 [%0], %1;" ::"r"(a), "r"(v) : "memory"); }
__device__ __forceinline__ void sts64f(uint32_t a, float x, float y) { asm volatile("st.shared.v2.f32 [%0], {%1,%2};" ::"r"(a), "f"(x), "f"(y) : "memory"); }
__device__ __forceinline__ void red_rlx(unsigned* p) { asm volatile("red.relaxed.gpu.global.add.u32 [%0], 1;" ::"l"(p) : "memory"); }
__device__ __forceinline__ void red_rel(unsigned* p) { asm volatile("red.release.gpu.global.add.u32 [%0], 1;" ::"l"(p) : "memory"); }
__device__ __forceinline__ void fence_async_global() { asm volatile("fence.proxy.async.global;" ::: "memory"); }
__device__ __forceinline__ void fence_async_smem() { asm volatile("fence.proxy.async.shared::cta;" ::: "memory"); }
__device__ __forceinline__ void rec_st(uint4* p, float a, float b, unsigned tag) {
  asm volatile("{\n.reg .b128 t;\n.reg .b64 lo, hi;\nmov.b64 lo, {%1,%2};\nmov.b64 hi, {%3,%3};\nmov.b128 t, {lo,hi};\n"
               "st.relaxed.gpu.global.b128 [%0], t;\n}\n" ::"l"(p), "r"(__float_as_uint(a)), "r"(__float_as_uint(b)), "r"(tag) : "memory");
}
__device__ __forceinline__ unsigned rec_ld(const uint4* p, float& a, float& b) {
  unsigned x, y, t;
  asm volatile("{\n.reg .b128 t;\n.reg .b64 lo, hi;\n.reg .b32 u;\nld.relaxed.gpu.global.b128 t, [%3];\nmov.b128 {lo,hi}, t;\n"
               "mov.b64 {%0,%1}, lo;\nmov.b64 {%2,u}, hi;\n}\n" : "=r"(x), "=r"(y), "=r"(t) : "l"(p) : "memory");
  a = __uint_as_float(x); b = __uint_as_float(y);
  return t;
}
__device__ __forceinline__ unsigned ld_rlx(const unsigned* p) { unsigned v; asm volatile("ld.relaxed.gpu.global.u32 %0, [%1];" : "=r"(v) : "l"(p) : "memory"); return v; }
__device__ __forceinline__ void flag_poll(const unsigned* p, unsigned target) {
  uint32_t it = 0;
  while (!__all_sync(0xffffffffu, (int)(ld_rlx(p) - target) >= 0)) { trap_if(++it > SPIN_LIMIT); }
  asm volatile("fence.acquire.gpu;" ::: "memory");
}
__device__ __forceinline__ void cnt_poll(const unsigned* p, unsigned target) {
  unsigned a = ld_rlx(p); __nanosleep(100);
  unsigned b = ld_rlx(p); __nanosleep(100);
  unsigned c = ld_rlx(p);
  uint32_t it = 0;
  while (true) {
    if (__all_sync(0xffffffffu, (int)(a - target) >= 0)) break;
    a = ld_rlx(p);
    if (__all_sync(0xffffffffu, (int)(b - target) >= 0)) break;
    b = ld_rlx(p);
    if (__all_sync(0xffffffffu, (int)(c - target) >= 0)) break;
    c = ld_rlx(p);
    trap_if(++it > SPIN_LIMIT);
  }
  asm volatile("fence.acquire.gpu;" ::: "memory");
}
__device__ __forceinline__ void validate_block(uint32_t bar, uint32_t full, uint32_t dst, const uint8_t* src, uint32_t woff, uint32_t rb, uint32_t& ph) {
  uint32_t it = 0, par = 0;
  while (true) {
    uint32_t ok, spins = 0;
    do {
      asm volatile("{\n.reg .pred p;\nmbarrier.try_wait.parity.shared::cta.b64 p, [%1], %2;\nselp.u32 %0, 1, 0, p;\n}\n" : "=r"(ok) : "r"(bar), "r"(par) : "memory");
      trap_if(++spins > SPIN_LIMIT);
    } while (!__all_sync(0xffffffffu, ok));
    uint32_t bad = 0;
#pragma unroll
    for (int i = 0; i < 8; i++) bad |= lds32(dst + woff + 128 * i);
    if (!__any_sync(0xffffffffu, bad & 1)) break;
    if (elect_one()) { mbar_expect_tx(rb, 8192); bulk_g2s(dst, src, 8192, rb); }
    bar = rb; par = ph; ph ^= 1;
    trap_if(++it > 100000);
  }
  if ((threadIdx.x & 31) == 0) mbar_arrive(full);
}
__device__ __forceinline__ uint32_t tag_word(uint32_t v, uint32_t m, uint32_t par) {
  uint32_t r; asm("lop3.b32 %0, %1, %2, %3, 0xb8;" : "=r"(r) : "r"(v), "r"(m), "r"(par)); return r;
}
__device__ __forceinline__ void h_release(int idx, int T, int i) {
  const int Q = (i & 2) ? (T + 2) / 3 - 1 : T / 3;
  if (Q >= 0 && Q < 4 && ((i & 2) == 0 || T % 3 == 0)) red_rel(&g_hcnt[(idx * 8 + 2 * Q + (i & 1)) * 32]);
}
__device__ __forceinline__ uint32_t pack_bf16(float lo, float hi) {
  uint32_t r; asm("cvt.rn.bf16x2.f32 %0, %1, %2;" : "=r"(r) : "f"(hi), "f"(lo)); return r;
}
__device__ __forceinline__ float bf_lo(uint32_t w) { return __uint_as_float(w << 16); }
__device__ __forceinline__ float bf_hi(uint32_t w) { return __uint_as_float(w & 0xffff0000u); }
__device__ __forceinline__ uint32_t hmul2(uint32_t a, uint32_t b) {
  __nv_bfloat162 r = __hmul2_rn(*(__nv_bfloat162*)&a, *(__nv_bfloat162*)&b); return *(uint32_t*)&r;
}
__device__ __forceinline__ uint32_t hadd2(uint32_t a, uint32_t b) {
  __nv_bfloat162 r = __hadd2_rn(*(__nv_bfloat162*)&a, *(__nv_bfloat162*)&b); return *(uint32_t*)&r;
}
__device__ __forceinline__ float2 cmul(float2 a, float2 b) { return make_float2(a.x * b.x - a.y * b.y, a.x * b.y + a.y * b.x); }
__device__ __forceinline__ float2 cfma(float2 a, float2 b, float2 c) {
  return make_float2(fmaf(a.x, b.x, fmaf(-a.y, b.y, c.x)), fmaf(a.x, b.y, fmaf(a.y, b.x, c.y)));
}
template <int N> __device__ __forceinline__ void fence_regs(float (&a)[N]) {
#pragma unroll
  for (int i = 0; i < N; i++) asm volatile("" : "+f"(a[i])::"memory");
}
__device__ __forceinline__ int tid_opaque() { int t; asm volatile("mov.u32 %0, %%tid.x;" : "=r"(t)); return t; }
struct Role { int T1, GP, side, m2, dg, cch0; bool last, has2; };
__device__ __forceinline__ Role unpack_role(int x) {
  Role r; r.T1 = x & 15; r.GP = (x >> 4) & 7; r.side = (x >> 7) & 1; r.m2 = (x >> 8) & 63; r.dg = (x >> 14) & 3;
  r.has2 = (x >> 16) & 1; r.last = r.T1 == NT1 - 1; r.cch0 = 160 * r.dg + r.m2; return r;
}
__device__ __forceinline__ Role fresh_role(int x) { asm volatile("" : "+r"(x)); return unpack_role(__shfl_sync(0xffffffffu, x, 0)); }
#define ROLE(x) const Role R_ = fresh_role(x); const int T1 = R_.T1, GP = R_.GP, side = R_.side, m2 = R_.m2, dg = R_.dg, cch0 = R_.cch0; \
  const bool last = R_.last, has2 = R_.has2; (void)T1; (void)GP; (void)side; (void)m2; (void)dg; (void)cch0; (void)last; (void)has2;
__device__ __forceinline__ int n_to_t(int n) {
  int T = n / 160, nl = n - T * 160;
  int L = (T == NT1 - 1) ? 32 : 40;
  return T * 160 + L * ((nl & 7) >> 1) + 2 * (nl >> 3) + (nl & 1);
}

template<int TA> __device__ __forceinline__ void wgmma_n160(float (&d)[80], uint32_t alo, uint32_t ahi, uint32_t blo, uint32_t bhi){
  asm volatile("{\n.reg .b64 da, db;\nmov.b64 da, {%80,%81};\nmov.b64 db, {%82,%83};\n"
    "wgmma.mma_async.sync.aligned.m64n160k16.f32.bf16.bf16 {%0, %1, %2, %3, %4, %5, %6, %7, %8, %9, %10, %11, %12, %13, %14, %15, %16, %17, %18, %19, %20, %21, %22, %23, %24, %25, %26, %27, %28, %29, %30, %31, %32, %33, %34, %35, %36, %37, %38, %39, %40, %41, %42, %43, %44, %45, %46, %47, %48, %49, %50, %51, %52, %53, %54, %55, %56, %57, %58, %59, %60, %61, %62, %63, %64, %65, %66, %67, %68, %69, %70, %71, %72, %73, %74, %75, %76, %77, %78, %79}, da, db, 1, 1, 1, %84, 0;\n}\n"
    : "+f"(d[0]), "+f"(d[1]), "+f"(d[2]), "+f"(d[3]), "+f"(d[4]), "+f"(d[5]), "+f"(d[6]), "+f"(d[7]), "+f"(d[8]), "+f"(d[9]), "+f"(d[10]), "+f"(d[11]), "+f"(d[12]), "+f"(d[13]), "+f"(d[14]), "+f"(d[15]), "+f"(d[16]), "+f"(d[17]), "+f"(d[18]), "+f"(d[19]), "+f"(d[20]), "+f"(d[21]), "+f"(d[22]), "+f"(d[23]), "+f"(d[24]), "+f"(d[25]), "+f"(d[26]), "+f"(d[27]), "+f"(d[28]), "+f"(d[29]), "+f"(d[30]), "+f"(d[31]), "+f"(d[32]), "+f"(d[33]), "+f"(d[34]), "+f"(d[35]), "+f"(d[36]), "+f"(d[37]), "+f"(d[38]), "+f"(d[39]), "+f"(d[40]), "+f"(d[41]), "+f"(d[42]), "+f"(d[43]), "+f"(d[44]), "+f"(d[45]), "+f"(d[46]), "+f"(d[47]), "+f"(d[48]), "+f"(d[49]), "+f"(d[50]), "+f"(d[51]), "+f"(d[52]), "+f"(d[53]), "+f"(d[54]), "+f"(d[55]), "+f"(d[56]), "+f"(d[57]), "+f"(d[58]), "+f"(d[59]), "+f"(d[60]), "+f"(d[61]), "+f"(d[62]), "+f"(d[63]), "+f"(d[64]), "+f"(d[65]), "+f"(d[66]), "+f"(d[67]), "+f"(d[68]), "+f"(d[69]), "+f"(d[70]), "+f"(d[71]), "+f"(d[72]), "+f"(d[73]), "+f"(d[74]), "+f"(d[75]), "+f"(d[76]), "+f"(d[77]), "+f"(d[78]), "+f"(d[79])
    : "r"(alo), "r"(ahi), "r"(blo), "r"(bhi), "n"(TA));
}
__device__ __forceinline__ void wgmma_rs_n160(float (&d)[80], uint32_t a0, uint32_t a1, uint32_t a2, uint32_t a3, uint32_t blo){
  asm volatile("{\n.reg .b64 db;\nmov.b64 db, {%84,8};\nwgmma.mma_async.sync.aligned.m64n160k16.f32.bf16.bf16 {%0, %1, %2, %3, %4, %5, %6, %7, %8, %9, %10, %11, %12, %13, %14, %15, %16, %17, %18, %19, %20, %21, %22, %23, %24, %25, %26, %27, %28, %29, %30, %31, %32, %33, %34, %35, %36, %37, %38, %39, %40, %41, %42, %43, %44, %45, %46, %47, %48, %49, %50, %51, %52, %53, %54, %55, %56, %57, %58, %59, %60, %61, %62, %63, %64, %65, %66, %67, %68, %69, %70, %71, %72, %73, %74, %75, %76, %77, %78, %79}, {%80,%81,%82,%83}, db, 1, 1, 1, 0;\n}\n"
    : "+f"(d[0]), "+f"(d[1]), "+f"(d[2]), "+f"(d[3]), "+f"(d[4]), "+f"(d[5]), "+f"(d[6]), "+f"(d[7]), "+f"(d[8]), "+f"(d[9]), "+f"(d[10]), "+f"(d[11]), "+f"(d[12]), "+f"(d[13]), "+f"(d[14]), "+f"(d[15]), "+f"(d[16]), "+f"(d[17]), "+f"(d[18]), "+f"(d[19]), "+f"(d[20]), "+f"(d[21]), "+f"(d[22]), "+f"(d[23]), "+f"(d[24]), "+f"(d[25]), "+f"(d[26]), "+f"(d[27]), "+f"(d[28]), "+f"(d[29]), "+f"(d[30]), "+f"(d[31]), "+f"(d[32]), "+f"(d[33]), "+f"(d[34]), "+f"(d[35]), "+f"(d[36]), "+f"(d[37]), "+f"(d[38]), "+f"(d[39]), "+f"(d[40]), "+f"(d[41]), "+f"(d[42]), "+f"(d[43]), "+f"(d[44]), "+f"(d[45]), "+f"(d[46]), "+f"(d[47]), "+f"(d[48]), "+f"(d[49]), "+f"(d[50]), "+f"(d[51]), "+f"(d[52]), "+f"(d[53]), "+f"(d[54]), "+f"(d[55]), "+f"(d[56]), "+f"(d[57]), "+f"(d[58]), "+f"(d[59]), "+f"(d[60]), "+f"(d[61]), "+f"(d[62]), "+f"(d[63]), "+f"(d[64]), "+f"(d[65]), "+f"(d[66]), "+f"(d[67]), "+f"(d[68]), "+f"(d[69]), "+f"(d[70]), "+f"(d[71]), "+f"(d[72]), "+f"(d[73]), "+f"(d[74]), "+f"(d[75]), "+f"(d[76]), "+f"(d[77]), "+f"(d[78]), "+f"(d[79])
    : "r"(a0), "r"(a1), "r"(a2), "r"(a3), "r"(blo));
}
template<int N> __device__ __forceinline__ void wgmma_rs_hi(float (&d)[64], uint32_t a0, uint32_t a1, uint32_t a2, uint32_t a3, uint32_t blo);
template<> __device__ __forceinline__ void wgmma_rs_hi<16>(float (&d)[64], uint32_t a0, uint32_t a1, uint32_t a2, uint32_t a3, uint32_t blo){
  asm volatile("{\n.reg .b64 db;\nmov.b64 db, {%12,8};\nwgmma.mma_async.sync.aligned.m64n16k16.f32.bf16.bf16 {%0, %1, %2, %3, %4, %5, %6, %7}, {%8,%9,%10,%11}, db, 1, 1, 1, 0;\n}\n"
    : "+f"(d[56]), "+f"(d[57]), "+f"(d[58]), "+f"(d[59]), "+f"(d[60]), "+f"(d[61]), "+f"(d[62]), "+f"(d[63])
    : "r"(a0), "r"(a1), "r"(a2), "r"(a3), "r"(blo));
}
template<> __device__ __forceinline__ void wgmma_rs_hi<32>(float (&d)[64], uint32_t a0, uint32_t a1, uint32_t a2, uint32_t a3, uint32_t blo){
  asm volatile("{\n.reg .b64 db;\nmov.b64 db, {%20,8};\nwgmma.mma_async.sync.aligned.m64n32k16.f32.bf16.bf16 {%0, %1, %2, %3, %4, %5, %6, %7, %8, %9, %10, %11, %12, %13, %14, %15}, {%16,%17,%18,%19}, db, 1, 1, 1, 0;\n}\n"
    : "+f"(d[48]), "+f"(d[49]), "+f"(d[50]), "+f"(d[51]), "+f"(d[52]), "+f"(d[53]), "+f"(d[54]), "+f"(d[55]), "+f"(d[56]), "+f"(d[57]), "+f"(d[58]), "+f"(d[59]), "+f"(d[60]), "+f"(d[61]), "+f"(d[62]), "+f"(d[63])
    : "r"(a0), "r"(a1), "r"(a2), "r"(a3), "r"(blo));
}
template<> __device__ __forceinline__ void wgmma_rs_hi<48>(float (&d)[64], uint32_t a0, uint32_t a1, uint32_t a2, uint32_t a3, uint32_t blo){
  asm volatile("{\n.reg .b64 db;\nmov.b64 db, {%28,8};\nwgmma.mma_async.sync.aligned.m64n48k16.f32.bf16.bf16 {%0, %1, %2, %3, %4, %5, %6, %7, %8, %9, %10, %11, %12, %13, %14, %15, %16, %17, %18, %19, %20, %21, %22, %23}, {%24,%25,%26,%27}, db, 1, 1, 1, 0;\n}\n"
    : "+f"(d[40]), "+f"(d[41]), "+f"(d[42]), "+f"(d[43]), "+f"(d[44]), "+f"(d[45]), "+f"(d[46]), "+f"(d[47]), "+f"(d[48]), "+f"(d[49]), "+f"(d[50]), "+f"(d[51]), "+f"(d[52]), "+f"(d[53]), "+f"(d[54]), "+f"(d[55]), "+f"(d[56]), "+f"(d[57]), "+f"(d[58]), "+f"(d[59]), "+f"(d[60]), "+f"(d[61]), "+f"(d[62]), "+f"(d[63])
    : "r"(a0), "r"(a1), "r"(a2), "r"(a3), "r"(blo));
}
template<> __device__ __forceinline__ void wgmma_rs_hi<64>(float (&d)[64], uint32_t a0, uint32_t a1, uint32_t a2, uint32_t a3, uint32_t blo){
  asm volatile("{\n.reg .b64 db;\nmov.b64 db, {%36,8};\nwgmma.mma_async.sync.aligned.m64n64k16.f32.bf16.bf16 {%0, %1, %2, %3, %4, %5, %6, %7, %8, %9, %10, %11, %12, %13, %14, %15, %16, %17, %18, %19, %20, %21, %22, %23, %24, %25, %26, %27, %28, %29, %30, %31}, {%32,%33,%34,%35}, db, 1, 1, 1, 0;\n}\n"
    : "+f"(d[32]), "+f"(d[33]), "+f"(d[34]), "+f"(d[35]), "+f"(d[36]), "+f"(d[37]), "+f"(d[38]), "+f"(d[39]), "+f"(d[40]), "+f"(d[41]), "+f"(d[42]), "+f"(d[43]), "+f"(d[44]), "+f"(d[45]), "+f"(d[46]), "+f"(d[47]), "+f"(d[48]), "+f"(d[49]), "+f"(d[50]), "+f"(d[51]), "+f"(d[52]), "+f"(d[53]), "+f"(d[54]), "+f"(d[55]), "+f"(d[56]), "+f"(d[57]), "+f"(d[58]), "+f"(d[59]), "+f"(d[60]), "+f"(d[61]), "+f"(d[62]), "+f"(d[63])
    : "r"(a0), "r"(a1), "r"(a2), "r"(a3), "r"(blo));
}
template<> __device__ __forceinline__ void wgmma_rs_hi<80>(float (&d)[64], uint32_t a0, uint32_t a1, uint32_t a2, uint32_t a3, uint32_t blo){
  asm volatile("{\n.reg .b64 db;\nmov.b64 db, {%44,8};\nwgmma.mma_async.sync.aligned.m64n80k16.f32.bf16.bf16 {%0, %1, %2, %3, %4, %5, %6, %7, %8, %9, %10, %11, %12, %13, %14, %15, %16, %17, %18, %19, %20, %21, %22, %23, %24, %25, %26, %27, %28, %29, %30, %31, %32, %33, %34, %35, %36, %37, %38, %39}, {%40,%41,%42,%43}, db, 1, 1, 1, 0;\n}\n"
    : "+f"(d[24]), "+f"(d[25]), "+f"(d[26]), "+f"(d[27]), "+f"(d[28]), "+f"(d[29]), "+f"(d[30]), "+f"(d[31]), "+f"(d[32]), "+f"(d[33]), "+f"(d[34]), "+f"(d[35]), "+f"(d[36]), "+f"(d[37]), "+f"(d[38]), "+f"(d[39]), "+f"(d[40]), "+f"(d[41]), "+f"(d[42]), "+f"(d[43]), "+f"(d[44]), "+f"(d[45]), "+f"(d[46]), "+f"(d[47]), "+f"(d[48]), "+f"(d[49]), "+f"(d[50]), "+f"(d[51]), "+f"(d[52]), "+f"(d[53]), "+f"(d[54]), "+f"(d[55]), "+f"(d[56]), "+f"(d[57]), "+f"(d[58]), "+f"(d[59]), "+f"(d[60]), "+f"(d[61]), "+f"(d[62]), "+f"(d[63])
    : "r"(a0), "r"(a1), "r"(a2), "r"(a3), "r"(blo));
}
template<> __device__ __forceinline__ void wgmma_rs_hi<96>(float (&d)[64], uint32_t a0, uint32_t a1, uint32_t a2, uint32_t a3, uint32_t blo){
  asm volatile("{\n.reg .b64 db;\nmov.b64 db, {%52,8};\nwgmma.mma_async.sync.aligned.m64n96k16.f32.bf16.bf16 {%0, %1, %2, %3, %4, %5, %6, %7, %8, %9, %10, %11, %12, %13, %14, %15, %16, %17, %18, %19, %20, %21, %22, %23, %24, %25, %26, %27, %28, %29, %30, %31, %32, %33, %34, %35, %36, %37, %38, %39, %40, %41, %42, %43, %44, %45, %46, %47}, {%48,%49,%50,%51}, db, 1, 1, 1, 0;\n}\n"
    : "+f"(d[16]), "+f"(d[17]), "+f"(d[18]), "+f"(d[19]), "+f"(d[20]), "+f"(d[21]), "+f"(d[22]), "+f"(d[23]), "+f"(d[24]), "+f"(d[25]), "+f"(d[26]), "+f"(d[27]), "+f"(d[28]), "+f"(d[29]), "+f"(d[30]), "+f"(d[31]), "+f"(d[32]), "+f"(d[33]), "+f"(d[34]), "+f"(d[35]), "+f"(d[36]), "+f"(d[37]), "+f"(d[38]), "+f"(d[39]), "+f"(d[40]), "+f"(d[41]), "+f"(d[42]), "+f"(d[43]), "+f"(d[44]), "+f"(d[45]), "+f"(d[46]), "+f"(d[47]), "+f"(d[48]), "+f"(d[49]), "+f"(d[50]), "+f"(d[51]), "+f"(d[52]), "+f"(d[53]), "+f"(d[54]), "+f"(d[55]), "+f"(d[56]), "+f"(d[57]), "+f"(d[58]), "+f"(d[59]), "+f"(d[60]), "+f"(d[61]), "+f"(d[62]), "+f"(d[63])
    : "r"(a0), "r"(a1), "r"(a2), "r"(a3), "r"(blo));
}
template<> __device__ __forceinline__ void wgmma_rs_hi<112>(float (&d)[64], uint32_t a0, uint32_t a1, uint32_t a2, uint32_t a3, uint32_t blo){
  asm volatile("{\n.reg .b64 db;\nmov.b64 db, {%60,8};\nwgmma.mma_async.sync.aligned.m64n112k16.f32.bf16.bf16 {%0, %1, %2, %3, %4, %5, %6, %7, %8, %9, %10, %11, %12, %13, %14, %15, %16, %17, %18, %19, %20, %21, %22, %23, %24, %25, %26, %27, %28, %29, %30, %31, %32, %33, %34, %35, %36, %37, %38, %39, %40, %41, %42, %43, %44, %45, %46, %47, %48, %49, %50, %51, %52, %53, %54, %55}, {%56,%57,%58,%59}, db, 1, 1, 1, 0;\n}\n"
    : "+f"(d[8]), "+f"(d[9]), "+f"(d[10]), "+f"(d[11]), "+f"(d[12]), "+f"(d[13]), "+f"(d[14]), "+f"(d[15]), "+f"(d[16]), "+f"(d[17]), "+f"(d[18]), "+f"(d[19]), "+f"(d[20]), "+f"(d[21]), "+f"(d[22]), "+f"(d[23]), "+f"(d[24]), "+f"(d[25]), "+f"(d[26]), "+f"(d[27]), "+f"(d[28]), "+f"(d[29]), "+f"(d[30]), "+f"(d[31]), "+f"(d[32]), "+f"(d[33]), "+f"(d[34]), "+f"(d[35]), "+f"(d[36]), "+f"(d[37]), "+f"(d[38]), "+f"(d[39]), "+f"(d[40]), "+f"(d[41]), "+f"(d[42]), "+f"(d[43]), "+f"(d[44]), "+f"(d[45]), "+f"(d[46]), "+f"(d[47]), "+f"(d[48]), "+f"(d[49]), "+f"(d[50]), "+f"(d[51]), "+f"(d[52]), "+f"(d[53]), "+f"(d[54]), "+f"(d[55]), "+f"(d[56]), "+f"(d[57]), "+f"(d[58]), "+f"(d[59]), "+f"(d[60]), "+f"(d[61]), "+f"(d[62]), "+f"(d[63])
    : "r"(a0), "r"(a1), "r"(a2), "r"(a3), "r"(blo));
}
template<> __device__ __forceinline__ void wgmma_rs_hi<128>(float (&d)[64], uint32_t a0, uint32_t a1, uint32_t a2, uint32_t a3, uint32_t blo){
  asm volatile("{\n.reg .b64 db;\nmov.b64 db, {%68,8};\nwgmma.mma_async.sync.aligned.m64n128k16.f32.bf16.bf16 {%0, %1, %2, %3, %4, %5, %6, %7, %8, %9, %10, %11, %12, %13, %14, %15, %16, %17, %18, %19, %20, %21, %22, %23, %24, %25, %26, %27, %28, %29, %30, %31, %32, %33, %34, %35, %36, %37, %38, %39, %40, %41, %42, %43, %44, %45, %46, %47, %48, %49, %50, %51, %52, %53, %54, %55, %56, %57, %58, %59, %60, %61, %62, %63}, {%64,%65,%66,%67}, db, 1, 1, 1, 0;\n}\n"
    : "+f"(d[0]), "+f"(d[1]), "+f"(d[2]), "+f"(d[3]), "+f"(d[4]), "+f"(d[5]), "+f"(d[6]), "+f"(d[7]), "+f"(d[8]), "+f"(d[9]), "+f"(d[10]), "+f"(d[11]), "+f"(d[12]), "+f"(d[13]), "+f"(d[14]), "+f"(d[15]), "+f"(d[16]), "+f"(d[17]), "+f"(d[18]), "+f"(d[19]), "+f"(d[20]), "+f"(d[21]), "+f"(d[22]), "+f"(d[23]), "+f"(d[24]), "+f"(d[25]), "+f"(d[26]), "+f"(d[27]), "+f"(d[28]), "+f"(d[29]), "+f"(d[30]), "+f"(d[31]), "+f"(d[32]), "+f"(d[33]), "+f"(d[34]), "+f"(d[35]), "+f"(d[36]), "+f"(d[37]), "+f"(d[38]), "+f"(d[39]), "+f"(d[40]), "+f"(d[41]), "+f"(d[42]), "+f"(d[43]), "+f"(d[44]), "+f"(d[45]), "+f"(d[46]), "+f"(d[47]), "+f"(d[48]), "+f"(d[49]), "+f"(d[50]), "+f"(d[51]), "+f"(d[52]), "+f"(d[53]), "+f"(d[54]), "+f"(d[55]), "+f"(d[56]), "+f"(d[57]), "+f"(d[58]), "+f"(d[59]), "+f"(d[60]), "+f"(d[61]), "+f"(d[62]), "+f"(d[63])
    : "r"(a0), "r"(a1), "r"(a2), "r"(a3), "r"(blo));
}

struct CvCtx {
  uint32_t koff, zero, so[3];
  int srcA, srcB;
  bool wrapA, s3, kodd;
};
struct CvPipe { uint32_t Ap, Ep, keep, send; };
template <int LO> __device__ __forceinline__ void cv_copy(float (&acc)[64]) {
#pragma unroll
  for (int i = LO; i < 64; i++) { float t; asm volatile("mov.b32 %0, %1;" : "=f"(t) : "f"(acc[i]) : "memory"); acc[i] = t; }
}
template <int G> __device__ __forceinline__ void cv_raw(uint32_t (&A)[4][4], uint32_t kaddr) {
#pragma unroll
  for (int i = 0; i < 4; i++) {
    const uint32_t a = kaddr + (4 * G + i) * 128;
    A[i][0] = lds32(a); A[i][1] = lds32(a + 4); A[i][3] = lds32(a + 8);
  }
}
__device__ __forceinline__ void cv_form(uint32_t (&A)[4][4], uint32_t sel) {
#pragma unroll
  for (int i = 0; i < 4; i++) {
    asm volatile("prmt.b32 %0, %0, %1, %2;" : "+r"(A[i][0]) : "r"(A[i][1]), "r"(sel));
    asm volatile("prmt.b32 %0, %1, %2, %3;" : "=r"(A[i][2]) : "r"(A[i][1]), "r"(A[i][3]), "r"(sel));
  }
}
#define CVV 2
template <int G> __device__ __forceinline__ void cv_step(float (&acc)[64], uint32_t (&A)[4][4], CvPipe& s, const CvCtx& c, uint32_t cb, uint32_t stg) {
  constexpr int JA = G - 1, JB = G - 2, NH = CVV == 1 ? 4 : (CVV == 3 ? 2 : 1);
  const uint32_t db0 = desc_lo(cb + CV_U + 192, CV_PL);
  uint32_t B[4][4];
  uint32_t ra[2], rb;
  if constexpr (G < 8) {
    wgmma_fence();
#pragma unroll
    for (int i = 0; i < NH; i++) wgmma_rs_hi<128 - 16 * (G & 7)>(acc, A[i][0], A[i][1], A[i][2], A[i][3], db0 - 4 * i);
    wgmma_commit();
    __syncwarp();
  }
  if constexpr (JA >= 0 && JA < 8) {
    const uint32_t p0 = pack_bf16(acc[8 * JA + 1], acc[8 * JA + 3]), p1 = pack_bf16(acc[8 * JA + 5], acc[8 * JA + 7]);
    ra[0] = __shfl_sync(0xffffffffu, c.wrapA ? s.Ap : p0, c.srcA);
    ra[1] = __shfl_sync(0xffffffffu, c.wrapA ? p0 : p1, c.srcA);
    s.Ap = p1;
  }
  if constexpr (JB >= 0) rb = __shfl_sync(0xffffffffu, s.send, c.srcB);
  if constexpr (G < 7) cv_raw<G + 1>(B, cb + c.koff);
  uint32_t z = 0;
  if constexpr (G < 8 && NH < 4) {
    __syncwarp();
    wgmma_fence();
#pragma unroll
    for (int i = NH; i < 4; i++) wgmma_rs_hi<128 - 16 * (G & 7)>(acc, A[i][0], A[i][1], A[i][2], A[i][3], db0 - 4 * i);
    wgmma_commit();
    asm volatile("mov.u32 %0, %%clock;" : "=r"(z)::"memory");
    z &= c.zero;
  }
  if constexpr (G < 7) cv_form(B, 0x5432u | z);
  if constexpr (JB >= 0) sts32(stg + ((c.so[JB / 3] >> (10 * (JB % 3))) & 0xffc), hadd2(rb | z, s.keep));
  if constexpr (JA >= 0 && JA < 8) {
    const uint32_t sh = 16 | z, mk = 0xffff0000u | z;
    const uint32_t ev = pack_bf16(acc[8 * JA] + __uint_as_float(ra[0] << sh), acc[8 * JA + 2] + __uint_as_float(ra[0] & mk));
    const uint32_t od = pack_bf16(acc[8 * JA + 4] + __uint_as_float(ra[1] << sh), acc[8 * JA + 6] + __uint_as_float(ra[1] & mk));
    s.send = c.kodd ? ev : (c.s3 ? s.Ep : od);
    s.keep = c.kodd ? od : ev;
    s.Ep = od;
  }
  if constexpr (G < 8) { __syncwarp(); wgmma_wait<0>(); cv_copy<8 * (G & 7)>(acc); }
  if constexpr (G < 9) cv_step<G + 1>(acc, B, s, c, cb, stg);
}
__device__ __forceinline__ uint32_t cv_stage(int slot) { return sb + (slot < 4 ? 40960 + slot * 4096 : CV_OFF + CV_K); }
__device__ __forceinline__ void cv_setup(CvCtx& c) {
  const int tid = tid_opaque() & 127, w = tid >> 5, lane = tid & 31, r = lane >> 2, q = lane & 3;
  const int i0 = (r >> 1) & 1, i1 = r >> 2;
  c.koff = CV_K - 32 + 4 * (8 * (r >> 1) + 2 * w + (r & 1) + 2 * q);
  c.srcA = i0 ? lane - 8 : lane + 8 - q + ((q + 3) & 3);
  c.wrapA = i0 && q == 3;
  c.srcB = i1 == 0 ? (lane - q + 16 + ((q + 3) & 3)) : (lane - q - 16 + ((q + 1) & 3));
  c.s3 = (i1 == 1 && q == 3); c.kodd = (i1 == 1 && q < 3);
  c.zero = lds32(sb + EP_OFF + 24);
#pragma unroll
  for (int i = 0; i < 3; i++) c.so[i] = lds32(sb + SO_OFF + 512 * i + 4 * tid);
}
__device__ __forceinline__ void cv_table() {
  const int tid = tid_opaque() & 127, r = (tid & 31) >> 2, q = tid & 3;
  int t = 16 * (2 * (r < 4 ? q : 4 + ((q + 1) & 3)) + ((r >> 1) & 1)) + 4 * (tid >> 5) + 2 * (r & 1);
#pragma unroll 1
  for (int i = 0; i < 3; i++) {
    uint32_t v = 0;
#pragma unroll 1
    for (int x = 0; x < 3; x++, t += 256) {
      const int T = t / 160, tl = t - T * 160;
      const int qq = (T >= NT1 - 1) ? (tl >> 5) : (tl / 40);
      int ck = 20 * T + ((tl - qq * ((T >= NT1 - 1) ? 32 : 40)) >> 1);
      ck ^= (ck >> 2) & 6;
      v |= (uint32_t)((ck * 4 + qq) & 1023) << (10 * x + 2);
    }
    sts32(sb + SO_OFF + 512 * i + 4 * tid, v);
  }
}
__device__ __forceinline__ void conv_channel(int slot, const CvCtx& c) {
  const uint32_t cb = sb + CV_OFF + slot * CV_B;
  float acc[64];
  CvPipe s;
  s.Ap = s.Ep = 0u;
  uint32_t A[4][4];
#pragma unroll
  for (int i = 0; i < 64; i++) acc[i] = 0.f;
  if (slot == 4) mbar_wait(bars + 8 * B_CVDONE);
  mbar_wait(bars + 8 * (B_CVFULL + slot));
  cv_raw<0>(A, cb + c.koff);
  {
    const uint32_t w0 = lds32(cb + CV_K);
    const uint32_t wp = __byte_perm(pack_bf16(bf_lo(w0) + __uint_as_float(lds32(sb + EP_OFF + 4 * slot)), 0.f), w0, 0x7610);
    if (c.koff == CV_K) A[0][0] = wp;
    if (c.koff == CV_K - 4) A[0][1] = wp;
    if (c.koff == CV_K - 8) A[0][3] = wp;
  }
  cv_form(A, 0x5432u);
  cv_copy<0>(acc);
  cv_step<0>(acc, A, s, c, cb, cv_stage(slot));
  fence_async_smem();
  mbar_arrive(bars + 8 * (B_CVDONE + slot));
}

__device__ __forceinline__ void kv_issue(const Params& p, int c, int m2, int dg) {
  const uint32_t fb = bars + 8 * (B_KV + c);
  mbar_expect_tx(fb, KV_PIECE);
  tma3(sb + KS_OFF + c * KV_PIECE, &p.mK, 160 * dg + 32 * c, 64 * m2 - 3, 0, fb);
  tma3(sb + KS_OFF + c * KV_PIECE + 4864, &p.mV, 160 * dg + 32 * c, 64 * m2 - 1, 0, fb);
}
__device__ __forceinline__ void kv_tile(int m, int c, int y, uint32_t (&o)[4][4]) {
  const int lane = tid_opaque() & 31, tg = lane & 3, pr = 8 * (y ^ (tg >> 1)) + (lane >> 2);
  const uint32_t pb = sb + KS_OFF + c * KV_PIECE + 4 * pr;
  const uint32_t ka = pb + tg * 1216, va = pb + 4864 + tg * 1088 + 64;
  const uint32_t kh = (m == 0 && tg > 0) ? ka - 192 : ka;
  uint32_t kk[19], u[16];
  const float4 t = lds128f(sb + TAP_OFF + 256 * c + 16 * pr);
#pragma unroll
  for (int i = 0; i < 19; i++) { kk[i] = lds32((i < 3 ? kh : ka) + i * 64); if (i >= 3) u[i - 3] = lds32(va + (i - 3) * 64); }
  const uint32_t dst = sb + KS_OFF + c * KV_PIECE + pr * 64 + tg * 16;
  if (y) {
    __syncwarp();
#pragma unroll
    for (int x = 0; x < 4; x++) sts128((dst ^ 512) + x * 1024, make_uint4(o[x][0], o[x][1], o[x][2], o[x][3]));
  }
  const uint32_t w0 = __byte_perm(__float_as_uint(t.x), __float_as_uint(t.z), 0x5410), w1 = __byte_perm(__float_as_uint(t.x), __float_as_uint(t.z), 0x7632);
  const uint32_t w2 = __byte_perm(__float_as_uint(t.y), __float_as_uint(t.w), 0x5410), w3 = __byte_perm(__float_as_uint(t.y), __float_as_uint(t.w), 0x7632);
#pragma unroll
  for (int i = 0; i < 16; i++) {
    uint32_t a = hmul2(kk[i], w3);
    a = hadd2(a, hmul2(kk[i + 1], w2)); a = hadd2(a, hmul2(kk[i + 2], w1)); a = hadd2(a, hmul2(kk[i + 3], w0));
    u[i] = hmul2(a, u[i]);
  }
#pragma unroll
  for (int x = 0; x < 4; x++) {
#pragma unroll
    for (int qq = 0; qq < 4; qq++) o[x][qq] = __byte_perm(u[15 - 4 * qq - (x & 2)], u[14 - 4 * qq - (x & 2)], (x & 1) ? 0x7632 : 0x5410);
    if (y) sts128(dst + x * 1024, make_uint4(o[x][0], o[x][1], o[x][2], o[x][3]));
  }
}
template <bool BF>
__device__ __forceinline__ void ln_finish(float s1, float s2, float& mean, float& rstd) {
  mean = s1 * (1.f / 640.f);
  float v = fmaxf(fmaf(-mean, mean, s2 * (1.f / 640.f)), 0.f);
  if (BF) {
    const uint32_t mv = pack_bf16(mean, v);
    mean = bf_lo(mv);
    asm("sqrt.approx.ftz.f32 %0, %1;" : "=f"(v) : "f"(bf_lo(pack_bf16(bf_hi(mv) + 1e-5f, 0.f))));
    asm("rcp.approx.ftz.f32 %0, %1;" : "=f"(rstd) : "f"(bf_lo(pack_bf16(v, 0.f))));
  } else {
    v += 1e-5f;
    asm("rsqrt.approx.ftz.f32 %0, %1;" : "=f"(rstd) : "f"(v));
  }
}
template <int l>
__device__ __forceinline__ void stat_table(int T1, unsigned want, int g, const uint4* x0, const uint4* x1, float (&xa)[2], float (&xb)[2]) {
  const int n = 32 * g + (tid_opaque() & 31);
  const uint4* rp = &g_stats[8 * l * SEQ + min(160 * T1 + n, SEQ - 1)];
  float a[4], b[4];
  uint32_t it = 0;
  while (true) {
    bool ok = true;
#pragma unroll
    for (int i = 0; i < 4; i++) ok &= (rec_ld(rp + SEQ * i, a[i], b[i]) == want);
    ok &= rec_ld(x0, xa[0], xb[0]) == want;
    ok &= rec_ld(x1, xa[1], xb[1]) == want;
    if (__all_sync(0xffffffffu, ok)) break;
    trap_if(++it > SPIN_LIMIT);
  }
  float m, rs;
  ln_finish<l == 0>((a[0] + a[1]) + (a[2] + a[3]), (b[0] + b[1]) + (b[2] + b[3]), m, rs);
  sts32(sb + STAB_OFF + ((n >> 1) & 3) * 160 + (n >> 3) * 8 + (n & 1) * 4, __float_as_uint(rs));
  const uint32_t hi = pack_bf16(-m, -m);
  const float lo = -m - bf_lo(hi);
  sts128(sb + (l ? MX1_OFF : MX0_OFF) + n * 16, make_uint4(hi, pack_bf16(lo, lo), 0u, 0u));
  fence_async_smem();
}
template <bool BF>
__device__ __forceinline__ void stats_reduce(float (&a)[2], float (&b)[2], float (&mean)[2], float (&rstd)[2]) {
#pragma unroll
  for (int o = 1; o < 4; o <<= 1)
#pragma unroll
    for (int h = 0; h < 2; h++) { a[h] += __shfl_xor_sync(0xffffffffu, a[h], o); b[h] += __shfl_xor_sync(0xffffffffu, b[h], o); }
#pragma unroll
  for (int h = 0; h < 2; h++) ln_finish<BF>(a[h], b[h], mean[h], rstd[h]);
}

template <bool FIRST>
__device__ __forceinline__ void stats_publish(int which, int n0, int dg, unsigned tag, const float (&acc)[80]) {
  const int q = tid_opaque() & 3, h = q & 1;
  float s1[2] = {0.f, 0.f}, s2[2] = {0.f, 0.f}, t1[2] = {0.f, 0.f}, t2[2] = {0.f, 0.f};
#pragma unroll
  for (int j = 0; j < 20; j++)
#pragma unroll
    for (int y = 0; y < 2; y++) {
      const float a = acc[4 * j + 2 * y], b = acc[4 * j + 2 * y + 1];
      s1[y] += a; t1[y] += b; s2[y] = fmaf(a, a, s2[y]); t2[y] = fmaf(b, b, t2[y]);
    }
#pragma unroll
  for (int y = 0; y < 2; y++) { s1[y] += t1[y]; s2[y] += t2[y]; }
  float a = (h ? s1[1] : s1[0]) + __shfl_xor_sync(0xffffffffu, h ? s1[0] : s1[1], 1);
  float b = (h ? s2[1] : s2[0]) + __shfl_xor_sync(0xffffffffu, h ? s2[0] : s2[1], 1);
  a += __shfl_xor_sync(0xffffffffu, a, 2);
  b += __shfl_xor_sync(0xffffffffu, b, 2);
  if (FIRST) {
    rec_st(&g_stats[((q >> 1) * 4 + dg) * SEQ + n0 + 8 * h], a, b, q < 2 ? tag : tag - 1);
    rec_st(&g_stats[((q >> 1) * 4 + 8 + dg) * SEQ + n0 + 8 * h], a, b, tag - 1);
  } else if (q < 2) rec_st(&g_stats[(which * 4 + dg) * SEQ + n0 + 8 * h], a, b, tag);
}
__device__ __forceinline__ void stats_get(int which, int n0, unsigned tag, float (&mean)[2], float (&rstd)[2]) {
  const uint4* p0 = &g_stats[(which * 4 + (tid_opaque() & 3)) * SEQ + n0];
  float a[2], b[2];
  uint32_t it = 0;
  while (true) {
    const unsigned t0 = rec_ld(p0, a[0], b[0]), t1 = rec_ld(p0 + 8, a[1], b[1]);
    if (__all_sync(0xffffffffu, t0 == tag && t1 == tag)) break;
    trap_if(++it > SPIN_LIMIT);
  }
  stats_reduce<false>(a, b, mean, rstd);
}
__device__ __forceinline__ void x0_load(float (&acc)[80]) {
  const int t = tid_opaque() & 127;
  const uint32_t xa = sb + XT_OFF + (16 * (t >> 5) + ((t & 31) >> 2)) * 320 + 8 * (t & 3);
  mbar_wait(bars + 8 * B_XT);
#pragma unroll
  for (int h = 0; h < 2; h++)
#pragma unroll
    for (int J = 0; J < 10; J++) {
      const float2 v = lds64f(xa + h * 2560 + 32 * J);
      const uint32_t x = __float_as_uint(v.x), y = __float_as_uint(v.y);
      acc[8 * J + 2 * h] = bf_lo(x); acc[8 * J + 2 * h + 1] = bf_hi(x);
      acc[8 * J + 4 + 2 * h] = bf_lo(y); acc[8 * J + 4 + 2 * h + 1] = bf_hi(y);
    }
}

template <bool FROM_X0>
__device__ __forceinline__ void dskip_init(float (&acc)[80], const float (&mean)[2], const float (&rstd)[2]) {
  const int t = tid_opaque() & 127;
  const uint32_t xa = sb + XT_OFF + (16 * (t >> 5) + ((t & 31) >> 2)) * 320 + 8 * (t & 3), da = sb + DTAB_OFF + 8 * (t & 3);
  float2 dw[10], xv[10][2];
#pragma unroll
  for (int J = 0; J < 2; J++) { dw[J] = lds64f(da + 32 * J); if (FROM_X0) { xv[J][0] = lds64f(xa + 32 * J); xv[J][1] = lds64f(xa + 2560 + 32 * J); } }
#pragma unroll
  for (int J = 0; J < 10; J++) {
    if (J + 2 < 10) { dw[J + 2] = lds64f(da + 32 * (J + 2)); if (FROM_X0) { xv[J + 2][0] = lds64f(xa + 32 * (J + 2)); xv[J + 2][1] = lds64f(xa + 2560 + 32 * (J + 2)); } }
#pragma unroll
    for (int x = 0; x < 8; x++) {
      const int h = (x >> 1) & 1;
      const uint32_t dwd = __float_as_uint(x < 4 ? dw[J].x : dw[J].y);
      const float tt = fmaf(rstd[h], (x & 1) ? bf_hi(dwd) : bf_lo(dwd), 1.f);
      float a = acc[8 * J + x];
      if (FROM_X0) { const uint32_t xw = __float_as_uint(x < 4 ? xv[J][h].x : xv[J][h].y); a = (x & 1) ? bf_hi(xw) : bf_lo(xw); }
      acc[8 * J + x] = FROM_X0 ? (a - mean[h]) * tt : fmaf(a, tt, -mean[h] * tt);
    }
  }
}

__global__ void __launch_bounds__(512, 1) fused_kernel(const __grid_constant__ Params p) {
  extern __shared__ __align__(1024) uint8_t smem_raw[];
  const int tid = threadIdx.x, lane = tid & 31;
  const int wid = __shfl_sync(0xffffffffu, tid >> 5, 0), wg = wid >> 2;
  unsigned smid; asm volatile("mov.u32 %0, %%smid;" : "=r"(smid));
  const int role = p.role[min(smid, 131u)];
  if (wid == 12) {
    const bool el = elect_one();
    if (el) {
      asm volatile("prefetch.tensormap [%0];" ::"l"(&p.mB) : "memory");
      asm volatile("prefetch.tensormap [%0];" ::"l"((role & 15) == NT1 - 1 ? &p.mXl : &p.mX) : "memory");
#pragma unroll
      for (int k = 0; k < S1; k++) mbar_init(bars + 8 * (B_G1FULL + k), 1);
#pragma unroll
      for (int k = 0; k < 6; k++) mbar_init(bars + 8 * (B_XT + k), 1);
      asm volatile("fence.mbarrier_init.release.cluster;" ::: "memory");
    }
    if (role >= 0) {
      __syncwarp();
      asm volatile("bar.arrive 5, 288;" ::: "memory");
      const Role R = unpack_role(role);
      if (elect_one()) {
        TS(45);
#pragma unroll 1
        for (int k = 0; k < S1; k++) {
          const uint32_t fb = bars + 8 * (B_G1FULL + k);
          mbar_expect_tx(fb, G1_STAGE);
          tma4(sb + k * G1_STAGE + G1_XOFF, R.last ? &p.mXl : &p.mX, 64 * k, 0, 0, R.last ? 0 : 80 * R.T1, fb);
          tma5(sb + k * G1_STAGE, &p.mB, 64 * k, 0, 0, 4 * R.side, 2 * R.GP, fb);
          if (PFD) asm volatile("prefetch.tensormap [%0];" ::"l"(&p.mK + k) : "memory");
        }
        if (R.has2) {
          mbar_expect_tx(bars + 8 * B_XT, 20480);
#pragma unroll 1
          for (int h = 0; h < 2; h++) {
            const int ng = 8 * R.m2 + 4 * h, T = ng / 20;
            tma4(sb + XT_OFF + h * 10240, T == NT1 - 1 ? &p.mXtl : &p.mXt, 160 * R.dg, 0, 0, T == NT1 - 1 ? ng - 240 : ng + 60 * T, bars + 8 * B_XT);
          }
#pragma unroll 1
          for (int c = 0; c < KV0; c++) kv_issue(p, c, R.m2, R.dg);
        }
        TS(44);
      }
      __syncwarp();
      bar_sync(6, 64);
    }
  }
  trap_if(smid >= 132 || smem_u32(smem_raw) != sb);
  if (role < 0) {
    if (wid == 0) {
      const unsigned tag = ld_rlx(g_epoch);
      uint32_t it = 0;
      while (!__all_sync(0xffffffffu, (int)(ld_rlx(&g_hcnt[(lane & 7) * 32]) - 40 * tag) >= 0)) { __nanosleep(500); trap_if(++it > SPIN_LIMIT); }
    }
    return;
  }
  float mean0[2] = {0.f, 0.f}, rstd0[2] = {0.f, 0.f};
  if (wg == 2 || wid == 14) {
    ROLE(role)
    const int c = wid == 14 ? 4 : wid - 8;
    const unsigned tag = ld_rlx(g_epoch);
    if (has2) {
      uint2 bv[2][5];
#pragma unroll
      for (int x = 0; x < 2; x++)
#pragma unroll
        for (int i = 0; i < 5; i++) bv[x][i] = ldv64((const uint2*)((x ? p.bim : p.bre) + (cch0 + 32 * c) * DM) + lane + 32 * i);
      float sv[2];
#pragma unroll
      for (int x = 0; x < 2; x++) {
        float a = 0.f;
#pragma unroll
        for (int i = 0; i < 5; i++) a += (bf_lo(bv[x][i].x) + bf_hi(bv[x][i].x)) + (bf_lo(bv[x][i].y) + bf_hi(bv[x][i].y));
        sv[x] = a;
      }
#pragma unroll
      for (int o = 16; o > 0; o >>= 1) { sv[0] += __shfl_xor_sync(0xffffffffu, sv[0], o); sv[1] += __shfl_xor_sync(0xffffffffu, sv[1], o); }
      if (lane < 2) rec_st(&g_sB[(cch0 + 32 * c) * 2 + lane], sv[0], sv[1], tag);
      if (tid == 256) TS(47);
      __syncwarp();
      bar_sync(8, 192);
      if (wg == 2) {
        float xs[80];
        x0_load(xs);
        stats_publish<true>(0, 64 * m2 + 16 * c + (lane >> 2), dg, tag, xs);
        if (tid == 256) TS(31);
      }
      mbar_wait(bars + 8 * B_EP);
      mbar_wait(bars + 8 * (B_KV + c));
      mbar_wait(bars + 8 * (B_G1DONE + PAUSE_K - 1));
      if (tid == 448) TS(52);
      uint32_t o[4][4] = {};
#pragma unroll 1
      for (int y = 0; y < 2; y++) kv_tile(m2, c, y, o);
      fence_async_smem();
      __syncwarp();
      if (lane == 0) { mbar_arrive(bars + 8 * B_PREP); mbar_arrive(bars + 8 * (B_PD + c)); }
      if (tid == 448) TS(51);
    } else bar_sync(8, 192);
    {
      const uint4* x0 = wg == 2 ? &g_stats[(lane & 3) * SEQ + (has2 ? 64 * m2 : 0) + 16 * c + (lane >> 2)] : &g_sB[(128 * GP + 32 * side + lane) * 2];
      float xa[2], xb[2];
      stat_table<0>(T1, tag, c, x0, x0 + (wg == 2 ? 8 : 128), xa, xb);
      if (wg == 2) stats_reduce<true>(xa, xb, mean0, rstd0);
      else {
#pragma unroll
        for (int i = 0; i < 2; i++) {
          const float ha = bf_lo(pack_bf16(xa[i], 0.f)), hb = bf_lo(pack_bf16(xb[i], 0.f));
          const float pa = __uint_as_float(pack_bf16(ha, xa[i] - ha)), pb = __uint_as_float(pack_bf16(hb, xb[i] - hb));
          sts64f(sb + CTAB_OFF + (32 * i + lane) * 24 + 16, p.swap ? pb : pa, p.swap ? pa : pb);
        }
      }
      mbar_arrive(bars + 8 * B_STAB);
      if (tid == 448) TS(26);
    }
  } else if (wid == 15) {
    ROLE(role)
    const int ch = 128 * GP + 32 * side + lane;
    uint32_t r0 = ldv16(p.lre + ch), r1 = ldv16(p.lim + ch), r2 = ldv16(p.logdt + ch);
    const uint32_t r3 = ldv16(p.lre + ch + 64), r4 = ldv16(p.lim + ch + 64), r5 = ldv16(p.logdt + ch + 64);
#pragma unroll 1
    for (int i = 0; i < 2; i++) {
      const float lr = bf_lo(r0), li = bf_lo(r1);
      const float dt = __bfloat162float(__float2bfloat16_rn(expf(bf_lo(r2))));
      const float mag = expf(dt * lr);
      float sn, cs; sincospif(dt * li * 0.31830988618379067f, &sn, &cs);
      const float ar = mag * cs, ai = mag * sn;
      const float inv = 2.f / (lr * lr + li * li);
      const uint32_t ad = sb + CTAB_OFF + (32 * i + lane) * 24;
      sts64f(ad, ar, ai);
      sts64f(ad + 8, ((ar - 1.f) * lr + ai * li) * inv, (ai * lr - (ar - 1.f) * li) * inv);
      r0 = r3; r1 = r4; r2 = r5;
    }
    if (lane == 0) TS(46);
    __syncwarp();
    bar_sync(7, 64);
    mbar_arrive(bars + 8 * B_CTAB);
  } else if (wid == 13) {
    ROLE(role)
    uint4 tv[3];
    const uint32_t e0 = ld_rlx(g_epoch);
    const uint32_t e1 = ldv16(p.ssmD + min(cch0 + 32 * lane, 639));
    const uint4 dv = ldv128((const uint4*)(p.dskip + 160 * dg) + min(lane, 19));
#pragma unroll
    for (int i = 0; i < 3; i++) tv[i] = ldv128((const uint4*)(p.shiftk + 640 * dg) + min(lane + 32 * i, 79));
    sts128(sb + DTAB_OFF + 16 * min(lane, 19), dv);
#pragma unroll
    for (int i = 0; i < 3; i++) sts128(sb + TAP_OFF + 16 * min(lane + 32 * i, 79), tv[i]);
    if (lane < 7) sts32(sb + EP_OFF + 4 * lane, lane < 5 ? e1 << 16 : (lane == 5 ? e0 : 0u));
    __syncwarp();
    bar_sync(9, 64);
    mbar_arrive(bars + 8 * B_CTAB);
    if (lane == 0) { mbar_arrive(bars + 8 * B_EP); TS(53); }
    if (has2) {
#pragma unroll 1
      for (int i = 0; i < 5; i++) {
        const int c = i == 2 ? 3 : (i == 3 ? 2 : i);
        mbar_wait(bars + 8 * (B_PD + c));
        if (lane == 0) bulk_s2g(g_kv + (dg * 32 + m2) * 20480 + c * 4096, sb + KS_OFF + c * KV_PIECE, 4096);
      }
      if (lane == 0) {
        asm volatile("cp.async.bulk.commit_group;" ::: "memory");
        asm volatile("cp.async.bulk.wait_group 0;" ::: "memory");
        mbar_arrive(bars + 8 * B_PREP2);
        fence_async_global();
      }
      __syncwarp();
      if (lane < 4) red_rel(&g_kvcnt[(dg * 4 + lane) * 32]);
      __syncwarp();
      if (lane == 0) { mbar_arrive(bars + 8 * B_PUB); TS(30); }
    }
  } else if (wid != 12) {
    if (elect_one()) {
      if (wid < 7) {
        const int b0 = wid < 4 ? 4 + 19 * wid : 85 + 21 * (wid - 4), cnt = wid < 4 ? 2 : 1;
#pragma unroll
        for (int i = 0; i < 21; i++) mbar_init(bars + 8 * (b0 + i), cnt);
#pragma unroll
        for (int i = 0; i < 5; i++) mbar_init(bars + 8 * (B_PD + 5 * wid + i), 1);
      } else {
#pragma unroll
        for (int i = 0; i < 12; i++) mbar_init(bars + 8 * (B_CVDONE + i), (i == 5 || i == 6) ? 160 : 128);
        mbar_init(bars + 8 * B_CTAB, 192); mbar_init(bars + 8 * B_PREP, 5); mbar_init(bars + 8 * B_PREP2, 1);
      }
      asm volatile("fence.mbarrier_init.release.cluster;" ::: "memory");
    }
    __syncwarp();
    bar_sync(5, 288);
    if (wid == 2) asm volatile("bar.arrive 8, 192;\nbar.arrive 6, 64;\nbar.arrive 9, 64;\nbar.arrive 7, 64;" ::: "memory");
    if (tid == 128) TS(0);
    if (wg == 1) { cv_table(); mbar_arrive(bars + 8 * B_CTAB); }
  }

  if (wid == 12) {
    ROLE(role)
    uint32_t dst = sb;
#pragma unroll 1
    for (int k = S1; k < 10; k++) {
      const uint32_t fb = bars + 8 * (B_G1FULL + k);
      mbar_wait(bars + 8 * (B_G1DONE + k - S1));
      if (elect_one()) {
        mbar_expect_tx(fb, 20480);
        tma4(dst + G1_XOFF, last ? &p.mXl : &p.mX, 64 * k, 0, 0, last ? 0 : 80 * T1, fb);
        mbar_expect_tx(fb, 16384);
        tma5(dst, &p.mB, 64 * k, 0, 0, 4 * side, 2 * GP, fb);
        if (has2 && k - S1 + KV0 < 5) kv_issue(p, k - S1 + KV0, m2, dg);
      }
      dst += G1_STAGE; if (k == 2 * S1 - 1) dst = sb;
    }
  } else if (wid == 15 && (role >> 16)) {
    ROLE(role)
    if (TPF >= 0) {
      mbar_wait(bars + 8 * (B_KV + TPF));
      if (elect_one()) {
#pragma unroll
        for (int c = 0; c < 5; c++) l2_prefetch(p.ssmk + (cch0 + 32 * c) * SEQ, 4096);
        if (CPF) { l2_prefetch(p.cre + (160 * dg + 5 * m2) * DM, 6400); l2_prefetch(p.cim + (160 * dg + 5 * m2) * DM, 6400); }
      }
    }
    mbar_wait(bars + 8 * B_PREP2);
    if (lane < 10) sts128(sb + CV_OFF + (lane >> 1) * CV_B + CV_K - 32 + 16 * (lane & 1), make_uint4(0, 0, 0, 0));
    fence_async_smem();
    __syncwarp();
    const unsigned tag = lds32(sb + EP_OFF + 20);
    if (TAPW) mbar_wait(bars + 8 * B_PUB);
    if (elect_one()) {
#pragma unroll 1
      for (int c = 0; c < 5; c++) {
        if (c == 0) asm volatile("prefetch.tensormap [%0];" ::"l"(&p.mU) : "memory");
        mbar_expect_tx(bars + 8 * (B_CVFULL + c), 4096 + 2 * CV_PL);
        if (c < TAPN) bulk_g2s(sb + CV_OFF + c * CV_B + CV_K, p.ssmk + (cch0 + 32 * c) * SEQ, 4096, bars + 8 * (B_CVFULL + c));
      }
    }
    mbar_wait(bars + 8 * B_PUB);
    cnt_poll(&g_kvcnt[(dg * 4 + (m2 >> 3)) * 32], 32 * tag);
    fence_async_global();
    if (elect_one()) {
      TS(28);
#pragma unroll
      for (int c = 0; c < 5; c++) {
        tma5(sb + CV_OFF + c * CV_B + CV_U, &p.mU, 0, -3, 2 * c, 16 * (m2 & 1) + (m2 >> 1), dg, bars + 8 * (B_CVFULL + c));
        if (c >= TAPN) bulk_g2s(sb + CV_OFF + c * CV_B + CV_K, p.ssmk + (cch0 + 32 * c) * SEQ, 4096, bars + 8 * (B_CVFULL + c));
      }
#pragma unroll
      for (int i = 0; i < 3; i++) asm volatile("prefetch.tensormap [%0];" ::"l"(&p.mCre + i) : "memory");
      TS(54);
    }
    __syncwarp();
  }
  {
    const int w = wid & 3;
    if (wg == 2 && !(role >> 16)) {
      float xa[2], xb[2];
      mbar_wait(bars + 8 * (B_G1FULL + 11));
      stat_table<1>(role & 15, lds32(sb + EP_OFF + 20), w, g_stats, g_stats, xa, xb);
      mbar_arrive(bars + 8 * (B_STAB + 1));
    }
#pragma unroll 1
    for (int l = 0; l < 2; l++) {
      if (wg < 2) {
        float acc[80];
#pragma unroll
        for (int i = 0; i < 80; i++) acc[i] = 0.f;
        ROLE(role)
        const int tid = tid_opaque(), r = (tid & 31) >> 2, q = tid & 3;
        const int ch = 128 * GP + 64 * wg + 32 * side + 8 * w + r;
        const uint32_t ca = sb + CTAB_OFF + (32 * wg + 8 * w + r) * 24;
        float2 lam = make_float2(0.f, 0.f), p8 = lam, p16 = lam, pL = lam, p2L = lam;
        fence_regs(acc);
        {
          const uint32_t alo0 = (l == 0 ? desc_lo(sb, 16) : desc_lo(sb + G2_WOFF, 16)) + wg * 512;
          const uint32_t blo0 = l == 0 ? desc_lo(sb + G1_XOFF, 16) : desc_lo(sb + X1_OFF, 128);
          const uint32_t bhi = l == 0 ? desc_hi(1024, 1) : desc_hi(1024, 0), xstep = l == 0 ? 2 : 16;
          const uint32_t astep = l == 0 ? G1_STAGE >> 4 : 1024, bstep = l == 0 ? G1_STAGE >> 4 : 1280, aend = alo0 + (S1 + l) * astep;
          uint32_t alo = alo0, blo = blo0;
          const uint32_t special = 8u | (l ? (1u << MK1) | (wg << (8 - STG_D)) : (1u << MK0) | (1u << PAUSE_K) | (wg << (9 - STG0)));
          uint32_t fb = bars + 8 * (B_G1FULL + 10 * l), nb = fb + 8;
          mbar_wait(fb);
          if (tid == 0) TS(1 + 8 * l);
#pragma unroll 1
          for (int k = 0; k < 10; k++) {
            uint32_t ok;
            wgmma_fence();
#pragma unroll
            for (int kk = 0; kk < 4; kk++) {
              wgmma_n160<0>(acc, alo + kk * 2, desc_hi(1024, 1), blo + kk * xstep, bhi);
              if (kk == 0) { ok = mbar_test(nb); asm volatile("add.u32 %0, %0, %1;" : "+r"(nb) : "r"(k < 8 ? 8 : 0)); }
              if (kk == STG_KK && k == 9 && tid == 0) mbar_arrive(bars + 8 * (B_STG + l));
            }
            wgmma_commit();
            alo += astep; blo += bstep;
            if (blo == desc_lo(sb + G_OFF, 128)) blo = desc_lo(sb, 128);
            if (alo == aend) { alo = alo0; blo = blo0; }
            wgmma_wait<1>();
            if (k > 0 && (tid & 127) == 0) mbar_arrive(fb + 8 * (B_G1DONE - B_G1FULL - 1));
            if (!ok) mbar_wait(fb + 8);
            if ((special >> k) & 1) {
            if (k == (l ? MK1 : MK0)) {
              mbar_wait(bars + 8 * (B_STAB + l));
              const float2 sB = lds64f(ca + 16);
              uint32_t a0 = q < 2 ? __float_as_uint(sB.x) : 0u, a1 = q < 2 ? __float_as_uint(sB.y) : 0u, a2 = 0u, a3 = 0u;
              asm volatile("" : "+r"(a0), "+r"(a1), "+r"(a2), "+r"(a3)::"memory");
              wgmma_fence();
              wgmma_rs_n160(acc, a0, a1, a2, a3, l ? desc_lo(sb + MX1_OFF, 0) : desc_lo(sb + MX0_OFF, 0));
              wgmma_commit();
            }
            if (wg == 1 && k == (l ? 8 - STG_D : 9 - STG0)) mbar_wait(bars + 8 * (B_STG + l));
            if (k == 3) {
              mbar_wait(bars + 8 * B_CTAB);
              lam = lds64f(ca);
              if (l == 0 && q < 2) rec_st(&g_E[(q * NT1 + T1) * DM + ch], 0.f, 0.f, lds32(sb + EP_OFF + 20) - 1);
              if (p.swap) lam.y = -lam.y;
              const float2 p2 = cmul(lam, lam), p4 = cmul(p2, p2);
              p8 = cmul(p4, p4); p16 = cmul(p8, p8);
              pL = cmul(p16, p16);
              if (!last) pL = cmul(pL, p8);
              p2L = cmul(pL, pL);
            }
            if (k == PAUSE_K && l == 0 && has2) mbar_wait(bars + 8 * B_PREP);
            }
            fb += 8;
          }
        }
        const unsigned tag = lds32(sb + EP_OFF + 20);
        wgmma_wait<0>();
        fence_regs(acc);
        if ((tid & 127) == 0) { mbar_arrive(bars + 8 * (B_G1DONE + 10 * l + 9)); TS(wg ? 17 + l : 2 + 8 * l); }
        float2 ec[3];
#pragma unroll
        for (int jj = 0; jj < 4; jj++)
#pragma unroll
          for (int y = 0; y < 3; y++) {
            if (y == 2 && (jj & 1)) continue;
            const int j = y == 2 ? 16 + jj : 8 * y + 2 * jj;
            const float4 st = lds128f(sb + STAB_OFF + q * 160 + j * 8);
            const float rs[4] = {st.x, st.y, st.z, st.w};
#pragma unroll
            for (int x = 0; x < 4; x++) {
              const int i = 4 * j + 4 * (x >> 1) + (x & 1);
              acc[i] *= rs[x]; acc[i + 2] *= rs[x];
              ec[y] = (jj == 0 && x == 0) ? make_float2(acc[i], acc[i + 2]) : cfma(lam, ec[y], make_float2(acc[i], acc[i + 2]));
            }
          }
        float2 e = cfma(p16, ec[0], ec[1]);
        if (!last) e = cfma(p8, e, ec[2]);
        {
          float2 v = make_float2(__shfl_up_sync(0xffffffffu, e.x, 1, 4), __shfl_up_sync(0xffffffffu, e.y, 1, 4));
          if (q >= 1) e = cfma(pL, v, e);
          v = make_float2(__shfl_up_sync(0xffffffffu, e.x, 2, 4), __shfl_up_sync(0xffffffffu, e.y, 2, 4));
          if (q >= 2) e = cfma(p2L, v, e);
        }
        if (!last && q == 3) rec_st(&g_E[(l * NT1 + T1) * DM + ch], e.x, e.y, tag);
        if (tid == 0) TS(3 + 8 * l);
        float2 ex = make_float2(__shfl_up_sync(0xffffffffu, e.x, 1, 4), __shfl_up_sync(0xffffffffu, e.y, 1, 4));
        if (q == 0) ex = make_float2(0.f, 0.f);
        const float2 coef = lds64f(ca + 8), lamc = make_float2(lam.x, p.swap ? lam.y : -lam.y);
        float m00 = coef.x, m01 = -coef.y, m10 = -coef.y, m11 = -coef.x;
        if (p.swap) { m00 = -coef.y; m01 = coef.x; m10 = -coef.x; m11 = -coef.y; }
        float2 pLq, p160q, p640;
        {
          const float2 p80 = last ? cmul(p2L, p16) : p2L, p160 = cmul(p80, p80), p320 = cmul(p160, p160), one = make_float2(1.f, 0.f);
          p640 = cmul(p320, p320);
          pLq = cmul((q & 1) ? pL : one, (q & 2) ? p2L : one);
          p160q = cmul((q & 1) ? p160 : one, (q & 2) ? p320 : one);
        }
        float2 c, ev[3];
        unsigned tg[3];
        const uint4* ep = &g_E[(l * NT1 + T1 - 1 - q) * DM + ch];
#pragma unroll
        for (int j = 0; j < 20; j++) {
          if (j == CPOLL) {
#pragma unroll
            for (int i = 0; i < 3; i++) {
              ev[i] = make_float2(0.f, 0.f); tg[i] = tag;
              if (T1 - 1 - q - 4 * i >= 0) tg[i] = rec_ld(ep - 4 * i * DM, ev[i].x, ev[i].y);
            }
          }
#pragma unroll
          for (int x = 0; x < 2; x++) {
            const float b0 = acc[4 * j + x], b1 = acc[4 * j + 2 + x];
            acc[4 * j + x] = fmaf(b0, m00, b1 * m01);
            acc[4 * j + 2 + x] = fmaf(b0, m10, b1 * m11);
          }
          if (j == CPOLL - 1 || j == 19) asm volatile("" : "+f"(acc[4 * j]), "+f"(acc[4 * j + 1]), "+f"(acc[4 * j + 2]), "+f"(acc[4 * j + 3])::"memory");
        }
        {
          uint32_t it = 0;
          while (__any_sync(0xffffffffu, tg[0] != tag || tg[1] != tag || tg[2] != tag)) {
#pragma unroll
            for (int i = 0; i < 3; i++)
              if (tg[i] != tag) tg[i] = rec_ld(ep - 4 * i * DM, ev[i].x, ev[i].y);
            trap_if(++it > SPIN_LIMIT);
          }
          c = cfma(p640, cfma(p640, ev[2], ev[1]), ev[0]);
          c = cmul(c, p160q);
          c.x += __shfl_xor_sync(0xffffffffu, c.x, 1); c.y += __shfl_xor_sync(0xffffffffu, c.y, 1);
          c.x += __shfl_xor_sync(0xffffffffu, c.x, 2); c.y += __shfl_xor_sync(0xffffffffu, c.y, 2);
        }
        if (tid == 0) TS(4 + 8 * l);
        if (HOLD1 && wg == 1 && l == 1 && has2) mbar_wait(bars + 8 * HOLD1);
        const uint32_t c0 = (uint32_t)clock(), tm = (tid & 7) == 4 * side + w;
        c = cfma(pLq, c, ex);
        float2 hh = make_float2(fmaf(c.x, m00, c.y * m01), fmaf(c.x, m10, c.y * m11));
        uint8_t* hb = g_h + (10 * wg + 2 * GP) * 8192 + (4 * side + w) * 1024 + (tid_opaque() & 31) * 4;
#pragma unroll
        for (int j4 = 0; j4 < 5; j4++) {
          if (PACE && j4 > 0 && wg == 1 && l == 1) { while (__any_sync(0xffffffffu, (uint32_t)clock() - c0 < PACE * j4)) {} }
          const int ng = 20 * T1 + 4 * j4;
          uint8_t* hp = hb + (size_t)(ng >> 3) * 163840 + (ng & 7) * 128;
#pragma unroll
          for (int jj = 0; jj < 4; jj++) {
            const int j = 4 * j4 + jj;
            const float2 h0 = cfma(lamc, hh, make_float2(acc[4 * j + 0], acc[4 * j + 2]));
            hh = cfma(lamc, h0, make_float2(acc[4 * j + 1], acc[4 * j + 3]));
            if (j4 < 4 || !last) {
              *(uint32_t*)(hp + jj * 128) = tag_word(pack_bf16(h0.x, hh.x), tm, 1 - l);
              *(uint32_t*)(hp + jj * 128 + 8192) = tag_word(pack_bf16(h0.y, hh.y), tm, 1 - l);
            }
          }
        }
        if (l == 0) mbar_arrive(bars + 8 * (B_HST + wg));
        if (tid == 0) TS(5 + 8 * l);
        if (tid == 128) TS(l ? 25 : 19);
        if (l == 0 && wid == 4) {
          mbar_wait(bars + 8 * B_HST);
          mbar_wait(bars + 8 * (B_HST + 1));
          if ((tid & 31) < 4) h_release(0, T1, tid & 3);
          __syncwarp();
          if (tid == 128) { mbar_arrive(bars + 8 * B_REL); TS(6); }
        }
      }
      if (l == 0) {
        ROLE(role)
        if (has2) {
          CvCtx cc;
          mbar_wait(bars + 8 * B_CTAB);
          cv_setup(cc);
          mbar_wait(bars + 8 * (B_G1DONE + 9));
#pragma unroll 1
          for (int c = (wg + 2) & 3; c < 5; c += 4) conv_channel(c, cc);
          if ((tid & 127) == 0) TS(wg == 2 ? 32 : (wg == 3 ? 50 : 7 + wg));
        }
      }
      if (wg >= 2) break;
    }
    if (wg < 2 && (role >> 16)) {
      const int ln = tid_opaque() & 31;
      const uint8_t* src = g_h + ((role >> 8) & 63) * 163840;
      uint32_t ph = 0;
      if (wg == 0) {
        mbar_wait(bars + 8 * (B_G1DONE + 19));
        if (SPEC0 + SPECW) __nanosleep(SPEC0 + SPECW * w);
        if (tid == 0) TS(23);
        if (!SPLITI && w < 3 && elect_one()) { mbar_expect_tx(bars + 8 * (B_XV + w + 4), G2_XB); }
      }
#pragma unroll 1
      for (int k = 10 * wg + w; k < 10 * wg + 10; k += 4) {
        if (k < (SPLITI ? S2 : 4) && elect_one()) {
          mbar_expect_tx(bars + 8 * (B_XV + k), G2_XB);
          bulk_g2s(sb + k * G2_XB, src + k * 8192, G2_XB, bars + 8 * (B_XV + k));
          if (!SPLITI && k < 3) bulk_g2s(sb + (k + 4) * G2_XB, src + (k + 4) * 8192, G2_XB, bars + 8 * (B_XV + k + 4));
        }
        validate_block(bars + 8 * (B_XV + k), bars + 8 * (B_G2FULL + 20 + k), sb + (k % S2) * G2_XB, src + k * 8192,
                       (ln & 7) * 1028 + (ln >> 3) * 32, bars + 8 * (B_RETRY + wid), ph);
      }
    }
    if (wg == 3) {
    ROLE(role)
    const int pw = wid & 3, gpc = 2 * min(m2 >> 3, 3) + (dg >> 1);
    mbar_wait(bars + 8 * B_EP);
    const unsigned tag = lds32(sb + EP_OFF + 20);
    if (pw == 0) {
      if (elect_one()) {
#pragma unroll 1
        for (int l = 0; l < 2; l++) {
          uint32_t dst = sb;
          if (l == 1) {
            dst = sb + G2_WOFF;
#pragma unroll 1
            for (int k = 0; k < 10; k++) {
              mbar_wait(k > 4 ? bars + 8 * (B_G1DONE + 5 + k) : (has2 ? bars + 8 * (B_G2DONE + 14 + min(k, 3)) : bars + 8 * (B_G1DONE + 9)));
              mbar_expect_tx(bars + 8 * (B_G1FULL + 10 + k), 16384);
              tma5(dst, &p.mB, 64 * k, 0, 0, 4 * side, 2 * GP, bars + 8 * (B_G1FULL + 10 + k));
              dst += 16384; if (k == 4) dst = sb + G2_WOFF;
            }
          }
          if (has2) {
            const uint32_t fb2 = bars + 8 * (B_G2FULL + 20 * l), wb2 = bars + 8 * (B_G2DONE + 20 * l - S2);
            dst = sb + G2_WOFF + (WTAIL ? 4 * l * G2_WB : 0);
            int kc = 0;
#pragma unroll 1
            for (int k = 0; k < 20; k++) {
              mbar_wait(k >= S2 ? wb2 + 8 * k : bars + 8 * (l ? B_G1DONE + (WTAIL ? (k < 3 ? 15 + k : 13 + k) : 19) : (k == 5 ? B_XFREE : (k == 6 ? B_SFREE : B_REL))));
              mbar_expect_tx(fb2 + 8 * k, G2_WB);
              tma5(dst, &p.mCre + (k & 1), kc, 0, 0, 0, 10 * dg, fb2 + 8 * k);
              kc += (k & 1) << 7; if (k == 9) kc = 64;
              dst += G2_WB; if (dst == sb + G2_WOFF + S2 * G2_WB) dst = sb + G2_WOFF;
            }
          }
        }
      }
    } else if (pw == 1) {
#pragma unroll 1
      for (int l = 0; l < 2; l++) {
        if (l == 1) {
          mbar_wait(bars + 8 * (has2 ? B_G2DONE + 19 : B_G1DONE + 9));
          if (has2) mbar_wait(bars + 8 * B_UST);
          cnt_poll(&g_ucnt[gpc * 32], 128 * tag);
          fence_async_global();
          if (elect_one()) {
            TS(20);
            const int bytes = last ? 16384 : 20480;
            const uint8_t* src = g_u + T1 * 204800;
            uint32_t dst = sb + X1_OFF;
#pragma unroll 1
            for (int k = 0; k < 10; k++) {
              if (k > 4) mbar_wait(bars + 8 * (B_G1DONE + 5 + k));
              mbar_expect_tx(bars + 8 * (B_G1FULL + 10 + k), bytes);
              bulk_g2s(dst, src, bytes, bars + 8 * (B_G1FULL + 10 + k));
              src += 20480; dst += 20480; if (dst == sb + G_OFF) dst = sb; if (k == 4) dst = sb + X1_OFF;
            }
          }
          __syncwarp();
        }
        if (has2) {
          if (l == 0) {
            mbar_wait(bars + 8 * B_REL);
            cnt_poll(&g_hcnt[gpc * 32], 40 * tag);
            fence_async_global();
          }
          if (elect_one()) {
            if (l == 0) TS(21);
            const uint32_t fb2 = bars + 8 * (l ? B_XV : B_G2FULL), wb2 = bars + 8 * (B_G2DONE + 20 * l - S2);
            const uint8_t* src = g_h + m2 * 163840 + l * S2 * 8192;
            uint32_t dst = sb;
#pragma unroll 1
            for (int k = l * S2; k < 20; k++) {
              if (k >= 5) mbar_wait(k >= S2 ? wb2 + 8 * k : bars + 8 * B_SFREE);
              mbar_expect_tx(fb2 + 8 * k, G2_XB);
              bulk_g2s(dst, src, G2_XB, fb2 + 8 * k);
              src += 8192; dst += G2_XB; if (dst == sb + S2 * G2_XB) dst = sb;
            }
          }
          __syncwarp();
        }
      }
    } else if (pw == 2) {
#pragma unroll 1
      for (int l = 0; l < 2; l++) {
        if (l == 1) {
          if (has2) {
            mbar_wait(bars + 8 * B_UST);
            if (lane < 8) red_rel(&g_ucnt[lane * 32]);
            __syncwarp();
            if (lane == 0) TS(38);
          }
          float xa[2], xb[2];
          mbar_wait(bars + 8 * (B_G1FULL + 11));
          stat_table<1>(T1, tag, 4, g_stats, g_stats, xa, xb);
          mbar_arrive(bars + 8 * (B_STAB + 1));
        }
        if (l == 0 && has2 && elect_one()) {
#pragma unroll 1
          for (int i = 0; i < 5; i++) {
            const int c = i < 3 ? i : 7 - i;
            mbar_wait(bars + 8 * (B_CVDONE + c));
            bulk_s2g(g_G + (cch0 + 32 * c) * 4096, cv_stage(c), 4096);
          }
          asm volatile("cp.async.bulk.commit_group;" ::: "memory");
          asm volatile("cp.async.bulk.wait_group.read 0;" ::: "memory");
          mbar_arrive(bars + 8 * B_SFREE);
          asm volatile("cp.async.bulk.wait_group 0;" ::: "memory");
          TS(48);
          fence_async_global();
          asm volatile("fence.acq_rel.gpu;" ::: "memory");
#pragma unroll
          for (int i = 0; i < 4; i++) red_rlx(&g_gcnt[(dg * 4 + i) * 32]);
          TS(49);
          mbar_arrive(bars + 8 * (B_GO + 1));
        }
        __syncwarp();
      }
    } else if (has2) {
      mbar_wait(bars + 8 * B_REL);
      if (!CPF && elect_one()) {
        l2_prefetch(p.cre + (160 * dg + 5 * m2) * DM, 6400); l2_prefetch(p.cim + (160 * dg + 5 * m2) * DM, 6400);
      }
      mbar_wait(bars + 8 * (B_GO + 1));
      flag_poll(&g_gcnt[(dg * 4 + (m2 >> 3)) * 32], 32 * tag);
      fence_async_global();
      if (elect_one()) {
        TS(29);
        mbar_expect_tx(bars + 8 * B_GFULL, 20480);
        tma5(sb + G_OFF, &p.mG, 64 * m2, 0, 0, 0, 10 * dg, bars + 8 * B_GFULL);
      }
    }
    } else if (wg == 2 && (role >> 16)) {
      float acc[80];
      float off[2] = {mean0[0], mean0[1]};
      const unsigned tag = lds32(sb + EP_OFF + 20);
      dskip_init<true>(acc, mean0, rstd0);
      mbar_arrive(bars + 8 * B_XFREE);
      mbar_wait(bars + 8 * (B_CVDONE + 2));
      mbar_wait(bars + 8 * (B_CVDONE + 3));
#pragma unroll 1
      for (int step = 1; step < 4; step++) {
        const int l = step >> 1;
        if (step != 2) {
          uint32_t alo = desc_lo(sb, 1024), blo = desc_lo(sb + G2_WOFF, 16) + (WTAIL ? l * (G2_WB >> 2) : 0);
          uint32_t fb = bars + 8 * (B_G2FULL + 20 * l);
          fence_regs(acc);
          mbar_wait(fb);
          if (tid == 256) TS(33 + 6 * l);
#pragma unroll 1
          for (int k = 0; k < 20; k++) {
            if (l == TSL && (k & 3) == 3 && tid == 256) TS(56 + (k >> 2));
            uint32_t ok; const uint32_t nb = k < 19 ? fb + 8 : fb;
            wgmma_fence();
#pragma unroll
            for (int kk = 0; kk < 4; kk++) {
              wgmma_n160<1>(acc, alo + kk * 128, desc_hi(128, 0), blo + kk * 2, desc_hi(1024, 1));
              if (kk == 0) ok = mbar_test(nb);
            }
            wgmma_commit();
            alo += G2_XB >> 4; blo += G2_WB >> 4;
            if (alo == desc_lo(sb + S2 * G2_XB, 1024)) alo = desc_lo(sb, 1024);
            if (blo == desc_lo(sb + G_OFF, 16)) blo = desc_lo(sb + G2_WOFF, 16);
            wgmma_wait<1>();
            if (k > 0 && tid == 256) mbar_arrive(fb + 8 * (B_G2DONE - B_G2FULL - 1));
            if (!ok) mbar_wait(nb);
            fb += 8;
          }
          wgmma_wait<0>();
          fence_regs(acc);
          if (tid == 256) TS(34 + 6 * l);
          if (tid == 256) mbar_arrive(bars + 8 * (B_G2DONE + 20 * l + 19));
        }
        ROLE(role)
        const int tq = tid_opaque() & 31, n0 = 64 * m2 + 16 * w + (tq >> 2);
        stats_publish<false>(step, n0, dg, tag, acc);
        uint32_t gf[10][4];
        mbar_wait(bars + 8 * B_GFULL);
        uint32_t ga = sb + G_OFF + (8 * (tq >> 4) + (tq & 7)) * 128 + (((2 * w + ((tq >> 3) & 1)) ^ ((2 * m2) & 6) ^ (tq & 7)) << 4), gstep = 2048;
        if (step == 2) { ga = sb + DX_OFF + (8 * (tq >> 4) + (tq & 7)) * 16; gstep = 256; }
#pragma unroll
        for (int J = 0; J < 2; J++) ldsm4t(gf[J], ga + J * gstep);
        if (tid == 256) TS(35 + 6 * l);
        uint8_t* dst[2][2];
#pragma unroll
        for (int h = 0; h < 2; h++) {
          if (l == 0) {
            const int ng = 8 * m2 + 2 * w + h, T = ng / 20;
            uint8_t* ub = g_u + (T * 204800 + (ng - 20 * T) * 1024 + (tq & 2) * 64 + (tq & 28) * 4 + (tq & 1) * 8 + (5 * dg >> 1) * 20480);
            dst[h][1] = ub + ((dg & 1) ? 20480 - 512 : 0);
            dst[h][0] = ub + (dg & 1) * 512;
          } else {
            dst[h][0] = dst[h][1] = (uint8_t*)(p.out + (n_to_t(n0 + 8 * h) * DM + 160 * dg + 4 * (tq & 3)));
          }
        }
        float mean[2], rstd[2];
        stats_get(step, n0, tag, mean, rstd);
        if (tid == 256) TS(36 + 6 * l);
        off[0] += mean[0]; off[1] += mean[1];
        const float ov[2] = {step == 3 ? off[0] : 0.f, step == 3 ? off[1] : 0.f};
#pragma unroll
        for (int J = 0; J < 10; J++) {
          if (J + 2 < 10) ldsm4t(gf[J + 2 < 10 ? J + 2 : 0], ga + (J + 2) * gstep);
#pragma unroll
          for (int x = 0; x < 8; x++) {
            const int h = (x >> 1) & 1;
            const uint32_t gwd = gf[J][x >> 1];
            const float t = fmaf(rstd[h], (x & 1) ? bf_hi(gwd) : bf_lo(gwd), 1.f);
            acc[8 * J + x] = fmaf(acc[8 * J + x], t, fmaf(-mean[h], t, ov[h]));
          }
#pragma unroll
          for (int h = 0; h < 2; h++) {
            if (step == 1)
              *(uint2*)(dst[h][(J >> 1) & 1] + (J >> 2) * 20480 + (J & 3) * 256) =
                  make_uint2(pack_bf16(acc[8 * J + 2 * h], acc[8 * J + 2 * h + 1]), pack_bf16(acc[8 * J + 4 + 2 * h], acc[8 * J + 5 + 2 * h]));
            if (step == 3)
              *(float4*)(dst[h][0] + 64 * J) = make_float4(acc[8 * J + 2 * h], acc[8 * J + 2 * h + 1], acc[8 * J + 4 + 2 * h], acc[8 * J + 5 + 2 * h]);
          }
          __syncwarp();
        }
        if (step == 1) {
          mbar_arrive(bars + 8 * B_UST);
          if (tid == 256) TS(37);
          for (int n = tid & 127; n < 160; n += 128) {
            const int d = 16 * (n >> 4) + 4 * ((n >> 1) & 3) + 2 * ((n >> 3) & 1) + (n & 1);
            const uint32_t dw = lds32(sb + DTAB_OFF + 2 * (d & ~1)), dd = __byte_perm(dw, dw, (d & 1) ? 0x3232 : 0x1010);
            sts128(sb + DX_OFF + 16 * n, make_uint4(dd, dd, dd, dd));
          }
          bar_sync(3, 128);
        } else if (step == 2) {
          if (tid == 256) TS(22);
          mbar_wait(bars + 8 * (B_G1FULL + 11));
          float xa[2], xb[2];
          stat_table<1>(T1, tag, w, g_stats, g_stats, xa, xb);
          mbar_arrive(bars + 8 * (B_STAB + 1));
          if (tid == 256) TS(27);
        } else {
          if (tid == 256) {
            TS(43);
            if (m2 == 31 && dg == 3) asm volatile("st.relaxed.gpu.global.u32 [%0], %1;" ::"l"(g_epoch), "r"(tag + 1) : "memory");
          }
        }
      }
    }
  }
}

typedef CUresult (*EncFn)(CUtensorMap*, CUtensorMapDataType, cuuint32_t, void*, const cuuint64_t*, const cuuint64_t*,
                          const cuuint32_t*, const cuuint32_t*, CUtensorMapInterleave, CUtensorMapSwizzle,
                          CUtensorMapL2promotion, CUtensorMapFloatOOBfill);

void encode(EncFn fn, CUtensorMap* m, const void* ptr, int rank, const cuuint64_t* dims, const cuuint64_t* strides, const cuuint32_t* box,
            CUtensorMapSwizzle swz = CU_TENSOR_MAP_SWIZZLE_128B, int prom = 2) {
  cuuint32_t es[5] = {1, 1, 1, 1, 1};
  fn(m, CU_TENSOR_MAP_DATA_TYPE_BFLOAT16, rank, (void*)ptr, dims, strides, box, es, CU_TENSOR_MAP_INTERLEAVE_NONE,
     swz, (CUtensorMapL2promotion)prom, CU_TENSOR_MAP_FLOAT_OOB_FILL_NONE);
}

}

extern "C" void kernel_launch(void* const* d_in, const int* in_sizes, int n_in, void* d_out, int out_size) {
  (void)in_sizes; (void)n_in; (void)out_size;
  Params p;
  typedef const __nv_bfloat16* BP;
  p.x = (BP)d_in[0]; p.lre = (BP)d_in[1]; p.lim = (BP)d_in[2]; p.bre = (BP)d_in[3]; p.bim = (BP)d_in[4];
  p.cre = (BP)d_in[5]; p.cim = (BP)d_in[6]; p.logdt = (BP)d_in[7]; p.dskip = (BP)d_in[8];
  p.k = (BP)d_in[10]; p.v = (BP)d_in[11]; p.shiftk = (BP)d_in[12]; p.ssmk = (BP)d_in[13]; p.ssmD = (BP)d_in[14];
  p.out = (float*)d_out;
  for (int sm = 0; sm < 132; sm++) {
    const int tpc = sm >> 1, side = sm & 1;
    int gpc, gi;
    if (tpc < 32) { gpc = tpc & 7; gi = tpc >> 3; }
    else if (tpc < 60) { gpc = 1 + (tpc - 32) % 7; gi = 4 + (tpc - 32) / 7; }
    else if (tpc < 62) { gpc = tpc - 54; gi = 8; }
    else { gpc = 0; gi = tpc - 58; }
    const int pos = 8 * gpc + gi + (gpc == 7 ? 1 : 0);
    int T1, GP;
    if (pos < 52) { const int hh = pos / 26, x = pos - 26 * hh; T1 = x >> 1; GP = 2 * hh + (x & 1); }
    else { T1 = pos - 52; GP = 4; }
    const int m2 = 8 * (gpc >> 1) + gi, dg = 2 * (gpc & 1) + side;
    p.role[sm] = pos == 65 ? -1 : (T1 | (GP << 4) | (side << 7) | (m2 << 8) | (dg << 14) | ((gi < 8) << 16));
  }
  void* fnp = nullptr;
  cudaDriverEntryPointQueryResult qr;
  cudaGetDriverEntryPoint("cuTensorMapEncodeTiled", &fnp, cudaEnableDefault, &qr);
  EncFn fn = (EncFn)fnp;
  void* gG = nullptr;
  cudaGetSymbolAddress(&gG, g_G);
  void* gKV = nullptr;
  cudaGetSymbolAddress(&gKV, g_kv);
  {
    cuuint64_t dims[5] = {32, 32, 10, 32, 4}, st[4] = {20480, 2048, 64, 655360}; cuuint32_t box[5] = {32, 35, 2, 1, 1};
    encode(fn, &p.mU, gKV, 5, dims, st, box, CU_TENSOR_MAP_SWIZZLE_NONE, 1);
  }
  const cuuint64_t RB = DM * 2;
  {
    p.swap = p.bim < p.bre;
    const char* lo = (const char*)(p.swap ? p.bim : p.bre); const char* hi = (const char*)(p.swap ? p.bre : p.bim);
    cuuint64_t dims[5] = {640, 8, 2, 8, 10}, st[4] = {RB, (cuuint64_t)(hi - lo), 8 * RB, 64 * RB}; cuuint32_t box[5] = {64, 8, 2, 4, 2};
    encode(fn, &p.mB, lo, 5, dims, st, box);
  }
  {
    cuuint64_t dims[5] = {640, 2, 4, 2, 40}, st[4] = {RB, 4 * RB, 2 * RB, 16 * RB}; cuuint32_t box[5] = {64, 2, 4, 2, 10};
    encode(fn, &p.mCre, p.cre, 5, dims, st, box); encode(fn, &p.mCim, p.cim, 5, dims, st, box);
    cuuint64_t dimg[5] = {2048, 2, 4, 2, 40}, stg[4] = {4096, 4 * 4096, 2 * 4096, 16 * 4096};
    encode(fn, &p.mG, gG, 5, dimg, stg, box);
  }
  {
    cuuint64_t dims[4] = {640, 2, 4, 900}, st[3] = {RB, 40 * RB, 2 * RB}; cuuint32_t box[4] = {64, 2, 4, 20};
    encode(fn, &p.mX, p.x, 4, dims, st, box);
    cuuint64_t diml[4] = {640, 2, 4, 16}, stl[3] = {RB, 32 * RB, 2 * RB};
    encode(fn, &p.mXl, p.x + (size_t)1920 * DM, 4, diml, stl, box);
    cuuint32_t boxt[4] = {160, 2, 4, 4};
    encode(fn, &p.mXt, p.x, 4, dims, st, boxt, CU_TENSOR_MAP_SWIZZLE_NONE);
    encode(fn, &p.mXtl, p.x + (size_t)1920 * DM, 4, diml, stl, boxt, CU_TENSOR_MAP_SWIZZLE_NONE);
    cuuint64_t dk[3] = {640, 2000, 4}, sk[2] = {RB, 16 * RB}; cuuint32_t bk[3] = {32, 19, 4}, bv[3] = {32, 17, 4};
    encode(fn, &p.mK, p.k, 3, dk, sk, bk, CU_TENSOR_MAP_SWIZZLE_NONE);
    encode(fn, &p.mV, p.v, 3, dk, sk, bv, CU_TENSOR_MAP_SWIZZLE_NONE);
  }
  cudaFuncSetAttribute(fused_kernel, cudaFuncAttributeMaxDynamicSharedMemorySize, SMEM_BYTES);
  cudaLaunchConfig_t cfg = {};
  cfg.gridDim = dim3(132); cfg.blockDim = dim3(512); cfg.dynamicSmemBytes = SMEM_BYTES; cfg.stream = cudaStreamPerThread;
  cudaLaunchKernelEx(&cfg, fused_kernel, p);
}
```

```cpp
#include <cuda_runtime.h>
#include <cuda.h>
#include <cuda_bf16.h>
#include <stdint.h>

namespace {

constexpr int SEQ = 2048, DM = 640;
constexpr int NT1 = 13;
#define EXP 0
#define WPF1 3
#define WPF2 7
#define CPOLL 10
#define KV0 1
#define TAPLATE 1
#define STG_D 3
#define STG_KK 1
#define HOLD1 0
#define SPEC0 100
#define WREL 0
#define UREL 1
#define TSL 1
#define STG0 2
#define WTAIL 1
#define PFD 1
#define TAPW 0
#define TPF 4
#define CPF 0
#define MK0 7
#define MK1 4
#define PACE 350
#define TAPN 2
#define SPLITI 1
#define SPECW 60
#define WEND B_SPEC
#define PAUSE_K 5
constexpr uint32_t SPIN_LIMIT = 1u << 22;

__device__ __align__(1024) uint8_t g_h[32 * 20 * 8192];
__device__ __align__(1024) uint8_t g_u[NT1 * 10 * 20480];
__device__ __align__(1024) uint8_t g_kv[DM * 4096];
__device__ __align__(1024) uint8_t g_G[DM * 4096];
__device__ __align__(128) uint4 g_E[2 * NT1 * DM];
__device__ __align__(128) uint4 g_stats[4 * 4 * SEQ];
__device__ __align__(128) uint4 g_sB[DM * 2];
__device__ __align__(128) unsigned g_hcnt[8 * 32];
__device__ __align__(128) unsigned g_ucnt[8 * 32];
__device__ __align__(128) unsigned g_kvcnt[16 * 32];
__device__ __align__(128) unsigned g_gcnt[16 * 32];
__device__ __align__(128) unsigned g_epoch[32] = {1};
#define TS(i) do {} while (0)

struct Params {
  CUtensorMap mX, mB, mXl, mK, mV, mXt, mXtl, mCre, mCim, mG, mU;
  const __nv_bfloat16 *x, *lre, *lim, *bre, *bim, *cre, *cim, *logdt, *dskip, *k, *v, *shiftk, *ssmk, *ssmD;
  float* out;
  int swap;
  int role[132];
};

constexpr uint32_t sb = 1024;
constexpr uint32_t G1_STAGE = 36864, G1_XOFF = 16384;
constexpr int S1 = 4;
constexpr uint32_t XT_OFF = 159744, KS_OFF = 180224, KV_PIECE = 9216;
constexpr uint32_t G2_XB = 8192, G2_WB = 20480, G2_WOFF = 57344, G_OFF = 200704;
constexpr uint32_t X1_OFF = 139264;
constexpr int S2 = 7;
constexpr uint32_t CV_OFF = KS_OFF, CV_K = 128, CV_PL = 2240, CV_U = CV_K + 4096, CV_B = KV_PIECE;
constexpr uint32_t MISC = 226304;
constexpr uint32_t BAR_OFF = MISC;
constexpr int B_G1FULL = 0, B_G1DONE = 20, B_G2FULL = 40,
              B_G2DONE = 85, B_GFULL = 125, B_EP = 126, B_CVFULL = 129  , B_STG = 134  , B_REL = 136  , B_SFREE = 138,
              B_GO = 139  , B_PUB = 147,
              B_CVDONE = 148  , B_STAB = 153  , B_XFREE = 155, B_HST = 156  , B_UST = 158,
              B_CTAB = 160, B_PREP = 161, B_XT = 162, B_KV = 163  , B_PREP2 = 84, B_PD = 168  ,
              B_XV = 173  , B_RETRY = 193  , B_SPEC = 202;
constexpr uint32_t bars = sb + BAR_OFF;
constexpr uint32_t STAB_OFF = MISC + 1648;
constexpr uint32_t CTAB_OFF = STAB_OFF + 640;
constexpr uint32_t DTAB_OFF = CTAB_OFF + 1536;
constexpr uint32_t EP_OFF = DTAB_OFF + 320;
constexpr uint32_t SO_OFF = EP_OFF + 32;
constexpr uint32_t TAP_OFF = 147456;
constexpr uint32_t MX0_OFF = TAP_OFF + 1280, MX1_OFF = G_OFF + 20480;
constexpr uint32_t DX_OFF = MX1_OFF + 2560;
constexpr uint32_t SMEM_BYTES = 232448;
static_assert(SO_OFF + 1536 <= SMEM_BYTES, "smem");

__device__ __forceinline__ void trap_if(bool c) { asm volatile("{\n.reg .pred p;\nsetp.ne.u32 p, %0, 0;\n@p trap;\n}\n" ::"r"((uint32_t)c)); }
__device__ __forceinline__ uint32_t smem_u32(const void* p) { return (uint32_t)__cvta_generic_to_shared(p); }
__device__ __forceinline__ void mbar_init(uint32_t bar, int cnt) { asm volatile("mbarrier.init.shared::cta.b64 [%0], %1;" ::"r"(bar), "r"(cnt) : "memory"); }
__device__ __forceinline__ void mbar_expect_tx(uint32_t bar, int bytes) { asm volatile("mbarrier.arrive.expect_tx.shared::cta.b64 _, [%0], %1;" ::"r"(bar), "r"(bytes) : "memory"); }
__device__ __forceinline__ void mbar_arrive(uint32_t bar) { asm volatile("mbarrier.arrive.shared::cta.b64 _, [%0];" ::"r"(bar) : "memory"); }
__device__ __forceinline__ bool elect_one() {
  uint32_t e; asm volatile("{\n.reg .pred P;\nelect.sync _|P, 0xffffffff;\nselp.u32 %0, 1, 0, P;\n}\n" : "=r"(e)); return e != 0;
}
__device__ __forceinline__ void mbar_wait(uint32_t bar) {
  asm volatile(
      "{\n.reg .pred p;\n.reg .u32 c;\nmov.u32 c, 0;\n"
      "W_%=:\nmbarrier.try_wait.parity.shared::cta.b64 p, [%0], 0;\n@p bra D_%=;\n"
      "add.u32 c, c, 1;\nsetp.lt.u32 p, c, %1;\n@p bra W_%=;\ntrap;\nD_%=:\n}\n" ::"r"(bar), "n"(SPIN_LIMIT) : "memory");
}
__device__ __forceinline__ uint32_t mbar_test(uint32_t bar) {
  uint32_t ok;
  asm volatile("{\n.reg .pred p;\nmbarrier.test_wait.parity.shared::cta.b64 p, [%1], 0;\nselp.u32 %0, 1, 0, p;\n}\n" : "=r"(ok) : "r"(bar) : "memory");
  return ok;
}
__device__ __forceinline__ void tma3(uint32_t dst, const CUtensorMap* m, int c0, int c1, int c2, uint32_t bar) {
  asm volatile("cp.async.bulk.tensor.3d.shared::cluster.global.mbarrier::complete_tx::bytes [%0], [%1, {%3,%4,%5}], [%2];"
               ::"r"(dst), "l"(m), "r"(bar), "r"(c0), "r"(c1), "r"(c2) : "memory");
}
__device__ __forceinline__ void tma4(uint32_t dst, const CUtensorMap* m, int c0, int c1, int c2, int c3, uint32_t bar) {
  asm volatile("cp.async.bulk.tensor.4d.shared::cluster.global.mbarrier::complete_tx::bytes [%0], [%1, {%3,%4,%5,%6}], [%2];"
               ::"r"(dst), "l"(m), "r"(bar), "r"(c0), "r"(c1), "r"(c2), "r"(c3) : "memory");
}
__device__ __forceinline__ void tma5(uint32_t dst, const CUtensorMap* m, int c0, int c1, int c2, int c3, int c4, uint32_t bar) {
  asm volatile("cp.async.bulk.tensor.5d.shared::cluster.global.mbarrier::complete_tx::bytes [%0], [%1, {%3,%4,%5,%6,%7}], [%2];"
               ::"r"(dst), "l"(m), "r"(bar), "r"(c0), "r"(c1), "r"(c2), "r"(c3), "r"(c4) : "memory");
}
__device__ __forceinline__ void bulk_g2s(uint32_t dst, const void* src, int bytes, uint32_t bar) {
  asm volatile("cp.async.bulk.shared::cluster.global.mbarrier::complete_tx::bytes [%0], [%1], %2, [%3];"
               ::"r"(dst), "l"(src), "r"(bytes), "r"(bar) : "memory");
}
__device__ __forceinline__ void bulk_s2g(void* dst, uint32_t src, int bytes) {
  asm volatile("cp.async.bulk.global.shared::cta.bulk_group [%0], [%1], %2;" ::"l"(dst), "r"(src), "r"(bytes) : "memory");
}
__device__ __forceinline__ void l2_prefetch(const void* src, int bytes) {
  asm volatile("cp.async.bulk.prefetch.L2.global [%0], %1;" ::"l"(src), "r"(bytes) : "memory");
}
__device__ __forceinline__ void wgmma_fence() { asm volatile("wgmma.fence.sync.aligned;" ::: "memory"); }
__device__ __forceinline__ void wgmma_commit() { asm volatile("wgmma.commit_group.sync.aligned;" ::: "memory"); }
template <int N> __device__ __forceinline__ void wgmma_wait() { asm volatile("wgmma.wait_group.sync.aligned %0;" ::"n"(N) : "memory"); }
__host__ __device__ constexpr uint32_t desc_lo(uint32_t addr, uint32_t lbo) { return ((addr & 0x3FFFF) >> 4) | ((lbo >> 4) << 16); }
__host__ __device__ constexpr uint32_t desc_hi(uint32_t sbo, uint32_t swz) { return (sbo >> 4) | (swz << 30); }
__device__ __forceinline__ void bar_sync(int id, int n) { asm volatile("bar.sync %0, %1;" ::"r"(id), "r"(n) : "memory"); }
__device__ __forceinline__ uint32_t lds32(uint32_t a) { uint32_t v; asm volatile("ld.shared.u32 %0, [%1];" : "=r"(v) : "r"(a) : "memory"); return v; }
__device__ __forceinline__ float2 lds64f(uint32_t a) { float2 v; asm volatile("ld.shared.v2.f32 {%0,%1}, [%2];" : "=f"(v.x), "=f"(v.y) : "r"(a) : "memory"); return v; }
__device__ __forceinline__ float4 lds128f(uint32_t a) { float4 v; asm volatile("ld.shared.v4.f32 {%0,%1,%2,%3}, [%4];" : "=f"(v.x), "=f"(v.y), "=f"(v.z), "=f"(v.w) : "r"(a) : "memory"); return v; }
__device__ __forceinline__ void ldsm4t(uint32_t (&r)[4], uint32_t a) {
  asm volatile("ldmatrix.sync.aligned.m8n8.x4.trans.shared.b16 {%0,%1,%2,%3}, [%4];" : "=r"(r[0]), "=r"(r[1]), "=r"(r[2]), "=r"(r[3]) : "r"(a) : "memory");
}
__device__ __forceinline__ uint4 ldv128(const void* a) { uint4 v; asm volatile("ld.global.nc.v4.u32 {%0,%1,%2,%3}, [%4];" : "=r"(v.x), "=r"(v.y), "=r"(v.z), "=r"(v.w) : "l"(a) : "memory"); return v; }
__device__ __forceinline__ uint2 ldv64(const void* a) { uint2 v; asm volatile("ld.global.nc.v2.u32 {%0,%1}, [%2];" : "=r"(v.x), "=r"(v.y) : "l"(a) : "memory"); return v; }
__device__ __forceinline__ uint32_t ldv16(const void* a) { uint32_t v; asm volatile("ld.global.nc.u16 %0, [%1];" : "=r"(v) : "l"(a) : "memory"); return v; }
__device__ __forceinline__ void sts128(uint32_t a, uint4 v) { asm volatile("st.shared.v4.u32 [%0], {%1,%2,%3,%4};" ::"r"(a), "r"(v.x), "r"(v.y), "r"(v.z), "r"(v.w) : "memory"); }
__device__ __forceinline__ void sts32(uint32_t a, uint32_t v) { asm volatile("st.shared.u32 [%0], %1;" ::"r"(a), "r"(v) : "memory"); }
__device__ __forceinline__ void sts64f(uint32_t a, float x, float y) { asm volatile("st.shared.v2.f32 [%0], {%1,%2};" ::"r"(a), "f"(x), "f"(y) : "memory"); }
__device__ __forceinline__ void red_rlx(unsigned* p) { asm volatile("red.relaxed.gpu.global.add.u32 [%0], 1;" ::"l"(p) : "memory"); }
__device__ __forceinline__ void red_rel(unsigned* p) { asm volatile("red.release.gpu.global.add.u32 [%0], 1;" ::"l"(p) : "memory"); }
__device__ __forceinline__ void fence_async_global() { asm volatile("fence.proxy.async.global;" ::: "memory"); }
__device__ __forceinline__ void fence_async_smem() { asm volatile("fence.proxy.async.shared::cta;" ::: "memory"); }
__device__ __forceinline__ void rec_st(uint4* p, float a, float b, unsigned tag) {
  asm volatile("{\n.reg .b128 t;\n.reg .b64 lo, hi;\nmov.b64 lo, {%1,%2};\nmov.b64 hi, {%3,%3};\nmov.b128 t, {lo,hi};\n"
               "st.relaxed.gpu.global.b128 [%0], t;\n}\n" ::"l"(p), "r"(__float_as_uint(a)), "r"(__float_as_uint(b)), "r"(tag) : "memory");
}
__device__ __forceinline__ unsigned rec_ld(const uint4* p, float& a, float& b) {
  unsigned x, y, t;
  asm volatile("{\n.reg .b128 t;\n.reg .b64 lo, hi;\n.reg .b32 u;\nld.relaxed.gpu.global.b128 t, [%3];\nmov.b128 {lo,hi}, t;\n"
               "mov.b64 {%0,%1}, lo;\nmov.b64 {%2,u}, hi;\n}\n" : "=r"(x), "=r"(y), "=r"(t) : "l"(p) : "memory");
  a = __uint_as_float(x); b = __uint_as_float(y);
  return t;
}
__device__ __forceinline__ unsigned ld_rlx(const unsigned* p) { unsigned v; asm volatile("ld.relaxed.gpu.global.u32 %0, [%1];" : "=r"(v) : "l"(p) : "memory"); return v; }
__device__ __forceinline__ void flag_poll(const unsigned* p, unsigned target) {
  uint32_t it = 0;
  while (!__all_sync(0xffffffffu, (int)(ld_rlx(p) - target) >= 0)) { trap_if(++it > SPIN_LIMIT); }
  asm volatile("fence.acquire.gpu;" ::: "memory");
}
__device__ __forceinline__ void cnt_poll(const unsigned* p, unsigned target) {
  unsigned a = ld_rlx(p); __nanosleep(100);
  unsigned b = ld_rlx(p); __nanosleep(100);
  unsigned c = ld_rlx(p);
  uint32_t it = 0;
  while (true) {
    if (__all_sync(0xffffffffu, (int)(a - target) >= 0)) break;
    a = ld_rlx(p);
    if (__all_sync(0xffffffffu, (int)(b - target) >= 0)) break;
    b = ld_rlx(p);
    if (__all_sync(0xffffffffu, (int)(c - target) >= 0)) break;
    c = ld_rlx(p);
    trap_if(++it > SPIN_LIMIT);
  }
  asm volatile("fence.acquire.gpu;" ::: "memory");
}
__device__ __forceinline__ void validate_block(uint32_t bar, uint32_t full, uint32_t dst, const uint8_t* src, uint32_t woff, uint32_t rb, uint32_t& ph) {
  uint32_t it = 0, par = 0;
  while (true) {
    uint32_t ok, spins = 0;
    do {
      asm volatile("{\n.reg .pred p;\nmbarrier.try_wait.parity.shared::cta.b64 p, [%1], %2;\nselp.u32 %0, 1, 0, p;\n}\n" : "=r"(ok) : "r"(bar), "r"(par) : "memory");
      trap_if(++spins > SPIN_LIMIT);
    } while (!__all_sync(0xffffffffu, ok));
    uint32_t bad = 0;
#pragma unroll
    for (int i = 0; i < 8; i++) bad |= lds32(dst + woff + 128 * i);
    if (!__any_sync(0xffffffffu, bad & 1)) break;
    if (elect_one()) { mbar_expect_tx(rb, 8192); bulk_g2s(dst, src, 8192, rb); }
    bar = rb; par = ph; ph ^= 1;
    trap_if(++it > 100000);
  }
  if ((threadIdx.x & 31) == 0) mbar_arrive(full);
}
__device__ __forceinline__ uint32_t tag_word(uint32_t v, uint32_t m, uint32_t par) {
  uint32_t r; asm("lop3.b32 %0, %1, %2, %3, 0xb8;" : "=r"(r) : "r"(v), "r"(m), "r"(par)); return r;
}
__device__ __forceinline__ void h_release(int idx, int T, int i) {
  const int Q = (i & 2) ? (T + 2) / 3 - 1 : T / 3;
  if (Q >= 0 && Q < 4 && ((i & 2) == 0 || T % 3 == 0)) red_rel(&g_hcnt[(idx * 8 + 2 * Q + (i & 1)) * 32]);
}
__device__ __forceinline__ uint32_t pack_bf16(float lo, float hi) {
  uint32_t r; asm("cvt.rn.bf16x2.f32 %0, %1, %2;" : "=r"(r) : "f"(hi), "f"(lo)); return r;
}
__device__ __forceinline__ float bf_lo(uint32_t w) { return __uint_as_float(w << 16); }
__device__ __forceinline__ float bf_hi(uint32_t w) { return __uint_as_float(w & 0xffff0000u); }
__device__ __forceinline__ uint32_t hmul2(uint32_t a, uint32_t b) {
  __nv_bfloat162 r = __hmul2_rn(*(__nv_bfloat162*)&a, *(__nv_bfloat162*)&b); return *(uint32_t*)&r;
}
__device__ __forceinline__ uint32_t hadd2(uint32_t a, uint32_t b) {
  __nv_bfloat162 r = __hadd2_rn(*(__nv_bfloat162*)&a, *(__nv_bfloat162*)&b); return *(uint32_t*)&r;
}
__device__ __forceinline__ float2 cmul(float2 a, float2 b) { return make_float2(a.x * b.x - a.y * b.y, a.x * b.y + a.y * b.x); }
__device__ __forceinline__ float2 cfma(float2 a, float2 b, float2 c) {
  return make_float2(fmaf(a.x, b.x, fmaf(-a.y, b.y, c.x)), fmaf(a.x, b.y, fmaf(a.y, b.x, c.y)));
}
template <int N> __device__ __forceinline__ void fence_regs(float (&a)[N]) {
#pragma unroll
  for (int i = 0; i < N; i++) asm volatile("" : "+f"(a[i])::"memory");
}
__device__ __forceinline__ int tid_opaque() { int t; asm volatile("mov.u32 %0, %%tid.x;" : "=r"(t)); return t; }
struct Role { int T1, GP, side, m2, dg, cch0; bool last, has2; };
__device__ __forceinline__ Role unpack_role(int x) {
  Role r; r.T1 = x & 15; r.GP = (x >> 4) & 7; r.side = (x >> 7) & 1; r.m2 = (x >> 8) & 63; r.dg = (x >> 14) & 3;
  r.has2 = (x >> 16) & 1; r.last = r.T1 == NT1 - 1; r.cch0 = 160 * r.dg + r.m2; return r;
}
__device__ __forceinline__ Role fresh_role(int x) { asm volatile("" : "+r"(x)); return unpack_role(__shfl_sync(0xffffffffu, x, 0)); }
#define ROLE(x) const Role R_ = fresh_role(x); const int T1 = R_.T1, GP = R_.GP, side = R_.side, m2 = R_.m2, dg = R_.dg, cch0 = R_.cch0; \
  const bool last = R_.last, has2 = R_.has2; (void)T1; (void)GP; (void)side; (void)m2; (void)dg; (void)cch0; (void)last; (void)has2;
__device__ __forceinline__ int n_to_t(int n) {
  int T = n / 160, nl = n - T * 160;
  int L = (T == NT1 - 1) ? 32 : 40;
  return T * 160 + L * ((nl & 7) >> 1) + 2 * (nl >> 3) + (nl & 1);
}

template<int TA> __device__ __forceinline__ void wgmma_n160(float (&d)[80], uint32_t alo, uint32_t ahi, uint32_t blo, uint32_t bhi){
  asm volatile("{\n.reg .b64 da, db;\nmov.b64 da, {%80,%81};\nmov.b64 db, {%82,%83};\n"
    "wgmma.mma_async.sync.aligned.m64n160k16.f32.bf16.bf16 {%0, %1, %2, %3, %4, %5, %6, %7, %8, %9, %10, %11, %12, %13, %14, %15, %16, %17, %18, %19, %20, %21, %22, %23, %24, %25, %26, %27, %28, %29, %30, %31, %32, %33, %34, %35, %36, %37, %38, %39, %40, %41, %42, %43, %44, %45, %46, %47, %48, %49, %50, %51, %52, %53, %54, %55, %56, %57, %58, %59, %60, %61, %62, %63, %64, %65, %66, %67, %68, %69, %70, %71, %72, %73, %74, %75, %76, %77, %78, %79}, da, db, 1, 1, 1, %84, 0;\n}\n"
    : "+f"(d[0]), "+f"(d[1]), "+f"(d[2]), "+f"(d[3]), "+f"(d[4]), "+f"(d[5]), "+f"(d[6]), "+f"(d[7]), "+f"(d[8]), "+f"(d[9]), "+f"(d[10]), "+f"(d[11]), "+f"(d[12]), "+f"(d[13]), "+f"(d[14]), "+f"(d[15]), "+f"(d[16]), "+f"(d[17]), "+f"(d[18]), "+f"(d[19]), "+f"(d[20]), "+f"(d[21]), "+f"(d[22]), "+f"(d[23]), "+f"(d[24]), "+f"(d[25]), "+f"(d[26]), "+f"(d[27]), "+f"(d[28]), "+f"(d[29]), "+f"(d[30]), "+f"(d[31]), "+f"(d[32]), "+f"(d[33]), "+f"(d[34]), "+f"(d[35]), "+f"(d[36]), "+f"(d[37]), "+f"(d[38]), "+f"(d[39]), "+f"(d[40]), "+f"(d[41]), "+f"(d[42]), "+f"(d[43]), "+f"(d[44]), "+f"(d[45]), "+f"(d[46]), "+f"(d[47]), "+f"(d[48]), "+f"(d[49]), "+f"(d[50]), "+f"(d[51]), "+f"(d[52]), "+f"(d[53]), "+f"(d[54]), "+f"(d[55]), "+f"(d[56]), "+f"(d[57]), "+f"(d[58]), "+f"(d[59]), "+f"(d[60]), "+f"(d[61]), "+f"(d[62]), "+f"(d[63]), "+f"(d[64]), "+f"(d[65]), "+f"(d[66]), "+f"(d[67]), "+f"(d[68]), "+f"(d[69]), "+f"(d[70]), "+f"(d[71]), "+f"(d[72]), "+f"(d[73]), "+f"(d[74]), "+f"(d[75]), "+f"(d[76]), "+f"(d[77]), "+f"(d[78]), "+f"(d[79])
    : "r"(alo), "r"(ahi), "r"(blo), "r"(bhi), "n"(TA));
}
__device__ __forceinline__ void wgmma_rs_n160(float (&d)[80], uint32_t a0, uint32_t a1, uint32_t a2, uint32_t a3, uint32_t blo){
  asm volatile("{\n.reg .b64 db;\nmov.b64 db, {%84,8};\nwgmma.mma_async.sync.aligned.m64n160k16.f32.bf16.bf16 {%0, %1, %2, %3, %4, %5, %6, %7, %8, %9, %10, %11, %12, %13, %14, %15, %16, %17, %18, %19, %20, %21, %22, %23, %24, %25, %26, %27, %28, %29, %30, %31, %32, %33, %34, %35, %36, %37, %38, %39, %40, %41, %42, %43, %44, %45, %46, %47, %48, %49, %50, %51, %52, %53, %54, %55, %56, %57, %58, %59, %60, %61, %62, %63, %64, %65, %66, %67, %68, %69, %70, %71, %72, %73, %74, %75, %76, %77, %78, %79}, {%80,%81,%82,%83}, db, 1, 1, 1, 0;\n}\n"
    : "+f"(d[0]), "+f"(d[1]), "+f"(d[2]), "+f"(d[3]), "+f"(d[4]), "+f"(d[5]), "+f"(d[6]), "+f"(d[7]), "+f"(d[8]), "+f"(d[9]), "+f"(d[10]), "+f"(d[11]), "+f"(d[12]), "+f"(d[13]), "+f"(d[14]), "+f"(d[15]), "+f"(d[16]), "+f"(d[17]), "+f"(d[18]), "+f"(d[19]), "+f"(d[20]), "+f"(d[21]), "+f"(d[22]), "+f"(d[23]), "+f"(d[24]), "+f"(d[25]), "+f"(d[26]), "+f"(d[27]), "+f"(d[28]), "+f"(d[29]), "+f"(d[30]), "+f"(d[31]), "+f"(d[32]), "+f"(d[33]), "+f"(d[34]), "+f"(d[35]), "+f"(d[36]), "+f"(d[37]), "+f"(d[38]), "+f"(d[39]), "+f"(d[40]), "+f"(d[41]), "+f"(d[42]), "+f"(d[43]), "+f"(d[44]), "+f"(d[45]), "+f"(d[46]), "+f"(d[47]), "+f"(d[48]), "+f"(d[49]), "+f"(d[50]), "+f"(d[51]), "+f"(d[52]), "+f"(d[53]), "+f"(d[54]), "+f"(d[55]), "+f"(d[56]), "+f"(d[57]), "+f"(d[58]), "+f"(d[59]), "+f"(d[60]), "+f"(d[61]), "+f"(d[62]), "+f"(d[63]), "+f"(d[64]), "+f"(d[65]), "+f"(d[66]), "+f"(d[67]), "+f"(d[68]), "+f"(d[69]), "+f"(d[70]), "+f"(d[71]), "+f"(d[72]), "+f"(d[73]), "+f"(d[74]), "+f"(d[75]), "+f"(d[76]), "+f"(d[77]), "+f"(d[78]), "+f"(d[79])
    : "r"(a0), "r"(a1), "r"(a2), "r"(a3), "r"(blo));
}
template<int N> __device__ __forceinline__ void wgmma_rs_hi(float (&d)[64], uint32_t a0, uint32_t a1, uint32_t a2, uint32_t a3, uint32_t blo);
template<> __device__ __forceinline__ void wgmma_rs_hi<16>(float (&d)[64], uint32_t a0, uint32_t a1, uint32_t a2, uint32_t a3, uint32_t blo){
  asm volatile("{\n.reg .b64 db;\nmov.b64 db, {%12,8};\nwgmma.mma_async.sync.aligned.m64n16k16.f32.bf16.bf16 {%0, %1, %2, %3, %4, %5, %6, %7}, {%8,%9,%10,%11}, db, 1, 1, 1, 0;\n}\n"
    : "+f"(d[56]), "+f"(d[57]), "+f"(d[58]), "+f"(d[59]), "+f"(d[60]), "+f"(d[61]), "+f"(d[62]), "+f"(d[63])
    : "r"(a0), "r"(a1), "r"(a2), "r"(a3), "r"(blo));
}
template<> __device__ __forceinline__ void wgmma_rs_hi<32>(float (&d)[64], uint32_t a0, uint32_t a1, uint32_t a2, uint32_t a3, uint32_t blo){
  asm volatile("{\n.reg .b64 db;\nmov.b64 db, {%20,8};\nwgmma.mma_async.sync.aligned.m64n32k16.f32.bf16.bf16 {%0, %1, %2, %3, %4, %5, %6, %7, %8, %9, %10, %11, %12, %13, %14, %15}, {%16,%17,%18,%19}, db, 1, 1, 1, 0;\n}\n"
    : "+f"(d[48]), "+f"(d[49]), "+f"(d[50]), "+f"(d[51]), "+f"(d[52]), "+f"(d[53]), "+f"(d[54]), "+f"(d[55]), "+f"(d[56]), "+f"(d[57]), "+f"(d[58]), "+f"(d[59]), "+f"(d[60]), "+f"(d[61]), "+f"(d[62]), "+f"(d[63])
    : "r"(a0), "r"(a1), "r"(a2), "r"(a3), "r"(blo));
}
template<> __device__ __forceinline__ void wgmma_rs_hi<48>(float (&d)[64], uint32_t a0, uint32_t a1, uint32_t a2, uint32_t a3, uint32_t blo){
  asm volatile("{\n.reg .b64 db;\nmov.b64 db, {%28,8};\nwgmma.mma_async.sync.aligned.m64n48k16.f32.bf16.bf16 {%0, %1, %2, %3, %4, %5, %6, %7, %8, %9, %10, %11, %12, %13, %14, %15, %16, %17, %18, %19, %20, %21, %22, %23}, {%24,%25,%26,%27}, db, 1, 1, 1, 0;\n}\n"
    : "+f"(d[40]), "+f"(d[41]), "+f"(d[42]), "+f"(d[43]), "+f"(d[44]), "+f"(d[45]), "+f"(d[46]), "+f"(d[47]), "+f"(d[48]), "+f"(d[49]), "+f"(d[50]), "+f"(d[51]), "+f"(d[52]), "+f"(d[53]), "+f"(d[54]), "+f"(d[55]), "+f"(d[56]), "+f"(d[57]), "+f"(d[58]), "+f"(d[59]), "+f"(d[60]), "+f"(d[61]), "+f"(d[62]), "+f"(d[63])
    : "r"(a0), "r"(a1), "r"(a2), "r"(a3), "r"(blo));
}
template<> __device__ __forceinline__ void wgmma_rs_hi<64>(float (&d)[64], uint32_t a0, uint32_t a1, uint32_t a2, uint32_t a3, uint32_t blo){
  asm volatile("{\n.reg .b64 db;\nmov.b64 db, {%36,8};\nwgmma.mma_async.sync.aligned.m64n64k16.f32.bf16.bf16 {%0, %1, %2, %3, %4, %5, %6, %7, %8, %9, %10, %11, %12, %13, %14, %15, %16, %17, %18, %19, %20, %21, %22, %23, %24, %25, %26, %27, %28, %29, %30, %31}, {%32,%33,%34,%35}, db, 1, 1, 1, 0;\n}\n"
    : "+f"(d[32]), "+f"(d[33]), "+f"(d[34]), "+f"(d[35]), "+f"(d[36]), "+f"(d[37]), "+f"(d[38]), "+f"(d[39]), "+f"(d[40]), "+f"(d[41]), "+f"(d[42]), "+f"(d[43]), "+f"(d[44]), "+f"(d[45]), "+f"(d[46]), "+f"(d[47]), "+f"(d[48]), "+f"(d[49]), "+f"(d[50]), "+f"(d[51]), "+f"(d[52]), "+f"(d[53]), "+f"(d[54]), "+f"(d[55]), "+f"(d[56]), "+f"(d[57]), "+f"(d[58]), "+f"(d[59]), "+f"(d[60]), "+f"(d[61]), "+f"(d[62]), "+f"(d[63])
    : "r"(a0), "r"(a1), "r"(a2), "r"(a3), "r"(blo));
}
template<> __device__ __forceinline__ void wgmma_rs_hi<80>(float (&d)[64], uint32_t a0, uint32_t a1, uint32_t a2, uint32_t a3, uint32_t blo){
  asm volatile("{\n.reg .b64 db;\nmov.b64 db, {%44,8};\nwgmma.mma_async.sync.aligned.m64n80k16.f32.bf16.bf16 {%0, %1, %2, %3, %4, %5, %6, %7, %8, %9, %10, %11, %12, %13, %14, %15, %16, %17, %18, %19, %20, %21, %22, %23, %24, %25, %26, %27, %28, %29, %30, %31, %32, %33, %34, %35, %36, %37, %38, %39}, {%40,%41,%42,%43}, db, 1, 1, 1, 0;\n}\n"
    : "+f"(d[24]), "+f"(d[25]), "+f"(d[26]), "+f"(d[27]), "+f"(d[28]), "+f"(d[29]), "+f"(d[30]), "+f"(d[31]), "+f"(d[32]), "+f"(d[33]), "+f"(d[34]), "+f"(d[35]), "+f"(d[36]), "+f"(d[37]), "+f"(d[38]), "+f"(d[39]), "+f"(d[40]), "+f"(d[41]), "+f"(d[42]), "+f"(d[43]), "+f"(d[44]), "+f"(d[45]), "+f"(d[46]), "+f"(d[47]), "+f"(d[48]), "+f"(d[49]), "+f"(d[50]), "+f"(d[51]), "+f"(d[52]), "+f"(d[53]), "+f"(d[54]), "+f"(d[55]), "+f"(d[56]), "+f"(d[57]), "+f"(d[58]), "+f"(d[59]), "+f"(d[60]), "+f"(d[61]), "+f"(d[62]), "+f"(d[63])
    : "r"(a0), "r"(a1), "r"(a2), "r"(a3), "r"(blo));
}
template<> __device__ __forceinline__ void wgmma_rs_hi<96>(float (&d)[64], uint32_t a0, uint32_t a1, uint32_t a2, uint32_t a3, uint32_t blo){
  asm volatile("{\n.reg .b64 db;\nmov.b64 db, {%52,8};\nwgmma.mma_async.sync.aligned.m64n96k16.f32.bf16.bf16 {%0, %1, %2, %3, %4, %5, %6, %7, %8, %9, %10, %11, %12, %13, %14, %15, %16, %17, %18, %19, %20, %21, %22, %23, %24, %25, %26, %27, %28, %29, %30, %31, %32, %33, %34, %35, %36, %37, %38, %39, %40, %41, %42, %43, %44, %45, %46, %47}, {%48,%49,%50,%51}, db, 1, 1, 1, 0;\n}\n"
    : "+f"(d[16]), "+f"(d[17]), "+f"(d[18]), "+f"(d[19]), "+f"(d[20]), "+f"(d[21]), "+f"(d[22]), "+f"(d[23]), "+f"(d[24]), "+f"(d[25]), "+f"(d[26]), "+f"(d[27]), "+f"(d[28]), "+f"(d[29]), "+f"(d[30]), "+f"(d[31]), "+f"(d[32]), "+f"(d[33]), "+f"(d[34]), "+f"(d[35]), "+f"(d[36]), "+f"(d[37]), "+f"(d[38]), "+f"(d[39]), "+f"(d[40]), "+f"(d[41]), "+f"(d[42]), "+f"(d[43]), "+f"(d[44]), "+f"(d[45]), "+f"(d[46]), "+f"(d[47]), "+f"(d[48]), "+f"(d[49]), "+f"(d[50]), "+f"(d[51]), "+f"(d[52]), "+f"(d[53]), "+f"(d[54]), "+f"(d[55]), "+f"(d[56]), "+f"(d[57]), "+f"(d[58]), "+f"(d[59]), "+f"(d[60]), "+f"(d[61]), "+f"(d[62]), "+f"(d[63])
    : "r"(a0), "r"(a1), "r"(a2), "r"(a3), "r"(blo));
}
template<> __device__ __forceinline__ void wgmma_rs_hi<112>(float (&d)[64], uint32_t a0, uint32_t a1, uint32_t a2, uint32_t a3, uint32_t blo){
  asm volatile("{\n.reg .b64 db;\nmov.b64 db, {%60,8};\nwgmma.mma_async.sync.aligned.m64n112k16.f32.bf16.bf16 {%0, %1, %2, %3, %4, %5, %6, %7, %8, %9, %10, %11, %12, %13, %14, %15, %16, %17, %18, %19, %20, %21, %22, %23, %24, %25, %26, %27, %28, %29, %30, %31, %32, %33, %34, %35, %36, %37, %38, %39, %40, %41, %42, %43, %44, %45, %46, %47, %48, %49, %50, %51, %52, %53, %54, %55}, {%56,%57,%58,%59}, db, 1, 1, 1, 0;\n}\n"
    : "+f"(d[8]), "+f"(d[9]), "+f"(d[10]), "+f"(d[11]), "+f"(d[12]), "+f"(d[13]), "+f"(d[14]), "+f"(d[15]), "+f"(d[16]), "+f"(d[17]), "+f"(d[18]), "+f"(d[19]), "+f"(d[20]), "+f"(d[21]), "+f"(d[22]), "+f"(d[23]), "+f"(d[24]), "+f"(d[25]), "+f"(d[26]), "+f"(d[27]), "+f"(d[28]), "+f"(d[29]), "+f"(d[30]), "+f"(d[31]), "+f"(d[32]), "+f"(d[33]), "+f"(d[34]), "+f"(d[35]), "+f"(d[36]), "+f"(d[37]), "+f"(d[38]), "+f"(d[39]), "+f"(d[40]), "+f"(d[41]), "+f"(d[42]), "+f"(d[43]), "+f"(d[44]), "+f"(d[45]), "+f"(d[46]), "+f"(d[47]), "+f"(d[48]), "+f"(d[49]), "+f"(d[50]), "+f"(d[51]), "+f"(d[52]), "+f"(d[53]), "+f"(d[54]), "+f"(d[55]), "+f"(d[56]), "+f"(d[57]), "+f"(d[58]), "+f"(d[59]), "+f"(d[60]), "+f"(d[61]), "+f"(d[62]), "+f"(d[63])
    : "r"(a0), "r"(a1), "r"(a2), "r"(a3), "r"(blo));
}
template<> __device__ __forceinline__ void wgmma_rs_hi<128>(float (&d)[64], uint32_t a0, uint32_t a1, uint32_t a2, uint32_t a3, uint32_t blo){
  asm volatile("{\n.reg .b64 db;\nmov.b64 db, {%68,8};\nwgmma.mma_async.sync.aligned.m64n128k16.f32.bf16.bf16 {%0, %1, %2, %3, %4, %5, %6, %7, %8, %9, %10, %11, %12, %13, %14, %15, %16, %17, %18, %19, %20, %21, %22, %23, %24, %25, %26, %27, %28, %29, %30, %31, %32, %33, %34, %35, %36, %37, %38, %39, %40, %41, %42, %43, %44, %45, %46, %47, %48, %49, %50, %51, %52, %53, %54, %55, %56, %57, %58, %59, %60, %61, %62, %63}, {%64,%65,%66,%67}, db, 1, 1, 1, 0;\n}\n"
    : "+f"(d[0]), "+f"(d[1]), "+f"(d[2]), "+f"(d[3]), "+f"(d[4]), "+f"(d[5]), "+f"(d[6]), "+f"(d[7]), "+f"(d[8]), "+f"(d[9]), "+f"(d[10]), "+f"(d[11]), "+f"(d[12]), "+f"(d[13]), "+f"(d[14]), "+f"(d[15]), "+f"(d[16]), "+f"(d[17]), "+f"(d[18]), "+f"(d[19]), "+f"(d[20]), "+f"(d[21]), "+f"(d[22]), "+f"(d[23]), "+f"(d[24]), "+f"(d[25]), "+f"(d[26]), "+f"(d[27]), "+f"(d[28]), "+f"(d[29]), "+f"(d[30]), "+f"(d[31]), "+f"(d[32]), "+f"(d[33]), "+f"(d[34]), "+f"(d[35]), "+f"(d[36]), "+f"(d[37]), "+f"(d[38]), "+f"(d[39]), "+f"(d[40]), "+f"(d[41]), "+f"(d[42]), "+f"(d[43]), "+f"(d[44]), "+f"(d[45]), "+f"(d[46]), "+f"(d[47]), "+f"(d[48]), "+f"(d[49]), "+f"(d[50]), "+f"(d[51]), "+f"(d[52]), "+f"(d[53]), "+f"(d[54]), "+f"(d[55]), "+f"(d[56]), "+f"(d[57]), "+f"(d[58]), "+f"(d[59]), "+f"(d[60]), "+f"(d[61]), "+f"(d[62]), "+f"(d[63])
    : "r"(a0), "r"(a1), "r"(a2), "r"(a3), "r"(blo));
}

__device__ __forceinline__ void keep_warm(uint32_t bar, int barid) {
  float d0 = 0.f, d1 = 0.f, d2 = 0.f, d3 = 0.f;
  uint32_t it = 0, go;
  const uint32_t z0 = lds32(sb + EP_OFF + 24), z1 = lds32(sb + EP_OFF + 24), z2 = lds32(sb + EP_OFF + 24), z3 = lds32(sb + EP_OFF + 24);
  do {
    wgmma_fence();
    asm volatile("{\n.reg .b64 db;\nmov.b64 db, {%8,8};\nwgmma.mma_async.sync.aligned.m64n8k16.f32.bf16.bf16 {%0,%1,%2,%3}, {%4,%5,%6,%7}, db, 1, 1, 1, 0;\n}\n"
                 : "+f"(d0), "+f"(d1), "+f"(d2), "+f"(d3) : "r"(z0), "r"(z1), "r"(z2), "r"(z3), "r"(desc_lo(sb + DTAB_OFF, 0)));
    wgmma_commit();
    wgmma_wait<0>();
    asm volatile("{\n.reg .pred p, q;\nmbarrier.test_wait.parity.shared::cta.b64 p, [%1], 0;\nbar.red.or.pred q, %2, 128, p;\nselp.u32 %0, 1, 0, q;\n}\n"
                 : "=r"(go) : "r"(bar), "r"(barid) : "memory");
    trap_if(++it > SPIN_LIMIT);
  } while (!__all_sync(0xffffffffu, go));
  sts32(sb + EP_OFF + 28, __float_as_uint(d0 + d1 + d2 + d3));
}

struct CvCtx {
  uint32_t koff, zero, so[3];
  int srcA, srcB;
  bool wrapA, s3, kodd;
};
struct CvPipe { uint32_t Ap, Ep, keep, send; };
template <int LO> __device__ __forceinline__ void cv_copy(float (&acc)[64]) {
#pragma unroll
  for (int i = LO; i < 64; i++) { float t; asm volatile("mov.b32 %0, %1;" : "=f"(t) : "f"(acc[i]) : "memory"); acc[i] = t; }
}
template <int G> __device__ __forceinline__ void cv_raw(uint32_t (&A)[4][4], uint32_t kaddr) {
#pragma unroll
  for (int i = 0; i < 4; i++) {
    const uint32_t a = kaddr + (4 * G + i) * 128;
    A[i][0] = lds32(a); A[i][1] = lds32(a + 4); A[i][3] = lds32(a + 8);
  }
}
__device__ __forceinline__ void cv_form(uint32_t (&A)[4][4], uint32_t sel) {
#pragma unroll
  for (int i = 0; i < 4; i++) {
    asm volatile("prmt.b32 %0, %0, %1, %2;" : "+r"(A[i][0]) : "r"(A[i][1]), "r"(sel));
    asm volatile("prmt.b32 %0, %1, %2, %3;" : "=r"(A[i][2]) : "r"(A[i][1]), "r"(A[i][3]), "r"(sel));
  }
}
#define CVV 2
template <int G> __device__ __forceinline__ void cv_step(float (&acc)[64], uint32_t (&A)[4][4], CvPipe& s, const CvCtx& c, uint32_t cb, uint32_t stg) {
  constexpr int JA = G - 1, JB = G - 2, NH = CVV == 1 ? 4 : (CVV == 3 ? 2 : 1);
  const uint32_t db0 = desc_lo(cb + CV_U + 192, CV_PL);
  uint32_t B[4][4];
  uint32_t ra[2], rb;
  if constexpr (G < 8) {
    wgmma_fence();
#pragma unroll
    for (int i = 0; i < NH; i++) wgmma_rs_hi<128 - 16 * (G & 7)>(acc, A[i][0], A[i][1], A[i][2], A[i][3], db0 - 4 * i);
    wgmma_commit();
    __syncwarp();
  }
  if constexpr (JA >= 0 && JA < 8) {
    const uint32_t p0 = pack_bf16(acc[8 * JA + 1], acc[8 * JA + 3]), p1 = pack_bf16(acc[8 * JA + 5], acc[8 * JA + 7]);
    ra[0] = __shfl_sync(0xffffffffu, c.wrapA ? s.Ap : p0, c.srcA);
    ra[1] = __shfl_sync(0xffffffffu, c.wrapA ? p0 : p1, c.srcA);
    s.Ap = p1;
  }
  if constexpr (JB >= 0) rb = __shfl_sync(0xffffffffu, s.send, c.srcB);
  if constexpr (G < 7) cv_raw<G + 1>(B, cb + c.koff);
  uint32_t z = 0;
  if constexpr (G < 8 && NH < 4) {
    __syncwarp();
    wgmma_fence();
#pragma unroll
    for (int i = NH; i < 4; i++) wgmma_rs_hi<128 - 16 * (G & 7)>(acc, A[i][0], A[i][1], A[i][2], A[i][3], db0 - 4 * i);
    wgmma_commit();
    asm volatile("mov.u32 %0, %%clock;" : "=r"(z)::"memory");
    z &= c.zero;
  }
  if constexpr (G < 7) cv_form(B, 0x5432u | z);
  if constexpr (JB >= 0) sts32(stg + ((c.so[JB / 3] >> (10 * (JB % 3))) & 0xffc), hadd2(rb | z, s.keep));
  if constexpr (JA >= 0 && JA < 8) {
    const uint32_t sh = 16 | z, mk = 0xffff0000u | z;
    const uint32_t ev = pack_bf16(acc[8 * JA] + __uint_as_float(ra[0] << sh), acc[8 * JA + 2] + __uint_as_float(ra[0] & mk));
    const uint32_t od = pack_bf16(acc[8 * JA + 4] + __uint_as_float(ra[1] << sh), acc[8 * JA + 6] + __uint_as_float(ra[1] & mk));
    s.send = c.kodd ? ev : (c.s3 ? s.Ep : od);
    s.keep = c.kodd ? od : ev;
    s.Ep = od;
  }
  if constexpr (G < 8) { __syncwarp(); wgmma_wait<0>(); cv_copy<8 * (G & 7)>(acc); }
  if constexpr (G < 9) cv_step<G + 1>(acc, B, s, c, cb, stg);
}
__device__ __forceinline__ uint32_t cv_stage(int slot) { return sb + (slot < 4 ? 40960 + slot * 4096 : CV_OFF + CV_K); }
__device__ __forceinline__ void cv_setup(CvCtx& c) {
  const int tid = tid_opaque() & 127, w = tid >> 5, lane = tid & 31, r = lane >> 2, q = lane & 3;
  const int i0 = (r >> 1) & 1, i1 = r >> 2;
  c.koff = CV_K - 32 + 4 * (8 * (r >> 1) + 2 * w + (r & 1) + 2 * q);
  c.srcA = i0 ? lane - 8 : lane + 8 - q + ((q + 3) & 3);
  c.wrapA = i0 && q == 3;
  c.srcB = i1 == 0 ? (lane - q + 16 + ((q + 3) & 3)) : (lane - q - 16 + ((q + 1) & 3));
  c.s3 = (i1 == 1 && q == 3); c.kodd = (i1 == 1 && q < 3);
  c.zero = lds32(sb + EP_OFF + 24);
#pragma unroll
  for (int i = 0; i < 3; i++) c.so[i] = lds32(sb + SO_OFF + 512 * i + 4 * tid);
}
__device__ __forceinline__ void cv_table() {
  const int tid = tid_opaque() & 127, r = (tid & 31) >> 2, q = tid & 3;
  int t = 16 * (2 * (r < 4 ? q : 4 + ((q + 1) & 3)) + ((r >> 1) & 1)) + 4 * (tid >> 5) + 2 * (r & 1);
#pragma unroll 1
  for (int i = 0; i < 3; i++) {
    uint32_t v = 0;
#pragma unroll 1
    for (int x = 0; x < 3; x++, t += 256) {
      const int T = t / 160, tl = t - T * 160;
      const int qq = (T >= NT1 - 1) ? (tl >> 5) : (tl / 40);
      int ck = 20 * T + ((tl - qq * ((T >= NT1 - 1) ? 32 : 40)) >> 1);
      ck ^= (ck >> 2) & 6;
      v |= (uint32_t)((ck * 4 + qq) & 1023) << (10 * x + 2);
    }
    sts32(sb + SO_OFF + 512 * i + 4 * tid, v);
  }
}
__device__ __forceinline__ void conv_channel(int slot, const CvCtx& c) {
  const uint32_t cb = sb + CV_OFF + slot * CV_B;
  float acc[64];
  CvPipe s;
  s.Ap = s.Ep = 0u;
  uint32_t A[4][4];
#pragma unroll
  for (int i = 0; i < 64; i++) acc[i] = 0.f;
  if (slot == 4) mbar_wait(bars + 8 * B_CVDONE);
  mbar_wait(bars + 8 * (B_CVFULL + slot));
  cv_raw<0>(A, cb + c.koff);
  {
    const uint32_t w0 = lds32(cb + CV_K);
    const uint32_t wp = __byte_perm(pack_bf16(bf_lo(w0) + __uint_as_float(lds32(sb + EP_OFF + 4 * slot)), 0.f), w0, 0x7610);
    if (c.koff == CV_K) A[0][0] = wp;
    if (c.koff == CV_K - 4) A[0][1] = wp;
    if (c.koff == CV_K - 8) A[0][3] = wp;
  }
  cv_form(A, 0x5432u);
  cv_copy<0>(acc);
  cv_step<0>(acc, A, s, c, cb, cv_stage(slot));
  fence_async_smem();
  mbar_arrive(bars + 8 * (B_CVDONE + slot));
}

__device__ __forceinline__ void kv_issue(const Params& p, int c, int m2, int dg) {
  const uint32_t fb = bars + 8 * (B_KV + c);
  mbar_expect_tx(fb, KV_PIECE);
  tma3(sb + KS_OFF + c * KV_PIECE, &p.mK, 160 * dg + 32 * c, 64 * m2 - 3, 0, fb);
  tma3(sb + KS_OFF + c * KV_PIECE + 4864, &p.mV, 160 * dg + 32 * c, 64 * m2 - 1, 0, fb);
}
__device__ __forceinline__ void kv_tile(int m, int c, int y, uint32_t (&o)[4][4]) {
  const int lane = tid_opaque() & 31, tg = lane & 3, pr = 8 * (y ^ (tg >> 1)) + (lane >> 2);
  const uint32_t pb = sb + KS_OFF + c * KV_PIECE + 4 * pr;
  const uint32_t ka = pb + tg * 1216, va = pb + 4864 + tg * 1088 + 64;
  const uint32_t kh = (m == 0 && tg > 0) ? ka - 192 : ka;
  uint32_t kk[19], u[16];
  const float4 t = lds128f(sb + TAP_OFF + 256 * c + 16 * pr);
#pragma unroll
  for (int i = 0; i < 19; i++) { kk[i] = lds32((i < 3 ? kh : ka) + i * 64); if (i >= 3) u[i - 3] = lds32(va + (i - 3) * 64); }
  const uint32_t dst = sb + KS_OFF + c * KV_PIECE + pr * 64 + tg * 16;
  if (y) {
    __syncwarp();
#pragma unroll
    for (int x = 0; x < 4; x++) sts128((dst ^ 512) + x * 1024, make_uint4(o[x][0], o[x][1], o[x][2], o[x][3]));
  }
  const uint32_t w0 = __byte_perm(__float_as_uint(t.x), __float_as_uint(t.z), 0x5410), w1 = __byte_perm(__float_as_uint(t.x), __float_as_uint(t.z), 0x7632);
  const uint32_t w2 = __byte_perm(__float_as_uint(t.y), __float_as_uint(t.w), 0x5410), w3 = __byte_perm(__float_as_uint(t.y), __float_as_uint(t.w), 0x7632);
#pragma unroll
  for (int i = 0; i < 16; i++) {
    uint32_t a = hmul2(kk[i], w3);
    a = hadd2(a, hmul2(kk[i + 1], w2)); a = hadd2(a, hmul2(kk[i + 2], w1)); a = hadd2(a, hmul2(kk[i + 3], w0));
    u[i] = hmul2(a, u[i]);
  }
#pragma unroll
  for (int x = 0; x < 4; x++) {
#pragma unroll
    for (int qq = 0; qq < 4; qq++) o[x][qq] = __byte_perm(u[15 - 4 * qq - (x & 2)], u[14 - 4 * qq - (x & 2)], (x & 1) ? 0x7632 : 0x5410);
    if (y) sts128(dst + x * 1024, make_uint4(o[x][0], o[x][1], o[x][2], o[x][3]));
  }
}
template <bool BF>
__device__ __forceinline__ void ln_finish(float s1, float s2, float& mean, float& rstd) {
  mean = s1 * (1.f / 640.f);
  float v = fmaxf(fmaf(-mean, mean, s2 * (1.f / 640.f)), 0.f);
  if (BF) {
    const uint32_t mv = pack_bf16(mean, v);
    mean = bf_lo(mv);
    asm("sqrt.approx.ftz.f32 %0, %1;" : "=f"(v) : "f"(bf_lo(pack_bf16(bf_hi(mv) + 1e-5f, 0.f))));
    asm("rcp.approx.ftz.f32 %0, %1;" : "=f"(rstd) : "f"(bf_lo(pack_bf16(v, 0.f))));
  } else {
    v += 1e-5f;
    asm("rsqrt.approx.ftz.f32 %0, %1;" : "=f"(rstd) : "f"(v));
  }
}
template <int l>
__device__ __forceinline__ void stat_table(int T1, unsigned want, int g, const uint4* x0, const uint4* x1, float (&xa)[2], float (&xb)[2]) {
  const int n = 32 * g + (tid_opaque() & 31);
  const uint4* rp = &g_stats[8 * l * SEQ + min(160 * T1 + n, SEQ - 1)];
  float a[4], b[4];
  uint32_t it = 0;
  while (true) {
    bool ok = true;
#pragma unroll
    for (int i = 0; i < 4; i++) ok &= (rec_ld(rp + SEQ * i, a[i], b[i]) == want);
    ok &= rec_ld(x0, xa[0], xb[0]) == want;
    ok &= rec_ld(x1, xa[1], xb[1]) == want;
    if (__all_sync(0xffffffffu, ok)) break;
    trap_if(++it > SPIN_LIMIT);
  }
  float m, rs;
  ln_finish<l == 0>((a[0] + a[1]) + (a[2] + a[3]), (b[0] + b[1]) + (b[2] + b[3]), m, rs);
  sts32(sb + STAB_OFF + ((n >> 1) & 3) * 160 + (n >> 3) * 8 + (n & 1) * 4, __float_as_uint(rs));
  const uint32_t hi = pack_bf16(-m, -m);
  const float lo = -m - bf_lo(hi);
  sts128(sb + (l ? MX1_OFF : MX0_OFF) + n * 16, make_uint4(hi, pack_bf16(lo, lo), 0u, 0u));
  fence_async_smem();
}
template <bool BF>
__device__ __forceinline__ void stats_reduce(float (&a)[2], float (&b)[2], float (&mean)[2], float (&rstd)[2]) {
#pragma unroll
  for (int o = 1; o < 4; o <<= 1)
#pragma unroll
    for (int h = 0; h < 2; h++) { a[h] += __shfl_xor_sync(0xffffffffu, a[h], o); b[h] += __shfl_xor_sync(0xffffffffu, b[h], o); }
#pragma unroll
  for (int h = 0; h < 2; h++) ln_finish<BF>(a[h], b[h], mean[h], rstd[h]);
}

template <bool FIRST>
__device__ __forceinline__ void stats_publish(int which, int n0, int dg, unsigned tag, const float (&acc)[80]) {
  const int q = tid_opaque() & 3, h = q & 1;
  float s1[2] = {0.f, 0.f}, s2[2] = {0.f, 0.f}, t1[2] = {0.f, 0.f}, t2[2] = {0.f, 0.f};
#pragma unroll
  for (int j = 0; j < 20; j++)
#pragma unroll
    for (int y = 0; y < 2; y++) {
      const float a = acc[4 * j + 2 * y], b = acc[4 * j + 2 * y + 1];
      s1[y] += a; t1[y] += b; s2[y] = fmaf(a, a, s2[y]); t2[y] = fmaf(b, b, t2[y]);
    }
#pragma unroll
  for (int y = 0; y < 2; y++) { s1[y] += t1[y]; s2[y] += t2[y]; }
  float a = (h ? s1[1] : s1[0]) + __shfl_xor_sync(0xffffffffu, h ? s1[0] : s1[1], 1);
  float b = (h ? s2[1] : s2[0]) + __shfl_xor_sync(0xffffffffu, h ? s2[0] : s2[1], 1);
  a += __shfl_xor_sync(0xffffffffu, a, 2);
  b += __shfl_xor_sync(0xffffffffu, b, 2);
  if (FIRST) {
    rec_st(&g_stats[((q >> 1) * 4 + dg) * SEQ + n0 + 8 * h], a, b, q < 2 ? tag : tag - 1);
    rec_st(&g_stats[((q >> 1) * 4 + 8 + dg) * SEQ + n0 + 8 * h], a, b, tag - 1);
  } else if (q < 2) rec_st(&g_stats[(which * 4 + dg) * SEQ + n0 + 8 * h], a, b, tag);
}
__device__ __forceinline__ void stats_get(int which, int n0, unsigned tag, float (&mean)[2], float (&rstd)[2]) {
  const uint4* p0 = &g_stats[(which * 4 + (tid_opaque() & 3)) * SEQ + n0];
  float a[2], b[2];
  uint32_t it = 0;
  while (true) {
    const unsigned t0 = rec_ld(p0, a[0], b[0]), t1 = rec_ld(p0 + 8, a[1], b[1]);
    if (__all_sync(0xffffffffu, t0 == tag && t1 == tag)) break;
    trap_if(++it > SPIN_LIMIT);
  }
  stats_reduce<false>(a, b, mean, rstd);
}
__device__ __forceinline__ void x0_load(float (&acc)[80]) {
  const int t = tid_opaque() & 127;
  const uint32_t xa = sb + XT_OFF + (16 * (t >> 5) + ((t & 31) >> 2)) * 320 + 8 * (t & 3);
  mbar_wait(bars + 8 * B_XT);
#pragma unroll
  for (int h = 0; h < 2; h++)
#pragma unroll
    for (int J = 0; J < 10; J++) {
      const float2 v = lds64f(xa + h * 2560 + 32 * J);
      const uint32_t x = __float_as_uint(v.x), y = __float_as_uint(v.y);
      acc[8 * J + 2 * h] = bf_lo(x); acc[8 * J + 2 * h + 1] = bf_hi(x);
      acc[8 * J + 4 + 2 * h] = bf_lo(y); acc[8 * J + 4 + 2 * h + 1] = bf_hi(y);
    }
}

template <bool FROM_X0>
__device__ __forceinline__ void dskip_init(float (&acc)[80], const float (&mean)[2], const float (&rstd)[2]) {
  const int t = tid_opaque() & 127;
  const uint32_t xa = sb + XT_OFF + (16 * (t >> 5) + ((t & 31) >> 2)) * 320 + 8 * (t & 3), da = sb + DTAB_OFF + 8 * (t & 3);
  float2 dw[10], xv[10][2];
#pragma unroll
  for (int J = 0; J < 2; J++) { dw[J] = lds64f(da + 32 * J); if (FROM_X0) { xv[J][0] = lds64f(xa + 32 * J); xv[J][1] = lds64f(xa + 2560 + 32 * J); } }
#pragma unroll
  for (int J = 0; J < 10; J++) {
    if (J + 2 < 10) { dw[J + 2] = lds64f(da + 32 * (J + 2)); if (FROM_X0) { xv[J + 2][0] = lds64f(xa + 32 * (J + 2)); xv[J + 2][1] = lds64f(xa + 2560 + 32 * (J + 2)); } }
#pragma unroll
    for (int x = 0; x < 8; x++) {
      const int h = (x >> 1) & 1;
      const uint32_t dwd = __float_as_uint(x < 4 ? dw[J].x : dw[J].y);
      const float tt = fmaf(rstd[h], (x & 1) ? bf_hi(dwd) : bf_lo(dwd), 1.f);
      float a = acc[8 * J + x];
      if (FROM_X0) { const uint32_t xw = __float_as_uint(x < 4 ? xv[J][h].x : xv[J][h].y); a = (x & 1) ? bf_hi(xw) : bf_lo(xw); }
      acc[8 * J + x] = FROM_X0 ? (a - mean[h]) * tt : fmaf(a, tt, -mean[h] * tt);
    }
  }
}

__global__ void __launch_bounds__(512, 1) fused_kernel(const __grid_constant__ Params p) {
  extern __shared__ __align__(1024) uint8_t smem_raw[];
  const int tid = threadIdx.x, lane = tid & 31;
  const int wid = __shfl_sync(0xffffffffu, tid >> 5, 0), wg = wid >> 2;
  unsigned smid; asm volatile("mov.u32 %0, %%smid;" : "=r"(smid));
  const int role = p.role[min(smid, 131u)];
  if (wid == 12) {
    const bool el = elect_one();
    if (el) {
      asm volatile("prefetch.tensormap [%0];" ::"l"(&p.mB) : "memory");
      asm volatile("prefetch.tensormap [%0];" ::"l"((role & 15) == NT1 - 1 ? &p.mXl : &p.mX) : "memory");
#pragma unroll
      for (int k = 0; k < S1; k++) mbar_init(bars + 8 * (B_G1FULL + k), 1);
#pragma unroll
      for (int k = 0; k < 6; k++) mbar_init(bars + 8 * (B_XT + k), 1);
      asm volatile("fence.mbarrier_init.release.cluster;" ::: "memory");
    }
    if (role >= 0) {
      __syncwarp();
      asm volatile("bar.arrive 5, 288;" ::: "memory");
      const Role R = unpack_role(role);
      if (elect_one()) {
        TS(45);
#pragma unroll 1
        for (int k = 0; k < S1; k++) {
          const uint32_t fb = bars + 8 * (B_G1FULL + k);
          mbar_expect_tx(fb, G1_STAGE);
          tma4(sb + k * G1_STAGE + G1_XOFF, R.last ? &p.mXl : &p.mX, 64 * k, 0, 0, R.last ? 0 : 80 * R.T1, fb);
          tma5(sb + k * G1_STAGE, &p.mB, 64 * k, 0, 0, 4 * R.side, 2 * R.GP, fb);
          if (PFD) asm volatile("prefetch.tensormap [%0];" ::"l"(&p.mK + k) : "memory");
        }
        if (R.has2) {
          mbar_expect_tx(bars + 8 * B_XT, 20480);
#pragma unroll 1
          for (int h = 0; h < 2; h++) {
            const int ng = 8 * R.m2 + 4 * h, T = ng / 20;
            tma4(sb + XT_OFF + h * 10240, T == NT1 - 1 ? &p.mXtl : &p.mXt, 160 * R.dg, 0, 0, T == NT1 - 1 ? ng - 240 : ng + 60 * T, bars + 8 * B_XT);
          }
#pragma unroll 1
          for (int c = 0; c < KV0; c++) kv_issue(p, c, R.m2, R.dg);
        }
        TS(44);
      }
      __syncwarp();
      bar_sync(6, 64);
    }
  }
  trap_if(smid >= 132 || smem_u32(smem_raw) != sb);
  if (role < 0) {
    if (wid == 0) {
      const unsigned tag = ld_rlx(g_epoch);
      uint32_t it = 0;
      while (!__all_sync(0xffffffffu, (int)(ld_rlx(&g_hcnt[(lane & 7) * 32]) - 40 * tag) >= 0)) { __nanosleep(500); trap_if(++it > SPIN_LIMIT); }
    }
    return;
  }
  float mean0[2] = {0.f, 0.f}, rstd0[2] = {0.f, 0.f};
  if (wg == 2 || wid == 14) {
    ROLE(role)
    const int c = wid == 14 ? 4 : wid - 8;
    const unsigned tag = ld_rlx(g_epoch);
    if (has2) {
      uint2 bv[2][5];
#pragma unroll
      for (int x = 0; x < 2; x++)
#pragma unroll
        for (int i = 0; i < 5; i++) bv[x][i] = ldv64((const uint2*)((x ? p.bim : p.bre) + (cch0 + 32 * c) * DM) + lane + 32 * i);
      float sv[2];
#pragma unroll
      for (int x = 0; x < 2; x++) {
        float a = 0.f;
#pragma unroll
        for (int i = 0; i < 5; i++) a += (bf_lo(bv[x][i].x) + bf_hi(bv[x][i].x)) + (bf_lo(bv[x][i].y) + bf_hi(bv[x][i].y));
        sv[x] = a;
      }
#pragma unroll
      for (int o = 16; o > 0; o >>= 1) { sv[0] += __shfl_xor_sync(0xffffffffu, sv[0], o); sv[1] += __shfl_xor_sync(0xffffffffu, sv[1], o); }
      if (lane < 2) rec_st(&g_sB[(cch0 + 32 * c) * 2 + lane], sv[0], sv[1], tag);
      if (tid == 256) TS(47);
      __syncwarp();
      bar_sync(8, 192);
      if (wg == 2) {
        float xs[80];
        x0_load(xs);
        stats_publish<true>(0, 64 * m2 + 16 * c + (lane >> 2), dg, tag, xs);
        if (tid == 256) TS(31);
      }
      mbar_wait(bars + 8 * B_EP);
      mbar_wait(bars + 8 * (B_KV + c));
      mbar_wait(bars + 8 * (B_G1DONE + PAUSE_K - 1));
      if (tid == 448) TS(52);
      uint32_t o[4][4] = {};
#pragma unroll 1
      for (int y = 0; y < 2; y++) kv_tile(m2, c, y, o);
      fence_async_smem();
      __syncwarp();
      if (lane == 0) { mbar_arrive(bars + 8 * B_PREP); mbar_arrive(bars + 8 * (B_PD + c)); }
      if (tid == 448) TS(51);
    } else bar_sync(8, 192);
    {
      const uint4* x0 = wg == 2 ? &g_stats[(lane & 3) * SEQ + (has2 ? 64 * m2 : 0) + 16 * c + (lane >> 2)] : &g_sB[(128 * GP + 32 * side + lane) * 2];
      float xa[2], xb[2];
      stat_table<0>(T1, tag, c, x0, x0 + (wg == 2 ? 8 : 128), xa, xb);
      if (wg == 2) stats_reduce<true>(xa, xb, mean0, rstd0);
      else {
#pragma unroll
        for (int i = 0; i < 2; i++) {
          const float ha = bf_lo(pack_bf16(xa[i], 0.f)), hb = bf_lo(pack_bf16(xb[i], 0.f));
          const float pa = __uint_as_float(pack_bf16(ha, xa[i] - ha)), pb = __uint_as_float(pack_bf16(hb, xb[i] - hb));
          sts64f(sb + CTAB_OFF + (32 * i + lane) * 24 + 16, p.swap ? pb : pa, p.swap ? pa : pb);
        }
      }
      mbar_arrive(bars + 8 * B_STAB);
      if (tid == 448) TS(26);
    }
  } else if (wid == 15) {
    ROLE(role)
    const int ch = 128 * GP + 32 * side + lane;
    uint32_t r0 = ldv16(p.lre + ch), r1 = ldv16(p.lim + ch), r2 = ldv16(p.logdt + ch);
    const uint32_t r3 = ldv16(p.lre + ch + 64), r4 = ldv16(p.lim + ch + 64), r5 = ldv16(p.logdt + ch + 64);
#pragma unroll 1
    for (int i = 0; i < 2; i++) {
      const float lr = bf_lo(r0), li = bf_lo(r1);
      const float dt = __bfloat162float(__float2bfloat16_rn(expf(bf_lo(r2))));
      const float mag = expf(dt * lr);
      float sn, cs; sincospif(dt * li * 0.31830988618379067f, &sn, &cs);
      const float ar = mag * cs, ai = mag * sn;
      const float inv = 2.f / (lr * lr + li * li);
      const uint32_t ad = sb + CTAB_OFF + (32 * i + lane) * 24;
      sts64f(ad, ar, ai);
      sts64f(ad + 8, ((ar - 1.f) * lr + ai * li) * inv, (ai * lr - (ar - 1.f) * li) * inv);
      r0 = r3; r1 = r4; r2 = r5;
    }
    if (lane == 0) TS(46);
    __syncwarp();
    bar_sync(7, 64);
    mbar_arrive(bars + 8 * B_CTAB);
  } else if (wid == 13) {
    ROLE(role)
    uint4 tv[3];
    const uint32_t e0 = ld_rlx(g_epoch);
    const uint32_t e1 = ldv16(p.ssmD + min(cch0 + 32 * lane, 639));
    const uint4 dv = ldv128((const uint4*)(p.dskip + 160 * dg) + min(lane, 19));
#pragma unroll
    for (int i = 0; i < 3; i++) tv[i] = ldv128((const uint4*)(p.shiftk + 640 * dg) + min(lane + 32 * i, 79));
    sts128(sb + DTAB_OFF + 16 * min(lane, 19), dv);
#pragma unroll
    for (int i = 0; i < 3; i++) sts128(sb + TAP_OFF + 16 * min(lane + 32 * i, 79), tv[i]);
    if (lane < 7) sts32(sb + EP_OFF + 4 * lane, lane < 5 ? e1 << 16 : (lane == 5 ? e0 : 0u));
    __syncwarp();
    bar_sync(9, 64);
    mbar_arrive(bars + 8 * B_CTAB);
    if (lane == 0) { mbar_arrive(bars + 8 * B_EP); TS(53); }
    if (has2) {
#pragma unroll 1
      for (int i = 0; i < 5; i++) {
        const int c = i == 2 ? 3 : (i == 3 ? 2 : i);
        mbar_wait(bars + 8 * (B_PD + c));
        if (lane == 0) bulk_s2g(g_kv + (dg * 32 + m2) * 20480 + c * 4096, sb + KS_OFF + c * KV_PIECE, 4096);
      }
      if (lane == 0) {
        asm volatile("cp.async.bulk.commit_group;" ::: "memory");
        asm volatile("cp.async.bulk.wait_group 0;" ::: "memory");
        mbar_arrive(bars + 8 * B_PREP2);
        fence_async_global();
      }
      __syncwarp();
      if (lane < 4) red_rel(&g_kvcnt[(dg * 4 + lane) * 32]);
      __syncwarp();
      if (lane == 0) { mbar_arrive(bars + 8 * B_PUB); TS(30); }
    }
  } else if (wid != 12) {
    if (elect_one()) {
      if (wid < 7) {
        const int b0 = wid < 4 ? 4 + 19 * wid : 85 + 21 * (wid - 4), cnt = wid < 4 ? 2 : 1;
#pragma unroll
        for (int i = 0; i < 21; i++) mbar_init(bars + 8 * (b0 + i), cnt);
#pragma unroll
        for (int i = 0; i < 5; i++) mbar_init(bars + 8 * (B_PD + 5 * wid + i), 1);
      } else {
#pragma unroll
        for (int i = 0; i < 12; i++) mbar_init(bars + 8 * (B_CVDONE + i), (i == 5 || i == 6) ? 160 : 128);
        mbar_init(bars + 8 * B_CTAB, 192); mbar_init(bars + 8 * B_PREP, 5); mbar_init(bars + 8 * B_PREP2, 1);
      }
      asm volatile("fence.mbarrier_init.release.cluster;" ::: "memory");
    }
    __syncwarp();
    bar_sync(5, 288);
    if (wid == 2) asm volatile("bar.arrive 8, 192;\nbar.arrive 6, 64;\nbar.arrive 9, 64;\nbar.arrive 7, 64;" ::: "memory");
    if (tid == 128) TS(0);
    if (wg == 1) { cv_table(); mbar_arrive(bars + 8 * B_CTAB); }
  }

  if (wid == 12) {
    ROLE(role)
    uint32_t dst = sb;
#pragma unroll 1
    for (int k = S1; k < 10; k++) {
      const uint32_t fb = bars + 8 * (B_G1FULL + k);
      mbar_wait(bars + 8 * (B_G1DONE + k - S1));
      if (elect_one()) {
        mbar_expect_tx(fb, 20480);
        tma4(dst + G1_XOFF, last ? &p.mXl : &p.mX, 64 * k, 0, 0, last ? 0 : 80 * T1, fb);
        mbar_expect_tx(fb, 16384);
        tma5(dst, &p.mB, 64 * k, 0, 0, 4 * side, 2 * GP, fb);
        if (has2 && k - S1 + KV0 < 5) kv_issue(p, k - S1 + KV0, m2, dg);
      }
      dst += G1_STAGE; if (k == 2 * S1 - 1) dst = sb;
    }
  } else if (wid == 15 && (role >> 16)) {
    ROLE(role)
    if (TPF >= 0) {
      mbar_wait(bars + 8 * (B_KV + TPF));
      if (elect_one()) {
#pragma unroll
        for (int c = 0; c < 5; c++) l2_prefetch(p.ssmk + (cch0 + 32 * c) * SEQ, 4096);
        if (CPF) { l2_prefetch(p.cre + (160 * dg + 5 * m2) * DM, 6400); l2_prefetch(p.cim + (160 * dg + 5 * m2) * DM, 6400); }
      }
    }
    mbar_wait(bars + 8 * B_PREP2);
    if (lane < 10) sts128(sb + CV_OFF + (lane >> 1) * CV_B + CV_K - 32 + 16 * (lane & 1), make_uint4(0, 0, 0, 0));
    fence_async_smem();
    __syncwarp();
    const unsigned tag = lds32(sb + EP_OFF + 20);
    if (TAPW) mbar_wait(bars + 8 * B_PUB);
    if (elect_one()) {
#pragma unroll 1
      for (int c = 0; c < 5; c++) {
        if (c == 0) asm volatile("prefetch.tensormap [%0];" ::"l"(&p.mU) : "memory");
        mbar_expect_tx(bars + 8 * (B_CVFULL + c), 4096 + 2 * CV_PL);
        if (c < TAPN) bulk_g2s(sb + CV_OFF + c * CV_B + CV_K, p.ssmk + (cch0 + 32 * c) * SEQ, 4096, bars + 8 * (B_CVFULL + c));
      }
    }
    mbar_wait(bars + 8 * B_PUB);
    cnt_poll(&g_kvcnt[(dg * 4 + (m2 >> 3)) * 32], 32 * tag);
    fence_async_global();
    if (elect_one()) {
      TS(28);
#pragma unroll
      for (int c = 0; c < 5; c++) {
        tma5(sb + CV_OFF + c * CV_B + CV_U, &p.mU, 0, -3, 2 * c, 16 * (m2 & 1) + (m2 >> 1), dg, bars + 8 * (B_CVFULL + c));
        if (c >= TAPN) bulk_g2s(sb + CV_OFF + c * CV_B + CV_K, p.ssmk + (cch0 + 32 * c) * SEQ, 4096, bars + 8 * (B_CVFULL + c));
      }
#pragma unroll
      for (int i = 0; i < 3; i++) asm volatile("prefetch.tensormap [%0];" ::"l"(&p.mCre + i) : "memory");
      TS(54);
    }
    __syncwarp();
  }
  {
    const int w = wid & 3;
    if (wg == 2 && !(role >> 16)) {
      float xa[2], xb[2];
      mbar_wait(bars + 8 * (B_G1FULL + 11));
      stat_table<1>(role & 15, lds32(sb + EP_OFF + 20), w, g_stats, g_stats, xa, xb);
      mbar_arrive(bars + 8 * (B_STAB + 1));
    }
#pragma unroll 1
    for (int l = 0; l < 2; l++) {
      if (wg < 2) {
        float acc[80];
#pragma unroll
        for (int i = 0; i < 80; i++) acc[i] = 0.f;
        ROLE(role)
        const int tid = tid_opaque(), r = (tid & 31) >> 2, q = tid & 3;
        const int ch = 128 * GP + 64 * wg + 32 * side + 8 * w + r;
        const uint32_t ca = sb + CTAB_OFF + (32 * wg + 8 * w + r) * 24;
        float2 lam = make_float2(0.f, 0.f), p8 = lam, p16 = lam, pL = lam, p2L = lam;
        fence_regs(acc);
        {
          const uint32_t alo0 = (l == 0 ? desc_lo(sb, 16) : desc_lo(sb + G2_WOFF, 16)) + wg * 512;
          const uint32_t blo0 = l == 0 ? desc_lo(sb + G1_XOFF, 16) : desc_lo(sb + X1_OFF, 128);
          const uint32_t bhi = l == 0 ? desc_hi(1024, 1) : desc_hi(1024, 0), xstep = l == 0 ? 2 : 16;
          const uint32_t astep = l == 0 ? G1_STAGE >> 4 : 1024, bstep = l == 0 ? G1_STAGE >> 4 : 1280, aend = alo0 + (S1 + l) * astep;
          uint32_t alo = alo0, blo = blo0;
          const uint32_t special = 8u | (l ? (1u << MK1) | (wg << (8 - STG_D)) : (1u << MK0) | (1u << PAUSE_K) | (wg << (9 - STG0)));
          uint32_t fb = bars + 8 * (B_G1FULL + 10 * l), nb = fb + 8;
          mbar_wait(fb);
          if (tid == 0) TS(1 + 8 * l);
#pragma unroll 1
          for (int k = 0; k < 10; k++) {
            uint32_t ok;
            wgmma_fence();
#pragma unroll
            for (int kk = 0; kk < 4; kk++) {
              wgmma_n160<0>(acc, alo + kk * 2, desc_hi(1024, 1), blo + kk * xstep, bhi);
              if (kk == 0) { ok = mbar_test(nb); asm volatile("add.u32 %0, %0, %1;" : "+r"(nb) : "r"(k < 8 ? 8 : 0)); }
              if (kk == STG_KK && k == 9 && tid == 0) mbar_arrive(bars + 8 * (B_STG + l));
            }
            wgmma_commit();
            alo += astep; blo += bstep;
            if (blo == desc_lo(sb + G_OFF, 128)) blo = desc_lo(sb, 128);
            if (alo == aend) { alo = alo0; blo = blo0; }
            wgmma_wait<1>();
            if (k > 0 && (tid & 127) == 0) mbar_arrive(fb + 8 * (B_G1DONE - B_G1FULL - 1));
            if (!ok) mbar_wait(fb + 8);
            if ((special >> k) & 1) {
            if (k == (l ? MK1 : MK0)) {
              mbar_wait(bars + 8 * (B_STAB + l));
              const float2 sB = lds64f(ca + 16);
              uint32_t a0 = q < 2 ? __float_as_uint(sB.x) : 0u, a1 = q < 2 ? __float_as_uint(sB.y) : 0u, a2 = 0u, a3 = 0u;
              asm volatile("" : "+r"(a0), "+r"(a1), "+r"(a2), "+r"(a3)::"memory");
              wgmma_fence();
              wgmma_rs_n160(acc, a0, a1, a2, a3, l ? desc_lo(sb + MX1_OFF, 0) : desc_lo(sb + MX0_OFF, 0));
              wgmma_commit();
            }
            if (wg == 1 && k == (l ? 8 - STG_D : 9 - STG0)) mbar_wait(bars + 8 * (B_STG + l));
            if (k == 3) {
              mbar_wait(bars + 8 * B_CTAB);
              lam = lds64f(ca);
              if (l == 0 && q < 2) rec_st(&g_E[(q * NT1 + T1) * DM + ch], 0.f, 0.f, lds32(sb + EP_OFF + 20) - 1);
              if (p.swap) lam.y = -lam.y;
              const float2 p2 = cmul(lam, lam), p4 = cmul(p2, p2);
              p8 = cmul(p4, p4); p16 = cmul(p8, p8);
              pL = cmul(p16, p16);
              if (!last) pL = cmul(pL, p8);
              p2L = cmul(pL, pL);
            }
            if (k == PAUSE_K && l == 0 && has2) mbar_wait(bars + 8 * B_PREP);
            }
            fb += 8;
          }
        }
        const unsigned tag = lds32(sb + EP_OFF + 20);
        wgmma_wait<0>();
        fence_regs(acc);
        if ((tid & 127) == 0) { mbar_arrive(bars + 8 * (B_G1DONE + 10 * l + 9)); TS(wg ? 17 + l : 2 + 8 * l); }
        float2 ec[3];
#pragma unroll
        for (int jj = 0; jj < 4; jj++)
#pragma unroll
          for (int y = 0; y < 3; y++) {
            if (y == 2 && (jj & 1)) continue;
            const int j = y == 2 ? 16 + jj : 8 * y + 2 * jj;
            const float4 st = lds128f(sb + STAB_OFF + q * 160 + j * 8);
            const float rs[4] = {st.x, st.y, st.z, st.w};
#pragma unroll
            for (int x = 0; x < 4; x++) {
              const int i = 4 * j + 4 * (x >> 1) + (x & 1);
              acc[i] *= rs[x]; acc[i + 2] *= rs[x];
              ec[y] = (jj == 0 && x == 0) ? make_float2(acc[i], acc[i + 2]) : cfma(lam, ec[y], make_float2(acc[i], acc[i + 2]));
            }
          }
        float2 e = cfma(p16, ec[0], ec[1]);
        if (!last) e = cfma(p8, e, ec[2]);
        {
          float2 v = make_float2(__shfl_up_sync(0xffffffffu, e.x, 1, 4), __shfl_up_sync(0xffffffffu, e.y, 1, 4));
          if (q >= 1) e = cfma(pL, v, e);
          v = make_float2(__shfl_up_sync(0xffffffffu, e.x, 2, 4), __shfl_up_sync(0xffffffffu, e.y, 2, 4));
          if (q >= 2) e = cfma(p2L, v, e);
        }
        if (!last && q == 3) rec_st(&g_E[(l * NT1 + T1) * DM + ch], e.x, e.y, tag);
        if (tid == 0) TS(3 + 8 * l);
        float2 ex = make_float2(__shfl_up_sync(0xffffffffu, e.x, 1, 4), __shfl_up_sync(0xffffffffu, e.y, 1, 4));
        if (q == 0) ex = make_float2(0.f, 0.f);
        const float2 coef = lds64f(ca + 8), lamc = make_float2(lam.x, p.swap ? lam.y : -lam.y);
        float m00 = coef.x, m01 = -coef.y, m10 = -coef.y, m11 = -coef.x;
        if (p.swap) { m00 = -coef.y; m01 = coef.x; m10 = -coef.x; m11 = -coef.y; }
        float2 pLq, p160q, p640;
        {
          const float2 p80 = last ? cmul(p2L, p16) : p2L, p160 = cmul(p80, p80), p320 = cmul(p160, p160), one = make_float2(1.f, 0.f);
          p640 = cmul(p320, p320);
          pLq = cmul((q & 1) ? pL : one, (q & 2) ? p2L : one);
          p160q = cmul((q & 1) ? p160 : one, (q & 2) ? p320 : one);
        }
        float2 c, ev[3];
        unsigned tg[3];
        const uint4* ep = &g_E[(l * NT1 + T1 - 1 - q) * DM + ch];
#pragma unroll
        for (int j = 0; j < 20; j++) {
          if (j == CPOLL) {
#pragma unroll
            for (int i = 0; i < 3; i++) {
              ev[i] = make_float2(0.f, 0.f); tg[i] = tag;
              if (T1 - 1 - q - 4 * i >= 0) tg[i] = rec_ld(ep - 4 * i * DM, ev[i].x, ev[i].y);
            }
          }
#pragma unroll
          for (int x = 0; x < 2; x++) {
            const float b0 = acc[4 * j + x], b1 = acc[4 * j + 2 + x];
            acc[4 * j + x] = fmaf(b0, m00, b1 * m01);
            acc[4 * j + 2 + x] = fmaf(b0, m10, b1 * m11);
          }
          if (j == CPOLL - 1 || j == 19) asm volatile("" : "+f"(acc[4 * j]), "+f"(acc[4 * j + 1]), "+f"(acc[4 * j + 2]), "+f"(acc[4 * j + 3])::"memory");
        }
        {
          uint32_t it = 0;
          while (__any_sync(0xffffffffu, tg[0] != tag || tg[1] != tag || tg[2] != tag)) {
#pragma unroll
            for (int i = 0; i < 3; i++)
              if (tg[i] != tag) tg[i] = rec_ld(ep - 4 * i * DM, ev[i].x, ev[i].y);
            trap_if(++it > SPIN_LIMIT);
          }
          c = cfma(p640, cfma(p640, ev[2], ev[1]), ev[0]);
          c = cmul(c, p160q);
          c.x += __shfl_xor_sync(0xffffffffu, c.x, 1); c.y += __shfl_xor_sync(0xffffffffu, c.y, 1);
          c.x += __shfl_xor_sync(0xffffffffu, c.x, 2); c.y += __shfl_xor_sync(0xffffffffu, c.y, 2);
        }
        if (tid == 0) TS(4 + 8 * l);
        if (HOLD1 && wg == 1 && l == 1 && has2) mbar_wait(bars + 8 * HOLD1);
        const uint32_t c0 = (uint32_t)clock(), tm = (tid & 7) == 4 * side + w;
        c = cfma(pLq, c, ex);
        float2 hh = make_float2(fmaf(c.x, m00, c.y * m01), fmaf(c.x, m10, c.y * m11));
        uint8_t* hb = g_h + (10 * wg + 2 * GP) * 8192 + (4 * side + w) * 1024 + (tid_opaque() & 31) * 4;
#pragma unroll
        for (int j4 = 0; j4 < 5; j4++) {
          if (PACE && j4 > 0 && wg == 1 && l == 1) { while (__any_sync(0xffffffffu, (uint32_t)clock() - c0 < PACE * j4)) {} }
          const int ng = 20 * T1 + 4 * j4;
          uint8_t* hp = hb + (size_t)(ng >> 3) * 163840 + (ng & 7) * 128;
#pragma unroll
          for (int jj = 0; jj < 4; jj++) {
            const int j = 4 * j4 + jj;
            const float2 h0 = cfma(lamc, hh, make_float2(acc[4 * j + 0], acc[4 * j + 2]));
            hh = cfma(lamc, h0, make_float2(acc[4 * j + 1], acc[4 * j + 3]));
            if (j4 < 4 || !last) {
              *(uint32_t*)(hp + jj * 128) = tag_word(pack_bf16(h0.x, hh.x), tm, 1 - l);
              *(uint32_t*)(hp + jj * 128 + 8192) = tag_word(pack_bf16(h0.y, hh.y), tm, 1 - l);
            }
          }
        }
        if (l == 0) mbar_arrive(bars + 8 * (B_HST + wg));
        if (tid == 0) TS(5 + 8 * l);
        if (tid == 128) TS(l ? 25 : 19);
        if (l == 0 && wid == 4) {
          mbar_wait(bars + 8 * B_HST);
          mbar_wait(bars + 8 * (B_HST + 1));
          if ((tid & 31) < 4) h_release(0, T1, tid & 3);
          __syncwarp();
          if (tid == 128) { mbar_arrive(bars + 8 * B_REL); TS(6); }
        }
      }
      if (l == 0) {
        ROLE(role)
        if (has2) {
          CvCtx cc;
          mbar_wait(bars + 8 * B_CTAB);
          cv_setup(cc);
          mbar_wait(bars + 8 * (B_G1DONE + 9));
#pragma unroll 1
          for (int c = (wg + 2) & 3; c < 5; c += 4) conv_channel(c, cc);
          if ((tid & 127) == 0) TS(wg == 2 ? 32 : (wg == 3 ? 50 : 7 + wg));
        }
      }
      if (wg >= 2) break;
    }
    if (wg < 2 && (role >> 16)) {
      const int ln = tid_opaque() & 31;
      const uint8_t* src = g_h + ((role >> 8) & 63) * 163840;
      uint32_t ph = 0;
      if (wg == 0) {
        mbar_wait(bars + 8 * (B_G1DONE + 19));
        if (SPEC0 + SPECW) __nanosleep(SPEC0 + SPECW * w);
        if (tid == 0) TS(23);
        if (tid == 96) mbar_arrive(bars + 8 * B_SPEC);
        if (!SPLITI && w < 3 && elect_one()) { mbar_expect_tx(bars + 8 * (B_XV + w + 4), G2_XB); }
      }
#pragma unroll 1
      for (int k = 10 * wg + w; k < 10 * wg + 10; k += 4) {
        if (k < (SPLITI ? S2 : 4) && elect_one()) {
          mbar_expect_tx(bars + 8 * (B_XV + k), G2_XB);
          bulk_g2s(sb + k * G2_XB, src + k * 8192, G2_XB, bars + 8 * (B_XV + k));
          if (!SPLITI && k < 3) bulk_g2s(sb + (k + 4) * G2_XB, src + (k + 4) * 8192, G2_XB, bars + 8 * (B_XV + k + 4));
        }
        validate_block(bars + 8 * (B_XV + k), bars + 8 * (B_G2FULL + 20 + k), sb + (k % S2) * G2_XB, src + k * 8192,
                       (ln & 7) * 1028 + (ln >> 3) * 32, bars + 8 * (B_RETRY + wid), ph);
      }
    }
    if (wg == 3) {
    ROLE(role)
    const int pw = wid & 3, gpc = 2 * min(m2 >> 3, 3) + (dg >> 1);
    mbar_wait(bars + 8 * B_EP);
    const unsigned tag = lds32(sb + EP_OFF + 20);
    if (pw == 0) {
      if (elect_one()) {
#pragma unroll 1
        for (int l = 0; l < 2; l++) {
          uint32_t dst = sb;
          if (l == 1) {
            dst = sb + G2_WOFF;
#pragma unroll 1
            for (int k = 0; k < 10; k++) {
              mbar_wait(k > 4 ? bars + 8 * (B_G1DONE + 5 + k) : (has2 ? bars + 8 * (B_G2DONE + 14 + min(k, 3)) : bars + 8 * (B_G1DONE + 9)));
              mbar_expect_tx(bars + 8 * (B_G1FULL + 10 + k), 16384);
              tma5(dst, &p.mB, 64 * k, 0, 0, 4 * side, 2 * GP, bars + 8 * (B_G1FULL + 10 + k));
              dst += 16384; if (k == 4) dst = sb + G2_WOFF;
            }
          }
          if (has2) {
            const uint32_t fb2 = bars + 8 * (B_G2FULL + 20 * l), wb2 = bars + 8 * (B_G2DONE + 20 * l - S2);
            dst = sb + G2_WOFF + (WTAIL ? 4 * l * G2_WB : 0);
            int kc = 0;
#pragma unroll 1
            for (int k = 0; k < 20; k++) {
              mbar_wait(k >= S2 ? wb2 + 8 * k : bars + 8 * (l ? B_G1DONE + (WTAIL ? (k < 3 ? 15 + k : 13 + k) : 19) : (k == 5 ? B_XFREE : (k == 6 ? B_SFREE : B_REL))));
              mbar_expect_tx(fb2 + 8 * k, G2_WB);
              tma5(dst, &p.mCre + (k & 1), kc, 0, 0, 0, 10 * dg, fb2 + 8 * k);
              kc += (k & 1) << 7; if (k == 9) kc = 64;
              dst += G2_WB; if (dst == sb + G2_WOFF + S2 * G2_WB) dst = sb + G2_WOFF;
            }
          }
        }
      }
    } else if (pw == 1) {
#pragma unroll 1
      for (int l = 0; l < 2; l++) {
        if (l == 1) {
          mbar_wait(bars + 8 * (has2 ? B_G2DONE + 19 : B_G1DONE + 9));
          if (has2) mbar_wait(bars + 8 * B_UST);
          cnt_poll(&g_ucnt[gpc * 32], 128 * tag);
          fence_async_global();
          if (elect_one()) {
            TS(20);
            const int bytes = last ? 16384 : 20480;
            const uint8_t* src = g_u + T1 * 204800;
            uint32_t dst = sb + X1_OFF;
#pragma unroll 1
            for (int k = 0; k < 10; k++) {
              if (k > 4) mbar_wait(bars + 8 * (B_G1DONE + 5 + k));
              mbar_expect_tx(bars + 8 * (B_G1FULL + 10 + k), bytes);
              bulk_g2s(dst, src, bytes, bars + 8 * (B_G1FULL + 10 + k));
              src += 20480; dst += 20480; if (dst == sb + G_OFF) dst = sb; if (k == 4) dst = sb + X1_OFF;
            }
          }
          __syncwarp();
        }
        if (has2) {
          if (l == 0) {
            mbar_wait(bars + 8 * B_REL);
            cnt_poll(&g_hcnt[gpc * 32], 40 * tag);
            fence_async_global();
          }
          if (elect_one()) {
            if (l == 0) TS(21);
            const uint32_t fb2 = bars + 8 * (l ? B_XV : B_G2FULL), wb2 = bars + 8 * (B_G2DONE + 20 * l - S2);
            const uint8_t* src = g_h + m2 * 163840 + l * S2 * 8192;
            uint32_t dst = sb;
#pragma unroll 1
            for (int k = l * S2; k < 20; k++) {
              if (k >= 5) mbar_wait(k >= S2 ? wb2 + 8 * k : bars + 8 * B_SFREE);
              mbar_expect_tx(fb2 + 8 * k, G2_XB);
              bulk_g2s(dst, src, G2_XB, fb2 + 8 * k);
              src += 8192; dst += G2_XB; if (dst == sb + S2 * G2_XB) dst = sb;
            }
          }
          __syncwarp();
        }
      }
    } else if (pw == 2) {
#pragma unroll 1
      for (int l = 0; l < 2; l++) {
        if (l == 1) {
          if (has2) {
            mbar_wait(bars + 8 * B_UST);
            if (lane < 8) red_rel(&g_ucnt[lane * 32]);
            __syncwarp();
            if (lane == 0) TS(38);
          }
          float xa[2], xb[2];
          mbar_wait(bars + 8 * (B_G1FULL + 11));
          stat_table<1>(T1, tag, 4, g_stats, g_stats, xa, xb);
          mbar_arrive(bars + 8 * (B_STAB + 1));
        }
        if (l == 0 && has2 && elect_one()) {
#pragma unroll 1
          for (int i = 0; i < 5; i++) {
            const int c = i < 3 ? i : 7 - i;
            mbar_wait(bars + 8 * (B_CVDONE + c));
            bulk_s2g(g_G + (cch0 + 32 * c) * 4096, cv_stage(c), 4096);
          }
          asm volatile("cp.async.bulk.commit_group;" ::: "memory");
          asm volatile("cp.async.bulk.wait_group.read 0;" ::: "memory");
          mbar_arrive(bars + 8 * B_SFREE);
          asm volatile("cp.async.bulk.wait_group 0;" ::: "memory");
          TS(48);
          fence_async_global();
          asm volatile("fence.acq_rel.gpu;" ::: "memory");
#pragma unroll
          for (int i = 0; i < 4; i++) red_rlx(&g_gcnt[(dg * 4 + i) * 32]);
          TS(49);
          mbar_arrive(bars + 8 * (B_GO + 1));
        }
        __syncwarp();
      }
    } else if (has2) {
      mbar_wait(bars + 8 * B_REL);
      if (!CPF && elect_one()) {
        l2_prefetch(p.cre + (160 * dg + 5 * m2) * DM, 6400); l2_prefetch(p.cim + (160 * dg + 5 * m2) * DM, 6400);
      }
      mbar_wait(bars + 8 * (B_GO + 1));
      flag_poll(&g_gcnt[(dg * 4 + (m2 >> 3)) * 32], 32 * tag);
      fence_async_global();
      if (elect_one()) {
        TS(29);
        mbar_expect_tx(bars + 8 * B_GFULL, 20480);
        tma5(sb + G_OFF, &p.mG, 64 * m2, 0, 0, 0, 10 * dg, bars + 8 * B_GFULL);
      }
    }
    } else if (wg == 2 && (role >> 16)) {
      float acc[80];
      float off[2] = {mean0[0], mean0[1]};
      const unsigned tag = lds32(sb + EP_OFF + 20);
      dskip_init<true>(acc, mean0, rstd0);
      mbar_arrive(bars + 8 * B_XFREE);
      mbar_wait(bars + 8 * (B_CVDONE + 2));
      mbar_wait(bars + 8 * (B_CVDONE + 3));
#pragma unroll 1
      for (int step = 1; step < 4; step++) {
        const int l = step >> 1;
        if (step != 2) {
          uint32_t alo = desc_lo(sb, 1024), blo = desc_lo(sb + G2_WOFF, 16) + (WTAIL ? l * (G2_WB >> 2) : 0);
          uint32_t fb = bars + 8 * (B_G2FULL + 20 * l);
          fence_regs(acc);
          mbar_wait(fb);
          if (tid == 256) TS(33 + 6 * l);
#pragma unroll 1
          for (int k = 0; k < 20; k++) {
            if (l == TSL && (k & 3) == 3 && tid == 256) TS(56 + (k >> 2));
            uint32_t ok; const uint32_t nb = k < 19 ? fb + 8 : fb;
            wgmma_fence();
#pragma unroll
            for (int kk = 0; kk < 4; kk++) {
              wgmma_n160<1>(acc, alo + kk * 128, desc_hi(128, 0), blo + kk * 2, desc_hi(1024, 1));
              if (kk == 0) ok = mbar_test(nb);
            }
            wgmma_commit();
            alo += G2_XB >> 4; blo += G2_WB >> 4;
            if (alo == desc_lo(sb + S2 * G2_XB, 1024)) alo = desc_lo(sb, 1024);
            if (blo == desc_lo(sb + G_OFF, 16)) blo = desc_lo(sb + G2_WOFF, 16);
            wgmma_wait<1>();
            if (k > 0 && tid == 256) mbar_arrive(fb + 8 * (B_G2DONE - B_G2FULL - 1));
            if (!ok) mbar_wait(nb);
            fb += 8;
          }
          wgmma_wait<0>();
          fence_regs(acc);
          if (tid == 256) TS(34 + 6 * l);
          if (tid == 256) mbar_arrive(bars + 8 * (B_G2DONE + 20 * l + 19));
        }
        ROLE(role)
        const int tq = tid_opaque() & 31, n0 = 64 * m2 + 16 * w + (tq >> 2);
        stats_publish<false>(step, n0, dg, tag, acc);
        uint32_t gf[10][4];
        mbar_wait(bars + 8 * B_GFULL);
        uint32_t ga = sb + G_OFF + (8 * (tq >> 4) + (tq & 7)) * 128 + (((2 * w + ((tq >> 3) & 1)) ^ ((2 * m2) & 6) ^ (tq & 7)) << 4), gstep = 2048;
        if (step == 2) { ga = sb + DX_OFF + (8 * (tq >> 4) + (tq & 7)) * 16; gstep = 256; }
#pragma unroll
        for (int J = 0; J < 2; J++) ldsm4t(gf[J], ga + J * gstep);
        if (tid == 256) TS(35 + 6 * l);
        uint8_t* dst[2][2];
#pragma unroll
        for (int h = 0; h < 2; h++) {
          if (l == 0) {
            const int ng = 8 * m2 + 2 * w + h, T = ng / 20;
            uint8_t* ub = g_u + (T * 204800 + (ng - 20 * T) * 1024 + (tq & 2) * 64 + (tq & 28) * 4 + (tq & 1) * 8 + (5 * dg >> 1) * 20480);
            dst[h][1] = ub + ((dg & 1) ? 20480 - 512 : 0);
            dst[h][0] = ub + (dg & 1) * 512;
          } else {
            dst[h][0] = dst[h][1] = (uint8_t*)(p.out + (n_to_t(n0 + 8 * h) * DM + 160 * dg + 4 * (tq & 3)));
          }
        }
        float mean[2], rstd[2];
        stats_get(step, n0, tag, mean, rstd);
        if (tid == 256) TS(36 + 6 * l);
        off[0] += mean[0]; off[1] += mean[1];
        const float ov[2] = {step == 3 ? off[0] : 0.f, step == 3 ? off[1] : 0.f};
#pragma unroll
        for (int J = 0; J < 10; J++) {
          if (J + 2 < 10) ldsm4t(gf[J + 2 < 10 ? J + 2 : 0], ga + (J + 2) * gstep);
#pragma unroll
          for (int x = 0; x < 8; x++) {
            const int h = (x >> 1) & 1;
            const uint32_t gwd = gf[J][x >> 1];
            const float t = fmaf(rstd[h], (x & 1) ? bf_hi(gwd) : bf_lo(gwd), 1.f);
            acc[8 * J + x] = fmaf(acc[8 * J + x], t, fmaf(-mean[h], t, ov[h]));
          }
#pragma unroll
          for (int h = 0; h < 2; h++) {
            if (step == 1)
              *(uint2*)(dst[h][(J >> 1) & 1] + (J >> 2) * 20480 + (J & 3) * 256) =
                  make_uint2(pack_bf16(acc[8 * J + 2 * h], acc[8 * J + 2 * h + 1]), pack_bf16(acc[8 * J + 4 + 2 * h], acc[8 * J + 5 + 2 * h]));
            if (step == 3)
              *(float4*)(dst[h][0] + 64 * J) = make_float4(acc[8 * J + 2 * h], acc[8 * J + 2 * h + 1], acc[8 * J + 4 + 2 * h], acc[8 * J + 5 + 2 * h]);
          }
          __syncwarp();
        }
        if (step == 1) {
          mbar_arrive(bars + 8 * B_UST);
          if (tid == 256) TS(37);
          for (int n = tid & 127; n < 160; n += 128) {
            const int d = 16 * (n >> 4) + 4 * ((n >> 1) & 3) + 2 * ((n >> 3) & 1) + (n & 1);
            const uint32_t dw = lds32(sb + DTAB_OFF + 2 * (d & ~1)), dd = __byte_perm(dw, dw, (d & 1) ? 0x3232 : 0x1010);
            sts128(sb + DX_OFF + 16 * n, make_uint4(dd, dd, dd, dd));
          }
          bar_sync(3, 128);
        } else if (step == 2) {
          if (tid == 256) TS(22);
          mbar_wait(bars + 8 * (B_G1FULL + 11));
          float xa[2], xb[2];
          stat_table<1>(T1, tag, w, g_stats, g_stats, xa, xb);
          mbar_arrive(bars + 8 * (B_STAB + 1));
          if (tid == 256) TS(27);
          mbar_wait(bars + 8 * (B_G1DONE + 19));
          keep_warm(bars + 8 * WEND, 3);
        } else {
          if (tid == 256) {
            TS(43);
            if (m2 == 31 && dg == 3) asm volatile("st.relaxed.gpu.global.u32 [%0], %1;" ::"l"(g_epoch), "r"(tag + 1) : "memory");
          }
        }
      }
    }
  }
}

typedef CUresult (*EncFn)(CUtensorMap*, CUtensorMapDataType, cuuint32_t, void*, const cuuint64_t*, const cuuint64_t*,
                          const cuuint32_t*, const cuuint32_t*, CUtensorMapInterleave, CUtensorMapSwizzle,
                          CUtensorMapL2promotion, CUtensorMapFloatOOBfill);

void encode(EncFn fn, CUtensorMap* m, const void* ptr, int rank, const cuuint64_t* dims, const cuuint64_t* strides, const cuuint32_t* box,
            CUtensorMapSwizzle swz = CU_TENSOR_MAP_SWIZZLE_128B, int prom = 2) {
  cuuint32_t es[5] = {1, 1, 1, 1, 1};
  fn(m, CU_TENSOR_MAP_DATA_TYPE_BFLOAT16, rank, (void*)ptr, dims, strides, box, es, CU_TENSOR_MAP_INTERLEAVE_NONE,
     swz, (CUtensorMapL2promotion)prom, CU_TENSOR_MAP_FLOAT_OOB_FILL_NONE);
}

}

extern "C" void kernel_launch(void* const* d_in, const int* in_sizes, int n_in, void* d_out, int out_size) {
  (void)in_sizes; (void)n_in; (void)out_size;
  Params p;
  typedef const __nv_bfloat16* BP;
  p.x = (BP)d_in[0]; p.lre = (BP)d_in[1]; p.lim = (BP)d_in[2]; p.bre = (BP)d_in[3]; p.bim = (BP)d_in[4];
  p.cre = (BP)d_in[5]; p.cim = (BP)d_in[6]; p.logdt = (BP)d_in[7]; p.dskip = (BP)d_in[8];
  p.k = (BP)d_in[10]; p.v = (BP)d_in[11]; p.shiftk = (BP)d_in[12]; p.ssmk = (BP)d_in[13]; p.ssmD = (BP)d_in[14];
  p.out = (float*)d_out;
  for (int sm = 0; sm < 132; sm++) {
    const int tpc = sm >> 1, side = sm & 1;
    int gpc, gi;
    if (tpc < 32) { gpc = tpc & 7; gi = tpc >> 3; }
    else if (tpc < 60) { gpc = 1 + (tpc - 32) % 7; gi = 4 + (tpc - 32) / 7; }
    else if (tpc < 62) { gpc = tpc - 54; gi = 8; }
    else { gpc = 0; gi = tpc - 58; }
    const int pos = 8 * gpc + gi + (gpc == 7 ? 1 : 0);
    int T1, GP;
    if (pos < 52) { const int hh = pos / 26, x = pos - 26 * hh; T1 = x >> 1; GP = 2 * hh + (x & 1); }
    else { T1 = pos - 52; GP = 4; }
    const int m2 = 8 * (gpc >> 1) + gi, dg = 2 * (gpc & 1) + side;
    p.role[sm] = pos == 65 ? -1 : (T1 | (GP << 4) | (side << 7) | (m2 << 8) | (dg << 14) | ((gi < 8) << 16));
  }
  void* fnp = nullptr;
  cudaDriverEntryPointQueryResult qr;
  cudaGetDriverEntryPoint("cuTensorMapEncodeTiled", &fnp, cudaEnableDefault, &qr);
  EncFn fn = (EncFn)fnp;
  void* gG = nullptr;
  cudaGetSymbolAddress(&gG, g_G);
  void* gKV = nullptr;
  cudaGetSymbolAddress(&gKV, g_kv);
  {
    cuuint64_t dims[5] = {32, 32, 10, 32, 4}, st[4] = {20480, 2048, 64, 655360}; cuuint32_t box[5] = {32, 35, 2, 1, 1};
    encode(fn, &p.mU, gKV, 5, dims, st, box, CU_TENSOR_MAP_SWIZZLE_NONE, 1);
  }
  const cuuint64_t RB = DM * 2;
  {
    p.swap = p.bim < p.bre;
    const char* lo = (const char*)(p.swap ? p.bim : p.bre); const char* hi = (const char*)(p.swap ? p.bre : p.bim);
    cuuint64_t dims[5] = {640, 8, 2, 8, 10}, st[4] = {RB, (cuuint64_t)(hi - lo), 8 * RB, 64 * RB}; cuuint32_t box[5] = {64, 8, 2, 4, 2};
    encode(fn, &p.mB, lo, 5, dims, st, box);
  }
  {
    cuuint64_t dims[5] = {640, 2, 4, 2, 40}, st[4] = {RB, 4 * RB, 2 * RB, 16 * RB}; cuuint32_t box[5] = {64, 2, 4, 2, 10};
    encode(fn, &p.mCre, p.cre, 5, dims, st, box); encode(fn, &p.mCim, p.cim, 5, dims, st, box);
    cuuint64_t dimg[5] = {2048, 2, 4, 2, 40}, stg[4] = {4096, 4 * 4096, 2 * 4096, 16 * 4096};
    encode(fn, &p.mG, gG, 5, dimg, stg, box);
  }
  {
    cuuint64_t dims[4] = {640, 2, 4, 900}, st[3] = {RB, 40 * RB, 2 * RB}; cuuint32_t box[4] = {64, 2, 4, 20};
    encode(fn, &p.mX, p.x, 4, dims, st, box);
    cuuint64_t diml[4] = {640, 2, 4, 16}, stl[3] = {RB, 32 * RB, 2 * RB};
    encode(fn, &p.mXl, p.x + (size_t)1920 * DM, 4, diml, stl, box);
    cuuint32_t boxt[4] = {160, 2, 4, 4};
    encode(fn, &p.mXt, p.x, 4, dims, st, boxt, CU_TENSOR_MAP_SWIZZLE_NONE);
    encode(fn, &p.mXtl, p.x + (size_t)1920 * DM, 4, diml, stl, boxt, CU_TENSOR_MAP_SWIZZLE_NONE);
    cuuint64_t dk[3] = {640, 2000, 4}, sk[2] = {RB, 16 * RB}; cuuint32_t bk[3] = {32, 19, 4}, bv[3] = {32, 17, 4};
    encode(fn, &p.mK, p.k, 3, dk, sk, bk, CU_TENSOR_MAP_SWIZZLE_NONE);
    encode(fn, &p.mV, p.v, 3, dk, sk, bv, CU_TENSOR_MAP_SWIZZLE_NONE);
  }
  cudaFuncSetAttribute(fused_kernel, cudaFuncAttributeMaxDynamicSharedMemorySize, SMEM_BYTES);
  cudaLaunchConfig_t cfg = {};
  cfg.gridDim = dim3(132); cfg.blockDim = dim3(512); cfg.dynamicSmemBytes = SMEM_BYTES; cfg.stream = cudaStreamPerThread;
  cudaLaunchKernelEx(&cfg, fused_kernel, p);
}
```

```cpp
#include <cuda_runtime.h>
#include <cuda.h>
#include <cuda_bf16.h>
#include <stdint.h>

namespace {

constexpr int SEQ = 2048, DM = 640;
constexpr int NT1 = 13;
#define EXP 0
#define WPF1 3
#define WPF2 7
#define CPOLL 10
#define KV0 1
#define TAPLATE 1
#define STG_D 3
#define STG_KK 1
#define HOLD1 0
#define SPEC0 100
#define WREL 0
#define UREL 1
#define TSL 1
#define STG0 2
#define WTAIL 1
#define PFD 1
#define TAPW 0
#define TPF 4
#define CPF 0
#define MK0 8
#define MK1 4
#define PACE 350
#define TAPN 2
#define SPLITI 1
#define SPECW 60
#define WEND B_SPEC
#define PAUSE0 6
#define PAUSE_K 5
constexpr uint32_t SPIN_LIMIT = 1u << 22;

__device__ __align__(1024) uint8_t g_h[32 * 20 * 8192];
__device__ __align__(1024) uint8_t g_u[NT1 * 10 * 20480];
__device__ __align__(1024) uint8_t g_kv[DM * 4096];
__device__ __align__(1024) uint8_t g_G[DM * 4096];
__device__ __align__(128) uint4 g_E[2 * NT1 * DM];
__device__ __align__(128) uint4 g_stats[4 * 4 * SEQ];
__device__ __align__(128) uint4 g_sB[DM * 2];
__device__ __align__(128) unsigned g_hcnt[8 * 32];
__device__ __align__(128) unsigned g_ucnt[8 * 32];
__device__ __align__(128) unsigned g_kvcnt[16 * 32];
__device__ __align__(128) unsigned g_gcnt[16 * 32];
__device__ __align__(128) unsigned g_epoch[32] = {1};
#define TS(i) do {} while (0)

struct Params {
  CUtensorMap mX, mB, mXl, mK, mV, mXt, mXtl, mCre, mCim, mG, mU;
  const __nv_bfloat16 *x, *lre, *lim, *bre, *bim, *cre, *cim, *logdt, *dskip, *k, *v, *shiftk, *ssmk, *ssmD;
  float* out;
  int swap;
  int role[132];
};

constexpr uint32_t sb = 1024;
constexpr uint32_t G1_STAGE = 36864, G1_XOFF = 16384;
constexpr int S1 = 4;
constexpr uint32_t XT_OFF = 159744, KS_OFF = 180224, KV_PIECE = 9216;
constexpr uint32_t G2_XB = 8192, G2_WB = 20480, G2_WOFF = 57344, G_OFF = 200704;
constexpr uint32_t X1_OFF = 139264;
constexpr int S2 = 7;
constexpr uint32_t CV_OFF = KS_OFF, CV_K = 128, CV_PL = 2240, CV_U = CV_K + 4096, CV_B = KV_PIECE;
constexpr uint32_t MISC = 226304;
constexpr uint32_t BAR_OFF = MISC;
constexpr int B_G1FULL = 0, B_G1DONE = 20, B_G2FULL = 40,
              B_G2DONE = 85, B_GFULL = 125, B_EP = 126, B_CVFULL = 129  , B_STG = 134  , B_REL = 136  , B_SFREE = 138,
              B_GO = 139  , B_PUB = 147,
              B_CVDONE = 148  , B_STAB = 153  , B_XFREE = 155, B_HST = 156  , B_UST = 158,
              B_CTAB = 160, B_PREP = 161, B_XT = 162, B_KV = 163  , B_PREP2 = 84, B_PD = 168  ,
              B_XV = 173  , B_RETRY = 193  , B_SPEC = 202;
constexpr uint32_t bars = sb + BAR_OFF;
constexpr uint32_t STAB_OFF = MISC + 1648;
constexpr uint32_t CTAB_OFF = STAB_OFF + 640;
constexpr uint32_t DTAB_OFF = CTAB_OFF + 1536;
constexpr uint32_t EP_OFF = DTAB_OFF + 320;
constexpr uint32_t SO_OFF = EP_OFF + 32;
constexpr uint32_t TAP_OFF = 147456;
constexpr uint32_t MX0_OFF = TAP_OFF + 1280, MX1_OFF = G_OFF + 20480;
constexpr uint32_t DX_OFF = MX1_OFF + 2560;
constexpr uint32_t SMEM_BYTES = 232448;
static_assert(SO_OFF + 1536 <= SMEM_BYTES, "smem");

__device__ __forceinline__ void trap_if(bool c) { asm volatile("{\n.reg .pred p;\nsetp.ne.u32 p, %0, 0;\n@p trap;\n}\n" ::"r"((uint32_t)c)); }
__device__ __forceinline__ uint32_t smem_u32(const void* p) { return (uint32_t)__cvta_generic_to_shared(p); }
__device__ __forceinline__ void mbar_init(uint32_t bar, int cnt) { asm volatile("mbarrier.init.shared::cta.b64 [%0], %1;" ::"r"(bar), "r"(cnt) : "memory"); }
__device__ __forceinline__ void mbar_expect_tx(uint32_t bar, int bytes) { asm volatile("mbarrier.arrive.expect_tx.shared::cta.b64 _, [%0], %1;" ::"r"(bar), "r"(bytes) : "memory"); }
__device__ __forceinline__ void mbar_arrive(uint32_t bar) { asm volatile("mbarrier.arrive.shared::cta.b64 _, [%0];" ::"r"(bar) : "memory"); }
__device__ __forceinline__ bool elect_one() {
  uint32_t e; asm volatile("{\n.reg .pred P;\nelect.sync _|P, 0xffffffff;\nselp.u32 %0, 1, 0, P;\n}\n" : "=r"(e)); return e != 0;
}
__device__ __forceinline__ void mbar_wait(uint32_t bar) {
  asm volatile(
      "{\n.reg .pred p;\n.reg .u32 c;\nmov.u32 c, 0;\n"
      "W_%=:\nmbarrier.try_wait.parity.shared::cta.b64 p, [%0], 0;\n@p bra D_%=;\n"
      "add.u32 c, c, 1;\nsetp.lt.u32 p, c, %1;\n@p bra W_%=;\ntrap;\nD_%=:\n}\n" ::"r"(bar), "n"(SPIN_LIMIT) : "memory");
}
__device__ __forceinline__ uint32_t mbar_test(uint32_t bar) {
  uint32_t ok;
  asm volatile("{\n.reg .pred p;\nmbarrier.test_wait.parity.shared::cta.b64 p, [%1], 0;\nselp.u32 %0, 1, 0, p;\n}\n" : "=r"(ok) : "r"(bar) : "memory");
  return ok;
}
__device__ __forceinline__ void tma3(uint32_t dst, const CUtensorMap* m, int c0, int c1, int c2, uint32_t bar) {
  asm volatile("cp.async.bulk.tensor.3d.shared::cluster.global.mbarrier::complete_tx::bytes [%0], [%1, {%3,%4,%5}], [%2];"
               ::"r"(dst), "l"(m), "r"(bar), "r"(c0), "r"(c1), "r"(c2) : "memory");
}
__device__ __forceinline__ void tma4(uint32_t dst, const CUtensorMap* m, int c0, int c1, int c2, int c3, uint32_t bar) {
  asm volatile("cp.async.bulk.tensor.4d.shared::cluster.global.mbarrier::complete_tx::bytes [%0], [%1, {%3,%4,%5,%6}], [%2];"
               ::"r"(dst), "l"(m), "r"(bar), "r"(c0), "r"(c1), "r"(c2), "r"(c3) : "memory");
}
__device__ __forceinline__ void tma5(uint32_t dst, const CUtensorMap* m, int c0, int c1, int c2, int c3, int c4, uint32_t bar) {
  asm volatile("cp.async.bulk.tensor.5d.shared::cluster.global.mbarrier::complete_tx::bytes [%0], [%1, {%3,%4,%5,%6,%7}], [%2];"
               ::"r"(dst), "l"(m), "r"(bar), "r"(c0), "r"(c1), "r"(c2), "r"(c3), "r"(c4) : "memory");
}
__device__ __forceinline__ void bulk_g2s(uint32_t dst, const void* src, int bytes, uint32_t bar) {
  asm volatile("cp.async.bulk.shared::cluster.global.mbarrier::complete_tx::bytes [%0], [%1], %2, [%3];"
               ::"r"(dst), "l"(src), "r"(bytes), "r"(bar) : "memory");
}
__device__ __forceinline__ void bulk_s2g(void* dst, uint32_t src, int bytes) {
  asm volatile("cp.async.bulk.global.shared::cta.bulk_group [%0], [%1], %2;" ::"l"(dst), "r"(src), "r"(bytes) : "memory");
}
__device__ __forceinline__ void l2_prefetch(const void* src, int bytes) {
  asm volatile("cp.async.bulk.prefetch.L2.global [%0], %1;" ::"l"(src), "r"(bytes) : "memory");
}
__device__ __forceinline__ void wgmma_fence() { asm volatile("wgmma.fence.sync.aligned;" ::: "memory"); }
__device__ __forceinline__ void wgmma_commit() { asm volatile("wgmma.commit_group.sync.aligned;" ::: "memory"); }
template <int N> __device__ __forceinline__ void wgmma_wait() { asm volatile("wgmma.wait_group.sync.aligned %0;" ::"n"(N) : "memory"); }
__host__ __device__ constexpr uint32_t desc_lo(uint32_t addr, uint32_t lbo) { return ((addr & 0x3FFFF) >> 4) | ((lbo >> 4) << 16); }
__host__ __device__ constexpr uint32_t desc_hi(uint32_t sbo, uint32_t swz) { return (sbo >> 4) | (swz << 30); }
__device__ __forceinline__ void bar_sync(int id, int n) { asm volatile("bar.sync %0, %1;" ::"r"(id), "r"(n) : "memory"); }
__device__ __forceinline__ uint32_t lds32(uint32_t a) { uint32_t v; asm volatile("ld.shared.u32 %0, [%1];" : "=r"(v) : "r"(a) : "memory"); return v; }
__device__ __forceinline__ float2 lds64f(uint32_t a) { float2 v; asm volatile("ld.shared.v2.f32 {%0,%1}, [%2];" : "=f"(v.x), "=f"(v.y) : "r"(a) : "memory"); return v; }
__device__ __forceinline__ float4 lds128f(uint32_t a) { float4 v; asm volatile("ld.shared.v4.f32 {%0,%1,%2,%3}, [%4];" : "=f"(v.x), "=f"(v.y), "=f"(v.z), "=f"(v.w) : "r"(a) : "memory"); return v; }
__device__ __forceinline__ void ldsm4t(uint32_t (&r)[4], uint32_t a) {
  asm volatile("ldmatrix.sync.aligned.m8n8.x4.trans.shared.b16 {%0,%1,%2,%3}, [%4];" : "=r"(r[0]), "=r"(r[1]), "=r"(r[2]), "=r"(r[3]) : "r"(a) : "memory");
}
__device__ __forceinline__ uint4 ldv128(const void* a) { uint4 v; asm volatile("ld.global.nc.v4.u32 {%0,%1,%2,%3}, [%4];" : "=r"(v.x), "=r"(v.y), "=r"(v.z), "=r"(v.w) : "l"(a) : "memory"); return v; }
__device__ __forceinline__ uint2 ldv64(const void* a) { uint2 v; asm volatile("ld.global.nc.v2.u32 {%0,%1}, [%2];" : "=r"(v.x), "=r"(v.y) : "l"(a) : "memory"); return v; }
__device__ __forceinline__ uint32_t ldv16(const void* a) { uint32_t v; asm volatile("ld.global.nc.u16 %0, [%1];" : "=r"(v) : "l"(a) : "memory"); return v; }
__device__ __forceinline__ void sts128(uint32_t a, uint4 v) { asm volatile("st.shared.v4.u32 [%0], {%1,%2,%3,%4};" ::"r"(a), "r"(v.x), "r"(v.y), "r"(v.z), "r"(v.w) : "memory"); }
__device__ __forceinline__ void sts32(uint32_t a, uint32_t v) { asm volatile("st.shared.u32 [%0], %1;" ::"r"(a), "r"(v) : "memory"); }
__device__ __forceinline__ void sts64f(uint32_t a, float x, float y) { asm volatile("st.shared.v2.f32 [%0], {%1,%2};" ::"r"(a), "f"(x), "f"(y) : "memory"); }
__device__ __forceinline__ void red_rlx(unsigned* p) { asm volatile("red.relaxed.gpu.global.add.u32 [%0], 1;" ::"l"(p) : "memory"); }
__device__ __forceinline__ void red_rel(unsigned* p) { asm volatile("red.release.gpu.global.add.u32 [%0], 1;" ::"l"(p) : "memory"); }
__device__ __forceinline__ void fence_async_global() { asm volatile("fence.proxy.async.global;" ::: "memory"); }
__device__ __forceinline__ void fence_async_smem() { asm volatile("fence.proxy.async.shared::cta;" ::: "memory"); }
__device__ __forceinline__ void rec_st(uint4* p, float a, float b, unsigned tag) {
  asm volatile("{\n.reg .b128 t;\n.reg .b64 lo, hi;\nmov.b64 lo, {%1,%2};\nmov.b64 hi, {%3,%3};\nmov.b128 t, {lo,hi};\n"
               "st.relaxed.gpu.global.b128 [%0], t;\n}\n" ::"l"(p), "r"(__float_as_uint(a)), "r"(__float_as_uint(b)), "r"(tag) : "memory");
}
__device__ __forceinline__ unsigned rec_ld(const uint4* p, float& a, float& b) {
  unsigned x, y, t;
  asm volatile("{\n.reg .b128 t;\n.reg .b64 lo, hi;\n.reg .b32 u;\nld.relaxed.gpu.global.b128 t, [%3];\nmov.b128 {lo,hi}, t;\n"
               "mov.b64 {%0,%1}, lo;\nmov.b64 {%2,u}, hi;\n}\n" : "=r"(x), "=r"(y), "=r"(t) : "l"(p) : "memory");
  a = __uint_as_float(x); b = __uint_as_float(y);
  return t;
}
__device__ __forceinline__ unsigned ld_rlx(const unsigned* p) { unsigned v; asm volatile("ld.relaxed.gpu.global.u32 %0, [%1];" : "=r"(v) : "l"(p) : "memory"); return v; }
__device__ __forceinline__ void flag_poll(const unsigned* p, unsigned target) {
  uint32_t it = 0;
  while (!__all_sync(0xffffffffu, (int)(ld_rlx(p) - target) >= 0)) { trap_if(++it > SPIN_LIMIT); }
  asm volatile("fence.acquire.gpu;" ::: "memory");
}
__device__ __forceinline__ void cnt_poll(const unsigned* p, unsigned target) {
  unsigned a = ld_rlx(p); __nanosleep(100);
  unsigned b = ld_rlx(p); __nanosleep(100);
  unsigned c = ld_rlx(p);
  uint32_t it = 0;
  while (true) {
    if (__all_sync(0xffffffffu, (int)(a - target) >= 0)) break;
    a = ld_rlx(p);
    if (__all_sync(0xffffffffu, (int)(b - target) >= 0)) break;
    b = ld_rlx(p);
    if (__all_sync(0xffffffffu, (int)(c - target) >= 0)) break;
    c = ld_rlx(p);
    trap_if(++it > SPIN_LIMIT);
  }
  asm volatile("fence.acquire.gpu;" ::: "memory");
}
__device__ __forceinline__ void validate_block(uint32_t bar, uint32_t full, uint32_t dst, const uint8_t* src, uint32_t woff, uint32_t rb, uint32_t& ph) {
  uint32_t it = 0, par = 0;
  while (true) {
    uint32_t ok, spins = 0;
    do {
      asm volatile("{\n.reg .pred p;\nmbarrier.try_wait.parity.shared::cta.b64 p, [%1], %2;\nselp.u32 %0, 1, 0, p;\n}\n" : "=r"(ok) : "r"(bar), "r"(par) : "memory");
      trap_if(++spins > SPIN_LIMIT);
    } while (!__all_sync(0xffffffffu, ok));
    uint32_t bad = 0;
#pragma unroll
    for (int i = 0; i < 8; i++) bad |= lds32(dst + woff + 128 * i);
    if (!__any_sync(0xffffffffu, bad & 1)) break;
    if (elect_one()) { mbar_expect_tx(rb, 8192); bulk_g2s(dst, src, 8192, rb); }
    bar = rb; par = ph; ph ^= 1;
    trap_if(++it > 100000);
  }
  if ((threadIdx.x & 31) == 0) mbar_arrive(full);
}
__device__ __forceinline__ uint32_t tag_word(uint32_t v, uint32_t m, uint32_t par) {
  uint32_t r; asm("lop3.b32 %0, %1, %2, %3, 0xb8;" : "=r"(r) : "r"(v), "r"(m), "r"(par)); return r;
}
__device__ __forceinline__ void h_release(int idx, int T, int i) {
  const int Q = (i & 2) ? (T + 2) / 3 - 1 : T / 3;
  if (Q >= 0 && Q < 4 && ((i & 2) == 0 || T % 3 == 0)) red_rel(&g_hcnt[(idx * 8 + 2 * Q + (i & 1)) * 32]);
}
__device__ __forceinline__ uint32_t pack_bf16(float lo, float hi) {
  uint32_t r; asm("cvt.rn.bf16x2.f32 %0, %1, %2;" : "=r"(r) : "f"(hi), "f"(lo)); return r;
}
__device__ __forceinline__ float bf_lo(uint32_t w) { return __uint_as_float(w << 16); }
__device__ __forceinline__ float bf_hi(uint32_t w) { return __uint_as_float(w & 0xffff0000u); }
__device__ __forceinline__ uint32_t hmul2(uint32_t a, uint32_t b) {
  __nv_bfloat162 r = __hmul2_rn(*(__nv_bfloat162*)&a, *(__nv_bfloat162*)&b); return *(uint32_t*)&r;
}
__device__ __forceinline__ uint32_t hadd2(uint32_t a, uint32_t b) {
  __nv_bfloat162 r = __hadd2_rn(*(__nv_bfloat162*)&a, *(__nv_bfloat162*)&b); return *(uint32_t*)&r;
}
__device__ __forceinline__ float2 cmul(float2 a, float2 b) { return make_float2(a.x * b.x - a.y * b.y, a.x * b.y + a.y * b.x); }
__device__ __forceinline__ float2 cfma(float2 a, float2 b, float2 c) {
  return make_float2(fmaf(a.x, b.x, fmaf(-a.y, b.y, c.x)), fmaf(a.x, b.y, fmaf(a.y, b.x, c.y)));
}
template <int N> __device__ __forceinline__ void fence_regs(float (&a)[N]) {
#pragma unroll
  for (int i = 0; i < N; i++) asm volatile("" : "+f"(a[i])::"memory");
}
__device__ __forceinline__ int tid_opaque() { int t; asm volatile("mov.u32 %0, %%tid.x;" : "=r"(t)); return t; }
struct Role { int T1, GP, side, m2, dg, cch0; bool last, has2; };
__device__ __forceinline__ Role unpack_role(int x) {
  Role r; r.T1 = x & 15; r.GP = (x >> 4) & 7; r.side = (x >> 7) & 1; r.m2 = (x >> 8) & 63; r.dg = (x >> 14) & 3;
  r.has2 = (x >> 16) & 1; r.last = r.T1 == NT1 - 1; r.cch0 = 160 * r.dg + r.m2; return r;
}
__device__ __forceinline__ Role fresh_role(int x) { asm volatile("" : "+r"(x)); return unpack_role(__shfl_sync(0xffffffffu, x, 0)); }
#define ROLE(x) const Role R_ = fresh_role(x); const int T1 = R_.T1, GP = R_.GP, side = R_.side, m2 = R_.m2, dg = R_.dg, cch0 = R_.cch0; \
  const bool last = R_.last, has2 = R_.has2; (void)T1; (void)GP; (void)side; (void)m2; (void)dg; (void)cch0; (void)last; (void)has2;
__device__ __forceinline__ int n_to_t(int n) {
  int T = n / 160, nl = n - T * 160;
  int L = (T == NT1 - 1) ? 32 : 40;
  return T * 160 + L * ((nl & 7) >> 1) + 2 * (nl >> 3) + (nl & 1);
}

template<int TA> __device__ __forceinline__ void wgmma_n160(float (&d)[80], uint32_t alo, uint32_t ahi, uint32_t blo, uint32_t bhi){
  asm volatile("{\n.reg .b64 da, db;\nmov.b64 da, {%80,%81};\nmov.b64 db, {%82,%83};\n"
    "wgmma.mma_async.sync.aligned.m64n160k16.f32.bf16.bf16 {%0, %1, %2, %3, %4, %5, %6, %7, %8, %9, %10, %11, %12, %13, %14, %15, %16, %17, %18, %19, %20, %21, %22, %23, %24, %25, %26, %27, %28, %29, %30, %31, %32, %33, %34, %35, %36, %37, %38, %39, %40, %41, %42, %43, %44, %45, %46, %47, %48, %49, %50, %51, %52, %53, %54, %55, %56, %57, %58, %59, %60, %61, %62, %63, %64, %65, %66, %67, %68, %69, %70, %71, %72, %73, %74, %75, %76, %77, %78, %79}, da, db, 1, 1, 1, %84, 0;\n}\n"
    : "+f"(d[0]), "+f"(d[1]), "+f"(d[2]), "+f"(d[3]), "+f"(d[4]), "+f"(d[5]), "+f"(d[6]), "+f"(d[7]), "+f"(d[8]), "+f"(d[9]), "+f"(d[10]), "+f"(d[11]), "+f"(d[12]), "+f"(d[13]), "+f"(d[14]), "+f"(d[15]), "+f"(d[16]), "+f"(d[17]), "+f"(d[18]), "+f"(d[19]), "+f"(d[20]), "+f"(d[21]), "+f"(d[22]), "+f"(d[23]), "+f"(d[24]), "+f"(d[25]), "+f"(d[26]), "+f"(d[27]), "+f"(d[28]), "+f"(d[29]), "+f"(d[30]), "+f"(d[31]), "+f"(d[32]), "+f"(d[33]), "+f"(d[34]), "+f"(d[35]), "+f"(d[36]), "+f"(d[37]), "+f"(d[38]), "+f"(d[39]), "+f"(d[40]), "+f"(d[41]), "+f"(d[42]), "+f"(d[43]), "+f"(d[44]), "+f"(d[45]), "+f"(d[46]), "+f"(d[47]), "+f"(d[48]), "+f"(d[49]), "+f"(d[50]), "+f"(d[51]), "+f"(d[52]), "+f"(d[53]), "+f"(d[54]), "+f"(d[55]), "+f"(d[56]), "+f"(d[57]), "+f"(d[58]), "+f"(d[59]), "+f"(d[60]), "+f"(d[61]), "+f"(d[62]), "+f"(d[63]), "+f"(d[64]), "+f"(d[65]), "+f"(d[66]), "+f"(d[67]), "+f"(d[68]), "+f"(d[69]), "+f"(d[70]), "+f"(d[71]), "+f"(d[72]), "+f"(d[73]), "+f"(d[74]), "+f"(d[75]), "+f"(d[76]), "+f"(d[77]), "+f"(d[78]), "+f"(d[79])
    : "r"(alo), "r"(ahi), "r"(blo), "r"(bhi), "n"(TA));
}
__device__ __forceinline__ void wgmma_rs_n160(float (&d)[80], uint32_t a0, uint32_t a1, uint32_t a2, uint32_t a3, uint32_t blo){
  asm volatile("{\n.reg .b64 db;\nmov.b64 db, {%84,8};\nwgmma.mma_async.sync.aligned.m64n160k16.f32.bf16.bf16 {%0, %1, %2, %3, %4, %5, %6, %7, %8, %9, %10, %11, %12, %13, %14, %15, %16, %17, %18, %19, %20, %21, %22, %23, %24, %25, %26, %27, %28, %29, %30, %31, %32, %33, %34, %35, %36, %37, %38, %39, %40, %41, %42, %43, %44, %45, %46, %47, %48, %49, %50, %51, %52, %53, %54, %55, %56, %57, %58, %59, %60, %61, %62, %63, %64, %65, %66, %67, %68, %69, %70, %71, %72, %73, %74, %75, %76, %77, %78, %79}, {%80,%81,%82,%83}, db, 1, 1, 1, 0;\n}\n"
    : "+f"(d[0]), "+f"(d[1]), "+f"(d[2]), "+f"(d[3]), "+f"(d[4]), "+f"(d[5]), "+f"(d[6]), "+f"(d[7]), "+f"(d[8]), "+f"(d[9]), "+f"(d[10]), "+f"(d[11]), "+f"(d[12]), "+f"(d[13]), "+f"(d[14]), "+f"(d[15]), "+f"(d[16]), "+f"(d[17]), "+f"(d[18]), "+f"(d[19]), "+f"(d[20]), "+f"(d[21]), "+f"(d[22]), "+f"(d[23]), "+f"(d[24]), "+f"(d[25]), "+f"(d[26]), "+f"(d[27]), "+f"(d[28]), "+f"(d[29]), "+f"(d[30]), "+f"(d[31]), "+f"(d[32]), "+f"(d[33]), "+f"(d[34]), "+f"(d[35]), "+f"(d[36]), "+f"(d[37]), "+f"(d[38]), "+f"(d[39]), "+f"(d[40]), "+f"(d[41]), "+f"(d[42]), "+f"(d[43]), "+f"(d[44]), "+f"(d[45]), "+f"(d[46]), "+f"(d[47]), "+f"(d[48]), "+f"(d[49]), "+f"(d[50]), "+f"(d[51]), "+f"(d[52]), "+f"(d[53]), "+f"(d[54]), "+f"(d[55]), "+f"(d[56]), "+f"(d[57]), "+f"(d[58]), "+f"(d[59]), "+f"(d[60]), "+f"(d[61]), "+f"(d[62]), "+f"(d[63]), "+f"(d[64]), "+f"(d[65]), "+f"(d[66]), "+f"(d[67]), "+f"(d[68]), "+f"(d[69]), "+f"(d[70]), "+f"(d[71]), "+f"(d[72]), "+f"(d[73]), "+f"(d[74]), "+f"(d[75]), "+f"(d[76]), "+f"(d[77]), "+f"(d[78]), "+f"(d[79])
    : "r"(a0), "r"(a1), "r"(a2), "r"(a3), "r"(blo));
}
template<int N> __device__ __forceinline__ void wgmma_rs_hi(float (&d)[64], uint32_t a0, uint32_t a1, uint32_t a2, uint32_t a3, uint32_t blo);
template<> __device__ __forceinline__ void wgmma_rs_hi<16>(float (&d)[64], uint32_t a0, uint32_t a1, uint32_t a2, uint32_t a3, uint32_t blo){
  asm volatile("{\n.reg .b64 db;\nmov.b64 db, {%12,8};\nwgmma.mma_async.sync.aligned.m64n16k16.f32.bf16.bf16 {%0, %1, %2, %3, %4, %5, %6, %7}, {%8,%9,%10,%11}, db, 1, 1, 1, 0;\n}\n"
    : "+f"(d[56]), "+f"(d[57]), "+f"(d[58]), "+f"(d[59]), "+f"(d[60]), "+f"(d[61]), "+f"(d[62]), "+f"(d[63])
    : "r"(a0), "r"(a1), "r"(a2), "r"(a3), "r"(blo));
}
template<> __device__ __forceinline__ void wgmma_rs_hi<32>(float (&d)[64], uint32_t a0, uint32_t a1, uint32_t a2, uint32_t a3, uint32_t blo){
  asm volatile("{\n.reg .b64 db;\nmov.b64 db, {%20,8};\nwgmma.mma_async.sync.aligned.m64n32k16.f32.bf16.bf16 {%0, %1, %2, %3, %4, %5, %6, %7, %8, %9, %10, %11, %12, %13, %14, %15}, {%16,%17,%18,%19}, db, 1, 1, 1, 0;\n}\n"
    : "+f"(d[48]), "+f"(d[49]), "+f"(d[50]), "+f"(d[51]), "+f"(d[52]), "+f"(d[53]), "+f"(d[54]), "+f"(d[55]), "+f"(d[56]), "+f"(d[57]), "+f"(d[58]), "+f"(d[59]), "+f"(d[60]), "+f"(d[61]), "+f"(d[62]), "+f"(d[63])
    : "r"(a0), "r"(a1), "r"(a2), "r"(a3), "r"(blo));
}
template<> __device__ __forceinline__ void wgmma_rs_hi<48>(float (&d)[64], uint32_t a0, uint32_t a1, uint32_t a2, uint32_t a3, uint32_t blo){
  asm volatile("{\n.reg .b64 db;\nmov.b64 db, {%28,8};\nwgmma.mma_async.sync.aligned.m64n48k16.f32.bf16.bf16 {%0, %1, %2, %3, %4, %5, %6, %7, %8, %9, %10, %11, %12, %13, %14, %15, %16, %17, %18, %19, %20, %21, %22, %23}, {%24,%25,%26,%27}, db, 1, 1, 1, 0;\n}\n"
    : "+f"(d[40]), "+f"(d[41]), "+f"(d[42]), "+f"(d[43]), "+f"(d[44]), "+f"(d[45]), "+f"(d[46]), "+f"(d[47]), "+f"(d[48]), "+f"(d[49]), "+f"(d[50]), "+f"(d[51]), "+f"(d[52]), "+f"(d[53]), "+f"(d[54]), "+f"(d[55]), "+f"(d[56]), "+f"(d[57]), "+f"(d[58]), "+f"(d[59]), "+f"(d[60]), "+f"(d[61]), "+f"(d[62]), "+f"(d[63])
    : "r"(a0), "r"(a1), "r"(a2), "r"(a3), "r"(blo));
}
template<> __device__ __forceinline__ void wgmma_rs_hi<64>(float (&d)[64], uint32_t a0, uint32_t a1, uint32_t a2, uint32_t a3, uint32_t blo){
  asm volatile("{\n.reg .b64 db;\nmov.b64 db, {%36,8};\nwgmma.mma_async.sync.aligned.m64n64k16.f32.bf16.bf16 {%0, %1, %2, %3, %4, %5, %6, %7, %8, %9, %10, %11, %12, %13, %14, %15, %16, %17, %18, %19, %20, %21, %22, %23, %24, %25, %26, %27, %28, %29, %30, %31}, {%32,%33,%34,%35}, db, 1, 1, 1, 0;\n}\n"
    : "+f"(d[32]), "+f"(d[33]), "+f"(d[34]), "+f"(d[35]), "+f"(d[36]), "+f"(d[37]), "+f"(d[38]), "+f"(d[39]), "+f"(d[40]), "+f"(d[41]), "+f"(d[42]), "+f"(d[43]), "+f"(d[44]), "+f"(d[45]), "+f"(d[46]), "+f"(d[47]), "+f"(d[48]), "+f"(d[49]), "+f"(d[50]), "+f"(d[51]), "+f"(d[52]), "+f"(d[53]), "+f"(d[54]), "+f"(d[55]), "+f"(d[56]), "+f"(d[57]), "+f"(d[58]), "+f"(d[59]), "+f"(d[60]), "+f"(d[61]), "+f"(d[62]), "+f"(d[63])
    : "r"(a0), "r"(a1), "r"(a2), "r"(a3), "r"(blo));
}
template<> __device__ __forceinline__ void wgmma_rs_hi<80>(float (&d)[64], uint32_t a0, uint32_t a1, uint32_t a2, uint32_t a3, uint32_t blo){
  asm volatile("{\n.reg .b64 db;\nmov.b64 db, {%44,8};\nwgmma.mma_async.sync.aligned.m64n80k16.f32.bf16.bf16 {%0, %1, %2, %3, %4, %5, %6, %7, %8, %9, %10, %11, %12, %13, %14, %15, %16, %17, %18, %19, %20, %21, %22, %23, %24, %25, %26, %27, %28, %29, %30, %31, %32, %33, %34, %35, %36, %37, %38, %39}, {%40,%41,%42,%43}, db, 1, 1, 1, 0;\n}\n"
    : "+f"(d[24]), "+f"(d[25]), "+f"(d[26]), "+f"(d[27]), "+f"(d[28]), "+f"(d[29]), "+f"(d[30]), "+f"(d[31]), "+f"(d[32]), "+f"(d[33]), "+f"(d[34]), "+f"(d[35]), "+f"(d[36]), "+f"(d[37]), "+f"(d[38]), "+f"(d[39]), "+f"(d[40]), "+f"(d[41]), "+f"(d[42]), "+f"(d[43]), "+f"(d[44]), "+f"(d[45]), "+f"(d[46]), "+f"(d[47]), "+f"(d[48]), "+f"(d[49]), "+f"(d[50]), "+f"(d[51]), "+f"(d[52]), "+f"(d[53]), "+f"(d[54]), "+f"(d[55]), "+f"(d[56]), "+f"(d[57]), "+f"(d[58]), "+f"(d[59]), "+f"(d[60]), "+f"(d[61]), "+f"(d[62]), "+f"(d[63])
    : "r"(a0), "r"(a1), "r"(a2), "r"(a3), "r"(blo));
}
template<> __device__ __forceinline__ void wgmma_rs_hi<96>(float (&d)[64], uint32_t a0, uint32_t a1, uint32_t a2, uint32_t a3, uint32_t blo){
  asm volatile("{\n.reg .b64 db;\nmov.b64 db, {%52,8};\nwgmma.mma_async.sync.aligned.m64n96k16.f32.bf16.bf16 {%0, %1, %2, %3, %4, %5, %6, %7, %8, %9, %10, %11, %12, %13, %14, %15, %16, %17, %18, %19, %20, %21, %22, %23, %24, %25, %26, %27, %28, %29, %30, %31, %32, %33, %34, %35, %36, %37, %38, %39, %40, %41, %42, %43, %44, %45, %46, %47}, {%48,%49,%50,%51}, db, 1, 1, 1, 0;\n}\n"
    : "+f"(d[16]), "+f"(d[17]), "+f"(d[18]), "+f"(d[19]), "+f"(d[20]), "+f"(d[21]), "+f"(d[22]), "+f"(d[23]), "+f"(d[24]), "+f"(d[25]), "+f"(d[26]), "+f"(d[27]), "+f"(d[28]), "+f"(d[29]), "+f"(d[30]), "+f"(d[31]), "+f"(d[32]), "+f"(d[33]), "+f"(d[34]), "+f"(d[35]), "+f"(d[36]), "+f"(d[37]), "+f"(d[38]), "+f"(d[39]), "+f"(d[40]), "+f"(d[41]), "+f"(d[42]), "+f"(d[43]), "+f"(d[44]), "+f"(d[45]), "+f"(d[46]), "+f"(d[47]), "+f"(d[48]), "+f"(d[49]), "+f"(d[50]), "+f"(d[51]), "+f"(d[52]), "+f"(d[53]), "+f"(d[54]), "+f"(d[55]), "+f"(d[56]), "+f"(d[57]), "+f"(d[58]), "+f"(d[59]), "+f"(d[60]), "+f"(d[61]), "+f"(d[62]), "+f"(d[63])
    : "r"(a0), "r"(a1), "r"(a2), "r"(a3), "r"(blo));
}
template<> __device__ __forceinline__ void wgmma_rs_hi<112>(float (&d)[64], uint32_t a0, uint32_t a1, uint32_t a2, uint32_t a3, uint32_t blo){
  asm volatile("{\n.reg .b64 db;\nmov.b64 db, {%60,8};\nwgmma.mma_async.sync.aligned.m64n112k16.f32.bf16.bf16 {%0, %1, %2, %3, %4, %5, %6, %7, %8, %9, %10, %11, %12, %13, %14, %15, %16, %17, %18, %19, %20, %21, %22, %23, %24, %25, %26, %27, %28, %29, %30, %31, %32, %33, %34, %35, %36, %37, %38, %39, %40, %41, %42, %43, %44, %45, %46, %47, %48, %49, %50, %51, %52, %53, %54, %55}, {%56,%57,%58,%59}, db, 1, 1, 1, 0;\n}\n"
    : "+f"(d[8]), "+f"(d[9]), "+f"(d[10]), "+f"(d[11]), "+f"(d[12]), "+f"(d[13]), "+f"(d[14]), "+f"(d[15]), "+f"(d[16]), "+f"(d[17]), "+f"(d[18]), "+f"(d[19]), "+f"(d[20]), "+f"(d[21]), "+f"(d[22]), "+f"(d[23]), "+f"(d[24]), "+f"(d[25]), "+f"(d[26]), "+f"(d[27]), "+f"(d[28]), "+f"(d[29]), "+f"(d[30]), "+f"(d[31]), "+f"(d[32]), "+f"(d[33]), "+f"(d[34]), "+f"(d[35]), "+f"(d[36]), "+f"(d[37]), "+f"(d[38]), "+f"(d[39]), "+f"(d[40]), "+f"(d[41]), "+f"(d[42]), "+f"(d[43]), "+f"(d[44]), "+f"(d[45]), "+f"(d[46]), "+f"(d[47]), "+f"(d[48]), "+f"(d[49]), "+f"(d[50]), "+f"(d[51]), "+f"(d[52]), "+f"(d[53]), "+f"(d[54]), "+f"(d[55]), "+f"(d[56]), "+f"(d[57]), "+f"(d[58]), "+f"(d[59]), "+f"(d[60]), "+f"(d[61]), "+f"(d[62]), "+f"(d[63])
    : "r"(a0), "r"(a1), "r"(a2), "r"(a3), "r"(blo));
}
template<> __device__ __forceinline__ void wgmma_rs_hi<128>(float (&d)[64], uint32_t a0, uint32_t a1, uint32_t a2, uint32_t a3, uint32_t blo){
  asm volatile("{\n.reg .b64 db;\nmov.b64 db, {%68,8};\nwgmma.mma_async.sync.aligned.m64n128k16.f32.bf16.bf16 {%0, %1, %2, %3, %4, %5, %6, %7, %8, %9, %10, %11, %12, %13, %14, %15, %16, %17, %18, %19, %20, %21, %22, %23, %24, %25, %26, %27, %28, %29, %30, %31, %32, %33, %34, %35, %36, %37, %38, %39, %40, %41, %42, %43, %44, %45, %46, %47, %48, %49, %50, %51, %52, %53, %54, %55, %56, %57, %58, %59, %60, %61, %62, %63}, {%64,%65,%66,%67}, db, 1, 1, 1, 0;\n}\n"
    : "+f"(d[0]), "+f"(d[1]), "+f"(d[2]), "+f"(d[3]), "+f"(d[4]), "+f"(d[5]), "+f"(d[6]), "+f"(d[7]), "+f"(d[8]), "+f"(d[9]), "+f"(d[10]), "+f"(d[11]), "+f"(d[12]), "+f"(d[13]), "+f"(d[14]), "+f"(d[15]), "+f"(d[16]), "+f"(d[17]), "+f"(d[18]), "+f"(d[19]), "+f"(d[20]), "+f"(d[21]), "+f"(d[22]), "+f"(d[23]), "+f"(d[24]), "+f"(d[25]), "+f"(d[26]), "+f"(d[27]), "+f"(d[28]), "+f"(d[29]), "+f"(d[30]), "+f"(d[31]), "+f"(d[32]), "+f"(d[33]), "+f"(d[34]), "+f"(d[35]), "+f"(d[36]), "+f"(d[37]), "+f"(d[38]), "+f"(d[39]), "+f"(d[40]), "+f"(d[41]), "+f"(d[42]), "+f"(d[43]), "+f"(d[44]), "+f"(d[45]), "+f"(d[46]), "+f"(d[47]), "+f"(d[48]), "+f"(d[49]), "+f"(d[50]), "+f"(d[51]), "+f"(d[52]), "+f"(d[53]), "+f"(d[54]), "+f"(d[55]), "+f"(d[56]), "+f"(d[57]), "+f"(d[58]), "+f"(d[59]), "+f"(d[60]), "+f"(d[61]), "+f"(d[62]), "+f"(d[63])
    : "r"(a0), "r"(a1), "r"(a2), "r"(a3), "r"(blo));
}

__device__ __forceinline__ void keep_warm(uint32_t bar, int barid) {
  float d0 = 0.f, d1 = 0.f, d2 = 0.f, d3 = 0.f;
  uint32_t it = 0, go;
  const uint32_t z0 = lds32(sb + EP_OFF + 24), z1 = lds32(sb + EP_OFF + 24), z2 = lds32(sb + EP_OFF + 24), z3 = lds32(sb + EP_OFF + 24);
  do {
    wgmma_fence();
    asm volatile("{\n.reg .b64 db;\nmov.b64 db, {%8,8};\nwgmma.mma_async.sync.aligned.m64n8k16.f32.bf16.bf16 {%0,%1,%2,%3}, {%4,%5,%6,%7}, db, 1, 1, 1, 0;\n}\n"
                 : "+f"(d0), "+f"(d1), "+f"(d2), "+f"(d3) : "r"(z0), "r"(z1), "r"(z2), "r"(z3), "r"(desc_lo(sb + DTAB_OFF, 0)));
    wgmma_commit();
    wgmma_wait<0>();
    asm volatile("{\n.reg .pred p, q;\nmbarrier.test_wait.parity.shared::cta.b64 p, [%1], 0;\nbar.red.or.pred q, %2, 128, p;\nselp.u32 %0, 1, 0, q;\n}\n"
                 : "=r"(go) : "r"(bar), "r"(barid) : "memory");
    trap_if(++it > SPIN_LIMIT);
  } while (!__all_sync(0xffffffffu, go));
  sts32(sb + EP_OFF + 28, __float_as_uint(d0 + d1 + d2 + d3));
}

struct CvCtx {
  uint32_t koff, zero, so[3];
  int srcA, srcB;
  bool wrapA, s3, kodd;
};
struct CvPipe { uint32_t Ap, Ep, keep, send; };
template <int LO> __device__ __forceinline__ void cv_copy(float (&acc)[64]) {
#pragma unroll
  for (int i = LO; i < 64; i++) { float t; asm volatile("mov.b32 %0, %1;" : "=f"(t) : "f"(acc[i]) : "memory"); acc[i] = t; }
}
template <int G> __device__ __forceinline__ void cv_raw(uint32_t (&A)[4][4], uint32_t kaddr) {
#pragma unroll
  for (int i = 0; i < 4; i++) {
    const uint32_t a = kaddr + (4 * G + i) * 128;
    A[i][0] = lds32(a); A[i][1] = lds32(a + 4); A[i][3] = lds32(a + 8);
  }
}
__device__ __forceinline__ void cv_form(uint32_t (&A)[4][4], uint32_t sel) {
#pragma unroll
  for (int i = 0; i < 4; i++) {
    asm volatile("prmt.b32 %0, %0, %1, %2;" : "+r"(A[i][0]) : "r"(A[i][1]), "r"(sel));
    asm volatile("prmt.b32 %0, %1, %2, %3;" : "=r"(A[i][2]) : "r"(A[i][1]), "r"(A[i][3]), "r"(sel));
  }
}
#define CVV 2
template <int G> __device__ __forceinline__ void cv_step(float (&acc)[64], uint32_t (&A)[4][4], CvPipe& s, const CvCtx& c, uint32_t cb, uint32_t stg) {
  constexpr int JA = G - 1, JB = G - 2, NH = CVV == 1 ? 4 : (CVV == 3 ? 2 : 1);
  const uint32_t db0 = desc_lo(cb + CV_U + 192, CV_PL);
  uint32_t B[4][4];
  uint32_t ra[2], rb;
  if constexpr (G < 8) {
    wgmma_fence();
#pragma unroll
    for (int i = 0; i < NH; i++) wgmma_rs_hi<128 - 16 * (G & 7)>(acc, A[i][0], A[i][1], A[i][2], A[i][3], db0 - 4 * i);
    wgmma_commit();
    __syncwarp();
  }
  if constexpr (JA >= 0 && JA < 8) {
    const uint32_t p0 = pack_bf16(acc[8 * JA + 1], acc[8 * JA + 3]), p1 = pack_bf16(acc[8 * JA + 5], acc[8 * JA + 7]);
    ra[0] = __shfl_sync(0xffffffffu, c.wrapA ? s.Ap : p0, c.srcA);
    ra[1] = __shfl_sync(0xffffffffu, c.wrapA ? p0 : p1, c.srcA);
    s.Ap = p1;
  }
  if constexpr (JB >= 0) rb = __shfl_sync(0xffffffffu, s.send, c.srcB);
  if constexpr (G < 7) cv_raw<G + 1>(B, cb + c.koff);
  uint32_t z = 0;
  if constexpr (G < 8 && NH < 4) {
    __syncwarp();
    wgmma_fence();
#pragma unroll
    for (int i = NH; i < 4; i++) wgmma_rs_hi<128 - 16 * (G & 7)>(acc, A[i][0], A[i][1], A[i][2], A[i][3], db0 - 4 * i);
    wgmma_commit();
    asm volatile("mov.u32 %0, %%clock;" : "=r"(z)::"memory");
    z &= c.zero;
  }
  if constexpr (G < 7) cv_form(B, 0x5432u | z);
  if constexpr (JB >= 0) sts32(stg + ((c.so[JB / 3] >> (10 * (JB % 3))) & 0xffc), hadd2(rb | z, s.keep));
  if constexpr (JA >= 0 && JA < 8) {
    const uint32_t sh = 16 | z, mk = 0xffff0000u | z;
    const uint32_t ev = pack_bf16(acc[8 * JA] + __uint_as_float(ra[0] << sh), acc[8 * JA + 2] + __uint_as_float(ra[0] & mk));
    const uint32_t od = pack_bf16(acc[8 * JA + 4] + __uint_as_float(ra[1] << sh), acc[8 * JA + 6] + __uint_as_float(ra[1] & mk));
    s.send = c.kodd ? ev : (c.s3 ? s.Ep : od);
    s.keep = c.kodd ? od : ev;
    s.Ep = od;
  }
  if constexpr (G < 8) { __syncwarp(); wgmma_wait<0>(); cv_copy<8 * (G & 7)>(acc); }
  if constexpr (G < 9) cv_step<G + 1>(acc, B, s, c, cb, stg);
}
__device__ __forceinline__ uint32_t cv_stage(int slot) { return sb + (slot < 4 ? 40960 + slot * 4096 : CV_OFF + CV_K); }
__device__ __forceinline__ void cv_setup(CvCtx& c) {
  const int tid = tid_opaque() & 127, w = tid >> 5, lane = tid & 31, r = lane >> 2, q = lane & 3;
  const int i0 = (r >> 1) & 1, i1 = r >> 2;
  c.koff = CV_K - 32 + 4 * (8 * (r >> 1) + 2 * w + (r & 1) + 2 * q);
  c.srcA = i0 ? lane - 8 : lane + 8 - q + ((q + 3) & 3);
  c.wrapA = i0 && q == 3;
  c.srcB = i1 == 0 ? (lane - q + 16 + ((q + 3) & 3)) : (lane - q - 16 + ((q + 1) & 3));
  c.s3 = (i1 == 1 && q == 3); c.kodd = (i1 == 1 && q < 3);
  c.zero = lds32(sb + EP_OFF + 24);
#pragma unroll
  for (int i = 0; i < 3; i++) c.so[i] = lds32(sb + SO_OFF + 512 * i + 4 * tid);
}
__device__ __forceinline__ void cv_table() {
  const int tid = tid_opaque() & 127, r = (tid & 31) >> 2, q = tid & 3;
  int t = 16 * (2 * (r < 4 ? q : 4 + ((q + 1) & 3)) + ((r >> 1) & 1)) + 4 * (tid >> 5) + 2 * (r & 1);
#pragma unroll 1
  for (int i = 0; i < 3; i++) {
    uint32_t v = 0;
#pragma unroll 1
    for (int x = 0; x < 3; x++, t += 256) {
      const int T = t / 160, tl = t - T * 160;
      const int qq = (T >= NT1 - 1) ? (tl >> 5) : (tl / 40);
      int ck = 20 * T + ((tl - qq * ((T >= NT1 - 1) ? 32 : 40)) >> 1);
      ck ^= (ck >> 2) & 6;
      v |= (uint32_t)((ck * 4 + qq) & 1023) << (10 * x + 2);
    }
    sts32(sb + SO_OFF + 512 * i + 4 * tid, v);
  }
}
__device__ __forceinline__ void conv_channel(int slot, const CvCtx& c) {
  const uint32_t cb = sb + CV_OFF + slot * CV_B;
  float acc[64];
  CvPipe s;
  s.Ap = s.Ep = 0u;
  uint32_t A[4][4];
#pragma unroll
  for (int i = 0; i < 64; i++) acc[i] = 0.f;
  if (slot == 4) mbar_wait(bars + 8 * B_CVDONE);
  mbar_wait(bars + 8 * (B_CVFULL + slot));
  cv_raw<0>(A, cb + c.koff);
  {
    const uint32_t w0 = lds32(cb + CV_K);
    const uint32_t wp = __byte_perm(pack_bf16(bf_lo(w0) + __uint_as_float(lds32(sb + EP_OFF + 4 * slot)), 0.f), w0, 0x7610);
    if (c.koff == CV_K) A[0][0] = wp;
    if (c.koff == CV_K - 4) A[0][1] = wp;
    if (c.koff == CV_K - 8) A[0][3] = wp;
  }
  cv_form(A, 0x5432u);
  cv_copy<0>(acc);
  cv_step<0>(acc, A, s, c, cb, cv_stage(slot));
  fence_async_smem();
  mbar_arrive(bars + 8 * (B_CVDONE + slot));
}

__device__ __forceinline__ void kv_issue(const Params& p, int c, int m2, int dg) {
  const uint32_t fb = bars + 8 * (B_KV + c);
  mbar_expect_tx(fb, KV_PIECE);
  tma3(sb + KS_OFF + c * KV_PIECE, &p.mK, 160 * dg + 32 * c, 64 * m2 - 3, 0, fb);
  tma3(sb + KS_OFF + c * KV_PIECE + 4864, &p.mV, 160 * dg + 32 * c, 64 * m2 - 1, 0, fb);
}
__device__ __forceinline__ void kv_tile(int m, int c, int y, uint32_t (&o)[4][4]) {
  const int lane = tid_opaque() & 31, tg = lane & 3, pr = 8 * (y ^ (tg >> 1)) + (lane >> 2);
  const uint32_t pb = sb + KS_OFF + c * KV_PIECE + 4 * pr;
  const uint32_t ka = pb + tg * 1216, va = pb + 4864 + tg * 1088 + 64;
  const uint32_t kh = (m == 0 && tg > 0) ? ka - 192 : ka;
  uint32_t kk[19], u[16];
  const float4 t = lds128f(sb + TAP_OFF + 256 * c + 16 * pr);
#pragma unroll
  for (int i = 0; i < 19; i++) { kk[i] = lds32((i < 3 ? kh : ka) + i * 64); if (i >= 3) u[i - 3] = lds32(va + (i - 3) * 64); }
  const uint32_t dst = sb + KS_OFF + c * KV_PIECE + pr * 64 + tg * 16;
  if (y) {
    __syncwarp();
#pragma unroll
    for (int x = 0; x < 4; x++) sts128((dst ^ 512) + x * 1024, make_uint4(o[x][0], o[x][1], o[x][2], o[x][3]));
  }
  const uint32_t w0 = __byte_perm(__float_as_uint(t.x), __float_as_uint(t.z), 0x5410), w1 = __byte_perm(__float_as_uint(t.x), __float_as_uint(t.z), 0x7632);
  const uint32_t w2 = __byte_perm(__float_as_uint(t.y), __float_as_uint(t.w), 0x5410), w3 = __byte_perm(__float_as_uint(t.y), __float_as_uint(t.w), 0x7632);
#pragma unroll
  for (int i = 0; i < 16; i++) {
    uint32_t a = hmul2(kk[i], w3);
    a = hadd2(a, hmul2(kk[i + 1], w2)); a = hadd2(a, hmul2(kk[i + 2], w1)); a = hadd2(a, hmul2(kk[i + 3], w0));
    u[i] = hmul2(a, u[i]);
  }
#pragma unroll
  for (int x = 0; x < 4; x++) {
#pragma unroll
    for (int qq = 0; qq < 4; qq++) o[x][qq] = __byte_perm(u[15 - 4 * qq - (x & 2)], u[14 - 4 * qq - (x & 2)], (x & 1) ? 0x7632 : 0x5410);
    if (y) sts128(dst + x * 1024, make_uint4(o[x][0], o[x][1], o[x][2], o[x][3]));
  }
}
template <bool BF>
__device__ __forceinline__ void ln_finish(float s1, float s2, float& mean, float& rstd) {
  mean = s1 * (1.f / 640.f);
  float v = fmaxf(fmaf(-mean, mean, s2 * (1.f / 640.f)), 0.f);
  if (BF) {
    const uint32_t mv = pack_bf16(mean, v);
    mean = bf_lo(mv);
    asm("sqrt.approx.ftz.f32 %0, %1;" : "=f"(v) : "f"(bf_lo(pack_bf16(bf_hi(mv) + 1e-5f, 0.f))));
    asm("rcp.approx.ftz.f32 %0, %1;" : "=f"(rstd) : "f"(bf_lo(pack_bf16(v, 0.f))));
  } else {
    v += 1e-5f;
    asm("rsqrt.approx.ftz.f32 %0, %1;" : "=f"(rstd) : "f"(v));
  }
}
template <int l>
__device__ __forceinline__ void stat_table(int T1, unsigned want, int g, const uint4* x0, const uint4* x1, float (&xa)[2], float (&xb)[2]) {
  const int n = 32 * g + (tid_opaque() & 31);
  const uint4* rp = &g_stats[8 * l * SEQ + min(160 * T1 + n, SEQ - 1)];
  float a[4], b[4];
  uint32_t it = 0;
  while (true) {
    bool ok = true;
#pragma unroll
    for (int i = 0; i < 4; i++) ok &= (rec_ld(rp + SEQ * i, a[i], b[i]) == want);
    ok &= rec_ld(x0, xa[0], xb[0]) == want;
    ok &= rec_ld(x1, xa[1], xb[1]) == want;
    if (__all_sync(0xffffffffu, ok)) break;
    trap_if(++it > SPIN_LIMIT);
  }
  float m, rs;
  ln_finish<l == 0>((a[0] + a[1]) + (a[2] + a[3]), (b[0] + b[1]) + (b[2] + b[3]), m, rs);
  sts32(sb + STAB_OFF + ((n >> 1) & 3) * 160 + (n >> 3) * 8 + (n & 1) * 4, __float_as_uint(rs));
  const uint32_t hi = pack_bf16(-m, -m);
  const float lo = -m - bf_lo(hi);
  sts128(sb + (l ? MX1_OFF : MX0_OFF) + n * 16, make_uint4(hi, pack_bf16(lo, lo), 0u, 0u));
  fence_async_smem();
}
template <bool BF>
__device__ __forceinline__ void stats_reduce(float (&a)[2], float (&b)[2], float (&mean)[2], float (&rstd)[2]) {
#pragma unroll
  for (int o = 1; o < 4; o <<= 1)
#pragma unroll
    for (int h = 0; h < 2; h++) { a[h] += __shfl_xor_sync(0xffffffffu, a[h], o); b[h] += __shfl_xor_sync(0xffffffffu, b[h], o); }
#pragma unroll
  for (int h = 0; h < 2; h++) ln_finish<BF>(a[h], b[h], mean[h], rstd[h]);
}

template <bool FIRST>
__device__ __forceinline__ void stats_publish(int which, int n0, int dg, unsigned tag, const float (&acc)[80]) {
  const int q = tid_opaque() & 3, h = q & 1;
  float s1[2] = {0.f, 0.f}, s2[2] = {0.f, 0.f}, t1[2] = {0.f, 0.f}, t2[2] = {0.f, 0.f};
#pragma unroll
  for (int j = 0; j < 20; j++)
#pragma unroll
    for (int y = 0; y < 2; y++) {
      const float a = acc[4 * j + 2 * y], b = acc[4 * j + 2 * y + 1];
      s1[y] += a; t1[y] += b; s2[y] = fmaf(a, a, s2[y]); t2[y] = fmaf(b, b, t2[y]);
    }
#pragma unroll
  for (int y = 0; y < 2; y++) { s1[y] += t1[y]; s2[y] += t2[y]; }
  float a = (h ? s1[1] : s1[0]) + __shfl_xor_sync(0xffffffffu, h ? s1[0] : s1[1], 1);
  float b = (h ? s2[1] : s2[0]) + __shfl_xor_sync(0xffffffffu, h ? s2[0] : s2[1], 1);
  a += __shfl_xor_sync(0xffffffffu, a, 2);
  b += __shfl_xor_sync(0xffffffffu, b, 2);
  if (FIRST) {
    rec_st(&g_stats[((q >> 1) * 4 + dg) * SEQ + n0 + 8 * h], a, b, q < 2 ? tag : tag - 1);
    rec_st(&g_stats[((q >> 1) * 4 + 8 + dg) * SEQ + n0 + 8 * h], a, b, tag - 1);
  } else if (q < 2) rec_st(&g_stats[(which * 4 + dg) * SEQ + n0 + 8 * h], a, b, tag);
}
__device__ __forceinline__ void stats_get(int which, int n0, unsigned tag, float (&mean)[2], float (&rstd)[2]) {
  const uint4* p0 = &g_stats[(which * 4 + (tid_opaque() & 3)) * SEQ + n0];
  float a[2], b[2];
  uint32_t it = 0;
  while (true) {
    const unsigned t0 = rec_ld(p0, a[0], b[0]), t1 = rec_ld(p0 + 8, a[1], b[1]);
    if (__all_sync(0xffffffffu, t0 == tag && t1 == tag)) break;
    trap_if(++it > SPIN_LIMIT);
  }
  stats_reduce<false>(a, b, mean, rstd);
}
__device__ __forceinline__ void x0_load(float (&acc)[80]) {
  const int t = tid_opaque() & 127;
  const uint32_t xa = sb + XT_OFF + (16 * (t >> 5) + ((t & 31) >> 2)) * 320 + 8 * (t & 3);
  mbar_wait(bars + 8 * B_XT);
#pragma unroll
  for (int h = 0; h < 2; h++)
#pragma unroll
    for (int J = 0; J < 10; J++) {
      const float2 v = lds64f(xa + h * 2560 + 32 * J);
      const uint32_t x = __float_as_uint(v.x), y = __float_as_uint(v.y);
      acc[8 * J + 2 * h] = bf_lo(x); acc[8 * J + 2 * h + 1] = bf_hi(x);
      acc[8 * J + 4 + 2 * h] = bf_lo(y); acc[8 * J + 4 + 2 * h + 1] = bf_hi(y);
    }
}

template <bool FROM_X0>
__device__ __forceinline__ void dskip_init(float (&acc)[80], const float (&mean)[2], const float (&rstd)[2]) {
  const int t = tid_opaque() & 127;
  const uint32_t xa = sb + XT_OFF + (16 * (t >> 5) + ((t & 31) >> 2)) * 320 + 8 * (t & 3), da = sb + DTAB_OFF + 8 * (t & 3);
  float2 dw[10], xv[10][2];
#pragma unroll
  for (int J = 0; J < 2; J++) { dw[J] = lds64f(da + 32 * J); if (FROM_X0) { xv[J][0] = lds64f(xa + 32 * J); xv[J][1] = lds64f(xa + 2560 + 32 * J); } }
#pragma unroll
  for (int J = 0; J < 10; J++) {
    if (J + 2 < 10) { dw[J + 2] = lds64f(da + 32 * (J + 2)); if (FROM_X0) { xv[J + 2][0] = lds64f(xa + 32 * (J + 2)); xv[J + 2][1] = lds64f(xa + 2560 + 32 * (J + 2)); } }
#pragma unroll
    for (int x = 0; x < 8; x++) {
      const int h = (x >> 1) & 1;
      const uint32_t dwd = __float_as_uint(x < 4 ? dw[J].x : dw[J].y);
      const float tt = fmaf(rstd[h], (x & 1) ? bf_hi(dwd) : bf_lo(dwd), 1.f);
      float a = acc[8 * J + x];
      if (FROM_X0) { const uint32_t xw = __float_as_uint(x < 4 ? xv[J][h].x : xv[J][h].y); a = (x & 1) ? bf_hi(xw) : bf_lo(xw); }
      acc[8 * J + x] = FROM_X0 ? (a - mean[h]) * tt : fmaf(a, tt, -mean[h] * tt);
    }
  }
}

__global__ void __launch_bounds__(512, 1) fused_kernel(const __grid_constant__ Params p) {
  extern __shared__ __align__(1024) uint8_t smem_raw[];
  const int tid = threadIdx.x, lane = tid & 31;
  const int wid = __shfl_sync(0xffffffffu, tid >> 5, 0), wg = wid >> 2;
  unsigned smid; asm volatile("mov.u32 %0, %%smid;" : "=r"(smid));
  const int role = p.role[min(smid, 131u)];
  if (wid == 12) {
    const bool el = elect_one();
    if (el) {
      asm volatile("prefetch.tensormap [%0];" ::"l"(&p.mB) : "memory");
      asm volatile("prefetch.tensormap [%0];" ::"l"((role & 15) == NT1 - 1 ? &p.mXl : &p.mX) : "memory");
#pragma unroll
      for (int k = 0; k < S1; k++) mbar_init(bars + 8 * (B_G1FULL + k), 1);
#pragma unroll
      for (int k = 0; k < 6; k++) mbar_init(bars + 8 * (B_XT + k), 1);
      asm volatile("fence.mbarrier_init.release.cluster;" ::: "memory");
    }
    if (role >= 0) {
      __syncwarp();
      asm volatile("bar.arrive 5, 288;" ::: "memory");
      const Role R = unpack_role(role);
      if (elect_one()) {
        TS(45);
#pragma unroll 1
        for (int k = 0; k < S1; k++) {
          const uint32_t fb = bars + 8 * (B_G1FULL + k);
          mbar_expect_tx(fb, G1_STAGE);
          tma4(sb + k * G1_STAGE + G1_XOFF, R.last ? &p.mXl : &p.mX, 64 * k, 0, 0, R.last ? 0 : 80 * R.T1, fb);
          tma5(sb + k * G1_STAGE, &p.mB, 64 * k, 0, 0, 4 * R.side, 2 * R.GP, fb);
          if (PFD) asm volatile("prefetch.tensormap [%0];" ::"l"(&p.mK + k) : "memory");
        }
        if (R.has2) {
          mbar_expect_tx(bars + 8 * B_XT, 20480);
#pragma unroll 1
          for (int h = 0; h < 2; h++) {
            const int ng = 8 * R.m2 + 4 * h, T = ng / 20;
            tma4(sb + XT_OFF + h * 10240, T == NT1 - 1 ? &p.mXtl : &p.mXt, 160 * R.dg, 0, 0, T == NT1 - 1 ? ng - 240 : ng + 60 * T, bars + 8 * B_XT);
          }
#pragma unroll 1
          for (int c = 0; c < KV0; c++) kv_issue(p, c, R.m2, R.dg);
        }
        TS(44);
      }
      __syncwarp();
      bar_sync(6, 64);
    }
  }
  trap_if(smid >= 132 || smem_u32(smem_raw) != sb);
  if (role < 0) {
    if (wid == 0) {
      const unsigned tag = ld_rlx(g_epoch);
      uint32_t it = 0;
      while (!__all_sync(0xffffffffu, (int)(ld_rlx(&g_hcnt[(lane & 7) * 32]) - 40 * tag) >= 0)) { __nanosleep(500); trap_if(++it > SPIN_LIMIT); }
    }
    return;
  }
  float mean0[2] = {0.f, 0.f}, rstd0[2] = {0.f, 0.f};
  if (wg == 2 || wid == 14) {
    ROLE(role)
    const int c = wid == 14 ? 4 : wid - 8;
    const unsigned tag = ld_rlx(g_epoch);
    if (has2) {
      uint2 bv[2][5];
#pragma unroll
      for (int x = 0; x < 2; x++)
#pragma unroll
        for (int i = 0; i < 5; i++) bv[x][i] = ldv64((const uint2*)((x ? p.bim : p.bre) + (cch0 + 32 * c) * DM) + lane + 32 * i);
      float sv[2];
#pragma unroll
      for (int x = 0; x < 2; x++) {
        float a = 0.f;
#pragma unroll
        for (int i = 0; i < 5; i++) a += (bf_lo(bv[x][i].x) + bf_hi(bv[x][i].x)) + (bf_lo(bv[x][i].y) + bf_hi(bv[x][i].y));
        sv[x] = a;
      }
#pragma unroll
      for (int o = 16; o > 0; o >>= 1) { sv[0] += __shfl_xor_sync(0xffffffffu, sv[0], o); sv[1] += __shfl_xor_sync(0xffffffffu, sv[1], o); }
      if (lane < 2) rec_st(&g_sB[(cch0 + 32 * c) * 2 + lane], sv[0], sv[1], tag);
      if (tid == 256) TS(47);
      __syncwarp();
      bar_sync(8, 192);
      if (wg == 2) {
        float xs[80];
        x0_load(xs);
        stats_publish<true>(0, 64 * m2 + 16 * c + (lane >> 2), dg, tag, xs);
        if (tid == 256) TS(31);
      }
      mbar_wait(bars + 8 * B_EP);
      mbar_wait(bars + 8 * (B_KV + c));
      mbar_wait(bars + 8 * (B_G1DONE + PAUSE_K - 1));
      if (tid == 448) TS(52);
      uint32_t o[4][4] = {};
#pragma unroll 1
      for (int y = 0; y < 2; y++) kv_tile(m2, c, y, o);
      fence_async_smem();
      __syncwarp();
      if (lane == 0) { mbar_arrive(bars + 8 * B_PREP); mbar_arrive(bars + 8 * (B_PD + c)); }
      if (tid == 448) TS(51);
    } else bar_sync(8, 192);
    {
      const uint4* x0 = wg == 2 ? &g_stats[(lane & 3) * SEQ + (has2 ? 64 * m2 : 0) + 16 * c + (lane >> 2)] : &g_sB[(128 * GP + 32 * side + lane) * 2];
      float xa[2], xb[2];
      stat_table<0>(T1, tag, c, x0, x0 + (wg == 2 ? 8 : 128), xa, xb);
      if (wg == 2) stats_reduce<true>(xa, xb, mean0, rstd0);
      else {
#pragma unroll
        for (int i = 0; i < 2; i++) {
          const float ha = bf_lo(pack_bf16(xa[i], 0.f)), hb = bf_lo(pack_bf16(xb[i], 0.f));
          const float pa = __uint_as_float(pack_bf16(ha, xa[i] - ha)), pb = __uint_as_float(pack_bf16(hb, xb[i] - hb));
          sts64f(sb + CTAB_OFF + (32 * i + lane) * 24 + 16, p.swap ? pb : pa, p.swap ? pa : pb);
        }
      }
      mbar_arrive(bars + 8 * B_STAB);
      if (tid == 448) TS(26);
    }
  } else if (wid == 15) {
    ROLE(role)
    const int ch = 128 * GP + 32 * side + lane;
    uint32_t r0 = ldv16(p.lre + ch), r1 = ldv16(p.lim + ch), r2 = ldv16(p.logdt + ch);
    const uint32_t r3 = ldv16(p.lre + ch + 64), r4 = ldv16(p.lim + ch + 64), r5 = ldv16(p.logdt + ch + 64);
#pragma unroll 1
    for (int i = 0; i < 2; i++) {
      const float lr = bf_lo(r0), li = bf_lo(r1);
      const float dt = __bfloat162float(__float2bfloat16_rn(expf(bf_lo(r2))));
      const float mag = expf(dt * lr);
      float sn, cs; sincospif(dt * li * 0.31830988618379067f, &sn, &cs);
      const float ar = mag * cs, ai = mag * sn;
      const float inv = 2.f / (lr * lr + li * li);
      const uint32_t ad = sb + CTAB_OFF + (32 * i + lane) * 24;
      sts64f(ad, ar, ai);
      sts64f(ad + 8, ((ar - 1.f) * lr + ai * li) * inv, (ai * lr - (ar - 1.f) * li) * inv);
      r0 = r3; r1 = r4; r2 = r5;
    }
    if (lane == 0) TS(46);
    __syncwarp();
    bar_sync(7, 64);
    mbar_arrive(bars + 8 * B_CTAB);
  } else if (wid == 13) {
    ROLE(role)
    uint4 tv[3];
    const uint32_t e0 = ld_rlx(g_epoch);
    const uint32_t e1 = ldv16(p.ssmD + min(cch0 + 32 * lane, 639));
    const uint4 dv = ldv128((const uint4*)(p.dskip + 160 * dg) + min(lane, 19));
#pragma unroll
    for (int i = 0; i < 3; i++) tv[i] = ldv128((const uint4*)(p.shiftk + 640 * dg) + min(lane + 32 * i, 79));
    sts128(sb + DTAB_OFF + 16 * min(lane, 19), dv);
#pragma unroll
    for (int i = 0; i < 3; i++) sts128(sb + TAP_OFF + 16 * min(lane + 32 * i, 79), tv[i]);
    if (lane < 7) sts32(sb + EP_OFF + 4 * lane, lane < 5 ? e1 << 16 : (lane == 5 ? e0 : 0u));
    __syncwarp();
    bar_sync(9, 64);
    mbar_arrive(bars + 8 * B_CTAB);
    if (lane == 0) { mbar_arrive(bars + 8 * B_EP); TS(53); }
    if (has2) {
#pragma unroll 1
      for (int i = 0; i < 5; i++) {
        const int c = i == 2 ? 3 : (i == 3 ? 2 : i);
        mbar_wait(bars + 8 * (B_PD + c));
        if (lane == 0) bulk_s2g(g_kv + (dg * 32 + m2) * 20480 + c * 4096, sb + KS_OFF + c * KV_PIECE, 4096);
      }
      if (lane == 0) {
        asm volatile("cp.async.bulk.commit_group;" ::: "memory");
        asm volatile("cp.async.bulk.wait_group 0;" ::: "memory");
        mbar_arrive(bars + 8 * B_PREP2);
        fence_async_global();
      }
      __syncwarp();
      if (lane < 4) red_rel(&g_kvcnt[(dg * 4 + lane) * 32]);
      __syncwarp();
      if (lane == 0) { mbar_arrive(bars + 8 * B_PUB); TS(30); }
    }
  } else if (wid != 12) {
    if (elect_one()) {
      if (wid < 7) {
        const int b0 = wid < 4 ? 4 + 19 * wid : 85 + 21 * (wid - 4), cnt = wid < 4 ? 2 : 1;
#pragma unroll
        for (int i = 0; i < 21; i++) mbar_init(bars + 8 * (b0 + i), cnt);
#pragma unroll
        for (int i = 0; i < 5; i++) mbar_init(bars + 8 * (B_PD + 5 * wid + i), 1);
      } else {
#pragma unroll
        for (int i = 0; i < 12; i++) mbar_init(bars + 8 * (B_CVDONE + i), (i == 5 || i == 6) ? 160 : 128);
        mbar_init(bars + 8 * B_CTAB, 192); mbar_init(bars + 8 * B_PREP, 5); mbar_init(bars + 8 * B_PREP2, 1);
      }
      asm volatile("fence.mbarrier_init.release.cluster;" ::: "memory");
    }
    __syncwarp();
    bar_sync(5, 288);
    if (wid == 2) asm volatile("bar.arrive 8, 192;\nbar.arrive 6, 64;\nbar.arrive 9, 64;\nbar.arrive 7, 64;" ::: "memory");
    if (tid == 128) TS(0);
    if (wg == 1) { cv_table(); mbar_arrive(bars + 8 * B_CTAB); }
  }

  if (wid == 12) {
    ROLE(role)
    uint32_t dst = sb;
#pragma unroll 1
    for (int k = S1; k < 10; k++) {
      const uint32_t fb = bars + 8 * (B_G1FULL + k);
      mbar_wait(bars + 8 * (B_G1DONE + k - S1));
      if (elect_one()) {
        mbar_expect_tx(fb, 20480);
        tma4(dst + G1_XOFF, last ? &p.mXl : &p.mX, 64 * k, 0, 0, last ? 0 : 80 * T1, fb);
        mbar_expect_tx(fb, 16384);
        tma5(dst, &p.mB, 64 * k, 0, 0, 4 * side, 2 * GP, fb);
        if (has2 && k - S1 + KV0 < 5) kv_issue(p, k - S1 + KV0, m2, dg);
      }
      dst += G1_STAGE; if (k == 2 * S1 - 1) dst = sb;
    }
  } else if (wid == 15 && (role >> 16)) {
    ROLE(role)
    if (TPF >= 0) {
      mbar_wait(bars + 8 * (B_KV + TPF));
      if (elect_one()) {
#pragma unroll
        for (int c = 0; c < 5; c++) l2_prefetch(p.ssmk + (cch0 + 32 * c) * SEQ, 4096);
        if (CPF) { l2_prefetch(p.cre + (160 * dg + 5 * m2) * DM, 6400); l2_prefetch(p.cim + (160 * dg + 5 * m2) * DM, 6400); }
      }
    }
    mbar_wait(bars + 8 * B_PREP2);
    if (lane < 10) sts128(sb + CV_OFF + (lane >> 1) * CV_B + CV_K - 32 + 16 * (lane & 1), make_uint4(0, 0, 0, 0));
    fence_async_smem();
    __syncwarp();
    const unsigned tag = lds32(sb + EP_OFF + 20);
    if (TAPW) mbar_wait(bars + 8 * B_PUB);
    if (elect_one()) {
#pragma unroll 1
      for (int c = 0; c < 5; c++) {
        if (c == 0) asm volatile("prefetch.tensormap [%0];" ::"l"(&p.mU) : "memory");
        mbar_expect_tx(bars + 8 * (B_CVFULL + c), 4096 + 2 * CV_PL);
        if (c < TAPN) bulk_g2s(sb + CV_OFF + c * CV_B + CV_K, p.ssmk + (cch0 + 32 * c) * SEQ, 4096, bars + 8 * (B_CVFULL + c));
      }
    }
    mbar_wait(bars + 8 * B_PUB);
    cnt_poll(&g_kvcnt[(dg * 4 + (m2 >> 3)) * 32], 32 * tag);
    fence_async_global();
    if (elect_one()) {
      TS(28);
#pragma unroll
      for (int c = 0; c < 5; c++) {
        tma5(sb + CV_OFF + c * CV_B + CV_U, &p.mU, 0, -3, 2 * c, 16 * (m2 & 1) + (m2 >> 1), dg, bars + 8 * (B_CVFULL + c));
        if (c >= TAPN) bulk_g2s(sb + CV_OFF + c * CV_B + CV_K, p.ssmk + (cch0 + 32 * c) * SEQ, 4096, bars + 8 * (B_CVFULL + c));
      }
#pragma unroll
      for (int i = 0; i < 3; i++) asm volatile("prefetch.tensormap [%0];" ::"l"(&p.mCre + i) : "memory");
      TS(54);
    }
    __syncwarp();
  }
  {
    const int w = wid & 3;
    if (wg == 2 && !(role >> 16)) {
      float xa[2], xb[2];
      mbar_wait(bars + 8 * (B_G1FULL + 11));
      stat_table<1>(role & 15, lds32(sb + EP_OFF + 20), w, g_stats, g_stats, xa, xb);
      mbar_arrive(bars + 8 * (B_STAB + 1));
    }
#pragma unroll 1
    for (int l = 0; l < 2; l++) {
      if (wg < 2) {
        float acc[80];
#pragma unroll
        for (int i = 0; i < 80; i++) acc[i] = 0.f;
        ROLE(role)
        const int tid = tid_opaque(), r = (tid & 31) >> 2, q = tid & 3;
        const int ch = 128 * GP + 64 * wg + 32 * side + 8 * w + r;
        const uint32_t ca = sb + CTAB_OFF + (32 * wg + 8 * w + r) * 24;
        float2 lam = make_float2(0.f, 0.f), p8 = lam, p16 = lam, pL = lam, p2L = lam;
        fence_regs(acc);
        {
          const uint32_t alo0 = (l == 0 ? desc_lo(sb, 16) : desc_lo(sb + G2_WOFF, 16)) + wg * 512;
          const uint32_t blo0 = l == 0 ? desc_lo(sb + G1_XOFF, 16) : desc_lo(sb + X1_OFF, 128);
          const uint32_t bhi = l == 0 ? desc_hi(1024, 1) : desc_hi(1024, 0), xstep = l == 0 ? 2 : 16;
          const uint32_t astep = l == 0 ? G1_STAGE >> 4 : 1024, bstep = l == 0 ? G1_STAGE >> 4 : 1280, aend = alo0 + (S1 + l) * astep;
          uint32_t alo = alo0, blo = blo0;
          const uint32_t special = 8u | (l ? (1u << MK1) | (wg << (8 - STG_D)) : (1u << MK0) | (1u << (wg ? PAUSE_K : PAUSE0)) | (wg << (9 - STG0)));
          uint32_t fb = bars + 8 * (B_G1FULL + 10 * l), nb = fb + 8;
          mbar_wait(fb);
          if (tid == 0) TS(1 + 8 * l);
#pragma unroll 1
          for (int k = 0; k < 10; k++) {
            uint32_t ok;
            wgmma_fence();
#pragma unroll
            for (int kk = 0; kk < 4; kk++) {
              wgmma_n160<0>(acc, alo + kk * 2, desc_hi(1024, 1), blo + kk * xstep, bhi);
              if (kk == 0) { ok = mbar_test(nb); asm volatile("add.u32 %0, %0, %1;" : "+r"(nb) : "r"(k < 8 ? 8 : 0)); }
              if (kk == STG_KK && k == 9 && tid == 0) mbar_arrive(bars + 8 * (B_STG + l));
            }
            wgmma_commit();
            alo += astep; blo += bstep;
            if (blo == desc_lo(sb + G_OFF, 128)) blo = desc_lo(sb, 128);
            if (alo == aend) { alo = alo0; blo = blo0; }
            wgmma_wait<1>();
            if (k > 0 && (tid & 127) == 0) mbar_arrive(fb + 8 * (B_G1DONE - B_G1FULL - 1));
            if (!ok) mbar_wait(fb + 8);
            if ((special >> k) & 1) {
            if (k == (l ? MK1 : MK0)) {
              mbar_wait(bars + 8 * (B_STAB + l));
              const float2 sB = lds64f(ca + 16);
              uint32_t a0 = q < 2 ? __float_as_uint(sB.x) : 0u, a1 = q < 2 ? __float_as_uint(sB.y) : 0u, a2 = 0u, a3 = 0u;
              asm volatile("" : "+r"(a0), "+r"(a1), "+r"(a2), "+r"(a3)::"memory");
              wgmma_fence();
              wgmma_rs_n160(acc, a0, a1, a2, a3, l ? desc_lo(sb + MX1_OFF, 0) : desc_lo(sb + MX0_OFF, 0));
              wgmma_commit();
            }
            if (wg == 1 && k == (l ? 8 - STG_D : 9 - STG0)) mbar_wait(bars + 8 * (B_STG + l));
            if (k == 3) {
              mbar_wait(bars + 8 * B_CTAB);
              lam = lds64f(ca);
              if (l == 0 && q < 2) rec_st(&g_E[(q * NT1 + T1) * DM + ch], 0.f, 0.f, lds32(sb + EP_OFF + 20) - 1);
              if (p.swap) lam.y = -lam.y;
              const float2 p2 = cmul(lam, lam), p4 = cmul(p2, p2);
              p8 = cmul(p4, p4); p16 = cmul(p8, p8);
              pL = cmul(p16, p16);
              if (!last) pL = cmul(pL, p8);
              p2L = cmul(pL, pL);
            }
            if (k == (wg ? PAUSE_K : PAUSE0) && l == 0 && has2) mbar_wait(bars + 8 * B_PREP);
            }
            fb += 8;
          }
        }
        const unsigned tag = lds32(sb + EP_OFF + 20);
        wgmma_wait<0>();
        fence_regs(acc);
        if ((tid & 127) == 0) { mbar_arrive(bars + 8 * (B_G1DONE + 10 * l + 9)); TS(wg ? 17 + l : 2 + 8 * l); }
        float2 ec[3];
#pragma unroll
        for (int jj = 0; jj < 4; jj++)
#pragma unroll
          for (int y = 0; y < 3; y++) {
            if (y == 2 && (jj & 1)) continue;
            const int j = y == 2 ? 16 + jj : 8 * y + 2 * jj;
            const float4 st = lds128f(sb + STAB_OFF + q * 160 + j * 8);
            const float rs[4] = {st.x, st.y, st.z, st.w};
#pragma unroll
            for (int x = 0; x < 4; x++) {
              const int i = 4 * j + 4 * (x >> 1) + (x & 1);
              acc[i] *= rs[x]; acc[i + 2] *= rs[x];
              ec[y] = (jj == 0 && x == 0) ? make_float2(acc[i], acc[i + 2]) : cfma(lam, ec[y], make_float2(acc[i], acc[i + 2]));
            }
          }
        float2 e = cfma(p16, ec[0], ec[1]);
        if (!last) e = cfma(p8, e, ec[2]);
        {
          float2 v = make_float2(__shfl_up_sync(0xffffffffu, e.x, 1, 4), __shfl_up_sync(0xffffffffu, e.y, 1, 4));
          if (q >= 1) e = cfma(pL, v, e);
          v = make_float2(__shfl_up_sync(0xffffffffu, e.x, 2, 4), __shfl_up_sync(0xffffffffu, e.y, 2, 4));
          if (q >= 2) e = cfma(p2L, v, e);
        }
        if (!last && q == 3) rec_st(&g_E[(l * NT1 + T1) * DM + ch], e.x, e.y, tag);
        if (tid == 0) TS(3 + 8 * l);
        float2 ex = make_float2(__shfl_up_sync(0xffffffffu, e.x, 1, 4), __shfl_up_sync(0xffffffffu, e.y, 1, 4));
        if (q == 0) ex = make_float2(0.f, 0.f);
        const float2 coef = lds64f(ca + 8), lamc = make_float2(lam.x, p.swap ? lam.y : -lam.y);
        float m00 = coef.x, m01 = -coef.y, m10 = -coef.y, m11 = -coef.x;
        if (p.swap) { m00 = -coef.y; m01 = coef.x; m10 = -coef.x; m11 = -coef.y; }
        float2 pLq, p160q, p640;
        {
          const float2 p80 = last ? cmul(p2L, p16) : p2L, p160 = cmul(p80, p80), p320 = cmul(p160, p160), one = make_float2(1.f, 0.f);
          p640 = cmul(p320, p320);
          pLq = cmul((q & 1) ? pL : one, (q & 2) ? p2L : one);
          p160q = cmul((q & 1) ? p160 : one, (q & 2) ? p320 : one);
        }
        float2 c, ev[3];
        unsigned tg[3];
        const uint4* ep = &g_E[(l * NT1 + T1 - 1 - q) * DM + ch];
#pragma unroll
        for (int j = 0; j < 20; j++) {
          if (j == CPOLL) {
#pragma unroll
            for (int i = 0; i < 3; i++) {
              ev[i] = make_float2(0.f, 0.f); tg[i] = tag;
              if (T1 - 1 - q - 4 * i >= 0) tg[i] = rec_ld(ep - 4 * i * DM, ev[i].x, ev[i].y);
            }
          }
#pragma unroll
          for (int x = 0; x < 2; x++) {
            const float b0 = acc[4 * j + x], b1 = acc[4 * j + 2 + x];
            acc[4 * j + x] = fmaf(b0, m00, b1 * m01);
            acc[4 * j + 2 + x] = fmaf(b0, m10, b1 * m11);
          }
          if (j == CPOLL - 1 || j == 19) asm volatile("" : "+f"(acc[4 * j]), "+f"(acc[4 * j + 1]), "+f"(acc[4 * j + 2]), "+f"(acc[4 * j + 3])::"memory");
        }
        {
          uint32_t it = 0;
          while (__any_sync(0xffffffffu, tg[0] != tag || tg[1] != tag || tg[2] != tag)) {
#pragma unroll
            for (int i = 0; i < 3; i++)
              if (tg[i] != tag) tg[i] = rec_ld(ep - 4 * i * DM, ev[i].x, ev[i].y);
            trap_if(++it > SPIN_LIMIT);
          }
          c = cfma(p640, cfma(p640, ev[2], ev[1]), ev[0]);
          c = cmul(c, p160q);
          c.x += __shfl_xor_sync(0xffffffffu, c.x, 1); c.y += __shfl_xor_sync(0xffffffffu, c.y, 1);
          c.x += __shfl_xor_sync(0xffffffffu, c.x, 2); c.y += __shfl_xor_sync(0xffffffffu, c.y, 2);
        }
        if (tid == 0) TS(4 + 8 * l);
        if (HOLD1 && wg == 1 && l == 1 && has2) mbar_wait(bars + 8 * HOLD1);
        const uint32_t c0 = (uint32_t)clock(), tm = (tid & 7) == 4 * side + w;
        c = cfma(pLq, c, ex);
        float2 hh = make_float2(fmaf(c.x, m00, c.y * m01), fmaf(c.x, m10, c.y * m11));
        uint8_t* hb = g_h + (10 * wg + 2 * GP) * 8192 + (4 * side + w) * 1024 + (tid_opaque() & 31) * 4;
#pragma unroll
        for (int j4 = 0; j4 < 5; j4++) {
          if (PACE && j4 > 0 && wg == 1 && l == 1) { while (__any_sync(0xffffffffu, (uint32_t)clock() - c0 < PACE * j4)) {} }
          const int ng = 20 * T1 + 4 * j4;
          uint8_t* hp = hb + (size_t)(ng >> 3) * 163840 + (ng & 7) * 128;
#pragma unroll
          for (int jj = 0; jj < 4; jj++) {
            const int j = 4 * j4 + jj;
            const float2 h0 = cfma(lamc, hh, make_float2(acc[4 * j + 0], acc[4 * j + 2]));
            hh = cfma(lamc, h0, make_float2(acc[4 * j + 1], acc[4 * j + 3]));
            if (j4 < 4 || !last) {
              *(uint32_t*)(hp + jj * 128) = tag_word(pack_bf16(h0.x, hh.x), tm, 1 - l);
              *(uint32_t*)(hp + jj * 128 + 8192) = tag_word(pack_bf16(h0.y, hh.y), tm, 1 - l);
            }
          }
        }
        if (l == 0) mbar_arrive(bars + 8 * (B_HST + wg));
        if (tid == 0) TS(5 + 8 * l);
        if (tid == 128) TS(l ? 25 : 19);
        if (l == 0 && wid == 4) {
          mbar_wait(bars + 8 * B_HST);
          mbar_wait(bars + 8 * (B_HST + 1));
          if ((tid & 31) < 4) h_release(0, T1, tid & 3);
          __syncwarp();
          if (tid == 128) { mbar_arrive(bars + 8 * B_REL); TS(6); }
        }
      }
      if (l == 0) {
        ROLE(role)
        if (has2) {
          CvCtx cc;
          mbar_wait(bars + 8 * B_CTAB);
          cv_setup(cc);
          mbar_wait(bars + 8 * (B_G1DONE + 9));
#pragma unroll 1
          for (int c = (wg + 2) & 3; c < 5; c += 4) conv_channel(c, cc);
          if ((tid & 127) == 0) TS(wg == 2 ? 32 : (wg == 3 ? 50 : 7 + wg));
        }
      }
      if (wg >= 2) break;
    }
    if (wg < 2 && (role >> 16)) {
      const int ln = tid_opaque() & 31;
      const uint8_t* src = g_h + ((role >> 8) & 63) * 163840;
      uint32_t ph = 0;
      if (wg == 0) {
        mbar_wait(bars + 8 * (B_G1DONE + 19));
        if (SPEC0 + SPECW) __nanosleep(SPEC0 + SPECW * w);
        if (tid == 0) TS(23);
        if (tid == 96) mbar_arrive(bars + 8 * B_SPEC);
        if (!SPLITI && w < 3 && elect_one()) { mbar_expect_tx(bars + 8 * (B_XV + w + 4), G2_XB); }
      }
#pragma unroll 1
      for (int k = 10 * wg + w; k < 10 * wg + 10; k += 4) {
        if (k < (SPLITI ? S2 : 4) && elect_one()) {
          mbar_expect_tx(bars + 8 * (B_XV + k), G2_XB);
          bulk_g2s(sb + k * G2_XB, src + k * 8192, G2_XB, bars + 8 * (B_XV + k));
          if (!SPLITI && k < 3) bulk_g2s(sb + (k + 4) * G2_XB, src + (k + 4) * 8192, G2_XB, bars + 8 * (B_XV + k + 4));
        }
        validate_block(bars + 8 * (B_XV + k), bars + 8 * (B_G2FULL + 20 + k), sb + (k % S2) * G2_XB, src + k * 8192,
                       (ln & 7) * 1028 + (ln >> 3) * 32, bars + 8 * (B_RETRY + wid), ph);
      }
    }
    if (wg == 3) {
    ROLE(role)
    const int pw = wid & 3, gpc = 2 * min(m2 >> 3, 3) + (dg >> 1);
    mbar_wait(bars + 8 * B_EP);
    const unsigned tag = lds32(sb + EP_OFF + 20);
    if (pw == 0) {
      if (elect_one()) {
#pragma unroll 1
        for (int l = 0; l < 2; l++) {
          uint32_t dst = sb;
          if (l == 1) {
            dst = sb + G2_WOFF;
#pragma unroll 1
            for (int k = 0; k < 10; k++) {
              mbar_wait(k > 4 ? bars + 8 * (B_G1DONE + 5 + k) : (has2 ? bars + 8 * (B_G2DONE + 14 + min(k, 3)) : bars + 8 * (B_G1DONE + 9)));
              mbar_expect_tx(bars + 8 * (B_G1FULL + 10 + k), 16384);
              tma5(dst, &p.mB, 64 * k, 0, 0, 4 * side, 2 * GP, bars + 8 * (B_G1FULL + 10 + k));
              dst += 16384; if (k == 4) dst = sb + G2_WOFF;
            }
          }
          if (has2) {
            const uint32_t fb2 = bars + 8 * (B_G2FULL + 20 * l), wb2 = bars + 8 * (B_G2DONE + 20 * l - S2);
            dst = sb + G2_WOFF + (WTAIL ? 4 * l * G2_WB : 0);
            int kc = 0;
#pragma unroll 1
            for (int k = 0; k < 20; k++) {
              mbar_wait(k >= S2 ? wb2 + 8 * k : bars + 8 * (l ? B_G1DONE + (WTAIL ? (k < 3 ? 15 + k : 13 + k) : 19) : (k == 5 ? B_XFREE : (k == 6 ? B_SFREE : B_REL))));
              mbar_expect_tx(fb2 + 8 * k, G2_WB);
              tma5(dst, &p.mCre + (k & 1), kc, 0, 0, 0, 10 * dg, fb2 + 8 * k);
              kc += (k & 1) << 7; if (k == 9) kc = 64;
              dst += G2_WB; if (dst == sb + G2_WOFF + S2 * G2_WB) dst = sb + G2_WOFF;
            }
          }
        }
      }
    } else if (pw == 1) {
#pragma unroll 1
      for (int l = 0; l < 2; l++) {
        if (l == 1) {
          mbar_wait(bars + 8 * (has2 ? B_G2DONE + 19 : B_G1DONE + 9));
          if (has2) mbar_wait(bars + 8 * B_UST);
          cnt_poll(&g_ucnt[gpc * 32], 128 * tag);
          fence_async_global();
          if (elect_one()) {
            TS(20);
            const int bytes = last ? 16384 : 20480;
            const uint8_t* src = g_u + T1 * 204800;
            uint32_t dst = sb + X1_OFF;
#pragma unroll 1
            for (int k = 0; k < 10; k++) {
              if (k > 4) mbar_wait(bars + 8 * (B_G1DONE + 5 + k));
              mbar_expect_tx(bars + 8 * (B_G1FULL + 10 + k), bytes);
              bulk_g2s(dst, src, bytes, bars + 8 * (B_G1FULL + 10 + k));
              src += 20480; dst += 20480; if (dst == sb + G_OFF) dst = sb; if (k == 4) dst = sb + X1_OFF;
            }
          }
          __syncwarp();
        }
        if (has2) {
          if (l == 0) {
            mbar_wait(bars + 8 * B_REL);
            cnt_poll(&g_hcnt[gpc * 32], 40 * tag);
            fence_async_global();
          }
          if (elect_one()) {
            if (l == 0) TS(21);
            const uint32_t fb2 = bars + 8 * (l ? B_XV : B_G2FULL), wb2 = bars + 8 * (B_G2DONE + 20 * l - S2);
            const uint8_t* src = g_h + m2 * 163840 + l * S2 * 8192;
            uint32_t dst = sb;
#pragma unroll 1
            for (int k = l * S2; k < 20; k++) {
              if (k >= 5) mbar_wait(k >= S2 ? wb2 + 8 * k : bars + 8 * B_SFREE);
              mbar_expect_tx(fb2 + 8 * k, G2_XB);
              bulk_g2s(dst, src, G2_XB, fb2 + 8 * k);
              src += 8192; dst += G2_XB; if (dst == sb + S2 * G2_XB) dst = sb;
            }
          }
          __syncwarp();
        }
      }
    } else if (pw == 2) {
#pragma unroll 1
      for (int l = 0; l < 2; l++) {
        if (l == 1) {
          if (has2) {
            mbar_wait(bars + 8 * B_UST);
            if (lane < 8) red_rel(&g_ucnt[lane * 32]);
            __syncwarp();
            if (lane == 0) TS(38);
          }
          float xa[2], xb[2];
          mbar_wait(bars + 8 * (B_G1FULL + 11));
          stat_table<1>(T1, tag, 4, g_stats, g_stats, xa, xb);
          mbar_arrive(bars + 8 * (B_STAB + 1));
        }
        if (l == 0 && has2 && elect_one()) {
#pragma unroll 1
          for (int i = 0; i < 5; i++) {
            const int c = i < 3 ? i : 7 - i;
            mbar_wait(bars + 8 * (B_CVDONE + c));
            bulk_s2g(g_G + (cch0 + 32 * c) * 4096, cv_stage(c), 4096);
          }
          asm volatile("cp.async.bulk.commit_group;" ::: "memory");
          asm volatile("cp.async.bulk.wait_group.read 0;" ::: "memory");
          mbar_arrive(bars + 8 * B_SFREE);
          asm volatile("cp.async.bulk.wait_group 0;" ::: "memory");
          TS(48);
          fence_async_global();
          asm volatile("fence.acq_rel.gpu;" ::: "memory");
#pragma unroll
          for (int i = 0; i < 4; i++) red_rlx(&g_gcnt[(dg * 4 + i) * 32]);
          TS(49);
          mbar_arrive(bars + 8 * (B_GO + 1));
        }
        __syncwarp();
      }
    } else if (has2) {
      mbar_wait(bars + 8 * B_REL);
      if (!CPF && elect_one()) {
        l2_prefetch(p.cre + (160 * dg + 5 * m2) * DM, 6400); l2_prefetch(p.cim + (160 * dg + 5 * m2) * DM, 6400);
      }
      mbar_wait(bars + 8 * (B_GO + 1));
      flag_poll(&g_gcnt[(dg * 4 + (m2 >> 3)) * 32], 32 * tag);
      fence_async_global();
      if (elect_one()) {
        TS(29);
        mbar_expect_tx(bars + 8 * B_GFULL, 20480);
        tma5(sb + G_OFF, &p.mG, 64 * m2, 0, 0, 0, 10 * dg, bars + 8 * B_GFULL);
      }
    }
    } else if (wg == 2 && (role >> 16)) {
      float acc[80];
      float off[2] = {mean0[0], mean0[1]};
      const unsigned tag = lds32(sb + EP_OFF + 20);
      dskip_init<true>(acc, mean0, rstd0);
      mbar_arrive(bars + 8 * B_XFREE);
      mbar_wait(bars + 8 * (B_CVDONE + 2));
      mbar_wait(bars + 8 * (B_CVDONE + 3));
#pragma unroll 1
      for (int step = 1; step < 4; step++) {
        const int l = step >> 1;
        if (step != 2) {
          uint32_t alo = desc_lo(sb, 1024), blo = desc_lo(sb + G2_WOFF, 16) + (WTAIL ? l * (G2_WB >> 2) : 0);
          uint32_t fb = bars + 8 * (B_G2FULL + 20 * l);
          fence_regs(acc);
          mbar_wait(fb);
          if (tid == 256) TS(33 + 6 * l);
#pragma unroll 1
          for (int k = 0; k < 20; k++) {
            if (l == TSL && (k & 3) == 3 && tid == 256) TS(56 + (k >> 2));
            uint32_t ok; const uint32_t nb = k < 19 ? fb + 8 : fb;
            wgmma_fence();
#pragma unroll
            for (int kk = 0; kk < 4; kk++) {
              wgmma_n160<1>(acc, alo + kk * 128, desc_hi(128, 0), blo + kk * 2, desc_hi(1024, 1));
              if (kk == 0) ok = mbar_test(nb);
            }
            wgmma_commit();
            alo += G2_XB >> 4; blo += G2_WB >> 4;
            if (alo == desc_lo(sb + S2 * G2_XB, 1024)) alo = desc_lo(sb, 1024);
            if (blo == desc_lo(sb + G_OFF, 16)) blo = desc_lo(sb + G2_WOFF, 16);
            wgmma_wait<1>();
            if (k > 0 && tid == 256) mbar_arrive(fb + 8 * (B_G2DONE - B_G2FULL - 1));
            if (!ok) mbar_wait(nb);
            fb += 8;
          }
          wgmma_wait<0>();
          fence_regs(acc);
          if (tid == 256) TS(34 + 6 * l);
          if (tid == 256) mbar_arrive(bars + 8 * (B_G2DONE + 20 * l + 19));
        }
        ROLE(role)
        const int tq = tid_opaque() & 31, n0 = 64 * m2 + 16 * w + (tq >> 2);
        stats_publish<false>(step, n0, dg, tag, acc);
        uint32_t gf[10][4];
        mbar_wait(bars + 8 * B_GFULL);
        uint32_t ga = sb + G_OFF + (8 * (tq >> 4) + (tq & 7)) * 128 + (((2 * w + ((tq >> 3) & 1)) ^ ((2 * m2) & 6) ^ (tq & 7)) << 4), gstep = 2048;
        if (step == 2) { ga = sb + DX_OFF + (8 * (tq >> 4) + (tq & 7)) * 16; gstep = 256; }
#pragma unroll
        for (int J = 0; J < 2; J++) ldsm4t(gf[J], ga + J * gstep);
        if (tid == 256) TS(35 + 6 * l);
        uint8_t* dst[2][2];
#pragma unroll
        for (int h = 0; h < 2; h++) {
          if (l == 0) {
            const int ng = 8 * m2 + 2 * w + h, T = ng / 20;
            uint8_t* ub = g_u + (T * 204800 + (ng - 20 * T) * 1024 + (tq & 2) * 64 + (tq & 28) * 4 + (tq & 1) * 8 + (5 * dg >> 1) * 20480);
            dst[h][1] = ub + ((dg & 1) ? 20480 - 512 : 0);
            dst[h][0] = ub + (dg & 1) * 512;
          } else {
            dst[h][0] = dst[h][1] = (uint8_t*)(p.out + (n_to_t(n0 + 8 * h) * DM + 160 * dg + 4 * (tq & 3)));
          }
        }
        float mean[2], rstd[2];
        stats_get(step, n0, tag, mean, rstd);
        if (tid == 256) TS(36 + 6 * l);
        off[0] += mean[0]; off[1] += mean[1];
        const float ov[2] = {step == 3 ? off[0] : 0.f, step == 3 ? off[1] : 0.f};
#pragma unroll
        for (int J = 0; J < 10; J++) {
          if (J + 2 < 10) ldsm4t(gf[J + 2 < 10 ? J + 2 : 0], ga + (J + 2) * gstep);
#pragma unroll
          for (int x = 0; x < 8; x++) {
            const int h = (x >> 1) & 1;
            const uint32_t gwd = gf[J][x >> 1];
            const float t = fmaf(rstd[h], (x & 1) ? bf_hi(gwd) : bf_lo(gwd), 1.f);
            acc[8 * J + x] = fmaf(acc[8 * J + x], t, fmaf(-mean[h], t, ov[h]));
          }
#pragma unroll
          for (int h = 0; h < 2; h++) {
            if (step == 1)
              *(uint2*)(dst[h][(J >> 1) & 1] + (J >> 2) * 20480 + (J & 3) * 256) =
                  make_uint2(pack_bf16(acc[8 * J + 2 * h], acc[8 * J + 2 * h + 1]), pack_bf16(acc[8 * J + 4 + 2 * h], acc[8 * J + 5 + 2 * h]));
            if (step == 3)
              *(float4*)(dst[h][0] + 64 * J) = make_float4(acc[8 * J + 2 * h], acc[8 * J + 2 * h + 1], acc[8 * J + 4 + 2 * h], acc[8 * J + 5 + 2 * h]);
          }
          __syncwarp();
        }
        if (step == 1) {
          mbar_arrive(bars + 8 * B_UST);
          if (tid == 256) TS(37);
          for (int n = tid & 127; n < 160; n += 128) {
            const int d = 16 * (n >> 4) + 4 * ((n >> 1) & 3) + 2 * ((n >> 3) & 1) + (n & 1);
            const uint32_t dw = lds32(sb + DTAB_OFF + 2 * (d & ~1)), dd = __byte_perm(dw, dw, (d & 1) ? 0x3232 : 0x1010);
            sts128(sb + DX_OFF + 16 * n, make_uint4(dd, dd, dd, dd));
          }
          bar_sync(3, 128);
        } else if (step == 2) {
          if (tid == 256) TS(22);
          mbar_wait(bars + 8 * (B_G1FULL + 11));
          float xa[2], xb[2];
          stat_table<1>(T1, tag, w, g_stats, g_stats, xa, xb);
          mbar_arrive(bars + 8 * (B_STAB + 1));
          if (tid == 256) TS(27);
          mbar_wait(bars + 8 * (B_G1DONE + 19));
          keep_warm(bars + 8 * WEND, 3);
        } else {
          if (tid == 256) {
            TS(43);
            if (m2 == 31 && dg == 3) asm volatile("st.relaxed.gpu.global.u32 [%0], %1;" ::"l"(g_epoch), "r"(tag + 1) : "memory");
          }
        }
      }
    }
  }
}

typedef CUresult (*EncFn)(CUtensorMap*, CUtensorMapDataType, cuuint32_t, void*, const cuuint64_t*, const cuuint64_t*,
                          const cuuint32_t*, const cuuint32_t*, CUtensorMapInterleave, CUtensorMapSwizzle,
                          CUtensorMapL2promotion, CUtensorMapFloatOOBfill);

void encode(EncFn fn, CUtensorMap* m, const void* ptr, int rank, const cuuint64_t* dims, const cuuint64_t* strides, const cuuint32_t* box,
            CUtensorMapSwizzle swz = CU_TENSOR_MAP_SWIZZLE_128B, int prom = 2) {
  cuuint32_t es[5] = {1, 1, 1, 1, 1};
  fn(m, CU_TENSOR_MAP_DATA_TYPE_BFLOAT16, rank, (void*)ptr, dims, strides, box, es, CU_TENSOR_MAP_INTERLEAVE_NONE,
     swz, (CUtensorMapL2promotion)prom, CU_TENSOR_MAP_FLOAT_OOB_FILL_NONE);
}

}

extern "C" void kernel_launch(void* const* d_in, const int* in_sizes, int n_in, void* d_out, int out_size) {
  (void)in_sizes; (void)n_in; (void)out_size;
  Params p;
  typedef const __nv_bfloat16* BP;
  p.x = (BP)d_in[0]; p.lre = (BP)d_in[1]; p.lim = (BP)d_in[2]; p.bre = (BP)d_in[3]; p.bim = (BP)d_in[4];
  p.cre = (BP)d_in[5]; p.cim = (BP)d_in[6]; p.logdt = (BP)d_in[7]; p.dskip = (BP)d_in[8];
  p.k = (BP)d_in[10]; p.v = (BP)d_in[11]; p.shiftk = (BP)d_in[12]; p.ssmk = (BP)d_in[13]; p.ssmD = (BP)d_in[14];
  p.out = (float*)d_out;
  for (int sm = 0; sm < 132; sm++) {
    const int tpc = sm >> 1, side = sm & 1;
    int gpc, gi;
    if (tpc < 32) { gpc = tpc & 7; gi = tpc >> 3; }
    else if (tpc < 60) { gpc = 1 + (tpc - 32) % 7; gi = 4 + (tpc - 32) / 7; }
    else if (tpc < 62) { gpc = tpc - 54; gi = 8; }
    else { gpc = 0; gi = tpc - 58; }
    const int pos = 8 * gpc + gi + (gpc == 7 ? 1 : 0);
    int T1, GP;
    if (pos < 52) { const int hh = pos / 26, x = pos - 26 * hh; T1 = x >> 1; GP = 2 * hh + (x & 1); }
    else { T1 = pos - 52; GP = 4; }
    const int m2 = 8 * (gpc >> 1) + gi, dg = 2 * (gpc & 1) + side;
    p.role[sm] = pos == 65 ? -1 : (T1 | (GP << 4) | (side << 7) | (m2 << 8) | (dg << 14) | ((gi < 8) << 16));
  }
  void* fnp = nullptr;
  cudaDriverEntryPointQueryResult qr;
  cudaGetDriverEntryPoint("cuTensorMapEncodeTiled", &fnp, cudaEnableDefault, &qr);
  EncFn fn = (EncFn)fnp;
  void* gG = nullptr;
  cudaGetSymbolAddress(&gG, g_G);
  void* gKV = nullptr;
  cudaGetSymbolAddress(&gKV, g_kv);
  {
    cuuint64_t dims[5] = {32, 32, 10, 32, 4}, st[4] = {20480, 2048, 64, 655360}; cuuint32_t box[5] = {32, 35, 2, 1, 1};
    encode(fn, &p.mU, gKV, 5, dims, st, box, CU_TENSOR_MAP_SWIZZLE_NONE, 1);
  }
  const cuuint64_t RB = DM * 2;
  {
    p.swap = p.bim < p.bre;
    const char* lo = (const char*)(p.swap ? p.bim : p.bre); const char* hi = (const char*)(p.swap ? p.bre : p.bim);
    cuuint64_t dims[5] = {640, 8, 2, 8, 10}, st[4] = {RB, (cuuint64_t)(hi - lo), 8 * RB, 64 * RB}; cuuint32_t box[5] = {64, 8, 2, 4, 2};
    encode(fn, &p.mB, lo, 5, dims, st, box);
  }
  {
    cuuint64_t dims[5] = {640, 2, 4, 2, 40}, st[4] = {RB, 4 * RB, 2 * RB, 16 * RB}; cuuint32_t box[5] = {64, 2, 4, 2, 10};
    encode(fn, &p.mCre, p.cre, 5, dims, st, box); encode(fn, &p.mCim, p.cim, 5, dims, st, box);
    cuuint64_t dimg[5] = {2048, 2, 4, 2, 40}, stg[4] = {4096, 4 * 4096, 2 * 4096, 16 * 4096};
    encode(fn, &p.mG, gG, 5, dimg, stg, box);
  }
  {
    cuuint64_t dims[4] = {640, 2, 4, 900}, st[3] = {RB, 40 * RB, 2 * RB}; cuuint32_t box[4] = {64, 2, 4, 20};
    encode(fn, &p.mX, p.x, 4, dims, st, box);
    cuuint64_t diml[4] = {640, 2, 4, 16}, stl[3] = {RB, 32 * RB, 2 * RB};
    encode(fn, &p.mXl, p.x + (size_t)1920 * DM, 4, diml, stl, box);
    cuuint32_t boxt[4] = {160, 2, 4, 4};
    encode(fn, &p.mXt, p.x, 4, dims, st, boxt, CU_TENSOR_MAP_SWIZZLE_NONE);
    encode(fn, &p.mXtl, p.x + (size_t)1920 * DM, 4, diml, stl, boxt, CU_TENSOR_MAP_SWIZZLE_NONE);
    cuuint64_t dk[3] = {640, 2000, 4}, sk[2] = {RB, 16 * RB}; cuuint32_t bk[3] = {32, 19, 4}, bv[3] = {32, 17, 4};
    encode(fn, &p.mK, p.k, 3, dk, sk, bk, CU_TENSOR_MAP_SWIZZLE_NONE);
    encode(fn, &p.mV, p.v, 3, dk, sk, bv, CU_TENSOR_MAP_SWIZZLE_NONE);
  }
  cudaFuncSetAttribute(fused_kernel, cudaFuncAttributeMaxDynamicSharedMemorySize, SMEM_BYTES);
  cudaLaunchConfig_t cfg = {};
  cfg.gridDim = dim3(132); cfg.blockDim = dim3(512); cfg.dynamicSmemBytes = SMEM_BYTES; cfg.stream = cudaStreamPerThread;
  cudaLaunchKernelEx(&cfg, fused_kernel, p);
}
```

```cpp
#include <cuda_runtime.h>
#include <cuda.h>
#include <cuda_bf16.h>
#include <stdint.h>

namespace {

constexpr int SEQ = 2048, DM = 640;
constexpr int NT1 = 13;
#define EXP 0
#define WPF1 3
#define WPF2 7
#define CPOLL 10
#define KV0 1
#define TAPLATE 1
#define STG_D 3
#define STG_KK 1
#define HOLD1 0
#define SPEC0 100
#define WREL 0
#define UREL 1
#define TSL 1
#define STG0 2
#define WTAIL 1
#define PFD 1
#define TAPW 0
#define TPF 4
#define CPF 0
#define MK0 8
#define MK1 4
#define PACE 350
#define TAPN 2
#define SPLITI 1
#define SPECW 60
#define WEND B_SPEC
#define PAUSE0 6
#define TISS 4
#define EARLY1 1
#define PAUSE_K 5
constexpr uint32_t SPIN_LIMIT = 1u << 22;

__device__ __align__(1024) uint8_t g_h[32 * 20 * 8192];
__device__ __align__(1024) uint8_t g_u[NT1 * 10 * 20480];
__device__ __align__(1024) uint8_t g_kv[DM * 4096];
__device__ __align__(1024) uint8_t g_G[DM * 4096];
__device__ __align__(128) uint4 g_E[2 * NT1 * DM];
__device__ __align__(128) uint4 g_stats[4 * 4 * SEQ];
__device__ __align__(128) uint4 g_sB[DM * 2];
__device__ __align__(128) unsigned g_hcnt[8 * 32];
__device__ __align__(128) unsigned g_ucnt[8 * 32];
__device__ __align__(128) unsigned g_kvcnt[16 * 32];
__device__ __align__(128) unsigned g_gcnt[16 * 32];
__device__ __align__(128) unsigned g_epoch[32] = {1};
#define TS(i) do {} while (0)

struct Params {
  CUtensorMap mX, mB, mXl, mK, mV, mXt, mXtl, mCre, mCim, mG, mU;
  const __nv_bfloat16 *x, *lre, *lim, *bre, *bim, *cre, *cim, *logdt, *dskip, *k, *v, *shiftk, *ssmk, *ssmD;
  float* out;
  int swap;
  int role[132];
};

constexpr uint32_t sb = 1024;
constexpr uint32_t G1_STAGE = 36864, G1_XOFF = 16384;
constexpr int S1 = 4;
constexpr uint32_t XT_OFF = 159744, KS_OFF = 180224, KV_PIECE = 9216;
constexpr uint32_t G2_XB = 8192, G2_WB = 20480, G2_WOFF = 57344, G_OFF = 200704;
constexpr uint32_t X1_OFF = 139264;
constexpr int S2 = 7;
constexpr uint32_t CV_OFF = KS_OFF, CV_K = 128, CV_PL = 2240, CV_U = CV_K + 4096, CV_B = KV_PIECE;
constexpr uint32_t MISC = 226304;
constexpr uint32_t BAR_OFF = MISC;
constexpr int B_G1FULL = 0, B_G1DONE = 20, B_G2FULL = 40,
              B_G2DONE = 85, B_GFULL = 125, B_EP = 126, B_CVFULL = 129  , B_STG = 134  , B_REL = 136  , B_SFREE = 138,
              B_GO = 139  , B_PUB = 147,
              B_CVDONE = 148  , B_STAB = 153  , B_XFREE = 155, B_HST = 156  , B_UST = 158,
              B_CTAB = 160, B_PREP = 161, B_XT = 162, B_KV = 163  , B_PREP2 = 84, B_PD = 168  ,
              B_XV = 173  , B_RETRY = 193  , B_SPEC = 202;
constexpr uint32_t bars = sb + BAR_OFF;
constexpr uint32_t STAB_OFF = MISC + 1648;
constexpr uint32_t CTAB_OFF = STAB_OFF + 640;
constexpr uint32_t DTAB_OFF = CTAB_OFF + 1536;
constexpr uint32_t EP_OFF = DTAB_OFF + 320;
constexpr uint32_t SO_OFF = EP_OFF + 32;
constexpr uint32_t TAP_OFF = 147456;
constexpr uint32_t MX0_OFF = TAP_OFF + 1280, MX1_OFF = G_OFF + 20480;
constexpr uint32_t DX_OFF = MX1_OFF + 2560;
constexpr uint32_t SMEM_BYTES = 232448;
static_assert(SO_OFF + 1536 <= SMEM_BYTES, "smem");

__device__ __forceinline__ void trap_if(bool c) { asm volatile("{\n.reg .pred p;\nsetp.ne.u32 p, %0, 0;\n@p trap;\n}\n" ::"r"((uint32_t)c)); }
__device__ __forceinline__ uint32_t smem_u32(const void* p) { return (uint32_t)__cvta_generic_to_shared(p); }
__device__ __forceinline__ void mbar_init(uint32_t bar, int cnt) { asm volatile("mbarrier.init.shared::cta.b64 [%0], %1;" ::"r"(bar), "r"(cnt) : "memory"); }
__device__ __forceinline__ void mbar_expect_tx(uint32_t bar, int bytes) { asm volatile("mbarrier.arrive.expect_tx.shared::cta.b64 _, [%0], %1;" ::"r"(bar), "r"(bytes) : "memory"); }
__device__ __forceinline__ void mbar_arrive(uint32_t bar) { asm volatile("mbarrier.arrive.shared::cta.b64 _, [%0];" ::"r"(bar) : "memory"); }
__device__ __forceinline__ bool elect_one() {
  uint32_t e; asm volatile("{\n.reg .pred P;\nelect.sync _|P, 0xffffffff;\nselp.u32 %0, 1, 0, P;\n}\n" : "=r"(e)); return e != 0;
}
__device__ __forceinline__ void mbar_wait(uint32_t bar) {
  asm volatile(
      "{\n.reg .pred p;\n.reg .u32 c;\nmov.u32 c, 0;\n"
      "W_%=:\nmbarrier.try_wait.parity.shared::cta.b64 p, [%0], 0;\n@p bra D_%=;\n"
      "add.u32 c, c, 1;\nsetp.lt.u32 p, c, %1;\n@p bra W_%=;\ntrap;\nD_%=:\n}\n" ::"r"(bar), "n"(SPIN_LIMIT) : "memory");
}
__device__ __forceinline__ uint32_t mbar_test(uint32_t bar) {
  uint32_t ok;
  asm volatile("{\n.reg .pred p;\nmbarrier.test_wait.parity.shared::cta.b64 p, [%1], 0;\nselp.u32 %0, 1, 0, p;\n}\n" : "=r"(ok) : "r"(bar) : "memory");
  return ok;
}
__device__ __forceinline__ void tma3(uint32_t dst, const CUtensorMap* m, int c0, int c1, int c2, uint32_t bar) {
  asm volatile("cp.async.bulk.tensor.3d.shared::cluster.global.mbarrier::complete_tx::bytes [%0], [%1, {%3,%4,%5}], [%2];"
               ::"r"(dst), "l"(m), "r"(bar), "r"(c0), "r"(c1), "r"(c2) : "memory");
}
__device__ __forceinline__ void tma4(uint32_t dst, const CUtensorMap* m, int c0, int c1, int c2, int c3, uint32_t bar) {
  asm volatile("cp.async.bulk.tensor.4d.shared::cluster.global.mbarrier::complete_tx::bytes [%0], [%1, {%3,%4,%5,%6}], [%2];"
               ::"r"(dst), "l"(m), "r"(bar), "r"(c0), "r"(c1), "r"(c2), "r"(c3) : "memory");
}
__device__ __forceinline__ void tma5(uint32_t dst, const CUtensorMap* m, int c0, int c1, int c2, int c3, int c4, uint32_t bar) {
  asm volatile("cp.async.bulk.tensor.5d.shared::cluster.global.mbarrier::complete_tx::bytes [%0], [%1, {%3,%4,%5,%6,%7}], [%2];"
               ::"r"(dst), "l"(m), "r"(bar), "r"(c0), "r"(c1), "r"(c2), "r"(c3), "r"(c4) : "memory");
}
__device__ __forceinline__ void bulk_g2s(uint32_t dst, const void* src, int bytes, uint32_t bar) {
  asm volatile("cp.async.bulk.shared::cluster.global.mbarrier::complete_tx::bytes [%0], [%1], %2, [%3];"
               ::"r"(dst), "l"(src), "r"(bytes), "r"(bar) : "memory");
}
__device__ __forceinline__ void bulk_s2g(void* dst, uint32_t src, int bytes) {
  asm volatile("cp.async.bulk.global.shared::cta.bulk_group [%0], [%1], %2;" ::"l"(dst), "r"(src), "r"(bytes) : "memory");
}
__device__ __forceinline__ void l2_prefetch(const void* src, int bytes) {
  asm volatile("cp.async.bulk.prefetch.L2.global [%0], %1;" ::"l"(src), "r"(bytes) : "memory");
}
__device__ __forceinline__ void wgmma_fence() { asm volatile("wgmma.fence.sync.aligned;" ::: "memory"); }
__device__ __forceinline__ void wgmma_commit() { asm volatile("wgmma.commit_group.sync.aligned;" ::: "memory"); }
template <int N> __device__ __forceinline__ void wgmma_wait() { asm volatile("wgmma.wait_group.sync.aligned %0;" ::"n"(N) : "memory"); }
__host__ __device__ constexpr uint32_t desc_lo(uint32_t addr, uint32_t lbo) { return ((addr & 0x3FFFF) >> 4) | ((lbo >> 4) << 16); }
__host__ __device__ constexpr uint32_t desc_hi(uint32_t sbo, uint32_t swz) { return (sbo >> 4) | (swz << 30); }
__device__ __forceinline__ void bar_sync(int id, int n) { asm volatile("bar.sync %0, %1;" ::"r"(id), "r"(n) : "memory"); }
__device__ __forceinline__ uint32_t lds32(uint32_t a) { uint32_t v; asm volatile("ld.shared.u32 %0, [%1];" : "=r"(v) : "r"(a) : "memory"); return v; }
__device__ __forceinline__ float2 lds64f(uint32_t a) { float2 v; asm volatile("ld.shared.v2.f32 {%0,%1}, [%2];" : "=f"(v.x), "=f"(v.y) : "r"(a) : "memory"); return v; }
__device__ __forceinline__ float4 lds128f(uint32_t a) { float4 v; asm volatile("ld.shared.v4.f32 {%0,%1,%2,%3}, [%4];" : "=f"(v.x), "=f"(v.y), "=f"(v.z), "=f"(v.w) : "r"(a) : "memory"); return v; }
__device__ __forceinline__ void ldsm4t(uint32_t (&r)[4], uint32_t a) {
  asm volatile("ldmatrix.sync.aligned.m8n8.x4.trans.shared.b16 {%0,%1,%2,%3}, [%4];" : "=r"(r[0]), "=r"(r[1]), "=r"(r[2]), "=r"(r[3]) : "r"(a) : "memory");
}
__device__ __forceinline__ uint4 ldv128(const void* a) { uint4 v; asm volatile("ld.global.nc.v4.u32 {%0,%1,%2,%3}, [%4];" : "=r"(v.x), "=r"(v.y), "=r"(v.z), "=r"(v.w) : "l"(a) : "memory"); return v; }
__device__ __forceinline__ uint2 ldv64(const void* a) { uint2 v; asm volatile("ld.global.nc.v2.u32 {%0,%1}, [%2];" : "=r"(v.x), "=r"(v.y) : "l"(a) : "memory"); return v; }
__device__ __forceinline__ uint32_t ldv16(const void* a) { uint32_t v; asm volatile("ld.global.nc.u16 %0, [%1];" : "=r"(v) : "l"(a) : "memory"); return v; }
__device__ __forceinline__ void sts128(uint32_t a, uint4 v) { asm volatile("st.shared.v4.u32 [%0], {%1,%2,%3,%4};" ::"r"(a), "r"(v.x), "r"(v.y), "r"(v.z), "r"(v.w) : "memory"); }
__device__ __forceinline__ void sts32(uint32_t a, uint32_t v) { asm volatile("st.shared.u32 [%0], %1;" ::"r"(a), "r"(v) : "memory"); }
__device__ __forceinline__ void sts64f(uint32_t a, float x, float y) { asm volatile("st.shared.v2.f32 [%0], {%1,%2};" ::"r"(a), "f"(x), "f"(y) : "memory"); }
__device__ __forceinline__ void red_rlx(unsigned* p) { asm volatile("red.relaxed.gpu.global.add.u32 [%0], 1;" ::"l"(p) : "memory"); }
__device__ __forceinline__ void red_rel(unsigned* p) { asm volatile("red.release.gpu.global.add.u32 [%0], 1;" ::"l"(p) : "memory"); }
__device__ __forceinline__ void fence_async_global() { asm volatile("fence.proxy.async.global;" ::: "memory"); }
__device__ __forceinline__ void fence_async_smem() { asm volatile("fence.proxy.async.shared::cta;" ::: "memory"); }
__device__ __forceinline__ void rec_st(uint4* p, float a, float b, unsigned tag) {
  asm volatile("{\n.reg .b128 t;\n.reg .b64 lo, hi;\nmov.b64 lo, {%1,%2};\nmov.b64 hi, {%3,%3};\nmov.b128 t, {lo,hi};\n"
               "st.relaxed.gpu.global.b128 [%0], t;\n}\n" ::"l"(p), "r"(__float_as_uint(a)), "r"(__float_as_uint(b)), "r"(tag) : "memory");
}
__device__ __forceinline__ unsigned rec_ld(const uint4* p, float& a, float& b) {
  unsigned x, y, t;
  asm volatile("{\n.reg .b128 t;\n.reg .b64 lo, hi;\n.reg .b32 u;\nld.relaxed.gpu.global.b128 t, [%3];\nmov.b128 {lo,hi}, t;\n"
               "mov.b64 {%0,%1}, lo;\nmov.b64 {%2,u}, hi;\n}\n" : "=r"(x), "=r"(y), "=r"(t) : "l"(p) : "memory");
  a = __uint_as_float(x); b = __uint_as_float(y);
  return t;
}
__device__ __forceinline__ unsigned ld_rlx(const unsigned* p) { unsigned v; asm volatile("ld.relaxed.gpu.global.u32 %0, [%1];" : "=r"(v) : "l"(p) : "memory"); return v; }
__device__ __forceinline__ void flag_poll(const unsigned* p, unsigned target) {
  uint32_t it = 0;
  while (!__all_sync(0xffffffffu, (int)(ld_rlx(p) - target) >= 0)) { trap_if(++it > SPIN_LIMIT); }
  asm volatile("fence.acquire.gpu;" ::: "memory");
}
__device__ __forceinline__ void cnt_poll(const unsigned* p, unsigned target) {
  unsigned a = ld_rlx(p); __nanosleep(100);
  unsigned b = ld_rlx(p); __nanosleep(100);
  unsigned c = ld_rlx(p);
  uint32_t it = 0;
  while (true) {
    if (__all_sync(0xffffffffu, (int)(a - target) >= 0)) break;
    a = ld_rlx(p);
    if (__all_sync(0xffffffffu, (int)(b - target) >= 0)) break;
    b = ld_rlx(p);
    if (__all_sync(0xffffffffu, (int)(c - target) >= 0)) break;
    c = ld_rlx(p);
    trap_if(++it > SPIN_LIMIT);
  }
  asm volatile("fence.acquire.gpu;" ::: "memory");
}
__device__ __forceinline__ void validate_block(uint32_t bar, uint32_t full, uint32_t dst, const uint8_t* src, uint32_t woff, uint32_t rb, uint32_t& ph) {
  uint32_t it = 0, par = 0;
  while (true) {
    uint32_t ok, spins = 0;
    do {
      asm volatile("{\n.reg .pred p;\nmbarrier.try_wait.parity.shared::cta.b64 p, [%1], %2;\nselp.u32 %0, 1, 0, p;\n}\n" : "=r"(ok) : "r"(bar), "r"(par) : "memory");
      trap_if(++spins > SPIN_LIMIT);
    } while (!__all_sync(0xffffffffu, ok));
    uint32_t bad = 0;
#pragma unroll
    for (int i = 0; i < 8; i++) bad |= lds32(dst + woff + 128 * i);
    if (!__any_sync(0xffffffffu, bad & 1)) break;
    if (elect_one()) { mbar_expect_tx(rb, 8192); bulk_g2s(dst, src, 8192, rb); }
    bar = rb; par = ph; ph ^= 1;
    trap_if(++it > 100000);
  }
  if ((threadIdx.x & 31) == 0) mbar_arrive(full);
}
__device__ __forceinline__ uint32_t tag_word(uint32_t v, uint32_t m, uint32_t par) {
  uint32_t r; asm("lop3.b32 %0, %1, %2, %3, 0xb8;" : "=r"(r) : "r"(v), "r"(m), "r"(par)); return r;
}
__device__ __forceinline__ void h_release(int idx, int T, int i) {
  const int Q = (i & 2) ? (T + 2) / 3 - 1 : T / 3;
  if (Q >= 0 && Q < 4 && ((i & 2) == 0 || T % 3 == 0)) red_rel(&g_hcnt[(idx * 8 + 2 * Q + (i & 1)) * 32]);
}
__device__ __forceinline__ uint32_t pack_bf16(float lo, float hi) {
  uint32_t r; asm("cvt.rn.bf16x2.f32 %0, %1, %2;" : "=r"(r) : "f"(hi), "f"(lo)); return r;
}
__device__ __forceinline__ float bf_lo(uint32_t w) { return __uint_as_float(w << 16); }
__device__ __forceinline__ float bf_hi(uint32_t w) { return __uint_as_float(w & 0xffff0000u); }
__device__ __forceinline__ uint32_t hmul2(uint32_t a, uint32_t b) {
  __nv_bfloat162 r = __hmul2_rn(*(__nv_bfloat162*)&a, *(__nv_bfloat162*)&b); return *(uint32_t*)&r;
}
__device__ __forceinline__ uint32_t hadd2(uint32_t a, uint32_t b) {
  __nv_bfloat162 r = __hadd2_rn(*(__nv_bfloat162*)&a, *(__nv_bfloat162*)&b); return *(uint32_t*)&r;
}
__device__ __forceinline__ float2 cmul(float2 a, float2 b) { return make_float2(a.x * b.x - a.y * b.y, a.x * b.y + a.y * b.x); }
__device__ __forceinline__ float2 cfma(float2 a, float2 b, float2 c) {
  return make_float2(fmaf(a.x, b.x, fmaf(-a.y, b.y, c.x)), fmaf(a.x, b.y, fmaf(a.y, b.x, c.y)));
}
template <int N> __device__ __forceinline__ void fence_regs(float (&a)[N]) {
#pragma unroll
  for (int i = 0; i < N; i++) asm volatile("" : "+f"(a[i])::"memory");
}
__device__ __forceinline__ int tid_opaque() { int t; asm volatile("mov.u32 %0, %%tid.x;" : "=r"(t)); return t; }
struct Role { int T1, GP, side, m2, dg, cch0; bool last, has2; };
__device__ __forceinline__ Role unpack_role(int x) {
  Role r; r.T1 = x & 15; r.GP = (x >> 4) & 7; r.side = (x >> 7) & 1; r.m2 = (x >> 8) & 63; r.dg = (x >> 14) & 3;
  r.has2 = (x >> 16) & 1; r.last = r.T1 == NT1 - 1; r.cch0 = 160 * r.dg + r.m2; return r;
}
__device__ __forceinline__ Role fresh_role(int x) { asm volatile("" : "+r"(x)); return unpack_role(__shfl_sync(0xffffffffu, x, 0)); }
#define ROLE(x) const Role R_ = fresh_role(x); const int T1 = R_.T1, GP = R_.GP, side = R_.side, m2 = R_.m2, dg = R_.dg, cch0 = R_.cch0; \
  const bool last = R_.last, has2 = R_.has2; (void)T1; (void)GP; (void)side; (void)m2; (void)dg; (void)cch0; (void)last; (void)has2;
__device__ __forceinline__ int n_to_t(int n) {
  int T = n / 160, nl = n - T * 160;
  int L = (T == NT1 - 1) ? 32 : 40;
  return T * 160 + L * ((nl & 7) >> 1) + 2 * (nl >> 3) + (nl & 1);
}

template<int TA> __device__ __forceinline__ void wgmma_n160(float (&d)[80], uint32_t alo, uint32_t ahi, uint32_t blo, uint32_t bhi){
  asm volatile("{\n.reg .b64 da, db;\nmov.b64 da, {%80,%81};\nmov.b64 db, {%82,%83};\n"
    "wgmma.mma_async.sync.aligned.m64n160k16.f32.bf16.bf16 {%0, %1, %2, %3, %4, %5, %6, %7, %8, %9, %10, %11, %12, %13, %14, %15, %16, %17, %18, %19, %20, %21, %22, %23, %24, %25, %26, %27, %28, %29, %30, %31, %32, %33, %34, %35, %36, %37, %38, %39, %40, %41, %42, %43, %44, %45, %46, %47, %48, %49, %50, %51, %52, %53, %54, %55, %56, %57, %58, %59, %60, %61, %62, %63, %64, %65, %66, %67, %68, %69, %70, %71, %72, %73, %74, %75, %76, %77, %78, %79}, da, db, 1, 1, 1, %84, 0;\n}\n"
    : "+f"(d[0]), "+f"(d[1]), "+f"(d[2]), "+f"(d[3]), "+f"(d[4]), "+f"(d[5]), "+f"(d[6]), "+f"(d[7]), "+f"(d[8]), "+f"(d[9]), "+f"(d[10]), "+f"(d[11]), "+f"(d[12]), "+f"(d[13]), "+f"(d[14]), "+f"(d[15]), "+f"(d[16]), "+f"(d[17]), "+f"(d[18]), "+f"(d[19]), "+f"(d[20]), "+f"(d[21]), "+f"(d[22]), "+f"(d[23]), "+f"(d[24]), "+f"(d[25]), "+f"(d[26]), "+f"(d[27]), "+f"(d[28]), "+f"(d[29]), "+f"(d[30]), "+f"(d[31]), "+f"(d[32]), "+f"(d[33]), "+f"(d[34]), "+f"(d[35]), "+f"(d[36]), "+f"(d[37]), "+f"(d[38]), "+f"(d[39]), "+f"(d[40]), "+f"(d[41]), "+f"(d[42]), "+f"(d[43]), "+f"(d[44]), "+f"(d[45]), "+f"(d[46]), "+f"(d[47]), "+f"(d[48]), "+f"(d[49]), "+f"(d[50]), "+f"(d[51]), "+f"(d[52]), "+f"(d[53]), "+f"(d[54]), "+f"(d[55]), "+f"(d[56]), "+f"(d[57]), "+f"(d[58]), "+f"(d[59]), "+f"(d[60]), "+f"(d[61]), "+f"(d[62]), "+f"(d[63]), "+f"(d[64]), "+f"(d[65]), "+f"(d[66]), "+f"(d[67]), "+f"(d[68]), "+f"(d[69]), "+f"(d[70]), "+f"(d[71]), "+f"(d[72]), "+f"(d[73]), "+f"(d[74]), "+f"(d[75]), "+f"(d[76]), "+f"(d[77]), "+f"(d[78]), "+f"(d[79])
    : "r"(alo), "r"(ahi), "r"(blo), "r"(bhi), "n"(TA));
}
__device__ __forceinline__ void wgmma_rs_n160(float (&d)[80], uint32_t a0, uint32_t a1, uint32_t a2, uint32_t a3, uint32_t blo){
  asm volatile("{\n.reg .b64 db;\nmov.b64 db, {%84,8};\nwgmma.mma_async.sync.aligned.m64n160k16.f32.bf16.bf16 {%0, %1, %2, %3, %4, %5, %6, %7, %8, %9, %10, %11, %12, %13, %14, %15, %16, %17, %18, %19, %20, %21, %22, %23, %24, %25, %26, %27, %28, %29, %30, %31, %32, %33, %34, %35, %36, %37, %38, %39, %40, %41, %42, %43, %44, %45, %46, %47, %48, %49, %50, %51, %52, %53, %54, %55, %56, %57, %58, %59, %60, %61, %62, %63, %64, %65, %66, %67, %68, %69, %70, %71, %72, %73, %74, %75, %76, %77, %78, %79}, {%80,%81,%82,%83}, db, 1, 1, 1, 0;\n}\n"
    : "+f"(d[0]), "+f"(d[1]), "+f"(d[2]), "+f"(d[3]), "+f"(d[4]), "+f"(d[5]), "+f"(d[6]), "+f"(d[7]), "+f"(d[8]), "+f"(d[9]), "+f"(d[10]), "+f"(d[11]), "+f"(d[12]), "+f"(d[13]), "+f"(d[14]), "+f"(d[15]), "+f"(d[16]), "+f"(d[17]), "+f"(d[18]), "+f"(d[19]), "+f"(d[20]), "+f"(d[21]), "+f"(d[22]), "+f"(d[23]), "+f"(d[24]), "+f"(d[25]), "+f"(d[26]), "+f"(d[27]), "+f"(d[28]), "+f"(d[29]), "+f"(d[30]), "+f"(d[31]), "+f"(d[32]), "+f"(d[33]), "+f"(d[34]), "+f"(d[35]), "+f"(d[36]), "+f"(d[37]), "+f"(d[38]), "+f"(d[39]), "+f"(d[40]), "+f"(d[41]), "+f"(d[42]), "+f"(d[43]), "+f"(d[44]), "+f"(d[45]), "+f"(d[46]), "+f"(d[47]), "+f"(d[48]), "+f"(d[49]), "+f"(d[50]), "+f"(d[51]), "+f"(d[52]), "+f"(d[53]), "+f"(d[54]), "+f"(d[55]), "+f"(d[56]), "+f"(d[57]), "+f"(d[58]), "+f"(d[59]), "+f"(d[60]), "+f"(d[61]), "+f"(d[62]), "+f"(d[63]), "+f"(d[64]), "+f"(d[65]), "+f"(d[66]), "+f"(d[67]), "+f"(d[68]), "+f"(d[69]), "+f"(d[70]), "+f"(d[71]), "+f"(d[72]), "+f"(d[73]), "+f"(d[74]), "+f"(d[75]), "+f"(d[76]), "+f"(d[77]), "+f"(d[78]), "+f"(d[79])
    : "r"(a0), "r"(a1), "r"(a2), "r"(a3), "r"(blo));
}
template<int N> __device__ __forceinline__ void wgmma_rs_hi(float (&d)[64], uint32_t a0, uint32_t a1, uint32_t a2, uint32_t a3, uint32_t blo);
template<> __device__ __forceinline__ void wgmma_rs_hi<16>(float (&d)[64], uint32_t a0, uint32_t a1, uint32_t a2, uint32_t a3, uint32_t blo){
  asm volatile("{\n.reg .b64 db;\nmov.b64 db, {%12,8};\nwgmma.mma_async.sync.aligned.m64n16k16.f32.bf16.bf16 {%0, %1, %2, %3, %4, %5, %6, %7}, {%8,%9,%10,%11}, db, 1, 1, 1, 0;\n}\n"
    : "+f"(d[56]), "+f"(d[57]), "+f"(d[58]), "+f"(d[59]), "+f"(d[60]), "+f"(d[61]), "+f"(d[62]), "+f"(d[63])
    : "r"(a0), "r"(a1), "r"(a2), "r"(a3), "r"(blo));
}
template<> __device__ __forceinline__ void wgmma_rs_hi<32>(float (&d)[64], uint32_t a0, uint32_t a1, uint32_t a2, uint32_t a3, uint32_t blo){
  asm volatile("{\n.reg .b64 db;\nmov.b64 db, {%20,8};\nwgmma.mma_async.sync.aligned.m64n32k16.f32.bf16.bf16 {%0, %1, %2, %3, %4, %5, %6, %7, %8, %9, %10, %11, %12, %13, %14, %15}, {%16,%17,%18,%19}, db, 1, 1, 1, 0;\n}\n"
    : "+f"(d[48]), "+f"(d[49]), "+f"(d[50]), "+f"(d[51]), "+f"(d[52]), "+f"(d[53]), "+f"(d[54]), "+f"(d[55]), "+f"(d[56]), "+f"(d[57]), "+f"(d[58]), "+f"(d[59]), "+f"(d[60]), "+f"(d[61]), "+f"(d[62]), "+f"(d[63])
    : "r"(a0), "r"(a1), "r"(a2), "r"(a3), "r"(blo));
}
template<> __device__ __forceinline__ void wgmma_rs_hi<48>(float (&d)[64], uint32_t a0, uint32_t a1, uint32_t a2, uint32_t a3, uint32_t blo){
  asm volatile("{\n.reg .b64 db;\nmov.b64 db, {%28,8};\nwgmma.mma_async.sync.aligned.m64n48k16.f32.bf16.bf16 {%0, %1, %2, %3, %4, %5, %6, %7, %8, %9, %10, %11, %12, %13, %14, %15, %16, %17, %18, %19, %20, %21, %22, %23}, {%24,%25,%26,%27}, db, 1, 1, 1, 0;\n}\n"
    : "+f"(d[40]), "+f"(d[41]), "+f"(d[42]), "+f"(d[43]), "+f"(d[44]), "+f"(d[45]), "+f"(d[46]), "+f"(d[47]), "+f"(d[48]), "+f"(d[49]), "+f"(d[50]), "+f"(d[51]), "+f"(d[52]), "+f"(d[53]), "+f"(d[54]), "+f"(d[55]), "+f"(d[56]), "+f"(d[57]), "+f"(d[58]), "+f"(d[59]), "+f"(d[60]), "+f"(d[61]), "+f"(d[62]), "+f"(d[63])
    : "r"(a0), "r"(a1), "r"(a2), "r"(a3), "r"(blo));
}
template<> __device__ __forceinline__ void wgmma_rs_hi<64>(float (&d)[64], uint32_t a0, uint32_t a1, uint32_t a2, uint32_t a3, uint32_t blo){
  asm volatile("{\n.reg .b64 db;\nmov.b64 db, {%36,8};\nwgmma.mma_async.sync.aligned.m64n64k16.f32.bf16.bf16 {%0, %1, %2, %3, %4, %5, %6, %7, %8, %9, %10, %11, %12, %13, %14, %15, %16, %17, %18, %19, %20, %21, %22, %23, %24, %25, %26, %27, %28, %29, %30, %31}, {%32,%33,%34,%35}, db, 1, 1, 1, 0;\n}\n"
    : "+f"(d[32]), "+f"(d[33]), "+f"(d[34]), "+f"(d[35]), "+f"(d[36]), "+f"(d[37]), "+f"(d[38]), "+f"(d[39]), "+f"(d[40]), "+f"(d[41]), "+f"(d[42]), "+f"(d[43]), "+f"(d[44]), "+f"(d[45]), "+f"(d[46]), "+f"(d[47]), "+f"(d[48]), "+f"(d[49]), "+f"(d[50]), "+f"(d[51]), "+f"(d[52]), "+f"(d[53]), "+f"(d[54]), "+f"(d[55]), "+f"(d[56]), "+f"(d[57]), "+f"(d[58]), "+f"(d[59]), "+f"(d[60]), "+f"(d[61]), "+f"(d[62]), "+f"(d[63])
    : "r"(a0), "r"(a1), "r"(a2), "r"(a3), "r"(blo));
}
template<> __device__ __forceinline__ void wgmma_rs_hi<80>(float (&d)[64], uint32_t a0, uint32_t a1, uint32_t a2, uint32_t a3, uint32_t blo){
  asm volatile("{\n.reg .b64 db;\nmov.b64 db, {%44,8};\nwgmma.mma_async.sync.aligned.m64n80k16.f32.bf16.bf16 {%0, %1, %2, %3, %4, %5, %6, %7, %8, %9, %10, %11, %12, %13, %14, %15, %16, %17, %18, %19, %20, %21, %22, %23, %24, %25, %26, %27, %28, %29, %30, %31, %32, %33, %34, %35, %36, %37, %38, %39}, {%40,%41,%42,%43}, db, 1, 1, 1, 0;\n}\n"
    : "+f"(d[24]), "+f"(d[25]), "+f"(d[26]), "+f"(d[27]), "+f"(d[28]), "+f"(d[29]), "+f"(d[30]), "+f"(d[31]), "+f"(d[32]), "+f"(d[33]), "+f"(d[34]), "+f"(d[35]), "+f"(d[36]), "+f"(d[37]), "+f"(d[38]), "+f"(d[39]), "+f"(d[40]), "+f"(d[41]), "+f"(d[42]), "+f"(d[43]), "+f"(d[44]), "+f"(d[45]), "+f"(d[46]), "+f"(d[47]), "+f"(d[48]), "+f"(d[49]), "+f"(d[50]), "+f"(d[51]), "+f"(d[52]), "+f"(d[53]), "+f"(d[54]), "+f"(d[55]), "+f"(d[56]), "+f"(d[57]), "+f"(d[58]), "+f"(d[59]), "+f"(d[60]), "+f"(d[61]), "+f"(d[62]), "+f"(d[63])
    : "r"(a0), "r"(a1), "r"(a2), "r"(a3), "r"(blo));
}
template<> __device__ __forceinline__ void wgmma_rs_hi<96>(float (&d)[64], uint32_t a0, uint32_t a1, uint32_t a2, uint32_t a3, uint32_t blo){
  asm volatile("{\n.reg .b64 db;\nmov.b64 db, {%52,8};\nwgmma.mma_async.sync.aligned.m64n96k16.f32.bf16.bf16 {%0, %1, %2, %3, %4, %5, %6, %7, %8, %9, %10, %11, %12, %13, %14, %15, %16, %17, %18, %19, %20, %21, %22, %23, %24, %25, %26, %27, %28, %29, %30, %31, %32, %33, %34, %35, %36, %37, %38, %39, %40, %41, %42, %43, %44, %45, %46, %47}, {%48,%49,%50,%51}, db, 1, 1, 1, 0;\n}\n"
    : "+f"(d[16]), "+f"(d[17]), "+f"(d[18]), "+f"(d[19]), "+f"(d[20]), "+f"(d[21]), "+f"(d[22]), "+f"(d[23]), "+f"(d[24]), "+f"(d[25]), "+f"(d[26]), "+f"(d[27]), "+f"(d[28]), "+f"(d[29]), "+f"(d[30]), "+f"(d[31]), "+f"(d[32]), "+f"(d[33]), "+f"(d[34]), "+f"(d[35]), "+f"(d[36]), "+f"(d[37]), "+f"(d[38]), "+f"(d[39]), "+f"(d[40]), "+f"(d[41]), "+f"(d[42]), "+f"(d[43]), "+f"(d[44]), "+f"(d[45]), "+f"(d[46]), "+f"(d[47]), "+f"(d[48]), "+f"(d[49]), "+f"(d[50]), "+f"(d[51]), "+f"(d[52]), "+f"(d[53]), "+f"(d[54]), "+f"(d[55]), "+f"(d[56]), "+f"(d[57]), "+f"(d[58]), "+f"(d[59]), "+f"(d[60]), "+f"(d[61]), "+f"(d[62]), "+f"(d[63])
    : "r"(a0), "r"(a1), "r"(a2), "r"(a3), "r"(blo));
}
template<> __device__ __forceinline__ void wgmma_rs_hi<112>(float (&d)[64], uint32_t a0, uint32_t a1, uint32_t a2, uint32_t a3, uint32_t blo){
  asm volatile("{\n.reg .b64 db;\nmov.b64 db, {%60,8};\nwgmma.mma_async.sync.aligned.m64n112k16.f32.bf16.bf16 {%0, %1, %2, %3, %4, %5, %6, %7, %8, %9, %10, %11, %12, %13, %14, %15, %16, %17, %18, %19, %20, %21, %22, %23, %24, %25, %26, %27, %28, %29, %30, %31, %32, %33, %34, %35, %36, %37, %38, %39, %40, %41, %42, %43, %44, %45, %46, %47, %48, %49, %50, %51, %52, %53, %54, %55}, {%56,%57,%58,%59}, db, 1, 1, 1, 0;\n}\n"
    : "+f"(d[8]), "+f"(d[9]), "+f"(d[10]), "+f"(d[11]), "+f"(d[12]), "+f"(d[13]), "+f"(d[14]), "+f"(d[15]), "+f"(d[16]), "+f"(d[17]), "+f"(d[18]), "+f"(d[19]), "+f"(d[20]), "+f"(d[21]), "+f"(d[22]), "+f"(d[23]), "+f"(d[24]), "+f"(d[25]), "+f"(d[26]), "+f"(d[27]), "+f"(d[28]), "+f"(d[29]), "+f"(d[30]), "+f"(d[31]), "+f"(d[32]), "+f"(d[33]), "+f"(d[34]), "+f"(d[35]), "+f"(d[36]), "+f"(d[37]), "+f"(d[38]), "+f"(d[39]), "+f"(d[40]), "+f"(d[41]), "+f"(d[42]), "+f"(d[43]), "+f"(d[44]), "+f"(d[45]), "+f"(d[46]), "+f"(d[47]), "+f"(d[48]), "+f"(d[49]), "+f"(d[50]), "+f"(d[51]), "+f"(d[52]), "+f"(d[53]), "+f"(d[54]), "+f"(d[55]), "+f"(d[56]), "+f"(d[57]), "+f"(d[58]), "+f"(d[59]), "+f"(d[60]), "+f"(d[61]), "+f"(d[62]), "+f"(d[63])
    : "r"(a0), "r"(a1), "r"(a2), "r"(a3), "r"(blo));
}
template<> __device__ __forceinline__ void wgmma_rs_hi<128>(float (&d)[64], uint32_t a0, uint32_t a1, uint32_t a2, uint32_t a3, uint32_t blo){
  asm volatile("{\n.reg .b64 db;\nmov.b64 db, {%68,8};\nwgmma.mma_async.sync.aligned.m64n128k16.f32.bf16.bf16 {%0, %1, %2, %3, %4, %5, %6, %7, %8, %9, %10, %11, %12, %13, %14, %15, %16, %17, %18, %19, %20, %21, %22, %23, %24, %25, %26, %27, %28, %29, %30, %31, %32, %33, %34, %35, %36, %37, %38, %39, %40, %41, %42, %43, %44, %45, %46, %47, %48, %49, %50, %51, %52, %53, %54, %55, %56, %57, %58, %59, %60, %61, %62, %63}, {%64,%65,%66,%67}, db, 1, 1, 1, 0;\n}\n"
    : "+f"(d[0]), "+f"(d[1]), "+f"(d[2]), "+f"(d[3]), "+f"(d[4]), "+f"(d[5]), "+f"(d[6]), "+f"(d[7]), "+f"(d[8]), "+f"(d[9]), "+f"(d[10]), "+f"(d[11]), "+f"(d[12]), "+f"(d[13]), "+f"(d[14]), "+f"(d[15]), "+f"(d[16]), "+f"(d[17]), "+f"(d[18]), "+f"(d[19]), "+f"(d[20]), "+f"(d[21]), "+f"(d[22]), "+f"(d[23]), "+f"(d[24]), "+f"(d[25]), "+f"(d[26]), "+f"(d[27]), "+f"(d[28]), "+f"(d[29]), "+f"(d[30]), "+f"(d[31]), "+f"(d[32]), "+f"(d[33]), "+f"(d[34]), "+f"(d[35]), "+f"(d[36]), "+f"(d[37]), "+f"(d[38]), "+f"(d[39]), "+f"(d[40]), "+f"(d[41]), "+f"(d[42]), "+f"(d[43]), "+f"(d[44]), "+f"(d[45]), "+f"(d[46]), "+f"(d[47]), "+f"(d[48]), "+f"(d[49]), "+f"(d[50]), "+f"(d[51]), "+f"(d[52]), "+f"(d[53]), "+f"(d[54]), "+f"(d[55]), "+f"(d[56]), "+f"(d[57]), "+f"(d[58]), "+f"(d[59]), "+f"(d[60]), "+f"(d[61]), "+f"(d[62]), "+f"(d[63])
    : "r"(a0), "r"(a1), "r"(a2), "r"(a3), "r"(blo));
}

__device__ __forceinline__ void keep_warm(uint32_t bar, int barid) {
  float d0 = 0.f, d1 = 0.f, d2 = 0.f, d3 = 0.f;
  uint32_t it = 0, go;
  const uint32_t z0 = lds32(sb + EP_OFF + 24), z1 = lds32(sb + EP_OFF + 24), z2 = lds32(sb + EP_OFF + 24), z3 = lds32(sb + EP_OFF + 24);
  do {
    wgmma_fence();
    asm volatile("{\n.reg .b64 db;\nmov.b64 db, {%8,8};\nwgmma.mma_async.sync.aligned.m64n8k16.f32.bf16.bf16 {%0,%1,%2,%3}, {%4,%5,%6,%7}, db, 1, 1, 1, 0;\n}\n"
                 : "+f"(d0), "+f"(d1), "+f"(d2), "+f"(d3) : "r"(z0), "r"(z1), "r"(z2), "r"(z3), "r"(desc_lo(sb + DTAB_OFF, 0)));
    wgmma_commit();
    wgmma_wait<0>();
    asm volatile("{\n.reg .pred p, q;\nmbarrier.test_wait.parity.shared::cta.b64 p, [%1], 0;\nbar.red.or.pred q, %2, 128, p;\nselp.u32 %0, 1, 0, q;\n}\n"
                 : "=r"(go) : "r"(bar), "r"(barid) : "memory");
    trap_if(++it > SPIN_LIMIT);
  } while (!__all_sync(0xffffffffu, go));
  sts32(sb + EP_OFF + 28, __float_as_uint(d0 + d1 + d2 + d3));
}

struct CvCtx {
  uint32_t koff, zero, so[3];
  int srcA, srcB;
  bool wrapA, s3, kodd;
};
struct CvPipe { uint32_t Ap, Ep, keep, send; };
template <int LO> __device__ __forceinline__ void cv_copy(float (&acc)[64]) {
#pragma unroll
  for (int i = LO; i < 64; i++) { float t; asm volatile("mov.b32 %0, %1;" : "=f"(t) : "f"(acc[i]) : "memory"); acc[i] = t; }
}
template <int G> __device__ __forceinline__ void cv_raw(uint32_t (&A)[4][4], uint32_t kaddr) {
#pragma unroll
  for (int i = 0; i < 4; i++) {
    const uint32_t a = kaddr + (4 * G + i) * 128;
    A[i][0] = lds32(a); A[i][1] = lds32(a + 4); A[i][3] = lds32(a + 8);
  }
}
__device__ __forceinline__ void cv_form(uint32_t (&A)[4][4], uint32_t sel) {
#pragma unroll
  for (int i = 0; i < 4; i++) {
    asm volatile("prmt.b32 %0, %0, %1, %2;" : "+r"(A[i][0]) : "r"(A[i][1]), "r"(sel));
    asm volatile("prmt.b32 %0, %1, %2, %3;" : "=r"(A[i][2]) : "r"(A[i][1]), "r"(A[i][3]), "r"(sel));
  }
}
#define CVV 2
template <int G> __device__ __forceinline__ void cv_step(float (&acc)[64], uint32_t (&A)[4][4], CvPipe& s, const CvCtx& c, uint32_t cb, uint32_t stg) {
  constexpr int JA = G - 1, JB = G - 2, NH = CVV == 1 ? 4 : (CVV == 3 ? 2 : 1);
  const uint32_t db0 = desc_lo(cb + CV_U + 192, CV_PL);
  uint32_t B[4][4];
  uint32_t ra[2], rb;
  if constexpr (G < 8) {
    wgmma_fence();
#pragma unroll
    for (int i = 0; i < NH; i++) wgmma_rs_hi<128 - 16 * (G & 7)>(acc, A[i][0], A[i][1], A[i][2], A[i][3], db0 - 4 * i);
    wgmma_commit();
    __syncwarp();
  }
  if constexpr (JA >= 0 && JA < 8) {
    const uint32_t p0 = pack_bf16(acc[8 * JA + 1], acc[8 * JA + 3]), p1 = pack_bf16(acc[8 * JA + 5], acc[8 * JA + 7]);
    ra[0] = __shfl_sync(0xffffffffu, c.wrapA ? s.Ap : p0, c.srcA);
    ra[1] = __shfl_sync(0xffffffffu, c.wrapA ? p0 : p1, c.srcA);
    s.Ap = p1;
  }
  if constexpr (JB >= 0) rb = __shfl_sync(0xffffffffu, s.send, c.srcB);
  if constexpr (G < 7) cv_raw<G + 1>(B, cb + c.koff);
  uint32_t z = 0;
  if constexpr (G < 8 && NH < 4) {
    __syncwarp();
    wgmma_fence();
#pragma unroll
    for (int i = NH; i < 4; i++) wgmma_rs_hi<128 - 16 * (G & 7)>(acc, A[i][0], A[i][1], A[i][2], A[i][3], db0 - 4 * i);
    wgmma_commit();
    asm volatile("mov.u32 %0, %%clock;" : "=r"(z)::"memory");
    z &= c.zero;
  }
  if constexpr (G < 7) cv_form(B, 0x5432u | z);
  if constexpr (JB >= 0) sts32(stg + ((c.so[JB / 3] >> (10 * (JB % 3))) & 0xffc), hadd2(rb | z, s.keep));
  if constexpr (JA >= 0 && JA < 8) {
    const uint32_t sh = 16 | z, mk = 0xffff0000u | z;
    const uint32_t ev = pack_bf16(acc[8 * JA] + __uint_as_float(ra[0] << sh), acc[8 * JA + 2] + __uint_as_float(ra[0] & mk));
    const uint32_t od = pack_bf16(acc[8 * JA + 4] + __uint_as_float(ra[1] << sh), acc[8 * JA + 6] + __uint_as_float(ra[1] & mk));
    s.send = c.kodd ? ev : (c.s3 ? s.Ep : od);
    s.keep = c.kodd ? od : ev;
    s.Ep = od;
  }
  if constexpr (G < 8) { __syncwarp(); wgmma_wait<0>(); cv_copy<8 * (G & 7)>(acc); }
  if constexpr (G < 9) cv_step<G + 1>(acc, B, s, c, cb, stg);
}
__device__ __forceinline__ uint32_t cv_stage(int slot) { return sb + (slot < 4 ? 40960 + slot * 4096 : CV_OFF + CV_K); }
__device__ __forceinline__ void cv_setup(CvCtx& c) {
  const int tid = tid_opaque() & 127, w = tid >> 5, lane = tid & 31, r = lane >> 2, q = lane & 3;
  const int i0 = (r >> 1) & 1, i1 = r >> 2;
  c.koff = CV_K - 32 + 4 * (8 * (r >> 1) + 2 * w + (r & 1) + 2 * q);
  c.srcA = i0 ? lane - 8 : lane + 8 - q + ((q + 3) & 3);
  c.wrapA = i0 && q == 3;
  c.srcB = i1 == 0 ? (lane - q + 16 + ((q + 3) & 3)) : (lane - q - 16 + ((q + 1) & 3));
  c.s3 = (i1 == 1 && q == 3); c.kodd = (i1 == 1 && q < 3);
  c.zero = lds32(sb + EP_OFF + 24);
#pragma unroll
  for (int i = 0; i < 3; i++) c.so[i] = lds32(sb + SO_OFF + 512 * i + 4 * tid);
}
__device__ __forceinline__ void cv_table() {
  const int tid = tid_opaque() & 127, r = (tid & 31) >> 2, q = tid & 3;
  int t = 16 * (2 * (r < 4 ? q : 4 + ((q + 1) & 3)) + ((r >> 1) & 1)) + 4 * (tid >> 5) + 2 * (r & 1);
#pragma unroll 1
  for (int i = 0; i < 3; i++) {
    uint32_t v = 0;
#pragma unroll 1
    for (int x = 0; x < 3; x++, t += 256) {
      const int T = t / 160, tl = t - T * 160;
      const int qq = (T >= NT1 - 1) ? (tl >> 5) : (tl / 40);
      int ck = 20 * T + ((tl - qq * ((T >= NT1 - 1) ? 32 : 40)) >> 1);
      ck ^= (ck >> 2) & 6;
      v |= (uint32_t)((ck * 4 + qq) & 1023) << (10 * x + 2);
    }
    sts32(sb + SO_OFF + 512 * i + 4 * tid, v);
  }
}
__device__ __forceinline__ void conv_channel(int slot, const CvCtx& c) {
  const uint32_t cb = sb + CV_OFF + slot * CV_B;
  float acc[64];
  CvPipe s;
  s.Ap = s.Ep = 0u;
  uint32_t A[4][4];
#pragma unroll
  for (int i = 0; i < 64; i++) acc[i] = 0.f;
  if (slot == 4) mbar_wait(bars + 8 * B_CVDONE);
  mbar_wait(bars + 8 * (B_CVFULL + slot));
  cv_raw<0>(A, cb + c.koff);
  {
    const uint32_t w0 = lds32(cb + CV_K);
    const uint32_t wp = __byte_perm(pack_bf16(bf_lo(w0) + __uint_as_float(lds32(sb + EP_OFF + 4 * slot)), 0.f), w0, 0x7610);
    if (c.koff == CV_K) A[0][0] = wp;
    if (c.koff == CV_K - 4) A[0][1] = wp;
    if (c.koff == CV_K - 8) A[0][3] = wp;
  }
  cv_form(A, 0x5432u);
  cv_copy<0>(acc);
  cv_step<0>(acc, A, s, c, cb, cv_stage(slot));
  fence_async_smem();
  mbar_arrive(bars + 8 * (B_CVDONE + slot));
}

__device__ __forceinline__ void kv_issue(const Params& p, int c, int m2, int dg) {
  const uint32_t fb = bars + 8 * (B_KV + c);
  mbar_expect_tx(fb, KV_PIECE);
  tma3(sb + KS_OFF + c * KV_PIECE, &p.mK, 160 * dg + 32 * c, 64 * m2 - 3, 0, fb);
  tma3(sb + KS_OFF + c * KV_PIECE + 4864, &p.mV, 160 * dg + 32 * c, 64 * m2 - 1, 0, fb);
}
__device__ __forceinline__ void kv_tile(int m, int c, int y, uint32_t (&o)[4][4]) {
  const int lane = tid_opaque() & 31, tg = lane & 3, pr = 8 * (y ^ (tg >> 1)) + (lane >> 2);
  const uint32_t pb = sb + KS_OFF + c * KV_PIECE + 4 * pr;
  const uint32_t ka = pb + tg * 1216, va = pb + 4864 + tg * 1088 + 64;
  const uint32_t kh = (m == 0 && tg > 0) ? ka - 192 : ka;
  uint32_t kk[19], u[16];
  const float4 t = lds128f(sb + TAP_OFF + 256 * c + 16 * pr);
#pragma unroll
  for (int i = 0; i < 19; i++) { kk[i] = lds32((i < 3 ? kh : ka) + i * 64); if (i >= 3) u[i - 3] = lds32(va + (i - 3) * 64); }
  const uint32_t dst = sb + KS_OFF + c * KV_PIECE + pr * 64 + tg * 16;
  if (y) {
    __syncwarp();
#pragma unroll
    for (int x = 0; x < 4; x++) sts128((dst ^ 512) + x * 1024, make_uint4(o[x][0], o[x][1], o[x][2], o[x][3]));
  }
  const uint32_t w0 = __byte_perm(__float_as_uint(t.x), __float_as_uint(t.z), 0x5410), w1 = __byte_perm(__float_as_uint(t.x), __float_as_uint(t.z), 0x7632);
  const uint32_t w2 = __byte_perm(__float_as_uint(t.y), __float_as_uint(t.w), 0x5410), w3 = __byte_perm(__float_as_uint(t.y), __float_as_uint(t.w), 0x7632);
#pragma unroll
  for (int i = 0; i < 16; i++) {
    uint32_t a = hmul2(kk[i], w3);
    a = hadd2(a, hmul2(kk[i + 1], w2)); a = hadd2(a, hmul2(kk[i + 2], w1)); a = hadd2(a, hmul2(kk[i + 3], w0));
    u[i] = hmul2(a, u[i]);
  }
#pragma unroll
  for (int x = 0; x < 4; x++) {
#pragma unroll
    for (int qq = 0; qq < 4; qq++) o[x][qq] = __byte_perm(u[15 - 4 * qq - (x & 2)], u[14 - 4 * qq - (x & 2)], (x & 1) ? 0x7632 : 0x5410);
    if (y) sts128(dst + x * 1024, make_uint4(o[x][0], o[x][1], o[x][2], o[x][3]));
  }
}
template <bool BF>
__device__ __forceinline__ void ln_finish(float s1, float s2, float& mean, float& rstd) {
  mean = s1 * (1.f / 640.f);
  float v = fmaxf(fmaf(-mean, mean, s2 * (1.f / 640.f)), 0.f);
  if (BF) {
    const uint32_t mv = pack_bf16(mean, v);
    mean = bf_lo(mv);
    asm("sqrt.approx.ftz.f32 %0, %1;" : "=f"(v) : "f"(bf_lo(pack_bf16(bf_hi(mv) + 1e-5f, 0.f))));
    asm("rcp.approx.ftz.f32 %0, %1;" : "=f"(rstd) : "f"(bf_lo(pack_bf16(v, 0.f))));
  } else {
    v += 1e-5f;
    asm("rsqrt.approx.ftz.f32 %0, %1;" : "=f"(rstd) : "f"(v));
  }
}
template <int l>
__device__ __forceinline__ void stat_write(int n, const float (&a)[4], const float (&b)[4]) {
  float m, rs;
  ln_finish<l == 0>((a[0] + a[1]) + (a[2] + a[3]), (b[0] + b[1]) + (b[2] + b[3]), m, rs);
  sts32(sb + STAB_OFF + ((n >> 1) & 3) * 160 + (n >> 3) * 8 + (n & 1) * 4, __float_as_uint(rs));
  const uint32_t hi = pack_bf16(-m, -m);
  const float lo = -m - bf_lo(hi);
  sts128(sb + (l ? MX1_OFF : MX0_OFF) + n * 16, make_uint4(hi, pack_bf16(lo, lo), 0u, 0u));
}
template <int l>
__device__ __forceinline__ void stat_table(int T1, unsigned want, int g, const uint4* x0, const uint4* x1, float (&xa)[2], float (&xb)[2]) {
  const int n = 32 * g + (tid_opaque() & 31);
  const uint4* rp = &g_stats[8 * l * SEQ + min(160 * T1 + n, SEQ - 1)];
  float a[4], b[4];
  uint32_t it = 0;
  while (true) {
    bool ok = true;
#pragma unroll
    for (int i = 0; i < 4; i++) ok &= (rec_ld(rp + SEQ * i, a[i], b[i]) == want);
    ok &= rec_ld(x0, xa[0], xb[0]) == want;
    ok &= rec_ld(x1, xa[1], xb[1]) == want;
    if (__all_sync(0xffffffffu, ok)) break;
    trap_if(++it > SPIN_LIMIT);
  }
  stat_write<l>(n, a, b);
  fence_async_smem();
}
template <bool BF>
__device__ __forceinline__ void stats_reduce(float (&a)[2], float (&b)[2], float (&mean)[2], float (&rstd)[2]) {
#pragma unroll
  for (int o = 1; o < 4; o <<= 1)
#pragma unroll
    for (int h = 0; h < 2; h++) { a[h] += __shfl_xor_sync(0xffffffffu, a[h], o); b[h] += __shfl_xor_sync(0xffffffffu, b[h], o); }
#pragma unroll
  for (int h = 0; h < 2; h++) ln_finish<BF>(a[h], b[h], mean[h], rstd[h]);
}

template <bool FIRST>
__device__ __forceinline__ void stats_publish(int which, int n0, int dg, unsigned tag, const float (&acc)[80]) {
  const int q = tid_opaque() & 3, h = q & 1;
  float s1[2] = {0.f, 0.f}, s2[2] = {0.f, 0.f}, t1[2] = {0.f, 0.f}, t2[2] = {0.f, 0.f};
#pragma unroll
  for (int j = 0; j < 20; j++)
#pragma unroll
    for (int y = 0; y < 2; y++) {
      const float a = acc[4 * j + 2 * y], b = acc[4 * j + 2 * y + 1];
      s1[y] += a; t1[y] += b; s2[y] = fmaf(a, a, s2[y]); t2[y] = fmaf(b, b, t2[y]);
    }
#pragma unroll
  for (int y = 0; y < 2; y++) { s1[y] += t1[y]; s2[y] += t2[y]; }
  float a = (h ? s1[1] : s1[0]) + __shfl_xor_sync(0xffffffffu, h ? s1[0] : s1[1], 1);
  float b = (h ? s2[1] : s2[0]) + __shfl_xor_sync(0xffffffffu, h ? s2[0] : s2[1], 1);
  a += __shfl_xor_sync(0xffffffffu, a, 2);
  b += __shfl_xor_sync(0xffffffffu, b, 2);
  if (FIRST) {
    rec_st(&g_stats[((q >> 1) * 4 + dg) * SEQ + n0 + 8 * h], a, b, q < 2 ? tag : tag - 1);
    rec_st(&g_stats[((q >> 1) * 4 + 8 + dg) * SEQ + n0 + 8 * h], a, b, tag - 1);
  } else if (q < 2) rec_st(&g_stats[(which * 4 + dg) * SEQ + n0 + 8 * h], a, b, tag);
}
template <bool BF>
__device__ __forceinline__ void stats_get(int which, int n0, unsigned tag, float (&mean)[2], float (&rstd)[2]) {
  const uint4* p0 = &g_stats[(which * 4 + (tid_opaque() & 3)) * SEQ + n0];
  float a[2], b[2];
  uint32_t it = 0;
  while (true) {
    const unsigned t0 = rec_ld(p0, a[0], b[0]), t1 = rec_ld(p0 + 8, a[1], b[1]);
    if (__all_sync(0xffffffffu, t0 == tag && t1 == tag)) break;
    trap_if(++it > SPIN_LIMIT);
  }
  stats_reduce<BF>(a, b, mean, rstd);
}
__device__ __forceinline__ void x0_load(float (&acc)[80]) {
  const int t = tid_opaque() & 127;
  const uint32_t xa = sb + XT_OFF + (16 * (t >> 5) + ((t & 31) >> 2)) * 320 + 8 * (t & 3);
  mbar_wait(bars + 8 * B_XT);
#pragma unroll
  for (int h = 0; h < 2; h++)
#pragma unroll
    for (int J = 0; J < 10; J++) {
      const float2 v = lds64f(xa + h * 2560 + 32 * J);
      const uint32_t x = __float_as_uint(v.x), y = __float_as_uint(v.y);
      acc[8 * J + 2 * h] = bf_lo(x); acc[8 * J + 2 * h + 1] = bf_hi(x);
      acc[8 * J + 4 + 2 * h] = bf_lo(y); acc[8 * J + 4 + 2 * h + 1] = bf_hi(y);
    }
}

template <bool FROM_X0>
__device__ __forceinline__ void dskip_init(float (&acc)[80], const float (&mean)[2], const float (&rstd)[2]) {
  const int t = tid_opaque() & 127;
  const uint32_t xa = sb + XT_OFF + (16 * (t >> 5) + ((t & 31) >> 2)) * 320 + 8 * (t & 3), da = sb + DTAB_OFF + 8 * (t & 3);
  float2 dw[10], xv[10][2];
#pragma unroll
  for (int J = 0; J < 2; J++) { dw[J] = lds64f(da + 32 * J); if (FROM_X0) { xv[J][0] = lds64f(xa + 32 * J); xv[J][1] = lds64f(xa + 2560 + 32 * J); } }
#pragma unroll
  for (int J = 0; J < 10; J++) {
    if (J + 2 < 10) { dw[J + 2] = lds64f(da + 32 * (J + 2)); if (FROM_X0) { xv[J + 2][0] = lds64f(xa + 32 * (J + 2)); xv[J + 2][1] = lds64f(xa + 2560 + 32 * (J + 2)); } }
#pragma unroll
    for (int x = 0; x < 8; x++) {
      const int h = (x >> 1) & 1;
      const uint32_t dwd = __float_as_uint(x < 4 ? dw[J].x : dw[J].y);
      const float tt = fmaf(rstd[h], (x & 1) ? bf_hi(dwd) : bf_lo(dwd), 1.f);
      float a = acc[8 * J + x];
      if (FROM_X0) { const uint32_t xw = __float_as_uint(x < 4 ? xv[J][h].x : xv[J][h].y); a = (x & 1) ? bf_hi(xw) : bf_lo(xw); }
      acc[8 * J + x] = FROM_X0 ? (a - mean[h]) * tt : fmaf(a, tt, -mean[h] * tt);
    }
  }
}

__global__ void __launch_bounds__(512, 1) fused_kernel(const __grid_constant__ Params p) {
  extern __shared__ __align__(1024) uint8_t smem_raw[];
  const int tid = threadIdx.x, lane = tid & 31;
  const int wid = __shfl_sync(0xffffffffu, tid >> 5, 0), wg = wid >> 2;
  unsigned smid; asm volatile("mov.u32 %0, %%smid;" : "=r"(smid));
  const int role = p.role[min(smid, 131u)];
  if (wid == 12) {
    const bool el = elect_one();
    if (el) {
      asm volatile("prefetch.tensormap [%0];" ::"l"(&p.mB) : "memory");
      asm volatile("prefetch.tensormap [%0];" ::"l"((role & 15) == NT1 - 1 ? &p.mXl : &p.mX) : "memory");
#pragma unroll
      for (int k = 0; k < S1; k++) mbar_init(bars + 8 * (B_G1FULL + k), 1);
#pragma unroll
      for (int k = 0; k < 6; k++) mbar_init(bars + 8 * (B_XT + k), 1);
      asm volatile("fence.mbarrier_init.release.cluster;" ::: "memory");
    }
    if (role >= 0) {
      __syncwarp();
      asm volatile("bar.arrive 5, 288;" ::: "memory");
      const Role R = unpack_role(role);
      if (elect_one()) {
        TS(45);
#pragma unroll 1
        for (int k = 0; k < S1; k++) {
          const uint32_t fb = bars + 8 * (B_G1FULL + k);
          mbar_expect_tx(fb, G1_STAGE);
          tma4(sb + k * G1_STAGE + G1_XOFF, R.last ? &p.mXl : &p.mX, 64 * k, 0, 0, R.last ? 0 : 80 * R.T1, fb);
          tma5(sb + k * G1_STAGE, &p.mB, 64 * k, 0, 0, 4 * R.side, 2 * R.GP, fb);
          if (PFD) asm volatile("prefetch.tensormap [%0];" ::"l"(&p.mK + k) : "memory");
        }
        if (R.has2) {
          mbar_expect_tx(bars + 8 * B_XT, 20480);
#pragma unroll 1
          for (int h = 0; h < 2; h++) {
            const int ng = 8 * R.m2 + 4 * h, T = ng / 20;
            tma4(sb + XT_OFF + h * 10240, T == NT1 - 1 ? &p.mXtl : &p.mXt, 160 * R.dg, 0, 0, T == NT1 - 1 ? ng - 240 : ng + 60 * T, bars + 8 * B_XT);
          }
#pragma unroll 1
          for (int c = 0; c < KV0; c++) kv_issue(p, c, R.m2, R.dg);
        }
        TS(44);
      }
      __syncwarp();
      bar_sync(6, 64);
    }
  }
  trap_if(smid >= 132 || smem_u32(smem_raw) != sb);
  if (role < 0) {
    if (wid == 0) {
      const unsigned tag = ld_rlx(g_epoch);
      uint32_t it = 0;
      while (!__all_sync(0xffffffffu, (int)(ld_rlx(&g_hcnt[(lane & 7) * 32]) - 40 * tag) >= 0)) { __nanosleep(500); trap_if(++it > SPIN_LIMIT); }
    }
    return;
  }
  float mean0[2] = {0.f, 0.f}, rstd0[2] = {0.f, 0.f};
  if (wg == 2 || wid == 14) {
    ROLE(role)
    const int c = wid == 14 ? 4 : wid - 8;
    const unsigned tag = ld_rlx(g_epoch);
    if (has2) {
      uint2 bv[2][5];
#pragma unroll
      for (int x = 0; x < 2; x++)
#pragma unroll
        for (int i = 0; i < 5; i++) bv[x][i] = ldv64((const uint2*)((x ? p.bim : p.bre) + (cch0 + 32 * c) * DM) + lane + 32 * i);
      float sv[2];
#pragma unroll
      for (int x = 0; x < 2; x++) {
        float a = 0.f;
#pragma unroll
        for (int i = 0; i < 5; i++) a += (bf_lo(bv[x][i].x) + bf_hi(bv[x][i].x)) + (bf_lo(bv[x][i].y) + bf_hi(bv[x][i].y));
        sv[x] = a;
      }
#pragma unroll
      for (int o = 16; o > 0; o >>= 1) { sv[0] += __shfl_xor_sync(0xffffffffu, sv[0], o); sv[1] += __shfl_xor_sync(0xffffffffu, sv[1], o); }
      if (lane < 2) rec_st(&g_sB[(cch0 + 32 * c) * 2 + lane], sv[0], sv[1], tag);
      if (tid == 256) TS(47);
      __syncwarp();
      bar_sync(8, 192);
      if (wg == 2) {
        float xs[80];
        x0_load(xs);
        stats_publish<true>(0, 64 * m2 + 16 * c + (lane >> 2), dg, tag, xs);
        if (tid == 256) TS(31);
      }
      mbar_wait(bars + 8 * B_EP);
      mbar_wait(bars + 8 * (B_KV + c));
      mbar_wait(bars + 8 * (B_G1DONE + PAUSE_K - 1));
      if (tid == 448) TS(52);
      uint32_t o[4][4] = {};
#pragma unroll 1
      for (int y = 0; y < 2; y++) kv_tile(m2, c, y, o);
      fence_async_smem();
      __syncwarp();
      if (lane == 0) { mbar_arrive(bars + 8 * B_PREP); mbar_arrive(bars + 8 * (B_PD + c)); }
      if (tid == 448) TS(51);
    } else bar_sync(8, 192);
    if (wg == 2 && has2) {
      mbar_wait(bars + 8 * B_PUB);
      stats_get<true>(0, 64 * m2 + 16 * c + (lane >> 2), tag, mean0, rstd0);
    }
  } else if (wid == 15) {
    ROLE(role)
    const int ch = 128 * GP + 32 * side + lane;
    uint32_t r0 = ldv16(p.lre + ch), r1 = ldv16(p.lim + ch), r2 = ldv16(p.logdt + ch);
    const uint32_t r3 = ldv16(p.lre + ch + 64), r4 = ldv16(p.lim + ch + 64), r5 = ldv16(p.logdt + ch + 64);
#pragma unroll 1
    for (int i = 0; i < 2; i++) {
      const float lr = bf_lo(r0), li = bf_lo(r1);
      const float dt = __bfloat162float(__float2bfloat16_rn(expf(bf_lo(r2))));
      const float mag = expf(dt * lr);
      float sn, cs; sincospif(dt * li * 0.31830988618379067f, &sn, &cs);
      const float ar = mag * cs, ai = mag * sn;
      const float inv = 2.f / (lr * lr + li * li);
      const uint32_t ad = sb + CTAB_OFF + (32 * i + lane) * 24;
      sts64f(ad, ar, ai);
      sts64f(ad + 8, ((ar - 1.f) * lr + ai * li) * inv, (ai * lr - (ar - 1.f) * li) * inv);
      r0 = r3; r1 = r4; r2 = r5;
    }
    if (lane == 0) TS(46);
    __syncwarp();
    bar_sync(7, 64);
    mbar_arrive(bars + 8 * B_CTAB);
    mbar_wait(bars + 8 * B_EP);
    const unsigned tag = lds32(sb + EP_OFF + 20);
    mbar_wait(bars + 8 * (B_G1DONE + TISS));
    float a[5][4], b[5][4], xa[2], xb[2];
    uint32_t it = 0;
    while (true) {
      bool ok = true;
#pragma unroll
      for (int g = 0; g < 5; g++)
#pragma unroll
        for (int i = 0; i < 4; i++) ok &= rec_ld(&g_stats[SEQ * i + 160 * T1 + lane + ((g == 4 && last) ? 0 : 32 * g)], a[g][i], b[g][i]) == tag;
#pragma unroll
      for (int i = 0; i < 2; i++) ok &= rec_ld(&g_sB[(ch + 64 * i) * 2], xa[i], xb[i]) == tag;
      if (__all_sync(0xffffffffu, ok)) break;
      trap_if(++it > SPIN_LIMIT);
    }
#pragma unroll
    for (int g = 0; g < 5; g++) stat_write<0>(32 * g + lane, a[g], b[g]);
#pragma unroll
    for (int i = 0; i < 2; i++) {
      const float ha = bf_lo(pack_bf16(xa[i], 0.f)), hb = bf_lo(pack_bf16(xb[i], 0.f));
      const float pa = __uint_as_float(pack_bf16(ha, xa[i] - ha)), pb = __uint_as_float(pack_bf16(hb, xb[i] - hb));
      sts64f(sb + CTAB_OFF + (32 * i + lane) * 24 + 16, p.swap ? pb : pa, p.swap ? pa : pb);
    }
    fence_async_smem();
    mbar_arrive(bars + 8 * B_STAB);
    if (lane == 0) TS(26);
  } else if (wid == 13) {
    ROLE(role)
    uint4 tv[3];
    const uint32_t e0 = ld_rlx(g_epoch);
    const uint32_t e1 = ldv16(p.ssmD + min(cch0 + 32 * lane, 639));
    const uint4 dv = ldv128((const uint4*)(p.dskip + 160 * dg) + min(lane, 19));
#pragma unroll
    for (int i = 0; i < 3; i++) tv[i] = ldv128((const uint4*)(p.shiftk + 640 * dg) + min(lane + 32 * i, 79));
    sts128(sb + DTAB_OFF + 16 * min(lane, 19), dv);
#pragma unroll
    for (int i = 0; i < 3; i++) sts128(sb + TAP_OFF + 16 * min(lane + 32 * i, 79), tv[i]);
    if (lane < 7) sts32(sb + EP_OFF + 4 * lane, lane < 5 ? e1 << 16 : (lane == 5 ? e0 : 0u));
    __syncwarp();
    bar_sync(9, 64);
    mbar_arrive(bars + 8 * B_CTAB);
    if (lane == 0) { mbar_arrive(bars + 8 * B_EP); TS(53); }
    if (has2) {
    if (TPF >= 0) {
      mbar_wait(bars + 8 * (B_KV + TPF));
      if (elect_one()) {
#pragma unroll
        for (int c = 0; c < 5; c++) l2_prefetch(p.ssmk + (cch0 + 32 * c) * SEQ, 4096);
        if (CPF) { l2_prefetch(p.cre + (160 * dg + 5 * m2) * DM, 6400); l2_prefetch(p.cim + (160 * dg + 5 * m2) * DM, 6400); }
      }
    }
#pragma unroll 1
      for (int i = 0; i < 5; i++) {
        const int c = i == 2 ? 3 : (i == 3 ? 2 : i);
        mbar_wait(bars + 8 * (B_PD + c));
        if (lane == 0) bulk_s2g(g_kv + (dg * 32 + m2) * 20480 + c * 4096, sb + KS_OFF + c * KV_PIECE, 4096);
      }
      if (lane == 0) {
        asm volatile("cp.async.bulk.commit_group;" ::: "memory");
        asm volatile("cp.async.bulk.wait_group 0;" ::: "memory");
        mbar_arrive(bars + 8 * B_PREP2);
        fence_async_global();
      }
      __syncwarp();
      if (lane < 4) red_rel(&g_kvcnt[(dg * 4 + lane) * 32]);
      __syncwarp();
      if (lane == 0) { mbar_arrive(bars + 8 * B_PUB); TS(30); }
    }
  } else if (wid != 12) {
    if (elect_one()) {
      if (wid < 7) {
        const int b0 = wid < 4 ? 4 + 19 * wid : 85 + 21 * (wid - 4), cnt = wid < 4 ? 2 : 1;
#pragma unroll
        for (int i = 0; i < 21; i++) mbar_init(bars + 8 * (b0 + i), cnt);
#pragma unroll
        for (int i = 0; i < 5; i++) mbar_init(bars + 8 * (B_PD + 5 * wid + i), 1);
      } else {
#pragma unroll
        for (int i = 0; i < 12; i++) mbar_init(bars + 8 * (B_CVDONE + i), i == 5 ? 32 : (i == 6 ? 160 : 128));
        mbar_init(bars + 8 * B_CTAB, 192); mbar_init(bars + 8 * B_PREP, 5); mbar_init(bars + 8 * B_PREP2, 1);
      }
      asm volatile("fence.mbarrier_init.release.cluster;" ::: "memory");
    }
    __syncwarp();
    bar_sync(5, 288);
    if (wid == 2) asm volatile("bar.arrive 8, 192;\nbar.arrive 6, 64;\nbar.arrive 9, 64;\nbar.arrive 7, 64;" ::: "memory");
    if (tid == 128) TS(0);
    if (wg == 1) { cv_table(); mbar_arrive(bars + 8 * B_CTAB); }
  }

  if (wid == 12) {
    ROLE(role)
    uint32_t dst = sb;
#pragma unroll 1
    for (int k = S1; k < 10; k++) {
      const uint32_t fb = bars + 8 * (B_G1FULL + k);
      mbar_wait(bars + 8 * (B_G1DONE + k - S1));
      if (elect_one()) {
        mbar_expect_tx(fb, 20480);
        tma4(dst + G1_XOFF, last ? &p.mXl : &p.mX, 64 * k, 0, 0, last ? 0 : 80 * T1, fb);
        mbar_expect_tx(fb, 16384);
        tma5(dst, &p.mB, 64 * k, 0, 0, 4 * side, 2 * GP, fb);
        if (has2 && k - S1 + KV0 < 5) kv_issue(p, k - S1 + KV0, m2, dg);
      }
      dst += G1_STAGE; if (k == 2 * S1 - 1) dst = sb;
    }
  } else if (wid == 15 && (role >> 16)) {
    ROLE(role)
    mbar_wait(bars + 8 * B_PREP2);
    if (lane < 10) sts128(sb + CV_OFF + (lane >> 1) * CV_B + CV_K - 32 + 16 * (lane & 1), make_uint4(0, 0, 0, 0));
    fence_async_smem();
    __syncwarp();
    const unsigned tag = lds32(sb + EP_OFF + 20);
    if (TAPW) mbar_wait(bars + 8 * B_PUB);
    if (elect_one()) {
#pragma unroll 1
      for (int c = 0; c < 5; c++) {
        if (c == 0) asm volatile("prefetch.tensormap [%0];" ::"l"(&p.mU) : "memory");
        mbar_expect_tx(bars + 8 * (B_CVFULL + c), 4096 + 2 * CV_PL);
        if (c < TAPN) bulk_g2s(sb + CV_OFF + c * CV_B + CV_K, p.ssmk + (cch0 + 32 * c) * SEQ, 4096, bars + 8 * (B_CVFULL + c));
      }
    }
    mbar_wait(bars + 8 * B_PUB);
    cnt_poll(&g_kvcnt[(dg * 4 + (m2 >> 3)) * 32], 32 * tag);
    fence_async_global();
    if (elect_one()) {
      TS(28);
#pragma unroll
      for (int c = 0; c < 5; c++) {
        tma5(sb + CV_OFF + c * CV_B + CV_U, &p.mU, 0, -3, 2 * c, 16 * (m2 & 1) + (m2 >> 1), dg, bars + 8 * (B_CVFULL + c));
        if (c >= TAPN) bulk_g2s(sb + CV_OFF + c * CV_B + CV_K, p.ssmk + (cch0 + 32 * c) * SEQ, 4096, bars + 8 * (B_CVFULL + c));
      }
#pragma unroll
      for (int i = 0; i < 3; i++) asm volatile("prefetch.tensormap [%0];" ::"l"(&p.mCre + i) : "memory");
      TS(54);
    }
    __syncwarp();
  }
  {
    const int w = wid & 3;
    if (wg == 2 && !(role >> 16)) {
      float xa[2], xb[2];
      mbar_wait(bars + 8 * (B_G1FULL + 11));
      stat_table<1>(role & 15, lds32(sb + EP_OFF + 20), w, g_stats, g_stats, xa, xb);
      mbar_arrive(bars + 8 * (B_STAB + 1));
    }
#pragma unroll 1
    for (int l = 0; l < 2; l++) {
      if (wg < 2) {
        float acc[80];
#pragma unroll
        for (int i = 0; i < 80; i++) acc[i] = 0.f;
        ROLE(role)
        const int tid = tid_opaque(), r = (tid & 31) >> 2, q = tid & 3;
        const int ch = 128 * GP + 64 * wg + 32 * side + 8 * w + r;
        const uint32_t ca = sb + CTAB_OFF + (32 * wg + 8 * w + r) * 24;
        float2 lam = make_float2(0.f, 0.f), p8 = lam, p16 = lam, pL = lam, p2L = lam;
        fence_regs(acc);
        {
          const uint32_t alo0 = (l == 0 ? desc_lo(sb, 16) : desc_lo(sb + G2_WOFF, 16)) + wg * 512;
          const uint32_t blo0 = l == 0 ? desc_lo(sb + G1_XOFF, 16) : desc_lo(sb + X1_OFF, 128);
          const uint32_t bhi = l == 0 ? desc_hi(1024, 1) : desc_hi(1024, 0), xstep = l == 0 ? 2 : 16;
          const uint32_t astep = l == 0 ? G1_STAGE >> 4 : 1024, bstep = l == 0 ? G1_STAGE >> 4 : 1280, aend = alo0 + (S1 + l) * astep;
          uint32_t alo = alo0, blo = blo0;
          int kskip = 0;
          const uint32_t special = 8u | (l ? (1u << MK1) | (wg << (8 - STG_D)) : (1u << MK0) | (1u << (wg ? PAUSE_K : PAUSE0)) | (wg << (9 - STG0)));
          uint32_t fb = bars + 8 * (B_G1FULL + 10 * l), nb = fb + 8;
          mbar_wait(fb);
          if (tid == 0) TS(1 + 8 * l);
#pragma unroll 1
          for (int k = 0; k < 10; k++) {
            uint32_t ok;
            wgmma_fence();
#pragma unroll
            for (int kk = 0; kk < 4; kk++) {
              wgmma_n160<0>(acc, alo + kk * 2, desc_hi(1024, 1), blo + kk * xstep, bhi);
              if (kk == 0) { ok = mbar_test(nb); asm volatile("add.u32 %0, %0, %1;" : "+r"(nb) : "r"(k < 8 ? 8 : 0)); }
              if (kk == STG_KK && k == 9 && tid == 0) mbar_arrive(bars + 8 * (B_STG + l));
            }
            wgmma_commit();
            alo += astep; blo += bstep;
            if (blo == desc_lo(sb + G_OFF, 128)) blo = desc_lo(sb, 128);
            if (alo == aend) { alo = alo0; blo = blo0; }
            wgmma_wait<1>();
            if (k != kskip && (tid & 127) == 0) mbar_arrive(fb + 8 * (B_G1DONE - B_G1FULL - 1));
            if (!ok) mbar_wait(fb + 8);
            if ((special >> k) & 1) {
            if (k == (l ? MK1 : MK0)) {
              mbar_wait(bars + 8 * (B_STAB + l));
              const float2 sB = lds64f(ca + 16);
              uint32_t a0 = q < 2 ? __float_as_uint(sB.x) : 0u, a1 = q < 2 ? __float_as_uint(sB.y) : 0u, a2 = 0u, a3 = 0u;
              asm volatile("" : "+r"(a0), "+r"(a1), "+r"(a2), "+r"(a3)::"memory");
              wgmma_fence();
              wgmma_rs_n160(acc, a0, a1, a2, a3, l ? desc_lo(sb + MX1_OFF, 0) : desc_lo(sb + MX0_OFF, 0));
              wgmma_commit();
            }
            if (wg == 1 && k == (l ? (EARLY1 ? 8 - STG_D : -1) : PAUSE_K)) {
              wgmma_wait<0>();
              if (tid == 128) mbar_arrive(fb + 8 * (B_G1DONE - B_G1FULL));
              kskip = k + 1;
            }
            if (wg == 1 && k == (l ? 8 - STG_D : 9 - STG0)) mbar_wait(bars + 8 * (B_STG + l));
            if (k == 3) {
              mbar_wait(bars + 8 * B_CTAB);
              lam = lds64f(ca);
              if (l == 0 && q < 2) rec_st(&g_E[(q * NT1 + T1) * DM + ch], 0.f, 0.f, lds32(sb + EP_OFF + 20) - 1);
              if (p.swap) lam.y = -lam.y;
              const float2 p2 = cmul(lam, lam), p4 = cmul(p2, p2);
              p8 = cmul(p4, p4); p16 = cmul(p8, p8);
              pL = cmul(p16, p16);
              if (!last) pL = cmul(pL, p8);
              p2L = cmul(pL, pL);
            }
            if (k == (wg ? PAUSE_K : PAUSE0) && l == 0 && has2) mbar_wait(bars + 8 * B_PREP);
            }
            fb += 8;
          }
        }
        const unsigned tag = lds32(sb + EP_OFF + 20);
        wgmma_wait<0>();
        fence_regs(acc);
        if ((tid & 127) == 0) { mbar_arrive(bars + 8 * (B_G1DONE + 10 * l + 9)); TS(wg ? 17 + l : 2 + 8 * l); }
        float2 ec[3];
#pragma unroll
        for (int jj = 0; jj < 4; jj++)
#pragma unroll
          for (int y = 0; y < 3; y++) {
            if (y == 2 && (jj & 1)) continue;
            const int j = y == 2 ? 16 + jj : 8 * y + 2 * jj;
            const float4 st = lds128f(sb + STAB_OFF + q * 160 + j * 8);
            const float rs[4] = {st.x, st.y, st.z, st.w};
#pragma unroll
            for (int x = 0; x < 4; x++) {
              const int i = 4 * j + 4 * (x >> 1) + (x & 1);
              acc[i] *= rs[x]; acc[i + 2] *= rs[x];
              ec[y] = (jj == 0 && x == 0) ? make_float2(acc[i], acc[i + 2]) : cfma(lam, ec[y], make_float2(acc[i], acc[i + 2]));
            }
          }
        float2 e = cfma(p16, ec[0], ec[1]);
        if (!last) e = cfma(p8, e, ec[2]);
        {
          float2 v = make_float2(__shfl_up_sync(0xffffffffu, e.x, 1, 4), __shfl_up_sync(0xffffffffu, e.y, 1, 4));
          if (q >= 1) e = cfma(pL, v, e);
          v = make_float2(__shfl_up_sync(0xffffffffu, e.x, 2, 4), __shfl_up_sync(0xffffffffu, e.y, 2, 4));
          if (q >= 2) e = cfma(p2L, v, e);
        }
        if (!last && q == 3) rec_st(&g_E[(l * NT1 + T1) * DM + ch], e.x, e.y, tag);
        if (tid == 0) TS(3 + 8 * l);
        float2 ex = make_float2(__shfl_up_sync(0xffffffffu, e.x, 1, 4), __shfl_up_sync(0xffffffffu, e.y, 1, 4));
        if (q == 0) ex = make_float2(0.f, 0.f);
        const float2 coef = lds64f(ca + 8), lamc = make_float2(lam.x, p.swap ? lam.y : -lam.y);
        float m00 = coef.x, m01 = -coef.y, m10 = -coef.y, m11 = -coef.x;
        if (p.swap) { m00 = -coef.y; m01 = coef.x; m10 = -coef.x; m11 = -coef.y; }
        float2 pLq, p160q, p640;
        {
          const float2 p80 = last ? cmul(p2L, p16) : p2L, p160 = cmul(p80, p80), p320 = cmul(p160, p160), one = make_float2(1.f, 0.f);
          p640 = cmul(p320, p320);
          pLq = cmul((q & 1) ? pL : one, (q & 2) ? p2L : one);
          p160q = cmul((q & 1) ? p160 : one, (q & 2) ? p320 : one);
        }
        float2 c, ev[3];
        unsigned tg[3];
        const uint4* ep = &g_E[(l * NT1 + T1 - 1 - q) * DM + ch];
#pragma unroll
        for (int j = 0; j < 20; j++) {
          if (j == CPOLL) {
#pragma unroll
            for (int i = 0; i < 3; i++) {
              ev[i] = make_float2(0.f, 0.f); tg[i] = tag;
              if (T1 - 1 - q - 4 * i >= 0) tg[i] = rec_ld(ep - 4 * i * DM, ev[i].x, ev[i].y);
            }
          }
#pragma unroll
          for (int x = 0; x < 2; x++) {
            const float b0 = acc[4 * j + x], b1 = acc[4 * j + 2 + x];
            acc[4 * j + x] = fmaf(b0, m00, b1 * m01);
            acc[4 * j + 2 + x] = fmaf(b0, m10, b1 * m11);
          }
          if (j == CPOLL - 1 || j == 19) asm volatile("" : "+f"(acc[4 * j]), "+f"(acc[4 * j + 1]), "+f"(acc[4 * j + 2]), "+f"(acc[4 * j + 3])::"memory");
        }
        {
          uint32_t it = 0;
          while (__any_sync(0xffffffffu, tg[0] != tag || tg[1] != tag || tg[2] != tag)) {
#pragma unroll
            for (int i = 0; i < 3; i++)
              if (tg[i] != tag) tg[i] = rec_ld(ep - 4 * i * DM, ev[i].x, ev[i].y);
            trap_if(++it > SPIN_LIMIT);
          }
          c = cfma(p640, cfma(p640, ev[2], ev[1]), ev[0]);
          c = cmul(c, p160q);
          c.x += __shfl_xor_sync(0xffffffffu, c.x, 1); c.y += __shfl_xor_sync(0xffffffffu, c.y, 1);
          c.x += __shfl_xor_sync(0xffffffffu, c.x, 2); c.y += __shfl_xor_sync(0xffffffffu, c.y, 2);
        }
        if (tid == 0) TS(4 + 8 * l);
        if (HOLD1 && wg == 1 && l == 1 && has2) mbar_wait(bars + 8 * HOLD1);
        const uint32_t c0 = (uint32_t)clock(), tm = (tid & 7) == 4 * side + w;
        c = cfma(pLq, c, ex);
        float2 hh = make_float2(fmaf(c.x, m00, c.y * m01), fmaf(c.x, m10, c.y * m11));
        uint8_t* hb = g_h + (10 * wg + 2 * GP) * 8192 + (4 * side + w) * 1024 + (tid_opaque() & 31) * 4;
#pragma unroll
        for (int j4 = 0; j4 < 5; j4++) {
          if (PACE && j4 > 0 && wg == 1 && l == 1) { while (__any_sync(0xffffffffu, (uint32_t)clock() - c0 < PACE * j4)) {} }
          const int ng = 20 * T1 + 4 * j4;
          uint8_t* hp = hb + (size_t)(ng >> 3) * 163840 + (ng & 7) * 128;
#pragma unroll
          for (int jj = 0; jj < 4; jj++) {
            const int j = 4 * j4 + jj;
            const float2 h0 = cfma(lamc, hh, make_float2(acc[4 * j + 0], acc[4 * j + 2]));
            hh = cfma(lamc, h0, make_float2(acc[4 * j + 1], acc[4 * j + 3]));
            if (j4 < 4 || !last) {
              *(uint32_t*)(hp + jj * 128) = tag_word(pack_bf16(h0.x, hh.x), tm, 1 - l);
              *(uint32_t*)(hp + jj * 128 + 8192) = tag_word(pack_bf16(h0.y, hh.y), tm, 1 - l);
            }
          }
        }
        if (l == 0) mbar_arrive(bars + 8 * (B_HST + wg));
        if (tid == 0) TS(5 + 8 * l);
        if (tid == 128) TS(l ? 25 : 19);
        if (l == 0 && wid == 4) {
          mbar_wait(bars + 8 * B_HST);
          mbar_wait(bars + 8 * (B_HST + 1));
          if ((tid & 31) < 4) h_release(0, T1, tid & 3);
          __syncwarp();
          if (tid == 128) { mbar_arrive(bars + 8 * B_REL); TS(6); }
        }
      }
      if (l == 0) {
        ROLE(role)
        if (has2) {
          CvCtx cc;
          mbar_wait(bars + 8 * B_CTAB);
          cv_setup(cc);
          mbar_wait(bars + 8 * (B_G1DONE + 9));
#pragma unroll 1
          for (int c = (wg + 2) & 3; c < 5; c += 4) conv_channel(c, cc);
          if ((tid & 127) == 0) TS(wg == 2 ? 32 : (wg == 3 ? 50 : 7 + wg));
        }
      }
      if (wg >= 2) break;
    }
    if (wg < 2 && (role >> 16)) {
      const int ln = tid_opaque() & 31;
      const uint8_t* src = g_h + ((role >> 8) & 63) * 163840;
      uint32_t ph = 0;
      if (wg == 0) {
        mbar_wait(bars + 8 * (B_G1DONE + 19));
        if (SPEC0 + SPECW) __nanosleep(SPEC0 + SPECW * w);
        if (tid == 0) TS(23);
        if (tid == 96) mbar_arrive(bars + 8 * B_SPEC);
        if (!SPLITI && w < 3 && elect_one()) { mbar_expect_tx(bars + 8 * (B_XV + w + 4), G2_XB); }
      }
#pragma unroll 1
      for (int k = 10 * wg + w; k < 10 * wg + 10; k += 4) {
        if (k < (SPLITI ? S2 : 4) && elect_one()) {
          mbar_expect_tx(bars + 8 * (B_XV + k), G2_XB);
          bulk_g2s(sb + k * G2_XB, src + k * 8192, G2_XB, bars + 8 * (B_XV + k));
          if (!SPLITI && k < 3) bulk_g2s(sb + (k + 4) * G2_XB, src + (k + 4) * 8192, G2_XB, bars + 8 * (B_XV + k + 4));
        }
        validate_block(bars + 8 * (B_XV + k), bars + 8 * (B_G2FULL + 20 + k), sb + (k % S2) * G2_XB, src + k * 8192,
                       (ln & 7) * 1028 + (ln >> 3) * 32, bars + 8 * (B_RETRY + wid), ph);
      }
    }
    if (wg == 3) {
    ROLE(role)
    const int pw = wid & 3, gpc = 2 * min(m2 >> 3, 3) + (dg >> 1);
    mbar_wait(bars + 8 * B_EP);
    const unsigned tag = lds32(sb + EP_OFF + 20);
    if (pw == 0) {
      if (elect_one()) {
#pragma unroll 1
        for (int l = 0; l < 2; l++) {
          uint32_t dst = sb;
          if (l == 1) {
            dst = sb + G2_WOFF;
#pragma unroll 1
            for (int k = 0; k < 10; k++) {
              mbar_wait(k > 4 ? bars + 8 * (B_G1DONE + 5 + k) : (has2 ? bars + 8 * (B_G2DONE + 14 + min(k, 3)) : bars + 8 * (B_G1DONE + 9)));
              mbar_expect_tx(bars + 8 * (B_G1FULL + 10 + k), 16384);
              tma5(dst, &p.mB, 64 * k, 0, 0, 4 * side, 2 * GP, bars + 8 * (B_G1FULL + 10 + k));
              dst += 16384; if (k == 4) dst = sb + G2_WOFF;
            }
          }
          if (has2) {
            const uint32_t fb2 = bars + 8 * (B_G2FULL + 20 * l), wb2 = bars + 8 * (B_G2DONE + 20 * l - S2);
            dst = sb + G2_WOFF + (WTAIL ? 4 * l * G2_WB : 0);
            int kc = 0;
#pragma unroll 1
            for (int k = 0; k < 20; k++) {
              mbar_wait(k >= S2 ? wb2 + 8 * k : bars + 8 * (l ? B_G1DONE + (WTAIL ? (k < 3 ? 15 + k : 13 + k) : 19) : (k == 5 ? B_XFREE : (k == 6 ? B_SFREE : B_REL))));
              mbar_expect_tx(fb2 + 8 * k, G2_WB);
              tma5(dst, &p.mCre + (k & 1), kc, 0, 0, 0, 10 * dg, fb2 + 8 * k);
              kc += (k & 1) << 7; if (k == 9) kc = 64;
              dst += G2_WB; if (dst == sb + G2_WOFF + S2 * G2_WB) dst = sb + G2_WOFF;
            }
          }
        }
      }
    } else if (pw == 1) {
#pragma unroll 1
      for (int l = 0; l < 2; l++) {
        if (l == 1) {
          mbar_wait(bars + 8 * (has2 ? B_G2DONE + 19 : B_G1DONE + 9));
          if (has2) mbar_wait(bars + 8 * B_UST);
          cnt_poll(&g_ucnt[gpc * 32], 128 * tag);
          fence_async_global();
          if (elect_one()) {
            TS(20);
            const int bytes = last ? 16384 : 20480;
            const uint8_t* src = g_u + T1 * 204800;
            uint32_t dst = sb + X1_OFF;
#pragma unroll 1
            for (int k = 0; k < 10; k++) {
              if (k > 4) mbar_wait(bars + 8 * (B_G1DONE + 5 + k));
              mbar_expect_tx(bars + 8 * (B_G1FULL + 10 + k), bytes);
              bulk_g2s(dst, src, bytes, bars + 8 * (B_G1FULL + 10 + k));
              src += 20480; dst += 20480; if (dst == sb + G_OFF) dst = sb; if (k == 4) dst = sb + X1_OFF;
            }
          }
          __syncwarp();
        }
        if (has2) {
          if (l == 0) {
            mbar_wait(bars + 8 * B_REL);
            cnt_poll(&g_hcnt[gpc * 32], 40 * tag);
            fence_async_global();
          }
          if (elect_one()) {
            if (l == 0) TS(21);
            const uint32_t fb2 = bars + 8 * (l ? B_XV : B_G2FULL), wb2 = bars + 8 * (B_G2DONE + 20 * l - S2);
            const uint8_t* src = g_h + m2 * 163840 + l * S2 * 8192;
            uint32_t dst = sb;
#pragma unroll 1
            for (int k = l * S2; k < 20; k++) {
              if (k >= 5) mbar_wait(k >= S2 ? wb2 + 8 * k : bars + 8 * B_SFREE);
              mbar_expect_tx(fb2 + 8 * k, G2_XB);
              bulk_g2s(dst, src, G2_XB, fb2 + 8 * k);
              src += 8192; dst += G2_XB; if (dst == sb + S2 * G2_XB) dst = sb;
            }
          }
          __syncwarp();
        }
      }
    } else if (pw == 2) {
#pragma unroll 1
      for (int l = 0; l < 2; l++) {
        if (l == 1) {
          if (has2) {
            mbar_wait(bars + 8 * B_UST);
            if (lane < 8) red_rel(&g_ucnt[lane * 32]);
            __syncwarp();
            if (lane == 0) TS(38);
          }
          float xa[2], xb[2];
          mbar_wait(bars + 8 * (B_G1FULL + 11));
          stat_table<1>(T1, tag, 4, g_stats, g_stats, xa, xb);
          mbar_arrive(bars + 8 * (B_STAB + 1));
        }
        if (l == 0 && has2 && elect_one()) {
#pragma unroll 1
          for (int i = 0; i < 5; i++) {
            const int c = i < 3 ? i : 7 - i;
            mbar_wait(bars + 8 * (B_CVDONE + c));
            bulk_s2g(g_G + (cch0 + 32 * c) * 4096, cv_stage(c), 4096);
          }
          asm volatile("cp.async.bulk.commit_group;" ::: "memory");
          asm volatile("cp.async.bulk.wait_group.read 0;" ::: "memory");
          mbar_arrive(bars + 8 * B_SFREE);
          asm volatile("cp.async.bulk.wait_group 0;" ::: "memory");
          TS(48);
          fence_async_global();
          asm volatile("fence.acq_rel.gpu;" ::: "memory");
#pragma unroll
          for (int i = 0; i < 4; i++) red_rlx(&g_gcnt[(dg * 4 + i) * 32]);
          TS(49);
          mbar_arrive(bars + 8 * (B_GO + 1));
        }
        __syncwarp();
      }
    } else if (has2) {
      mbar_wait(bars + 8 * B_REL);
      if (!CPF && elect_one()) {
        l2_prefetch(p.cre + (160 * dg + 5 * m2) * DM, 6400); l2_prefetch(p.cim + (160 * dg + 5 * m2) * DM, 6400);
      }
      mbar_wait(bars + 8 * (B_GO + 1));
      flag_poll(&g_gcnt[(dg * 4 + (m2 >> 3)) * 32], 32 * tag);
      fence_async_global();
      if (elect_one()) {
        TS(29);
        mbar_expect_tx(bars + 8 * B_GFULL, 20480);
        tma5(sb + G_OFF, &p.mG, 64 * m2, 0, 0, 0, 10 * dg, bars + 8 * B_GFULL);
      }
    }
    } else if (wg == 2 && (role >> 16)) {
      float acc[80];
      float off[2] = {mean0[0], mean0[1]};
      const unsigned tag = lds32(sb + EP_OFF + 20);
      dskip_init<true>(acc, mean0, rstd0);
      mbar_arrive(bars + 8 * B_XFREE);
      mbar_wait(bars + 8 * (B_CVDONE + 2));
      mbar_wait(bars + 8 * (B_CVDONE + 3));
#pragma unroll 1
      for (int step = 1; step < 4; step++) {
        const int l = step >> 1;
        if (step != 2) {
          uint32_t alo = desc_lo(sb, 1024), blo = desc_lo(sb + G2_WOFF, 16) + (WTAIL ? l * (G2_WB >> 2) : 0);
          uint32_t fb = bars + 8 * (B_G2FULL + 20 * l);
          fence_regs(acc);
          mbar_wait(fb);
          if (tid == 256) TS(33 + 6 * l);
#pragma unroll 1
          for (int k = 0; k < 20; k++) {
            if (l == TSL && (k & 3) == 3 && tid == 256) TS(56 + (k >> 2));
            uint32_t ok; const uint32_t nb = k < 19 ? fb + 8 : fb;
            wgmma_fence();
#pragma unroll
            for (int kk = 0; kk < 4; kk++) {
              wgmma_n160<1>(acc, alo + kk * 128, desc_hi(128, 0), blo + kk * 2, desc_hi(1024, 1));
              if (kk == 0) ok = mbar_test(nb);
            }
            wgmma_commit();
            alo += G2_XB >> 4; blo += G2_WB >> 4;
            if (alo == desc_lo(sb + S2 * G2_XB, 1024)) alo = desc_lo(sb, 1024);
            if (blo == desc_lo(sb + G_OFF, 16)) blo = desc_lo(sb + G2_WOFF, 16);
            wgmma_wait<1>();
            if (k > 0 && tid == 256) mbar_arrive(fb + 8 * (B_G2DONE - B_G2FULL - 1));
            if (!ok) mbar_wait(nb);
            fb += 8;
          }
          wgmma_wait<0>();
          fence_regs(acc);
          if (tid == 256) TS(34 + 6 * l);
          if (tid == 256) mbar_arrive(bars + 8 * (B_G2DONE + 20 * l + 19));
        }
        ROLE(role)
        const int tq = tid_opaque() & 31, n0 = 64 * m2 + 16 * w + (tq >> 2);
        stats_publish<false>(step, n0, dg, tag, acc);
        uint32_t gf[10][4];
        mbar_wait(bars + 8 * B_GFULL);
        uint32_t ga = sb + G_OFF + (8 * (tq >> 4) + (tq & 7)) * 128 + (((2 * w + ((tq >> 3) & 1)) ^ ((2 * m2) & 6) ^ (tq & 7)) << 4), gstep = 2048;
        if (step == 2) { ga = sb + DX_OFF + (8 * (tq >> 4) + (tq & 7)) * 16; gstep = 256; }
#pragma unroll
        for (int J = 0; J < 2; J++) ldsm4t(gf[J], ga + J * gstep);
        if (tid == 256) TS(35 + 6 * l);
        uint8_t* dst[2][2];
#pragma unroll
        for (int h = 0; h < 2; h++) {
          if (l == 0) {
            const int ng = 8 * m2 + 2 * w + h, T = ng / 20;
            uint8_t* ub = g_u + (T * 204800 + (ng - 20 * T) * 1024 + (tq & 2) * 64 + (tq & 28) * 4 + (tq & 1) * 8 + (5 * dg >> 1) * 20480);
            dst[h][1] = ub + ((dg & 1) ? 20480 - 512 : 0);
            dst[h][0] = ub + (dg & 1) * 512;
          } else {
            dst[h][0] = dst[h][1] = (uint8_t*)(p.out + (n_to_t(n0 + 8 * h) * DM + 160 * dg + 4 * (tq & 3)));
          }
        }
        float mean[2], rstd[2];
        stats_get<false>(step, n0, tag, mean, rstd);
        if (tid == 256) TS(36 + 6 * l);
        off[0] += mean[0]; off[1] += mean[1];
        const float ov[2] = {step == 3 ? off[0] : 0.f, step == 3 ? off[1] : 0.f};
#pragma unroll
        for (int J = 0; J < 10; J++) {
          if (J + 2 < 10) ldsm4t(gf[J + 2 < 10 ? J + 2 : 0], ga + (J + 2) * gstep);
#pragma unroll
          for (int x = 0; x < 8; x++) {
            const int h = (x >> 1) & 1;
            const uint32_t gwd = gf[J][x >> 1];
            const float t = fmaf(rstd[h], (x & 1) ? bf_hi(gwd) : bf_lo(gwd), 1.f);
            acc[8 * J + x] = fmaf(acc[8 * J + x], t, fmaf(-mean[h], t, ov[h]));
          }
#pragma unroll
          for (int h = 0; h < 2; h++) {
            if (step == 1)
              *(uint2*)(dst[h][(J >> 1) & 1] + (J >> 2) * 20480 + (J & 3) * 256) =
                  make_uint2(pack_bf16(acc[8 * J + 2 * h], acc[8 * J + 2 * h + 1]), pack_bf16(acc[8 * J + 4 + 2 * h], acc[8 * J + 5 + 2 * h]));
            if (step == 3)
              *(float4*)(dst[h][0] + 64 * J) = make_float4(acc[8 * J + 2 * h], acc[8 * J + 2 * h + 1], acc[8 * J + 4 + 2 * h], acc[8 * J + 5 + 2 * h]);
          }
          __syncwarp();
        }
        if (step == 1) {
          mbar_arrive(bars + 8 * B_UST);
          if (tid == 256) TS(37);
          for (int n = tid & 127; n < 160; n += 128) {
            const int d = 16 * (n >> 4) + 4 * ((n >> 1) & 3) + 2 * ((n >> 3) & 1) + (n & 1);
            const uint32_t dw = lds32(sb + DTAB_OFF + 2 * (d & ~1)), dd = __byte_perm(dw, dw, (d & 1) ? 0x3232 : 0x1010);
            sts128(sb + DX_OFF + 16 * n, make_uint4(dd, dd, dd, dd));
          }
          bar_sync(3, 128);
        } else if (step == 2) {
          if (tid == 256) TS(22);
          mbar_wait(bars + 8 * (B_G1FULL + 11));
          float xa[2], xb[2];
          stat_table<1>(T1, tag, w, g_stats, g_stats, xa, xb);
          mbar_arrive(bars + 8 * (B_STAB + 1));
          if (tid == 256) TS(27);
          mbar_wait(bars + 8 * (B_G1DONE + 19));
          keep_warm(bars + 8 * WEND, 3);
        } else {
          if (tid == 256) {
            TS(43);
            if (m2 == 31 && dg == 3) asm volatile("st.relaxed.gpu.global.u32 [%0], %1;" ::"l"(g_epoch), "r"(tag + 1) : "memory");
          }
        }
      }
    }
  }
}

typedef CUresult (*EncFn)(CUtensorMap*, CUtensorMapDataType, cuuint32_t, void*, const cuuint64_t*, const cuuint64_t*,
                          const cuuint32_t*, const cuuint32_t*, CUtensorMapInterleave, CUtensorMapSwizzle,
                          CUtensorMapL2promotion, CUtensorMapFloatOOBfill);

void encode(EncFn fn, CUtensorMap* m, const void* ptr, int rank, const cuuint64_t* dims, const cuuint64_t* strides, const cuuint32_t* box,
            CUtensorMapSwizzle swz = CU_TENSOR_MAP_SWIZZLE_128B, int prom = 2) {
  cuuint32_t es[5] = {1, 1, 1, 1, 1};
  fn(m, CU_TENSOR_MAP_DATA_TYPE_BFLOAT16, rank, (void*)ptr, dims, strides, box, es, CU_TENSOR_MAP_INTERLEAVE_NONE,
     swz, (CUtensorMapL2promotion)prom, CU_TENSOR_MAP_FLOAT_OOB_FILL_NONE);
}

}

extern "C" void kernel_launch(void* const* d_in, const int* in_sizes, int n_in, void* d_out, int out_size) {
  (void)in_sizes; (void)n_in; (void)out_size;
  Params p;
  typedef const __nv_bfloat16* BP;
  p.x = (BP)d_in[0]; p.lre = (BP)d_in[1]; p.lim = (BP)d_in[2]; p.bre = (BP)d_in[3]; p.bim = (BP)d_in[4];
  p.cre = (BP)d_in[5]; p.cim = (BP)d_in[6]; p.logdt = (BP)d_in[7]; p.dskip = (BP)d_in[8];
  p.k = (BP)d_in[10]; p.v = (BP)d_in[11]; p.shiftk = (BP)d_in[12]; p.ssmk = (BP)d_in[13]; p.ssmD = (BP)d_in[14];
  p.out = (float*)d_out;
  for (int sm = 0; sm < 132; sm++) {
    const int tpc = sm >> 1, side = sm & 1;
    int gpc, gi;
    if (tpc < 32) { gpc = tpc & 7; gi = tpc >> 3; }
    else if (tpc < 60) { gpc = 1 + (tpc - 32) % 7; gi = 4 + (tpc - 32) / 7; }
    else if (tpc < 62) { gpc = tpc - 54; gi = 8; }
    else { gpc = 0; gi = tpc - 58; }
    const int pos = 8 * gpc + gi + (gpc == 7 ? 1 : 0);
    int T1, GP;
    if (pos < 52) { const int hh = pos / 26, x = pos - 26 * hh; T1 = x >> 1; GP = 2 * hh + (x & 1); }
    else { T1 = pos - 52; GP = 4; }
    const int m2 = 8 * (gpc >> 1) + gi, dg = 2 * (gpc & 1) + side;
    p.role[sm] = pos == 65 ? -1 : (T1 | (GP << 4) | (side << 7) | (m2 << 8) | (dg << 14) | ((gi < 8) << 16));
  }
  void* fnp = nullptr;
  cudaDriverEntryPointQueryResult qr;
  cudaGetDriverEntryPoint("cuTensorMapEncodeTiled", &fnp, cudaEnableDefault, &qr);
  EncFn fn = (EncFn)fnp;
  void* gG = nullptr;
  cudaGetSymbolAddress(&gG, g_G);
  void* gKV = nullptr;
  cudaGetSymbolAddress(&gKV, g_kv);
  {
    cuuint64_t dims[5] = {32, 32, 10, 32, 4}, st[4] = {20480, 2048, 64, 655360}; cuuint32_t box[5] = {32, 35, 2, 1, 1};
    encode(fn, &p.mU, gKV, 5, dims, st, box, CU_TENSOR_MAP_SWIZZLE_NONE, 1);
  }
  const cuuint64_t RB = DM * 2;
  {
    p.swap = p.bim < p.bre;
    const char* lo = (const char*)(p.swap ? p.bim : p.bre); const char* hi = (const char*)(p.swap ? p.bre : p.bim);
    cuuint64_t dims[5] = {640, 8, 2, 8, 10}, st[4] = {RB, (cuuint64_t)(hi - lo), 8 * RB, 64 * RB}; cuuint32_t box[5] = {64, 8, 2, 4, 2};
    encode(fn, &p.mB, lo, 5, dims, st, box);
  }
  {
    cuuint64_t dims[5] = {640, 2, 4, 2, 40}, st[4] = {RB, 4 * RB, 2 * RB, 16 * RB}; cuuint32_t box[5] = {64, 2, 4, 2, 10};
    encode(fn, &p.mCre, p.cre, 5, dims, st, box); encode(fn, &p.mCim, p.cim, 5, dims, st, box);
    cuuint64_t dimg[5] = {2048, 2, 4, 2, 40}, stg[4] = {4096, 4 * 4096, 2 * 4096, 16 * 4096};
    encode(fn, &p.mG, gG, 5, dimg, stg, box);
  }
  {
    cuuint64_t dims[4] = {640, 2, 4, 900}, st[3] = {RB, 40 * RB, 2 * RB}; cuuint32_t box[4] = {64, 2, 4, 20};
    encode(fn, &p.mX, p.x, 4, dims, st, box);
    cuuint64_t diml[4] = {640, 2, 4, 16}, stl[3] = {RB, 32 * RB, 2 * RB};
    encode(fn, &p.mXl, p.x + (size_t)1920 * DM, 4, diml, stl, box);
    cuuint32_t boxt[4] = {160, 2, 4, 4};
    encode(fn, &p.mXt, p.x, 4, dims, st, boxt, CU_TENSOR_MAP_SWIZZLE_NONE);
    encode(fn, &p.mXtl, p.x + (size_t)1920 * DM, 4, diml, stl, boxt, CU_TENSOR_MAP_SWIZZLE_NONE);
    cuuint64_t dk[3] = {640, 2000, 4}, sk[2] = {RB, 16 * RB}; cuuint32_t bk[3] = {32, 19, 4}, bv[3] = {32, 17, 4};
    encode(fn, &p.mK, p.k, 3, dk, sk, bk, CU_TENSOR_MAP_SWIZZLE_NONE);
    encode(fn, &p.mV, p.v, 3, dk, sk, bv, CU_TENSOR_MAP_SWIZZLE_NONE);
  }
  cudaFuncSetAttribute(fused_kernel, cudaFuncAttributeMaxDynamicSharedMemorySize, SMEM_BYTES);
  cudaLaunchConfig_t cfg = {};
  cfg.gridDim = dim3(132); cfg.blockDim = dim3(512); cfg.dynamicSmemBytes = SMEM_BYTES; cfg.stream = cudaStreamPerThread;
  cudaLaunchKernelEx(&cfg, fused_kernel, p);
}
```
